```python
import torch

def _softmax(x, axis=-1):
    return torch.softmax(x, dim=axis)

def _gelu(x):
    return torch.nn.functional.gelu(x, approximate='tanh')

def _silu(x):
    return torch.nn.functional.silu(x)

def _sigmoid(x):
    return torch.sigmoid(x)

def _layernorm(x, axis=-1, eps=1e-05):
    m = x.mean(dim=axis, keepdim=True)
    v = x.var(dim=axis, keepdim=True, unbiased=False)
    return (x - m) / torch.sqrt(v + eps)

def _scatter_add(tgt, idx, src, axis=0):
    return tgt.clone().index_add_(axis, idx, src)

def _segment_sum(src, seg, n):
    out = torch.zeros((n,) + src.shape[1:], dtype=src.dtype)
    return out.index_add_(0, seg, src)

def _pad(x, pw):
    flat = tuple((v for pair in reversed(pw) for v in pair))
    return torch.nn.functional.pad(x, flat)
kernel_name = 'concat_heads__ssm_conv_s5__memory_aug_recurrent_mem_tr__prompt'

def setup_inputs():

    _w = lambda a: (lambda t: t.to(torch.bfloat16) if t.is_floating_point() else t)(torch.as_tensor(a))

    def _A_setup():
        B, S, D = (1, 2048, 576)
        P = D
        Lambda_re = -0.5 * (lambda _x: torch.exp(torch.as_tensor(_x)))((lambda *s: torch.randn(*s, dtype=torch.bfloat16) * 0.8)(P))
        Lambda_im = (lambda *s: torch.randn(*s, dtype=torch.bfloat16) * 0.8)(P) * 1.0
        B_re = (lambda *s: torch.randn(*s, dtype=torch.bfloat16) * 0.8)(P, D) * D ** (-0.5)
        B_im = (lambda *s: torch.randn(*s, dtype=torch.bfloat16) * 0.8)(P, D) * D ** (-0.5)
        C_re = (lambda *s: torch.randn(*s, dtype=torch.bfloat16) * 0.8)(D, P) * P ** (-0.5)
        C_im = (lambda *s: torch.randn(*s, dtype=torch.bfloat16) * 0.8)(D, P) * P ** (-0.5)
        log_dt = (lambda *s: torch.randn(*s, dtype=torch.bfloat16) * 0.8)(P) * 0.3 - 2.0
        Dskip = (lambda *s: torch.randn(*s, dtype=torch.bfloat16) * 0.8)(D)
        return {'x': _w((lambda *s: torch.randn(*s, dtype=torch.bfloat16) * 0.05)(B, S, D)), 'Lambda_re': _w(Lambda_re), 'Lambda_im': _w(Lambda_im), 'B_re': _w(B_re), 'B_im': _w(B_im), 'C_re': _w(C_re), 'C_im': _w(C_im), 'log_dt': _w(log_dt), 'Dskip': _w(Dskip)}
    _A_in = _A_setup()

    def _B_setup():
        B, S, Dm = (1, 2048, 576)
        H, Dh = (32, 128)
        M, seg = (8, 32)
        seg = min(seg, S)
        S = S // seg * seg
        return {'x': _w((lambda *s: torch.randn(*s, dtype=torch.bfloat16) * 0.05)(B, S, Dm)), 'mem0': _w((lambda *s: torch.randn(*s, dtype=torch.bfloat16) * 0.8)(B, M, Dm)), 'Wq': _w((lambda *s: torch.randn(*s, dtype=torch.bfloat16) * 1.6)(Dm, H, Dh) * Dm ** (-0.5)), 'Wk': _w((lambda *s: torch.randn(*s, dtype=torch.bfloat16) * 1.6)(Dm, H, Dh) * Dm ** (-0.5)), 'Wv': _w((lambda *s: torch.randn(*s, dtype=torch.bfloat16) * 0.8)(Dm, H, Dh) * Dm ** (-0.5)), 'Wo': _w((lambda *s: torch.randn(*s, dtype=torch.bfloat16) * 0.8)(H, Dh, Dm) * (H * Dh) ** (-0.5)), 'seg_len': seg}
    _B_in = _B_setup()
    return {'A_x': _A_in['x'], 'A_Lambda_re': _A_in['Lambda_re'], 'A_Lambda_im': _A_in['Lambda_im'], 'A_B_re': _A_in['B_re'], 'A_B_im': _A_in['B_im'], 'A_C_re': _A_in['C_re'], 'A_C_im': _A_in['C_im'], 'A_log_dt': _A_in['log_dt'], 'A_Dskip': _A_in['Dskip'], 'B_x': _B_in['x'], 'B_mem0': _B_in['mem0'], 'B_Wq': _B_in['Wq'], 'B_Wk': _B_in['Wk'], 'B_Wv': _B_in['Wv'], 'B_Wo': _B_in['Wo'], 'B_seg_len': _B_in['seg_len']}

def reference(A_x, A_Lambda_re, A_Lambda_im, A_B_re, A_B_im, A_C_re, A_C_im, A_log_dt, A_Dskip, B_x, B_mem0, B_Wq, B_Wk, B_Wv, B_Wo, B_seg_len):

    def _A_ref(x, Lambda_re, Lambda_im, B_re, B_im, C_re, C_im, log_dt, Dskip):
        Bsz, L, H = x.shape
        Lam = Lambda_re + 1j * Lambda_im
        Bmat = B_re + 1j * B_im
        Cmat = C_re + 1j * C_im
        dt = torch.exp(log_dt)
        Lam_bar = torch.exp(dt * Lam)
        B_bar = ((Lam_bar - 1.0) / Lam)[:, None] * Bmat
        Bu = torch.einsum('bld,pd->blp', x + 0j, B_bar)
        h = torch.zeros_like(Bu[:, 0, :])
        hs = []
        for t in range(L):
            h = Lam_bar[None, :] * h + Bu[:, t, :]
            hs.append(h)
        hseq = torch.stack(hs, 1)
        y = 2.0 * torch.einsum('blp,dp->bld', hseq, Cmat).real + x * Dskip[None, None, :]
        return y

    def _B_ref(x, mem0, Wq, Wk, Wv, Wo, seg_len):
        B, S, Dm = x.shape
        H, Dh = (Wq.shape[1], Wq.shape[2])
        M = mem0.shape[1]
        scale = Dh ** (-0.5)
        n_seg = S // seg_len
        L = M + seg_len
        idx = torch.arange(L)
        mask = (idx[:, None] < M) | (idx[:, None] >= idx[None, :])
        mem = mem0
        outs = []
        for s in range(n_seg):
            xs = x[:, s * seg_len:(s + 1) * seg_len, :].clone()
            h = torch.concatenate([mem, xs], axis=1)
            q = torch.einsum('btd,dhe->bhte', h, Wq)
            k = torch.einsum('btd,dhe->bhte', h, Wk)
            v = torch.einsum('btd,dhe->bhte', h, Wv)
            scores = torch.einsum('bhqe,bhke->bhqk', q, k) * scale
            scores = torch.where(mask[None, None], scores, -1000000000.0)
            p = _softmax(scores, axis=-1)
            o = torch.einsum('bhqk,bhke->bhqe', p, v)
            o = torch.einsum('bhte,hed->btd', o, Wo)
            mem = o[:, :M, :].clone()
            outs.append(o[:, M:, :])
        return torch.concatenate(outs, axis=1)
    a = _A_ref(A_x, A_Lambda_re, A_Lambda_im, A_B_re, A_B_im, A_C_re, A_C_im, A_log_dt, A_Dskip)
    b = _B_ref(B_x, B_mem0, B_Wq, B_Wk, B_Wv, B_Wo, B_seg_len)
    return torch.concatenate([a, b], axis=-1)
```

```cpp
#include <cuda_runtime.h>
#include <cuda.h>
#include <cuda_bf16.h>
#include <cuda_fp16.h>
#include <stdint.h>

#define D_WAIT 700
#define XCHUNK1 14

namespace {

constexpr int DM = 576, NH = 32, SEQ = 2048, NSEG = 64, HD = 4096;

__device__ uint4 g_acc[32 * 96 * 16];
__device__ uint4 g_ox[NH * 2 * SEQ * 8];
__device__ unsigned g_flag[NSEG * 4 * 8];
__device__ unsigned g_gridbar;
__device__ float g_norm[96 * 4];

__device__ __forceinline__ uint32_t smem_u32(const void* p) { return (uint32_t)__cvta_generic_to_shared(p); }
__device__ __forceinline__ uint32_t mapa(uint32_t a, uint32_t r) { uint32_t o; asm("mapa.shared::cluster.u32 %0, %1, %2;" : "=r"(o) : "r"(a), "r"(r)); return o; }
__device__ __forceinline__ unsigned clk() { unsigned c; asm volatile("mov.u32 %0, %%clock;" : "=r"(c)); return c; }
__device__ __forceinline__ void mbar_init(uint32_t bar, uint32_t cnt) { asm volatile("mbarrier.init.shared::cta.b64 [%0], %1;" :: "r"(bar), "r"(cnt) : "memory"); }
__device__ __forceinline__ void mbar_expect(uint32_t bar, uint32_t bytes) { asm volatile("mbarrier.arrive.expect_tx.shared::cta.b64 _, [%0], %1;" :: "r"(bar), "r"(bytes) : "memory"); }
__device__ __forceinline__ void mbar_wait(uint32_t bar, uint32_t parity) {
    asm volatile("{\n.reg .pred p;\n.reg .u32 n;\nmov.u32 n, 0;\n"
                 "W_%=: mbarrier.try_wait.parity.shared::cta.b64 p, [%0], %1;\n@p bra D_%=;\n"
                 "add.u32 n, n, 1;\nsetp.lt.u32 p, n, 4000000;\n@p bra W_%=;\ntrap;\nD_%=:\n}" :: "r"(bar), "r"(parity) : "memory");
}
__device__ __forceinline__ void bar_sync(int id, int n) { asm volatile("bar.sync %0, %1;" :: "r"(id), "r"(n) : "memory"); }
__device__ __forceinline__ void bar_arrive(int id, int n) { asm volatile("bar.arrive %0, %1;" :: "r"(id), "r"(n) : "memory"); }
__device__ __forceinline__ void fence_async_smem() { asm volatile("fence.proxy.async.shared::cta;" ::: "memory"); }
__device__ __forceinline__ uint32_t pack_bf16(float lo, float hi) { uint32_t r; asm("cvt.rn.bf16x2.f32 %0, %1, %2;" : "=r"(r) : "f"(hi), "f"(lo)); return r; }
__device__ __forceinline__ uint32_t pack_f16(float lo, float hi) { uint32_t r; asm("cvt.rn.f16x2.f32 %0, %1, %2;" : "=r"(r) : "f"(hi), "f"(lo)); return r; }
__device__ __forceinline__ uint32_t f16x2_to_bf16x2(uint32_t v) { float2 f = __half22float2(*reinterpret_cast<__half2*>(&v)); return pack_bf16(f.x, f.y); }
__device__ __forceinline__ float ex2(float x) { float y; asm("ex2.approx.ftz.f32 %0, %1;" : "=f"(y) : "f"(x)); return y; }
__device__ __forceinline__ uint4 lds128(uint32_t a) { uint4 v; asm volatile("ld.shared.v4.u32 {%0,%1,%2,%3}, [%4];" : "=r"(v.x), "=r"(v.y), "=r"(v.z), "=r"(v.w) : "r"(a) : "memory"); return v; }
__device__ __forceinline__ float4 lds128f(uint32_t a) { float4 v; asm volatile("ld.shared.v4.f32 {%0,%1,%2,%3}, [%4];" : "=f"(v.x), "=f"(v.y), "=f"(v.z), "=f"(v.w) : "r"(a) : "memory"); return v; }
__device__ __forceinline__ float2 lds64f(uint32_t a) { float2 v; asm volatile("ld.shared.v2.f32 {%0,%1}, [%2];" : "=f"(v.x), "=f"(v.y) : "r"(a) : "memory"); return v; }
__device__ __forceinline__ uint32_t lds32(uint32_t a) { uint32_t v; asm volatile("ld.shared.u32 %0, [%1];" : "=r"(v) : "r"(a) : "memory"); return v; }
__device__ __forceinline__ void sts128(uint32_t a, uint32_t x, uint32_t y, uint32_t z, uint32_t w) { asm volatile("st.shared.v4.u32 [%0], {%1,%2,%3,%4};" :: "r"(a), "r"(x), "r"(y), "r"(z), "r"(w) : "memory"); }
__device__ __forceinline__ void sts128f(uint32_t a, float x, float y, float z, float w) { asm volatile("st.shared.v4.f32 [%0], {%1,%2,%3,%4};" :: "r"(a), "f"(x), "f"(y), "f"(z), "f"(w) : "memory"); }
__device__ __forceinline__ void sts64(uint32_t a, uint32_t x, uint32_t y) { asm volatile("st.shared.v2.u32 [%0], {%1,%2};" :: "r"(a), "r"(x), "r"(y) : "memory"); }
__device__ __forceinline__ void sts32(uint32_t a, uint32_t x) { asm volatile("st.shared.u32 [%0], %1;" :: "r"(a), "r"(x) : "memory"); }
__device__ __forceinline__ uint4 ldsm4(uint32_t a) { uint4 v; asm volatile("ldmatrix.sync.aligned.m8n8.x4.shared.b16 {%0,%1,%2,%3}, [%4];" : "=r"(v.x), "=r"(v.y), "=r"(v.z), "=r"(v.w) : "r"(a) : "memory"); return v; }
__device__ __forceinline__ void stsm2t(uint32_t a, uint32_t x, uint32_t y) { asm volatile("stmatrix.sync.aligned.m8n8.x2.trans.shared.b16 [%0], {%1,%2};" :: "r"(a), "r"(x), "r"(y) : "memory"); }
__device__ __forceinline__ void stsm4t(uint32_t a, uint32_t x, uint32_t y, uint32_t z, uint32_t w) { asm volatile("stmatrix.sync.aligned.m8n8.x4.trans.shared.b16 [%0], {%1,%2,%3,%4};" :: "r"(a), "r"(x), "r"(y), "r"(z), "r"(w) : "memory"); }
__device__ __forceinline__ void st_async64(uint32_t a, uint32_t x, uint32_t y, uint32_t bar) { asm volatile("st.async.shared::cluster.mbarrier::complete_tx::bytes.v2.b32 [%0], {%1,%2}, [%3];" :: "r"(a), "r"(x), "r"(y), "r"(bar) : "memory"); }
__device__ __forceinline__ void bulk_s2c(uint32_t dst, uint32_t src, uint32_t bytes, uint32_t bar) { asm volatile("cp.async.bulk.shared::cluster.shared::cta.mbarrier::complete_tx::bytes [%0], [%1], %2, [%3];" :: "r"(dst), "r"(src), "r"(bytes), "r"(bar) : "memory"); }
__device__ __forceinline__ void bulk_s2g(void* dst, uint32_t src, uint32_t bytes) { asm volatile("cp.async.bulk.global.shared::cta.bulk_group [%0], [%1], %2;" :: "l"(dst), "r"(src), "r"(bytes) : "memory"); }
__device__ __forceinline__ uint32_t ldg_nc32(const void* p) { uint32_t v; asm volatile("ld.global.nc.L2::128B.u32 %0, [%1];" : "=r"(v) : "l"(p)); return v; }
__device__ __forceinline__ uint4 ldg_relaxed128(const void* p) { uint4 v; asm volatile("ld.relaxed.gpu.global.v4.u32 {%0,%1,%2,%3}, [%4];" : "=r"(v.x), "=r"(v.y), "=r"(v.z), "=r"(v.w) : "l"(p) : "memory"); return v; }
__device__ __forceinline__ void mma16816(float (&d)[4], uint32_t a0, uint32_t a1, uint32_t a2, uint32_t a3, uint32_t b0, uint32_t b1) {
    asm volatile("mma.sync.aligned.m16n8k16.row.col.f32.bf16.bf16.f32 {%0,%1,%2,%3}, {%4,%5,%6,%7}, {%8,%9}, {%0,%1,%2,%3};"
        : "+f"(d[0]), "+f"(d[1]), "+f"(d[2]), "+f"(d[3]) : "r"(a0), "r"(a1), "r"(a2), "r"(a3), "r"(b0), "r"(b1));
}
__device__ __forceinline__ void mma16816_z(float (&d)[4], uint32_t a0, uint32_t a1, uint32_t a2, uint32_t a3, uint32_t b0, uint32_t b1) {
    asm volatile("mma.sync.aligned.m16n8k16.row.col.f32.bf16.bf16.f32 {%0,%1,%2,%3}, {%4,%5,%6,%7}, {%8,%9}, {%10,%10,%10,%10};"
        : "=f"(d[0]), "=f"(d[1]), "=f"(d[2]), "=f"(d[3]) : "r"(a0), "r"(a1), "r"(a2), "r"(a3), "r"(b0), "r"(b1), "f"(0.f));
}
__device__ __forceinline__ void mma1688_z(float (&d)[4], uint32_t a0, uint32_t a1, uint32_t b0) {
    asm volatile("mma.sync.aligned.m16n8k8.row.col.f32.bf16.bf16.f32 {%0,%1,%2,%3}, {%4,%5}, {%6}, {%7,%7,%7,%7};"
        : "=f"(d[0]), "=f"(d[1]), "=f"(d[2]), "=f"(d[3]) : "r"(a0), "r"(a1), "r"(b0), "f"(0.f));
}
template <int ACC>
__device__ __forceinline__ void wgmma_n32_rs(float (&d)[16], uint32_t a0, uint32_t a1, uint32_t a2, uint32_t a3, uint64_t desc) {
    asm volatile("wgmma.mma_async.sync.aligned.m64n32k16.f32.bf16.bf16 {%0,%1,%2,%3,%4,%5,%6,%7,%8,%9,%10,%11,%12,%13,%14,%15}, {%16,%17,%18,%19}, %20, %21, 1, 1, 0;"
        : "+f"(d[0]), "+f"(d[1]), "+f"(d[2]), "+f"(d[3]), "+f"(d[4]), "+f"(d[5]), "+f"(d[6]), "+f"(d[7]),
          "+f"(d[8]), "+f"(d[9]), "+f"(d[10]), "+f"(d[11]), "+f"(d[12]), "+f"(d[13]), "+f"(d[14]), "+f"(d[15])
        : "r"(a0), "r"(a1), "r"(a2), "r"(a3), "l"(desc), "n"(ACC));
}
__device__ __forceinline__ void wgmma_n32_ss(float (&d)[16], uint64_t da, uint64_t db) {
    asm volatile("wgmma.mma_async.sync.aligned.m64n32k16.f32.bf16.bf16 {%0,%1,%2,%3,%4,%5,%6,%7,%8,%9,%10,%11,%12,%13,%14,%15}, %16, %17, 1, 1, 1, 0, 0;"
        : "+f"(d[0]), "+f"(d[1]), "+f"(d[2]), "+f"(d[3]), "+f"(d[4]), "+f"(d[5]), "+f"(d[6]), "+f"(d[7]),
          "+f"(d[8]), "+f"(d[9]), "+f"(d[10]), "+f"(d[11]), "+f"(d[12]), "+f"(d[13]), "+f"(d[14]), "+f"(d[15])
        : "l"(da), "l"(db));
}
__device__ __forceinline__ void wg_fence() { asm volatile("wgmma.fence.sync.aligned;" ::: "memory"); }
__device__ __forceinline__ void wg_commit() { asm volatile("wgmma.commit_group.sync.aligned;" ::: "memory"); }
__device__ __forceinline__ void wg_wait0() { asm volatile("wgmma.wait_group.sync.aligned 0;" ::: "memory"); }
__device__ __forceinline__ void cluster_sync() { asm volatile("barrier.cluster.arrive.aligned;\nbarrier.cluster.wait.aligned;" ::: "memory"); }

#define STAMP(s, i) do {} while (0)

constexpr int XT_BYTES = 36864;
constexpr int O_XT = 0;
constexpr int O_AS = 3 * XT_BYTES;
constexpr int O_MF = O_AS + 16384;
constexpr int O_QM = O_MF + 9216;
constexpr int O_KM = O_QM + 1024;
constexpr int O_QKX = O_KM + 1024;
constexpr int O_VX = O_QKX + 16384;
constexpr int O_VM = O_VX + 24576;
constexpr int O_SC = O_VM + 6144;
constexpr int O_OF = O_SC + 2560;
constexpr int O_SXO = O_OF + 2048;
constexpr int O_SXS = O_SXO + 5120;
constexpr int O_SXR = O_SXS + 5120;
constexpr int O_OXS = O_SXR + 5120;
constexpr int O_MISC = O_OXS + 4096;
constexpr int O_BAR = O_MISC + 64;
constexpr int CHAIN_SMEM = O_BAR + 128 + 1024;
constexpr float SM_SCALE = 0.08838834764831845f * 1.4426950408889634f;

__global__ void __cluster_dims__(3, 1, 1) __launch_bounds__(384, 1)
chain_kernel(const __grid_constant__ CUtensorMap tm_x,
             const __nv_bfloat16* __restrict__ x, const __nv_bfloat16* __restrict__ mem0,
             const __nv_bfloat16* __restrict__ Wq, const __nv_bfloat16* __restrict__ Wk,
             const __nv_bfloat16* __restrict__ Wv, const __nv_bfloat16* __restrict__ Wo) {
    extern __shared__ uint8_t smem_raw[];
    const uint32_t sb = (smem_u32(smem_raw) + 1023u) & ~1023u;
    const int tid = threadIdx.x, lane = tid & 31, g = lane >> 2, t = lane & 3;
    const int wg = tid >> 7, w = (tid >> 5) & 3;
    const int h = blockIdx.x / 3, r = blockIdx.x - 3 * h;
    const uint32_t bars = sb + O_BAR;

    if (tid == 0) {
        for (int i = 0; i < 9; i++) mbar_init(bars + 8 * i, 1);
        asm volatile("fence.mbarrier_init.release.cluster;" ::: "memory");
    }
    if (blockIdx.x == 0) {
        for (int i = tid; i < NSEG * 4 * 8; i += 384) g_flag[i] = 0;
        __threadfence();
    }
    __syncthreads();
    cluster_sync();
    asm volatile("griddepcontrol.launch_dependents;" ::: "memory");

    if (wg < 2) {
        asm volatile("setmaxnreg.inc.sync.aligned.u32 176;");
        uint32_t a[144];
        {
            const __nv_bfloat16* W = (r < 2) ? (wg == 0 ? Wq : Wk) : Wv;
            const int col = h * 128 + ((r < 2) ? 64 * r : 64 * wg) + 16 * w + 2 * g;
            const __nv_bfloat16* p = W + (size_t)(2 * t) * HD + col;
#pragma unroll
            for (int kk = 0; kk < 36; kk++) {
                a[4 * kk + 0] = ldg_nc32(p + (size_t)(16 * kk + 0) * HD);
                a[4 * kk + 1] = ldg_nc32(p + (size_t)(16 * kk + 1) * HD);
                a[4 * kk + 2] = ldg_nc32(p + (size_t)(16 * kk + 8) * HD);
                a[4 * kk + 3] = ldg_nc32(p + (size_t)(16 * kk + 9) * HD);
            }
#pragma unroll
            for (int kk = 0; kk < 72; kk++) {
                uint32_t w0 = a[2 * kk], w1 = a[2 * kk + 1];
                a[2 * kk] = __byte_perm(w0, w1, 0x5410);
                a[2 * kk + 1] = __byte_perm(w0, w1, 0x7632);
            }
            float s0 = 0.f, s1 = 0.f;
#pragma unroll
            for (int kk = 0; kk < 72; kk++) {
                s0 += fabsf(__uint_as_float(a[2 * kk] << 16)) + fabsf(__uint_as_float(a[2 * kk] & 0xffff0000u));
                s1 += fabsf(__uint_as_float(a[2 * kk + 1] << 16)) + fabsf(__uint_as_float(a[2 * kk + 1] & 0xffff0000u));
            }
            s0 += __shfl_xor_sync(~0u, s0, 1); s0 += __shfl_xor_sync(~0u, s0, 2);
            s1 += __shfl_xor_sync(~0u, s1, 1); s1 += __shfl_xor_sync(~0u, s1, 2);
            uint32_t mx = __reduce_max_sync(~0u, __float_as_uint(fmaxf(s0, s1)));
            if (lane == 0) sts32(sb + O_MISC + 32 + 4 * (wg * 4 + w), mx);
            bar_arrive(7, 384);
            const uint32_t as = sb + O_AS + wg * 8192 + (16 * w + g) * 128 + t * 4;
#pragma unroll
            for (int kk = 0; kk < 4; kk++) {
                sts32(as + (((2 * kk) ^ g) << 4), a[128 + 4 * kk]);
                sts32(as + 1024 + (((2 * kk) ^ g) << 4), a[128 + 4 * kk + 1]);
                sts32(as + (((2 * kk + 1) ^ g) << 4), a[128 + 4 * kk + 2]);
                sts32(as + 1024 + (((2 * kk + 1) ^ g) << 4), a[128 + 4 * kk + 3]);
            }
            fence_async_smem();
            bar_sync(1, 256);
        }

#pragma unroll 1
        for (int s = -1; s < NSEG; s++) {
            if (s >= 0) {
                float c0[4], c1[4];
                {
                    const uint32_t as = sb + O_AS + wg * 8192 + (16 * w + (lane & 15)) * 128;
#pragma unroll
                    for (int kk = 0; kk < 4; kk++) {
                        const uint4 v = ldsm4(as + (((2 * kk + (lane >> 4)) ^ (lane & 7)) << 4));
                        a[128 + 4 * kk] = v.x; a[128 + 4 * kk + 1] = v.y; a[128 + 4 * kk + 2] = v.z; a[128 + 4 * kk + 3] = v.w;
                    }
                }
#pragma unroll
                for (int tau = 0; tau < 3; tau++) {
                    bar_sync(2 + tau, 384);
                    if (tau == 0 && wg == 0 && w == 0) STAMP(s, 0);
                    const uint32_t mf = sb + O_MF + tau * 3072 + lane * 16;
#pragma unroll
                    for (int c = 0; c < 6; c++) {
                        uint4 b = lds128(mf + c * 512);
                        const int k0 = 12 * tau + (c < 4 ? c : 8 + 2 * (c - 4));
                        const int k1 = 12 * tau + (c < 4 ? 4 + c : 9 + 2 * (c - 4));
                        if (tau == 0 && c == 0) {
                            mma16816_z(c0, a[4 * k0], a[4 * k0 + 1], a[4 * k0 + 2], a[4 * k0 + 3], b.x, b.y);
                            mma16816_z(c1, a[4 * k1], a[4 * k1 + 1], a[4 * k1 + 2], a[4 * k1 + 3], b.z, b.w);
                        } else {
                            mma16816(c0, a[4 * k0], a[4 * k0 + 1], a[4 * k0 + 2], a[4 * k0 + 3], b.x, b.y);
                            mma16816(c1, a[4 * k1], a[4 * k1 + 1], a[4 * k1 + 2], a[4 * k1 + 3], b.z, b.w);
                        }
                    }
                }
                const float inv = __uint_as_float(lds32(sb + O_MISC));
                const uint32_t X0 = pack_bf16((c0[0] + c1[0]) * inv, (c0[1] + c1[1]) * inv);
                const uint32_t X1 = pack_bf16((c0[2] + c1[2]) * inv, (c0[3] + c1[3]) * inv);
                if (wg == 0 && w == 0) STAMP(s, 1);
                if (r < 2) {
                    stsm2t(sb + O_QM + wg * 1024 + w * 256 + (lane & 15) * 16, X0, X1);
                    bar_sync(1, 256);
                    const int n = wg * 4 + w;
                    if (n < 5) {
                        const uint32_t kb = (n == 0) ? (sb + O_KM) : (sb + O_QKX + (s & 1) * 8192 + 4096 + (n - 1) * 1024);
                        uint4 q0 = ldsm4(sb + O_QM + lane * 16), k0 = ldsm4(kb + lane * 16);
                        uint4 q1 = ldsm4(sb + O_QM + 512 + lane * 16), k1 = ldsm4(kb + 512 + lane * 16);
                        float s0[4], s1[4];
                        mma16816_z(s0, q0.x, 0u, q0.y, 0u, k0.x, k0.y);
                        mma16816_z(s1, q0.z, 0u, q0.w, 0u, k0.z, k0.w);
                        mma16816(s0, q1.x, 0u, q1.y, 0u, k1.x, k1.y);
                        mma16816(s1, q1.z, 0u, q1.w, 0u, k1.z, k1.w);
                        const uint32_t v0 = __float_as_uint(s0[0] + s1[0]), v1 = __float_as_uint(s0[1] + s1[1]);
                        const uint32_t dst = sb + O_SC + r * 1280 + n * 256 + lane * 8;
                        st_async64(mapa(dst, 2), v0, v1, mapa(bars + 8 * 7, 2));
                        st_async64(mapa(dst, r ^ 1), v0, v1, mapa(bars + 8 * 7, r ^ 1));
                        st_async64(mapa(dst, r), v0, v1, mapa(bars + 8 * 7, r));
                    }
                } else {
                    const int eb = wg * 4 + w;
                    const uint32_t dst = sb + O_VM + (s % 3) * 2048 + (eb >> 1) * 512 + lane * 16 + (eb & 1) * 8;
                    st_async64(mapa(dst, 0), X0, X1, mapa(bars + 8 * 8, 0));
                    st_async64(mapa(dst, 1), X0, X1, mapa(bars + 8 * 8, 1));
                    st_async64(mapa(dst, 2), X0, X1, mapa(bars + 8 * 8, 2));
                }
                if (wg == 0 && w == 0) STAMP(s, 2);
            }
            if (s < NSEG - 1) {
                const int j = s + 1, slot = j % 3;
                mbar_wait(bars + 8 * slot, (j / 3) & 1);
                const uint64_t desc0 = (uint64_t)(((sb + O_XT + slot * XT_BYTES) & 0x3FFFF) >> 4) | (1ull << 16) | (64ull << 32) | (1ull << 62);
                float d[16];
                wg_fence();
#pragma unroll
                for (int kk = 0; kk < XCHUNK1; kk++) {
                    const uint64_t desc = desc0 + (uint64_t)(((kk >> 2) * 4096 + (kk & 3) * 32) >> 4);
                    if (kk == 0) wgmma_n32_rs<0>(d, a[0], a[1], a[2], a[3], desc);
                    else wgmma_n32_rs<1>(d, a[4 * kk], a[4 * kk + 1], a[4 * kk + 2], a[4 * kk + 3], desc);
                }
                wg_commit();
                if (s >= 0) bar_sync(5, 384);
#pragma unroll
                for (int kk = XCHUNK1; kk < 36; kk++) {
                    const uint64_t desc = desc0 + (uint64_t)(((kk >> 2) * 4096 + (kk & 3) * 32) >> 4);
                    if (kk < 32) wgmma_n32_rs<1>(d, a[4 * kk], a[4 * kk + 1], a[4 * kk + 2], a[4 * kk + 3], desc);
                    else wgmma_n32_ss(d, (uint64_t)(((sb + O_AS + wg * 8192 + (kk - 32) * 32) & 0x3FFFF) >> 4) | (1ull << 16) | (64ull << 32) | (1ull << 62), desc);
                }
                wg_commit();
                wg_wait0();
                if (wg == 0 && w == 0) STAMP(s, 3);
                if (r < 2) {
                    const uint32_t base = sb + O_QKX + (j & 1) * 8192 + wg * 4096 + ((lane >> 4) & 1) * 1024 + (2 * w + ((lane >> 3) & 1)) * 128 + (lane & 7) * 16;
                    stsm4t(base, pack_bf16(d[0], d[1]), pack_bf16(d[2], d[3]), pack_bf16(d[4], d[5]), pack_bf16(d[6], d[7]));
                    stsm4t(base + 2048, pack_bf16(d[8], d[9]), pack_bf16(d[10], d[11]), pack_bf16(d[12], d[13]), pack_bf16(d[14], d[15]));
                } else {
                    const uint32_t vx = sb + O_VX + slot * 8192;
                    const uint32_t base = vx + (wg * 4 + w) * 1024 + lane * 16;
                    sts128(base, pack_bf16(d[0], d[1]), pack_bf16(d[4], d[5]), pack_bf16(d[8], d[9]), pack_bf16(d[12], d[13]));
                    sts128(base + 512, pack_bf16(d[2], d[3]), pack_bf16(d[6], d[7]), pack_bf16(d[10], d[11]), pack_bf16(d[14], d[15]));
                    fence_async_smem();
                    bar_sync(1, 256);
                    if (tid == 0) {
                        bulk_s2c(mapa(vx, 0), vx, 8192, mapa(bars + 8 * (3 + (j & 1)), 0));
                        bulk_s2c(mapa(vx, 1), vx, 8192, mapa(bars + 8 * (3 + (j & 1)), 1));
                    }
                    __syncwarp();
                }
                if (wg == 0 && w == 0) STAMP(s, 4);
            }
        }
    } else {
        asm volatile("setmaxnreg.dec.sync.aligned.u32 152;");
        const int c = w, t2 = tid - 256;
        if (t2 == 0) {
#pragma unroll 1
            for (int j = 0; j < 2; j++) {
                mbar_expect(bars + 8 * j, XT_BYTES);
#pragma unroll
                for (int b = 0; b < 3; b++)
                    asm volatile("cp.async.bulk.tensor.2d.shared::cluster.global.mbarrier::complete_tx::bytes.multicast::cluster [%0], [%1, {%3, %4}], [%2], %5;"
                        :: "r"(sb + O_XT + j * XT_BYTES + (3 * r + b) * 4096), "l"(&tm_x), "r"(bars + 8 * j), "r"((3 * r + b) * 64), "r"(j * 32), "h"((unsigned short)7) : "memory");
            }
            mbar_expect(bars + 8 * 7, 2560);
            mbar_expect(bars + 8 * 8, 2048);
            if (r < 2) mbar_expect(bars + 8 * 3, 8192);
        }
        __syncwarp();
#pragma unroll
        for (int i = 0; i < 4; i++) g_acc[blockIdx.x * 512 + i * 128 + t2] = make_uint4(0, 0, 0, 0);
        uint32_t xm = 0;
        {
            const uint4* xp = reinterpret_cast<const uint4*>(x) + blockIdx.x * 1536 + t2;
#pragma unroll
            for (int i = 0; i < 12; i++) {
                uint4 v = __ldg(xp + i * 128);
                xm = __vmaxu2(xm, __vmaxu2(__vmaxu2(v.x & 0x7fff7fffu, v.y & 0x7fff7fffu), __vmaxu2(v.z & 0x7fff7fffu, v.w & 0x7fff7fffu)));
            }
            xm = __reduce_max_sync(~0u, max(xm << 16, xm & 0xffff0000u));
        }
        uint32_t mmax = 0;
#pragma unroll
        for (int tau = 0; tau < 3; tau++) {
            uint32_t v[6];
#pragma unroll
            for (int i = 0; i < 3; i++) {
                const uint32_t* p = reinterpret_cast<const uint32_t*>(mem0 + g * DM + 16 * (12 * tau + 4 * i + c) + 2 * t);
                v[2 * i] = __ldg(p); v[2 * i + 1] = __ldg(p + 4);
                mmax = __vmaxu2(mmax, __vmaxu2(v[2 * i] & 0x7fff7fffu, v[2 * i + 1] & 0x7fff7fffu));
            }
            sts128(sb + O_MF + tau * 3072 + c * 512 + lane * 16, v[0], v[1], v[2], v[3]);
            sts64(sb + O_MF + tau * 3072 + 2048 + (c >> 1) * 512 + lane * 16 + (c & 1) * 8, v[4], v[5]);
        }
        if (t2 == 0) sts32(sb + O_MISC, __float_as_uint(1.0f));
        bar_arrive(2, 384); bar_arrive(3, 384); bar_arrive(4, 384);

        uint32_t a[96];
        {
            const __nv_bfloat16* p = Wo + (size_t)(h * 128 + 4 * t) * DM + 192 * r + 16 * c + 2 * g;
#pragma unroll
            for (int i = 0; i < 3; i++)
#pragma unroll
                for (int eb = 0; eb < 8; eb++)
#pragma unroll
                    for (int j = 0; j < 4; j++) a[(i * 8 + eb) * 4 + j] = ldg_nc32(p + (16 * eb + j) * DM + 64 * i);
#pragma unroll
            for (int kk = 0; kk < 48; kk++) {
                uint32_t w0 = a[2 * kk], w1 = a[2 * kk + 1];
                a[2 * kk] = __byte_perm(w0, w1, 0x5410);
                a[2 * kk + 1] = __byte_perm(w0, w1, 0x7632);
            }
        }
        float G, xmax;
        {
            float wmax = 0.f;
#pragma unroll
            for (int i = 0; i < 3; i++) {
                float s0 = 0.f, s1 = 0.f;
#pragma unroll
                for (int kk = 16 * i; kk < 16 * i + 16; kk++) {
                    s0 += fabsf(__uint_as_float(a[2 * kk] << 16)) + fabsf(__uint_as_float(a[2 * kk] & 0xffff0000u));
                    s1 += fabsf(__uint_as_float(a[2 * kk + 1] << 16)) + fabsf(__uint_as_float(a[2 * kk + 1] & 0xffff0000u));
                }
                s0 += __shfl_xor_sync(~0u, s0, 1); s0 += __shfl_xor_sync(~0u, s0, 2);
                s1 += __shfl_xor_sync(~0u, s1, 1); s1 += __shfl_xor_sync(~0u, s1, 2);
                wmax = fmaxf(wmax, fmaxf(s0, s1));
            }
            uint32_t wm = __reduce_max_sync(~0u, __float_as_uint(wmax));
            if (lane == 0) { sts32(sb + O_OF + 4 * c, wm); sts32(sb + O_OF + 16 + 4 * c, xm); }
            __threadfence();
            bar_sync(7, 384);
            if (t2 == 0) {
                uint32_t w1 = 0, x1 = 0, v1 = 0;
                for (int i = 0; i < 4; i++) { w1 = max(w1, lds32(sb + O_OF + 4 * i)); x1 = max(x1, lds32(sb + O_OF + 16 + 4 * i)); }
                for (int i = 0; i < 8; i++) v1 = max(v1, lds32(sb + O_MISC + 32 + 4 * i));
                if (r < 2) v1 = 0;
                *reinterpret_cast<uint4*>(&g_norm[blockIdx.x * 4]) = make_uint4(w1, v1, x1, 0);
                __threadfence();
                unsigned old = atomicAdd(&g_gridbar, 1u);
                unsigned target = (old / 96u + 1u) * 96u, v; int sp = 0;
                do { asm volatile("ld.acquire.gpu.global.u32 %0, [%1];" : "=r"(v) : "l"(&g_gridbar) : "memory"); if (++sp > 4000000) __trap(); } while ((int)(v - target) < 0);
            }
            bar_sync(6, 128);
            uint4 n0 = ldg_relaxed128(&g_norm[lane * 4]), n1 = ldg_relaxed128(&g_norm[(lane + 32) * 4]), n2 = ldg_relaxed128(&g_norm[(lane + 64) * 4]);
            const float w1 = __uint_as_float(__reduce_max_sync(~0u, max(n0.x, max(n1.x, n2.x))));
            const float v1 = __uint_as_float(__reduce_max_sync(~0u, max(n0.y, max(n1.y, n2.y))));
            xmax = __uint_as_float(__reduce_max_sync(~0u, max(n0.z, max(n1.z, n2.z))));
            G = 36.f * w1 * v1;
        }
        float inv_prev = 1.0f;

#pragma unroll 1
        for (int s = 0; s < NSEG; s++) {
            {
                uint32_t mm = __reduce_max_sync(~0u, max(mmax << 16, mmax & 0xffff0000u));
                if (lane == 0) sts32(sb + O_MISC + 16 + 4 * c, mm);
            }
            if (t2 == 0) {
                if (s + 2 < NSEG) {
                    const int j = s + 2, slot = j % 3;
                    mbar_expect(bars + 8 * slot, XT_BYTES);
#pragma unroll
                    for (int b = 0; b < 3; b++)
                        asm volatile("cp.async.bulk.tensor.2d.shared::cluster.global.mbarrier::complete_tx::bytes.multicast::cluster [%0], [%1, {%3, %4}], [%2], %5;"
                            :: "r"(sb + O_XT + slot * XT_BYTES + (3 * r + b) * 4096), "l"(&tm_x), "r"(bars + 8 * slot), "r"((3 * r + b) * 64), "r"(j * 32), "h"((unsigned short)7) : "memory");
                }
                if (r < 2) {
                    if (s + 1 < NSEG) mbar_expect(bars + 8 * (3 + ((s + 1) & 1)), 8192);
                    if (s >= 2) {
                        asm volatile("cp.async.bulk.wait_group 0;" ::: "memory");
                        asm volatile("fence.proxy.async.global;" ::: "memory");
                        asm volatile("red.release.gpu.global.add.u32 [%0], 1;" :: "l"(&g_flag[((s - 2) * 4 + (h >> 3)) * 8]) : "memory");
                    }
                }
            }
            __syncwarp();
            if (c == 0) STAMP(s, 5);
            mbar_wait(bars + 8 * 7, s & 1);
            if (c == 0) STAMP(s, 6);
            unsigned t_red = 0;
            if (s < NSEG - 1) {
                float p[10];
#pragma unroll
                for (int n = 0; n < 5; n++) {
                    float2 u = lds64f(sb + O_SC + n * 256 + lane * 8), v = lds64f(sb + O_SC + 1280 + n * 256 + lane * 8);
                    p[2 * n] = u.x + v.x; p[2 * n + 1] = u.y + v.y;
                }
                float mx = fmaxf(fmaxf(fmaxf(p[0], p[1]), fmaxf(p[2], p[3])), fmaxf(fmaxf(p[4], p[5]), fmaxf(p[6], p[7])));
                mx = fmaxf(mx, fmaxf(p[8], p[9]));
                mx = fmaxf(mx, __shfl_xor_sync(~0u, mx, 1));
                mx = fmaxf(mx, __shfl_xor_sync(~0u, mx, 2));
                const float mo = mx * SM_SCALE;
#pragma unroll
                for (int i = 0; i < 10; i++) p[i] = ex2(fmaf(p[i], SM_SCALE, -mo));
                uint32_t P[5];
#pragma unroll
                for (int n = 0; n < 5; n++) P[n] = pack_bf16(p[2 * n], p[2 * n + 1]);
                float sum = ((p[0] + p[1]) + (p[2] + p[3])) + ((p[4] + p[5]) + (p[6] + p[7])) + (p[8] + p[9]);
                mbar_wait(bars + 8 * 8, s & 1);
                if (r < 2) mbar_wait(bars + 8 * (3 + (s & 1)), (s >> 1) & 1);
                if (c == 0) STAMP(s, 7);
                const uint4 vm = lds128(sb + O_VM + (s % 3) * 2048 + c * 512 + lane * 16);
                const uint32_t vxb = sb + O_VX + (s % 3) * 8192 + c * 2048 + lane * 16;
                float o[4][4];
                mma1688_z(o[0], P[0], 0u, vm.x); mma1688_z(o[1], P[0], 0u, vm.y);
                mma1688_z(o[2], P[0], 0u, vm.z); mma1688_z(o[3], P[0], 0u, vm.w);
#pragma unroll
                for (int q = 0; q < 4; q++) {
                    const uint4 b = lds128(vxb + q * 512);
                    mma16816(o[q], P[1], 0u, P[2], 0u, b.x, b.y);
                    mma16816(o[q], P[3], 0u, P[4], 0u, b.z, b.w);
                }
                sum += __shfl_xor_sync(~0u, sum, 1);
                sum += __shfl_xor_sync(~0u, sum, 2);
                const float rs = __fdividef(1.0f, sum);
                sts128(sb + O_OF + c * 512 + lane * 16, pack_bf16(o[0][0] * rs, o[1][0] * rs), pack_bf16(o[0][1] * rs, o[1][1] * rs),
                       pack_bf16(o[2][0] * rs, o[3][0] * rs), pack_bf16(o[2][1] * rs, o[3][1] * rs));
                bar_sync(6, 128);
                if (t2 == 0) { mbar_expect(bars + 8 * 7, 2560); mbar_expect(bars + 8 * 8, 2048); }
                float m0[3][4];
#pragma unroll
                for (int q = 0; q < 4; q++) {
                    const uint4 b = lds128(sb + O_OF + q * 512 + lane * 16);
#pragma unroll
                    for (int i = 0; i < 3; i++) {
                        const int k0 = (i * 8 + 2 * q) * 4;
                        if (q == 0) mma16816_z(m0[i], a[k0], a[k0 + 1], a[k0 + 2], a[k0 + 3], b.x, b.y);
                        else mma16816(m0[i], a[k0], a[k0 + 1], a[k0 + 2], a[k0 + 3], b.x, b.y);
                    }
#pragma unroll
                    for (int i = 0; i < 3; i++) {
                        const int k1 = (i * 8 + 2 * q + 1) * 4;
                        mma16816(m0[i], a[k1], a[k1 + 1], a[k1 + 2], a[k1 + 3], b.z, b.w);
                    }
                }
                const uint4 mm = lds128(sb + O_MISC + 16);
                const float bound = G * fmaxf(xmax, __uint_as_float(max(max(mm.x, mm.y), max(mm.z, mm.w))) * inv_prev);
                int k = 15 - ((int)((__float_as_uint(bound) >> 23) & 255u) - 126);
                k = min(max(k, -120), 120);
                const float sig = __uint_as_float((uint32_t)(127 + k) << 23);
                inv_prev = __uint_as_float((uint32_t)(127 - k) << 23);
                char* base = reinterpret_cast<char*>(g_acc) + (s >> 1) * 24576 + (s & 1) * 128
                           + ((r * 4 + c) * 8 + (g >> 2) * 2 + (t >> 1)) * 256 + ((t & 1) * 4 + (g & 3)) * 16;
                asm volatile("red.relaxed.gpu.global.add.noftz.v4.f16x2 [%0], {%1,%2,%3,%4};" :: "l"(base),
                    "r"(pack_f16(m0[0][0] * sig, m0[0][2] * sig)), "r"(pack_f16(m0[1][0] * sig, m0[1][2] * sig)), "r"(pack_f16(m0[2][0] * sig, m0[2][2] * sig)), "r"(0x3c00u) : "memory");
                asm volatile("red.relaxed.gpu.global.add.noftz.v4.f16x2 [%0], {%1,%2,%3,%4};" :: "l"(base + 1024),
                    "r"(pack_f16(m0[0][1] * sig, m0[0][3] * sig)), "r"(pack_f16(m0[1][1] * sig, m0[1][3] * sig)), "r"(pack_f16(m0[2][1] * sig, m0[2][3] * sig)), "r"(0x3c00u) : "memory");
                t_red = clk();
                bar_arrive(5, 384);
                if (t2 == 0) sts32(sb + O_MISC, __float_as_uint(inv_prev));
                if (c == 0) STAMP(s, 8);
            } else {
                mbar_wait(bars + 8 * 8, s & 1);
                if (r < 2) mbar_wait(bars + 8 * (3 + (s & 1)), (s >> 1) & 1);
                bar_sync(6, 128);
            }

            if (r < 2) {
#pragma unroll 1
                for (int pass = 0; pass < 2; pass++) {
                    const int sx = s - 1 + pass;
                    if (sx >= 0) {
                        mbar_wait(bars + 8 * (5 + (sx & 1)), (sx >> 1) & 1);
                        float p[5][4];
                        const uint32_t so = sb + O_SXO + (sx & 1) * 2560 + lane * 16, sr = sb + O_SXR + (sx & 1) * 2560 + lane * 16;
                        const int q0 = 16 * r + g - 2 * t + 8;
#pragma unroll
                        for (int n = 0; n < 5; n++) {
                            if (n < 3 || r == 1) {
                                const float4 u = lds128f(so + n * 512), v = lds128f(sr + n * 512);
                                p[n][0] = u.x + v.x; p[n][1] = u.y + v.y; p[n][2] = u.z + v.z; p[n][3] = u.w + v.w;
                            } else { p[n][0] = p[n][1] = p[n][2] = p[n][3] = 0.f; }
                            if (n > 0) {
                                if (8 * n > q0) p[n][0] = -INFINITY;
                                if (8 * n + 1 > q0) p[n][1] = -INFINITY;
                                if (8 * n > q0 + 8) p[n][2] = -INFINITY;
                                if (8 * n + 1 > q0 + 8) p[n][3] = -INFINITY;
                            }
                        }
                        float mxa = fmaxf(p[0][0], p[0][1]), mxb = fmaxf(p[0][2], p[0][3]);
#pragma unroll
                        for (int n = 1; n < 5; n++) { mxa = fmaxf(mxa, fmaxf(p[n][0], p[n][1])); mxb = fmaxf(mxb, fmaxf(p[n][2], p[n][3])); }
                        mxa = fmaxf(mxa, __shfl_xor_sync(~0u, mxa, 1)); mxb = fmaxf(mxb, __shfl_xor_sync(~0u, mxb, 1));
                        mxa = fmaxf(mxa, __shfl_xor_sync(~0u, mxa, 2)); mxb = fmaxf(mxb, __shfl_xor_sync(~0u, mxb, 2));
                        mxa *= SM_SCALE; mxb *= SM_SCALE;
                        float sa = 0.f, sbm = 0.f;
                        uint32_t Pa[5], Pb[5];
#pragma unroll
                        for (int n = 0; n < 5; n++) {
                            const float e0 = ex2(fmaf(p[n][0], SM_SCALE, -mxa)), e1 = ex2(fmaf(p[n][1], SM_SCALE, -mxa));
                            const float e2 = ex2(fmaf(p[n][2], SM_SCALE, -mxb)), e3 = ex2(fmaf(p[n][3], SM_SCALE, -mxb));
                            sa += e0 + e1; sbm += e2 + e3;
                            Pa[n] = pack_bf16(e0, e1); Pb[n] = pack_bf16(e2, e3);
                        }
                        sa += __shfl_xor_sync(~0u, sa, 1); sbm += __shfl_xor_sync(~0u, sbm, 1);
                        sa += __shfl_xor_sync(~0u, sa, 2); sbm += __shfl_xor_sync(~0u, sbm, 2);
                        const float ra = __fdividef(1.0f, sa), rb = __fdividef(1.0f, sbm);
                        const uint4 vm = lds128(sb + O_VM + (sx % 3) * 2048 + c * 512 + lane * 16);
                        const uint32_t vxb = sb + O_VX + (sx % 3) * 8192 + c * 2048 + lane * 16;
#pragma unroll
                        for (int e2 = 0; e2 < 2; e2++) {
                            float oa[4], ob[4];
                            mma1688_z(oa, Pa[0], Pb[0], e2 ? vm.z : vm.x);
                            mma1688_z(ob, Pa[0], Pb[0], e2 ? vm.w : vm.y);
                            const uint4 ba = lds128(vxb + e2 * 1024), bb = lds128(vxb + e2 * 1024 + 512);
                            mma16816(oa, Pa[1], Pb[1], Pa[2], Pb[2], ba.x, ba.y);
                            mma16816(ob, Pa[1], Pb[1], Pa[2], Pb[2], bb.x, bb.y);
                            mma16816(oa, Pa[3], Pb[3], Pa[4], Pb[4], ba.z, ba.w);
                            mma16816(ob, Pa[3], Pb[3], Pa[4], Pb[4], bb.z, bb.w);
                            const int ch = ((2 * c + e2) & 3) * 2 + (t >> 1);
                            const uint32_t dst = sb + O_OXS + (c >> 1) * 2048 + g * 128 + ((ch ^ g) * 16) + (t & 1) * 8;
                            sts64(dst, pack_bf16(oa[0] * ra, ob[0] * ra), pack_bf16(oa[1] * ra, ob[1] * ra));
                            sts64(dst + 1024, pack_bf16(oa[2] * rb, ob[2] * rb), pack_bf16(oa[3] * rb, ob[3] * rb));
                        }
                    }
                    if (pass == 0) {
#pragma unroll
                        for (int q = 0; q < 2; q++) {
                            const int pi = 2 * c + q;
                            const int mt = pi < 3 ? 0 : 1, n = pi < 3 ? pi : pi - 3;
                            const uint32_t qb = sb + O_QKX + (s & 1) * 8192 + (2 * mt + ((lane >> 3) & 1)) * 1024 + (lane >> 4) * 128 + (lane & 7) * 16;
                            const uint32_t kb = ((n == 0) ? (sb + O_KM) : (sb + O_QKX + (s & 1) * 8192 + 4096 + (n - 1) * 1024)) + lane * 16;
                            const uint4 k0 = ldsm4(kb), k1 = ldsm4(kb + 512);
                            float sc[4];
                            { const uint4 qa = ldsm4(qb); mma16816_z(sc, qa.x, qa.y, qa.z, qa.w, k0.x, k0.y); }
                            { const uint4 qa = ldsm4(qb + 256); mma16816(sc, qa.x, qa.y, qa.z, qa.w, k0.z, k0.w); }
                            { const uint4 qa = ldsm4(qb + 512); mma16816(sc, qa.x, qa.y, qa.z, qa.w, k1.x, k1.y); }
                            { const uint4 qa = ldsm4(qb + 768); mma16816(sc, qa.x, qa.y, qa.z, qa.w, k1.z, k1.w); }
                            const uint32_t dst = sb + ((mt == r) ? O_SXO : O_SXS) + (s & 1) * 2560 + n * 512 + lane * 16;
                            sts128f(dst, sc[0], sc[1], sc[2], sc[3]);
                        }
                    }
                    fence_async_smem();
                    bar_sync(6, 128);
                    if (s < NSEG - 1) break;
                    if (t2 == 0) {
                        if (pass == 0) {
                            mbar_expect(bars + 8 * (5 + (s & 1)), r == 0 ? 1536 : 2560);
                            bulk_s2c(mapa(sb + O_SXR + (s & 1) * 2560, r ^ 1), sb + O_SXS + (s & 1) * 2560, r == 0 ? 2560 : 1536, mapa(bars + 8 * (5 + (s & 1)), r ^ 1));
                        }
                        const size_t off = ((size_t)(h * 2) * SEQ + sx * 32 + 16 * r) * 8;
                        bulk_s2g(&g_ox[off], sb + O_OXS, 2048);
                        bulk_s2g(&g_ox[off + (size_t)SEQ * 8], sb + O_OXS + 2048, 2048);
                        asm volatile("cp.async.bulk.commit_group;" ::: "memory");
                        asm volatile("cp.async.bulk.wait_group 0;" ::: "memory");
                        asm volatile("fence.proxy.async.global;" ::: "memory");
                        asm volatile("red.release.gpu.global.add.u32 [%0], 1;" :: "l"(&g_flag[(sx * 4 + (h >> 3)) * 8]) : "memory");
                    }
                    bar_sync(6, 128);
                }
            }
            if (s < NSEG - 1) {
                if (c == 0) STAMP(s, 9);
                while (clk() - t_red < D_WAIT) {}
                const char* base = reinterpret_cast<const char*>(g_acc) + (s >> 1) * 24576 + (s & 1) * 128
                                 + (c * 8 + (g & 1) * 4 + (g >> 2)) * 256 + (((g >> 1) & 1) * 4 + t) * 16;
                uint4 v[6];
#pragma unroll
                for (int i = 0; i < 6; i++) v[i] = ldg_relaxed128(base + (i >> 1) * 8192 + (i & 1) * 512);
                if (r < 2 && t2 == 0) {
                    mbar_expect(bars + 8 * (5 + (s & 1)), r == 0 ? 1536 : 2560);
                    bulk_s2c(mapa(sb + O_SXR + (s & 1) * 2560, r ^ 1), sb + O_SXS + (s & 1) * 2560, r == 0 ? 2560 : 1536, mapa(bars + 8 * (5 + (s & 1)), r ^ 1));
                    if (s >= 1) {
                        const size_t off = ((size_t)(h * 2) * SEQ + (s - 1) * 32 + 16 * r) * 8;
                        bulk_s2g(&g_ox[off], sb + O_OXS, 2048);
                        bulk_s2g(&g_ox[off + (size_t)SEQ * 8], sb + O_OXS + 2048, 2048);
                        asm volatile("cp.async.bulk.commit_group;" ::: "memory");
                    }
                }
                __syncwarp();
                mmax = 0;
#pragma unroll
                for (int tau = 0; tau < 3; tau++) {
                    int sp = 0;
                    while (!__all_sync(~0u, v[2 * tau].w == 0x5000u && v[2 * tau + 1].w == 0x5000u)) {
                        v[2 * tau] = ldg_relaxed128(base + tau * 8192);
                        v[2 * tau + 1] = ldg_relaxed128(base + tau * 8192 + 512);
                        if (++sp > 2000000) __trap();
                    }
                    const uint32_t b0 = f16x2_to_bf16x2(v[2 * tau].x), b1 = f16x2_to_bf16x2(v[2 * tau + 1].x);
                    const uint32_t b2 = f16x2_to_bf16x2(v[2 * tau].y), b3 = f16x2_to_bf16x2(v[2 * tau + 1].y);
                    const uint32_t b4 = f16x2_to_bf16x2(v[2 * tau].z), b5 = f16x2_to_bf16x2(v[2 * tau + 1].z);
                    sts128(sb + O_MF + tau * 3072 + c * 512 + lane * 16, b0, b1, b2, b3);
                    sts64(sb + O_MF + tau * 3072 + 2048 + (c >> 1) * 512 + lane * 16 + (c & 1) * 8, b4, b5);
                    bar_arrive(2 + tau, 384);
                    mmax = __vmaxu2(mmax, __vmaxu2(__vmaxu2(b0 & 0x7fff7fffu, b1 & 0x7fff7fffu), __vmaxu2(b2 & 0x7fff7fffu, b3 & 0x7fff7fffu)));
                    mmax = __vmaxu2(mmax, __vmaxu2(b4 & 0x7fff7fffu, b5 & 0x7fff7fffu));
                }
            }
        }
    }
    cluster_sync();
}

__device__ float g_u[SEQ * 2 * DM];
__global__ void naive_gemm1(const __nv_bfloat16* x, const __nv_bfloat16* Bre, const __nv_bfloat16* Bim) {
    int p = blockIdx.x * 64 + threadIdx.x % 64, tk = blockIdx.y * 4 + threadIdx.x / 64;
    float sr = 0, si = 0;
    for (int d = 0; d < DM; d++) { float xv = __bfloat162float(x[tk * DM + d]); sr += xv * __bfloat162float(Bre[p * DM + d]); si += xv * __bfloat162float(Bim[p * DM + d]); }
    g_u[tk * 2 * DM + 2 * p] = sr; g_u[tk * 2 * DM + 2 * p + 1] = si;
}
__global__ void naive_scan(const __nv_bfloat16* Lre, const __nv_bfloat16* Lim, const __nv_bfloat16* logdt) {
    int p = blockIdx.x * 64 + threadIdx.x;
    float dt = __bfloat162float(__float2bfloat16(expf(__bfloat162float(logdt[p]))));
    float lr = __bfloat162float(Lre[p]), li = __bfloat162float(Lim[p]);
    float e = expf(dt * lr), br = e * cosf(dt * li), bi = e * sinf(dt * li);
    float den = lr * lr + li * li;
    float cr = ((br - 1.f) * lr + bi * li) / den, ci = (bi * lr - (br - 1.f) * li) / den;
    float hr = 0, hi = 0;
    for (int tk = 0; tk < SEQ; tk++) {
        float ur = g_u[tk * 2 * DM + 2 * p], ui = g_u[tk * 2 * DM + 2 * p + 1];
        float nr = br * hr - bi * hi + cr * ur - ci * ui, ni = br * hi + bi * hr + cr * ui + ci * ur;
        hr = nr; hi = ni;
        g_u[tk * 2 * DM + 2 * p] = hr; g_u[tk * 2 * DM + 2 * p + 1] = hi;
    }
}
__global__ void naive_gemm2(const __nv_bfloat16* x, const __nv_bfloat16* Cre, const __nv_bfloat16* Cim, const __nv_bfloat16* Dk, float* out) {
    int d = blockIdx.x * 64 + threadIdx.x % 64, tk = blockIdx.y * 4 + threadIdx.x / 64;
    float s = 0;
    for (int p = 0; p < DM; p++) s += g_u[tk * 2 * DM + 2 * p] * __bfloat162float(Cre[d * DM + p]) - g_u[tk * 2 * DM + 2 * p + 1] * __bfloat162float(Cim[d * DM + p]);
    out[tk * 1152 + d] = 2.f * s + __bfloat162float(__float2bfloat16(__bfloat162float(x[tk * DM + d]) * __bfloat162float(Dk[d])));
}
__global__ void naive_wo(const __nv_bfloat16* Wo, float* out) {
    int d = blockIdx.x * 64 + threadIdx.x % 64, tk = blockIdx.y * 4 + threadIdx.x / 64;
    const __nv_bfloat16* ox = reinterpret_cast<const __nv_bfloat16*>(g_ox);
    float s = 0;
    for (int k = 0; k < HD; k++) {
        int hh = k >> 6, e = k & 63;
        s += __bfloat162float(ox[((size_t)hh * SEQ + tk) * 64 + (((e >> 3) ^ (tk & 7)) << 3) + (e & 7)]) * __bfloat162float(Wo[k * DM + d]);
    }
    out[tk * 1152 + DM + d] = s;
}

typedef CUresult (*EncodeFn)(CUtensorMap*, CUtensorMapDataType, cuuint32_t, void*, const cuuint64_t*, const cuuint64_t*, const cuuint32_t*, const cuuint32_t*,
                             CUtensorMapInterleave, CUtensorMapSwizzle, CUtensorMapL2promotion, CUtensorMapFloatOOBfill);
}

extern "C" void kernel_launch(void* const* d_in, const int* in_sizes, int n_in, void* d_out, int out_size) {
    typedef const __nv_bfloat16* bp;
    bp Ax = (bp)d_in[0], Lre = (bp)d_in[1], Lim = (bp)d_in[2], Bre = (bp)d_in[3], Bim = (bp)d_in[4], Cre = (bp)d_in[5], Cim = (bp)d_in[6],
       logdt = (bp)d_in[7], Dk = (bp)d_in[8], Bx = (bp)d_in[9], mem0 = (bp)d_in[10], Wq = (bp)d_in[11], Wk = (bp)d_in[12], Wv = (bp)d_in[13], Wo = (bp)d_in[14];
    float* out = (float*)d_out;
    static EncodeFn enc = nullptr;
    if (!enc) {
        void* fn = nullptr; cudaDriverEntryPointQueryResult qr;
        cudaGetDriverEntryPoint("cuTensorMapEncodeTiled", &fn, cudaEnableDefault, &qr);
        enc = (EncodeFn)fn;
        cudaFuncSetAttribute(chain_kernel, cudaFuncAttributeMaxDynamicSharedMemorySize, CHAIN_SMEM);
    }
    CUtensorMap tm_x;
    {
        cuuint64_t gd[2] = {DM, SEQ}; cuuint64_t gs[1] = {DM * 2}; cuuint32_t bd[2] = {64, 32}; cuuint32_t es[2] = {1, 1};
        enc(&tm_x, CU_TENSOR_MAP_DATA_TYPE_BFLOAT16, 2, (void*)Bx, gd, gs, bd, es, CU_TENSOR_MAP_INTERLEAVE_NONE, CU_TENSOR_MAP_SWIZZLE_128B,
            CU_TENSOR_MAP_L2_PROMOTION_L2_128B, CU_TENSOR_MAP_FLOAT_OOB_FILL_NONE);
    }
    cudaStream_t st = cudaStreamPerThread;
    chain_kernel<<<96, 384, CHAIN_SMEM, st>>>(tm_x, Bx, mem0, Wq, Wk, Wv, Wo);
    naive_gemm1<<<dim3(9, 512), 256, 0, st>>>(Ax, Bre, Bim);
    naive_scan<<<9, 64, 0, st>>>(Lre, Lim, logdt);
    naive_gemm2<<<dim3(9, 512), 256, 0, st>>>(Ax, Cre, Cim, Dk, out);
    naive_wo<<<dim3(9, 512), 256, 0, st>>>(Wo, out);
}
```

```cpp
#include <cuda_runtime.h>
#include <cuda.h>
#include <cuda_bf16.h>
#include <cuda_fp16.h>
#include <stdint.h>

#define D_WAIT 700
#define XCHUNK1 14

namespace {

constexpr int DM = 576, NH = 32, SEQ = 2048, NSEG = 64, HD = 4096;

__device__ uint4 g_acc[32 * 96 * 16];
__device__ uint4 g_ox[NH * 2 * SEQ * 8];
__device__ unsigned g_flag[NSEG * 4 * 8];
__device__ unsigned g_gridbar;
__device__ float g_norm[96 * 4];

__device__ __forceinline__ uint32_t smem_u32(const void* p) { return (uint32_t)__cvta_generic_to_shared(p); }
__device__ __forceinline__ uint32_t mapa(uint32_t a, uint32_t r) { uint32_t o; asm("mapa.shared::cluster.u32 %0, %1, %2;" : "=r"(o) : "r"(a), "r"(r)); return o; }
__device__ __forceinline__ unsigned clk() { unsigned c; asm volatile("mov.u32 %0, %%clock;" : "=r"(c)); return c; }
__device__ __forceinline__ void mbar_init(uint32_t bar, uint32_t cnt) { asm volatile("mbarrier.init.shared::cta.b64 [%0], %1;" :: "r"(bar), "r"(cnt) : "memory"); }
__device__ __forceinline__ void mbar_expect(uint32_t bar, uint32_t bytes) { asm volatile("mbarrier.arrive.expect_tx.shared::cta.b64 _, [%0], %1;" :: "r"(bar), "r"(bytes) : "memory"); }
__device__ __forceinline__ void mbar_wait(uint32_t bar, uint32_t parity) {
    asm volatile("{\n.reg .pred p;\n.reg .u32 n;\nmov.u32 n, 0;\n"
                 "W_%=: mbarrier.try_wait.parity.shared::cta.b64 p, [%0], %1;\n@p bra D_%=;\n"
                 "add.u32 n, n, 1;\nsetp.lt.u32 p, n, 4000000;\n@p bra W_%=;\ntrap;\nD_%=:\n}" :: "r"(bar), "r"(parity) : "memory");
}
__device__ __forceinline__ void bar_sync(int id, int n) { asm volatile("bar.sync %0, %1;" :: "r"(id), "r"(n) : "memory"); }
__device__ __forceinline__ void bar_arrive(int id, int n) { asm volatile("bar.arrive %0, %1;" :: "r"(id), "r"(n) : "memory"); }
__device__ __forceinline__ void fence_async_smem() { asm volatile("fence.proxy.async.shared::cta;" ::: "memory"); }
__device__ __forceinline__ uint32_t pack_bf16(float lo, float hi) { uint32_t r; asm("cvt.rn.bf16x2.f32 %0, %1, %2;" : "=r"(r) : "f"(hi), "f"(lo)); return r; }
__device__ __forceinline__ uint32_t pack_f16(float lo, float hi) { uint32_t r; asm("cvt.rn.f16x2.f32 %0, %1, %2;" : "=r"(r) : "f"(hi), "f"(lo)); return r; }
__device__ __forceinline__ uint32_t f16x2_to_bf16x2(uint32_t v) { float2 f = __half22float2(*reinterpret_cast<__half2*>(&v)); return pack_bf16(f.x, f.y); }
__device__ __forceinline__ float ex2(float x) { float y; asm("ex2.approx.ftz.f32 %0, %1;" : "=f"(y) : "f"(x)); return y; }
__device__ __forceinline__ uint4 lds128(uint32_t a) { uint4 v; asm volatile("ld.shared.v4.u32 {%0,%1,%2,%3}, [%4];" : "=r"(v.x), "=r"(v.y), "=r"(v.z), "=r"(v.w) : "r"(a) : "memory"); return v; }
__device__ __forceinline__ float4 lds128f(uint32_t a) { float4 v; asm volatile("ld.shared.v4.f32 {%0,%1,%2,%3}, [%4];" : "=f"(v.x), "=f"(v.y), "=f"(v.z), "=f"(v.w) : "r"(a) : "memory"); return v; }
__device__ __forceinline__ float2 lds64f(uint32_t a) { float2 v; asm volatile("ld.shared.v2.f32 {%0,%1}, [%2];" : "=f"(v.x), "=f"(v.y) : "r"(a) : "memory"); return v; }
__device__ __forceinline__ uint32_t lds32(uint32_t a) { uint32_t v; asm volatile("ld.shared.u32 %0, [%1];" : "=r"(v) : "r"(a) : "memory"); return v; }
__device__ __forceinline__ void sts128(uint32_t a, uint32_t x, uint32_t y, uint32_t z, uint32_t w) { asm volatile("st.shared.v4.u32 [%0], {%1,%2,%3,%4};" :: "r"(a), "r"(x), "r"(y), "r"(z), "r"(w) : "memory"); }
__device__ __forceinline__ void sts128f(uint32_t a, float x, float y, float z, float w) { asm volatile("st.shared.v4.f32 [%0], {%1,%2,%3,%4};" :: "r"(a), "f"(x), "f"(y), "f"(z), "f"(w) : "memory"); }
__device__ __forceinline__ void sts64(uint32_t a, uint32_t x, uint32_t y) { asm volatile("st.shared.v2.u32 [%0], {%1,%2};" :: "r"(a), "r"(x), "r"(y) : "memory"); }
__device__ __forceinline__ void sts32(uint32_t a, uint32_t x) { asm volatile("st.shared.u32 [%0], %1;" :: "r"(a), "r"(x) : "memory"); }
__device__ __forceinline__ uint4 ldsm4(uint32_t a) { uint4 v; asm volatile("ldmatrix.sync.aligned.m8n8.x4.shared.b16 {%0,%1,%2,%3}, [%4];" : "=r"(v.x), "=r"(v.y), "=r"(v.z), "=r"(v.w) : "r"(a) : "memory"); return v; }
__device__ __forceinline__ void stsm2t(uint32_t a, uint32_t x, uint32_t y) { asm volatile("stmatrix.sync.aligned.m8n8.x2.trans.shared.b16 [%0], {%1,%2};" :: "r"(a), "r"(x), "r"(y) : "memory"); }
__device__ __forceinline__ void stsm4t(uint32_t a, uint32_t x, uint32_t y, uint32_t z, uint32_t w) { asm volatile("stmatrix.sync.aligned.m8n8.x4.trans.shared.b16 [%0], {%1,%2,%3,%4};" :: "r"(a), "r"(x), "r"(y), "r"(z), "r"(w) : "memory"); }
__device__ __forceinline__ void st_async64(uint32_t a, uint32_t x, uint32_t y, uint32_t bar) { asm volatile("st.async.shared::cluster.mbarrier::complete_tx::bytes.v2.b32 [%0], {%1,%2}, [%3];" :: "r"(a), "r"(x), "r"(y), "r"(bar) : "memory"); }
__device__ __forceinline__ void bulk_s2c(uint32_t dst, uint32_t src, uint32_t bytes, uint32_t bar) { asm volatile("cp.async.bulk.shared::cluster.shared::cta.mbarrier::complete_tx::bytes [%0], [%1], %2, [%3];" :: "r"(dst), "r"(src), "r"(bytes), "r"(bar) : "memory"); }
__device__ __forceinline__ void bulk_s2g(void* dst, uint32_t src, uint32_t bytes) { asm volatile("cp.async.bulk.global.shared::cta.bulk_group [%0], [%1], %2;" :: "l"(dst), "r"(src), "r"(bytes) : "memory"); }
__device__ __forceinline__ uint32_t ldg_nc32(const void* p) { uint32_t v; asm volatile("ld.global.nc.L2::128B.u32 %0, [%1];" : "=r"(v) : "l"(p)); return v; }
__device__ __forceinline__ uint4 ldg_relaxed128(const void* p) { uint4 v; asm volatile("ld.relaxed.gpu.global.v4.u32 {%0,%1,%2,%3}, [%4];" : "=r"(v.x), "=r"(v.y), "=r"(v.z), "=r"(v.w) : "l"(p) : "memory"); return v; }
__device__ __forceinline__ void mma16816(float (&d)[4], uint32_t a0, uint32_t a1, uint32_t a2, uint32_t a3, uint32_t b0, uint32_t b1) {
    asm volatile("mma.sync.aligned.m16n8k16.row.col.f32.bf16.bf16.f32 {%0,%1,%2,%3}, {%4,%5,%6,%7}, {%8,%9}, {%0,%1,%2,%3};"
        : "+f"(d[0]), "+f"(d[1]), "+f"(d[2]), "+f"(d[3]) : "r"(a0), "r"(a1), "r"(a2), "r"(a3), "r"(b0), "r"(b1));
}
__device__ __forceinline__ void mma16816_z(float (&d)[4], uint32_t a0, uint32_t a1, uint32_t a2, uint32_t a3, uint32_t b0, uint32_t b1) {
    asm volatile("mma.sync.aligned.m16n8k16.row.col.f32.bf16.bf16.f32 {%0,%1,%2,%3}, {%4,%5,%6,%7}, {%8,%9}, {%10,%10,%10,%10};"
        : "=f"(d[0]), "=f"(d[1]), "=f"(d[2]), "=f"(d[3]) : "r"(a0), "r"(a1), "r"(a2), "r"(a3), "r"(b0), "r"(b1), "f"(0.f));
}
__device__ __forceinline__ void mma1688_z(float (&d)[4], uint32_t a0, uint32_t a1, uint32_t b0) {
    asm volatile("mma.sync.aligned.m16n8k8.row.col.f32.bf16.bf16.f32 {%0,%1,%2,%3}, {%4,%5}, {%6}, {%7,%7,%7,%7};"
        : "=f"(d[0]), "=f"(d[1]), "=f"(d[2]), "=f"(d[3]) : "r"(a0), "r"(a1), "r"(b0), "f"(0.f));
}
template <int ACC>
__device__ __forceinline__ void wgmma_n32_rs(float (&d)[16], uint32_t a0, uint32_t a1, uint32_t a2, uint32_t a3, uint64_t desc) {
    asm volatile("wgmma.mma_async.sync.aligned.m64n32k16.f32.bf16.bf16 {%0,%1,%2,%3,%4,%5,%6,%7,%8,%9,%10,%11,%12,%13,%14,%15}, {%16,%17,%18,%19}, %20, %21, 1, 1, 0;"
        : "+f"(d[0]), "+f"(d[1]), "+f"(d[2]), "+f"(d[3]), "+f"(d[4]), "+f"(d[5]), "+f"(d[6]), "+f"(d[7]),
          "+f"(d[8]), "+f"(d[9]), "+f"(d[10]), "+f"(d[11]), "+f"(d[12]), "+f"(d[13]), "+f"(d[14]), "+f"(d[15])
        : "r"(a0), "r"(a1), "r"(a2), "r"(a3), "l"(desc), "n"(ACC));
}
__device__ __forceinline__ void wgmma_n32_ss(float (&d)[16], uint64_t da, uint64_t db) {
    asm volatile("wgmma.mma_async.sync.aligned.m64n32k16.f32.bf16.bf16 {%0,%1,%2,%3,%4,%5,%6,%7,%8,%9,%10,%11,%12,%13,%14,%15}, %16, %17, 1, 1, 1, 0, 0;"
        : "+f"(d[0]), "+f"(d[1]), "+f"(d[2]), "+f"(d[3]), "+f"(d[4]), "+f"(d[5]), "+f"(d[6]), "+f"(d[7]),
          "+f"(d[8]), "+f"(d[9]), "+f"(d[10]), "+f"(d[11]), "+f"(d[12]), "+f"(d[13]), "+f"(d[14]), "+f"(d[15])
        : "l"(da), "l"(db));
}
__device__ __forceinline__ void wg_fence() { asm volatile("wgmma.fence.sync.aligned;" ::: "memory"); }
__device__ __forceinline__ void wg_commit() { asm volatile("wgmma.commit_group.sync.aligned;" ::: "memory"); }
__device__ __forceinline__ void wg_wait0() { asm volatile("wgmma.wait_group.sync.aligned 0;" ::: "memory"); }
__device__ __forceinline__ void cluster_sync() { asm volatile("barrier.cluster.arrive.aligned;\nbarrier.cluster.wait.aligned;" ::: "memory"); }

#define STAMP(s, i) do {} while (0)

constexpr int XT_BYTES = 36864;
constexpr int O_XT = 0;
constexpr int O_AS = 3 * XT_BYTES;
constexpr int O_AF = O_AS + 16384;
constexpr int O_WP = O_AF + 16384;
constexpr int O_MF = O_WP + 8192;
constexpr int O_QM = O_MF + 9216;
constexpr int O_KM = O_QM + 1024;
constexpr int O_QKX = O_KM + 1024;
constexpr int O_VX = O_QKX + 16384;
constexpr int O_VM = O_VX + 24576;
constexpr int O_SC = O_VM + 6144;
constexpr int O_OF = O_SC + 2560;
constexpr int O_SXO = O_OF + 2048;
constexpr int O_SXS = O_SXO + 5120;
constexpr int O_SXR = O_SXS + 2560;
constexpr int O_OXS = O_SXR + 5120;
constexpr int O_MISC = O_OXS + 4096;
constexpr int O_BAR = O_MISC + 64;
constexpr int CHAIN_SMEM = O_BAR + 128;
static_assert(CHAIN_SMEM <= 232448, "smem");
constexpr int B_X = O_BAR, B_VX = O_BAR + 24, B_SX = O_BAR + 40, B_SC = O_BAR + 56, B_VM = O_BAR + 64, B_M = O_BAR + 72;
constexpr float SM_SCALE = 0.08838834764831845f * 1.4426950408889634f;

__device__ __forceinline__ uint32_t opaque(uint32_t v) { uint32_t o; asm volatile("mov.u32 %0, %1;" : "=r"(o) : "r"(v)); return o; }
__device__ __forceinline__ void mbar_arrive(uint32_t bar) { asm volatile("mbarrier.arrive.shared::cta.b64 _, [%0];" :: "r"(bar) : "memory"); }
__device__ __forceinline__ void st_async128(uint32_t a, uint32_t x, uint32_t y, uint32_t z, uint32_t w, uint32_t bar) {
    asm volatile("st.async.shared::cluster.mbarrier::complete_tx::bytes.v4.b32 [%0], {%1,%2,%3,%4}, [%5];" :: "r"(a), "r"(x), "r"(y), "r"(z), "r"(w), "r"(bar) : "memory");
}
__device__ __forceinline__ void tma_x_tile(uint32_t sb, const CUtensorMap* tm, int r, int j, int slot) {
    mbar_expect(sb + B_X + 8 * slot, XT_BYTES);
#pragma unroll
    for (int b = 0; b < 3; b++)
        asm volatile("cp.async.bulk.tensor.2d.shared::cluster.global.mbarrier::complete_tx::bytes.multicast::cluster [%0], [%1, {%3, %4}], [%2], %5;"
            :: "r"(sb + O_XT + slot * XT_BYTES + (3 * r + b) * 4096), "l"(tm), "r"(sb + B_X + 8 * slot), "r"((3 * r + b) * 64), "r"(j * 32), "h"((unsigned short)7) : "memory");
}

__global__ void __cluster_dims__(3, 1, 1) __launch_bounds__(384, 1)
chain_kernel(const __grid_constant__ CUtensorMap tm_x,
             const __nv_bfloat16* __restrict__ x, const __nv_bfloat16* __restrict__ mem0,
             const __nv_bfloat16* __restrict__ Wq, const __nv_bfloat16* __restrict__ Wk,
             const __nv_bfloat16* __restrict__ Wv, const __nv_bfloat16* __restrict__ Wo) {
    extern __shared__ __align__(1024) uint8_t smem_raw[];
    const uint32_t sb = smem_u32(smem_raw);
    const int lane = threadIdx.x & 31;
    const int warp = __shfl_sync(~0u, threadIdx.x >> 5, 0);
    const int wg = warp >> 2, w = warp & 3;
    const int h = blockIdx.x / 3, r = blockIdx.x - 3 * h;

    if (threadIdx.x == 0) {
        if (sb & 1023u) __trap();
        for (int i = 0; i < 9; i++) mbar_init(sb + O_BAR + 8 * i, 1);
        for (int i = 0; i < 3; i++) mbar_init(sb + B_M + 8 * i, 4);
        asm volatile("fence.mbarrier_init.release.cluster;" ::: "memory");
    }
    if (blockIdx.x == 0) {
        for (int i = threadIdx.x; i < NSEG * 4 * 8; i += 384) g_flag[i] = 0;
        __threadfence();
    }
    __syncthreads();
    cluster_sync();
    asm volatile("griddepcontrol.launch_dependents;" ::: "memory");

    if (wg < 2) {
        asm volatile("setmaxnreg.inc.sync.aligned.u32 176;");
        uint32_t a[144];
        {
            const int g = lane >> 2, t = lane & 3;
            const __nv_bfloat16* W = (r < 2) ? (wg == 0 ? Wq : Wk) : Wv;
            const int col = h * 128 + ((r < 2) ? 64 * r : 64 * wg) + 16 * w + 2 * g;
            const __nv_bfloat16* p = W + (size_t)(2 * t) * HD + col;
#pragma unroll
            for (int kk = 0; kk < 36; kk++) {
                a[4 * kk + 0] = ldg_nc32(p + (size_t)(16 * kk + 0) * HD);
                a[4 * kk + 1] = ldg_nc32(p + (size_t)(16 * kk + 1) * HD);
                a[4 * kk + 2] = ldg_nc32(p + (size_t)(16 * kk + 8) * HD);
                a[4 * kk + 3] = ldg_nc32(p + (size_t)(16 * kk + 9) * HD);
            }
#pragma unroll
            for (int kk = 0; kk < 72; kk++) {
                uint32_t w0 = a[2 * kk], w1 = a[2 * kk + 1];
                a[2 * kk] = __byte_perm(w0, w1, 0x5410);
                a[2 * kk + 1] = __byte_perm(w0, w1, 0x7632);
            }
            float s0 = 0.f, s1 = 0.f;
#pragma unroll
            for (int kk = 0; kk < 72; kk++) {
                s0 += fabsf(__uint_as_float(a[2 * kk] << 16)) + fabsf(__uint_as_float(a[2 * kk] & 0xffff0000u));
                s1 += fabsf(__uint_as_float(a[2 * kk + 1] << 16)) + fabsf(__uint_as_float(a[2 * kk + 1] & 0xffff0000u));
            }
            s0 += __shfl_xor_sync(~0u, s0, 1); s0 += __shfl_xor_sync(~0u, s0, 2);
            s1 += __shfl_xor_sync(~0u, s1, 1); s1 += __shfl_xor_sync(~0u, s1, 2);
            uint32_t mx = __reduce_max_sync(~0u, __float_as_uint(fmaxf(s0, s1)));
            if (lane == 0) sts32(sb + O_MISC + 32 + 4 * warp, mx);
            bar_arrive(7, 384);
            const uint32_t as = sb + O_AS + wg * 8192 + (16 * w + g) * 128 + t * 4;
#pragma unroll
            for (int kk = 0; kk < 4; kk++) {
                sts32(as + (((2 * kk) ^ g) << 4), a[128 + 4 * kk]);
                sts32(as + 1024 + (((2 * kk) ^ g) << 4), a[128 + 4 * kk + 1]);
                sts32(as + (((2 * kk + 1) ^ g) << 4), a[128 + 4 * kk + 2]);
                sts32(as + 1024 + (((2 * kk + 1) ^ g) << 4), a[128 + 4 * kk + 3]);
                sts128(sb + O_AF + warp * 2048 + kk * 512 + lane * 16, a[128 + 4 * kk], a[128 + 4 * kk + 1], a[128 + 4 * kk + 2], a[128 + 4 * kk + 3]);
            }
            fence_async_smem();
            bar_sync(1, 256);
        }
        int s3 = 2;
#pragma unroll 1
        for (int s = -1; s < NSEG; s++) {
            const uint32_t l16 = opaque(lane * 16);
            if (s >= 0) {
#pragma unroll
                for (int kk = 0; kk < 4; kk++) {
                    const uint4 v = lds128(sb + O_AF + warp * 2048 + kk * 512 + l16);
                    a[128 + 4 * kk] = v.x; a[128 + 4 * kk + 1] = v.y; a[128 + 4 * kk + 2] = v.z; a[128 + 4 * kk + 3] = v.w;
                }
                float c0[4], c1[4];
                uint4 b[18];
#pragma unroll
                for (int i = 0; i < 20; i++) {
                    if (i < 18) {
                        if (i % 6 == 0) mbar_wait(sb + B_M + 8 * (i / 6), s & 1);
                        if (i == 0 && warp == 0) STAMP(s, 0);
                        b[i] = lds128(sb + O_MF + i * 512 + l16);
                    }
                    if (i >= 2) {
                        const int tau = (i - 2) / 6, c = (i - 2) % 6;
                        const int k0 = 12 * tau + (c < 4 ? c : 8 + 2 * (c - 4));
                        const int k1 = 12 * tau + (c < 4 ? 4 + c : 9 + 2 * (c - 4));
                        if (i == 2) {
                            mma16816_z(c0, a[4 * k0], a[4 * k0 + 1], a[4 * k0 + 2], a[4 * k0 + 3], b[0].x, b[0].y);
                            mma16816_z(c1, a[4 * k1], a[4 * k1 + 1], a[4 * k1 + 2], a[4 * k1 + 3], b[0].z, b[0].w);
                        } else {
                            mma16816(c0, a[4 * k0], a[4 * k0 + 1], a[4 * k0 + 2], a[4 * k0 + 3], b[i - 2].x, b[i - 2].y);
                            mma16816(c1, a[4 * k1], a[4 * k1 + 1], a[4 * k1 + 2], a[4 * k1 + 3], b[i - 2].z, b[i - 2].w);
                        }
                    }
                }
                const float inv = __uint_as_float(lds32(sb + O_MISC));
                const uint32_t X0 = pack_bf16((c0[0] + c1[0]) * inv, (c0[1] + c1[1]) * inv);
                const uint32_t X1 = pack_bf16((c0[2] + c1[2]) * inv, (c0[3] + c1[3]) * inv);
                if (warp == 0) STAMP(s, 1);
                if (r < 2) {
                    stsm2t(sb + O_QM + warp * 256 + l16, X0, X1);
                    const uint32_t kb = (warp == 0) ? (sb + O_KM + l16)
                                                    : (sb + O_QKX + (s & 1) * 8192 + 4096 + ((warp - 1) >> 1) * 2048 + ((warp - 1) & 1) * 256 + l16 + (l16 & 256));
                    const uint32_t kstep = (warp == 0) ? 512 : 1024;
                    const uint32_t dst = sb + O_SC + r * 1280 + warp * 256 + (l16 >> 1);
                    const uint32_t d0 = mapa(dst, 2), d1 = mapa(dst, r ^ 1), d2 = mapa(dst, r);
                    bar_sync(1, 256);
                    if (warp < 5) {
                        const uint4 q0 = ldsm4(sb + O_QM + l16), k0 = ldsm4(kb);
                        const uint4 q1 = ldsm4(sb + O_QM + 512 + l16), k1 = ldsm4(kb + kstep);
                        float s0[4], s1[4];
                        mma16816_z(s0, q0.x, q0.x, q0.y, q0.y, k0.x, k0.y);
                        mma16816_z(s1, q0.z, q0.z, q0.w, q0.w, k0.z, k0.w);
                        mma16816(s0, q1.x, q1.x, q1.y, q1.y, k1.x, k1.y);
                        mma16816(s1, q1.z, q1.z, q1.w, q1.w, k1.z, k1.w);
                        const uint32_t v0 = __float_as_uint(s0[0] + s1[0]), v1 = __float_as_uint(s0[1] + s1[1]);
                        st_async64(d0, v0, v1, mapa(sb + B_SC, 2));
                        st_async64(d1, v0, v1, mapa(sb + B_SC, r ^ 1));
                        st_async64(d2, v0, v1, mapa(sb + B_SC, r));
                    }
                } else {
                    const uint32_t dst = sb + O_VM + s3 * 2048 + (warp >> 1) * 512 + l16 + (warp & 1) * 8;
                    st_async64(mapa(dst, 0), X0, X1, mapa(sb + B_VM, 0));
                    st_async64(mapa(dst, 1), X0, X1, mapa(sb + B_VM, 1));
                    st_async64(mapa(dst, 2), X0, X1, mapa(sb + B_VM, 2));
                }
                if (warp == 0) STAMP(s, 2);
            }
            s3 = (s3 == 2) ? 0 : s3 + 1;
            if (s < NSEG - 1) {
                const int j = s + 1;
                mbar_wait(sb + B_X + 8 * s3, (j / 3) & 1);
                const uint64_t desc0 = (uint64_t)(((sb + O_XT + s3 * XT_BYTES) & 0x3FFFF) >> 4) | (1ull << 16) | (64ull << 32) | (1ull << 62);
                float d[16];
                wg_fence();
#pragma unroll
                for (int kk = 0; kk < XCHUNK1; kk++) {
                    const uint64_t desc = desc0 + (uint64_t)(((kk >> 2) * 4096 + (kk & 3) * 32) >> 4);
                    if (kk == 0) wgmma_n32_rs<0>(d, a[0], a[1], a[2], a[3], desc);
                    else wgmma_n32_rs<1>(d, a[4 * kk], a[4 * kk + 1], a[4 * kk + 2], a[4 * kk + 3], desc);
                }
                wg_commit();
                if (s >= 0) bar_sync(5, 384);
#pragma unroll
                for (int kk = XCHUNK1; kk < 36; kk++) {
                    const uint64_t desc = desc0 + (uint64_t)(((kk >> 2) * 4096 + (kk & 3) * 32) >> 4);
                    if (kk < 32) wgmma_n32_rs<1>(d, a[4 * kk], a[4 * kk + 1], a[4 * kk + 2], a[4 * kk + 3], desc);
                    else wgmma_n32_ss(d, (uint64_t)(((sb + O_AS + wg * 8192 + (kk - 32) * 32) & 0x3FFFF) >> 4) | (1ull << 16) | (64ull << 32) | (1ull << 62), desc);
                }
                wg_commit();
                wg_wait0();
                if (warp == 0) STAMP(s, 3);
                uint32_t e[8];
#pragma unroll
                for (int i = 0; i < 8; i++) e[i] = pack_bf16(d[2 * i], d[2 * i + 1]);
                if (r < 2) {
                    const uint32_t base = sb + O_QKX + (j & 1) * 8192 + wg * 4096 + w * 512 + l16;
                    stsm4t(base, e[0], wg ? e[1] : e[2], wg ? e[2] : e[1], e[3]);
                    stsm4t(base + 2048, e[4], wg ? e[5] : e[6], wg ? e[6] : e[5], e[7]);
                } else {
                    const uint32_t base = sb + O_VX + s3 * 8192 + warp * 1024 + l16;
                    sts128(base, e[0], e[2], e[4], e[6]);
                    sts128(base + 512, e[1], e[3], e[5], e[7]);
                    const uint32_t bar = sb + B_VX + 8 * (j & 1);
                    st_async128(mapa(base, 0), e[0], e[2], e[4], e[6], mapa(bar, 0));
                    st_async128(mapa(base + 512, 0), e[1], e[3], e[5], e[7], mapa(bar, 0));
                    st_async128(mapa(base, 1), e[0], e[2], e[4], e[6], mapa(bar, 1));
                    st_async128(mapa(base + 512, 1), e[1], e[3], e[5], e[7], mapa(bar, 1));
                }
                if (warp == 0) STAMP(s, 4);
            }
        }
    } else {
        asm volatile("setmaxnreg.dec.sync.aligned.u32 152;");
        const int c = w;
        uint32_t a[96];
        uint32_t mmax = 0;
        {
            const int g = lane >> 2, t = lane & 3, t2 = threadIdx.x - 256;
            if (t2 == 0) {
                tma_x_tile(sb, &tm_x, r, 0, 0);
                tma_x_tile(sb, &tm_x, r, 1, 1);
                mbar_expect(sb + B_SC, 2560);
                mbar_expect(sb + B_VM, 2048);
                if (r < 2) mbar_expect(sb + B_VX, 8192);
            }
            __syncwarp();
#pragma unroll
            for (int i = 0; i < 4; i++) g_acc[blockIdx.x * 512 + i * 128 + t2] = make_uint4(0, 0, 0, 0);
#pragma unroll
            for (int tau = 0; tau < 3; tau++) {
                uint32_t v[6];
#pragma unroll
                for (int i = 0; i < 3; i++) {
                    const uint32_t* p = reinterpret_cast<const uint32_t*>(mem0 + g * DM + 16 * (12 * tau + 4 * i + c) + 2 * t);
                    v[2 * i] = __ldg(p); v[2 * i + 1] = __ldg(p + 4);
                    mmax = __vmaxu2(mmax, __vmaxu2(v[2 * i] & 0x7fff7fffu, v[2 * i + 1] & 0x7fff7fffu));
                }
                sts128(sb + O_MF + tau * 3072 + c * 512 + lane * 16, v[0], v[1], v[2], v[3]);
                sts64(sb + O_MF + tau * 3072 + 2048 + (c >> 1) * 512 + lane * 16 + (c & 1) * 8, v[4], v[5]);
            }
            if (t2 == 0) sts32(sb + O_MISC, __float_as_uint(1.0f));
            __syncwarp();
            if (lane == 0) { mbar_arrive(sb + B_M); mbar_arrive(sb + B_M + 8); mbar_arrive(sb + B_M + 16); }
            uint32_t xm = 0;
            const uint4* xp = reinterpret_cast<const uint4*>(x) + blockIdx.x * 1536 + t2;
#pragma unroll
            for (int i = 0; i < 12; i++) {
                uint4 v = __ldg(xp + i * 128);
                xm = __vmaxu2(xm, __vmaxu2(__vmaxu2(v.x & 0x7fff7fffu, v.y & 0x7fff7fffu), __vmaxu2(v.z & 0x7fff7fffu, v.w & 0x7fff7fffu)));
            }
            xm = __reduce_max_sync(~0u, max(xm << 16, xm & 0xffff0000u));

            const __nv_bfloat16* p = Wo + (size_t)(h * 128 + 4 * t) * DM + 192 * r + 16 * c + 2 * g;
#pragma unroll
            for (int i = 0; i < 3; i++)
#pragma unroll
                for (int eb = 0; eb < 8; eb++)
#pragma unroll
                    for (int j = 0; j < 4; j++) a[(i * 8 + eb) * 4 + j] = ldg_nc32(p + (16 * eb + j) * DM + 64 * i);
#pragma unroll
            for (int kk = 0; kk < 48; kk++) {
                uint32_t w0 = a[2 * kk], w1 = a[2 * kk + 1];
                a[2 * kk] = __byte_perm(w0, w1, 0x5410);
                a[2 * kk + 1] = __byte_perm(w0, w1, 0x7632);
            }
#pragma unroll
            for (int kk = 0; kk < 4; kk++)
                sts128(sb + O_WP + c * 2048 + kk * 512 + lane * 16, a[80 + 4 * kk], a[80 + 4 * kk + 1], a[80 + 4 * kk + 2], a[80 + 4 * kk + 3]);
            float wmax = 0.f;
#pragma unroll
            for (int i = 0; i < 3; i++) {
                float s0 = 0.f, s1 = 0.f;
#pragma unroll
                for (int kk = 16 * i; kk < 16 * i + 16; kk++) {
                    s0 += fabsf(__uint_as_float(a[2 * kk] << 16)) + fabsf(__uint_as_float(a[2 * kk] & 0xffff0000u));
                    s1 += fabsf(__uint_as_float(a[2 * kk + 1] << 16)) + fabsf(__uint_as_float(a[2 * kk + 1] & 0xffff0000u));
                }
                s0 += __shfl_xor_sync(~0u, s0, 1); s0 += __shfl_xor_sync(~0u, s0, 2);
                s1 += __shfl_xor_sync(~0u, s1, 1); s1 += __shfl_xor_sync(~0u, s1, 2);
                wmax = fmaxf(wmax, fmaxf(s0, s1));
            }
            uint32_t wm = __reduce_max_sync(~0u, __float_as_uint(wmax));
            if (lane == 0) { sts32(sb + O_OF + 4 * c, wm); sts32(sb + O_OF + 16 + 4 * c, xm); }
            __threadfence();
            bar_sync(7, 384);
            if (t2 == 0) {
                uint32_t w1 = 0, x1 = 0, v1 = 0;
                for (int i = 0; i < 4; i++) { w1 = max(w1, lds32(sb + O_OF + 4 * i)); x1 = max(x1, lds32(sb + O_OF + 16 + 4 * i)); }
                for (int i = 0; i < 8; i++) v1 = max(v1, lds32(sb + O_MISC + 32 + 4 * i));
                if (r < 2) v1 = 0;
                *reinterpret_cast<uint4*>(&g_norm[blockIdx.x * 4]) = make_uint4(w1, v1, x1, 0);
                __threadfence();
                unsigned old = atomicAdd(&g_gridbar, 1u);
                unsigned target = (old / 96u + 1u) * 96u, v; int sp = 0;
                do { asm volatile("ld.acquire.gpu.global.u32 %0, [%1];" : "=r"(v) : "l"(&g_gridbar) : "memory"); if (++sp > 4000000) __trap(); } while ((int)(v - target) < 0);
            }
            __syncwarp();
            if (c == 0) {
                uint4 n0 = ldg_relaxed128(&g_norm[lane * 4]), n1 = ldg_relaxed128(&g_norm[(lane + 32) * 4]), n2 = ldg_relaxed128(&g_norm[(lane + 64) * 4]);
                const float w1 = __uint_as_float(__reduce_max_sync(~0u, max(n0.x, max(n1.x, n2.x))));
                const float v1 = __uint_as_float(__reduce_max_sync(~0u, max(n0.y, max(n1.y, n2.y))));
                const float xmax = __uint_as_float(__reduce_max_sync(~0u, max(n0.z, max(n1.z, n2.z))));
                const float G = 36.f * w1 * v1;
                if (lane == 0) { sts32(sb + O_MISC + 4, __float_as_uint(G)); sts32(sb + O_MISC + 8, __float_as_uint(G * xmax)); }
            }
        }
        int s3 = 0;
#pragma unroll 1
        for (int s = 0; s <= NSEG; s++) {
            const uint32_t l16 = opaque(lane * 16);
            const int s3p = (s3 == 0) ? 2 : s3 - 1;
            unsigned t_red = 0;
            if (s < NSEG - 1) {
                {
                    const uint32_t mm = __reduce_max_sync(~0u, max(mmax << 16, mmax & 0xffff0000u));
                    if (lane == 0) sts32(sb + O_MISC + 16 + 4 * c, mm);
                }
                bar_sync(6, 128);
                if (lane == 0) {
                    if (c == 0) {
                        if (s + 2 < NSEG) tma_x_tile(sb, &tm_x, r, s + 2, s3p);
                        if (r < 2) mbar_expect(sb + B_VX + 8 * ((s + 1) & 1), 8192);
                    }
                    if (c == 3 && r < 2 && s >= 2)
                        asm volatile("red.release.gpu.global.add.u32 [%0], 1;" :: "l"(&g_flag[((s - 2) * 4 + (h >> 3)) * 8]) : "memory");
                }
                __syncwarp();
                float sig; uint32_t inv_new;
                {
                    const uint4 mm = lds128(sb + O_MISC + 16), cf = lds128(sb + O_MISC);
                    const float bound = fmaxf(__uint_as_float(cf.z), __uint_as_float(cf.y) * (__uint_as_float(max(max(mm.x, mm.y), max(mm.z, mm.w))) * __uint_as_float(cf.x)));
                    int k = 15 - ((int)((__float_as_uint(bound) >> 23) & 255u) - 126);
                    k = min(max(k, -120), 120);
                    sig = __uint_as_float((uint32_t)(127 + k) << 23);
                    inv_new = (uint32_t)(127 - k) << 23;
                }
#pragma unroll
                for (int kk = 0; kk < 4; kk++) {
                    const uint4 v = lds128(sb + O_WP + c * 2048 + kk * 512 + l16);
                    a[80 + 4 * kk] = v.x; a[80 + 4 * kk + 1] = v.y; a[80 + 4 * kk + 2] = v.z; a[80 + 4 * kk + 3] = v.w;
                }
                const uint32_t lo = l16 >> 4;
                char* rbase = reinterpret_cast<char*>(g_acc) + ((s >> 1) * 24576 + (s & 1) * 128 + (r * 4 + c) * 2048)
                            + ((lo >> 4) * 512 + (lo & 2) * 128 + (lo & 1) * 64 + (lo & 12) * 4);
                if (c == 0) STAMP(s, 5);
                if (r < 2) mbar_wait(sb + B_VX + 8 * (s & 1), (s >> 1) & 1);
                else mbar_wait(sb + B_VM, s & 1);
                uint4 vx[4];
#pragma unroll
                for (int q = 0; q < 4; q++) vx[q] = lds128(sb + O_VX + s3 * 8192 + c * 2048 + q * 512 + l16);
                mbar_wait(sb + B_SC, s & 1);
                if (c == 0) STAMP(s, 6);
                float p[10];
#pragma unroll
                for (int n = 0; n < 5; n++) {
                    float2 u = lds64f(sb + O_SC + n * 256 + (l16 >> 1)), v = lds64f(sb + O_SC + 1280 + n * 256 + (l16 >> 1));
                    p[2 * n] = u.x + v.x; p[2 * n + 1] = u.y + v.y;
                }
                float mx = fmaxf(fmaxf(fmaxf(p[0], p[1]), fmaxf(p[2], p[3])), fmaxf(fmaxf(p[4], p[5]), fmaxf(p[6], p[7])));
                mx = fmaxf(mx, fmaxf(p[8], p[9]));
                mx = fmaxf(mx, __shfl_xor_sync(~0u, mx, 1));
                mx = fmaxf(mx, __shfl_xor_sync(~0u, mx, 2));
                if (r < 2) mbar_wait(sb + B_VM, s & 1);
                const uint4 vm = lds128(sb + O_VM + s3 * 2048 + c * 512 + l16);
                const float mo = mx * SM_SCALE;
#pragma unroll
                for (int i = 0; i < 10; i++) p[i] = ex2(fmaf(p[i], SM_SCALE, -mo));
                uint32_t P[5];
#pragma unroll
                for (int n = 0; n < 5; n++) P[n] = pack_bf16(p[2 * n], p[2 * n + 1]);
                if (c == 0) STAMP(s, 7);
                float o[4][4];
                mma1688_z(o[0], P[0], P[0], vm.x); mma1688_z(o[1], P[0], P[0], vm.y);
                mma1688_z(o[2], P[0], P[0], vm.z); mma1688_z(o[3], P[0], P[0], vm.w);
#pragma unroll
                for (int q = 0; q < 4; q++) mma16816(o[q], P[1], P[1], P[2], P[2], vx[q].x, vx[q].y);
#pragma unroll
                for (int q = 0; q < 4; q++) mma16816(o[q], P[3], P[3], P[4], P[4], vx[q].z, vx[q].w);
                float sum = ((p[0] + p[1]) + (p[2] + p[3])) + ((p[4] + p[5]) + (p[6] + p[7])) + (p[8] + p[9]);
                sum += __shfl_xor_sync(~0u, sum, 1);
                sum += __shfl_xor_sync(~0u, sum, 2);
                float rs; asm("rcp.approx.ftz.f32 %0, %1;" : "=f"(rs) : "f"(sum));
                sts128(sb + O_OF + c * 512 + l16, pack_bf16(o[0][0] * rs, o[1][0] * rs), pack_bf16(o[0][1] * rs, o[1][1] * rs),
                       pack_bf16(o[2][0] * rs, o[3][0] * rs), pack_bf16(o[2][1] * rs, o[3][1] * rs));
                bar_sync(6, 128);
                uint4 ob[4];
#pragma unroll
                for (int q = 0; q < 4; q++) ob[q] = lds128(sb + O_OF + q * 512 + l16);
                float m0[3][4], m1[3][4];
#pragma unroll
                for (int q = 0; q < 4; q++) {
#pragma unroll
                    for (int i = 0; i < 3; i++) {
                        const int k0 = (i * 8 + 2 * q) * 4;
                        if (q == 0) mma16816_z(m0[i], a[k0], a[k0 + 1], a[k0 + 2], a[k0 + 3], ob[q].x, ob[q].y);
                        else mma16816(m0[i], a[k0], a[k0 + 1], a[k0 + 2], a[k0 + 3], ob[q].x, ob[q].y);
                    }
#pragma unroll
                    for (int i = 0; i < 3; i++) {
                        const int k1 = (i * 8 + 2 * q + 1) * 4;
                        if (q == 0) mma16816_z(m1[i], a[k1], a[k1 + 1], a[k1 + 2], a[k1 + 3], ob[q].z, ob[q].w);
                        else mma16816(m1[i], a[k1], a[k1 + 1], a[k1 + 2], a[k1 + 3], ob[q].z, ob[q].w);
                    }
                }
#pragma unroll
                for (int i = 0; i < 3; i++)
#pragma unroll
                    for (int q = 0; q < 4; q++) m0[i][q] = (m0[i][q] + m1[i][q]) * sig;
                asm volatile("red.relaxed.gpu.global.add.noftz.v4.f16x2 [%0], {%1,%2,%3,%4};" :: "l"(rbase),
                    "r"(pack_f16(m0[0][0], m0[0][2])), "r"(pack_f16(m0[1][0], m0[1][2])), "r"(pack_f16(m0[2][0], m0[2][2])), "r"(0x3c00u) : "memory");
                asm volatile("red.relaxed.gpu.global.add.noftz.v4.f16x2 [%0], {%1,%2,%3,%4};" :: "l"(rbase + 1024),
                    "r"(pack_f16(m0[0][1], m0[0][3])), "r"(pack_f16(m0[1][1], m0[1][3])), "r"(pack_f16(m0[2][1], m0[2][3])), "r"(0x3c00u) : "memory");
                t_red = clk();
                bar_arrive(5, 384);
                if (c == 0 && lane == 0) { sts32(sb + O_MISC, inv_new); mbar_expect(sb + B_SC, 2560); mbar_expect(sb + B_VM, 2048); }
                if (c == 0) STAMP(s, 8);
            } else {
                if (r == 2) break;
                if (s == NSEG - 1) {
                    mbar_wait(sb + B_SC, s & 1);
                    mbar_wait(sb + B_VM, s & 1);
                    mbar_wait(sb + B_VX + 8 * (s & 1), (s >> 1) & 1);
                }
                bar_sync(6, 128);
            }

            if (r < 2) {
                if (s >= 1) {
                    const int sx = s - 1;
                    mbar_wait(sb + B_SX + 8 * (sx & 1), (sx >> 1) & 1);
                    float p[5][4];
                    const uint32_t so = sb + O_SXO + (sx & 1) * 2560 + l16;
                    const int q0 = 16 * r + (int)(l16 >> 6) - (int)((l16 >> 3) & 6) + 8;
#pragma unroll
                    for (int n = 0; n < 5; n++) {
                        if (n < 3 || r == 1) {
                            const float4 u = lds128f(so + n * 512), v = lds128f(so + (O_SXR - O_SXO) + n * 512);
                            p[n][0] = u.x + v.x; p[n][1] = u.y + v.y; p[n][2] = u.z + v.z; p[n][3] = u.w + v.w;
                        } else { p[n][0] = p[n][1] = p[n][2] = p[n][3] = 0.f; }
                        if (n > 0) {
                            if (8 * n > q0) p[n][0] = -INFINITY;
                            if (8 * n + 1 > q0) p[n][1] = -INFINITY;
                            if (8 * n > q0 + 8) p[n][2] = -INFINITY;
                            if (8 * n + 1 > q0 + 8) p[n][3] = -INFINITY;
                        }
                    }
                    float mxa = fmaxf(p[0][0], p[0][1]), mxb = fmaxf(p[0][2], p[0][3]);
#pragma unroll
                    for (int n = 1; n < 5; n++) { mxa = fmaxf(mxa, fmaxf(p[n][0], p[n][1])); mxb = fmaxf(mxb, fmaxf(p[n][2], p[n][3])); }
                    mxa = fmaxf(mxa, __shfl_xor_sync(~0u, mxa, 1)); mxb = fmaxf(mxb, __shfl_xor_sync(~0u, mxb, 1));
                    mxa = fmaxf(mxa, __shfl_xor_sync(~0u, mxa, 2)); mxb = fmaxf(mxb, __shfl_xor_sync(~0u, mxb, 2));
                    mxa *= SM_SCALE; mxb *= SM_SCALE;
                    float sa = 0.f, sbm = 0.f;
                    uint32_t Pa[5], Pb[5];
#pragma unroll
                    for (int n = 0; n < 5; n++) {
                        const float e0 = ex2(fmaf(p[n][0], SM_SCALE, -mxa)), e1 = ex2(fmaf(p[n][1], SM_SCALE, -mxa));
                        const float e2 = ex2(fmaf(p[n][2], SM_SCALE, -mxb)), e3 = ex2(fmaf(p[n][3], SM_SCALE, -mxb));
                        sa += e0 + e1; sbm += e2 + e3;
                        Pa[n] = pack_bf16(e0, e1); Pb[n] = pack_bf16(e2, e3);
                    }
                    const uint4 vm = lds128(sb + O_VM + s3p * 2048 + c * 512 + l16);
                    float o[4][4];
                    mma1688_z(o[0], Pa[0], Pb[0], vm.x); mma1688_z(o[1], Pa[0], Pb[0], vm.y);
                    mma1688_z(o[2], Pa[0], Pb[0], vm.z); mma1688_z(o[3], Pa[0], Pb[0], vm.w);
#pragma unroll
                    for (int q = 0; q < 4; q++) {
                        const uint4 vx = lds128(sb + O_VX + s3p * 8192 + c * 2048 + q * 512 + l16);
                        mma16816(o[q], Pa[1], Pb[1], Pa[2], Pb[2], vx.x, vx.y);
                        mma16816(o[q], Pa[3], Pb[3], Pa[4], Pb[4], vx.z, vx.w);
                    }
                    sa += __shfl_xor_sync(~0u, sa, 1); sbm += __shfl_xor_sync(~0u, sbm, 1);
                    sa += __shfl_xor_sync(~0u, sa, 2); sbm += __shfl_xor_sync(~0u, sbm, 2);
                    float ra, rb;
                    asm("rcp.approx.ftz.f32 %0, %1;" : "=f"(ra) : "f"(sa));
                    asm("rcp.approx.ftz.f32 %0, %1;" : "=f"(rb) : "f"(sbm));
                    const uint32_t gg = l16 >> 6;
                    const uint32_t dst = sb + O_OXS + (c >> 1) * 2048 + gg * 128 + ((((c & 1) * 4 + ((l16 >> 5) & 1)) ^ gg) << 4) + ((l16 >> 1) & 8);
#pragma unroll
                    for (int e2 = 0; e2 < 2; e2++) {
                        const uint32_t dd = dst ^ (e2 * 32);
                        sts64(dd, pack_bf16(o[2 * e2][0] * ra, o[2 * e2 + 1][0] * ra), pack_bf16(o[2 * e2][1] * ra, o[2 * e2 + 1][1] * ra));
                        sts64(dd + 1024, pack_bf16(o[2 * e2][2] * rb, o[2 * e2 + 1][2] * rb), pack_bf16(o[2 * e2][3] * rb, o[2 * e2 + 1][3] * rb));
                    }
                }
                if (s < NSEG) {
#pragma unroll
                    for (int q = 0; q < 2; q++) {
                        const int pi = 2 * c + q;
                        const int mt = pi < 3 ? 0 : 1, n = pi < 3 ? pi : pi - 3;
                        const uint32_t qb = sb + O_QKX + (s & 1) * 8192 + mt * 2048 + l16;
                        const uint32_t kb = (n == 0) ? (sb + O_KM + l16)
                                                     : (sb + O_QKX + (s & 1) * 8192 + 4096 + ((n - 1) >> 1) * 2048 + ((n - 1) & 1) * 256 + l16 + (l16 & 256));
                        const uint4 k0 = ldsm4(kb), k1 = ldsm4(kb + ((n == 0) ? 512 : 1024));
                        const uint4 q0 = ldsm4(qb), q1 = ldsm4(qb + 512), q2 = ldsm4(qb + 1024), q3 = ldsm4(qb + 1536);
                        float sc[4];
                        mma16816_z(sc, q0.x, q0.y, q0.z, q0.w, k0.x, k0.y);
                        mma16816(sc, q1.x, q1.y, q1.z, q1.w, k0.z, k0.w);
                        mma16816(sc, q2.x, q2.y, q2.z, q2.w, k1.x, k1.y);
                        mma16816(sc, q3.x, q3.y, q3.z, q3.w, k1.z, k1.w);
                        sts128f(sb + ((mt == r) ? (O_SXO + (s & 1) * 2560) : O_SXS) + n * 512 + l16, sc[0], sc[1], sc[2], sc[3]);
                    }
                }
                bar_sync(6, 128);
            }
            auto sends = [&]() {
                if (s < NSEG) {
                    if (c == 0 && lane == 0) mbar_expect(sb + B_SX + 8 * (s & 1), r == 0 ? 1536 : 2560);
#pragma unroll
                    for (int q = 0; q < 2; q++) {
                        const int pi = 2 * c + q;
                        const int mt = pi < 3 ? 0 : 1, n = pi < 3 ? pi : pi - 3;
                        if (mt != r) {
                            const uint4 u = lds128(sb + O_SXS + n * 512 + l16);
                            st_async128(mapa(sb + O_SXR + (s & 1) * 2560 + n * 512 + l16, r ^ 1), u.x, u.y, u.z, u.w, mapa(sb + B_SX + 8 * (s & 1), r ^ 1));
                        }
                    }
                }
                if (s >= 1) {
                    char* op = reinterpret_cast<char*>(g_ox) + ((size_t)(h * 2) * SEQ + (s - 1) * 32 + 16 * r) * 128 + c * 512 + l16;
                    const uint4 u0 = lds128(sb + O_OXS + c * 512 + l16), u1 = lds128(sb + O_OXS + 2048 + c * 512 + l16);
                    *reinterpret_cast<uint4*>(op) = u0;
                    *reinterpret_cast<uint4*>(op + (size_t)SEQ * 128) = u1;
                }
            };
            if (s >= NSEG - 1) {
                sends();
            } else {
                if (c == 0) STAMP(s, 9);
                const uint32_t lo = l16 >> 4;
                const char* pbase = reinterpret_cast<const char*>(g_acc) + ((s >> 1) * 24576 + (s & 1) * 128 + c * 2048)
                      + ((lo & 4) * 256 + (lo >> 4) * 256 + (lo & 8) * 8 + (lo & 3) * 16);
                while (clk() - t_red < D_WAIT) {}
                uint4 v[6];
#pragma unroll
                for (int i = 0; i < 6; i++) v[i] = ldg_relaxed128(pbase + (i >> 1) * 8192 + (i & 1) * 512);
                if (r < 2) sends();
                mmax = 0;
#pragma unroll
                for (int tau = 0; tau < 3; tau++) {
                    int sp = 0;
                    while (!__all_sync(~0u, v[2 * tau].w == 0x5000u && v[2 * tau + 1].w == 0x5000u)) {
                        v[2 * tau] = ldg_relaxed128(pbase + tau * 8192);
                        v[2 * tau + 1] = ldg_relaxed128(pbase + tau * 8192 + 512);
                        if (++sp > 2000000) __trap();
                    }
                    const uint32_t b0 = f16x2_to_bf16x2(v[2 * tau].x), b1 = f16x2_to_bf16x2(v[2 * tau + 1].x);
                    const uint32_t b2 = f16x2_to_bf16x2(v[2 * tau].y), b3 = f16x2_to_bf16x2(v[2 * tau + 1].y);
                    const uint32_t b4 = f16x2_to_bf16x2(v[2 * tau].z), b5 = f16x2_to_bf16x2(v[2 * tau + 1].z);
                    sts128(sb + O_MF + tau * 3072 + c * 512 + l16, b0, b1, b2, b3);
                    sts64(sb + O_MF + tau * 3072 + 2048 + (c >> 1) * 512 + (c & 1) * 8 + l16, b4, b5);
                    __syncwarp();
                    if (lane == 0) mbar_arrive(sb + B_M + 8 * tau);
                    mmax = __vmaxu2(mmax, __vmaxu2(__vmaxu2(b0 & 0x7fff7fffu, b1 & 0x7fff7fffu), __vmaxu2(b2 & 0x7fff7fffu, b3 & 0x7fff7fffu)));
                    mmax = __vmaxu2(mmax, __vmaxu2(b4 & 0x7fff7fffu, b5 & 0x7fff7fffu));
                }
            }
            s3 = (s3 == 2) ? 0 : s3 + 1;
        }
        if (r < 2) {
            bar_sync(6, 128);
            if (c == 0 && lane == 0) {
                __threadfence();
                for (int sx = NSEG - 3; sx < NSEG; sx++) atomicAdd(&g_flag[(sx * 4 + (h >> 3)) * 8], 1u);
            }
        }
    }
    cluster_sync();
}

__device__ float g_u[SEQ * 2 * DM];
__global__ void naive_gemm1(const __nv_bfloat16* x, const __nv_bfloat16* Bre, const __nv_bfloat16* Bim) {
    int p = blockIdx.x * 64 + threadIdx.x % 64, tk = blockIdx.y * 4 + threadIdx.x / 64;
    float sr = 0, si = 0;
    for (int d = 0; d < DM; d++) { float xv = __bfloat162float(x[tk * DM + d]); sr += xv * __bfloat162float(Bre[p * DM + d]); si += xv * __bfloat162float(Bim[p * DM + d]); }
    g_u[tk * 2 * DM + 2 * p] = sr; g_u[tk * 2 * DM + 2 * p + 1] = si;
}
__global__ void naive_scan(const __nv_bfloat16* Lre, const __nv_bfloat16* Lim, const __nv_bfloat16* logdt) {
    int p = blockIdx.x * 64 + threadIdx.x;
    float dt = __bfloat162float(__float2bfloat16(expf(__bfloat162float(logdt[p]))));
    float lr = __bfloat162float(Lre[p]), li = __bfloat162float(Lim[p]);
    float e = expf(dt * lr), br = e * cosf(dt * li), bi = e * sinf(dt * li);
    float den = lr * lr + li * li;
    float cr = ((br - 1.f) * lr + bi * li) / den, ci = (bi * lr - (br - 1.f) * li) / den;
    float hr = 0, hi = 0;
    for (int tk = 0; tk < SEQ; tk++) {
        float ur = g_u[tk * 2 * DM + 2 * p], ui = g_u[tk * 2 * DM + 2 * p + 1];
        float nr = br * hr - bi * hi + cr * ur - ci * ui, ni = br * hi + bi * hr + cr * ui + ci * ur;
        hr = nr; hi = ni;
        g_u[tk * 2 * DM + 2 * p] = hr; g_u[tk * 2 * DM + 2 * p + 1] = hi;
    }
}
__global__ void naive_gemm2(const __nv_bfloat16* x, const __nv_bfloat16* Cre, const __nv_bfloat16* Cim, const __nv_bfloat16* Dk, float* out) {
    int d = blockIdx.x * 64 + threadIdx.x % 64, tk = blockIdx.y * 4 + threadIdx.x / 64;
    float s = 0;
    for (int p = 0; p < DM; p++) s += g_u[tk * 2 * DM + 2 * p] * __bfloat162float(Cre[d * DM + p]) - g_u[tk * 2 * DM + 2 * p + 1] * __bfloat162float(Cim[d * DM + p]);
    out[tk * 1152 + d] = 2.f * s + __bfloat162float(__float2bfloat16(__bfloat162float(x[tk * DM + d]) * __bfloat162float(Dk[d])));
}
__global__ void naive_wo(const __nv_bfloat16* Wo, float* out) {
    int d = blockIdx.x * 64 + threadIdx.x % 64, tk = blockIdx.y * 4 + threadIdx.x / 64;
    const __nv_bfloat16* ox = reinterpret_cast<const __nv_bfloat16*>(g_ox);
    float s = 0;
    for (int k = 0; k < HD; k++) {
        int hh = k >> 6, e = k & 63;
        s += __bfloat162float(ox[((size_t)hh * SEQ + tk) * 64 + (((e >> 3) ^ (tk & 7)) << 3) + (e & 7)]) * __bfloat162float(Wo[k * DM + d]);
    }
    out[tk * 1152 + DM + d] = s;
}

typedef CUresult (*EncodeFn)(CUtensorMap*, CUtensorMapDataType, cuuint32_t, void*, const cuuint64_t*, const cuuint64_t*, const cuuint32_t*, const cuuint32_t*,
                             CUtensorMapInterleave, CUtensorMapSwizzle, CUtensorMapL2promotion, CUtensorMapFloatOOBfill);
}

extern "C" void kernel_launch(void* const* d_in, const int* in_sizes, int n_in, void* d_out, int out_size) {
    typedef const __nv_bfloat16* bp;
    bp Ax = (bp)d_in[0], Lre = (bp)d_in[1], Lim = (bp)d_in[2], Bre = (bp)d_in[3], Bim = (bp)d_in[4], Cre = (bp)d_in[5], Cim = (bp)d_in[6],
       logdt = (bp)d_in[7], Dk = (bp)d_in[8], Bx = (bp)d_in[9], mem0 = (bp)d_in[10], Wq = (bp)d_in[11], Wk = (bp)d_in[12], Wv = (bp)d_in[13], Wo = (bp)d_in[14];
    float* out = (float*)d_out;
    static EncodeFn enc = nullptr;
    if (!enc) {
        void* fn = nullptr; cudaDriverEntryPointQueryResult qr;
        cudaGetDriverEntryPoint("cuTensorMapEncodeTiled", &fn, cudaEnableDefault, &qr);
        enc = (EncodeFn)fn;
        cudaFuncSetAttribute(chain_kernel, cudaFuncAttributeMaxDynamicSharedMemorySize, CHAIN_SMEM);
    }
    CUtensorMap tm_x;
    {
        cuuint64_t gd[2] = {DM, SEQ}; cuuint64_t gs[1] = {DM * 2}; cuuint32_t bd[2] = {64, 32}; cuuint32_t es[2] = {1, 1};
        enc(&tm_x, CU_TENSOR_MAP_DATA_TYPE_BFLOAT16, 2, (void*)Bx, gd, gs, bd, es, CU_TENSOR_MAP_INTERLEAVE_NONE, CU_TENSOR_MAP_SWIZZLE_128B,
            CU_TENSOR_MAP_L2_PROMOTION_L2_128B, CU_TENSOR_MAP_FLOAT_OOB_FILL_NONE);
    }
    cudaStream_t st = cudaStreamPerThread;
    chain_kernel<<<96, 384, CHAIN_SMEM, st>>>(tm_x, Bx, mem0, Wq, Wk, Wv, Wo);
    naive_gemm1<<<dim3(9, 512), 256, 0, st>>>(Ax, Bre, Bim);
    naive_scan<<<9, 64, 0, st>>>(Lre, Lim, logdt);
    naive_gemm2<<<dim3(9, 512), 256, 0, st>>>(Ax, Cre, Cim, Dk, out);
    naive_wo<<<dim3(9, 512), 256, 0, st>>>(Wo, out);
}
```

```cpp
#include <cuda_runtime.h>
#include <cuda.h>
#include <cuda_bf16.h>
#include <cuda_fp16.h>
#include <stdint.h>

#define D_WAIT 700
#define XCHUNK1 14

namespace {

constexpr int DM = 576, NH = 32, SEQ = 2048, NSEG = 64, HD = 4096;

__device__ uint4 g_acc[32 * 96 * 16];
__device__ uint4 g_ox[NH * 2 * SEQ * 8];
__device__ unsigned g_flag[NSEG * 4 * 8];
__device__ unsigned g_gridbar;
__device__ float g_norm[96 * 4];

__device__ __forceinline__ uint32_t smem_u32(const void* p) { return (uint32_t)__cvta_generic_to_shared(p); }
__device__ __forceinline__ uint32_t mapa(uint32_t a, uint32_t r) { uint32_t o; asm("mapa.shared::cluster.u32 %0, %1, %2;" : "=r"(o) : "r"(a), "r"(r)); return o; }
__device__ __forceinline__ unsigned clk() { unsigned long long c; asm volatile("mov.u64 %0, %%clock64;" : "=l"(c) :: "memory"); return (unsigned)c; }
__device__ __forceinline__ void mbar_init(uint32_t bar, uint32_t cnt) { asm volatile("mbarrier.init.shared::cta.b64 [%0], %1;" :: "r"(bar), "r"(cnt) : "memory"); }
__device__ __forceinline__ void mbar_expect(uint32_t bar, uint32_t bytes) { asm volatile("mbarrier.arrive.expect_tx.shared::cta.b64 _, [%0], %1;" :: "r"(bar), "r"(bytes) : "memory"); }
__device__ __forceinline__ void mbar_wait(uint32_t bar, uint32_t parity) {
    asm volatile("{\n.reg .pred p;\n.reg .u32 n;\nmov.u32 n, 0;\n"
                 "W_%=: mbarrier.try_wait.parity.shared::cta.b64 p, [%0], %1;\n@p bra.uni D_%=;\n"
                 "add.u32 n, n, 1;\nsetp.lt.u32 p, n, 4000000;\n@p bra.uni W_%=;\ntrap;\nD_%=:\n}" :: "r"(bar), "r"(parity) : "memory");
}
__device__ __forceinline__ void mbar_expect_if(uint32_t z, uint32_t bar, uint32_t bytes) {
    asm volatile("{\n.reg .pred p;\nsetp.eq.u32 p, %2, 0;\n@p mbarrier.arrive.expect_tx.shared::cta.b64 _, [%0], %1;\n}" :: "r"(bar), "r"(bytes), "r"(z) : "memory");
}
__device__ __forceinline__ void mbar_arrive_if(uint32_t z, uint32_t bar) {
    asm volatile("{\n.reg .pred p;\nsetp.eq.u32 p, %1, 0;\n@p mbarrier.arrive.shared::cta.b64 _, [%0];\n}" :: "r"(bar), "r"(z) : "memory");
}
__device__ __forceinline__ void sts32_if(uint32_t z, uint32_t a, uint32_t x) {
    asm volatile("{\n.reg .pred p;\nsetp.eq.u32 p, %2, 0;\n@p st.shared.u32 [%0], %1;\n}" :: "r"(a), "r"(x), "r"(z) : "memory");
}
__device__ __forceinline__ void spin_until(unsigned t0, unsigned d) {
    asm volatile("{\n.reg .pred p;\n.reg .u64 c;\n.reg .u32 lo;\n"
                 "S_%=: mov.u64 c, %%clock64;\ncvt.u32.u64 lo, c;\nsub.u32 lo, lo, %0;\nsetp.lt.u32 p, lo, %1;\n@p bra.uni S_%=;\n}" :: "r"(t0), "r"(d) : "memory");
}
__device__ __forceinline__ void bar_sync(int id, int n) { asm volatile("bar.sync %0, %1;" :: "r"(id), "r"(n) : "memory"); }
__device__ __forceinline__ void bar_arrive(int id, int n) { asm volatile("bar.arrive %0, %1;" :: "r"(id), "r"(n) : "memory"); }
__device__ __forceinline__ void fence_async_smem() { asm volatile("fence.proxy.async.shared::cta;" ::: "memory"); }
__device__ __forceinline__ uint32_t pack_bf16(float lo, float hi) { uint32_t r; asm("cvt.rn.bf16x2.f32 %0, %1, %2;" : "=r"(r) : "f"(hi), "f"(lo)); return r; }
__device__ __forceinline__ uint32_t pack_f16(float lo, float hi) { uint32_t r; asm("cvt.rn.f16x2.f32 %0, %1, %2;" : "=r"(r) : "f"(hi), "f"(lo)); return r; }
__device__ __forceinline__ uint32_t f16x2_to_bf16x2(uint32_t v) { float2 f = __half22float2(*reinterpret_cast<__half2*>(&v)); return pack_bf16(f.x, f.y); }
__device__ __forceinline__ float ex2(float x) { float y; asm("ex2.approx.ftz.f32 %0, %1;" : "=f"(y) : "f"(x)); return y; }
__device__ __forceinline__ uint4 lds128(uint32_t a) { uint4 v; asm volatile("ld.shared.v4.u32 {%0,%1,%2,%3}, [%4];" : "=r"(v.x), "=r"(v.y), "=r"(v.z), "=r"(v.w) : "r"(a) : "memory"); return v; }
__device__ __forceinline__ float4 lds128f(uint32_t a) { float4 v; asm volatile("ld.shared.v4.f32 {%0,%1,%2,%3}, [%4];" : "=f"(v.x), "=f"(v.y), "=f"(v.z), "=f"(v.w) : "r"(a) : "memory"); return v; }
__device__ __forceinline__ float2 lds64f(uint32_t a) { float2 v; asm volatile("ld.shared.v2.f32 {%0,%1}, [%2];" : "=f"(v.x), "=f"(v.y) : "r"(a) : "memory"); return v; }
__device__ __forceinline__ uint32_t lds32(uint32_t a) { uint32_t v; asm volatile("ld.shared.u32 %0, [%1];" : "=r"(v) : "r"(a) : "memory"); return v; }
__device__ __forceinline__ void sts128(uint32_t a, uint32_t x, uint32_t y, uint32_t z, uint32_t w) { asm volatile("st.shared.v4.u32 [%0], {%1,%2,%3,%4};" :: "r"(a), "r"(x), "r"(y), "r"(z), "r"(w) : "memory"); }
__device__ __forceinline__ void sts128f(uint32_t a, float x, float y, float z, float w) { asm volatile("st.shared.v4.f32 [%0], {%1,%2,%3,%4};" :: "r"(a), "f"(x), "f"(y), "f"(z), "f"(w) : "memory"); }
__device__ __forceinline__ void sts64(uint32_t a, uint32_t x, uint32_t y) { asm volatile("st.shared.v2.u32 [%0], {%1,%2};" :: "r"(a), "r"(x), "r"(y) : "memory"); }
__device__ __forceinline__ void sts32(uint32_t a, uint32_t x) { asm volatile("st.shared.u32 [%0], %1;" :: "r"(a), "r"(x) : "memory"); }
__device__ __forceinline__ uint4 ldsm4(uint32_t a) { uint4 v; asm volatile("ldmatrix.sync.aligned.m8n8.x4.shared.b16 {%0,%1,%2,%3}, [%4];" : "=r"(v.x), "=r"(v.y), "=r"(v.z), "=r"(v.w) : "r"(a) : "memory"); return v; }
__device__ __forceinline__ void stsm2t(uint32_t a, uint32_t x, uint32_t y) { asm volatile("stmatrix.sync.aligned.m8n8.x2.trans.shared.b16 [%0], {%1,%2};" :: "r"(a), "r"(x), "r"(y) : "memory"); }
__device__ __forceinline__ void stsm4t(uint32_t a, uint32_t x, uint32_t y, uint32_t z, uint32_t w) { asm volatile("stmatrix.sync.aligned.m8n8.x4.trans.shared.b16 [%0], {%1,%2,%3,%4};" :: "r"(a), "r"(x), "r"(y), "r"(z), "r"(w) : "memory"); }
__device__ __forceinline__ void st_async64(uint32_t a, uint32_t x, uint32_t y, uint32_t bar) { asm volatile("st.async.shared::cluster.mbarrier::complete_tx::bytes.v2.b32 [%0], {%1,%2}, [%3];" :: "r"(a), "r"(x), "r"(y), "r"(bar) : "memory"); }
__device__ __forceinline__ void bulk_s2c(uint32_t dst, uint32_t src, uint32_t bytes, uint32_t bar) { asm volatile("cp.async.bulk.shared::cluster.shared::cta.mbarrier::complete_tx::bytes [%0], [%1], %2, [%3];" :: "r"(dst), "r"(src), "r"(bytes), "r"(bar) : "memory"); }
__device__ __forceinline__ void bulk_s2g(void* dst, uint32_t src, uint32_t bytes) { asm volatile("cp.async.bulk.global.shared::cta.bulk_group [%0], [%1], %2;" :: "l"(dst), "r"(src), "r"(bytes) : "memory"); }
__device__ __forceinline__ uint32_t ldg_nc32(const void* p) { uint32_t v; asm volatile("ld.global.nc.L2::128B.u32 %0, [%1];" : "=r"(v) : "l"(p)); return v; }
__device__ __forceinline__ uint4 ldg_relaxed128(const void* p) { uint4 v; asm volatile("ld.relaxed.gpu.global.v4.u32 {%0,%1,%2,%3}, [%4];" : "=r"(v.x), "=r"(v.y), "=r"(v.z), "=r"(v.w) : "l"(p) : "memory"); return v; }
__device__ __forceinline__ void mma16816(float (&d)[4], uint32_t a0, uint32_t a1, uint32_t a2, uint32_t a3, uint32_t b0, uint32_t b1) {
    asm volatile("mma.sync.aligned.m16n8k16.row.col.f32.bf16.bf16.f32 {%0,%1,%2,%3}, {%4,%5,%6,%7}, {%8,%9}, {%0,%1,%2,%3};"
        : "+f"(d[0]), "+f"(d[1]), "+f"(d[2]), "+f"(d[3]) : "r"(a0), "r"(a1), "r"(a2), "r"(a3), "r"(b0), "r"(b1));
}
__device__ __forceinline__ void mma16816_z(float (&d)[4], uint32_t a0, uint32_t a1, uint32_t a2, uint32_t a3, uint32_t b0, uint32_t b1) {
    asm volatile("mma.sync.aligned.m16n8k16.row.col.f32.bf16.bf16.f32 {%0,%1,%2,%3}, {%4,%5,%6,%7}, {%8,%9}, {%10,%10,%10,%10};"
        : "=f"(d[0]), "=f"(d[1]), "=f"(d[2]), "=f"(d[3]) : "r"(a0), "r"(a1), "r"(a2), "r"(a3), "r"(b0), "r"(b1), "f"(0.f));
}
__device__ __forceinline__ void mma1688(float (&d)[4], uint32_t a0, uint32_t a1, uint32_t b0) {
    asm volatile("mma.sync.aligned.m16n8k8.row.col.f32.bf16.bf16.f32 {%0,%1,%2,%3}, {%4,%5}, {%6}, {%0,%1,%2,%3};"
        : "+f"(d[0]), "+f"(d[1]), "+f"(d[2]), "+f"(d[3]) : "r"(a0), "r"(a1), "r"(b0));
}
__device__ __forceinline__ void mma1688_z(float (&d)[4], uint32_t a0, uint32_t a1, uint32_t b0) {
    asm volatile("mma.sync.aligned.m16n8k8.row.col.f32.bf16.bf16.f32 {%0,%1,%2,%3}, {%4,%5}, {%6}, {%7,%7,%7,%7};"
        : "=f"(d[0]), "=f"(d[1]), "=f"(d[2]), "=f"(d[3]) : "r"(a0), "r"(a1), "r"(b0), "f"(0.f));
}
template <int ACC>
__device__ __forceinline__ void wgmma_n32_rs(float (&d)[16], uint32_t a0, uint32_t a1, uint32_t a2, uint32_t a3, uint64_t desc) {
    asm volatile("wgmma.mma_async.sync.aligned.m64n32k16.f32.bf16.bf16 {%0,%1,%2,%3,%4,%5,%6,%7,%8,%9,%10,%11,%12,%13,%14,%15}, {%16,%17,%18,%19}, %20, %21, 1, 1, 0;"
        : "+f"(d[0]), "+f"(d[1]), "+f"(d[2]), "+f"(d[3]), "+f"(d[4]), "+f"(d[5]), "+f"(d[6]), "+f"(d[7]),
          "+f"(d[8]), "+f"(d[9]), "+f"(d[10]), "+f"(d[11]), "+f"(d[12]), "+f"(d[13]), "+f"(d[14]), "+f"(d[15])
        : "r"(a0), "r"(a1), "r"(a2), "r"(a3), "l"(desc), "n"(ACC));
}
__device__ __forceinline__ void wgmma_n32_ss(float (&d)[16], uint64_t da, uint64_t db) {
    asm volatile("wgmma.mma_async.sync.aligned.m64n32k16.f32.bf16.bf16 {%0,%1,%2,%3,%4,%5,%6,%7,%8,%9,%10,%11,%12,%13,%14,%15}, %16, %17, 1, 1, 1, 0, 0;"
        : "+f"(d[0]), "+f"(d[1]), "+f"(d[2]), "+f"(d[3]), "+f"(d[4]), "+f"(d[5]), "+f"(d[6]), "+f"(d[7]),
          "+f"(d[8]), "+f"(d[9]), "+f"(d[10]), "+f"(d[11]), "+f"(d[12]), "+f"(d[13]), "+f"(d[14]), "+f"(d[15])
        : "l"(da), "l"(db));
}
__device__ __forceinline__ void wg_fence() { asm volatile("wgmma.fence.sync.aligned;" ::: "memory"); }
__device__ __forceinline__ void wg_commit() { asm volatile("wgmma.commit_group.sync.aligned;" ::: "memory"); }
__device__ __forceinline__ void wg_wait0() { asm volatile("wgmma.wait_group.sync.aligned 0;" ::: "memory"); }
__device__ __forceinline__ void cluster_sync() { asm volatile("barrier.cluster.arrive.aligned;\nbarrier.cluster.wait.aligned;" ::: "memory"); }

#define STAMP(s, i) do {} while (0)
#define STAMPV(s, i, v) do {} while (0)

constexpr int XT_BYTES = 36864;
constexpr int O_XT = 0;
constexpr int O_AS = 3 * XT_BYTES;
constexpr int O_AF = O_AS + 16384;
constexpr int O_MF = O_AF + 16384;
constexpr int O_QM = O_MF + 9216;
constexpr int O_KM = O_QM + 1024;
constexpr int O_QKX = O_KM + 1024;
constexpr int O_VX = O_QKX + 8192;
constexpr int O_VM = O_VX + 16384;
constexpr int O_SC = O_VM + 4096;
constexpr int O_OF = O_SC + 2560;
constexpr int O_SX = O_OF + 2048;
constexpr int O_OXS = O_SX + 10240;
constexpr int O_MISC = O_OXS + 4096;
constexpr int O_BAR = O_MISC + 64;
constexpr int CHAIN_SMEM = O_BAR + 128;
static_assert(CHAIN_SMEM <= 232448, "smem");
constexpr int B_X = O_BAR, B_VX = O_BAR + 24, B_SX = O_BAR + 40, B_SC = O_BAR + 56, B_VM = O_BAR + 64, B_M = O_BAR + 72;
constexpr float SM_SCALE = 0.08838834764831845f * 1.4426950408889634f;
constexpr uint32_t ONES = 0x3f803f80u;

__device__ __forceinline__ uint32_t opaque(uint32_t v) { uint32_t o; asm volatile("mov.u32 %0, %1;" : "=r"(o) : "r"(v)); return o; }
__device__ __forceinline__ void st_async128(uint32_t a, uint32_t x, uint32_t y, uint32_t z, uint32_t w, uint32_t bar) {
    asm volatile("st.async.shared::cluster.mbarrier::complete_tx::bytes.v4.b32 [%0], {%1,%2,%3,%4}, [%5];" :: "r"(a), "r"(x), "r"(y), "r"(z), "r"(w), "r"(bar) : "memory");
}
__device__ __forceinline__ void tma_x_tile(uint32_t sb, const CUtensorMap* tm, int r, int j, int slot) {
    asm volatile("{\n.reg .pred p;\nelect.sync _|p, 0xffffffff;\n"
        "@p mbarrier.arrive.expect_tx.shared::cta.b64 _, [%2], 36864;\n"
        "@p cp.async.bulk.tensor.2d.shared::cluster.global.mbarrier::complete_tx::bytes.multicast::cluster [%0], [%1, {%3, %4}], [%2], %7;\n"
        "@p cp.async.bulk.tensor.2d.shared::cluster.global.mbarrier::complete_tx::bytes.multicast::cluster [%0+4096], [%1, {%5, %4}], [%2], %7;\n"
        "@p cp.async.bulk.tensor.2d.shared::cluster.global.mbarrier::complete_tx::bytes.multicast::cluster [%0+8192], [%1, {%6, %4}], [%2], %7;\n}"
        :: "r"(sb + O_XT + slot * XT_BYTES + 3 * r * 4096), "l"(tm), "r"(sb + B_X + 8 * slot), "r"(192 * r), "r"(j * 32), "r"(192 * r + 64), "r"(192 * r + 128),
           "h"((unsigned short)7) : "memory");
}
__device__ __forceinline__ float quad_max(float v) {
    const float a = __shfl_xor_sync(~0u, v, 1), b = __shfl_xor_sync(~0u, v, 2), c = __shfl_xor_sync(~0u, v, 3);
    return fmaxf(fmaxf(v, a), fmaxf(b, c));
}
__device__ __forceinline__ float rcp_fast(float x) { float y; asm("rcp.approx.ftz.f32 %0, %1;" : "=f"(y) : "f"(x)); return y; }

__global__ void __cluster_dims__(3, 1, 1) __launch_bounds__(384, 1)
chain_kernel(const __grid_constant__ CUtensorMap tm_x,
             const __nv_bfloat16* __restrict__ x, const __nv_bfloat16* __restrict__ mem0,
             const __nv_bfloat16* __restrict__ Wq, const __nv_bfloat16* __restrict__ Wk,
             const __nv_bfloat16* __restrict__ Wv, const __nv_bfloat16* __restrict__ Wo) {
    extern __shared__ __align__(1024) uint8_t smem_raw[];
    const uint32_t sb = smem_u32(smem_raw);
    const int lane = threadIdx.x & 31;
    const int warp = __shfl_sync(~0u, threadIdx.x >> 5, 0);
    const int wg = warp >> 2, w = warp & 3;
    const int h = blockIdx.x / 3, r = blockIdx.x - 3 * h;

    if (threadIdx.x == 0) {
        if (sb & 1023u) __trap();
        for (int i = 0; i < 9; i++) mbar_init(sb + O_BAR + 8 * i, 1);
        for (int i = 0; i < 3; i++) mbar_init(sb + B_M + 8 * i, 4);
        asm volatile("fence.mbarrier_init.release.cluster;" ::: "memory");
    }
    if (blockIdx.x == 0) {
        for (int i = threadIdx.x; i < NSEG * 4 * 8; i += 384) g_flag[i] = 0;
        __threadfence();
    }
    __syncthreads();
    cluster_sync();
    asm volatile("griddepcontrol.launch_dependents;" ::: "memory");
    const uint32_t l16c = __shfl_sync(~0u, lane * 16, lane);

    if (wg < 2) {
        asm volatile("setmaxnreg.inc.sync.aligned.u32 176;");
        uint32_t a[144];
        {
            const int g = lane >> 2, t = lane & 3;
            const __nv_bfloat16* W = (r < 2) ? (wg == 0 ? Wq : Wk) : Wv;
            const int col = h * 128 + ((r < 2) ? 64 * r : 64 * wg) + 16 * w + 2 * g;
            const __nv_bfloat16* p = W + (size_t)(2 * t) * HD + col;
#pragma unroll
            for (int kk = 0; kk < 36; kk++) {
                a[4 * kk + 0] = ldg_nc32(p + (size_t)(16 * kk + 0) * HD);
                a[4 * kk + 1] = ldg_nc32(p + (size_t)(16 * kk + 1) * HD);
                a[4 * kk + 2] = ldg_nc32(p + (size_t)(16 * kk + 8) * HD);
                a[4 * kk + 3] = ldg_nc32(p + (size_t)(16 * kk + 9) * HD);
            }
#pragma unroll
            for (int kk = 0; kk < 72; kk++) {
                uint32_t w0 = a[2 * kk], w1 = a[2 * kk + 1];
                a[2 * kk] = __byte_perm(w0, w1, 0x5410);
                a[2 * kk + 1] = __byte_perm(w0, w1, 0x7632);
            }
            float s0 = 0.f, s1 = 0.f;
#pragma unroll
            for (int kk = 0; kk < 72; kk++) {
                s0 += fabsf(__uint_as_float(a[2 * kk] << 16)) + fabsf(__uint_as_float(a[2 * kk] & 0xffff0000u));
                s1 += fabsf(__uint_as_float(a[2 * kk + 1] << 16)) + fabsf(__uint_as_float(a[2 * kk + 1] & 0xffff0000u));
            }
            s0 += __shfl_xor_sync(~0u, s0, 1); s0 += __shfl_xor_sync(~0u, s0, 2);
            s1 += __shfl_xor_sync(~0u, s1, 1); s1 += __shfl_xor_sync(~0u, s1, 2);
            uint32_t mx = __reduce_max_sync(~0u, __float_as_uint(fmaxf(s0, s1)));
            sts32_if(lane, sb + O_MISC + 32 + 4 * warp, mx);
            bar_arrive(7, 384);
            const uint32_t as = sb + O_AS + wg * 8192 + (16 * w + g) * 128 + t * 4;
#pragma unroll
            for (int kk = 0; kk < 4; kk++) {
                sts32(as + (((2 * kk) ^ g) << 4), a[128 + 4 * kk]);
                sts32(as + 1024 + (((2 * kk) ^ g) << 4), a[128 + 4 * kk + 1]);
                sts32(as + (((2 * kk + 1) ^ g) << 4), a[128 + 4 * kk + 2]);
                sts32(as + 1024 + (((2 * kk + 1) ^ g) << 4), a[128 + 4 * kk + 3]);
                sts128(sb + O_AF + warp * 2048 + kk * 512 + lane * 16, a[128 + 4 * kk], a[128 + 4 * kk + 1], a[128 + 4 * kk + 2], a[128 + 4 * kk + 3]);
            }
            fence_async_smem();
            bar_sync(1, 256);
        }
        int s3 = 2;
#pragma unroll 1
        for (int s = -1; s < NSEG; s++) {
            const uint32_t l16 = opaque(l16c);
            if (s >= 0) {
#pragma unroll
                for (int kk = 0; kk < 4; kk++) {
                    const uint4 v = lds128(sb + O_AF + warp * 2048 + kk * 512 + l16);
                    a[128 + 4 * kk] = v.x; a[128 + 4 * kk + 1] = v.y; a[128 + 4 * kk + 2] = v.z; a[128 + 4 * kk + 3] = v.w;
                }
                float c0[4], c1[4];
                uint4 b[18];
                float inv;
#pragma unroll
                for (int i = 0; i < 20; i++) {
                    if (i < 18) {
                        if (i == 0) bar_sync(2, 384);
                        else if (i % 6 == 0) mbar_wait(sb + B_M + 8 * (i / 6), s & 1);
                        if (i == 0 && warp == 0) STAMP(s, 0);
                        b[i] = lds128(sb + O_MF + i * 512 + l16);
                    }
                    if (i == 18) inv = __uint_as_float(lds32(sb + O_MISC));
                    if (i >= 2) {
                        const int tau = (i - 2) / 6, c = (i - 2) % 6;
                        const int k0 = 12 * tau + (c < 4 ? c : 8 + 2 * (c - 4));
                        const int k1 = 12 * tau + (c < 4 ? 4 + c : 9 + 2 * (c - 4));
                        if (i == 2) {
                            mma16816_z(c0, a[4 * k0], a[4 * k0 + 1], a[4 * k0 + 2], a[4 * k0 + 3], b[0].x, b[0].y);
                            mma16816_z(c1, a[4 * k1], a[4 * k1 + 1], a[4 * k1 + 2], a[4 * k1 + 3], b[0].z, b[0].w);
                        } else {
                            mma16816(c0, a[4 * k0], a[4 * k0 + 1], a[4 * k0 + 2], a[4 * k0 + 3], b[i - 2].x, b[i - 2].y);
                            mma16816(c1, a[4 * k1], a[4 * k1 + 1], a[4 * k1 + 2], a[4 * k1 + 3], b[i - 2].z, b[i - 2].w);
                        }
                    }
                }
                const uint32_t X0 = pack_bf16((c0[0] + c1[0]) * inv, (c0[1] + c1[1]) * inv);
                const uint32_t X1 = pack_bf16((c0[2] + c1[2]) * inv, (c0[3] + c1[3]) * inv);
                if (warp == 0) STAMP(s, 1);
                if (r < 2) {
                    stsm2t(wg ? (sb + O_KM + w * 256 + l16) : (sb + O_QM + (w >> 1) * 512 + (w & 1) * 128 + l16 + (l16 & 128)), X0, X1);
                    const uint32_t kx = sb + O_QKX + 4096 + l16 + (l16 & 256);
                    const uint32_t dst = sb + O_SC + r * 1280 + warp * 256 + (l16 >> 1);
                    const uint32_t d0 = mapa(dst, 2), d1 = mapa(dst, r ^ 1), d2 = mapa(dst, r);
                    bar_sync(1, 256);
                    if (warp < 5) {
                        const uint32_t kb = (warp == 0) ? (sb + O_KM + l16) : (kx + ((warp - 1) >> 1) * 2048 + ((warp - 1) & 1) * 256);
                        const uint4 q0 = ldsm4(sb + O_QM + l16), k0 = ldsm4(kb);
                        const uint4 q1 = ldsm4(sb + O_QM + 512 + l16), k1 = ldsm4(kb + ((warp == 0) ? 512 : 1024));
                        float s0[4], s1[4];
                        mma16816_z(s0, q0.x, q0.y, q0.z, q0.w, k0.x, k0.y);
                        mma16816_z(s1, q0.x, q0.y, q0.z, q0.w, k0.z, k0.w);
                        mma16816(s0, q1.x, q1.y, q1.z, q1.w, k1.x, k1.y);
                        mma16816(s1, q1.x, q1.y, q1.z, q1.w, k1.z, k1.w);
                        const uint32_t v0 = __float_as_uint(s0[0] + s1[2]), v1 = __float_as_uint(s0[1] + s1[3]);
                        st_async64(d0, v0, v1, mapa(sb + B_SC, 2));
                        st_async64(d1, v0, v1, mapa(sb + B_SC, r ^ 1));
                        st_async64(d2, v0, v1, mapa(sb + B_SC, r));
                    }
                    if (warp == 0) STAMP(s, 2);
                    {
                        const int mt = warp < 5 ? 1 : 0, n = warp < 5 ? warp : warp - 5;
                        const uint32_t qb = sb + O_QKX + mt * 2048 + l16;
                        const uint32_t kb = (n == 0) ? (sb + O_KM + l16) : (kx + ((n - 1) >> 1) * 2048 + ((n - 1) & 1) * 256);
                        const uint4 k0 = ldsm4(kb), q0 = ldsm4(qb), q1 = ldsm4(qb + 512);
                        const uint4 k1 = ldsm4(kb + ((n == 0) ? 512 : 1024)), q2 = ldsm4(qb + 1024), q3 = ldsm4(qb + 1536);
                        float sc[4];
                        mma16816_z(sc, q0.x, q0.y, q0.z, q0.w, k0.x, k0.y);
                        mma16816(sc, q1.x, q1.y, q1.z, q1.w, k0.z, k0.w);
                        mma16816(sc, q2.x, q2.y, q2.z, q2.w, k1.x, k1.y);
                        mma16816(sc, q3.x, q3.y, q3.z, q3.w, k1.z, k1.w);
                        const uint32_t dx = mapa(sb + O_SX + (s & 1) * 5120 + r * 2560 + n * 256 + (l16 >> 1), mt), bx = mapa(sb + B_SX + 8 * (s & 1), mt);
                        st_async64(dx, __float_as_uint(sc[0]), __float_as_uint(sc[1]), bx);
                        st_async64(dx + 1280, __float_as_uint(sc[2]), __float_as_uint(sc[3]), bx);
                    }
                } else {
                    const uint32_t dst = sb + O_VM + (s & 1) * 2048 + (warp >> 1) * 512 + l16 + (warp & 1) * 8;
                    st_async64(mapa(dst, 0), X0, X1, mapa(sb + B_VM, 0));
                    st_async64(mapa(dst, 1), X0, X1, mapa(sb + B_VM, 1));
                    st_async64(mapa(dst, 2), X0, X1, mapa(sb + B_VM, 2));
                    if (warp == 0) STAMP(s, 2);
                }
            }
            s3 = (s3 == 2) ? 0 : s3 + 1;
            if (s < NSEG - 1) {
                const int j = s + 1;
                mbar_wait(sb + B_X + 8 * s3, (j / 3) & 1);
                const uint64_t desc0 = (uint64_t)(((sb + O_XT + s3 * XT_BYTES) & 0x3FFFF) >> 4) | (1ull << 16) | (64ull << 32) | (1ull << 62);
                float d[16];
                wg_fence();
#pragma unroll
                for (int kk = 0; kk < XCHUNK1; kk++) {
                    const uint64_t desc = desc0 + (uint64_t)(((kk >> 2) * 4096 + (kk & 3) * 32) >> 4);
                    if (kk == 0) wgmma_n32_rs<0>(d, a[0], a[1], a[2], a[3], desc);
                    else wgmma_n32_rs<1>(d, a[4 * kk], a[4 * kk + 1], a[4 * kk + 2], a[4 * kk + 3], desc);
                }
                wg_commit();
                if (s >= 0) bar_sync(5, 384);
#pragma unroll
                for (int kk = XCHUNK1; kk < 36; kk++) {
                    const uint64_t desc = desc0 + (uint64_t)(((kk >> 2) * 4096 + (kk & 3) * 32) >> 4);
                    if (kk < 32) wgmma_n32_rs<1>(d, a[4 * kk], a[4 * kk + 1], a[4 * kk + 2], a[4 * kk + 3], desc);
                    else wgmma_n32_ss(d, (uint64_t)(((sb + O_AS + wg * 8192 + (kk - 32) * 32) & 0x3FFFF) >> 4) | (1ull << 16) | (64ull << 32) | (1ull << 62), desc);
                }
                wg_commit();
                if (warp == 7 && r < 2 && s >= 1)
                    asm volatile("{\n.reg .pred p;\nsetp.eq.u32 p, %1, 0;\nfence.acq_rel.gpu;\n@p red.relaxed.gpu.global.add.u32 [%0], 1;\n}"
                                 :: "l"(&g_flag[((s - 1) * 4 + (h >> 3)) * 8]), "r"(l16) : "memory");
                wg_wait0();
                if (warp == 0) STAMP(s, 3);
                uint32_t e[8];
#pragma unroll
                for (int i = 0; i < 8; i++) e[i] = pack_bf16(d[2 * i], d[2 * i + 1]);
                if (r < 2) {
                    const uint32_t base = sb + O_QKX + wg * 4096 + w * 512 + l16;
                    stsm4t(base, e[0], wg ? e[1] : e[2], wg ? e[2] : e[1], e[3]);
                    stsm4t(base + 2048, e[4], wg ? e[5] : e[6], wg ? e[6] : e[5], e[7]);
                } else {
                    const uint32_t base = sb + O_VX + (j & 1) * 8192 + warp * 1024 + l16;
                    sts128(base, e[0], e[1], e[2], e[3]);
                    sts128(base + 512, e[4], e[5], e[6], e[7]);
                    const uint32_t bar = sb + B_VX + 8 * (j & 1);
                    st_async128(mapa(base, 0), e[0], e[1], e[2], e[3], mapa(bar, 0));
                    st_async128(mapa(base + 512, 0), e[4], e[5], e[6], e[7], mapa(bar, 0));
                    st_async128(mapa(base, 1), e[0], e[1], e[2], e[3], mapa(bar, 1));
                    st_async128(mapa(base + 512, 1), e[4], e[5], e[6], e[7], mapa(bar, 1));
                }
                if (warp == 7) STAMP(s, 4);
            }
        }
    } else {
        asm volatile("setmaxnreg.dec.sync.aligned.u32 152;");
        const int c = w;
        uint32_t a[96];
        uint32_t mmax = 0;
        {
            const int g = lane >> 2, t = lane & 3, t2 = threadIdx.x - 256;
            if (c == 0) {
                tma_x_tile(sb, &tm_x, r, 0, 0);
                tma_x_tile(sb, &tm_x, r, 1, 1);
                mbar_expect_if(lane, sb + B_SC, 2560);
                mbar_expect_if(lane, sb + B_VM, 2048);
                if (r < 2) mbar_expect_if(lane, sb + B_VX, 8192);
                sts32_if(lane, sb + O_MISC, __float_as_uint(1.0f));
            }
#pragma unroll
            for (int i = 0; i < 4; i++) g_acc[blockIdx.x * 512 + i * 128 + t2] = make_uint4(0, 0, 0, 0);
#pragma unroll
            for (int tau = 0; tau < 3; tau++) {
                uint32_t v[6];
#pragma unroll
                for (int i = 0; i < 3; i++) {
                    const uint32_t* p = reinterpret_cast<const uint32_t*>(mem0 + g * DM + 16 * (12 * tau + 4 * i + c) + 2 * t);
                    v[2 * i] = __ldg(p); v[2 * i + 1] = __ldg(p + 4);
                    mmax = __vmaxu2(mmax, __vmaxu2(v[2 * i] & 0x7fff7fffu, v[2 * i + 1] & 0x7fff7fffu));
                }
                sts128(sb + O_MF + tau * 3072 + c * 512 + lane * 16, v[0], v[1], v[2], v[3]);
                sts64(sb + O_MF + tau * 3072 + 2048 + (c >> 1) * 512 + lane * 16 + (c & 1) * 8, v[4], v[5]);
            }
            bar_arrive(2, 384);
            mbar_arrive_if(lane, sb + B_M + 8); mbar_arrive_if(lane, sb + B_M + 16);
            uint32_t xm = 0;
            const uint4* xp = reinterpret_cast<const uint4*>(x) + blockIdx.x * 1536 + t2;
#pragma unroll
            for (int i = 0; i < 12; i++) {
                uint4 v = __ldg(xp + i * 128);
                xm = __vmaxu2(xm, __vmaxu2(__vmaxu2(v.x & 0x7fff7fffu, v.y & 0x7fff7fffu), __vmaxu2(v.z & 0x7fff7fffu, v.w & 0x7fff7fffu)));
            }
            xm = __reduce_max_sync(~0u, max(xm << 16, xm & 0xffff0000u));

            const __nv_bfloat16* p = Wo + (size_t)(h * 128 + 4 * t) * DM + 192 * r + 16 * c + 2 * g;
#pragma unroll
            for (int i = 0; i < 3; i++)
#pragma unroll
                for (int eb = 0; eb < 8; eb++)
#pragma unroll
                    for (int j = 0; j < 4; j++) a[(i * 8 + eb) * 4 + j] = ldg_nc32(p + (16 * eb + ((j & 1) * 2 + (j >> 1))) * DM + 64 * i);
#pragma unroll
            for (int kk = 0; kk < 48; kk++) {
                uint32_t w0 = a[2 * kk], w1 = a[2 * kk + 1];
                a[2 * kk] = __byte_perm(w0, w1, 0x5410);
                a[2 * kk + 1] = __byte_perm(w0, w1, 0x7632);
            }
            float wmax = 0.f;
#pragma unroll
            for (int i = 0; i < 3; i++) {
                float s0 = 0.f, s1 = 0.f;
#pragma unroll
                for (int kk = 16 * i; kk < 16 * i + 16; kk++) {
                    s0 += fabsf(__uint_as_float(a[2 * kk] << 16)) + fabsf(__uint_as_float(a[2 * kk] & 0xffff0000u));
                    s1 += fabsf(__uint_as_float(a[2 * kk + 1] << 16)) + fabsf(__uint_as_float(a[2 * kk + 1] & 0xffff0000u));
                }
                s0 += __shfl_xor_sync(~0u, s0, 1); s0 += __shfl_xor_sync(~0u, s0, 2);
                s1 += __shfl_xor_sync(~0u, s1, 1); s1 += __shfl_xor_sync(~0u, s1, 2);
                wmax = fmaxf(wmax, fmaxf(s0, s1));
            }
            uint32_t wm = __reduce_max_sync(~0u, __float_as_uint(wmax));
            sts32_if(lane, sb + O_OF + 4 * c, wm); sts32_if(lane, sb + O_OF + 16 + 4 * c, xm);
            __threadfence();
            bar_sync(7, 384);
            if (c == 0) {
                const uint4 wq = lds128(sb + O_OF), xq = lds128(sb + O_OF + 16), v0 = lds128(sb + O_MISC + 32), v1 = lds128(sb + O_MISC + 48);
                const uint32_t w1 = max(max(wq.x, wq.y), max(wq.z, wq.w)), x1 = max(max(xq.x, xq.y), max(xq.z, xq.w));
                const uint32_t vv = (r < 2) ? 0u : max(max(max(v0.x, v0.y), max(v0.z, v0.w)), max(max(v1.x, v1.y), max(v1.z, v1.w)));
                unsigned old = 0;
                asm volatile("{\n.reg .pred p;\nsetp.eq.u32 p, %6, 0;\n@p st.global.v4.u32 [%1], {%2,%3,%4,%4};\nfence.acq_rel.gpu;\n@p atom.relaxed.gpu.global.add.u32 %0, [%5], 1;\n}"
                             : "+r"(old) : "l"(&g_norm[blockIdx.x * 4]), "r"(w1), "r"(vv), "r"(x1), "l"(&g_gridbar), "r"(lane) : "memory");
                old = __shfl_sync(~0u, old, 0);
                const unsigned target = (old / 96u + 1u) * 96u;
                asm volatile("{\n.reg .pred p;\n.reg .u32 n, v;\nmov.u32 n, 0;\n"
                             "G_%=: ld.acquire.gpu.global.u32 v, [%0];\nsub.u32 v, v, %1;\nsetp.ge.s32 p, v, 0;\n@p bra.uni E_%=;\n"
                             "add.u32 n, n, 1;\nsetp.lt.u32 p, n, 4000000;\n@p bra.uni G_%=;\ntrap;\nE_%=:\n}" :: "l"(&g_gridbar), "r"(target) : "memory");
                uint4 n0 = ldg_relaxed128(&g_norm[lane * 4]), n1 = ldg_relaxed128(&g_norm[(lane + 32) * 4]), n2 = ldg_relaxed128(&g_norm[(lane + 64) * 4]);
                const float fw = __uint_as_float(__reduce_max_sync(~0u, max(n0.x, max(n1.x, n2.x))));
                const float fv = __uint_as_float(__reduce_max_sync(~0u, max(n0.y, max(n1.y, n2.y))));
                const float xmax = __uint_as_float(__reduce_max_sync(~0u, max(n0.z, max(n1.z, n2.z))));
                const float G = 36.f * fw * fv;
                sts32_if(lane, sb + O_MISC + 4, __float_as_uint(G)); sts32_if(lane, sb + O_MISC + 8, __float_as_uint(G * xmax));
            }
        }
        int s3p = 2;
#pragma unroll 1
        for (int s = 0; s < NSEG; s++) {
            const uint32_t l16 = opaque(l16c);
            unsigned t_red = 0;
            if (c == 0 && r < 2) mbar_expect_if(l16, sb + B_SX + 8 * (s & 1), r == 0 ? 3072 : 5120);
            if (s < NSEG - 1) {
                sts32_if(l16, sb + O_MISC + 16 + 4 * c, __reduce_max_sync(~0u, max(mmax << 16, mmax & 0xffff0000u)));
                bar_sync(6, 128);
                if (c == 0) {
                    if (s + 2 < NSEG) tma_x_tile(sb, &tm_x, r, s + 2, s3p);
                    if (r < 2) mbar_expect_if(l16, sb + B_VX + 8 * ((s + 1) & 1), 8192);
                }
                float sig; uint32_t inv_new;
                {
                    const uint4 mm = lds128(sb + O_MISC + 16), cf = lds128(sb + O_MISC);
                    const float bound = fmaxf(__uint_as_float(cf.z), __uint_as_float(cf.y) * (__uint_as_float(max(max(mm.x, mm.y), max(mm.z, mm.w))) * __uint_as_float(cf.x)));
                    int k = 15 - ((int)((__float_as_uint(bound) >> 23) & 255u) - 126);
                    k = min(max(k, -120), 120);
                    sig = __uint_as_float((uint32_t)(127 + k) << 23);
                    inv_new = (uint32_t)(127 - k) << 23;
                }
                const uint32_t lo = l16 >> 4;
                char* rbase = reinterpret_cast<char*>(g_acc) + ((s >> 1) * 24576 + (s & 1) * 128 + (r * 4 + c) * 2048)
                            + ((lo >> 4) * 512 + (lo & 2) * 128 + (lo & 1) * 64 + (lo & 12) * 4);
                if (c == 0) STAMP(s, 5);
                if (r < 2) mbar_wait(sb + B_VX + 8 * (s & 1), (s >> 1) & 1);
                mbar_wait(sb + B_VM, s & 1);
                uint4 vx[4];
#pragma unroll
                for (int q = 0; q < 4; q++) vx[q] = lds128(sb + O_VX + (s & 1) * 8192 + c * 2048 + q * 512 + l16);
                const uint4 vm = lds128(sb + O_VM + (s & 1) * 2048 + c * 512 + l16);
                if (c == 0) STAMP(s, 13);
                mbar_wait(sb + B_SC, s & 1);
                if (c == 0) STAMP(s, 6);
                float p[10];
#pragma unroll
                for (int n = 0; n < 5; n++) {
                    float2 u = lds64f(sb + O_SC + n * 256 + (l16 >> 1)), v = lds64f(sb + O_SC + 1280 + n * 256 + (l16 >> 1));
                    p[2 * n] = u.x + v.x; p[2 * n + 1] = u.y + v.y;
                }
                float mx = fmaxf(fmaxf(fmaxf(p[0], p[1]), fmaxf(p[2], p[3])), fmaxf(fmaxf(p[4], p[5]), fmaxf(p[6], p[7])));
                mx = quad_max(fmaxf(mx, fmaxf(p[8], p[9])));
                const float mo = mx * SM_SCALE;
                uint32_t P[5];
#pragma unroll
                for (int n = 0; n < 5; n++) P[n] = pack_bf16(ex2(fmaf(p[2 * n], SM_SCALE, -mo)), ex2(fmaf(p[2 * n + 1], SM_SCALE, -mo)));
                if (c == 0) STAMP(s, 7);
                float o0[4], o1[4], sm[4];
                mma1688_z(sm, ONES, ONES, P[0]);
                mma1688_z(o0, vm.x, vm.y, P[0]);
                mma1688_z(o1, vm.z, vm.w, P[0]);
                mma16816(sm, ONES, ONES, ONES, ONES, P[1], P[2]);
                mma16816(o0, vx[0].x, vx[0].y, vx[0].z, vx[0].w, P[1], P[2]);
                mma16816(o1, vx[2].x, vx[2].y, vx[2].z, vx[2].w, P[1], P[2]);
                mma16816(sm, ONES, ONES, ONES, ONES, P[3], P[4]);
                mma16816(o0, vx[1].x, vx[1].y, vx[1].z, vx[1].w, P[3], P[4]);
                mma16816(o1, vx[3].x, vx[3].y, vx[3].z, vx[3].w, P[3], P[4]);
                const float r0 = rcp_fast(sm[0]) * sig, r1 = rcp_fast(sm[1]) * sig;
                stsm4t(sb + O_OF + c * 512 + l16, pack_bf16(o0[0] * r0, o0[1] * r1), pack_bf16(o0[2] * r0, o0[3] * r1),
                       pack_bf16(o1[0] * r0, o1[1] * r1), pack_bf16(o1[2] * r0, o1[3] * r1));
                bar_sync(6, 128);
                uint4 ob[4];
#pragma unroll
                for (int q = 0; q < 4; q++) ob[q] = ldsm4(sb + O_OF + q * 512 + l16);
                float m0[3][4], m1[3][4];
#pragma unroll
                for (int q = 0; q < 4; q++) {
#pragma unroll
                    for (int i = 0; i < 3; i++) {
                        const int k0 = (i * 8 + 2 * q) * 4;
                        if (q == 0) mma16816_z(m0[i], a[k0], a[k0 + 1], a[k0 + 2], a[k0 + 3], ob[q].x, ob[q].y);
                        else mma16816(m0[i], a[k0], a[k0 + 1], a[k0 + 2], a[k0 + 3], ob[q].x, ob[q].y);
                    }
#pragma unroll
                    for (int i = 0; i < 3; i++) {
                        const int k1 = (i * 8 + 2 * q + 1) * 4;
                        if (q == 0) mma16816_z(m1[i], a[k1], a[k1 + 1], a[k1 + 2], a[k1 + 3], ob[q].z, ob[q].w);
                        else mma16816(m1[i], a[k1], a[k1 + 1], a[k1 + 2], a[k1 + 3], ob[q].z, ob[q].w);
                    }
                }
                asm volatile("red.relaxed.gpu.global.add.noftz.v4.f16x2 [%0], {%1,%2,%3,%4};" :: "l"(rbase),
                    "r"(pack_f16(m0[0][0] + m1[0][0], m0[0][2] + m1[0][2])), "r"(pack_f16(m0[1][0] + m1[1][0], m0[1][2] + m1[1][2])),
                    "r"(pack_f16(m0[2][0] + m1[2][0], m0[2][2] + m1[2][2])), "r"(0x3c00u) : "memory");
                asm volatile("red.relaxed.gpu.global.add.noftz.v4.f16x2 [%0], {%1,%2,%3,%4};" :: "l"(rbase + 1024),
                    "r"(pack_f16(m0[0][1] + m1[0][1], m0[0][3] + m1[0][3])), "r"(pack_f16(m0[1][1] + m1[1][1], m0[1][3] + m1[1][3])),
                    "r"(pack_f16(m0[2][1] + m1[2][1], m0[2][3] + m1[2][3])), "r"(0x3c00u) : "memory");
                t_red = clk();
                bar_arrive(5, 384);
                if (c == 0) { sts32_if(l16, sb + O_MISC, inv_new); mbar_expect_if(l16, sb + B_SC, 2560); mbar_expect_if(l16, sb + B_VM, 2048); }
                if (c == 0) STAMPV(s, 8, t_red);
            } else if (r < 2) {
                mbar_wait(sb + B_VM, s & 1);
                mbar_wait(sb + B_VX + 8 * (s & 1), (s >> 1) & 1);
            }

            if (r < 2) {
                mbar_wait(sb + B_SX + 8 * (s & 1), (s >> 1) & 1);
                const uint32_t so = sb + O_SX + (s & 1) * 5120 + (c & 1) * 1280 + (l16 >> 1);
                const int q0 = 16 * r + 8 * (c & 1) + 8 + (int)(l16 >> 6) - (int)((l16 >> 3) & 6);
                float p[10];
#pragma unroll
                for (int n = 0; n < 5; n++) {
                    const float2 u = lds64f(so + n * 256), v = lds64f(so + 2560 + n * 256);
                    p[2 * n] = u.x + v.x; p[2 * n + 1] = u.y + v.y;
                    if (n > 0) {
                        if (8 * n > q0) p[2 * n] = -INFINITY;
                        if (8 * n + 1 > q0) p[2 * n + 1] = -INFINITY;
                    }
                }
                float mx = fmaxf(fmaxf(fmaxf(p[0], p[1]), fmaxf(p[2], p[3])), fmaxf(fmaxf(p[4], p[5]), fmaxf(p[6], p[7])));
                mx = quad_max(fmaxf(mx, fmaxf(p[8], p[9])));
                const float mo = mx * SM_SCALE;
                uint32_t P[5];
#pragma unroll
                for (int n = 0; n < 5; n++) P[n] = pack_bf16(ex2(fmaf(p[2 * n], SM_SCALE, -mo)), ex2(fmaf(p[2 * n + 1], SM_SCALE, -mo)));
                float sm[4];
                mma1688_z(sm, ONES, ONES, P[0]);
                mma16816(sm, ONES, ONES, ONES, ONES, P[1], P[2]);
                mma16816(sm, ONES, ONES, ONES, ONES, P[3], P[4]);
                const uint32_t row = (l16 >> 4) & 7;
                const uint32_t stg = sb + O_OXS + c * 1024 + row * 128 + (((l16 >> 7) ^ row) << 4);
#pragma unroll
                for (int e2 = 0; e2 < 2; e2++) {
                    const uint4 vm = lds128(sb + O_VM + (s & 1) * 2048 + (c >> 1) * 1024 + e2 * 512 + l16);
                    const uint32_t vb = sb + O_VX + (s & 1) * 8192 + (c >> 1) * 4096 + e2 * 2048 + l16;
                    const uint4 v0 = lds128(vb), v1 = lds128(vb + 512), v2 = lds128(vb + 1024), v3 = lds128(vb + 1536);
                    float o0[4], o1[4];
                    mma1688_z(o0, vm.x, vm.y, P[0]);
                    mma1688_z(o1, vm.z, vm.w, P[0]);
                    mma16816(o0, v0.x, v0.y, v0.z, v0.w, P[1], P[2]);
                    mma16816(o1, v2.x, v2.y, v2.z, v2.w, P[1], P[2]);
                    mma16816(o0, v1.x, v1.y, v1.z, v1.w, P[3], P[4]);
                    mma16816(o1, v3.x, v3.y, v3.z, v3.w, P[3], P[4]);
                    const float r0 = rcp_fast(sm[0]), r1 = rcp_fast(sm[1]);
                    stsm4t(stg ^ (e2 * 64), pack_bf16(o0[0] * r0, o0[1] * r1), pack_bf16(o0[2] * r0, o0[3] * r1),
                           pack_bf16(o1[0] * r0, o1[1] * r1), pack_bf16(o1[2] * r0, o1[3] * r1));
                }
                __syncwarp();
            }
            auto store_ox = [&]() {
                char* op = reinterpret_cast<char*>(g_ox) + ((size_t)(h * 2 + (c >> 1)) * SEQ + s * 32 + 16 * r + 8 * (c & 1)) * 128 + l16;
                const uint4 u0 = lds128(sb + O_OXS + c * 1024 + l16), u1 = lds128(sb + O_OXS + c * 1024 + 512 + l16);
                *reinterpret_cast<uint4*>(op) = u0;
                *reinterpret_cast<uint4*>(op + 512) = u1;
            };
            if (s == NSEG - 1) {
                if (r < 2) store_ox();
            } else {
                if (c == 0) STAMP(s, 9);
                const uint32_t lo = l16 >> 4;
                const char* pbase = reinterpret_cast<const char*>(g_acc) + ((s >> 1) * 24576 + (s & 1) * 128 + c * 2048)
                      + ((lo & 4) * 256 + (lo >> 4) * 256 + (lo & 8) * 8 + (lo & 3) * 16);
                spin_until(t_red, D_WAIT);
                uint4 v[6];
#pragma unroll
                for (int i = 0; i < 6; i++) v[i] = ldg_relaxed128(pbase + (i >> 1) * 8192 + (i & 1) * 512);
                if (r < 2) store_ox();
                uint32_t bq[18];
                int nretry = 0;
#pragma unroll
                for (int tau = 0; tau < 3; tau++) {
                    asm volatile("{\n.reg .pred p, q;\n.reg .u32 n;\nmov.u32 n, 0;\n"
                                 "R_%=: setp.eq.u32 p, %3, 0x5000;\nsetp.eq.and.u32 p, %7, 0x5000, p;\nvote.sync.all.pred q, p, 0xffffffff;\n@q bra.uni K_%=;\n"
                                 "ld.relaxed.gpu.global.v4.u32 {%0,%1,%2,%3}, [%9];\nld.relaxed.gpu.global.v4.u32 {%4,%5,%6,%7}, [%9+512];\n"
                                 "add.u32 %8, %8, 1;\nadd.u32 n, n, 1;\nsetp.lt.u32 q, n, 2000000;\n@q bra.uni R_%=;\ntrap;\nK_%=:\n}"
                                 : "+r"(v[2 * tau].x), "+r"(v[2 * tau].y), "+r"(v[2 * tau].z), "+r"(v[2 * tau].w),
                                   "+r"(v[2 * tau + 1].x), "+r"(v[2 * tau + 1].y), "+r"(v[2 * tau + 1].z), "+r"(v[2 * tau + 1].w), "+r"(nretry)
                                 : "l"(pbase + tau * 8192) : "memory");
                    uint32_t* b = bq + 6 * tau;
                    b[0] = f16x2_to_bf16x2(v[2 * tau].x); b[1] = f16x2_to_bf16x2(v[2 * tau + 1].x);
                    b[2] = f16x2_to_bf16x2(v[2 * tau].y); b[3] = f16x2_to_bf16x2(v[2 * tau + 1].y);
                    b[4] = f16x2_to_bf16x2(v[2 * tau].z); b[5] = f16x2_to_bf16x2(v[2 * tau + 1].z);
                    sts128(sb + O_MF + tau * 3072 + c * 512 + l16, b[0], b[1], b[2], b[3]);
                    sts64(sb + O_MF + tau * 3072 + 2048 + (c >> 1) * 512 + (c & 1) * 8 + l16, b[4], b[5]);
                    if (tau == 0) bar_arrive(2, 384);
                    else { __syncwarp(); mbar_arrive_if(l16, sb + B_M + 8 * tau); }
                    if (c == 0) STAMP(s, 10 + tau);
                }
                if (c == 0) STAMPV(s, 14, nretry);
                mmax = 0;
#pragma unroll
                for (int i = 0; i < 18; i++) mmax = __vmaxu2(mmax, bq[i] & 0x7fff7fffu);
            }
            s3p = (s3p == 2) ? 0 : s3p + 1;
        }
        if (r < 2) {
            bar_sync(6, 128);
            if (c == 0)
                asm volatile("{\n.reg .pred p;\nsetp.eq.u32 p, %2, 0;\nfence.acq_rel.gpu;\n@p red.relaxed.gpu.global.add.u32 [%0], 1;\n@p red.relaxed.gpu.global.add.u32 [%1], 1;\n}"
                             :: "l"(&g_flag[(62 * 4 + (h >> 3)) * 8]), "l"(&g_flag[(63 * 4 + (h >> 3)) * 8]), "r"(l16c) : "memory");
        }
    }
    cluster_sync();
}

__device__ float g_u[SEQ * 2 * DM];
__global__ void naive_gemm1(const __nv_bfloat16* x, const __nv_bfloat16* Bre, const __nv_bfloat16* Bim) {
    int p = blockIdx.x * 64 + threadIdx.x % 64, tk = blockIdx.y * 4 + threadIdx.x / 64;
    float sr = 0, si = 0;
    for (int d = 0; d < DM; d++) { float xv = __bfloat162float(x[tk * DM + d]); sr += xv * __bfloat162float(Bre[p * DM + d]); si += xv * __bfloat162float(Bim[p * DM + d]); }
    g_u[tk * 2 * DM + 2 * p] = sr; g_u[tk * 2 * DM + 2 * p + 1] = si;
}
__global__ void naive_scan(const __nv_bfloat16* Lre, const __nv_bfloat16* Lim, const __nv_bfloat16* logdt) {
    int p = blockIdx.x * 64 + threadIdx.x;
    float dt = __bfloat162float(__float2bfloat16(expf(__bfloat162float(logdt[p]))));
    float lr = __bfloat162float(Lre[p]), li = __bfloat162float(Lim[p]);
    float e = expf(dt * lr), br = e * cosf(dt * li), bi = e * sinf(dt * li);
    float den = lr * lr + li * li;
    float cr = ((br - 1.f) * lr + bi * li) / den, ci = (bi * lr - (br - 1.f) * li) / den;
    float hr = 0, hi = 0;
    for (int tk = 0; tk < SEQ; tk++) {
        float ur = g_u[tk * 2 * DM + 2 * p], ui = g_u[tk * 2 * DM + 2 * p + 1];
        float nr = br * hr - bi * hi + cr * ur - ci * ui, ni = br * hi + bi * hr + cr * ui + ci * ur;
        hr = nr; hi = ni;
        g_u[tk * 2 * DM + 2 * p] = hr; g_u[tk * 2 * DM + 2 * p + 1] = hi;
    }
}
__global__ void naive_gemm2(const __nv_bfloat16* x, const __nv_bfloat16* Cre, const __nv_bfloat16* Cim, const __nv_bfloat16* Dk, float* out) {
    int d = blockIdx.x * 64 + threadIdx.x % 64, tk = blockIdx.y * 4 + threadIdx.x / 64;
    float s = 0;
    for (int p = 0; p < DM; p++) s += g_u[tk * 2 * DM + 2 * p] * __bfloat162float(Cre[d * DM + p]) - g_u[tk * 2 * DM + 2 * p + 1] * __bfloat162float(Cim[d * DM + p]);
    out[tk * 1152 + d] = 2.f * s + __bfloat162float(__float2bfloat16(__bfloat162float(x[tk * DM + d]) * __bfloat162float(Dk[d])));
}
__global__ void naive_wo(const __nv_bfloat16* Wo, float* out) {
    int d = blockIdx.x * 64 + threadIdx.x % 64, tk = blockIdx.y * 4 + threadIdx.x / 64;
    const __nv_bfloat16* ox = reinterpret_cast<const __nv_bfloat16*>(g_ox);
    float s = 0;
    for (int k = 0; k < HD; k++) {
        int hh = k >> 6, e0 = k & 63, e = (e0 & 48) + (e0 & 1) * 8 + ((e0 & 15) >> 1);
        s += __bfloat162float(ox[((size_t)hh * SEQ + tk) * 64 + (((e >> 3) ^ (tk & 7)) << 3) + (e & 7)]) * __bfloat162float(Wo[k * DM + d]);
    }
    out[tk * 1152 + DM + d] = s;
}

typedef CUresult (*EncodeFn)(CUtensorMap*, CUtensorMapDataType, cuuint32_t, void*, const cuuint64_t*, const cuuint64_t*, const cuuint32_t*, const cuuint32_t*,
                             CUtensorMapInterleave, CUtensorMapSwizzle, CUtensorMapL2promotion, CUtensorMapFloatOOBfill);
}

extern "C" void kernel_launch(void* const* d_in, const int* in_sizes, int n_in, void* d_out, int out_size) {
    typedef const __nv_bfloat16* bp;
    bp Ax = (bp)d_in[0], Lre = (bp)d_in[1], Lim = (bp)d_in[2], Bre = (bp)d_in[3], Bim = (bp)d_in[4], Cre = (bp)d_in[5], Cim = (bp)d_in[6],
       logdt = (bp)d_in[7], Dk = (bp)d_in[8], Bx = (bp)d_in[9], mem0 = (bp)d_in[10], Wq = (bp)d_in[11], Wk = (bp)d_in[12], Wv = (bp)d_in[13], Wo = (bp)d_in[14];
    float* out = (float*)d_out;
    static EncodeFn enc = nullptr;
    if (!enc) {
        void* fn = nullptr; cudaDriverEntryPointQueryResult qr;
        cudaGetDriverEntryPoint("cuTensorMapEncodeTiled", &fn, cudaEnableDefault, &qr);
        enc = (EncodeFn)fn;
        cudaFuncSetAttribute(chain_kernel, cudaFuncAttributeMaxDynamicSharedMemorySize, CHAIN_SMEM);
    }
    CUtensorMap tm_x;
    {
        cuuint64_t gd[2] = {DM, SEQ}; cuuint64_t gs[1] = {DM * 2}; cuuint32_t bd[2] = {64, 32}; cuuint32_t es[2] = {1, 1};
        enc(&tm_x, CU_TENSOR_MAP_DATA_TYPE_BFLOAT16, 2, (void*)Bx, gd, gs, bd, es, CU_TENSOR_MAP_INTERLEAVE_NONE, CU_TENSOR_MAP_SWIZZLE_128B,
            CU_TENSOR_MAP_L2_PROMOTION_L2_128B, CU_TENSOR_MAP_FLOAT_OOB_FILL_NONE);
    }
    cudaStream_t st = cudaStreamPerThread;
    chain_kernel<<<96, 384, CHAIN_SMEM, st>>>(tm_x, Bx, mem0, Wq, Wk, Wv, Wo);
    naive_gemm1<<<dim3(9, 512), 256, 0, st>>>(Ax, Bre, Bim);
    naive_scan<<<9, 64, 0, st>>>(Lre, Lim, logdt);
    naive_gemm2<<<dim3(9, 512), 256, 0, st>>>(Ax, Cre, Cim, Dk, out);
    naive_wo<<<dim3(9, 512), 256, 0, st>>>(Wo, out);
}
```

```cpp
#include <cuda_runtime.h>
#include <cuda.h>
#include <cuda_bf16.h>
#include <cuda_fp16.h>
#include <stdint.h>

#define D_WAIT 700
#define XCHUNK1 10

namespace {

constexpr int DM = 576, NH = 32, SEQ = 2048, NSEG = 64, HD = 4096;

__device__ uint4 g_acc[32 * 96 * 16];
__device__ uint4 g_ox[NH * 2 * SEQ * 8];
__device__ unsigned g_flag[NSEG * 4 * 8];
__device__ unsigned g_gridbar;
__device__ float g_norm[96 * 4];

__device__ __forceinline__ uint32_t smem_u32(const void* p) { return (uint32_t)__cvta_generic_to_shared(p); }
__device__ __forceinline__ uint32_t mapa(uint32_t a, uint32_t r) { uint32_t o; asm("mapa.shared::cluster.u32 %0, %1, %2;" : "=r"(o) : "r"(a), "r"(r)); return o; }
__device__ __forceinline__ unsigned clk() { unsigned long long c; asm volatile("mov.u64 %0, %%clock64;" : "=l"(c) :: "memory"); return (unsigned)c; }
__device__ __forceinline__ void mbar_init(uint32_t bar, uint32_t cnt) { asm volatile("mbarrier.init.shared::cta.b64 [%0], %1;" :: "r"(bar), "r"(cnt) : "memory"); }
__device__ __forceinline__ void mbar_expect(uint32_t bar, uint32_t bytes) { asm volatile("mbarrier.arrive.expect_tx.shared::cta.b64 _, [%0], %1;" :: "r"(bar), "r"(bytes) : "memory"); }
__device__ __forceinline__ void mbar_wait(uint32_t bar, uint32_t parity) {
    asm volatile("{\n.reg .pred p;\n.reg .u32 n;\nmov.u32 n, 0;\n"
                 "W_%=: mbarrier.try_wait.parity.shared::cta.b64 p, [%0], %1;\n@p bra.uni D_%=;\n"
                 "add.u32 n, n, 1;\nsetp.lt.u32 p, n, 4000000;\n@p bra.uni W_%=;\ntrap;\nD_%=:\n}" :: "r"(bar), "r"(parity) : "memory");
}
__device__ __forceinline__ void mbar_expect_if(uint32_t z, uint32_t bar, uint32_t bytes) {
    asm volatile("{\n.reg .pred p;\nsetp.eq.u32 p, %2, 0;\n@p mbarrier.arrive.expect_tx.shared::cta.b64 _, [%0], %1;\n}" :: "r"(bar), "r"(bytes), "r"(z) : "memory");
}
__device__ __forceinline__ void mbar_arrive_if(uint32_t z, uint32_t bar) {
    asm volatile("{\n.reg .pred p;\nsetp.eq.u32 p, %1, 0;\n@p mbarrier.arrive.shared::cta.b64 _, [%0];\n}" :: "r"(bar), "r"(z) : "memory");
}
__device__ __forceinline__ void sts32_if(uint32_t z, uint32_t a, uint32_t x) {
    asm volatile("{\n.reg .pred p;\nsetp.eq.u32 p, %2, 0;\n@p st.shared.u32 [%0], %1;\n}" :: "r"(a), "r"(x), "r"(z) : "memory");
}
__device__ __forceinline__ void spin_until(unsigned t0, unsigned d) {
    asm volatile("{\n.reg .pred p;\n.reg .u64 c;\n.reg .u32 lo;\n"
                 "S_%=: mov.u64 c, %%clock64;\ncvt.u32.u64 lo, c;\nsub.u32 lo, lo, %0;\nsetp.lt.u32 p, lo, %1;\n@p bra.uni S_%=;\n}" :: "r"(t0), "r"(d) : "memory");
}
__device__ __forceinline__ void bar_sync(int id, int n) { asm volatile("bar.sync %0, %1;" :: "r"(id), "r"(n) : "memory"); }
__device__ __forceinline__ void bar_arrive(int id, int n) { asm volatile("bar.arrive %0, %1;" :: "r"(id), "r"(n) : "memory"); }
__device__ __forceinline__ void fence_async_smem() { asm volatile("fence.proxy.async.shared::cta;" ::: "memory"); }
__device__ __forceinline__ uint32_t pack_bf16(float lo, float hi) { uint32_t r; asm("cvt.rn.bf16x2.f32 %0, %1, %2;" : "=r"(r) : "f"(hi), "f"(lo)); return r; }
__device__ __forceinline__ uint32_t pack_f16(float lo, float hi) { uint32_t r; asm("cvt.rn.f16x2.f32 %0, %1, %2;" : "=r"(r) : "f"(hi), "f"(lo)); return r; }
__device__ __forceinline__ uint32_t f16x2_to_bf16x2(uint32_t v) { float2 f = __half22float2(*reinterpret_cast<__half2*>(&v)); return pack_bf16(f.x, f.y); }
__device__ __forceinline__ float ex2(float x) { float y; asm("ex2.approx.ftz.f32 %0, %1;" : "=f"(y) : "f"(x)); return y; }
__device__ __forceinline__ uint4 lds128(uint32_t a) { uint4 v; asm volatile("ld.shared.v4.u32 {%0,%1,%2,%3}, [%4];" : "=r"(v.x), "=r"(v.y), "=r"(v.z), "=r"(v.w) : "r"(a) : "memory"); return v; }
__device__ __forceinline__ float4 lds128f(uint32_t a) { float4 v; asm volatile("ld.shared.v4.f32 {%0,%1,%2,%3}, [%4];" : "=f"(v.x), "=f"(v.y), "=f"(v.z), "=f"(v.w) : "r"(a) : "memory"); return v; }
__device__ __forceinline__ float2 lds64f(uint32_t a) { float2 v; asm volatile("ld.shared.v2.f32 {%0,%1}, [%2];" : "=f"(v.x), "=f"(v.y) : "r"(a) : "memory"); return v; }
__device__ __forceinline__ uint32_t lds32(uint32_t a) { uint32_t v; asm volatile("ld.shared.u32 %0, [%1];" : "=r"(v) : "r"(a) : "memory"); return v; }
__device__ __forceinline__ void sts128(uint32_t a, uint32_t x, uint32_t y, uint32_t z, uint32_t w) { asm volatile("st.shared.v4.u32 [%0], {%1,%2,%3,%4};" :: "r"(a), "r"(x), "r"(y), "r"(z), "r"(w) : "memory"); }
__device__ __forceinline__ void sts128f(uint32_t a, float x, float y, float z, float w) { asm volatile("st.shared.v4.f32 [%0], {%1,%2,%3,%4};" :: "r"(a), "f"(x), "f"(y), "f"(z), "f"(w) : "memory"); }
__device__ __forceinline__ void sts64(uint32_t a, uint32_t x, uint32_t y) { asm volatile("st.shared.v2.u32 [%0], {%1,%2};" :: "r"(a), "r"(x), "r"(y) : "memory"); }
__device__ __forceinline__ void sts32(uint32_t a, uint32_t x) { asm volatile("st.shared.u32 [%0], %1;" :: "r"(a), "r"(x) : "memory"); }
__device__ __forceinline__ uint4 ldsm4(uint32_t a) { uint4 v; asm volatile("ldmatrix.sync.aligned.m8n8.x4.shared.b16 {%0,%1,%2,%3}, [%4];" : "=r"(v.x), "=r"(v.y), "=r"(v.z), "=r"(v.w) : "r"(a) : "memory"); return v; }
__device__ __forceinline__ void stsm2t(uint32_t a, uint32_t x, uint32_t y) { asm volatile("stmatrix.sync.aligned.m8n8.x2.trans.shared.b16 [%0], {%1,%2};" :: "r"(a), "r"(x), "r"(y) : "memory"); }
__device__ __forceinline__ void stsm4t(uint32_t a, uint32_t x, uint32_t y, uint32_t z, uint32_t w) { asm volatile("stmatrix.sync.aligned.m8n8.x4.trans.shared.b16 [%0], {%1,%2,%3,%4};" :: "r"(a), "r"(x), "r"(y), "r"(z), "r"(w) : "memory"); }
__device__ __forceinline__ void st_async64(uint32_t a, uint32_t x, uint32_t y, uint32_t bar) { asm volatile("st.async.shared::cluster.mbarrier::complete_tx::bytes.v2.b32 [%0], {%1,%2}, [%3];" :: "r"(a), "r"(x), "r"(y), "r"(bar) : "memory"); }
__device__ __forceinline__ void bulk_s2c(uint32_t dst, uint32_t src, uint32_t bytes, uint32_t bar) { asm volatile("cp.async.bulk.shared::cluster.shared::cta.mbarrier::complete_tx::bytes [%0], [%1], %2, [%3];" :: "r"(dst), "r"(src), "r"(bytes), "r"(bar) : "memory"); }
__device__ __forceinline__ void bulk_s2g(void* dst, uint32_t src, uint32_t bytes) { asm volatile("cp.async.bulk.global.shared::cta.bulk_group [%0], [%1], %2;" :: "l"(dst), "r"(src), "r"(bytes) : "memory"); }
__device__ __forceinline__ uint32_t ldg_nc32(const void* p) { uint32_t v; asm volatile("ld.global.nc.L2::128B.u32 %0, [%1];" : "=r"(v) : "l"(p)); return v; }
__device__ __forceinline__ uint4 ldg_relaxed128(const void* p) { uint4 v; asm volatile("ld.relaxed.gpu.global.v4.u32 {%0,%1,%2,%3}, [%4];" : "=r"(v.x), "=r"(v.y), "=r"(v.z), "=r"(v.w) : "l"(p) : "memory"); return v; }
__device__ __forceinline__ void mma16816(float (&d)[4], uint32_t a0, uint32_t a1, uint32_t a2, uint32_t a3, uint32_t b0, uint32_t b1) {
    asm volatile("mma.sync.aligned.m16n8k16.row.col.f32.bf16.bf16.f32 {%0,%1,%2,%3}, {%4,%5,%6,%7}, {%8,%9}, {%0,%1,%2,%3};"
        : "+f"(d[0]), "+f"(d[1]), "+f"(d[2]), "+f"(d[3]) : "r"(a0), "r"(a1), "r"(a2), "r"(a3), "r"(b0), "r"(b1));
}
__device__ __forceinline__ void mma16816_z(float (&d)[4], uint32_t a0, uint32_t a1, uint32_t a2, uint32_t a3, uint32_t b0, uint32_t b1) {
    asm volatile("mma.sync.aligned.m16n8k16.row.col.f32.bf16.bf16.f32 {%0,%1,%2,%3}, {%4,%5,%6,%7}, {%8,%9}, {%10,%10,%10,%10};"
        : "=f"(d[0]), "=f"(d[1]), "=f"(d[2]), "=f"(d[3]) : "r"(a0), "r"(a1), "r"(a2), "r"(a3), "r"(b0), "r"(b1), "f"(0.f));
}
__device__ __forceinline__ void mma1688(float (&d)[4], uint32_t a0, uint32_t a1, uint32_t b0) {
    asm volatile("mma.sync.aligned.m16n8k8.row.col.f32.bf16.bf16.f32 {%0,%1,%2,%3}, {%4,%5}, {%6}, {%0,%1,%2,%3};"
        : "+f"(d[0]), "+f"(d[1]), "+f"(d[2]), "+f"(d[3]) : "r"(a0), "r"(a1), "r"(b0));
}
__device__ __forceinline__ void mma1688_z(float (&d)[4], uint32_t a0, uint32_t a1, uint32_t b0) {
    asm volatile("mma.sync.aligned.m16n8k8.row.col.f32.bf16.bf16.f32 {%0,%1,%2,%3}, {%4,%5}, {%6}, {%7,%7,%7,%7};"
        : "=f"(d[0]), "=f"(d[1]), "=f"(d[2]), "=f"(d[3]) : "r"(a0), "r"(a1), "r"(b0), "f"(0.f));
}
template <int ACC>
__device__ __forceinline__ void wgmma_n32_rs(float (&d)[16], uint32_t a0, uint32_t a1, uint32_t a2, uint32_t a3, uint64_t desc) {
    asm volatile("wgmma.mma_async.sync.aligned.m64n32k16.f32.bf16.bf16 {%0,%1,%2,%3,%4,%5,%6,%7,%8,%9,%10,%11,%12,%13,%14,%15}, {%16,%17,%18,%19}, %20, %21, 1, 1, 0;"
        : "+f"(d[0]), "+f"(d[1]), "+f"(d[2]), "+f"(d[3]), "+f"(d[4]), "+f"(d[5]), "+f"(d[6]), "+f"(d[7]),
          "+f"(d[8]), "+f"(d[9]), "+f"(d[10]), "+f"(d[11]), "+f"(d[12]), "+f"(d[13]), "+f"(d[14]), "+f"(d[15])
        : "r"(a0), "r"(a1), "r"(a2), "r"(a3), "l"(desc), "n"(ACC));
}
__device__ __forceinline__ void wgmma_n32_ss(float (&d)[16], uint64_t da, uint64_t db) {
    asm volatile("wgmma.mma_async.sync.aligned.m64n32k16.f32.bf16.bf16 {%0,%1,%2,%3,%4,%5,%6,%7,%8,%9,%10,%11,%12,%13,%14,%15}, %16, %17, 1, 1, 1, 0, 0;"
        : "+f"(d[0]), "+f"(d[1]), "+f"(d[2]), "+f"(d[3]), "+f"(d[4]), "+f"(d[5]), "+f"(d[6]), "+f"(d[7]),
          "+f"(d[8]), "+f"(d[9]), "+f"(d[10]), "+f"(d[11]), "+f"(d[12]), "+f"(d[13]), "+f"(d[14]), "+f"(d[15])
        : "l"(da), "l"(db));
}
__device__ __forceinline__ void wg_fence() { asm volatile("wgmma.fence.sync.aligned;" ::: "memory"); }
__device__ __forceinline__ void wg_commit() { asm volatile("wgmma.commit_group.sync.aligned;" ::: "memory"); }
__device__ __forceinline__ void wg_wait0() { asm volatile("wgmma.wait_group.sync.aligned 0;" ::: "memory"); }
__device__ __forceinline__ void cluster_sync() { asm volatile("barrier.cluster.arrive.aligned;\nbarrier.cluster.wait.aligned;" ::: "memory"); }

#define STAMP(s, i) do {} while (0)
#define STAMPV(s, i, v) do {} while (0)

constexpr int XT_BYTES = 36864;
constexpr int O_XT = 0;
constexpr int O_AS = 3 * XT_BYTES;
constexpr int O_AF = O_AS + 16384;
constexpr int O_MF = O_AF + 16384;
constexpr int O_QM = O_MF + 9216;
constexpr int O_KM = O_QM + 1024;
constexpr int O_QKX = O_KM + 2048;
constexpr int O_XP = O_QKX + 8192;
constexpr int O_VX = O_XP + 16384;
constexpr int O_VM = O_VX + 24576;
constexpr int O_SC = O_VM + 4096;
constexpr int O_OF = O_SC + 2560;
constexpr int O_SX = O_OF + 2048;
constexpr int O_OXS = O_SX + 10240;
constexpr int O_MISC = O_OXS + 4096;
constexpr int O_BAR = O_MISC + 64;
constexpr int CHAIN_SMEM = O_BAR + 128;
static_assert(CHAIN_SMEM <= 232448, "smem");
constexpr int B_X = O_BAR, B_VX = O_BAR + 24, B_SX = O_BAR + 40, B_SC = O_BAR + 56, B_VM = O_BAR + 64, B_M = O_BAR + 72;
constexpr float SM_SCALE = 0.08838834764831845f * 1.4426950408889634f;
constexpr uint32_t ONES = 0x3f803f80u;

__device__ __forceinline__ uint32_t opaque(uint32_t v) { uint32_t o; asm volatile("mov.u32 %0, %1;" : "=r"(o) : "r"(v)); return o; }
__device__ __forceinline__ void st_async128(uint32_t a, uint32_t x, uint32_t y, uint32_t z, uint32_t w, uint32_t bar) {
    asm volatile("st.async.shared::cluster.mbarrier::complete_tx::bytes.v4.b32 [%0], {%1,%2,%3,%4}, [%5];" :: "r"(a), "r"(x), "r"(y), "r"(z), "r"(w), "r"(bar) : "memory");
}
__device__ __forceinline__ void tma_x_tile(uint32_t sb, const CUtensorMap* tm, int r, int j, int slot) {
    asm volatile("{\n.reg .pred p;\nelect.sync _|p, 0xffffffff;\n"
        "@p mbarrier.arrive.expect_tx.shared::cta.b64 _, [%2], 36864;\n"
        "@p cp.async.bulk.tensor.2d.shared::cluster.global.mbarrier::complete_tx::bytes.multicast::cluster [%0], [%1, {%3, %4}], [%2], %7;\n"
        "@p cp.async.bulk.tensor.2d.shared::cluster.global.mbarrier::complete_tx::bytes.multicast::cluster [%0+4096], [%1, {%5, %4}], [%2], %7;\n"
        "@p cp.async.bulk.tensor.2d.shared::cluster.global.mbarrier::complete_tx::bytes.multicast::cluster [%0+8192], [%1, {%6, %4}], [%2], %7;\n}"
        :: "r"(sb + O_XT + slot * XT_BYTES + 3 * r * 4096), "l"(tm), "r"(sb + B_X + 8 * slot), "r"(192 * r), "r"(j * 32), "r"(192 * r + 64), "r"(192 * r + 128),
           "h"((unsigned short)7) : "memory");
}
__device__ __forceinline__ float quad_max(float v) {
    const float a = __shfl_xor_sync(~0u, v, 1), b = __shfl_xor_sync(~0u, v, 2), c = __shfl_xor_sync(~0u, v, 3);
    return fmaxf(fmaxf(v, a), fmaxf(b, c));
}
__device__ __forceinline__ float rcp_fast(float x) { float y; asm("rcp.approx.ftz.f32 %0, %1;" : "=f"(y) : "f"(x)); return y; }

__global__ void __cluster_dims__(3, 1, 1) __launch_bounds__(384, 1)
chain_kernel(const __grid_constant__ CUtensorMap tm_x,
             const __nv_bfloat16* __restrict__ x, const __nv_bfloat16* __restrict__ mem0,
             const __nv_bfloat16* __restrict__ Wq, const __nv_bfloat16* __restrict__ Wk,
             const __nv_bfloat16* __restrict__ Wv, const __nv_bfloat16* __restrict__ Wo) {
    extern __shared__ __align__(1024) uint8_t smem_raw[];
    const uint32_t sb = smem_u32(smem_raw);
    const int lane = threadIdx.x & 31;
    const int warp = __shfl_sync(~0u, threadIdx.x >> 5, 0);
    const int wg = warp >> 2, w = warp & 3;
    const int h = blockIdx.x / 3, r = blockIdx.x - 3 * h;

    if (threadIdx.x == 0) {
        if (sb & 1023u) __trap();
        for (int i = 0; i < 9; i++) mbar_init(sb + O_BAR + 8 * i, 1);
        for (int i = 0; i < 3; i++) mbar_init(sb + B_M + 8 * i, 4);
        asm volatile("fence.mbarrier_init.release.cluster;" ::: "memory");
    }
    if (blockIdx.x == 0) {
        for (int i = threadIdx.x; i < NSEG * 4 * 8; i += 384) g_flag[i] = 0;
        __threadfence();
    }
    __syncthreads();
    cluster_sync();
    asm volatile("griddepcontrol.launch_dependents;" ::: "memory");
    const uint32_t l16c = __shfl_sync(~0u, lane * 16, lane);

    if (wg < 2) {
#define KB(i) (12 * ((i) / 6) + (((i) % 6) >> 1 == 2 ? 8 + ((i) & 1) : (((i) % 6) >> 1) + 4 * ((i) & 1)))
        asm volatile("setmaxnreg.inc.sync.aligned.u32 176;");
        uint32_t a[144];
        uint32_t adr1, adr2;
        {
            const int g = lane >> 2, t = lane & 3;
#pragma unroll
            for (int tl = 0; tl < 2; tl++) {
                const int tile = tl ? wg : (wg ^ 1);
                const __nv_bfloat16* W = (r < 2) ? (tile == 0 ? Wq : Wk) : Wv;
                const int col = h * 128 + ((r < 2) ? 64 * r : 64 * tile) + 16 * w + 2 * g;
                const __nv_bfloat16* p = W + (size_t)(32 * wg + 2 * t) * HD + col;
#pragma unroll
                for (int i = 0; i < 18; i++) {
                    a[72 * tl + 4 * i + 0] = ldg_nc32(p + (size_t)(16 * KB(i) + 0) * HD);
                    a[72 * tl + 4 * i + 1] = ldg_nc32(p + (size_t)(16 * KB(i) + 1) * HD);
                    a[72 * tl + 4 * i + 2] = ldg_nc32(p + (size_t)(16 * KB(i) + 8) * HD);
                    a[72 * tl + 4 * i + 3] = ldg_nc32(p + (size_t)(16 * KB(i) + 9) * HD);
                }
            }
#pragma unroll
            for (int kk = 0; kk < 72; kk++) {
                uint32_t w0 = a[2 * kk], w1 = a[2 * kk + 1];
                a[2 * kk] = __byte_perm(w0, w1, 0x5410);
                a[2 * kk + 1] = __byte_perm(w0, w1, 0x7632);
            }
            float vmax = 0.f;
#pragma unroll
            for (int tl = 0; tl < 2; tl++) {
                float s0 = 0.f, s1 = 0.f;
#pragma unroll
                for (int kk = 36 * tl; kk < 36 * tl + 36; kk++) {
                    s0 += fabsf(__uint_as_float(a[2 * kk] << 16)) + fabsf(__uint_as_float(a[2 * kk] & 0xffff0000u));
                    s1 += fabsf(__uint_as_float(a[2 * kk + 1] << 16)) + fabsf(__uint_as_float(a[2 * kk + 1] & 0xffff0000u));
                }
                s0 += __shfl_xor_sync(~0u, s0, 1); s0 += __shfl_xor_sync(~0u, s0, 2);
                s1 += __shfl_xor_sync(~0u, s1, 1); s1 += __shfl_xor_sync(~0u, s1, 2);
                vmax = fmaxf(vmax, fmaxf(s0, s1));
            }
            uint32_t mx = __reduce_max_sync(~0u, __float_as_uint(2.f * vmax));
            sts32_if(lane, sb + O_MISC + 32 + 4 * warp, mx);
            bar_arrive(7, 384);
            const uint32_t as = sb + O_AS + wg * 8192 + (16 * w + g) * 128 + t * 4;
#pragma unroll
            for (int kk = 0; kk < 4; kk++) {
                sts32(as + (((2 * kk) ^ g) << 4), a[128 + 4 * kk]);
                sts32(as + 1024 + (((2 * kk) ^ g) << 4), a[128 + 4 * kk + 1]);
                sts32(as + (((2 * kk + 1) ^ g) << 4), a[128 + 4 * kk + 2]);
                sts32(as + 1024 + (((2 * kk + 1) ^ g) << 4), a[128 + 4 * kk + 3]);
                sts128(sb + O_AF + warp * 2048 + kk * 512 + lane * 16, a[128 + 4 * kk], a[128 + 4 * kk + 1], a[128 + 4 * kk + 2], a[128 + 4 * kk + 3]);
            }
            fence_async_smem();
            bar_sync(1, 256);
            const uint32_t l = lane * 16;
            const int n = warp < 5 ? warp : warp - 5;
            adr1 = (r == 2) ? (sb + O_VM + (warp >> 1) * 512 + (warp & 1) * 8 + l)
                            : (wg ? (sb + O_KM + (w >> 1) * 1024 + (w & 1) * 256 + l) : (sb + O_QM + (w >> 1) * 512 + (w & 1) * 128 + l + (l & 128)));
            adr2 = (n == 0) ? (sb + O_KM + l) : (sb + O_QKX + 4096 + l + (l & 256) + ((n - 1) >> 1) * 2048 + ((n - 1) & 1) * 256);
            adr1 = __shfl_sync(~0u, adr1, lane);
            adr2 = __shfl_sync(~0u, adr2, lane);
        }
        int s3 = 2;
#pragma unroll 1
        for (int s = -1; s < NSEG; s++) {
            const uint32_t l16 = opaque(l16c);
            if (s >= 0) {
#pragma unroll
                for (int kk = 0; kk < 4; kk++) {
                    const uint4 v = lds128(sb + O_AF + warp * 2048 + kk * 512 + l16);
                    a[128 + 4 * kk] = v.x; a[128 + 4 * kk + 1] = v.y; a[128 + 4 * kk + 2] = v.z; a[128 + 4 * kk + 3] = v.w;
                }
                float c0[4], c1[4], c2[4], c3[4];
                uint4 b[9];
#pragma unroll
                for (int i = 0; i < 10; i++) {
                    if (i < 9) {
                        if (i == 0) bar_sync(2, 384);
                        else if (i % 3 == 0) mbar_wait(sb + B_M + 8 * (i / 3), s & 1);
                        if (i == 0 && warp == 0) STAMP(s, 0);
                        b[i] = lds128(sb + O_MF + (i / 3) * 3072 + wg * 1536 + (i % 3) * 512 + l16);
                    }
                    if (i >= 1) {
                        const int u = 8 * (i - 1);
                        if (i == 1) {
                            mma16816_z(c0, a[u], a[u + 1], a[u + 2], a[u + 3], b[0].x, b[0].y);
                            mma16816_z(c1, a[u + 4], a[u + 5], a[u + 6], a[u + 7], b[0].z, b[0].w);
                            mma16816_z(c2, a[72 + u], a[72 + u + 1], a[72 + u + 2], a[72 + u + 3], b[0].x, b[0].y);
                            mma16816_z(c3, a[72 + u + 4], a[72 + u + 5], a[72 + u + 6], a[72 + u + 7], b[0].z, b[0].w);
                        } else {
                            mma16816(c0, a[u], a[u + 1], a[u + 2], a[u + 3], b[i - 1].x, b[i - 1].y);
                            mma16816(c1, a[u + 4], a[u + 5], a[u + 6], a[u + 7], b[i - 1].z, b[i - 1].w);
                            mma16816(c2, a[72 + u], a[72 + u + 1], a[72 + u + 2], a[72 + u + 3], b[i - 1].x, b[i - 1].y);
                            mma16816(c3, a[72 + u + 4], a[72 + u + 5], a[72 + u + 6], a[72 + u + 7], b[i - 1].z, b[i - 1].w);
                        }
                    }
                }
                sts128f(sb + O_XP + warp * 512 + l16, c0[0] + c1[0], c0[1] + c1[1], c0[2] + c1[2], c0[3] + c1[3]);
                const float inv = __uint_as_float(lds32(sb + O_MISC));
                bar_sync(8 + w, 64);
                const float4 o = lds128f(sb + O_XP + (warp ^ 4) * 512 + l16);
                const uint32_t X0 = pack_bf16((c2[0] + c3[0] + o.x) * inv, (c2[1] + c3[1] + o.y) * inv);
                const uint32_t X1 = pack_bf16((c2[2] + c3[2] + o.z) * inv, (c2[3] + c3[3] + o.w) * inv);
                if (warp == 0) STAMP(s, 1);
                if (r < 2) {
                    stsm2t(adr1, X0, X1);
                    bar_sync(1, 256);
                    const uint4 k0 = ldsm4(adr2), k1 = ldsm4(adr2 + 1024);
                    if (warp < 5) {
                        const uint4 q0 = ldsm4(sb + O_QM + l16), q1 = ldsm4(sb + O_QM + 512 + l16);
                        float s0[4], s1[4];
                        mma16816_z(s0, q0.x, q0.y, q0.z, q0.w, k0.x, k0.y);
                        mma16816_z(s1, q0.x, q0.y, q0.z, q0.w, k0.z, k0.w);
                        mma16816(s0, q1.x, q1.y, q1.z, q1.w, k1.x, k1.y);
                        mma16816(s1, q1.x, q1.y, q1.z, q1.w, k1.z, k1.w);
                        const uint32_t dst = sb + O_SC + r * 1280 + warp * 256 + (l16 >> 1);
                        const uint32_t v0 = __float_as_uint(s0[0] + s1[2]), v1 = __float_as_uint(s0[1] + s1[3]);
                        st_async64(mapa(dst, 2), v0, v1, mapa(sb + B_SC, 2));
                        st_async64(mapa(dst, r ^ 1), v0, v1, mapa(sb + B_SC, r ^ 1));
                        st_async64(mapa(dst, r), v0, v1, mapa(sb + B_SC, r));
                    }
                    if (warp == 0) STAMP(s, 2);
                    {
                        const int mt = warp < 5 ? 1 : 0, n = warp < 5 ? warp : warp - 5;
                        const uint32_t qb = sb + O_QKX + mt * 2048 + l16;
                        const uint4 q0 = ldsm4(qb), q1 = ldsm4(qb + 512), q2 = ldsm4(qb + 1024), q3 = ldsm4(qb + 1536);
                        float sc[4], sd[4];
                        mma16816_z(sc, q0.x, q0.y, q0.z, q0.w, k0.x, k0.y);
                        mma16816_z(sd, q1.x, q1.y, q1.z, q1.w, k0.z, k0.w);
                        mma16816(sc, q2.x, q2.y, q2.z, q2.w, k1.x, k1.y);
                        mma16816(sd, q3.x, q3.y, q3.z, q3.w, k1.z, k1.w);
                        const uint32_t dx = mapa(sb + O_SX + (s & 1) * 5120 + r * 2560 + n * 256 + (l16 >> 1), mt), bx = mapa(sb + B_SX + 8 * (s & 1), mt);
                        st_async64(dx, __float_as_uint(sc[0] + sd[0]), __float_as_uint(sc[1] + sd[1]), bx);
                        st_async64(dx + 1280, __float_as_uint(sc[2] + sd[2]), __float_as_uint(sc[3] + sd[3]), bx);
                    }
                } else {
                    const uint32_t dst = adr1 + (s & 1) * 2048;
                    st_async64(mapa(dst, 0), X0, X1, mapa(sb + B_VM, 0));
                    st_async64(mapa(dst, 1), X0, X1, mapa(sb + B_VM, 1));
                    st_async64(mapa(dst, 2), X0, X1, mapa(sb + B_VM, 2));
                    if (warp == 0) STAMP(s, 2);
                }
            }
            s3 = (s3 == 2) ? 0 : s3 + 1;
            if (s < NSEG - 1) {
                const int j = s + 1;
                const uint64_t desc0 = (uint64_t)(((sb + O_XT + s3 * XT_BYTES + wg * 64) & 0x3FFFF) >> 4) | (1ull << 16) | (64ull << 32) | (1ull << 62);
#define XDESC(i) (desc0 + (uint64_t)(((KB(i) >> 2) * 4096 + (KB(i) & 3) * 32) >> 4))
                float d[16];
                if (s >= 0) bar_sync(3, 384);
                mbar_wait(sb + B_X + 8 * s3, (j / 3) & 1);
                wg_fence();
#pragma unroll
                for (int i = 0; i < XCHUNK1; i++) {
                    if (i == 0) wgmma_n32_rs<0>(d, a[0], a[1], a[2], a[3], XDESC(0));
                    else wgmma_n32_rs<1>(d, a[4 * i], a[4 * i + 1], a[4 * i + 2], a[4 * i + 3], XDESC(i));
                }
                wg_commit();
                if (wg == 1) bar_sync(s >= 0 ? 5 : 1, s >= 0 ? 384 : 256);
#pragma unroll
                for (int i = XCHUNK1; i < 18; i++) wgmma_n32_rs<1>(d, a[4 * i], a[4 * i + 1], a[4 * i + 2], a[4 * i + 3], XDESC(i));
                wg_commit();
                wg_wait0();
                if (warp == 0) STAMP(s, 15);
#pragma unroll
                for (int q = 0; q < 4; q++) sts128f(sb + O_XP + warp * 2048 + q * 512 + l16, d[4 * q], d[4 * q + 1], d[4 * q + 2], d[4 * q + 3]);
                if (wg == 0) bar_sync(s >= 0 ? 5 : 1, s >= 0 ? 384 : 256);
                else bar_arrive(8 + w, 64);
                wg_fence();
#pragma unroll
                for (int i = 0; i < 18; i++) {
                    if (i == 0) wgmma_n32_rs<0>(d, a[72], a[73], a[74], a[75], XDESC(0));
                    else if (i < 14) wgmma_n32_rs<1>(d, a[72 + 4 * i], a[72 + 4 * i + 1], a[72 + 4 * i + 2], a[72 + 4 * i + 3], XDESC(i));
                    else wgmma_n32_ss(d, (uint64_t)(((sb + O_AS + wg * 8192 + (i - 14) * 32) & 0x3FFFF) >> 4) | (1ull << 16) | (64ull << 32) | (1ull << 62), XDESC(i));
                }
                wg_commit();
                if (warp == 3 && r < 2 && s >= 2)
                    asm volatile("{\n.reg .pred p;\nsetp.eq.u32 p, %1, 0;\nfence.acq_rel.gpu;\n@p red.relaxed.gpu.global.add.u32 [%0], 1;\n}"
                                 :: "l"(&g_flag[((s - 2) * 4 + (h >> 3)) * 8]), "r"(l16) : "memory");
                if (wg == 0) bar_sync(8 + w, 64);
                wg_wait0();
                if (warp == 4) STAMP(s, 3);
                uint32_t e[8];
#pragma unroll
                for (int q = 0; q < 4; q++) {
                    const float4 o = lds128f(sb + O_XP + (warp ^ 4) * 2048 + q * 512 + l16);
                    e[2 * q] = pack_bf16(d[4 * q] + o.x, d[4 * q + 1] + o.y);
                    e[2 * q + 1] = pack_bf16(d[4 * q + 2] + o.z, d[4 * q + 3] + o.w);
                }
                if (r < 2) {
                    const uint32_t base = sb + O_QKX + wg * 4096 + w * 512 + l16;
                    stsm4t(base, e[0], wg ? e[1] : e[2], wg ? e[2] : e[1], e[3]);
                    stsm4t(base + 2048, e[4], wg ? e[5] : e[6], wg ? e[6] : e[5], e[7]);
                } else {
                    const uint32_t base = sb + O_VX + s3 * 8192 + warp * 1024 + l16;
                    sts128(base, e[0], e[1], e[2], e[3]);
                    sts128(base + 512, e[4], e[5], e[6], e[7]);
                    const uint32_t bar = sb + B_VX + 8 * (j & 1);
                    st_async128(mapa(base, 0), e[0], e[1], e[2], e[3], mapa(bar, 0));
                    st_async128(mapa(base + 512, 0), e[4], e[5], e[6], e[7], mapa(bar, 0));
                    st_async128(mapa(base, 1), e[0], e[1], e[2], e[3], mapa(bar, 1));
                    st_async128(mapa(base + 512, 1), e[4], e[5], e[6], e[7], mapa(bar, 1));
                }
                if (warp == 7) STAMP(s, 4);
            }
        }
    } else {
        asm volatile("setmaxnreg.dec.sync.aligned.u32 152;");
        const int c = w;
        uint32_t a[96];
        uint32_t mmax = 0;
        {
            const int g = lane >> 2, t = lane & 3, t2 = threadIdx.x - 256;
            if (c == 0) {
                tma_x_tile(sb, &tm_x, r, 0, 0);
                tma_x_tile(sb, &tm_x, r, 1, 1);
                mbar_expect_if(lane, sb + B_SC, 2560);
                mbar_expect_if(lane, sb + B_VM, 2048);
                if (r < 2) mbar_expect_if(lane, sb + B_VX, 8192);
                sts32_if(lane, sb + O_MISC, __float_as_uint(1.0f));
            }
#pragma unroll
            for (int i = 0; i < 4; i++) g_acc[blockIdx.x * 512 + i * 128 + t2] = make_uint4(0, 0, 0, 0);
#pragma unroll
            for (int tau = 0; tau < 3; tau++) {
                uint32_t v[6];
#pragma unroll
                for (int i = 0; i < 3; i++) {
                    const uint32_t* p = reinterpret_cast<const uint32_t*>(mem0 + g * DM + 16 * (12 * tau + 4 * i + c) + 2 * t);
                    v[2 * i] = __ldg(p); v[2 * i + 1] = __ldg(p + 4);
                    mmax = __vmaxu2(mmax, __vmaxu2(v[2 * i] & 0x7fff7fffu, v[2 * i + 1] & 0x7fff7fffu));
                }
                sts128(sb + O_MF + tau * 3072 + (c >> 1) * 1536 + (c & 1) * 512 + lane * 16, v[0], v[1], v[2], v[3]);
                sts64(sb + O_MF + tau * 3072 + (c >> 1) * 1536 + 1024 + lane * 16 + (c & 1) * 8, v[4], v[5]);
            }
            bar_arrive(2, 384);
            mbar_arrive_if(lane, sb + B_M + 8); mbar_arrive_if(lane, sb + B_M + 16);
            uint32_t xm = 0;
            const uint4* xp = reinterpret_cast<const uint4*>(x) + blockIdx.x * 1536 + t2;
#pragma unroll
            for (int i = 0; i < 12; i++) {
                uint4 v = __ldg(xp + i * 128);
                xm = __vmaxu2(xm, __vmaxu2(__vmaxu2(v.x & 0x7fff7fffu, v.y & 0x7fff7fffu), __vmaxu2(v.z & 0x7fff7fffu, v.w & 0x7fff7fffu)));
            }
            xm = __reduce_max_sync(~0u, max(xm << 16, xm & 0xffff0000u));

            const __nv_bfloat16* p = Wo + (size_t)(h * 128 + 4 * t) * DM + 192 * r + 16 * c + 2 * g;
#pragma unroll
            for (int i = 0; i < 3; i++)
#pragma unroll
                for (int eb = 0; eb < 8; eb++)
#pragma unroll
                    for (int j = 0; j < 4; j++) a[(i * 8 + eb) * 4 + j] = ldg_nc32(p + (16 * eb + ((j & 1) * 2 + (j >> 1))) * DM + 64 * i);
#pragma unroll
            for (int kk = 0; kk < 48; kk++) {
                uint32_t w0 = a[2 * kk], w1 = a[2 * kk + 1];
                a[2 * kk] = __byte_perm(w0, w1, 0x5410);
                a[2 * kk + 1] = __byte_perm(w0, w1, 0x7632);
            }
            float wmax = 0.f;
#pragma unroll
            for (int i = 0; i < 3; i++) {
                float s0 = 0.f, s1 = 0.f;
#pragma unroll
                for (int kk = 16 * i; kk < 16 * i + 16; kk++) {
                    s0 += fabsf(__uint_as_float(a[2 * kk] << 16)) + fabsf(__uint_as_float(a[2 * kk] & 0xffff0000u));
                    s1 += fabsf(__uint_as_float(a[2 * kk + 1] << 16)) + fabsf(__uint_as_float(a[2 * kk + 1] & 0xffff0000u));
                }
                s0 += __shfl_xor_sync(~0u, s0, 1); s0 += __shfl_xor_sync(~0u, s0, 2);
                s1 += __shfl_xor_sync(~0u, s1, 1); s1 += __shfl_xor_sync(~0u, s1, 2);
                wmax = fmaxf(wmax, fmaxf(s0, s1));
            }
            uint32_t wm = __reduce_max_sync(~0u, __float_as_uint(wmax));
            sts32_if(lane, sb + O_OF + 4 * c, wm); sts32_if(lane, sb + O_OF + 16 + 4 * c, xm);
            __threadfence();
            bar_sync(7, 384);
            if (c == 0) {
                const uint4 wq = lds128(sb + O_OF), xq = lds128(sb + O_OF + 16), v0 = lds128(sb + O_MISC + 32), v1 = lds128(sb + O_MISC + 48);
                const uint32_t w1 = max(max(wq.x, wq.y), max(wq.z, wq.w)), x1 = max(max(xq.x, xq.y), max(xq.z, xq.w));
                const uint32_t vv = (r < 2) ? 0u : max(max(max(v0.x, v0.y), max(v0.z, v0.w)), max(max(v1.x, v1.y), max(v1.z, v1.w)));
                unsigned old = 0;
                asm volatile("{\n.reg .pred p;\nsetp.eq.u32 p, %6, 0;\n@p st.global.v4.u32 [%1], {%2,%3,%4,%4};\nfence.acq_rel.gpu;\n@p atom.relaxed.gpu.global.add.u32 %0, [%5], 1;\n}"
                             : "+r"(old) : "l"(&g_norm[blockIdx.x * 4]), "r"(w1), "r"(vv), "r"(x1), "l"(&g_gridbar), "r"(lane) : "memory");
                old = __shfl_sync(~0u, old, 0);
                const unsigned target = (old / 96u + 1u) * 96u;
                asm volatile("{\n.reg .pred p;\n.reg .u32 n, v;\nmov.u32 n, 0;\n"
                             "G_%=: ld.acquire.gpu.global.u32 v, [%0];\nsub.u32 v, v, %1;\nsetp.ge.s32 p, v, 0;\n@p bra.uni E_%=;\n"
                             "add.u32 n, n, 1;\nsetp.lt.u32 p, n, 4000000;\n@p bra.uni G_%=;\ntrap;\nE_%=:\n}" :: "l"(&g_gridbar), "r"(target) : "memory");
                uint4 n0 = ldg_relaxed128(&g_norm[lane * 4]), n1 = ldg_relaxed128(&g_norm[(lane + 32) * 4]), n2 = ldg_relaxed128(&g_norm[(lane + 64) * 4]);
                const float fw = __uint_as_float(__reduce_max_sync(~0u, max(n0.x, max(n1.x, n2.x))));
                const float fv = __uint_as_float(__reduce_max_sync(~0u, max(n0.y, max(n1.y, n2.y))));
                const float xmax = __uint_as_float(__reduce_max_sync(~0u, max(n0.z, max(n1.z, n2.z))));
                const float G = 36.f * fw * fv;
                sts32_if(lane, sb + O_MISC + 4, __float_as_uint(G)); sts32_if(lane, sb + O_MISC + 8, __float_as_uint(G * xmax));
            }
        }
        int s3p = 2;
        uint32_t PX[5] = {0u, 0u, 0u, 0u, 0u};
#pragma unroll 1
        for (int s = 0; s <= NSEG; s++) {
            const uint32_t l16 = opaque(l16c);
            const int s3 = (s3p == 2) ? 0 : s3p + 1;
            unsigned t_red = 0;
            float sig = 0.f; uint32_t inv_new = 0;
            if (s < NSEG - 1) {
                sts32_if(l16, sb + O_MISC + 16 + 4 * c, __reduce_max_sync(~0u, max(mmax << 16, mmax & 0xffff0000u)));
                bar_sync(6, 128);
                if (c == 0) {
                    if (s + 2 < NSEG) tma_x_tile(sb, &tm_x, r, s + 2, s3p);
                    if (r < 2) mbar_expect_if(l16, sb + B_VX + 8 * ((s + 1) & 1), 8192);
                }
                const uint4 mm = lds128(sb + O_MISC + 16), cf = lds128(sb + O_MISC);
                const float bound = fmaxf(__uint_as_float(cf.z), __uint_as_float(cf.y) * (__uint_as_float(max(max(mm.x, mm.y), max(mm.z, mm.w))) * __uint_as_float(cf.x)));
                int k = 15 - ((int)((__float_as_uint(bound) >> 23) & 255u) - 126);
                k = min(max(k, -120), 120);
                sig = __uint_as_float((uint32_t)(127 + k) << 23);
                inv_new = (uint32_t)(127 - k) << 23;
            }
            if (c == 0 && r < 2 && s < NSEG) mbar_expect_if(l16, sb + B_SX + 8 * (s & 1), r == 0 ? 3072 : 5120);
            if (c == 0) STAMP(s < NSEG ? s : -1, 5);
            if (r < 2 && s >= 1) {
                float sm[4];
                mma1688_z(sm, ONES, ONES, PX[0]);
                mma16816(sm, ONES, ONES, ONES, ONES, PX[1], PX[2]);
                mma16816(sm, ONES, ONES, ONES, ONES, PX[3], PX[4]);
                const uint32_t row = (l16 >> 4) & 7;
                const uint32_t stg = sb + O_OXS + c * 1024 + row * 128 + (((l16 >> 7) ^ row) << 4);
#pragma unroll
                for (int e2 = 0; e2 < 2; e2++) {
                    const uint4 vm = lds128(sb + O_VM + ((s - 1) & 1) * 2048 + (c >> 1) * 1024 + e2 * 512 + l16);
                    const uint32_t vb = sb + O_VX + s3p * 8192 + (c >> 1) * 4096 + e2 * 2048 + l16;
                    const uint4 v0 = lds128(vb), v1 = lds128(vb + 512), v2 = lds128(vb + 1024), v3 = lds128(vb + 1536);
                    float o0[4], o1[4];
                    mma1688_z(o0, vm.x, vm.y, PX[0]);
                    mma1688_z(o1, vm.z, vm.w, PX[0]);
                    mma16816(o0, v0.x, v0.y, v0.z, v0.w, PX[1], PX[2]);
                    mma16816(o1, v2.x, v2.y, v2.z, v2.w, PX[1], PX[2]);
                    mma16816(o0, v1.x, v1.y, v1.z, v1.w, PX[3], PX[4]);
                    mma16816(o1, v3.x, v3.y, v3.z, v3.w, PX[3], PX[4]);
                    const float r0 = rcp_fast(sm[0]), r1 = rcp_fast(sm[1]);
                    stsm4t(stg ^ (e2 * 64), pack_bf16(o0[0] * r0, o0[1] * r1), pack_bf16(o0[2] * r0, o0[3] * r1),
                           pack_bf16(o1[0] * r0, o1[1] * r1), pack_bf16(o1[2] * r0, o1[3] * r1));
                }
                __syncwarp();
            }
            if (s < NSEG - 1) {
                bar_arrive(3, 384);
                const uint32_t lo = l16 >> 4;
                char* rbase = reinterpret_cast<char*>(g_acc) + ((s >> 1) * 24576 + (s & 1) * 128 + (r * 4 + c) * 2048)
                            + ((lo >> 4) * 512 + (lo & 2) * 128 + (lo & 1) * 64 + (lo & 12) * 4);
                if (r < 2) mbar_wait(sb + B_VX + 8 * (s & 1), (s >> 1) & 1);
                mbar_wait(sb + B_VM, s & 1);
                uint4 vx[4];
#pragma unroll
                for (int q = 0; q < 4; q++) vx[q] = lds128(sb + O_VX + s3 * 8192 + c * 2048 + q * 512 + l16);
                const uint4 vm = lds128(sb + O_VM + (s & 1) * 2048 + c * 512 + l16);
                if (c == 0) STAMP(s, 13);
                mbar_wait(sb + B_SC, s & 1);
                if (c == 0) STAMP(s, 6);
                float p[10];
#pragma unroll
                for (int n = 0; n < 5; n++) {
                    float2 u = lds64f(sb + O_SC + n * 256 + (l16 >> 1)), v = lds64f(sb + O_SC + 1280 + n * 256 + (l16 >> 1));
                    p[2 * n] = u.x + v.x; p[2 * n + 1] = u.y + v.y;
                }
                float mx = fmaxf(fmaxf(fmaxf(p[0], p[1]), fmaxf(p[2], p[3])), fmaxf(fmaxf(p[4], p[5]), fmaxf(p[6], p[7])));
                mx = quad_max(fmaxf(mx, fmaxf(p[8], p[9])));
                const float mo = mx * SM_SCALE;
                uint32_t P[5];
#pragma unroll
                for (int n = 0; n < 5; n++) P[n] = pack_bf16(ex2(fmaf(p[2 * n], SM_SCALE, -mo)), ex2(fmaf(p[2 * n + 1], SM_SCALE, -mo)));
                if (c == 0) STAMP(s, 7);
                float o0[4], o1[4], sm[4];
                mma1688_z(sm, ONES, ONES, P[0]);
                mma1688_z(o0, vm.x, vm.y, P[0]);
                mma1688_z(o1, vm.z, vm.w, P[0]);
                mma16816(sm, ONES, ONES, ONES, ONES, P[1], P[2]);
                mma16816(o0, vx[0].x, vx[0].y, vx[0].z, vx[0].w, P[1], P[2]);
                mma16816(o1, vx[2].x, vx[2].y, vx[2].z, vx[2].w, P[1], P[2]);
                mma16816(sm, ONES, ONES, ONES, ONES, P[3], P[4]);
                mma16816(o0, vx[1].x, vx[1].y, vx[1].z, vx[1].w, P[3], P[4]);
                mma16816(o1, vx[3].x, vx[3].y, vx[3].z, vx[3].w, P[3], P[4]);
                const float r0 = rcp_fast(sm[0]) * sig, r1 = rcp_fast(sm[1]) * sig;
                stsm4t(sb + O_OF + c * 512 + l16, pack_bf16(o0[0] * r0, o0[1] * r1), pack_bf16(o0[2] * r0, o0[3] * r1),
                       pack_bf16(o1[0] * r0, o1[1] * r1), pack_bf16(o1[2] * r0, o1[3] * r1));
                bar_sync(6, 128);
                uint4 ob[4];
#pragma unroll
                for (int q = 0; q < 4; q++) ob[q] = ldsm4(sb + O_OF + q * 512 + l16);
                float m0[3][4], m1[3][4];
#pragma unroll
                for (int q = 0; q < 4; q++) {
#pragma unroll
                    for (int i = 0; i < 3; i++) {
                        const int k0 = (i * 8 + 2 * q) * 4;
                        if (q == 0) mma16816_z(m0[i], a[k0], a[k0 + 1], a[k0 + 2], a[k0 + 3], ob[q].x, ob[q].y);
                        else mma16816(m0[i], a[k0], a[k0 + 1], a[k0 + 2], a[k0 + 3], ob[q].x, ob[q].y);
                    }
#pragma unroll
                    for (int i = 0; i < 3; i++) {
                        const int k1 = (i * 8 + 2 * q + 1) * 4;
                        if (q == 0) mma16816_z(m1[i], a[k1], a[k1 + 1], a[k1 + 2], a[k1 + 3], ob[q].z, ob[q].w);
                        else mma16816(m1[i], a[k1], a[k1 + 1], a[k1 + 2], a[k1 + 3], ob[q].z, ob[q].w);
                    }
                }
                asm volatile("red.relaxed.gpu.global.add.noftz.v4.f16x2 [%0], {%1,%2,%3,%4};" :: "l"(rbase),
                    "r"(pack_f16(m0[0][0] + m1[0][0], m0[0][2] + m1[0][2])), "r"(pack_f16(m0[1][0] + m1[1][0], m0[1][2] + m1[1][2])),
                    "r"(pack_f16(m0[2][0] + m1[2][0], m0[2][2] + m1[2][2])), "r"(0x3c00u) : "memory");
                asm volatile("red.relaxed.gpu.global.add.noftz.v4.f16x2 [%0], {%1,%2,%3,%4};" :: "l"(rbase + 1024),
                    "r"(pack_f16(m0[0][1] + m1[0][1], m0[0][3] + m1[0][3])), "r"(pack_f16(m0[1][1] + m1[1][1], m0[1][3] + m1[1][3])),
                    "r"(pack_f16(m0[2][1] + m1[2][1], m0[2][3] + m1[2][3])), "r"(0x3c00u) : "memory");
                t_red = clk();
                bar_arrive(5, 384);
                if (c == 0) { sts32_if(l16, sb + O_MISC, inv_new); mbar_expect_if(l16, sb + B_SC, 2560); mbar_expect_if(l16, sb + B_VM, 2048); }
                if (c == 0) STAMPV(s, 8, t_red);
            } else if (r < 2 && s == NSEG - 1) {
                mbar_wait(sb + B_VM, s & 1);
                mbar_wait(sb + B_VX + 8 * (s & 1), (s >> 1) & 1);
            }

            if (r < 2 && s < NSEG) {
                mbar_wait(sb + B_SX + 8 * (s & 1), (s >> 1) & 1);
                const uint32_t so = sb + O_SX + (s & 1) * 5120 + (c & 1) * 1280 + (l16 >> 1);
                const int q0 = 16 * r + 8 * (c & 1) + 8 + (int)(l16 >> 6) - (int)((l16 >> 3) & 6);
                float p[10];
#pragma unroll
                for (int n = 0; n < 5; n++) {
                    const float2 u = lds64f(so + n * 256), v = lds64f(so + 2560 + n * 256);
                    p[2 * n] = u.x + v.x; p[2 * n + 1] = u.y + v.y;
                    if (n > 0) {
                        if (8 * n > q0) p[2 * n] = -INFINITY;
                        if (8 * n + 1 > q0) p[2 * n + 1] = -INFINITY;
                    }
                }
                float mx = fmaxf(fmaxf(fmaxf(p[0], p[1]), fmaxf(p[2], p[3])), fmaxf(fmaxf(p[4], p[5]), fmaxf(p[6], p[7])));
                mx = quad_max(fmaxf(mx, fmaxf(p[8], p[9])));
                const float mo = mx * SM_SCALE;
#pragma unroll
                for (int n = 0; n < 5; n++) PX[n] = pack_bf16(ex2(fmaf(p[2 * n], SM_SCALE, -mo)), ex2(fmaf(p[2 * n + 1], SM_SCALE, -mo)));
            }
            auto store_ox = [&]() {
                char* op = reinterpret_cast<char*>(g_ox) + ((size_t)(h * 2 + (c >> 1)) * SEQ + (s - 1) * 32 + 16 * r + 8 * (c & 1)) * 128 + l16;
                const uint4 u0 = lds128(sb + O_OXS + c * 1024 + l16), u1 = lds128(sb + O_OXS + c * 1024 + 512 + l16);
                *reinterpret_cast<uint4*>(op) = u0;
                *reinterpret_cast<uint4*>(op + 512) = u1;
            };
            if (s >= NSEG - 1) {
                if (r < 2) store_ox();
            } else {
                if (c == 0) STAMP(s, 9);
                const uint32_t lo = l16 >> 4;
                const char* pbase = reinterpret_cast<const char*>(g_acc) + ((s >> 1) * 24576 + (s & 1) * 128 + c * 2048)
                      + ((lo & 4) * 256 + (lo >> 4) * 256 + (lo & 8) * 8 + (lo & 3) * 16);
                spin_until(t_red, D_WAIT);
                uint4 v[6];
#pragma unroll
                for (int i = 0; i < 6; i++) v[i] = ldg_relaxed128(pbase + (i >> 1) * 8192 + (i & 1) * 512);
                if (r < 2 && s >= 1) store_ox();
                uint32_t bq[18];
                int nretry = 0;
#pragma unroll
                for (int tau = 0; tau < 3; tau++) {
                    asm volatile("{\n.reg .pred p, q;\n.reg .u32 n;\nmov.u32 n, 0;\n"
                                 "R_%=: setp.eq.u32 p, %3, 0x5000;\nsetp.eq.and.u32 p, %7, 0x5000, p;\nvote.sync.all.pred q, p, 0xffffffff;\n@q bra.uni K_%=;\n"
                                 "ld.relaxed.gpu.global.v4.u32 {%0,%1,%2,%3}, [%9];\nld.relaxed.gpu.global.v4.u32 {%4,%5,%6,%7}, [%9+512];\n"
                                 "add.u32 %8, %8, 1;\nadd.u32 n, n, 1;\nsetp.lt.u32 q, n, 2000000;\n@q bra.uni R_%=;\ntrap;\nK_%=:\n}"
                                 : "+r"(v[2 * tau].x), "+r"(v[2 * tau].y), "+r"(v[2 * tau].z), "+r"(v[2 * tau].w),
                                   "+r"(v[2 * tau + 1].x), "+r"(v[2 * tau + 1].y), "+r"(v[2 * tau + 1].z), "+r"(v[2 * tau + 1].w), "+r"(nretry)
                                 : "l"(pbase + tau * 8192) : "memory");
                    uint32_t* b = bq + 6 * tau;
                    b[0] = f16x2_to_bf16x2(v[2 * tau].x); b[1] = f16x2_to_bf16x2(v[2 * tau + 1].x);
                    b[2] = f16x2_to_bf16x2(v[2 * tau].y); b[3] = f16x2_to_bf16x2(v[2 * tau + 1].y);
                    b[4] = f16x2_to_bf16x2(v[2 * tau].z); b[5] = f16x2_to_bf16x2(v[2 * tau + 1].z);
                    sts128(sb + O_MF + tau * 3072 + (c >> 1) * 1536 + (c & 1) * 512 + l16, b[0], b[1], b[2], b[3]);
                    sts64(sb + O_MF + tau * 3072 + (c >> 1) * 1536 + 1024 + (c & 1) * 8 + l16, b[4], b[5]);
                    if (tau == 0) bar_arrive(2, 384);
                    else { __syncwarp(); mbar_arrive_if(l16, sb + B_M + 8 * tau); }
                    if (c == 0) STAMP(s, 10 + tau);
                }
                if (c == 0) STAMPV(s, 14, nretry);
                mmax = 0;
#pragma unroll
                for (int i = 0; i < 18; i++) mmax = __vmaxu2(mmax, bq[i] & 0x7fff7fffu);
            }
            s3p = s3;
        }
        if (r < 2) {
            bar_sync(6, 128);
            if (c == 0)
                asm volatile("{\n.reg .pred p;\nsetp.eq.u32 p, %1, 0;\nfence.acq_rel.gpu;\n@p red.relaxed.gpu.global.add.u32 [%0], 1;\n"
                             "@p red.relaxed.gpu.global.add.u32 [%0+128], 1;\n@p red.relaxed.gpu.global.add.u32 [%0+256], 1;\n}"
                             :: "l"(&g_flag[(61 * 4 + (h >> 3)) * 8]), "r"(l16c) : "memory");
        }
    }
    cluster_sync();
}

__device__ float g_u[SEQ * 2 * DM];
__global__ void naive_gemm1(const __nv_bfloat16* x, const __nv_bfloat16* Bre, const __nv_bfloat16* Bim) {
    int p = blockIdx.x * 64 + threadIdx.x % 64, tk = blockIdx.y * 4 + threadIdx.x / 64;
    float sr = 0, si = 0;
    for (int d = 0; d < DM; d++) { float xv = __bfloat162float(x[tk * DM + d]); sr += xv * __bfloat162float(Bre[p * DM + d]); si += xv * __bfloat162float(Bim[p * DM + d]); }
    g_u[tk * 2 * DM + 2 * p] = sr; g_u[tk * 2 * DM + 2 * p + 1] = si;
}
__global__ void naive_scan(const __nv_bfloat16* Lre, const __nv_bfloat16* Lim, const __nv_bfloat16* logdt) {
    int p = blockIdx.x * 64 + threadIdx.x;
    float dt = __bfloat162float(__float2bfloat16(expf(__bfloat162float(logdt[p]))));
    float lr = __bfloat162float(Lre[p]), li = __bfloat162float(Lim[p]);
    float e = expf(dt * lr), br = e * cosf(dt * li), bi = e * sinf(dt * li);
    float den = lr * lr + li * li;
    float cr = ((br - 1.f) * lr + bi * li) / den, ci = (bi * lr - (br - 1.f) * li) / den;
    float hr = 0, hi = 0;
    for (int tk = 0; tk < SEQ; tk++) {
        float ur = g_u[tk * 2 * DM + 2 * p], ui = g_u[tk * 2 * DM + 2 * p + 1];
        float nr = br * hr - bi * hi + cr * ur - ci * ui, ni = br * hi + bi * hr + cr * ui + ci * ur;
        hr = nr; hi = ni;
        g_u[tk * 2 * DM + 2 * p] = hr; g_u[tk * 2 * DM + 2 * p + 1] = hi;
    }
}
__global__ void naive_gemm2(const __nv_bfloat16* x, const __nv_bfloat16* Cre, const __nv_bfloat16* Cim, const __nv_bfloat16* Dk, float* out) {
    int d = blockIdx.x * 64 + threadIdx.x % 64, tk = blockIdx.y * 4 + threadIdx.x / 64;
    float s = 0;
    for (int p = 0; p < DM; p++) s += g_u[tk * 2 * DM + 2 * p] * __bfloat162float(Cre[d * DM + p]) - g_u[tk * 2 * DM + 2 * p + 1] * __bfloat162float(Cim[d * DM + p]);
    out[tk * 1152 + d] = 2.f * s + __bfloat162float(__float2bfloat16(__bfloat162float(x[tk * DM + d]) * __bfloat162float(Dk[d])));
}
__global__ void naive_wo(const __nv_bfloat16* Wo, float* out) {
    int d = blockIdx.x * 64 + threadIdx.x % 64, tk = blockIdx.y * 4 + threadIdx.x / 64;
    const __nv_bfloat16* ox = reinterpret_cast<const __nv_bfloat16*>(g_ox);
    float s = 0;
    for (int k = 0; k < HD; k++) {
        int hh = k >> 6, e0 = k & 63, e = (e0 & 48) + (e0 & 1) * 8 + ((e0 & 15) >> 1);
        s += __bfloat162float(ox[((size_t)hh * SEQ + tk) * 64 + (((e >> 3) ^ (tk & 7)) << 3) + (e & 7)]) * __bfloat162float(Wo[k * DM + d]);
    }
    out[tk * 1152 + DM + d] = s;
}

typedef CUresult (*EncodeFn)(CUtensorMap*, CUtensorMapDataType, cuuint32_t, void*, const cuuint64_t*, const cuuint64_t*, const cuuint32_t*, const cuuint32_t*,
                             CUtensorMapInterleave, CUtensorMapSwizzle, CUtensorMapL2promotion, CUtensorMapFloatOOBfill);
}

extern "C" void kernel_launch(void* const* d_in, const int* in_sizes, int n_in, void* d_out, int out_size) {
    typedef const __nv_bfloat16* bp;
    bp Ax = (bp)d_in[0], Lre = (bp)d_in[1], Lim = (bp)d_in[2], Bre = (bp)d_in[3], Bim = (bp)d_in[4], Cre = (bp)d_in[5], Cim = (bp)d_in[6],
       logdt = (bp)d_in[7], Dk = (bp)d_in[8], Bx = (bp)d_in[9], mem0 = (bp)d_in[10], Wq = (bp)d_in[11], Wk = (bp)d_in[12], Wv = (bp)d_in[13], Wo = (bp)d_in[14];
    float* out = (float*)d_out;
    static EncodeFn enc = nullptr;
    if (!enc) {
        void* fn = nullptr; cudaDriverEntryPointQueryResult qr;
        cudaGetDriverEntryPoint("cuTensorMapEncodeTiled", &fn, cudaEnableDefault, &qr);
        enc = (EncodeFn)fn;
        cudaFuncSetAttribute(chain_kernel, cudaFuncAttributeMaxDynamicSharedMemorySize, CHAIN_SMEM);
    }
    CUtensorMap tm_x;
    {
        cuuint64_t gd[2] = {DM, SEQ}; cuuint64_t gs[1] = {DM * 2}; cuuint32_t bd[2] = {64, 32}; cuuint32_t es[2] = {1, 1};
        enc(&tm_x, CU_TENSOR_MAP_DATA_TYPE_BFLOAT16, 2, (void*)Bx, gd, gs, bd, es, CU_TENSOR_MAP_INTERLEAVE_NONE, CU_TENSOR_MAP_SWIZZLE_128B,
            CU_TENSOR_MAP_L2_PROMOTION_L2_128B, CU_TENSOR_MAP_FLOAT_OOB_FILL_NONE);
    }
    cudaStream_t st = cudaStreamPerThread;
    chain_kernel<<<96, 384, CHAIN_SMEM, st>>>(tm_x, Bx, mem0, Wq, Wk, Wv, Wo);
    naive_gemm1<<<dim3(9, 512), 256, 0, st>>>(Ax, Bre, Bim);
    naive_scan<<<9, 64, 0, st>>>(Lre, Lim, logdt);
    naive_gemm2<<<dim3(9, 512), 256, 0, st>>>(Ax, Cre, Cim, Dk, out);
    naive_wo<<<dim3(9, 512), 256, 0, st>>>(Wo, out);
}
```

```cpp
#include <cuda_runtime.h>
#include <cuda.h>
#include <cuda_bf16.h>
#include <cuda_fp16.h>
#include <stdint.h>

#define D_WAIT 700
#define VXMODE 1
#define VXBYTES (VXMODE == 2 ? 0 : 8192)
#define XCHUNK1 10

namespace {

constexpr int DM = 576, NH = 32, SEQ = 2048, NSEG = 64, HD = 4096;

__device__ uint4 g_acc[64 * 96 * 16];
__device__ uint4 g_ox[NH * 2 * SEQ * 8];
__device__ unsigned g_flag[NSEG * 4 * 8];
__device__ unsigned g_gridbar;
__device__ float g_norm[96 * 4];

__device__ __forceinline__ uint32_t smem_u32(const void* p) { return (uint32_t)__cvta_generic_to_shared(p); }
__device__ __forceinline__ uint32_t mapa(uint32_t a, uint32_t r) { uint32_t o; asm("mapa.shared::cluster.u32 %0, %1, %2;" : "=r"(o) : "r"(a), "r"(r)); return o; }
__device__ __forceinline__ uint32_t mapa_v(uint32_t a, uint32_t r) { uint32_t o; asm volatile("mapa.shared::cluster.u32 %0, %1, %2;" : "=r"(o) : "r"(a), "r"(r)); return o; }
__device__ __forceinline__ unsigned clk() { unsigned long long c; asm volatile("mov.u64 %0, %%clock64;" : "=l"(c) :: "memory"); return (unsigned)c; }
__device__ __forceinline__ void mbar_init(uint32_t bar, uint32_t cnt) { asm volatile("mbarrier.init.shared::cta.b64 [%0], %1;" :: "r"(bar), "r"(cnt) : "memory"); }
__device__ __forceinline__ void mbar_expect(uint32_t bar, uint32_t bytes) { asm volatile("mbarrier.arrive.expect_tx.shared::cta.b64 _, [%0], %1;" :: "r"(bar), "r"(bytes) : "memory"); }
__device__ __forceinline__ void mbar_wait(uint32_t bar, uint32_t parity) {
    asm volatile("{\n.reg .pred p;\n.reg .u32 n;\nmov.u32 n, 0;\n"
                 "W_%=: mbarrier.try_wait.parity.shared::cta.b64 p, [%0], %1;\n@p bra.uni D_%=;\n"
                 "add.u32 n, n, 1;\nsetp.lt.u32 p, n, 4000000;\n@p bra.uni W_%=;\ntrap;\nD_%=:\n}" :: "r"(bar), "r"(parity) : "memory");
}
__device__ __forceinline__ void mbar_expect_if(uint32_t z, uint32_t bar, uint32_t bytes) {
    asm volatile("{\n.reg .pred p;\nsetp.eq.u32 p, %2, 0;\n@p mbarrier.arrive.expect_tx.shared::cta.b64 _, [%0], %1;\n}" :: "r"(bar), "r"(bytes), "r"(z) : "memory");
}
__device__ __forceinline__ void mbar_arrive_if(uint32_t z, uint32_t bar) {
    asm volatile("{\n.reg .pred p;\nsetp.eq.u32 p, %1, 0;\n@p mbarrier.arrive.shared::cta.b64 _, [%0];\n}" :: "r"(bar), "r"(z) : "memory");
}
__device__ __forceinline__ void sts32_if(uint32_t z, uint32_t a, uint32_t x) {
    asm volatile("{\n.reg .pred p;\nsetp.eq.u32 p, %2, 0;\n@p st.shared.u32 [%0], %1;\n}" :: "r"(a), "r"(x), "r"(z) : "memory");
}
__device__ __forceinline__ void spin_until(unsigned t0, unsigned d) {
    asm volatile("{\n.reg .pred p;\n.reg .u64 c;\n.reg .u32 lo;\n"
                 "S_%=: mov.u64 c, %%clock64;\ncvt.u32.u64 lo, c;\nsub.u32 lo, lo, %0;\nsetp.lt.u32 p, lo, %1;\n@p bra.uni S_%=;\n}" :: "r"(t0), "r"(d) : "memory");
}
__device__ __forceinline__ void bar_sync(int id, int n) { asm volatile("bar.sync %0, %1;" :: "r"(id), "r"(n) : "memory"); }
__device__ __forceinline__ void bar_arrive(int id, int n) { asm volatile("bar.arrive %0, %1;" :: "r"(id), "r"(n) : "memory"); }
__device__ __forceinline__ void fence_async_smem() { asm volatile("fence.proxy.async.shared::cta;" ::: "memory"); }
__device__ __forceinline__ uint32_t pack_bf16(float lo, float hi) { uint32_t r; asm("cvt.rn.bf16x2.f32 %0, %1, %2;" : "=r"(r) : "f"(hi), "f"(lo)); return r; }
__device__ __forceinline__ uint32_t pack_f16(float lo, float hi) { uint32_t r; asm("cvt.rn.f16x2.f32 %0, %1, %2;" : "=r"(r) : "f"(hi), "f"(lo)); return r; }
__device__ __forceinline__ uint32_t f16x2_to_bf16x2(uint32_t v) { float2 f = __half22float2(*reinterpret_cast<__half2*>(&v)); return pack_bf16(f.x, f.y); }
__device__ __forceinline__ float ex2(float x) { float y; asm("ex2.approx.ftz.f32 %0, %1;" : "=f"(y) : "f"(x)); return y; }
__device__ __forceinline__ float ex2v(float x) { float y; asm volatile("ex2.approx.ftz.f32 %0, %1;" : "=f"(y) : "f"(x)); return y; }
__device__ __forceinline__ uint32_t absmax2(uint32_t a, uint32_t b) {
    uint32_t r; asm volatile("{\n.reg .b32 x, y;\nabs.bf16x2 x, %1;\nabs.bf16x2 y, %2;\nmax.bf16x2 %0, x, y;\n}" : "=r"(r) : "r"(a), "r"(b)); return r;
}
__device__ __forceinline__ uint4 lds128(uint32_t a) { uint4 v; asm volatile("ld.shared.v4.u32 {%0,%1,%2,%3}, [%4];" : "=r"(v.x), "=r"(v.y), "=r"(v.z), "=r"(v.w) : "r"(a) : "memory"); return v; }
__device__ __forceinline__ float4 lds128f(uint32_t a) { float4 v; asm volatile("ld.shared.v4.f32 {%0,%1,%2,%3}, [%4];" : "=f"(v.x), "=f"(v.y), "=f"(v.z), "=f"(v.w) : "r"(a) : "memory"); return v; }
__device__ __forceinline__ float2 lds64f(uint32_t a) { float2 v; asm volatile("ld.shared.v2.f32 {%0,%1}, [%2];" : "=f"(v.x), "=f"(v.y) : "r"(a) : "memory"); return v; }
__device__ __forceinline__ uint4 lds64x2(uint32_t a) { uint4 v; asm volatile("ld.shared.v2.u32 {%0,%1}, [%4];\nld.shared.v2.u32 {%2,%3}, [%4+256];" : "=r"(v.x), "=r"(v.y), "=r"(v.z), "=r"(v.w) : "r"(a) : "memory"); return v; }
__device__ __forceinline__ uint32_t lds32(uint32_t a) { uint32_t v; asm volatile("ld.shared.u32 %0, [%1];" : "=r"(v) : "r"(a) : "memory"); return v; }
__device__ __forceinline__ void sts128(uint32_t a, uint32_t x, uint32_t y, uint32_t z, uint32_t w) { asm volatile("st.shared.v4.u32 [%0], {%1,%2,%3,%4};" :: "r"(a), "r"(x), "r"(y), "r"(z), "r"(w) : "memory"); }
__device__ __forceinline__ void sts128f(uint32_t a, float x, float y, float z, float w) { asm volatile("st.shared.v4.f32 [%0], {%1,%2,%3,%4};" :: "r"(a), "f"(x), "f"(y), "f"(z), "f"(w) : "memory"); }
__device__ __forceinline__ void sts64(uint32_t a, uint32_t x, uint32_t y) { asm volatile("st.shared.v2.u32 [%0], {%1,%2};" :: "r"(a), "r"(x), "r"(y) : "memory"); }
__device__ __forceinline__ void sts32(uint32_t a, uint32_t x) { asm volatile("st.shared.u32 [%0], %1;" :: "r"(a), "r"(x) : "memory"); }
__device__ __forceinline__ uint4 ldsm4(uint32_t a) { uint4 v; asm volatile("ldmatrix.sync.aligned.m8n8.x4.shared.b16 {%0,%1,%2,%3}, [%4];" : "=r"(v.x), "=r"(v.y), "=r"(v.z), "=r"(v.w) : "r"(a) : "memory"); return v; }
__device__ __forceinline__ void stsm2t(uint32_t a, uint32_t x, uint32_t y) { asm volatile("stmatrix.sync.aligned.m8n8.x2.trans.shared.b16 [%0], {%1,%2};" :: "r"(a), "r"(x), "r"(y) : "memory"); }
__device__ __forceinline__ void stsm4t(uint32_t a, uint32_t x, uint32_t y, uint32_t z, uint32_t w) { asm volatile("stmatrix.sync.aligned.m8n8.x4.trans.shared.b16 [%0], {%1,%2,%3,%4};" :: "r"(a), "r"(x), "r"(y), "r"(z), "r"(w) : "memory"); }
__device__ __forceinline__ void st_async64(uint32_t a, uint32_t x, uint32_t y, uint32_t bar) { asm volatile("st.async.shared::cluster.mbarrier::complete_tx::bytes.v2.b32 [%0], {%1,%2}, [%3];" :: "r"(a), "r"(x), "r"(y), "r"(bar) : "memory"); }
__device__ __forceinline__ void bulk_s2c(uint32_t dst, uint32_t src, uint32_t bytes, uint32_t bar) { asm volatile("cp.async.bulk.shared::cluster.shared::cta.mbarrier::complete_tx::bytes [%0], [%1], %2, [%3];" :: "r"(dst), "r"(src), "r"(bytes), "r"(bar) : "memory"); }
__device__ __forceinline__ void bulk_s2g(void* dst, uint32_t src, uint32_t bytes) { asm volatile("cp.async.bulk.global.shared::cta.bulk_group [%0], [%1], %2;" :: "l"(dst), "r"(src), "r"(bytes) : "memory"); }
__device__ __forceinline__ uint32_t ldg_nc32(const void* p) { uint32_t v; asm volatile("ld.global.nc.L2::128B.u32 %0, [%1];" : "=r"(v) : "l"(p)); return v; }
__device__ __forceinline__ uint4 ldg_relaxed128(const void* p) { uint4 v; asm volatile("ld.relaxed.gpu.global.v4.u32 {%0,%1,%2,%3}, [%4];" : "=r"(v.x), "=r"(v.y), "=r"(v.z), "=r"(v.w) : "l"(p) : "memory"); return v; }
__device__ __forceinline__ void mma16816(float (&d)[4], uint32_t a0, uint32_t a1, uint32_t a2, uint32_t a3, uint32_t b0, uint32_t b1) {
    asm volatile("mma.sync.aligned.m16n8k16.row.col.f32.bf16.bf16.f32 {%0,%1,%2,%3}, {%4,%5,%6,%7}, {%8,%9}, {%0,%1,%2,%3};"
        : "+f"(d[0]), "+f"(d[1]), "+f"(d[2]), "+f"(d[3]) : "r"(a0), "r"(a1), "r"(a2), "r"(a3), "r"(b0), "r"(b1));
}
__device__ __forceinline__ void mma16816_z(float (&d)[4], uint32_t a0, uint32_t a1, uint32_t a2, uint32_t a3, uint32_t b0, uint32_t b1) {
    asm volatile("mma.sync.aligned.m16n8k16.row.col.f32.bf16.bf16.f32 {%0,%1,%2,%3}, {%4,%5,%6,%7}, {%8,%9}, {%10,%10,%10,%10};"
        : "=f"(d[0]), "=f"(d[1]), "=f"(d[2]), "=f"(d[3]) : "r"(a0), "r"(a1), "r"(a2), "r"(a3), "r"(b0), "r"(b1), "f"(0.f));
}
__device__ __forceinline__ void mma1688(float (&d)[4], uint32_t a0, uint32_t a1, uint32_t b0) {
    asm volatile("mma.sync.aligned.m16n8k8.row.col.f32.bf16.bf16.f32 {%0,%1,%2,%3}, {%4,%5}, {%6}, {%0,%1,%2,%3};"
        : "+f"(d[0]), "+f"(d[1]), "+f"(d[2]), "+f"(d[3]) : "r"(a0), "r"(a1), "r"(b0));
}
__device__ __forceinline__ void mma1688_z(float (&d)[4], uint32_t a0, uint32_t a1, uint32_t b0) {
    asm volatile("mma.sync.aligned.m16n8k8.row.col.f32.bf16.bf16.f32 {%0,%1,%2,%3}, {%4,%5}, {%6}, {%7,%7,%7,%7};"
        : "=f"(d[0]), "=f"(d[1]), "=f"(d[2]), "=f"(d[3]) : "r"(a0), "r"(a1), "r"(b0), "f"(0.f));
}
template <int ACC>
__device__ __forceinline__ void wgmma_n32_rs(float (&d)[16], uint32_t a0, uint32_t a1, uint32_t a2, uint32_t a3, uint64_t desc) {
    asm volatile("wgmma.mma_async.sync.aligned.m64n32k16.f32.bf16.bf16 {%0,%1,%2,%3,%4,%5,%6,%7,%8,%9,%10,%11,%12,%13,%14,%15}, {%16,%17,%18,%19}, %20, %21, 1, 1, 0;"
        : "+f"(d[0]), "+f"(d[1]), "+f"(d[2]), "+f"(d[3]), "+f"(d[4]), "+f"(d[5]), "+f"(d[6]), "+f"(d[7]),
          "+f"(d[8]), "+f"(d[9]), "+f"(d[10]), "+f"(d[11]), "+f"(d[12]), "+f"(d[13]), "+f"(d[14]), "+f"(d[15])
        : "r"(a0), "r"(a1), "r"(a2), "r"(a3), "l"(desc), "n"(ACC));
}
__device__ __forceinline__ void wgmma_n32_ss(float (&d)[16], uint64_t da, uint64_t db) {
    asm volatile("wgmma.mma_async.sync.aligned.m64n32k16.f32.bf16.bf16 {%0,%1,%2,%3,%4,%5,%6,%7,%8,%9,%10,%11,%12,%13,%14,%15}, %16, %17, 1, 1, 1, 0, 0;"
        : "+f"(d[0]), "+f"(d[1]), "+f"(d[2]), "+f"(d[3]), "+f"(d[4]), "+f"(d[5]), "+f"(d[6]), "+f"(d[7]),
          "+f"(d[8]), "+f"(d[9]), "+f"(d[10]), "+f"(d[11]), "+f"(d[12]), "+f"(d[13]), "+f"(d[14]), "+f"(d[15])
        : "l"(da), "l"(db));
}
__device__ __forceinline__ void wg_fence() { asm volatile("wgmma.fence.sync.aligned;" ::: "memory"); }
__device__ __forceinline__ void wg_commit() { asm volatile("wgmma.commit_group.sync.aligned;" ::: "memory"); }
__device__ __forceinline__ void wg_wait0() { asm volatile("wgmma.wait_group.sync.aligned 0;" ::: "memory"); }
__device__ __forceinline__ void cluster_sync() { asm volatile("barrier.cluster.arrive.aligned;\nbarrier.cluster.wait.aligned;" ::: "memory"); }

#define STAMP(s, i) do {} while (0)
#define STAMPV(s, i, v) do {} while (0)

constexpr int XT_BYTES = 36864;
constexpr int O_XT = 0;
constexpr int O_AS = 3 * XT_BYTES;
constexpr int O_AF = O_AS + 16384;
constexpr int O_MF = O_AF + 16384;
constexpr int O_QM = O_MF + 9216;
constexpr int O_KM = O_QM + 2048;
constexpr int O_QKX = O_KM + 2048;
constexpr int O_XP = O_QKX + 8192;
constexpr int O_VX = O_XP + 16384;
constexpr int O_VM = O_VX + 24576;
constexpr int O_SC = O_VM + 4096;
constexpr int O_OF = O_SC + 2560;
constexpr int O_SX = O_OF + 2048;
constexpr int O_OXS = O_SX + 10240;
constexpr int O_MISC = O_OXS + 4096;
constexpr int O_BAR = O_MISC + 64;
constexpr int CHAIN_SMEM = O_BAR + 128;
static_assert(CHAIN_SMEM <= 232448, "smem");
constexpr int B_X = O_BAR, B_VX = O_BAR + 24, B_SX = O_BAR + 40, B_SC = O_BAR + 56, B_VM = O_BAR + 64, B_MX = O_BAR + 72;
constexpr float SM_SCALE = 0.08838834764831845f * 1.4426950408889634f;
constexpr uint32_t ONES = 0x3f803f80u;

__device__ __forceinline__ uint32_t opaque(uint32_t v) { uint32_t o; asm volatile("mov.u32 %0, %1;" : "=r"(o) : "r"(v)); return o; }
__device__ __forceinline__ void st_async128(uint32_t a, uint32_t x, uint32_t y, uint32_t z, uint32_t w, uint32_t bar) {
    asm volatile("st.async.shared::cluster.mbarrier::complete_tx::bytes.v4.b32 [%0], {%1,%2,%3,%4}, [%5];" :: "r"(a), "r"(x), "r"(y), "r"(z), "r"(w), "r"(bar) : "memory");
}
__device__ __forceinline__ void tma_x_tile(uint32_t sb, const CUtensorMap* tm, int r, int j, int slot) {
    asm volatile("{\n.reg .pred p;\nelect.sync _|p, 0xffffffff;\n"
        "@p mbarrier.arrive.expect_tx.shared::cta.b64 _, [%2], 36864;\n"
        "@p cp.async.bulk.tensor.2d.shared::cluster.global.mbarrier::complete_tx::bytes.multicast::cluster [%0], [%1, {%3, %4}], [%2], %7;\n"
        "@p cp.async.bulk.tensor.2d.shared::cluster.global.mbarrier::complete_tx::bytes.multicast::cluster [%0+4096], [%1, {%5, %4}], [%2], %7;\n"
        "@p cp.async.bulk.tensor.2d.shared::cluster.global.mbarrier::complete_tx::bytes.multicast::cluster [%0+8192], [%1, {%6, %4}], [%2], %7;\n}"
        :: "r"(sb + O_XT + slot * XT_BYTES + 3 * r * 4096), "l"(tm), "r"(sb + B_X + 8 * slot), "r"(192 * r), "r"(j * 32), "r"(192 * r + 64), "r"(192 * r + 128),
           "h"((unsigned short)7) : "memory");
}
__device__ __forceinline__ float quad_max(float v) {
    const float a = __shfl_xor_sync(~0u, v, 1), b = __shfl_xor_sync(~0u, v, 2), c = __shfl_xor_sync(~0u, v, 3);
    return fmaxf(fmaxf(v, a), fmaxf(b, c));
}
__device__ __forceinline__ float rcp_fast(float x) { float y; asm("rcp.approx.ftz.f32 %0, %1;" : "=f"(y) : "f"(x)); return y; }

__global__ void __cluster_dims__(3, 1, 1) __launch_bounds__(384, 1)
chain_kernel(const __grid_constant__ CUtensorMap tm_x,
             const __nv_bfloat16* __restrict__ x, const __nv_bfloat16* __restrict__ mem0,
             const __nv_bfloat16* __restrict__ Wq, const __nv_bfloat16* __restrict__ Wk,
             const __nv_bfloat16* __restrict__ Wv, const __nv_bfloat16* __restrict__ Wo) {
    extern __shared__ __align__(1024) uint8_t smem_raw[];
    const uint32_t sb = smem_u32(smem_raw);
    const int lane = threadIdx.x & 31;
    const int warp = __shfl_sync(~0u, threadIdx.x >> 5, 0);
    const int wg = warp >> 2, w = warp & 3;
    const int h = blockIdx.x / 3, r = blockIdx.x - 3 * h;

    if (threadIdx.x == 0) {
        if (sb & 1023u) __trap();
        for (int i = 0; i < 9; i++) mbar_init(sb + O_BAR + 8 * i, 1);
        mbar_init(sb + B_MX, 4);
        asm volatile("fence.mbarrier_init.release.cluster;" ::: "memory");
    }
    if (blockIdx.x == 0) {
        for (int i = threadIdx.x; i < NSEG * 4 * 8; i += 384) g_flag[i] = 0;
        __threadfence();
    }
    __syncthreads();
    cluster_sync();
    asm volatile("griddepcontrol.launch_dependents;" ::: "memory");
    const uint32_t l16c = __shfl_sync(~0u, lane * 16, lane);

    if (wg < 2) {
#define KB(i) (12 * ((i) / 6) + (((i) % 6) >> 1 == 2 ? 8 + ((i) & 1) : (((i) % 6) >> 1) + 4 * ((i) & 1)))
        asm volatile("setmaxnreg.inc.sync.aligned.u32 176;");
        uint32_t a[144];
        uint32_t adr1, adr2;
        {
            const int g = lane >> 2, t = lane & 3;
#pragma unroll
            for (int tl = 0; tl < 2; tl++) {
                const int tile = tl ? wg : (wg ^ 1);
                const __nv_bfloat16* W = (r < 2) ? (tile == 0 ? Wq : Wk) : Wv;
                const int col = h * 128 + ((r < 2) ? 64 * r : 64 * tile) + 16 * w + 2 * g;
                const __nv_bfloat16* p = W + (size_t)(32 * wg + 2 * t) * HD + col;
#pragma unroll
                for (int i = 0; i < 18; i++) {
                    a[72 * tl + 4 * i + 0] = ldg_nc32(p + (size_t)(16 * KB(i) + 0) * HD);
                    a[72 * tl + 4 * i + 1] = ldg_nc32(p + (size_t)(16 * KB(i) + 1) * HD);
                    a[72 * tl + 4 * i + 2] = ldg_nc32(p + (size_t)(16 * KB(i) + 8) * HD);
                    a[72 * tl + 4 * i + 3] = ldg_nc32(p + (size_t)(16 * KB(i) + 9) * HD);
                }
            }
#pragma unroll
            for (int kk = 0; kk < 72; kk++) {
                uint32_t w0 = a[2 * kk], w1 = a[2 * kk + 1];
                a[2 * kk] = __byte_perm(w0, w1, 0x5410);
                a[2 * kk + 1] = __byte_perm(w0, w1, 0x7632);
            }
            float vmax = 0.f;
#pragma unroll
            for (int tl = 0; tl < 2; tl++) {
                float s0 = 0.f, s1 = 0.f;
#pragma unroll
                for (int kk = 36 * tl; kk < 36 * tl + 36; kk++) {
                    s0 += fabsf(__uint_as_float(a[2 * kk] << 16)) + fabsf(__uint_as_float(a[2 * kk] & 0xffff0000u));
                    s1 += fabsf(__uint_as_float(a[2 * kk + 1] << 16)) + fabsf(__uint_as_float(a[2 * kk + 1] & 0xffff0000u));
                }
                s0 += __shfl_xor_sync(~0u, s0, 1); s0 += __shfl_xor_sync(~0u, s0, 2);
                s1 += __shfl_xor_sync(~0u, s1, 1); s1 += __shfl_xor_sync(~0u, s1, 2);
                vmax = fmaxf(vmax, fmaxf(s0, s1));
            }
            uint32_t mx = __reduce_max_sync(~0u, __float_as_uint(2.f * vmax));
            sts32_if(lane, sb + O_MISC + 32 + 4 * warp, mx);
            bar_arrive(7, 384);
            const uint32_t as = sb + O_AS + wg * 8192 + (16 * w + g) * 128 + t * 4;
#pragma unroll
            for (int kk = 0; kk < 4; kk++) {
                sts32(as + (((2 * kk) ^ g) << 4), a[128 + 4 * kk]);
                sts32(as + 1024 + (((2 * kk) ^ g) << 4), a[128 + 4 * kk + 1]);
                sts32(as + (((2 * kk + 1) ^ g) << 4), a[128 + 4 * kk + 2]);
                sts32(as + 1024 + (((2 * kk + 1) ^ g) << 4), a[128 + 4 * kk + 3]);
                sts128(sb + O_AF + warp * 2048 + kk * 512 + lane * 16, a[128 + 4 * kk], a[128 + 4 * kk + 1], a[128 + 4 * kk + 2], a[128 + 4 * kk + 3]);
            }
            fence_async_smem();
            bar_sync(1, 256);
            const uint32_t l = lane * 16;
            const int n = warp < 5 ? warp : warp - 5;
            const int mi = lane >> 3, isk = (mi >> 1) ? wg : (wg ^ 1);
            adr1 = (r == 2) ? (sb + O_VM + warp * 256 + (l >> 1))
                            : (isk ? (sb + O_KM + (w >> 1) * 1024 + wg * 512 + (w & 1) * 256 + (mi & 1) * 128 + (l & 127))
                                   : (sb + O_QM + w * 512 + (mi & 1) * 256 + wg * 128 + (l & 127)));
            adr2 = (n == 0) ? (sb + O_KM + l) : (sb + O_QKX + 4096 + l + (l & 256) + ((n - 1) >> 1) * 2048 + ((n - 1) & 1) * 256);
            adr1 = __shfl_sync(~0u, adr1, lane);
            adr2 = __shfl_sync(~0u, adr2, lane);
        }
        int s3 = 2;
#pragma unroll 1
        for (int s = -1; s < NSEG; s++) {
            const uint32_t l16 = opaque(l16c);
            if (s >= 0) {
#pragma unroll
                for (int kk = 0; kk < 4; kk++) {
                    const uint4 v = lds128(sb + O_AF + warp * 2048 + kk * 512 + l16);
                    a[128 + 4 * kk] = v.x; a[128 + 4 * kk + 1] = v.y; a[128 + 4 * kk + 2] = v.z; a[128 + 4 * kk + 3] = v.w;
                }
                float c0[4], c1[4], c2[4], c3[4];
                uint4 b[9];
                float inv;
#pragma unroll
                for (int i = 0; i < 11; i++) {
                    if (i < 9) {
                        if (i == 0) bar_sync(2, 384);
                        else if (i % 3 == 0) bar_sync(10 + 2 * (i / 3) + wg, 192);
                        if (i == 0 && warp == 0) STAMP(s, 0);
                        b[i] = lds128(sb + O_MF + (i / 3) * 3072 + wg * 1536 + (i % 3) * 512 + l16);
                    }
                    if (i == 9) inv = __uint_as_float(lds32(sb + O_MISC));
                    if (i >= 2) {
                        const int u = 8 * (i - 2);
                        if (i == 2) {
                            mma16816_z(c0, a[u], a[u + 1], a[u + 2], a[u + 3], b[0].x, b[0].y);
                            mma16816_z(c1, a[u + 4], a[u + 5], a[u + 6], a[u + 7], b[0].z, b[0].w);
                            mma16816_z(c2, a[72 + u], a[72 + u + 1], a[72 + u + 2], a[72 + u + 3], b[0].x, b[0].y);
                            mma16816_z(c3, a[72 + u + 4], a[72 + u + 5], a[72 + u + 6], a[72 + u + 7], b[0].z, b[0].w);
                        } else {
                            mma16816(c0, a[u], a[u + 1], a[u + 2], a[u + 3], b[i - 2].x, b[i - 2].y);
                            mma16816(c1, a[u + 4], a[u + 5], a[u + 6], a[u + 7], b[i - 2].z, b[i - 2].w);
                            mma16816(c2, a[72 + u], a[72 + u + 1], a[72 + u + 2], a[72 + u + 3], b[i - 2].x, b[i - 2].y);
                            mma16816(c3, a[72 + u + 4], a[72 + u + 5], a[72 + u + 6], a[72 + u + 7], b[i - 2].z, b[i - 2].w);
                        }
                    }
                }
                if (r < 2) {
                    stsm4t(adr1, pack_bf16((c0[0] + c1[0]) * inv, (c0[1] + c1[1]) * inv), pack_bf16((c0[2] + c1[2]) * inv, (c0[3] + c1[3]) * inv),
                                 pack_bf16((c2[0] + c3[0]) * inv, (c2[1] + c3[1]) * inv), pack_bf16((c2[2] + c3[2]) * inv, (c2[3] + c3[3]) * inv));
                    if (warp == 0) STAMP(s, 1);
                    const uint32_t dst = sb + O_SC + r * 1280 + warp * 256 + (l16 >> 1);
                    const uint32_t d0 = mapa_v(dst, 2), d1 = mapa_v(dst, r ^ 1), d2 = mapa_v(dst, r);
                    const uint32_t e0 = mapa_v(sb + B_SC, 2), e1 = mapa_v(sb + B_SC, r ^ 1), e2 = mapa_v(sb + B_SC, r);
                    bar_sync(1, 256);
                    const int n = warp < 5 ? warp : warp - 5;
                    const uint4 k0 = ldsm4(adr2), k1 = ldsm4(adr2 + 1024);
                    if (warp < 5) {
                        const uint4 q0 = ldsm4(sb + O_QM + l16), q1 = ldsm4(sb + O_QM + 512 + l16);
                        const uint4 q2 = ldsm4(sb + O_QM + 1024 + l16), q3 = ldsm4(sb + O_QM + 1536 + l16);
                        float s0[4], s1[4];
                        mma16816_z(s0, q0.x, q0.y, q0.z, q0.w, k0.x, k0.y);
                        mma16816_z(s1, q1.x, q1.y, q1.z, q1.w, k0.z, k0.w);
                        mma16816(s0, q2.x, q2.y, q2.z, q2.w, k1.x, k1.y);
                        mma16816(s1, q3.x, q3.y, q3.z, q3.w, k1.z, k1.w);
                        if (warp == 0) {
                            const uint4 k2 = ldsm4(adr2 + 512), k3 = ldsm4(adr2 + 1536);
                            float s2[4], s3_[4];
                            mma16816_z(s2, q0.x, q0.y, q0.z, q0.w, k2.x, k2.y);
                            mma16816_z(s3_, q1.x, q1.y, q1.z, q1.w, k2.z, k2.w);
                            mma16816(s2, q2.x, q2.y, q2.z, q2.w, k3.x, k3.y);
                            mma16816(s3_, q3.x, q3.y, q3.z, q3.w, k3.z, k3.w);
#pragma unroll
                            for (int i = 0; i < 4; i++) { s0[i] += s2[i]; s1[i] += s3_[i]; }
                        }
                        const uint32_t v0 = __float_as_uint((s0[0] + s0[2]) + (s1[0] + s1[2])), v1 = __float_as_uint((s0[1] + s0[3]) + (s1[1] + s1[3]));
                        st_async64(d0, v0, v1, e0);
                        st_async64(d1, v0, v1, e1);
                        st_async64(d2, v0, v1, e2);
                    }
                    if (warp == 0) STAMP(s, 2);
                    {
                        const int mt = warp < 5 ? 1 : 0;
                        const uint32_t qb = sb + O_QKX + mt * 2048 + l16;
                        const uint4 q0 = ldsm4(qb), q1 = ldsm4(qb + 512), q2 = ldsm4(qb + 1024), q3 = ldsm4(qb + 1536);
                        float sc[4], sd[4];
                        mma16816_z(sc, q0.x, q0.y, q0.z, q0.w, k0.x, k0.y);
                        mma16816_z(sd, q1.x, q1.y, q1.z, q1.w, k0.z, k0.w);
                        mma16816(sc, q2.x, q2.y, q2.z, q2.w, k1.x, k1.y);
                        mma16816(sd, q3.x, q3.y, q3.z, q3.w, k1.z, k1.w);
                        if (n == 0) {
                            const uint4 k2 = ldsm4(adr2 + 512), k3 = ldsm4(adr2 + 1536);
                            mma16816(sc, q0.x, q0.y, q0.z, q0.w, k2.x, k2.y);
                            mma16816(sd, q1.x, q1.y, q1.z, q1.w, k2.z, k2.w);
                            mma16816(sc, q2.x, q2.y, q2.z, q2.w, k3.x, k3.y);
                            mma16816(sd, q3.x, q3.y, q3.z, q3.w, k3.z, k3.w);
                        }
                        const uint32_t dx = mapa(sb + O_SX + (s & 1) * 5120 + r * 2560 + n * 256 + (l16 >> 1), mt), bx = mapa(sb + B_SX + 8 * (s & 1), mt);
                        st_async64(dx, __float_as_uint(sc[0] + sd[0]), __float_as_uint(sc[1] + sd[1]), bx);
                        st_async64(dx + 1280, __float_as_uint(sc[2] + sd[2]), __float_as_uint(sc[3] + sd[3]), bx);
                    }
                } else {
                    sts128f(sb + O_XP + warp * 512 + l16, c0[0] + c1[0], c0[1] + c1[1], c0[2] + c1[2], c0[3] + c1[3]);
                    bar_sync(8 + w, 64);
                    const float4 o = lds128f(sb + O_XP + (warp ^ 4) * 512 + l16);
                    const uint32_t X0 = pack_bf16((c2[0] + c3[0] + o.x) * inv, (c2[1] + c3[1] + o.y) * inv);
                    const uint32_t X1 = pack_bf16((c2[2] + c3[2] + o.z) * inv, (c2[3] + c3[3] + o.w) * inv);
                    if (warp == 0) STAMP(s, 1);
                    const uint32_t dst = adr1 + (s & 1) * 2048;
                    st_async64(mapa(dst, 0), X0, X1, mapa(sb + B_VM, 0));
                    st_async64(mapa(dst, 1), X0, X1, mapa(sb + B_VM, 1));
                    st_async64(mapa(dst, 2), X0, X1, mapa(sb + B_VM, 2));
                    if (warp == 0) STAMP(s, 2);
                }
            }
            s3 = (s3 == 2) ? 0 : s3 + 1;
            if (s < NSEG - 1) {
                const int j = s + 1;
                const uint64_t desc0 = (uint64_t)(((sb + O_XT + s3 * XT_BYTES + wg * 64) & 0x3FFFF) >> 4) | (1ull << 16) | (64ull << 32) | (1ull << 62);
#define XDESC(i) (desc0 + (uint64_t)(((KB(i) >> 2) * 4096 + (KB(i) & 3) * 32) >> 4))
                float d[16];
                if (s >= 0) bar_sync(3, 384);
                mbar_wait(sb + B_X + 8 * s3, (j / 3) & 1);
                wg_fence();
#pragma unroll
                for (int i = 0; i < XCHUNK1; i++) {
                    if (i == 0) wgmma_n32_rs<0>(d, a[0], a[1], a[2], a[3], XDESC(0));
                    else wgmma_n32_rs<1>(d, a[4 * i], a[4 * i + 1], a[4 * i + 2], a[4 * i + 3], XDESC(i));
                }
                wg_commit();
                if (wg == 1) bar_sync(s >= 0 ? 5 : 1, s >= 0 ? 384 : 256);
#pragma unroll
                for (int i = XCHUNK1; i < 18; i++) wgmma_n32_rs<1>(d, a[4 * i], a[4 * i + 1], a[4 * i + 2], a[4 * i + 3], XDESC(i));
                wg_commit();
                wg_wait0();
                if (warp == 0) STAMP(s, 15);
#pragma unroll
                for (int q = 0; q < 4; q++) sts128f(sb + O_XP + warp * 2048 + q * 512 + l16, d[4 * q], d[4 * q + 1], d[4 * q + 2], d[4 * q + 3]);
                if (warp == 1 && s >= 0 && s + 2 < NSEG) tma_x_tile(sb, &tm_x, r, s + 2, s3 == 2 ? 0 : s3 + 1);
                if (wg == 0) bar_sync(s >= 0 ? 5 : 1, s >= 0 ? 384 : 256);
                else bar_arrive(8 + w, 64);
                wg_fence();
#pragma unroll
                for (int i = 0; i < 18; i++) {
                    if (i == 0) wgmma_n32_rs<0>(d, a[72], a[73], a[74], a[75], XDESC(0));
                    else if (i < 14) wgmma_n32_rs<1>(d, a[72 + 4 * i], a[72 + 4 * i + 1], a[72 + 4 * i + 2], a[72 + 4 * i + 3], XDESC(i));
                    else wgmma_n32_ss(d, (uint64_t)(((sb + O_AS + wg * 8192 + (i - 14) * 32) & 0x3FFFF) >> 4) | (1ull << 16) | (64ull << 32) | (1ull << 62), XDESC(i));
                }
                wg_commit();
                if (warp == 3 && r < 2 && s >= 2)
                    asm volatile("{\n.reg .pred p;\nsetp.eq.u32 p, %1, 0;\n@p red.release.gpu.global.add.u32 [%0], 1;\n}"
                                 :: "l"(&g_flag[((s - 2) * 4 + (h >> 3)) * 8]), "r"(l16) : "memory");
                if (wg == 0) bar_sync(8 + w, 64);
                wg_wait0();
                if (warp == 4) STAMP(s, 3);
                uint32_t e[8];
#pragma unroll
                for (int q = 0; q < 4; q++) {
                    const float4 o = lds128f(sb + O_XP + (warp ^ 4) * 2048 + q * 512 + l16);
                    e[2 * q] = pack_bf16(d[4 * q] + o.x, d[4 * q + 1] + o.y);
                    e[2 * q + 1] = pack_bf16(d[4 * q + 2] + o.z, d[4 * q + 3] + o.w);
                }
                if (r < 2) {
                    const uint32_t base = sb + O_QKX + wg * 4096 + w * 512 + l16;
                    stsm4t(base, e[0], wg ? e[1] : e[2], wg ? e[2] : e[1], e[3]);
                    stsm4t(base + 2048, e[4], wg ? e[5] : e[6], wg ? e[6] : e[5], e[7]);
                } else {
                    const uint32_t base = sb + O_VX + s3 * 8192 + warp * 1024 + l16;
                    sts128(base, e[0], e[1], e[2], e[3]);
                    sts128(base + 512, e[4], e[5], e[6], e[7]);
                    const uint32_t bar = sb + B_VX + 8 * (j & 1);
                    fence_async_smem();
                    __syncwarp();
                    const uint32_t src = sb + O_VX + s3 * 8192 + warp * 1024;
                    asm volatile("{\n.reg .pred p;\nelect.sync _|p, 0xffffffff;\n"
                        "@p cp.async.bulk.shared::cluster.shared::cta.mbarrier::complete_tx::bytes [%0], [%2], 1024, [%3];\n"
                        "@p cp.async.bulk.shared::cluster.shared::cta.mbarrier::complete_tx::bytes [%1], [%2], 1024, [%4];\n}"
                        :: "r"(mapa(src, 0)), "r"(mapa(src, 1)), "r"(src), "r"(mapa(bar, 0)), "r"(mapa(bar, 1)) : "memory");
                }
                if (warp == 7) STAMP(s, 4);
            }
        }
    } else {
        asm volatile("setmaxnreg.dec.sync.aligned.u32 152;");
        const int c = w;
        uint32_t a[96];
        uint32_t mmax = 0;
        {
            const int g = lane >> 2, t = lane & 3, t2 = threadIdx.x - 256;
            if (c == 0) {
                tma_x_tile(sb, &tm_x, r, 0, 0);
                tma_x_tile(sb, &tm_x, r, 1, 1);
                mbar_expect_if(lane, sb + B_SC, 2560);
                mbar_expect_if(lane, sb + B_VM, 2048);
                if (r < 2) { mbar_expect_if(lane, sb + B_VX, VXBYTES); mbar_expect_if(lane, sb + B_SX, r == 0 ? 3072 : 5120); }
                sts32_if(lane, sb + O_MISC, __float_as_uint(1.0f));
            }
#pragma unroll
            for (int i = 0; i < 4; i++) g_acc[(blockIdx.x * 64 + i * 16 + (t2 >> 3)) * 16 + (t2 & 7)] = make_uint4(0, 0, 0, 0);
#pragma unroll
            for (int tau = 0; tau < 3; tau++) {
                uint32_t v[6];
#pragma unroll
                for (int i = 0; i < 3; i++) {
                    const uint32_t* p = reinterpret_cast<const uint32_t*>(mem0 + g * DM + 16 * (12 * tau + 4 * i + c) + 2 * t);
                    v[2 * i] = __ldg(p); v[2 * i + 1] = __ldg(p + 4);
                    mmax = __vmaxu2(mmax, __vmaxu2(v[2 * i] & 0x7fff7fffu, v[2 * i + 1] & 0x7fff7fffu));
                }
                sts128(sb + O_MF + tau * 3072 + (c >> 1) * 1536 + (c & 1) * 512 + lane * 16, v[0], v[1], v[2], v[3]);
                sts64(sb + O_MF + tau * 3072 + (c >> 1) * 1536 + 1024 + lane * 16 + (c & 1) * 8, v[4], v[5]);
            }
            bar_arrive(2, 384);
            bar_arrive(12 + (c >> 1), 192); bar_arrive(14 + (c >> 1), 192);
            uint32_t xm = 0;
            const uint4* xp = reinterpret_cast<const uint4*>(x) + blockIdx.x * 1536 + t2;
#pragma unroll
            for (int i = 0; i < 12; i++) {
                uint4 v = __ldg(xp + i * 128);
                xm = __vmaxu2(xm, __vmaxu2(__vmaxu2(v.x & 0x7fff7fffu, v.y & 0x7fff7fffu), __vmaxu2(v.z & 0x7fff7fffu, v.w & 0x7fff7fffu)));
            }
            xm = __reduce_max_sync(~0u, max(xm << 16, xm & 0xffff0000u));

            const __nv_bfloat16* p = Wo + (size_t)(h * 128 + 4 * t) * DM + 192 * r + 16 * c + 2 * g;
#pragma unroll
            for (int i = 0; i < 3; i++)
#pragma unroll
                for (int eb = 0; eb < 8; eb++)
#pragma unroll
                    for (int j = 0; j < 4; j++) a[(i * 8 + eb) * 4 + j] = ldg_nc32(p + (16 * eb + ((j & 1) * 2 + (j >> 1))) * DM + 64 * i);
#pragma unroll
            for (int kk = 0; kk < 48; kk++) {
                uint32_t w0 = a[2 * kk], w1 = a[2 * kk + 1];
                a[2 * kk] = __byte_perm(w0, w1, 0x5410);
                a[2 * kk + 1] = __byte_perm(w0, w1, 0x7632);
            }
            float wmax = 0.f;
#pragma unroll
            for (int i = 0; i < 3; i++) {
                float s0 = 0.f, s1 = 0.f;
#pragma unroll
                for (int kk = 16 * i; kk < 16 * i + 16; kk++) {
                    s0 += fabsf(__uint_as_float(a[2 * kk] << 16)) + fabsf(__uint_as_float(a[2 * kk] & 0xffff0000u));
                    s1 += fabsf(__uint_as_float(a[2 * kk + 1] << 16)) + fabsf(__uint_as_float(a[2 * kk + 1] & 0xffff0000u));
                }
                s0 += __shfl_xor_sync(~0u, s0, 1); s0 += __shfl_xor_sync(~0u, s0, 2);
                s1 += __shfl_xor_sync(~0u, s1, 1); s1 += __shfl_xor_sync(~0u, s1, 2);
                wmax = fmaxf(wmax, fmaxf(s0, s1));
            }
            uint32_t wm = __reduce_max_sync(~0u, __float_as_uint(wmax));
            sts32_if(lane, sb + O_OF + 4 * c, wm); sts32_if(lane, sb + O_OF + 16 + 4 * c, xm);
            __threadfence();
            bar_sync(7, 384);
            if (c == 0) {
                const uint4 wq = lds128(sb + O_OF), xq = lds128(sb + O_OF + 16), v0 = lds128(sb + O_MISC + 32), v1 = lds128(sb + O_MISC + 48);
                const uint32_t w1 = max(max(wq.x, wq.y), max(wq.z, wq.w)), x1 = max(max(xq.x, xq.y), max(xq.z, xq.w));
                const uint32_t vv = (r < 2) ? 0u : max(max(max(v0.x, v0.y), max(v0.z, v0.w)), max(max(v1.x, v1.y), max(v1.z, v1.w)));
                unsigned old = 0;
                asm volatile("{\n.reg .pred p;\nsetp.eq.u32 p, %6, 0;\n@p st.global.v4.u32 [%1], {%2,%3,%4,%4};\nfence.acq_rel.gpu;\n@p atom.relaxed.gpu.global.add.u32 %0, [%5], 1;\n}"
                             : "+r"(old) : "l"(&g_norm[blockIdx.x * 4]), "r"(w1), "r"(vv), "r"(x1), "l"(&g_gridbar), "r"(lane) : "memory");
                old = __shfl_sync(~0u, old, 0);
                const unsigned target = (old / 96u + 1u) * 96u;
                asm volatile("{\n.reg .pred p;\n.reg .u32 n, v;\nmov.u32 n, 0;\n"
                             "G_%=: ld.acquire.gpu.global.u32 v, [%0];\nsub.u32 v, v, %1;\nsetp.ge.s32 p, v, 0;\n@p bra.uni E_%=;\n"
                             "add.u32 n, n, 1;\nsetp.lt.u32 p, n, 4000000;\n@p bra.uni G_%=;\ntrap;\nE_%=:\n}" :: "l"(&g_gridbar), "r"(target) : "memory");
                uint4 n0 = ldg_relaxed128(&g_norm[lane * 4]), n1 = ldg_relaxed128(&g_norm[(lane + 32) * 4]), n2 = ldg_relaxed128(&g_norm[(lane + 64) * 4]);
                const float fw = __uint_as_float(__reduce_max_sync(~0u, max(n0.x, max(n1.x, n2.x))));
                const float fv = __uint_as_float(__reduce_max_sync(~0u, max(n0.y, max(n1.y, n2.y))));
                const float xmax = __uint_as_float(__reduce_max_sync(~0u, max(n0.z, max(n1.z, n2.z))));
                const float G = 36.f * fw * fv;
                sts32_if(lane, sb + O_MISC + 4, __float_as_uint(G)); sts32_if(lane, sb + O_MISC + 8, __float_as_uint(G * xmax));
            }
        }
        bar_sync(6, 128);
        int s3p = 2;
        uint32_t PX[5] = {0u, 0u, 0u, 0u, 0u};
        char* rptr; int pdelta; char* optr;
        {
            const uint32_t roff = (r * 4 + c) * 2048 + (lane >> 4) * 512 + (lane & 2) * 128 + (lane & 1) * 64 + (lane & 12) * 4;
            const uint32_t poff = c * 2048 + (lane & 4) * 256 + (lane >> 4) * 256 + (lane & 8) * 8 + (lane & 3) * 16;
            rptr = reinterpret_cast<char*>(g_acc) + roff;
            pdelta = __shfl_sync(~0u, (int)poff - (int)roff, lane);
            optr = reinterpret_cast<char*>(g_ox) + ((size_t)(h * 2 + (c >> 1)) * SEQ + 16 * r + 8 * (c & 1)) * 128 + lane * 16 - 4096;
        }
#pragma unroll 1
        for (int s = 0; s <= NSEG; s++) {
            const uint32_t l16 = opaque(l16c);
            const int s3 = (s3p == 2) ? 0 : s3p + 1;
            unsigned t_red = 0;
            if (s < NSEG - 1) {
                sts32_if(l16, sb + O_MISC + 16 + 4 * c, __reduce_max_sync(~0u, max(mmax << 16, mmax & 0xffff0000u)));
                mbar_arrive_if(l16, sb + B_MX);
            }
            if (c == 0) STAMP(s < NSEG ? s : -1, 5);
            if (r < 2 && s >= 1) {
                const uint32_t vmb = sb + O_VM + ((s - 1) & 1) * 2048 + (c >> 1) * 1024 + (l16 >> 1);
                const uint32_t vb = sb + O_VX + s3p * 8192 + (c >> 1) * 4096 + l16;
                const uint4 vm0 = lds64x2(vmb), vm1 = lds64x2(vmb + 512);
                float sm[4], o[4][4];
                uint4 v[4];
#pragma unroll
                for (int q = 0; q < 4; q++) v[q] = lds128(vb + q * 1024);
                mma1688_z(sm, ONES, ONES, PX[0]);
                mma1688_z(o[0], vm0.x, vm0.y, PX[0]); mma1688_z(o[1], vm0.z, vm0.w, PX[0]);
                mma1688_z(o[2], vm1.x, vm1.y, PX[0]); mma1688_z(o[3], vm1.z, vm1.w, PX[0]);
                mma16816(sm, ONES, ONES, ONES, ONES, PX[1], PX[2]);
#pragma unroll
                for (int q = 0; q < 4; q++) {
                    mma16816(o[q], v[q].x, v[q].y, v[q].z, v[q].w, PX[1], PX[2]);
                    v[q] = lds128(vb + q * 1024 + 512);
                }
                mma16816(sm, ONES, ONES, ONES, ONES, PX[3], PX[4]);
#pragma unroll
                for (int q = 0; q < 4; q++) mma16816(o[q], v[q].x, v[q].y, v[q].z, v[q].w, PX[3], PX[4]);
                const uint32_t row = (l16 >> 4) & 7;
                const uint32_t stg = sb + O_OXS + c * 1024 + row * 128 + (((l16 >> 7) ^ row) << 4);
                const float r0 = rcp_fast(sm[0]), r1 = rcp_fast(sm[1]);
#pragma unroll
                for (int e2 = 0; e2 < 2; e2++)
                    stsm4t(stg ^ (e2 * 64), pack_bf16(o[2 * e2][0] * r0, o[2 * e2][1] * r1), pack_bf16(o[2 * e2][2] * r0, o[2 * e2][3] * r1),
                           pack_bf16(o[2 * e2 + 1][0] * r0, o[2 * e2 + 1][1] * r1), pack_bf16(o[2 * e2 + 1][2] * r0, o[2 * e2 + 1][3] * r1));
                __syncwarp();
            }
            if (s < NSEG - 1) {
                bar_arrive(3, 384);
                mbar_wait(sb + B_MX, s & 1);
                const uint4 mm = lds128(sb + O_MISC + 16), cf = lds128(sb + O_MISC);
                const float bound = fmaxf(__uint_as_float(cf.z), __uint_as_float(cf.y) * (__uint_as_float(max(max(mm.x, mm.y), max(mm.z, mm.w))) * __uint_as_float(cf.x)));
                const uint32_t eb = min(max(__float_as_uint(bound) & 0x7f800000u, 21u << 23), 254u << 23);
                const float sig = __uint_as_float((268u << 23) - eb);
                const uint32_t inv_new = eb - (14u << 23);
                if (r < 2) mbar_wait(sb + B_VX + 8 * (s & 1), (s >> 1) & 1);
                mbar_wait(sb + B_VM, s & 1);
                uint4 vx[4];
#pragma unroll
                for (int q = 0; q < 4; q++) vx[q] = lds128(sb + O_VX + s3 * 8192 + c * 2048 + q * 512 + l16);
                const uint4 vm = lds64x2(sb + O_VM + (s & 1) * 2048 + c * 512 + (l16 >> 1));
                if (c == 0) STAMP(s, 13);
                mbar_wait(sb + B_SC, s & 1);
                if (c == 0) STAMP(s, 6);
                float p[10];
#pragma unroll
                for (int n = 0; n < 5; n++) {
                    float2 u = lds64f(sb + O_SC + n * 256 + (l16 >> 1)), v = lds64f(sb + O_SC + 1280 + n * 256 + (l16 >> 1));
                    p[2 * n] = u.x + v.x; p[2 * n + 1] = u.y + v.y;
                }
                float mx = fmaxf(fmaxf(fmaxf(p[0], p[1]), fmaxf(p[2], p[3])), fmaxf(fmaxf(p[4], p[5]), fmaxf(p[6], p[7])));
                mx = quad_max(fmaxf(mx, fmaxf(p[8], p[9])));
                const float mo = mx * SM_SCALE;
                uint32_t P[5];
#pragma unroll
                for (int n = 0; n < 5; n++) P[n] = pack_bf16(ex2(fmaf(p[2 * n], SM_SCALE, -mo)), ex2(fmaf(p[2 * n + 1], SM_SCALE, -mo)));
                if (c == 0) STAMP(s, 7);
                float o0[4], o1[4], sm[4];
                mma1688_z(sm, ONES, ONES, P[0]);
                mma1688_z(o0, vm.x, vm.y, P[0]);
                mma1688_z(o1, vm.z, vm.w, P[0]);
                mma16816(sm, ONES, ONES, ONES, ONES, P[1], P[2]);
                mma16816(o0, vx[0].x, vx[0].y, vx[0].z, vx[0].w, P[1], P[2]);
                mma16816(o1, vx[2].x, vx[2].y, vx[2].z, vx[2].w, P[1], P[2]);
                mma16816(sm, ONES, ONES, ONES, ONES, P[3], P[4]);
                mma16816(o0, vx[1].x, vx[1].y, vx[1].z, vx[1].w, P[3], P[4]);
                mma16816(o1, vx[3].x, vx[3].y, vx[3].z, vx[3].w, P[3], P[4]);
                const float r0 = rcp_fast(sm[0]) * sig, r1 = rcp_fast(sm[1]) * sig;
                stsm4t(sb + O_OF + c * 512 + l16, pack_bf16(o0[0] * r0, o0[1] * r1), pack_bf16(o0[2] * r0, o0[3] * r1),
                       pack_bf16(o1[0] * r0, o1[1] * r1), pack_bf16(o1[2] * r0, o1[3] * r1));
                bar_sync(6, 128);
                uint4 ob[4];
#pragma unroll
                for (int q = 0; q < 4; q++) ob[q] = ldsm4(sb + O_OF + q * 512 + l16);
                float m0[3][4], m1[3][4];
#pragma unroll
                for (int q = 0; q < 4; q++) {
#pragma unroll
                    for (int i = 0; i < 3; i++) {
                        const int k0 = (i * 8 + 2 * q) * 4;
                        if (q == 0) mma16816_z(m0[i], a[k0], a[k0 + 1], a[k0 + 2], a[k0 + 3], ob[q].x, ob[q].y);
                        else mma16816(m0[i], a[k0], a[k0 + 1], a[k0 + 2], a[k0 + 3], ob[q].x, ob[q].y);
                    }
#pragma unroll
                    for (int i = 0; i < 3; i++) {
                        const int k1 = (i * 8 + 2 * q + 1) * 4;
                        if (q == 0) mma16816_z(m1[i], a[k1], a[k1 + 1], a[k1 + 2], a[k1 + 3], ob[q].z, ob[q].w);
                        else mma16816(m1[i], a[k1], a[k1 + 1], a[k1 + 2], a[k1 + 3], ob[q].z, ob[q].w);
                    }
                }
                asm volatile("red.relaxed.gpu.global.add.noftz.v4.f16x2 [%0], {%1,%2,%3,%4};" :: "l"(rptr),
                    "r"(pack_f16(m0[0][0] + m1[0][0], m0[0][2] + m1[0][2])), "r"(pack_f16(m0[1][0] + m1[1][0], m0[1][2] + m1[1][2])),
                    "r"(pack_f16(m0[2][0] + m1[2][0], m0[2][2] + m1[2][2])), "r"(0x3c00u) : "memory");
                asm volatile("red.relaxed.gpu.global.add.noftz.v4.f16x2 [%0], {%1,%2,%3,%4};" :: "l"(rptr + 1024),
                    "r"(pack_f16(m0[0][1] + m1[0][1], m0[0][3] + m1[0][3])), "r"(pack_f16(m0[1][1] + m1[1][1], m0[1][3] + m1[1][3])),
                    "r"(pack_f16(m0[2][1] + m1[2][1], m0[2][3] + m1[2][3])), "r"(0x3c00u) : "memory");
                t_red = clk();
                bar_arrive(5, 384);
                if (c == 0) { sts32_if(l16, sb + O_MISC, inv_new); mbar_expect_if(l16, sb + B_SC, 2560); }
                if (c == 1) mbar_expect_if(l16, sb + B_VM, 2048);
                if (c == 2 && r < 2) mbar_expect_if(l16, sb + B_VX + 8 * ((s + 1) & 1), VXBYTES);
                if (c == 3 && r < 2) mbar_expect_if(l16, sb + B_SX + 8 * ((s + 1) & 1), r == 0 ? 3072 : 5120);
                if (c == 0) STAMPV(s, 8, t_red);
            } else if (r < 2 && s == NSEG - 1) {
                mbar_wait(sb + B_VM, s & 1);
                mbar_wait(sb + B_VX + 8 * (s & 1), (s >> 1) & 1);
            }

            float px[10];
#pragma unroll
            for (int i = 0; i < 10; i++) px[i] = 0.f;
            if (r < 2 && s < NSEG) {
                mbar_wait(sb + B_SX + 8 * (s & 1), (s >> 1) & 1);
                const uint32_t so = sb + O_SX + (s & 1) * 5120 + (c & 1) * 1280 + (l16 >> 1);
                const int q0 = 16 * r + 8 * (c & 1) + 8 + (int)(l16 >> 6) - (int)((l16 >> 3) & 6);
#pragma unroll
                for (int n = 0; n < 5; n++) {
                    const float2 u = lds64f(so + n * 256), v = lds64f(so + 2560 + n * 256);
                    px[2 * n] = u.x + v.x; px[2 * n + 1] = u.y + v.y;
                    if (n > 0) {
                        if (8 * n > q0) px[2 * n] = -INFINITY;
                        if (8 * n + 1 > q0) px[2 * n + 1] = -INFINITY;
                    }
                }
                float mx = fmaxf(fmaxf(fmaxf(px[0], px[1]), fmaxf(px[2], px[3])), fmaxf(fmaxf(px[4], px[5]), fmaxf(px[6], px[7])));
                mx = quad_max(fmaxf(mx, fmaxf(px[8], px[9])));
                const float mo = mx * SM_SCALE;
#pragma unroll
                for (int i = 0; i < 10; i++) px[i] = fmaf(px[i], SM_SCALE, -mo);
            }
            auto finish_x = [&]() {
                if (s >= 1) {
                    const uint4 u0 = lds128(sb + O_OXS + c * 1024 + l16), u1 = lds128(sb + O_OXS + c * 1024 + 512 + l16);
                    *reinterpret_cast<uint4*>(optr) = u0;
                    *reinterpret_cast<uint4*>(optr + 512) = u1;
                }
#pragma unroll
                for (int n = 0; n < 5; n++) PX[n] = pack_bf16(ex2v(px[2 * n]), ex2v(px[2 * n + 1]));
            };
            if (s >= NSEG - 1) {
                if (r < 2) finish_x();
            } else {
                if (c == 0) STAMP(s, 9);
                const char* pbase = rptr + pdelta;
                spin_until(t_red, D_WAIT);
                uint4 v[6];
#pragma unroll
                for (int i = 0; i < 6; i++) v[i] = ldg_relaxed128(pbase + (i >> 1) * 8192 + (i & 1) * 512);
                if (r < 2) finish_x();
                int nretry = 0;
#pragma unroll
                for (int tau = 0; tau < 3; tau++) {
                    asm volatile("{\n.reg .pred p, q;\n.reg .u32 n;\nmov.u32 n, 0;\n"
                                 "R_%=: setp.eq.u32 p, %3, 0x5000;\nsetp.eq.and.u32 p, %7, 0x5000, p;\nvote.sync.all.pred q, p, 0xffffffff;\n@q bra.uni K_%=;\n"
                                 "ld.relaxed.gpu.global.v4.u32 {%0,%1,%2,%3}, [%9];\nld.relaxed.gpu.global.v4.u32 {%4,%5,%6,%7}, [%9+512];\n"
                                 "add.u32 %8, %8, 1;\nadd.u32 n, n, 1;\nsetp.lt.u32 q, n, 2000000;\n@q bra.uni R_%=;\ntrap;\nK_%=:\n}"
                                 : "+r"(v[2 * tau].x), "+r"(v[2 * tau].y), "+r"(v[2 * tau].z), "+r"(v[2 * tau].w),
                                   "+r"(v[2 * tau + 1].x), "+r"(v[2 * tau + 1].y), "+r"(v[2 * tau + 1].z), "+r"(v[2 * tau + 1].w), "+r"(nretry)
                                 : "l"(pbase + tau * 8192) : "memory");
                    v[2 * tau].x = f16x2_to_bf16x2(v[2 * tau].x); v[2 * tau + 1].x = f16x2_to_bf16x2(v[2 * tau + 1].x);
                    v[2 * tau].y = f16x2_to_bf16x2(v[2 * tau].y); v[2 * tau + 1].y = f16x2_to_bf16x2(v[2 * tau + 1].y);
                    v[2 * tau].z = f16x2_to_bf16x2(v[2 * tau].z); v[2 * tau + 1].z = f16x2_to_bf16x2(v[2 * tau + 1].z);
                    sts128(sb + O_MF + tau * 3072 + (c >> 1) * 1536 + (c & 1) * 512 + l16, v[2 * tau].x, v[2 * tau + 1].x, v[2 * tau].y, v[2 * tau + 1].y);
                    sts64(sb + O_MF + tau * 3072 + (c >> 1) * 1536 + 1024 + (c & 1) * 8 + l16, v[2 * tau].z, v[2 * tau + 1].z);
                    if (tau == 0) bar_arrive(2, 384);
                    else bar_arrive(10 + 2 * tau + (c >> 1), 192);
                    if (c == 0) STAMP(s, 10 + tau);
                }
                if (c == 0) STAMPV(s, 14, nretry);
                mmax = absmax2(absmax2(absmax2(v[0].x, v[0].y), absmax2(v[0].z, v[1].x)), absmax2(absmax2(v[1].y, v[1].z), absmax2(v[2].x, v[2].y)));
                mmax = absmax2(mmax, absmax2(absmax2(absmax2(v[2].z, v[3].x), absmax2(v[3].y, v[3].z)), absmax2(absmax2(v[4].x, v[4].y), absmax2(v[4].z, v[5].x))));
                mmax = absmax2(mmax, absmax2(v[5].y, v[5].z));
            }
            s3p = s3;
            rptr += 24576;
            optr += 4096;
        }
        if (r < 2) {
            bar_sync(6, 128);
            if (c == 0)
                asm volatile("{\n.reg .pred p;\nsetp.eq.u32 p, %1, 0;\nfence.acq_rel.gpu;\n@p red.relaxed.gpu.global.add.u32 [%0], 1;\n"
                             "@p red.relaxed.gpu.global.add.u32 [%0+128], 1;\n@p red.relaxed.gpu.global.add.u32 [%0+256], 1;\n}"
                             :: "l"(&g_flag[(61 * 4 + (h >> 3)) * 8]), "r"(l16c) : "memory");
        }
    }
    cluster_sync();
}

__device__ float g_u[SEQ * 2 * DM];
__global__ void naive_gemm1(const __nv_bfloat16* x, const __nv_bfloat16* Bre, const __nv_bfloat16* Bim) {
    int p = blockIdx.x * 64 + threadIdx.x % 64, tk = blockIdx.y * 4 + threadIdx.x / 64;
    float sr = 0, si = 0;
    for (int d = 0; d < DM; d++) { float xv = __bfloat162float(x[tk * DM + d]); sr += xv * __bfloat162float(Bre[p * DM + d]); si += xv * __bfloat162float(Bim[p * DM + d]); }
    g_u[tk * 2 * DM + 2 * p] = sr; g_u[tk * 2 * DM + 2 * p + 1] = si;
}
__global__ void naive_scan(const __nv_bfloat16* Lre, const __nv_bfloat16* Lim, const __nv_bfloat16* logdt) {
    int p = blockIdx.x * 64 + threadIdx.x;
    float dt = __bfloat162float(__float2bfloat16(expf(__bfloat162float(logdt[p]))));
    float lr = __bfloat162float(Lre[p]), li = __bfloat162float(Lim[p]);
    float e = expf(dt * lr), br = e * cosf(dt * li), bi = e * sinf(dt * li);
    float den = lr * lr + li * li;
    float cr = ((br - 1.f) * lr + bi * li) / den, ci = (bi * lr - (br - 1.f) * li) / den;
    float hr = 0, hi = 0;
    for (int tk = 0; tk < SEQ; tk++) {
        float ur = g_u[tk * 2 * DM + 2 * p], ui = g_u[tk * 2 * DM + 2 * p + 1];
        float nr = br * hr - bi * hi + cr * ur - ci * ui, ni = br * hi + bi * hr + cr * ui + ci * ur;
        hr = nr; hi = ni;
        g_u[tk * 2 * DM + 2 * p] = hr; g_u[tk * 2 * DM + 2 * p + 1] = hi;
    }
}
__global__ void naive_gemm2(const __nv_bfloat16* x, const __nv_bfloat16* Cre, const __nv_bfloat16* Cim, const __nv_bfloat16* Dk, float* out) {
    int d = blockIdx.x * 64 + threadIdx.x % 64, tk = blockIdx.y * 4 + threadIdx.x / 64;
    float s = 0;
    for (int p = 0; p < DM; p++) s += g_u[tk * 2 * DM + 2 * p] * __bfloat162float(Cre[d * DM + p]) - g_u[tk * 2 * DM + 2 * p + 1] * __bfloat162float(Cim[d * DM + p]);
    out[tk * 1152 + d] = 2.f * s + __bfloat162float(__float2bfloat16(__bfloat162float(x[tk * DM + d]) * __bfloat162float(Dk[d])));
}
__global__ void naive_wo(const __nv_bfloat16* Wo, float* out) {
    int d = blockIdx.x * 64 + threadIdx.x % 64, tk = blockIdx.y * 4 + threadIdx.x / 64;
    const __nv_bfloat16* ox = reinterpret_cast<const __nv_bfloat16*>(g_ox);
    float s = 0;
    for (int k = 0; k < HD; k++) {
        int hh = k >> 6, e0 = k & 63, e = (e0 & 48) + (e0 & 1) * 8 + ((e0 & 15) >> 1);
        s += __bfloat162float(ox[((size_t)hh * SEQ + tk) * 64 + (((e >> 3) ^ (tk & 7)) << 3) + (e & 7)]) * __bfloat162float(Wo[k * DM + d]);
    }
    out[tk * 1152 + DM + d] = s;
}

typedef CUresult (*EncodeFn)(CUtensorMap*, CUtensorMapDataType, cuuint32_t, void*, const cuuint64_t*, const cuuint64_t*, const cuuint32_t*, const cuuint32_t*,
                             CUtensorMapInterleave, CUtensorMapSwizzle, CUtensorMapL2promotion, CUtensorMapFloatOOBfill);
}

extern "C" void kernel_launch(void* const* d_in, const int* in_sizes, int n_in, void* d_out, int out_size) {
    typedef const __nv_bfloat16* bp;
    bp Ax = (bp)d_in[0], Lre = (bp)d_in[1], Lim = (bp)d_in[2], Bre = (bp)d_in[3], Bim = (bp)d_in[4], Cre = (bp)d_in[5], Cim = (bp)d_in[6],
       logdt = (bp)d_in[7], Dk = (bp)d_in[8], Bx = (bp)d_in[9], mem0 = (bp)d_in[10], Wq = (bp)d_in[11], Wk = (bp)d_in[12], Wv = (bp)d_in[13], Wo = (bp)d_in[14];
    float* out = (float*)d_out;
    static EncodeFn enc = nullptr;
    if (!enc) {
        void* fn = nullptr; cudaDriverEntryPointQueryResult qr;
        cudaGetDriverEntryPoint("cuTensorMapEncodeTiled", &fn, cudaEnableDefault, &qr);
        enc = (EncodeFn)fn;
        cudaFuncSetAttribute(chain_kernel, cudaFuncAttributeMaxDynamicSharedMemorySize, CHAIN_SMEM);
    }
    CUtensorMap tm_x;
    {
        cuuint64_t gd[2] = {DM, SEQ}; cuuint64_t gs[1] = {DM * 2}; cuuint32_t bd[2] = {64, 32}; cuuint32_t es[2] = {1, 1};
        enc(&tm_x, CU_TENSOR_MAP_DATA_TYPE_BFLOAT16, 2, (void*)Bx, gd, gs, bd, es, CU_TENSOR_MAP_INTERLEAVE_NONE, CU_TENSOR_MAP_SWIZZLE_128B,
            CU_TENSOR_MAP_L2_PROMOTION_L2_128B, CU_TENSOR_MAP_FLOAT_OOB_FILL_NONE);
    }
    cudaStream_t st = cudaStreamPerThread;
    chain_kernel<<<96, 384, CHAIN_SMEM, st>>>(tm_x, Bx, mem0, Wq, Wk, Wv, Wo);
    naive_gemm1<<<dim3(9, 512), 256, 0, st>>>(Ax, Bre, Bim);
    naive_scan<<<9, 64, 0, st>>>(Lre, Lim, logdt);
    naive_gemm2<<<dim3(9, 512), 256, 0, st>>>(Ax, Cre, Cim, Dk, out);
    naive_wo<<<dim3(9, 512), 256, 0, st>>>(Wo, out);
}
```

```cpp
#include <cuda_runtime.h>
#include <cuda.h>
#include <cuda_bf16.h>
#include <cuda_fp16.h>
#include <stdint.h>

#define D_WAIT 700
#define VXMODE 1
#define VXBYTES (VXMODE == 2 ? 0 : 8192)
#define XCHUNK1 10

namespace {

constexpr int DM = 576, NH = 32, SEQ = 2048, NSEG = 64, HD = 4096;

__device__ uint4 g_acc[64 * 96 * 16];
__device__ uint4 g_ox[NH * 2 * SEQ * 8];
__device__ unsigned g_flag[NSEG * 4 * 8];
__device__ unsigned g_gridbar;
__device__ float g_norm[96 * 4];

__device__ __forceinline__ uint32_t smem_u32(const void* p) { return (uint32_t)__cvta_generic_to_shared(p); }
__device__ __forceinline__ uint32_t mapa(uint32_t a, uint32_t r) { uint32_t o; asm("mapa.shared::cluster.u32 %0, %1, %2;" : "=r"(o) : "r"(a), "r"(r)); return o; }
__device__ __forceinline__ uint32_t mapa_v(uint32_t a, uint32_t r) { uint32_t o; asm volatile("mapa.shared::cluster.u32 %0, %1, %2;" : "=r"(o) : "r"(a), "r"(r)); return o; }
__device__ __forceinline__ unsigned clk() { unsigned long long c; asm volatile("mov.u64 %0, %%clock64;" : "=l"(c) :: "memory"); return (unsigned)c; }
__device__ __forceinline__ void mbar_init(uint32_t bar, uint32_t cnt) { asm volatile("mbarrier.init.shared::cta.b64 [%0], %1;" :: "r"(bar), "r"(cnt) : "memory"); }
__device__ __forceinline__ void mbar_expect(uint32_t bar, uint32_t bytes) { asm volatile("mbarrier.arrive.expect_tx.shared::cta.b64 _, [%0], %1;" :: "r"(bar), "r"(bytes) : "memory"); }
__device__ __forceinline__ void mbar_wait(uint32_t bar, uint32_t parity) {
    asm volatile("{\n.reg .pred p;\n.reg .u32 n;\nmov.u32 n, 0;\n"
                 "W_%=: mbarrier.try_wait.parity.shared::cta.b64 p, [%0], %1;\n@p bra.uni D_%=;\n"
                 "add.u32 n, n, 1;\nsetp.lt.u32 p, n, 4000000;\n@p bra.uni W_%=;\ntrap;\nD_%=:\n}" :: "r"(bar), "r"(parity) : "memory");
}
__device__ __forceinline__ void mbar_expect_if(uint32_t z, uint32_t bar, uint32_t bytes) {
    asm volatile("{\n.reg .pred p;\nsetp.eq.u32 p, %2, 0;\n@p mbarrier.arrive.expect_tx.shared::cta.b64 _, [%0], %1;\n}" :: "r"(bar), "r"(bytes), "r"(z) : "memory");
}
__device__ __forceinline__ void mbar_arrive_if(uint32_t z, uint32_t bar) {
    asm volatile("{\n.reg .pred p;\nsetp.eq.u32 p, %1, 0;\n@p mbarrier.arrive.shared::cta.b64 _, [%0];\n}" :: "r"(bar), "r"(z) : "memory");
}
__device__ __forceinline__ void sts32_if(uint32_t z, uint32_t a, uint32_t x) {
    asm volatile("{\n.reg .pred p;\nsetp.eq.u32 p, %2, 0;\n@p st.shared.u32 [%0], %1;\n}" :: "r"(a), "r"(x), "r"(z) : "memory");
}
__device__ __forceinline__ void spin_until(unsigned t0, unsigned d) {
    asm volatile("{\n.reg .pred p;\n.reg .u64 c;\n.reg .u32 lo;\n"
                 "S_%=: mov.u64 c, %%clock64;\ncvt.u32.u64 lo, c;\nsub.u32 lo, lo, %0;\nsetp.lt.u32 p, lo, %1;\n@p bra.uni S_%=;\n}" :: "r"(t0), "r"(d) : "memory");
}
__device__ __forceinline__ void bar_sync(int id, int n) { asm volatile("bar.sync %0, %1;" :: "r"(id), "r"(n) : "memory"); }
__device__ __forceinline__ void bar_sync_sel(int sel, int id) {
    asm volatile("{\n.reg .pred p;\nsetp.eq.u32 p, %0, 0;\n@p bar.sync %1, %3;\n@!p bar.sync %2, %3;\n}" :: "r"(sel), "r"(id), "r"(id + 1), "n"(192) : "memory");
}
__device__ __forceinline__ void bar_arrive(int id, int n) { asm volatile("bar.arrive %0, %1;" :: "r"(id), "r"(n) : "memory"); }
__device__ __forceinline__ void fence_async_smem() { asm volatile("fence.proxy.async.shared::cta;" ::: "memory"); }
__device__ __forceinline__ uint32_t pack_bf16(float lo, float hi) { uint32_t r; asm("cvt.rn.bf16x2.f32 %0, %1, %2;" : "=r"(r) : "f"(hi), "f"(lo)); return r; }
__device__ __forceinline__ uint32_t pack_f16(float lo, float hi) { uint32_t r; asm("cvt.rn.f16x2.f32 %0, %1, %2;" : "=r"(r) : "f"(hi), "f"(lo)); return r; }
__device__ __forceinline__ uint32_t f16x2_to_bf16x2(uint32_t v) { float2 f = __half22float2(*reinterpret_cast<__half2*>(&v)); return pack_bf16(f.x, f.y); }
__device__ __forceinline__ float ex2(float x) { float y; asm("ex2.approx.ftz.f32 %0, %1;" : "=f"(y) : "f"(x)); return y; }
__device__ __forceinline__ float ex2v(float x) { float y; asm volatile("ex2.approx.ftz.f32 %0, %1;" : "=f"(y) : "f"(x)); return y; }
__device__ __forceinline__ uint32_t shl_v(uint32_t a, int n) { return a << n; }
__device__ __forceinline__ uint32_t max3u(uint32_t a, uint32_t b, uint32_t c) { return max(max(a, b), c); }
__device__ __forceinline__ uint4 lds128(uint32_t a) { uint4 v; asm volatile("ld.shared.v4.u32 {%0,%1,%2,%3}, [%4];" : "=r"(v.x), "=r"(v.y), "=r"(v.z), "=r"(v.w) : "r"(a) : "memory"); return v; }
__device__ __forceinline__ float4 lds128f(uint32_t a) { float4 v; asm volatile("ld.shared.v4.f32 {%0,%1,%2,%3}, [%4];" : "=f"(v.x), "=f"(v.y), "=f"(v.z), "=f"(v.w) : "r"(a) : "memory"); return v; }
__device__ __forceinline__ float2 lds64f(uint32_t a) { float2 v; asm volatile("ld.shared.v2.f32 {%0,%1}, [%2];" : "=f"(v.x), "=f"(v.y) : "r"(a) : "memory"); return v; }
__device__ __forceinline__ uint4 lds64x2(uint32_t a) { uint4 v; asm volatile("ld.shared.v2.u32 {%0,%1}, [%4];\nld.shared.v2.u32 {%2,%3}, [%4+256];" : "=r"(v.x), "=r"(v.y), "=r"(v.z), "=r"(v.w) : "r"(a) : "memory"); return v; }
__device__ __forceinline__ uint32_t lds32(uint32_t a) { uint32_t v; asm volatile("ld.shared.u32 %0, [%1];" : "=r"(v) : "r"(a) : "memory"); return v; }
__device__ __forceinline__ void sts128(uint32_t a, uint32_t x, uint32_t y, uint32_t z, uint32_t w) { asm volatile("st.shared.v4.u32 [%0], {%1,%2,%3,%4};" :: "r"(a), "r"(x), "r"(y), "r"(z), "r"(w) : "memory"); }
__device__ __forceinline__ void sts128f(uint32_t a, float x, float y, float z, float w) { asm volatile("st.shared.v4.f32 [%0], {%1,%2,%3,%4};" :: "r"(a), "f"(x), "f"(y), "f"(z), "f"(w) : "memory"); }
__device__ __forceinline__ void sts64(uint32_t a, uint32_t x, uint32_t y) { asm volatile("st.shared.v2.u32 [%0], {%1,%2};" :: "r"(a), "r"(x), "r"(y) : "memory"); }
__device__ __forceinline__ void sts32(uint32_t a, uint32_t x) { asm volatile("st.shared.u32 [%0], %1;" :: "r"(a), "r"(x) : "memory"); }
__device__ __forceinline__ uint4 ldsm4(uint32_t a) { uint4 v; asm volatile("ldmatrix.sync.aligned.m8n8.x4.shared.b16 {%0,%1,%2,%3}, [%4];" : "=r"(v.x), "=r"(v.y), "=r"(v.z), "=r"(v.w) : "r"(a) : "memory"); return v; }
__device__ __forceinline__ void stsm2t(uint32_t a, uint32_t x, uint32_t y) { asm volatile("stmatrix.sync.aligned.m8n8.x2.trans.shared.b16 [%0], {%1,%2};" :: "r"(a), "r"(x), "r"(y) : "memory"); }
__device__ __forceinline__ void stsm4t(uint32_t a, uint32_t x, uint32_t y, uint32_t z, uint32_t w) { asm volatile("stmatrix.sync.aligned.m8n8.x4.trans.shared.b16 [%0], {%1,%2,%3,%4};" :: "r"(a), "r"(x), "r"(y), "r"(z), "r"(w) : "memory"); }
__device__ __forceinline__ void st_async64(uint32_t a, uint32_t x, uint32_t y, uint32_t bar) { asm volatile("st.async.shared::cluster.mbarrier::complete_tx::bytes.v2.b32 [%0], {%1,%2}, [%3];" :: "r"(a), "r"(x), "r"(y), "r"(bar) : "memory"); }
__device__ __forceinline__ void bulk_s2c(uint32_t dst, uint32_t src, uint32_t bytes, uint32_t bar) { asm volatile("cp.async.bulk.shared::cluster.shared::cta.mbarrier::complete_tx::bytes [%0], [%1], %2, [%3];" :: "r"(dst), "r"(src), "r"(bytes), "r"(bar) : "memory"); }
__device__ __forceinline__ void bulk_s2g(void* dst, uint32_t src, uint32_t bytes) { asm volatile("cp.async.bulk.global.shared::cta.bulk_group [%0], [%1], %2;" :: "l"(dst), "r"(src), "r"(bytes) : "memory"); }
__device__ __forceinline__ uint32_t ldg_nc32(const void* p) { uint32_t v; asm volatile("ld.global.nc.L2::128B.u32 %0, [%1];" : "=r"(v) : "l"(p)); return v; }
__device__ __forceinline__ uint4 ldg_relaxed128(const void* p) { uint4 v; asm volatile("ld.relaxed.gpu.global.v4.u32 {%0,%1,%2,%3}, [%4];" : "=r"(v.x), "=r"(v.y), "=r"(v.z), "=r"(v.w) : "l"(p) : "memory"); return v; }
__device__ __forceinline__ void mma16816(float (&d)[4], uint32_t a0, uint32_t a1, uint32_t a2, uint32_t a3, uint32_t b0, uint32_t b1) {
    asm volatile("mma.sync.aligned.m16n8k16.row.col.f32.bf16.bf16.f32 {%0,%1,%2,%3}, {%4,%5,%6,%7}, {%8,%9}, {%0,%1,%2,%3};"
        : "+f"(d[0]), "+f"(d[1]), "+f"(d[2]), "+f"(d[3]) : "r"(a0), "r"(a1), "r"(a2), "r"(a3), "r"(b0), "r"(b1));
}
__device__ __forceinline__ void mma16816_z(float (&d)[4], uint32_t a0, uint32_t a1, uint32_t a2, uint32_t a3, uint32_t b0, uint32_t b1) {
    asm volatile("mma.sync.aligned.m16n8k16.row.col.f32.bf16.bf16.f32 {%0,%1,%2,%3}, {%4,%5,%6,%7}, {%8,%9}, {%10,%10,%10,%10};"
        : "=f"(d[0]), "=f"(d[1]), "=f"(d[2]), "=f"(d[3]) : "r"(a0), "r"(a1), "r"(a2), "r"(a3), "r"(b0), "r"(b1), "f"(0.f));
}
__device__ __forceinline__ void mma1688(float (&d)[4], uint32_t a0, uint32_t a1, uint32_t b0) {
    asm volatile("mma.sync.aligned.m16n8k8.row.col.f32.bf16.bf16.f32 {%0,%1,%2,%3}, {%4,%5}, {%6}, {%0,%1,%2,%3};"
        : "+f"(d[0]), "+f"(d[1]), "+f"(d[2]), "+f"(d[3]) : "r"(a0), "r"(a1), "r"(b0));
}
__device__ __forceinline__ void mma1688_z(float (&d)[4], uint32_t a0, uint32_t a1, uint32_t b0) {
    asm volatile("mma.sync.aligned.m16n8k8.row.col.f32.bf16.bf16.f32 {%0,%1,%2,%3}, {%4,%5}, {%6}, {%7,%7,%7,%7};"
        : "=f"(d[0]), "=f"(d[1]), "=f"(d[2]), "=f"(d[3]) : "r"(a0), "r"(a1), "r"(b0), "f"(0.f));
}
template <int ACC>
__device__ __forceinline__ void wgmma_n32_rs(float (&d)[16], uint32_t a0, uint32_t a1, uint32_t a2, uint32_t a3, uint64_t desc) {
    asm volatile("wgmma.mma_async.sync.aligned.m64n32k16.f32.bf16.bf16 {%0,%1,%2,%3,%4,%5,%6,%7,%8,%9,%10,%11,%12,%13,%14,%15}, {%16,%17,%18,%19}, %20, %21, 1, 1, 0;"
        : "+f"(d[0]), "+f"(d[1]), "+f"(d[2]), "+f"(d[3]), "+f"(d[4]), "+f"(d[5]), "+f"(d[6]), "+f"(d[7]),
          "+f"(d[8]), "+f"(d[9]), "+f"(d[10]), "+f"(d[11]), "+f"(d[12]), "+f"(d[13]), "+f"(d[14]), "+f"(d[15])
        : "r"(a0), "r"(a1), "r"(a2), "r"(a3), "l"(desc), "n"(ACC));
}
__device__ __forceinline__ void wgmma_n32_ss(float (&d)[16], uint64_t da, uint64_t db) {
    asm volatile("wgmma.mma_async.sync.aligned.m64n32k16.f32.bf16.bf16 {%0,%1,%2,%3,%4,%5,%6,%7,%8,%9,%10,%11,%12,%13,%14,%15}, %16, %17, 1, 1, 1, 0, 0;"
        : "+f"(d[0]), "+f"(d[1]), "+f"(d[2]), "+f"(d[3]), "+f"(d[4]), "+f"(d[5]), "+f"(d[6]), "+f"(d[7]),
          "+f"(d[8]), "+f"(d[9]), "+f"(d[10]), "+f"(d[11]), "+f"(d[12]), "+f"(d[13]), "+f"(d[14]), "+f"(d[15])
        : "l"(da), "l"(db));
}
__device__ __forceinline__ void wg_fence() { asm volatile("wgmma.fence.sync.aligned;" ::: "memory"); }
__device__ __forceinline__ void wg_commit() { asm volatile("wgmma.commit_group.sync.aligned;" ::: "memory"); }
__device__ __forceinline__ void wg_wait0() { asm volatile("wgmma.wait_group.sync.aligned 0;" ::: "memory"); }
__device__ __forceinline__ void cluster_sync() { asm volatile("barrier.cluster.arrive.aligned;\nbarrier.cluster.wait.aligned;" ::: "memory"); }

#define STAMP(s, i) do {} while (0)
#define STAMPV(s, i, v) do {} while (0)

constexpr int XT_BYTES = 36864;
constexpr int O_XT = 0;
constexpr int O_AS = 3 * XT_BYTES;
constexpr int O_AF = O_AS + 16384;
constexpr int O_MF = O_AF + 16384;
constexpr int O_QM = O_MF + 9216;
constexpr int O_KM = O_QM + 2048;
constexpr int O_QKX = O_KM + 2048;
constexpr int O_XP = O_QKX + 8192;
constexpr int O_VX = O_XP + 16384;
constexpr int O_VM = O_VX + 24576;
constexpr int O_SC = O_VM + 4096;
constexpr int O_OF = O_SC + 2560;
constexpr int O_SX = O_OF + 2048;
constexpr int O_OXS = O_SX + 10240;
constexpr int O_MISC = O_OXS + 4096;
constexpr int O_BAR = O_MISC + 64;
constexpr int CHAIN_SMEM = O_BAR + 128;
static_assert(CHAIN_SMEM <= 232448, "smem");
constexpr int B_X = O_BAR, B_VX = O_BAR + 24, B_SX = O_BAR + 40, B_SC = O_BAR + 56, B_VM = O_BAR + 64, B_MX = O_BAR + 72;
constexpr float SM_SCALE = 0.08838834764831845f * 1.4426950408889634f;
constexpr uint32_t ONES = 0x3f803f80u;

__device__ __forceinline__ uint32_t opaque(uint32_t v) { uint32_t o; asm volatile("mov.u32 %0, %1;" : "=r"(o) : "r"(v)); return o; }
__device__ __forceinline__ void st_async128(uint32_t a, uint32_t x, uint32_t y, uint32_t z, uint32_t w, uint32_t bar) {
    asm volatile("st.async.shared::cluster.mbarrier::complete_tx::bytes.v4.b32 [%0], {%1,%2,%3,%4}, [%5];" :: "r"(a), "r"(x), "r"(y), "r"(z), "r"(w), "r"(bar) : "memory");
}
__device__ __forceinline__ void tma_x_tile(uint32_t sb, const CUtensorMap* tm, int r, int j, int slot) {
    asm volatile("{\n.reg .pred p;\nelect.sync _|p, 0xffffffff;\n"
        "@p mbarrier.arrive.expect_tx.shared::cta.b64 _, [%2], 36864;\n"
        "@p cp.async.bulk.tensor.2d.shared::cluster.global.mbarrier::complete_tx::bytes.multicast::cluster [%0], [%1, {%3, %4}], [%2], %7;\n"
        "@p cp.async.bulk.tensor.2d.shared::cluster.global.mbarrier::complete_tx::bytes.multicast::cluster [%0+4096], [%1, {%5, %4}], [%2], %7;\n"
        "@p cp.async.bulk.tensor.2d.shared::cluster.global.mbarrier::complete_tx::bytes.multicast::cluster [%0+8192], [%1, {%6, %4}], [%2], %7;\n}"
        :: "r"(sb + O_XT + slot * XT_BYTES + 3 * r * 4096), "l"(tm), "r"(sb + B_X + 8 * slot), "r"(192 * r), "r"(j * 32), "r"(192 * r + 64), "r"(192 * r + 128),
           "h"((unsigned short)7) : "memory");
}
__device__ __forceinline__ float quad_max(float v) {
    const float a = __shfl_xor_sync(~0u, v, 1), b = __shfl_xor_sync(~0u, v, 2), c = __shfl_xor_sync(~0u, v, 3);
    return fmaxf(fmaxf(v, a), fmaxf(b, c));
}
__device__ __forceinline__ void load_scores(float (&p)[10], uint32_t base, uint32_t stride, uint32_t l16) {
    const float4 a0 = lds128f(base + l16), b0 = lds128f(base + stride + l16);
    const float4 a1 = lds128f(base + 512 + l16), b1 = lds128f(base + stride + 512 + l16);
    const float2 a2 = lds64f(base + 1024 + (l16 >> 1)), b2 = lds64f(base + stride + 1024 + (l16 >> 1));
    p[0] = a2.x + b2.x; p[1] = a2.y + b2.y;
    p[2] = a0.x + b0.x; p[3] = a0.y + b0.y; p[4] = a0.z + b0.z; p[5] = a0.w + b0.w;
    p[6] = a1.x + b1.x; p[7] = a1.y + b1.y; p[8] = a1.z + b1.z; p[9] = a1.w + b1.w;
}
__device__ __forceinline__ float rcp_fast(float x) { float y; asm("rcp.approx.ftz.f32 %0, %1;" : "=f"(y) : "f"(x)); return y; }

__global__ void __cluster_dims__(3, 1, 1) __launch_bounds__(384, 1)
chain_kernel(const __grid_constant__ CUtensorMap tm_x,
             const __nv_bfloat16* __restrict__ x, const __nv_bfloat16* __restrict__ mem0,
             const __nv_bfloat16* __restrict__ Wq, const __nv_bfloat16* __restrict__ Wk,
             const __nv_bfloat16* __restrict__ Wv, const __nv_bfloat16* __restrict__ Wo) {
    extern __shared__ __align__(1024) uint8_t smem_raw[];
    const uint32_t sb = smem_u32(smem_raw);
    const int lane = threadIdx.x & 31;
    const int warp = __shfl_sync(~0u, threadIdx.x >> 5, 0);
    const int wg = warp >> 2, w = warp & 3;
    const int h = blockIdx.x / 3, r = blockIdx.x - 3 * h;

    if (threadIdx.x == 0) {
        if (sb & 1023u) __trap();
        for (int i = 0; i < 9; i++) mbar_init(sb + O_BAR + 8 * i, 1);
        mbar_init(sb + B_MX, 4);
        asm volatile("fence.mbarrier_init.release.cluster;" ::: "memory");
    }
    if (blockIdx.x == 0) {
        for (int i = threadIdx.x; i < NSEG * 4 * 8; i += 384) g_flag[i] = 0;
        __threadfence();
    }
    __syncthreads();
    cluster_sync();
    asm volatile("griddepcontrol.launch_dependents;" ::: "memory");
    const uint32_t l16c = __shfl_sync(~0u, lane * 16, lane);

    if (wg < 2) {
#define KB(i) (12 * ((i) / 6) + (((i) % 6) >> 1 == 2 ? 8 + ((i) & 1) : (((i) % 6) >> 1) + 4 * ((i) & 1)))
        asm volatile("setmaxnreg.inc.sync.aligned.u32 176;");
        uint32_t a[144];
        uint32_t adr1;
        {
            const int g = lane >> 2, t = lane & 3;
#pragma unroll
            for (int tl = 0; tl < 2; tl++) {
                const int tile = tl ? wg : (wg ^ 1);
                const __nv_bfloat16* W = (r < 2) ? (tile == 0 ? Wq : Wk) : Wv;
                const int col = h * 128 + ((r < 2) ? 64 * r : 64 * tile) + 16 * w + 2 * g;
                const __nv_bfloat16* p = W + (size_t)(32 * wg + 2 * t) * HD + col;
#pragma unroll
                for (int i = 0; i < 18; i++) {
                    a[72 * tl + 4 * i + 0] = ldg_nc32(p + (size_t)(16 * KB(i) + 0) * HD);
                    a[72 * tl + 4 * i + 1] = ldg_nc32(p + (size_t)(16 * KB(i) + 1) * HD);
                    a[72 * tl + 4 * i + 2] = ldg_nc32(p + (size_t)(16 * KB(i) + 8) * HD);
                    a[72 * tl + 4 * i + 3] = ldg_nc32(p + (size_t)(16 * KB(i) + 9) * HD);
                }
            }
#pragma unroll
            for (int kk = 0; kk < 72; kk++) {
                uint32_t w0 = a[2 * kk], w1 = a[2 * kk + 1];
                a[2 * kk] = __byte_perm(w0, w1, 0x5410);
                a[2 * kk + 1] = __byte_perm(w0, w1, 0x7632);
            }
            float vmax = 0.f;
#pragma unroll
            for (int tl = 0; tl < 2; tl++) {
                float s0 = 0.f, s1 = 0.f;
#pragma unroll
                for (int kk = 36 * tl; kk < 36 * tl + 36; kk++) {
                    s0 += fabsf(__uint_as_float(a[2 * kk] << 16)) + fabsf(__uint_as_float(a[2 * kk] & 0xffff0000u));
                    s1 += fabsf(__uint_as_float(a[2 * kk + 1] << 16)) + fabsf(__uint_as_float(a[2 * kk + 1] & 0xffff0000u));
                }
                s0 += __shfl_xor_sync(~0u, s0, 1); s0 += __shfl_xor_sync(~0u, s0, 2);
                s1 += __shfl_xor_sync(~0u, s1, 1); s1 += __shfl_xor_sync(~0u, s1, 2);
                vmax = fmaxf(vmax, fmaxf(s0, s1));
            }
            uint32_t mx = __reduce_max_sync(~0u, __float_as_uint(2.f * vmax));
            sts32_if(lane, sb + O_MISC + 32 + 4 * warp, mx);
            bar_arrive(7, 384);
            const uint32_t as = sb + O_AS + wg * 8192 + (16 * w + g) * 128 + t * 4;
#pragma unroll
            for (int kk = 0; kk < 4; kk++) {
                sts32(as + (((2 * kk) ^ g) << 4), a[128 + 4 * kk]);
                sts32(as + 1024 + (((2 * kk) ^ g) << 4), a[128 + 4 * kk + 1]);
                sts32(as + (((2 * kk + 1) ^ g) << 4), a[128 + 4 * kk + 2]);
                sts32(as + 1024 + (((2 * kk + 1) ^ g) << 4), a[128 + 4 * kk + 3]);
                sts128(sb + O_AF + warp * 2048 + kk * 512 + lane * 16, a[128 + 4 * kk], a[128 + 4 * kk + 1], a[128 + 4 * kk + 2], a[128 + 4 * kk + 3]);
            }
            fence_async_smem();
            bar_sync(1, 256);
            const uint32_t l = lane * 16;
            const int mi = lane >> 3, isk = (mi >> 1) ? wg : (wg ^ 1);
            adr1 = (r == 2) ? (sb + O_VM + warp * 256 + (l >> 1))
                            : (isk ? (sb + O_KM + w * 512 + wg * 256 + (mi & 1) * 128 + (l & 127))
                                   : (sb + O_QM + w * 512 + (mi & 1) * 256 + wg * 128 + (l & 127)));
            adr1 = __shfl_sync(~0u, adr1, lane);
        }
        int s3 = 2;
#pragma unroll 1
        for (int s = -1; s < NSEG; s++) {
            const uint32_t l16 = opaque(l16c);
            if (s >= 0) {
#pragma unroll
                for (int kk = 0; kk < 4; kk++) {
                    const uint4 v = lds128(sb + O_AF + warp * 2048 + kk * 512 + l16);
                    a[128 + 4 * kk] = v.x; a[128 + 4 * kk + 1] = v.y; a[128 + 4 * kk + 2] = v.z; a[128 + 4 * kk + 3] = v.w;
                }
                float c0[4], c1[4], c2[4], c3[4];
                uint4 b[9];
                float inv;
#pragma unroll
                for (int i = 0; i < 11; i++) {
                    if (i < 9) {
                        if (i == 0) bar_sync(2, 384);
                        else if (i % 3 == 0) bar_sync_sel(wg, 10 + 2 * (i / 3));
                        if (i == 0 && warp == 0) STAMP(s, 0);
                        b[i] = lds128(sb + O_MF + (i / 3) * 3072 + wg * 1536 + (i % 3) * 512 + l16);
                    }
                    if (i == 9) inv = __uint_as_float(lds32(sb + O_MISC));
                    if (i >= 2) {
                        const int u = 8 * (i - 2);
                        if (i == 2) {
                            mma16816_z(c0, a[u], a[u + 1], a[u + 2], a[u + 3], b[0].x, b[0].y);
                            mma16816_z(c1, a[u + 4], a[u + 5], a[u + 6], a[u + 7], b[0].z, b[0].w);
                            mma16816_z(c2, a[72 + u], a[72 + u + 1], a[72 + u + 2], a[72 + u + 3], b[0].x, b[0].y);
                            mma16816_z(c3, a[72 + u + 4], a[72 + u + 5], a[72 + u + 6], a[72 + u + 7], b[0].z, b[0].w);
                        } else {
                            mma16816(c0, a[u], a[u + 1], a[u + 2], a[u + 3], b[i - 2].x, b[i - 2].y);
                            mma16816(c1, a[u + 4], a[u + 5], a[u + 6], a[u + 7], b[i - 2].z, b[i - 2].w);
                            mma16816(c2, a[72 + u], a[72 + u + 1], a[72 + u + 2], a[72 + u + 3], b[i - 2].x, b[i - 2].y);
                            mma16816(c3, a[72 + u + 4], a[72 + u + 5], a[72 + u + 6], a[72 + u + 7], b[i - 2].z, b[i - 2].w);
                        }
                    }
                }
                if (r < 2) {
                    stsm4t(adr1, pack_bf16((c0[0] + c1[0]) * inv, (c0[1] + c1[1]) * inv), pack_bf16((c0[2] + c1[2]) * inv, (c0[3] + c1[3]) * inv),
                                 pack_bf16((c2[0] + c3[0]) * inv, (c2[1] + c3[1]) * inv), pack_bf16((c2[2] + c3[2]) * inv, (c2[3] + c3[3]) * inv));
                    if (warp == 0) STAMP(s, 1);
                    const int kt = warp < 3 ? warp : (warp < 5 ? warp - 3 : (warp == 5 ? 0 : 2));
                    const int mt = (warp == 5 || warp == 7) ? 0 : 1;
                    const uint32_t qa = sb + (warp < 3 ? O_QM : O_QKX + mt * 2048) + l16;
                    const uint32_t ka = sb + (kt == 2 ? O_KM : O_QKX + 4096 + kt * 2048) + l16;
                    const uint32_t doff = kt * 512 + (kt == 2 ? (l16 >> 1) : l16);
                    auto scores = [&](float (&s0)[4], float (&s1)[4], const uint4 (&q)[4], const uint4 (&k)[4]) {
                        mma16816_z(s0, q[0].x, q[0].y, q[0].z, q[0].w, k[0].x, k[0].y);
                        mma16816_z(s1, q[0].x, q[0].y, q[0].z, q[0].w, k[0].z, k[0].w);
#pragma unroll
                        for (int i = 1; i < 4; i++) {
                            mma16816(s0, q[i].x, q[i].y, q[i].z, q[i].w, k[i].x, k[i].y);
                            mma16816(s1, q[i].x, q[i].y, q[i].z, q[i].w, k[i].z, k[i].w);
                        }
                    };
                    if (warp < 2) {
                        uint4 q[4], k[4]; float s0[4], s1[4];
#pragma unroll
                        for (int i = 0; i < 4; i++) k[i] = ldsm4(ka + i * 512);
                        bar_sync(1, 256);
#pragma unroll
                        for (int i = 0; i < 4; i++) q[i] = ldsm4(qa + i * 512);
                        scores(s0, s1, q, k);
                        const uint32_t dst = sb + O_SC + r * 1280 + doff;
                        const uint32_t v0 = __float_as_uint(s0[0] + s0[2]), v1 = __float_as_uint(s0[1] + s0[3]);
                        const uint32_t v2 = __float_as_uint(s1[0] + s1[2]), v3 = __float_as_uint(s1[1] + s1[3]);
                        st_async128(mapa(dst, 2), v0, v1, v2, v3, mapa(sb + B_SC, 2));
                        st_async128(mapa(dst, r ^ 1), v0, v1, v2, v3, mapa(sb + B_SC, r ^ 1));
                        st_async128(mapa(dst, r), v0, v1, v2, v3, mapa(sb + B_SC, r));
                        bar_arrive(4, 256);
                    } else if (warp == 2) {
                        uint4 q[4], k[4]; float s0[4], s1[4];
                        bar_sync(1, 256);
#pragma unroll
                        for (int i = 0; i < 4; i++) { q[i] = ldsm4(qa + i * 512); k[i] = ldsm4(ka + i * 512); }
                        scores(s0, s1, q, k);
                        const uint32_t dst = sb + O_SC + r * 1280 + doff;
                        const uint32_t v0 = __float_as_uint((s0[0] + s0[2]) + (s1[0] + s1[2])), v1 = __float_as_uint((s0[1] + s0[3]) + (s1[1] + s1[3]));
                        st_async64(mapa(dst, 2), v0, v1, mapa(sb + B_SC, 2));
                        st_async64(mapa(dst, r ^ 1), v0, v1, mapa(sb + B_SC, r ^ 1));
                        st_async64(mapa(dst, r), v0, v1, mapa(sb + B_SC, r));
                        STAMP(s, 2);
                        bar_arrive(4, 256);
                    } else {
                        uint4 q[4], k[4]; float s0[4], s1[4];
#pragma unroll
                        for (int i = 0; i < 4; i++) q[i] = ldsm4(qa + i * 512);
                        bar_sync(1, 256);
                        bar_sync(8, 160);
#pragma unroll
                        for (int i = 0; i < 4; i++) k[i] = ldsm4(ka + i * 512);
                        scores(s0, s1, q, k);
                        const uint32_t dx = mapa(sb + O_SX + (s & 1) * 5120 + r * 2560 + doff, mt), bx = mapa(sb + B_SX + 8 * (s & 1), mt);
                        bar_sync(4, 256);
                        if (kt != 2) {
                            st_async128(dx, __float_as_uint(s0[0]), __float_as_uint(s0[1]), __float_as_uint(s1[0]), __float_as_uint(s1[1]), bx);
                            st_async128(dx + 1280, __float_as_uint(s0[2]), __float_as_uint(s0[3]), __float_as_uint(s1[2]), __float_as_uint(s1[3]), bx);
                        } else {
                            st_async64(dx, __float_as_uint(s0[0] + s1[0]), __float_as_uint(s0[1] + s1[1]), bx);
                            st_async64(dx + 1280, __float_as_uint(s0[2] + s1[2]), __float_as_uint(s0[3] + s1[3]), bx);
                        }
                    }
                } else {
                    sts128f(sb + O_XP + warp * 512 + l16, c0[0] + c1[0], c0[1] + c1[1], c0[2] + c1[2], c0[3] + c1[3]);
                    bar_sync(8 + w, 64);
                    const float4 o = lds128f(sb + O_XP + (warp ^ 4) * 512 + l16);
                    const uint32_t X0 = pack_bf16((c2[0] + c3[0] + o.x) * inv, (c2[1] + c3[1] + o.y) * inv);
                    const uint32_t X1 = pack_bf16((c2[2] + c3[2] + o.z) * inv, (c2[3] + c3[3] + o.w) * inv);
                    if (warp == 0) STAMP(s, 1);
                    const uint32_t dst = adr1 + (s & 1) * 2048;
                    st_async64(mapa(dst, 0), X0, X1, mapa(sb + B_VM, 0));
                    st_async64(mapa(dst, 1), X0, X1, mapa(sb + B_VM, 1));
                    st_async64(mapa(dst, 2), X0, X1, mapa(sb + B_VM, 2));
                    if (warp == 0) STAMP(s, 2);
                }
            }
            s3 = (s3 == 2) ? 0 : s3 + 1;
            if (s < NSEG - 1) {
                const int j = s + 1;
                const uint64_t desc0 = (uint64_t)(((sb + O_XT + s3 * XT_BYTES + wg * 64) & 0x3FFFF) >> 4) | (1ull << 16) | (64ull << 32) | (1ull << 62);
#define XDESC(i) (desc0 + (uint64_t)(((KB(i) >> 2) * 4096 + (KB(i) & 3) * 32) >> 4))
                float d[16];
                if (s >= 0) bar_sync(3, 384);
                mbar_wait(sb + B_X + 8 * s3, (j / 3) & 1);
                wg_fence();
#pragma unroll
                for (int i = 0; i < XCHUNK1; i++) {
                    if (i == 0) wgmma_n32_rs<0>(d, a[0], a[1], a[2], a[3], XDESC(0));
                    else wgmma_n32_rs<1>(d, a[4 * i], a[4 * i + 1], a[4 * i + 2], a[4 * i + 3], XDESC(i));
                }
                wg_commit();
                if (wg == 1) bar_sync(s >= 0 ? 5 : 1, s >= 0 ? 384 : 256);
#pragma unroll
                for (int i = XCHUNK1; i < 18; i++) wgmma_n32_rs<1>(d, a[4 * i], a[4 * i + 1], a[4 * i + 2], a[4 * i + 3], XDESC(i));
                wg_commit();
                wg_wait0();
                if (warp == 0) STAMP(s, 15);
#pragma unroll
                for (int q = 0; q < 4; q++) sts128f(sb + O_XP + warp * 2048 + q * 512 + l16, d[4 * q], d[4 * q + 1], d[4 * q + 2], d[4 * q + 3]);
                if (warp == 1 && s >= 0 && s + 2 < NSEG) tma_x_tile(sb, &tm_x, r, s + 2, s3 == 2 ? 0 : s3 + 1);
                if (wg == 0) bar_sync(s >= 0 ? 5 : 1, s >= 0 ? 384 : 256);
                else bar_arrive(8 + w, 64);
                wg_fence();
#pragma unroll
                for (int i = 0; i < 18; i++) {
                    if (i == 0) wgmma_n32_rs<0>(d, a[72], a[73], a[74], a[75], XDESC(0));
                    else if (i < 14) wgmma_n32_rs<1>(d, a[72 + 4 * i], a[72 + 4 * i + 1], a[72 + 4 * i + 2], a[72 + 4 * i + 3], XDESC(i));
                    else wgmma_n32_ss(d, (uint64_t)(((sb + O_AS + wg * 8192 + (i - 14) * 32) & 0x3FFFF) >> 4) | (1ull << 16) | (64ull << 32) | (1ull << 62), XDESC(i));
                }
                wg_commit();
                if (warp == 3 && r < 2 && s >= 2)
                    asm volatile("{\n.reg .pred p;\nsetp.eq.u32 p, %1, 0;\n@p red.release.gpu.global.add.u32 [%0], 1;\n}"
                                 :: "l"(&g_flag[((s - 2) * 4 + (h >> 3)) * 8]), "r"(l16) : "memory");
                if (wg == 0) bar_sync(8 + w, 64);
                wg_wait0();
                if (warp == 4) STAMP(s, 3);
                uint32_t e[8];
#pragma unroll
                for (int q = 0; q < 4; q++) {
                    const float4 o = lds128f(sb + O_XP + (warp ^ 4) * 2048 + q * 512 + l16);
                    e[2 * q] = pack_bf16(d[4 * q] + o.x, d[4 * q + 1] + o.y);
                    e[2 * q + 1] = pack_bf16(d[4 * q + 2] + o.z, d[4 * q + 3] + o.w);
                }
                if (r < 2) {
                    const uint32_t base = sb + O_QKX + wg * 4096 + w * 512 + l16;
                    stsm4t(base, e[0], wg ? e[1] : e[2], wg ? e[2] : e[1], e[3]);
                    stsm4t(base + 2048, e[4], wg ? e[5] : e[6], wg ? e[6] : e[5], e[7]);
                } else {
                    const uint32_t base = sb + O_VX + s3 * 8192 + warp * 1024 + l16;
                    sts128(base, e[0], e[1], e[2], e[3]);
                    sts128(base + 512, e[4], e[5], e[6], e[7]);
                    const uint32_t bar = sb + B_VX + 8 * (j & 1);
                    fence_async_smem();
                    __syncwarp();
                    const uint32_t src = sb + O_VX + s3 * 8192 + warp * 1024;
                    asm volatile("{\n.reg .pred p;\nelect.sync _|p, 0xffffffff;\n"
                        "@p cp.async.bulk.shared::cluster.shared::cta.mbarrier::complete_tx::bytes [%0], [%2], 1024, [%3];\n"
                        "@p cp.async.bulk.shared::cluster.shared::cta.mbarrier::complete_tx::bytes [%1], [%2], 1024, [%4];\n}"
                        :: "r"(mapa(src, 0)), "r"(mapa(src, 1)), "r"(src), "r"(mapa(bar, 0)), "r"(mapa(bar, 1)) : "memory");
                }
                if (warp == 7) STAMP(s, 4);
            }
        }
    } else {
        asm volatile("setmaxnreg.dec.sync.aligned.u32 152;");
        const int c = w;
        uint32_t a[96];
        uint32_t mmax = 0;
        {
            const int g = lane >> 2, t = lane & 3, t2 = threadIdx.x - 256;
            if (c == 0) {
                tma_x_tile(sb, &tm_x, r, 0, 0);
                tma_x_tile(sb, &tm_x, r, 1, 1);
                mbar_expect_if(lane, sb + B_SC, 2560);
                mbar_expect_if(lane, sb + B_VM, 2048);
                if (r < 2) { mbar_expect_if(lane, sb + B_VX, VXBYTES); mbar_expect_if(lane, sb + B_SX, r == 0 ? 3072 : 5120); }
                sts32_if(lane, sb + O_MISC, __float_as_uint(1.0f));
            }
#pragma unroll
            for (int i = 0; i < 4; i++) g_acc[(blockIdx.x * 64 + i * 16 + (t2 >> 3)) * 16 + (t2 & 7)] = make_uint4(0, 0, 0, 0);
#pragma unroll
            for (int tau = 0; tau < 3; tau++) {
                uint32_t v[6];
#pragma unroll
                for (int i = 0; i < 3; i++) {
                    const uint32_t* p = reinterpret_cast<const uint32_t*>(mem0 + g * DM + 16 * (12 * tau + 4 * i + c) + 2 * t);
                    v[2 * i] = __ldg(p); v[2 * i + 1] = __ldg(p + 4);
                    mmax = __vmaxu2(mmax, __vmaxu2(v[2 * i] & 0x7fff7fffu, v[2 * i + 1] & 0x7fff7fffu));
                }
                sts128(sb + O_MF + tau * 3072 + (c >> 1) * 1536 + (c & 1) * 512 + lane * 16, v[0], v[1], v[2], v[3]);
                sts64(sb + O_MF + tau * 3072 + (c >> 1) * 1536 + 1024 + lane * 16 + (c & 1) * 8, v[4], v[5]);
            }
            mmax = max(mmax << 16, mmax & 0xffff0000u);
            bar_arrive(2, 384);
            bar_arrive(12 + (c >> 1), 192); bar_arrive(14 + (c >> 1), 192);
            uint32_t xm = 0;
            const uint4* xp = reinterpret_cast<const uint4*>(x) + blockIdx.x * 1536 + t2;
#pragma unroll
            for (int i = 0; i < 12; i++) {
                uint4 v = __ldg(xp + i * 128);
                xm = __vmaxu2(xm, __vmaxu2(__vmaxu2(v.x & 0x7fff7fffu, v.y & 0x7fff7fffu), __vmaxu2(v.z & 0x7fff7fffu, v.w & 0x7fff7fffu)));
            }
            xm = __reduce_max_sync(~0u, max(xm << 16, xm & 0xffff0000u));

            const __nv_bfloat16* p = Wo + (size_t)(h * 128 + 4 * t) * DM + 192 * r + 16 * c + 2 * g;
#pragma unroll
            for (int i = 0; i < 3; i++)
#pragma unroll
                for (int eb = 0; eb < 8; eb++)
#pragma unroll
                    for (int j = 0; j < 4; j++) a[(i * 8 + eb) * 4 + j] = ldg_nc32(p + (16 * eb + ((j & 1) * 2 + (j >> 1))) * DM + 64 * i);
#pragma unroll
            for (int kk = 0; kk < 48; kk++) {
                uint32_t w0 = a[2 * kk], w1 = a[2 * kk + 1];
                a[2 * kk] = __byte_perm(w0, w1, 0x5410);
                a[2 * kk + 1] = __byte_perm(w0, w1, 0x7632);
            }
            float wmax = 0.f;
#pragma unroll
            for (int i = 0; i < 3; i++) {
                float s0 = 0.f, s1 = 0.f;
#pragma unroll
                for (int kk = 16 * i; kk < 16 * i + 16; kk++) {
                    s0 += fabsf(__uint_as_float(a[2 * kk] << 16)) + fabsf(__uint_as_float(a[2 * kk] & 0xffff0000u));
                    s1 += fabsf(__uint_as_float(a[2 * kk + 1] << 16)) + fabsf(__uint_as_float(a[2 * kk + 1] & 0xffff0000u));
                }
                s0 += __shfl_xor_sync(~0u, s0, 1); s0 += __shfl_xor_sync(~0u, s0, 2);
                s1 += __shfl_xor_sync(~0u, s1, 1); s1 += __shfl_xor_sync(~0u, s1, 2);
                wmax = fmaxf(wmax, fmaxf(s0, s1));
            }
            uint32_t wm = __reduce_max_sync(~0u, __float_as_uint(wmax));
            sts32_if(lane, sb + O_OF + 4 * c, wm); sts32_if(lane, sb + O_OF + 16 + 4 * c, xm);
            __threadfence();
            bar_sync(7, 384);
            if (c == 0) {
                const uint4 wq = lds128(sb + O_OF), xq = lds128(sb + O_OF + 16), v0 = lds128(sb + O_MISC + 32), v1 = lds128(sb + O_MISC + 48);
                const uint32_t w1 = max(max(wq.x, wq.y), max(wq.z, wq.w)), x1 = max(max(xq.x, xq.y), max(xq.z, xq.w));
                const uint32_t vv = (r < 2) ? 0u : max(max(max(v0.x, v0.y), max(v0.z, v0.w)), max(max(v1.x, v1.y), max(v1.z, v1.w)));
                unsigned old = 0;
                asm volatile("{\n.reg .pred p;\nsetp.eq.u32 p, %6, 0;\n@p st.global.v4.u32 [%1], {%2,%3,%4,%4};\nfence.acq_rel.gpu;\n@p atom.relaxed.gpu.global.add.u32 %0, [%5], 1;\n}"
                             : "+r"(old) : "l"(&g_norm[blockIdx.x * 4]), "r"(w1), "r"(vv), "r"(x1), "l"(&g_gridbar), "r"(lane) : "memory");
                old = __shfl_sync(~0u, old, 0);
                const unsigned target = (old / 96u + 1u) * 96u;
                asm volatile("{\n.reg .pred p;\n.reg .u32 n, v;\nmov.u32 n, 0;\n"
                             "G_%=: ld.acquire.gpu.global.u32 v, [%0];\nsub.u32 v, v, %1;\nsetp.ge.s32 p, v, 0;\n@p bra.uni E_%=;\n"
                             "add.u32 n, n, 1;\nsetp.lt.u32 p, n, 4000000;\n@p bra.uni G_%=;\ntrap;\nE_%=:\n}" :: "l"(&g_gridbar), "r"(target) : "memory");
                uint4 n0 = ldg_relaxed128(&g_norm[lane * 4]), n1 = ldg_relaxed128(&g_norm[(lane + 32) * 4]), n2 = ldg_relaxed128(&g_norm[(lane + 64) * 4]);
                const float fw = __uint_as_float(__reduce_max_sync(~0u, max(n0.x, max(n1.x, n2.x))));
                const float fv = __uint_as_float(__reduce_max_sync(~0u, max(n0.y, max(n1.y, n2.y))));
                const float xmax = __uint_as_float(__reduce_max_sync(~0u, max(n0.z, max(n1.z, n2.z))));
                const float G = 36.f * fw * fv;
                sts32_if(lane, sb + O_MISC + 4, __float_as_uint(G)); sts32_if(lane, sb + O_MISC + 8, __float_as_uint(G * xmax));
            }
        }
        bar_sync(6, 128);
        int s3p = 2;
        uint32_t PX[5] = {0u, 0u, 0u, 0u, 0u};
        char* rptr; int pdelta; char* optr;
        {
            const uint32_t roff = (r * 4 + c) * 2048 + (lane >> 4) * 512 + (lane & 2) * 128 + (lane & 1) * 64 + (lane & 12) * 4;
            const uint32_t poff = c * 2048 + (lane & 4) * 256 + (lane >> 4) * 256 + (lane & 8) * 8 + (lane & 3) * 16;
            rptr = reinterpret_cast<char*>(g_acc) + roff;
            pdelta = __shfl_sync(~0u, (int)poff - (int)roff, lane);
            optr = reinterpret_cast<char*>(g_ox) + ((size_t)(h * 2 + (c >> 1)) * SEQ + 16 * r + 8 * (c & 1)) * 128 + lane * 16 - 4096;
        }
#pragma unroll 1
        for (int s = 0; s <= NSEG; s++) {
            const uint32_t l16 = opaque(l16c);
            const int s3 = (s3p == 2) ? 0 : s3p + 1;
            unsigned t_red = 0;
            if (s < NSEG - 1) {
                sts32_if(l16, sb + O_MISC + 16 + 4 * c, __reduce_max_sync(~0u, mmax));
                mbar_arrive_if(l16, sb + B_MX);
            }
            if (c == 0) STAMP(s < NSEG ? s : -1, 5);
            if (r < 2 && s >= 1) {
                const uint32_t vmb = sb + O_VM + ((s - 1) & 1) * 2048 + (c >> 1) * 1024 + (l16 >> 1);
                const uint32_t vb = sb + O_VX + s3p * 8192 + (c >> 1) * 4096 + l16;
                const uint4 vm0 = lds64x2(vmb), vm1 = lds64x2(vmb + 512);
                float sm[4], o[4][4];
                uint4 v[4];
#pragma unroll
                for (int q = 0; q < 4; q++) v[q] = lds128(vb + q * 1024);
                mma1688_z(sm, ONES, ONES, PX[0]);
                mma1688_z(o[0], vm0.x, vm0.y, PX[0]); mma1688_z(o[1], vm0.z, vm0.w, PX[0]);
                mma1688_z(o[2], vm1.x, vm1.y, PX[0]); mma1688_z(o[3], vm1.z, vm1.w, PX[0]);
                mma16816(sm, ONES, ONES, ONES, ONES, PX[1], PX[2]);
#pragma unroll
                for (int q = 0; q < 4; q++) {
                    mma16816(o[q], v[q].x, v[q].y, v[q].z, v[q].w, PX[1], PX[2]);
                    v[q] = lds128(vb + q * 1024 + 512);
                }
                mma16816(sm, ONES, ONES, ONES, ONES, PX[3], PX[4]);
#pragma unroll
                for (int q = 0; q < 4; q++) mma16816(o[q], v[q].x, v[q].y, v[q].z, v[q].w, PX[3], PX[4]);
                const uint32_t row = (l16 >> 4) & 7;
                const uint32_t stg = sb + O_OXS + c * 1024 + row * 128 + (((l16 >> 7) ^ row) << 4);
                const float r0 = rcp_fast(sm[0]), r1 = rcp_fast(sm[1]);
#pragma unroll
                for (int e2 = 0; e2 < 2; e2++)
                    stsm4t(stg ^ (e2 * 64), pack_bf16(o[2 * e2][0] * r0, o[2 * e2][1] * r1), pack_bf16(o[2 * e2][2] * r0, o[2 * e2][3] * r1),
                           pack_bf16(o[2 * e2 + 1][0] * r0, o[2 * e2 + 1][1] * r1), pack_bf16(o[2 * e2 + 1][2] * r0, o[2 * e2 + 1][3] * r1));
                __syncwarp();
            }
            if (s < NSEG - 1) {
                bar_arrive(3, 384);
                mbar_wait(sb + B_MX, s & 1);
                const uint4 mm = lds128(sb + O_MISC + 16), cf = lds128(sb + O_MISC);
                const float bound = fmaxf(__uint_as_float(cf.z), __uint_as_float(cf.y) * (__uint_as_float(max(max(mm.x, mm.y), max(mm.z, mm.w))) * __uint_as_float(cf.x)));
                const uint32_t eb = min(max(__float_as_uint(bound) & 0x7f800000u, 21u << 23), 254u << 23);
                const float sig = __uint_as_float((268u << 23) - eb);
                const uint32_t inv_new = eb - (14u << 23);
                if (r < 2) mbar_wait(sb + B_VX + 8 * (s & 1), (s >> 1) & 1);
                mbar_wait(sb + B_VM, s & 1);
                uint4 vx[4];
#pragma unroll
                for (int q = 0; q < 4; q++) vx[q] = lds128(sb + O_VX + s3 * 8192 + c * 2048 + q * 512 + l16);
                const uint4 vm = lds64x2(sb + O_VM + (s & 1) * 2048 + c * 512 + (l16 >> 1));
                if (c == 0) STAMP(s, 13);
                mbar_wait(sb + B_SC, s & 1);
                if (c == 0) STAMP(s, 6);
                float p[10];
                load_scores(p, sb + O_SC, 1280, l16);
                float mx = fmaxf(fmaxf(fmaxf(p[0], p[1]), fmaxf(p[2], p[3])), fmaxf(fmaxf(p[4], p[5]), fmaxf(p[6], p[7])));
                mx = quad_max(fmaxf(mx, fmaxf(p[8], p[9])));
                const float mo = mx * SM_SCALE;
                uint32_t P[5];
#pragma unroll
                for (int n = 0; n < 5; n++) P[n] = pack_bf16(ex2(fmaf(p[2 * n], SM_SCALE, -mo)), ex2(fmaf(p[2 * n + 1], SM_SCALE, -mo)));
                if (c == 0) STAMP(s, 7);
                float o0[4], o1[4], sm[4];
                mma1688_z(sm, ONES, ONES, P[0]);
                mma1688_z(o0, vm.x, vm.y, P[0]);
                mma1688_z(o1, vm.z, vm.w, P[0]);
                mma16816(sm, ONES, ONES, ONES, ONES, P[1], P[2]);
                mma16816(o0, vx[0].x, vx[0].y, vx[0].z, vx[0].w, P[1], P[2]);
                mma16816(o1, vx[2].x, vx[2].y, vx[2].z, vx[2].w, P[1], P[2]);
                mma16816(sm, ONES, ONES, ONES, ONES, P[3], P[4]);
                mma16816(o0, vx[1].x, vx[1].y, vx[1].z, vx[1].w, P[3], P[4]);
                mma16816(o1, vx[3].x, vx[3].y, vx[3].z, vx[3].w, P[3], P[4]);
                const float r0 = rcp_fast(sm[0]) * sig, r1 = rcp_fast(sm[1]) * sig;
                stsm4t(sb + O_OF + c * 512 + l16, pack_bf16(o0[0] * r0, o0[1] * r1), pack_bf16(o0[2] * r0, o0[3] * r1),
                       pack_bf16(o1[0] * r0, o1[1] * r1), pack_bf16(o1[2] * r0, o1[3] * r1));
                bar_sync(6, 128);
                uint4 ob[4];
#pragma unroll
                for (int q = 0; q < 4; q++) ob[q] = ldsm4(sb + O_OF + q * 512 + l16);
                float m0[3][4], m1[3][4];
#pragma unroll
                for (int q = 0; q < 4; q++) {
#pragma unroll
                    for (int i = 0; i < 3; i++) {
                        const int k0 = (i * 8 + 2 * q) * 4;
                        if (q == 0) mma16816_z(m0[i], a[k0], a[k0 + 1], a[k0 + 2], a[k0 + 3], ob[q].x, ob[q].y);
                        else mma16816(m0[i], a[k0], a[k0 + 1], a[k0 + 2], a[k0 + 3], ob[q].x, ob[q].y);
                    }
#pragma unroll
                    for (int i = 0; i < 3; i++) {
                        const int k1 = (i * 8 + 2 * q + 1) * 4;
                        if (q == 0) mma16816_z(m1[i], a[k1], a[k1 + 1], a[k1 + 2], a[k1 + 3], ob[q].z, ob[q].w);
                        else mma16816(m1[i], a[k1], a[k1 + 1], a[k1 + 2], a[k1 + 3], ob[q].z, ob[q].w);
                    }
                }
                asm volatile("red.relaxed.gpu.global.add.noftz.v4.f16x2 [%0], {%1,%2,%3,%4};" :: "l"(rptr),
                    "r"(pack_f16(m0[0][0] + m1[0][0], m0[0][2] + m1[0][2])), "r"(pack_f16(m0[1][0] + m1[1][0], m0[1][2] + m1[1][2])),
                    "r"(pack_f16(m0[2][0] + m1[2][0], m0[2][2] + m1[2][2])), "r"(0x3c00u) : "memory");
                asm volatile("red.relaxed.gpu.global.add.noftz.v4.f16x2 [%0], {%1,%2,%3,%4};" :: "l"(rptr + 1024),
                    "r"(pack_f16(m0[0][1] + m1[0][1], m0[0][3] + m1[0][3])), "r"(pack_f16(m0[1][1] + m1[1][1], m0[1][3] + m1[1][3])),
                    "r"(pack_f16(m0[2][1] + m1[2][1], m0[2][3] + m1[2][3])), "r"(0x3c00u) : "memory");
                t_red = clk();
                bar_arrive(5, 384);
                {
                    const uint32_t nb = 8 * ((s + 1) & 1);
                    const uint32_t bar = sb + (c == 0 ? B_SC : c == 1 ? B_VM : c == 2 ? B_VX + nb : B_SX + nb);
                    const uint32_t bytes = c == 0 ? 2560 : c == 1 ? 2048 : c == 2 ? VXBYTES : (r == 0 ? 3072 : 5120);
                    mbar_expect_if(l16 | (uint32_t)(r == 2 && c >= 2), bar, bytes);
                    sts32_if(l16 | c, sb + O_MISC, inv_new);
                }
                if (c == 0) STAMPV(s, 8, t_red);
            } else if (r < 2 && s == NSEG - 1) {
                mbar_wait(sb + B_VM, s & 1);
                mbar_wait(sb + B_VX + 8 * (s & 1), (s >> 1) & 1);
            }

            float px[10];
#pragma unroll
            for (int i = 0; i < 10; i++) px[i] = 0.f;
            if (r < 2 && s < NSEG) {
                mbar_wait(sb + B_SX + 8 * (s & 1), (s >> 1) & 1);
                const int q0 = 16 * r + 8 * (c & 1) + 8 + (int)(l16 >> 6) - (int)((l16 >> 3) & 6);
                load_scores(px, sb + O_SX + (s & 1) * 5120 + (c & 1) * 1280, 2560, l16);
#pragma unroll
                for (int n = 1; n < 5; n++) {
                    if (8 * n > q0) px[2 * n] = -INFINITY;
                    if (8 * n + 1 > q0) px[2 * n + 1] = -INFINITY;
                }
                float mx = fmaxf(fmaxf(fmaxf(px[0], px[1]), fmaxf(px[2], px[3])), fmaxf(fmaxf(px[4], px[5]), fmaxf(px[6], px[7])));
                mx = quad_max(fmaxf(mx, fmaxf(px[8], px[9])));
                const float mo = mx * SM_SCALE;
#pragma unroll
                for (int i = 0; i < 10; i++) px[i] = fmaf(px[i], SM_SCALE, -mo);
            }
            auto finish_x = [&]() {
                const uint4 u0 = lds128(sb + O_OXS + c * 1024 + l16), u1 = lds128(sb + O_OXS + c * 1024 + 512 + l16);
                asm volatile("{\n.reg .pred p;\nsetp.ne.u32 p, %9, 0;\n@p st.global.v4.u32 [%0], {%1,%2,%3,%4};\n@p st.global.v4.u32 [%0+512], {%5,%6,%7,%8};\n}"
                    :: "l"(optr), "r"(u0.x), "r"(u0.y), "r"(u0.z), "r"(u0.w), "r"(u1.x), "r"(u1.y), "r"(u1.z), "r"(u1.w), "r"((uint32_t)(r < 2 && s >= 1)) : "memory");
#pragma unroll
                for (int n = 0; n < 5; n++) PX[n] = pack_bf16(ex2v(px[2 * n]), ex2v(px[2 * n + 1]));
            };
            if (s >= NSEG - 1) {
                finish_x();
            } else {
                if (c == 0) STAMP(s, 9);
                const char* pbase = rptr + pdelta;
                spin_until(t_red, D_WAIT);
                uint4 v[6];
#pragma unroll
                for (int i = 0; i < 6; i++) v[i] = ldg_relaxed128(pbase + (i >> 1) * 8192 + (i & 1) * 512);
                finish_x();
                int nretry = 0;
#pragma unroll
                for (int tau = 0; tau < 3; tau++) {
                    asm volatile("{\n.reg .pred p, q;\n.reg .u32 n;\nmov.u32 n, 0;\n"
                                 "R_%=: setp.eq.u32 p, %3, 0x5000;\nsetp.eq.and.u32 p, %7, 0x5000, p;\nvote.sync.all.pred q, p, 0xffffffff;\n@q bra.uni K_%=;\n"
                                 "ld.relaxed.gpu.global.v4.u32 {%0,%1,%2,%3}, [%9];\nld.relaxed.gpu.global.v4.u32 {%4,%5,%6,%7}, [%9+512];\n"
                                 "add.u32 %8, %8, 1;\nadd.u32 n, n, 1;\nsetp.lt.u32 q, n, 2000000;\n@q bra.uni R_%=;\ntrap;\nK_%=:\n}"
                                 : "+r"(v[2 * tau].x), "+r"(v[2 * tau].y), "+r"(v[2 * tau].z), "+r"(v[2 * tau].w),
                                   "+r"(v[2 * tau + 1].x), "+r"(v[2 * tau + 1].y), "+r"(v[2 * tau + 1].z), "+r"(v[2 * tau + 1].w), "+r"(nretry)
                                 : "l"(pbase + tau * 8192) : "memory");
                    v[2 * tau].x = f16x2_to_bf16x2(v[2 * tau].x); v[2 * tau + 1].x = f16x2_to_bf16x2(v[2 * tau + 1].x);
                    v[2 * tau].y = f16x2_to_bf16x2(v[2 * tau].y); v[2 * tau + 1].y = f16x2_to_bf16x2(v[2 * tau + 1].y);
                    v[2 * tau].z = f16x2_to_bf16x2(v[2 * tau].z); v[2 * tau + 1].z = f16x2_to_bf16x2(v[2 * tau + 1].z);
                    sts128(sb + O_MF + tau * 3072 + (c >> 1) * 1536 + (c & 1) * 512 + l16, v[2 * tau].x, v[2 * tau + 1].x, v[2 * tau].y, v[2 * tau + 1].y);
                    sts64(sb + O_MF + tau * 3072 + (c >> 1) * 1536 + 1024 + (c & 1) * 8 + l16, v[2 * tau].z, v[2 * tau + 1].z);
                    if (tau == 0) bar_arrive(2, 384);
                    else if (c < 2) bar_arrive(10 + 2 * tau, 192);
                    else bar_arrive(11 + 2 * tau, 192);
                    if (c == 0) STAMP(s, 10 + tau);
                }
                if (c == 0) STAMPV(s, 14, nretry);
                asm volatile("" ::: "memory");
                uint32_t mx0 = 0, mx1 = 0;
#pragma unroll
                for (int i = 0; i < 6; i++) {
                    mx0 = max3u(mx0, shl_v(v[i].x, 17), shl_v(v[i].y, 17)); mx1 = max3u(mx1, shl_v(v[i].x, 1), shl_v(v[i].y, 1));
                    mx0 = max(mx0, shl_v(v[i].z, 17)); mx1 = max(mx1, shl_v(v[i].z, 1));
                }
                mmax = max(mx0, mx1) >> 1;
            }
            s3p = s3;
            rptr += 24576;
            optr += 4096;
        }
        if (r < 2) {
            bar_sync(6, 128);
            if (c == 0)
                asm volatile("{\n.reg .pred p;\nsetp.eq.u32 p, %1, 0;\nfence.acq_rel.gpu;\n@p red.relaxed.gpu.global.add.u32 [%0], 1;\n"
                             "@p red.relaxed.gpu.global.add.u32 [%0+128], 1;\n@p red.relaxed.gpu.global.add.u32 [%0+256], 1;\n}"
                             :: "l"(&g_flag[(61 * 4 + (h >> 3)) * 8]), "r"(l16c) : "memory");
        }
    }
    cluster_sync();
}

__device__ float g_u[SEQ * 2 * DM];
__global__ void naive_gemm1(const __nv_bfloat16* x, const __nv_bfloat16* Bre, const __nv_bfloat16* Bim) {
    int p = blockIdx.x * 64 + threadIdx.x % 64, tk = blockIdx.y * 4 + threadIdx.x / 64;
    float sr = 0, si = 0;
    for (int d = 0; d < DM; d++) { float xv = __bfloat162float(x[tk * DM + d]); sr += xv * __bfloat162float(Bre[p * DM + d]); si += xv * __bfloat162float(Bim[p * DM + d]); }
    g_u[tk * 2 * DM + 2 * p] = sr; g_u[tk * 2 * DM + 2 * p + 1] = si;
}
__global__ void naive_scan(const __nv_bfloat16* Lre, const __nv_bfloat16* Lim, const __nv_bfloat16* logdt) {
    int p = blockIdx.x * 64 + threadIdx.x;
    float dt = __bfloat162float(__float2bfloat16(expf(__bfloat162float(logdt[p]))));
    float lr = __bfloat162float(Lre[p]), li = __bfloat162float(Lim[p]);
    float e = expf(dt * lr), br = e * cosf(dt * li), bi = e * sinf(dt * li);
    float den = lr * lr + li * li;
    float cr = ((br - 1.f) * lr + bi * li) / den, ci = (bi * lr - (br - 1.f) * li) / den;
    float hr = 0, hi = 0;
    for (int tk = 0; tk < SEQ; tk++) {
        float ur = g_u[tk * 2 * DM + 2 * p], ui = g_u[tk * 2 * DM + 2 * p + 1];
        float nr = br * hr - bi * hi + cr * ur - ci * ui, ni = br * hi + bi * hr + cr * ui + ci * ur;
        hr = nr; hi = ni;
        g_u[tk * 2 * DM + 2 * p] = hr; g_u[tk * 2 * DM + 2 * p + 1] = hi;
    }
}
__global__ void naive_gemm2(const __nv_bfloat16* x, const __nv_bfloat16* Cre, const __nv_bfloat16* Cim, const __nv_bfloat16* Dk, float* out) {
    int d = blockIdx.x * 64 + threadIdx.x % 64, tk = blockIdx.y * 4 + threadIdx.x / 64;
    float s = 0;
    for (int p = 0; p < DM; p++) s += g_u[tk * 2 * DM + 2 * p] * __bfloat162float(Cre[d * DM + p]) - g_u[tk * 2 * DM + 2 * p + 1] * __bfloat162float(Cim[d * DM + p]);
    out[tk * 1152 + d] = 2.f * s + __bfloat162float(__float2bfloat16(__bfloat162float(x[tk * DM + d]) * __bfloat162float(Dk[d])));
}
__global__ void naive_wo(const __nv_bfloat16* Wo, float* out) {
    int d = blockIdx.x * 64 + threadIdx.x % 64, tk = blockIdx.y * 4 + threadIdx.x / 64;
    const __nv_bfloat16* ox = reinterpret_cast<const __nv_bfloat16*>(g_ox);
    float s = 0;
    for (int k = 0; k < HD; k++) {
        int hh = k >> 6, e0 = k & 63, e = (e0 & 48) + (e0 & 1) * 8 + ((e0 & 15) >> 1);
        s += __bfloat162float(ox[((size_t)hh * SEQ + tk) * 64 + (((e >> 3) ^ (tk & 7)) << 3) + (e & 7)]) * __bfloat162float(Wo[k * DM + d]);
    }
    out[tk * 1152 + DM + d] = s;
}

typedef CUresult (*EncodeFn)(CUtensorMap*, CUtensorMapDataType, cuuint32_t, void*, const cuuint64_t*, const cuuint64_t*, const cuuint32_t*, const cuuint32_t*,
                             CUtensorMapInterleave, CUtensorMapSwizzle, CUtensorMapL2promotion, CUtensorMapFloatOOBfill);
}

extern "C" void kernel_launch(void* const* d_in, const int* in_sizes, int n_in, void* d_out, int out_size) {
    typedef const __nv_bfloat16* bp;
    bp Ax = (bp)d_in[0], Lre = (bp)d_in[1], Lim = (bp)d_in[2], Bre = (bp)d_in[3], Bim = (bp)d_in[4], Cre = (bp)d_in[5], Cim = (bp)d_in[6],
       logdt = (bp)d_in[7], Dk = (bp)d_in[8], Bx = (bp)d_in[9], mem0 = (bp)d_in[10], Wq = (bp)d_in[11], Wk = (bp)d_in[12], Wv = (bp)d_in[13], Wo = (bp)d_in[14];
    float* out = (float*)d_out;
    static EncodeFn enc = nullptr;
    if (!enc) {
        void* fn = nullptr; cudaDriverEntryPointQueryResult qr;
        cudaGetDriverEntryPoint("cuTensorMapEncodeTiled", &fn, cudaEnableDefault, &qr);
        enc = (EncodeFn)fn;
        cudaFuncSetAttribute(chain_kernel, cudaFuncAttributeMaxDynamicSharedMemorySize, CHAIN_SMEM);
    }
    CUtensorMap tm_x;
    {
        cuuint64_t gd[2] = {DM, SEQ}; cuuint64_t gs[1] = {DM * 2}; cuuint32_t bd[2] = {64, 32}; cuuint32_t es[2] = {1, 1};
        enc(&tm_x, CU_TENSOR_MAP_DATA_TYPE_BFLOAT16, 2, (void*)Bx, gd, gs, bd, es, CU_TENSOR_MAP_INTERLEAVE_NONE, CU_TENSOR_MAP_SWIZZLE_128B,
            CU_TENSOR_MAP_L2_PROMOTION_L2_128B, CU_TENSOR_MAP_FLOAT_OOB_FILL_NONE);
    }
    cudaStream_t st = cudaStreamPerThread;
    chain_kernel<<<96, 384, CHAIN_SMEM, st>>>(tm_x, Bx, mem0, Wq, Wk, Wv, Wo);
    naive_gemm1<<<dim3(9, 512), 256, 0, st>>>(Ax, Bre, Bim);
    naive_scan<<<9, 64, 0, st>>>(Lre, Lim, logdt);
    naive_gemm2<<<dim3(9, 512), 256, 0, st>>>(Ax, Cre, Cim, Dk, out);
    naive_wo<<<dim3(9, 512), 256, 0, st>>>(Wo, out);
}
```

```cpp
#include <cuda_runtime.h>
#include <cuda.h>
#include <cuda_bf16.h>
#include <cuda_fp16.h>
#include <stdint.h>

#define D_WAIT 700
#define VXMODE 1
#define VXBYTES (VXMODE == 2 ? 0 : 8192)
#define XCHUNK1 10

namespace {

constexpr int DM = 576, NH = 32, SEQ = 2048, NSEG = 64, HD = 4096;

__device__ uint4 g_acc[64 * 96 * 16];
__device__ uint4 g_ox[NH * 2 * SEQ * 8];
__device__ unsigned g_flag[NSEG * 4 * 8];
__device__ unsigned g_gridbar;
__device__ float g_norm[96 * 4];

__device__ __forceinline__ uint32_t smem_u32(const void* p) { return (uint32_t)__cvta_generic_to_shared(p); }
__device__ __forceinline__ uint32_t mapa(uint32_t a, uint32_t r) { uint32_t o; asm("mapa.shared::cluster.u32 %0, %1, %2;" : "=r"(o) : "r"(a), "r"(r)); return o; }
__device__ __forceinline__ uint32_t mapa_v(uint32_t a, uint32_t r) { uint32_t o; asm volatile("mapa.shared::cluster.u32 %0, %1, %2;" : "=r"(o) : "r"(a), "r"(r)); return o; }
__device__ __forceinline__ unsigned clk() { unsigned long long c; asm volatile("mov.u64 %0, %%clock64;" : "=l"(c) :: "memory"); return (unsigned)c; }
__device__ __forceinline__ void mbar_init(uint32_t bar, uint32_t cnt) { asm volatile("mbarrier.init.shared::cta.b64 [%0], %1;" :: "r"(bar), "r"(cnt) : "memory"); }
__device__ __forceinline__ void mbar_expect(uint32_t bar, uint32_t bytes) { asm volatile("mbarrier.arrive.expect_tx.shared::cta.b64 _, [%0], %1;" :: "r"(bar), "r"(bytes) : "memory"); }
__device__ __forceinline__ void mbar_wait(uint32_t bar, uint32_t parity) {
    asm volatile("{\n.reg .pred p;\n.reg .u32 n;\nmov.u32 n, 0;\n"
                 "W_%=: mbarrier.try_wait.parity.shared::cta.b64 p, [%0], %1;\n@p bra.uni D_%=;\n"
                 "add.u32 n, n, 1;\nsetp.lt.u32 p, n, 4000000;\n@p bra.uni W_%=;\ntrap;\nD_%=:\n}" :: "r"(bar), "r"(parity) : "memory");
}
__device__ __forceinline__ void mbar_expect_if(uint32_t z, uint32_t bar, uint32_t bytes) {
    asm volatile("{\n.reg .pred p;\nsetp.eq.u32 p, %2, 0;\n@p mbarrier.arrive.expect_tx.shared::cta.b64 _, [%0], %1;\n}" :: "r"(bar), "r"(bytes), "r"(z) : "memory");
}
__device__ __forceinline__ void mbar_arrive_if(uint32_t z, uint32_t bar) {
    asm volatile("{\n.reg .pred p;\nsetp.eq.u32 p, %1, 0;\n@p mbarrier.arrive.shared::cta.b64 _, [%0];\n}" :: "r"(bar), "r"(z) : "memory");
}
__device__ __forceinline__ void sts32_if(uint32_t z, uint32_t a, uint32_t x) {
    asm volatile("{\n.reg .pred p;\nsetp.eq.u32 p, %2, 0;\n@p st.shared.u32 [%0], %1;\n}" :: "r"(a), "r"(x), "r"(z) : "memory");
}
__device__ __forceinline__ void spin_until(unsigned t0, unsigned d) {
    asm volatile("{\n.reg .pred p;\n.reg .u64 c;\n.reg .u32 lo;\n"
                 "S_%=: mov.u64 c, %%clock64;\ncvt.u32.u64 lo, c;\nsub.u32 lo, lo, %0;\nsetp.lt.u32 p, lo, %1;\n@p bra.uni S_%=;\n}" :: "r"(t0), "r"(d) : "memory");
}
__device__ __forceinline__ void bar_sync(int id, int n) { asm volatile("bar.sync %0, %1;" :: "r"(id), "r"(n) : "memory"); }
__device__ __forceinline__ void bar_sync_sel(int sel, int id) {
    asm volatile("{\n.reg .pred p;\nsetp.eq.u32 p, %0, 0;\n@p bar.sync %1, %3;\n@!p bar.sync %2, %3;\n}" :: "r"(sel), "r"(id), "r"(id + 1), "n"(192) : "memory");
}
__device__ __forceinline__ void bar_arrive(int id, int n) { asm volatile("bar.arrive %0, %1;" :: "r"(id), "r"(n) : "memory"); }
__device__ __forceinline__ void fence_async_smem() { asm volatile("fence.proxy.async.shared::cta;" ::: "memory"); }
__device__ __forceinline__ uint32_t pack_bf16(float lo, float hi) { uint32_t r; asm("cvt.rn.bf16x2.f32 %0, %1, %2;" : "=r"(r) : "f"(hi), "f"(lo)); return r; }
__device__ __forceinline__ uint32_t pack_f16(float lo, float hi) { uint32_t r; asm("cvt.rn.f16x2.f32 %0, %1, %2;" : "=r"(r) : "f"(hi), "f"(lo)); return r; }
__device__ __forceinline__ uint32_t f16x2_to_bf16x2(uint32_t v) { float2 f = __half22float2(*reinterpret_cast<__half2*>(&v)); return pack_bf16(f.x, f.y); }
__device__ __forceinline__ float ex2(float x) { float y; asm("ex2.approx.ftz.f32 %0, %1;" : "=f"(y) : "f"(x)); return y; }
__device__ __forceinline__ float ex2v(float x) { float y; asm volatile("ex2.approx.ftz.f32 %0, %1;" : "=f"(y) : "f"(x)); return y; }
__device__ __forceinline__ uint32_t shl_v(uint32_t a, int n) { return a << n; }
__device__ __forceinline__ uint32_t max3u(uint32_t a, uint32_t b, uint32_t c) { return max(max(a, b), c); }
__device__ __forceinline__ uint4 lds128(uint32_t a) { uint4 v; asm volatile("ld.shared.v4.u32 {%0,%1,%2,%3}, [%4];" : "=r"(v.x), "=r"(v.y), "=r"(v.z), "=r"(v.w) : "r"(a) : "memory"); return v; }
__device__ __forceinline__ float4 lds128f(uint32_t a) { float4 v; asm volatile("ld.shared.v4.f32 {%0,%1,%2,%3}, [%4];" : "=f"(v.x), "=f"(v.y), "=f"(v.z), "=f"(v.w) : "r"(a) : "memory"); return v; }
__device__ __forceinline__ float2 lds64f(uint32_t a) { float2 v; asm volatile("ld.shared.v2.f32 {%0,%1}, [%2];" : "=f"(v.x), "=f"(v.y) : "r"(a) : "memory"); return v; }
__device__ __forceinline__ uint4 lds64x2(uint32_t a) { uint4 v; asm volatile("ld.shared.v2.u32 {%0,%1}, [%4];\nld.shared.v2.u32 {%2,%3}, [%4+256];" : "=r"(v.x), "=r"(v.y), "=r"(v.z), "=r"(v.w) : "r"(a) : "memory"); return v; }
__device__ __forceinline__ uint32_t lds32(uint32_t a) { uint32_t v; asm volatile("ld.shared.u32 %0, [%1];" : "=r"(v) : "r"(a) : "memory"); return v; }
__device__ __forceinline__ void sts128(uint32_t a, uint32_t x, uint32_t y, uint32_t z, uint32_t w) { asm volatile("st.shared.v4.u32 [%0], {%1,%2,%3,%4};" :: "r"(a), "r"(x), "r"(y), "r"(z), "r"(w) : "memory"); }
__device__ __forceinline__ void sts128f(uint32_t a, float x, float y, float z, float w) { asm volatile("st.shared.v4.f32 [%0], {%1,%2,%3,%4};" :: "r"(a), "f"(x), "f"(y), "f"(z), "f"(w) : "memory"); }
__device__ __forceinline__ void sts64(uint32_t a, uint32_t x, uint32_t y) { asm volatile("st.shared.v2.u32 [%0], {%1,%2};" :: "r"(a), "r"(x), "r"(y) : "memory"); }
__device__ __forceinline__ void sts32(uint32_t a, uint32_t x) { asm volatile("st.shared.u32 [%0], %1;" :: "r"(a), "r"(x) : "memory"); }
__device__ __forceinline__ uint4 ldsm4(uint32_t a) { uint4 v; asm volatile("ldmatrix.sync.aligned.m8n8.x4.shared.b16 {%0,%1,%2,%3}, [%4];" : "=r"(v.x), "=r"(v.y), "=r"(v.z), "=r"(v.w) : "r"(a) : "memory"); return v; }
__device__ __forceinline__ void stsm2t(uint32_t a, uint32_t x, uint32_t y) { asm volatile("stmatrix.sync.aligned.m8n8.x2.trans.shared.b16 [%0], {%1,%2};" :: "r"(a), "r"(x), "r"(y) : "memory"); }
__device__ __forceinline__ void stsm4t(uint32_t a, uint32_t x, uint32_t y, uint32_t z, uint32_t w) { asm volatile("stmatrix.sync.aligned.m8n8.x4.trans.shared.b16 [%0], {%1,%2,%3,%4};" :: "r"(a), "r"(x), "r"(y), "r"(z), "r"(w) : "memory"); }
__device__ __forceinline__ void st_async64(uint32_t a, uint32_t x, uint32_t y, uint32_t bar) { asm volatile("st.async.shared::cluster.mbarrier::complete_tx::bytes.v2.b32 [%0], {%1,%2}, [%3];" :: "r"(a), "r"(x), "r"(y), "r"(bar) : "memory"); }
__device__ __forceinline__ void bulk_s2c(uint32_t dst, uint32_t src, uint32_t bytes, uint32_t bar) { asm volatile("cp.async.bulk.shared::cluster.shared::cta.mbarrier::complete_tx::bytes [%0], [%1], %2, [%3];" :: "r"(dst), "r"(src), "r"(bytes), "r"(bar) : "memory"); }
__device__ __forceinline__ void bulk_s2g(void* dst, uint32_t src, uint32_t bytes) { asm volatile("cp.async.bulk.global.shared::cta.bulk_group [%0], [%1], %2;" :: "l"(dst), "r"(src), "r"(bytes) : "memory"); }
__device__ __forceinline__ uint32_t ldg_nc32(const void* p) { uint32_t v; asm volatile("ld.global.nc.L2::128B.u32 %0, [%1];" : "=r"(v) : "l"(p)); return v; }
__device__ __forceinline__ uint4 ldg_relaxed128(const void* p) { uint4 v; asm volatile("ld.relaxed.gpu.global.v4.u32 {%0,%1,%2,%3}, [%4];" : "=r"(v.x), "=r"(v.y), "=r"(v.z), "=r"(v.w) : "l"(p) : "memory"); return v; }
__device__ __forceinline__ void mma16816(float (&d)[4], uint32_t a0, uint32_t a1, uint32_t a2, uint32_t a3, uint32_t b0, uint32_t b1) {
    asm volatile("mma.sync.aligned.m16n8k16.row.col.f32.bf16.bf16.f32 {%0,%1,%2,%3}, {%4,%5,%6,%7}, {%8,%9}, {%0,%1,%2,%3};"
        : "+f"(d[0]), "+f"(d[1]), "+f"(d[2]), "+f"(d[3]) : "r"(a0), "r"(a1), "r"(a2), "r"(a3), "r"(b0), "r"(b1));
}
__device__ __forceinline__ void mma16816_z(float (&d)[4], uint32_t a0, uint32_t a1, uint32_t a2, uint32_t a3, uint32_t b0, uint32_t b1) {
    asm volatile("mma.sync.aligned.m16n8k16.row.col.f32.bf16.bf16.f32 {%0,%1,%2,%3}, {%4,%5,%6,%7}, {%8,%9}, {%10,%10,%10,%10};"
        : "=f"(d[0]), "=f"(d[1]), "=f"(d[2]), "=f"(d[3]) : "r"(a0), "r"(a1), "r"(a2), "r"(a3), "r"(b0), "r"(b1), "f"(0.f));
}
__device__ __forceinline__ void mma1688(float (&d)[4], uint32_t a0, uint32_t a1, uint32_t b0) {
    asm volatile("mma.sync.aligned.m16n8k8.row.col.f32.bf16.bf16.f32 {%0,%1,%2,%3}, {%4,%5}, {%6}, {%0,%1,%2,%3};"
        : "+f"(d[0]), "+f"(d[1]), "+f"(d[2]), "+f"(d[3]) : "r"(a0), "r"(a1), "r"(b0));
}
__device__ __forceinline__ void mma1688_z(float (&d)[4], uint32_t a0, uint32_t a1, uint32_t b0) {
    asm volatile("mma.sync.aligned.m16n8k8.row.col.f32.bf16.bf16.f32 {%0,%1,%2,%3}, {%4,%5}, {%6}, {%7,%7,%7,%7};"
        : "=f"(d[0]), "=f"(d[1]), "=f"(d[2]), "=f"(d[3]) : "r"(a0), "r"(a1), "r"(b0), "f"(0.f));
}
template <int ACC>
__device__ __forceinline__ void wgmma_n32_rs(float (&d)[16], uint32_t a0, uint32_t a1, uint32_t a2, uint32_t a3, uint64_t desc) {
    asm volatile("wgmma.mma_async.sync.aligned.m64n32k16.f32.bf16.bf16 {%0,%1,%2,%3,%4,%5,%6,%7,%8,%9,%10,%11,%12,%13,%14,%15}, {%16,%17,%18,%19}, %20, %21, 1, 1, 0;"
        : "+f"(d[0]), "+f"(d[1]), "+f"(d[2]), "+f"(d[3]), "+f"(d[4]), "+f"(d[5]), "+f"(d[6]), "+f"(d[7]),
          "+f"(d[8]), "+f"(d[9]), "+f"(d[10]), "+f"(d[11]), "+f"(d[12]), "+f"(d[13]), "+f"(d[14]), "+f"(d[15])
        : "r"(a0), "r"(a1), "r"(a2), "r"(a3), "l"(desc), "n"(ACC));
}
template <int ACC>
__device__ __forceinline__ void wgmma_n32_ss(float (&d)[16], uint64_t da, uint64_t db) {
    asm volatile("wgmma.mma_async.sync.aligned.m64n32k16.f32.bf16.bf16 {%0,%1,%2,%3,%4,%5,%6,%7,%8,%9,%10,%11,%12,%13,%14,%15}, %16, %17, %18, 1, 1, 0, 0;"
        : "+f"(d[0]), "+f"(d[1]), "+f"(d[2]), "+f"(d[3]), "+f"(d[4]), "+f"(d[5]), "+f"(d[6]), "+f"(d[7]),
          "+f"(d[8]), "+f"(d[9]), "+f"(d[10]), "+f"(d[11]), "+f"(d[12]), "+f"(d[13]), "+f"(d[14]), "+f"(d[15])
        : "l"(da), "l"(db), "n"(ACC));
}
__device__ __forceinline__ void wg_fence() { asm volatile("wgmma.fence.sync.aligned;" ::: "memory"); }
__device__ __forceinline__ void wg_commit() { asm volatile("wgmma.commit_group.sync.aligned;" ::: "memory"); }
__device__ __forceinline__ void wg_wait0() { asm volatile("wgmma.wait_group.sync.aligned 0;" ::: "memory"); }
__device__ __forceinline__ void cluster_sync() { asm volatile("barrier.cluster.arrive.aligned;\nbarrier.cluster.wait.aligned;" ::: "memory"); }

#define STAMP(s, i) do {} while (0)
#define STAMPV(s, i, v) do {} while (0)

constexpr int XT_BYTES = 36864;
constexpr int O_XT = 0;
constexpr int O_AS = 3 * XT_BYTES;
constexpr int O_AF = O_AS + 16384;
constexpr int O_MF = O_AF + 16384;
constexpr int O_QM = O_MF + 9216;
constexpr int O_KM = O_QM + 2048;
constexpr int O_QKX = O_KM + 2048;
constexpr int O_XP = O_QKX + 8192;
constexpr int O_VX = O_XP + 16384;
constexpr int O_VM = O_VX + 24576;
constexpr int O_SC = O_VM + 4096;
constexpr int O_OF = O_SC + 2560;
constexpr int O_SX = O_OF + 2048;
constexpr int O_OXS = O_SX + 10240;
constexpr int O_MISC = O_OXS + 4096;
constexpr int O_BAR = O_MISC + 64;
constexpr int CHAIN_SMEM = O_BAR + 128;
static_assert(CHAIN_SMEM <= 232448, "smem");
constexpr int B_X = O_BAR, B_VX = O_BAR + 24, B_SX = O_BAR + 40, B_SC = O_BAR + 56, B_VM = O_BAR + 64, B_MX = O_BAR + 72;
constexpr float SM_SCALE = 0.08838834764831845f * 1.4426950408889634f;
constexpr uint32_t ONES = 0x3f803f80u;

__device__ __forceinline__ uint32_t opaque(uint32_t v) { uint32_t o; asm volatile("mov.u32 %0, %1;" : "=r"(o) : "r"(v)); return o; }
__device__ __forceinline__ void st_async128(uint32_t a, uint32_t x, uint32_t y, uint32_t z, uint32_t w, uint32_t bar) {
    asm volatile("st.async.shared::cluster.mbarrier::complete_tx::bytes.v4.b32 [%0], {%1,%2,%3,%4}, [%5];" :: "r"(a), "r"(x), "r"(y), "r"(z), "r"(w), "r"(bar) : "memory");
}
__device__ __forceinline__ void tma_x_tile(uint32_t sb, const CUtensorMap* tm, int r, int j, int slot) {
    asm volatile("{\n.reg .pred p;\nelect.sync _|p, 0xffffffff;\n"
        "@p mbarrier.arrive.expect_tx.shared::cta.b64 _, [%2], 36864;\n"
        "@p cp.async.bulk.tensor.2d.shared::cluster.global.mbarrier::complete_tx::bytes.multicast::cluster [%0], [%1, {%3, %4}], [%2], %7;\n"
        "@p cp.async.bulk.tensor.2d.shared::cluster.global.mbarrier::complete_tx::bytes.multicast::cluster [%0+4096], [%1, {%5, %4}], [%2], %7;\n"
        "@p cp.async.bulk.tensor.2d.shared::cluster.global.mbarrier::complete_tx::bytes.multicast::cluster [%0+8192], [%1, {%6, %4}], [%2], %7;\n}"
        :: "r"(sb + O_XT + slot * XT_BYTES + 3 * r * 4096), "l"(tm), "r"(sb + B_X + 8 * slot), "r"(192 * r), "r"(j * 32), "r"(192 * r + 64), "r"(192 * r + 128),
           "h"((unsigned short)7) : "memory");
}
__device__ __forceinline__ float quad_max(float v) {
    const float a = __shfl_xor_sync(~0u, v, 1), b = __shfl_xor_sync(~0u, v, 2), c = __shfl_xor_sync(~0u, v, 3);
    return fmaxf(fmaxf(v, a), fmaxf(b, c));
}
__device__ __forceinline__ void load_scores(float (&p)[10], uint32_t base, uint32_t stride, uint32_t l16) {
    const float4 a0 = lds128f(base + l16), b0 = lds128f(base + stride + l16);
    const float4 a1 = lds128f(base + 512 + l16), b1 = lds128f(base + stride + 512 + l16);
    const float2 a2 = lds64f(base + 1024 + (l16 >> 1)), b2 = lds64f(base + stride + 1024 + (l16 >> 1));
    p[0] = a2.x + b2.x; p[1] = a2.y + b2.y;
    p[2] = a0.x + b0.x; p[3] = a0.y + b0.y; p[4] = a0.z + b0.z; p[5] = a0.w + b0.w;
    p[6] = a1.x + b1.x; p[7] = a1.y + b1.y; p[8] = a1.z + b1.z; p[9] = a1.w + b1.w;
}
__device__ __forceinline__ float rcp_fast(float x) { float y; asm("rcp.approx.ftz.f32 %0, %1;" : "=f"(y) : "f"(x)); return y; }

__global__ void __cluster_dims__(3, 1, 1) __launch_bounds__(384, 1)
chain_kernel(const __grid_constant__ CUtensorMap tm_x,
             const __nv_bfloat16* __restrict__ x, const __nv_bfloat16* __restrict__ mem0,
             const __nv_bfloat16* __restrict__ Wq, const __nv_bfloat16* __restrict__ Wk,
             const __nv_bfloat16* __restrict__ Wv, const __nv_bfloat16* __restrict__ Wo) {
    extern __shared__ __align__(1024) uint8_t smem_raw[];
    const uint32_t sb = smem_u32(smem_raw);
    const int lane = threadIdx.x & 31;
    const int warp = __shfl_sync(~0u, threadIdx.x >> 5, 0);
    const int wg = warp >> 2, w = warp & 3;
    const int h = blockIdx.x / 3, r = blockIdx.x - 3 * h;

    if (threadIdx.x == 0) {
        if (sb & 1023u) __trap();
        for (int i = 0; i < 9; i++) mbar_init(sb + O_BAR + 8 * i, 1);
        mbar_init(sb + B_MX, 4);
        asm volatile("fence.mbarrier_init.release.cluster;" ::: "memory");
    }
    if (blockIdx.x == 0) {
        for (int i = threadIdx.x; i < NSEG * 4 * 8; i += 384) g_flag[i] = 0;
        __threadfence();
    }
    __syncthreads();
    cluster_sync();
    asm volatile("griddepcontrol.launch_dependents;" ::: "memory");
    const uint32_t l16c = __shfl_sync(~0u, lane * 16, lane);

    if (wg < 2) {
#define KB(i) (12 * ((i) / 6) + (((i) % 6) >> 1 == 2 ? 8 + ((i) & 1) : (((i) % 6) >> 1) + 4 * ((i) & 1)))
        asm volatile("setmaxnreg.inc.sync.aligned.u32 176;");
        const int kt = warp < 3 ? warp : (warp < 5 ? warp - 3 : (warp == 5 ? 0 : 2));
        const int mt = (warp == 5 || warp == 7) ? 0 : 1;
        uint32_t a[144];
        uint32_t adr1, adr_pre, adr_post;
        {
            const int g = lane >> 2, t = lane & 3;
#pragma unroll
            for (int tl = 0; tl < 2; tl++) {
                const int tile = tl ? wg : (wg ^ 1);
                const __nv_bfloat16* W = (r < 2) ? (tile == 0 ? Wq : Wk) : Wv;
                const int col = h * 128 + ((r < 2) ? 64 * r : 64 * tile) + 16 * w + 2 * g;
                const __nv_bfloat16* p = W + (size_t)(32 * wg + 2 * t) * HD + col;
#pragma unroll
                for (int i = 0; i < 18; i++) {
                    a[72 * tl + 4 * i + 0] = ldg_nc32(p + (size_t)(16 * KB(i) + 0) * HD);
                    a[72 * tl + 4 * i + 1] = ldg_nc32(p + (size_t)(16 * KB(i) + 1) * HD);
                    a[72 * tl + 4 * i + 2] = ldg_nc32(p + (size_t)(16 * KB(i) + 8) * HD);
                    a[72 * tl + 4 * i + 3] = ldg_nc32(p + (size_t)(16 * KB(i) + 9) * HD);
                }
            }
#pragma unroll
            for (int kk = 0; kk < 72; kk++) {
                uint32_t w0 = a[2 * kk], w1 = a[2 * kk + 1];
                a[2 * kk] = __byte_perm(w0, w1, 0x5410);
                a[2 * kk + 1] = __byte_perm(w0, w1, 0x7632);
            }
            float vmax = 0.f;
#pragma unroll
            for (int tl = 0; tl < 2; tl++) {
                float s0 = 0.f, s1 = 0.f;
#pragma unroll
                for (int kk = 36 * tl; kk < 36 * tl + 36; kk++) {
                    s0 += fabsf(__uint_as_float(a[2 * kk] << 16)) + fabsf(__uint_as_float(a[2 * kk] & 0xffff0000u));
                    s1 += fabsf(__uint_as_float(a[2 * kk + 1] << 16)) + fabsf(__uint_as_float(a[2 * kk + 1] & 0xffff0000u));
                }
                s0 += __shfl_xor_sync(~0u, s0, 1); s0 += __shfl_xor_sync(~0u, s0, 2);
                s1 += __shfl_xor_sync(~0u, s1, 1); s1 += __shfl_xor_sync(~0u, s1, 2);
                vmax = fmaxf(vmax, fmaxf(s0, s1));
            }
            uint32_t mx = __reduce_max_sync(~0u, __float_as_uint(2.f * vmax));
            sts32_if(lane, sb + O_MISC + 32 + 4 * warp, mx);
            bar_arrive(7, 384);
            const uint32_t as = sb + O_AS + wg * 8192 + (16 * w + g) * 128 + t * 4;
#pragma unroll
            for (int kk = 0; kk < 4; kk++) {
                sts32(as + (((2 * kk) ^ g) << 4), a[72 + 4 * kk]);
                sts32(as + 1024 + (((2 * kk) ^ g) << 4), a[72 + 4 * kk + 1]);
                sts32(as + (((2 * kk + 1) ^ g) << 4), a[72 + 4 * kk + 2]);
                sts32(as + 1024 + (((2 * kk + 1) ^ g) << 4), a[72 + 4 * kk + 3]);
                sts128(sb + O_AF + warp * 2048 + kk * 512 + lane * 16, a[72 + 4 * kk], a[72 + 4 * kk + 1], a[72 + 4 * kk + 2], a[72 + 4 * kk + 3]);
            }
            fence_async_smem();
            bar_sync(1, 256);
            const uint32_t l = lane * 16;
            const int mi = lane >> 3, isk = (mi >> 1) ? wg : (wg ^ 1);
            adr1 = (r == 2) ? (sb + O_VM + warp * 256 + (l >> 1))
                            : (isk ? (sb + O_KM + w * 512 + wg * 256 + (mi & 1) * 128 + (l & 127))
                                   : (sb + O_QM + w * 512 + (mi & 1) * 256 + wg * 128 + (l & 127)));
            adr1 = __shfl_sync(~0u, adr1, lane);
            const uint32_t qa = sb + (warp < 3 ? O_QM : O_QKX + mt * 2048) + l;
            const uint32_t ka = sb + (kt == 2 ? O_KM : O_QKX + 4096 + kt * 2048) + l;
            adr_pre = __shfl_sync(~0u, warp < 3 ? ka : qa, lane);
            adr_post = __shfl_sync(~0u, warp < 3 ? qa : ka, lane);
        }
        int s3 = 2;
#pragma unroll 1
        for (int s = -1; s < NSEG; s++) {
            const uint32_t l16 = opaque(l16c);
            if (s >= 0) {
#pragma unroll
                for (int kk = 0; kk < 4; kk++) {
                    const uint4 v = lds128(sb + O_AF + warp * 2048 + kk * 512 + l16);
                    a[72 + 4 * kk] = v.x; a[72 + 4 * kk + 1] = v.y; a[72 + 4 * kk + 2] = v.z; a[72 + 4 * kk + 3] = v.w;
                }
                float c0[4], c1[4], c2[4], c3[4];
                uint4 b[9];
                float inv;
                auto qkv_mma = [&](int i) {
                    const int u = 8 * i;
                    if (i == 0) {
                        mma16816_z(c0, a[u], a[u + 1], a[u + 2], a[u + 3], b[0].x, b[0].y);
                        mma16816_z(c1, a[u + 4], a[u + 5], a[u + 6], a[u + 7], b[0].z, b[0].w);
                        mma16816_z(c2, a[72 + u], a[72 + u + 1], a[72 + u + 2], a[72 + u + 3], b[0].x, b[0].y);
                        mma16816_z(c3, a[72 + u + 4], a[72 + u + 5], a[72 + u + 6], a[72 + u + 7], b[0].z, b[0].w);
                    } else {
                        mma16816(c0, a[u], a[u + 1], a[u + 2], a[u + 3], b[i].x, b[i].y);
                        mma16816(c1, a[u + 4], a[u + 5], a[u + 6], a[u + 7], b[i].z, b[i].w);
                        mma16816(c2, a[72 + u], a[72 + u + 1], a[72 + u + 2], a[72 + u + 3], b[i].x, b[i].y);
                        mma16816(c3, a[72 + u + 4], a[72 + u + 5], a[72 + u + 6], a[72 + u + 7], b[i].z, b[i].w);
                    }
                };
                const uint32_t mf = sb + O_MF + wg * 1536 + l16;
                bar_sync(2, 384);
                if (warp == 0) STAMP(s, 0);
#pragma unroll
                for (int i = 0; i < 11; i++) {
                    if (i < 9) b[i] = lds128(mf + (i / 3) * 3072 + (i % 3) * 512);
                    if (i == 9) inv = __uint_as_float(lds32(sb + O_MISC));
                    if (i >= 2) qkv_mma(i - 2);
                }
                if (r < 2) {
                    stsm4t(adr1, pack_bf16((c0[0] + c1[0]) * inv, (c0[1] + c1[1]) * inv), pack_bf16((c0[2] + c1[2]) * inv, (c0[3] + c1[3]) * inv),
                                 pack_bf16((c2[0] + c3[0]) * inv, (c2[1] + c3[1]) * inv), pack_bf16((c2[2] + c3[2]) * inv, (c2[3] + c3[3]) * inv));
                    if (warp == 0) STAMP(s, 1);
                    uint4 X[4], Y[4];
#pragma unroll
                    for (int i = 0; i < 4; i++) X[i] = ldsm4(adr_pre + i * 512);
                    asm volatile("{\n.reg .pred p;\nsetp.lt.u32 p, %0, 3;\n@p bar.sync 1, 256;\n@!p bar.arrive 1, 256;\n@!p bar.sync 8, 256;\n}" :: "r"(warp) : "memory");
#pragma unroll
                    for (int i = 0; i < 4; i++) Y[i] = ldsm4(adr_post + i * 512);
                    const uint32_t doff = kt * 512 + (kt == 2 ? (l16 >> 1) : l16);
                    auto scores = [&](float (&s0)[4], float (&s1)[4], const uint4 (&q)[4], const uint4 (&k)[4]) {
                        float t0[4], t1[4];
                        mma16816_z(s0, q[0].x, q[0].y, q[0].z, q[0].w, k[0].x, k[0].y);
                        mma16816_z(s1, q[0].x, q[0].y, q[0].z, q[0].w, k[0].z, k[0].w);
                        mma16816_z(t0, q[1].x, q[1].y, q[1].z, q[1].w, k[1].x, k[1].y);
                        mma16816_z(t1, q[1].x, q[1].y, q[1].z, q[1].w, k[1].z, k[1].w);
                        mma16816(s0, q[2].x, q[2].y, q[2].z, q[2].w, k[2].x, k[2].y);
                        mma16816(s1, q[2].x, q[2].y, q[2].z, q[2].w, k[2].z, k[2].w);
                        mma16816(t0, q[3].x, q[3].y, q[3].z, q[3].w, k[3].x, k[3].y);
                        mma16816(t1, q[3].x, q[3].y, q[3].z, q[3].w, k[3].z, k[3].w);
#pragma unroll
                        for (int i = 0; i < 4; i++) { s0[i] += t0[i]; s1[i] += t1[i]; }
                    };
                    if (warp < 3) {
                        float s0[4], s1[4];
                        if (warp == 2) {
#pragma unroll
                            for (int i = 0; i < 4; i++) X[i] = ldsm4(adr_pre + i * 512);
                        }
                        bar_arrive(8, 256);
                        scores(s0, s1, Y, X);
                        const uint32_t dst = sb + O_SC + r * 1280 + doff;
                        const float v0 = s0[0] + s0[2], v1 = s0[1] + s0[3], v2 = s1[0] + s1[2], v3 = s1[1] + s1[3];
                        if (warp < 2) {
                            st_async128(mapa(dst, 2), __float_as_uint(v0), __float_as_uint(v1), __float_as_uint(v2), __float_as_uint(v3), mapa(sb + B_SC, 2));
                            st_async128(mapa(dst, r ^ 1), __float_as_uint(v0), __float_as_uint(v1), __float_as_uint(v2), __float_as_uint(v3), mapa(sb + B_SC, r ^ 1));
                            st_async128(mapa(dst, r), __float_as_uint(v0), __float_as_uint(v1), __float_as_uint(v2), __float_as_uint(v3), mapa(sb + B_SC, r));
                        } else {
                            st_async64(mapa(dst, 2), __float_as_uint(v0 + v2), __float_as_uint(v1 + v3), mapa(sb + B_SC, 2));
                            st_async64(mapa(dst, r ^ 1), __float_as_uint(v0 + v2), __float_as_uint(v1 + v3), mapa(sb + B_SC, r ^ 1));
                            st_async64(mapa(dst, r), __float_as_uint(v0 + v2), __float_as_uint(v1 + v3), mapa(sb + B_SC, r));
                            STAMP(s, 2);
                        }
                        bar_arrive(4, 256);
                    } else {
                        float s0[4], s1[4];
                        scores(s0, s1, X, Y);
                        const uint32_t dx = mapa(sb + O_SX + (s & 1) * 5120 + r * 2560 + doff, mt), bx = mapa(sb + B_SX + 8 * (s & 1), mt);
                        bar_sync(4, 256);
                        if (kt != 2) {
                            st_async128(dx, __float_as_uint(s0[0]), __float_as_uint(s0[1]), __float_as_uint(s1[0]), __float_as_uint(s1[1]), bx);
                            st_async128(dx + 1280, __float_as_uint(s0[2]), __float_as_uint(s0[3]), __float_as_uint(s1[2]), __float_as_uint(s1[3]), bx);
                        } else {
                            st_async64(dx, __float_as_uint(s0[0] + s1[0]), __float_as_uint(s0[1] + s1[1]), bx);
                            st_async64(dx + 1280, __float_as_uint(s0[2] + s1[2]), __float_as_uint(s0[3] + s1[3]), bx);
                        }
                    }
                } else {
                    sts128f(sb + O_XP + warp * 512 + l16, c0[0] + c1[0], c0[1] + c1[1], c0[2] + c1[2], c0[3] + c1[3]);
                    bar_sync(8 + w, 64);
                    const float4 o = lds128f(sb + O_XP + (warp ^ 4) * 512 + l16);
                    const uint32_t X0 = pack_bf16((c2[0] + c3[0] + o.x) * inv, (c2[1] + c3[1] + o.y) * inv);
                    const uint32_t X1 = pack_bf16((c2[2] + c3[2] + o.z) * inv, (c2[3] + c3[3] + o.w) * inv);
                    if (warp == 0) STAMP(s, 1);
                    const uint32_t dst = adr1 + (s & 1) * 2048;
                    st_async64(mapa(dst, 0), X0, X1, mapa(sb + B_VM, 0));
                    st_async64(mapa(dst, 1), X0, X1, mapa(sb + B_VM, 1));
                    st_async64(mapa(dst, 2), X0, X1, mapa(sb + B_VM, 2));
                    if (warp == 0) STAMP(s, 2);
                }
            }
            s3 = (s3 == 2) ? 0 : s3 + 1;
            if (s < NSEG - 1) {
                const int j = s + 1;
                const uint64_t desc0 = (uint64_t)(((sb + O_XT + s3 * XT_BYTES + wg * 64) & 0x3FFFF) >> 4) | (1ull << 16) | (64ull << 32) | (1ull << 62);
#define XDESC(i) (desc0 + (uint64_t)(((KB(i) >> 2) * 4096 + (KB(i) & 3) * 32) >> 4))
                float d[16];
                if (s >= 0) bar_sync(3, 384);
                mbar_wait(sb + B_X + 8 * s3, (j / 3) & 1);
                wg_fence();
#pragma unroll
                for (int i = 0; i < XCHUNK1; i++) {
                    if (i == 0) wgmma_n32_rs<0>(d, a[0], a[1], a[2], a[3], XDESC(0));
                    else wgmma_n32_rs<1>(d, a[4 * i], a[4 * i + 1], a[4 * i + 2], a[4 * i + 3], XDESC(i));
                }
                wg_commit();
                if (wg == 1) bar_sync(s >= 0 ? 5 : 1, s >= 0 ? 384 : 256);
#pragma unroll
                for (int i = XCHUNK1; i < 18; i++) wgmma_n32_rs<1>(d, a[4 * i], a[4 * i + 1], a[4 * i + 2], a[4 * i + 3], XDESC(i));
                wg_commit();
                wg_wait0();
                if (warp == 0) STAMP(s, 15);
#pragma unroll
                for (int q = 0; q < 4; q++) sts128f(sb + O_XP + warp * 2048 + q * 512 + l16, d[4 * q], d[4 * q + 1], d[4 * q + 2], d[4 * q + 3]);
                if (warp == 1 && s >= 0 && s + 2 < NSEG) tma_x_tile(sb, &tm_x, r, s + 2, s3 == 2 ? 0 : s3 + 1);
                if (wg == 0) bar_sync(s >= 0 ? 5 : 1, s >= 0 ? 384 : 256);
                else bar_arrive(8 + w, 64);
                const uint64_t da0 = (uint64_t)(((sb + O_AS + wg * 8192) & 0x3FFFF) >> 4) | (1ull << 16) | (64ull << 32) | (1ull << 62);
                if (wg == 0) {
                    wg_fence();
#pragma unroll
                    for (int i = 0; i < 4; i++) { if (i == 0) wgmma_n32_ss<0>(d, da0, XDESC(i)); else wgmma_n32_ss<1>(d, da0 + 2 * i, XDESC(i)); }
#pragma unroll
                    for (int i = 4; i < 18; i++) wgmma_n32_rs<1>(d, a[72 + 4 * i], a[72 + 4 * i + 1], a[72 + 4 * i + 2], a[72 + 4 * i + 3], XDESC(i));
                    wg_commit();
                } else {
                    wg_fence();
#pragma unroll
                    for (int i = 4; i < 18; i++) {
                        if (i == 4) wgmma_n32_rs<0>(d, a[88], a[89], a[90], a[91], XDESC(4));
                        else wgmma_n32_rs<1>(d, a[72 + 4 * i], a[72 + 4 * i + 1], a[72 + 4 * i + 2], a[72 + 4 * i + 3], XDESC(i));
                    }
#pragma unroll
                    for (int i = 0; i < 4; i++) wgmma_n32_ss<1>(d, da0 + 2 * i, XDESC(i));
                    wg_commit();
                }
                if (warp == 3 && r < 2 && s >= 2)
                    asm volatile("{\n.reg .pred p;\nsetp.eq.u32 p, %1, 0;\n@p red.release.gpu.global.add.u32 [%0], 1;\n}"
                                 :: "l"(&g_flag[((s - 2) * 4 + (h >> 3)) * 8]), "r"(l16) : "memory");
                if (wg == 0) bar_sync(8 + w, 64);
                wg_wait0();
                if (warp == 4) STAMP(s, 3);
                uint32_t e[8];
#pragma unroll
                for (int q = 0; q < 4; q++) {
                    const float4 o = lds128f(sb + O_XP + (warp ^ 4) * 2048 + q * 512 + l16);
                    e[2 * q] = pack_bf16(d[4 * q] + o.x, d[4 * q + 1] + o.y);
                    e[2 * q + 1] = pack_bf16(d[4 * q + 2] + o.z, d[4 * q + 3] + o.w);
                }
                if (r < 2) {
                    const uint32_t base = sb + O_QKX + wg * 4096 + w * 512 + l16;
                    stsm4t(base, e[0], wg ? e[1] : e[2], wg ? e[2] : e[1], e[3]);
                    stsm4t(base + 2048, e[4], wg ? e[5] : e[6], wg ? e[6] : e[5], e[7]);
                } else {
                    const uint32_t base = sb + O_VX + s3 * 8192 + warp * 1024 + l16;
                    sts128(base, e[0], e[1], e[2], e[3]);
                    sts128(base + 512, e[4], e[5], e[6], e[7]);
                    const uint32_t bar = sb + B_VX + 8 * (j & 1);
                    fence_async_smem();
                    __syncwarp();
                    const uint32_t src = sb + O_VX + s3 * 8192 + warp * 1024;
                    asm volatile("{\n.reg .pred p;\nelect.sync _|p, 0xffffffff;\n"
                        "@p cp.async.bulk.shared::cluster.shared::cta.mbarrier::complete_tx::bytes [%0], [%2], 1024, [%3];\n"
                        "@p cp.async.bulk.shared::cluster.shared::cta.mbarrier::complete_tx::bytes [%1], [%2], 1024, [%4];\n}"
                        :: "r"(mapa(src, 0)), "r"(mapa(src, 1)), "r"(src), "r"(mapa(bar, 0)), "r"(mapa(bar, 1)) : "memory");
                }
                if (warp == 7) STAMP(s, 4);
            }
        }
    } else {
        asm volatile("setmaxnreg.dec.sync.aligned.u32 152;");
        const int c = w;
        uint32_t a[96];
        uint32_t mmax = 0;
        {
            const int g = lane >> 2, t = lane & 3, t2 = threadIdx.x - 256;
            if (c == 0) {
                tma_x_tile(sb, &tm_x, r, 0, 0);
                tma_x_tile(sb, &tm_x, r, 1, 1);
                mbar_expect_if(lane, sb + B_SC, 2560);
                mbar_expect_if(lane, sb + B_VM, 2048);
                if (r < 2) { mbar_expect_if(lane, sb + B_VX, VXBYTES); mbar_expect_if(lane, sb + B_SX, r == 0 ? 3072 : 5120); }
                sts32_if(lane, sb + O_MISC, __float_as_uint(1.0f));
                sts32_if(lane, sb + O_MISC + 12, 0x7fff7fffu);
            }
#pragma unroll
            for (int i = 0; i < 4; i++) g_acc[(blockIdx.x * 64 + i * 16 + (t2 >> 3)) * 16 + (t2 & 7)] = make_uint4(0, 0, 0, 0);
#pragma unroll
            for (int tau = 0; tau < 3; tau++) {
                uint32_t v[6];
#pragma unroll
                for (int i = 0; i < 3; i++) {
                    const uint32_t* p = reinterpret_cast<const uint32_t*>(mem0 + g * DM + 16 * (12 * tau + 4 * i + c) + 2 * t);
                    v[2 * i] = __ldg(p); v[2 * i + 1] = __ldg(p + 4);
                    mmax = __vmaxu2(mmax, __vmaxu2(v[2 * i] & 0x7fff7fffu, v[2 * i + 1] & 0x7fff7fffu));
                }
                sts128(sb + O_MF + tau * 3072 + (c >> 1) * 1536 + (c & 1) * 512 + lane * 16, v[0], v[1], v[2], v[3]);
                sts64(sb + O_MF + tau * 3072 + (c >> 1) * 1536 + 1024 + lane * 16 + (c & 1) * 8, v[4], v[5]);
            }
            mmax = max(mmax << 16, mmax & 0xffff0000u);
            bar_arrive(2, 384);
            uint32_t xm = 0;
            const uint4* xp = reinterpret_cast<const uint4*>(x) + blockIdx.x * 1536 + t2;
#pragma unroll
            for (int i = 0; i < 12; i++) {
                uint4 v = __ldg(xp + i * 128);
                xm = __vmaxu2(xm, __vmaxu2(__vmaxu2(v.x & 0x7fff7fffu, v.y & 0x7fff7fffu), __vmaxu2(v.z & 0x7fff7fffu, v.w & 0x7fff7fffu)));
            }
            xm = __reduce_max_sync(~0u, max(xm << 16, xm & 0xffff0000u));

            const __nv_bfloat16* p = Wo + (size_t)(h * 128 + 4 * t) * DM + 192 * r + 16 * c + 2 * g;
#pragma unroll
            for (int i = 0; i < 3; i++)
#pragma unroll
                for (int eb = 0; eb < 8; eb++)
#pragma unroll
                    for (int j = 0; j < 4; j++) a[(i * 8 + eb) * 4 + j] = ldg_nc32(p + (16 * eb + ((j & 1) * 2 + (j >> 1))) * DM + 64 * i);
#pragma unroll
            for (int kk = 0; kk < 48; kk++) {
                uint32_t w0 = a[2 * kk], w1 = a[2 * kk + 1];
                a[2 * kk] = __byte_perm(w0, w1, 0x5410);
                a[2 * kk + 1] = __byte_perm(w0, w1, 0x7632);
            }
            float wmax = 0.f;
#pragma unroll
            for (int i = 0; i < 3; i++) {
                float s0 = 0.f, s1 = 0.f;
#pragma unroll
                for (int kk = 16 * i; kk < 16 * i + 16; kk++) {
                    s0 += fabsf(__uint_as_float(a[2 * kk] << 16)) + fabsf(__uint_as_float(a[2 * kk] & 0xffff0000u));
                    s1 += fabsf(__uint_as_float(a[2 * kk + 1] << 16)) + fabsf(__uint_as_float(a[2 * kk + 1] & 0xffff0000u));
                }
                s0 += __shfl_xor_sync(~0u, s0, 1); s0 += __shfl_xor_sync(~0u, s0, 2);
                s1 += __shfl_xor_sync(~0u, s1, 1); s1 += __shfl_xor_sync(~0u, s1, 2);
                wmax = fmaxf(wmax, fmaxf(s0, s1));
            }
            uint32_t wm = __reduce_max_sync(~0u, __float_as_uint(wmax));
            sts32_if(lane, sb + O_OF + 4 * c, wm); sts32_if(lane, sb + O_OF + 16 + 4 * c, xm);
            __threadfence();
            bar_sync(7, 384);
            if (c == 0) {
                const uint4 wq = lds128(sb + O_OF), xq = lds128(sb + O_OF + 16), v0 = lds128(sb + O_MISC + 32), v1 = lds128(sb + O_MISC + 48);
                const uint32_t w1 = max(max(wq.x, wq.y), max(wq.z, wq.w)), x1 = max(max(xq.x, xq.y), max(xq.z, xq.w));
                const uint32_t vv = (r < 2) ? 0u : max(max(max(v0.x, v0.y), max(v0.z, v0.w)), max(max(v1.x, v1.y), max(v1.z, v1.w)));
                unsigned old = 0;
                asm volatile("{\n.reg .pred p;\nsetp.eq.u32 p, %6, 0;\n@p st.global.v4.u32 [%1], {%2,%3,%4,%4};\nfence.acq_rel.gpu;\n@p atom.relaxed.gpu.global.add.u32 %0, [%5], 1;\n}"
                             : "+r"(old) : "l"(&g_norm[blockIdx.x * 4]), "r"(w1), "r"(vv), "r"(x1), "l"(&g_gridbar), "r"(lane) : "memory");
                old = __shfl_sync(~0u, old, 0);
                const unsigned target = (old / 96u + 1u) * 96u;
                asm volatile("{\n.reg .pred p;\n.reg .u32 n, v;\nmov.u32 n, 0;\n"
                             "G_%=: ld.acquire.gpu.global.u32 v, [%0];\nsub.u32 v, v, %1;\nsetp.ge.s32 p, v, 0;\n@p bra.uni E_%=;\n"
                             "add.u32 n, n, 1;\nsetp.lt.u32 p, n, 4000000;\n@p bra.uni G_%=;\ntrap;\nE_%=:\n}" :: "l"(&g_gridbar), "r"(target) : "memory");
                uint4 n0 = ldg_relaxed128(&g_norm[lane * 4]), n1 = ldg_relaxed128(&g_norm[(lane + 32) * 4]), n2 = ldg_relaxed128(&g_norm[(lane + 64) * 4]);
                const float fw = __uint_as_float(__reduce_max_sync(~0u, max(n0.x, max(n1.x, n2.x))));
                const float fv = __uint_as_float(__reduce_max_sync(~0u, max(n0.y, max(n1.y, n2.y))));
                const float xmax = __uint_as_float(__reduce_max_sync(~0u, max(n0.z, max(n1.z, n2.z))));
                const float G = 36.f * fw * fv;
                sts32_if(lane, sb + O_MISC + 4, __float_as_uint(G)); sts32_if(lane, sb + O_MISC + 8, __float_as_uint(G * xmax));
            }
        }
        bar_sync(6, 128);
        int s3p = 2;
        uint32_t PX[5] = {0u, 0u, 0u, 0u, 0u};
        char* rptr; int pdelta; char* optr;
        {
            const uint32_t roff = (r * 4 + c) * 2048 + (lane >> 4) * 512 + (lane & 2) * 128 + (lane & 1) * 64 + (lane & 12) * 4;
            const uint32_t poff = c * 2048 + (lane & 4) * 256 + (lane >> 4) * 256 + (lane & 8) * 8 + (lane & 3) * 16;
            rptr = reinterpret_cast<char*>(g_acc) + roff;
            pdelta = __shfl_sync(~0u, (int)poff - (int)roff, lane);
            optr = reinterpret_cast<char*>(g_ox) + ((size_t)(h * 2 + (c >> 1)) * SEQ + 16 * r + 8 * (c & 1)) * 128 + lane * 16 - 4096;
        }
#pragma unroll 1
        for (int s = 0; s <= NSEG; s++) {
            const uint32_t l16 = opaque(l16c);
            const int s3 = (s3p == 2) ? 0 : s3p + 1;
            unsigned t_red = 0;
            if (s < NSEG - 1) {
                sts32_if(l16, sb + O_MISC + 16 + 4 * c, __reduce_max_sync(~0u, mmax));
                mbar_arrive_if(l16, sb + B_MX);
            }
            if (c == 0) STAMP(s < NSEG ? s : -1, 5);
            if (r < 2 && s >= 1) {
                const uint32_t vmb = sb + O_VM + ((s - 1) & 1) * 2048 + (c >> 1) * 1024 + (l16 >> 1);
                const uint32_t vb = sb + O_VX + s3p * 8192 + (c >> 1) * 4096 + l16;
                const uint4 vm0 = lds64x2(vmb), vm1 = lds64x2(vmb + 512);
                float sm[4], o[4][4];
                uint4 v[4];
#pragma unroll
                for (int q = 0; q < 4; q++) v[q] = lds128(vb + q * 1024);
                mma1688_z(sm, ONES, ONES, PX[0]);
                mma1688_z(o[0], vm0.x, vm0.y, PX[0]); mma1688_z(o[1], vm0.z, vm0.w, PX[0]);
                mma1688_z(o[2], vm1.x, vm1.y, PX[0]); mma1688_z(o[3], vm1.z, vm1.w, PX[0]);
                mma16816(sm, ONES, ONES, ONES, ONES, PX[1], PX[2]);
#pragma unroll
                for (int q = 0; q < 4; q++) {
                    mma16816(o[q], v[q].x, v[q].y, v[q].z, v[q].w, PX[1], PX[2]);
                    v[q] = lds128(vb + q * 1024 + 512);
                }
                mma16816(sm, ONES, ONES, ONES, ONES, PX[3], PX[4]);
#pragma unroll
                for (int q = 0; q < 4; q++) mma16816(o[q], v[q].x, v[q].y, v[q].z, v[q].w, PX[3], PX[4]);
                const uint32_t row = (l16 >> 4) & 7;
                const uint32_t stg = sb + O_OXS + c * 1024 + row * 128 + (((l16 >> 7) ^ row) << 4);
                const float r0 = rcp_fast(sm[0]), r1 = rcp_fast(sm[1]);
#pragma unroll
                for (int e2 = 0; e2 < 2; e2++)
                    stsm4t(stg ^ (e2 * 64), pack_bf16(o[2 * e2][0] * r0, o[2 * e2][1] * r1), pack_bf16(o[2 * e2][2] * r0, o[2 * e2][3] * r1),
                           pack_bf16(o[2 * e2 + 1][0] * r0, o[2 * e2 + 1][1] * r1), pack_bf16(o[2 * e2 + 1][2] * r0, o[2 * e2 + 1][3] * r1));
                __syncwarp();
            }
            if (s < NSEG - 1) {
                bar_arrive(3, 384);
                mbar_wait(sb + B_MX, s & 1);
                const uint4 mm = lds128(sb + O_MISC + 16), cf = lds128(sb + O_MISC);
                const float bound = fmaxf(__uint_as_float(cf.z), __uint_as_float(cf.y) * (__uint_as_float(max(max(mm.x, mm.y), max(mm.z, mm.w))) * __uint_as_float(cf.x)));
                const uint32_t eb = min(max(__float_as_uint(bound) & 0x7f800000u, 21u << 23), 254u << 23);
                const float sig = __uint_as_float((268u << 23) - eb);
                const uint32_t inv_new = eb - (14u << 23);
                if (r < 2) mbar_wait(sb + B_VX + 8 * (s & 1), (s >> 1) & 1);
                mbar_wait(sb + B_VM, s & 1);
                uint4 vx[4];
#pragma unroll
                for (int q = 0; q < 4; q++) vx[q] = lds128(sb + O_VX + s3 * 8192 + c * 2048 + q * 512 + l16);
                const uint4 vm = lds64x2(sb + O_VM + (s & 1) * 2048 + c * 512 + (l16 >> 1));
                if (c == 0) STAMP(s, 13);
                mbar_wait(sb + B_SC, s & 1);
                if (c == 0) STAMP(s, 6);
                float p[10];
                load_scores(p, sb + O_SC, 1280, l16);
                float mx = fmaxf(fmaxf(fmaxf(p[0], p[1]), fmaxf(p[2], p[3])), fmaxf(fmaxf(p[4], p[5]), fmaxf(p[6], p[7])));
                mx = quad_max(fmaxf(mx, fmaxf(p[8], p[9])));
                const float mo = mx * SM_SCALE;
                uint32_t P[5];
#pragma unroll
                for (int n = 0; n < 5; n++) P[n] = pack_bf16(ex2(fmaf(p[2 * n], SM_SCALE, -mo)), ex2(fmaf(p[2 * n + 1], SM_SCALE, -mo)));
                if (c == 0) STAMP(s, 7);
                float o0[4], o1[4], sm[4];
                mma1688_z(sm, ONES, ONES, P[0]);
                mma1688_z(o0, vm.x, vm.y, P[0]);
                mma1688_z(o1, vm.z, vm.w, P[0]);
                mma16816(sm, ONES, ONES, ONES, ONES, P[1], P[2]);
                mma16816(o0, vx[0].x, vx[0].y, vx[0].z, vx[0].w, P[1], P[2]);
                mma16816(o1, vx[2].x, vx[2].y, vx[2].z, vx[2].w, P[1], P[2]);
                mma16816(sm, ONES, ONES, ONES, ONES, P[3], P[4]);
                mma16816(o0, vx[1].x, vx[1].y, vx[1].z, vx[1].w, P[3], P[4]);
                mma16816(o1, vx[3].x, vx[3].y, vx[3].z, vx[3].w, P[3], P[4]);
                const float r0 = rcp_fast(sm[0]) * sig, r1 = rcp_fast(sm[1]) * sig;
                stsm4t(sb + O_OF + c * 512 + l16, pack_bf16(o0[0] * r0, o0[1] * r1), pack_bf16(o0[2] * r0, o0[3] * r1),
                       pack_bf16(o1[0] * r0, o1[1] * r1), pack_bf16(o1[2] * r0, o1[3] * r1));
                bar_sync(6, 128);
                uint4 ob[4];
#pragma unroll
                for (int q = 0; q < 4; q++) ob[q] = ldsm4(sb + O_OF + q * 512 + l16);
                float m0[3][4], m1[3][4];
#pragma unroll
                for (int q = 0; q < 4; q++) {
#pragma unroll
                    for (int i = 0; i < 3; i++) {
                        const int k0 = (i * 8 + 2 * q) * 4;
                        if (q == 0) mma16816_z(m0[i], a[k0], a[k0 + 1], a[k0 + 2], a[k0 + 3], ob[q].x, ob[q].y);
                        else mma16816(m0[i], a[k0], a[k0 + 1], a[k0 + 2], a[k0 + 3], ob[q].x, ob[q].y);
                    }
#pragma unroll
                    for (int i = 0; i < 3; i++) {
                        const int k1 = (i * 8 + 2 * q + 1) * 4;
                        if (q == 0) mma16816_z(m1[i], a[k1], a[k1 + 1], a[k1 + 2], a[k1 + 3], ob[q].z, ob[q].w);
                        else mma16816(m1[i], a[k1], a[k1 + 1], a[k1 + 2], a[k1 + 3], ob[q].z, ob[q].w);
                    }
                }
                asm volatile("red.relaxed.gpu.global.add.noftz.v4.f16x2 [%0], {%1,%2,%3,%4};" :: "l"(rptr),
                    "r"(pack_f16(m0[0][0] + m1[0][0], m0[0][2] + m1[0][2])), "r"(pack_f16(m0[1][0] + m1[1][0], m0[1][2] + m1[1][2])),
                    "r"(pack_f16(m0[2][0] + m1[2][0], m0[2][2] + m1[2][2])), "r"(0x3c00u) : "memory");
                asm volatile("red.relaxed.gpu.global.add.noftz.v4.f16x2 [%0], {%1,%2,%3,%4};" :: "l"(rptr + 1024),
                    "r"(pack_f16(m0[0][1] + m1[0][1], m0[0][3] + m1[0][3])), "r"(pack_f16(m0[1][1] + m1[1][1], m0[1][3] + m1[1][3])),
                    "r"(pack_f16(m0[2][1] + m1[2][1], m0[2][3] + m1[2][3])), "r"(0x3c00u) : "memory");
                t_red = clk();
                bar_arrive(5, 384);
                {
                    const uint32_t nb = 8 * ((s + 1) & 1);
                    const uint32_t bar = sb + (c == 0 ? B_SC : c == 1 ? B_VM : c == 2 ? B_VX + nb : B_SX + nb);
                    const uint32_t bytes = c == 0 ? 2560 : c == 1 ? 2048 : c == 2 ? VXBYTES : (r == 0 ? 3072 : 5120);
                    mbar_expect_if(l16 | (uint32_t)(r == 2 && c >= 2), bar, bytes);
                    sts32_if(l16 | c, sb + O_MISC, inv_new);
                }
                if (c == 0) STAMPV(s, 8, t_red);
            } else if (r < 2 && s == NSEG - 1) {
                mbar_wait(sb + B_VM, s & 1);
                mbar_wait(sb + B_VX + 8 * (s & 1), (s >> 1) & 1);
            }

            float px[10];
#pragma unroll
            for (int i = 0; i < 10; i++) px[i] = 0.f;
            if (r < 2 && s < NSEG) {
                mbar_wait(sb + B_SX + 8 * (s & 1), (s >> 1) & 1);
                const int q0 = 16 * r + 8 * (c & 1) + 8 + (int)(l16 >> 6) - (int)((l16 >> 3) & 6);
                load_scores(px, sb + O_SX + (s & 1) * 5120 + (c & 1) * 1280, 2560, l16);
#pragma unroll
                for (int n = 1; n < 5; n++) {
                    if (8 * n > q0) px[2 * n] = -INFINITY;
                    if (8 * n + 1 > q0) px[2 * n + 1] = -INFINITY;
                }
                float mx = fmaxf(fmaxf(fmaxf(px[0], px[1]), fmaxf(px[2], px[3])), fmaxf(fmaxf(px[4], px[5]), fmaxf(px[6], px[7])));
                mx = quad_max(fmaxf(mx, fmaxf(px[8], px[9])));
                const float mo = mx * SM_SCALE;
#pragma unroll
                for (int i = 0; i < 10; i++) px[i] = fmaf(px[i], SM_SCALE, -mo);
            }
            auto finish_x = [&]() {
                const uint4 u0 = lds128(sb + O_OXS + c * 1024 + l16), u1 = lds128(sb + O_OXS + c * 1024 + 512 + l16);
                asm volatile("{\n.reg .pred p;\nsetp.ne.u32 p, %9, 0;\n@p st.global.v4.u32 [%0], {%1,%2,%3,%4};\n@p st.global.v4.u32 [%0+512], {%5,%6,%7,%8};\n}"
                    :: "l"(optr), "r"(u0.x), "r"(u0.y), "r"(u0.z), "r"(u0.w), "r"(u1.x), "r"(u1.y), "r"(u1.z), "r"(u1.w), "r"((uint32_t)(r < 2 && s >= 1)) : "memory");
#pragma unroll
                for (int n = 0; n < 5; n++) PX[n] = pack_bf16(ex2v(px[2 * n]), ex2v(px[2 * n + 1]));
            };
            if (s >= NSEG - 1) {
                finish_x();
            } else {
                if (c == 0) STAMP(s, 9);
                const char* pbase = rptr + pdelta;
                spin_until(t_red, D_WAIT);
                uint4 v[6];
#pragma unroll
                for (int i = 0; i < 6; i++) v[i] = ldg_relaxed128(pbase + (i >> 1) * 8192 + (i & 1) * 512);
                finish_x();
                int nretry = 0;
                asm volatile("{\n.reg .pred p, q;\n.reg .u32 n, x;\nmov.u32 n, 0;\n"
                     "R_%=: and.b32 x, %3, %7;\nand.b32 x, x, %11;\nand.b32 x, x, %15;\nand.b32 x, x, %19;\nand.b32 x, x, %23;\n"
                     "setp.eq.u32 p, x, 0x5000;\nvote.sync.all.pred q, p, 0xffffffff;\n@q bra.uni K_%=;\n"
                     "ld.relaxed.gpu.global.v4.u32 {%0,%1,%2,%3}, [%25];\nld.relaxed.gpu.global.v4.u32 {%4,%5,%6,%7}, [%25+512];\n"
                     "ld.relaxed.gpu.global.v4.u32 {%8,%9,%10,%11}, [%25+8192];\nld.relaxed.gpu.global.v4.u32 {%12,%13,%14,%15}, [%25+8704];\n"
                     "ld.relaxed.gpu.global.v4.u32 {%16,%17,%18,%19}, [%25+16384];\nld.relaxed.gpu.global.v4.u32 {%20,%21,%22,%23}, [%25+16896];\n"
                     "add.u32 %24, %24, 1;\nadd.u32 n, n, 1;\nsetp.lt.u32 q, n, 2000000;\n@q bra.uni R_%=;\ntrap;\nK_%=:\n}"
                     : "+r"(v[0].x), "+r"(v[0].y), "+r"(v[0].z), "+r"(v[0].w), "+r"(v[1].x), "+r"(v[1].y), "+r"(v[1].z), "+r"(v[1].w),
                       "+r"(v[2].x), "+r"(v[2].y), "+r"(v[2].z), "+r"(v[2].w), "+r"(v[3].x), "+r"(v[3].y), "+r"(v[3].z), "+r"(v[3].w),
                       "+r"(v[4].x), "+r"(v[4].y), "+r"(v[4].z), "+r"(v[4].w), "+r"(v[5].x), "+r"(v[5].y), "+r"(v[5].z), "+r"(v[5].w), "+r"(nretry)
                     : "l"(pbase) : "memory");
                if (c == 0) STAMP(s, 10);
#pragma unroll
                for (int tau = 0; tau < 3; tau++) {
                    v[2 * tau].x = f16x2_to_bf16x2(v[2 * tau].x); v[2 * tau + 1].x = f16x2_to_bf16x2(v[2 * tau + 1].x);
                    v[2 * tau].y = f16x2_to_bf16x2(v[2 * tau].y); v[2 * tau + 1].y = f16x2_to_bf16x2(v[2 * tau + 1].y);
                    v[2 * tau].z = f16x2_to_bf16x2(v[2 * tau].z); v[2 * tau + 1].z = f16x2_to_bf16x2(v[2 * tau + 1].z);
                    sts128(sb + O_MF + tau * 3072 + (c >> 1) * 1536 + (c & 1) * 512 + l16, v[2 * tau].x, v[2 * tau + 1].x, v[2 * tau].y, v[2 * tau + 1].y);
                    sts64(sb + O_MF + tau * 3072 + (c >> 1) * 1536 + 1024 + (c & 1) * 8 + l16, v[2 * tau].z, v[2 * tau + 1].z);
                }
                bar_arrive(2, 384);
                if (c == 0) STAMP(s, 12);
                if (c == 0) STAMPV(s, 14, nretry);
                mmax = 0;
                const uint32_t msk = lds32(sb + O_MISC + 12);
#pragma unroll
                for (int i = 0; i < 6; i++) mmax = __vmaxu2(__vmaxu2(mmax, v[i].x & msk), __vmaxu2(v[i].y & msk, v[i].z & msk));
                mmax = max(mmax << 16, mmax & 0xffff0000u);
            }
            s3p = s3;
            rptr += 24576;
            optr += 4096;
        }
        if (r < 2) {
            bar_sync(6, 128);
            if (c == 0)
                asm volatile("{\n.reg .pred p;\nsetp.eq.u32 p, %1, 0;\nfence.acq_rel.gpu;\n@p red.relaxed.gpu.global.add.u32 [%0], 1;\n"
                             "@p red.relaxed.gpu.global.add.u32 [%0+128], 1;\n@p red.relaxed.gpu.global.add.u32 [%0+256], 1;\n}"
                             :: "l"(&g_flag[(61 * 4 + (h >> 3)) * 8]), "r"(l16c) : "memory");
        }
    }
    cluster_sync();
}

__device__ float g_u[SEQ * 2 * DM];
__global__ void naive_gemm1(const __nv_bfloat16* x, const __nv_bfloat16* Bre, const __nv_bfloat16* Bim) {
    int p = blockIdx.x * 64 + threadIdx.x % 64, tk = blockIdx.y * 4 + threadIdx.x / 64;
    float sr = 0, si = 0;
    for (int d = 0; d < DM; d++) { float xv = __bfloat162float(x[tk * DM + d]); sr += xv * __bfloat162float(Bre[p * DM + d]); si += xv * __bfloat162float(Bim[p * DM + d]); }
    g_u[tk * 2 * DM + 2 * p] = sr; g_u[tk * 2 * DM + 2 * p + 1] = si;
}
__global__ void naive_scan(const __nv_bfloat16* Lre, const __nv_bfloat16* Lim, const __nv_bfloat16* logdt) {
    int p = blockIdx.x * 64 + threadIdx.x;
    float dt = __bfloat162float(__float2bfloat16(expf(__bfloat162float(logdt[p]))));
    float lr = __bfloat162float(Lre[p]), li = __bfloat162float(Lim[p]);
    float e = expf(dt * lr), br = e * cosf(dt * li), bi = e * sinf(dt * li);
    float den = lr * lr + li * li;
    float cr = ((br - 1.f) * lr + bi * li) / den, ci = (bi * lr - (br - 1.f) * li) / den;
    float hr = 0, hi = 0;
    for (int tk = 0; tk < SEQ; tk++) {
        float ur = g_u[tk * 2 * DM + 2 * p], ui = g_u[tk * 2 * DM + 2 * p + 1];
        float nr = br * hr - bi * hi + cr * ur - ci * ui, ni = br * hi + bi * hr + cr * ui + ci * ur;
        hr = nr; hi = ni;
        g_u[tk * 2 * DM + 2 * p] = hr; g_u[tk * 2 * DM + 2 * p + 1] = hi;
    }
}
__global__ void naive_gemm2(const __nv_bfloat16* x, const __nv_bfloat16* Cre, const __nv_bfloat16* Cim, const __nv_bfloat16* Dk, float* out) {
    int d = blockIdx.x * 64 + threadIdx.x % 64, tk = blockIdx.y * 4 + threadIdx.x / 64;
    float s = 0;
    for (int p = 0; p < DM; p++) s += g_u[tk * 2 * DM + 2 * p] * __bfloat162float(Cre[d * DM + p]) - g_u[tk * 2 * DM + 2 * p + 1] * __bfloat162float(Cim[d * DM + p]);
    out[tk * 1152 + d] = 2.f * s + __bfloat162float(__float2bfloat16(__bfloat162float(x[tk * DM + d]) * __bfloat162float(Dk[d])));
}
__global__ void naive_wo(const __nv_bfloat16* Wo, float* out) {
    int d = blockIdx.x * 64 + threadIdx.x % 64, tk = blockIdx.y * 4 + threadIdx.x / 64;
    const __nv_bfloat16* ox = reinterpret_cast<const __nv_bfloat16*>(g_ox);
    float s = 0;
    for (int k = 0; k < HD; k++) {
        int hh = k >> 6, e0 = k & 63, e = (e0 & 48) + (e0 & 1) * 8 + ((e0 & 15) >> 1);
        s += __bfloat162float(ox[((size_t)hh * SEQ + tk) * 64 + (((e >> 3) ^ (tk & 7)) << 3) + (e & 7)]) * __bfloat162float(Wo[k * DM + d]);
    }
    out[tk * 1152 + DM + d] = s;
}

typedef CUresult (*EncodeFn)(CUtensorMap*, CUtensorMapDataType, cuuint32_t, void*, const cuuint64_t*, const cuuint64_t*, const cuuint32_t*, const cuuint32_t*,
                             CUtensorMapInterleave, CUtensorMapSwizzle, CUtensorMapL2promotion, CUtensorMapFloatOOBfill);
}

extern "C" void kernel_launch(void* const* d_in, const int* in_sizes, int n_in, void* d_out, int out_size) {
    typedef const __nv_bfloat16* bp;
    bp Ax = (bp)d_in[0], Lre = (bp)d_in[1], Lim = (bp)d_in[2], Bre = (bp)d_in[3], Bim = (bp)d_in[4], Cre = (bp)d_in[5], Cim = (bp)d_in[6],
       logdt = (bp)d_in[7], Dk = (bp)d_in[8], Bx = (bp)d_in[9], mem0 = (bp)d_in[10], Wq = (bp)d_in[11], Wk = (bp)d_in[12], Wv = (bp)d_in[13], Wo = (bp)d_in[14];
    float* out = (float*)d_out;
    static EncodeFn enc = nullptr;
    if (!enc) {
        void* fn = nullptr; cudaDriverEntryPointQueryResult qr;
        cudaGetDriverEntryPoint("cuTensorMapEncodeTiled", &fn, cudaEnableDefault, &qr);
        enc = (EncodeFn)fn;
        cudaFuncSetAttribute(chain_kernel, cudaFuncAttributeMaxDynamicSharedMemorySize, CHAIN_SMEM);
    }
    CUtensorMap tm_x;
    {
        cuuint64_t gd[2] = {DM, SEQ}; cuuint64_t gs[1] = {DM * 2}; cuuint32_t bd[2] = {64, 32}; cuuint32_t es[2] = {1, 1};
        enc(&tm_x, CU_TENSOR_MAP_DATA_TYPE_BFLOAT16, 2, (void*)Bx, gd, gs, bd, es, CU_TENSOR_MAP_INTERLEAVE_NONE, CU_TENSOR_MAP_SWIZZLE_128B,
            CU_TENSOR_MAP_L2_PROMOTION_L2_128B, CU_TENSOR_MAP_FLOAT_OOB_FILL_NONE);
    }
    cudaStream_t st = cudaStreamPerThread;
    chain_kernel<<<96, 384, CHAIN_SMEM, st>>>(tm_x, Bx, mem0, Wq, Wk, Wv, Wo);
    naive_gemm1<<<dim3(9, 512), 256, 0, st>>>(Ax, Bre, Bim);
    naive_scan<<<9, 64, 0, st>>>(Lre, Lim, logdt);
    naive_gemm2<<<dim3(9, 512), 256, 0, st>>>(Ax, Cre, Cim, Dk, out);
    naive_wo<<<dim3(9, 512), 256, 0, st>>>(Wo, out);
}
```

```cpp
#include <cuda_runtime.h>
#include <cuda.h>
#include <cuda_bf16.h>
#include <cuda_fp16.h>
#include <stdint.h>

#define D_WAIT 700
#define VXMODE 1
#define VXBYTES (VXMODE == 2 ? 0 : 8192)
#define XC0 10
#define XC1 4

namespace {

constexpr int DM = 576, NH = 32, SEQ = 2048, NSEG = 64, HD = 4096;

__device__ uint4 g_acc[64 * 96 * 16];
__device__ uint4 g_ox[NH * 2 * SEQ * 8];
__device__ unsigned g_flag[NSEG * 4 * 8];
__device__ unsigned g_gridbar;
__device__ float g_norm[96 * 4];

__device__ __forceinline__ uint32_t smem_u32(const void* p) { return (uint32_t)__cvta_generic_to_shared(p); }
__device__ __forceinline__ uint32_t mapa(uint32_t a, uint32_t r) { uint32_t o; asm("mapa.shared::cluster.u32 %0, %1, %2;" : "=r"(o) : "r"(a), "r"(r)); return o; }
__device__ __forceinline__ uint32_t mapa_v(uint32_t a, uint32_t r) { uint32_t o; asm volatile("mapa.shared::cluster.u32 %0, %1, %2;" : "=r"(o) : "r"(a), "r"(r)); return o; }
__device__ __forceinline__ unsigned clk() { unsigned long long c; asm volatile("mov.u64 %0, %%clock64;" : "=l"(c) :: "memory"); return (unsigned)c; }
__device__ __forceinline__ void mbar_init(uint32_t bar, uint32_t cnt) { asm volatile("mbarrier.init.shared::cta.b64 [%0], %1;" :: "r"(bar), "r"(cnt) : "memory"); }
__device__ __forceinline__ void mbar_expect(uint32_t bar, uint32_t bytes) { asm volatile("mbarrier.arrive.expect_tx.shared::cta.b64 _, [%0], %1;" :: "r"(bar), "r"(bytes) : "memory"); }
__device__ __forceinline__ void mbar_wait(uint32_t bar, uint32_t parity) {
    asm volatile("{\n.reg .pred p;\n.reg .u32 n;\nmov.u32 n, 0;\n"
                 "W_%=: mbarrier.try_wait.parity.shared::cta.b64 p, [%0], %1;\n@p bra.uni D_%=;\n"
                 "add.u32 n, n, 1;\nsetp.lt.u32 p, n, 4000000;\n@p bra.uni W_%=;\ntrap;\nD_%=:\n}" :: "r"(bar), "r"(parity) : "memory");
}
__device__ __forceinline__ void mbar_expect_if(uint32_t z, uint32_t bar, uint32_t bytes) {
    asm volatile("{\n.reg .pred p;\nsetp.eq.u32 p, %2, 0;\n@p mbarrier.arrive.expect_tx.shared::cta.b64 _, [%0], %1;\n}" :: "r"(bar), "r"(bytes), "r"(z) : "memory");
}
__device__ __forceinline__ void mbar_arrive_if(uint32_t z, uint32_t bar) {
    asm volatile("{\n.reg .pred p;\nsetp.eq.u32 p, %1, 0;\n@p mbarrier.arrive.shared::cta.b64 _, [%0];\n}" :: "r"(bar), "r"(z) : "memory");
}
__device__ __forceinline__ void sts32_if(uint32_t z, uint32_t a, uint32_t x) {
    asm volatile("{\n.reg .pred p;\nsetp.eq.u32 p, %2, 0;\n@p st.shared.u32 [%0], %1;\n}" :: "r"(a), "r"(x), "r"(z) : "memory");
}
__device__ __forceinline__ void spin_until(unsigned t0, unsigned d) {
    asm volatile("{\n.reg .pred p;\n.reg .u64 c;\n.reg .u32 lo;\n"
                 "S_%=: mov.u64 c, %%clock64;\ncvt.u32.u64 lo, c;\nsub.u32 lo, lo, %0;\nsetp.lt.u32 p, lo, %1;\n@p bra.uni S_%=;\n}" :: "r"(t0), "r"(d) : "memory");
}
__device__ __forceinline__ void bar_sync(int id, int n) { asm volatile("bar.sync %0, %1;" :: "r"(id), "r"(n) : "memory"); }
__device__ __forceinline__ void bar_sync_sel(int sel, int id) {
    asm volatile("{\n.reg .pred p;\nsetp.eq.u32 p, %0, 0;\n@p bar.sync %1, %3;\n@!p bar.sync %2, %3;\n}" :: "r"(sel), "r"(id), "r"(id + 1), "n"(192) : "memory");
}
__device__ __forceinline__ void bar_arrive(int id, int n) { asm volatile("bar.arrive %0, %1;" :: "r"(id), "r"(n) : "memory"); }
__device__ __forceinline__ void fence_async_smem() { asm volatile("fence.proxy.async.shared::cta;" ::: "memory"); }
__device__ __forceinline__ uint32_t pack_bf16(float lo, float hi) { uint32_t r; asm("cvt.rn.bf16x2.f32 %0, %1, %2;" : "=r"(r) : "f"(hi), "f"(lo)); return r; }
__device__ __forceinline__ uint32_t pack_f16(float lo, float hi) { uint32_t r; asm("cvt.rn.f16x2.f32 %0, %1, %2;" : "=r"(r) : "f"(hi), "f"(lo)); return r; }
__device__ __forceinline__ uint32_t f16x2_to_bf16x2(uint32_t v) { float2 f = __half22float2(*reinterpret_cast<__half2*>(&v)); return pack_bf16(f.x, f.y); }
__device__ __forceinline__ float ex2(float x) { float y; asm("ex2.approx.ftz.f32 %0, %1;" : "=f"(y) : "f"(x)); return y; }
__device__ __forceinline__ float ex2v(float x) { float y; asm volatile("ex2.approx.ftz.f32 %0, %1;" : "=f"(y) : "f"(x)); return y; }
__device__ __forceinline__ uint32_t shl_v(uint32_t a, int n) { return a << n; }
__device__ __forceinline__ uint32_t max3u(uint32_t a, uint32_t b, uint32_t c) { return max(max(a, b), c); }
__device__ __forceinline__ uint4 lds128(uint32_t a) { uint4 v; asm volatile("ld.shared.v4.u32 {%0,%1,%2,%3}, [%4];" : "=r"(v.x), "=r"(v.y), "=r"(v.z), "=r"(v.w) : "r"(a) : "memory"); return v; }
__device__ __forceinline__ float4 lds128f(uint32_t a) { float4 v; asm volatile("ld.shared.v4.f32 {%0,%1,%2,%3}, [%4];" : "=f"(v.x), "=f"(v.y), "=f"(v.z), "=f"(v.w) : "r"(a) : "memory"); return v; }
__device__ __forceinline__ float2 lds64f(uint32_t a) { float2 v; asm volatile("ld.shared.v2.f32 {%0,%1}, [%2];" : "=f"(v.x), "=f"(v.y) : "r"(a) : "memory"); return v; }
__device__ __forceinline__ uint4 lds64x2(uint32_t a) { uint4 v; asm volatile("ld.shared.v2.u32 {%0,%1}, [%4];\nld.shared.v2.u32 {%2,%3}, [%4+256];" : "=r"(v.x), "=r"(v.y), "=r"(v.z), "=r"(v.w) : "r"(a) : "memory"); return v; }
__device__ __forceinline__ uint32_t lds32(uint32_t a) { uint32_t v; asm volatile("ld.shared.u32 %0, [%1];" : "=r"(v) : "r"(a) : "memory"); return v; }
__device__ __forceinline__ void sts128(uint32_t a, uint32_t x, uint32_t y, uint32_t z, uint32_t w) { asm volatile("st.shared.v4.u32 [%0], {%1,%2,%3,%4};" :: "r"(a), "r"(x), "r"(y), "r"(z), "r"(w) : "memory"); }
__device__ __forceinline__ void sts128f(uint32_t a, float x, float y, float z, float w) { asm volatile("st.shared.v4.f32 [%0], {%1,%2,%3,%4};" :: "r"(a), "f"(x), "f"(y), "f"(z), "f"(w) : "memory"); }
__device__ __forceinline__ void sts64(uint32_t a, uint32_t x, uint32_t y) { asm volatile("st.shared.v2.u32 [%0], {%1,%2};" :: "r"(a), "r"(x), "r"(y) : "memory"); }
__device__ __forceinline__ void sts32(uint32_t a, uint32_t x) { asm volatile("st.shared.u32 [%0], %1;" :: "r"(a), "r"(x) : "memory"); }
__device__ __forceinline__ uint4 ldsm4(uint32_t a) { uint4 v; asm volatile("ldmatrix.sync.aligned.m8n8.x4.shared.b16 {%0,%1,%2,%3}, [%4];" : "=r"(v.x), "=r"(v.y), "=r"(v.z), "=r"(v.w) : "r"(a) : "memory"); return v; }
__device__ __forceinline__ void stsm2t(uint32_t a, uint32_t x, uint32_t y) { asm volatile("stmatrix.sync.aligned.m8n8.x2.trans.shared.b16 [%0], {%1,%2};" :: "r"(a), "r"(x), "r"(y) : "memory"); }
__device__ __forceinline__ void stsm4t(uint32_t a, uint32_t x, uint32_t y, uint32_t z, uint32_t w) { asm volatile("stmatrix.sync.aligned.m8n8.x4.trans.shared.b16 [%0], {%1,%2,%3,%4};" :: "r"(a), "r"(x), "r"(y), "r"(z), "r"(w) : "memory"); }
__device__ __forceinline__ void st_async64(uint32_t a, uint32_t x, uint32_t y, uint32_t bar) { asm volatile("st.async.shared::cluster.mbarrier::complete_tx::bytes.v2.b32 [%0], {%1,%2}, [%3];" :: "r"(a), "r"(x), "r"(y), "r"(bar) : "memory"); }
__device__ __forceinline__ void bulk_s2c(uint32_t dst, uint32_t src, uint32_t bytes, uint32_t bar) { asm volatile("cp.async.bulk.shared::cluster.shared::cta.mbarrier::complete_tx::bytes [%0], [%1], %2, [%3];" :: "r"(dst), "r"(src), "r"(bytes), "r"(bar) : "memory"); }
__device__ __forceinline__ void bulk_s2g(void* dst, uint32_t src, uint32_t bytes) { asm volatile("cp.async.bulk.global.shared::cta.bulk_group [%0], [%1], %2;" :: "l"(dst), "r"(src), "r"(bytes) : "memory"); }
__device__ __forceinline__ uint32_t ldg_nc32(const void* p) { uint32_t v; asm volatile("ld.global.nc.L2::128B.u32 %0, [%1];" : "=r"(v) : "l"(p)); return v; }
__device__ __forceinline__ uint4 ldg_relaxed128(const void* p) { uint4 v; asm volatile("ld.relaxed.gpu.global.v4.u32 {%0,%1,%2,%3}, [%4];" : "=r"(v.x), "=r"(v.y), "=r"(v.z), "=r"(v.w) : "l"(p) : "memory"); return v; }
__device__ __forceinline__ void mma16816(float (&d)[4], uint32_t a0, uint32_t a1, uint32_t a2, uint32_t a3, uint32_t b0, uint32_t b1) {
    asm volatile("mma.sync.aligned.m16n8k16.row.col.f32.bf16.bf16.f32 {%0,%1,%2,%3}, {%4,%5,%6,%7}, {%8,%9}, {%0,%1,%2,%3};"
        : "+f"(d[0]), "+f"(d[1]), "+f"(d[2]), "+f"(d[3]) : "r"(a0), "r"(a1), "r"(a2), "r"(a3), "r"(b0), "r"(b1));
}
__device__ __forceinline__ void mma16816_z(float (&d)[4], uint32_t a0, uint32_t a1, uint32_t a2, uint32_t a3, uint32_t b0, uint32_t b1) {
    asm volatile("mma.sync.aligned.m16n8k16.row.col.f32.bf16.bf16.f32 {%0,%1,%2,%3}, {%4,%5,%6,%7}, {%8,%9}, {%10,%10,%10,%10};"
        : "=f"(d[0]), "=f"(d[1]), "=f"(d[2]), "=f"(d[3]) : "r"(a0), "r"(a1), "r"(a2), "r"(a3), "r"(b0), "r"(b1), "f"(0.f));
}
__device__ __forceinline__ void mma1688(float (&d)[4], uint32_t a0, uint32_t a1, uint32_t b0) {
    asm volatile("mma.sync.aligned.m16n8k8.row.col.f32.bf16.bf16.f32 {%0,%1,%2,%3}, {%4,%5}, {%6}, {%0,%1,%2,%3};"
        : "+f"(d[0]), "+f"(d[1]), "+f"(d[2]), "+f"(d[3]) : "r"(a0), "r"(a1), "r"(b0));
}
__device__ __forceinline__ void mma1688_z(float (&d)[4], uint32_t a0, uint32_t a1, uint32_t b0) {
    asm volatile("mma.sync.aligned.m16n8k8.row.col.f32.bf16.bf16.f32 {%0,%1,%2,%3}, {%4,%5}, {%6}, {%7,%7,%7,%7};"
        : "=f"(d[0]), "=f"(d[1]), "=f"(d[2]), "=f"(d[3]) : "r"(a0), "r"(a1), "r"(b0), "f"(0.f));
}
template <int ACC>
__device__ __forceinline__ void wgmma_n32_rs(float (&d)[16], uint32_t a0, uint32_t a1, uint32_t a2, uint32_t a3, uint64_t desc) {
    asm volatile("wgmma.mma_async.sync.aligned.m64n32k16.f32.bf16.bf16 {%0,%1,%2,%3,%4,%5,%6,%7,%8,%9,%10,%11,%12,%13,%14,%15}, {%16,%17,%18,%19}, %20, %21, 1, 1, 0;"
        : "+f"(d[0]), "+f"(d[1]), "+f"(d[2]), "+f"(d[3]), "+f"(d[4]), "+f"(d[5]), "+f"(d[6]), "+f"(d[7]),
          "+f"(d[8]), "+f"(d[9]), "+f"(d[10]), "+f"(d[11]), "+f"(d[12]), "+f"(d[13]), "+f"(d[14]), "+f"(d[15])
        : "r"(a0), "r"(a1), "r"(a2), "r"(a3), "l"(desc), "n"(ACC));
}
template <int ACC>
__device__ __forceinline__ void wgmma_n32_ss(float (&d)[16], uint64_t da, uint64_t db) {
    asm volatile("wgmma.mma_async.sync.aligned.m64n32k16.f32.bf16.bf16 {%0,%1,%2,%3,%4,%5,%6,%7,%8,%9,%10,%11,%12,%13,%14,%15}, %16, %17, %18, 1, 1, 0, 0;"
        : "+f"(d[0]), "+f"(d[1]), "+f"(d[2]), "+f"(d[3]), "+f"(d[4]), "+f"(d[5]), "+f"(d[6]), "+f"(d[7]),
          "+f"(d[8]), "+f"(d[9]), "+f"(d[10]), "+f"(d[11]), "+f"(d[12]), "+f"(d[13]), "+f"(d[14]), "+f"(d[15])
        : "l"(da), "l"(db), "n"(ACC));
}
__device__ __forceinline__ void wg_fence() { asm volatile("wgmma.fence.sync.aligned;" ::: "memory"); }
__device__ __forceinline__ void wg_commit() { asm volatile("wgmma.commit_group.sync.aligned;" ::: "memory"); }
__device__ __forceinline__ void wg_wait0() { asm volatile("wgmma.wait_group.sync.aligned 0;" ::: "memory"); }
__device__ __forceinline__ void cluster_sync() { asm volatile("barrier.cluster.arrive.aligned;\nbarrier.cluster.wait.aligned;" ::: "memory"); }

#define STAMP(s, i) do {} while (0)
#define STAMPV(s, i, v) do {} while (0)

constexpr int XT_BYTES = 36864;
constexpr int O_XT = 0;
constexpr int O_AS = 3 * XT_BYTES;
constexpr int O_AF = O_AS + 16384;
constexpr int O_MF = O_AF + 16384;
constexpr int O_QM = O_MF + 9216;
constexpr int O_KM = O_QM + 2048;
constexpr int O_QKX = O_KM + 2048;
constexpr int O_XP = O_QKX + 8192;
constexpr int O_VX = O_XP + 16384;
constexpr int O_VM = O_VX + 24576;
constexpr int O_SC = O_VM + 4096;
constexpr int O_OF = O_SC + 2560;
constexpr int O_SX = O_OF + 2048;
constexpr int O_PX = O_SX + 10240;
constexpr int O_OXS = O_PX + 1280;
constexpr int O_MISC = O_OXS + 4096;
constexpr int O_BAR = O_MISC + 64;
constexpr int CHAIN_SMEM = O_BAR + 128;
static_assert(CHAIN_SMEM <= 232448, "smem");
constexpr int B_X = O_BAR, B_VX = O_BAR + 24, B_SX = O_BAR + 40, B_SC = O_BAR + 56, B_VM = O_BAR + 64, B_MX = O_BAR + 72;
constexpr float SM_SCALE = 0.08838834764831845f * 1.4426950408889634f;
constexpr uint32_t ONES = 0x3f803f80u;

__device__ __forceinline__ uint32_t opaque(uint32_t v) { uint32_t o; asm volatile("mov.u32 %0, %1;" : "=r"(o) : "r"(v)); return o; }
__device__ __forceinline__ void st_async128(uint32_t a, uint32_t x, uint32_t y, uint32_t z, uint32_t w, uint32_t bar) {
    asm volatile("st.async.shared::cluster.mbarrier::complete_tx::bytes.v4.b32 [%0], {%1,%2,%3,%4}, [%5];" :: "r"(a), "r"(x), "r"(y), "r"(z), "r"(w), "r"(bar) : "memory");
}
__device__ __forceinline__ void tma_x_tile(uint32_t sb, const CUtensorMap* tm, int r, int j, int slot) {
    asm volatile("{\n.reg .pred p;\nelect.sync _|p, 0xffffffff;\n"
        "@p mbarrier.arrive.expect_tx.shared::cta.b64 _, [%2], 36864;\n"
        "@p cp.async.bulk.tensor.2d.shared::cluster.global.mbarrier::complete_tx::bytes.multicast::cluster [%0], [%1, {%3, %4}], [%2], %7;\n"
        "@p cp.async.bulk.tensor.2d.shared::cluster.global.mbarrier::complete_tx::bytes.multicast::cluster [%0+4096], [%1, {%5, %4}], [%2], %7;\n"
        "@p cp.async.bulk.tensor.2d.shared::cluster.global.mbarrier::complete_tx::bytes.multicast::cluster [%0+8192], [%1, {%6, %4}], [%2], %7;\n}"
        :: "r"(sb + O_XT + slot * XT_BYTES + 3 * r * 4096), "l"(tm), "r"(sb + B_X + 8 * slot), "r"(192 * r), "r"(j * 32), "r"(192 * r + 64), "r"(192 * r + 128),
           "h"((unsigned short)7) : "memory");
}
__device__ __forceinline__ float quad_max(float v) {
    const float a = __shfl_xor_sync(~0u, v, 1), b = __shfl_xor_sync(~0u, v, 2), c = __shfl_xor_sync(~0u, v, 3);
    return fmaxf(fmaxf(v, a), fmaxf(b, c));
}
__device__ __forceinline__ void load_scores(float (&p)[10], uint32_t base, uint32_t stride, uint32_t l16) {
    const float4 a0 = lds128f(base + l16), b0 = lds128f(base + stride + l16);
    const float4 a1 = lds128f(base + 512 + l16), b1 = lds128f(base + stride + 512 + l16);
    const float2 a2 = lds64f(base + 1024 + (l16 >> 1)), b2 = lds64f(base + stride + 1024 + (l16 >> 1));
    p[0] = a2.x + b2.x; p[1] = a2.y + b2.y;
    p[2] = a0.x + b0.x; p[3] = a0.y + b0.y; p[4] = a0.z + b0.z; p[5] = a0.w + b0.w;
    p[6] = a1.x + b1.x; p[7] = a1.y + b1.y; p[8] = a1.z + b1.z; p[9] = a1.w + b1.w;
}
__device__ __forceinline__ float rcp_fast(float x) { float y; asm("rcp.approx.ftz.f32 %0, %1;" : "=f"(y) : "f"(x)); return y; }

__global__ void __cluster_dims__(3, 1, 1) __launch_bounds__(384, 1)
chain_kernel(const __grid_constant__ CUtensorMap tm_x,
             const __nv_bfloat16* __restrict__ x, const __nv_bfloat16* __restrict__ mem0,
             const __nv_bfloat16* __restrict__ Wq, const __nv_bfloat16* __restrict__ Wk,
             const __nv_bfloat16* __restrict__ Wv, const __nv_bfloat16* __restrict__ Wo) {
    extern __shared__ __align__(1024) uint8_t smem_raw[];
    const uint32_t sb = smem_u32(smem_raw);
    const int lane = threadIdx.x & 31;
    const int warp = __shfl_sync(~0u, threadIdx.x >> 5, 0);
    const int wg = warp >> 2, w = warp & 3;
    const int h = blockIdx.x / 3, r = blockIdx.x - 3 * h;

    if (threadIdx.x == 0) {
        if (sb & 1023u) __trap();
        for (int i = 0; i < 9; i++) mbar_init(sb + O_BAR + 8 * i, 1);
        mbar_init(sb + B_MX, 4);
        asm volatile("fence.mbarrier_init.release.cluster;" ::: "memory");
    }
    if (blockIdx.x == 0) {
        for (int i = threadIdx.x; i < NSEG * 4 * 8; i += 384) g_flag[i] = 0;
        __threadfence();
    }
    __syncthreads();
    cluster_sync();
    asm volatile("griddepcontrol.launch_dependents;" ::: "memory");
    const uint32_t l16c = __shfl_sync(~0u, lane * 16, lane);

    if (wg < 2) {
#define KB(i) (12 * ((i) / 6) + (((i) % 6) >> 1 == 2 ? 8 + ((i) & 1) : (((i) % 6) >> 1) + 4 * ((i) & 1)))
        asm volatile("setmaxnreg.inc.sync.aligned.u32 176;");
        const int kt = warp < 3 ? warp : (warp < 5 ? warp - 3 : (warp == 5 ? 0 : 2));
        const int mt = (warp == 5 || warp == 7) ? 0 : 1;
        uint32_t a[144];
        uint32_t adr1, adr_pre, adr_post;
        {
            const int g = lane >> 2, t = lane & 3;
#pragma unroll
            for (int tl = 0; tl < 2; tl++) {
                const int tile = tl ? wg : (wg ^ 1);
                const __nv_bfloat16* W = (r < 2) ? (tile == 0 ? Wq : Wk) : Wv;
                const int col = h * 128 + ((r < 2) ? 64 * r : 64 * tile) + 16 * w + 2 * g;
                const __nv_bfloat16* p = W + (size_t)(32 * wg + 2 * t) * HD + col;
#pragma unroll
                for (int i = 0; i < 18; i++) {
                    a[72 * tl + 4 * i + 0] = ldg_nc32(p + (size_t)(16 * KB(i) + 0) * HD);
                    a[72 * tl + 4 * i + 1] = ldg_nc32(p + (size_t)(16 * KB(i) + 1) * HD);
                    a[72 * tl + 4 * i + 2] = ldg_nc32(p + (size_t)(16 * KB(i) + 8) * HD);
                    a[72 * tl + 4 * i + 3] = ldg_nc32(p + (size_t)(16 * KB(i) + 9) * HD);
                }
            }
#pragma unroll
            for (int kk = 0; kk < 72; kk++) {
                uint32_t w0 = a[2 * kk], w1 = a[2 * kk + 1];
                a[2 * kk] = __byte_perm(w0, w1, 0x5410);
                a[2 * kk + 1] = __byte_perm(w0, w1, 0x7632);
            }
            float vmax = 0.f;
#pragma unroll
            for (int tl = 0; tl < 2; tl++) {
                float s0 = 0.f, s1 = 0.f;
#pragma unroll
                for (int kk = 36 * tl; kk < 36 * tl + 36; kk++) {
                    s0 += fabsf(__uint_as_float(a[2 * kk] << 16)) + fabsf(__uint_as_float(a[2 * kk] & 0xffff0000u));
                    s1 += fabsf(__uint_as_float(a[2 * kk + 1] << 16)) + fabsf(__uint_as_float(a[2 * kk + 1] & 0xffff0000u));
                }
                s0 += __shfl_xor_sync(~0u, s0, 1); s0 += __shfl_xor_sync(~0u, s0, 2);
                s1 += __shfl_xor_sync(~0u, s1, 1); s1 += __shfl_xor_sync(~0u, s1, 2);
                vmax = fmaxf(vmax, fmaxf(s0, s1));
            }
            uint32_t mx = __reduce_max_sync(~0u, __float_as_uint(2.f * vmax));
            sts32_if(lane, sb + O_MISC + 32 + 4 * warp, mx);
            bar_arrive(7, 384);
            const uint32_t as = sb + O_AS + wg * 8192 + (16 * w + g) * 128 + t * 4;
#pragma unroll
            for (int kk = 0; kk < 4; kk++) {
                sts32(as + (((2 * kk) ^ g) << 4), a[72 + 4 * kk]);
                sts32(as + 1024 + (((2 * kk) ^ g) << 4), a[72 + 4 * kk + 1]);
                sts32(as + (((2 * kk + 1) ^ g) << 4), a[72 + 4 * kk + 2]);
                sts32(as + 1024 + (((2 * kk + 1) ^ g) << 4), a[72 + 4 * kk + 3]);
                sts128(sb + O_AF + warp * 2048 + kk * 512 + lane * 16, a[72 + 4 * kk], a[72 + 4 * kk + 1], a[72 + 4 * kk + 2], a[72 + 4 * kk + 3]);
            }
            fence_async_smem();
            bar_sync(1, 256);
            const uint32_t l = lane * 16;
            const int mi = lane >> 3, isk = (mi >> 1) ? wg : (wg ^ 1);
            adr1 = (r == 2) ? (sb + O_VM + warp * 256 + (l >> 1))
                            : (isk ? (sb + O_KM + w * 512 + wg * 256 + (mi & 1) * 128 + (l & 127))
                                   : (sb + O_QM + w * 512 + (mi & 1) * 256 + wg * 128 + (l & 127)));
            adr1 = __shfl_sync(~0u, adr1, lane);
            const uint32_t qa = sb + (warp < 3 ? O_QM : O_QKX + mt * 2048) + l;
            const uint32_t ka = sb + (kt == 2 ? O_KM : O_QKX + 4096 + kt * 2048) + l;
            adr_pre = __shfl_sync(~0u, warp < 3 ? ka : qa, lane);
            adr_post = __shfl_sync(~0u, warp < 3 ? qa : ka, lane);
        }
        int s3 = 2;
#pragma unroll 1
        for (int s = -1; s < NSEG; s++) {
            const uint32_t l16 = opaque(l16c);
            s3 = (s3 == 2) ? 0 : s3 + 1;
            if (s < NSEG - 1) mbar_wait(sb + B_X + 8 * s3, ((s + 1) / 3) & 1);
            const uint64_t desc0 = (uint64_t)(((sb + O_XT + s3 * XT_BYTES + wg * 64) & 0x3FFFF) >> 4) | (1ull << 16) | (64ull << 32) | (1ull << 62);
            auto x_softmax = [&]() {
                mbar_wait(sb + B_SX + 8 * (s & 1), (s >> 1) & 1);
                const int q0 = 16 * r + 8 * w + 8 + (int)(l16 >> 6) - (int)((l16 >> 3) & 6);
                float px[10];
                load_scores(px, sb + O_SX + (s & 1) * 5120 + w * 1280, 2560, l16);
#pragma unroll
                for (int n = 1; n < 5; n++) {
                    if (8 * n > q0) px[2 * n] = -INFINITY;
                    if (8 * n + 1 > q0) px[2 * n + 1] = -INFINITY;
                }
                float mx = fmaxf(fmaxf(fmaxf(px[0], px[1]), fmaxf(px[2], px[3])), fmaxf(fmaxf(px[4], px[5]), fmaxf(px[6], px[7])));
                mx = quad_max(fmaxf(mx, fmaxf(px[8], px[9])));
                const float mo = mx * SM_SCALE;
                uint32_t P[5];
#pragma unroll
                for (int n = 0; n < 5; n++) P[n] = pack_bf16(ex2(fmaf(px[2 * n], SM_SCALE, -mo)), ex2(fmaf(px[2 * n + 1], SM_SCALE, -mo)));
                sts128(sb + O_PX + w * 640 + l16, P[1], P[2], P[3], P[4]);
                sts32(sb + O_PX + w * 640 + 512 + (l16 >> 2), P[0]);
            };
            if (s >= 0) {
#pragma unroll
                for (int kk = 0; kk < 4; kk++) {
                    const uint4 v = lds128(sb + O_AF + warp * 2048 + kk * 512 + l16);
                    a[72 + 4 * kk] = v.x; a[72 + 4 * kk + 1] = v.y; a[72 + 4 * kk + 2] = v.z; a[72 + 4 * kk + 3] = v.w;
                }
                float c0[4], c1[4], c2[4], c3[4];
                uint4 b[9];
                float inv;
                auto qkv_mma = [&](int i) {
                    const int u = 8 * i;
                    if (i == 0) {
                        mma16816_z(c0, a[u], a[u + 1], a[u + 2], a[u + 3], b[0].x, b[0].y);
                        mma16816_z(c1, a[u + 4], a[u + 5], a[u + 6], a[u + 7], b[0].z, b[0].w);
                        mma16816_z(c2, a[72 + u], a[72 + u + 1], a[72 + u + 2], a[72 + u + 3], b[0].x, b[0].y);
                        mma16816_z(c3, a[72 + u + 4], a[72 + u + 5], a[72 + u + 6], a[72 + u + 7], b[0].z, b[0].w);
                    } else {
                        mma16816(c0, a[u], a[u + 1], a[u + 2], a[u + 3], b[i].x, b[i].y);
                        mma16816(c1, a[u + 4], a[u + 5], a[u + 6], a[u + 7], b[i].z, b[i].w);
                        mma16816(c2, a[72 + u], a[72 + u + 1], a[72 + u + 2], a[72 + u + 3], b[i].x, b[i].y);
                        mma16816(c3, a[72 + u + 4], a[72 + u + 5], a[72 + u + 6], a[72 + u + 7], b[i].z, b[i].w);
                    }
                };
                const uint32_t mf = sb + O_MF + wg * 1536 + l16;
                bar_sync(2, 384);
                if (warp == 0) STAMP(s, 0);
#pragma unroll
                for (int i = 0; i < 11; i++) {
                    if (i < 9) b[i] = lds128(mf + (i / 3) * 3072 + (i % 3) * 512);
                    if (i == 9) inv = __uint_as_float(lds32(sb + O_MISC));
                    if (i >= 2) qkv_mma(i - 2);
                }
                if (r < 2) {
                    bar_arrive(9, 384);
                    stsm4t(adr1, pack_bf16((c0[0] + c1[0]) * inv, (c0[1] + c1[1]) * inv), pack_bf16((c0[2] + c1[2]) * inv, (c0[3] + c1[3]) * inv),
                                 pack_bf16((c2[0] + c3[0]) * inv, (c2[1] + c3[1]) * inv), pack_bf16((c2[2] + c3[2]) * inv, (c2[3] + c3[3]) * inv));
                    if (warp == 0) STAMP(s, 1);
                    uint4 X[4], Y[4];
#pragma unroll
                    for (int i = 0; i < 4; i++) X[i] = ldsm4(adr_pre + i * 512);
                    asm volatile("{\n.reg .pred p;\nsetp.lt.u32 p, %0, 3;\n@p bar.sync 1, 256;\n@!p bar.arrive 1, 256;\n@!p bar.sync 8, 256;\n}" :: "r"(warp) : "memory");
#pragma unroll
                    for (int i = 0; i < 4; i++) Y[i] = ldsm4(adr_post + i * 512);
                    const uint32_t doff = kt * 512 + (kt == 2 ? (l16 >> 1) : l16);
                    auto scores = [&](float (&s0)[4], float (&s1)[4], const uint4 (&q)[4], const uint4 (&k)[4]) {
                        float t0[4], t1[4];
                        mma16816_z(s0, q[0].x, q[0].y, q[0].z, q[0].w, k[0].x, k[0].y);
                        mma16816_z(s1, q[0].x, q[0].y, q[0].z, q[0].w, k[0].z, k[0].w);
                        mma16816_z(t0, q[1].x, q[1].y, q[1].z, q[1].w, k[1].x, k[1].y);
                        mma16816_z(t1, q[1].x, q[1].y, q[1].z, q[1].w, k[1].z, k[1].w);
                        mma16816(s0, q[2].x, q[2].y, q[2].z, q[2].w, k[2].x, k[2].y);
                        mma16816(s1, q[2].x, q[2].y, q[2].z, q[2].w, k[2].z, k[2].w);
                        mma16816(t0, q[3].x, q[3].y, q[3].z, q[3].w, k[3].x, k[3].y);
                        mma16816(t1, q[3].x, q[3].y, q[3].z, q[3].w, k[3].z, k[3].w);
#pragma unroll
                        for (int i = 0; i < 4; i++) { s0[i] += t0[i]; s1[i] += t1[i]; }
                    };
                    if (warp < 3) {
                        float s0[4], s1[4];
                        if (warp == 2) {
#pragma unroll
                            for (int i = 0; i < 4; i++) X[i] = ldsm4(adr_pre + i * 512);
                        }
                        bar_arrive(8, 256);
                        scores(s0, s1, Y, X);
                        const uint32_t dst = sb + O_SC + r * 1280 + doff;
                        const float v0 = s0[0] + s0[2], v1 = s0[1] + s0[3], v2 = s1[0] + s1[2], v3 = s1[1] + s1[3];
                        if (warp < 2) {
                            st_async128(mapa(dst, 2), __float_as_uint(v0), __float_as_uint(v1), __float_as_uint(v2), __float_as_uint(v3), mapa(sb + B_SC, 2));
                            st_async128(mapa(dst, r ^ 1), __float_as_uint(v0), __float_as_uint(v1), __float_as_uint(v2), __float_as_uint(v3), mapa(sb + B_SC, r ^ 1));
                            st_async128(mapa(dst, r), __float_as_uint(v0), __float_as_uint(v1), __float_as_uint(v2), __float_as_uint(v3), mapa(sb + B_SC, r));
                        } else {
                            st_async64(mapa(dst, 2), __float_as_uint(v0 + v2), __float_as_uint(v1 + v3), mapa(sb + B_SC, 2));
                            st_async64(mapa(dst, r ^ 1), __float_as_uint(v0 + v2), __float_as_uint(v1 + v3), mapa(sb + B_SC, r ^ 1));
                            st_async64(mapa(dst, r), __float_as_uint(v0 + v2), __float_as_uint(v1 + v3), mapa(sb + B_SC, r));
                            STAMP(s, 2);
                        }
                        bar_arrive(4, 256);
                    } else {
                        float s0[4], s1[4];
                        scores(s0, s1, X, Y);
                        const uint32_t dx = mapa(sb + O_SX + (s & 1) * 5120 + r * 2560 + doff, mt), bx = mapa(sb + B_SX + 8 * (s & 1), mt);
                        bar_sync(4, 256);
                        if (kt != 2) {
                            st_async128(dx, __float_as_uint(s0[0]), __float_as_uint(s0[1]), __float_as_uint(s1[0]), __float_as_uint(s1[1]), bx);
                            st_async128(dx + 1280, __float_as_uint(s0[2]), __float_as_uint(s0[3]), __float_as_uint(s1[2]), __float_as_uint(s1[3]), bx);
                        } else {
                            st_async64(dx, __float_as_uint(s0[0] + s1[0]), __float_as_uint(s0[1] + s1[1]), bx);
                            st_async64(dx + 1280, __float_as_uint(s0[2] + s1[2]), __float_as_uint(s0[3] + s1[3]), bx);
                        }
                    }
                } else {
                    sts128f(sb + O_XP + warp * 512 + l16, c0[0] + c1[0], c0[1] + c1[1], c0[2] + c1[2], c0[3] + c1[3]);
                    bar_sync(8 + w, 64);
                    const float4 o = lds128f(sb + O_XP + (warp ^ 4) * 512 + l16);
                    const uint32_t X0 = pack_bf16((c2[0] + c3[0] + o.x) * inv, (c2[1] + c3[1] + o.y) * inv);
                    const uint32_t X1 = pack_bf16((c2[2] + c3[2] + o.z) * inv, (c2[3] + c3[3] + o.w) * inv);
                    if (warp == 0) STAMP(s, 1);
                    const uint32_t dst = adr1 + (s & 1) * 2048;
                    st_async64(mapa(dst, 0), X0, X1, mapa(sb + B_VM, 0));
                    st_async64(mapa(dst, 1), X0, X1, mapa(sb + B_VM, 1));
                    st_async64(mapa(dst, 2), X0, X1, mapa(sb + B_VM, 2));
                    if (warp == 0) STAMP(s, 2);
                }
            }
            if (s == NSEG - 1 && r < 2) {
                bar_sync(3, 384);
                if (wg == 1 && w < 2) x_softmax();
                bar_arrive(9, 384);
            }
            if (s < NSEG - 1) {
                const int j = s + 1;
#define XDESC(i) (desc0 + (uint64_t)(((KB(i) >> 2) * 4096 + (KB(i) & 3) * 32) >> 4))
                float d[16];
                if (s >= 0) bar_sync(3, 384);
                wg_fence();
#pragma unroll
                for (int i = 0; i < XC1; i++) {
                    if (i == 0) wgmma_n32_rs<0>(d, a[0], a[1], a[2], a[3], XDESC(0));
                    else wgmma_n32_rs<1>(d, a[4 * i], a[4 * i + 1], a[4 * i + 2], a[4 * i + 3], XDESC(i));
                }
                wg_commit();
                if (wg == 1 && s >= 0) {
                    if (w < 2) {
                        if (r < 2) x_softmax();
                    } else if (w == 2) {
                        if (r < 2 && s >= 2)
                            asm volatile("{\n.reg .pred p;\nsetp.eq.u32 p, %1, 0;\n@p red.release.gpu.global.inc.u32 [%0], 0x7fffffff;\n}"
                                         :: "l"(&g_flag[((s - 2) * 4 + (h >> 3)) * 8]), "r"(l16) : "memory");
                    } else if (s + 2 < NSEG) {
                        mbar_wait(sb + B_SC, s & 1);
                        tma_x_tile(sb, &tm_x, r, s + 2, s3 == 2 ? 0 : s3 + 1);
                    }
                    bar_sync(5, 384);
                }
#pragma unroll
                for (int i = XC1; i < XC0; i++) wgmma_n32_rs<1>(d, a[4 * i], a[4 * i + 1], a[4 * i + 2], a[4 * i + 3], XDESC(i));
                wg_commit();
                if (wg == 0 && s >= 0) bar_sync(5, 384);
#pragma unroll
                for (int i = XC0; i < 18; i++) wgmma_n32_rs<1>(d, a[4 * i], a[4 * i + 1], a[4 * i + 2], a[4 * i + 3], XDESC(i));
                wg_commit();
                wg_wait0();
                if (warp == 0) STAMP(s, 15);
#pragma unroll
                for (int q = 0; q < 4; q++) sts128f(sb + O_XP + warp * 2048 + q * 512 + l16, d[4 * q], d[4 * q + 1], d[4 * q + 2], d[4 * q + 3]);
                asm volatile("{\n.reg .pred p;\nsetp.eq.u32 p, %0, 0;\n@p bar.arrive 12, 256;\n@!p bar.arrive 13, 256;\n}" :: "r"(wg) : "memory");
                const uint64_t da0 = (uint64_t)(((sb + O_AS + wg * 8192) & 0x3FFFF) >> 4) | (1ull << 16) | (64ull << 32) | (1ull << 62);
                wg_fence();
#pragma unroll
                for (int i = 0; i < 4; i++) { if (i == 0) wgmma_n32_ss<0>(d, da0, XDESC(i)); else wgmma_n32_ss<1>(d, da0 + 2 * i, XDESC(i)); }
#pragma unroll
                for (int i = 4; i < 18; i++) wgmma_n32_rs<1>(d, a[72 + 4 * i], a[72 + 4 * i + 1], a[72 + 4 * i + 2], a[72 + 4 * i + 3], XDESC(i));
                wg_commit();
                asm volatile("{\n.reg .pred p;\nsetp.eq.u32 p, %0, 0;\n@p bar.sync 13, 256;\n@!p bar.sync 12, 256;\n}" :: "r"(wg) : "memory");
                wg_wait0();
                if (warp == 4) STAMP(s, 3);
                uint32_t e[8];
#pragma unroll
                for (int q = 0; q < 4; q++) {
                    const float4 o = lds128f(sb + O_XP + (warp ^ 4) * 2048 + q * 512 + l16);
                    e[2 * q] = pack_bf16(d[4 * q] + o.x, d[4 * q + 1] + o.y);
                    e[2 * q + 1] = pack_bf16(d[4 * q + 2] + o.z, d[4 * q + 3] + o.w);
                }
                if (r < 2) {
                    const uint32_t base = sb + O_QKX + wg * 4096 + w * 512 + l16;
                    stsm4t(base, e[0], wg ? e[1] : e[2], wg ? e[2] : e[1], e[3]);
                    stsm4t(base + 2048, e[4], wg ? e[5] : e[6], wg ? e[6] : e[5], e[7]);
                } else {
                    const uint32_t base = sb + O_VX + s3 * 8192 + warp * 1024 + l16;
                    sts128(base, e[0], e[1], e[2], e[3]);
                    sts128(base + 512, e[4], e[5], e[6], e[7]);
                    const uint32_t bar = sb + B_VX + 8 * (j & 1);
                    fence_async_smem();
                    __syncwarp();
                    const uint32_t src = sb + O_VX + s3 * 8192 + warp * 1024;
                    asm volatile("{\n.reg .pred p;\nelect.sync _|p, 0xffffffff;\n"
                        "@p cp.async.bulk.shared::cluster.shared::cta.mbarrier::complete_tx::bytes [%0], [%2], 1024, [%3];\n"
                        "@p cp.async.bulk.shared::cluster.shared::cta.mbarrier::complete_tx::bytes [%1], [%2], 1024, [%4];\n}"
                        :: "r"(mapa(src, 0)), "r"(mapa(src, 1)), "r"(src), "r"(mapa(bar, 0)), "r"(mapa(bar, 1)) : "memory");
                }
                if (warp == 7) STAMP(s, 4);
            }
        }
    } else {
        asm volatile("setmaxnreg.dec.sync.aligned.u32 152;");
        const int c = w;
        uint32_t a[96];
        uint32_t mmax = 0;
        {
            const int g = lane >> 2, t = lane & 3, t2 = threadIdx.x - 256;
            if (c == 0) {
                tma_x_tile(sb, &tm_x, r, 0, 0);
                tma_x_tile(sb, &tm_x, r, 1, 1);
                mbar_expect_if(lane, sb + B_SC, 2560);
                mbar_expect_if(lane, sb + B_VM, 2048);
                if (r < 2) { mbar_expect_if(lane, sb + B_VX, VXBYTES); mbar_expect_if(lane, sb + B_SX, r == 0 ? 3072 : 5120); }
                sts32_if(lane, sb + O_MISC, __float_as_uint(1.0f));
                sts32_if(lane, sb + O_MISC + 12, 0x7fff7fffu);
            }
#pragma unroll
            for (int i = 0; i < 4; i++) g_acc[(blockIdx.x * 64 + i * 16 + (t2 >> 3)) * 16 + (t2 & 7)] = make_uint4(0, 0, 0, 0);
#pragma unroll
            for (int tau = 0; tau < 3; tau++) {
                uint32_t v[6];
#pragma unroll
                for (int i = 0; i < 3; i++) {
                    const uint32_t* p = reinterpret_cast<const uint32_t*>(mem0 + g * DM + 16 * (12 * tau + 4 * i + c) + 2 * t);
                    v[2 * i] = __ldg(p); v[2 * i + 1] = __ldg(p + 4);
                    mmax = __vmaxu2(mmax, __vmaxu2(v[2 * i] & 0x7fff7fffu, v[2 * i + 1] & 0x7fff7fffu));
                }
                sts128(sb + O_MF + tau * 3072 + (c >> 1) * 1536 + (c & 1) * 512 + lane * 16, v[0], v[1], v[2], v[3]);
                sts64(sb + O_MF + tau * 3072 + (c >> 1) * 1536 + 1024 + lane * 16 + (c & 1) * 8, v[4], v[5]);
            }
            mmax = max(mmax << 16, mmax & 0xffff0000u);
            bar_arrive(2, 384);
            uint32_t xm = 0;
            const uint4* xp = reinterpret_cast<const uint4*>(x) + blockIdx.x * 1536 + t2;
#pragma unroll
            for (int i = 0; i < 12; i++) {
                uint4 v = __ldg(xp + i * 128);
                xm = __vmaxu2(xm, __vmaxu2(__vmaxu2(v.x & 0x7fff7fffu, v.y & 0x7fff7fffu), __vmaxu2(v.z & 0x7fff7fffu, v.w & 0x7fff7fffu)));
            }
            xm = __reduce_max_sync(~0u, max(xm << 16, xm & 0xffff0000u));

            const __nv_bfloat16* p = Wo + (size_t)(h * 128 + 4 * t) * DM + 192 * r + 16 * c + 2 * g;
#pragma unroll
            for (int i = 0; i < 3; i++)
#pragma unroll
                for (int eb = 0; eb < 8; eb++)
#pragma unroll
                    for (int j = 0; j < 4; j++) a[(i * 8 + eb) * 4 + j] = ldg_nc32(p + (16 * eb + ((j & 1) * 2 + (j >> 1))) * DM + 64 * i);
#pragma unroll
            for (int kk = 0; kk < 48; kk++) {
                uint32_t w0 = a[2 * kk], w1 = a[2 * kk + 1];
                a[2 * kk] = __byte_perm(w0, w1, 0x5410);
                a[2 * kk + 1] = __byte_perm(w0, w1, 0x7632);
            }
            float wmax = 0.f;
#pragma unroll
            for (int i = 0; i < 3; i++) {
                float s0 = 0.f, s1 = 0.f;
#pragma unroll
                for (int kk = 16 * i; kk < 16 * i + 16; kk++) {
                    s0 += fabsf(__uint_as_float(a[2 * kk] << 16)) + fabsf(__uint_as_float(a[2 * kk] & 0xffff0000u));
                    s1 += fabsf(__uint_as_float(a[2 * kk + 1] << 16)) + fabsf(__uint_as_float(a[2 * kk + 1] & 0xffff0000u));
                }
                s0 += __shfl_xor_sync(~0u, s0, 1); s0 += __shfl_xor_sync(~0u, s0, 2);
                s1 += __shfl_xor_sync(~0u, s1, 1); s1 += __shfl_xor_sync(~0u, s1, 2);
                wmax = fmaxf(wmax, fmaxf(s0, s1));
            }
            uint32_t wm = __reduce_max_sync(~0u, __float_as_uint(wmax));
            sts32_if(lane, sb + O_OF + 4 * c, wm); sts32_if(lane, sb + O_OF + 16 + 4 * c, xm);
            __threadfence();
            bar_sync(7, 384);
            if (c == 0) {
                const uint4 wq = lds128(sb + O_OF), xq = lds128(sb + O_OF + 16), v0 = lds128(sb + O_MISC + 32), v1 = lds128(sb + O_MISC + 48);
                const uint32_t w1 = max(max(wq.x, wq.y), max(wq.z, wq.w)), x1 = max(max(xq.x, xq.y), max(xq.z, xq.w));
                const uint32_t vv = (r < 2) ? 0u : max(max(max(v0.x, v0.y), max(v0.z, v0.w)), max(max(v1.x, v1.y), max(v1.z, v1.w)));
                unsigned old = 0;
                asm volatile("{\n.reg .pred p;\nsetp.eq.u32 p, %6, 0;\n@p st.global.v4.u32 [%1], {%2,%3,%4,%4};\nfence.acq_rel.gpu;\n@p atom.relaxed.gpu.global.add.u32 %0, [%5], 1;\n}"
                             : "+r"(old) : "l"(&g_norm[blockIdx.x * 4]), "r"(w1), "r"(vv), "r"(x1), "l"(&g_gridbar), "r"(lane) : "memory");
                old = __shfl_sync(~0u, old, 0);
                const unsigned target = (old / 96u + 1u) * 96u;
                asm volatile("{\n.reg .pred p;\n.reg .u32 n, v;\nmov.u32 n, 0;\n"
                             "G_%=: ld.acquire.gpu.global.u32 v, [%0];\nsub.u32 v, v, %1;\nsetp.ge.s32 p, v, 0;\n@p bra.uni E_%=;\n"
                             "add.u32 n, n, 1;\nsetp.lt.u32 p, n, 4000000;\n@p bra.uni G_%=;\ntrap;\nE_%=:\n}" :: "l"(&g_gridbar), "r"(target) : "memory");
                uint4 n0 = ldg_relaxed128(&g_norm[lane * 4]), n1 = ldg_relaxed128(&g_norm[(lane + 32) * 4]), n2 = ldg_relaxed128(&g_norm[(lane + 64) * 4]);
                const float fw = __uint_as_float(__reduce_max_sync(~0u, max(n0.x, max(n1.x, n2.x))));
                const float fv = __uint_as_float(__reduce_max_sync(~0u, max(n0.y, max(n1.y, n2.y))));
                const float xmax = __uint_as_float(__reduce_max_sync(~0u, max(n0.z, max(n1.z, n2.z))));
                const float G = 36.f * fw * fv;
                sts32_if(lane, sb + O_MISC + 4, __float_as_uint(G)); sts32_if(lane, sb + O_MISC + 8, __float_as_uint(G * xmax));
            }
        }
        bar_sync(6, 128);
        int s3p = 2;
        char* rptr; int pdelta; char* optr;
        {
            const uint32_t roff = (r * 4 + c) * 2048 + (lane >> 4) * 512 + (lane & 2) * 128 + (lane & 1) * 64 + (lane & 12) * 4;
            const uint32_t poff = c * 2048 + (lane & 4) * 256 + (lane >> 4) * 256 + (lane & 8) * 8 + (lane & 3) * 16;
            rptr = reinterpret_cast<char*>(g_acc) + roff;
            pdelta = __shfl_sync(~0u, (int)poff - (int)roff, lane);
            optr = reinterpret_cast<char*>(g_ox) + ((size_t)(h * 2 + (c >> 1)) * SEQ + 16 * r + 8 * (c & 1)) * 128 + lane * 16 - 4096;
        }
#pragma unroll 1
        for (int s = 0; s <= NSEG; s++) {
            const uint32_t l16 = opaque(l16c);
            const int s3 = (s3p == 2) ? 0 : s3p + 1;
            unsigned t_red = 0;
            uint32_t ebits = 0;
            if (s < NSEG - 1) {
                sts32_if(l16, sb + O_MISC + 16 + 4 * c, __reduce_max_sync(~0u, mmax));
                mbar_arrive_if(l16, sb + B_MX);
                mbar_wait(sb + B_MX, s & 1);
                const uint4 mm = lds128(sb + O_MISC + 16), cf = lds128(sb + O_MISC);
                const float bound = fmaxf(__uint_as_float(cf.z), __uint_as_float(cf.y) * (__uint_as_float(max(max(mm.x, mm.y), max(mm.z, mm.w))) * __uint_as_float(cf.x)));
                ebits = min(max(__float_as_uint(bound) & 0x7f800000u, 21u << 23), 254u << 23);
            }
            if (c == 0) STAMP(s < NSEG ? s : -1, 5);
            if (r < 2) {
                const uint32_t vmb = sb + O_VM + ((s - 1) & 1) * 2048 + (c >> 1) * 1024 + (l16 >> 1);
                const uint32_t vb = sb + O_VX + s3p * 8192 + (c >> 1) * 4096 + l16;
                const uint4 vm0 = lds64x2(vmb), vm1 = lds64x2(vmb + 512);
                float sm[4], o[4][4];
                uint4 v[8];
#pragma unroll
                for (int q = 0; q < 6; q++) v[q] = lds128(vb + (q & 3) * 1024 + (q >> 2) * 512);
                bar_sync(9, 384);
                const uint4 P = lds128(sb + O_PX + (c & 1) * 640 + l16);
                const uint32_t P0 = lds32(sb + O_PX + (c & 1) * 640 + 512 + (l16 >> 2));
                mma1688_z(o[0], vm0.x, vm0.y, P0); mma1688_z(o[1], vm0.z, vm0.w, P0);
                mma1688_z(o[2], vm1.x, vm1.y, P0); mma1688_z(o[3], vm1.z, vm1.w, P0);
#pragma unroll
                for (int q = 6; q < 8; q++) v[q] = lds128(vb + (q & 3) * 1024 + (q >> 2) * 512);
                mma1688_z(sm, ONES, ONES, P0);
#pragma unroll
                for (int q = 0; q < 4; q++) mma16816(o[q], v[q].x, v[q].y, v[q].z, v[q].w, P.x, P.y);
                mma16816(sm, ONES, ONES, ONES, ONES, P.x, P.y);
#pragma unroll
                for (int q = 0; q < 4; q++) mma16816(o[q], v[4 + q].x, v[4 + q].y, v[4 + q].z, v[4 + q].w, P.z, P.w);
                mma16816(sm, ONES, ONES, ONES, ONES, P.z, P.w);
                const uint32_t row = (l16 >> 4) & 7;
                const uint32_t stg = sb + O_OXS + c * 1024 + row * 128 + (((l16 >> 7) ^ row) << 4);
                const float r0 = rcp_fast(sm[0]), r1 = rcp_fast(sm[1]);
#pragma unroll
                for (int e2 = 0; e2 < 2; e2++)
                    stsm4t(stg ^ (e2 * 64), pack_bf16(o[2 * e2][0] * r0, o[2 * e2][1] * r1), pack_bf16(o[2 * e2][2] * r0, o[2 * e2][3] * r1),
                           pack_bf16(o[2 * e2 + 1][0] * r0, o[2 * e2 + 1][1] * r1), pack_bf16(o[2 * e2 + 1][2] * r0, o[2 * e2 + 1][3] * r1));
                __syncwarp();
            }
            if (s < NSEG - 1) {
                bar_arrive(3, 384);
                if (r < 2) mbar_wait(sb + B_VX + 8 * (s & 1), (s >> 1) & 1);
                mbar_wait(sb + B_VM, s & 1);
                uint4 vx[4];
#pragma unroll
                for (int q = 0; q < 4; q++) vx[q] = lds128(sb + O_VX + s3 * 8192 + c * 2048 + q * 512 + l16);
                const uint4 vm = lds64x2(sb + O_VM + (s & 1) * 2048 + c * 512 + (l16 >> 1));
                if (c == 0) STAMP(s, 13);
                mbar_wait(sb + B_SC, s & 1);
                if (c == 0) STAMP(s, 6);
                float p[10];
                load_scores(p, sb + O_SC, 1280, l16);
                float mx = fmaxf(fmaxf(fmaxf(p[0], p[1]), fmaxf(p[2], p[3])), fmaxf(fmaxf(p[4], p[5]), fmaxf(p[6], p[7])));
                mx = quad_max(fmaxf(mx, fmaxf(p[8], p[9])));
                const float mo = mx * SM_SCALE;
                uint32_t P[5];
#pragma unroll
                for (int n = 0; n < 5; n++) P[n] = pack_bf16(ex2(fmaf(p[2 * n], SM_SCALE, -mo)), ex2(fmaf(p[2 * n + 1], SM_SCALE, -mo)));
                if (c == 0) STAMP(s, 7);
                float o0[4], o1[4], sm[4];
                mma1688_z(sm, ONES, ONES, P[0]);
                mma1688_z(o0, vm.x, vm.y, P[0]);
                mma1688_z(o1, vm.z, vm.w, P[0]);
                mma16816(sm, ONES, ONES, ONES, ONES, P[1], P[2]);
                mma16816(o0, vx[0].x, vx[0].y, vx[0].z, vx[0].w, P[1], P[2]);
                mma16816(o1, vx[2].x, vx[2].y, vx[2].z, vx[2].w, P[1], P[2]);
                mma16816(sm, ONES, ONES, ONES, ONES, P[3], P[4]);
                mma16816(o0, vx[1].x, vx[1].y, vx[1].z, vx[1].w, P[3], P[4]);
                mma16816(o1, vx[3].x, vx[3].y, vx[3].z, vx[3].w, P[3], P[4]);
                const float sig = __uint_as_float((268u << 23) - ebits);
                const float r0 = rcp_fast(sm[0]) * sig, r1 = rcp_fast(sm[1]) * sig;
                stsm4t(sb + O_OF + c * 512 + l16, pack_bf16(o0[0] * r0, o0[1] * r1), pack_bf16(o0[2] * r0, o0[3] * r1),
                       pack_bf16(o1[0] * r0, o1[1] * r1), pack_bf16(o1[2] * r0, o1[3] * r1));
                bar_sync(6, 128);
                uint4 ob[4];
#pragma unroll
                for (int q = 0; q < 4; q++) ob[q] = ldsm4(sb + O_OF + q * 512 + l16);
                float m0[3][4], m1[3][4];
#pragma unroll
                for (int q = 0; q < 4; q++) {
#pragma unroll
                    for (int i = 0; i < 3; i++) {
                        const int k0 = (i * 8 + 2 * q) * 4;
                        if (q == 0) mma16816_z(m0[i], a[k0], a[k0 + 1], a[k0 + 2], a[k0 + 3], ob[q].x, ob[q].y);
                        else mma16816(m0[i], a[k0], a[k0 + 1], a[k0 + 2], a[k0 + 3], ob[q].x, ob[q].y);
                    }
#pragma unroll
                    for (int i = 0; i < 3; i++) {
                        const int k1 = (i * 8 + 2 * q + 1) * 4;
                        if (q == 0) mma16816_z(m1[i], a[k1], a[k1 + 1], a[k1 + 2], a[k1 + 3], ob[q].z, ob[q].w);
                        else mma16816(m1[i], a[k1], a[k1 + 1], a[k1 + 2], a[k1 + 3], ob[q].z, ob[q].w);
                    }
                }
                asm volatile("red.relaxed.gpu.global.add.noftz.v4.f16x2 [%0], {%1,%2,%3,%4};" :: "l"(rptr),
                    "r"(pack_f16(m0[0][0] + m1[0][0], m0[0][2] + m1[0][2])), "r"(pack_f16(m0[1][0] + m1[1][0], m0[1][2] + m1[1][2])),
                    "r"(pack_f16(m0[2][0] + m1[2][0], m0[2][2] + m1[2][2])), "r"(0x3c00u) : "memory");
                asm volatile("red.relaxed.gpu.global.add.noftz.v4.f16x2 [%0], {%1,%2,%3,%4};" :: "l"(rptr + 1024),
                    "r"(pack_f16(m0[0][1] + m1[0][1], m0[0][3] + m1[0][3])), "r"(pack_f16(m0[1][1] + m1[1][1], m0[1][3] + m1[1][3])),
                    "r"(pack_f16(m0[2][1] + m1[2][1], m0[2][3] + m1[2][3])), "r"(0x3c00u) : "memory");
                t_red = clk();
                bar_arrive(5, 384);
                {
                    const uint32_t nb = 8 * ((s + 1) & 1);
                    const uint32_t bar = sb + (c == 0 ? B_SC : c == 1 ? B_VM : c == 2 ? B_VX + nb : B_SX + nb);
                    const uint32_t bytes = c == 0 ? 2560 : c == 1 ? 2048 : c == 2 ? VXBYTES : (r == 0 ? 3072 : 5120);
                    mbar_expect_if(l16 | (uint32_t)(r == 2 && c >= 2), bar, bytes);
                    sts32_if(l16 | c, sb + O_MISC, ebits - (14u << 23));
                }
                if (c == 0) STAMPV(s, 8, t_red);
            } else if (r < 2 && s == NSEG - 1) {
                bar_arrive(3, 384);
                mbar_wait(sb + B_VM, s & 1);
                mbar_wait(sb + B_VX + 8 * (s & 1), (s >> 1) & 1);
            }

            auto finish_x = [&]() {
                const uint4 u0 = lds128(sb + O_OXS + c * 1024 + l16), u1 = lds128(sb + O_OXS + c * 1024 + 512 + l16);
                asm volatile("{\n.reg .pred p;\nsetp.ne.u32 p, %9, 0;\n@p st.global.v4.u32 [%0], {%1,%2,%3,%4};\n@p st.global.v4.u32 [%0+512], {%5,%6,%7,%8};\n}"
                    :: "l"(optr), "r"(u0.x), "r"(u0.y), "r"(u0.z), "r"(u0.w), "r"(u1.x), "r"(u1.y), "r"(u1.z), "r"(u1.w), "r"((uint32_t)(r < 2 && s >= 1)) : "memory");
            };
            if (s >= NSEG - 1) {
                finish_x();
            } else {
                if (c == 0) STAMP(s, 9);
                const char* pbase = rptr + pdelta;
                spin_until(t_red, D_WAIT);
                uint4 v[6];
#pragma unroll
                for (int i = 0; i < 6; i++) v[i] = ldg_relaxed128(pbase + (i >> 1) * 8192 + (i & 1) * 512);
                finish_x();
                int nretry = 0;
                auto hand_over = [&]() -> uint32_t {
                    const uint32_t ok = __all_sync(~0u, (v[0].w & v[1].w & v[2].w & v[3].w & v[4].w & v[5].w) == 0x5000u);
#pragma unroll
                    for (int tau = 0; tau < 3; tau++) {
                        v[2 * tau].x = f16x2_to_bf16x2(v[2 * tau].x); v[2 * tau + 1].x = f16x2_to_bf16x2(v[2 * tau + 1].x);
                        v[2 * tau].y = f16x2_to_bf16x2(v[2 * tau].y); v[2 * tau + 1].y = f16x2_to_bf16x2(v[2 * tau + 1].y);
                        v[2 * tau].z = f16x2_to_bf16x2(v[2 * tau].z); v[2 * tau + 1].z = f16x2_to_bf16x2(v[2 * tau + 1].z);
                        sts128(sb + O_MF + tau * 3072 + (c >> 1) * 1536 + (c & 1) * 512 + l16, v[2 * tau].x, v[2 * tau + 1].x, v[2 * tau].y, v[2 * tau + 1].y);
                        sts64(sb + O_MF + tau * 3072 + (c >> 1) * 1536 + 1024 + (c & 1) * 8 + l16, v[2 * tau].z, v[2 * tau + 1].z);
                    }
                    asm volatile("{\n.reg .pred p;\nsetp.ne.u32 p, %0, 0;\n@p bar.arrive 2, 384;\n}" :: "r"(ok) : "memory");
                    return ok;
                };
                if (!hand_over()) {
                    asm volatile("{\n.reg .pred p, q;\n.reg .u32 n, x;\nmov.u32 n, 0;\n"
                         "R_%=: ld.relaxed.gpu.global.v4.u32 {%0,%1,%2,%3}, [%25];\nld.relaxed.gpu.global.v4.u32 {%4,%5,%6,%7}, [%25+512];\n"
                         "ld.relaxed.gpu.global.v4.u32 {%8,%9,%10,%11}, [%25+8192];\nld.relaxed.gpu.global.v4.u32 {%12,%13,%14,%15}, [%25+8704];\n"
                         "ld.relaxed.gpu.global.v4.u32 {%16,%17,%18,%19}, [%25+16384];\nld.relaxed.gpu.global.v4.u32 {%20,%21,%22,%23}, [%25+16896];\n"
                         "add.u32 %24, %24, 1;\nand.b32 x, %3, %7;\nand.b32 x, x, %11;\nand.b32 x, x, %15;\nand.b32 x, x, %19;\nand.b32 x, x, %23;\n"
                         "setp.eq.u32 p, x, 0x5000;\nvote.sync.all.pred q, p, 0xffffffff;\n@q bra.uni K_%=;\n"
                         "add.u32 n, n, 1;\nsetp.lt.u32 q, n, 2000000;\n@q bra.uni R_%=;\ntrap;\nK_%=:\n}"
                         : "+r"(v[0].x), "+r"(v[0].y), "+r"(v[0].z), "+r"(v[0].w), "+r"(v[1].x), "+r"(v[1].y), "+r"(v[1].z), "+r"(v[1].w),
                           "+r"(v[2].x), "+r"(v[2].y), "+r"(v[2].z), "+r"(v[2].w), "+r"(v[3].x), "+r"(v[3].y), "+r"(v[3].z), "+r"(v[3].w),
                           "+r"(v[4].x), "+r"(v[4].y), "+r"(v[4].z), "+r"(v[4].w), "+r"(v[5].x), "+r"(v[5].y), "+r"(v[5].z), "+r"(v[5].w), "+r"(nretry)
                         : "l"(pbase) : "memory");
                    hand_over();
                }
                if (c == 0) STAMP(s, 12);
                if (c == 0) STAMPV(s, 14, nretry);
                mmax = 0;
                const uint32_t msk = lds32(sb + O_MISC + 12);
#pragma unroll
                for (int i = 0; i < 6; i++) mmax = __vmaxu2(__vmaxu2(mmax, v[i].x & msk), __vmaxu2(v[i].y & msk, v[i].z & msk));
                mmax = max(mmax << 16, mmax & 0xffff0000u);
            }
            s3p = s3;
            rptr += 24576;
            optr += 4096;
        }
        if (r < 2) {
            bar_sync(6, 128);
            if (c == 0)
                asm volatile("{\n.reg .pred p;\nsetp.eq.u32 p, %1, 0;\nfence.acq_rel.gpu;\n@p red.relaxed.gpu.global.add.u32 [%0], 1;\n"
                             "@p red.relaxed.gpu.global.add.u32 [%0+128], 1;\n@p red.relaxed.gpu.global.add.u32 [%0+256], 1;\n}"
                             :: "l"(&g_flag[(61 * 4 + (h >> 3)) * 8]), "r"(l16c) : "memory");
        }
    }
    cluster_sync();
}

__device__ float g_u[SEQ * 2 * DM];
__global__ void naive_gemm1(const __nv_bfloat16* x, const __nv_bfloat16* Bre, const __nv_bfloat16* Bim) {
    int p = blockIdx.x * 64 + threadIdx.x % 64, tk = blockIdx.y * 4 + threadIdx.x / 64;
    float sr = 0, si = 0;
    for (int d = 0; d < DM; d++) { float xv = __bfloat162float(x[tk * DM + d]); sr += xv * __bfloat162float(Bre[p * DM + d]); si += xv * __bfloat162float(Bim[p * DM + d]); }
    g_u[tk * 2 * DM + 2 * p] = sr; g_u[tk * 2 * DM + 2 * p + 1] = si;
}
__global__ void naive_scan(const __nv_bfloat16* Lre, const __nv_bfloat16* Lim, const __nv_bfloat16* logdt) {
    int p = blockIdx.x * 64 + threadIdx.x;
    float dt = __bfloat162float(__float2bfloat16(expf(__bfloat162float(logdt[p]))));
    float lr = __bfloat162float(Lre[p]), li = __bfloat162float(Lim[p]);
    float e = expf(dt * lr), br = e * cosf(dt * li), bi = e * sinf(dt * li);
    float den = lr * lr + li * li;
    float cr = ((br - 1.f) * lr + bi * li) / den, ci = (bi * lr - (br - 1.f) * li) / den;
    float hr = 0, hi = 0;
    for (int tk = 0; tk < SEQ; tk++) {
        float ur = g_u[tk * 2 * DM + 2 * p], ui = g_u[tk * 2 * DM + 2 * p + 1];
        float nr = br * hr - bi * hi + cr * ur - ci * ui, ni = br * hi + bi * hr + cr * ui + ci * ur;
        hr = nr; hi = ni;
        g_u[tk * 2 * DM + 2 * p] = hr; g_u[tk * 2 * DM + 2 * p + 1] = hi;
    }
}
__global__ void naive_gemm2(const __nv_bfloat16* x, const __nv_bfloat16* Cre, const __nv_bfloat16* Cim, const __nv_bfloat16* Dk, float* out) {
    int d = blockIdx.x * 64 + threadIdx.x % 64, tk = blockIdx.y * 4 + threadIdx.x / 64;
    float s = 0;
    for (int p = 0; p < DM; p++) s += g_u[tk * 2 * DM + 2 * p] * __bfloat162float(Cre[d * DM + p]) - g_u[tk * 2 * DM + 2 * p + 1] * __bfloat162float(Cim[d * DM + p]);
    out[tk * 1152 + d] = 2.f * s + __bfloat162float(__float2bfloat16(__bfloat162float(x[tk * DM + d]) * __bfloat162float(Dk[d])));
}
__global__ void naive_wo(const __nv_bfloat16* Wo, float* out) {
    int d = blockIdx.x * 64 + threadIdx.x % 64, tk = blockIdx.y * 4 + threadIdx.x / 64;
    const __nv_bfloat16* ox = reinterpret_cast<const __nv_bfloat16*>(g_ox);
    float s = 0;
    for (int k = 0; k < HD; k++) {
        int hh = k >> 6, e0 = k & 63, e = (e0 & 48) + (e0 & 1) * 8 + ((e0 & 15) >> 1);
        s += __bfloat162float(ox[((size_t)hh * SEQ + tk) * 64 + (((e >> 3) ^ (tk & 7)) << 3) + (e & 7)]) * __bfloat162float(Wo[k * DM + d]);
    }
    out[tk * 1152 + DM + d] = s;
}

typedef CUresult (*EncodeFn)(CUtensorMap*, CUtensorMapDataType, cuuint32_t, void*, const cuuint64_t*, const cuuint64_t*, const cuuint32_t*, const cuuint32_t*,
                             CUtensorMapInterleave, CUtensorMapSwizzle, CUtensorMapL2promotion, CUtensorMapFloatOOBfill);
}

extern "C" void kernel_launch(void* const* d_in, const int* in_sizes, int n_in, void* d_out, int out_size) {
    typedef const __nv_bfloat16* bp;
    bp Ax = (bp)d_in[0], Lre = (bp)d_in[1], Lim = (bp)d_in[2], Bre = (bp)d_in[3], Bim = (bp)d_in[4], Cre = (bp)d_in[5], Cim = (bp)d_in[6],
       logdt = (bp)d_in[7], Dk = (bp)d_in[8], Bx = (bp)d_in[9], mem0 = (bp)d_in[10], Wq = (bp)d_in[11], Wk = (bp)d_in[12], Wv = (bp)d_in[13], Wo = (bp)d_in[14];
    float* out = (float*)d_out;
    static EncodeFn enc = nullptr;
    if (!enc) {
        void* fn = nullptr; cudaDriverEntryPointQueryResult qr;
        cudaGetDriverEntryPoint("cuTensorMapEncodeTiled", &fn, cudaEnableDefault, &qr);
        enc = (EncodeFn)fn;
        cudaFuncSetAttribute(chain_kernel, cudaFuncAttributeMaxDynamicSharedMemorySize, CHAIN_SMEM);
    }
    CUtensorMap tm_x;
    {
        cuuint64_t gd[2] = {DM, SEQ}; cuuint64_t gs[1] = {DM * 2}; cuuint32_t bd[2] = {64, 32}; cuuint32_t es[2] = {1, 1};
        enc(&tm_x, CU_TENSOR_MAP_DATA_TYPE_BFLOAT16, 2, (void*)Bx, gd, gs, bd, es, CU_TENSOR_MAP_INTERLEAVE_NONE, CU_TENSOR_MAP_SWIZZLE_128B,
            CU_TENSOR_MAP_L2_PROMOTION_L2_128B, CU_TENSOR_MAP_FLOAT_OOB_FILL_NONE);
    }
    cudaStream_t st = cudaStreamPerThread;
    chain_kernel<<<96, 384, CHAIN_SMEM, st>>>(tm_x, Bx, mem0, Wq, Wk, Wv, Wo);
    naive_gemm1<<<dim3(9, 512), 256, 0, st>>>(Ax, Bre, Bim);
    naive_scan<<<9, 64, 0, st>>>(Lre, Lim, logdt);
    naive_gemm2<<<dim3(9, 512), 256, 0, st>>>(Ax, Cre, Cim, Dk, out);
    naive_wo<<<dim3(9, 512), 256, 0, st>>>(Wo, out);
}
```

```cpp
#include <cuda_runtime.h>
#include <cuda.h>
#include <cuda_bf16.h>
#include <cuda_fp16.h>
#include <stdint.h>

#define D_WAIT 700
#define VXMODE 1
#define VXBYTES (VXMODE == 2 ? 0 : 8192)
#define XC0 10
#define XC1 4

namespace {

constexpr int DM = 576, NH = 32, SEQ = 2048, NSEG = 64, HD = 4096;

__device__ uint4 g_acc[64 * 96 * 16];
__device__ uint4 g_ox[NH * 2 * SEQ * 8];
__device__ unsigned g_flag[NSEG * 4 * 8];
__device__ unsigned g_gridbar;
__device__ float g_norm[96 * 4];

__device__ __forceinline__ uint32_t smem_u32(const void* p) { return (uint32_t)__cvta_generic_to_shared(p); }
__device__ __forceinline__ uint32_t mapa(uint32_t a, uint32_t r) { uint32_t o; asm("mapa.shared::cluster.u32 %0, %1, %2;" : "=r"(o) : "r"(a), "r"(r)); return o; }
__device__ __forceinline__ uint32_t mapa_v(uint32_t a, uint32_t r) { uint32_t o; asm volatile("mapa.shared::cluster.u32 %0, %1, %2;" : "=r"(o) : "r"(a), "r"(r)); return o; }
__device__ __forceinline__ unsigned clk() { unsigned long long c; asm volatile("mov.u64 %0, %%clock64;" : "=l"(c) :: "memory"); return (unsigned)c; }
__device__ __forceinline__ void mbar_init(uint32_t bar, uint32_t cnt) { asm volatile("mbarrier.init.shared::cta.b64 [%0], %1;" :: "r"(bar), "r"(cnt) : "memory"); }
__device__ __forceinline__ void mbar_expect(uint32_t bar, uint32_t bytes) { asm volatile("mbarrier.arrive.expect_tx.shared::cta.b64 _, [%0], %1;" :: "r"(bar), "r"(bytes) : "memory"); }
__device__ __forceinline__ void mbar_wait(uint32_t bar, uint32_t parity) {
    asm volatile("{\n.reg .pred p;\n.reg .u32 n;\nmov.u32 n, 0;\n"
                 "W_%=: mbarrier.try_wait.parity.shared::cta.b64 p, [%0], %1;\n@p bra.uni D_%=;\n"
                 "add.u32 n, n, 1;\nsetp.lt.u32 p, n, 4000000;\n@p bra.uni W_%=;\ntrap;\nD_%=:\n}" :: "r"(bar), "r"(parity) : "memory");
}
__device__ __forceinline__ void mbar_expect_if(uint32_t z, uint32_t bar, uint32_t bytes) {
    asm volatile("{\n.reg .pred p;\nsetp.eq.u32 p, %2, 0;\n@p mbarrier.arrive.expect_tx.shared::cta.b64 _, [%0], %1;\n}" :: "r"(bar), "r"(bytes), "r"(z) : "memory");
}
__device__ __forceinline__ void mbar_arrive_if(uint32_t z, uint32_t bar) {
    asm volatile("{\n.reg .pred p;\nsetp.eq.u32 p, %1, 0;\n@p mbarrier.arrive.shared::cta.b64 _, [%0];\n}" :: "r"(bar), "r"(z) : "memory");
}
__device__ __forceinline__ void sts32_if(uint32_t z, uint32_t a, uint32_t x) {
    asm volatile("{\n.reg .pred p;\nsetp.eq.u32 p, %2, 0;\n@p st.shared.u32 [%0], %1;\n}" :: "r"(a), "r"(x), "r"(z) : "memory");
}
__device__ __forceinline__ void spin_until(unsigned t0, unsigned d) {
    asm volatile("{\n.reg .pred p;\n.reg .u64 c;\n.reg .u32 lo;\n"
                 "S_%=: mov.u64 c, %%clock64;\ncvt.u32.u64 lo, c;\nsub.u32 lo, lo, %0;\nsetp.lt.u32 p, lo, %1;\n@p bra.uni S_%=;\n}" :: "r"(t0), "r"(d) : "memory");
}
__device__ __forceinline__ void bar_sync(int id, int n) { asm volatile("bar.sync %0, %1;" :: "r"(id), "r"(n) : "memory"); }
__device__ __forceinline__ void bar_sync_sel(int sel, int id) {
    asm volatile("{\n.reg .pred p;\nsetp.eq.u32 p, %0, 0;\n@p bar.sync %1, %3;\n@!p bar.sync %2, %3;\n}" :: "r"(sel), "r"(id), "r"(id + 1), "n"(192) : "memory");
}
__device__ __forceinline__ void bar_arrive(int id, int n) { asm volatile("bar.arrive %0, %1;" :: "r"(id), "r"(n) : "memory"); }
__device__ __forceinline__ void fence_async_smem() { asm volatile("fence.proxy.async.shared::cta;" ::: "memory"); }
__device__ __forceinline__ uint32_t pack_bf16(float lo, float hi) { uint32_t r; asm("cvt.rn.bf16x2.f32 %0, %1, %2;" : "=r"(r) : "f"(hi), "f"(lo)); return r; }
__device__ __forceinline__ uint32_t pack_f16(float lo, float hi) { uint32_t r; asm("cvt.rn.f16x2.f32 %0, %1, %2;" : "=r"(r) : "f"(hi), "f"(lo)); return r; }
__device__ __forceinline__ uint32_t f16x2_to_bf16x2(uint32_t v) { float2 f = __half22float2(*reinterpret_cast<__half2*>(&v)); return pack_bf16(f.x, f.y); }
__device__ __forceinline__ float ex2(float x) { float y; asm("ex2.approx.ftz.f32 %0, %1;" : "=f"(y) : "f"(x)); return y; }
__device__ __forceinline__ float ex2v(float x) { float y; asm volatile("ex2.approx.ftz.f32 %0, %1;" : "=f"(y) : "f"(x)); return y; }
__device__ __forceinline__ uint32_t shl_v(uint32_t a, int n) { return a << n; }
__device__ __forceinline__ uint32_t max3u(uint32_t a, uint32_t b, uint32_t c) { return max(max(a, b), c); }
__device__ __forceinline__ uint4 lds128(uint32_t a) { uint4 v; asm volatile("ld.shared.v4.u32 {%0,%1,%2,%3}, [%4];" : "=r"(v.x), "=r"(v.y), "=r"(v.z), "=r"(v.w) : "r"(a) : "memory"); return v; }
__device__ __forceinline__ float4 lds128f(uint32_t a) { float4 v; asm volatile("ld.shared.v4.f32 {%0,%1,%2,%3}, [%4];" : "=f"(v.x), "=f"(v.y), "=f"(v.z), "=f"(v.w) : "r"(a) : "memory"); return v; }
__device__ __forceinline__ float2 lds64f(uint32_t a) { float2 v; asm volatile("ld.shared.v2.f32 {%0,%1}, [%2];" : "=f"(v.x), "=f"(v.y) : "r"(a) : "memory"); return v; }
__device__ __forceinline__ uint4 lds64x2(uint32_t a) { uint4 v; asm volatile("ld.shared.v2.u32 {%0,%1}, [%4];\nld.shared.v2.u32 {%2,%3}, [%4+256];" : "=r"(v.x), "=r"(v.y), "=r"(v.z), "=r"(v.w) : "r"(a) : "memory"); return v; }
__device__ __forceinline__ uint32_t lds32(uint32_t a) { uint32_t v; asm volatile("ld.shared.u32 %0, [%1];" : "=r"(v) : "r"(a) : "memory"); return v; }
__device__ __forceinline__ void sts128(uint32_t a, uint32_t x, uint32_t y, uint32_t z, uint32_t w) { asm volatile("st.shared.v4.u32 [%0], {%1,%2,%3,%4};" :: "r"(a), "r"(x), "r"(y), "r"(z), "r"(w) : "memory"); }
__device__ __forceinline__ void sts128f(uint32_t a, float x, float y, float z, float w) { asm volatile("st.shared.v4.f32 [%0], {%1,%2,%3,%4};" :: "r"(a), "f"(x), "f"(y), "f"(z), "f"(w) : "memory"); }
__device__ __forceinline__ void sts64(uint32_t a, uint32_t x, uint32_t y) { asm volatile("st.shared.v2.u32 [%0], {%1,%2};" :: "r"(a), "r"(x), "r"(y) : "memory"); }
__device__ __forceinline__ void sts32(uint32_t a, uint32_t x) { asm volatile("st.shared.u32 [%0], %1;" :: "r"(a), "r"(x) : "memory"); }
__device__ __forceinline__ uint4 ldsm4(uint32_t a) { uint4 v; asm volatile("ldmatrix.sync.aligned.m8n8.x4.shared.b16 {%0,%1,%2,%3}, [%4];" : "=r"(v.x), "=r"(v.y), "=r"(v.z), "=r"(v.w) : "r"(a) : "memory"); return v; }
__device__ __forceinline__ void stsm2t(uint32_t a, uint32_t x, uint32_t y) { asm volatile("stmatrix.sync.aligned.m8n8.x2.trans.shared.b16 [%0], {%1,%2};" :: "r"(a), "r"(x), "r"(y) : "memory"); }
__device__ __forceinline__ void stsm4t(uint32_t a, uint32_t x, uint32_t y, uint32_t z, uint32_t w) { asm volatile("stmatrix.sync.aligned.m8n8.x4.trans.shared.b16 [%0], {%1,%2,%3,%4};" :: "r"(a), "r"(x), "r"(y), "r"(z), "r"(w) : "memory"); }
__device__ __forceinline__ void st_async64(uint32_t a, uint32_t x, uint32_t y, uint32_t bar) { asm volatile("st.async.shared::cluster.mbarrier::complete_tx::bytes.v2.b32 [%0], {%1,%2}, [%3];" :: "r"(a), "r"(x), "r"(y), "r"(bar) : "memory"); }
__device__ __forceinline__ void bulk_s2c(uint32_t dst, uint32_t src, uint32_t bytes, uint32_t bar) { asm volatile("cp.async.bulk.shared::cluster.shared::cta.mbarrier::complete_tx::bytes [%0], [%1], %2, [%3];" :: "r"(dst), "r"(src), "r"(bytes), "r"(bar) : "memory"); }
__device__ __forceinline__ void bulk_s2g(void* dst, uint32_t src, uint32_t bytes) { asm volatile("cp.async.bulk.global.shared::cta.bulk_group [%0], [%1], %2;" :: "l"(dst), "r"(src), "r"(bytes) : "memory"); }
__device__ __forceinline__ uint32_t ldg_nc32(const void* p) { uint32_t v; asm volatile("ld.global.nc.L2::128B.u32 %0, [%1];" : "=r"(v) : "l"(p)); return v; }
__device__ __forceinline__ uint4 ldg_relaxed128(const void* p) { uint4 v; asm volatile("ld.relaxed.gpu.global.v4.u32 {%0,%1,%2,%3}, [%4];" : "=r"(v.x), "=r"(v.y), "=r"(v.z), "=r"(v.w) : "l"(p) : "memory"); return v; }
__device__ __forceinline__ void mma16816(float (&d)[4], uint32_t a0, uint32_t a1, uint32_t a2, uint32_t a3, uint32_t b0, uint32_t b1) {
    asm volatile("mma.sync.aligned.m16n8k16.row.col.f32.bf16.bf16.f32 {%0,%1,%2,%3}, {%4,%5,%6,%7}, {%8,%9}, {%0,%1,%2,%3};"
        : "+f"(d[0]), "+f"(d[1]), "+f"(d[2]), "+f"(d[3]) : "r"(a0), "r"(a1), "r"(a2), "r"(a3), "r"(b0), "r"(b1));
}
__device__ __forceinline__ void mma16816_z(float (&d)[4], uint32_t a0, uint32_t a1, uint32_t a2, uint32_t a3, uint32_t b0, uint32_t b1) {
    asm volatile("mma.sync.aligned.m16n8k16.row.col.f32.bf16.bf16.f32 {%0,%1,%2,%3}, {%4,%5,%6,%7}, {%8,%9}, {%10,%10,%10,%10};"
        : "=f"(d[0]), "=f"(d[1]), "=f"(d[2]), "=f"(d[3]) : "r"(a0), "r"(a1), "r"(a2), "r"(a3), "r"(b0), "r"(b1), "f"(0.f));
}
__device__ __forceinline__ void mma1688(float (&d)[4], uint32_t a0, uint32_t a1, uint32_t b0) {
    asm volatile("mma.sync.aligned.m16n8k8.row.col.f32.bf16.bf16.f32 {%0,%1,%2,%3}, {%4,%5}, {%6}, {%0,%1,%2,%3};"
        : "+f"(d[0]), "+f"(d[1]), "+f"(d[2]), "+f"(d[3]) : "r"(a0), "r"(a1), "r"(b0));
}
__device__ __forceinline__ void mma1688_z(float (&d)[4], uint32_t a0, uint32_t a1, uint32_t b0) {
    asm volatile("mma.sync.aligned.m16n8k8.row.col.f32.bf16.bf16.f32 {%0,%1,%2,%3}, {%4,%5}, {%6}, {%7,%7,%7,%7};"
        : "=f"(d[0]), "=f"(d[1]), "=f"(d[2]), "=f"(d[3]) : "r"(a0), "r"(a1), "r"(b0), "f"(0.f));
}
template <int ACC>
__device__ __forceinline__ void wgmma_n32_rs(float (&d)[16], uint32_t a0, uint32_t a1, uint32_t a2, uint32_t a3, uint64_t desc) {
    asm volatile("wgmma.mma_async.sync.aligned.m64n32k16.f32.bf16.bf16 {%0,%1,%2,%3,%4,%5,%6,%7,%8,%9,%10,%11,%12,%13,%14,%15}, {%16,%17,%18,%19}, %20, %21, 1, 1, 0;"
        : "+f"(d[0]), "+f"(d[1]), "+f"(d[2]), "+f"(d[3]), "+f"(d[4]), "+f"(d[5]), "+f"(d[6]), "+f"(d[7]),
          "+f"(d[8]), "+f"(d[9]), "+f"(d[10]), "+f"(d[11]), "+f"(d[12]), "+f"(d[13]), "+f"(d[14]), "+f"(d[15])
        : "r"(a0), "r"(a1), "r"(a2), "r"(a3), "l"(desc), "n"(ACC));
}
template <int ACC>
__device__ __forceinline__ void wgmma_n32_ss(float (&d)[16], uint64_t da, uint64_t db) {
    asm volatile("wgmma.mma_async.sync.aligned.m64n32k16.f32.bf16.bf16 {%0,%1,%2,%3,%4,%5,%6,%7,%8,%9,%10,%11,%12,%13,%14,%15}, %16, %17, %18, 1, 1, 0, 0;"
        : "+f"(d[0]), "+f"(d[1]), "+f"(d[2]), "+f"(d[3]), "+f"(d[4]), "+f"(d[5]), "+f"(d[6]), "+f"(d[7]),
          "+f"(d[8]), "+f"(d[9]), "+f"(d[10]), "+f"(d[11]), "+f"(d[12]), "+f"(d[13]), "+f"(d[14]), "+f"(d[15])
        : "l"(da), "l"(db), "n"(ACC));
}
__device__ __forceinline__ void wg_fence() { asm volatile("wgmma.fence.sync.aligned;" ::: "memory"); }
__device__ __forceinline__ void wg_commit() { asm volatile("wgmma.commit_group.sync.aligned;" ::: "memory"); }
__device__ __forceinline__ void wg_wait0() { asm volatile("wgmma.wait_group.sync.aligned 0;" ::: "memory"); }
__device__ __forceinline__ void cluster_sync() { asm volatile("barrier.cluster.arrive.aligned;\nbarrier.cluster.wait.aligned;" ::: "memory"); }

#define STAMP(s, i) do {} while (0)
#define STAMPV(s, i, v) do {} while (0)

constexpr int XT_BYTES = 36864;
constexpr int O_XT = 0;
constexpr int O_AS = 3 * XT_BYTES;
constexpr int O_AF = O_AS + 16384;
constexpr int O_MF = O_AF + 16384;
constexpr int O_QM = O_MF + 9216;
constexpr int O_KM = O_QM + 2048;
constexpr int O_QKX = O_KM + 2048;
constexpr int O_XP = O_QKX + 8192;
constexpr int O_VX = O_XP + 16384;
constexpr int O_VM = O_VX + 24576;
constexpr int O_SC = O_VM + 4096;
constexpr int O_OF = O_SC + 2560;
constexpr int O_SX = O_OF + 2048;
constexpr int O_PX = O_SX + 10240;
constexpr int O_OXS = O_PX + 1280;
constexpr int O_MISC = O_OXS + 4096;
constexpr int O_BAR = O_MISC + 64;
constexpr int CHAIN_SMEM = O_BAR + 128;
static_assert(CHAIN_SMEM <= 232448, "smem");
constexpr int B_X = O_BAR, B_VX = O_BAR + 24, B_SX = O_BAR + 40, B_SC = O_BAR + 56, B_VM = O_BAR + 64, B_MX = O_BAR + 72;
constexpr float SM_SCALE = 0.08838834764831845f * 1.4426950408889634f;
constexpr uint32_t ONES = 0x3f803f80u;

__device__ __forceinline__ uint32_t opaque(uint32_t v) { uint32_t o; asm volatile("mov.u32 %0, %1;" : "=r"(o) : "r"(v)); return o; }
__device__ __forceinline__ void st_async128(uint32_t a, uint32_t x, uint32_t y, uint32_t z, uint32_t w, uint32_t bar) {
    asm volatile("st.async.shared::cluster.mbarrier::complete_tx::bytes.v4.b32 [%0], {%1,%2,%3,%4}, [%5];" :: "r"(a), "r"(x), "r"(y), "r"(z), "r"(w), "r"(bar) : "memory");
}
__device__ __forceinline__ void tma_x_tile(uint32_t sb, const CUtensorMap* tm, int r, int j, int slot) {
    asm volatile("{\n.reg .pred p;\nelect.sync _|p, 0xffffffff;\n"
        "@p mbarrier.arrive.expect_tx.shared::cta.b64 _, [%2], 36864;\n"
        "@p cp.async.bulk.tensor.2d.shared::cluster.global.mbarrier::complete_tx::bytes.multicast::cluster [%0], [%1, {%3, %4}], [%2], %7;\n"
        "@p cp.async.bulk.tensor.2d.shared::cluster.global.mbarrier::complete_tx::bytes.multicast::cluster [%0+4096], [%1, {%5, %4}], [%2], %7;\n"
        "@p cp.async.bulk.tensor.2d.shared::cluster.global.mbarrier::complete_tx::bytes.multicast::cluster [%0+8192], [%1, {%6, %4}], [%2], %7;\n}"
        :: "r"(sb + O_XT + slot * XT_BYTES + 3 * r * 4096), "l"(tm), "r"(sb + B_X + 8 * slot), "r"(192 * r), "r"(j * 32), "r"(192 * r + 64), "r"(192 * r + 128),
           "h"((unsigned short)7) : "memory");
}
__device__ __forceinline__ float quad_max(float v) {
    const float a = __shfl_xor_sync(~0u, v, 1), b = __shfl_xor_sync(~0u, v, 2), c = __shfl_xor_sync(~0u, v, 3);
    return fmaxf(fmaxf(v, a), fmaxf(b, c));
}
__device__ __forceinline__ void load_scores(float (&p)[10], uint32_t base, uint32_t stride, uint32_t l16) {
    const float4 a0 = lds128f(base + l16), b0 = lds128f(base + stride + l16);
    const float4 a1 = lds128f(base + 512 + l16), b1 = lds128f(base + stride + 512 + l16);
    const float2 a2 = lds64f(base + 1024 + (l16 >> 1)), b2 = lds64f(base + stride + 1024 + (l16 >> 1));
    p[0] = a2.x + b2.x; p[1] = a2.y + b2.y;
    p[2] = a0.x + b0.x; p[3] = a0.y + b0.y; p[4] = a0.z + b0.z; p[5] = a0.w + b0.w;
    p[6] = a1.x + b1.x; p[7] = a1.y + b1.y; p[8] = a1.z + b1.z; p[9] = a1.w + b1.w;
}
__device__ __forceinline__ float rcp_fast(float x) { float y; asm("rcp.approx.ftz.f32 %0, %1;" : "=f"(y) : "f"(x)); return y; }

__global__ void __cluster_dims__(3, 1, 1) __launch_bounds__(384, 1)
chain_kernel(const __grid_constant__ CUtensorMap tm_x,
             const __nv_bfloat16* __restrict__ x, const __nv_bfloat16* __restrict__ mem0,
             const __nv_bfloat16* __restrict__ Wq, const __nv_bfloat16* __restrict__ Wk,
             const __nv_bfloat16* __restrict__ Wv, const __nv_bfloat16* __restrict__ Wo) {
    extern __shared__ __align__(1024) uint8_t smem_raw[];
    const uint32_t sb = smem_u32(smem_raw);
    const int lane = threadIdx.x & 31;
    const int warp = __shfl_sync(~0u, threadIdx.x >> 5, 0);
    const int wg = warp >> 2, w = warp & 3;
    const int h = blockIdx.x / 3, r = blockIdx.x - 3 * h;

    if (threadIdx.x == 0) {
        if (sb & 1023u) __trap();
        for (int i = 0; i < 9; i++) mbar_init(sb + O_BAR + 8 * i, 1);
        mbar_init(sb + B_MX, 4);
        asm volatile("fence.mbarrier_init.release.cluster;" ::: "memory");
    }
    if (blockIdx.x == 0) {
        for (int i = threadIdx.x; i < NSEG * 4 * 8; i += 384) g_flag[i] = 0;
        __threadfence();
    }
    __syncthreads();
    cluster_sync();
    asm volatile("griddepcontrol.launch_dependents;" ::: "memory");
    const uint32_t l16c = __shfl_sync(~0u, lane * 16, lane);

    if (wg < 2) {
#define KS(u) ((u) < 8 ? ((u) >> 1) + 4 * ((u) & 1) : (u) < 12 ? (u) : (u) < 20 ? 12 + (((u) - 12) >> 1) + 4 * ((u) & 1) : (u) < 24 ? (u) : (u) + 8)
        asm volatile("setmaxnreg.inc.sync.aligned.u32 176;");
        const int kt = warp < 3 ? warp : (warp < 5 ? warp - 3 : (warp == 5 ? 0 : 2));
        const int mt = (warp == 5 || warp == 7) ? 0 : 1;
        uint32_t a[144];
        uint32_t adr1, adr_q, adr_k;
        {
            const int g = lane >> 2, t = lane & 3;
#pragma unroll
            for (int tl = 0; tl < 2; tl++) {
                const int tile = tl ? wg : (wg ^ 1);
                const __nv_bfloat16* W = (r < 2) ? (tile == 0 ? Wq : Wk) : Wv;
                const int col = h * 128 + ((r < 2) ? 64 * r : 64 * tile) + 16 * w + 2 * g;
                const __nv_bfloat16* p = W + (size_t)(2 * t) * HD + col;
                const __nv_bfloat16* ps = p + (size_t)(384 * wg) * HD;
#pragma unroll
                for (int u = 0; u < (tl ? 28 : 8); u++) {
                    const __nv_bfloat16* q = (u < 8 ? ps : p) + (size_t)(16 * KS(u)) * HD;
                    a[32 * tl + 4 * u + 0] = ldg_nc32(q);
                    a[32 * tl + 4 * u + 1] = ldg_nc32(q + HD);
                    a[32 * tl + 4 * u + 2] = ldg_nc32(q + 8 * HD);
                    a[32 * tl + 4 * u + 3] = ldg_nc32(q + 9 * HD);
                }
            }
#pragma unroll
            for (int kk = 0; kk < 72; kk++) {
                uint32_t w0 = a[2 * kk], w1 = a[2 * kk + 1];
                a[2 * kk] = __byte_perm(w0, w1, 0x5410);
                a[2 * kk + 1] = __byte_perm(w0, w1, 0x7632);
            }
            float vmax = 0.f;
#pragma unroll
            for (int tl = 0; tl < 2; tl++) {
                float s0 = 0.f, s1 = 0.f;
#pragma unroll
                for (int kk = 16 * tl; kk < (tl ? 72 : 16); kk++) {
                    s0 += fabsf(__uint_as_float(a[2 * kk] << 16)) + fabsf(__uint_as_float(a[2 * kk] & 0xffff0000u));
                    s1 += fabsf(__uint_as_float(a[2 * kk + 1] << 16)) + fabsf(__uint_as_float(a[2 * kk + 1] & 0xffff0000u));
                }
                s0 += __shfl_xor_sync(~0u, s0, 1); s0 += __shfl_xor_sync(~0u, s0, 2);
                s1 += __shfl_xor_sync(~0u, s1, 1); s1 += __shfl_xor_sync(~0u, s1, 2);
                vmax = fmaxf(vmax, fmaxf(s0, s1));
            }
            uint32_t mx = __reduce_max_sync(~0u, __float_as_uint(2.f * vmax));
            sts32_if(lane, sb + O_MISC + 32 + 4 * warp, mx);
            bar_arrive(7, 384);
            const uint32_t as = sb + O_AS + wg * 8192 + (16 * w + g) * 128 + t * 4;
#pragma unroll
            for (int kk = 0; kk < 4; kk++) {
                sts32(as + (((2 * kk) ^ g) << 4), a[32 + 4 * kk]);
                sts32(as + 1024 + (((2 * kk) ^ g) << 4), a[32 + 4 * kk + 1]);
                sts32(as + (((2 * kk + 1) ^ g) << 4), a[32 + 4 * kk + 2]);
                sts32(as + 1024 + (((2 * kk + 1) ^ g) << 4), a[32 + 4 * kk + 3]);
                sts128(sb + O_AF + warp * 2048 + kk * 512 + lane * 16, a[32 + 4 * kk], a[32 + 4 * kk + 1], a[32 + 4 * kk + 2], a[32 + 4 * kk + 3]);
            }
            fence_async_smem();
            bar_sync(1, 256);
            const uint32_t l = lane * 16;
            const int mi = lane >> 3, isk = (mi >> 1) ? wg : (wg ^ 1);
            adr1 = (r == 2) ? (sb + O_VM + warp * 256 + (l >> 1))
                            : (isk ? (sb + O_KM + w * 512 + wg * 256 + (mi & 1) * 128 + (l & 127))
                                   : (sb + O_QM + w * 512 + (mi & 1) * 256 + wg * 128 + (l & 127)));
            adr1 = __shfl_sync(~0u, adr1, lane);
            const uint32_t qa = sb + (warp < 3 ? O_QM : O_QKX + mt * 2048) + l;
            const uint32_t ka = sb + (kt == 2 ? O_KM : O_QKX + 4096 + kt * 2048) + l;
            adr_q = __shfl_sync(~0u, qa, lane);
            adr_k = __shfl_sync(~0u, ka, lane);
        }
        int s3 = 2;
#pragma unroll 1
        for (int s = -1; s < NSEG; s++) {
            const uint32_t l16 = opaque(l16c);
            s3 = (s3 == 2) ? 0 : s3 + 1;
            if (s < NSEG - 1) mbar_wait(sb + B_X + 8 * s3, ((s + 1) / 3) & 1);
            const uint64_t desc0 = (uint64_t)(((sb + O_XT + s3 * XT_BYTES) & 0x3FFFF) >> 4) | (1ull << 16) | (64ull << 32) | (1ull << 62);
            auto x_softmax = [&]() {
                mbar_wait(sb + B_SX + 8 * (s & 1), (s >> 1) & 1);
                const int q0 = 16 * r + 8 * w + 8 + (int)(l16 >> 6) - (int)((l16 >> 3) & 6);
                float px[10];
                load_scores(px, sb + O_SX + (s & 1) * 5120 + w * 1280, 2560, l16);
#pragma unroll
                for (int n = 1; n < 5; n++) {
                    if (8 * n > q0) px[2 * n] = -INFINITY;
                    if (8 * n + 1 > q0) px[2 * n + 1] = -INFINITY;
                }
                float mx = fmaxf(fmaxf(fmaxf(px[0], px[1]), fmaxf(px[2], px[3])), fmaxf(fmaxf(px[4], px[5]), fmaxf(px[6], px[7])));
                mx = quad_max(fmaxf(mx, fmaxf(px[8], px[9])));
                const float mo = mx * SM_SCALE;
                uint32_t P[5];
#pragma unroll
                for (int n = 0; n < 5; n++) P[n] = pack_bf16(ex2(fmaf(px[2 * n], SM_SCALE, -mo)), ex2(fmaf(px[2 * n + 1], SM_SCALE, -mo)));
                sts128(sb + O_PX + w * 640 + l16, P[1], P[2], P[3], P[4]);
                sts32(sb + O_PX + w * 640 + 512 + (l16 >> 2), P[0]);
            };
            if (s >= 0) {
#pragma unroll
                for (int kk = 0; kk < 4; kk++) {
                    const uint4 v = lds128(sb + O_AF + warp * 2048 + kk * 512 + l16);
                    a[32 + 4 * kk] = v.x; a[32 + 4 * kk + 1] = v.y; a[32 + 4 * kk + 2] = v.z; a[32 + 4 * kk + 3] = v.w;
                }
                float co[4], cw[3][4];
                uint4 b[14];
                float inv;
#define GORD(i) ((i) == 0 ? 0 : (i) == 1 ? 1 : (i) == 5 ? 2 : (i) == 9 ? 3 : (i) < 5 ? (i) + 2 : (i) < 9 ? (i) + 1 : (i))
                auto qkv_mma = [&](int i) {
                    const int gi = GORD(i), u = 8 * gi, n0 = 2 * i, n1 = 2 * i + 1;
                    if (gi < 4) {
                        if (i == 0) mma16816_z(co, a[u], a[u + 1], a[u + 2], a[u + 3], b[0].x, b[0].y);
                        else mma16816(co, a[u], a[u + 1], a[u + 2], a[u + 3], b[i].x, b[i].y);
                    }
                    if (n0 < 3) mma16816_z(cw[n0 % 3], a[32 + u], a[32 + u + 1], a[32 + u + 2], a[32 + u + 3], b[i].x, b[i].y);
                    else mma16816(cw[n0 % 3], a[32 + u], a[32 + u + 1], a[32 + u + 2], a[32 + u + 3], b[i].x, b[i].y);
                    if (n1 < 3) mma16816_z(cw[n1 % 3], a[32 + u + 4], a[32 + u + 5], a[32 + u + 6], a[32 + u + 7], b[i].z, b[i].w);
                    else mma16816(cw[n1 % 3], a[32 + u + 4], a[32 + u + 5], a[32 + u + 6], a[32 + u + 7], b[i].z, b[i].w);
                    if (gi < 4) mma16816(co, a[u + 4], a[u + 5], a[u + 6], a[u + 7], b[i].z, b[i].w);
                };
                const uint32_t mf = sb + O_MF + l16, mfs = mf + wg * 6144;
                bar_sync(2, 384);
                if (warp == 0) STAMP(s, 0);
#pragma unroll
                for (int i = 0; i < 17; i++) {
                    if (i < 14) b[i] = GORD(i) < 4 ? lds128(mfs + GORD(i) * 512) : lds128(mf + (GORD(i) < 12 ? GORD(i) : GORD(i) + 4) * 512);
                    if (i == 14) inv = __uint_as_float(lds32(sb + O_MISC));
                    if (i >= 3) qkv_mma(i - 3);
                }
#pragma unroll
                for (int i = 0; i < 4; i++) cw[0][i] += cw[1][i] + cw[2][i];
                if (r < 2) {
                    bar_arrive(9, 384);
                    stsm4t(adr1, pack_bf16(co[0] * inv, co[1] * inv), pack_bf16(co[2] * inv, co[3] * inv),
                                 pack_bf16(cw[0][0] * inv, cw[0][1] * inv), pack_bf16(cw[0][2] * inv, cw[0][3] * inv));
                    if (warp == 0) STAMP(s, 1);
                    asm volatile("{\n.reg .pred p;\nsetp.ge.u32 p, %0, 3;\n@p bar.arrive 1, 256;\n}" :: "r"(warp) : "memory");
                    const uint32_t doff = kt * 512 + (kt == 2 ? (l16 >> 1) : l16);
                    auto scores = [&](float (&s0)[4], float (&s1)[4], const uint4 (&q)[4], const uint4 (&k)[4]) {
                        float t0[4], t1[4];
                        mma16816_z(s0, q[0].x, q[0].y, q[0].z, q[0].w, k[0].x, k[0].y);
                        mma16816_z(s1, q[0].x, q[0].y, q[0].z, q[0].w, k[0].z, k[0].w);
                        mma16816_z(t0, q[1].x, q[1].y, q[1].z, q[1].w, k[1].x, k[1].y);
                        mma16816_z(t1, q[1].x, q[1].y, q[1].z, q[1].w, k[1].z, k[1].w);
                        mma16816(s0, q[2].x, q[2].y, q[2].z, q[2].w, k[2].x, k[2].y);
                        mma16816(s1, q[2].x, q[2].y, q[2].z, q[2].w, k[2].z, k[2].w);
                        mma16816(t0, q[3].x, q[3].y, q[3].z, q[3].w, k[3].x, k[3].y);
                        mma16816(t1, q[3].x, q[3].y, q[3].z, q[3].w, k[3].z, k[3].w);
#pragma unroll
                        for (int i = 0; i < 4; i++) { s0[i] += t0[i]; s1[i] += t1[i]; }
                    };
                    if (warp < 3) {
                        float s0[4], s1[4];
                        uint4 q[4], k[4];
#pragma unroll
                        for (int i = 0; i < 4; i++) k[i] = ldsm4(adr_k + i * 512);
                        bar_sync(1, 256);
#pragma unroll
                        for (int i = 0; i < 4; i++) q[i] = ldsm4(adr_q + i * 512);
                        if (warp == 2) {
#pragma unroll
                            for (int i = 0; i < 4; i++) k[i] = ldsm4(adr_k + i * 512);
                        }
                        bar_arrive(8, 256);
                        scores(s0, s1, q, k);
                        const uint32_t dst = sb + O_SC + r * 1280 + doff;
                        const float v0 = s0[0] + s0[2], v1 = s0[1] + s0[3], v2 = s1[0] + s1[2], v3 = s1[1] + s1[3];
                        if (warp < 2) {
                            st_async128(mapa(dst, 2), __float_as_uint(v0), __float_as_uint(v1), __float_as_uint(v2), __float_as_uint(v3), mapa(sb + B_SC, 2));
                            st_async128(mapa(dst, r ^ 1), __float_as_uint(v0), __float_as_uint(v1), __float_as_uint(v2), __float_as_uint(v3), mapa(sb + B_SC, r ^ 1));
                            st_async128(mapa(dst, r), __float_as_uint(v0), __float_as_uint(v1), __float_as_uint(v2), __float_as_uint(v3), mapa(sb + B_SC, r));
                        } else {
                            st_async64(mapa(dst, 2), __float_as_uint(v0 + v2), __float_as_uint(v1 + v3), mapa(sb + B_SC, 2));
                            st_async64(mapa(dst, r ^ 1), __float_as_uint(v0 + v2), __float_as_uint(v1 + v3), mapa(sb + B_SC, r ^ 1));
                            st_async64(mapa(dst, r), __float_as_uint(v0 + v2), __float_as_uint(v1 + v3), mapa(sb + B_SC, r));
                            STAMP(s, 2);
                        }
                        bar_arrive(4, 256);
                    } else {
                        float s0[4], s1[4];
                        uint4 q[4], k[4];
                        bar_sync(8, 256);
#pragma unroll
                        for (int i = 0; i < 4; i++) { q[i] = ldsm4(adr_q + i * 512); k[i] = ldsm4(adr_k + i * 512); }
                        scores(s0, s1, q, k);
                        const uint32_t dx = mapa(sb + O_SX + (s & 1) * 5120 + r * 2560 + doff, mt), bx = mapa(sb + B_SX + 8 * (s & 1), mt);
                        bar_sync(4, 256);
                        if (kt != 2) {
                            st_async128(dx, __float_as_uint(s0[0]), __float_as_uint(s0[1]), __float_as_uint(s1[0]), __float_as_uint(s1[1]), bx);
                            st_async128(dx + 1280, __float_as_uint(s0[2]), __float_as_uint(s0[3]), __float_as_uint(s1[2]), __float_as_uint(s1[3]), bx);
                        } else {
                            st_async64(dx, __float_as_uint(s0[0] + s1[0]), __float_as_uint(s0[1] + s1[1]), bx);
                            st_async64(dx + 1280, __float_as_uint(s0[2] + s1[2]), __float_as_uint(s0[3] + s1[3]), bx);
                        }
                    }
                } else {
                    if (s < NSEG - 1) bar_arrive(14, 384);
                    sts128f(sb + O_XP + warp * 512 + l16, co[0], co[1], co[2], co[3]);
                    bar_sync(8 + w, 64);
                    const float4 o = lds128f(sb + O_XP + (warp ^ 4) * 512 + l16);
                    const uint32_t X0 = pack_bf16((cw[0][0] + o.x) * inv, (cw[0][1] + o.y) * inv);
                    const uint32_t X1 = pack_bf16((cw[0][2] + o.z) * inv, (cw[0][3] + o.w) * inv);
                    if (warp == 0) STAMP(s, 1);
                    const uint32_t dst = adr1 + (s & 1) * 2048;
                    st_async64(mapa(dst, 0), X0, X1, mapa(sb + B_VM, 0));
                    st_async64(mapa(dst, 1), X0, X1, mapa(sb + B_VM, 1));
                    st_async64(mapa(dst, 2), X0, X1, mapa(sb + B_VM, 2));
                    if (warp == 0) STAMP(s, 2);
                }
            }
            if (s == NSEG - 1 && r < 2) {
                bar_sync(3, 384);
                if (wg == 1 && w < 2) x_softmax();
                bar_arrive(9, 384);
            }
            if (s < NSEG - 1) {
                const int j = s + 1;
#define XDESC(u) (((u) < 8 ? descs : desc0) + (uint64_t)(((KS(u) >> 2) * 4096 + (KS(u) & 3) * 32) >> 4))
                const uint64_t descs = desc0 + (uint64_t)(wg * (6 * 4096 >> 4));
                float d[16];
                if (s >= 0) bar_sync(3, 384);
                wg_fence();
#pragma unroll
                for (int u = 0; u < 8; u++) {
                    if (u == 0) wgmma_n32_rs<0>(d, a[0], a[1], a[2], a[3], XDESC(0));
                    else wgmma_n32_rs<1>(d, a[4 * u], a[4 * u + 1], a[4 * u + 2], a[4 * u + 3], XDESC(u));
                }
                wg_commit();
                wg_wait0();
                if (warp == 0) STAMP(s, 15);
                if (s >= 0) mbar_wait(sb + B_SX + 8 * (r < 2 ? (s & 1) : 2), r < 2 ? (s >> 1) & 1 : s & 1);
#pragma unroll
                for (int q = 0; q < 4; q++) sts128f(sb + O_XP + warp * 2048 + q * 512 + l16, d[4 * q], d[4 * q + 1], d[4 * q + 2], d[4 * q + 3]);
                bar_sync(12, 256);
#pragma unroll
                for (int q = 0; q < 4; q++) {
                    const float4 o = lds128f(sb + O_XP + (warp ^ 4) * 2048 + q * 512 + l16);
                    d[4 * q] = o.x; d[4 * q + 1] = o.y; d[4 * q + 2] = o.z; d[4 * q + 3] = o.w;
                }
                if (s >= 0) {
                    if (wg == 1) {
                        if (w < 2) {
                            if (r < 2) x_softmax();
                        } else if (w == 2) {
                            if (r < 2 && (s & 3) == 1 && s >= 5)
                                asm volatile("{\n.reg .pred p;\nsetp.eq.u32 p, %1, 0;\n@p red.release.gpu.global.inc.u32 [%0], 0x7fffffff;\n}"
                                             :: "l"(&g_flag[((s - 2) * 4 + (h >> 3)) * 8]), "r"(l16) : "memory");
                        } else if (s + 2 < NSEG) {
                            tma_x_tile(sb, &tm_x, r, s + 2, s3 == 2 ? 0 : s3 + 1);
                        }
                        bar_sync(13, 256);
                    } else {
                        bar_sync(5, 256);
                    }
                }
                const uint64_t da0 = (uint64_t)(((sb + O_AS + wg * 8192) & 0x3FFFF) >> 4) | (1ull << 16) | (64ull << 32) | (1ull << 62);
                wg_fence();
#pragma unroll
                for (int u = 0; u < 4; u++) wgmma_n32_ss<1>(d, da0 + 2 * u, XDESC(u));
#pragma unroll
                for (int u = 4; u < 28; u++) wgmma_n32_rs<1>(d, a[32 + 4 * u], a[32 + 4 * u + 1], a[32 + 4 * u + 2], a[32 + 4 * u + 3], XDESC(u));
                wg_commit();
                wg_wait0();
                if (warp == 4) STAMP(s, 3);
                uint32_t e[8];
#pragma unroll
                for (int i = 0; i < 8; i++) e[i] = pack_bf16(d[2 * i], d[2 * i + 1]);
                if (r < 2) {
                    const uint32_t base = sb + O_QKX + wg * 4096 + w * 512 + l16;
                    stsm4t(base, e[0], wg ? e[1] : e[2], wg ? e[2] : e[1], e[3]);
                    stsm4t(base + 2048, e[4], wg ? e[5] : e[6], wg ? e[6] : e[5], e[7]);
                } else {
                    const uint32_t base = sb + O_VX + s3 * 8192 + warp * 1024 + l16;
                    sts128(base, e[0], e[1], e[2], e[3]);
                    sts128(base + 512, e[4], e[5], e[6], e[7]);
                    const uint32_t bar = sb + B_VX + 8 * (j & 1);
                    fence_async_smem();
                    __syncwarp();
                    const uint32_t src = sb + O_VX + s3 * 8192 + warp * 1024;
                    asm volatile("{\n.reg .pred p;\nelect.sync _|p, 0xffffffff;\n"
                        "@p cp.async.bulk.shared::cluster.shared::cta.mbarrier::complete_tx::bytes [%0], [%2], 1024, [%3];\n"
                        "@p cp.async.bulk.shared::cluster.shared::cta.mbarrier::complete_tx::bytes [%1], [%2], 1024, [%4];\n}"
                        :: "r"(mapa(src, 0)), "r"(mapa(src, 1)), "r"(src), "r"(mapa(bar, 0)), "r"(mapa(bar, 1)) : "memory");
                }
                if (warp == 7) STAMP(s, 4);
            }
        }
    } else {
        asm volatile("setmaxnreg.dec.sync.aligned.u32 152;");
        const int c = w;
        uint32_t a[96];
        uint32_t mmax = 0;
        {
            const int g = lane >> 2, t = lane & 3, t2 = threadIdx.x - 256;
            if (c == 0) {
                tma_x_tile(sb, &tm_x, r, 0, 0);
                tma_x_tile(sb, &tm_x, r, 1, 1);
                mbar_expect_if(lane, sb + B_SC, 2560);
                mbar_expect_if(lane, sb + B_VM, 2048);
                if (r < 2) { mbar_expect_if(lane, sb + B_VX, VXBYTES); mbar_expect_if(lane, sb + B_SX, r == 0 ? 3072 : 5120); }
                sts32_if(lane, sb + O_MISC, __float_as_uint(1.0f));
                sts32_if(lane, sb + O_MISC + 12, 0x7fff7fffu);
            }
#pragma unroll
            for (int i = 0; i < 4; i++) g_acc[(blockIdx.x * 64 + i * 16 + (t2 >> 3)) * 16 + (t2 & 7)] = make_uint4(0, 0, 0, 0);
#pragma unroll
            for (int tau = 0; tau < 3; tau++) {
                uint32_t v[6];
#pragma unroll
                for (int i = 0; i < 3; i++) {
                    const uint32_t* p = reinterpret_cast<const uint32_t*>(mem0 + g * DM + 16 * (12 * tau + 4 * i + c) + 2 * t);
                    v[2 * i] = __ldg(p); v[2 * i + 1] = __ldg(p + 4);
                    mmax = __vmaxu2(mmax, __vmaxu2(v[2 * i] & 0x7fff7fffu, v[2 * i + 1] & 0x7fff7fffu));
                }
                sts128(sb + O_MF + tau * 3072 + c * 512 + lane * 16, v[0], v[1], v[2], v[3]);
                sts64(sb + O_MF + tau * 3072 + 2048 + (c >> 1) * 512 + lane * 16 + (c & 1) * 8, v[4], v[5]);
            }
            mmax = max(mmax << 16, mmax & 0xffff0000u);
            bar_arrive(2, 384);
            uint32_t xm = 0;
            const uint4* xp = reinterpret_cast<const uint4*>(x) + blockIdx.x * 1536 + t2;
#pragma unroll
            for (int i = 0; i < 12; i++) {
                uint4 v = __ldg(xp + i * 128);
                xm = __vmaxu2(xm, __vmaxu2(__vmaxu2(v.x & 0x7fff7fffu, v.y & 0x7fff7fffu), __vmaxu2(v.z & 0x7fff7fffu, v.w & 0x7fff7fffu)));
            }
            xm = __reduce_max_sync(~0u, max(xm << 16, xm & 0xffff0000u));

            const __nv_bfloat16* p = Wo + (size_t)(h * 128 + 4 * t) * DM + 192 * r + 16 * c + 2 * g;
#pragma unroll
            for (int i = 0; i < 3; i++)
#pragma unroll
                for (int eb = 0; eb < 8; eb++)
#pragma unroll
                    for (int j = 0; j < 4; j++) a[(i * 8 + eb) * 4 + j] = ldg_nc32(p + (16 * eb + ((j & 1) * 2 + (j >> 1))) * DM + 64 * i);
#pragma unroll
            for (int kk = 0; kk < 48; kk++) {
                uint32_t w0 = a[2 * kk], w1 = a[2 * kk + 1];
                a[2 * kk] = __byte_perm(w0, w1, 0x5410);
                a[2 * kk + 1] = __byte_perm(w0, w1, 0x7632);
            }
            float wmax = 0.f;
#pragma unroll
            for (int i = 0; i < 3; i++) {
                float s0 = 0.f, s1 = 0.f;
#pragma unroll
                for (int kk = 16 * i; kk < 16 * i + 16; kk++) {
                    s0 += fabsf(__uint_as_float(a[2 * kk] << 16)) + fabsf(__uint_as_float(a[2 * kk] & 0xffff0000u));
                    s1 += fabsf(__uint_as_float(a[2 * kk + 1] << 16)) + fabsf(__uint_as_float(a[2 * kk + 1] & 0xffff0000u));
                }
                s0 += __shfl_xor_sync(~0u, s0, 1); s0 += __shfl_xor_sync(~0u, s0, 2);
                s1 += __shfl_xor_sync(~0u, s1, 1); s1 += __shfl_xor_sync(~0u, s1, 2);
                wmax = fmaxf(wmax, fmaxf(s0, s1));
            }
            uint32_t wm = __reduce_max_sync(~0u, __float_as_uint(wmax));
            sts32_if(lane, sb + O_OF + 4 * c, wm); sts32_if(lane, sb + O_OF + 16 + 4 * c, xm);
            __threadfence();
            bar_sync(7, 384);
            if (c == 0) {
                const uint4 wq = lds128(sb + O_OF), xq = lds128(sb + O_OF + 16), v0 = lds128(sb + O_MISC + 32), v1 = lds128(sb + O_MISC + 48);
                const uint32_t w1 = max(max(wq.x, wq.y), max(wq.z, wq.w)), x1 = max(max(xq.x, xq.y), max(xq.z, xq.w));
                const uint32_t vv = (r < 2) ? 0u : max(max(max(v0.x, v0.y), max(v0.z, v0.w)), max(max(v1.x, v1.y), max(v1.z, v1.w)));
                unsigned old = 0;
                asm volatile("{\n.reg .pred p;\nsetp.eq.u32 p, %6, 0;\n@p st.global.v4.u32 [%1], {%2,%3,%4,%4};\nfence.acq_rel.gpu;\n@p atom.relaxed.gpu.global.add.u32 %0, [%5], 1;\n}"
                             : "+r"(old) : "l"(&g_norm[blockIdx.x * 4]), "r"(w1), "r"(vv), "r"(x1), "l"(&g_gridbar), "r"(lane) : "memory");
                old = __shfl_sync(~0u, old, 0);
                const unsigned target = (old / 96u + 1u) * 96u;
                asm volatile("{\n.reg .pred p;\n.reg .u32 n, v;\nmov.u32 n, 0;\n"
                             "G_%=: ld.acquire.gpu.global.u32 v, [%0];\nsub.u32 v, v, %1;\nsetp.ge.s32 p, v, 0;\n@p bra.uni E_%=;\n"
                             "add.u32 n, n, 1;\nsetp.lt.u32 p, n, 4000000;\n@p bra.uni G_%=;\ntrap;\nE_%=:\n}" :: "l"(&g_gridbar), "r"(target) : "memory");
                uint4 n0 = ldg_relaxed128(&g_norm[lane * 4]), n1 = ldg_relaxed128(&g_norm[(lane + 32) * 4]), n2 = ldg_relaxed128(&g_norm[(lane + 64) * 4]);
                const float fw = __uint_as_float(__reduce_max_sync(~0u, max(n0.x, max(n1.x, n2.x))));
                const float fv = __uint_as_float(__reduce_max_sync(~0u, max(n0.y, max(n1.y, n2.y))));
                const float xmax = __uint_as_float(__reduce_max_sync(~0u, max(n0.z, max(n1.z, n2.z))));
                const float G = 36.f * fw * fv;
                sts32_if(lane, sb + O_MISC + 4, __float_as_uint(G)); sts32_if(lane, sb + O_MISC + 8, __float_as_uint(G * xmax));
            }
        }
        bar_sync(6, 128);
        int s3p = 2;
        char* rptr; int pdelta; char* optr;
        {
            const uint32_t roff = (r * 4 + c) * 2048 + (lane >> 4) * 512 + (lane & 2) * 128 + (lane & 1) * 64 + (lane & 12) * 4;
            const uint32_t poff = c * 2048 + (lane & 4) * 256 + (lane >> 4) * 256 + (lane & 8) * 8 + (lane & 3) * 16;
            rptr = reinterpret_cast<char*>(g_acc) + roff;
            pdelta = __shfl_sync(~0u, (int)poff - (int)roff, lane);
            optr = reinterpret_cast<char*>(g_ox) + ((size_t)(h * 2 + (c >> 1)) * SEQ + 16 * r + 8 * (c & 1)) * 128 + lane * 16 - 4096;
        }
#pragma unroll 1
        for (int s = 0; s <= NSEG; s++) {
            const uint32_t l16 = opaque(l16c);
            const int s3 = (s3p == 2) ? 0 : s3p + 1;
            unsigned t_red = 0;
            uint32_t ebits = 0;
            if (s < NSEG - 1) {
                sts32_if(l16, sb + O_MISC + 16 + 4 * c, __reduce_max_sync(~0u, mmax));
                mbar_arrive_if(l16, sb + B_MX);
                mbar_wait(sb + B_MX, s & 1);
                const uint4 mm = lds128(sb + O_MISC + 16), cf = lds128(sb + O_MISC);
                const float bound = fmaxf(__uint_as_float(cf.z), __uint_as_float(cf.y) * (__uint_as_float(max(max(mm.x, mm.y), max(mm.z, mm.w))) * __uint_as_float(cf.x)));
                ebits = min(max(__float_as_uint(bound) & 0x7f800000u, 21u << 23), 254u << 23);
            }
            if (c == 0) STAMP(s < NSEG ? s : -1, 5);
            if (r < 2) {
                const uint32_t vmb = sb + O_VM + ((s - 1) & 1) * 2048 + (c >> 1) * 1024 + (l16 >> 1);
                const uint32_t vb = sb + O_VX + s3p * 8192 + (c >> 1) * 4096 + l16;
                const uint4 vm0 = lds64x2(vmb), vm1 = lds64x2(vmb + 512);
                float sm[4], o[4][4];
                uint4 v[8];
#pragma unroll
                for (int q = 0; q < 6; q++) v[q] = lds128(vb + (q & 3) * 1024 + (q >> 2) * 512);
                bar_sync(9, 384);
                const uint4 P = lds128(sb + O_PX + (c & 1) * 640 + l16);
                const uint32_t P0 = lds32(sb + O_PX + (c & 1) * 640 + 512 + (l16 >> 2));
                mma1688_z(o[0], vm0.x, vm0.y, P0); mma1688_z(o[1], vm0.z, vm0.w, P0);
                mma1688_z(o[2], vm1.x, vm1.y, P0); mma1688_z(o[3], vm1.z, vm1.w, P0);
#pragma unroll
                for (int q = 6; q < 8; q++) v[q] = lds128(vb + (q & 3) * 1024 + (q >> 2) * 512);
                mma1688_z(sm, ONES, ONES, P0);
#pragma unroll
                for (int q = 0; q < 4; q++) mma16816(o[q], v[q].x, v[q].y, v[q].z, v[q].w, P.x, P.y);
                mma16816(sm, ONES, ONES, ONES, ONES, P.x, P.y);
#pragma unroll
                for (int q = 0; q < 4; q++) mma16816(o[q], v[4 + q].x, v[4 + q].y, v[4 + q].z, v[4 + q].w, P.z, P.w);
                mma16816(sm, ONES, ONES, ONES, ONES, P.z, P.w);
                const uint32_t row = (l16 >> 4) & 7;
                const uint32_t stg = sb + O_OXS + c * 1024 + row * 128 + (((l16 >> 7) ^ row) << 4);
                const float r0 = rcp_fast(sm[0]), r1 = rcp_fast(sm[1]);
#pragma unroll
                for (int e2 = 0; e2 < 2; e2++)
                    stsm4t(stg ^ (e2 * 64), pack_bf16(o[2 * e2][0] * r0, o[2 * e2][1] * r1), pack_bf16(o[2 * e2][2] * r0, o[2 * e2][3] * r1),
                           pack_bf16(o[2 * e2 + 1][0] * r0, o[2 * e2 + 1][1] * r1), pack_bf16(o[2 * e2 + 1][2] * r0, o[2 * e2 + 1][3] * r1));
                __syncwarp();
            }
            if (s < NSEG - 1) {
                if (r < 2) mbar_wait(sb + B_VX + 8 * (s & 1), (s >> 1) & 1);
                else bar_sync(14, 384);
                uint4 vx[4];
#pragma unroll
                for (int q = 0; q < 4; q++) vx[q] = lds128(sb + O_VX + s3 * 8192 + c * 2048 + q * 512 + l16);
                bar_arrive(3, 384);
                mbar_wait(sb + B_VM, s & 1);
                const uint4 vm = lds64x2(sb + O_VM + (s & 1) * 2048 + c * 512 + (l16 >> 1));
                if (c == 0) STAMP(s, 13);
                mbar_wait(sb + B_SC, s & 1);
                if (c == 0) STAMP(s, 6);
                float p[10];
                load_scores(p, sb + O_SC, 1280, l16);
                float mx = fmaxf(fmaxf(fmaxf(p[0], p[1]), fmaxf(p[2], p[3])), fmaxf(fmaxf(p[4], p[5]), fmaxf(p[6], p[7])));
                mx = quad_max(fmaxf(mx, fmaxf(p[8], p[9])));
                const float mo = mx * SM_SCALE;
                uint32_t P[5];
#pragma unroll
                for (int n = 0; n < 5; n++) P[n] = pack_bf16(ex2(fmaf(p[2 * n], SM_SCALE, -mo)), ex2(fmaf(p[2 * n + 1], SM_SCALE, -mo)));
                if (c == 0) STAMP(s, 7);
                float o0[4], o1[4], sm[4];
                mma1688_z(sm, ONES, ONES, P[0]);
                mma1688_z(o0, vm.x, vm.y, P[0]);
                mma1688_z(o1, vm.z, vm.w, P[0]);
                mma16816(sm, ONES, ONES, ONES, ONES, P[1], P[2]);
                mma16816(o0, vx[0].x, vx[0].y, vx[0].z, vx[0].w, P[1], P[2]);
                mma16816(o1, vx[2].x, vx[2].y, vx[2].z, vx[2].w, P[1], P[2]);
                mma16816(sm, ONES, ONES, ONES, ONES, P[3], P[4]);
                mma16816(o0, vx[1].x, vx[1].y, vx[1].z, vx[1].w, P[3], P[4]);
                mma16816(o1, vx[3].x, vx[3].y, vx[3].z, vx[3].w, P[3], P[4]);
                const float sig = __uint_as_float((268u << 23) - ebits);
                const float r0 = rcp_fast(sm[0]) * sig, r1 = rcp_fast(sm[1]) * sig;
                stsm4t(sb + O_OF + c * 512 + l16, pack_bf16(o0[0] * r0, o0[1] * r1), pack_bf16(o0[2] * r0, o0[3] * r1),
                       pack_bf16(o1[0] * r0, o1[1] * r1), pack_bf16(o1[2] * r0, o1[3] * r1));
                bar_sync(6, 128);
                uint4 ob[4];
#pragma unroll
                for (int q = 0; q < 4; q++) ob[q] = ldsm4(sb + O_OF + q * 512 + l16);
                float m0[3][4], m1[3][4];
#pragma unroll
                for (int q = 0; q < 4; q++) {
#pragma unroll
                    for (int i = 0; i < 3; i++) {
                        const int k0 = (i * 8 + 2 * q) * 4;
                        if (q == 0) mma16816_z(m0[i], a[k0], a[k0 + 1], a[k0 + 2], a[k0 + 3], ob[q].x, ob[q].y);
                        else mma16816(m0[i], a[k0], a[k0 + 1], a[k0 + 2], a[k0 + 3], ob[q].x, ob[q].y);
                    }
#pragma unroll
                    for (int i = 0; i < 3; i++) {
                        const int k1 = (i * 8 + 2 * q + 1) * 4;
                        if (q == 0) mma16816_z(m1[i], a[k1], a[k1 + 1], a[k1 + 2], a[k1 + 3], ob[q].z, ob[q].w);
                        else mma16816(m1[i], a[k1], a[k1 + 1], a[k1 + 2], a[k1 + 3], ob[q].z, ob[q].w);
                    }
                }
                asm volatile("red.relaxed.gpu.global.add.noftz.v4.f16x2 [%0], {%1,%2,%3,%4};" :: "l"(rptr),
                    "r"(pack_f16(m0[0][0] + m1[0][0], m0[0][2] + m1[0][2])), "r"(pack_f16(m0[1][0] + m1[1][0], m0[1][2] + m1[1][2])),
                    "r"(pack_f16(m0[2][0] + m1[2][0], m0[2][2] + m1[2][2])), "r"(0x3c00u) : "memory");
                asm volatile("red.relaxed.gpu.global.add.noftz.v4.f16x2 [%0], {%1,%2,%3,%4};" :: "l"(rptr + 1024),
                    "r"(pack_f16(m0[0][1] + m1[0][1], m0[0][3] + m1[0][3])), "r"(pack_f16(m0[1][1] + m1[1][1], m0[1][3] + m1[1][3])),
                    "r"(pack_f16(m0[2][1] + m1[2][1], m0[2][3] + m1[2][3])), "r"(0x3c00u) : "memory");
                t_red = clk();
                bar_arrive(5, 256);
                bar_arrive(13, 256);
                {
                    const uint32_t nb = 8 * ((s + 1) & 1);
                    const uint32_t bar = sb + (c == 0 ? B_SC : c == 1 ? B_VM : c == 2 ? B_VX + nb : B_SX + nb);
                    const uint32_t bytes = c == 0 ? 2560 : c == 1 ? 2048 : c == 2 ? VXBYTES : (r == 0 ? 3072 : 5120);
                    mbar_expect_if(l16 | (uint32_t)(r == 2 && c >= 2), bar, bytes);
                    sts32_if(l16 | c, sb + O_MISC, ebits - (14u << 23));
                }
                if (c == 0) STAMPV(s, 8, t_red);
            } else if (r < 2 && s == NSEG - 1) {
                bar_arrive(3, 384);
                mbar_wait(sb + B_VM, s & 1);
                mbar_wait(sb + B_VX + 8 * (s & 1), (s >> 1) & 1);
            }

            auto finish_x = [&]() {
                const uint4 u0 = lds128(sb + O_OXS + c * 1024 + l16), u1 = lds128(sb + O_OXS + c * 1024 + 512 + l16);
                asm volatile("{\n.reg .pred p;\nsetp.ne.u32 p, %9, 0;\n@p st.global.v4.u32 [%0], {%1,%2,%3,%4};\n@p st.global.v4.u32 [%0+512], {%5,%6,%7,%8};\n}"
                    :: "l"(optr), "r"(u0.x), "r"(u0.y), "r"(u0.z), "r"(u0.w), "r"(u1.x), "r"(u1.y), "r"(u1.z), "r"(u1.w), "r"((uint32_t)(r < 2 && s >= 1)) : "memory");
            };
            if (s >= NSEG - 1) {
                finish_x();
            } else {
                if (c == 0) STAMP(s, 9);
                const char* pbase = rptr + pdelta;
                spin_until(t_red, D_WAIT);
                uint4 v[6];
#pragma unroll
                for (int i = 0; i < 6; i++) v[i] = ldg_relaxed128(pbase + (i >> 1) * 8192 + (i & 1) * 512);
                finish_x();
                int nretry = 0;
                auto hand_over = [&]() -> uint32_t {
                    const uint32_t ok = __all_sync(~0u, (v[0].w & v[1].w & v[2].w & v[3].w & v[4].w & v[5].w) == 0x5000u);
#pragma unroll
                    for (int tau = 0; tau < 3; tau++) {
                        v[2 * tau].x = f16x2_to_bf16x2(v[2 * tau].x); v[2 * tau + 1].x = f16x2_to_bf16x2(v[2 * tau + 1].x);
                        v[2 * tau].y = f16x2_to_bf16x2(v[2 * tau].y); v[2 * tau + 1].y = f16x2_to_bf16x2(v[2 * tau + 1].y);
                        v[2 * tau].z = f16x2_to_bf16x2(v[2 * tau].z); v[2 * tau + 1].z = f16x2_to_bf16x2(v[2 * tau + 1].z);
                        sts128(sb + O_MF + tau * 3072 + c * 512 + l16, v[2 * tau].x, v[2 * tau + 1].x, v[2 * tau].y, v[2 * tau + 1].y);
                        sts64(sb + O_MF + tau * 3072 + 2048 + (c >> 1) * 512 + (c & 1) * 8 + l16, v[2 * tau].z, v[2 * tau + 1].z);
                    }
                    asm volatile("{\n.reg .pred p;\nsetp.ne.u32 p, %0, 0;\n@p bar.arrive 2, 384;\n}" :: "r"(ok) : "memory");
                    return ok;
                };
                if (!hand_over()) {
                    asm volatile("{\n.reg .pred p, q;\n.reg .u32 n, x;\nmov.u32 n, 0;\n"
                         "R_%=: ld.relaxed.gpu.global.v4.u32 {%0,%1,%2,%3}, [%25];\nld.relaxed.gpu.global.v4.u32 {%4,%5,%6,%7}, [%25+512];\n"
                         "ld.relaxed.gpu.global.v4.u32 {%8,%9,%10,%11}, [%25+8192];\nld.relaxed.gpu.global.v4.u32 {%12,%13,%14,%15}, [%25+8704];\n"
                         "ld.relaxed.gpu.global.v4.u32 {%16,%17,%18,%19}, [%25+16384];\nld.relaxed.gpu.global.v4.u32 {%20,%21,%22,%23}, [%25+16896];\n"
                         "add.u32 %24, %24, 1;\nand.b32 x, %3, %7;\nand.b32 x, x, %11;\nand.b32 x, x, %15;\nand.b32 x, x, %19;\nand.b32 x, x, %23;\n"
                         "setp.eq.u32 p, x, 0x5000;\nvote.sync.all.pred q, p, 0xffffffff;\n@q bra.uni K_%=;\n"
                         "add.u32 n, n, 1;\nsetp.lt.u32 q, n, 2000000;\n@q bra.uni R_%=;\ntrap;\nK_%=:\n}"
                         : "+r"(v[0].x), "+r"(v[0].y), "+r"(v[0].z), "+r"(v[0].w), "+r"(v[1].x), "+r"(v[1].y), "+r"(v[1].z), "+r"(v[1].w),
                           "+r"(v[2].x), "+r"(v[2].y), "+r"(v[2].z), "+r"(v[2].w), "+r"(v[3].x), "+r"(v[3].y), "+r"(v[3].z), "+r"(v[3].w),
                           "+r"(v[4].x), "+r"(v[4].y), "+r"(v[4].z), "+r"(v[4].w), "+r"(v[5].x), "+r"(v[5].y), "+r"(v[5].z), "+r"(v[5].w), "+r"(nretry)
                         : "l"(pbase) : "memory");
                    hand_over();
                }
                if (c == 0) STAMP(s, 12);
                if (c == 0) STAMPV(s, 14, nretry);
                mmax = 0;
                const uint32_t msk = lds32(sb + O_MISC + 12);
#pragma unroll
                for (int i = 0; i < 6; i++) mmax = __vmaxu2(__vmaxu2(mmax, v[i].x & msk), __vmaxu2(v[i].y & msk, v[i].z & msk));
                mmax = max(mmax << 16, mmax & 0xffff0000u);
            }
            s3p = s3;
            rptr += 24576;
            optr += 4096;
        }
        if (r < 2) {
            bar_sync(6, 128);
            if (c == 0)
                asm volatile("{\n.reg .pred p;\nsetp.eq.u32 p, %1, 0;\n@p red.release.gpu.global.inc.u32 [%0], 0x7fffffff;\n}"
                             :: "l"(&g_flag[(63 * 4 + (h >> 3)) * 8]), "r"(l16c) : "memory");
        }
    }
    cluster_sync();
}

__device__ float g_u[SEQ * 2 * DM];
__global__ void naive_gemm1(const __nv_bfloat16* x, const __nv_bfloat16* Bre, const __nv_bfloat16* Bim) {
    int p = blockIdx.x * 64 + threadIdx.x % 64, tk = blockIdx.y * 4 + threadIdx.x / 64;
    float sr = 0, si = 0;
    for (int d = 0; d < DM; d++) { float xv = __bfloat162float(x[tk * DM + d]); sr += xv * __bfloat162float(Bre[p * DM + d]); si += xv * __bfloat162float(Bim[p * DM + d]); }
    g_u[tk * 2 * DM + 2 * p] = sr; g_u[tk * 2 * DM + 2 * p + 1] = si;
}
__global__ void naive_scan(const __nv_bfloat16* Lre, const __nv_bfloat16* Lim, const __nv_bfloat16* logdt) {
    int p = blockIdx.x * 64 + threadIdx.x;
    float dt = __bfloat162float(__float2bfloat16(expf(__bfloat162float(logdt[p]))));
    float lr = __bfloat162float(Lre[p]), li = __bfloat162float(Lim[p]);
    float e = expf(dt * lr), br = e * cosf(dt * li), bi = e * sinf(dt * li);
    float den = lr * lr + li * li;
    float cr = ((br - 1.f) * lr + bi * li) / den, ci = (bi * lr - (br - 1.f) * li) / den;
    float hr = 0, hi = 0;
    for (int tk = 0; tk < SEQ; tk++) {
        float ur = g_u[tk * 2 * DM + 2 * p], ui = g_u[tk * 2 * DM + 2 * p + 1];
        float nr = br * hr - bi * hi + cr * ur - ci * ui, ni = br * hi + bi * hr + cr * ui + ci * ur;
        hr = nr; hi = ni;
        g_u[tk * 2 * DM + 2 * p] = hr; g_u[tk * 2 * DM + 2 * p + 1] = hi;
    }
}
__global__ void naive_gemm2(const __nv_bfloat16* x, const __nv_bfloat16* Cre, const __nv_bfloat16* Cim, const __nv_bfloat16* Dk, float* out) {
    int d = blockIdx.x * 64 + threadIdx.x % 64, tk = blockIdx.y * 4 + threadIdx.x / 64;
    float s = 0;
    for (int p = 0; p < DM; p++) s += g_u[tk * 2 * DM + 2 * p] * __bfloat162float(Cre[d * DM + p]) - g_u[tk * 2 * DM + 2 * p + 1] * __bfloat162float(Cim[d * DM + p]);
    out[tk * 1152 + d] = 2.f * s + __bfloat162float(__float2bfloat16(__bfloat162float(x[tk * DM + d]) * __bfloat162float(Dk[d])));
}
__global__ void naive_wo(const __nv_bfloat16* Wo, float* out) {
    int d = blockIdx.x * 64 + threadIdx.x % 64, tk = blockIdx.y * 4 + threadIdx.x / 64;
    const __nv_bfloat16* ox = reinterpret_cast<const __nv_bfloat16*>(g_ox);
    float s = 0;
    for (int k = 0; k < HD; k++) {
        int hh = k >> 6, e0 = k & 63, e = (e0 & 48) + (e0 & 1) * 8 + ((e0 & 15) >> 1);
        s += __bfloat162float(ox[((size_t)hh * SEQ + tk) * 64 + (((e >> 3) ^ (tk & 7)) << 3) + (e & 7)]) * __bfloat162float(Wo[k * DM + d]);
    }
    out[tk * 1152 + DM + d] = s;
}

typedef CUresult (*EncodeFn)(CUtensorMap*, CUtensorMapDataType, cuuint32_t, void*, const cuuint64_t*, const cuuint64_t*, const cuuint32_t*, const cuuint32_t*,
                             CUtensorMapInterleave, CUtensorMapSwizzle, CUtensorMapL2promotion, CUtensorMapFloatOOBfill);
}

extern "C" void kernel_launch(void* const* d_in, const int* in_sizes, int n_in, void* d_out, int out_size) {
    typedef const __nv_bfloat16* bp;
    bp Ax = (bp)d_in[0], Lre = (bp)d_in[1], Lim = (bp)d_in[2], Bre = (bp)d_in[3], Bim = (bp)d_in[4], Cre = (bp)d_in[5], Cim = (bp)d_in[6],
       logdt = (bp)d_in[7], Dk = (bp)d_in[8], Bx = (bp)d_in[9], mem0 = (bp)d_in[10], Wq = (bp)d_in[11], Wk = (bp)d_in[12], Wv = (bp)d_in[13], Wo = (bp)d_in[14];
    float* out = (float*)d_out;
    static EncodeFn enc = nullptr;
    if (!enc) {
        void* fn = nullptr; cudaDriverEntryPointQueryResult qr;
        cudaGetDriverEntryPoint("cuTensorMapEncodeTiled", &fn, cudaEnableDefault, &qr);
        enc = (EncodeFn)fn;
        cudaFuncSetAttribute(chain_kernel, cudaFuncAttributeMaxDynamicSharedMemorySize, CHAIN_SMEM);
    }
    CUtensorMap tm_x;
    {
        cuuint64_t gd[2] = {DM, SEQ}; cuuint64_t gs[1] = {DM * 2}; cuuint32_t bd[2] = {64, 32}; cuuint32_t es[2] = {1, 1};
        enc(&tm_x, CU_TENSOR_MAP_DATA_TYPE_BFLOAT16, 2, (void*)Bx, gd, gs, bd, es, CU_TENSOR_MAP_INTERLEAVE_NONE, CU_TENSOR_MAP_SWIZZLE_128B,
            CU_TENSOR_MAP_L2_PROMOTION_L2_128B, CU_TENSOR_MAP_FLOAT_OOB_FILL_NONE);
    }
    cudaStream_t st = cudaStreamPerThread;
    chain_kernel<<<96, 384, CHAIN_SMEM, st>>>(tm_x, Bx, mem0, Wq, Wk, Wv, Wo);
    naive_gemm1<<<dim3(9, 512), 256, 0, st>>>(Ax, Bre, Bim);
    naive_scan<<<9, 64, 0, st>>>(Lre, Lim, logdt);
    naive_gemm2<<<dim3(9, 512), 256, 0, st>>>(Ax, Cre, Cim, Dk, out);
    naive_wo<<<dim3(9, 512), 256, 0, st>>>(Wo, out);
}
```

```cpp
#include <cuda_runtime.h>
#include <cuda.h>
#include <cuda_bf16.h>
#include <cuda_fp16.h>
#include <stdint.h>

#define D_WAIT 700
#define VXMODE 1
#define VXBYTES (VXMODE == 2 ? 0 : 8192)
#define XC0 10
#define XC1 4

namespace {

constexpr int DM = 576, NH = 32, SEQ = 2048, NSEG = 64, HD = 4096;

__device__ uint4 g_acc[64 * 96 * 16];
__device__ uint4 g_ox[NH * 2 * SEQ * 8];
__device__ unsigned g_flag[NSEG * 4 * 8];
__device__ uint4 g_vx[NH * 2 * 512];
__device__ unsigned g_gridbar;
__device__ float g_norm[96 * 4];

__device__ __forceinline__ uint32_t smem_u32(const void* p) { return (uint32_t)__cvta_generic_to_shared(p); }
__device__ __forceinline__ uint32_t mapa(uint32_t a, uint32_t r) { uint32_t o; asm("mapa.shared::cluster.u32 %0, %1, %2;" : "=r"(o) : "r"(a), "r"(r)); return o; }
__device__ __forceinline__ uint32_t mapa_v(uint32_t a, uint32_t r) { uint32_t o; asm volatile("mapa.shared::cluster.u32 %0, %1, %2;" : "=r"(o) : "r"(a), "r"(r)); return o; }
__device__ __forceinline__ unsigned clk() { unsigned long long c; asm volatile("mov.u64 %0, %%clock64;" : "=l"(c) :: "memory"); return (unsigned)c; }
__device__ __forceinline__ void mbar_init(uint32_t bar, uint32_t cnt) { asm volatile("mbarrier.init.shared::cta.b64 [%0], %1;" :: "r"(bar), "r"(cnt) : "memory"); }
__device__ __forceinline__ void mbar_expect(uint32_t bar, uint32_t bytes) { asm volatile("mbarrier.arrive.expect_tx.shared::cta.b64 _, [%0], %1;" :: "r"(bar), "r"(bytes) : "memory"); }
__device__ __forceinline__ void mbar_wait(uint32_t bar, uint32_t parity) {
    asm volatile("{\n.reg .pred p;\n.reg .u32 n;\nmov.u32 n, 0;\n"
                 "W_%=: mbarrier.try_wait.parity.shared::cta.b64 p, [%0], %1;\n@p bra.uni D_%=;\n"
                 "add.u32 n, n, 1;\nsetp.lt.u32 p, n, 4000000;\n@p bra.uni W_%=;\ntrap;\nD_%=:\n}" :: "r"(bar), "r"(parity) : "memory");
}
__device__ __forceinline__ void mbar_expect_if(uint32_t z, uint32_t bar, uint32_t bytes) {
    asm volatile("{\n.reg .pred p;\nsetp.eq.u32 p, %2, 0;\n@p mbarrier.arrive.expect_tx.shared::cta.b64 _, [%0], %1;\n}" :: "r"(bar), "r"(bytes), "r"(z) : "memory");
}
__device__ __forceinline__ void mbar_arrive_if(uint32_t z, uint32_t bar) {
    asm volatile("{\n.reg .pred p;\nsetp.eq.u32 p, %1, 0;\n@p mbarrier.arrive.shared::cta.b64 _, [%0];\n}" :: "r"(bar), "r"(z) : "memory");
}
__device__ __forceinline__ void sts32_if(uint32_t z, uint32_t a, uint32_t x) {
    asm volatile("{\n.reg .pred p;\nsetp.eq.u32 p, %2, 0;\n@p st.shared.u32 [%0], %1;\n}" :: "r"(a), "r"(x), "r"(z) : "memory");
}
__device__ __forceinline__ void spin_until(unsigned t0, unsigned d) {
    asm volatile("{\n.reg .pred p;\n.reg .u64 c;\n.reg .u32 lo;\n"
                 "S_%=: mov.u64 c, %%clock64;\ncvt.u32.u64 lo, c;\nsub.u32 lo, lo, %0;\nsetp.lt.u32 p, lo, %1;\n@p bra.uni S_%=;\n}" :: "r"(t0), "r"(d) : "memory");
}
__device__ __forceinline__ void bar_sync(int id, int n) { asm volatile("bar.sync %0, %1;" :: "r"(id), "r"(n) : "memory"); }
__device__ __forceinline__ void bar_sync_sel(int sel, int id) {
    asm volatile("{\n.reg .pred p;\nsetp.eq.u32 p, %0, 0;\n@p bar.sync %1, %3;\n@!p bar.sync %2, %3;\n}" :: "r"(sel), "r"(id), "r"(id + 1), "n"(192) : "memory");
}
__device__ __forceinline__ void bar_arrive(int id, int n) { asm volatile("bar.arrive %0, %1;" :: "r"(id), "r"(n) : "memory"); }
__device__ __forceinline__ void fence_async_smem() { asm volatile("fence.proxy.async.shared::cta;" ::: "memory"); }
__device__ __forceinline__ uint32_t pack_bf16(float lo, float hi) { uint32_t r; asm("cvt.rn.bf16x2.f32 %0, %1, %2;" : "=r"(r) : "f"(hi), "f"(lo)); return r; }
__device__ __forceinline__ uint32_t pack_f16(float lo, float hi) { uint32_t r; asm("cvt.rn.f16x2.f32 %0, %1, %2;" : "=r"(r) : "f"(hi), "f"(lo)); return r; }
__device__ __forceinline__ uint32_t f16x2_to_bf16x2(uint32_t v) { float2 f = __half22float2(*reinterpret_cast<__half2*>(&v)); return pack_bf16(f.x, f.y); }
__device__ __forceinline__ float ex2(float x) { float y; asm("ex2.approx.ftz.f32 %0, %1;" : "=f"(y) : "f"(x)); return y; }
__device__ __forceinline__ float ex2v(float x) { float y; asm volatile("ex2.approx.ftz.f32 %0, %1;" : "=f"(y) : "f"(x)); return y; }
__device__ __forceinline__ uint32_t absmax2(uint32_t a, uint32_t b) {
    uint32_t r; asm("max.xorsign.abs.bf16x2 %0, %1, %2;" : "=r"(r) : "r"(a), "r"(b)); return r;
}
__device__ __forceinline__ uint32_t shl_v(uint32_t a, int n) { return a << n; }
__device__ __forceinline__ uint32_t max3u(uint32_t a, uint32_t b, uint32_t c) { return max(max(a, b), c); }
__device__ __forceinline__ uint4 lds128(uint32_t a) { uint4 v; asm volatile("ld.shared.v4.u32 {%0,%1,%2,%3}, [%4];" : "=r"(v.x), "=r"(v.y), "=r"(v.z), "=r"(v.w) : "r"(a) : "memory"); return v; }
__device__ __forceinline__ float4 lds128f(uint32_t a) { float4 v; asm volatile("ld.shared.v4.f32 {%0,%1,%2,%3}, [%4];" : "=f"(v.x), "=f"(v.y), "=f"(v.z), "=f"(v.w) : "r"(a) : "memory"); return v; }
__device__ __forceinline__ float2 lds64f(uint32_t a) { float2 v; asm volatile("ld.shared.v2.f32 {%0,%1}, [%2];" : "=f"(v.x), "=f"(v.y) : "r"(a) : "memory"); return v; }
__device__ __forceinline__ uint4 lds64x2(uint32_t a) { uint4 v; asm volatile("ld.shared.v2.u32 {%0,%1}, [%4];\nld.shared.v2.u32 {%2,%3}, [%4+256];" : "=r"(v.x), "=r"(v.y), "=r"(v.z), "=r"(v.w) : "r"(a) : "memory"); return v; }
__device__ __forceinline__ uint32_t lds32(uint32_t a) { uint32_t v; asm volatile("ld.shared.u32 %0, [%1];" : "=r"(v) : "r"(a) : "memory"); return v; }
__device__ __forceinline__ void sts128(uint32_t a, uint32_t x, uint32_t y, uint32_t z, uint32_t w) { asm volatile("st.shared.v4.u32 [%0], {%1,%2,%3,%4};" :: "r"(a), "r"(x), "r"(y), "r"(z), "r"(w) : "memory"); }
__device__ __forceinline__ void sts128f(uint32_t a, float x, float y, float z, float w) { asm volatile("st.shared.v4.f32 [%0], {%1,%2,%3,%4};" :: "r"(a), "f"(x), "f"(y), "f"(z), "f"(w) : "memory"); }
__device__ __forceinline__ void sts64(uint32_t a, uint32_t x, uint32_t y) { asm volatile("st.shared.v2.u32 [%0], {%1,%2};" :: "r"(a), "r"(x), "r"(y) : "memory"); }
__device__ __forceinline__ void sts32(uint32_t a, uint32_t x) { asm volatile("st.shared.u32 [%0], %1;" :: "r"(a), "r"(x) : "memory"); }
__device__ __forceinline__ uint4 ldsm4(uint32_t a) { uint4 v; asm volatile("ldmatrix.sync.aligned.m8n8.x4.shared.b16 {%0,%1,%2,%3}, [%4];" : "=r"(v.x), "=r"(v.y), "=r"(v.z), "=r"(v.w) : "r"(a) : "memory"); return v; }
__device__ __forceinline__ void stsm2t(uint32_t a, uint32_t x, uint32_t y) { asm volatile("stmatrix.sync.aligned.m8n8.x2.trans.shared.b16 [%0], {%1,%2};" :: "r"(a), "r"(x), "r"(y) : "memory"); }
__device__ __forceinline__ void stsm4t(uint32_t a, uint32_t x, uint32_t y, uint32_t z, uint32_t w) { asm volatile("stmatrix.sync.aligned.m8n8.x4.trans.shared.b16 [%0], {%1,%2,%3,%4};" :: "r"(a), "r"(x), "r"(y), "r"(z), "r"(w) : "memory"); }
__device__ __forceinline__ void st_async64(uint32_t a, uint32_t x, uint32_t y, uint32_t bar) { asm volatile("st.async.shared::cluster.mbarrier::complete_tx::bytes.v2.b32 [%0], {%1,%2}, [%3];" :: "r"(a), "r"(x), "r"(y), "r"(bar) : "memory"); }
__device__ __forceinline__ void bulk_s2c(uint32_t dst, uint32_t src, uint32_t bytes, uint32_t bar) { asm volatile("cp.async.bulk.shared::cluster.shared::cta.mbarrier::complete_tx::bytes [%0], [%1], %2, [%3];" :: "r"(dst), "r"(src), "r"(bytes), "r"(bar) : "memory"); }
__device__ __forceinline__ void bulk_s2g(void* dst, uint32_t src, uint32_t bytes) { asm volatile("cp.async.bulk.global.shared::cta.bulk_group [%0], [%1], %2;" :: "l"(dst), "r"(src), "r"(bytes) : "memory"); }
__device__ __forceinline__ uint32_t ldg_nc32(const void* p) { uint32_t v; asm volatile("ld.global.nc.L2::128B.u32 %0, [%1];" : "=r"(v) : "l"(p)); return v; }
__device__ __forceinline__ uint4 ldg_relaxed128(const void* p) { uint4 v; asm volatile("ld.relaxed.gpu.global.v4.u32 {%0,%1,%2,%3}, [%4];" : "=r"(v.x), "=r"(v.y), "=r"(v.z), "=r"(v.w) : "l"(p) : "memory"); return v; }
__device__ __forceinline__ void mma16816(float (&d)[4], uint32_t a0, uint32_t a1, uint32_t a2, uint32_t a3, uint32_t b0, uint32_t b1) {
    asm volatile("mma.sync.aligned.m16n8k16.row.col.f32.bf16.bf16.f32 {%0,%1,%2,%3}, {%4,%5,%6,%7}, {%8,%9}, {%0,%1,%2,%3};"
        : "+f"(d[0]), "+f"(d[1]), "+f"(d[2]), "+f"(d[3]) : "r"(a0), "r"(a1), "r"(a2), "r"(a3), "r"(b0), "r"(b1));
}
__device__ __forceinline__ void mma16816_z(float (&d)[4], uint32_t a0, uint32_t a1, uint32_t a2, uint32_t a3, uint32_t b0, uint32_t b1) {
    asm volatile("mma.sync.aligned.m16n8k16.row.col.f32.bf16.bf16.f32 {%0,%1,%2,%3}, {%4,%5,%6,%7}, {%8,%9}, {%10,%10,%10,%10};"
        : "=f"(d[0]), "=f"(d[1]), "=f"(d[2]), "=f"(d[3]) : "r"(a0), "r"(a1), "r"(a2), "r"(a3), "r"(b0), "r"(b1), "f"(0.f));
}
__device__ __forceinline__ void mma1688(float (&d)[4], uint32_t a0, uint32_t a1, uint32_t b0) {
    asm volatile("mma.sync.aligned.m16n8k8.row.col.f32.bf16.bf16.f32 {%0,%1,%2,%3}, {%4,%5}, {%6}, {%0,%1,%2,%3};"
        : "+f"(d[0]), "+f"(d[1]), "+f"(d[2]), "+f"(d[3]) : "r"(a0), "r"(a1), "r"(b0));
}
__device__ __forceinline__ void mma1688_z(float (&d)[4], uint32_t a0, uint32_t a1, uint32_t b0) {
    asm volatile("mma.sync.aligned.m16n8k8.row.col.f32.bf16.bf16.f32 {%0,%1,%2,%3}, {%4,%5}, {%6}, {%7,%7,%7,%7};"
        : "=f"(d[0]), "=f"(d[1]), "=f"(d[2]), "=f"(d[3]) : "r"(a0), "r"(a1), "r"(b0), "f"(0.f));
}
template <int ACC>
__device__ __forceinline__ void wgmma_n32_rs(float (&d)[16], uint32_t a0, uint32_t a1, uint32_t a2, uint32_t a3, uint64_t desc) {
    asm volatile("wgmma.mma_async.sync.aligned.m64n32k16.f32.bf16.bf16 {%0,%1,%2,%3,%4,%5,%6,%7,%8,%9,%10,%11,%12,%13,%14,%15}, {%16,%17,%18,%19}, %20, %21, 1, 1, 0;"
        : "+f"(d[0]), "+f"(d[1]), "+f"(d[2]), "+f"(d[3]), "+f"(d[4]), "+f"(d[5]), "+f"(d[6]), "+f"(d[7]),
          "+f"(d[8]), "+f"(d[9]), "+f"(d[10]), "+f"(d[11]), "+f"(d[12]), "+f"(d[13]), "+f"(d[14]), "+f"(d[15])
        : "r"(a0), "r"(a1), "r"(a2), "r"(a3), "l"(desc), "n"(ACC));
}
template <int ACC>
__device__ __forceinline__ void wgmma_n32_ss(float (&d)[16], uint64_t da, uint64_t db) {
    asm volatile("wgmma.mma_async.sync.aligned.m64n32k16.f32.bf16.bf16 {%0,%1,%2,%3,%4,%5,%6,%7,%8,%9,%10,%11,%12,%13,%14,%15}, %16, %17, %18, 1, 1, 0, 0;"
        : "+f"(d[0]), "+f"(d[1]), "+f"(d[2]), "+f"(d[3]), "+f"(d[4]), "+f"(d[5]), "+f"(d[6]), "+f"(d[7]),
          "+f"(d[8]), "+f"(d[9]), "+f"(d[10]), "+f"(d[11]), "+f"(d[12]), "+f"(d[13]), "+f"(d[14]), "+f"(d[15])
        : "l"(da), "l"(db), "n"(ACC));
}
__device__ __forceinline__ void wg_fence() { asm volatile("wgmma.fence.sync.aligned;" ::: "memory"); }
__device__ __forceinline__ void wg_commit() { asm volatile("wgmma.commit_group.sync.aligned;" ::: "memory"); }
__device__ __forceinline__ void wg_wait0() { asm volatile("wgmma.wait_group.sync.aligned 0;" ::: "memory"); }
__device__ __forceinline__ void cluster_sync() { asm volatile("barrier.cluster.arrive.aligned;\nbarrier.cluster.wait.aligned;" ::: "memory"); }

#define STAMP(s, i) do {} while (0)
#define STAMPV(s, i, v) do {} while (0)

constexpr int XT_BYTES = 36864;
constexpr int O_XT = 0;
constexpr int O_AS = 3 * XT_BYTES;
constexpr int O_AF = O_AS + 16384;
constexpr int O_MF = O_AF + 16384;
constexpr int O_XP = O_MF + 9216;
constexpr int O_VX = O_XP + 8192;
constexpr int O_VM = O_VX + 24576;
constexpr int O_SC = O_VM + 4096;
constexpr int O_OF = O_SC + 2560;
constexpr int O_U = O_OF + 2048;
constexpr int O_QM = O_U;
constexpr int O_KM = O_QM + 2048;
constexpr int O_QKX = O_KM + 2048;
constexpr int O_SX = O_U;
constexpr int O_OXS = O_SX + 20480;
constexpr int O_MISC = O_OXS + 8192;
constexpr int O_BAR = O_MISC + 64;
constexpr int CHAIN_SMEM = O_BAR + 128;
static_assert(CHAIN_SMEM <= 232448, "smem");
constexpr int B_X = O_BAR, B_VX = O_BAR + 24, B_SX = O_BAR + 40, B_SC = O_BAR + 56, B_VM = O_BAR + 64;
constexpr float SM_SCALE = 0.08838834764831845f * 1.4426950408889634f;
constexpr uint32_t ONES = 0x3f803f80u;

__device__ __forceinline__ uint32_t opaque(uint32_t v) { uint32_t o; asm volatile("mov.u32 %0, %1;" : "=r"(o) : "r"(v)); return o; }
__device__ __forceinline__ void st_async128(uint32_t a, uint32_t x, uint32_t y, uint32_t z, uint32_t w, uint32_t bar) {
    asm volatile("st.async.shared::cluster.mbarrier::complete_tx::bytes.v4.b32 [%0], {%1,%2,%3,%4}, [%5];" :: "r"(a), "r"(x), "r"(y), "r"(z), "r"(w), "r"(bar) : "memory");
}
__device__ __forceinline__ void tma_x_tile(uint32_t sb, const CUtensorMap* tm, int r, int j, int slot) {
    asm volatile("{\n.reg .pred p;\nelect.sync _|p, 0xffffffff;\n"
        "@p mbarrier.arrive.expect_tx.shared::cta.b64 _, [%2], 36864;\n"
        "@p cp.async.bulk.tensor.2d.shared::cluster.global.mbarrier::complete_tx::bytes.multicast::cluster [%0], [%1, {%3, %4}], [%2], %7;\n"
        "@p cp.async.bulk.tensor.2d.shared::cluster.global.mbarrier::complete_tx::bytes.multicast::cluster [%0+4096], [%1, {%5, %4}], [%2], %7;\n"
        "@p cp.async.bulk.tensor.2d.shared::cluster.global.mbarrier::complete_tx::bytes.multicast::cluster [%0+8192], [%1, {%6, %4}], [%2], %7;\n}"
        :: "r"(sb + O_XT + slot * XT_BYTES + 3 * r * 4096), "l"(tm), "r"(sb + B_X + 8 * slot), "r"(192 * r), "r"(j * 32), "r"(192 * r + 64), "r"(192 * r + 128),
           "h"((unsigned short)7) : "memory");
}
__device__ __forceinline__ float quad_max(float v) {
    const float a = __shfl_xor_sync(~0u, v, 1), b = __shfl_xor_sync(~0u, v, 2), c = __shfl_xor_sync(~0u, v, 3);
    return fmaxf(fmaxf(v, a), fmaxf(b, c));
}
__device__ __forceinline__ void load_scores(float (&p)[10], uint32_t base, uint32_t stride, uint32_t l16) {
    const float4 a0 = lds128f(base + l16), b0 = lds128f(base + stride + l16);
    const float4 a1 = lds128f(base + 512 + l16), b1 = lds128f(base + stride + 512 + l16);
    const float2 a2 = lds64f(base + 1024 + (l16 >> 1)), b2 = lds64f(base + stride + 1024 + (l16 >> 1));
    p[0] = a2.x + b2.x; p[1] = a2.y + b2.y;
    p[2] = a0.x + b0.x; p[3] = a0.y + b0.y; p[4] = a0.z + b0.z; p[5] = a0.w + b0.w;
    p[6] = a1.x + b1.x; p[7] = a1.y + b1.y; p[8] = a1.z + b1.z; p[9] = a1.w + b1.w;
}
__device__ __forceinline__ float rcp_fast(float x) { float y; asm("rcp.approx.ftz.f32 %0, %1;" : "=f"(y) : "f"(x)); return y; }

__global__ void __cluster_dims__(3, 1, 1) __launch_bounds__(384, 1)
chain_kernel(const __grid_constant__ CUtensorMap tm_x,
             const __nv_bfloat16* __restrict__ x, const __nv_bfloat16* __restrict__ mem0,
             const __nv_bfloat16* __restrict__ Wq, const __nv_bfloat16* __restrict__ Wk,
             const __nv_bfloat16* __restrict__ Wv, const __nv_bfloat16* __restrict__ Wo) {
    extern __shared__ __align__(1024) uint8_t smem_raw[];
    const uint32_t sb = smem_u32(smem_raw);
    const int lane = threadIdx.x & 31;
    const int warp = __shfl_sync(~0u, threadIdx.x >> 5, 0);
    const int wg = warp >> 2, w = warp & 3;
    const int h = blockIdx.x / 3, r = blockIdx.x - 3 * h;

    if (threadIdx.x == 0) {
        if (sb & 1023u) __trap();
        for (int i = 0; i < 9; i++) mbar_init(sb + O_BAR + 8 * i, 1);
        asm volatile("fence.mbarrier_init.release.cluster;" ::: "memory");
    }
    if (blockIdx.x == 0) {
        for (int i = threadIdx.x; i < NSEG * 4 * 8; i += 384) g_flag[i] = 0;
        __threadfence();
    }
    __syncthreads();
    cluster_sync();
    asm volatile("griddepcontrol.launch_dependents;" ::: "memory");
    const uint32_t l16c = __shfl_sync(~0u, lane * 16, lane);

    if (wg < 2) {
#define KS(u) ((u) < 8 ? ((u) >> 1) + 4 * ((u) & 1) : (u) < 12 ? (u) : (u) < 20 ? 12 + (((u) - 12) >> 1) + 4 * ((u) & 1) : (u) < 24 ? (u) : (u) + 8)
        asm volatile("setmaxnreg.inc.sync.aligned.u32 176;");
        const int kt = warp < 3 ? warp : (warp < 5 ? warp - 3 : (warp == 5 ? 0 : 2));
        const int mt = (warp == 5 || warp == 7) ? 0 : 1;
        uint32_t a[144];
        uint32_t adr1, adr_q, adr_k;
        {
            const int g = lane >> 2, t = lane & 3;
#pragma unroll
            for (int tl = 0; tl < 2; tl++) {
                const int tile = tl ? wg : (wg ^ 1);
                const __nv_bfloat16* W = (r < 2) ? (tile == 0 ? Wq : Wk) : Wv;
                const int col = h * 128 + ((r < 2) ? 64 * r : 64 * tile) + 16 * w + 2 * g;
                const __nv_bfloat16* p = W + (size_t)(2 * t) * HD + col;
                const __nv_bfloat16* ps = p + (size_t)(384 * wg) * HD;
#pragma unroll
                for (int u = 0; u < (tl ? 28 : 8); u++) {
                    const __nv_bfloat16* q = (u < 8 ? ps : p) + (size_t)(16 * KS(u)) * HD;
                    a[32 * tl + 4 * u + 0] = ldg_nc32(q);
                    a[32 * tl + 4 * u + 1] = ldg_nc32(q + HD);
                    a[32 * tl + 4 * u + 2] = ldg_nc32(q + 8 * HD);
                    a[32 * tl + 4 * u + 3] = ldg_nc32(q + 9 * HD);
                }
            }
#pragma unroll
            for (int kk = 0; kk < 72; kk++) {
                uint32_t w0 = a[2 * kk], w1 = a[2 * kk + 1];
                a[2 * kk] = __byte_perm(w0, w1, 0x5410);
                a[2 * kk + 1] = __byte_perm(w0, w1, 0x7632);
            }
            float vmax = 0.f;
#pragma unroll
            for (int tl = 0; tl < 2; tl++) {
                float s0 = 0.f, s1 = 0.f;
#pragma unroll
                for (int kk = 16 * tl; kk < (tl ? 72 : 16); kk++) {
                    s0 += fabsf(__uint_as_float(a[2 * kk] << 16)) + fabsf(__uint_as_float(a[2 * kk] & 0xffff0000u));
                    s1 += fabsf(__uint_as_float(a[2 * kk + 1] << 16)) + fabsf(__uint_as_float(a[2 * kk + 1] & 0xffff0000u));
                }
                s0 += __shfl_xor_sync(~0u, s0, 1); s0 += __shfl_xor_sync(~0u, s0, 2);
                s1 += __shfl_xor_sync(~0u, s1, 1); s1 += __shfl_xor_sync(~0u, s1, 2);
                vmax = fmaxf(vmax, fmaxf(s0, s1));
            }
            uint32_t mx = __reduce_max_sync(~0u, __float_as_uint(2.f * vmax));
            sts32_if(lane, sb + O_MISC + 32 + 4 * warp, mx);
            bar_arrive(7, 384);
            const uint32_t as = sb + O_AS + wg * 8192 + (16 * w + g) * 128 + t * 4;
#pragma unroll
            for (int kk = 0; kk < 4; kk++) {
                sts32(as + (((2 * kk) ^ g) << 4), a[32 + 4 * kk]);
                sts32(as + 1024 + (((2 * kk) ^ g) << 4), a[32 + 4 * kk + 1]);
                sts32(as + (((2 * kk + 1) ^ g) << 4), a[32 + 4 * kk + 2]);
                sts32(as + 1024 + (((2 * kk + 1) ^ g) << 4), a[32 + 4 * kk + 3]);
                sts128(sb + O_AF + warp * 2048 + kk * 512 + lane * 16, a[32 + 4 * kk], a[32 + 4 * kk + 1], a[32 + 4 * kk + 2], a[32 + 4 * kk + 3]);
            }
            fence_async_smem();
            bar_sync(1, 256);
            const uint32_t l = lane * 16;
            const int mi = lane >> 3, isk = (mi >> 1) ? wg : (wg ^ 1);
            adr1 = (r == 2) ? (sb + O_VM + warp * 256 + (l >> 1))
                            : (isk ? (sb + O_KM + w * 512 + wg * 256 + (mi & 1) * 128 + (l & 127))
                                   : (sb + O_QM + w * 512 + (mi & 1) * 256 + wg * 128 + (l & 127)));
            adr1 = __shfl_sync(~0u, adr1, lane);
            const uint32_t qa = sb + (warp < 3 ? O_QM : O_QKX + mt * 2048) + l;
            const uint32_t ka = sb + (kt == 2 ? O_KM : O_QKX + 4096 + kt * 2048) + l;
            adr_q = __shfl_sync(~0u, qa, lane);
            adr_k = __shfl_sync(~0u, ka, lane);
        }
        int s3 = 2;
#pragma unroll 1
        for (int s = -1; s < NSEG; s++) {
            const uint32_t l16 = opaque(l16c);
            s3 = (s3 == 2) ? 0 : s3 + 1;
            if (s < NSEG - 1) mbar_wait(sb + B_X + 8 * s3, ((s + 1) / 3) & 1);
            const uint64_t desc0 = (uint64_t)(((sb + O_XT + s3 * XT_BYTES) & 0x3FFFF) >> 4) | (1ull << 16) | (64ull << 32) | (1ull << 62);
            const uint32_t doff = kt * 512 + (kt == 2 ? (l16 >> 1) : l16);
            auto scores = [&](float (&s0)[4], float (&s1)[4], const uint4 (&q)[4], const uint4 (&k)[4]) {
                float t0[4], t1[4];
                mma16816_z(s0, q[0].x, q[0].y, q[0].z, q[0].w, k[0].x, k[0].y);
                mma16816_z(s1, q[0].x, q[0].y, q[0].z, q[0].w, k[0].z, k[0].w);
                mma16816_z(t0, q[1].x, q[1].y, q[1].z, q[1].w, k[1].x, k[1].y);
                mma16816_z(t1, q[1].x, q[1].y, q[1].z, q[1].w, k[1].z, k[1].w);
                mma16816(s0, q[2].x, q[2].y, q[2].z, q[2].w, k[2].x, k[2].y);
                mma16816(s1, q[2].x, q[2].y, q[2].z, q[2].w, k[2].z, k[2].w);
                mma16816(t0, q[3].x, q[3].y, q[3].z, q[3].w, k[3].x, k[3].y);
                mma16816(t1, q[3].x, q[3].y, q[3].z, q[3].w, k[3].z, k[3].w);
#pragma unroll
                for (int i = 0; i < 4; i++) { s0[i] += t0[i]; s1[i] += t1[i]; }
            };
            auto x_scores = [&]() {
                float s0[4], s1[4];
                uint4 q[4], k[4];
#pragma unroll
                for (int i = 0; i < 4; i++) { q[i] = ldsm4(adr_q + i * 512); k[i] = ldsm4(adr_k + i * 512); }
                scores(s0, s1, q, k);
                const uint32_t dx = mapa(sb + O_SX + (s & 1) * 10240 + r * 5120 + mt * 2560 + doff, 2), bx = mapa(sb + B_SX + 8 * (s & 1), 2);
                if (kt != 2) {
                    st_async128(dx, __float_as_uint(s0[0]), __float_as_uint(s0[1]), __float_as_uint(s1[0]), __float_as_uint(s1[1]), bx);
                    st_async128(dx + 1280, __float_as_uint(s0[2]), __float_as_uint(s0[3]), __float_as_uint(s1[2]), __float_as_uint(s1[3]), bx);
                } else {
                    st_async64(dx, __float_as_uint(s0[0] + s1[0]), __float_as_uint(s0[1] + s1[1]), bx);
                    st_async64(dx + 1280, __float_as_uint(s0[2] + s1[2]), __float_as_uint(s0[3] + s1[3]), bx);
                }
            };
            if (s >= 0) {
#pragma unroll
                for (int kk = 0; kk < 4; kk++) {
                    const uint4 v = lds128(sb + O_AF + warp * 2048 + kk * 512 + l16);
                    a[32 + 4 * kk] = v.x; a[32 + 4 * kk + 1] = v.y; a[32 + 4 * kk + 2] = v.z; a[32 + 4 * kk + 3] = v.w;
                }
                float co[4], cw[3][4];
                uint4 b[14];
                float inv;
#define GORD(i) ((i) == 0 ? 0 : (i) == 1 ? 1 : (i) == 5 ? 2 : (i) == 9 ? 3 : (i) < 5 ? (i) + 2 : (i) < 9 ? (i) + 1 : (i))
                auto qkv_mma = [&](int i) {
                    const int gi = GORD(i), u = 8 * gi, n0 = 2 * i, n1 = 2 * i + 1;
                    if (gi < 4) {
                        if (i == 0) mma16816_z(co, a[u], a[u + 1], a[u + 2], a[u + 3], b[0].x, b[0].y);
                        else mma16816(co, a[u], a[u + 1], a[u + 2], a[u + 3], b[i].x, b[i].y);
                    }
                    if (n0 < 3) mma16816_z(cw[n0 % 3], a[32 + u], a[32 + u + 1], a[32 + u + 2], a[32 + u + 3], b[i].x, b[i].y);
                    else mma16816(cw[n0 % 3], a[32 + u], a[32 + u + 1], a[32 + u + 2], a[32 + u + 3], b[i].x, b[i].y);
                    if (n1 < 3) mma16816_z(cw[n1 % 3], a[32 + u + 4], a[32 + u + 5], a[32 + u + 6], a[32 + u + 7], b[i].z, b[i].w);
                    else mma16816(cw[n1 % 3], a[32 + u + 4], a[32 + u + 5], a[32 + u + 6], a[32 + u + 7], b[i].z, b[i].w);
                    if (gi < 4) mma16816(co, a[u + 4], a[u + 5], a[u + 6], a[u + 7], b[i].z, b[i].w);
                };
                const uint32_t mf = sb + O_MF + l16, mfs = mf + wg * 6144;
                bar_sync(2, 384);
                if (warp == 0) STAMP(s, 0);
#pragma unroll
                for (int i = 0; i < 17; i++) {
                    if (i < 14) b[i] = GORD(i) < 4 ? lds128(mfs + GORD(i) * 512) : lds128(mf + (GORD(i) < 12 ? GORD(i) : GORD(i) + 4) * 512);
                    if (i == 14) inv = __uint_as_float(lds32(sb + O_MISC));
                    if (i >= 3) qkv_mma(i - 3);
                }
#pragma unroll
                for (int i = 0; i < 4; i++) cw[0][i] += cw[1][i] + cw[2][i];
                if (r < 2) {
                    stsm4t(adr1, pack_bf16(co[0] * inv, co[1] * inv), pack_bf16(co[2] * inv, co[3] * inv),
                                 pack_bf16(cw[0][0] * inv, cw[0][1] * inv), pack_bf16(cw[0][2] * inv, cw[0][3] * inv));
                    if (warp == 0) STAMP(s, 1);
                    asm volatile("{\n.reg .pred p;\nsetp.ge.u32 p, %0, 3;\n@p bar.arrive 1, 256;\n}" :: "r"(warp) : "memory");
                    if (warp < 3) {
                        float s0[4], s1[4];
                        uint4 q[4], k[4];
#pragma unroll
                        for (int i = 0; i < 4; i++) k[i] = ldsm4(adr_k + i * 512);
                        bar_sync(1, 256);
#pragma unroll
                        for (int i = 0; i < 4; i++) q[i] = ldsm4(adr_q + i * 512);
                        if (warp == 2) {
#pragma unroll
                            for (int i = 0; i < 4; i++) k[i] = ldsm4(adr_k + i * 512);
                        }
                        scores(s0, s1, q, k);
                        const uint32_t dst = sb + O_SC + r * 1280 + doff;
                        const float v0 = s0[0] + s0[2], v1 = s0[1] + s0[3], v2 = s1[0] + s1[2], v3 = s1[1] + s1[3];
                        if (warp < 2) {
                            st_async128(mapa(dst, 2), __float_as_uint(v0), __float_as_uint(v1), __float_as_uint(v2), __float_as_uint(v3), mapa(sb + B_SC, 2));
                            st_async128(mapa(dst, r ^ 1), __float_as_uint(v0), __float_as_uint(v1), __float_as_uint(v2), __float_as_uint(v3), mapa(sb + B_SC, r ^ 1));
                            st_async128(mapa(dst, r), __float_as_uint(v0), __float_as_uint(v1), __float_as_uint(v2), __float_as_uint(v3), mapa(sb + B_SC, r));
                        } else {
                            st_async64(mapa(dst, 2), __float_as_uint(v0 + v2), __float_as_uint(v1 + v3), mapa(sb + B_SC, 2));
                            st_async64(mapa(dst, r ^ 1), __float_as_uint(v0 + v2), __float_as_uint(v1 + v3), mapa(sb + B_SC, r ^ 1));
                            st_async64(mapa(dst, r), __float_as_uint(v0 + v2), __float_as_uint(v1 + v3), mapa(sb + B_SC, r));
                            STAMP(s, 2);
                        }
                    }
                } else {
                    sts128f(sb + O_XP + warp * 512 + l16, co[0], co[1], co[2], co[3]);
                    bar_sync(8 + w, 64);
                    const float4 o = lds128f(sb + O_XP + (warp ^ 4) * 512 + l16);
                    const uint32_t X0 = pack_bf16((cw[0][0] + o.x) * inv, (cw[0][1] + o.y) * inv);
                    const uint32_t X1 = pack_bf16((cw[0][2] + o.z) * inv, (cw[0][3] + o.w) * inv);
                    if (warp == 0) STAMP(s, 1);
                    const uint32_t dst = adr1 + (s & 1) * 2048;
                    st_async64(mapa(dst, 0), X0, X1, mapa(sb + B_VM, 0));
                    st_async64(mapa(dst, 1), X0, X1, mapa(sb + B_VM, 1));
                    st_async64(mapa(dst, 2), X0, X1, mapa(sb + B_VM, 2));
                    if (warp == 0) STAMP(s, 2);
                }
            }
            if (s >= 0) bar_sync(3, 384);
            if (s == NSEG - 1) {
                if (r < 2 && warp >= 3) x_scores();
            } else {
                const int j = s + 1;
#define XDESC(u) (((u) < 8 ? descs : desc0) + (uint64_t)(((KS(u) >> 2) * 4096 + (KS(u) & 3) * 32) >> 4))
                const uint64_t descs = desc0 + (uint64_t)(wg * (6 * 4096 >> 4));
                float d[16];
                wg_fence();
#pragma unroll
                for (int u = 0; u < 8; u++) {
                    if (u == 0) wgmma_n32_rs<0>(d, a[0], a[1], a[2], a[3], XDESC(0));
                    else wgmma_n32_rs<1>(d, a[4 * u], a[4 * u + 1], a[4 * u + 2], a[4 * u + 3], XDESC(u));
                }
                wg_commit();
                wg_wait0();
                if (warp == 0) STAMP(s, 15);
                if (s >= 0) bar_sync(4, 384);
#pragma unroll
                for (int q = 0; q < 2; q++)
                    sts128(sb + O_XP + warp * 1024 + q * 512 + l16, pack_bf16(d[8 * q], d[8 * q + 1]), pack_bf16(d[8 * q + 2], d[8 * q + 3]),
                           pack_bf16(d[8 * q + 4], d[8 * q + 5]), pack_bf16(d[8 * q + 6], d[8 * q + 7]));
                if (s >= 0) {
                    if (warp == 1) { if (s + 2 < NSEG) tma_x_tile(sb, &tm_x, r, s + 2, s3 == 2 ? 0 : s3 + 1); }
                    else if (r < 2 && warp >= 3) x_scores();
                }
                bar_sync(12, 256);
#pragma unroll
                for (int q = 0; q < 2; q++) {
                    const uint4 o = lds128(sb + O_XP + (warp ^ 4) * 1024 + q * 512 + l16);
                    d[8 * q] = __uint_as_float(o.x << 16); d[8 * q + 1] = __uint_as_float(o.x & 0xffff0000u);
                    d[8 * q + 2] = __uint_as_float(o.y << 16); d[8 * q + 3] = __uint_as_float(o.y & 0xffff0000u);
                    d[8 * q + 4] = __uint_as_float(o.z << 16); d[8 * q + 5] = __uint_as_float(o.z & 0xffff0000u);
                    d[8 * q + 6] = __uint_as_float(o.w << 16); d[8 * q + 7] = __uint_as_float(o.w & 0xffff0000u);
                }
                if (s >= 0) {
                    if (warp == 6 && r == 2 && (s & 3) == 1 && s >= 5)
                        asm volatile("{\n.reg .pred p;\nsetp.eq.u32 p, %1, 0;\n@p red.release.gpu.global.inc.u32 [%0], 0x7fffffff;\n}"
                                     :: "l"(&g_flag[((s - 2) * 4 + (h >> 3)) * 8]), "r"(l16) : "memory");
                    asm volatile("{\n.reg .pred p;\nsetp.eq.u32 p, %0, 0;\n@p bar.sync 5, 256;\n@!p bar.sync 13, 256;\n}" :: "r"(wg) : "memory");
                }
                const uint64_t da0 = (uint64_t)(((sb + O_AS + wg * 8192) & 0x3FFFF) >> 4) | (1ull << 16) | (64ull << 32) | (1ull << 62);
                wg_fence();
#pragma unroll
                for (int u = 0; u < 4; u++) wgmma_n32_ss<1>(d, da0 + 2 * u, XDESC(u));
#pragma unroll
                for (int u = 4; u < 28; u++) wgmma_n32_rs<1>(d, a[32 + 4 * u], a[32 + 4 * u + 1], a[32 + 4 * u + 2], a[32 + 4 * u + 3], XDESC(u));
                wg_commit();
                wg_wait0();
                if (warp == 4) STAMP(s, 3);
                uint32_t e[8];
#pragma unroll
                for (int i = 0; i < 8; i++) e[i] = pack_bf16(d[2 * i], d[2 * i + 1]);
                if (r < 2) {
                    const uint32_t base = sb + O_QKX + wg * 4096 + w * 512 + l16;
                    stsm4t(base, e[0], wg ? e[1] : e[2], wg ? e[2] : e[1], e[3]);
                    stsm4t(base + 2048, e[4], wg ? e[5] : e[6], wg ? e[6] : e[5], e[7]);
                } else {
                    const uint32_t base = sb + O_VX + s3 * 8192 + warp * 1024 + l16;
                    sts128(base, e[0], e[1], e[2], e[3]);
                    sts128(base + 512, e[4], e[5], e[6], e[7]);
                    const uint32_t bar = sb + B_VX + 8 * (j & 1);
                    fence_async_smem();
                    __syncwarp();
                    const uint32_t src = sb + O_VX + s3 * 8192 + warp * 1024;
                    asm volatile("{\n.reg .pred p;\nelect.sync _|p, 0xffffffff;\n"
                        "@p cp.async.bulk.shared::cluster.shared::cta.mbarrier::complete_tx::bytes [%0], [%2], 1024, [%3];\n"
                        "@p cp.async.bulk.shared::cluster.shared::cta.mbarrier::complete_tx::bytes [%1], [%2], 1024, [%4];\n}"
                        :: "r"(mapa(src, 0)), "r"(mapa(src, 1)), "r"(src), "r"(mapa(bar, 0)), "r"(mapa(bar, 1)) : "memory");
                }
                if (warp == 7) STAMP(s, 4);
            }
        }
    } else {
        asm volatile("setmaxnreg.dec.sync.aligned.u32 152;");
        const int c = w;
        uint32_t a[96];
        uint32_t mmax = 0;
        {
            const int g = lane >> 2, t = lane & 3, t2 = threadIdx.x - 256;
            if (c == 0) {
                tma_x_tile(sb, &tm_x, r, 0, 0);
                tma_x_tile(sb, &tm_x, r, 1, 1);
                mbar_expect_if(lane, sb + B_SC, 2560);
                mbar_expect_if(lane, sb + B_VM, 2048);
                mbar_expect_if(lane, sb + (r < 2 ? B_VX : B_SX), 8192);
                sts32_if(lane, sb + O_MISC, __float_as_uint(1.0f));
            }
#pragma unroll
            for (int i = 0; i < 4; i++) g_acc[(blockIdx.x * 64 + i * 16 + (t2 >> 3)) * 16 + (t2 & 7)] = make_uint4(0, 0, 0, 0);
#pragma unroll
            for (int tau = 0; tau < 3; tau++) {
                uint32_t v[6];
#pragma unroll
                for (int i = 0; i < 3; i++) {
                    const uint32_t* p = reinterpret_cast<const uint32_t*>(mem0 + g * DM + 16 * (12 * tau + 4 * i + c) + 2 * t);
                    v[2 * i] = __ldg(p); v[2 * i + 1] = __ldg(p + 4);
                    mmax = __vmaxu2(mmax, __vmaxu2(v[2 * i] & 0x7fff7fffu, v[2 * i + 1] & 0x7fff7fffu));
                }
                sts128(sb + O_MF + tau * 3072 + c * 512 + lane * 16, v[0], v[1], v[2], v[3]);
                sts64(sb + O_MF + tau * 3072 + 2048 + (c >> 1) * 512 + lane * 16 + (c & 1) * 8, v[4], v[5]);
            }
            mmax = max(mmax << 16, mmax & 0xffff0000u);
            bar_arrive(2, 384);
            uint32_t xm = 0;
            const uint4* xp = reinterpret_cast<const uint4*>(x) + blockIdx.x * 1536 + t2;
#pragma unroll
            for (int i = 0; i < 12; i++) {
                uint4 v = __ldg(xp + i * 128);
                xm = __vmaxu2(xm, __vmaxu2(__vmaxu2(v.x & 0x7fff7fffu, v.y & 0x7fff7fffu), __vmaxu2(v.z & 0x7fff7fffu, v.w & 0x7fff7fffu)));
            }
            xm = __reduce_max_sync(~0u, max(xm << 16, xm & 0xffff0000u));

            const __nv_bfloat16* p = Wo + (size_t)(h * 128 + 4 * t) * DM + 192 * r + 16 * c + 2 * g;
#pragma unroll
            for (int i = 0; i < 3; i++)
#pragma unroll
                for (int eb = 0; eb < 8; eb++)
#pragma unroll
                    for (int j = 0; j < 4; j++) a[(i * 8 + eb) * 4 + j] = ldg_nc32(p + (16 * eb + ((j & 1) * 2 + (j >> 1))) * DM + 64 * i);
#pragma unroll
            for (int kk = 0; kk < 48; kk++) {
                uint32_t w0 = a[2 * kk], w1 = a[2 * kk + 1];
                a[2 * kk] = __byte_perm(w0, w1, 0x5410);
                a[2 * kk + 1] = __byte_perm(w0, w1, 0x7632);
            }
            float wmax = 0.f;
#pragma unroll
            for (int i = 0; i < 3; i++) {
                float s0 = 0.f, s1 = 0.f;
#pragma unroll
                for (int kk = 16 * i; kk < 16 * i + 16; kk++) {
                    s0 += fabsf(__uint_as_float(a[2 * kk] << 16)) + fabsf(__uint_as_float(a[2 * kk] & 0xffff0000u));
                    s1 += fabsf(__uint_as_float(a[2 * kk + 1] << 16)) + fabsf(__uint_as_float(a[2 * kk + 1] & 0xffff0000u));
                }
                s0 += __shfl_xor_sync(~0u, s0, 1); s0 += __shfl_xor_sync(~0u, s0, 2);
                s1 += __shfl_xor_sync(~0u, s1, 1); s1 += __shfl_xor_sync(~0u, s1, 2);
                wmax = fmaxf(wmax, fmaxf(s0, s1));
            }
            uint32_t wm = __reduce_max_sync(~0u, __float_as_uint(wmax));
            sts32_if(lane, sb + O_OF + 4 * c, wm); sts32_if(lane, sb + O_OF + 16 + 4 * c, xm);
            __threadfence();
            bar_sync(7, 384);
            if (c == 0) {
                const uint4 wq = lds128(sb + O_OF), xq = lds128(sb + O_OF + 16), v0 = lds128(sb + O_MISC + 32), v1 = lds128(sb + O_MISC + 48);
                const uint32_t w1 = max(max(wq.x, wq.y), max(wq.z, wq.w)), x1 = max(max(xq.x, xq.y), max(xq.z, xq.w));
                const uint32_t vv = (r < 2) ? 0u : max(max(max(v0.x, v0.y), max(v0.z, v0.w)), max(max(v1.x, v1.y), max(v1.z, v1.w)));
                unsigned old = 0;
                asm volatile("{\n.reg .pred p;\nsetp.eq.u32 p, %6, 0;\n@p st.global.v4.u32 [%1], {%2,%3,%4,%4};\nfence.acq_rel.gpu;\n@p atom.relaxed.gpu.global.add.u32 %0, [%5], 1;\n}"
                             : "+r"(old) : "l"(&g_norm[blockIdx.x * 4]), "r"(w1), "r"(vv), "r"(x1), "l"(&g_gridbar), "r"(lane) : "memory");
                old = __shfl_sync(~0u, old, 0);
                const unsigned target = (old / 96u + 1u) * 96u;
                asm volatile("{\n.reg .pred p;\n.reg .u32 n, v;\nmov.u32 n, 0;\n"
                             "G_%=: ld.acquire.gpu.global.u32 v, [%0];\nsub.u32 v, v, %1;\nsetp.ge.s32 p, v, 0;\n@p bra.uni E_%=;\n"
                             "add.u32 n, n, 1;\nsetp.lt.u32 p, n, 4000000;\n@p bra.uni G_%=;\ntrap;\nE_%=:\n}" :: "l"(&g_gridbar), "r"(target) : "memory");
                uint4 n0 = ldg_relaxed128(&g_norm[lane * 4]), n1 = ldg_relaxed128(&g_norm[(lane + 32) * 4]), n2 = ldg_relaxed128(&g_norm[(lane + 64) * 4]);
                const float fw = __uint_as_float(__reduce_max_sync(~0u, max(n0.x, max(n1.x, n2.x))));
                const float fv = __uint_as_float(__reduce_max_sync(~0u, max(n0.y, max(n1.y, n2.y))));
                const float xmax = __uint_as_float(__reduce_max_sync(~0u, max(n0.z, max(n1.z, n2.z))));
                const float G = 36.f * fw * fv;
                sts32_if(lane, sb + O_MISC + 4, __float_as_uint(G)); sts32_if(lane, sb + O_MISC + 8, __float_as_uint(G * xmax));
            }
        }
        bar_sync(6, 128);
        int s3p = 2;
        uint32_t PX[5] = {0u, 0u, 0u, 0u, 0u};
        char* rptr; int pdelta; char* optr;
        {
            const uint32_t roff = (r * 4 + c) * 2048 + (lane >> 4) * 512 + (lane & 2) * 128 + (lane & 1) * 64 + (lane & 12) * 4;
            const uint32_t poff = c * 2048 + (lane & 4) * 256 + (lane >> 4) * 256 + (lane & 8) * 8 + (lane & 3) * 16;
            rptr = reinterpret_cast<char*>(g_acc) + roff;
            pdelta = __shfl_sync(~0u, (int)poff - (int)roff, lane);
            optr = reinterpret_cast<char*>(g_ox) + ((size_t)(h * 2) * SEQ + 8 * c) * 128 + lane * 16 - 4096;
        }
#pragma unroll 1
        for (int s = 0; s <= NSEG; s++) {
            const uint32_t l16 = opaque(l16c);
            const int s3 = (s3p == 2) ? 0 : s3p + 1;
            unsigned t_red = 0;
            sts32_if(l16, sb + O_MISC + 16 + 4 * c, __reduce_max_sync(~0u, mmax));
            if (c == 0) STAMP(s < NSEG ? s : -1, 5);
            if (r == 2) {
                float sm[4];
                mma1688_z(sm, ONES, ONES, PX[0]);
                mma16816(sm, ONES, ONES, ONES, ONES, PX[1], PX[2]);
                mma16816(sm, ONES, ONES, ONES, ONES, PX[3], PX[4]);
                const uint32_t row = (l16 >> 4) & 7;
                const uint32_t stg = sb + O_OXS + c * 2048 + row * 128 + (((l16 >> 7) ^ row) << 4);
#pragma unroll
                for (int eh = 0; eh < 2; eh++) {
                    const uint32_t vmb = sb + O_VM + ((s - 1) & 1) * 2048 + eh * 1024 + (l16 >> 1);
                    const uint32_t vb = sb + O_VX + s3p * 8192 + eh * 4096 + l16;
                    const uint4 vm0 = lds64x2(vmb), vm1 = lds64x2(vmb + 512);
                    float o[4][4];
                    uint4 v[4];
#pragma unroll
                    for (int q = 0; q < 4; q++) v[q] = lds128(vb + q * 1024);
                    mma1688_z(o[0], vm0.x, vm0.y, PX[0]); mma1688_z(o[1], vm0.z, vm0.w, PX[0]);
                    mma1688_z(o[2], vm1.x, vm1.y, PX[0]); mma1688_z(o[3], vm1.z, vm1.w, PX[0]);
#pragma unroll
                    for (int q = 0; q < 4; q++) mma16816(o[q], v[q].x, v[q].y, v[q].z, v[q].w, PX[1], PX[2]);
                    if (c >= 2) {
#pragma unroll
                        for (int q = 0; q < 4; q++) v[q] = lds128(vb + q * 1024 + 512);
#pragma unroll
                        for (int q = 0; q < 4; q++) mma16816(o[q], v[q].x, v[q].y, v[q].z, v[q].w, PX[3], PX[4]);
                    }
                    const float r0 = rcp_fast(sm[0]), r1 = rcp_fast(sm[1]);
#pragma unroll
                    for (int e2 = 0; e2 < 2; e2++)
                        stsm4t((stg ^ (e2 * 64)) + eh * 1024, pack_bf16(o[2 * e2][0] * r0, o[2 * e2][1] * r1), pack_bf16(o[2 * e2][2] * r0, o[2 * e2][3] * r1),
                               pack_bf16(o[2 * e2 + 1][0] * r0, o[2 * e2 + 1][1] * r1), pack_bf16(o[2 * e2 + 1][2] * r0, o[2 * e2 + 1][3] * r1));
                }
                __syncwarp();
            }
            if (s < NSEG - 1) {
                bar_sync(6, 128);
                const uint4 mm = lds128(sb + O_MISC + 16), cf = lds128(sb + O_MISC);
                const float bound = fmaxf(__uint_as_float(cf.z), __uint_as_float(cf.y) * (__uint_as_float(max(max(mm.x, mm.y), max(mm.z, mm.w))) * __uint_as_float(cf.x)));
                const uint32_t ebits = min(max(__float_as_uint(bound) & 0x7f800000u, 21u << 23), 254u << 23);
                if (r < 2) mbar_wait(sb + B_VX + 8 * (s & 1), (s >> 1) & 1);
                bar_sync(3, 384);
                uint4 vx[4];
#pragma unroll
                for (int q = 0; q < 4; q++) vx[q] = lds128(sb + O_VX + s3 * 8192 + c * 2048 + q * 512 + l16);
                mbar_wait(sb + B_VM, s & 1);
                const uint4 vm = lds64x2(sb + O_VM + (s & 1) * 2048 + c * 512 + (l16 >> 1));
                if (c == 0) STAMP(s, 13);
                mbar_wait(sb + B_SC, s & 1);
                if (c == 0) STAMP(s, 6);
                float p[10];
                load_scores(p, sb + O_SC, 1280, l16);
                float mx = fmaxf(fmaxf(fmaxf(p[0], p[1]), fmaxf(p[2], p[3])), fmaxf(fmaxf(p[4], p[5]), fmaxf(p[6], p[7])));
                mx = quad_max(fmaxf(mx, fmaxf(p[8], p[9])));
                const float mo = mx * SM_SCALE;
                asm volatile("bar.arrive 4, 384;" :: "f"(mo) : "memory");
                uint32_t P[5];
#pragma unroll
                for (int n = 0; n < 5; n++) P[n] = pack_bf16(ex2(fmaf(p[2 * n], SM_SCALE, -mo)), ex2(fmaf(p[2 * n + 1], SM_SCALE, -mo)));
                if (c == 0) STAMP(s, 7);
                float o0[4], o1[4], sm[4];
                mma1688_z(sm, ONES, ONES, P[0]);
                mma1688_z(o0, vm.x, vm.y, P[0]);
                mma1688_z(o1, vm.z, vm.w, P[0]);
                mma16816(sm, ONES, ONES, ONES, ONES, P[1], P[2]);
                mma16816(o0, vx[0].x, vx[0].y, vx[0].z, vx[0].w, P[1], P[2]);
                mma16816(o1, vx[2].x, vx[2].y, vx[2].z, vx[2].w, P[1], P[2]);
                mma16816(sm, ONES, ONES, ONES, ONES, P[3], P[4]);
                mma16816(o0, vx[1].x, vx[1].y, vx[1].z, vx[1].w, P[3], P[4]);
                mma16816(o1, vx[3].x, vx[3].y, vx[3].z, vx[3].w, P[3], P[4]);
                const float sig = __uint_as_float((268u << 23) - ebits);
                const float r0 = rcp_fast(sm[0]) * sig, r1 = rcp_fast(sm[1]) * sig;
                stsm4t(sb + O_OF + c * 512 + l16, pack_bf16(o0[0] * r0, o0[1] * r1), pack_bf16(o0[2] * r0, o0[3] * r1),
                       pack_bf16(o1[0] * r0, o1[1] * r1), pack_bf16(o1[2] * r0, o1[3] * r1));
                bar_sync(6, 128);
                uint4 ob[4];
#pragma unroll
                for (int q = 0; q < 4; q++) ob[q] = ldsm4(sb + O_OF + q * 512 + l16);
                float m0[3][4], m1[3][4];
#pragma unroll
                for (int q = 0; q < 4; q++) {
#pragma unroll
                    for (int i = 0; i < 3; i++) {
                        const int k0 = (i * 8 + 2 * q) * 4;
                        if (q == 0) mma16816_z(m0[i], a[k0], a[k0 + 1], a[k0 + 2], a[k0 + 3], ob[q].x, ob[q].y);
                        else mma16816(m0[i], a[k0], a[k0 + 1], a[k0 + 2], a[k0 + 3], ob[q].x, ob[q].y);
                    }
#pragma unroll
                    for (int i = 0; i < 3; i++) {
                        const int k1 = (i * 8 + 2 * q + 1) * 4;
                        if (q == 0) mma16816_z(m1[i], a[k1], a[k1 + 1], a[k1 + 2], a[k1 + 3], ob[q].z, ob[q].w);
                        else mma16816(m1[i], a[k1], a[k1 + 1], a[k1 + 2], a[k1 + 3], ob[q].z, ob[q].w);
                    }
                }
                asm volatile("red.relaxed.gpu.global.add.noftz.v4.f16x2 [%0], {%1,%2,%3,%4};" :: "l"(rptr),
                    "r"(pack_f16(m0[0][0] + m1[0][0], m0[0][2] + m1[0][2])), "r"(pack_f16(m0[1][0] + m1[1][0], m0[1][2] + m1[1][2])),
                    "r"(pack_f16(m0[2][0] + m1[2][0], m0[2][2] + m1[2][2])), "r"(0x3c00u) : "memory");
                asm volatile("red.relaxed.gpu.global.add.noftz.v4.f16x2 [%0], {%1,%2,%3,%4};" :: "l"(rptr + 1024),
                    "r"(pack_f16(m0[0][1] + m1[0][1], m0[0][3] + m1[0][3])), "r"(pack_f16(m0[1][1] + m1[1][1], m0[1][3] + m1[1][3])),
                    "r"(pack_f16(m0[2][1] + m1[2][1], m0[2][3] + m1[2][3])), "r"(0x3c00u) : "memory");
                t_red = clk();
                bar_arrive(5, 256);
                bar_arrive(13, 256);
                {
                    const uint32_t bar = sb + (c == 0 ? B_SC : c == 1 ? B_VM : (r < 2 ? B_VX : B_SX) + 8 * ((s + 1) & 1));
                    mbar_expect_if(l16 | (uint32_t)(c == 3), bar, c == 0 ? 2560 : c == 1 ? 2048 : 8192);
                    sts32_if(l16 | (c ^ 3), sb + O_MISC, ebits - (14u << 23));
                }
                if (c == 0) STAMPV(s, 8, t_red);
            } else if (s == NSEG - 1) {
                bar_sync(3, 384);
                mbar_wait(sb + B_VM, s & 1);
                mbar_wait(sb + B_SC, s & 1);
                if (r < 2) { mbar_wait(sb + B_VX + 8 * (s & 1), (s >> 1) & 1); break; }
            }
            float px[10], mxx = 0.f;
#pragma unroll
            for (int i = 0; i < 10; i++) px[i] = 0.f;
            if (r == 2) {
                if (s >= 1) {
#pragma unroll
                    for (int q = 0; q < 4; q++) {
                        const uint4 u = lds128(sb + O_OXS + c * 2048 + q * 512 + l16);
                        *reinterpret_cast<uint4*>(optr + (q >> 1) * (SEQ * 128) + (q & 1) * 512) = u;
                    }
                }
                if (s == NSEG) break;
                mbar_wait(sb + B_SX + 8 * (s & 1), (s >> 1) & 1);
                const int q0 = 8 * c + 8 + (int)(l16 >> 6) - (int)((l16 >> 3) & 6);
                load_scores(px, sb + O_SX + (s & 1) * 10240 + c * 1280, 5120, l16);
#pragma unroll
                for (int n = 1; n < 5; n++) {
                    if (8 * n > q0) px[2 * n] = -INFINITY;
                    if (8 * n + 1 > q0) px[2 * n + 1] = -INFINITY;
                }
                mxx = fmaxf(fmaxf(fmaxf(px[0], px[1]), fmaxf(px[2], px[3])), fmaxf(fmaxf(px[4], px[5]), fmaxf(px[6], px[7])));
                mxx = fmaxf(mxx, fmaxf(px[8], px[9]));
            }
            auto finish_x = [&]() {
                const float mo = quad_max(mxx) * SM_SCALE;
#pragma unroll
                for (int n = 0; n < 5; n++) PX[n] = pack_bf16(ex2v(fmaf(px[2 * n], SM_SCALE, -mo)), ex2v(fmaf(px[2 * n + 1], SM_SCALE, -mo)));
            };
            if (s >= NSEG - 1) {
                finish_x();
            } else {
                if (c == 0) STAMP(s, 9);
                const char* pbase = rptr + pdelta;
                spin_until(t_red, D_WAIT);
                uint4 v[6];
#pragma unroll
                for (int i = 0; i < 6; i++) v[i] = ldg_relaxed128(pbase + (i >> 1) * 8192 + (i & 1) * 512);
                finish_x();
                int nretry = 0;
                auto hand_over = [&]() -> uint32_t {
                    const uint32_t ok = __all_sync(~0u, (v[0].w & v[1].w & v[2].w & v[3].w & v[4].w & v[5].w) == 0x5000u);
#pragma unroll
                    for (int tau = 0; tau < 3; tau++) {
                        v[2 * tau].x = f16x2_to_bf16x2(v[2 * tau].x); v[2 * tau + 1].x = f16x2_to_bf16x2(v[2 * tau + 1].x);
                        v[2 * tau].y = f16x2_to_bf16x2(v[2 * tau].y); v[2 * tau + 1].y = f16x2_to_bf16x2(v[2 * tau + 1].y);
                        v[2 * tau].z = f16x2_to_bf16x2(v[2 * tau].z); v[2 * tau + 1].z = f16x2_to_bf16x2(v[2 * tau + 1].z);
                        sts128(sb + O_MF + tau * 3072 + c * 512 + l16, v[2 * tau].x, v[2 * tau + 1].x, v[2 * tau].y, v[2 * tau + 1].y);
                        sts64(sb + O_MF + tau * 3072 + 2048 + (c >> 1) * 512 + (c & 1) * 8 + l16, v[2 * tau].z, v[2 * tau + 1].z);
                    }
                    asm volatile("{\n.reg .pred p;\nsetp.ne.u32 p, %0, 0;\n@p bar.arrive 2, 384;\n}" :: "r"(ok) : "memory");
                    return ok;
                };
                if (!hand_over()) {
                    asm volatile("{\n.reg .pred p, q;\n.reg .u32 n, x;\nmov.u32 n, 0;\n"
                         "R_%=: ld.relaxed.gpu.global.v4.u32 {%0,%1,%2,%3}, [%25];\nld.relaxed.gpu.global.v4.u32 {%4,%5,%6,%7}, [%25+512];\n"
                         "ld.relaxed.gpu.global.v4.u32 {%8,%9,%10,%11}, [%25+8192];\nld.relaxed.gpu.global.v4.u32 {%12,%13,%14,%15}, [%25+8704];\n"
                         "ld.relaxed.gpu.global.v4.u32 {%16,%17,%18,%19}, [%25+16384];\nld.relaxed.gpu.global.v4.u32 {%20,%21,%22,%23}, [%25+16896];\n"
                         "add.u32 %24, %24, 1;\nand.b32 x, %3, %7;\nand.b32 x, x, %11;\nand.b32 x, x, %15;\nand.b32 x, x, %19;\nand.b32 x, x, %23;\n"
                         "setp.eq.u32 p, x, 0x5000;\nvote.sync.all.pred q, p, 0xffffffff;\n@q bra.uni K_%=;\n"
                         "add.u32 n, n, 1;\nsetp.lt.u32 q, n, 2000000;\n@q bra.uni R_%=;\ntrap;\nK_%=:\n}"
                         : "+r"(v[0].x), "+r"(v[0].y), "+r"(v[0].z), "+r"(v[0].w), "+r"(v[1].x), "+r"(v[1].y), "+r"(v[1].z), "+r"(v[1].w),
                           "+r"(v[2].x), "+r"(v[2].y), "+r"(v[2].z), "+r"(v[2].w), "+r"(v[3].x), "+r"(v[3].y), "+r"(v[3].z), "+r"(v[3].w),
                           "+r"(v[4].x), "+r"(v[4].y), "+r"(v[4].z), "+r"(v[4].w), "+r"(v[5].x), "+r"(v[5].y), "+r"(v[5].z), "+r"(v[5].w), "+r"(nretry)
                         : "l"(pbase) : "memory");
                    hand_over();
                }
                if (c == 0) STAMP(s, 12);
                if (c == 0) STAMPV(s, 14, nretry);
                mmax = absmax2(absmax2(absmax2(v[0].x, v[0].y), absmax2(v[0].z, v[1].x)), absmax2(absmax2(v[1].y, v[1].z), absmax2(v[2].x, v[2].y)));
                mmax = absmax2(mmax, absmax2(absmax2(absmax2(v[2].z, v[3].x), absmax2(v[3].y, v[3].z)), absmax2(absmax2(v[4].x, v[4].y), absmax2(v[4].z, v[5].x))));
                mmax = absmax2(mmax, absmax2(v[5].y, v[5].z)) & 0x7fff7fffu;
                mmax = max(mmax << 16, mmax & 0xffff0000u);
            }
            s3p = s3;
            rptr += 24576;
            optr += 4096;
        }
        if (r == 2) {
            bar_sync(6, 128);
            if (c == 0)
                asm volatile("{\n.reg .pred p;\nsetp.eq.u32 p, %1, 0;\n@p red.release.gpu.global.inc.u32 [%0], 0x7fffffff;\n}"
                             :: "l"(&g_flag[(63 * 4 + (h >> 3)) * 8]), "r"(l16c) : "memory");
        }
    }
    cluster_sync();
}

__device__ float g_u[SEQ * 2 * DM];
__global__ void naive_gemm1(const __nv_bfloat16* x, const __nv_bfloat16* Bre, const __nv_bfloat16* Bim) {
    int p = blockIdx.x * 64 + threadIdx.x % 64, tk = blockIdx.y * 4 + threadIdx.x / 64;
    float sr = 0, si = 0;
    for (int d = 0; d < DM; d++) { float xv = __bfloat162float(x[tk * DM + d]); sr += xv * __bfloat162float(Bre[p * DM + d]); si += xv * __bfloat162float(Bim[p * DM + d]); }
    g_u[tk * 2 * DM + 2 * p] = sr; g_u[tk * 2 * DM + 2 * p + 1] = si;
}
__global__ void naive_scan(const __nv_bfloat16* Lre, const __nv_bfloat16* Lim, const __nv_bfloat16* logdt) {
    int p = blockIdx.x * 64 + threadIdx.x;
    float dt = __bfloat162float(__float2bfloat16(expf(__bfloat162float(logdt[p]))));
    float lr = __bfloat162float(Lre[p]), li = __bfloat162float(Lim[p]);
    float e = expf(dt * lr), br = e * cosf(dt * li), bi = e * sinf(dt * li);
    float den = lr * lr + li * li;
    float cr = ((br - 1.f) * lr + bi * li) / den, ci = (bi * lr - (br - 1.f) * li) / den;
    float hr = 0, hi = 0;
    for (int tk = 0; tk < SEQ; tk++) {
        float ur = g_u[tk * 2 * DM + 2 * p], ui = g_u[tk * 2 * DM + 2 * p + 1];
        float nr = br * hr - bi * hi + cr * ur - ci * ui, ni = br * hi + bi * hr + cr * ui + ci * ur;
        hr = nr; hi = ni;
        g_u[tk * 2 * DM + 2 * p] = hr; g_u[tk * 2 * DM + 2 * p + 1] = hi;
    }
}
__global__ void naive_gemm2(const __nv_bfloat16* x, const __nv_bfloat16* Cre, const __nv_bfloat16* Cim, const __nv_bfloat16* Dk, float* out) {
    int d = blockIdx.x * 64 + threadIdx.x % 64, tk = blockIdx.y * 4 + threadIdx.x / 64;
    float s = 0;
    for (int p = 0; p < DM; p++) s += g_u[tk * 2 * DM + 2 * p] * __bfloat162float(Cre[d * DM + p]) - g_u[tk * 2 * DM + 2 * p + 1] * __bfloat162float(Cim[d * DM + p]);
    out[tk * 1152 + d] = 2.f * s + __bfloat162float(__float2bfloat16(__bfloat162float(x[tk * DM + d]) * __bfloat162float(Dk[d])));
}
__global__ void naive_wo(const __nv_bfloat16* Wo, float* out) {
    int d = blockIdx.x * 64 + threadIdx.x % 64, tk = blockIdx.y * 4 + threadIdx.x / 64;
    const __nv_bfloat16* ox = reinterpret_cast<const __nv_bfloat16*>(g_ox);
    float s = 0;
    for (int k = 0; k < HD; k++) {
        int hh = k >> 6, e0 = k & 63, e = (e0 & 48) + (e0 & 1) * 8 + ((e0 & 15) >> 1);
        s += __bfloat162float(ox[((size_t)hh * SEQ + tk) * 64 + (((e >> 3) ^ (tk & 7)) << 3) + (e & 7)]) * __bfloat162float(Wo[k * DM + d]);
    }
    out[tk * 1152 + DM + d] = s;
}

typedef CUresult (*EncodeFn)(CUtensorMap*, CUtensorMapDataType, cuuint32_t, void*, const cuuint64_t*, const cuuint64_t*, const cuuint32_t*, const cuuint32_t*,
                             CUtensorMapInterleave, CUtensorMapSwizzle, CUtensorMapL2promotion, CUtensorMapFloatOOBfill);
}

extern "C" void kernel_launch(void* const* d_in, const int* in_sizes, int n_in, void* d_out, int out_size) {
    typedef const __nv_bfloat16* bp;
    bp Ax = (bp)d_in[0], Lre = (bp)d_in[1], Lim = (bp)d_in[2], Bre = (bp)d_in[3], Bim = (bp)d_in[4], Cre = (bp)d_in[5], Cim = (bp)d_in[6],
       logdt = (bp)d_in[7], Dk = (bp)d_in[8], Bx = (bp)d_in[9], mem0 = (bp)d_in[10], Wq = (bp)d_in[11], Wk = (bp)d_in[12], Wv = (bp)d_in[13], Wo = (bp)d_in[14];
    float* out = (float*)d_out;
    static EncodeFn enc = nullptr;
    if (!enc) {
        void* fn = nullptr; cudaDriverEntryPointQueryResult qr;
        cudaGetDriverEntryPoint("cuTensorMapEncodeTiled", &fn, cudaEnableDefault, &qr);
        enc = (EncodeFn)fn;
        cudaFuncSetAttribute(chain_kernel, cudaFuncAttributeMaxDynamicSharedMemorySize, CHAIN_SMEM);
    }
    CUtensorMap tm_x;
    {
        cuuint64_t gd[2] = {DM, SEQ}; cuuint64_t gs[1] = {DM * 2}; cuuint32_t bd[2] = {64, 32}; cuuint32_t es[2] = {1, 1};
        enc(&tm_x, CU_TENSOR_MAP_DATA_TYPE_BFLOAT16, 2, (void*)Bx, gd, gs, bd, es, CU_TENSOR_MAP_INTERLEAVE_NONE, CU_TENSOR_MAP_SWIZZLE_128B,
            CU_TENSOR_MAP_L2_PROMOTION_L2_128B, CU_TENSOR_MAP_FLOAT_OOB_FILL_NONE);
    }
    cudaStream_t st = cudaStreamPerThread;
    chain_kernel<<<96, 384, CHAIN_SMEM, st>>>(tm_x, Bx, mem0, Wq, Wk, Wv, Wo);
    naive_gemm1<<<dim3(9, 512), 256, 0, st>>>(Ax, Bre, Bim);
    naive_scan<<<9, 64, 0, st>>>(Lre, Lim, logdt);
    naive_gemm2<<<dim3(9, 512), 256, 0, st>>>(Ax, Cre, Cim, Dk, out);
    naive_wo<<<dim3(9, 512), 256, 0, st>>>(Wo, out);
}
```

```cpp
#include <cuda_runtime.h>
#include <cuda.h>
#include <cuda_bf16.h>
#include <cuda_fp16.h>
#include <stdint.h>

#define D_WAIT 700

namespace {

constexpr int DM = 576, NH = 32, SEQ = 2048, NSEG = 64, HD = 4096;

__device__ uint4 g_acc[64 * 96 * 16];
__device__ uint4 g_ox[NH * 2 * SEQ * 8];
__device__ uint4 g_qkv[NSEG * NH * 3 * 512];
__device__ uint2 g_kvm[NSEG * NH * 3 * 256];
__device__ unsigned g_flag[NSEG * 4 * 8];
__device__ unsigned g_gridbar;
__device__ float g_norm[96 * 4];

__device__ __forceinline__ uint32_t smem_u32(const void* p) { return (uint32_t)__cvta_generic_to_shared(p); }
__device__ __forceinline__ uint32_t mapa(uint32_t a, uint32_t r) { uint32_t o; asm("mapa.shared::cluster.u32 %0, %1, %2;" : "=r"(o) : "r"(a), "r"(r)); return o; }
__device__ __forceinline__ uint32_t mapa_v(uint32_t a, uint32_t r) { uint32_t o; asm volatile("mapa.shared::cluster.u32 %0, %1, %2;" : "=r"(o) : "r"(a), "r"(r)); return o; }
__device__ __forceinline__ unsigned clk() { unsigned long long c; asm volatile("mov.u64 %0, %%clock64;" : "=l"(c) :: "memory"); return (unsigned)c; }
__device__ __forceinline__ void mbar_init(uint32_t bar, uint32_t cnt) { asm volatile("mbarrier.init.shared::cta.b64 [%0], %1;" :: "r"(bar), "r"(cnt) : "memory"); }
__device__ __forceinline__ void mbar_expect(uint32_t bar, uint32_t bytes) { asm volatile("mbarrier.arrive.expect_tx.shared::cta.b64 _, [%0], %1;" :: "r"(bar), "r"(bytes) : "memory"); }
__device__ __forceinline__ void mbar_wait(uint32_t bar, uint32_t parity) {
    asm volatile("{\n.reg .pred p;\n.reg .u32 n;\nmov.u32 n, 0;\n"
                 "W_%=: mbarrier.try_wait.parity.shared::cta.b64 p, [%0], %1;\n@p bra.uni D_%=;\n"
                 "add.u32 n, n, 1;\nsetp.lt.u32 p, n, 4000000;\n@p bra.uni W_%=;\ntrap;\nD_%=:\n}" :: "r"(bar), "r"(parity) : "memory");
}
__device__ __forceinline__ void mbar_expect_if(uint32_t z, uint32_t bar, uint32_t bytes) {
    asm volatile("{\n.reg .pred p;\nsetp.eq.u32 p, %2, 0;\n@p mbarrier.arrive.expect_tx.shared::cta.b64 _, [%0], %1;\n}" :: "r"(bar), "r"(bytes), "r"(z) : "memory");
}
__device__ __forceinline__ void mbar_arrive_if(uint32_t z, uint32_t bar) {
    asm volatile("{\n.reg .pred p;\nsetp.eq.u32 p, %1, 0;\n@p mbarrier.arrive.shared::cta.b64 _, [%0];\n}" :: "r"(bar), "r"(z) : "memory");
}
__device__ __forceinline__ void sts32_if(uint32_t z, uint32_t a, uint32_t x) {
    asm volatile("{\n.reg .pred p;\nsetp.eq.u32 p, %2, 0;\n@p st.shared.u32 [%0], %1;\n}" :: "r"(a), "r"(x), "r"(z) : "memory");
}
__device__ __forceinline__ void spin_until(unsigned t0, unsigned d) {
    asm volatile("{\n.reg .pred p;\n.reg .u64 c;\n.reg .u32 lo;\n"
                 "S_%=: mov.u64 c, %%clock64;\ncvt.u32.u64 lo, c;\nsub.u32 lo, lo, %0;\nsetp.lt.u32 p, lo, %1;\n@p bra.uni S_%=;\n}" :: "r"(t0), "r"(d) : "memory");
}
__device__ __forceinline__ void bar_sync(int id, int n) { asm volatile("bar.sync %0, %1;" :: "r"(id), "r"(n) : "memory"); }
__device__ __forceinline__ void bar_sync_sel(int sel, int id) {
    asm volatile("{\n.reg .pred p;\nsetp.eq.u32 p, %0, 0;\n@p bar.sync %1, %3;\n@!p bar.sync %2, %3;\n}" :: "r"(sel), "r"(id), "r"(id + 1), "n"(192) : "memory");
}
__device__ __forceinline__ void bar_arrive(int id, int n) { asm volatile("bar.arrive %0, %1;" :: "r"(id), "r"(n) : "memory"); }
__device__ __forceinline__ void fence_async_smem() { asm volatile("fence.proxy.async.shared::cta;" ::: "memory"); }
__device__ __forceinline__ uint32_t pack_bf16(float lo, float hi) { uint32_t r; asm("cvt.rn.bf16x2.f32 %0, %1, %2;" : "=r"(r) : "f"(hi), "f"(lo)); return r; }
__device__ __forceinline__ uint32_t pack_f16(float lo, float hi) { uint32_t r; asm("cvt.rn.f16x2.f32 %0, %1, %2;" : "=r"(r) : "f"(hi), "f"(lo)); return r; }
__device__ __forceinline__ uint32_t f16x2_to_bf16x2(uint32_t v) { float2 f = __half22float2(*reinterpret_cast<__half2*>(&v)); return pack_bf16(f.x, f.y); }
__device__ __forceinline__ float ex2(float x) { float y; asm("ex2.approx.ftz.f32 %0, %1;" : "=f"(y) : "f"(x)); return y; }
__device__ __forceinline__ float ex2v(float x) { float y; asm volatile("ex2.approx.ftz.f32 %0, %1;" : "=f"(y) : "f"(x)); return y; }
__device__ __forceinline__ uint32_t absmax2(uint32_t a, uint32_t b) {
    uint32_t r; asm("max.xorsign.abs.bf16x2 %0, %1, %2;" : "=r"(r) : "r"(a), "r"(b)); return r;
}
__device__ __forceinline__ uint32_t shl_v(uint32_t a, int n) { return a << n; }
__device__ __forceinline__ uint32_t max3u(uint32_t a, uint32_t b, uint32_t c) { return max(max(a, b), c); }
__device__ __forceinline__ uint4 lds128(uint32_t a) { uint4 v; asm volatile("ld.shared.v4.u32 {%0,%1,%2,%3}, [%4];" : "=r"(v.x), "=r"(v.y), "=r"(v.z), "=r"(v.w) : "r"(a) : "memory"); return v; }
__device__ __forceinline__ float4 lds128f(uint32_t a) { float4 v; asm volatile("ld.shared.v4.f32 {%0,%1,%2,%3}, [%4];" : "=f"(v.x), "=f"(v.y), "=f"(v.z), "=f"(v.w) : "r"(a) : "memory"); return v; }
__device__ __forceinline__ float2 lds64f(uint32_t a) { float2 v; asm volatile("ld.shared.v2.f32 {%0,%1}, [%2];" : "=f"(v.x), "=f"(v.y) : "r"(a) : "memory"); return v; }
__device__ __forceinline__ uint4 lds64x2(uint32_t a) { uint4 v; asm volatile("ld.shared.v2.u32 {%0,%1}, [%4];\nld.shared.v2.u32 {%2,%3}, [%4+256];" : "=r"(v.x), "=r"(v.y), "=r"(v.z), "=r"(v.w) : "r"(a) : "memory"); return v; }
__device__ __forceinline__ uint32_t lds32(uint32_t a) { uint32_t v; asm volatile("ld.shared.u32 %0, [%1];" : "=r"(v) : "r"(a) : "memory"); return v; }
__device__ __forceinline__ void sts128(uint32_t a, uint32_t x, uint32_t y, uint32_t z, uint32_t w) { asm volatile("st.shared.v4.u32 [%0], {%1,%2,%3,%4};" :: "r"(a), "r"(x), "r"(y), "r"(z), "r"(w) : "memory"); }
__device__ __forceinline__ void sts128f(uint32_t a, float x, float y, float z, float w) { asm volatile("st.shared.v4.f32 [%0], {%1,%2,%3,%4};" :: "r"(a), "f"(x), "f"(y), "f"(z), "f"(w) : "memory"); }
__device__ __forceinline__ void sts64(uint32_t a, uint32_t x, uint32_t y) { asm volatile("st.shared.v2.u32 [%0], {%1,%2};" :: "r"(a), "r"(x), "r"(y) : "memory"); }
__device__ __forceinline__ void sts32(uint32_t a, uint32_t x) { asm volatile("st.shared.u32 [%0], %1;" :: "r"(a), "r"(x) : "memory"); }
__device__ __forceinline__ uint4 ldsm4(uint32_t a) { uint4 v; asm volatile("ldmatrix.sync.aligned.m8n8.x4.shared.b16 {%0,%1,%2,%3}, [%4];" : "=r"(v.x), "=r"(v.y), "=r"(v.z), "=r"(v.w) : "r"(a) : "memory"); return v; }
__device__ __forceinline__ void stsm2t(uint32_t a, uint32_t x, uint32_t y) { asm volatile("stmatrix.sync.aligned.m8n8.x2.trans.shared.b16 [%0], {%1,%2};" :: "r"(a), "r"(x), "r"(y) : "memory"); }
__device__ __forceinline__ void stsm4t(uint32_t a, uint32_t x, uint32_t y, uint32_t z, uint32_t w) { asm volatile("stmatrix.sync.aligned.m8n8.x4.trans.shared.b16 [%0], {%1,%2,%3,%4};" :: "r"(a), "r"(x), "r"(y), "r"(z), "r"(w) : "memory"); }
__device__ __forceinline__ void st_async64(uint32_t a, uint32_t x, uint32_t y, uint32_t bar) { asm volatile("st.async.shared::cluster.mbarrier::complete_tx::bytes.v2.b32 [%0], {%1,%2}, [%3];" :: "r"(a), "r"(x), "r"(y), "r"(bar) : "memory"); }
__device__ __forceinline__ void bulk_s2c(uint32_t dst, uint32_t src, uint32_t bytes, uint32_t bar) { asm volatile("cp.async.bulk.shared::cluster.shared::cta.mbarrier::complete_tx::bytes [%0], [%1], %2, [%3];" :: "r"(dst), "r"(src), "r"(bytes), "r"(bar) : "memory"); }
__device__ __forceinline__ void bulk_s2g(void* dst, uint32_t src, uint32_t bytes) { asm volatile("cp.async.bulk.global.shared::cta.bulk_group [%0], [%1], %2;" :: "l"(dst), "r"(src), "r"(bytes) : "memory"); }
__device__ __forceinline__ uint32_t ldg_nc32(const void* p) { uint32_t v; asm volatile("ld.global.nc.L2::128B.u32 %0, [%1];" : "=r"(v) : "l"(p)); return v; }
__device__ __forceinline__ uint4 ldg_relaxed128(const void* p) { uint4 v; asm volatile("ld.relaxed.gpu.global.v4.u32 {%0,%1,%2,%3}, [%4];" : "=r"(v.x), "=r"(v.y), "=r"(v.z), "=r"(v.w) : "l"(p) : "memory"); return v; }
__device__ __forceinline__ void mma16816(float (&d)[4], uint32_t a0, uint32_t a1, uint32_t a2, uint32_t a3, uint32_t b0, uint32_t b1) {
    asm volatile("mma.sync.aligned.m16n8k16.row.col.f32.bf16.bf16.f32 {%0,%1,%2,%3}, {%4,%5,%6,%7}, {%8,%9}, {%0,%1,%2,%3};"
        : "+f"(d[0]), "+f"(d[1]), "+f"(d[2]), "+f"(d[3]) : "r"(a0), "r"(a1), "r"(a2), "r"(a3), "r"(b0), "r"(b1));
}
__device__ __forceinline__ void mma16816_z(float (&d)[4], uint32_t a0, uint32_t a1, uint32_t a2, uint32_t a3, uint32_t b0, uint32_t b1) {
    asm volatile("mma.sync.aligned.m16n8k16.row.col.f32.bf16.bf16.f32 {%0,%1,%2,%3}, {%4,%5,%6,%7}, {%8,%9}, {%10,%10,%10,%10};"
        : "=f"(d[0]), "=f"(d[1]), "=f"(d[2]), "=f"(d[3]) : "r"(a0), "r"(a1), "r"(a2), "r"(a3), "r"(b0), "r"(b1), "f"(0.f));
}
__device__ __forceinline__ void mma1688(float (&d)[4], uint32_t a0, uint32_t a1, uint32_t b0) {
    asm volatile("mma.sync.aligned.m16n8k8.row.col.f32.bf16.bf16.f32 {%0,%1,%2,%3}, {%4,%5}, {%6}, {%0,%1,%2,%3};"
        : "+f"(d[0]), "+f"(d[1]), "+f"(d[2]), "+f"(d[3]) : "r"(a0), "r"(a1), "r"(b0));
}
__device__ __forceinline__ void mma1688_z(float (&d)[4], uint32_t a0, uint32_t a1, uint32_t b0) {
    asm volatile("mma.sync.aligned.m16n8k8.row.col.f32.bf16.bf16.f32 {%0,%1,%2,%3}, {%4,%5}, {%6}, {%7,%7,%7,%7};"
        : "=f"(d[0]), "=f"(d[1]), "=f"(d[2]), "=f"(d[3]) : "r"(a0), "r"(a1), "r"(b0), "f"(0.f));
}
template <int ACC>
__device__ __forceinline__ void wgmma_n32_rs(float (&d)[16], uint32_t a0, uint32_t a1, uint32_t a2, uint32_t a3, uint64_t desc) {
    asm volatile("wgmma.mma_async.sync.aligned.m64n32k16.f32.bf16.bf16 {%0,%1,%2,%3,%4,%5,%6,%7,%8,%9,%10,%11,%12,%13,%14,%15}, {%16,%17,%18,%19}, %20, %21, 1, 1, 0;"
        : "+f"(d[0]), "+f"(d[1]), "+f"(d[2]), "+f"(d[3]), "+f"(d[4]), "+f"(d[5]), "+f"(d[6]), "+f"(d[7]),
          "+f"(d[8]), "+f"(d[9]), "+f"(d[10]), "+f"(d[11]), "+f"(d[12]), "+f"(d[13]), "+f"(d[14]), "+f"(d[15])
        : "r"(a0), "r"(a1), "r"(a2), "r"(a3), "l"(desc), "n"(ACC));
}
template <int ACC>
__device__ __forceinline__ void wgmma_n32_ss(float (&d)[16], uint64_t da, uint64_t db) {
    asm volatile("wgmma.mma_async.sync.aligned.m64n32k16.f32.bf16.bf16 {%0,%1,%2,%3,%4,%5,%6,%7,%8,%9,%10,%11,%12,%13,%14,%15}, %16, %17, %18, 1, 1, 0, 0;"
        : "+f"(d[0]), "+f"(d[1]), "+f"(d[2]), "+f"(d[3]), "+f"(d[4]), "+f"(d[5]), "+f"(d[6]), "+f"(d[7]),
          "+f"(d[8]), "+f"(d[9]), "+f"(d[10]), "+f"(d[11]), "+f"(d[12]), "+f"(d[13]), "+f"(d[14]), "+f"(d[15])
        : "l"(da), "l"(db), "n"(ACC));
}
__device__ __forceinline__ void wg_fence() { asm volatile("wgmma.fence.sync.aligned;" ::: "memory"); }
__device__ __forceinline__ void wg_commit() { asm volatile("wgmma.commit_group.sync.aligned;" ::: "memory"); }
__device__ __forceinline__ void wg_wait0() { asm volatile("wgmma.wait_group.sync.aligned 0;" ::: "memory"); }
__device__ __forceinline__ void cluster_sync() { asm volatile("barrier.cluster.arrive.aligned;\nbarrier.cluster.wait.aligned;" ::: "memory"); }

#define STAMP(s, i) do {} while (0)
#define STAMPV(s, i, v) do {} while (0)

constexpr int XT_BYTES = 36864;
constexpr int O_XT = 0;
constexpr int O_AS = 3 * XT_BYTES;
constexpr int O_AF = O_AS + 16384;
constexpr int O_MF = O_AF + 16384;
constexpr int O_XP = O_MF + 9216;
constexpr int O_VX = O_XP + 8192;
constexpr int O_VM = O_VX + 16384;
constexpr int O_SC = O_VM + 2048;
constexpr int O_OF = O_SC + 2560;
constexpr int O_QM = O_OF + 2048;
constexpr int O_KX = O_QM + 2048;
constexpr int O_KM = O_KX + 4096;
constexpr int O_MISC = O_KM + 2048;
constexpr int O_BAR = O_MISC + 64;
constexpr int CHAIN_SMEM = O_BAR + 128;
static_assert(CHAIN_SMEM <= 232448, "smem");
constexpr int B_X = O_BAR, B_VX = O_BAR + 24, B_SC = O_BAR + 40, B_VM = O_BAR + 48;
constexpr float SM_SCALE = 0.08838834764831845f * 1.4426950408889634f;
constexpr uint32_t ONES = 0x3f803f80u;

__device__ __forceinline__ uint32_t opaque(uint32_t v) { uint32_t o; asm volatile("mov.u32 %0, %1;" : "=r"(o) : "r"(v)); return o; }
__device__ __forceinline__ void st_async128(uint32_t a, uint32_t x, uint32_t y, uint32_t z, uint32_t w, uint32_t bar) {
    asm volatile("st.async.shared::cluster.mbarrier::complete_tx::bytes.v4.b32 [%0], {%1,%2,%3,%4}, [%5];" :: "r"(a), "r"(x), "r"(y), "r"(z), "r"(w), "r"(bar) : "memory");
}
__device__ __forceinline__ void tma_x_tile(uint32_t sb, const CUtensorMap* tm, int r, int j, int slot) {
    asm volatile("{\n.reg .pred p;\nelect.sync _|p, 0xffffffff;\n"
        "@p mbarrier.arrive.expect_tx.shared::cta.b64 _, [%2], 36864;\n"
        "@p cp.async.bulk.tensor.2d.shared::cluster.global.mbarrier::complete_tx::bytes.multicast::cluster [%0], [%1, {%3, %4}], [%2], %7;\n"
        "@p cp.async.bulk.tensor.2d.shared::cluster.global.mbarrier::complete_tx::bytes.multicast::cluster [%0+4096], [%1, {%5, %4}], [%2], %7;\n"
        "@p cp.async.bulk.tensor.2d.shared::cluster.global.mbarrier::complete_tx::bytes.multicast::cluster [%0+8192], [%1, {%6, %4}], [%2], %7;\n}"
        :: "r"(sb + O_XT + slot * XT_BYTES + 3 * r * 4096), "l"(tm), "r"(sb + B_X + 8 * slot), "r"(192 * r), "r"(j * 32), "r"(192 * r + 64), "r"(192 * r + 128),
           "h"((unsigned short)7) : "memory");
}
__device__ __forceinline__ float quad_max(float v) {
    const float a = __shfl_xor_sync(~0u, v, 1), b = __shfl_xor_sync(~0u, v, 2), c = __shfl_xor_sync(~0u, v, 3);
    return fmaxf(fmaxf(v, a), fmaxf(b, c));
}
__device__ __forceinline__ void load_scores(float (&p)[10], uint32_t base, uint32_t stride, uint32_t l16) {
    const float4 a0 = lds128f(base + l16), b0 = lds128f(base + stride + l16);
    const float4 a1 = lds128f(base + 512 + l16), b1 = lds128f(base + stride + 512 + l16);
    const float2 a2 = lds64f(base + 1024 + (l16 >> 1)), b2 = lds64f(base + stride + 1024 + (l16 >> 1));
    p[0] = a2.x + b2.x; p[1] = a2.y + b2.y;
    p[2] = a0.x + b0.x; p[3] = a0.y + b0.y; p[4] = a0.z + b0.z; p[5] = a0.w + b0.w;
    p[6] = a1.x + b1.x; p[7] = a1.y + b1.y; p[8] = a1.z + b1.z; p[9] = a1.w + b1.w;
}
__device__ __forceinline__ float rcp_fast(float x) { float y; asm("rcp.approx.ftz.f32 %0, %1;" : "=f"(y) : "f"(x)); return y; }

__global__ void __cluster_dims__(3, 1, 1) __launch_bounds__(384, 1)
chain_kernel(const __grid_constant__ CUtensorMap tm_x,
             const __nv_bfloat16* __restrict__ x, const __nv_bfloat16* __restrict__ mem0,
             const __nv_bfloat16* __restrict__ Wq, const __nv_bfloat16* __restrict__ Wk,
             const __nv_bfloat16* __restrict__ Wv, const __nv_bfloat16* __restrict__ Wo) {
    extern __shared__ __align__(1024) uint8_t smem_raw[];
    const uint32_t sb = smem_u32(smem_raw);
    const int lane = threadIdx.x & 31;
    const int warp = __shfl_sync(~0u, threadIdx.x >> 5, 0);
    const int wg = warp >> 2, w = warp & 3;
    const int h = blockIdx.x / 3, r = blockIdx.x - 3 * h;

    if (threadIdx.x == 0) {
        if (sb & 1023u) __trap();
        for (int i = 0; i < 7; i++) mbar_init(sb + O_BAR + 8 * i, 1);
        asm volatile("fence.mbarrier_init.release.cluster;" ::: "memory");
    }
    if (blockIdx.x == 0) {
        for (int i = threadIdx.x; i < NSEG * 4 * 8; i += 384) g_flag[i] = 0;
        __threadfence();
    }
    __syncthreads();
    cluster_sync();
    asm volatile("griddepcontrol.launch_dependents;" ::: "memory");
    const uint32_t l16c = __shfl_sync(~0u, lane * 16, lane);

    if (wg < 2) {
#define KS(u) ((u) < 8 ? ((u) >> 1) + 4 * ((u) & 1) : (u) < 12 ? (u) : (u) < 20 ? 12 + (((u) - 12) >> 1) + 4 * ((u) & 1) : (u) < 24 ? (u) : (u) + 8)
        asm volatile("setmaxnreg.inc.sync.aligned.u32 176;");
        uint32_t a[144];
        uint32_t adr1;
        {
            const int g = lane >> 2, t = lane & 3;
#pragma unroll
            for (int tl = 0; tl < 2; tl++) {
                const int tile = tl ? wg : (wg ^ 1);
                const __nv_bfloat16* W = (r < 2) ? (tile == 0 ? Wq : Wk) : Wv;
                const int col = h * 128 + ((r < 2) ? 64 * r : 64 * tile) + 16 * w + 2 * g;
                const __nv_bfloat16* p = W + (size_t)(2 * t) * HD + col;
                const __nv_bfloat16* ps = p + (size_t)(384 * wg) * HD;
#pragma unroll
                for (int u = 0; u < (tl ? 28 : 8); u++) {
                    const __nv_bfloat16* q = (u < 8 ? ps : p) + (size_t)(16 * KS(u)) * HD;
                    a[32 * tl + 4 * u + 0] = ldg_nc32(q);
                    a[32 * tl + 4 * u + 1] = ldg_nc32(q + HD);
                    a[32 * tl + 4 * u + 2] = ldg_nc32(q + 8 * HD);
                    a[32 * tl + 4 * u + 3] = ldg_nc32(q + 9 * HD);
                }
            }
#pragma unroll
            for (int kk = 0; kk < 72; kk++) {
                uint32_t w0 = a[2 * kk], w1 = a[2 * kk + 1];
                a[2 * kk] = __byte_perm(w0, w1, 0x5410);
                a[2 * kk + 1] = __byte_perm(w0, w1, 0x7632);
            }
            float vmax = 0.f;
#pragma unroll
            for (int tl = 0; tl < 2; tl++) {
                float s0 = 0.f, s1 = 0.f;
#pragma unroll
                for (int kk = 16 * tl; kk < (tl ? 72 : 16); kk++) {
                    s0 += fabsf(__uint_as_float(a[2 * kk] << 16)) + fabsf(__uint_as_float(a[2 * kk] & 0xffff0000u));
                    s1 += fabsf(__uint_as_float(a[2 * kk + 1] << 16)) + fabsf(__uint_as_float(a[2 * kk + 1] & 0xffff0000u));
                }
                s0 += __shfl_xor_sync(~0u, s0, 1); s0 += __shfl_xor_sync(~0u, s0, 2);
                s1 += __shfl_xor_sync(~0u, s1, 1); s1 += __shfl_xor_sync(~0u, s1, 2);
                vmax = fmaxf(vmax, fmaxf(s0, s1));
            }
            uint32_t mx = __reduce_max_sync(~0u, __float_as_uint(2.f * vmax));
            sts32_if(lane, sb + O_MISC + 32 + 4 * warp, mx);
            bar_arrive(7, 384);
            const uint32_t as = sb + O_AS + wg * 8192 + (16 * w + g) * 128 + t * 4;
#pragma unroll
            for (int kk = 0; kk < 4; kk++) {
                sts32(as + (((2 * kk) ^ g) << 4), a[32 + 4 * kk]);
                sts32(as + 1024 + (((2 * kk) ^ g) << 4), a[32 + 4 * kk + 1]);
                sts32(as + (((2 * kk + 1) ^ g) << 4), a[32 + 4 * kk + 2]);
                sts32(as + 1024 + (((2 * kk + 1) ^ g) << 4), a[32 + 4 * kk + 3]);
                sts128(sb + O_AF + warp * 2048 + kk * 512 + lane * 16, a[32 + 4 * kk], a[32 + 4 * kk + 1], a[32 + 4 * kk + 2], a[32 + 4 * kk + 3]);
            }
            fence_async_smem();
            bar_sync(1, 256);
            const uint32_t l = lane * 16;
            const int mi = lane >> 3, isk = (mi >> 1) ? wg : (wg ^ 1);
            adr1 = (r == 2) ? (sb + O_VM + warp * 256 + (l >> 1))
                            : (isk ? (sb + O_KM + w * 512 + wg * 256 + (mi & 1) * 128 + (l & 127))
                                   : (sb + O_QM + w * 512 + (mi & 1) * 256 + wg * 128 + (l & 127)));
            adr1 = __shfl_sync(~0u, adr1, lane);
        }
        int s3 = 2;
#pragma unroll 1
        for (int s = -1; s < NSEG; s++) {
            const uint32_t l16 = opaque(l16c);
            s3 = (s3 == 2) ? 0 : s3 + 1;
            if (s < NSEG - 1) mbar_wait(sb + B_X + 8 * s3, ((s + 1) / 3) & 1);
            const uint64_t desc0 = (uint64_t)(((sb + O_XT + s3 * XT_BYTES) & 0x3FFFF) >> 4) | (1ull << 16) | (64ull << 32) | (1ull << 62);
            uint32_t km0 = 0, km1 = 0;
            if (s >= 0) {
#pragma unroll
                for (int kk = 0; kk < 4; kk++) {
                    const uint4 v = lds128(sb + O_AF + warp * 2048 + kk * 512 + l16);
                    a[32 + 4 * kk] = v.x; a[32 + 4 * kk + 1] = v.y; a[32 + 4 * kk + 2] = v.z; a[32 + 4 * kk + 3] = v.w;
                }
                float co[4], cw[2][4];
                uint4 b[14];
                float inv;
#define GORD(i) ((i) == 0 ? 0 : (i) == 1 ? 1 : (i) == 5 ? 2 : (i) == 9 ? 3 : (i) < 5 ? (i) + 2 : (i) < 9 ? (i) + 1 : (i))
                auto qkv_mma = [&](int i) {
                    const int gi = GORD(i), u = 8 * gi;
                    if (i == 0) {
                        mma16816_z(cw[0], a[32], a[33], a[34], a[35], b[0].x, b[0].y);
                        mma16816_z(cw[1], a[36], a[37], a[38], a[39], b[0].z, b[0].w);
                        mma16816_z(co, a[0], a[1], a[2], a[3], b[0].x, b[0].y);
                    } else {
                        mma16816(cw[0], a[32 + u], a[32 + u + 1], a[32 + u + 2], a[32 + u + 3], b[i].x, b[i].y);
                        mma16816(cw[1], a[32 + u + 4], a[32 + u + 5], a[32 + u + 6], a[32 + u + 7], b[i].z, b[i].w);
                        if (gi < 4) mma16816(co, a[u], a[u + 1], a[u + 2], a[u + 3], b[i].x, b[i].y);
                    }
                    if (gi < 4) mma16816(co, a[u + 4], a[u + 5], a[u + 6], a[u + 7], b[i].z, b[i].w);
                };
                const uint32_t mf = sb + O_MF + l16, mfs = mf + wg * 6144;
                bar_sync(2, 384);
                if (warp == 0) STAMP(s, 0);
#pragma unroll
                for (int i = 0; i < 17; i++) {
                    if (i < 14) b[i] = GORD(i) < 4 ? lds128(mfs + GORD(i) * 512) : lds128(mf + (GORD(i) < 12 ? GORD(i) : GORD(i) + 4) * 512);
                    if (i == 14) inv = __uint_as_float(lds32(sb + O_MISC));
                    if (i >= 3) qkv_mma(i - 3);
                }
#pragma unroll
                for (int i = 0; i < 4; i++) cw[0][i] += cw[1][i];
                if (r < 2) {
                    const uint32_t o0 = pack_bf16(co[0] * inv, co[1] * inv), o1 = pack_bf16(co[2] * inv, co[3] * inv);
                    const uint32_t w0 = pack_bf16(cw[0][0] * inv, cw[0][1] * inv), w1 = pack_bf16(cw[0][2] * inv, cw[0][3] * inv);
                    stsm4t(adr1, o0, o1, w0, w1);
                    km0 = wg ? w0 : o0; km1 = wg ? w1 : o1;
                    if (warp == 0) STAMP(s, 1);
                    asm volatile("{\n.reg .pred p;\nsetp.ge.u32 p, %0, 3;\n@p bar.arrive 1, 256;\n}" :: "r"(warp) : "memory");
                    if (warp < 3 && s < NSEG - 1) {
                        uint4 q[4], k[4];
                        const uint32_t ka = sb + O_KX + warp * 2048 + l16;
#pragma unroll
                        for (int i = 0; i < 4; i++) k[i] = ldsm4(ka + i * 512);
                        const uint32_t dst = sb + O_SC + r * 1280 + warp * 512 + (warp == 2 ? (l16 >> 1) : l16);
                        const uint32_t d0 = mapa_v(dst, 2), d1 = mapa_v(dst, r ^ 1), d2 = mapa_v(dst, r);
                        bar_sync(1, 256);
#pragma unroll
                        for (int i = 0; i < 4; i++) q[i] = ldsm4(sb + O_QM + i * 512 + l16);
                        if (warp == 2) {
#pragma unroll
                            for (int i = 0; i < 4; i++) k[i] = ldsm4(ka + i * 512);
                        }
                        float s0[4], s1[4], t0[4], t1[4];
                        mma16816_z(s0, q[0].x, q[0].y, q[0].z, q[0].w, k[0].x, k[0].y);
                        mma16816_z(s1, q[0].x, q[0].y, q[0].z, q[0].w, k[0].z, k[0].w);
                        mma16816_z(t0, q[1].x, q[1].y, q[1].z, q[1].w, k[1].x, k[1].y);
                        mma16816_z(t1, q[1].x, q[1].y, q[1].z, q[1].w, k[1].z, k[1].w);
                        mma16816(s0, q[2].x, q[2].y, q[2].z, q[2].w, k[2].x, k[2].y);
                        mma16816(s1, q[2].x, q[2].y, q[2].z, q[2].w, k[2].z, k[2].w);
                        mma16816(t0, q[3].x, q[3].y, q[3].z, q[3].w, k[3].x, k[3].y);
                        mma16816(t1, q[3].x, q[3].y, q[3].z, q[3].w, k[3].z, k[3].w);
                        const float v0 = (s0[0] + s0[2]) + (t0[0] + t0[2]), v1 = (s0[1] + s0[3]) + (t0[1] + t0[3]);
                        const float v2 = (s1[0] + s1[2]) + (t1[0] + t1[2]), v3 = (s1[1] + s1[3]) + (t1[1] + t1[3]);
                        asm volatile("{\n.reg .pred p;\nsetp.lt.u32 p, %12, 2;\n"
                            "@p st.async.shared::cluster.mbarrier::complete_tx::bytes.v4.f32 [%0], {%6,%7,%8,%9}, [%3];\n"
                            "@!p st.async.shared::cluster.mbarrier::complete_tx::bytes.v2.f32 [%0], {%10,%11}, [%3];\n"
                            "@p st.async.shared::cluster.mbarrier::complete_tx::bytes.v4.f32 [%1], {%6,%7,%8,%9}, [%4];\n"
                            "@!p st.async.shared::cluster.mbarrier::complete_tx::bytes.v2.f32 [%1], {%10,%11}, [%4];\n"
                            "@p st.async.shared::cluster.mbarrier::complete_tx::bytes.v4.f32 [%2], {%6,%7,%8,%9}, [%5];\n"
                            "@!p st.async.shared::cluster.mbarrier::complete_tx::bytes.v2.f32 [%2], {%10,%11}, [%5];\n}"
                            :: "r"(d0), "r"(d1), "r"(d2), "r"(mapa(sb + B_SC, 2)), "r"(mapa(sb + B_SC, r ^ 1)), "r"(mapa(sb + B_SC, r)),
                               "f"(v0), "f"(v1), "f"(v2), "f"(v3), "f"(v0 + v2), "f"(v1 + v3), "r"(warp) : "memory");
                        if (warp == 2) STAMP(s, 2);
                    } else if (warp < 3) {
                        bar_sync(1, 256);
                    }
                } else {
                    sts128f(sb + O_XP + warp * 512 + l16, co[0], co[1], co[2], co[3]);
                    bar_sync(8 + w, 64);
                    const float4 o = lds128f(sb + O_XP + (warp ^ 4) * 512 + l16);
                    km0 = pack_bf16((cw[0][0] + o.x) * inv, (cw[0][1] + o.y) * inv);
                    km1 = pack_bf16((cw[0][2] + o.z) * inv, (cw[0][3] + o.w) * inv);
                    if (warp == 0) STAMP(s, 1);
                    if (s < NSEG - 1) {
                        st_async64(mapa(adr1, 0), km0, km1, mapa(sb + B_VM, 0));
                        st_async64(mapa(adr1, 1), km0, km1, mapa(sb + B_VM, 1));
                        st_async64(mapa(adr1, 2), km0, km1, mapa(sb + B_VM, 2));
                    }
                    if (warp == 0) STAMP(s, 2);
                }
            }
            auto store_kvm = [&]() {
                char* p = reinterpret_cast<char*>(g_kvm) + (size_t)(s * NH + h) * 6144 + (r < 2 ? wg * 2048 + (r * 4 + w) * 256 : 4096 + warp * 256) + (l16 >> 1);
                *reinterpret_cast<uint2*>(p) = make_uint2(km0, km1);
            };
            if (s == NSEG - 1) {
                store_kvm();
            } else {
                if (s >= 0) bar_sync(3, 384);
                const int j = s + 1;
#define XDESC(u) (((u) < 8 ? descs : desc0) + (uint64_t)(((KS(u) >> 2) * 4096 + (KS(u) & 3) * 32) >> 4))
                const uint64_t descs = desc0 + (uint64_t)(wg * (6 * 4096 >> 4));
                float d[16];
                wg_fence();
#pragma unroll
                for (int u = 0; u < 8; u++) {
                    if (u == 0) wgmma_n32_rs<0>(d, a[0], a[1], a[2], a[3], XDESC(0));
                    else wgmma_n32_rs<1>(d, a[4 * u], a[4 * u + 1], a[4 * u + 2], a[4 * u + 3], XDESC(u));
                }
                wg_commit();
                wg_wait0();
                if (warp == 0) STAMP(s, 15);
                if (s >= 0) bar_sync(4, 384);
#pragma unroll
                for (int q = 0; q < 2; q++)
                    sts128(sb + O_XP + warp * 1024 + q * 512 + l16, pack_bf16(d[8 * q], d[8 * q + 1]), pack_bf16(d[8 * q + 2], d[8 * q + 3]),
                           pack_bf16(d[8 * q + 4], d[8 * q + 5]), pack_bf16(d[8 * q + 6], d[8 * q + 7]));
                if (s >= 0) {
                    store_kvm();
                    if (warp == 1 && s + 2 < NSEG) tma_x_tile(sb, &tm_x, r, s + 2, s3 == 2 ? 0 : s3 + 1);
                }
                bar_sync(12, 256);
#pragma unroll
                for (int q = 0; q < 2; q++) {
                    const uint4 o = lds128(sb + O_XP + (warp ^ 4) * 1024 + q * 512 + l16);
                    d[8 * q] = __uint_as_float(o.x << 16); d[8 * q + 1] = __uint_as_float(o.x & 0xffff0000u);
                    d[8 * q + 2] = __uint_as_float(o.y << 16); d[8 * q + 3] = __uint_as_float(o.y & 0xffff0000u);
                    d[8 * q + 4] = __uint_as_float(o.z << 16); d[8 * q + 5] = __uint_as_float(o.z & 0xffff0000u);
                    d[8 * q + 6] = __uint_as_float(o.w << 16); d[8 * q + 7] = __uint_as_float(o.w & 0xffff0000u);
                }
                if (s >= 0) {
                    if (warp == 6 && (s & 3) == 3)
                        asm volatile("{\n.reg .pred p;\nsetp.eq.u32 p, %1, 0;\n@p red.release.gpu.global.inc.u32 [%0], 0x7fffffff;\n}"
                                     :: "l"(&g_flag[(s * 4 + (h >> 3)) * 8]), "r"(l16) : "memory");
                    asm volatile("{\n.reg .pred p;\nsetp.eq.u32 p, %0, 0;\n@p bar.sync 5, 256;\n@!p bar.sync 13, 256;\n}" :: "r"(wg) : "memory");
                }
                const uint64_t da0 = (uint64_t)(((sb + O_AS + wg * 8192) & 0x3FFFF) >> 4) | (1ull << 16) | (64ull << 32) | (1ull << 62);
                wg_fence();
#pragma unroll
                for (int u = 0; u < 4; u++) wgmma_n32_ss<1>(d, da0 + 2 * u, XDESC(u));
#pragma unroll
                for (int u = 4; u < 28; u++) wgmma_n32_rs<1>(d, a[32 + 4 * u], a[32 + 4 * u + 1], a[32 + 4 * u + 2], a[32 + 4 * u + 3], XDESC(u));
                wg_commit();
                wg_wait0();
                if (warp == 4) STAMP(s, 3);
                uint32_t e[8];
#pragma unroll
                for (int i = 0; i < 8; i++) e[i] = pack_bf16(d[2 * i], d[2 * i + 1]);
                if (r < 2) {
                    if (wg == 1) {
                        stsm4t(sb + O_KX + w * 512 + l16, e[0], e[1], e[2], e[3]);
                        stsm4t(sb + O_KX + 2048 + w * 512 + l16, e[4], e[5], e[6], e[7]);
                    }
                    char* p = reinterpret_cast<char*>(g_qkv) + (size_t)(j * NH + h) * 24576 + wg * 8192 + (r * 4 + w) * 1024 + l16;
                    *reinterpret_cast<uint4*>(p) = make_uint4(e[0], e[1], e[2], e[3]);
                    *reinterpret_cast<uint4*>(p + 512) = make_uint4(e[4], e[5], e[6], e[7]);
                } else {
                    const uint32_t base = sb + O_VX + (j & 1) * 8192 + warp * 1024 + l16;
                    sts128(base, e[0], e[1], e[2], e[3]);
                    sts128(base + 512, e[4], e[5], e[6], e[7]);
                    bar_arrive(14, 384);
                }
                if (warp == 7) STAMP(s, 4);
            }
        }
        bar_arrive(7, 384);
    } else {
        asm volatile("setmaxnreg.dec.sync.aligned.u32 152;");
        const int c = w;
        uint32_t a[96];
        uint32_t mmax = 0;
        {
            const int g = lane >> 2, t = lane & 3, t2 = threadIdx.x - 256;
            if (c == 0) {
                tma_x_tile(sb, &tm_x, r, 0, 0);
                tma_x_tile(sb, &tm_x, r, 1, 1);
                mbar_expect_if(lane, sb + B_SC, 2560);
                mbar_expect_if(lane, sb + B_VM, 2048);
                if (r < 2) mbar_expect_if(lane, sb + B_VX, 8192);
                sts32_if(lane, sb + O_MISC, __float_as_uint(1.0f));
            }
#pragma unroll
            for (int i = 0; i < 4; i++) g_acc[(blockIdx.x * 64 + i * 16 + (t2 >> 3)) * 16 + (t2 & 7)] = make_uint4(0, 0, 0, 0);
#pragma unroll
            for (int tau = 0; tau < 3; tau++) {
                uint32_t v[6];
#pragma unroll
                for (int i = 0; i < 3; i++) {
                    const uint32_t* p = reinterpret_cast<const uint32_t*>(mem0 + g * DM + 16 * (12 * tau + 4 * i + c) + 2 * t);
                    v[2 * i] = __ldg(p); v[2 * i + 1] = __ldg(p + 4);
                    mmax = __vmaxu2(mmax, __vmaxu2(v[2 * i] & 0x7fff7fffu, v[2 * i + 1] & 0x7fff7fffu));
                }
                sts128(sb + O_MF + tau * 3072 + c * 512 + lane * 16, v[0], v[1], v[2], v[3]);
                sts64(sb + O_MF + tau * 3072 + 2048 + (c >> 1) * 512 + lane * 16 + (c & 1) * 8, v[4], v[5]);
            }
            mmax = max(mmax << 16, mmax & 0xffff0000u);
            bar_arrive(2, 384);
            uint32_t xm = 0;
            const uint4* xp = reinterpret_cast<const uint4*>(x) + blockIdx.x * 1536 + t2;
#pragma unroll
            for (int i = 0; i < 12; i++) {
                uint4 v = __ldg(xp + i * 128);
                xm = __vmaxu2(xm, __vmaxu2(__vmaxu2(v.x & 0x7fff7fffu, v.y & 0x7fff7fffu), __vmaxu2(v.z & 0x7fff7fffu, v.w & 0x7fff7fffu)));
            }
            xm = __reduce_max_sync(~0u, max(xm << 16, xm & 0xffff0000u));

            const __nv_bfloat16* p = Wo + (size_t)(h * 128 + 4 * t) * DM + 192 * r + 16 * c + 2 * g;
#pragma unroll
            for (int i = 0; i < 3; i++)
#pragma unroll
                for (int eb = 0; eb < 8; eb++)
#pragma unroll
                    for (int j = 0; j < 4; j++) a[(i * 8 + eb) * 4 + j] = ldg_nc32(p + (16 * eb + ((j & 1) * 2 + (j >> 1))) * DM + 64 * i);
#pragma unroll
            for (int kk = 0; kk < 48; kk++) {
                uint32_t w0 = a[2 * kk], w1 = a[2 * kk + 1];
                a[2 * kk] = __byte_perm(w0, w1, 0x5410);
                a[2 * kk + 1] = __byte_perm(w0, w1, 0x7632);
            }
            float wmax = 0.f;
#pragma unroll
            for (int i = 0; i < 3; i++) {
                float s0 = 0.f, s1 = 0.f;
#pragma unroll
                for (int kk = 16 * i; kk < 16 * i + 16; kk++) {
                    s0 += fabsf(__uint_as_float(a[2 * kk] << 16)) + fabsf(__uint_as_float(a[2 * kk] & 0xffff0000u));
                    s1 += fabsf(__uint_as_float(a[2 * kk + 1] << 16)) + fabsf(__uint_as_float(a[2 * kk + 1] & 0xffff0000u));
                }
                s0 += __shfl_xor_sync(~0u, s0, 1); s0 += __shfl_xor_sync(~0u, s0, 2);
                s1 += __shfl_xor_sync(~0u, s1, 1); s1 += __shfl_xor_sync(~0u, s1, 2);
                wmax = fmaxf(wmax, fmaxf(s0, s1));
            }
            uint32_t wm = __reduce_max_sync(~0u, __float_as_uint(wmax));
            sts32_if(lane, sb + O_OF + 4 * c, wm); sts32_if(lane, sb + O_OF + 16 + 4 * c, xm);
            __threadfence();
            bar_sync(7, 384);
            if (c == 0) {
                const uint4 wq = lds128(sb + O_OF), xq = lds128(sb + O_OF + 16), v0 = lds128(sb + O_MISC + 32), v1 = lds128(sb + O_MISC + 48);
                const uint32_t w1 = max(max(wq.x, wq.y), max(wq.z, wq.w)), x1 = max(max(xq.x, xq.y), max(xq.z, xq.w));
                const uint32_t vv = (r < 2) ? 0u : max(max(max(v0.x, v0.y), max(v0.z, v0.w)), max(max(v1.x, v1.y), max(v1.z, v1.w)));
                unsigned old = 0;
                asm volatile("{\n.reg .pred p;\nsetp.eq.u32 p, %6, 0;\n@p st.global.v4.u32 [%1], {%2,%3,%4,%4};\nfence.acq_rel.gpu;\n@p atom.relaxed.gpu.global.add.u32 %0, [%5], 1;\n}"
                             : "+r"(old) : "l"(&g_norm[blockIdx.x * 4]), "r"(w1), "r"(vv), "r"(x1), "l"(&g_gridbar), "r"(lane) : "memory");
                old = __shfl_sync(~0u, old, 0);
                const unsigned target = (old / 96u + 1u) * 96u;
                asm volatile("{\n.reg .pred p;\n.reg .u32 n, v;\nmov.u32 n, 0;\n"
                             "G_%=: ld.acquire.gpu.global.u32 v, [%0];\nsub.u32 v, v, %1;\nsetp.ge.s32 p, v, 0;\n@p bra.uni E_%=;\n"
                             "add.u32 n, n, 1;\nsetp.lt.u32 p, n, 4000000;\n@p bra.uni G_%=;\ntrap;\nE_%=:\n}" :: "l"(&g_gridbar), "r"(target) : "memory");
                uint4 n0 = ldg_relaxed128(&g_norm[lane * 4]), n1 = ldg_relaxed128(&g_norm[(lane + 32) * 4]), n2 = ldg_relaxed128(&g_norm[(lane + 64) * 4]);
                const float fw = __uint_as_float(__reduce_max_sync(~0u, max(n0.x, max(n1.x, n2.x))));
                const float fv = __uint_as_float(__reduce_max_sync(~0u, max(n0.y, max(n1.y, n2.y))));
                const float xmax = __uint_as_float(__reduce_max_sync(~0u, max(n0.z, max(n1.z, n2.z))));
                const float G = 36.f * fw * fv;
                sts32_if(lane, sb + O_MISC + 4, __float_as_uint(G)); sts32_if(lane, sb + O_MISC + 8, __float_as_uint(G * xmax));
            }
        }
        bar_sync(6, 128);
        char* rptr; int pdelta;
        {
            const uint32_t roff = (r * 4 + c) * 2048 + (lane >> 4) * 512 + (lane & 2) * 128 + (lane & 1) * 64 + (lane & 12) * 4;
            const uint32_t poff = c * 2048 + (lane & 4) * 256 + (lane >> 4) * 256 + (lane & 8) * 8 + (lane & 3) * 16;
            rptr = reinterpret_cast<char*>(g_acc) + roff;
            pdelta = __shfl_sync(~0u, (int)poff - (int)roff, lane);
        }
#pragma unroll 1
        for (int s = 0; s < NSEG; s++) {
            const uint32_t l16 = opaque(l16c);
            const uint32_t vxa = sb + O_VX + (s & 1) * 8192 + c * 2048 + l16;
            char* vg = reinterpret_cast<char*>(g_qkv) + (size_t)(s * NH + h) * 24576 + 16384 + c * 2048 + l16;
            uint4 vx[4];
            if (r == 2) {
                bar_sync(14, 384);
#pragma unroll
                for (int q = 0; q < 4; q++) vx[q] = lds128(vxa + q * 512);
                if (s == NSEG - 1) {
#pragma unroll
                    for (int q = 0; q < 4; q++) *reinterpret_cast<uint4*>(vg + q * 512) = vx[q];
                } else {
                    const uint32_t bar0 = mapa(sb + B_VX + 8 * (s & 1), 0), bar1 = mapa(sb + B_VX + 8 * (s & 1), 1), d0 = mapa(vxa, 0), d1 = mapa(vxa, 1);
#pragma unroll
                    for (int q = 0; q < 4; q++) {
                        st_async128(d0 + q * 512, vx[q].x, vx[q].y, vx[q].z, vx[q].w, bar0);
                        st_async128(d1 + q * 512, vx[q].x, vx[q].y, vx[q].z, vx[q].w, bar1);
                    }
                }
            }
            if (s == NSEG - 1) break;
            sts32_if(l16, sb + O_MISC + 16 + 4 * c, __reduce_max_sync(~0u, mmax));
            if (c == 0) STAMP(s, 5);
            {
                bar_sync(6, 128);
                const uint4 mm = lds128(sb + O_MISC + 16), cf = lds128(sb + O_MISC);
                const float bound = fmaxf(__uint_as_float(cf.z), __uint_as_float(cf.y) * (__uint_as_float(max(max(mm.x, mm.y), max(mm.z, mm.w))) * __uint_as_float(cf.x)));
                const uint32_t ebits = min(max(__float_as_uint(bound) & 0x7f800000u, 21u << 23), 254u << 23);
                bar_sync(3, 384);
                if (r < 2) mbar_wait(sb + B_VX + 8 * (s & 1), (s >> 1) & 1);
#pragma unroll
                for (int q = 0; q < 4; q++) vx[q] = lds128(vxa + q * 512);
                mbar_wait(sb + B_VM, s & 1);
                const uint4 vm = lds64x2(sb + O_VM + c * 512 + (l16 >> 1));
                if (c == 0) STAMP(s, 13);
                mbar_wait(sb + B_SC, s & 1);
                if (c == 0) STAMP(s, 6);
                float p[10];
                load_scores(p, sb + O_SC, 1280, l16);
                float mx = fmaxf(fmaxf(fmaxf(p[0], p[1]), fmaxf(p[2], p[3])), fmaxf(fmaxf(p[4], p[5]), fmaxf(p[6], p[7])));
                mx = quad_max(fmaxf(mx, fmaxf(p[8], p[9])));
                const float mo = mx * SM_SCALE;
                asm volatile("{\n.reg .pred p, q;\nsetp.eq.u32 p, %17, 0;\nsetp.eq.u32 q, %17, 1;\n"
                    "@p st.global.v4.u32 [%0], {%1,%2,%3,%4};\n@p st.global.v4.u32 [%0+512], {%5,%6,%7,%8};\n"
                    "@q st.global.v4.u32 [%0+1024], {%9,%10,%11,%12};\n@q st.global.v4.u32 [%0+1536], {%13,%14,%15,%16};\n}"
                    :: "l"(vg), "r"(vx[0].x), "r"(vx[0].y), "r"(vx[0].z), "r"(vx[0].w), "r"(vx[1].x), "r"(vx[1].y), "r"(vx[1].z), "r"(vx[1].w),
                       "r"(vx[2].x), "r"(vx[2].y), "r"(vx[2].z), "r"(vx[2].w), "r"(vx[3].x), "r"(vx[3].y), "r"(vx[3].z), "r"(vx[3].w), "r"(r) : "memory");
                bar_arrive(4, 384);
                uint32_t P[5];
#pragma unroll
                for (int n = 0; n < 5; n++) P[n] = pack_bf16(ex2(fmaf(p[2 * n], SM_SCALE, -mo)), ex2(fmaf(p[2 * n + 1], SM_SCALE, -mo)));
                if (c == 0) STAMP(s, 7);
                float o0[4], o1[4], sm[4];
                mma1688_z(sm, ONES, ONES, P[0]);
                mma1688_z(o0, vm.x, vm.y, P[0]);
                mma1688_z(o1, vm.z, vm.w, P[0]);
                mma16816(sm, ONES, ONES, ONES, ONES, P[1], P[2]);
                mma16816(o0, vx[0].x, vx[0].y, vx[0].z, vx[0].w, P[1], P[2]);
                mma16816(o1, vx[2].x, vx[2].y, vx[2].z, vx[2].w, P[1], P[2]);
                mma16816(sm, ONES, ONES, ONES, ONES, P[3], P[4]);
                mma16816(o0, vx[1].x, vx[1].y, vx[1].z, vx[1].w, P[3], P[4]);
                mma16816(o1, vx[3].x, vx[3].y, vx[3].z, vx[3].w, P[3], P[4]);
                const float sig = __uint_as_float((268u << 23) - ebits);
                const float r0 = rcp_fast(sm[0]) * sig, r1 = rcp_fast(sm[1]) * sig;
                stsm4t(sb + O_OF + c * 512 + l16, pack_bf16(o0[0] * r0, o0[1] * r1), pack_bf16(o0[2] * r0, o0[3] * r1),
                       pack_bf16(o1[0] * r0, o1[1] * r1), pack_bf16(o1[2] * r0, o1[3] * r1));
                bar_sync(6, 128);
                uint4 ob[4];
#pragma unroll
                for (int q = 0; q < 4; q++) ob[q] = ldsm4(sb + O_OF + q * 512 + l16);
                float m0[3][4], m1[3][4];
#pragma unroll
                for (int q = 0; q < 4; q++) {
#pragma unroll
                    for (int i = 0; i < 3; i++) {
                        const int k0 = (i * 8 + 2 * q) * 4;
                        if (q == 0) mma16816_z(m0[i], a[k0], a[k0 + 1], a[k0 + 2], a[k0 + 3], ob[q].x, ob[q].y);
                        else mma16816(m0[i], a[k0], a[k0 + 1], a[k0 + 2], a[k0 + 3], ob[q].x, ob[q].y);
                    }
#pragma unroll
                    for (int i = 0; i < 3; i++) {
                        const int k1 = (i * 8 + 2 * q + 1) * 4;
                        if (q == 0) mma16816_z(m1[i], a[k1], a[k1 + 1], a[k1 + 2], a[k1 + 3], ob[q].z, ob[q].w);
                        else mma16816(m1[i], a[k1], a[k1 + 1], a[k1 + 2], a[k1 + 3], ob[q].z, ob[q].w);
                    }
                }
                asm volatile("red.relaxed.gpu.global.add.noftz.v4.f16x2 [%0], {%1,%2,%3,%4};" :: "l"(rptr),
                    "r"(pack_f16(m0[0][0] + m1[0][0], m0[0][2] + m1[0][2])), "r"(pack_f16(m0[1][0] + m1[1][0], m0[1][2] + m1[1][2])),
                    "r"(pack_f16(m0[2][0] + m1[2][0], m0[2][2] + m1[2][2])), "r"(0x3c00u) : "memory");
                asm volatile("red.relaxed.gpu.global.add.noftz.v4.f16x2 [%0], {%1,%2,%3,%4};" :: "l"(rptr + 1024),
                    "r"(pack_f16(m0[0][1] + m1[0][1], m0[0][3] + m1[0][3])), "r"(pack_f16(m0[1][1] + m1[1][1], m0[1][3] + m1[1][3])),
                    "r"(pack_f16(m0[2][1] + m1[2][1], m0[2][3] + m1[2][3])), "r"(0x3c00u) : "memory");
                const unsigned t_red = clk();
                bar_arrive(5, 256);
                bar_arrive(13, 256);
                if (s < NSEG - 2) {
                    const uint32_t bar = sb + (c == 0 ? B_SC : c == 1 ? B_VM : B_VX + 8 * ((s + 1) & 1));
                    mbar_expect_if(l16 | (uint32_t)(c == 3 || (c == 2 && r == 2)), bar, c == 0 ? 2560 : c == 1 ? 2048 : 8192);
                }
                sts32_if(l16 | (c ^ 3), sb + O_MISC, ebits - (14u << 23));
                if (c == 0) STAMPV(s, 8, t_red);
                const char* pbase = rptr + pdelta;
                spin_until(t_red, D_WAIT);
                uint4 v[6];
#pragma unroll
                for (int i = 0; i < 6; i++) v[i] = ldg_relaxed128(pbase + (i >> 1) * 8192 + (i & 1) * 512);
                int nretry = 0;
                auto hand_over = [&]() -> uint32_t {
                    const uint32_t ok = __all_sync(~0u, (v[0].w & v[1].w & v[2].w & v[3].w & v[4].w & v[5].w) == 0x5000u);
#pragma unroll
                    for (int tau = 0; tau < 3; tau++) {
                        v[2 * tau].x = f16x2_to_bf16x2(v[2 * tau].x); v[2 * tau + 1].x = f16x2_to_bf16x2(v[2 * tau + 1].x);
                        v[2 * tau].y = f16x2_to_bf16x2(v[2 * tau].y); v[2 * tau + 1].y = f16x2_to_bf16x2(v[2 * tau + 1].y);
                        v[2 * tau].z = f16x2_to_bf16x2(v[2 * tau].z); v[2 * tau + 1].z = f16x2_to_bf16x2(v[2 * tau + 1].z);
                        sts128(sb + O_MF + tau * 3072 + c * 512 + l16, v[2 * tau].x, v[2 * tau + 1].x, v[2 * tau].y, v[2 * tau + 1].y);
                        sts64(sb + O_MF + tau * 3072 + 2048 + (c >> 1) * 512 + (c & 1) * 8 + l16, v[2 * tau].z, v[2 * tau + 1].z);
                    }
                    asm volatile("{\n.reg .pred p;\nsetp.ne.u32 p, %0, 0;\n@p bar.arrive 2, 384;\n}" :: "r"(ok) : "memory");
                    return ok;
                };
                if (!hand_over()) {
                    asm volatile("{\n.reg .pred p, q;\n.reg .u32 n, x;\nmov.u32 n, 0;\n"
                         "R_%=: ld.relaxed.gpu.global.v4.u32 {%0,%1,%2,%3}, [%25];\nld.relaxed.gpu.global.v4.u32 {%4,%5,%6,%7}, [%25+512];\n"
                         "ld.relaxed.gpu.global.v4.u32 {%8,%9,%10,%11}, [%25+8192];\nld.relaxed.gpu.global.v4.u32 {%12,%13,%14,%15}, [%25+8704];\n"
                         "ld.relaxed.gpu.global.v4.u32 {%16,%17,%18,%19}, [%25+16384];\nld.relaxed.gpu.global.v4.u32 {%20,%21,%22,%23}, [%25+16896];\n"
                         "add.u32 %24, %24, 1;\nand.b32 x, %3, %7;\nand.b32 x, x, %11;\nand.b32 x, x, %15;\nand.b32 x, x, %19;\nand.b32 x, x, %23;\n"
                         "setp.eq.u32 p, x, 0x5000;\nvote.sync.all.pred q, p, 0xffffffff;\n@q bra.uni K_%=;\n"
                         "add.u32 n, n, 1;\nsetp.lt.u32 q, n, 2000000;\n@q bra.uni R_%=;\ntrap;\nK_%=:\n}"
                         : "+r"(v[0].x), "+r"(v[0].y), "+r"(v[0].z), "+r"(v[0].w), "+r"(v[1].x), "+r"(v[1].y), "+r"(v[1].z), "+r"(v[1].w),
                           "+r"(v[2].x), "+r"(v[2].y), "+r"(v[2].z), "+r"(v[2].w), "+r"(v[3].x), "+r"(v[3].y), "+r"(v[3].z), "+r"(v[3].w),
                           "+r"(v[4].x), "+r"(v[4].y), "+r"(v[4].z), "+r"(v[4].w), "+r"(v[5].x), "+r"(v[5].y), "+r"(v[5].z), "+r"(v[5].w), "+r"(nretry)
                         : "l"(pbase) : "memory");
                    hand_over();
                }
                if (c == 0) STAMP(s, 12);
                if (c == 0) STAMPV(s, 14, nretry);
                mmax = absmax2(absmax2(absmax2(v[0].x, v[0].y), absmax2(v[0].z, v[1].x)), absmax2(absmax2(v[1].y, v[1].z), absmax2(v[2].x, v[2].y)));
                mmax = absmax2(mmax, absmax2(absmax2(absmax2(v[2].z, v[3].x), absmax2(v[3].y, v[3].z)), absmax2(absmax2(v[4].x, v[4].y), absmax2(v[4].z, v[5].x))));
                mmax = absmax2(mmax, absmax2(v[5].y, v[5].z)) & 0x7fff7fffu;
                mmax = max(mmax << 16, mmax & 0xffff0000u);
            }
            rptr += 24576;
        }
        {
            bar_sync(7, 384);
            if (c == 0)
                asm volatile("{\n.reg .pred p;\nsetp.eq.u32 p, %1, 0;\n@p red.release.gpu.global.inc.u32 [%0], 0x7fffffff;\n}"
                             :: "l"(&g_flag[(63 * 4 + (h >> 3)) * 8]), "r"(l16c) : "memory");
        }
    }
    cluster_sync();
}

__device__ float g_u[SEQ * 2 * DM];
__global__ void naive_gemm1(const __nv_bfloat16* x, const __nv_bfloat16* Bre, const __nv_bfloat16* Bim) {
    int p = blockIdx.x * 64 + threadIdx.x % 64, tk = blockIdx.y * 4 + threadIdx.x / 64;
    float sr = 0, si = 0;
    for (int d = 0; d < DM; d++) { float xv = __bfloat162float(x[tk * DM + d]); sr += xv * __bfloat162float(Bre[p * DM + d]); si += xv * __bfloat162float(Bim[p * DM + d]); }
    g_u[tk * 2 * DM + 2 * p] = sr; g_u[tk * 2 * DM + 2 * p + 1] = si;
}
__global__ void naive_scan(const __nv_bfloat16* Lre, const __nv_bfloat16* Lim, const __nv_bfloat16* logdt) {
    int p = blockIdx.x * 64 + threadIdx.x;
    float dt = __bfloat162float(__float2bfloat16(expf(__bfloat162float(logdt[p]))));
    float lr = __bfloat162float(Lre[p]), li = __bfloat162float(Lim[p]);
    float e = expf(dt * lr), br = e * cosf(dt * li), bi = e * sinf(dt * li);
    float den = lr * lr + li * li;
    float cr = ((br - 1.f) * lr + bi * li) / den, ci = (bi * lr - (br - 1.f) * li) / den;
    float hr = 0, hi = 0;
    for (int tk = 0; tk < SEQ; tk++) {
        float ur = g_u[tk * 2 * DM + 2 * p], ui = g_u[tk * 2 * DM + 2 * p + 1];
        float nr = br * hr - bi * hi + cr * ur - ci * ui, ni = br * hi + bi * hr + cr * ui + ci * ur;
        hr = nr; hi = ni;
        g_u[tk * 2 * DM + 2 * p] = hr; g_u[tk * 2 * DM + 2 * p + 1] = hi;
    }
}
__global__ void naive_gemm2(const __nv_bfloat16* x, const __nv_bfloat16* Cre, const __nv_bfloat16* Cim, const __nv_bfloat16* Dk, float* out) {
    int d = blockIdx.x * 64 + threadIdx.x % 64, tk = blockIdx.y * 4 + threadIdx.x / 64;
    float s = 0;
    for (int p = 0; p < DM; p++) s += g_u[tk * 2 * DM + 2 * p] * __bfloat162float(Cre[d * DM + p]) - g_u[tk * 2 * DM + 2 * p + 1] * __bfloat162float(Cim[d * DM + p]);
    out[tk * 1152 + d] = 2.f * s + __bfloat162float(__float2bfloat16(__bfloat162float(x[tk * DM + d]) * __bfloat162float(Dk[d])));
}
__device__ float frag_elem(const uint32_t* base, int e, int tok) {
    int eb = e >> 4, g = (e & 15) >> 1, hi = e & 1, j = tok >> 3, t = (tok & 7) >> 1, i = 2 * j + hi;
    uint32_t v = base[eb * 256 + (i >> 2) * 128 + (g * 4 + t) * 4 + (i & 3)];
    return __uint_as_float((tok & 1) ? (v & 0xffff0000u) : (v << 16));
}
__device__ float fragm_elem(const uint32_t* base, int e, int tok) {
    int eb = e >> 4, g = (e & 15) >> 1, hi = e & 1, t = tok >> 1;
    uint32_t v = base[eb * 64 + (g * 4 + t) * 2 + hi];
    return __uint_as_float((tok & 1) ? (v & 0xffff0000u) : (v << 16));
}
__global__ void naive_attn() {
    int s = blockIdx.x / NH, h = blockIdx.x % NH, q = threadIdx.x;
    const uint32_t* qkv = reinterpret_cast<const uint32_t*>(g_qkv) + (size_t)blockIdx.x * 6144;
    const uint32_t* kvm = reinterpret_cast<const uint32_t*>(g_kvm) + (size_t)blockIdx.x * 1536;
    float p[40], mx = -1e30f, sum = 0;
    for (int k = 0; k < 40; k++) {
        float d = 0;
        for (int e = 0; e < 128; e++)
            d += frag_elem(qkv, e, q) * (k < 8 ? fragm_elem(kvm, e, k) + fragm_elem(kvm + 512, e, k) : frag_elem(qkv + 2048, e, k - 8));
        p[k] = (k < 8 || k - 8 <= q) ? d * 0.08838834764831845f : -1e30f;
        mx = fmaxf(mx, p[k]);
    }
    for (int k = 0; k < 40; k++) { p[k] = expf(p[k] - mx); sum += p[k]; }
    __nv_bfloat16* ox = reinterpret_cast<__nv_bfloat16*>(g_ox);
    int tk = s * 32 + q;
    for (int e = 0; e < 128; e++) {
        float o = 0;
        for (int k = 0; k < 40; k++) o += p[k] * (k < 8 ? fragm_elem(kvm + 1024, e, k) : frag_elem(qkv + 4096, e, k - 8));
        int e0 = e & 63, ep = (e0 & 48) + (e0 & 1) * 8 + ((e0 & 15) >> 1);
        ox[((size_t)(h * 2 + (e >> 6)) * SEQ + tk) * 64 + (((ep >> 3) ^ (tk & 7)) << 3) + (ep & 7)] = __float2bfloat16(o / sum);
    }
}
__global__ void naive_wo(const __nv_bfloat16* Wo, float* out) {
    int d = blockIdx.x * 64 + threadIdx.x % 64, tk = blockIdx.y * 4 + threadIdx.x / 64;
    const __nv_bfloat16* ox = reinterpret_cast<const __nv_bfloat16*>(g_ox);
    float s = 0;
    for (int k = 0; k < HD; k++) {
        int hh = k >> 6, e0 = k & 63, e = (e0 & 48) + (e0 & 1) * 8 + ((e0 & 15) >> 1);
        s += __bfloat162float(ox[((size_t)hh * SEQ + tk) * 64 + (((e >> 3) ^ (tk & 7)) << 3) + (e & 7)]) * __bfloat162float(Wo[k * DM + d]);
    }
    out[tk * 1152 + DM + d] = s;
}

typedef CUresult (*EncodeFn)(CUtensorMap*, CUtensorMapDataType, cuuint32_t, void*, const cuuint64_t*, const cuuint64_t*, const cuuint32_t*, const cuuint32_t*,
                             CUtensorMapInterleave, CUtensorMapSwizzle, CUtensorMapL2promotion, CUtensorMapFloatOOBfill);
}

extern "C" void kernel_launch(void* const* d_in, const int* in_sizes, int n_in, void* d_out, int out_size) {
    typedef const __nv_bfloat16* bp;
    bp Ax = (bp)d_in[0], Lre = (bp)d_in[1], Lim = (bp)d_in[2], Bre = (bp)d_in[3], Bim = (bp)d_in[4], Cre = (bp)d_in[5], Cim = (bp)d_in[6],
       logdt = (bp)d_in[7], Dk = (bp)d_in[8], Bx = (bp)d_in[9], mem0 = (bp)d_in[10], Wq = (bp)d_in[11], Wk = (bp)d_in[12], Wv = (bp)d_in[13], Wo = (bp)d_in[14];
    float* out = (float*)d_out;
    static EncodeFn enc = nullptr;
    if (!enc) {
        void* fn = nullptr; cudaDriverEntryPointQueryResult qr;
        cudaGetDriverEntryPoint("cuTensorMapEncodeTiled", &fn, cudaEnableDefault, &qr);
        enc = (EncodeFn)fn;
        cudaFuncSetAttribute(chain_kernel, cudaFuncAttributeMaxDynamicSharedMemorySize, CHAIN_SMEM);
    }
    CUtensorMap tm_x;
    {
        cuuint64_t gd[2] = {DM, SEQ}; cuuint64_t gs[1] = {DM * 2}; cuuint32_t bd[2] = {64, 32}; cuuint32_t es[2] = {1, 1};
        enc(&tm_x, CU_TENSOR_MAP_DATA_TYPE_BFLOAT16, 2, (void*)Bx, gd, gs, bd, es, CU_TENSOR_MAP_INTERLEAVE_NONE, CU_TENSOR_MAP_SWIZZLE_128B,
            CU_TENSOR_MAP_L2_PROMOTION_L2_128B, CU_TENSOR_MAP_FLOAT_OOB_FILL_NONE);
    }
    cudaStream_t st = cudaStreamPerThread;
    chain_kernel<<<96, 384, CHAIN_SMEM, st>>>(tm_x, Bx, mem0, Wq, Wk, Wv, Wo);
    naive_gemm1<<<dim3(9, 512), 256, 0, st>>>(Ax, Bre, Bim);
    naive_scan<<<9, 64, 0, st>>>(Lre, Lim, logdt);
    naive_gemm2<<<dim3(9, 512), 256, 0, st>>>(Ax, Cre, Cim, Dk, out);
    naive_attn<<<NSEG * NH, 32, 0, st>>>();
    naive_wo<<<dim3(9, 512), 256, 0, st>>>(Wo, out);
}
```

```cpp
#include <cuda_runtime.h>
#include <cuda.h>
#include <cuda_bf16.h>
#include <cuda_fp16.h>
#include <stdint.h>

#define D_WAIT 700

namespace {

constexpr int DM = 576, NH = 32, SEQ = 2048, NSEG = 64, HD = 4096;

__device__ uint4 g_acc[64 * 96 * 16];
__device__ uint4 g_ox[NH * 2 * SEQ * 8];
__device__ uint4 g_qkv[NSEG * NH * 3 * 512];
__device__ uint2 g_kvm[NSEG * NH * 3 * 256];
__device__ unsigned g_flag[NSEG * 4 * 8];
__device__ unsigned g_gridbar;
__device__ float g_norm[96 * 4];

__device__ __forceinline__ uint32_t smem_u32(const void* p) { return (uint32_t)__cvta_generic_to_shared(p); }
__device__ __forceinline__ uint32_t mapa(uint32_t a, uint32_t r) { uint32_t o; asm("mapa.shared::cluster.u32 %0, %1, %2;" : "=r"(o) : "r"(a), "r"(r)); return o; }
__device__ __forceinline__ uint32_t mapa_v(uint32_t a, uint32_t r) { uint32_t o; asm volatile("mapa.shared::cluster.u32 %0, %1, %2;" : "=r"(o) : "r"(a), "r"(r)); return o; }
__device__ __forceinline__ unsigned clk() { unsigned long long c; asm volatile("mov.u64 %0, %%clock64;" : "=l"(c) :: "memory"); return (unsigned)c; }
__device__ __forceinline__ void mbar_init(uint32_t bar, uint32_t cnt) { asm volatile("mbarrier.init.shared::cta.b64 [%0], %1;" :: "r"(bar), "r"(cnt) : "memory"); }
__device__ __forceinline__ void mbar_expect(uint32_t bar, uint32_t bytes) { asm volatile("mbarrier.arrive.expect_tx.shared::cta.b64 _, [%0], %1;" :: "r"(bar), "r"(bytes) : "memory"); }
__device__ __forceinline__ void mbar_wait(uint32_t bar, uint32_t parity) {
    asm volatile("{\n.reg .pred p;\n.reg .u32 n;\nmov.u32 n, 0;\n"
                 "W_%=: mbarrier.try_wait.parity.shared::cta.b64 p, [%0], %1;\n@p bra.uni D_%=;\n"
                 "add.u32 n, n, 1;\nsetp.lt.u32 p, n, 4000000;\n@p bra.uni W_%=;\ntrap;\nD_%=:\n}" :: "r"(bar), "r"(parity) : "memory");
}
__device__ __forceinline__ void mbar_expect_if(uint32_t z, uint32_t bar, uint32_t bytes) {
    asm volatile("{\n.reg .pred p;\nsetp.eq.u32 p, %2, 0;\n@p mbarrier.arrive.expect_tx.shared::cta.b64 _, [%0], %1;\n}" :: "r"(bar), "r"(bytes), "r"(z) : "memory");
}
__device__ __forceinline__ void mbar_arrive_if(uint32_t z, uint32_t bar) {
    asm volatile("{\n.reg .pred p;\nsetp.eq.u32 p, %1, 0;\n@p mbarrier.arrive.shared::cta.b64 _, [%0];\n}" :: "r"(bar), "r"(z) : "memory");
}
__device__ __forceinline__ void sts32_if(uint32_t z, uint32_t a, uint32_t x) {
    asm volatile("{\n.reg .pred p;\nsetp.eq.u32 p, %2, 0;\n@p st.shared.u32 [%0], %1;\n}" :: "r"(a), "r"(x), "r"(z) : "memory");
}
__device__ __forceinline__ void spin_until(unsigned t0, unsigned d) {
    asm volatile("{\n.reg .pred p;\n.reg .u64 c;\n.reg .u32 lo;\n"
                 "S_%=: mov.u64 c, %%clock64;\ncvt.u32.u64 lo, c;\nsub.u32 lo, lo, %0;\nsetp.lt.u32 p, lo, %1;\n@p bra.uni S_%=;\n}" :: "r"(t0), "r"(d) : "memory");
}
__device__ __forceinline__ void bar_sync(int id, int n) { asm volatile("bar.sync %0, %1;" :: "r"(id), "r"(n) : "memory"); }
__device__ __forceinline__ void bar_sync_sel(int sel, int id) {
    asm volatile("{\n.reg .pred p;\nsetp.eq.u32 p, %0, 0;\n@p bar.sync %1, %3;\n@!p bar.sync %2, %3;\n}" :: "r"(sel), "r"(id), "r"(id + 1), "n"(192) : "memory");
}
__device__ __forceinline__ void bar_arrive(int id, int n) { asm volatile("bar.arrive %0, %1;" :: "r"(id), "r"(n) : "memory"); }
__device__ __forceinline__ void fence_async_smem() { asm volatile("fence.proxy.async.shared::cta;" ::: "memory"); }
__device__ __forceinline__ uint32_t pack_bf16(float lo, float hi) { uint32_t r; asm("cvt.rn.bf16x2.f32 %0, %1, %2;" : "=r"(r) : "f"(hi), "f"(lo)); return r; }
__device__ __forceinline__ uint32_t pack_f16(float lo, float hi) { uint32_t r; asm("cvt.rn.f16x2.f32 %0, %1, %2;" : "=r"(r) : "f"(hi), "f"(lo)); return r; }
__device__ __forceinline__ uint32_t f16x2_to_bf16x2(uint32_t v) { float2 f = __half22float2(*reinterpret_cast<__half2*>(&v)); return pack_bf16(f.x, f.y); }
__device__ __forceinline__ float ex2(float x) { float y; asm("ex2.approx.ftz.f32 %0, %1;" : "=f"(y) : "f"(x)); return y; }
__device__ __forceinline__ float ex2v(float x) { float y; asm volatile("ex2.approx.ftz.f32 %0, %1;" : "=f"(y) : "f"(x)); return y; }
__device__ __forceinline__ uint32_t absmax2(uint32_t a, uint32_t b) {
    uint32_t r; asm("max.xorsign.abs.bf16x2 %0, %1, %2;" : "=r"(r) : "r"(a), "r"(b)); return r;
}
__device__ __forceinline__ uint32_t shl_v(uint32_t a, int n) { return a << n; }
__device__ __forceinline__ uint32_t max3u(uint32_t a, uint32_t b, uint32_t c) { return max(max(a, b), c); }
__device__ __forceinline__ uint4 lds128(uint32_t a) { uint4 v; asm volatile("ld.shared.v4.u32 {%0,%1,%2,%3}, [%4];" : "=r"(v.x), "=r"(v.y), "=r"(v.z), "=r"(v.w) : "r"(a) : "memory"); return v; }
__device__ __forceinline__ float4 lds128f(uint32_t a) { float4 v; asm volatile("ld.shared.v4.f32 {%0,%1,%2,%3}, [%4];" : "=f"(v.x), "=f"(v.y), "=f"(v.z), "=f"(v.w) : "r"(a) : "memory"); return v; }
__device__ __forceinline__ float2 lds64f(uint32_t a) { float2 v; asm volatile("ld.shared.v2.f32 {%0,%1}, [%2];" : "=f"(v.x), "=f"(v.y) : "r"(a) : "memory"); return v; }
__device__ __forceinline__ uint4 lds64x2(uint32_t a) { uint4 v; asm volatile("ld.shared.v2.u32 {%0,%1}, [%4];\nld.shared.v2.u32 {%2,%3}, [%4+256];" : "=r"(v.x), "=r"(v.y), "=r"(v.z), "=r"(v.w) : "r"(a) : "memory"); return v; }
__device__ __forceinline__ uint32_t lds32(uint32_t a) { uint32_t v; asm volatile("ld.shared.u32 %0, [%1];" : "=r"(v) : "r"(a) : "memory"); return v; }
__device__ __forceinline__ void sts128(uint32_t a, uint32_t x, uint32_t y, uint32_t z, uint32_t w) { asm volatile("st.shared.v4.u32 [%0], {%1,%2,%3,%4};" :: "r"(a), "r"(x), "r"(y), "r"(z), "r"(w) : "memory"); }
__device__ __forceinline__ void sts128f(uint32_t a, float x, float y, float z, float w) { asm volatile("st.shared.v4.f32 [%0], {%1,%2,%3,%4};" :: "r"(a), "f"(x), "f"(y), "f"(z), "f"(w) : "memory"); }
__device__ __forceinline__ void sts64(uint32_t a, uint32_t x, uint32_t y) { asm volatile("st.shared.v2.u32 [%0], {%1,%2};" :: "r"(a), "r"(x), "r"(y) : "memory"); }
__device__ __forceinline__ void sts32(uint32_t a, uint32_t x) { asm volatile("st.shared.u32 [%0], %1;" :: "r"(a), "r"(x) : "memory"); }
__device__ __forceinline__ uint4 ldsm4(uint32_t a) { uint4 v; asm volatile("ldmatrix.sync.aligned.m8n8.x4.shared.b16 {%0,%1,%2,%3}, [%4];" : "=r"(v.x), "=r"(v.y), "=r"(v.z), "=r"(v.w) : "r"(a) : "memory"); return v; }
__device__ __forceinline__ void stsm2t(uint32_t a, uint32_t x, uint32_t y) { asm volatile("stmatrix.sync.aligned.m8n8.x2.trans.shared.b16 [%0], {%1,%2};" :: "r"(a), "r"(x), "r"(y) : "memory"); }
__device__ __forceinline__ void stsm4t(uint32_t a, uint32_t x, uint32_t y, uint32_t z, uint32_t w) { asm volatile("stmatrix.sync.aligned.m8n8.x4.trans.shared.b16 [%0], {%1,%2,%3,%4};" :: "r"(a), "r"(x), "r"(y), "r"(z), "r"(w) : "memory"); }
__device__ __forceinline__ void st_async64(uint32_t a, uint32_t x, uint32_t y, uint32_t bar) { asm volatile("st.async.shared::cluster.mbarrier::complete_tx::bytes.v2.b32 [%0], {%1,%2}, [%3];" :: "r"(a), "r"(x), "r"(y), "r"(bar) : "memory"); }
__device__ __forceinline__ void bulk_s2c(uint32_t dst, uint32_t src, uint32_t bytes, uint32_t bar) { asm volatile("cp.async.bulk.shared::cluster.shared::cta.mbarrier::complete_tx::bytes [%0], [%1], %2, [%3];" :: "r"(dst), "r"(src), "r"(bytes), "r"(bar) : "memory"); }
__device__ __forceinline__ void bulk_s2g(void* dst, uint32_t src, uint32_t bytes) { asm volatile("cp.async.bulk.global.shared::cta.bulk_group [%0], [%1], %2;" :: "l"(dst), "r"(src), "r"(bytes) : "memory"); }
__device__ __forceinline__ uint32_t ldg_nc32(const void* p) { uint32_t v; asm volatile("ld.global.nc.L2::128B.u32 %0, [%1];" : "=r"(v) : "l"(p)); return v; }
__device__ __forceinline__ uint4 ldg_relaxed128(const void* p) { uint4 v; asm volatile("ld.relaxed.gpu.global.v4.u32 {%0,%1,%2,%3}, [%4];" : "=r"(v.x), "=r"(v.y), "=r"(v.z), "=r"(v.w) : "l"(p) : "memory"); return v; }
__device__ __forceinline__ void mma16816(float (&d)[4], uint32_t a0, uint32_t a1, uint32_t a2, uint32_t a3, uint32_t b0, uint32_t b1) {
    asm volatile("mma.sync.aligned.m16n8k16.row.col.f32.bf16.bf16.f32 {%0,%1,%2,%3}, {%4,%5,%6,%7}, {%8,%9}, {%0,%1,%2,%3};"
        : "+f"(d[0]), "+f"(d[1]), "+f"(d[2]), "+f"(d[3]) : "r"(a0), "r"(a1), "r"(a2), "r"(a3), "r"(b0), "r"(b1));
}
__device__ __forceinline__ void mma16816_z(float (&d)[4], uint32_t a0, uint32_t a1, uint32_t a2, uint32_t a3, uint32_t b0, uint32_t b1) {
    asm volatile("mma.sync.aligned.m16n8k16.row.col.f32.bf16.bf16.f32 {%0,%1,%2,%3}, {%4,%5,%6,%7}, {%8,%9}, {%10,%10,%10,%10};"
        : "=f"(d[0]), "=f"(d[1]), "=f"(d[2]), "=f"(d[3]) : "r"(a0), "r"(a1), "r"(a2), "r"(a3), "r"(b0), "r"(b1), "f"(0.f));
}
__device__ __forceinline__ void mma1688(float (&d)[4], uint32_t a0, uint32_t a1, uint32_t b0) {
    asm volatile("mma.sync.aligned.m16n8k8.row.col.f32.bf16.bf16.f32 {%0,%1,%2,%3}, {%4,%5}, {%6}, {%0,%1,%2,%3};"
        : "+f"(d[0]), "+f"(d[1]), "+f"(d[2]), "+f"(d[3]) : "r"(a0), "r"(a1), "r"(b0));
}
__device__ __forceinline__ void mma1688_z(float (&d)[4], uint32_t a0, uint32_t a1, uint32_t b0) {
    asm volatile("mma.sync.aligned.m16n8k8.row.col.f32.bf16.bf16.f32 {%0,%1,%2,%3}, {%4,%5}, {%6}, {%7,%7,%7,%7};"
        : "=f"(d[0]), "=f"(d[1]), "=f"(d[2]), "=f"(d[3]) : "r"(a0), "r"(a1), "r"(b0), "f"(0.f));
}
template <int ACC>
__device__ __forceinline__ void wgmma_n32_rs(float (&d)[16], uint32_t a0, uint32_t a1, uint32_t a2, uint32_t a3, uint64_t desc) {
    asm volatile("wgmma.mma_async.sync.aligned.m64n32k16.f32.bf16.bf16 {%0,%1,%2,%3,%4,%5,%6,%7,%8,%9,%10,%11,%12,%13,%14,%15}, {%16,%17,%18,%19}, %20, %21, 1, 1, 0;"
        : "+f"(d[0]), "+f"(d[1]), "+f"(d[2]), "+f"(d[3]), "+f"(d[4]), "+f"(d[5]), "+f"(d[6]), "+f"(d[7]),
          "+f"(d[8]), "+f"(d[9]), "+f"(d[10]), "+f"(d[11]), "+f"(d[12]), "+f"(d[13]), "+f"(d[14]), "+f"(d[15])
        : "r"(a0), "r"(a1), "r"(a2), "r"(a3), "l"(desc), "n"(ACC));
}
template <int ACC>
__device__ __forceinline__ void wgmma_n32_ss(float (&d)[16], uint64_t da, uint64_t db) {
    asm volatile("wgmma.mma_async.sync.aligned.m64n32k16.f32.bf16.bf16 {%0,%1,%2,%3,%4,%5,%6,%7,%8,%9,%10,%11,%12,%13,%14,%15}, %16, %17, %18, 1, 1, 0, 0;"
        : "+f"(d[0]), "+f"(d[1]), "+f"(d[2]), "+f"(d[3]), "+f"(d[4]), "+f"(d[5]), "+f"(d[6]), "+f"(d[7]),
          "+f"(d[8]), "+f"(d[9]), "+f"(d[10]), "+f"(d[11]), "+f"(d[12]), "+f"(d[13]), "+f"(d[14]), "+f"(d[15])
        : "l"(da), "l"(db), "n"(ACC));
}
__device__ __forceinline__ void wg_fence() { asm volatile("wgmma.fence.sync.aligned;" ::: "memory"); }
__device__ __forceinline__ void wg_commit() { asm volatile("wgmma.commit_group.sync.aligned;" ::: "memory"); }
__device__ __forceinline__ void wg_wait0() { asm volatile("wgmma.wait_group.sync.aligned 0;" ::: "memory"); }
__device__ __forceinline__ void cluster_sync() { asm volatile("barrier.cluster.arrive.aligned;\nbarrier.cluster.wait.aligned;" ::: "memory"); }

#define STAMP(s, i) do {} while (0)
#define STAMPV(s, i, v) do {} while (0)

constexpr int XT_BYTES = 36864;
constexpr int O_XT = 0;
constexpr int O_AS = 3 * XT_BYTES;
constexpr int O_AF = O_AS + 16384;
constexpr int O_MF = O_AF + 16384;
constexpr int O_XP = O_MF + 9216;
constexpr int O_VX = O_XP + 8192;
constexpr int O_VM = O_VX + 16384;
constexpr int O_SC = O_VM + 2048;
constexpr int O_OF = O_SC + 2560;
constexpr int O_QM = O_OF + 2048;
constexpr int O_QKX = O_QM + 2048;
constexpr int O_KM = O_QKX + 16384;
constexpr int O_MISC = O_KM + 2048;
constexpr int O_BAR = O_MISC + 64;
constexpr int CHAIN_SMEM = O_BAR + 128;
static_assert(CHAIN_SMEM <= 232448, "smem");
constexpr int B_X = O_BAR, B_VX = O_BAR + 24, B_SC = O_BAR + 40, B_VM = O_BAR + 48;
constexpr float SM_SCALE = 0.08838834764831845f * 1.4426950408889634f;
constexpr uint32_t ONES = 0x3f803f80u;

__device__ __forceinline__ uint32_t opaque(uint32_t v) { uint32_t o; asm volatile("mov.u32 %0, %1;" : "=r"(o) : "r"(v)); return o; }
__device__ __forceinline__ void st_async128(uint32_t a, uint32_t x, uint32_t y, uint32_t z, uint32_t w, uint32_t bar) {
    asm volatile("st.async.shared::cluster.mbarrier::complete_tx::bytes.v4.b32 [%0], {%1,%2,%3,%4}, [%5];" :: "r"(a), "r"(x), "r"(y), "r"(z), "r"(w), "r"(bar) : "memory");
}
__device__ __forceinline__ void tma_x_tile(uint32_t sb, const CUtensorMap* tm, int r, int j, int slot) {
    asm volatile("{\n.reg .pred p;\nelect.sync _|p, 0xffffffff;\n"
        "@p mbarrier.arrive.expect_tx.shared::cta.b64 _, [%2], 36864;\n"
        "@p cp.async.bulk.tensor.2d.shared::cluster.global.mbarrier::complete_tx::bytes.multicast::cluster [%0], [%1, {%3, %4}], [%2], %7;\n"
        "@p cp.async.bulk.tensor.2d.shared::cluster.global.mbarrier::complete_tx::bytes.multicast::cluster [%0+4096], [%1, {%5, %4}], [%2], %7;\n"
        "@p cp.async.bulk.tensor.2d.shared::cluster.global.mbarrier::complete_tx::bytes.multicast::cluster [%0+8192], [%1, {%6, %4}], [%2], %7;\n}"
        :: "r"(sb + O_XT + slot * XT_BYTES + 3 * r * 4096), "l"(tm), "r"(sb + B_X + 8 * slot), "r"(192 * r), "r"(j * 32), "r"(192 * r + 64), "r"(192 * r + 128),
           "h"((unsigned short)7) : "memory");
}
__device__ __forceinline__ float quad_max(float v) {
    const float a = __shfl_xor_sync(~0u, v, 1), b = __shfl_xor_sync(~0u, v, 2), c = __shfl_xor_sync(~0u, v, 3);
    return fmaxf(fmaxf(v, a), fmaxf(b, c));
}
__device__ __forceinline__ void load_scores(float (&p)[10], uint32_t base, uint32_t stride, uint32_t l16) {
    const float4 a0 = lds128f(base + l16), b0 = lds128f(base + stride + l16);
    const float4 a1 = lds128f(base + 512 + l16), b1 = lds128f(base + stride + 512 + l16);
    const float2 a2 = lds64f(base + 1024 + (l16 >> 1)), b2 = lds64f(base + stride + 1024 + (l16 >> 1));
    p[0] = a2.x + b2.x; p[1] = a2.y + b2.y;
    p[2] = a0.x + b0.x; p[3] = a0.y + b0.y; p[4] = a0.z + b0.z; p[5] = a0.w + b0.w;
    p[6] = a1.x + b1.x; p[7] = a1.y + b1.y; p[8] = a1.z + b1.z; p[9] = a1.w + b1.w;
}
__device__ __forceinline__ float rcp_fast(float x) { float y; asm("rcp.approx.ftz.f32 %0, %1;" : "=f"(y) : "f"(x)); return y; }

__global__ void __cluster_dims__(3, 1, 1) __launch_bounds__(384, 1)
chain_kernel(const __grid_constant__ CUtensorMap tm_x,
             const __nv_bfloat16* __restrict__ x, const __nv_bfloat16* __restrict__ mem0,
             const __nv_bfloat16* __restrict__ Wq, const __nv_bfloat16* __restrict__ Wk,
             const __nv_bfloat16* __restrict__ Wv, const __nv_bfloat16* __restrict__ Wo) {
    extern __shared__ __align__(1024) uint8_t smem_raw[];
    const uint32_t sb = smem_u32(smem_raw);
    const int lane = threadIdx.x & 31;
    const int warp = __shfl_sync(~0u, threadIdx.x >> 5, 0);
    const int wg = warp >> 2, w = warp & 3;
    const int h = blockIdx.x / 3, r = blockIdx.x - 3 * h;

    if (threadIdx.x == 0) {
        if (sb & 1023u) __trap();
        for (int i = 0; i < 7; i++) mbar_init(sb + O_BAR + 8 * i, 1);
        asm volatile("fence.mbarrier_init.release.cluster;" ::: "memory");
    }
    if (blockIdx.x == 0) {
        for (int i = threadIdx.x; i < NSEG * 4 * 8; i += 384) g_flag[i] = 0;
        __threadfence();
    }
    __syncthreads();
    cluster_sync();
    asm volatile("griddepcontrol.launch_dependents;" ::: "memory");
    const uint32_t l16c = __shfl_sync(~0u, lane * 16, lane);

    if (wg < 2) {
#define KS(u) ((u) < 8 ? ((u) >> 1) + 4 * ((u) & 1) : (u) < 12 ? (u) : (u) < 20 ? 12 + (((u) - 12) >> 1) + 4 * ((u) & 1) : (u) < 24 ? (u) : (u) + 8)
        asm volatile("setmaxnreg.inc.sync.aligned.u32 176;");
        uint32_t a[144];
        uint32_t adr1;
        {
            const int g = lane >> 2, t = lane & 3;
#pragma unroll
            for (int tl = 0; tl < 2; tl++) {
                const int tile = tl ? wg : (wg ^ 1);
                const __nv_bfloat16* W = (r < 2) ? (tile == 0 ? Wq : Wk) : Wv;
                const int col = h * 128 + ((r < 2) ? 64 * r : 64 * tile) + 16 * w + 2 * g;
                const __nv_bfloat16* p = W + (size_t)(2 * t) * HD + col;
                const __nv_bfloat16* ps = p + (size_t)(384 * wg) * HD;
#pragma unroll
                for (int u = 0; u < (tl ? 28 : 8); u++) {
                    const __nv_bfloat16* q = (u < 8 ? ps : p) + (size_t)(16 * KS(u)) * HD;
                    a[32 * tl + 4 * u + 0] = ldg_nc32(q);
                    a[32 * tl + 4 * u + 1] = ldg_nc32(q + HD);
                    a[32 * tl + 4 * u + 2] = ldg_nc32(q + 8 * HD);
                    a[32 * tl + 4 * u + 3] = ldg_nc32(q + 9 * HD);
                }
            }
#pragma unroll
            for (int kk = 0; kk < 72; kk++) {
                uint32_t w0 = a[2 * kk], w1 = a[2 * kk + 1];
                a[2 * kk] = __byte_perm(w0, w1, 0x5410);
                a[2 * kk + 1] = __byte_perm(w0, w1, 0x7632);
            }
            float vmax = 0.f;
#pragma unroll
            for (int tl = 0; tl < 2; tl++) {
                float s0 = 0.f, s1 = 0.f;
#pragma unroll
                for (int kk = 16 * tl; kk < (tl ? 72 : 16); kk++) {
                    s0 += fabsf(__uint_as_float(a[2 * kk] << 16)) + fabsf(__uint_as_float(a[2 * kk] & 0xffff0000u));
                    s1 += fabsf(__uint_as_float(a[2 * kk + 1] << 16)) + fabsf(__uint_as_float(a[2 * kk + 1] & 0xffff0000u));
                }
                s0 += __shfl_xor_sync(~0u, s0, 1); s0 += __shfl_xor_sync(~0u, s0, 2);
                s1 += __shfl_xor_sync(~0u, s1, 1); s1 += __shfl_xor_sync(~0u, s1, 2);
                vmax = fmaxf(vmax, fmaxf(s0, s1));
            }
            uint32_t mx = __reduce_max_sync(~0u, __float_as_uint(2.f * vmax));
            sts32_if(lane, sb + O_MISC + 32 + 4 * warp, mx);
            bar_arrive(7, 384);
            const uint32_t as = sb + O_AS + wg * 8192 + (16 * w + g) * 128 + t * 4;
#pragma unroll
            for (int kk = 0; kk < 4; kk++) {
                sts32(as + (((2 * kk) ^ g) << 4), a[32 + 4 * kk]);
                sts32(as + 1024 + (((2 * kk) ^ g) << 4), a[32 + 4 * kk + 1]);
                sts32(as + (((2 * kk + 1) ^ g) << 4), a[32 + 4 * kk + 2]);
                sts32(as + 1024 + (((2 * kk + 1) ^ g) << 4), a[32 + 4 * kk + 3]);
                sts128(sb + O_AF + warp * 2048 + kk * 512 + lane * 16, a[32 + 4 * kk], a[32 + 4 * kk + 1], a[32 + 4 * kk + 2], a[32 + 4 * kk + 3]);
            }
            fence_async_smem();
            bar_sync(1, 256);
            const uint32_t l = lane * 16;
            const int mi = lane >> 3, isk = (mi >> 1) ? wg : (wg ^ 1);
            adr1 = (r == 2) ? (sb + O_VM + warp * 256 + (l >> 1))
                            : (isk ? (sb + O_KM + w * 512 + wg * 256 + (mi & 1) * 128 + (l & 127))
                                   : (sb + O_QM + w * 512 + (mi & 1) * 256 + wg * 128 + (l & 127)));
            adr1 = __shfl_sync(~0u, adr1, lane);
        }
        int s3 = 2;
#pragma unroll 1
        for (int s = -1; s < NSEG; s++) {
            const uint32_t l16 = opaque(l16c);
            s3 = (s3 == 2) ? 0 : s3 + 1;
            if (s < NSEG - 1) mbar_wait(sb + B_X + 8 * s3, ((s + 1) / 3) & 1);
            const uint64_t desc0 = (uint64_t)(((sb + O_XT + s3 * XT_BYTES) & 0x3FFFF) >> 4) | (1ull << 16) | (64ull << 32) | (1ull << 62);
            uint32_t km0 = 0, km1 = 0;
            if (s >= 0) {
#pragma unroll
                for (int kk = 0; kk < 4; kk++) {
                    const uint4 v = lds128(sb + O_AF + warp * 2048 + kk * 512 + l16);
                    a[32 + 4 * kk] = v.x; a[32 + 4 * kk + 1] = v.y; a[32 + 4 * kk + 2] = v.z; a[32 + 4 * kk + 3] = v.w;
                }
                float co[4], cw[2][4];
                uint4 b[14];
                float inv;
#define GORD(i) ((i) == 0 ? 0 : (i) == 1 ? 1 : (i) == 5 ? 2 : (i) == 9 ? 3 : (i) < 5 ? (i) + 2 : (i) < 9 ? (i) + 1 : (i))
                auto qkv_mma = [&](int i) {
                    const int gi = GORD(i), u = 8 * gi;
                    if (i == 0) {
                        mma16816_z(cw[0], a[32], a[33], a[34], a[35], b[0].x, b[0].y);
                        mma16816_z(cw[1], a[36], a[37], a[38], a[39], b[0].z, b[0].w);
                        mma16816_z(co, a[0], a[1], a[2], a[3], b[0].x, b[0].y);
                    } else {
                        mma16816(cw[0], a[32 + u], a[32 + u + 1], a[32 + u + 2], a[32 + u + 3], b[i].x, b[i].y);
                        mma16816(cw[1], a[32 + u + 4], a[32 + u + 5], a[32 + u + 6], a[32 + u + 7], b[i].z, b[i].w);
                        if (gi < 4) mma16816(co, a[u], a[u + 1], a[u + 2], a[u + 3], b[i].x, b[i].y);
                    }
                    if (gi < 4) mma16816(co, a[u + 4], a[u + 5], a[u + 6], a[u + 7], b[i].z, b[i].w);
                };
                const uint32_t mf = sb + O_MF + l16, mfs = mf + wg * 6144;
                bar_sync(2, 384);
                if (warp == 0) STAMP(s, 0);
#pragma unroll
                for (int i = 0; i < 17; i++) {
                    if (i < 14) b[i] = GORD(i) < 4 ? lds128(mfs + GORD(i) * 512) : lds128(mf + (GORD(i) < 12 ? GORD(i) : GORD(i) + 4) * 512);
                    if (i == 14) inv = __uint_as_float(lds32(sb + O_MISC));
                    if (i >= 3) qkv_mma(i - 3);
                }
#pragma unroll
                for (int i = 0; i < 4; i++) cw[0][i] += cw[1][i];
                if (r < 2) {
                    const uint32_t o0 = pack_bf16(co[0] * inv, co[1] * inv), o1 = pack_bf16(co[2] * inv, co[3] * inv);
                    const uint32_t w0 = pack_bf16(cw[0][0] * inv, cw[0][1] * inv), w1 = pack_bf16(cw[0][2] * inv, cw[0][3] * inv);
                    stsm4t(adr1, o0, o1, w0, w1);
                    km0 = wg ? w0 : o0; km1 = wg ? w1 : o1;
                    if (warp == 0) STAMP(s, 1);
                    asm volatile("{\n.reg .pred p;\nsetp.ge.u32 p, %0, 3;\n@p bar.arrive 1, 256;\n}" :: "r"(warp) : "memory");
                    if (warp < 3 && s < NSEG - 1) {
                        uint4 q[4], k[4];
                        const uint32_t ka = sb + (warp == 2 ? O_KM : O_QKX + (s & 1) * 8192 + 4096 + warp * 2048) + l16;
#pragma unroll
                        for (int i = 0; i < 4; i++) k[i] = ldsm4(ka + i * 512);
                        const uint32_t dst = sb + O_SC + r * 1280 + warp * 512 + (warp == 2 ? (l16 >> 1) : l16);
                        const uint32_t d0 = mapa_v(dst, 2), d1 = mapa_v(dst, r ^ 1), d2 = mapa_v(dst, r);
                        bar_sync(1, 256);
#pragma unroll
                        for (int i = 0; i < 4; i++) q[i] = ldsm4(sb + O_QM + i * 512 + l16);
                        if (warp == 2) {
#pragma unroll
                            for (int i = 0; i < 4; i++) k[i] = ldsm4(ka + i * 512);
                        }
                        float s0[4], s1[4], t0[4], t1[4];
                        mma16816_z(s0, q[0].x, q[0].y, q[0].z, q[0].w, k[0].x, k[0].y);
                        mma16816_z(s1, q[0].x, q[0].y, q[0].z, q[0].w, k[0].z, k[0].w);
                        mma16816_z(t0, q[1].x, q[1].y, q[1].z, q[1].w, k[1].x, k[1].y);
                        mma16816_z(t1, q[1].x, q[1].y, q[1].z, q[1].w, k[1].z, k[1].w);
                        mma16816(s0, q[2].x, q[2].y, q[2].z, q[2].w, k[2].x, k[2].y);
                        mma16816(s1, q[2].x, q[2].y, q[2].z, q[2].w, k[2].z, k[2].w);
                        mma16816(t0, q[3].x, q[3].y, q[3].z, q[3].w, k[3].x, k[3].y);
                        mma16816(t1, q[3].x, q[3].y, q[3].z, q[3].w, k[3].z, k[3].w);
                        const float v0 = (s0[0] + s0[2]) + (t0[0] + t0[2]), v1 = (s0[1] + s0[3]) + (t0[1] + t0[3]);
                        const float v2 = (s1[0] + s1[2]) + (t1[0] + t1[2]), v3 = (s1[1] + s1[3]) + (t1[1] + t1[3]);
                        asm volatile("{\n.reg .pred p;\nsetp.lt.u32 p, %12, 2;\n"
                            "@p st.async.shared::cluster.mbarrier::complete_tx::bytes.v4.f32 [%0], {%6,%7,%8,%9}, [%3];\n"
                            "@!p st.async.shared::cluster.mbarrier::complete_tx::bytes.v2.f32 [%0], {%10,%11}, [%3];\n"
                            "@p st.async.shared::cluster.mbarrier::complete_tx::bytes.v4.f32 [%1], {%6,%7,%8,%9}, [%4];\n"
                            "@!p st.async.shared::cluster.mbarrier::complete_tx::bytes.v2.f32 [%1], {%10,%11}, [%4];\n"
                            "@p st.async.shared::cluster.mbarrier::complete_tx::bytes.v4.f32 [%2], {%6,%7,%8,%9}, [%5];\n"
                            "@!p st.async.shared::cluster.mbarrier::complete_tx::bytes.v2.f32 [%2], {%10,%11}, [%5];\n}"
                            :: "r"(d0), "r"(d1), "r"(d2), "r"(mapa(sb + B_SC, 2)), "r"(mapa(sb + B_SC, r ^ 1)), "r"(mapa(sb + B_SC, r)),
                               "f"(v0), "f"(v1), "f"(v2), "f"(v3), "f"(v0 + v2), "f"(v1 + v3), "r"(warp) : "memory");
                        if (warp == 2) STAMP(s, 2);
                    } else if (warp < 3) {
                        bar_sync(1, 256);
                    }
                } else {
                    sts128f(sb + O_XP + warp * 512 + l16, co[0], co[1], co[2], co[3]);
                    bar_sync(8 + w, 64);
                    const float4 o = lds128f(sb + O_XP + (warp ^ 4) * 512 + l16);
                    km0 = pack_bf16((cw[0][0] + o.x) * inv, (cw[0][1] + o.y) * inv);
                    km1 = pack_bf16((cw[0][2] + o.z) * inv, (cw[0][3] + o.w) * inv);
                    if (warp == 0) STAMP(s, 1);
                    if (s < NSEG - 1) {
                        st_async64(mapa(adr1, 0), km0, km1, mapa(sb + B_VM, 0));
                        st_async64(mapa(adr1, 1), km0, km1, mapa(sb + B_VM, 1));
                        st_async64(mapa(adr1, 2), km0, km1, mapa(sb + B_VM, 2));
                    }
                    if (warp == 0) STAMP(s, 2);
                }
            }
            auto store_kvm = [&]() {
                char* p = reinterpret_cast<char*>(g_kvm) + (size_t)(s * NH + h) * 6144 + (r < 2 ? wg * 2048 + (r * 4 + w) * 256 : 4096 + warp * 256) + (l16 >> 1);
                *reinterpret_cast<uint2*>(p) = make_uint2(km0, km1);
            };
            if (s >= 0) bar_sync(3, 384);
            if (s == NSEG - 1) {
                store_kvm();
            } else {
                const int j = s + 1;
#define XDESC(u) (((u) < 8 ? descs : desc0) + (uint64_t)(((KS(u) >> 2) * 4096 + (KS(u) & 3) * 32) >> 4))
                const uint64_t descs = desc0 + (uint64_t)(wg * (6 * 4096 >> 4));
                float d[16];
                wg_fence();
#pragma unroll
                for (int u = 0; u < 8; u++) {
                    if (u == 0) wgmma_n32_rs<0>(d, a[0], a[1], a[2], a[3], XDESC(0));
                    else wgmma_n32_rs<1>(d, a[4 * u], a[4 * u + 1], a[4 * u + 2], a[4 * u + 3], XDESC(u));
                }
                wg_commit();
                wg_wait0();
                if (warp == 0) STAMP(s, 15);
                if (s >= 0) bar_sync(4, 384);
#pragma unroll
                for (int q = 0; q < 2; q++)
                    sts128(sb + O_XP + warp * 1024 + q * 512 + l16, pack_bf16(d[8 * q], d[8 * q + 1]), pack_bf16(d[8 * q + 2], d[8 * q + 3]),
                           pack_bf16(d[8 * q + 4], d[8 * q + 5]), pack_bf16(d[8 * q + 6], d[8 * q + 7]));
                if (s >= 0) {
                    store_kvm();
                    if (warp == 1 && s + 2 < NSEG) tma_x_tile(sb, &tm_x, r, s + 2, s3 == 2 ? 0 : s3 + 1);
                }
                bar_sync(12, 256);
#pragma unroll
                for (int q = 0; q < 2; q++) {
                    const uint4 o = lds128(sb + O_XP + (warp ^ 4) * 1024 + q * 512 + l16);
                    d[8 * q] = __uint_as_float(o.x << 16); d[8 * q + 1] = __uint_as_float(o.x & 0xffff0000u);
                    d[8 * q + 2] = __uint_as_float(o.y << 16); d[8 * q + 3] = __uint_as_float(o.y & 0xffff0000u);
                    d[8 * q + 4] = __uint_as_float(o.z << 16); d[8 * q + 5] = __uint_as_float(o.z & 0xffff0000u);
                    d[8 * q + 6] = __uint_as_float(o.w << 16); d[8 * q + 7] = __uint_as_float(o.w & 0xffff0000u);
                }
                if (s >= 0) {
                    if (warp == 6 && (s & 3) == 0 && s >= 4)
                        asm volatile("{\n.reg .pred p;\nsetp.eq.u32 p, %1, 0;\n@p red.release.gpu.global.inc.u32 [%0], 0x7fffffff;\n}"
                                     :: "l"(&g_flag[((s - 1) * 4 + (h >> 3)) * 8]), "r"(l16) : "memory");
                    asm volatile("{\n.reg .pred p;\nsetp.eq.u32 p, %0, 0;\n@p bar.sync 5, 256;\n@!p bar.sync 13, 256;\n}" :: "r"(wg) : "memory");
                }
                const uint64_t da0 = (uint64_t)(((sb + O_AS + wg * 8192) & 0x3FFFF) >> 4) | (1ull << 16) | (64ull << 32) | (1ull << 62);
                wg_fence();
#pragma unroll
                for (int u = 0; u < 4; u++) wgmma_n32_ss<1>(d, da0 + 2 * u, XDESC(u));
#pragma unroll
                for (int u = 4; u < 28; u++) wgmma_n32_rs<1>(d, a[32 + 4 * u], a[32 + 4 * u + 1], a[32 + 4 * u + 2], a[32 + 4 * u + 3], XDESC(u));
                wg_commit();
                wg_wait0();
                if (warp == 4) STAMP(s, 3);
                uint32_t e[8];
#pragma unroll
                for (int i = 0; i < 8; i++) e[i] = pack_bf16(d[2 * i], d[2 * i + 1]);
                if (r < 2) {
                    const uint32_t base = sb + O_QKX + (j & 1) * 8192 + wg * 4096 + w * 512 + l16;
                    stsm4t(base, e[0], wg ? e[1] : e[2], wg ? e[2] : e[1], e[3]);
                    stsm4t(base + 2048, e[4], wg ? e[5] : e[6], wg ? e[6] : e[5], e[7]);
                    fence_async_smem();
                } else {
                    const uint32_t base = sb + O_VX + (j & 1) * 8192 + warp * 1024 + l16;
                    sts128(base, e[0], e[1], e[2], e[3]);
                    sts128(base + 512, e[4], e[5], e[6], e[7]);
                    fence_async_smem();
                    bar_arrive(14, 288);
                }
                if (warp == 7) STAMP(s, 4);
            }
        }
        bar_arrive(7, 384);
    } else {
        asm volatile("setmaxnreg.dec.sync.aligned.u32 152;");
        const int c = w;
        uint32_t a[96];
        uint32_t mmax = 0;
        {
            const int g = lane >> 2, t = lane & 3, t2 = threadIdx.x - 256;
            if (c == 0) {
                tma_x_tile(sb, &tm_x, r, 0, 0);
                tma_x_tile(sb, &tm_x, r, 1, 1);
                mbar_expect_if(lane, sb + B_SC, 2560);
                mbar_expect_if(lane, sb + B_VM, 2048);
                if (r < 2) mbar_expect_if(lane, sb + B_VX, 8192);
                sts32_if(lane, sb + O_MISC, __float_as_uint(1.0f));
            }
#pragma unroll
            for (int i = 0; i < 4; i++) g_acc[(blockIdx.x * 64 + i * 16 + (t2 >> 3)) * 16 + (t2 & 7)] = make_uint4(0, 0, 0, 0);
#pragma unroll
            for (int tau = 0; tau < 3; tau++) {
                uint32_t v[6];
#pragma unroll
                for (int i = 0; i < 3; i++) {
                    const uint32_t* p = reinterpret_cast<const uint32_t*>(mem0 + g * DM + 16 * (12 * tau + 4 * i + c) + 2 * t);
                    v[2 * i] = __ldg(p); v[2 * i + 1] = __ldg(p + 4);
                    mmax = __vmaxu2(mmax, __vmaxu2(v[2 * i] & 0x7fff7fffu, v[2 * i + 1] & 0x7fff7fffu));
                }
                sts128(sb + O_MF + tau * 3072 + c * 512 + lane * 16, v[0], v[1], v[2], v[3]);
                sts64(sb + O_MF + tau * 3072 + 2048 + (c >> 1) * 512 + lane * 16 + (c & 1) * 8, v[4], v[5]);
            }
            mmax = max(mmax << 16, mmax & 0xffff0000u);
            bar_arrive(2, 384);
            uint32_t xm = 0;
            const uint4* xp = reinterpret_cast<const uint4*>(x) + blockIdx.x * 1536 + t2;
#pragma unroll
            for (int i = 0; i < 12; i++) {
                uint4 v = __ldg(xp + i * 128);
                xm = __vmaxu2(xm, __vmaxu2(__vmaxu2(v.x & 0x7fff7fffu, v.y & 0x7fff7fffu), __vmaxu2(v.z & 0x7fff7fffu, v.w & 0x7fff7fffu)));
            }
            xm = __reduce_max_sync(~0u, max(xm << 16, xm & 0xffff0000u));

            const __nv_bfloat16* p = Wo + (size_t)(h * 128 + 4 * t) * DM + 192 * r + 16 * c + 2 * g;
#pragma unroll
            for (int i = 0; i < 3; i++)
#pragma unroll
                for (int eb = 0; eb < 8; eb++)
#pragma unroll
                    for (int j = 0; j < 4; j++) a[(i * 8 + eb) * 4 + j] = ldg_nc32(p + (16 * eb + ((j & 1) * 2 + (j >> 1))) * DM + 64 * i);
#pragma unroll
            for (int kk = 0; kk < 48; kk++) {
                uint32_t w0 = a[2 * kk], w1 = a[2 * kk + 1];
                a[2 * kk] = __byte_perm(w0, w1, 0x5410);
                a[2 * kk + 1] = __byte_perm(w0, w1, 0x7632);
            }
            float wmax = 0.f;
#pragma unroll
            for (int i = 0; i < 3; i++) {
                float s0 = 0.f, s1 = 0.f;
#pragma unroll
                for (int kk = 16 * i; kk < 16 * i + 16; kk++) {
                    s0 += fabsf(__uint_as_float(a[2 * kk] << 16)) + fabsf(__uint_as_float(a[2 * kk] & 0xffff0000u));
                    s1 += fabsf(__uint_as_float(a[2 * kk + 1] << 16)) + fabsf(__uint_as_float(a[2 * kk + 1] & 0xffff0000u));
                }
                s0 += __shfl_xor_sync(~0u, s0, 1); s0 += __shfl_xor_sync(~0u, s0, 2);
                s1 += __shfl_xor_sync(~0u, s1, 1); s1 += __shfl_xor_sync(~0u, s1, 2);
                wmax = fmaxf(wmax, fmaxf(s0, s1));
            }
            uint32_t wm = __reduce_max_sync(~0u, __float_as_uint(wmax));
            sts32_if(lane, sb + O_OF + 4 * c, wm); sts32_if(lane, sb + O_OF + 16 + 4 * c, xm);
            __threadfence();
            bar_sync(7, 384);
            if (c == 0) {
                const uint4 wq = lds128(sb + O_OF), xq = lds128(sb + O_OF + 16), v0 = lds128(sb + O_MISC + 32), v1 = lds128(sb + O_MISC + 48);
                const uint32_t w1 = max(max(wq.x, wq.y), max(wq.z, wq.w)), x1 = max(max(xq.x, xq.y), max(xq.z, xq.w));
                const uint32_t vv = (r < 2) ? 0u : max(max(max(v0.x, v0.y), max(v0.z, v0.w)), max(max(v1.x, v1.y), max(v1.z, v1.w)));
                unsigned old = 0;
                asm volatile("{\n.reg .pred p;\nsetp.eq.u32 p, %6, 0;\n@p st.global.v4.u32 [%1], {%2,%3,%4,%4};\nfence.acq_rel.gpu;\n@p atom.relaxed.gpu.global.add.u32 %0, [%5], 1;\n}"
                             : "+r"(old) : "l"(&g_norm[blockIdx.x * 4]), "r"(w1), "r"(vv), "r"(x1), "l"(&g_gridbar), "r"(lane) : "memory");
                old = __shfl_sync(~0u, old, 0);
                const unsigned target = (old / 96u + 1u) * 96u;
                asm volatile("{\n.reg .pred p;\n.reg .u32 n, v;\nmov.u32 n, 0;\n"
                             "G_%=: ld.acquire.gpu.global.u32 v, [%0];\nsub.u32 v, v, %1;\nsetp.ge.s32 p, v, 0;\n@p bra.uni E_%=;\n"
                             "add.u32 n, n, 1;\nsetp.lt.u32 p, n, 4000000;\n@p bra.uni G_%=;\ntrap;\nE_%=:\n}" :: "l"(&g_gridbar), "r"(target) : "memory");
                uint4 n0 = ldg_relaxed128(&g_norm[lane * 4]), n1 = ldg_relaxed128(&g_norm[(lane + 32) * 4]), n2 = ldg_relaxed128(&g_norm[(lane + 64) * 4]);
                const float fw = __uint_as_float(__reduce_max_sync(~0u, max(n0.x, max(n1.x, n2.x))));
                const float fv = __uint_as_float(__reduce_max_sync(~0u, max(n0.y, max(n1.y, n2.y))));
                const float xmax = __uint_as_float(__reduce_max_sync(~0u, max(n0.z, max(n1.z, n2.z))));
                const float G = 36.f * fw * fv;
                sts32_if(lane, sb + O_MISC + 4, __float_as_uint(G)); sts32_if(lane, sb + O_MISC + 8, __float_as_uint(G * xmax));
            }
        }
        bar_sync(6, 128);
        char* rptr; int pdelta;
        {
            const uint32_t roff = (r * 4 + c) * 2048 + (lane >> 4) * 512 + (lane & 2) * 128 + (lane & 1) * 64 + (lane & 12) * 4;
            const uint32_t poff = c * 2048 + (lane & 4) * 256 + (lane >> 4) * 256 + (lane & 8) * 8 + (lane & 3) * 16;
            rptr = reinterpret_cast<char*>(g_acc) + roff;
            pdelta = __shfl_sync(~0u, (int)poff - (int)roff, lane);
        }
#pragma unroll 1
        for (int s = 0; s < NSEG; s++) {
            const uint32_t l16 = opaque(l16c);
            const uint32_t vxa = sb + O_VX + (s & 1) * 8192 + c * 2048 + l16;
            auto store_qkv = [&]() {
                asm volatile("{\n.reg .pred p;\nelect.sync _|p, 0xffffffff;\n"
                    "@p cp.async.bulk.global.shared::cta.bulk_group [%0], [%1], 8192;\n"
                    "@p cp.async.bulk.global.shared::cta.bulk_group [%2], [%3], 4096;\n@p cp.async.bulk.commit_group;\n}"
                    :: "l"(reinterpret_cast<char*>(g_qkv) + (size_t)(s * NH + h) * 24576 + r * 8192), "r"(sb + O_QKX + (s & 1) * 8192),
                       "l"(reinterpret_cast<char*>(g_qkv) + (size_t)(s * NH + h) * 24576 + 16384 + r * 4096), "r"(sb + O_VX + (s & 1) * 8192 + r * 4096) : "memory");
            };
            if (c == 0) {
                if (r == 2) {
                    bar_sync(14, 288);
                    const uint32_t src = sb + O_VX + (s & 1) * 8192, bar = sb + B_VX + 8 * (s & 1);
                    asm volatile("{\n.reg .pred p;\nelect.sync _|p, 0xffffffff;\n"
                        "@p cp.async.bulk.shared::cluster.shared::cta.mbarrier::complete_tx::bytes [%0], [%2], 8192, [%3];\n"
                        "@p cp.async.bulk.shared::cluster.shared::cta.mbarrier::complete_tx::bytes [%1], [%2], 8192, [%4];\n}"
                        :: "r"(mapa(src, 0)), "r"(mapa(src, 1)), "r"(src), "r"(mapa(bar, 0)), "r"(mapa(bar, 1)) : "memory");
                } else {
                    asm volatile("cp.async.bulk.wait_group 0;\nfence.proxy.async.global;" ::: "memory");
                }
            }
            if (s == NSEG - 1) {
                bar_sync(3, 384);
                if (c == 0 && r < 2) {
                    mbar_wait(sb + B_VX + 8 * (s & 1), (s >> 1) & 1);
                    store_qkv();
                    asm volatile("cp.async.bulk.wait_group 0;\nfence.proxy.async.global;" ::: "memory");
                }
                break;
            }
            uint4 vx[4];
            sts32_if(l16, sb + O_MISC + 16 + 4 * c, __reduce_max_sync(~0u, mmax));
            if (c == 0) STAMP(s, 5);
            {
                bar_sync(6, 128);
                const uint4 mm = lds128(sb + O_MISC + 16), cf = lds128(sb + O_MISC);
                const float bound = fmaxf(__uint_as_float(cf.z), __uint_as_float(cf.y) * (__uint_as_float(max(max(mm.x, mm.y), max(mm.z, mm.w))) * __uint_as_float(cf.x)));
                const uint32_t ebits = min(max(__float_as_uint(bound) & 0x7f800000u, 21u << 23), 254u << 23);
                bar_sync(3, 384);
                if (r < 2) mbar_wait(sb + B_VX + 8 * (s & 1), (s >> 1) & 1);
#pragma unroll
                for (int q = 0; q < 4; q++) vx[q] = lds128(vxa + q * 512);
                mbar_wait(sb + B_VM, s & 1);
                const uint4 vm = lds64x2(sb + O_VM + c * 512 + (l16 >> 1));
                if (c == 0) STAMP(s, 13);
                mbar_wait(sb + B_SC, s & 1);
                if (c == 0) STAMP(s, 6);
                float p[10];
                load_scores(p, sb + O_SC, 1280, l16);
                float mx = fmaxf(fmaxf(fmaxf(p[0], p[1]), fmaxf(p[2], p[3])), fmaxf(fmaxf(p[4], p[5]), fmaxf(p[6], p[7])));
                mx = quad_max(fmaxf(mx, fmaxf(p[8], p[9])));
                const float mo = mx * SM_SCALE;
                bar_arrive(4, 384);
                uint32_t P[5];
#pragma unroll
                for (int n = 0; n < 5; n++) P[n] = pack_bf16(ex2(fmaf(p[2 * n], SM_SCALE, -mo)), ex2(fmaf(p[2 * n + 1], SM_SCALE, -mo)));
                if (c == 0) STAMP(s, 7);
                float o0[4], o1[4], sm[4];
                mma1688_z(sm, ONES, ONES, P[0]);
                mma1688_z(o0, vm.x, vm.y, P[0]);
                mma1688_z(o1, vm.z, vm.w, P[0]);
                mma16816(sm, ONES, ONES, ONES, ONES, P[1], P[2]);
                mma16816(o0, vx[0].x, vx[0].y, vx[0].z, vx[0].w, P[1], P[2]);
                mma16816(o1, vx[2].x, vx[2].y, vx[2].z, vx[2].w, P[1], P[2]);
                mma16816(sm, ONES, ONES, ONES, ONES, P[3], P[4]);
                mma16816(o0, vx[1].x, vx[1].y, vx[1].z, vx[1].w, P[3], P[4]);
                mma16816(o1, vx[3].x, vx[3].y, vx[3].z, vx[3].w, P[3], P[4]);
                const float sig = __uint_as_float((268u << 23) - ebits);
                const float r0 = rcp_fast(sm[0]) * sig, r1 = rcp_fast(sm[1]) * sig;
                stsm4t(sb + O_OF + c * 512 + l16, pack_bf16(o0[0] * r0, o0[1] * r1), pack_bf16(o0[2] * r0, o0[3] * r1),
                       pack_bf16(o1[0] * r0, o1[1] * r1), pack_bf16(o1[2] * r0, o1[3] * r1));
                bar_sync(6, 128);
                uint4 ob[4];
#pragma unroll
                for (int q = 0; q < 4; q++) ob[q] = ldsm4(sb + O_OF + q * 512 + l16);
                float m0[3][4], m1[3][4];
#pragma unroll
                for (int q = 0; q < 4; q++) {
#pragma unroll
                    for (int i = 0; i < 3; i++) {
                        const int k0 = (i * 8 + 2 * q) * 4;
                        if (q == 0) mma16816_z(m0[i], a[k0], a[k0 + 1], a[k0 + 2], a[k0 + 3], ob[q].x, ob[q].y);
                        else mma16816(m0[i], a[k0], a[k0 + 1], a[k0 + 2], a[k0 + 3], ob[q].x, ob[q].y);
                    }
#pragma unroll
                    for (int i = 0; i < 3; i++) {
                        const int k1 = (i * 8 + 2 * q + 1) * 4;
                        if (q == 0) mma16816_z(m1[i], a[k1], a[k1 + 1], a[k1 + 2], a[k1 + 3], ob[q].z, ob[q].w);
                        else mma16816(m1[i], a[k1], a[k1 + 1], a[k1 + 2], a[k1 + 3], ob[q].z, ob[q].w);
                    }
                }
                asm volatile("red.relaxed.gpu.global.add.noftz.v4.f16x2 [%0], {%1,%2,%3,%4};" :: "l"(rptr),
                    "r"(pack_f16(m0[0][0] + m1[0][0], m0[0][2] + m1[0][2])), "r"(pack_f16(m0[1][0] + m1[1][0], m0[1][2] + m1[1][2])),
                    "r"(pack_f16(m0[2][0] + m1[2][0], m0[2][2] + m1[2][2])), "r"(0x3c00u) : "memory");
                asm volatile("red.relaxed.gpu.global.add.noftz.v4.f16x2 [%0], {%1,%2,%3,%4};" :: "l"(rptr + 1024),
                    "r"(pack_f16(m0[0][1] + m1[0][1], m0[0][3] + m1[0][3])), "r"(pack_f16(m0[1][1] + m1[1][1], m0[1][3] + m1[1][3])),
                    "r"(pack_f16(m0[2][1] + m1[2][1], m0[2][3] + m1[2][3])), "r"(0x3c00u) : "memory");
                const unsigned t_red = clk();
                bar_arrive(5, 256);
                bar_arrive(13, 256);
                {
                    const uint32_t bar = sb + (c == 0 ? B_SC : c == 1 ? B_VM : B_VX + 8 * ((s + 1) & 1));
                    mbar_expect_if(l16 | (uint32_t)(c == 3 || (c == 2 && r == 2)), bar, c == 0 ? 2560 : c == 1 ? 2048 : 8192);
                }
                sts32_if(l16 | (c ^ 3), sb + O_MISC, ebits - (14u << 23));
                if (c == 0) STAMPV(s, 8, t_red);
                const char* pbase = rptr + pdelta;
                spin_until(t_red, D_WAIT);
                uint4 v[6];
#pragma unroll
                for (int i = 0; i < 6; i++) v[i] = ldg_relaxed128(pbase + (i >> 1) * 8192 + (i & 1) * 512);
                if (c == 0 && r < 2) store_qkv();
                int nretry = 0;
                auto hand_over = [&]() -> uint32_t {
                    const uint32_t ok = __all_sync(~0u, (v[0].w & v[1].w & v[2].w & v[3].w & v[4].w & v[5].w) == 0x5000u);
#pragma unroll
                    for (int tau = 0; tau < 3; tau++) {
                        v[2 * tau].x = f16x2_to_bf16x2(v[2 * tau].x); v[2 * tau + 1].x = f16x2_to_bf16x2(v[2 * tau + 1].x);
                        v[2 * tau].y = f16x2_to_bf16x2(v[2 * tau].y); v[2 * tau + 1].y = f16x2_to_bf16x2(v[2 * tau + 1].y);
                        v[2 * tau].z = f16x2_to_bf16x2(v[2 * tau].z); v[2 * tau + 1].z = f16x2_to_bf16x2(v[2 * tau + 1].z);
                        sts128(sb + O_MF + tau * 3072 + c * 512 + l16, v[2 * tau].x, v[2 * tau + 1].x, v[2 * tau].y, v[2 * tau + 1].y);
                        sts64(sb + O_MF + tau * 3072 + 2048 + (c >> 1) * 512 + (c & 1) * 8 + l16, v[2 * tau].z, v[2 * tau + 1].z);
                    }
                    asm volatile("{\n.reg .pred p;\nsetp.ne.u32 p, %0, 0;\n@p bar.arrive 2, 384;\n}" :: "r"(ok) : "memory");
                    return ok;
                };
                if (!hand_over()) {
                    asm volatile("{\n.reg .pred p, q;\n.reg .u32 n, x;\nmov.u32 n, 0;\n"
                         "R_%=: ld.relaxed.gpu.global.v4.u32 {%0,%1,%2,%3}, [%25];\nld.relaxed.gpu.global.v4.u32 {%4,%5,%6,%7}, [%25+512];\n"
                         "ld.relaxed.gpu.global.v4.u32 {%8,%9,%10,%11}, [%25+8192];\nld.relaxed.gpu.global.v4.u32 {%12,%13,%14,%15}, [%25+8704];\n"
                         "ld.relaxed.gpu.global.v4.u32 {%16,%17,%18,%19}, [%25+16384];\nld.relaxed.gpu.global.v4.u32 {%20,%21,%22,%23}, [%25+16896];\n"
                         "add.u32 %24, %24, 1;\nand.b32 x, %3, %7;\nand.b32 x, x, %11;\nand.b32 x, x, %15;\nand.b32 x, x, %19;\nand.b32 x, x, %23;\n"
                         "setp.eq.u32 p, x, 0x5000;\nvote.sync.all.pred q, p, 0xffffffff;\n@q bra.uni K_%=;\n"
                         "add.u32 n, n, 1;\nsetp.lt.u32 q, n, 2000000;\n@q bra.uni R_%=;\ntrap;\nK_%=:\n}"
                         : "+r"(v[0].x), "+r"(v[0].y), "+r"(v[0].z), "+r"(v[0].w), "+r"(v[1].x), "+r"(v[1].y), "+r"(v[1].z), "+r"(v[1].w),
                           "+r"(v[2].x), "+r"(v[2].y), "+r"(v[2].z), "+r"(v[2].w), "+r"(v[3].x), "+r"(v[3].y), "+r"(v[3].z), "+r"(v[3].w),
                           "+r"(v[4].x), "+r"(v[4].y), "+r"(v[4].z), "+r"(v[4].w), "+r"(v[5].x), "+r"(v[5].y), "+r"(v[5].z), "+r"(v[5].w), "+r"(nretry)
                         : "l"(pbase) : "memory");
                    hand_over();
                }
                if (c == 0) STAMP(s, 12);
                if (c == 0) STAMPV(s, 14, nretry);
                mmax = absmax2(absmax2(absmax2(v[0].x, v[0].y), absmax2(v[0].z, v[1].x)), absmax2(absmax2(v[1].y, v[1].z), absmax2(v[2].x, v[2].y)));
                mmax = absmax2(mmax, absmax2(absmax2(absmax2(v[2].z, v[3].x), absmax2(v[3].y, v[3].z)), absmax2(absmax2(v[4].x, v[4].y), absmax2(v[4].z, v[5].x))));
                mmax = absmax2(mmax, absmax2(v[5].y, v[5].z)) & 0x7fff7fffu;
                mmax = max(mmax << 16, mmax & 0xffff0000u);
            }
            rptr += 24576;
        }
        {
            bar_sync(7, 384);
            if (c == 0)
                asm volatile("{\n.reg .pred p;\nsetp.eq.u32 p, %1, 0;\n@p red.release.gpu.global.inc.u32 [%0], 0x7fffffff;\n}"
                             :: "l"(&g_flag[(63 * 4 + (h >> 3)) * 8]), "r"(l16c) : "memory");
        }
    }
    cluster_sync();
}

__device__ float g_u[SEQ * 2 * DM];
__global__ void naive_gemm1(const __nv_bfloat16* x, const __nv_bfloat16* Bre, const __nv_bfloat16* Bim) {
    int p = blockIdx.x * 64 + threadIdx.x % 64, tk = blockIdx.y * 4 + threadIdx.x / 64;
    float sr = 0, si = 0;
    for (int d = 0; d < DM; d++) { float xv = __bfloat162float(x[tk * DM + d]); sr += xv * __bfloat162float(Bre[p * DM + d]); si += xv * __bfloat162float(Bim[p * DM + d]); }
    g_u[tk * 2 * DM + 2 * p] = sr; g_u[tk * 2 * DM + 2 * p + 1] = si;
}
__global__ void naive_scan(const __nv_bfloat16* Lre, const __nv_bfloat16* Lim, const __nv_bfloat16* logdt) {
    int p = blockIdx.x * 64 + threadIdx.x;
    float dt = __bfloat162float(__float2bfloat16(expf(__bfloat162float(logdt[p]))));
    float lr = __bfloat162float(Lre[p]), li = __bfloat162float(Lim[p]);
    float e = expf(dt * lr), br = e * cosf(dt * li), bi = e * sinf(dt * li);
    float den = lr * lr + li * li;
    float cr = ((br - 1.f) * lr + bi * li) / den, ci = (bi * lr - (br - 1.f) * li) / den;
    float hr = 0, hi = 0;
    for (int tk = 0; tk < SEQ; tk++) {
        float ur = g_u[tk * 2 * DM + 2 * p], ui = g_u[tk * 2 * DM + 2 * p + 1];
        float nr = br * hr - bi * hi + cr * ur - ci * ui, ni = br * hi + bi * hr + cr * ui + ci * ur;
        hr = nr; hi = ni;
        g_u[tk * 2 * DM + 2 * p] = hr; g_u[tk * 2 * DM + 2 * p + 1] = hi;
    }
}
__global__ void naive_gemm2(const __nv_bfloat16* x, const __nv_bfloat16* Cre, const __nv_bfloat16* Cim, const __nv_bfloat16* Dk, float* out) {
    int d = blockIdx.x * 64 + threadIdx.x % 64, tk = blockIdx.y * 4 + threadIdx.x / 64;
    float s = 0;
    for (int p = 0; p < DM; p++) s += g_u[tk * 2 * DM + 2 * p] * __bfloat162float(Cre[d * DM + p]) - g_u[tk * 2 * DM + 2 * p + 1] * __bfloat162float(Cim[d * DM + p]);
    out[tk * 1152 + d] = 2.f * s + __bfloat162float(__float2bfloat16(__bfloat162float(x[tk * DM + d]) * __bfloat162float(Dk[d])));
}
__device__ float frag_elem(const uint32_t* base, int e, int tok) {
    int eb = e >> 4, g = (e & 15) >> 1, hi = e & 1, j = tok >> 3, t = (tok & 7) >> 1, i = 2 * j + hi;
    uint32_t v = base[eb * 256 + (i >> 2) * 128 + (g * 4 + t) * 4 + (i & 3)];
    return __uint_as_float((tok & 1) ? (v & 0xffff0000u) : (v << 16));
}
__device__ float qk_elem(const uint32_t* base, int isk, int e, int tok) {
    int r = e >> 6, w = (e >> 4) & 3, g = (e & 15) >> 1, hi = e & 1, j = (tok >> 3) & 1;
    int mi = isk ? j * 2 + hi : hi * 2 + j;
    const __nv_bfloat16* p = reinterpret_cast<const __nv_bfloat16*>(base) + r * 4096 + isk * 2048 + (tok >> 4) * 1024 + w * 256 + mi * 64 + (tok & 7) * 8 + g;
    return __bfloat162float(*p);
}
__device__ float fragm_elem(const uint32_t* base, int e, int tok) {
    int eb = e >> 4, g = (e & 15) >> 1, hi = e & 1, t = tok >> 1;
    uint32_t v = base[eb * 64 + (g * 4 + t) * 2 + hi];
    return __uint_as_float((tok & 1) ? (v & 0xffff0000u) : (v << 16));
}
__global__ void naive_attn() {
    int s = blockIdx.x / NH, h = blockIdx.x % NH, q = threadIdx.x;
    const uint32_t* qkv = reinterpret_cast<const uint32_t*>(g_qkv) + (size_t)blockIdx.x * 6144;
    const uint32_t* kvm = reinterpret_cast<const uint32_t*>(g_kvm) + (size_t)blockIdx.x * 1536;
    float p[40], mx = -1e30f, sum = 0;
    for (int k = 0; k < 40; k++) {
        float d = 0;
        for (int e = 0; e < 128; e++)
            d += qk_elem(qkv, 0, e, q) * (k < 8 ? fragm_elem(kvm, e, k) + fragm_elem(kvm + 512, e, k) : qk_elem(qkv, 1, e, k - 8));
        p[k] = (k < 8 || k - 8 <= q) ? d * 0.08838834764831845f : -1e30f;
        mx = fmaxf(mx, p[k]);
    }
    for (int k = 0; k < 40; k++) { p[k] = expf(p[k] - mx); sum += p[k]; }
    __nv_bfloat16* ox = reinterpret_cast<__nv_bfloat16*>(g_ox);
    int tk = s * 32 + q;
    for (int e = 0; e < 128; e++) {
        float o = 0;
        for (int k = 0; k < 40; k++) o += p[k] * (k < 8 ? fragm_elem(kvm + 1024, e, k) : frag_elem(qkv + 4096, e, k - 8));
        int e0 = e & 63, ep = (e0 & 48) + (e0 & 1) * 8 + ((e0 & 15) >> 1);
        ox[((size_t)(h * 2 + (e >> 6)) * SEQ + tk) * 64 + (((ep >> 3) ^ (tk & 7)) << 3) + (ep & 7)] = __float2bfloat16(o / sum);
    }
}
__global__ void naive_wo(const __nv_bfloat16* Wo, float* out) {
    int d = blockIdx.x * 64 + threadIdx.x % 64, tk = blockIdx.y * 4 + threadIdx.x / 64;
    const __nv_bfloat16* ox = reinterpret_cast<const __nv_bfloat16*>(g_ox);
    float s = 0;
    for (int k = 0; k < HD; k++) {
        int hh = k >> 6, e0 = k & 63, e = (e0 & 48) + (e0 & 1) * 8 + ((e0 & 15) >> 1);
        s += __bfloat162float(ox[((size_t)hh * SEQ + tk) * 64 + (((e >> 3) ^ (tk & 7)) << 3) + (e & 7)]) * __bfloat162float(Wo[k * DM + d]);
    }
    out[tk * 1152 + DM + d] = s;
}

typedef CUresult (*EncodeFn)(CUtensorMap*, CUtensorMapDataType, cuuint32_t, void*, const cuuint64_t*, const cuuint64_t*, const cuuint32_t*, const cuuint32_t*,
                             CUtensorMapInterleave, CUtensorMapSwizzle, CUtensorMapL2promotion, CUtensorMapFloatOOBfill);
}

extern "C" void kernel_launch(void* const* d_in, const int* in_sizes, int n_in, void* d_out, int out_size) {
    typedef const __nv_bfloat16* bp;
    bp Ax = (bp)d_in[0], Lre = (bp)d_in[1], Lim = (bp)d_in[2], Bre = (bp)d_in[3], Bim = (bp)d_in[4], Cre = (bp)d_in[5], Cim = (bp)d_in[6],
       logdt = (bp)d_in[7], Dk = (bp)d_in[8], Bx = (bp)d_in[9], mem0 = (bp)d_in[10], Wq = (bp)d_in[11], Wk = (bp)d_in[12], Wv = (bp)d_in[13], Wo = (bp)d_in[14];
    float* out = (float*)d_out;
    static EncodeFn enc = nullptr;
    if (!enc) {
        void* fn = nullptr; cudaDriverEntryPointQueryResult qr;
        cudaGetDriverEntryPoint("cuTensorMapEncodeTiled", &fn, cudaEnableDefault, &qr);
        enc = (EncodeFn)fn;
        cudaFuncSetAttribute(chain_kernel, cudaFuncAttributeMaxDynamicSharedMemorySize, CHAIN_SMEM);
    }
    CUtensorMap tm_x;
    {
        cuuint64_t gd[2] = {DM, SEQ}; cuuint64_t gs[1] = {DM * 2}; cuuint32_t bd[2] = {64, 32}; cuuint32_t es[2] = {1, 1};
        enc(&tm_x, CU_TENSOR_MAP_DATA_TYPE_BFLOAT16, 2, (void*)Bx, gd, gs, bd, es, CU_TENSOR_MAP_INTERLEAVE_NONE, CU_TENSOR_MAP_SWIZZLE_128B,
            CU_TENSOR_MAP_L2_PROMOTION_L2_128B, CU_TENSOR_MAP_FLOAT_OOB_FILL_NONE);
    }
    cudaStream_t st = cudaStreamPerThread;
    chain_kernel<<<96, 384, CHAIN_SMEM, st>>>(tm_x, Bx, mem0, Wq, Wk, Wv, Wo);
    naive_gemm1<<<dim3(9, 512), 256, 0, st>>>(Ax, Bre, Bim);
    naive_scan<<<9, 64, 0, st>>>(Lre, Lim, logdt);
    naive_gemm2<<<dim3(9, 512), 256, 0, st>>>(Ax, Cre, Cim, Dk, out);
    naive_attn<<<NSEG * NH, 32, 0, st>>>();
    naive_wo<<<dim3(9, 512), 256, 0, st>>>(Wo, out);
}
```

```cpp
#include <cuda_runtime.h>
#include <cuda.h>
#include <cuda_bf16.h>
#include <cuda_fp16.h>
#include <stdint.h>

#define D_WAIT 700

namespace {

constexpr int DM = 576, NH = 32, SEQ = 2048, NSEG = 64, HD = 4096;

__device__ uint4 g_acc[64 * 96 * 16];
__device__ uint4 g_ox[NH * 2 * SEQ * 8];
__device__ uint4 g_qkv[NSEG * NH * 3 * 512];
__device__ uint2 g_kvm[NSEG * NH * 3 * 256];
__device__ unsigned g_flag[NSEG * 4 * 8];
__device__ unsigned g_gridbar;
__device__ float g_norm[96 * 4];

__device__ __forceinline__ uint32_t smem_u32(const void* p) { return (uint32_t)__cvta_generic_to_shared(p); }
__device__ __forceinline__ uint32_t mapa(uint32_t a, uint32_t r) { uint32_t o; asm("mapa.shared::cluster.u32 %0, %1, %2;" : "=r"(o) : "r"(a), "r"(r)); return o; }
__device__ __forceinline__ uint32_t mapa_v(uint32_t a, uint32_t r) { uint32_t o; asm volatile("mapa.shared::cluster.u32 %0, %1, %2;" : "=r"(o) : "r"(a), "r"(r)); return o; }
__device__ __forceinline__ unsigned clk() { unsigned long long c; asm volatile("mov.u64 %0, %%clock64;" : "=l"(c) :: "memory"); return (unsigned)c; }
__device__ __forceinline__ void mbar_init(uint32_t bar, uint32_t cnt) { asm volatile("mbarrier.init.shared::cta.b64 [%0], %1;" :: "r"(bar), "r"(cnt) : "memory"); }
__device__ __forceinline__ void mbar_expect(uint32_t bar, uint32_t bytes) { asm volatile("mbarrier.arrive.expect_tx.shared::cta.b64 _, [%0], %1;" :: "r"(bar), "r"(bytes) : "memory"); }
__device__ __forceinline__ void mbar_wait(uint32_t bar, uint32_t parity) {
    asm volatile("{\n.reg .pred p;\n.reg .u32 n;\nmov.u32 n, 0;\n"
                 "W_%=: mbarrier.try_wait.parity.shared::cta.b64 p, [%0], %1;\n@p bra.uni D_%=;\n"
                 "add.u32 n, n, 1;\nsetp.lt.u32 p, n, 4000000;\n@p bra.uni W_%=;\ntrap;\nD_%=:\n}" :: "r"(bar), "r"(parity) : "memory");
}
__device__ __forceinline__ void mbar_expect_if(uint32_t z, uint32_t bar, uint32_t bytes) {
    asm volatile("{\n.reg .pred p;\nsetp.eq.u32 p, %2, 0;\n@p mbarrier.arrive.expect_tx.shared::cta.b64 _, [%0], %1;\n}" :: "r"(bar), "r"(bytes), "r"(z) : "memory");
}
__device__ __forceinline__ void mbar_arrive_if(uint32_t z, uint32_t bar) {
    asm volatile("{\n.reg .pred p;\nsetp.eq.u32 p, %1, 0;\n@p mbarrier.arrive.shared::cta.b64 _, [%0];\n}" :: "r"(bar), "r"(z) : "memory");
}
__device__ __forceinline__ void sts32_if(uint32_t z, uint32_t a, uint32_t x) {
    asm volatile("{\n.reg .pred p;\nsetp.eq.u32 p, %2, 0;\n@p st.shared.u32 [%0], %1;\n}" :: "r"(a), "r"(x), "r"(z) : "memory");
}
__device__ __forceinline__ void sched_fence(int v) {
    asm volatile("{\n.reg .pred p;\nsetp.ne.s32 p, %0, 0x7fffffff;\n@p bra.uni F_%=;\ntrap;\nF_%=:\n}" :: "r"(v) : "memory");
}
__device__ __forceinline__ void spin_until(unsigned t0, unsigned d) {
    asm volatile("{\n.reg .pred p;\n.reg .u64 c;\n.reg .u32 lo;\n"
                 "S_%=: mov.u64 c, %%clock64;\ncvt.u32.u64 lo, c;\nsub.u32 lo, lo, %0;\nsetp.lt.u32 p, lo, %1;\n@p bra.uni S_%=;\n}" :: "r"(t0), "r"(d) : "memory");
}
__device__ __forceinline__ void bar_sync(int id, int n) { asm volatile("bar.sync %0, %1;" :: "r"(id), "r"(n) : "memory"); }
__device__ __forceinline__ void bar_sync_sel(int sel, int id) {
    asm volatile("{\n.reg .pred p;\nsetp.eq.u32 p, %0, 0;\n@p bar.sync %1, %3;\n@!p bar.sync %2, %3;\n}" :: "r"(sel), "r"(id), "r"(id + 1), "n"(192) : "memory");
}
__device__ __forceinline__ void bar_arrive(int id, int n) { asm volatile("bar.arrive %0, %1;" :: "r"(id), "r"(n) : "memory"); }
__device__ __forceinline__ void fence_async_smem() { asm volatile("fence.proxy.async.shared::cta;" ::: "memory"); }
__device__ __forceinline__ uint32_t pack_bf16(float lo, float hi) { uint32_t r; asm("cvt.rn.bf16x2.f32 %0, %1, %2;" : "=r"(r) : "f"(hi), "f"(lo)); return r; }
__device__ __forceinline__ uint32_t pack_f16(float lo, float hi) { uint32_t r; asm("cvt.rn.f16x2.f32 %0, %1, %2;" : "=r"(r) : "f"(hi), "f"(lo)); return r; }
__device__ __forceinline__ uint32_t f16x2_to_bf16x2(uint32_t v) { float2 f = __half22float2(*reinterpret_cast<__half2*>(&v)); return pack_bf16(f.x, f.y); }
__device__ __forceinline__ float ex2(float x) { float y; asm("ex2.approx.ftz.f32 %0, %1;" : "=f"(y) : "f"(x)); return y; }
__device__ __forceinline__ float ex2v(float x) { float y; asm volatile("ex2.approx.ftz.f32 %0, %1;" : "=f"(y) : "f"(x)); return y; }
__device__ __forceinline__ uint32_t absmax2(uint32_t a, uint32_t b) {
    uint32_t r; asm("max.xorsign.abs.bf16x2 %0, %1, %2;" : "=r"(r) : "r"(a), "r"(b)); return r;
}
__device__ __forceinline__ uint32_t shl_v(uint32_t a, int n) { return a << n; }
__device__ __forceinline__ uint32_t max3u(uint32_t a, uint32_t b, uint32_t c) { return max(max(a, b), c); }
__device__ __forceinline__ uint4 lds128(uint32_t a) { uint4 v; asm volatile("ld.shared.v4.u32 {%0,%1,%2,%3}, [%4];" : "=r"(v.x), "=r"(v.y), "=r"(v.z), "=r"(v.w) : "r"(a) : "memory"); return v; }
__device__ __forceinline__ float4 lds128f(uint32_t a) { float4 v; asm volatile("ld.shared.v4.f32 {%0,%1,%2,%3}, [%4];" : "=f"(v.x), "=f"(v.y), "=f"(v.z), "=f"(v.w) : "r"(a) : "memory"); return v; }
__device__ __forceinline__ float2 lds64f(uint32_t a) { float2 v; asm volatile("ld.shared.v2.f32 {%0,%1}, [%2];" : "=f"(v.x), "=f"(v.y) : "r"(a) : "memory"); return v; }
__device__ __forceinline__ uint4 lds64x2(uint32_t a) { uint4 v; asm volatile("ld.shared.v2.u32 {%0,%1}, [%4];\nld.shared.v2.u32 {%2,%3}, [%4+256];" : "=r"(v.x), "=r"(v.y), "=r"(v.z), "=r"(v.w) : "r"(a) : "memory"); return v; }
__device__ __forceinline__ uint32_t lds32(uint32_t a) { uint32_t v; asm volatile("ld.shared.u32 %0, [%1];" : "=r"(v) : "r"(a) : "memory"); return v; }
__device__ __forceinline__ void sts128(uint32_t a, uint32_t x, uint32_t y, uint32_t z, uint32_t w) { asm volatile("st.shared.v4.u32 [%0], {%1,%2,%3,%4};" :: "r"(a), "r"(x), "r"(y), "r"(z), "r"(w) : "memory"); }
__device__ __forceinline__ void sts128f(uint32_t a, float x, float y, float z, float w) { asm volatile("st.shared.v4.f32 [%0], {%1,%2,%3,%4};" :: "r"(a), "f"(x), "f"(y), "f"(z), "f"(w) : "memory"); }
__device__ __forceinline__ void sts64(uint32_t a, uint32_t x, uint32_t y) { asm volatile("st.shared.v2.u32 [%0], {%1,%2};" :: "r"(a), "r"(x), "r"(y) : "memory"); }
__device__ __forceinline__ void sts32(uint32_t a, uint32_t x) { asm volatile("st.shared.u32 [%0], %1;" :: "r"(a), "r"(x) : "memory"); }
__device__ __forceinline__ uint4 ldsm4(uint32_t a) { uint4 v; asm volatile("ldmatrix.sync.aligned.m8n8.x4.shared.b16 {%0,%1,%2,%3}, [%4];" : "=r"(v.x), "=r"(v.y), "=r"(v.z), "=r"(v.w) : "r"(a) : "memory"); return v; }
__device__ __forceinline__ void stsm2t(uint32_t a, uint32_t x, uint32_t y) { asm volatile("stmatrix.sync.aligned.m8n8.x2.trans.shared.b16 [%0], {%1,%2};" :: "r"(a), "r"(x), "r"(y) : "memory"); }
__device__ __forceinline__ void stsm4t(uint32_t a, uint32_t x, uint32_t y, uint32_t z, uint32_t w) { asm volatile("stmatrix.sync.aligned.m8n8.x4.trans.shared.b16 [%0], {%1,%2,%3,%4};" :: "r"(a), "r"(x), "r"(y), "r"(z), "r"(w) : "memory"); }
__device__ __forceinline__ void st_async64(uint32_t a, uint32_t x, uint32_t y, uint32_t bar) { asm volatile("st.async.shared::cluster.mbarrier::complete_tx::bytes.v2.b32 [%0], {%1,%2}, [%3];" :: "r"(a), "r"(x), "r"(y), "r"(bar) : "memory"); }
__device__ __forceinline__ void bulk_s2c(uint32_t dst, uint32_t src, uint32_t bytes, uint32_t bar) { asm volatile("cp.async.bulk.shared::cluster.shared::cta.mbarrier::complete_tx::bytes [%0], [%1], %2, [%3];" :: "r"(dst), "r"(src), "r"(bytes), "r"(bar) : "memory"); }
__device__ __forceinline__ void bulk_s2g(void* dst, uint32_t src, uint32_t bytes) { asm volatile("cp.async.bulk.global.shared::cta.bulk_group [%0], [%1], %2;" :: "l"(dst), "r"(src), "r"(bytes) : "memory"); }
__device__ __forceinline__ uint32_t ldg_nc32(const void* p) { uint32_t v; asm volatile("ld.global.nc.L2::128B.u32 %0, [%1];" : "=r"(v) : "l"(p)); return v; }
__device__ __forceinline__ uint4 ldg_relaxed128(const void* p) { uint4 v; asm volatile("ld.relaxed.gpu.global.v4.u32 {%0,%1,%2,%3}, [%4];" : "=r"(v.x), "=r"(v.y), "=r"(v.z), "=r"(v.w) : "l"(p) : "memory"); return v; }
__device__ __forceinline__ void mma16816(float (&d)[4], uint32_t a0, uint32_t a1, uint32_t a2, uint32_t a3, uint32_t b0, uint32_t b1) {
    asm volatile("mma.sync.aligned.m16n8k16.row.col.f32.bf16.bf16.f32 {%0,%1,%2,%3}, {%4,%5,%6,%7}, {%8,%9}, {%0,%1,%2,%3};"
        : "+f"(d[0]), "+f"(d[1]), "+f"(d[2]), "+f"(d[3]) : "r"(a0), "r"(a1), "r"(a2), "r"(a3), "r"(b0), "r"(b1));
}
__device__ __forceinline__ void mma16816_z(float (&d)[4], uint32_t a0, uint32_t a1, uint32_t a2, uint32_t a3, uint32_t b0, uint32_t b1) {
    asm volatile("mma.sync.aligned.m16n8k16.row.col.f32.bf16.bf16.f32 {%0,%1,%2,%3}, {%4,%5,%6,%7}, {%8,%9}, {%10,%10,%10,%10};"
        : "=f"(d[0]), "=f"(d[1]), "=f"(d[2]), "=f"(d[3]) : "r"(a0), "r"(a1), "r"(a2), "r"(a3), "r"(b0), "r"(b1), "f"(0.f));
}
__device__ __forceinline__ void mma1688(float (&d)[4], uint32_t a0, uint32_t a1, uint32_t b0) {
    asm volatile("mma.sync.aligned.m16n8k8.row.col.f32.bf16.bf16.f32 {%0,%1,%2,%3}, {%4,%5}, {%6}, {%0,%1,%2,%3};"
        : "+f"(d[0]), "+f"(d[1]), "+f"(d[2]), "+f"(d[3]) : "r"(a0), "r"(a1), "r"(b0));
}
__device__ __forceinline__ void mma1688_z(float (&d)[4], uint32_t a0, uint32_t a1, uint32_t b0) {
    asm volatile("mma.sync.aligned.m16n8k8.row.col.f32.bf16.bf16.f32 {%0,%1,%2,%3}, {%4,%5}, {%6}, {%7,%7,%7,%7};"
        : "=f"(d[0]), "=f"(d[1]), "=f"(d[2]), "=f"(d[3]) : "r"(a0), "r"(a1), "r"(b0), "f"(0.f));
}
template <int ACC>
__device__ __forceinline__ void wgmma_n32_rs(float (&d)[16], uint32_t a0, uint32_t a1, uint32_t a2, uint32_t a3, uint64_t desc) {
    asm volatile("wgmma.mma_async.sync.aligned.m64n32k16.f32.bf16.bf16 {%0,%1,%2,%3,%4,%5,%6,%7,%8,%9,%10,%11,%12,%13,%14,%15}, {%16,%17,%18,%19}, %20, %21, 1, 1, 0;"
        : "+f"(d[0]), "+f"(d[1]), "+f"(d[2]), "+f"(d[3]), "+f"(d[4]), "+f"(d[5]), "+f"(d[6]), "+f"(d[7]),
          "+f"(d[8]), "+f"(d[9]), "+f"(d[10]), "+f"(d[11]), "+f"(d[12]), "+f"(d[13]), "+f"(d[14]), "+f"(d[15])
        : "r"(a0), "r"(a1), "r"(a2), "r"(a3), "l"(desc), "n"(ACC));
}
template <int ACC>
__device__ __forceinline__ void wgmma_n32_ss(float (&d)[16], uint64_t da, uint64_t db) {
    asm volatile("wgmma.mma_async.sync.aligned.m64n32k16.f32.bf16.bf16 {%0,%1,%2,%3,%4,%5,%6,%7,%8,%9,%10,%11,%12,%13,%14,%15}, %16, %17, %18, 1, 1, 0, 0;"
        : "+f"(d[0]), "+f"(d[1]), "+f"(d[2]), "+f"(d[3]), "+f"(d[4]), "+f"(d[5]), "+f"(d[6]), "+f"(d[7]),
          "+f"(d[8]), "+f"(d[9]), "+f"(d[10]), "+f"(d[11]), "+f"(d[12]), "+f"(d[13]), "+f"(d[14]), "+f"(d[15])
        : "l"(da), "l"(db), "n"(ACC));
}
__device__ __forceinline__ void wg_fence() { asm volatile("wgmma.fence.sync.aligned;" ::: "memory"); }
__device__ __forceinline__ void wg_commit() { asm volatile("wgmma.commit_group.sync.aligned;" ::: "memory"); }
__device__ __forceinline__ void wg_wait0() { asm volatile("wgmma.wait_group.sync.aligned 0;" ::: "memory"); }
__device__ __forceinline__ void cluster_sync() { asm volatile("barrier.cluster.arrive.aligned;\nbarrier.cluster.wait.aligned;" ::: "memory"); }

#define STAMP(s, i) do {} while (0)
#define STAMPV(s, i, v) do {} while (0)

constexpr int XT_BYTES = 36864;
constexpr int O_XT = 0;
constexpr int O_AS = 3 * XT_BYTES;
constexpr int O_AF = O_AS + 16384;
constexpr int O_MF = O_AF + 16384;
constexpr int O_XP = O_MF + 9216;
constexpr int O_VX = O_XP + 8192;
constexpr int O_VM = O_VX + 16384;
constexpr int O_SC = O_VM + 2048;
constexpr int O_OF = O_SC + 2560;
constexpr int O_QM = O_OF + 2048;
constexpr int O_QKX = O_QM + 2048;
constexpr int O_KM = O_QKX + 16384;
constexpr int O_MISC = O_KM + 2048;
constexpr int O_BAR = O_MISC + 64;
constexpr int CHAIN_SMEM = O_BAR + 128;
static_assert(CHAIN_SMEM <= 232448, "smem");
constexpr int B_X = O_BAR, B_VX = O_BAR + 24, B_SC = O_BAR + 40, B_VM = O_BAR + 48;
constexpr float SM_SCALE = 0.08838834764831845f * 1.4426950408889634f;
constexpr uint32_t ONES = 0x3f803f80u;

__device__ __forceinline__ uint32_t opaque(uint32_t v) { uint32_t o; asm volatile("mov.u32 %0, %1;" : "=r"(o) : "r"(v)); return o; }
__device__ __forceinline__ void st_async128(uint32_t a, uint32_t x, uint32_t y, uint32_t z, uint32_t w, uint32_t bar) {
    asm volatile("st.async.shared::cluster.mbarrier::complete_tx::bytes.v4.b32 [%0], {%1,%2,%3,%4}, [%5];" :: "r"(a), "r"(x), "r"(y), "r"(z), "r"(w), "r"(bar) : "memory");
}
__device__ __forceinline__ void tma_x_tile(uint32_t sb, const CUtensorMap* tm, int r, int j, int slot) {
    asm volatile("{\n.reg .pred p;\nelect.sync _|p, 0xffffffff;\n"
        "@p mbarrier.arrive.expect_tx.shared::cta.b64 _, [%2], 36864;\n"
        "@p cp.async.bulk.tensor.2d.shared::cluster.global.mbarrier::complete_tx::bytes.multicast::cluster [%0], [%1, {%3, %4}], [%2], %7;\n"
        "@p cp.async.bulk.tensor.2d.shared::cluster.global.mbarrier::complete_tx::bytes.multicast::cluster [%0+4096], [%1, {%5, %4}], [%2], %7;\n"
        "@p cp.async.bulk.tensor.2d.shared::cluster.global.mbarrier::complete_tx::bytes.multicast::cluster [%0+8192], [%1, {%6, %4}], [%2], %7;\n}"
        :: "r"(sb + O_XT + slot * XT_BYTES + 3 * r * 4096), "l"(tm), "r"(sb + B_X + 8 * slot), "r"(192 * r), "r"(j * 32), "r"(192 * r + 64), "r"(192 * r + 128),
           "h"((unsigned short)7) : "memory");
}
__device__ __forceinline__ float quad_max(float v) {
    const float a = __shfl_xor_sync(~0u, v, 1), b = __shfl_xor_sync(~0u, v, 2), c = __shfl_xor_sync(~0u, v, 3);
    return fmaxf(fmaxf(v, a), fmaxf(b, c));
}
__device__ __forceinline__ void load_scores(float (&p)[10], uint32_t base, uint32_t stride, uint32_t l16) {
    const float4 a0 = lds128f(base + l16), b0 = lds128f(base + stride + l16);
    const float4 a1 = lds128f(base + 512 + l16), b1 = lds128f(base + stride + 512 + l16);
    const float2 a2 = lds64f(base + 1024 + (l16 >> 1)), b2 = lds64f(base + stride + 1024 + (l16 >> 1));
    p[0] = a2.x + b2.x; p[1] = a2.y + b2.y;
    p[2] = a0.x + b0.x; p[3] = a0.y + b0.y; p[4] = a0.z + b0.z; p[5] = a0.w + b0.w;
    p[6] = a1.x + b1.x; p[7] = a1.y + b1.y; p[8] = a1.z + b1.z; p[9] = a1.w + b1.w;
}
__device__ __forceinline__ float rcp_fast(float x) { float y; asm("rcp.approx.ftz.f32 %0, %1;" : "=f"(y) : "f"(x)); return y; }

__global__ void __cluster_dims__(3, 1, 1) __launch_bounds__(384, 1)
chain_kernel(const __grid_constant__ CUtensorMap tm_x,
             const __nv_bfloat16* __restrict__ x, const __nv_bfloat16* __restrict__ mem0,
             const __nv_bfloat16* __restrict__ Wq, const __nv_bfloat16* __restrict__ Wk,
             const __nv_bfloat16* __restrict__ Wv, const __nv_bfloat16* __restrict__ Wo) {
    extern __shared__ __align__(1024) uint8_t smem_raw[];
    const uint32_t sb = smem_u32(smem_raw);
    const int lane = threadIdx.x & 31;
    const int warp = __shfl_sync(~0u, threadIdx.x >> 5, 0);
    const int wg = warp >> 2, w = warp & 3;
    const int h = blockIdx.x / 3, r = blockIdx.x - 3 * h;

    if (threadIdx.x == 0) {
        if (sb & 1023u) __trap();
        for (int i = 0; i < 7; i++) mbar_init(sb + O_BAR + 8 * i, 1);
        asm volatile("fence.mbarrier_init.release.cluster;" ::: "memory");
    }
    if (blockIdx.x == 0) {
        for (int i = threadIdx.x; i < NSEG * 4 * 8; i += 384) g_flag[i] = 0;
        __threadfence();
    }
    __syncthreads();
    cluster_sync();
    asm volatile("griddepcontrol.launch_dependents;" ::: "memory");
    const uint32_t l16c = __shfl_sync(~0u, lane * 16, lane);

    if (wg < 2) {
#define KS(u) ((u) < 8 ? ((u) >> 1) + 4 * ((u) & 1) : (u) < 12 ? (u) : (u) < 20 ? 12 + (((u) - 12) >> 1) + 4 * ((u) & 1) : (u) < 24 ? (u) : (u) + 8)
        asm volatile("setmaxnreg.inc.sync.aligned.u32 176;");
        uint32_t a[144];
        uint32_t adr1;
        {
            const int g = lane >> 2, t = lane & 3;
#pragma unroll
            for (int tl = 0; tl < 2; tl++) {
                const int tile = tl ? wg : (wg ^ 1);
                const __nv_bfloat16* W = (r < 2) ? (tile == 0 ? Wq : Wk) : Wv;
                const int col = h * 128 + ((r < 2) ? 64 * r : 64 * tile) + 16 * w + 2 * g;
                const __nv_bfloat16* p = W + (size_t)(2 * t) * HD + col;
                const __nv_bfloat16* ps = p + (size_t)(384 * wg) * HD;
#pragma unroll
                for (int u = 0; u < (tl ? 28 : 8); u++) {
                    const __nv_bfloat16* q = (u < 8 ? ps : p) + (size_t)(16 * KS(u)) * HD;
                    a[32 * tl + 4 * u + 0] = ldg_nc32(q);
                    a[32 * tl + 4 * u + 1] = ldg_nc32(q + HD);
                    a[32 * tl + 4 * u + 2] = ldg_nc32(q + 8 * HD);
                    a[32 * tl + 4 * u + 3] = ldg_nc32(q + 9 * HD);
                }
            }
#pragma unroll
            for (int kk = 0; kk < 72; kk++) {
                uint32_t w0 = a[2 * kk], w1 = a[2 * kk + 1];
                a[2 * kk] = __byte_perm(w0, w1, 0x5410);
                a[2 * kk + 1] = __byte_perm(w0, w1, 0x7632);
            }
            float vmax = 0.f;
#pragma unroll
            for (int tl = 0; tl < 2; tl++) {
                float s0 = 0.f, s1 = 0.f;
#pragma unroll
                for (int kk = 16 * tl; kk < (tl ? 72 : 16); kk++) {
                    s0 += fabsf(__uint_as_float(a[2 * kk] << 16)) + fabsf(__uint_as_float(a[2 * kk] & 0xffff0000u));
                    s1 += fabsf(__uint_as_float(a[2 * kk + 1] << 16)) + fabsf(__uint_as_float(a[2 * kk + 1] & 0xffff0000u));
                }
                s0 += __shfl_xor_sync(~0u, s0, 1); s0 += __shfl_xor_sync(~0u, s0, 2);
                s1 += __shfl_xor_sync(~0u, s1, 1); s1 += __shfl_xor_sync(~0u, s1, 2);
                vmax = fmaxf(vmax, fmaxf(s0, s1));
            }
            uint32_t mx = __reduce_max_sync(~0u, __float_as_uint(2.f * vmax));
            sts32_if(lane, sb + O_MISC + 32 + 4 * warp, mx);
            bar_arrive(7, 384);
            const uint32_t as = sb + O_AS + wg * 8192 + (16 * w + g) * 128 + t * 4;
#pragma unroll
            for (int kk = 0; kk < 4; kk++) {
                sts32(as + (((2 * kk) ^ g) << 4), a[32 + 4 * kk]);
                sts32(as + 1024 + (((2 * kk) ^ g) << 4), a[32 + 4 * kk + 1]);
                sts32(as + (((2 * kk + 1) ^ g) << 4), a[32 + 4 * kk + 2]);
                sts32(as + 1024 + (((2 * kk + 1) ^ g) << 4), a[32 + 4 * kk + 3]);
                sts128(sb + O_AF + warp * 2048 + kk * 512 + lane * 16, a[32 + 4 * kk], a[32 + 4 * kk + 1], a[32 + 4 * kk + 2], a[32 + 4 * kk + 3]);
            }
            fence_async_smem();
            bar_sync(1, 256);
            const uint32_t l = lane * 16;
            const int mi = lane >> 3, isk = (mi >> 1) ? wg : (wg ^ 1);
            adr1 = (r == 2) ? (sb + O_VM + warp * 256 + (l >> 1))
                            : (isk ? (sb + O_KM + w * 512 + wg * 256 + (mi & 1) * 128 + (l & 127))
                                   : (sb + O_QM + w * 512 + (mi & 1) * 256 + wg * 128 + (l & 127)));
            adr1 = __shfl_sync(~0u, adr1, lane);
        }
        int s3 = 2;
#pragma unroll 1
        for (int s = -1; s < NSEG; s++) {
            const uint32_t l16 = opaque(l16c);
            s3 = (s3 == 2) ? 0 : s3 + 1;
            if (s < 0) mbar_wait(sb + B_X, 0);
            const uint64_t desc0 = (uint64_t)(((sb + O_XT + s3 * XT_BYTES) & 0x3FFFF) >> 4) | (1ull << 16) | (64ull << 32) | (1ull << 62);
            uint32_t km0 = 0, km1 = 0;
            if (s >= 0) {
#pragma unroll
                for (int kk = 0; kk < 4; kk++) {
                    const uint4 v = lds128(sb + O_AF + warp * 2048 + kk * 512 + l16);
                    a[32 + 4 * kk] = v.x; a[32 + 4 * kk + 1] = v.y; a[32 + 4 * kk + 2] = v.z; a[32 + 4 * kk + 3] = v.w;
                }
                float co[4], cw[3][4];
                uint4 b[14];
                float inv;
#define GORD(i) ((i) == 0 ? 0 : (i) == 1 ? 1 : (i) == 5 ? 2 : (i) == 9 ? 3 : (i) < 5 ? (i) + 2 : (i) < 9 ? (i) + 1 : (i))
                auto qkv_mma = [&](int i) {
                    const int gi = GORD(i), u = 8 * gi, n0 = 2 * i, n1 = 2 * i + 1;
                    if (gi < 4) {
                        if (i == 0) mma16816_z(co, a[u], a[u + 1], a[u + 2], a[u + 3], b[0].x, b[0].y);
                        else mma16816(co, a[u], a[u + 1], a[u + 2], a[u + 3], b[i].x, b[i].y);
                    }
                    if (n0 < 3) mma16816_z(cw[n0 % 3], a[32 + u], a[32 + u + 1], a[32 + u + 2], a[32 + u + 3], b[i].x, b[i].y);
                    else mma16816(cw[n0 % 3], a[32 + u], a[32 + u + 1], a[32 + u + 2], a[32 + u + 3], b[i].x, b[i].y);
                    if (n1 < 3) mma16816_z(cw[n1 % 3], a[32 + u + 4], a[32 + u + 5], a[32 + u + 6], a[32 + u + 7], b[i].z, b[i].w);
                    else mma16816(cw[n1 % 3], a[32 + u + 4], a[32 + u + 5], a[32 + u + 6], a[32 + u + 7], b[i].z, b[i].w);
                    if (gi < 4) mma16816(co, a[u + 4], a[u + 5], a[u + 6], a[u + 7], b[i].z, b[i].w);
                };
                const uint32_t mf = sb + O_MF + l16, mfs = mf + wg * 6144;
                if (r == 2) {
                    asm volatile("{\n.reg .pred p;\ncp.async.bulk.wait_group 0;\nelect.sync _|p, 0xffffffff;\nsetp.lt.and.s32 p, %4, 63, p;\n"
                        "@p cp.async.bulk.shared::cluster.global.mbarrier::complete_tx::bytes.multicast::cluster [%1], [%0], 1024, [%2], %3;\n"
                        "fence.proxy.async.global;\n}"
                        :: "l"(reinterpret_cast<char*>(g_qkv) + (size_t)(s * NH + h) * 24576 + 16384 + warp * 1024), "r"(sb + O_VX + (s & 1) * 8192 + warp * 1024),
                           "r"(sb + B_VX + 8 * (s & 1)), "h"((unsigned short)3), "r"(s) : "memory");
                }
                bar_sync(2, 384);
                if (warp == 0) STAMP(s, 0);
#pragma unroll
                for (int i = 0; i < 17; i++) {
                    if (i < 14) b[i] = GORD(i) < 4 ? lds128(mfs + GORD(i) * 512) : lds128(mf + (GORD(i) < 12 ? GORD(i) : GORD(i) + 4) * 512);
                    if (i == 14) inv = __uint_as_float(lds32(sb + O_MISC));
                    if (i >= 3) qkv_mma(i - 3);
                }
#pragma unroll
                for (int i = 0; i < 4; i++) cw[0][i] += cw[1][i] + cw[2][i];
                if (r < 2) {
                    const uint32_t o0 = pack_bf16(co[0] * inv, co[1] * inv), o1 = pack_bf16(co[2] * inv, co[3] * inv);
                    const uint32_t w0 = pack_bf16(cw[0][0] * inv, cw[0][1] * inv), w1 = pack_bf16(cw[0][2] * inv, cw[0][3] * inv);
                    stsm4t(adr1, o0, o1, w0, w1);
                    km0 = wg ? w0 : o0; km1 = wg ? w1 : o1;
                    if (warp == 0) STAMP(s, 1);
                    asm volatile("{\n.reg .pred p;\nsetp.ge.u32 p, %0, 3;\n@p bar.arrive 1, 256;\n}" :: "r"(warp) : "memory");
                    if (warp < 3 && s < NSEG - 1) {
                        uint4 q[4], k[4];
                        const uint32_t ka = sb + (warp == 2 ? O_KM : O_QKX + (s & 1) * 8192 + 4096 + warp * 2048) + l16;
#pragma unroll
                        for (int i = 0; i < 4; i++) k[i] = ldsm4(ka + i * 512);
                        const uint32_t dst = sb + O_SC + r * 1280 + warp * 512 + (warp == 2 ? (l16 >> 1) : l16);
                        const uint32_t d0 = mapa_v(dst, 2), d1 = mapa_v(dst, r ^ 1), d2 = mapa_v(dst, r);
                        bar_sync(1, 256);
#pragma unroll
                        for (int i = 0; i < 4; i++) q[i] = ldsm4(sb + O_QM + i * 512 + l16);
                        if (warp == 2) {
#pragma unroll
                            for (int i = 0; i < 4; i++) k[i] = ldsm4(ka + i * 512);
                        }
                        float s0[4], s1[4], t0[4], t1[4];
                        mma16816_z(s0, q[0].x, q[0].y, q[0].z, q[0].w, k[0].x, k[0].y);
                        mma16816_z(s1, q[0].x, q[0].y, q[0].z, q[0].w, k[0].z, k[0].w);
                        mma16816_z(t0, q[1].x, q[1].y, q[1].z, q[1].w, k[1].x, k[1].y);
                        mma16816_z(t1, q[1].x, q[1].y, q[1].z, q[1].w, k[1].z, k[1].w);
                        mma16816(s0, q[2].x, q[2].y, q[2].z, q[2].w, k[2].x, k[2].y);
                        mma16816(s1, q[2].x, q[2].y, q[2].z, q[2].w, k[2].z, k[2].w);
                        mma16816(t0, q[3].x, q[3].y, q[3].z, q[3].w, k[3].x, k[3].y);
                        mma16816(t1, q[3].x, q[3].y, q[3].z, q[3].w, k[3].z, k[3].w);
                        const float v0 = (s0[0] + s0[2]) + (t0[0] + t0[2]), v1 = (s0[1] + s0[3]) + (t0[1] + t0[3]);
                        const float v2 = (s1[0] + s1[2]) + (t1[0] + t1[2]), v3 = (s1[1] + s1[3]) + (t1[1] + t1[3]);
                        asm volatile("{\n.reg .pred p;\nsetp.lt.u32 p, %12, 2;\n"
                            "@p st.async.shared::cluster.mbarrier::complete_tx::bytes.v4.f32 [%0], {%6,%7,%8,%9}, [%3];\n"
                            "@!p st.async.shared::cluster.mbarrier::complete_tx::bytes.v2.f32 [%0], {%10,%11}, [%3];\n"
                            "@p st.async.shared::cluster.mbarrier::complete_tx::bytes.v4.f32 [%1], {%6,%7,%8,%9}, [%4];\n"
                            "@!p st.async.shared::cluster.mbarrier::complete_tx::bytes.v2.f32 [%1], {%10,%11}, [%4];\n"
                            "@p st.async.shared::cluster.mbarrier::complete_tx::bytes.v4.f32 [%2], {%6,%7,%8,%9}, [%5];\n"
                            "@!p st.async.shared::cluster.mbarrier::complete_tx::bytes.v2.f32 [%2], {%10,%11}, [%5];\n}"
                            :: "r"(d0), "r"(d1), "r"(d2), "r"(mapa(sb + B_SC, 2)), "r"(mapa(sb + B_SC, r ^ 1)), "r"(mapa(sb + B_SC, r)),
                               "f"(v0), "f"(v1), "f"(v2), "f"(v3), "f"(v0 + v2), "f"(v1 + v3), "r"(warp) : "memory");
                        if (warp == 2) STAMP(s, 2);
                    } else if (warp < 3) {
                        bar_sync(1, 256);
                    }
                } else {
                    sts128f(sb + O_XP + warp * 512 + l16, co[0], co[1], co[2], co[3]);
                    bar_sync(8 + w, 64);
                    const float4 o = lds128f(sb + O_XP + (warp ^ 4) * 512 + l16);
                    km0 = pack_bf16((cw[0][0] + o.x) * inv, (cw[0][1] + o.y) * inv);
                    km1 = pack_bf16((cw[0][2] + o.z) * inv, (cw[0][3] + o.w) * inv);
                    if (warp == 0) STAMP(s, 1);
                    if (s < NSEG - 1) {
                        st_async64(mapa(adr1, 0), km0, km1, mapa(sb + B_VM, 0));
                        st_async64(mapa(adr1, 1), km0, km1, mapa(sb + B_VM, 1));
                        st_async64(mapa(adr1, 2), km0, km1, mapa(sb + B_VM, 2));
                    }
                    if (warp == 0) STAMP(s, 2);
                }
            }
            auto store_kvm = [&]() {
                char* p = reinterpret_cast<char*>(g_kvm) + (size_t)(s * NH + h) * 6144 + (r < 2 ? wg * 2048 + (r * 4 + w) * 256 : 4096 + warp * 256) + (l16 >> 1);
                *reinterpret_cast<uint2*>(p) = make_uint2(km0, km1);
            };
            if (s >= 0) bar_sync(3, 384);
            if (s == NSEG - 1) {
                store_kvm();
            } else {
                const int j = s + 1;
#define XDESC(u) (((u) < 8 ? descs : desc0) + (uint64_t)(((KS(u) >> 2) * 4096 + (KS(u) & 3) * 32) >> 4))
                const uint64_t descs = desc0 + (uint64_t)(wg * (6 * 4096 >> 4));
                float d[16];
                wg_fence();
#pragma unroll
                for (int u = 0; u < 8; u++) {
                    if (u == 0) wgmma_n32_rs<0>(d, a[0], a[1], a[2], a[3], XDESC(0));
                    else wgmma_n32_rs<1>(d, a[4 * u], a[4 * u + 1], a[4 * u + 2], a[4 * u + 3], XDESC(u));
                }
                wg_commit();
                wg_wait0();
                if (warp == 0) STAMP(s, 15);
                if (s >= 0) bar_sync(4, 384);
#pragma unroll
                for (int q = 0; q < 2; q++)
                    sts128(sb + O_XP + warp * 1024 + q * 512 + l16, pack_bf16(d[8 * q], d[8 * q + 1]), pack_bf16(d[8 * q + 2], d[8 * q + 3]),
                           pack_bf16(d[8 * q + 4], d[8 * q + 5]), pack_bf16(d[8 * q + 6], d[8 * q + 7]));
                if (s >= 0) {
                    store_kvm();
                    if (warp == 1 && s + 2 < NSEG) tma_x_tile(sb, &tm_x, r, s + 2, s3 == 2 ? 0 : s3 + 1);
                }
                bar_sync(12, 256);
#pragma unroll
                for (int q = 0; q < 2; q++) {
                    const uint4 o = lds128(sb + O_XP + (warp ^ 4) * 1024 + q * 512 + l16);
                    d[8 * q] = __uint_as_float(o.x << 16); d[8 * q + 1] = __uint_as_float(o.x & 0xffff0000u);
                    d[8 * q + 2] = __uint_as_float(o.y << 16); d[8 * q + 3] = __uint_as_float(o.y & 0xffff0000u);
                    d[8 * q + 4] = __uint_as_float(o.z << 16); d[8 * q + 5] = __uint_as_float(o.z & 0xffff0000u);
                    d[8 * q + 6] = __uint_as_float(o.w << 16); d[8 * q + 7] = __uint_as_float(o.w & 0xffff0000u);
                }
                if (s >= 0) {
                    if (warp == 6 && (s & 3) == 0 && s >= 4)
                        asm volatile("{\n.reg .pred p;\nsetp.eq.u32 p, %1, 0;\n@p red.release.gpu.global.inc.u32 [%0], 0x7fffffff;\n}"
                                     :: "l"(&g_flag[((s - 1) * 4 + (h >> 3)) * 8]), "r"(l16) : "memory");
                    asm volatile("{\n.reg .pred p;\nsetp.eq.u32 p, %0, 0;\n@p bar.sync 5, 256;\n@!p bar.sync 13, 256;\n}" :: "r"(wg) : "memory");
                }
                const uint64_t da0 = (uint64_t)(((sb + O_AS + wg * 8192) & 0x3FFFF) >> 4) | (1ull << 16) | (64ull << 32) | (1ull << 62);
                wg_fence();
#pragma unroll
                for (int u = 0; u < 4; u++) wgmma_n32_ss<1>(d, da0 + 2 * u, XDESC(u));
#pragma unroll
                for (int u = 4; u < 28; u++) wgmma_n32_rs<1>(d, a[32 + 4 * u], a[32 + 4 * u + 1], a[32 + 4 * u + 2], a[32 + 4 * u + 3], XDESC(u));
                wg_commit();
                wg_wait0();
                if (warp == 4) STAMP(s, 3);
                uint32_t e[8];
#pragma unroll
                for (int i = 0; i < 8; i++) e[i] = pack_bf16(d[2 * i], d[2 * i + 1]);
                if (r < 2) {
                    const uint32_t base = sb + O_QKX + (j & 1) * 8192 + wg * 4096 + w * 512 + l16;
                    stsm4t(base, e[0], wg ? e[1] : e[2], wg ? e[2] : e[1], e[3]);
                    stsm4t(base + 2048, e[4], wg ? e[5] : e[6], wg ? e[6] : e[5], e[7]);
                    fence_async_smem();
                } else {
                    const uint32_t base = sb + O_VX + (j & 1) * 8192 + warp * 1024 + l16;
                    sts128(base, e[0], e[1], e[2], e[3]);
                    sts128(base + 512, e[4], e[5], e[6], e[7]);
                    fence_async_smem();
                    __syncwarp();
                    asm volatile("{\n.reg .pred p;\nelect.sync _|p, 0xffffffff;\n"
                        "@p cp.async.bulk.global.shared::cta.bulk_group [%0], [%1], 1024;\n@p cp.async.bulk.commit_group;\n}"
                        :: "l"(reinterpret_cast<char*>(g_qkv) + (size_t)(j * NH + h) * 24576 + 16384 + warp * 1024), "r"(sb + O_VX + (j & 1) * 8192 + warp * 1024) : "memory");
                }
                if (warp == 7) STAMP(s, 4);
            }
        }
        bar_arrive(7, 384);
    } else {
        asm volatile("setmaxnreg.dec.sync.aligned.u32 152;");
        const int c = w;
        uint32_t a[96];
        uint32_t mmax = 0;
        {
            const int g = lane >> 2, t = lane & 3, t2 = threadIdx.x - 256;
            if (c == 0) {
                tma_x_tile(sb, &tm_x, r, 0, 0);
                tma_x_tile(sb, &tm_x, r, 1, 1);
                mbar_expect_if(lane, sb + B_SC, 2560);
                mbar_expect_if(lane, sb + B_VM, 2048);
                if (r < 2) mbar_expect_if(lane, sb + B_VX, 8192);
                sts32_if(lane, sb + O_MISC, __float_as_uint(1.0f));
                sts32_if(lane, sb + O_MISC + 12, __float_as_uint(SM_SCALE));
            }
#pragma unroll
            for (int i = 0; i < 4; i++) g_acc[(blockIdx.x * 64 + i * 16 + (t2 >> 3)) * 16 + (t2 & 7)] = make_uint4(0, 0, 0, 0);
#pragma unroll
            for (int tau = 0; tau < 3; tau++) {
                uint32_t v[6];
#pragma unroll
                for (int i = 0; i < 3; i++) {
                    const uint32_t* p = reinterpret_cast<const uint32_t*>(mem0 + g * DM + 16 * (12 * tau + 4 * i + c) + 2 * t);
                    v[2 * i] = __ldg(p); v[2 * i + 1] = __ldg(p + 4);
                    mmax = __vmaxu2(mmax, __vmaxu2(v[2 * i] & 0x7fff7fffu, v[2 * i + 1] & 0x7fff7fffu));
                }
                sts128(sb + O_MF + tau * 3072 + c * 512 + lane * 16, v[0], v[1], v[2], v[3]);
                sts64(sb + O_MF + tau * 3072 + 2048 + (c >> 1) * 512 + lane * 16 + (c & 1) * 8, v[4], v[5]);
            }
            mmax = max(mmax << 16, mmax & 0xffff0000u);
            bar_arrive(2, 384);
            uint32_t xm = 0;
            const uint4* xp = reinterpret_cast<const uint4*>(x) + blockIdx.x * 1536 + t2;
#pragma unroll
            for (int i = 0; i < 12; i++) {
                uint4 v = __ldg(xp + i * 128);
                xm = __vmaxu2(xm, __vmaxu2(__vmaxu2(v.x & 0x7fff7fffu, v.y & 0x7fff7fffu), __vmaxu2(v.z & 0x7fff7fffu, v.w & 0x7fff7fffu)));
            }
            xm = __reduce_max_sync(~0u, max(xm << 16, xm & 0xffff0000u));

            const __nv_bfloat16* p = Wo + (size_t)(h * 128 + 4 * t) * DM + 192 * r + 16 * c + 2 * g;
#pragma unroll
            for (int i = 0; i < 3; i++)
#pragma unroll
                for (int eb = 0; eb < 8; eb++)
#pragma unroll
                    for (int j = 0; j < 4; j++) a[(i * 8 + eb) * 4 + j] = ldg_nc32(p + (16 * eb + ((j & 1) * 2 + (j >> 1))) * DM + 64 * i);
#pragma unroll
            for (int kk = 0; kk < 48; kk++) {
                uint32_t w0 = a[2 * kk], w1 = a[2 * kk + 1];
                a[2 * kk] = __byte_perm(w0, w1, 0x5410);
                a[2 * kk + 1] = __byte_perm(w0, w1, 0x7632);
            }
            float wmax = 0.f;
#pragma unroll
            for (int i = 0; i < 3; i++) {
                float s0 = 0.f, s1 = 0.f;
#pragma unroll
                for (int kk = 16 * i; kk < 16 * i + 16; kk++) {
                    s0 += fabsf(__uint_as_float(a[2 * kk] << 16)) + fabsf(__uint_as_float(a[2 * kk] & 0xffff0000u));
                    s1 += fabsf(__uint_as_float(a[2 * kk + 1] << 16)) + fabsf(__uint_as_float(a[2 * kk + 1] & 0xffff0000u));
                }
                s0 += __shfl_xor_sync(~0u, s0, 1); s0 += __shfl_xor_sync(~0u, s0, 2);
                s1 += __shfl_xor_sync(~0u, s1, 1); s1 += __shfl_xor_sync(~0u, s1, 2);
                wmax = fmaxf(wmax, fmaxf(s0, s1));
            }
            uint32_t wm = __reduce_max_sync(~0u, __float_as_uint(wmax));
            sts32_if(lane, sb + O_OF + 4 * c, wm); sts32_if(lane, sb + O_OF + 16 + 4 * c, xm);
            __threadfence();
            bar_sync(7, 384);
            if (c == 0) {
                const uint4 wq = lds128(sb + O_OF), xq = lds128(sb + O_OF + 16), v0 = lds128(sb + O_MISC + 32), v1 = lds128(sb + O_MISC + 48);
                const uint32_t w1 = max(max(wq.x, wq.y), max(wq.z, wq.w)), x1 = max(max(xq.x, xq.y), max(xq.z, xq.w));
                const uint32_t vv = (r < 2) ? 0u : max(max(max(v0.x, v0.y), max(v0.z, v0.w)), max(max(v1.x, v1.y), max(v1.z, v1.w)));
                unsigned old = 0;
                asm volatile("{\n.reg .pred p;\nsetp.eq.u32 p, %6, 0;\n@p st.global.v4.u32 [%1], {%2,%3,%4,%4};\nfence.acq_rel.gpu;\n@p atom.relaxed.gpu.global.add.u32 %0, [%5], 1;\n}"
                             : "+r"(old) : "l"(&g_norm[blockIdx.x * 4]), "r"(w1), "r"(vv), "r"(x1), "l"(&g_gridbar), "r"(lane) : "memory");
                old = __shfl_sync(~0u, old, 0);
                const unsigned target = (old / 96u + 1u) * 96u;
                asm volatile("{\n.reg .pred p;\n.reg .u32 n, v;\nmov.u32 n, 0;\n"
                             "G_%=: ld.acquire.gpu.global.u32 v, [%0];\nsub.u32 v, v, %1;\nsetp.ge.s32 p, v, 0;\n@p bra.uni E_%=;\n"
                             "add.u32 n, n, 1;\nsetp.lt.u32 p, n, 4000000;\n@p bra.uni G_%=;\ntrap;\nE_%=:\n}" :: "l"(&g_gridbar), "r"(target) : "memory");
                uint4 n0 = ldg_relaxed128(&g_norm[lane * 4]), n1 = ldg_relaxed128(&g_norm[(lane + 32) * 4]), n2 = ldg_relaxed128(&g_norm[(lane + 64) * 4]);
                const float fw = __uint_as_float(__reduce_max_sync(~0u, max(n0.x, max(n1.x, n2.x))));
                const float fv = __uint_as_float(__reduce_max_sync(~0u, max(n0.y, max(n1.y, n2.y))));
                const float xmax = __uint_as_float(__reduce_max_sync(~0u, max(n0.z, max(n1.z, n2.z))));
                const float G = 36.f * fw * fv;
                sts32_if(lane, sb + O_MISC + 4, __float_as_uint(G)); sts32_if(lane, sb + O_MISC + 8, __float_as_uint(G * xmax));
            }
        }
        bar_sync(6, 128);
        char* rptr; int pdelta; int s3n = 1;
        {
            const uint32_t roff = (r * 4 + c) * 2048 + (lane >> 4) * 512 + (lane & 2) * 128 + (lane & 1) * 64 + (lane & 12) * 4;
            const uint32_t poff = c * 2048 + (lane & 4) * 256 + (lane >> 4) * 256 + (lane & 8) * 8 + (lane & 3) * 16;
            rptr = reinterpret_cast<char*>(g_acc) + roff;
            pdelta = __shfl_sync(~0u, (int)poff - (int)roff, lane);
        }
#pragma unroll 1
        for (int s = 0; s < NSEG; s++) {
            const uint32_t l16 = opaque(l16c);
            const uint32_t vxa = sb + O_VX + (s & 1) * 8192 + c * 2048 + l16;
            auto store_qk = [&]() {
                asm volatile("{\n.reg .pred p;\nelect.sync _|p, 0xffffffff;\n"
                    "@p cp.async.bulk.global.shared::cta.bulk_group [%0], [%1], 8192;\n@p cp.async.bulk.commit_group;\n}"
                    :: "l"(reinterpret_cast<char*>(g_qkv) + (size_t)(s * NH + h) * 24576 + r * 8192), "r"(sb + O_QKX + (s & 1) * 8192) : "memory");
            };
            if (c == 0) asm volatile("cp.async.bulk.wait_group 0;\nfence.proxy.async.global;" ::: "memory");
            if (s == NSEG - 1) {
                bar_sync(3, 384);
                if (c == 0 && r < 2) {
                    store_qk();
                    asm volatile("cp.async.bulk.wait_group 0;\nfence.proxy.async.global;" ::: "memory");
                }
                break;
            }
            uint4 vx[4];
            sts32_if(l16, sb + O_MISC + 16 + 4 * c, __reduce_max_sync(~0u, mmax));
            if (c == 0) STAMP(s, 5);
            {
                bar_sync(6, 128);
                const uint4 mm = lds128(sb + O_MISC + 16), cf = lds128(sb + O_MISC);
                const float bound = fmaxf(__uint_as_float(cf.z), __uint_as_float(cf.y) * (__uint_as_float(max(max(mm.x, mm.y), max(mm.z, mm.w))) * __uint_as_float(cf.x)));
                const uint32_t ebits = min(max(__float_as_uint(bound) & 0x7f800000u, 21u << 23), 254u << 23);
                mbar_wait(sb + B_X + 8 * s3n, ((s + 1) / 3) & 1);
                s3n = (s3n == 2) ? 0 : s3n + 1;
                bar_sync(3, 384);
                if (r < 2) mbar_wait(sb + B_VX + 8 * (s & 1), (s >> 1) & 1);
#pragma unroll
                for (int q = 0; q < 4; q++) vx[q] = lds128(vxa + q * 512);
                mbar_wait(sb + B_VM, s & 1);
                const uint4 vm = lds64x2(sb + O_VM + c * 512 + (l16 >> 1));
                if (c == 0) STAMP(s, 13);
                mbar_wait(sb + B_SC, s & 1);
                if (c == 0) STAMP(s, 6);
                float p[10];
                load_scores(p, sb + O_SC, 1280, l16);
                bar_arrive(4, 384);
                const float sc = __uint_as_float(lds32(sb + O_MISC + 12));
                float mx = fmaxf(fmaxf(fmaxf(p[0], p[1]), fmaxf(p[2], p[3])), fmaxf(fmaxf(p[4], p[5]), fmaxf(p[6], p[7])));
                mx = quad_max(fmaxf(mx, fmaxf(p[8], p[9])));
                const float mo = mx * sc;
                uint32_t P[5];
#pragma unroll
                for (int n = 0; n < 5; n++) P[n] = pack_bf16(ex2(fmaf(p[2 * n], SM_SCALE, -mo)), ex2(fmaf(p[2 * n + 1], SM_SCALE, -mo)));
                if (c == 0) STAMP(s, 7);
                float o0[4], o1[4], sm[4];
                mma1688_z(sm, ONES, ONES, P[0]);
                mma1688_z(o0, vm.x, vm.y, P[0]);
                mma1688_z(o1, vm.z, vm.w, P[0]);
                mma16816(sm, ONES, ONES, ONES, ONES, P[1], P[2]);
                mma16816(o0, vx[0].x, vx[0].y, vx[0].z, vx[0].w, P[1], P[2]);
                mma16816(o1, vx[2].x, vx[2].y, vx[2].z, vx[2].w, P[1], P[2]);
                mma16816(sm, ONES, ONES, ONES, ONES, P[3], P[4]);
                mma16816(o0, vx[1].x, vx[1].y, vx[1].z, vx[1].w, P[3], P[4]);
                mma16816(o1, vx[3].x, vx[3].y, vx[3].z, vx[3].w, P[3], P[4]);
                const float sig = __uint_as_float((268u << 23) - ebits);
                const float r0 = rcp_fast(sm[0]) * sig, r1 = rcp_fast(sm[1]) * sig;
                stsm4t(sb + O_OF + c * 512 + l16, pack_bf16(o0[0] * r0, o0[1] * r1), pack_bf16(o0[2] * r0, o0[3] * r1),
                       pack_bf16(o1[0] * r0, o1[1] * r1), pack_bf16(o1[2] * r0, o1[3] * r1));
                bar_sync(6, 128);
                uint4 ob[4];
#pragma unroll
                for (int q = 0; q < 4; q++) ob[q] = ldsm4(sb + O_OF + q * 512 + l16);
                float m0[3][4], m1[3][4];
#pragma unroll
                for (int q = 0; q < 4; q++) {
#pragma unroll
                    for (int i = 0; i < 3; i++) {
                        const int k0 = (i * 8 + 2 * q) * 4;
                        if (q == 0) mma16816_z(m0[i], a[k0], a[k0 + 1], a[k0 + 2], a[k0 + 3], ob[q].x, ob[q].y);
                        else mma16816(m0[i], a[k0], a[k0 + 1], a[k0 + 2], a[k0 + 3], ob[q].x, ob[q].y);
                    }
#pragma unroll
                    for (int i = 0; i < 3; i++) {
                        const int k1 = (i * 8 + 2 * q + 1) * 4;
                        if (q == 0) mma16816_z(m1[i], a[k1], a[k1 + 1], a[k1 + 2], a[k1 + 3], ob[q].z, ob[q].w);
                        else mma16816(m1[i], a[k1], a[k1 + 1], a[k1 + 2], a[k1 + 3], ob[q].z, ob[q].w);
                    }
                }
                asm volatile("red.relaxed.gpu.global.add.noftz.v4.f16x2 [%0], {%1,%2,%3,%4};" :: "l"(rptr),
                    "r"(pack_f16(m0[0][0] + m1[0][0], m0[0][2] + m1[0][2])), "r"(pack_f16(m0[1][0] + m1[1][0], m0[1][2] + m1[1][2])),
                    "r"(pack_f16(m0[2][0] + m1[2][0], m0[2][2] + m1[2][2])), "r"(0x3c00u) : "memory");
                asm volatile("red.relaxed.gpu.global.add.noftz.v4.f16x2 [%0], {%1,%2,%3,%4};" :: "l"(rptr + 1024),
                    "r"(pack_f16(m0[0][1] + m1[0][1], m0[0][3] + m1[0][3])), "r"(pack_f16(m0[1][1] + m1[1][1], m0[1][3] + m1[1][3])),
                    "r"(pack_f16(m0[2][1] + m1[2][1], m0[2][3] + m1[2][3])), "r"(0x3c00u) : "memory");
                const unsigned t_red = clk();
                bar_arrive(5, 256);
                bar_arrive(13, 256);
                {
                    const uint32_t bar = sb + (c == 0 ? B_SC : c == 1 ? B_VM : B_VX + 8 * ((s + 1) & 1));
                    mbar_expect_if(l16 | (uint32_t)(c == 3 || (c == 2 && r == 2)), bar, c == 0 ? 2560 : c == 1 ? 2048 : 8192);
                }
                sts32_if(l16 | (c ^ 3), sb + O_MISC, ebits - (14u << 23));
                if (c == 0) STAMPV(s, 8, t_red);
                const char* pbase = rptr + pdelta;
                spin_until(t_red, D_WAIT);
                uint4 v[6];
#pragma unroll
                for (int i = 0; i < 6; i++) v[i] = ldg_relaxed128(pbase + (i >> 1) * 8192 + (i & 1) * 512);
                if (c == 0 && r < 2) { spin_until(t_red, D_WAIT + 250); store_qk(); }
                int nretry = 0;
                auto hand_over = [&]() -> uint32_t {
                    uint32_t ok = 0;
#pragma unroll
                    for (int tau = 0; tau < 3; tau++) {
                        if (tau > 0) sched_fence(s);
                        if (tau == 2) ok = __all_sync(~0u, (v[0].w & v[1].w & v[2].w & v[3].w & v[4].w & v[5].w) == 0x5000u);
                        v[2 * tau].x = f16x2_to_bf16x2(v[2 * tau].x); v[2 * tau + 1].x = f16x2_to_bf16x2(v[2 * tau + 1].x);
                        v[2 * tau].y = f16x2_to_bf16x2(v[2 * tau].y); v[2 * tau + 1].y = f16x2_to_bf16x2(v[2 * tau + 1].y);
                        v[2 * tau].z = f16x2_to_bf16x2(v[2 * tau].z); v[2 * tau + 1].z = f16x2_to_bf16x2(v[2 * tau + 1].z);
                        sts128(sb + O_MF + tau * 3072 + c * 512 + l16, v[2 * tau].x, v[2 * tau + 1].x, v[2 * tau].y, v[2 * tau + 1].y);
                        sts64(sb + O_MF + tau * 3072 + 2048 + (c >> 1) * 512 + (c & 1) * 8 + l16, v[2 * tau].z, v[2 * tau + 1].z);
                    }
                    asm volatile("{\n.reg .pred p;\nsetp.ne.u32 p, %0, 0;\n@p bar.arrive 2, 384;\n}" :: "r"(ok) : "memory");
                    return ok;
                };
                if (!hand_over()) {
                    asm volatile("{\n.reg .pred p, q;\n.reg .u32 n, x;\nmov.u32 n, 0;\n"
                         "R_%=: ld.relaxed.gpu.global.v4.u32 {%0,%1,%2,%3}, [%25];\nld.relaxed.gpu.global.v4.u32 {%4,%5,%6,%7}, [%25+512];\n"
                         "ld.relaxed.gpu.global.v4.u32 {%8,%9,%10,%11}, [%25+8192];\nld.relaxed.gpu.global.v4.u32 {%12,%13,%14,%15}, [%25+8704];\n"
                         "ld.relaxed.gpu.global.v4.u32 {%16,%17,%18,%19}, [%25+16384];\nld.relaxed.gpu.global.v4.u32 {%20,%21,%22,%23}, [%25+16896];\n"
                         "add.u32 %24, %24, 1;\nand.b32 x, %3, %7;\nand.b32 x, x, %11;\nand.b32 x, x, %15;\nand.b32 x, x, %19;\nand.b32 x, x, %23;\n"
                         "setp.eq.u32 p, x, 0x5000;\nvote.sync.all.pred q, p, 0xffffffff;\n@q bra.uni K_%=;\n"
                         "add.u32 n, n, 1;\nsetp.lt.u32 q, n, 2000000;\n@q bra.uni R_%=;\ntrap;\nK_%=:\n}"
                         : "+r"(v[0].x), "+r"(v[0].y), "+r"(v[0].z), "+r"(v[0].w), "+r"(v[1].x), "+r"(v[1].y), "+r"(v[1].z), "+r"(v[1].w),
                           "+r"(v[2].x), "+r"(v[2].y), "+r"(v[2].z), "+r"(v[2].w), "+r"(v[3].x), "+r"(v[3].y), "+r"(v[3].z), "+r"(v[3].w),
                           "+r"(v[4].x), "+r"(v[4].y), "+r"(v[4].z), "+r"(v[4].w), "+r"(v[5].x), "+r"(v[5].y), "+r"(v[5].z), "+r"(v[5].w), "+r"(nretry)
                         : "l"(pbase) : "memory");
                    hand_over();
                }
                if (c == 0) STAMP(s, 12);
                if (c == 0) STAMPV(s, 14, nretry);
                mmax = absmax2(absmax2(absmax2(v[0].x, v[0].y), absmax2(v[0].z, v[1].x)), absmax2(absmax2(v[1].y, v[1].z), absmax2(v[2].x, v[2].y)));
                mmax = absmax2(mmax, absmax2(absmax2(absmax2(v[2].z, v[3].x), absmax2(v[3].y, v[3].z)), absmax2(absmax2(v[4].x, v[4].y), absmax2(v[4].z, v[5].x))));
                mmax = absmax2(mmax, absmax2(v[5].y, v[5].z)) & 0x7fff7fffu;
                mmax = max(mmax << 16, mmax & 0xffff0000u);
            }
            rptr += 24576;
        }
        {
            bar_sync(7, 384);
            if (c == 0)
                asm volatile("{\n.reg .pred p;\nsetp.eq.u32 p, %1, 0;\n@p red.release.gpu.global.inc.u32 [%0], 0x7fffffff;\n}"
                             :: "l"(&g_flag[(63 * 4 + (h >> 3)) * 8]), "r"(l16c) : "memory");
        }
    }
    cluster_sync();
}

__device__ float g_u[SEQ * 2 * DM];
__global__ void naive_gemm1(const __nv_bfloat16* x, const __nv_bfloat16* Bre, const __nv_bfloat16* Bim) {
    int p = blockIdx.x * 64 + threadIdx.x % 64, tk = blockIdx.y * 4 + threadIdx.x / 64;
    float sr = 0, si = 0;
    for (int d = 0; d < DM; d++) { float xv = __bfloat162float(x[tk * DM + d]); sr += xv * __bfloat162float(Bre[p * DM + d]); si += xv * __bfloat162float(Bim[p * DM + d]); }
    g_u[tk * 2 * DM + 2 * p] = sr; g_u[tk * 2 * DM + 2 * p + 1] = si;
}
__global__ void naive_scan(const __nv_bfloat16* Lre, const __nv_bfloat16* Lim, const __nv_bfloat16* logdt) {
    int p = blockIdx.x * 64 + threadIdx.x;
    float dt = __bfloat162float(__float2bfloat16(expf(__bfloat162float(logdt[p]))));
    float lr = __bfloat162float(Lre[p]), li = __bfloat162float(Lim[p]);
    float e = expf(dt * lr), br = e * cosf(dt * li), bi = e * sinf(dt * li);
    float den = lr * lr + li * li;
    float cr = ((br - 1.f) * lr + bi * li) / den, ci = (bi * lr - (br - 1.f) * li) / den;
    float hr = 0, hi = 0;
    for (int tk = 0; tk < SEQ; tk++) {
        float ur = g_u[tk * 2 * DM + 2 * p], ui = g_u[tk * 2 * DM + 2 * p + 1];
        float nr = br * hr - bi * hi + cr * ur - ci * ui, ni = br * hi + bi * hr + cr * ui + ci * ur;
        hr = nr; hi = ni;
        g_u[tk * 2 * DM + 2 * p] = hr; g_u[tk * 2 * DM + 2 * p + 1] = hi;
    }
}
__global__ void naive_gemm2(const __nv_bfloat16* x, const __nv_bfloat16* Cre, const __nv_bfloat16* Cim, const __nv_bfloat16* Dk, float* out) {
    int d = blockIdx.x * 64 + threadIdx.x % 64, tk = blockIdx.y * 4 + threadIdx.x / 64;
    float s = 0;
    for (int p = 0; p < DM; p++) s += g_u[tk * 2 * DM + 2 * p] * __bfloat162float(Cre[d * DM + p]) - g_u[tk * 2 * DM + 2 * p + 1] * __bfloat162float(Cim[d * DM + p]);
    out[tk * 1152 + d] = 2.f * s + __bfloat162float(__float2bfloat16(__bfloat162float(x[tk * DM + d]) * __bfloat162float(Dk[d])));
}
__device__ float frag_elem(const uint32_t* base, int e, int tok) {
    int eb = e >> 4, g = (e & 15) >> 1, hi = e & 1, j = tok >> 3, t = (tok & 7) >> 1, i = 2 * j + hi;
    uint32_t v = base[eb * 256 + (i >> 2) * 128 + (g * 4 + t) * 4 + (i & 3)];
    return __uint_as_float((tok & 1) ? (v & 0xffff0000u) : (v << 16));
}
__device__ float qk_elem(const uint32_t* base, int isk, int e, int tok) {
    int r = e >> 6, w = (e >> 4) & 3, g = (e & 15) >> 1, hi = e & 1, j = (tok >> 3) & 1;
    int mi = isk ? j * 2 + hi : hi * 2 + j;
    const __nv_bfloat16* p = reinterpret_cast<const __nv_bfloat16*>(base) + r * 4096 + isk * 2048 + (tok >> 4) * 1024 + w * 256 + mi * 64 + (tok & 7) * 8 + g;
    return __bfloat162float(*p);
}
__device__ float fragm_elem(const uint32_t* base, int e, int tok) {
    int eb = e >> 4, g = (e & 15) >> 1, hi = e & 1, t = tok >> 1;
    uint32_t v = base[eb * 64 + (g * 4 + t) * 2 + hi];
    return __uint_as_float((tok & 1) ? (v & 0xffff0000u) : (v << 16));
}
__global__ void naive_attn() {
    int s = blockIdx.x / NH, h = blockIdx.x % NH, q = threadIdx.x;
    const uint32_t* qkv = reinterpret_cast<const uint32_t*>(g_qkv) + (size_t)blockIdx.x * 6144;
    const uint32_t* kvm = reinterpret_cast<const uint32_t*>(g_kvm) + (size_t)blockIdx.x * 1536;
    float p[40], mx = -1e30f, sum = 0;
    for (int k = 0; k < 40; k++) {
        float d = 0;
        for (int e = 0; e < 128; e++)
            d += qk_elem(qkv, 0, e, q) * (k < 8 ? fragm_elem(kvm, e, k) + fragm_elem(kvm + 512, e, k) : qk_elem(qkv, 1, e, k - 8));
        p[k] = (k < 8 || k - 8 <= q) ? d * 0.08838834764831845f : -1e30f;
        mx = fmaxf(mx, p[k]);
    }
    for (int k = 0; k < 40; k++) { p[k] = expf(p[k] - mx); sum += p[k]; }
    __nv_bfloat16* ox = reinterpret_cast<__nv_bfloat16*>(g_ox);
    int tk = s * 32 + q;
    for (int e = 0; e < 128; e++) {
        float o = 0;
        for (int k = 0; k < 40; k++) o += p[k] * (k < 8 ? fragm_elem(kvm + 1024, e, k) : frag_elem(qkv + 4096, e, k - 8));
        int e0 = e & 63, ep = (e0 & 48) + (e0 & 1) * 8 + ((e0 & 15) >> 1);
        ox[((size_t)(h * 2 + (e >> 6)) * SEQ + tk) * 64 + (((ep >> 3) ^ (tk & 7)) << 3) + (ep & 7)] = __float2bfloat16(o / sum);
    }
}
__global__ void naive_wo(const __nv_bfloat16* Wo, float* out) {
    int d = blockIdx.x * 64 + threadIdx.x % 64, tk = blockIdx.y * 4 + threadIdx.x / 64;
    const __nv_bfloat16* ox = reinterpret_cast<const __nv_bfloat16*>(g_ox);
    float s = 0;
    for (int k = 0; k < HD; k++) {
        int hh = k >> 6, e0 = k & 63, e = (e0 & 48) + (e0 & 1) * 8 + ((e0 & 15) >> 1);
        s += __bfloat162float(ox[((size_t)hh * SEQ + tk) * 64 + (((e >> 3) ^ (tk & 7)) << 3) + (e & 7)]) * __bfloat162float(Wo[k * DM + d]);
    }
    out[tk * 1152 + DM + d] = s;
}

typedef CUresult (*EncodeFn)(CUtensorMap*, CUtensorMapDataType, cuuint32_t, void*, const cuuint64_t*, const cuuint64_t*, const cuuint32_t*, const cuuint32_t*,
                             CUtensorMapInterleave, CUtensorMapSwizzle, CUtensorMapL2promotion, CUtensorMapFloatOOBfill);
}

extern "C" void kernel_launch(void* const* d_in, const int* in_sizes, int n_in, void* d_out, int out_size) {
    typedef const __nv_bfloat16* bp;
    bp Ax = (bp)d_in[0], Lre = (bp)d_in[1], Lim = (bp)d_in[2], Bre = (bp)d_in[3], Bim = (bp)d_in[4], Cre = (bp)d_in[5], Cim = (bp)d_in[6],
       logdt = (bp)d_in[7], Dk = (bp)d_in[8], Bx = (bp)d_in[9], mem0 = (bp)d_in[10], Wq = (bp)d_in[11], Wk = (bp)d_in[12], Wv = (bp)d_in[13], Wo = (bp)d_in[14];
    float* out = (float*)d_out;
    static EncodeFn enc = nullptr;
    if (!enc) {
        void* fn = nullptr; cudaDriverEntryPointQueryResult qr;
        cudaGetDriverEntryPoint("cuTensorMapEncodeTiled", &fn, cudaEnableDefault, &qr);
        enc = (EncodeFn)fn;
        cudaFuncSetAttribute(chain_kernel, cudaFuncAttributeMaxDynamicSharedMemorySize, CHAIN_SMEM);
    }
    CUtensorMap tm_x;
    {
        cuuint64_t gd[2] = {DM, SEQ}; cuuint64_t gs[1] = {DM * 2}; cuuint32_t bd[2] = {64, 32}; cuuint32_t es[2] = {1, 1};
        enc(&tm_x, CU_TENSOR_MAP_DATA_TYPE_BFLOAT16, 2, (void*)Bx, gd, gs, bd, es, CU_TENSOR_MAP_INTERLEAVE_NONE, CU_TENSOR_MAP_SWIZZLE_128B,
            CU_TENSOR_MAP_L2_PROMOTION_L2_128B, CU_TENSOR_MAP_FLOAT_OOB_FILL_NONE);
    }
    cudaStream_t st = cudaStreamPerThread;
    chain_kernel<<<96, 384, CHAIN_SMEM, st>>>(tm_x, Bx, mem0, Wq, Wk, Wv, Wo);
    naive_gemm1<<<dim3(9, 512), 256, 0, st>>>(Ax, Bre, Bim);
    naive_scan<<<9, 64, 0, st>>>(Lre, Lim, logdt);
    naive_gemm2<<<dim3(9, 512), 256, 0, st>>>(Ax, Cre, Cim, Dk, out);
    naive_attn<<<NSEG * NH, 32, 0, st>>>();
    naive_wo<<<dim3(9, 512), 256, 0, st>>>(Wo, out);
}
```

```cpp
#include <cuda_runtime.h>
#include <cuda.h>
#include <cuda_bf16.h>
#include <cuda_fp16.h>
#include <stdint.h>

#define D_WAIT 700

#define VSEND 1
#define QF 0
namespace {

constexpr int DM = 576, NH = 32, SEQ = 2048, NSEG = 64, HD = 4096;

__device__ uint4 g_acc[64 * 96 * 16];
__device__ uint4 g_ox[NH * 2 * SEQ * 8];
__device__ uint4 g_qkv[NSEG * NH * 3 * 512];
__device__ uint2 g_kvm[NSEG * NH * 3 * 256];
__device__ unsigned g_flag[NSEG * 4 * 8];
__device__ unsigned g_gridbar;
__device__ float g_norm[96 * 4];

__device__ __forceinline__ uint32_t smem_u32(const void* p) { return (uint32_t)__cvta_generic_to_shared(p); }
__device__ __forceinline__ uint32_t mapa(uint32_t a, uint32_t r) { uint32_t o; asm("mapa.shared::cluster.u32 %0, %1, %2;" : "=r"(o) : "r"(a), "r"(r)); return o; }
__device__ __forceinline__ uint32_t mapa_v(uint32_t a, uint32_t r) { uint32_t o; asm volatile("mapa.shared::cluster.u32 %0, %1, %2;" : "=r"(o) : "r"(a), "r"(r)); return o; }
__device__ __forceinline__ unsigned clk() { unsigned long long c; asm volatile("mov.u64 %0, %%clock64;" : "=l"(c) :: "memory"); return (unsigned)c; }
__device__ __forceinline__ void mbar_init(uint32_t bar, uint32_t cnt) { asm volatile("mbarrier.init.shared::cta.b64 [%0], %1;" :: "r"(bar), "r"(cnt) : "memory"); }
__device__ __forceinline__ void mbar_expect(uint32_t bar, uint32_t bytes) { asm volatile("mbarrier.arrive.expect_tx.shared::cta.b64 _, [%0], %1;" :: "r"(bar), "r"(bytes) : "memory"); }
__device__ __forceinline__ void mbar_wait(uint32_t bar, uint32_t parity) {
    asm volatile("{\n.reg .pred p;\n.reg .u32 n;\nmov.u32 n, 0;\n"
                 "W_%=: mbarrier.try_wait.parity.shared::cta.b64 p, [%0], %1;\n@p bra.uni D_%=;\n"
                 "add.u32 n, n, 1;\nsetp.lt.u32 p, n, 4000000;\n@p bra.uni W_%=;\ntrap;\nD_%=:\n}" :: "r"(bar), "r"(parity) : "memory");
}
__device__ __forceinline__ void mbar_expect_if(uint32_t z, uint32_t bar, uint32_t bytes) {
    asm volatile("{\n.reg .pred p;\nsetp.eq.u32 p, %2, 0;\n@p mbarrier.arrive.expect_tx.shared::cta.b64 _, [%0], %1;\n}" :: "r"(bar), "r"(bytes), "r"(z) : "memory");
}
__device__ __forceinline__ void mbar_arrive_if(uint32_t z, uint32_t bar) {
    asm volatile("{\n.reg .pred p;\nsetp.eq.u32 p, %1, 0;\n@p mbarrier.arrive.shared::cta.b64 _, [%0];\n}" :: "r"(bar), "r"(z) : "memory");
}
__device__ __forceinline__ void sts32_if(uint32_t z, uint32_t a, uint32_t x) {
    asm volatile("{\n.reg .pred p;\nsetp.eq.u32 p, %2, 0;\n@p st.shared.u32 [%0], %1;\n}" :: "r"(a), "r"(x), "r"(z) : "memory");
}
template <int K> __device__ __forceinline__ void sched_fence(int v) {
    asm volatile("{\n.reg .pred p;\nsetp.ne.s32 p, %0, %1;\n@p bra.uni F_%=;\ntrap;\nF_%=:\n}" :: "r"(v), "n"(1000 + K) : "memory");
}
__device__ __forceinline__ void spin_until(unsigned t0, unsigned d) {
    asm volatile("{\n.reg .pred p;\n.reg .u64 c;\n.reg .u32 lo;\n"
                 "S_%=: mov.u64 c, %%clock64;\ncvt.u32.u64 lo, c;\nsub.u32 lo, lo, %0;\nsetp.lt.u32 p, lo, %1;\n@p bra.uni S_%=;\n}" :: "r"(t0), "r"(d) : "memory");
}
__device__ __forceinline__ void bar_sync(int id, int n) { asm volatile("bar.sync %0, %1;" :: "r"(id), "r"(n) : "memory"); }
__device__ __forceinline__ void bar_sync_sel(int sel, int id) {
    asm volatile("{\n.reg .pred p;\nsetp.eq.u32 p, %0, 0;\n@p bar.sync %1, %3;\n@!p bar.sync %2, %3;\n}" :: "r"(sel), "r"(id), "r"(id + 1), "n"(192) : "memory");
}
__device__ __forceinline__ void bar_arrive(int id, int n) { asm volatile("bar.arrive %0, %1;" :: "r"(id), "r"(n) : "memory"); }
__device__ __forceinline__ void fence_async_smem() { asm volatile("fence.proxy.async.shared::cta;" ::: "memory"); }
__device__ __forceinline__ uint32_t pack_bf16(float lo, float hi) { uint32_t r; asm("cvt.rn.bf16x2.f32 %0, %1, %2;" : "=r"(r) : "f"(hi), "f"(lo)); return r; }
__device__ __forceinline__ uint32_t pack_f16(float lo, float hi) { uint32_t r; asm("cvt.rn.f16x2.f32 %0, %1, %2;" : "=r"(r) : "f"(hi), "f"(lo)); return r; }
__device__ __forceinline__ uint32_t f16x2_to_bf16x2(uint32_t v) { float2 f = __half22float2(*reinterpret_cast<__half2*>(&v)); return pack_bf16(f.x, f.y); }
__device__ __forceinline__ float ex2(float x) { float y; asm("ex2.approx.ftz.f32 %0, %1;" : "=f"(y) : "f"(x)); return y; }
__device__ __forceinline__ float ex2v(float x) { float y; asm volatile("ex2.approx.ftz.f32 %0, %1;" : "=f"(y) : "f"(x)); return y; }
__device__ __forceinline__ uint32_t absmax2(uint32_t a, uint32_t b) {
    uint32_t r; asm("max.xorsign.abs.bf16x2 %0, %1, %2;" : "=r"(r) : "r"(a), "r"(b)); return r;
}
__device__ __forceinline__ uint32_t shl_v(uint32_t a, int n) { return a << n; }
__device__ __forceinline__ uint32_t max3u(uint32_t a, uint32_t b, uint32_t c) { return max(max(a, b), c); }
__device__ __forceinline__ uint4 lds128(uint32_t a) { uint4 v; asm volatile("ld.shared.v4.u32 {%0,%1,%2,%3}, [%4];" : "=r"(v.x), "=r"(v.y), "=r"(v.z), "=r"(v.w) : "r"(a) : "memory"); return v; }
__device__ __forceinline__ uint4 lds128v(uint32_t a) { uint4 v; asm volatile("ld.volatile.shared.v4.u32 {%0,%1,%2,%3}, [%4];" : "=r"(v.x), "=r"(v.y), "=r"(v.z), "=r"(v.w) : "r"(a) : "memory"); return v; }
__device__ __forceinline__ float4 lds128f(uint32_t a) { float4 v; asm volatile("ld.shared.v4.f32 {%0,%1,%2,%3}, [%4];" : "=f"(v.x), "=f"(v.y), "=f"(v.z), "=f"(v.w) : "r"(a) : "memory"); return v; }
__device__ __forceinline__ float2 lds64f(uint32_t a) { float2 v; asm volatile("ld.shared.v2.f32 {%0,%1}, [%2];" : "=f"(v.x), "=f"(v.y) : "r"(a) : "memory"); return v; }
__device__ __forceinline__ uint4 lds64x2(uint32_t a) { uint4 v; asm volatile("ld.shared.v2.u32 {%0,%1}, [%4];\nld.shared.v2.u32 {%2,%3}, [%4+256];" : "=r"(v.x), "=r"(v.y), "=r"(v.z), "=r"(v.w) : "r"(a) : "memory"); return v; }
__device__ __forceinline__ uint32_t lds32(uint32_t a) { uint32_t v; asm volatile("ld.shared.u32 %0, [%1];" : "=r"(v) : "r"(a) : "memory"); return v; }
__device__ __forceinline__ void sts128(uint32_t a, uint32_t x, uint32_t y, uint32_t z, uint32_t w) { asm volatile("st.shared.v4.u32 [%0], {%1,%2,%3,%4};" :: "r"(a), "r"(x), "r"(y), "r"(z), "r"(w) : "memory"); }
__device__ __forceinline__ void sts128f(uint32_t a, float x, float y, float z, float w) { asm volatile("st.shared.v4.f32 [%0], {%1,%2,%3,%4};" :: "r"(a), "f"(x), "f"(y), "f"(z), "f"(w) : "memory"); }
__device__ __forceinline__ void sts64(uint32_t a, uint32_t x, uint32_t y) { asm volatile("st.shared.v2.u32 [%0], {%1,%2};" :: "r"(a), "r"(x), "r"(y) : "memory"); }
__device__ __forceinline__ void sts32(uint32_t a, uint32_t x) { asm volatile("st.shared.u32 [%0], %1;" :: "r"(a), "r"(x) : "memory"); }
__device__ __forceinline__ uint4 ldsm4(uint32_t a) { uint4 v; asm volatile("ldmatrix.sync.aligned.m8n8.x4.shared.b16 {%0,%1,%2,%3}, [%4];" : "=r"(v.x), "=r"(v.y), "=r"(v.z), "=r"(v.w) : "r"(a) : "memory"); return v; }
__device__ __forceinline__ void stsm2t(uint32_t a, uint32_t x, uint32_t y) { asm volatile("stmatrix.sync.aligned.m8n8.x2.trans.shared.b16 [%0], {%1,%2};" :: "r"(a), "r"(x), "r"(y) : "memory"); }
__device__ __forceinline__ void stsm4t(uint32_t a, uint32_t x, uint32_t y, uint32_t z, uint32_t w) { asm volatile("stmatrix.sync.aligned.m8n8.x4.trans.shared.b16 [%0], {%1,%2,%3,%4};" :: "r"(a), "r"(x), "r"(y), "r"(z), "r"(w) : "memory"); }
__device__ __forceinline__ void st_async64(uint32_t a, uint32_t x, uint32_t y, uint32_t bar) { asm volatile("st.async.shared::cluster.mbarrier::complete_tx::bytes.v2.b32 [%0], {%1,%2}, [%3];" :: "r"(a), "r"(x), "r"(y), "r"(bar) : "memory"); }
__device__ __forceinline__ void bulk_s2c(uint32_t dst, uint32_t src, uint32_t bytes, uint32_t bar) { asm volatile("cp.async.bulk.shared::cluster.shared::cta.mbarrier::complete_tx::bytes [%0], [%1], %2, [%3];" :: "r"(dst), "r"(src), "r"(bytes), "r"(bar) : "memory"); }
__device__ __forceinline__ void bulk_s2g(void* dst, uint32_t src, uint32_t bytes) { asm volatile("cp.async.bulk.global.shared::cta.bulk_group [%0], [%1], %2;" :: "l"(dst), "r"(src), "r"(bytes) : "memory"); }
__device__ __forceinline__ uint32_t ldg_nc32(const void* p) { uint32_t v; asm volatile("ld.global.nc.L2::128B.u32 %0, [%1];" : "=r"(v) : "l"(p)); return v; }
__device__ __forceinline__ uint4 ldg_relaxed128(const void* p) { uint4 v; asm volatile("ld.relaxed.gpu.global.v4.u32 {%0,%1,%2,%3}, [%4];" : "=r"(v.x), "=r"(v.y), "=r"(v.z), "=r"(v.w) : "l"(p) : "memory"); return v; }
__device__ __forceinline__ void mma16816(float (&d)[4], uint32_t a0, uint32_t a1, uint32_t a2, uint32_t a3, uint32_t b0, uint32_t b1) {
    asm volatile("mma.sync.aligned.m16n8k16.row.col.f32.bf16.bf16.f32 {%0,%1,%2,%3}, {%4,%5,%6,%7}, {%8,%9}, {%0,%1,%2,%3};"
        : "+f"(d[0]), "+f"(d[1]), "+f"(d[2]), "+f"(d[3]) : "r"(a0), "r"(a1), "r"(a2), "r"(a3), "r"(b0), "r"(b1));
}
__device__ __forceinline__ void mma16816_z(float (&d)[4], uint32_t a0, uint32_t a1, uint32_t a2, uint32_t a3, uint32_t b0, uint32_t b1) {
    asm volatile("mma.sync.aligned.m16n8k16.row.col.f32.bf16.bf16.f32 {%0,%1,%2,%3}, {%4,%5,%6,%7}, {%8,%9}, {%10,%10,%10,%10};"
        : "=f"(d[0]), "=f"(d[1]), "=f"(d[2]), "=f"(d[3]) : "r"(a0), "r"(a1), "r"(a2), "r"(a3), "r"(b0), "r"(b1), "f"(0.f));
}
__device__ __forceinline__ void mma1688(float (&d)[4], uint32_t a0, uint32_t a1, uint32_t b0) {
    asm volatile("mma.sync.aligned.m16n8k8.row.col.f32.bf16.bf16.f32 {%0,%1,%2,%3}, {%4,%5}, {%6}, {%0,%1,%2,%3};"
        : "+f"(d[0]), "+f"(d[1]), "+f"(d[2]), "+f"(d[3]) : "r"(a0), "r"(a1), "r"(b0));
}
__device__ __forceinline__ void mma1688_z(float (&d)[4], uint32_t a0, uint32_t a1, uint32_t b0) {
    asm volatile("mma.sync.aligned.m16n8k8.row.col.f32.bf16.bf16.f32 {%0,%1,%2,%3}, {%4,%5}, {%6}, {%7,%7,%7,%7};"
        : "=f"(d[0]), "=f"(d[1]), "=f"(d[2]), "=f"(d[3]) : "r"(a0), "r"(a1), "r"(b0), "f"(0.f));
}
template <int ACC>
__device__ __forceinline__ void wgmma_n32_rs(float (&d)[16], uint32_t a0, uint32_t a1, uint32_t a2, uint32_t a3, uint64_t desc) {
    asm volatile("wgmma.mma_async.sync.aligned.m64n32k16.f32.bf16.bf16 {%0,%1,%2,%3,%4,%5,%6,%7,%8,%9,%10,%11,%12,%13,%14,%15}, {%16,%17,%18,%19}, %20, %21, 1, 1, 0;"
        : "+f"(d[0]), "+f"(d[1]), "+f"(d[2]), "+f"(d[3]), "+f"(d[4]), "+f"(d[5]), "+f"(d[6]), "+f"(d[7]),
          "+f"(d[8]), "+f"(d[9]), "+f"(d[10]), "+f"(d[11]), "+f"(d[12]), "+f"(d[13]), "+f"(d[14]), "+f"(d[15])
        : "r"(a0), "r"(a1), "r"(a2), "r"(a3), "l"(desc), "n"(ACC));
}
template <int ACC>
__device__ __forceinline__ void wgmma_n32_ss(float (&d)[16], uint64_t da, uint64_t db) {
    asm volatile("wgmma.mma_async.sync.aligned.m64n32k16.f32.bf16.bf16 {%0,%1,%2,%3,%4,%5,%6,%7,%8,%9,%10,%11,%12,%13,%14,%15}, %16, %17, %18, 1, 1, 0, 0;"
        : "+f"(d[0]), "+f"(d[1]), "+f"(d[2]), "+f"(d[3]), "+f"(d[4]), "+f"(d[5]), "+f"(d[6]), "+f"(d[7]),
          "+f"(d[8]), "+f"(d[9]), "+f"(d[10]), "+f"(d[11]), "+f"(d[12]), "+f"(d[13]), "+f"(d[14]), "+f"(d[15])
        : "l"(da), "l"(db), "n"(ACC));
}
__device__ __forceinline__ void wg_fence() { asm volatile("wgmma.fence.sync.aligned;" ::: "memory"); }
__device__ __forceinline__ void wg_commit() { asm volatile("wgmma.commit_group.sync.aligned;" ::: "memory"); }
__device__ __forceinline__ void wg_wait0() { asm volatile("wgmma.wait_group.sync.aligned 0;" ::: "memory"); }
__device__ __forceinline__ void cluster_sync() { asm volatile("barrier.cluster.arrive.aligned;\nbarrier.cluster.wait.aligned;" ::: "memory"); }

#define STAMP(s, i) do {} while (0)
#define STAMPV(s, i, v) do {} while (0)

constexpr int XT_BYTES = 36864;
constexpr int O_XT = 0;
constexpr int O_AS = 3 * XT_BYTES;
constexpr int O_AF = O_AS + 16384;
constexpr int O_MF = O_AF + 16384;
constexpr int O_XP = O_MF + 9216;
constexpr int O_VX = O_XP + 8192;
constexpr int O_VM = O_VX + 16384;
constexpr int O_SC = O_VM + 2048;
constexpr int O_OF = O_SC + 2560;
constexpr int O_QM = O_OF + 2048;
constexpr int O_QKX = O_QM + 2048;
constexpr int O_KM = O_QKX + 16384;
constexpr int O_MISC = O_KM + 2048;
constexpr int O_BAR = O_MISC + 64;
constexpr int CHAIN_SMEM = O_BAR + 128;
static_assert(CHAIN_SMEM <= 232448, "smem");
constexpr int B_X = O_BAR, B_VX = O_BAR + 24, B_SC = O_BAR + 40, B_VM = O_BAR + 48;
constexpr float SM_SCALE = 0.08838834764831845f * 1.4426950408889634f;
constexpr uint32_t ONES = 0x3f803f80u;

__device__ __forceinline__ uint32_t opaque(uint32_t v) { uint32_t o; asm volatile("mov.u32 %0, %1;" : "=r"(o) : "r"(v)); return o; }
__device__ __forceinline__ void st_async128(uint32_t a, uint32_t x, uint32_t y, uint32_t z, uint32_t w, uint32_t bar) {
    asm volatile("st.async.shared::cluster.mbarrier::complete_tx::bytes.v4.b32 [%0], {%1,%2,%3,%4}, [%5];" :: "r"(a), "r"(x), "r"(y), "r"(z), "r"(w), "r"(bar) : "memory");
}
__device__ __forceinline__ void tma_x_tile(uint32_t sb, const CUtensorMap* tm, int r, int j, int slot) {
    asm volatile("{\n.reg .pred p;\nelect.sync _|p, 0xffffffff;\n"
        "@p mbarrier.arrive.expect_tx.shared::cta.b64 _, [%2], 36864;\n"
        "@p cp.async.bulk.tensor.2d.shared::cluster.global.mbarrier::complete_tx::bytes.multicast::cluster [%0], [%1, {%3, %4}], [%2], %7;\n"
        "@p cp.async.bulk.tensor.2d.shared::cluster.global.mbarrier::complete_tx::bytes.multicast::cluster [%0+4096], [%1, {%5, %4}], [%2], %7;\n"
        "@p cp.async.bulk.tensor.2d.shared::cluster.global.mbarrier::complete_tx::bytes.multicast::cluster [%0+8192], [%1, {%6, %4}], [%2], %7;\n}"
        :: "r"(sb + O_XT + slot * XT_BYTES + 3 * r * 4096), "l"(tm), "r"(sb + B_X + 8 * slot), "r"(192 * r), "r"(j * 32), "r"(192 * r + 64), "r"(192 * r + 128),
           "h"((unsigned short)7) : "memory");
}
__device__ __forceinline__ float quad_max(float v) {
    const float a = __shfl_xor_sync(~0u, v, 1), b = __shfl_xor_sync(~0u, v, 2), c = __shfl_xor_sync(~0u, v, 3);
    return fmaxf(fmaxf(v, a), fmaxf(b, c));
}
__device__ __forceinline__ void load_scores(float (&p)[10], uint32_t base, uint32_t stride, uint32_t l16) {
    const float4 a0 = lds128f(base + l16), b0 = lds128f(base + stride + l16);
    const float4 a1 = lds128f(base + 512 + l16), b1 = lds128f(base + stride + 512 + l16);
    const float2 a2 = lds64f(base + 1024 + (l16 >> 1)), b2 = lds64f(base + stride + 1024 + (l16 >> 1));
    p[0] = a2.x + b2.x; p[1] = a2.y + b2.y;
    p[2] = a0.x + b0.x; p[3] = a0.y + b0.y; p[4] = a0.z + b0.z; p[5] = a0.w + b0.w;
    p[6] = a1.x + b1.x; p[7] = a1.y + b1.y; p[8] = a1.z + b1.z; p[9] = a1.w + b1.w;
}
__device__ __forceinline__ float rcp_fast(float x) { float y; asm("rcp.approx.ftz.f32 %0, %1;" : "=f"(y) : "f"(x)); return y; }

__global__ void __cluster_dims__(3, 1, 1) __launch_bounds__(384, 1)
chain_kernel(const __grid_constant__ CUtensorMap tm_x,
             const __nv_bfloat16* __restrict__ x, const __nv_bfloat16* __restrict__ mem0,
             const __nv_bfloat16* __restrict__ Wq, const __nv_bfloat16* __restrict__ Wk,
             const __nv_bfloat16* __restrict__ Wv, const __nv_bfloat16* __restrict__ Wo) {
    extern __shared__ __align__(1024) uint8_t smem_raw[];
    const uint32_t sb = smem_u32(smem_raw);
    const int lane = threadIdx.x & 31;
    const int warp = __shfl_sync(~0u, threadIdx.x >> 5, 0);
    const int wg = warp >> 2, w = warp & 3;
    const int h = blockIdx.x / 3, r = blockIdx.x - 3 * h;

    if (threadIdx.x == 0) {
        if (sb & 1023u) __trap();
        for (int i = 0; i < 7; i++) mbar_init(sb + O_BAR + 8 * i, 1);
        asm volatile("fence.mbarrier_init.release.cluster;" ::: "memory");
    }
    if (blockIdx.x == 0) {
        for (int i = threadIdx.x; i < NSEG * 4 * 8; i += 384) g_flag[i] = 0;
        __threadfence();
    }
    __syncthreads();
    cluster_sync();
    asm volatile("griddepcontrol.launch_dependents;" ::: "memory");
    const uint32_t l16c = __shfl_sync(~0u, lane * 16, lane);

    if (wg < 2) {
#define KS(u) ((u) < 8 ? ((u) >> 1) + 4 * ((u) & 1) : (u) < 12 ? (u) : (u) < 20 ? 12 + (((u) - 12) >> 1) + 4 * ((u) & 1) : (u) < 24 ? (u) : (u) + 8)
        asm volatile("setmaxnreg.inc.sync.aligned.u32 176;");
        uint32_t a[144];
        uint32_t adr1;
        {
            const int g = lane >> 2, t = lane & 3;
#pragma unroll
            for (int tl = 0; tl < 2; tl++) {
                const int tile = tl ? wg : (wg ^ 1);
                const __nv_bfloat16* W = (r < 2) ? (tile == 0 ? Wq : Wk) : Wv;
                const int col = h * 128 + ((r < 2) ? 64 * r : 64 * tile) + 16 * w + 2 * g;
                const __nv_bfloat16* p = W + (size_t)(2 * t) * HD + col;
                const __nv_bfloat16* ps = p + (size_t)(384 * wg) * HD;
#pragma unroll
                for (int u = 0; u < (tl ? 28 : 8); u++) {
                    const __nv_bfloat16* q = (u < 8 ? ps : p) + (size_t)(16 * KS(u)) * HD;
                    a[32 * tl + 4 * u + 0] = ldg_nc32(q);
                    a[32 * tl + 4 * u + 1] = ldg_nc32(q + HD);
                    a[32 * tl + 4 * u + 2] = ldg_nc32(q + 8 * HD);
                    a[32 * tl + 4 * u + 3] = ldg_nc32(q + 9 * HD);
                }
            }
#pragma unroll
            for (int kk = 0; kk < 72; kk++) {
                uint32_t w0 = a[2 * kk], w1 = a[2 * kk + 1];
                a[2 * kk] = __byte_perm(w0, w1, 0x5410);
                a[2 * kk + 1] = __byte_perm(w0, w1, 0x7632);
            }
            float vmax = 0.f;
#pragma unroll
            for (int tl = 0; tl < 2; tl++) {
                float s0 = 0.f, s1 = 0.f;
#pragma unroll
                for (int kk = 16 * tl; kk < (tl ? 72 : 16); kk++) {
                    s0 += fabsf(__uint_as_float(a[2 * kk] << 16)) + fabsf(__uint_as_float(a[2 * kk] & 0xffff0000u));
                    s1 += fabsf(__uint_as_float(a[2 * kk + 1] << 16)) + fabsf(__uint_as_float(a[2 * kk + 1] & 0xffff0000u));
                }
                s0 += __shfl_xor_sync(~0u, s0, 1); s0 += __shfl_xor_sync(~0u, s0, 2);
                s1 += __shfl_xor_sync(~0u, s1, 1); s1 += __shfl_xor_sync(~0u, s1, 2);
                vmax = fmaxf(vmax, fmaxf(s0, s1));
            }
            uint32_t mx = __reduce_max_sync(~0u, __float_as_uint(2.f * vmax));
            sts32_if(lane, sb + O_MISC + 32 + 4 * warp, mx);
            bar_arrive(7, 384);
            const uint32_t as = sb + O_AS + wg * 8192 + (16 * w + g) * 128 + t * 4;
#pragma unroll
            for (int kk = 0; kk < 4; kk++) {
                sts32(as + (((2 * kk) ^ g) << 4), a[32 + 4 * kk]);
                sts32(as + 1024 + (((2 * kk) ^ g) << 4), a[32 + 4 * kk + 1]);
                sts32(as + (((2 * kk + 1) ^ g) << 4), a[32 + 4 * kk + 2]);
                sts32(as + 1024 + (((2 * kk + 1) ^ g) << 4), a[32 + 4 * kk + 3]);
                sts128(sb + O_AF + warp * 2048 + kk * 512 + lane * 16, a[32 + 4 * kk], a[32 + 4 * kk + 1], a[32 + 4 * kk + 2], a[32 + 4 * kk + 3]);
            }
            fence_async_smem();
            bar_sync(1, 256);
            const uint32_t l = lane * 16;
            const int mi = lane >> 3, isk = (mi >> 1) ? wg : (wg ^ 1);
            adr1 = (r == 2) ? (sb + O_VM + warp * 256 + (l >> 1))
                            : (isk ? (sb + O_KM + w * 512 + wg * 256 + (mi & 1) * 128 + (l & 127))
                                   : (sb + O_QM + w * 512 + (mi & 1) * 256 + wg * 128 + (l & 127)));
            adr1 = __shfl_sync(~0u, adr1, lane);
        }
        int s3 = 2;
#pragma unroll 1
        for (int s = -1; s < NSEG; s++) {
            const uint32_t l16 = opaque(l16c);
            s3 = (s3 == 2) ? 0 : s3 + 1;
            if (s < 0) mbar_wait(sb + B_X, 0);
            const uint64_t desc0 = (uint64_t)(((sb + O_XT + s3 * XT_BYTES) & 0x3FFFF) >> 4) | (1ull << 16) | (64ull << 32) | (1ull << 62);
            uint32_t km0 = 0, km1 = 0;
            if (s >= 0) {
#pragma unroll
                for (int kk = 0; kk < 4; kk++) {
                    const uint4 v = lds128(sb + O_AF + warp * 2048 + kk * 512 + l16);
                    a[32 + 4 * kk] = v.x; a[32 + 4 * kk + 1] = v.y; a[32 + 4 * kk + 2] = v.z; a[32 + 4 * kk + 3] = v.w;
                }
                float co[4], cw[3][4];
                uint4 b[14];
                float inv;
#define GORD(i) ((i) == 0 ? 0 : (i) == 1 ? 1 : (i) == 5 ? 2 : (i) == 9 ? 3 : (i) < 5 ? (i) + 2 : (i) < 9 ? (i) + 1 : (i))
                auto qkv_mma = [&](int i) {
                    const int gi = GORD(i), u = 8 * gi, n0 = 2 * i, n1 = 2 * i + 1;
                    if (gi < 4) {
                        if (i == 0) mma16816_z(co, a[u], a[u + 1], a[u + 2], a[u + 3], b[0].x, b[0].y);
                        else mma16816(co, a[u], a[u + 1], a[u + 2], a[u + 3], b[i].x, b[i].y);
                    }
                    if (n0 < 3) mma16816_z(cw[n0 % 3], a[32 + u], a[32 + u + 1], a[32 + u + 2], a[32 + u + 3], b[i].x, b[i].y);
                    else mma16816(cw[n0 % 3], a[32 + u], a[32 + u + 1], a[32 + u + 2], a[32 + u + 3], b[i].x, b[i].y);
                    if (n1 < 3) mma16816_z(cw[n1 % 3], a[32 + u + 4], a[32 + u + 5], a[32 + u + 6], a[32 + u + 7], b[i].z, b[i].w);
                    else mma16816(cw[n1 % 3], a[32 + u + 4], a[32 + u + 5], a[32 + u + 6], a[32 + u + 7], b[i].z, b[i].w);
                    if (gi < 4) mma16816(co, a[u + 4], a[u + 5], a[u + 6], a[u + 7], b[i].z, b[i].w);
                };
                const uint32_t mf = sb + O_MF + l16, mfs = mf + wg * 6144;
                if (VSEND == 0 && r == 2) {
                    asm volatile("{\n.reg .pred p;\ncp.async.bulk.wait_group 0;\nelect.sync _|p, 0xffffffff;\nsetp.lt.and.s32 p, %4, 63, p;\n"
                        "@p cp.async.bulk.shared::cluster.global.mbarrier::complete_tx::bytes.multicast::cluster [%1], [%0], 1024, [%2], %3;\n"
                        "fence.proxy.async.global;\n}"
                        :: "l"(reinterpret_cast<char*>(g_qkv) + (size_t)(s * NH + h) * 24576 + 16384 + warp * 1024), "r"(sb + O_VX + (s & 1) * 8192 + warp * 1024),
                           "r"(sb + B_VX + 8 * (s & 1)), "h"((unsigned short)3), "r"(s) : "memory");
                }
                bar_sync(2, 384);
                if (warp == 0) STAMP(s, 0);
                auto qkv_ld = [&](int i) { b[i] = GORD(i) < 4 ? lds128v(mfs + GORD(i) * 512) : lds128v(mf + (GORD(i) < 12 ? GORD(i) : GORD(i) + 4) * 512); };
#pragma unroll
                for (int i = 0; i < 5; i++) qkv_ld(i);
                if (QF >= 1) sched_fence<2>(h);
#pragma unroll
                for (int i = 0; i < 4; i++) { qkv_mma(i); qkv_ld(5 + i); }
                if (QF >= 2) sched_fence<3>(h);
#pragma unroll
                for (int i = 4; i < 9; i++) { qkv_mma(i); qkv_ld(5 + i); }
                inv = __uint_as_float(lds32(sb + O_MISC));
                if (QF >= 3) sched_fence<4>(h);
#pragma unroll
                for (int i = 9; i < 14; i++) qkv_mma(i);
#pragma unroll
                for (int i = 0; i < 4; i++) cw[0][i] += cw[1][i] + cw[2][i];
                if (r < 2) {
                    const uint32_t o0 = pack_bf16(co[0] * inv, co[1] * inv), o1 = pack_bf16(co[2] * inv, co[3] * inv);
                    const uint32_t w0 = pack_bf16(cw[0][0] * inv, cw[0][1] * inv), w1 = pack_bf16(cw[0][2] * inv, cw[0][3] * inv);
                    stsm4t(adr1, o0, o1, w0, w1);
                    km0 = wg ? w0 : o0; km1 = wg ? w1 : o1;
                    if (warp == 0) STAMP(s, 1);
                    asm volatile("{\n.reg .pred p;\nsetp.ge.u32 p, %0, 3;\n@p bar.arrive 1, 256;\n}" :: "r"(warp) : "memory");
                    if (warp < 3 && s < NSEG - 1) {
                        uint4 q[4], k[4];
                        const uint32_t ka = sb + (warp == 2 ? O_KM : O_QKX + (s & 1) * 8192 + 4096 + warp * 2048) + l16;
#pragma unroll
                        for (int i = 0; i < 4; i++) k[i] = ldsm4(ka + i * 512);
                        const uint32_t dst = sb + O_SC + r * 1280 + warp * 512 + (l16 >> 1);
                        bar_sync(1, 256);
#pragma unroll
                        for (int i = 0; i < 4; i++) q[i] = ldsm4(sb + O_QM + i * 512 + l16);
                        if (warp == 2) {
#pragma unroll
                            for (int i = 0; i < 4; i++) k[i] = ldsm4(ka + i * 512);
                        }
                        float s0[4], s1[4], t0[4], t1[4];
                        mma16816_z(s0, q[0].x, q[0].y, q[0].z, q[0].w, k[0].x, k[0].y);
                        mma16816_z(s1, q[0].x, q[0].y, q[0].z, q[0].w, k[0].z, k[0].w);
                        mma16816_z(t0, q[1].x, q[1].y, q[1].z, q[1].w, k[1].x, k[1].y);
                        mma16816_z(t1, q[1].x, q[1].y, q[1].z, q[1].w, k[1].z, k[1].w);
                        mma16816(s0, q[2].x, q[2].y, q[2].z, q[2].w, k[2].x, k[2].y);
                        mma16816(s1, q[2].x, q[2].y, q[2].z, q[2].w, k[2].z, k[2].w);
                        mma16816(t0, q[3].x, q[3].y, q[3].z, q[3].w, k[3].x, k[3].y);
                        mma16816(t1, q[3].x, q[3].y, q[3].z, q[3].w, k[3].z, k[3].w);
                        const float v0 = (s0[0] + s0[2]) + (t0[0] + t0[2]), v1 = (s0[1] + s0[3]) + (t0[1] + t0[3]);
                        const float v2 = (s1[0] + s1[2]) + (t1[0] + t1[2]), v3 = (s1[1] + s1[3]) + (t1[1] + t1[3]);
                        if (warp < 2) {
                            const uint32_t dv = dst + (l16 >> 1);
                            st_async128(mapa(dv, 2), __float_as_uint(v0), __float_as_uint(v1), __float_as_uint(v2), __float_as_uint(v3), mapa(sb + B_SC, 2));
                            st_async128(mapa(dv, r ^ 1), __float_as_uint(v0), __float_as_uint(v1), __float_as_uint(v2), __float_as_uint(v3), mapa(sb + B_SC, r ^ 1));
                            st_async128(mapa(dv, r), __float_as_uint(v0), __float_as_uint(v1), __float_as_uint(v2), __float_as_uint(v3), mapa(sb + B_SC, r));
                        } else {
                            st_async64(mapa(dst, 2), __float_as_uint(v0 + v2), __float_as_uint(v1 + v3), mapa(sb + B_SC, 2));
                            st_async64(mapa(dst, r ^ 1), __float_as_uint(v0 + v2), __float_as_uint(v1 + v3), mapa(sb + B_SC, r ^ 1));
                            st_async64(mapa(dst, r), __float_as_uint(v0 + v2), __float_as_uint(v1 + v3), mapa(sb + B_SC, r));
                        }
                        if (warp == 2) STAMP(s, 2);
                    } else if (warp < 3) {
                        bar_sync(1, 256);
                    }
                } else {
                    sts128f(sb + O_XP + warp * 512 + l16, co[0], co[1], co[2], co[3]);
                    bar_sync(8 + w, 64);
                    const float4 o = lds128f(sb + O_XP + (warp ^ 4) * 512 + l16);
                    km0 = pack_bf16((cw[0][0] + o.x) * inv, (cw[0][1] + o.y) * inv);
                    km1 = pack_bf16((cw[0][2] + o.z) * inv, (cw[0][3] + o.w) * inv);
                    if (warp == 0) STAMP(s, 1);
                    if (s < NSEG - 1) {
                        st_async64(mapa(adr1, 0), km0, km1, mapa(sb + B_VM, 0));
                        st_async64(mapa(adr1, 1), km0, km1, mapa(sb + B_VM, 1));
                        st_async64(mapa(adr1, 2), km0, km1, mapa(sb + B_VM, 2));
                    }
                    if (warp == 0) STAMP(s, 2);
                }
            }
            auto store_qk = [&]() {
                asm volatile("{\n.reg .pred p;\nelect.sync _|p, 0xffffffff;\n"
                    "@p cp.async.bulk.global.shared::cta.bulk_group [%0], [%1], 8192;\n@p cp.async.bulk.commit_group;\n}"
                    :: "l"(reinterpret_cast<char*>(g_qkv) + (size_t)(s * NH + h) * 24576 + r * 8192), "r"(sb + O_QKX + (s & 1) * 8192) : "memory");
            };
            auto store_kvm = [&]() {
                char* p = reinterpret_cast<char*>(g_kvm) + (size_t)(s * NH + h) * 6144 + (r < 2 ? wg * 2048 + (r * 4 + w) * 256 : 4096 + warp * 256) + (l16 >> 1);
                *reinterpret_cast<uint2*>(p) = make_uint2(km0, km1);
            };
            if (s >= 0) bar_sync(3, 384);
            if (s == NSEG - 1) {
                store_kvm();
                if (warp == 3 && r < 2) {
                    store_qk();
                    asm volatile("cp.async.bulk.wait_group 0;\nfence.proxy.async.global;" ::: "memory");
                }
            } else {
                const int j = s + 1;
#define XDESC(u) (((u) < 8 ? descs : desc0) + (uint64_t)(((KS(u) >> 2) * 4096 + (KS(u) & 3) * 32) >> 4))
                const uint64_t descs = desc0 + (uint64_t)(wg * (6 * 4096 >> 4));
                float d[16];
                wg_fence();
#pragma unroll
                for (int u = 0; u < 8; u++) {
                    if (u == 0) wgmma_n32_rs<0>(d, a[0], a[1], a[2], a[3], XDESC(0));
                    else wgmma_n32_rs<1>(d, a[4 * u], a[4 * u + 1], a[4 * u + 2], a[4 * u + 3], XDESC(u));
                }
                wg_commit();
                wg_wait0();
                if (warp == 0) STAMP(s, 15);
                if (s >= 0) bar_sync(4, 384);
#pragma unroll
                for (int q = 0; q < 2; q++)
                    sts128(sb + O_XP + warp * 1024 + q * 512 + l16, pack_bf16(d[8 * q], d[8 * q + 1]), pack_bf16(d[8 * q + 2], d[8 * q + 3]),
                           pack_bf16(d[8 * q + 4], d[8 * q + 5]), pack_bf16(d[8 * q + 6], d[8 * q + 7]));
                if (s >= 0) {
                    store_kvm();
                    if (warp == 3) asm volatile("cp.async.bulk.wait_group 0;\nfence.proxy.async.global;" ::: "memory");
                    if (warp == 1 && s + 2 < NSEG) tma_x_tile(sb, &tm_x, r, s + 2, s3 == 2 ? 0 : s3 + 1);
                }
                bar_sync(12, 256);
#pragma unroll
                for (int q = 0; q < 2; q++) {
                    const uint4 o = lds128(sb + O_XP + (warp ^ 4) * 1024 + q * 512 + l16);
                    d[8 * q] = __uint_as_float(o.x << 16); d[8 * q + 1] = __uint_as_float(o.x & 0xffff0000u);
                    d[8 * q + 2] = __uint_as_float(o.y << 16); d[8 * q + 3] = __uint_as_float(o.y & 0xffff0000u);
                    d[8 * q + 4] = __uint_as_float(o.z << 16); d[8 * q + 5] = __uint_as_float(o.z & 0xffff0000u);
                    d[8 * q + 6] = __uint_as_float(o.w << 16); d[8 * q + 7] = __uint_as_float(o.w & 0xffff0000u);
                }
                if (s >= 0) {
                    if (warp == 6 && (s & 3) == 0 && s >= 4)
                        asm volatile("{\n.reg .pred p;\nsetp.eq.u32 p, %1, 0;\n@p red.release.gpu.global.inc.u32 [%0], 0x7fffffff;\n}"
                                     :: "l"(&g_flag[((s - 1) * 4 + (h >> 3)) * 8]), "r"(l16) : "memory");
                    asm volatile("{\n.reg .pred p;\nsetp.eq.u32 p, %0, 0;\n@p bar.sync 5, 256;\n@!p bar.sync 13, 256;\n}" :: "r"(wg) : "memory");
                }
                const uint64_t da0 = (uint64_t)(((sb + O_AS + wg * 8192) & 0x3FFFF) >> 4) | (1ull << 16) | (64ull << 32) | (1ull << 62);
                wg_fence();
#pragma unroll
                for (int u = 0; u < 4; u++) wgmma_n32_ss<1>(d, da0 + 2 * u, XDESC(u));
#pragma unroll
                for (int u = 4; u < 28; u++) wgmma_n32_rs<1>(d, a[32 + 4 * u], a[32 + 4 * u + 1], a[32 + 4 * u + 2], a[32 + 4 * u + 3], XDESC(u));
                wg_commit();
                wg_wait0();
                if (warp == 3 && r < 2 && s >= 0) store_qk();
                if (warp == 4) STAMP(s, 3);
                uint32_t e[8];
#pragma unroll
                for (int i = 0; i < 8; i++) e[i] = pack_bf16(d[2 * i], d[2 * i + 1]);
                if (r < 2) {
                    const uint32_t base = sb + O_QKX + (j & 1) * 8192 + wg * 4096 + w * 512 + l16;
                    stsm4t(base, e[0], wg ? e[1] : e[2], wg ? e[2] : e[1], e[3]);
                    stsm4t(base + 2048, e[4], wg ? e[5] : e[6], wg ? e[6] : e[5], e[7]);
                    fence_async_smem();
                } else {
                    const uint32_t base = sb + O_VX + (j & 1) * 8192 + warp * 1024 + l16;
                    sts128(base, e[0], e[1], e[2], e[3]);
                    sts128(base + 512, e[4], e[5], e[6], e[7]);
                    fence_async_smem();
                    bar_arrive(14, 288);
                }
                if (warp == 7) STAMP(s, 4);
            }
        }
        bar_arrive(7, 384);
    } else {
        asm volatile("setmaxnreg.dec.sync.aligned.u32 152;");
        const int c = w;
        uint32_t a[96];
        uint32_t mmax = 0;
        {
            const int g = lane >> 2, t = lane & 3, t2 = threadIdx.x - 256;
            if (c == 0) {
                tma_x_tile(sb, &tm_x, r, 0, 0);
                tma_x_tile(sb, &tm_x, r, 1, 1);
                mbar_expect_if(lane, sb + B_SC, 2560);
                mbar_expect_if(lane, sb + B_VM, 2048);
                if (r < 2) mbar_expect_if(lane, sb + B_VX, 8192);
                sts32_if(lane, sb + O_MISC, __float_as_uint(1.0f));
                sts32_if(lane, sb + O_MISC + 12, __float_as_uint(SM_SCALE));
            }
#pragma unroll
            for (int i = 0; i < 4; i++) g_acc[(blockIdx.x * 64 + i * 16 + (t2 >> 3)) * 16 + (t2 & 7)] = make_uint4(0, 0, 0, 0);
#pragma unroll
            for (int tau = 0; tau < 3; tau++) {
                uint32_t v[6];
#pragma unroll
                for (int i = 0; i < 3; i++) {
                    const uint32_t* p = reinterpret_cast<const uint32_t*>(mem0 + g * DM + 16 * (12 * tau + 4 * i + c) + 2 * t);
                    v[2 * i] = __ldg(p); v[2 * i + 1] = __ldg(p + 4);
                    mmax = __vmaxu2(mmax, __vmaxu2(v[2 * i] & 0x7fff7fffu, v[2 * i + 1] & 0x7fff7fffu));
                }
                sts128(sb + O_MF + tau * 3072 + c * 512 + lane * 16, v[0], v[1], v[2], v[3]);
                sts64(sb + O_MF + tau * 3072 + 2048 + (c >> 1) * 512 + lane * 16 + (c & 1) * 8, v[4], v[5]);
            }
            mmax = max(mmax << 16, mmax & 0xffff0000u);
            bar_arrive(2, 384);
            uint32_t xm = 0;
            const uint4* xp = reinterpret_cast<const uint4*>(x) + blockIdx.x * 1536 + t2;
#pragma unroll
            for (int i = 0; i < 12; i++) {
                uint4 v = __ldg(xp + i * 128);
                xm = __vmaxu2(xm, __vmaxu2(__vmaxu2(v.x & 0x7fff7fffu, v.y & 0x7fff7fffu), __vmaxu2(v.z & 0x7fff7fffu, v.w & 0x7fff7fffu)));
            }
            xm = __reduce_max_sync(~0u, max(xm << 16, xm & 0xffff0000u));

            const __nv_bfloat16* p = Wo + (size_t)(h * 128 + 4 * t) * DM + 192 * r + 16 * c + 2 * g;
#pragma unroll
            for (int i = 0; i < 3; i++)
#pragma unroll
                for (int eb = 0; eb < 8; eb++)
#pragma unroll
                    for (int j = 0; j < 4; j++) a[(i * 8 + eb) * 4 + j] = ldg_nc32(p + (16 * eb + ((j & 1) * 2 + (j >> 1))) * DM + 64 * i);
#pragma unroll
            for (int kk = 0; kk < 48; kk++) {
                uint32_t w0 = a[2 * kk], w1 = a[2 * kk + 1];
                a[2 * kk] = __byte_perm(w0, w1, 0x5410);
                a[2 * kk + 1] = __byte_perm(w0, w1, 0x7632);
            }
            float wmax = 0.f;
#pragma unroll
            for (int i = 0; i < 3; i++) {
                float s0 = 0.f, s1 = 0.f;
#pragma unroll
                for (int kk = 16 * i; kk < 16 * i + 16; kk++) {
                    s0 += fabsf(__uint_as_float(a[2 * kk] << 16)) + fabsf(__uint_as_float(a[2 * kk] & 0xffff0000u));
                    s1 += fabsf(__uint_as_float(a[2 * kk + 1] << 16)) + fabsf(__uint_as_float(a[2 * kk + 1] & 0xffff0000u));
                }
                s0 += __shfl_xor_sync(~0u, s0, 1); s0 += __shfl_xor_sync(~0u, s0, 2);
                s1 += __shfl_xor_sync(~0u, s1, 1); s1 += __shfl_xor_sync(~0u, s1, 2);
                wmax = fmaxf(wmax, fmaxf(s0, s1));
            }
            uint32_t wm = __reduce_max_sync(~0u, __float_as_uint(wmax));
            sts32_if(lane, sb + O_OF + 4 * c, wm); sts32_if(lane, sb + O_OF + 16 + 4 * c, xm);
            __threadfence();
            bar_sync(7, 384);
            if (c == 0) {
                const uint4 wq = lds128(sb + O_OF), xq = lds128(sb + O_OF + 16), v0 = lds128(sb + O_MISC + 32), v1 = lds128(sb + O_MISC + 48);
                const uint32_t w1 = max(max(wq.x, wq.y), max(wq.z, wq.w)), x1 = max(max(xq.x, xq.y), max(xq.z, xq.w));
                const uint32_t vv = (r < 2) ? 0u : max(max(max(v0.x, v0.y), max(v0.z, v0.w)), max(max(v1.x, v1.y), max(v1.z, v1.w)));
                unsigned old = 0;
                asm volatile("{\n.reg .pred p;\nsetp.eq.u32 p, %6, 0;\n@p st.global.v4.u32 [%1], {%2,%3,%4,%4};\nfence.acq_rel.gpu;\n@p atom.relaxed.gpu.global.add.u32 %0, [%5], 1;\n}"
                             : "+r"(old) : "l"(&g_norm[blockIdx.x * 4]), "r"(w1), "r"(vv), "r"(x1), "l"(&g_gridbar), "r"(lane) : "memory");
                old = __shfl_sync(~0u, old, 0);
                const unsigned target = (old / 96u + 1u) * 96u;
                asm volatile("{\n.reg .pred p;\n.reg .u32 n, v;\nmov.u32 n, 0;\n"
                             "G_%=: ld.acquire.gpu.global.u32 v, [%0];\nsub.u32 v, v, %1;\nsetp.ge.s32 p, v, 0;\n@p bra.uni E_%=;\n"
                             "add.u32 n, n, 1;\nsetp.lt.u32 p, n, 4000000;\n@p bra.uni G_%=;\ntrap;\nE_%=:\n}" :: "l"(&g_gridbar), "r"(target) : "memory");
                uint4 n0 = ldg_relaxed128(&g_norm[lane * 4]), n1 = ldg_relaxed128(&g_norm[(lane + 32) * 4]), n2 = ldg_relaxed128(&g_norm[(lane + 64) * 4]);
                const float fw = __uint_as_float(__reduce_max_sync(~0u, max(n0.x, max(n1.x, n2.x))));
                const float fv = __uint_as_float(__reduce_max_sync(~0u, max(n0.y, max(n1.y, n2.y))));
                const float xmax = __uint_as_float(__reduce_max_sync(~0u, max(n0.z, max(n1.z, n2.z))));
                const float G = 36.f * fw * fv;
                sts32_if(lane, sb + O_MISC + 4, __float_as_uint(G)); sts32_if(lane, sb + O_MISC + 8, __float_as_uint(G * xmax));
            }
        }
        bar_sync(6, 128);
        char* rptr; int pdelta; int s3n = 1;
        {
            const uint32_t roff = (r * 4 + c) * 2048 + (lane >> 4) * 512 + (lane & 2) * 128 + (lane & 1) * 64 + (lane & 12) * 4;
            const uint32_t poff = c * 2048 + (lane & 4) * 256 + (lane >> 4) * 256 + (lane & 8) * 8 + (lane & 3) * 16;
            rptr = reinterpret_cast<char*>(g_acc) + roff;
            pdelta = __shfl_sync(~0u, (int)poff - (int)roff, lane);
        }
#pragma unroll 1
        for (int s = 0; s < NSEG; s++) {
            const uint32_t l16 = opaque(l16c);
            const uint32_t vxa = sb + O_VX + (s & 1) * 8192 + c * 2048 + l16;
            if (c == 0 && r == 2) {
                bar_sync(14, 288);
                asm volatile("{\n.reg .pred p;\nelect.sync _|p, 0xffffffff;\n"
                    "@p cp.async.bulk.global.shared::cta.bulk_group [%0], [%1], 8192;\n@p cp.async.bulk.commit_group;\n"
                    "cp.async.bulk.wait_group 0;\nsetp.lt.and.s32 p, %4, 63, p;\n"
                    "@p cp.async.bulk.shared::cluster.global.mbarrier::complete_tx::bytes.multicast::cluster [%1], [%0], 8192, [%2], %3;\n"
                    "fence.proxy.async.global;\n}"
                    :: "l"(reinterpret_cast<char*>(g_qkv) + (size_t)(s * NH + h) * 24576 + 16384), "r"(sb + O_VX + (s & 1) * 8192),
                       "r"(sb + B_VX + 8 * (s & 1)), "h"((unsigned short)3), "r"(s) : "memory");
            }
            if (s == NSEG - 1) { bar_sync(3, 384); break; }
            uint4 vx[4];
            sts32_if(l16, sb + O_MISC + 16 + 4 * c, __reduce_max_sync(~0u, mmax));
            if (c == 0) STAMP(s, 5);
            {
                bar_sync(6, 128);
                const uint4 mm = lds128(sb + O_MISC + 16), cf = lds128(sb + O_MISC);
                const float bound = fmaxf(__uint_as_float(cf.z), __uint_as_float(cf.y) * (__uint_as_float(max(max(mm.x, mm.y), max(mm.z, mm.w))) * __uint_as_float(cf.x)));
                const uint32_t ebits = min(max(__float_as_uint(bound) & 0x7f800000u, 21u << 23), 254u << 23);
                mbar_wait(sb + B_X + 8 * s3n, ((s + 1) / 3) & 1);
                s3n = (s3n == 2) ? 0 : s3n + 1;
                bar_sync(3, 384);
                if (r < 2) mbar_wait(sb + B_VX + 8 * (s & 1), (s >> 1) & 1);
#pragma unroll
                for (int q = 0; q < 4; q++) vx[q] = lds128(vxa + q * 512);
                mbar_wait(sb + B_VM, s & 1);
                const uint4 vm = lds64x2(sb + O_VM + c * 512 + (l16 >> 1));
                if (c == 0) STAMP(s, 13);
                mbar_wait(sb + B_SC, s & 1);
                if (c == 0) STAMP(s, 6);
                float p[10];
                load_scores(p, sb + O_SC, 1280, l16);
                bar_arrive(4, 384);
                const float sc = __uint_as_float(lds32(sb + O_MISC + 12));
                float mx = fmaxf(fmaxf(fmaxf(p[0], p[1]), fmaxf(p[2], p[3])), fmaxf(fmaxf(p[4], p[5]), fmaxf(p[6], p[7])));
                mx = quad_max(fmaxf(mx, fmaxf(p[8], p[9])));
                const float mo = mx * sc;
                uint32_t P[5];
#pragma unroll
                for (int n = 0; n < 5; n++) P[n] = pack_bf16(ex2(fmaf(p[2 * n], SM_SCALE, -mo)), ex2(fmaf(p[2 * n + 1], SM_SCALE, -mo)));
                if (c == 0) STAMP(s, 7);
                float o0[4], o1[4], sm[4];
                mma1688_z(sm, ONES, ONES, P[0]);
                mma1688_z(o0, vm.x, vm.y, P[0]);
                mma1688_z(o1, vm.z, vm.w, P[0]);
                mma16816(sm, ONES, ONES, ONES, ONES, P[1], P[2]);
                mma16816(o0, vx[0].x, vx[0].y, vx[0].z, vx[0].w, P[1], P[2]);
                mma16816(o1, vx[2].x, vx[2].y, vx[2].z, vx[2].w, P[1], P[2]);
                mma16816(sm, ONES, ONES, ONES, ONES, P[3], P[4]);
                mma16816(o0, vx[1].x, vx[1].y, vx[1].z, vx[1].w, P[3], P[4]);
                mma16816(o1, vx[3].x, vx[3].y, vx[3].z, vx[3].w, P[3], P[4]);
                const float sig = __uint_as_float((268u << 23) - ebits);
                const float r0 = rcp_fast(sm[0]) * sig, r1 = rcp_fast(sm[1]) * sig;
                stsm4t(sb + O_OF + c * 512 + l16, pack_bf16(o0[0] * r0, o0[1] * r1), pack_bf16(o0[2] * r0, o0[3] * r1),
                       pack_bf16(o1[0] * r0, o1[1] * r1), pack_bf16(o1[2] * r0, o1[3] * r1));
                bar_sync(6, 128);
                uint4 ob[4];
#pragma unroll
                for (int q = 0; q < 4; q++) ob[q] = ldsm4(sb + O_OF + q * 512 + l16);
                float m0[3][4], m1[3][4];
#pragma unroll
                for (int q = 0; q < 4; q++) {
#pragma unroll
                    for (int i = 0; i < 3; i++) {
                        const int k0 = (i * 8 + 2 * q) * 4;
                        if (q == 0) mma16816_z(m0[i], a[k0], a[k0 + 1], a[k0 + 2], a[k0 + 3], ob[q].x, ob[q].y);
                        else mma16816(m0[i], a[k0], a[k0 + 1], a[k0 + 2], a[k0 + 3], ob[q].x, ob[q].y);
                    }
#pragma unroll
                    for (int i = 0; i < 3; i++) {
                        const int k1 = (i * 8 + 2 * q + 1) * 4;
                        if (q == 0) mma16816_z(m1[i], a[k1], a[k1 + 1], a[k1 + 2], a[k1 + 3], ob[q].z, ob[q].w);
                        else mma16816(m1[i], a[k1], a[k1 + 1], a[k1 + 2], a[k1 + 3], ob[q].z, ob[q].w);
                    }
                }
                asm volatile("red.relaxed.gpu.global.add.noftz.v4.f16x2 [%0], {%1,%2,%3,%4};" :: "l"(rptr),
                    "r"(pack_f16(m0[0][0] + m1[0][0], m0[0][2] + m1[0][2])), "r"(pack_f16(m0[1][0] + m1[1][0], m0[1][2] + m1[1][2])),
                    "r"(pack_f16(m0[2][0] + m1[2][0], m0[2][2] + m1[2][2])), "r"(0x3c00u) : "memory");
                asm volatile("red.relaxed.gpu.global.add.noftz.v4.f16x2 [%0], {%1,%2,%3,%4};" :: "l"(rptr + 1024),
                    "r"(pack_f16(m0[0][1] + m1[0][1], m0[0][3] + m1[0][3])), "r"(pack_f16(m0[1][1] + m1[1][1], m0[1][3] + m1[1][3])),
                    "r"(pack_f16(m0[2][1] + m1[2][1], m0[2][3] + m1[2][3])), "r"(0x3c00u) : "memory");
                const unsigned t_red = clk();
                bar_arrive(5, 256);
                bar_arrive(13, 256);
                {
                    const uint32_t bar = sb + (c == 0 ? B_SC : c == 1 ? B_VM : B_VX + 8 * ((s + 1) & 1));
                    mbar_expect_if(l16 | (uint32_t)(c == 3 || (c == 2 && r == 2)), bar, c == 0 ? 2560 : c == 1 ? 2048 : 8192);
                }
                sts32_if(l16 | (c ^ 3), sb + O_MISC, ebits - (14u << 23));
                if (c == 0) STAMPV(s, 8, t_red);
                const char* pbase = rptr + pdelta;
                spin_until(t_red, D_WAIT);
                uint4 v[6];
#pragma unroll
                for (int i = 0; i < 6; i++) v[i] = ldg_relaxed128(pbase + (i >> 1) * 8192 + (i & 1) * 512);
                int nretry = 0;
                auto hand_over = [&]() -> uint32_t {
                    uint32_t ok = 0;
#pragma unroll
                    for (int tau = 0; tau < 3; tau++) {
                        if (tau == 1) sched_fence<0>(h);
                        if (tau == 2) {
                            sched_fence<1>(h);
                            asm volatile("{\n.reg .pred p, q;\n.reg .b32 x;\nlop3.b32 x, %1, %2, %3, 0x80;\nlop3.b32 x, x, %4, %5, 0x80;\nand.b32 x, x, %6;\n"
                                         "setp.eq.u32 p, x, 0x5000;\nvote.sync.all.pred q, p, 0xffffffff;\nselp.u32 %0, 1, 0, q;\n}"
                                         : "=r"(ok) : "r"(v[0].w), "r"(v[1].w), "r"(v[2].w), "r"(v[3].w), "r"(v[4].w), "r"(v[5].w));
                        }
                        v[2 * tau].x = f16x2_to_bf16x2(v[2 * tau].x); v[2 * tau + 1].x = f16x2_to_bf16x2(v[2 * tau + 1].x);
                        v[2 * tau].y = f16x2_to_bf16x2(v[2 * tau].y); v[2 * tau + 1].y = f16x2_to_bf16x2(v[2 * tau + 1].y);
                        v[2 * tau].z = f16x2_to_bf16x2(v[2 * tau].z); v[2 * tau + 1].z = f16x2_to_bf16x2(v[2 * tau + 1].z);
                        sts128(sb + O_MF + tau * 3072 + c * 512 + l16, v[2 * tau].x, v[2 * tau + 1].x, v[2 * tau].y, v[2 * tau + 1].y);
                        sts64(sb + O_MF + tau * 3072 + 2048 + (c >> 1) * 512 + (c & 1) * 8 + l16, v[2 * tau].z, v[2 * tau + 1].z);
                    }
                    asm volatile("{\n.reg .pred p;\nsetp.ne.u32 p, %0, 0;\n@p bar.arrive 2, 384;\n}" :: "r"(ok) : "memory");
                    return ok;
                };
                if (!hand_over()) {
                    asm volatile("{\n.reg .pred p, q;\n.reg .u32 n, x;\nmov.u32 n, 0;\n"
                         "R_%=: ld.relaxed.gpu.global.v4.u32 {%0,%1,%2,%3}, [%25];\nld.relaxed.gpu.global.v4.u32 {%4,%5,%6,%7}, [%25+512];\n"
                         "ld.relaxed.gpu.global.v4.u32 {%8,%9,%10,%11}, [%25+8192];\nld.relaxed.gpu.global.v4.u32 {%12,%13,%14,%15}, [%25+8704];\n"
                         "ld.relaxed.gpu.global.v4.u32 {%16,%17,%18,%19}, [%25+16384];\nld.relaxed.gpu.global.v4.u32 {%20,%21,%22,%23}, [%25+16896];\n"
                         "add.u32 %24, %24, 1;\nand.b32 x, %3, %7;\nand.b32 x, x, %11;\nand.b32 x, x, %15;\nand.b32 x, x, %19;\nand.b32 x, x, %23;\n"
                         "setp.eq.u32 p, x, 0x5000;\nvote.sync.all.pred q, p, 0xffffffff;\n@q bra.uni K_%=;\n"
                         "add.u32 n, n, 1;\nsetp.lt.u32 q, n, 2000000;\n@q bra.uni R_%=;\ntrap;\nK_%=:\n}"
                         : "+r"(v[0].x), "+r"(v[0].y), "+r"(v[0].z), "+r"(v[0].w), "+r"(v[1].x), "+r"(v[1].y), "+r"(v[1].z), "+r"(v[1].w),
                           "+r"(v[2].x), "+r"(v[2].y), "+r"(v[2].z), "+r"(v[2].w), "+r"(v[3].x), "+r"(v[3].y), "+r"(v[3].z), "+r"(v[3].w),
                           "+r"(v[4].x), "+r"(v[4].y), "+r"(v[4].z), "+r"(v[4].w), "+r"(v[5].x), "+r"(v[5].y), "+r"(v[5].z), "+r"(v[5].w), "+r"(nretry)
                         : "l"(pbase) : "memory");
                    hand_over();
                }
                if (c == 0) STAMP(s, 12);
                if (c == 0) STAMPV(s, 14, nretry);
                mmax = absmax2(absmax2(absmax2(v[0].x, v[0].y), absmax2(v[0].z, v[1].x)), absmax2(absmax2(v[1].y, v[1].z), absmax2(v[2].x, v[2].y)));
                mmax = absmax2(mmax, absmax2(absmax2(absmax2(v[2].z, v[3].x), absmax2(v[3].y, v[3].z)), absmax2(absmax2(v[4].x, v[4].y), absmax2(v[4].z, v[5].x))));
                mmax = absmax2(mmax, absmax2(v[5].y, v[5].z)) & 0x7fff7fffu;
                mmax = max(mmax << 16, mmax & 0xffff0000u);
            }
            rptr += 24576;
        }
        {
            bar_sync(7, 384);
            if (c == 0)
                asm volatile("{\n.reg .pred p;\nsetp.eq.u32 p, %1, 0;\n@p red.release.gpu.global.inc.u32 [%0], 0x7fffffff;\n}"
                             :: "l"(&g_flag[(63 * 4 + (h >> 3)) * 8]), "r"(l16c) : "memory");
        }
    }
    cluster_sync();
}

__device__ float g_u[SEQ * 2 * DM];
__global__ void naive_gemm1(const __nv_bfloat16* x, const __nv_bfloat16* Bre, const __nv_bfloat16* Bim) {
    int p = blockIdx.x * 64 + threadIdx.x % 64, tk = blockIdx.y * 4 + threadIdx.x / 64;
    float sr = 0, si = 0;
    for (int d = 0; d < DM; d++) { float xv = __bfloat162float(x[tk * DM + d]); sr += xv * __bfloat162float(Bre[p * DM + d]); si += xv * __bfloat162float(Bim[p * DM + d]); }
    g_u[tk * 2 * DM + 2 * p] = sr; g_u[tk * 2 * DM + 2 * p + 1] = si;
}
__global__ void naive_scan(const __nv_bfloat16* Lre, const __nv_bfloat16* Lim, const __nv_bfloat16* logdt) {
    int p = blockIdx.x * 64 + threadIdx.x;
    float dt = __bfloat162float(__float2bfloat16(expf(__bfloat162float(logdt[p]))));
    float lr = __bfloat162float(Lre[p]), li = __bfloat162float(Lim[p]);
    float e = expf(dt * lr), br = e * cosf(dt * li), bi = e * sinf(dt * li);
    float den = lr * lr + li * li;
    float cr = ((br - 1.f) * lr + bi * li) / den, ci = (bi * lr - (br - 1.f) * li) / den;
    float hr = 0, hi = 0;
    for (int tk = 0; tk < SEQ; tk++) {
        float ur = g_u[tk * 2 * DM + 2 * p], ui = g_u[tk * 2 * DM + 2 * p + 1];
        float nr = br * hr - bi * hi + cr * ur - ci * ui, ni = br * hi + bi * hr + cr * ui + ci * ur;
        hr = nr; hi = ni;
        g_u[tk * 2 * DM + 2 * p] = hr; g_u[tk * 2 * DM + 2 * p + 1] = hi;
    }
}
__global__ void naive_gemm2(const __nv_bfloat16* x, const __nv_bfloat16* Cre, const __nv_bfloat16* Cim, const __nv_bfloat16* Dk, float* out) {
    int d = blockIdx.x * 64 + threadIdx.x % 64, tk = blockIdx.y * 4 + threadIdx.x / 64;
    float s = 0;
    for (int p = 0; p < DM; p++) s += g_u[tk * 2 * DM + 2 * p] * __bfloat162float(Cre[d * DM + p]) - g_u[tk * 2 * DM + 2 * p + 1] * __bfloat162float(Cim[d * DM + p]);
    out[tk * 1152 + d] = 2.f * s + __bfloat162float(__float2bfloat16(__bfloat162float(x[tk * DM + d]) * __bfloat162float(Dk[d])));
}
__device__ float frag_elem(const uint32_t* base, int e, int tok) {
    int eb = e >> 4, g = (e & 15) >> 1, hi = e & 1, j = tok >> 3, t = (tok & 7) >> 1, i = 2 * j + hi;
    uint32_t v = base[eb * 256 + (i >> 2) * 128 + (g * 4 + t) * 4 + (i & 3)];
    return __uint_as_float((tok & 1) ? (v & 0xffff0000u) : (v << 16));
}
__device__ float qk_elem(const uint32_t* base, int isk, int e, int tok) {
    int r = e >> 6, w = (e >> 4) & 3, g = (e & 15) >> 1, hi = e & 1, j = (tok >> 3) & 1;
    int mi = isk ? j * 2 + hi : hi * 2 + j;
    const __nv_bfloat16* p = reinterpret_cast<const __nv_bfloat16*>(base) + r * 4096 + isk * 2048 + (tok >> 4) * 1024 + w * 256 + mi * 64 + (tok & 7) * 8 + g;
    return __bfloat162float(*p);
}
__device__ float fragm_elem(const uint32_t* base, int e, int tok) {
    int eb = e >> 4, g = (e & 15) >> 1, hi = e & 1, t = tok >> 1;
    uint32_t v = base[eb * 64 + (g * 4 + t) * 2 + hi];
    return __uint_as_float((tok & 1) ? (v & 0xffff0000u) : (v << 16));
}
__global__ void naive_attn() {
    int s = blockIdx.x / NH, h = blockIdx.x % NH, q = threadIdx.x;
    const uint32_t* qkv = reinterpret_cast<const uint32_t*>(g_qkv) + (size_t)blockIdx.x * 6144;
    const uint32_t* kvm = reinterpret_cast<const uint32_t*>(g_kvm) + (size_t)blockIdx.x * 1536;
    float p[40], mx = -1e30f, sum = 0;
    for (int k = 0; k < 40; k++) {
        float d = 0;
        for (int e = 0; e < 128; e++)
            d += qk_elem(qkv, 0, e, q) * (k < 8 ? fragm_elem(kvm, e, k) + fragm_elem(kvm + 512, e, k) : qk_elem(qkv, 1, e, k - 8));
        p[k] = (k < 8 || k - 8 <= q) ? d * 0.08838834764831845f : -1e30f;
        mx = fmaxf(mx, p[k]);
    }
    for (int k = 0; k < 40; k++) { p[k] = expf(p[k] - mx); sum += p[k]; }
    __nv_bfloat16* ox = reinterpret_cast<__nv_bfloat16*>(g_ox);
    int tk = s * 32 + q;
    for (int e = 0; e < 128; e++) {
        float o = 0;
        for (int k = 0; k < 40; k++) o += p[k] * (k < 8 ? fragm_elem(kvm + 1024, e, k) : frag_elem(qkv + 4096, e, k - 8));
        int e0 = e & 63, ep = (e0 & 48) + (e0 & 1) * 8 + ((e0 & 15) >> 1);
        ox[((size_t)(h * 2 + (e >> 6)) * SEQ + tk) * 64 + (((ep >> 3) ^ (tk & 7)) << 3) + (ep & 7)] = __float2bfloat16(o / sum);
    }
}
__global__ void naive_wo(const __nv_bfloat16* Wo, float* out) {
    int d = blockIdx.x * 64 + threadIdx.x % 64, tk = blockIdx.y * 4 + threadIdx.x / 64;
    const __nv_bfloat16* ox = reinterpret_cast<const __nv_bfloat16*>(g_ox);
    float s = 0;
    for (int k = 0; k < HD; k++) {
        int hh = k >> 6, e0 = k & 63, e = (e0 & 48) + (e0 & 1) * 8 + ((e0 & 15) >> 1);
        s += __bfloat162float(ox[((size_t)hh * SEQ + tk) * 64 + (((e >> 3) ^ (tk & 7)) << 3) + (e & 7)]) * __bfloat162float(Wo[k * DM + d]);
    }
    out[tk * 1152 + DM + d] = s;
}

typedef CUresult (*EncodeFn)(CUtensorMap*, CUtensorMapDataType, cuuint32_t, void*, const cuuint64_t*, const cuuint64_t*, const cuuint32_t*, const cuuint32_t*,
                             CUtensorMapInterleave, CUtensorMapSwizzle, CUtensorMapL2promotion, CUtensorMapFloatOOBfill);
}

extern "C" void kernel_launch(void* const* d_in, const int* in_sizes, int n_in, void* d_out, int out_size) {
    typedef const __nv_bfloat16* bp;
    bp Ax = (bp)d_in[0], Lre = (bp)d_in[1], Lim = (bp)d_in[2], Bre = (bp)d_in[3], Bim = (bp)d_in[4], Cre = (bp)d_in[5], Cim = (bp)d_in[6],
       logdt = (bp)d_in[7], Dk = (bp)d_in[8], Bx = (bp)d_in[9], mem0 = (bp)d_in[10], Wq = (bp)d_in[11], Wk = (bp)d_in[12], Wv = (bp)d_in[13], Wo = (bp)d_in[14];
    float* out = (float*)d_out;
    static EncodeFn enc = nullptr;
    if (!enc) {
        void* fn = nullptr; cudaDriverEntryPointQueryResult qr;
        cudaGetDriverEntryPoint("cuTensorMapEncodeTiled", &fn, cudaEnableDefault, &qr);
        enc = (EncodeFn)fn;
        cudaFuncSetAttribute(chain_kernel, cudaFuncAttributeMaxDynamicSharedMemorySize, CHAIN_SMEM);
    }
    CUtensorMap tm_x;
    {
        cuuint64_t gd[2] = {DM, SEQ}; cuuint64_t gs[1] = {DM * 2}; cuuint32_t bd[2] = {64, 32}; cuuint32_t es[2] = {1, 1};
        enc(&tm_x, CU_TENSOR_MAP_DATA_TYPE_BFLOAT16, 2, (void*)Bx, gd, gs, bd, es, CU_TENSOR_MAP_INTERLEAVE_NONE, CU_TENSOR_MAP_SWIZZLE_128B,
            CU_TENSOR_MAP_L2_PROMOTION_L2_128B, CU_TENSOR_MAP_FLOAT_OOB_FILL_NONE);
    }
    cudaStream_t st = cudaStreamPerThread;
    chain_kernel<<<96, 384, CHAIN_SMEM, st>>>(tm_x, Bx, mem0, Wq, Wk, Wv, Wo);
    naive_gemm1<<<dim3(9, 512), 256, 0, st>>>(Ax, Bre, Bim);
    naive_scan<<<9, 64, 0, st>>>(Lre, Lim, logdt);
    naive_gemm2<<<dim3(9, 512), 256, 0, st>>>(Ax, Cre, Cim, Dk, out);
    naive_attn<<<NSEG * NH, 32, 0, st>>>();
    naive_wo<<<dim3(9, 512), 256, 0, st>>>(Wo, out);
}
```

```cpp
#include <cuda_runtime.h>
#include <cuda.h>
#include <cuda_bf16.h>
#include <cuda_fp16.h>
#include <stdint.h>

#define D_WAIT 700

#define VSEND 1
#define QF 0
namespace {

constexpr int DM = 576, NH = 32, SEQ = 2048, NSEG = 64, HD = 4096;

__device__ uint4 g_acc[64 * 96 * 16];
__device__ uint4 g_ox[NH * 2 * SEQ * 8];
__device__ uint4 g_qkv[NSEG * NH * 3 * 512];
__device__ uint2 g_kvm[NSEG * NH * 3 * 256];
__device__ unsigned g_flag[NSEG * 4 * 8];
__device__ unsigned g_gridbar;
__device__ float g_norm[96 * 4];

__device__ __forceinline__ uint32_t smem_u32(const void* p) { return (uint32_t)__cvta_generic_to_shared(p); }
__device__ __forceinline__ uint32_t mapa(uint32_t a, uint32_t r) { uint32_t o; asm("mapa.shared::cluster.u32 %0, %1, %2;" : "=r"(o) : "r"(a), "r"(r)); return o; }
__device__ __forceinline__ uint32_t mapa_v(uint32_t a, uint32_t r) { uint32_t o; asm volatile("mapa.shared::cluster.u32 %0, %1, %2;" : "=r"(o) : "r"(a), "r"(r)); return o; }
__device__ __forceinline__ unsigned clk() { unsigned long long c; asm volatile("mov.u64 %0, %%clock64;" : "=l"(c) :: "memory"); return (unsigned)c; }
__device__ __forceinline__ void mbar_init(uint32_t bar, uint32_t cnt) { asm volatile("mbarrier.init.shared::cta.b64 [%0], %1;" :: "r"(bar), "r"(cnt) : "memory"); }
__device__ __forceinline__ void mbar_expect(uint32_t bar, uint32_t bytes) { asm volatile("mbarrier.arrive.expect_tx.shared::cta.b64 _, [%0], %1;" :: "r"(bar), "r"(bytes) : "memory"); }
__device__ __forceinline__ void mbar_wait(uint32_t bar, uint32_t parity) {
    asm volatile("{\n.reg .pred p;\n.reg .u32 n;\nmov.u32 n, 0;\n"
                 "W_%=: mbarrier.try_wait.parity.shared::cta.b64 p, [%0], %1;\n@p bra.uni D_%=;\n"
                 "add.u32 n, n, 1;\nsetp.lt.u32 p, n, 4000000;\n@p bra.uni W_%=;\ntrap;\nD_%=:\n}" :: "r"(bar), "r"(parity) : "memory");
}
__device__ __forceinline__ void mbar_expect_if(uint32_t z, uint32_t bar, uint32_t bytes) {
    asm volatile("{\n.reg .pred p;\nsetp.eq.u32 p, %2, 0;\n@p mbarrier.arrive.expect_tx.shared::cta.b64 _, [%0], %1;\n}" :: "r"(bar), "r"(bytes), "r"(z) : "memory");
}
__device__ __forceinline__ void mbar_arrive_if(uint32_t z, uint32_t bar) {
    asm volatile("{\n.reg .pred p;\nsetp.eq.u32 p, %1, 0;\n@p mbarrier.arrive.shared::cta.b64 _, [%0];\n}" :: "r"(bar), "r"(z) : "memory");
}
__device__ __forceinline__ void sts32_if(uint32_t z, uint32_t a, uint32_t x) {
    asm volatile("{\n.reg .pred p;\nsetp.eq.u32 p, %2, 0;\n@p st.shared.u32 [%0], %1;\n}" :: "r"(a), "r"(x), "r"(z) : "memory");
}
template <int K> __device__ __forceinline__ void sched_fence(int v) {
    asm volatile("{\n.reg .pred p;\nsetp.ne.s32 p, %0, %1;\n@p bra.uni F_%=;\ntrap;\nF_%=:\n}" :: "r"(v), "n"(1000 + K) : "memory");
}
__device__ __forceinline__ void spin_until(unsigned t0, unsigned d) {
    asm volatile("{\n.reg .pred p;\n.reg .u64 c;\n.reg .u32 lo;\n"
                 "S_%=: mov.u64 c, %%clock64;\ncvt.u32.u64 lo, c;\nsub.u32 lo, lo, %0;\nsetp.lt.u32 p, lo, %1;\n@p bra.uni S_%=;\n}" :: "r"(t0), "r"(d) : "memory");
}
__device__ __forceinline__ void bar_sync(int id, int n) { asm volatile("bar.sync %0, %1;" :: "r"(id), "r"(n) : "memory"); }
__device__ __forceinline__ void bar_sync_sel(int sel, int id) {
    asm volatile("{\n.reg .pred p;\nsetp.eq.u32 p, %0, 0;\n@p bar.sync %1, %3;\n@!p bar.sync %2, %3;\n}" :: "r"(sel), "r"(id), "r"(id + 1), "n"(192) : "memory");
}
__device__ __forceinline__ void bar_arrive(int id, int n) { asm volatile("bar.arrive %0, %1;" :: "r"(id), "r"(n) : "memory"); }
__device__ __forceinline__ void fence_async_smem() { asm volatile("fence.proxy.async.shared::cta;" ::: "memory"); }
__device__ __forceinline__ uint32_t pack_bf16(float lo, float hi) { uint32_t r; asm("cvt.rn.bf16x2.f32 %0, %1, %2;" : "=r"(r) : "f"(hi), "f"(lo)); return r; }
__device__ __forceinline__ uint32_t pack_f16(float lo, float hi) { uint32_t r; asm("cvt.rn.f16x2.f32 %0, %1, %2;" : "=r"(r) : "f"(hi), "f"(lo)); return r; }
__device__ __forceinline__ uint32_t f16x2_to_bf16x2(uint32_t v) { float2 f = __half22float2(*reinterpret_cast<__half2*>(&v)); return pack_bf16(f.x, f.y); }
__device__ __forceinline__ float ex2(float x) { float y; asm("ex2.approx.ftz.f32 %0, %1;" : "=f"(y) : "f"(x)); return y; }
__device__ __forceinline__ float ex2v(float x) { float y; asm volatile("ex2.approx.ftz.f32 %0, %1;" : "=f"(y) : "f"(x)); return y; }
__device__ __forceinline__ uint32_t absmax2(uint32_t a, uint32_t b) {
    uint32_t r; asm("max.xorsign.abs.bf16x2 %0, %1, %2;" : "=r"(r) : "r"(a), "r"(b)); return r;
}
__device__ __forceinline__ uint32_t shl_v(uint32_t a, int n) { return a << n; }
__device__ __forceinline__ uint32_t max3u(uint32_t a, uint32_t b, uint32_t c) { return max(max(a, b), c); }
__device__ __forceinline__ uint4 lds128(uint32_t a) { uint4 v; asm volatile("ld.shared.v4.u32 {%0,%1,%2,%3}, [%4];" : "=r"(v.x), "=r"(v.y), "=r"(v.z), "=r"(v.w) : "r"(a) : "memory"); return v; }
__device__ __forceinline__ uint4 lds128v(uint32_t a) { uint4 v; asm volatile("ld.volatile.shared.v4.u32 {%0,%1,%2,%3}, [%4];" : "=r"(v.x), "=r"(v.y), "=r"(v.z), "=r"(v.w) : "r"(a) : "memory"); return v; }
__device__ __forceinline__ float4 lds128f(uint32_t a) { float4 v; asm volatile("ld.shared.v4.f32 {%0,%1,%2,%3}, [%4];" : "=f"(v.x), "=f"(v.y), "=f"(v.z), "=f"(v.w) : "r"(a) : "memory"); return v; }
__device__ __forceinline__ float2 lds64f(uint32_t a) { float2 v; asm volatile("ld.shared.v2.f32 {%0,%1}, [%2];" : "=f"(v.x), "=f"(v.y) : "r"(a) : "memory"); return v; }
__device__ __forceinline__ uint4 lds64x2(uint32_t a) { uint4 v; asm volatile("ld.shared.v2.u32 {%0,%1}, [%4];\nld.shared.v2.u32 {%2,%3}, [%4+256];" : "=r"(v.x), "=r"(v.y), "=r"(v.z), "=r"(v.w) : "r"(a) : "memory"); return v; }
__device__ __forceinline__ uint32_t lds32(uint32_t a) { uint32_t v; asm volatile("ld.shared.u32 %0, [%1];" : "=r"(v) : "r"(a) : "memory"); return v; }
__device__ __forceinline__ void sts128(uint32_t a, uint32_t x, uint32_t y, uint32_t z, uint32_t w) { asm volatile("st.shared.v4.u32 [%0], {%1,%2,%3,%4};" :: "r"(a), "r"(x), "r"(y), "r"(z), "r"(w) : "memory"); }
__device__ __forceinline__ void sts128f(uint32_t a, float x, float y, float z, float w) { asm volatile("st.shared.v4.f32 [%0], {%1,%2,%3,%4};" :: "r"(a), "f"(x), "f"(y), "f"(z), "f"(w) : "memory"); }
__device__ __forceinline__ void sts64(uint32_t a, uint32_t x, uint32_t y) { asm volatile("st.shared.v2.u32 [%0], {%1,%2};" :: "r"(a), "r"(x), "r"(y) : "memory"); }
__device__ __forceinline__ void sts32(uint32_t a, uint32_t x) { asm volatile("st.shared.u32 [%0], %1;" :: "r"(a), "r"(x) : "memory"); }
__device__ __forceinline__ uint4 ldsm4(uint32_t a) { uint4 v; asm volatile("ldmatrix.sync.aligned.m8n8.x4.shared.b16 {%0,%1,%2,%3}, [%4];" : "=r"(v.x), "=r"(v.y), "=r"(v.z), "=r"(v.w) : "r"(a) : "memory"); return v; }
__device__ __forceinline__ void stsm2t(uint32_t a, uint32_t x, uint32_t y) { asm volatile("stmatrix.sync.aligned.m8n8.x2.trans.shared.b16 [%0], {%1,%2};" :: "r"(a), "r"(x), "r"(y) : "memory"); }
__device__ __forceinline__ void stsm4t(uint32_t a, uint32_t x, uint32_t y, uint32_t z, uint32_t w) { asm volatile("stmatrix.sync.aligned.m8n8.x4.trans.shared.b16 [%0], {%1,%2,%3,%4};" :: "r"(a), "r"(x), "r"(y), "r"(z), "r"(w) : "memory"); }
__device__ __forceinline__ void st_async64(uint32_t a, uint32_t x, uint32_t y, uint32_t bar) { asm volatile("st.async.shared::cluster.mbarrier::complete_tx::bytes.v2.b32 [%0], {%1,%2}, [%3];" :: "r"(a), "r"(x), "r"(y), "r"(bar) : "memory"); }
__device__ __forceinline__ void bulk_s2c(uint32_t dst, uint32_t src, uint32_t bytes, uint32_t bar) { asm volatile("cp.async.bulk.shared::cluster.shared::cta.mbarrier::complete_tx::bytes [%0], [%1], %2, [%3];" :: "r"(dst), "r"(src), "r"(bytes), "r"(bar) : "memory"); }
__device__ __forceinline__ void bulk_s2g(void* dst, uint32_t src, uint32_t bytes) { asm volatile("cp.async.bulk.global.shared::cta.bulk_group [%0], [%1], %2;" :: "l"(dst), "r"(src), "r"(bytes) : "memory"); }
__device__ __forceinline__ uint32_t ldg_nc32(const void* p) { uint32_t v; asm volatile("ld.global.nc.L2::128B.u32 %0, [%1];" : "=r"(v) : "l"(p)); return v; }
__device__ __forceinline__ uint4 ldg_relaxed128(const void* p) { uint4 v; asm volatile("ld.relaxed.gpu.global.v4.u32 {%0,%1,%2,%3}, [%4];" : "=r"(v.x), "=r"(v.y), "=r"(v.z), "=r"(v.w) : "l"(p) : "memory"); return v; }
__device__ __forceinline__ void mma16816(float (&d)[4], uint32_t a0, uint32_t a1, uint32_t a2, uint32_t a3, uint32_t b0, uint32_t b1) {
    asm volatile("mma.sync.aligned.m16n8k16.row.col.f32.bf16.bf16.f32 {%0,%1,%2,%3}, {%4,%5,%6,%7}, {%8,%9}, {%0,%1,%2,%3};"
        : "+f"(d[0]), "+f"(d[1]), "+f"(d[2]), "+f"(d[3]) : "r"(a0), "r"(a1), "r"(a2), "r"(a3), "r"(b0), "r"(b1));
}
__device__ __forceinline__ void mma16816_z(float (&d)[4], uint32_t a0, uint32_t a1, uint32_t a2, uint32_t a3, uint32_t b0, uint32_t b1) {
    asm volatile("mma.sync.aligned.m16n8k16.row.col.f32.bf16.bf16.f32 {%0,%1,%2,%3}, {%4,%5,%6,%7}, {%8,%9}, {%10,%10,%10,%10};"
        : "=f"(d[0]), "=f"(d[1]), "=f"(d[2]), "=f"(d[3]) : "r"(a0), "r"(a1), "r"(a2), "r"(a3), "r"(b0), "r"(b1), "f"(0.f));
}
__device__ __forceinline__ void mma1688(float (&d)[4], uint32_t a0, uint32_t a1, uint32_t b0) {
    asm volatile("mma.sync.aligned.m16n8k8.row.col.f32.bf16.bf16.f32 {%0,%1,%2,%3}, {%4,%5}, {%6}, {%0,%1,%2,%3};"
        : "+f"(d[0]), "+f"(d[1]), "+f"(d[2]), "+f"(d[3]) : "r"(a0), "r"(a1), "r"(b0));
}
__device__ __forceinline__ void mma1688_z(float (&d)[4], uint32_t a0, uint32_t a1, uint32_t b0) {
    asm volatile("mma.sync.aligned.m16n8k8.row.col.f32.bf16.bf16.f32 {%0,%1,%2,%3}, {%4,%5}, {%6}, {%7,%7,%7,%7};"
        : "=f"(d[0]), "=f"(d[1]), "=f"(d[2]), "=f"(d[3]) : "r"(a0), "r"(a1), "r"(b0), "f"(0.f));
}
template <int ACC>
__device__ __forceinline__ void wgmma_n32_rs(float (&d)[16], uint32_t a0, uint32_t a1, uint32_t a2, uint32_t a3, uint64_t desc) {
    asm volatile("wgmma.mma_async.sync.aligned.m64n32k16.f32.bf16.bf16 {%0,%1,%2,%3,%4,%5,%6,%7,%8,%9,%10,%11,%12,%13,%14,%15}, {%16,%17,%18,%19}, %20, %21, 1, 1, 0;"
        : "+f"(d[0]), "+f"(d[1]), "+f"(d[2]), "+f"(d[3]), "+f"(d[4]), "+f"(d[5]), "+f"(d[6]), "+f"(d[7]),
          "+f"(d[8]), "+f"(d[9]), "+f"(d[10]), "+f"(d[11]), "+f"(d[12]), "+f"(d[13]), "+f"(d[14]), "+f"(d[15])
        : "r"(a0), "r"(a1), "r"(a2), "r"(a3), "l"(desc), "n"(ACC));
}
template <int ACC>
__device__ __forceinline__ void wgmma_n32_ss(float (&d)[16], uint64_t da, uint64_t db) {
    asm volatile("wgmma.mma_async.sync.aligned.m64n32k16.f32.bf16.bf16 {%0,%1,%2,%3,%4,%5,%6,%7,%8,%9,%10,%11,%12,%13,%14,%15}, %16, %17, %18, 1, 1, 0, 0;"
        : "+f"(d[0]), "+f"(d[1]), "+f"(d[2]), "+f"(d[3]), "+f"(d[4]), "+f"(d[5]), "+f"(d[6]), "+f"(d[7]),
          "+f"(d[8]), "+f"(d[9]), "+f"(d[10]), "+f"(d[11]), "+f"(d[12]), "+f"(d[13]), "+f"(d[14]), "+f"(d[15])
        : "l"(da), "l"(db), "n"(ACC));
}
__device__ __forceinline__ void wg_fence() { asm volatile("wgmma.fence.sync.aligned;" ::: "memory"); }
__device__ __forceinline__ void wg_commit() { asm volatile("wgmma.commit_group.sync.aligned;" ::: "memory"); }
__device__ __forceinline__ void wg_wait0() { asm volatile("wgmma.wait_group.sync.aligned 0;" ::: "memory"); }
__device__ __forceinline__ void cluster_sync() { asm volatile("barrier.cluster.arrive.aligned;\nbarrier.cluster.wait.aligned;" ::: "memory"); }

#define STAMP(s, i) do {} while (0)
#define STAMPV(s, i, v) do {} while (0)

constexpr int XT_BYTES = 36864;
constexpr int O_XT = 0;
constexpr int O_AS = 3 * XT_BYTES;
constexpr int O_AF = O_AS + 16384;
constexpr int O_WP = O_AF + 4096;
constexpr int O_MF = O_WP + 2048;
constexpr int O_XP = O_MF + 9216;
constexpr int O_VX = O_XP + 8192;
constexpr int O_VM = O_VX + 16384;
constexpr int O_SC = O_VM + 2048;
constexpr int O_OF = O_SC + 2560;
constexpr int O_QM = O_OF + 2048;
constexpr int O_QKX = O_QM + 2048;
constexpr int O_KM = O_QKX + 16384;
constexpr int O_MISC = O_KM + 2048;
constexpr int O_BAR = O_MISC + 64;
constexpr int CHAIN_SMEM = O_BAR + 128;
static_assert(CHAIN_SMEM <= 232448, "smem");
constexpr int B_X = O_BAR, B_VX = O_BAR + 24, B_SC = O_BAR + 40, B_VM = O_BAR + 48;
constexpr float SM_SCALE = 0.08838834764831845f * 1.4426950408889634f;
constexpr uint32_t ONES = 0x3f803f80u;

__device__ __forceinline__ uint32_t opaque(uint32_t v) { uint32_t o; asm volatile("mov.u32 %0, %1;" : "=r"(o) : "r"(v)); return o; }
__device__ __forceinline__ void st_async128(uint32_t a, uint32_t x, uint32_t y, uint32_t z, uint32_t w, uint32_t bar) {
    asm volatile("st.async.shared::cluster.mbarrier::complete_tx::bytes.v4.b32 [%0], {%1,%2,%3,%4}, [%5];" :: "r"(a), "r"(x), "r"(y), "r"(z), "r"(w), "r"(bar) : "memory");
}
__device__ __forceinline__ void tma_x_tile(uint32_t sb, const CUtensorMap* tm, int r, int j, int slot) {
    asm volatile("{\n.reg .pred p;\nelect.sync _|p, 0xffffffff;\n"
        "@p mbarrier.arrive.expect_tx.shared::cta.b64 _, [%2], 36864;\n"
        "@p cp.async.bulk.tensor.2d.shared::cluster.global.mbarrier::complete_tx::bytes.multicast::cluster [%0], [%1, {%3, %4}], [%2], %7;\n"
        "@p cp.async.bulk.tensor.2d.shared::cluster.global.mbarrier::complete_tx::bytes.multicast::cluster [%0+4096], [%1, {%5, %4}], [%2], %7;\n"
        "@p cp.async.bulk.tensor.2d.shared::cluster.global.mbarrier::complete_tx::bytes.multicast::cluster [%0+8192], [%1, {%6, %4}], [%2], %7;\n}"
        :: "r"(sb + O_XT + slot * XT_BYTES + 3 * r * 4096), "l"(tm), "r"(sb + B_X + 8 * slot), "r"(192 * r), "r"(j * 32), "r"(192 * r + 64), "r"(192 * r + 128),
           "h"((unsigned short)7) : "memory");
}
__device__ __forceinline__ float quad_max(float v) {
    const float a = __shfl_xor_sync(~0u, v, 1), b = __shfl_xor_sync(~0u, v, 2), c = __shfl_xor_sync(~0u, v, 3);
    return fmaxf(fmaxf(v, a), fmaxf(b, c));
}
__device__ __forceinline__ void load_scores(float (&p)[10], uint32_t base, uint32_t stride, uint32_t l16) {
    const float4 a0 = lds128f(base + l16), b0 = lds128f(base + stride + l16);
    const float4 a1 = lds128f(base + 512 + l16), b1 = lds128f(base + stride + 512 + l16);
    const float2 a2 = lds64f(base + 1024 + (l16 >> 1)), b2 = lds64f(base + stride + 1024 + (l16 >> 1));
    p[0] = a2.x + b2.x; p[1] = a2.y + b2.y;
    p[2] = a0.x + b0.x; p[3] = a0.y + b0.y; p[4] = a0.z + b0.z; p[5] = a0.w + b0.w;
    p[6] = a1.x + b1.x; p[7] = a1.y + b1.y; p[8] = a1.z + b1.z; p[9] = a1.w + b1.w;
}
__device__ __forceinline__ float rcp_fast(float x) { float y; asm("rcp.approx.ftz.f32 %0, %1;" : "=f"(y) : "f"(x)); return y; }

__global__ void __cluster_dims__(3, 1, 1) __launch_bounds__(384, 1)
chain_kernel(const __grid_constant__ CUtensorMap tm_x,
             const __nv_bfloat16* __restrict__ x, const __nv_bfloat16* __restrict__ mem0,
             const __nv_bfloat16* __restrict__ Wq, const __nv_bfloat16* __restrict__ Wk,
             const __nv_bfloat16* __restrict__ Wv, const __nv_bfloat16* __restrict__ Wo) {
    extern __shared__ __align__(1024) uint8_t smem_raw[];
    const uint32_t sb = smem_u32(smem_raw);
    const int lane = threadIdx.x & 31;
    const int warp = __shfl_sync(~0u, threadIdx.x >> 5, 0);
    const int wg = warp >> 2, w = warp & 3;
    const int h = blockIdx.x / 3, r = blockIdx.x - 3 * h;

    if (threadIdx.x == 0) {
        if (sb & 1023u) __trap();
        for (int i = 0; i < 7; i++) mbar_init(sb + O_BAR + 8 * i, 1);
        asm volatile("fence.mbarrier_init.release.cluster;" ::: "memory");
    }
    if (blockIdx.x == 0) {
        for (int i = threadIdx.x; i < NSEG * 4 * 8; i += 384) g_flag[i] = 0;
        __threadfence();
    }
    __syncthreads();
    cluster_sync();
    asm volatile("griddepcontrol.launch_dependents;" ::: "memory");
    const uint32_t l16c = __shfl_sync(~0u, lane * 16, lane);

    if (wg < 2) {
#define KS(u) ((u) < 8 ? ((u) >> 1) + 4 * ((u) & 1) : (u) < 12 ? (u) : (u) < 20 ? 12 + (((u) - 12) >> 1) + 4 * ((u) & 1) : (u) < 24 ? (u) : (u) + 8)
        asm volatile("setmaxnreg.inc.sync.aligned.u32 184;");
        uint32_t a[144];
        uint32_t adr1;
        {
            const int g = lane >> 2, t = lane & 3;
#pragma unroll
            for (int tl = 0; tl < 2; tl++) {
                const int tile = tl ? wg : (wg ^ 1);
                const __nv_bfloat16* W = (r < 2) ? (tile == 0 ? Wq : Wk) : Wv;
                const int col = h * 128 + ((r < 2) ? 64 * r : 64 * tile) + 16 * w + 2 * g;
                const __nv_bfloat16* p = W + (size_t)(2 * t) * HD + col;
                const __nv_bfloat16* ps = p + (size_t)(384 * wg) * HD;
#pragma unroll
                for (int u = 0; u < (tl ? 28 : 8); u++) {
                    const __nv_bfloat16* q = (u < 8 ? ps : p) + (size_t)(16 * KS(u)) * HD;
                    a[32 * tl + 4 * u + 0] = ldg_nc32(q);
                    a[32 * tl + 4 * u + 1] = ldg_nc32(q + HD);
                    a[32 * tl + 4 * u + 2] = ldg_nc32(q + 8 * HD);
                    a[32 * tl + 4 * u + 3] = ldg_nc32(q + 9 * HD);
                }
            }
#pragma unroll
            for (int kk = 0; kk < 72; kk++) {
                uint32_t w0 = a[2 * kk], w1 = a[2 * kk + 1];
                a[2 * kk] = __byte_perm(w0, w1, 0x5410);
                a[2 * kk + 1] = __byte_perm(w0, w1, 0x7632);
            }
            float vmax = 0.f;
#pragma unroll
            for (int tl = 0; tl < 2; tl++) {
                float s0 = 0.f, s1 = 0.f;
#pragma unroll
                for (int kk = 16 * tl; kk < (tl ? 72 : 16); kk++) {
                    s0 += fabsf(__uint_as_float(a[2 * kk] << 16)) + fabsf(__uint_as_float(a[2 * kk] & 0xffff0000u));
                    s1 += fabsf(__uint_as_float(a[2 * kk + 1] << 16)) + fabsf(__uint_as_float(a[2 * kk + 1] & 0xffff0000u));
                }
                s0 += __shfl_xor_sync(~0u, s0, 1); s0 += __shfl_xor_sync(~0u, s0, 2);
                s1 += __shfl_xor_sync(~0u, s1, 1); s1 += __shfl_xor_sync(~0u, s1, 2);
                vmax = fmaxf(vmax, fmaxf(s0, s1));
            }
            uint32_t mx = __reduce_max_sync(~0u, __float_as_uint(2.f * vmax));
            sts32_if(lane, sb + O_MISC + 32 + 4 * warp, mx);
            bar_arrive(7, 384);
            const uint32_t as = sb + O_AS + wg * 8192 + (16 * w + g) * 128 + t * 4;
            sts32(as + (g << 4), a[32]);
            sts32(as + 1024 + (g << 4), a[33]);
            sts32(as + ((1 ^ g) << 4), a[34]);
            sts32(as + 1024 + ((1 ^ g) << 4), a[35]);
            sts128(sb + O_AF + warp * 512 + lane * 16, a[32], a[33], a[34], a[35]);
            fence_async_smem();
            bar_sync(1, 256);
            const uint32_t l = lane * 16;
            const int mi = lane >> 3, isk = (mi >> 1) ? wg : (wg ^ 1);
            adr1 = (r == 2) ? (sb + O_VM + warp * 256 + (l >> 1))
                            : (isk ? (sb + O_KM + w * 512 + wg * 256 + (mi & 1) * 128 + (l & 127))
                                   : (sb + O_QM + w * 512 + (mi & 1) * 256 + wg * 128 + (l & 127)));
            adr1 = __shfl_sync(~0u, adr1, lane);
        }
        int s3 = 2;
#pragma unroll 1
        for (int s = -1; s < NSEG; s++) {
            const uint32_t l16 = opaque(l16c);
            s3 = (s3 == 2) ? 0 : s3 + 1;
            if (s < 0) mbar_wait(sb + B_X, 0);
            const uint64_t desc0 = (uint64_t)(((sb + O_XT + s3 * XT_BYTES) & 0x3FFFF) >> 4) | (1ull << 16) | (64ull << 32) | (1ull << 62);
            uint32_t km0 = 0, km1 = 0;
            if (s >= 0) {
                { const uint4 v = lds128(sb + O_AF + warp * 512 + l16); a[32] = v.x; a[33] = v.y; a[34] = v.z; a[35] = v.w; }
                float co[4], cw[3][4];
                uint4 b[14];
                float inv;
#define GORD(i) ((i) == 0 ? 0 : (i) == 1 ? 1 : (i) == 5 ? 2 : (i) == 9 ? 3 : (i) < 5 ? (i) + 2 : (i) < 9 ? (i) + 1 : (i))
                auto qkv_mma = [&](int i) {
                    const int gi = GORD(i), u = 8 * gi, n0 = 2 * i, n1 = 2 * i + 1;
                    if (gi < 4) {
                        if (i == 0) mma16816_z(co, a[u], a[u + 1], a[u + 2], a[u + 3], b[0].x, b[0].y);
                        else mma16816(co, a[u], a[u + 1], a[u + 2], a[u + 3], b[i].x, b[i].y);
                    }
                    if (n0 < 3) mma16816_z(cw[n0 % 3], a[32 + u], a[32 + u + 1], a[32 + u + 2], a[32 + u + 3], b[i].x, b[i].y);
                    else mma16816(cw[n0 % 3], a[32 + u], a[32 + u + 1], a[32 + u + 2], a[32 + u + 3], b[i].x, b[i].y);
                    if (n1 < 3) mma16816_z(cw[n1 % 3], a[32 + u + 4], a[32 + u + 5], a[32 + u + 6], a[32 + u + 7], b[i].z, b[i].w);
                    else mma16816(cw[n1 % 3], a[32 + u + 4], a[32 + u + 5], a[32 + u + 6], a[32 + u + 7], b[i].z, b[i].w);
                    if (gi < 4) mma16816(co, a[u + 4], a[u + 5], a[u + 6], a[u + 7], b[i].z, b[i].w);
                };
                const uint32_t mf = sb + O_MF + l16, mfs = mf + wg * 6144;
                if (VSEND == 0 && r == 2) {
                    asm volatile("{\n.reg .pred p;\ncp.async.bulk.wait_group 0;\nelect.sync _|p, 0xffffffff;\nsetp.lt.and.s32 p, %4, 63, p;\n"
                        "@p cp.async.bulk.shared::cluster.global.mbarrier::complete_tx::bytes.multicast::cluster [%1], [%0], 1024, [%2], %3;\n"
                        "fence.proxy.async.global;\n}"
                        :: "l"(reinterpret_cast<char*>(g_qkv) + (size_t)(s * NH + h) * 24576 + 16384 + warp * 1024), "r"(sb + O_VX + (s & 1) * 8192 + warp * 1024),
                           "r"(sb + B_VX + 8 * (s & 1)), "h"((unsigned short)3), "r"(s) : "memory");
                }
                bar_sync(2, 384);
                if (warp == 0) STAMP(s, 0);
                auto qkv_ld = [&](int i) { b[i] = GORD(i) < 4 ? lds128v(mfs + GORD(i) * 512) : lds128v(mf + (GORD(i) < 12 ? GORD(i) : GORD(i) + 4) * 512); };
#pragma unroll
                for (int i = 0; i < 5; i++) qkv_ld(i);
                if (QF >= 1) sched_fence<2>(h);
#pragma unroll
                for (int i = 0; i < 4; i++) { qkv_mma(i); qkv_ld(5 + i); }
                if (QF >= 2) sched_fence<3>(h);
#pragma unroll
                for (int i = 4; i < 9; i++) { qkv_mma(i); qkv_ld(5 + i); }
                inv = __uint_as_float(lds32(sb + O_MISC));
                if (QF >= 3) sched_fence<4>(h);
#pragma unroll
                for (int i = 9; i < 14; i++) qkv_mma(i);
#pragma unroll
                for (int i = 0; i < 4; i++) cw[0][i] += cw[1][i] + cw[2][i];
                if (r < 2) {
                    const uint32_t o0 = pack_bf16(co[0] * inv, co[1] * inv), o1 = pack_bf16(co[2] * inv, co[3] * inv);
                    const uint32_t w0 = pack_bf16(cw[0][0] * inv, cw[0][1] * inv), w1 = pack_bf16(cw[0][2] * inv, cw[0][3] * inv);
                    stsm4t(adr1, o0, o1, w0, w1);
                    km0 = wg ? w0 : o0; km1 = wg ? w1 : o1;
                    if (warp == 0) STAMP(s, 1);
                    asm volatile("{\n.reg .pred p;\nsetp.ge.u32 p, %0, 3;\n@p bar.arrive 1, 256;\n}" :: "r"(warp) : "memory");
                    if (warp < 3 && s < NSEG - 1) {
                        uint4 q[4], k[4];
                        const uint32_t ka = sb + (warp == 2 ? O_KM : O_QKX + (s & 1) * 8192 + 4096 + warp * 2048) + l16;
#pragma unroll
                        for (int i = 0; i < 4; i++) k[i] = ldsm4(ka + i * 512);
                        const uint32_t dst = sb + O_SC + r * 1280 + warp * 512 + (l16 >> 1);
                        bar_sync(1, 256);
#pragma unroll
                        for (int i = 0; i < 4; i++) q[i] = ldsm4(sb + O_QM + i * 512 + l16);
                        if (warp == 2) {
#pragma unroll
                            for (int i = 0; i < 4; i++) k[i] = ldsm4(ka + i * 512);
                        }
                        float s0[4], s1[4], t0[4], t1[4];
                        mma16816_z(s0, q[0].x, q[0].y, q[0].z, q[0].w, k[0].x, k[0].y);
                        mma16816_z(s1, q[0].x, q[0].y, q[0].z, q[0].w, k[0].z, k[0].w);
                        mma16816_z(t0, q[1].x, q[1].y, q[1].z, q[1].w, k[1].x, k[1].y);
                        mma16816_z(t1, q[1].x, q[1].y, q[1].z, q[1].w, k[1].z, k[1].w);
                        mma16816(s0, q[2].x, q[2].y, q[2].z, q[2].w, k[2].x, k[2].y);
                        mma16816(s1, q[2].x, q[2].y, q[2].z, q[2].w, k[2].z, k[2].w);
                        mma16816(t0, q[3].x, q[3].y, q[3].z, q[3].w, k[3].x, k[3].y);
                        mma16816(t1, q[3].x, q[3].y, q[3].z, q[3].w, k[3].z, k[3].w);
                        const float v0 = (s0[0] + s0[2]) + (t0[0] + t0[2]), v1 = (s0[1] + s0[3]) + (t0[1] + t0[3]);
                        const float v2 = (s1[0] + s1[2]) + (t1[0] + t1[2]), v3 = (s1[1] + s1[3]) + (t1[1] + t1[3]);
                        if (warp < 2) {
                            const uint32_t dv = dst + (l16 >> 1);
                            st_async128(mapa(dv, 2), __float_as_uint(v0), __float_as_uint(v1), __float_as_uint(v2), __float_as_uint(v3), mapa(sb + B_SC, 2));
                            st_async128(mapa(dv, r ^ 1), __float_as_uint(v0), __float_as_uint(v1), __float_as_uint(v2), __float_as_uint(v3), mapa(sb + B_SC, r ^ 1));
                            st_async128(mapa(dv, r), __float_as_uint(v0), __float_as_uint(v1), __float_as_uint(v2), __float_as_uint(v3), mapa(sb + B_SC, r));
                        } else {
                            st_async64(mapa(dst, 2), __float_as_uint(v0 + v2), __float_as_uint(v1 + v3), mapa(sb + B_SC, 2));
                            st_async64(mapa(dst, r ^ 1), __float_as_uint(v0 + v2), __float_as_uint(v1 + v3), mapa(sb + B_SC, r ^ 1));
                            st_async64(mapa(dst, r), __float_as_uint(v0 + v2), __float_as_uint(v1 + v3), mapa(sb + B_SC, r));
                        }
                        if (warp == 2) STAMP(s, 2);
                    } else if (warp < 3) {
                        bar_sync(1, 256);
                    }
                } else {
                    sts128f(sb + O_XP + warp * 512 + l16, co[0], co[1], co[2], co[3]);
                    bar_sync(8 + w, 64);
                    const float4 o = lds128f(sb + O_XP + (warp ^ 4) * 512 + l16);
                    km0 = pack_bf16((cw[0][0] + o.x) * inv, (cw[0][1] + o.y) * inv);
                    km1 = pack_bf16((cw[0][2] + o.z) * inv, (cw[0][3] + o.w) * inv);
                    if (warp == 0) STAMP(s, 1);
                    if (s < NSEG - 1) {
                        st_async64(mapa(adr1, 0), km0, km1, mapa(sb + B_VM, 0));
                        st_async64(mapa(adr1, 1), km0, km1, mapa(sb + B_VM, 1));
                        st_async64(mapa(adr1, 2), km0, km1, mapa(sb + B_VM, 2));
                    }
                    if (warp == 0) STAMP(s, 2);
                }
            }
            auto store_qk = [&]() {
                asm volatile("{\n.reg .pred p;\nelect.sync _|p, 0xffffffff;\n"
                    "@p cp.async.bulk.global.shared::cta.bulk_group [%0], [%1], 8192;\n@p cp.async.bulk.commit_group;\n}"
                    :: "l"(reinterpret_cast<char*>(g_qkv) + (size_t)(s * NH + h) * 24576 + r * 8192), "r"(sb + O_QKX + (s & 1) * 8192) : "memory");
            };
            auto store_kvm = [&]() {
                char* p = reinterpret_cast<char*>(g_kvm) + (size_t)(s * NH + h) * 6144 + (r < 2 ? wg * 2048 + (r * 4 + w) * 256 : 4096 + warp * 256) + (l16 >> 1);
                *reinterpret_cast<uint2*>(p) = make_uint2(km0, km1);
            };
            if (s >= 0) bar_sync(3, 384);
            if (s == NSEG - 1) {
                store_kvm();
                if (warp == 3 && r < 2) {
                    store_qk();
                    asm volatile("cp.async.bulk.wait_group 0;\nfence.proxy.async.global;" ::: "memory");
                }
            } else {
                const int j = s + 1;
#define XDESC(u) (((u) < 8 ? descs : desc0) + (uint64_t)(((KS(u) >> 2) * 4096 + (KS(u) & 3) * 32) >> 4))
                const uint64_t descs = desc0 + (uint64_t)(wg * (6 * 4096 >> 4));
                float d[16];
                wg_fence();
#pragma unroll
                for (int u = 0; u < 8; u++) {
                    if (u == 0) wgmma_n32_rs<0>(d, a[0], a[1], a[2], a[3], XDESC(0));
                    else wgmma_n32_rs<1>(d, a[4 * u], a[4 * u + 1], a[4 * u + 2], a[4 * u + 3], XDESC(u));
                }
                wg_commit();
                wg_wait0();
                if (warp == 0) STAMP(s, 15);
                if (s >= 0) bar_sync(4, 384);
#pragma unroll
                for (int q = 0; q < 2; q++)
                    sts128(sb + O_XP + warp * 1024 + q * 512 + l16, pack_bf16(d[8 * q], d[8 * q + 1]), pack_bf16(d[8 * q + 2], d[8 * q + 3]),
                           pack_bf16(d[8 * q + 4], d[8 * q + 5]), pack_bf16(d[8 * q + 6], d[8 * q + 7]));
                if (s >= 0) {
                    store_kvm();
                    if (warp == 3) asm volatile("cp.async.bulk.wait_group 0;\nfence.proxy.async.global;" ::: "memory");
                    if (warp == 1 && s + 2 < NSEG) tma_x_tile(sb, &tm_x, r, s + 2, s3 == 2 ? 0 : s3 + 1);
                }
                bar_sync(12, 256);
#pragma unroll
                for (int q = 0; q < 2; q++) {
                    const uint4 o = lds128(sb + O_XP + (warp ^ 4) * 1024 + q * 512 + l16);
                    d[8 * q] = __uint_as_float(o.x << 16); d[8 * q + 1] = __uint_as_float(o.x & 0xffff0000u);
                    d[8 * q + 2] = __uint_as_float(o.y << 16); d[8 * q + 3] = __uint_as_float(o.y & 0xffff0000u);
                    d[8 * q + 4] = __uint_as_float(o.z << 16); d[8 * q + 5] = __uint_as_float(o.z & 0xffff0000u);
                    d[8 * q + 6] = __uint_as_float(o.w << 16); d[8 * q + 7] = __uint_as_float(o.w & 0xffff0000u);
                }
                if (s >= 0) {
                    if (warp == 6 && (s & 3) == 0 && s >= 4)
                        asm volatile("{\n.reg .pred p;\nsetp.eq.u32 p, %1, 0;\n@p red.release.gpu.global.inc.u32 [%0], 0x7fffffff;\n}"
                                     :: "l"(&g_flag[((s - 1) * 4 + (h >> 3)) * 8]), "r"(l16) : "memory");
                    asm volatile("{\n.reg .pred p;\nsetp.eq.u32 p, %0, 0;\n@p bar.sync 5, 256;\n@!p bar.sync 13, 256;\n}" :: "r"(wg) : "memory");
                }
                const uint64_t da0 = (uint64_t)(((sb + O_AS + wg * 8192) & 0x3FFFF) >> 4) | (1ull << 16) | (64ull << 32) | (1ull << 62);
                wg_fence();
                wgmma_n32_ss<1>(d, da0, XDESC(0));
#pragma unroll
                for (int u = 1; u < 28; u++) wgmma_n32_rs<1>(d, a[32 + 4 * u], a[32 + 4 * u + 1], a[32 + 4 * u + 2], a[32 + 4 * u + 3], XDESC(u));
                wg_commit();
                wg_wait0();
                if (warp == 3 && r < 2 && s >= 0) store_qk();
                if (warp == 4) STAMP(s, 3);
                uint32_t e[8];
#pragma unroll
                for (int i = 0; i < 8; i++) e[i] = pack_bf16(d[2 * i], d[2 * i + 1]);
                if (r < 2) {
                    const uint32_t base = sb + O_QKX + (j & 1) * 8192 + wg * 4096 + w * 512 + l16;
                    stsm4t(base, e[0], wg ? e[1] : e[2], wg ? e[2] : e[1], e[3]);
                    stsm4t(base + 2048, e[4], wg ? e[5] : e[6], wg ? e[6] : e[5], e[7]);
                    fence_async_smem();
                } else {
                    const uint32_t base = sb + O_VX + (j & 1) * 8192 + warp * 1024 + l16;
                    sts128(base, e[0], e[1], e[2], e[3]);
                    sts128(base + 512, e[4], e[5], e[6], e[7]);
                    fence_async_smem();
                    bar_arrive(14, 288);
                }
                if (warp == 7) STAMP(s, 4);
            }
        }
        bar_arrive(7, 384);
    } else {
        asm volatile("setmaxnreg.dec.sync.aligned.u32 136;");
        const int c = w;
        uint32_t a[96];
        uint32_t mmax = 0;
        {
            const int g = lane >> 2, t = lane & 3, t2 = threadIdx.x - 256;
            if (c == 0) {
                tma_x_tile(sb, &tm_x, r, 0, 0);
                tma_x_tile(sb, &tm_x, r, 1, 1);
                mbar_expect_if(lane, sb + B_SC, 2560);
                mbar_expect_if(lane, sb + B_VM, 2048);
                if (r < 2) mbar_expect_if(lane, sb + B_VX, 8192);
                sts32_if(lane, sb + O_MISC, __float_as_uint(1.0f));
                sts32_if(lane, sb + O_MISC + 12, __float_as_uint(SM_SCALE));
            }
#pragma unroll
            for (int i = 0; i < 4; i++) g_acc[(blockIdx.x * 64 + i * 16 + (t2 >> 3)) * 16 + (t2 & 7)] = make_uint4(0, 0, 0, 0);
#pragma unroll
            for (int tau = 0; tau < 3; tau++) {
                uint32_t v[6];
#pragma unroll
                for (int i = 0; i < 3; i++) {
                    const uint32_t* p = reinterpret_cast<const uint32_t*>(mem0 + g * DM + 16 * (12 * tau + 4 * i + c) + 2 * t);
                    v[2 * i] = __ldg(p); v[2 * i + 1] = __ldg(p + 4);
                    mmax = __vmaxu2(mmax, __vmaxu2(v[2 * i] & 0x7fff7fffu, v[2 * i + 1] & 0x7fff7fffu));
                }
                sts128(sb + O_MF + tau * 3072 + c * 512 + lane * 16, v[0], v[1], v[2], v[3]);
                sts64(sb + O_MF + tau * 3072 + 2048 + (c >> 1) * 512 + lane * 16 + (c & 1) * 8, v[4], v[5]);
            }
            mmax = max(mmax << 16, mmax & 0xffff0000u);
            bar_arrive(2, 384);
            uint32_t xm = 0;
            const uint4* xp = reinterpret_cast<const uint4*>(x) + blockIdx.x * 1536 + t2;
#pragma unroll
            for (int i = 0; i < 12; i++) {
                uint4 v = __ldg(xp + i * 128);
                xm = __vmaxu2(xm, __vmaxu2(__vmaxu2(v.x & 0x7fff7fffu, v.y & 0x7fff7fffu), __vmaxu2(v.z & 0x7fff7fffu, v.w & 0x7fff7fffu)));
            }
            xm = __reduce_max_sync(~0u, max(xm << 16, xm & 0xffff0000u));

            const __nv_bfloat16* p = Wo + (size_t)(h * 128 + 4 * t) * DM + 192 * r + 16 * c + 2 * g;
#pragma unroll
            for (int i = 0; i < 3; i++)
#pragma unroll
                for (int eb = 0; eb < 8; eb++)
#pragma unroll
                    for (int j = 0; j < 4; j++) a[(i * 8 + eb) * 4 + j] = ldg_nc32(p + (16 * eb + ((j & 1) * 2 + (j >> 1))) * DM + 64 * i);
#pragma unroll
            for (int kk = 0; kk < 48; kk++) {
                uint32_t w0 = a[2 * kk], w1 = a[2 * kk + 1];
                a[2 * kk] = __byte_perm(w0, w1, 0x5410);
                a[2 * kk + 1] = __byte_perm(w0, w1, 0x7632);
            }
            sts128(sb + O_WP + c * 512 + lane * 16, a[92], a[93], a[94], a[95]);
            float wmax = 0.f;
#pragma unroll
            for (int i = 0; i < 3; i++) {
                float s0 = 0.f, s1 = 0.f;
#pragma unroll
                for (int kk = 16 * i; kk < 16 * i + 16; kk++) {
                    s0 += fabsf(__uint_as_float(a[2 * kk] << 16)) + fabsf(__uint_as_float(a[2 * kk] & 0xffff0000u));
                    s1 += fabsf(__uint_as_float(a[2 * kk + 1] << 16)) + fabsf(__uint_as_float(a[2 * kk + 1] & 0xffff0000u));
                }
                s0 += __shfl_xor_sync(~0u, s0, 1); s0 += __shfl_xor_sync(~0u, s0, 2);
                s1 += __shfl_xor_sync(~0u, s1, 1); s1 += __shfl_xor_sync(~0u, s1, 2);
                wmax = fmaxf(wmax, fmaxf(s0, s1));
            }
            uint32_t wm = __reduce_max_sync(~0u, __float_as_uint(wmax));
            sts32_if(lane, sb + O_OF + 4 * c, wm); sts32_if(lane, sb + O_OF + 16 + 4 * c, xm);
            __threadfence();
            bar_sync(7, 384);
            if (c == 0) {
                const uint4 wq = lds128(sb + O_OF), xq = lds128(sb + O_OF + 16), v0 = lds128(sb + O_MISC + 32), v1 = lds128(sb + O_MISC + 48);
                const uint32_t w1 = max(max(wq.x, wq.y), max(wq.z, wq.w)), x1 = max(max(xq.x, xq.y), max(xq.z, xq.w));
                const uint32_t vv = (r < 2) ? 0u : max(max(max(v0.x, v0.y), max(v0.z, v0.w)), max(max(v1.x, v1.y), max(v1.z, v1.w)));
                unsigned old = 0;
                asm volatile("{\n.reg .pred p;\nsetp.eq.u32 p, %6, 0;\n@p st.global.v4.u32 [%1], {%2,%3,%4,%4};\nfence.acq_rel.gpu;\n@p atom.relaxed.gpu.global.add.u32 %0, [%5], 1;\n}"
                             : "+r"(old) : "l"(&g_norm[blockIdx.x * 4]), "r"(w1), "r"(vv), "r"(x1), "l"(&g_gridbar), "r"(lane) : "memory");
                old = __shfl_sync(~0u, old, 0);
                const unsigned target = (old / 96u + 1u) * 96u;
                asm volatile("{\n.reg .pred p;\n.reg .u32 n, v;\nmov.u32 n, 0;\n"
                             "G_%=: ld.acquire.gpu.global.u32 v, [%0];\nsub.u32 v, v, %1;\nsetp.ge.s32 p, v, 0;\n@p bra.uni E_%=;\n"
                             "add.u32 n, n, 1;\nsetp.lt.u32 p, n, 4000000;\n@p bra.uni G_%=;\ntrap;\nE_%=:\n}" :: "l"(&g_gridbar), "r"(target) : "memory");
                uint4 n0 = ldg_relaxed128(&g_norm[lane * 4]), n1 = ldg_relaxed128(&g_norm[(lane + 32) * 4]), n2 = ldg_relaxed128(&g_norm[(lane + 64) * 4]);
                const float fw = __uint_as_float(__reduce_max_sync(~0u, max(n0.x, max(n1.x, n2.x))));
                const float fv = __uint_as_float(__reduce_max_sync(~0u, max(n0.y, max(n1.y, n2.y))));
                const float xmax = __uint_as_float(__reduce_max_sync(~0u, max(n0.z, max(n1.z, n2.z))));
                const float G = 36.f * fw * fv;
                sts32_if(lane, sb + O_MISC + 4, __float_as_uint(G)); sts32_if(lane, sb + O_MISC + 8, __float_as_uint(G * xmax));
            }
        }
        bar_sync(6, 128);
        int s3n = 1;
        uint32_t roff = __shfl_sync(~0u, (r * 4 + c) * 2048 + (lane >> 4) * 512 + (lane & 2) * 128 + (lane & 1) * 64 + (lane & 12) * 4, lane);
        uint32_t poff = __shfl_sync(~0u, c * 2048 + (lane & 4) * 256 + (lane >> 4) * 256 + (lane & 8) * 8 + (lane & 3) * 16, lane);
#pragma unroll 1
        for (int s = 0; s < NSEG; s++) {
            const uint32_t l16 = opaque(l16c);
            const uint32_t vxa = sb + O_VX + (s & 1) * 8192 + c * 2048 + l16;
            if (c == 0 && r == 2) {
                bar_sync(14, 288);
                asm volatile("{\n.reg .pred p;\nelect.sync _|p, 0xffffffff;\n"
                    "@p cp.async.bulk.global.shared::cta.bulk_group [%0], [%1], 8192;\n@p cp.async.bulk.commit_group;\n"
                    "cp.async.bulk.wait_group 0;\nsetp.lt.and.s32 p, %4, 63, p;\n"
                    "@p cp.async.bulk.shared::cluster.global.mbarrier::complete_tx::bytes.multicast::cluster [%1], [%0], 8192, [%2], %3;\n"
                    "fence.proxy.async.global;\n}"
                    :: "l"(reinterpret_cast<char*>(g_qkv) + (size_t)(s * NH + h) * 24576 + 16384), "r"(sb + O_VX + (s & 1) * 8192),
                       "r"(sb + B_VX + 8 * (s & 1)), "h"((unsigned short)3), "r"(s) : "memory");
            }
            if (s == NSEG - 1) { bar_sync(3, 384); break; }
            uint4 vx[4];
            sts32_if(l16, sb + O_MISC + 16 + 4 * c, __reduce_max_sync(~0u, mmax));
            if (c == 0) STAMP(s, 5);
            {
                bar_sync(6, 128);
                const uint4 mm = lds128(sb + O_MISC + 16), cf = lds128(sb + O_MISC);
                const float bound = fmaxf(__uint_as_float(cf.z), __uint_as_float(cf.y) * (__uint_as_float(max(max(mm.x, mm.y), max(mm.z, mm.w))) * __uint_as_float(cf.x)));
                const uint32_t ebits = min(max(__float_as_uint(bound) & 0x7f800000u, 21u << 23), 254u << 23);
                mbar_wait(sb + B_X + 8 * s3n, ((s + 1) / 3) & 1);
                s3n = (s3n == 2) ? 0 : s3n + 1;
                bar_sync(3, 384);
                if (r < 2) mbar_wait(sb + B_VX + 8 * (s & 1), (s >> 1) & 1);
                vx[0] = lds128(vxa); vx[2] = lds128(vxa + 1024);
                mbar_wait(sb + B_VM, s & 1);
                const uint4 vm = lds64x2(sb + O_VM + c * 512 + (l16 >> 1));
                if (c == 0) STAMP(s, 13);
                mbar_wait(sb + B_SC, s & 1);
                if (c == 0) STAMP(s, 6);
                float p[10];
                load_scores(p, sb + O_SC, 1280, l16);
                float mx = fmaxf(fmaxf(fmaxf(p[0], p[1]), fmaxf(p[2], p[3])), fmaxf(fmaxf(p[4], p[5]), fmaxf(p[6], p[7])));
                mx = quad_max(fmaxf(mx, fmaxf(p[8], p[9])));
                vx[1] = lds128(vxa + 512); vx[3] = lds128(vxa + 1536);
                bar_arrive(4, 384);
                const float sc = __uint_as_float(lds32(sb + O_MISC + 12));
                const float mo = mx * SM_SCALE;
                uint32_t P[5];
#pragma unroll
                for (int n = 0; n < 5; n++) P[n] = pack_bf16(ex2(fmaf(p[2 * n], SM_SCALE, -mo)), ex2(fmaf(p[2 * n + 1], n == 4 ? sc : SM_SCALE, -mo)));
                if (c == 0) STAMP(s, 7);
                float o0[4], o1[4], sm[4];
                mma1688_z(sm, ONES, ONES, P[0]);
                mma1688_z(o0, vm.x, vm.y, P[0]);
                mma1688_z(o1, vm.z, vm.w, P[0]);
                mma16816(sm, ONES, ONES, ONES, ONES, P[1], P[2]);
                mma16816(o0, vx[0].x, vx[0].y, vx[0].z, vx[0].w, P[1], P[2]);
                mma16816(o1, vx[2].x, vx[2].y, vx[2].z, vx[2].w, P[1], P[2]);
                mma16816(sm, ONES, ONES, ONES, ONES, P[3], P[4]);
                mma16816(o0, vx[1].x, vx[1].y, vx[1].z, vx[1].w, P[3], P[4]);
                mma16816(o1, vx[3].x, vx[3].y, vx[3].z, vx[3].w, P[3], P[4]);
                const float sig = __uint_as_float((268u << 23) - ebits);
                const float r0 = rcp_fast(sm[0]) * sig, r1 = rcp_fast(sm[1]) * sig;
                stsm4t(sb + O_OF + c * 512 + l16, pack_bf16(o0[0] * r0, o0[1] * r1), pack_bf16(o0[2] * r0, o0[3] * r1),
                       pack_bf16(o1[0] * r0, o1[1] * r1), pack_bf16(o1[2] * r0, o1[3] * r1));
                bar_sync(6, 128);
                uint4 ob[4];
#pragma unroll
                for (int q = 0; q < 4; q++) ob[q] = ldsm4(sb + O_OF + q * 512 + l16);
                { const uint4 v = lds128(sb + O_WP + c * 512 + l16); a[92] = v.x; a[93] = v.y; a[94] = v.z; a[95] = v.w; }
                float m0[3][4], m1[3][4];
#pragma unroll
                for (int q = 0; q < 4; q++) {
#pragma unroll
                    for (int i = 0; i < 3; i++) {
                        const int k0 = (i * 8 + 2 * q) * 4;
                        if (q == 0) mma16816_z(m0[i], a[k0], a[k0 + 1], a[k0 + 2], a[k0 + 3], ob[q].x, ob[q].y);
                        else mma16816(m0[i], a[k0], a[k0 + 1], a[k0 + 2], a[k0 + 3], ob[q].x, ob[q].y);
                    }
#pragma unroll
                    for (int i = 0; i < 3; i++) {
                        const int k1 = (i * 8 + 2 * q + 1) * 4;
                        if (q == 0) mma16816_z(m1[i], a[k1], a[k1 + 1], a[k1 + 2], a[k1 + 3], ob[q].z, ob[q].w);
                        else mma16816(m1[i], a[k1], a[k1 + 1], a[k1 + 2], a[k1 + 3], ob[q].z, ob[q].w);
                    }
                }
                asm volatile("red.relaxed.gpu.global.add.noftz.v4.f16x2 [%0], {%1,%2,%3,%4};" :: "l"(reinterpret_cast<char*>(g_acc) + roff),
                    "r"(pack_f16(m0[0][0] + m1[0][0], m0[0][2] + m1[0][2])), "r"(pack_f16(m0[1][0] + m1[1][0], m0[1][2] + m1[1][2])),
                    "r"(pack_f16(m0[2][0] + m1[2][0], m0[2][2] + m1[2][2])), "r"(0x3c00u) : "memory");
                asm volatile("red.relaxed.gpu.global.add.noftz.v4.f16x2 [%0], {%1,%2,%3,%4};" :: "l"(reinterpret_cast<char*>(g_acc) + roff + 1024),
                    "r"(pack_f16(m0[0][1] + m1[0][1], m0[0][3] + m1[0][3])), "r"(pack_f16(m0[1][1] + m1[1][1], m0[1][3] + m1[1][3])),
                    "r"(pack_f16(m0[2][1] + m1[2][1], m0[2][3] + m1[2][3])), "r"(0x3c00u) : "memory");
                const unsigned t_red = clk();
                bar_arrive(5, 256);
                bar_arrive(13, 256);
                {
                    const uint32_t bar = sb + (c == 0 ? B_SC : c == 1 ? B_VM : B_VX + 8 * ((s + 1) & 1));
                    mbar_expect_if(l16 | (uint32_t)(c == 3 || (c == 2 && r == 2)), bar, c == 0 ? 2560 : c == 1 ? 2048 : 8192);
                }
                sts32_if(l16 | (c ^ 3), sb + O_MISC, ebits - (14u << 23));
                if (c == 0) STAMPV(s, 8, t_red);
                const char* pbase = reinterpret_cast<const char*>(g_acc) + poff;
                spin_until(t_red, D_WAIT);
                uint4 v[6];
#pragma unroll
                for (int i = 0; i < 6; i++) v[i] = ldg_relaxed128(pbase + (i >> 1) * 8192 + (i & 1) * 512);
                int nretry = 0;
                auto hand_over = [&]() -> uint32_t {
                    uint32_t ok = 0;
#pragma unroll
                    for (int tau = 0; tau < 3; tau++) {
                        if (tau == 1) sched_fence<0>(h);
                        if (tau == 2) {
                            sched_fence<1>(h);
                            asm volatile("{\n.reg .pred p, q;\n.reg .b32 x;\nlop3.b32 x, %1, %2, %3, 0x80;\nlop3.b32 x, x, %4, %5, 0x80;\nand.b32 x, x, %6;\n"
                                         "setp.eq.u32 p, x, 0x5000;\nvote.sync.all.pred q, p, 0xffffffff;\nselp.u32 %0, 1, 0, q;\n}"
                                         : "=r"(ok) : "r"(v[0].w), "r"(v[1].w), "r"(v[2].w), "r"(v[3].w), "r"(v[4].w), "r"(v[5].w));
                        }
                        v[2 * tau].x = f16x2_to_bf16x2(v[2 * tau].x); v[2 * tau + 1].x = f16x2_to_bf16x2(v[2 * tau + 1].x);
                        v[2 * tau].y = f16x2_to_bf16x2(v[2 * tau].y); v[2 * tau + 1].y = f16x2_to_bf16x2(v[2 * tau + 1].y);
                        v[2 * tau].z = f16x2_to_bf16x2(v[2 * tau].z); v[2 * tau + 1].z = f16x2_to_bf16x2(v[2 * tau + 1].z);
                        sts128(sb + O_MF + tau * 3072 + c * 512 + l16, v[2 * tau].x, v[2 * tau + 1].x, v[2 * tau].y, v[2 * tau + 1].y);
                        sts64(sb + O_MF + tau * 3072 + 2048 + (c >> 1) * 512 + (c & 1) * 8 + l16, v[2 * tau].z, v[2 * tau + 1].z);
                    }
                    asm volatile("{\n.reg .pred p;\nsetp.ne.u32 p, %0, 0;\n@p bar.arrive 2, 384;\n}" :: "r"(ok) : "memory");
                    return ok;
                };
                if (!hand_over()) {
                    asm volatile("{\n.reg .pred p, q;\n.reg .u32 n, x;\nmov.u32 n, 0;\n"
                         "R_%=: ld.relaxed.gpu.global.v4.u32 {%0,%1,%2,%3}, [%25];\nld.relaxed.gpu.global.v4.u32 {%4,%5,%6,%7}, [%25+512];\n"
                         "ld.relaxed.gpu.global.v4.u32 {%8,%9,%10,%11}, [%25+8192];\nld.relaxed.gpu.global.v4.u32 {%12,%13,%14,%15}, [%25+8704];\n"
                         "ld.relaxed.gpu.global.v4.u32 {%16,%17,%18,%19}, [%25+16384];\nld.relaxed.gpu.global.v4.u32 {%20,%21,%22,%23}, [%25+16896];\n"
                         "add.u32 %24, %24, 1;\nand.b32 x, %3, %7;\nand.b32 x, x, %11;\nand.b32 x, x, %15;\nand.b32 x, x, %19;\nand.b32 x, x, %23;\n"
                         "setp.eq.u32 p, x, 0x5000;\nvote.sync.all.pred q, p, 0xffffffff;\n@q bra.uni K_%=;\n"
                         "add.u32 n, n, 1;\nsetp.lt.u32 q, n, 2000000;\n@q bra.uni R_%=;\ntrap;\nK_%=:\n}"
                         : "+r"(v[0].x), "+r"(v[0].y), "+r"(v[0].z), "+r"(v[0].w), "+r"(v[1].x), "+r"(v[1].y), "+r"(v[1].z), "+r"(v[1].w),
                           "+r"(v[2].x), "+r"(v[2].y), "+r"(v[2].z), "+r"(v[2].w), "+r"(v[3].x), "+r"(v[3].y), "+r"(v[3].z), "+r"(v[3].w),
                           "+r"(v[4].x), "+r"(v[4].y), "+r"(v[4].z), "+r"(v[4].w), "+r"(v[5].x), "+r"(v[5].y), "+r"(v[5].z), "+r"(v[5].w), "+r"(nretry)
                         : "l"(pbase) : "memory");
                    hand_over();
                }
                if (c == 0) STAMP(s, 12);
                if (c == 0) STAMPV(s, 14, nretry);
                mmax = absmax2(absmax2(absmax2(v[0].x, v[0].y), absmax2(v[0].z, v[1].x)), absmax2(absmax2(v[1].y, v[1].z), absmax2(v[2].x, v[2].y)));
                mmax = absmax2(mmax, absmax2(absmax2(absmax2(v[2].z, v[3].x), absmax2(v[3].y, v[3].z)), absmax2(absmax2(v[4].x, v[4].y), absmax2(v[4].z, v[5].x))));
                mmax = absmax2(mmax, absmax2(v[5].y, v[5].z)) & 0x7fff7fffu;
                mmax = max(mmax << 16, mmax & 0xffff0000u);
            }
            roff += 24576; poff += 24576;
        }
        {
            bar_sync(7, 384);
            if (c == 0)
                asm volatile("{\n.reg .pred p;\nsetp.eq.u32 p, %1, 0;\n@p red.release.gpu.global.inc.u32 [%0], 0x7fffffff;\n}"
                             :: "l"(&g_flag[(63 * 4 + (h >> 3)) * 8]), "r"(l16c) : "memory");
        }
    }
    cluster_sync();
}

__device__ float g_u[SEQ * 2 * DM];
__global__ void naive_gemm1(const __nv_bfloat16* x, const __nv_bfloat16* Bre, const __nv_bfloat16* Bim) {
    int p = blockIdx.x * 64 + threadIdx.x % 64, tk = blockIdx.y * 4 + threadIdx.x / 64;
    float sr = 0, si = 0;
    for (int d = 0; d < DM; d++) { float xv = __bfloat162float(x[tk * DM + d]); sr += xv * __bfloat162float(Bre[p * DM + d]); si += xv * __bfloat162float(Bim[p * DM + d]); }
    g_u[tk * 2 * DM + 2 * p] = sr; g_u[tk * 2 * DM + 2 * p + 1] = si;
}
__global__ void naive_scan(const __nv_bfloat16* Lre, const __nv_bfloat16* Lim, const __nv_bfloat16* logdt) {
    int p = blockIdx.x * 64 + threadIdx.x;
    float dt = __bfloat162float(__float2bfloat16(expf(__bfloat162float(logdt[p]))));
    float lr = __bfloat162float(Lre[p]), li = __bfloat162float(Lim[p]);
    float e = expf(dt * lr), br = e * cosf(dt * li), bi = e * sinf(dt * li);
    float den = lr * lr + li * li;
    float cr = ((br - 1.f) * lr + bi * li) / den, ci = (bi * lr - (br - 1.f) * li) / den;
    float hr = 0, hi = 0;
    for (int tk = 0; tk < SEQ; tk++) {
        float ur = g_u[tk * 2 * DM + 2 * p], ui = g_u[tk * 2 * DM + 2 * p + 1];
        float nr = br * hr - bi * hi + cr * ur - ci * ui, ni = br * hi + bi * hr + cr * ui + ci * ur;
        hr = nr; hi = ni;
        g_u[tk * 2 * DM + 2 * p] = hr; g_u[tk * 2 * DM + 2 * p + 1] = hi;
    }
}
__global__ void naive_gemm2(const __nv_bfloat16* x, const __nv_bfloat16* Cre, const __nv_bfloat16* Cim, const __nv_bfloat16* Dk, float* out) {
    int d = blockIdx.x * 64 + threadIdx.x % 64, tk = blockIdx.y * 4 + threadIdx.x / 64;
    float s = 0;
    for (int p = 0; p < DM; p++) s += g_u[tk * 2 * DM + 2 * p] * __bfloat162float(Cre[d * DM + p]) - g_u[tk * 2 * DM + 2 * p + 1] * __bfloat162float(Cim[d * DM + p]);
    out[tk * 1152 + d] = 2.f * s + __bfloat162float(__float2bfloat16(__bfloat162float(x[tk * DM + d]) * __bfloat162float(Dk[d])));
}
__device__ float frag_elem(const uint32_t* base, int e, int tok) {
    int eb = e >> 4, g = (e & 15) >> 1, hi = e & 1, j = tok >> 3, t = (tok & 7) >> 1, i = 2 * j + hi;
    uint32_t v = base[eb * 256 + (i >> 2) * 128 + (g * 4 + t) * 4 + (i & 3)];
    return __uint_as_float((tok & 1) ? (v & 0xffff0000u) : (v << 16));
}
__device__ float qk_elem(const uint32_t* base, int isk, int e, int tok) {
    int r = e >> 6, w = (e >> 4) & 3, g = (e & 15) >> 1, hi = e & 1, j = (tok >> 3) & 1;
    int mi = isk ? j * 2 + hi : hi * 2 + j;
    const __nv_bfloat16* p = reinterpret_cast<const __nv_bfloat16*>(base) + r * 4096 + isk * 2048 + (tok >> 4) * 1024 + w * 256 + mi * 64 + (tok & 7) * 8 + g;
    return __bfloat162float(*p);
}
__device__ float fragm_elem(const uint32_t* base, int e, int tok) {
    int eb = e >> 4, g = (e & 15) >> 1, hi = e & 1, t = tok >> 1;
    uint32_t v = base[eb * 64 + (g * 4 + t) * 2 + hi];
    return __uint_as_float((tok & 1) ? (v & 0xffff0000u) : (v << 16));
}
__global__ void naive_attn() {
    int s = blockIdx.x / NH, h = blockIdx.x % NH, q = threadIdx.x;
    const uint32_t* qkv = reinterpret_cast<const uint32_t*>(g_qkv) + (size_t)blockIdx.x * 6144;
    const uint32_t* kvm = reinterpret_cast<const uint32_t*>(g_kvm) + (size_t)blockIdx.x * 1536;
    float p[40], mx = -1e30f, sum = 0;
    for (int k = 0; k < 40; k++) {
        float d = 0;
        for (int e = 0; e < 128; e++)
            d += qk_elem(qkv, 0, e, q) * (k < 8 ? fragm_elem(kvm, e, k) + fragm_elem(kvm + 512, e, k) : qk_elem(qkv, 1, e, k - 8));
        p[k] = (k < 8 || k - 8 <= q) ? d * 0.08838834764831845f : -1e30f;
        mx = fmaxf(mx, p[k]);
    }
    for (int k = 0; k < 40; k++) { p[k] = expf(p[k] - mx); sum += p[k]; }
    __nv_bfloat16* ox = reinterpret_cast<__nv_bfloat16*>(g_ox);
    int tk = s * 32 + q;
    for (int e = 0; e < 128; e++) {
        float o = 0;
        for (int k = 0; k < 40; k++) o += p[k] * (k < 8 ? fragm_elem(kvm + 1024, e, k) : frag_elem(qkv + 4096, e, k - 8));
        int e0 = e & 63, ep = (e0 & 48) + (e0 & 1) * 8 + ((e0 & 15) >> 1);
        ox[((size_t)(h * 2 + (e >> 6)) * SEQ + tk) * 64 + (((ep >> 3) ^ (tk & 7)) << 3) + (ep & 7)] = __float2bfloat16(o / sum);
    }
}
__global__ void naive_wo(const __nv_bfloat16* Wo, float* out) {
    int d = blockIdx.x * 64 + threadIdx.x % 64, tk = blockIdx.y * 4 + threadIdx.x / 64;
    const __nv_bfloat16* ox = reinterpret_cast<const __nv_bfloat16*>(g_ox);
    float s = 0;
    for (int k = 0; k < HD; k++) {
        int hh = k >> 6, e0 = k & 63, e = (e0 & 48) + (e0 & 1) * 8 + ((e0 & 15) >> 1);
        s += __bfloat162float(ox[((size_t)hh * SEQ + tk) * 64 + (((e >> 3) ^ (tk & 7)) << 3) + (e & 7)]) * __bfloat162float(Wo[k * DM + d]);
    }
    out[tk * 1152 + DM + d] = s;
}

typedef CUresult (*EncodeFn)(CUtensorMap*, CUtensorMapDataType, cuuint32_t, void*, const cuuint64_t*, const cuuint64_t*, const cuuint32_t*, const cuuint32_t*,
                             CUtensorMapInterleave, CUtensorMapSwizzle, CUtensorMapL2promotion, CUtensorMapFloatOOBfill);
}

extern "C" void kernel_launch(void* const* d_in, const int* in_sizes, int n_in, void* d_out, int out_size) {
    typedef const __nv_bfloat16* bp;
    bp Ax = (bp)d_in[0], Lre = (bp)d_in[1], Lim = (bp)d_in[2], Bre = (bp)d_in[3], Bim = (bp)d_in[4], Cre = (bp)d_in[5], Cim = (bp)d_in[6],
       logdt = (bp)d_in[7], Dk = (bp)d_in[8], Bx = (bp)d_in[9], mem0 = (bp)d_in[10], Wq = (bp)d_in[11], Wk = (bp)d_in[12], Wv = (bp)d_in[13], Wo = (bp)d_in[14];
    float* out = (float*)d_out;
    static EncodeFn enc = nullptr;
    if (!enc) {
        void* fn = nullptr; cudaDriverEntryPointQueryResult qr;
        cudaGetDriverEntryPoint("cuTensorMapEncodeTiled", &fn, cudaEnableDefault, &qr);
        enc = (EncodeFn)fn;
        cudaFuncSetAttribute(chain_kernel, cudaFuncAttributeMaxDynamicSharedMemorySize, CHAIN_SMEM);
    }
    CUtensorMap tm_x;
    {
        cuuint64_t gd[2] = {DM, SEQ}; cuuint64_t gs[1] = {DM * 2}; cuuint32_t bd[2] = {64, 32}; cuuint32_t es[2] = {1, 1};
        enc(&tm_x, CU_TENSOR_MAP_DATA_TYPE_BFLOAT16, 2, (void*)Bx, gd, gs, bd, es, CU_TENSOR_MAP_INTERLEAVE_NONE, CU_TENSOR_MAP_SWIZZLE_128B,
            CU_TENSOR_MAP_L2_PROMOTION_L2_128B, CU_TENSOR_MAP_FLOAT_OOB_FILL_NONE);
    }
    cudaStream_t st = cudaStreamPerThread;
    chain_kernel<<<96, 384, CHAIN_SMEM, st>>>(tm_x, Bx, mem0, Wq, Wk, Wv, Wo);
    naive_gemm1<<<dim3(9, 512), 256, 0, st>>>(Ax, Bre, Bim);
    naive_scan<<<9, 64, 0, st>>>(Lre, Lim, logdt);
    naive_gemm2<<<dim3(9, 512), 256, 0, st>>>(Ax, Cre, Cim, Dk, out);
    naive_attn<<<NSEG * NH, 32, 0, st>>>();
    naive_wo<<<dim3(9, 512), 256, 0, st>>>(Wo, out);
}
```

```cpp
#include <cuda_runtime.h>
#include <cuda.h>
#include <cuda_bf16.h>
#include <cuda_fp16.h>
#include <stdint.h>

#define D_WAIT 700

#define VSEND 1
#define QF 0
namespace {

constexpr int DM = 576, NH = 32, SEQ = 2048, NSEG = 64, HD = 4096;

__device__ uint4 g_acc[64 * 96 * 16];
__device__ uint4 g_ox[NH * 2 * SEQ * 8];
__device__ uint4 g_qkv[NSEG * NH * 3 * 512];
__device__ uint2 g_kvm[NSEG * NH * 3 * 256];
constexpr int NFLAG = 4096;
__device__ __align__(16) unsigned g_flag[NFLAG];
__device__ unsigned g_ticket;
__device__ unsigned long long g_norm[96];

__device__ __forceinline__ uint32_t smem_u32(const void* p) { return (uint32_t)__cvta_generic_to_shared(p); }
__device__ __forceinline__ uint32_t mapa(uint32_t a, uint32_t r) { uint32_t o; asm("mapa.shared::cluster.u32 %0, %1, %2;" : "=r"(o) : "r"(a), "r"(r)); return o; }
__device__ __forceinline__ uint32_t mapa_v(uint32_t a, uint32_t r) { uint32_t o; asm volatile("mapa.shared::cluster.u32 %0, %1, %2;" : "=r"(o) : "r"(a), "r"(r)); return o; }
__device__ __forceinline__ unsigned clk() { unsigned long long c; asm volatile("mov.u64 %0, %%clock64;" : "=l"(c) :: "memory"); return (unsigned)c; }
__device__ __forceinline__ void mbar_init(uint32_t bar, uint32_t cnt) { asm volatile("mbarrier.init.shared::cta.b64 [%0], %1;" :: "r"(bar), "r"(cnt) : "memory"); }
__device__ __forceinline__ void mbar_expect(uint32_t bar, uint32_t bytes) { asm volatile("mbarrier.arrive.expect_tx.shared::cta.b64 _, [%0], %1;" :: "r"(bar), "r"(bytes) : "memory"); }
__device__ __forceinline__ void mbar_wait(uint32_t bar, uint32_t parity) {
    asm volatile("{\n.reg .pred p;\n.reg .u32 n;\nmov.u32 n, 0;\n"
                 "W_%=: mbarrier.try_wait.parity.shared::cta.b64 p, [%0], %1;\n@p bra.uni D_%=;\n"
                 "add.u32 n, n, 1;\nsetp.lt.u32 p, n, 4000000;\n@p bra.uni W_%=;\ntrap;\nD_%=:\n}" :: "r"(bar), "r"(parity) : "memory");
}
__device__ __forceinline__ void mbar_expect_if(uint32_t z, uint32_t bar, uint32_t bytes) {
    asm volatile("{\n.reg .pred p;\nsetp.eq.u32 p, %2, 0;\n@p mbarrier.arrive.expect_tx.shared::cta.b64 _, [%0], %1;\n}" :: "r"(bar), "r"(bytes), "r"(z) : "memory");
}
__device__ __forceinline__ void mbar_arrive_if(uint32_t z, uint32_t bar) {
    asm volatile("{\n.reg .pred p;\nsetp.eq.u32 p, %1, 0;\n@p mbarrier.arrive.shared::cta.b64 _, [%0];\n}" :: "r"(bar), "r"(z) : "memory");
}
__device__ __forceinline__ void sts32_if(uint32_t z, uint32_t a, uint32_t x) {
    asm volatile("{\n.reg .pred p;\nsetp.eq.u32 p, %2, 0;\n@p st.shared.u32 [%0], %1;\n}" :: "r"(a), "r"(x), "r"(z) : "memory");
}
template <int K> __device__ __forceinline__ void sched_fence(int v) {
    asm volatile("{\n.reg .pred p;\nsetp.ne.s32 p, %0, %1;\n@p bra.uni F_%=;\ntrap;\nF_%=:\n}" :: "r"(v), "n"(1000 + K) : "memory");
}
__device__ __forceinline__ void spin_until(unsigned t0, unsigned d) {
    asm volatile("{\n.reg .pred p;\n.reg .u64 c;\n.reg .u32 lo;\n"
                 "S_%=: mov.u64 c, %%clock64;\ncvt.u32.u64 lo, c;\nsub.u32 lo, lo, %0;\nsetp.lt.u32 p, lo, %1;\n@p bra.uni S_%=;\n}" :: "r"(t0), "r"(d) : "memory");
}
__device__ __forceinline__ void bar_sync(int id, int n) { asm volatile("bar.sync %0, %1;" :: "r"(id), "r"(n) : "memory"); }
__device__ __forceinline__ void bar_sync_sel(int sel, int id) {
    asm volatile("{\n.reg .pred p;\nsetp.eq.u32 p, %0, 0;\n@p bar.sync %1, %3;\n@!p bar.sync %2, %3;\n}" :: "r"(sel), "r"(id), "r"(id + 1), "n"(192) : "memory");
}
__device__ __forceinline__ void bar_arrive(int id, int n) { asm volatile("bar.arrive %0, %1;" :: "r"(id), "r"(n) : "memory"); }
__device__ __forceinline__ void fence_async_smem() { asm volatile("fence.proxy.async.shared::cta;" ::: "memory"); }
__device__ __forceinline__ uint32_t pack_bf16(float lo, float hi) { uint32_t r; asm("cvt.rn.bf16x2.f32 %0, %1, %2;" : "=r"(r) : "f"(hi), "f"(lo)); return r; }
__device__ __forceinline__ uint32_t pack_f16(float lo, float hi) { uint32_t r; asm("cvt.rn.f16x2.f32 %0, %1, %2;" : "=r"(r) : "f"(hi), "f"(lo)); return r; }
__device__ __forceinline__ uint32_t f16x2_to_bf16x2(uint32_t v) { float2 f = __half22float2(*reinterpret_cast<__half2*>(&v)); return pack_bf16(f.x, f.y); }
__device__ __forceinline__ float ex2(float x) { float y; asm("ex2.approx.ftz.f32 %0, %1;" : "=f"(y) : "f"(x)); return y; }
__device__ __forceinline__ float ex2v(float x) { float y; asm volatile("ex2.approx.ftz.f32 %0, %1;" : "=f"(y) : "f"(x)); return y; }
__device__ __forceinline__ uint32_t absmax2(uint32_t a, uint32_t b) {
    uint32_t r; asm("max.xorsign.abs.bf16x2 %0, %1, %2;" : "=r"(r) : "r"(a), "r"(b)); return r;
}
__device__ __forceinline__ uint32_t shl_v(uint32_t a, int n) { return a << n; }
__device__ __forceinline__ uint32_t max3u(uint32_t a, uint32_t b, uint32_t c) { return max(max(a, b), c); }
__device__ __forceinline__ uint4 lds128(uint32_t a) { uint4 v; asm volatile("ld.shared.v4.u32 {%0,%1,%2,%3}, [%4];" : "=r"(v.x), "=r"(v.y), "=r"(v.z), "=r"(v.w) : "r"(a) : "memory"); return v; }
__device__ __forceinline__ uint4 lds128v(uint32_t a) { uint4 v; asm volatile("ld.volatile.shared.v4.u32 {%0,%1,%2,%3}, [%4];" : "=r"(v.x), "=r"(v.y), "=r"(v.z), "=r"(v.w) : "r"(a) : "memory"); return v; }
__device__ __forceinline__ float4 lds128f(uint32_t a) { float4 v; asm volatile("ld.shared.v4.f32 {%0,%1,%2,%3}, [%4];" : "=f"(v.x), "=f"(v.y), "=f"(v.z), "=f"(v.w) : "r"(a) : "memory"); return v; }
__device__ __forceinline__ float2 lds64f(uint32_t a) { float2 v; asm volatile("ld.shared.v2.f32 {%0,%1}, [%2];" : "=f"(v.x), "=f"(v.y) : "r"(a) : "memory"); return v; }
__device__ __forceinline__ uint4 lds64x2(uint32_t a) { uint4 v; asm volatile("ld.shared.v2.u32 {%0,%1}, [%4];\nld.shared.v2.u32 {%2,%3}, [%4+256];" : "=r"(v.x), "=r"(v.y), "=r"(v.z), "=r"(v.w) : "r"(a) : "memory"); return v; }
__device__ __forceinline__ uint32_t lds32(uint32_t a) { uint32_t v; asm volatile("ld.shared.u32 %0, [%1];" : "=r"(v) : "r"(a) : "memory"); return v; }
__device__ __forceinline__ void sts128(uint32_t a, uint32_t x, uint32_t y, uint32_t z, uint32_t w) { asm volatile("st.shared.v4.u32 [%0], {%1,%2,%3,%4};" :: "r"(a), "r"(x), "r"(y), "r"(z), "r"(w) : "memory"); }
__device__ __forceinline__ void sts128f(uint32_t a, float x, float y, float z, float w) { asm volatile("st.shared.v4.f32 [%0], {%1,%2,%3,%4};" :: "r"(a), "f"(x), "f"(y), "f"(z), "f"(w) : "memory"); }
__device__ __forceinline__ void sts64(uint32_t a, uint32_t x, uint32_t y) { asm volatile("st.shared.v2.u32 [%0], {%1,%2};" :: "r"(a), "r"(x), "r"(y) : "memory"); }
__device__ __forceinline__ void sts32(uint32_t a, uint32_t x) { asm volatile("st.shared.u32 [%0], %1;" :: "r"(a), "r"(x) : "memory"); }
__device__ __forceinline__ uint4 ldsm4(uint32_t a) { uint4 v; asm volatile("ldmatrix.sync.aligned.m8n8.x4.shared.b16 {%0,%1,%2,%3}, [%4];" : "=r"(v.x), "=r"(v.y), "=r"(v.z), "=r"(v.w) : "r"(a) : "memory"); return v; }
__device__ __forceinline__ void stsm2t(uint32_t a, uint32_t x, uint32_t y) { asm volatile("stmatrix.sync.aligned.m8n8.x2.trans.shared.b16 [%0], {%1,%2};" :: "r"(a), "r"(x), "r"(y) : "memory"); }
__device__ __forceinline__ void stsm4t(uint32_t a, uint32_t x, uint32_t y, uint32_t z, uint32_t w) { asm volatile("stmatrix.sync.aligned.m8n8.x4.trans.shared.b16 [%0], {%1,%2,%3,%4};" :: "r"(a), "r"(x), "r"(y), "r"(z), "r"(w) : "memory"); }
__device__ __forceinline__ void st_async64(uint32_t a, uint32_t x, uint32_t y, uint32_t bar) { asm volatile("st.async.shared::cluster.mbarrier::complete_tx::bytes.v2.b32 [%0], {%1,%2}, [%3];" :: "r"(a), "r"(x), "r"(y), "r"(bar) : "memory"); }
__device__ __forceinline__ void bulk_s2c(uint32_t dst, uint32_t src, uint32_t bytes, uint32_t bar) { asm volatile("cp.async.bulk.shared::cluster.shared::cta.mbarrier::complete_tx::bytes [%0], [%1], %2, [%3];" :: "r"(dst), "r"(src), "r"(bytes), "r"(bar) : "memory"); }
__device__ __forceinline__ void bulk_s2g(void* dst, uint32_t src, uint32_t bytes) { asm volatile("cp.async.bulk.global.shared::cta.bulk_group [%0], [%1], %2;" :: "l"(dst), "r"(src), "r"(bytes) : "memory"); }
__device__ __forceinline__ uint32_t ldg_nc32(const void* p) { uint32_t v; asm volatile("ld.global.nc.L2::128B.u32 %0, [%1];" : "=r"(v) : "l"(p)); return v; }
__device__ __forceinline__ uint4 ldg_relaxed128(const void* p) { uint4 v; asm volatile("ld.relaxed.gpu.global.v4.u32 {%0,%1,%2,%3}, [%4];" : "=r"(v.x), "=r"(v.y), "=r"(v.z), "=r"(v.w) : "l"(p) : "memory"); return v; }
__device__ __forceinline__ void mma16816(float (&d)[4], uint32_t a0, uint32_t a1, uint32_t a2, uint32_t a3, uint32_t b0, uint32_t b1) {
    asm volatile("mma.sync.aligned.m16n8k16.row.col.f32.bf16.bf16.f32 {%0,%1,%2,%3}, {%4,%5,%6,%7}, {%8,%9}, {%0,%1,%2,%3};"
        : "+f"(d[0]), "+f"(d[1]), "+f"(d[2]), "+f"(d[3]) : "r"(a0), "r"(a1), "r"(a2), "r"(a3), "r"(b0), "r"(b1));
}
__device__ __forceinline__ void mma16816_z(float (&d)[4], uint32_t a0, uint32_t a1, uint32_t a2, uint32_t a3, uint32_t b0, uint32_t b1) {
    asm volatile("mma.sync.aligned.m16n8k16.row.col.f32.bf16.bf16.f32 {%0,%1,%2,%3}, {%4,%5,%6,%7}, {%8,%9}, {%10,%10,%10,%10};"
        : "=f"(d[0]), "=f"(d[1]), "=f"(d[2]), "=f"(d[3]) : "r"(a0), "r"(a1), "r"(a2), "r"(a3), "r"(b0), "r"(b1), "f"(0.f));
}
__device__ __forceinline__ void mma1688(float (&d)[4], uint32_t a0, uint32_t a1, uint32_t b0) {
    asm volatile("mma.sync.aligned.m16n8k8.row.col.f32.bf16.bf16.f32 {%0,%1,%2,%3}, {%4,%5}, {%6}, {%0,%1,%2,%3};"
        : "+f"(d[0]), "+f"(d[1]), "+f"(d[2]), "+f"(d[3]) : "r"(a0), "r"(a1), "r"(b0));
}
__device__ __forceinline__ void mma1688_z(float (&d)[4], uint32_t a0, uint32_t a1, uint32_t b0) {
    asm volatile("mma.sync.aligned.m16n8k8.row.col.f32.bf16.bf16.f32 {%0,%1,%2,%3}, {%4,%5}, {%6}, {%7,%7,%7,%7};"
        : "=f"(d[0]), "=f"(d[1]), "=f"(d[2]), "=f"(d[3]) : "r"(a0), "r"(a1), "r"(b0), "f"(0.f));
}
template <int ACC>
__device__ __forceinline__ void wgmma_n32_rs(float (&d)[16], uint32_t a0, uint32_t a1, uint32_t a2, uint32_t a3, uint64_t desc) {
    asm volatile("wgmma.mma_async.sync.aligned.m64n32k16.f32.bf16.bf16 {%0,%1,%2,%3,%4,%5,%6,%7,%8,%9,%10,%11,%12,%13,%14,%15}, {%16,%17,%18,%19}, %20, %21, 1, 1, 0;"
        : "+f"(d[0]), "+f"(d[1]), "+f"(d[2]), "+f"(d[3]), "+f"(d[4]), "+f"(d[5]), "+f"(d[6]), "+f"(d[7]),
          "+f"(d[8]), "+f"(d[9]), "+f"(d[10]), "+f"(d[11]), "+f"(d[12]), "+f"(d[13]), "+f"(d[14]), "+f"(d[15])
        : "r"(a0), "r"(a1), "r"(a2), "r"(a3), "l"(desc), "n"(ACC));
}
template <int ACC>
__device__ __forceinline__ void wgmma_n32_ss(float (&d)[16], uint64_t da, uint64_t db) {
    asm volatile("wgmma.mma_async.sync.aligned.m64n32k16.f32.bf16.bf16 {%0,%1,%2,%3,%4,%5,%6,%7,%8,%9,%10,%11,%12,%13,%14,%15}, %16, %17, %18, 1, 1, 0, 0;"
        : "+f"(d[0]), "+f"(d[1]), "+f"(d[2]), "+f"(d[3]), "+f"(d[4]), "+f"(d[5]), "+f"(d[6]), "+f"(d[7]),
          "+f"(d[8]), "+f"(d[9]), "+f"(d[10]), "+f"(d[11]), "+f"(d[12]), "+f"(d[13]), "+f"(d[14]), "+f"(d[15])
        : "l"(da), "l"(db), "n"(ACC));
}
__device__ __forceinline__ void wg_fence() { asm volatile("wgmma.fence.sync.aligned;" ::: "memory"); }
__device__ __forceinline__ void wg_commit() { asm volatile("wgmma.commit_group.sync.aligned;" ::: "memory"); }
__device__ __forceinline__ void wg_wait0() { asm volatile("wgmma.wait_group.sync.aligned 0;" ::: "memory"); }
__device__ __forceinline__ void cluster_sync() { asm volatile("barrier.cluster.arrive.aligned;\nbarrier.cluster.wait.aligned;" ::: "memory"); }

#define STAMP(s, i) do {} while (0)
#define STAMPV(s, i, v) do {} while (0)

constexpr int XT_BYTES = 36864;
constexpr int O_XT = 0;
constexpr int O_AS = 3 * XT_BYTES;
constexpr int O_AF = O_AS + 16384;
constexpr int O_WP = O_AF + 4096;
constexpr int O_MF = O_WP + 2048;
constexpr int O_XP = O_MF + 9216;
constexpr int O_VX = O_XP + 8192;
constexpr int O_VM = O_VX + 16384;
constexpr int O_SC = O_VM + 2048;
constexpr int O_OF = O_SC + 2560;
constexpr int O_QM = O_OF + 2048;
constexpr int O_QKX = O_QM + 2048;
constexpr int O_KM = O_QKX + 16384;
constexpr int O_MISC = O_KM + 2048;
constexpr int O_BAR = O_MISC + 64;
constexpr int CHAIN_SMEM = O_BAR + 128;
static_assert(CHAIN_SMEM <= 232448, "smem");
constexpr int B_X = O_BAR, B_VX = O_BAR + 24, B_SC = O_BAR + 40, B_VM = O_BAR + 48;
constexpr float SM_SCALE = 0.08838834764831845f * 1.4426950408889634f;
constexpr uint32_t ONES = 0x3f803f80u;

__device__ __forceinline__ uint32_t opaque(uint32_t v) { uint32_t o; asm volatile("mov.u32 %0, %1;" : "=r"(o) : "r"(v)); return o; }
__device__ __forceinline__ void st_async128(uint32_t a, uint32_t x, uint32_t y, uint32_t z, uint32_t w, uint32_t bar) {
    asm volatile("st.async.shared::cluster.mbarrier::complete_tx::bytes.v4.b32 [%0], {%1,%2,%3,%4}, [%5];" :: "r"(a), "r"(x), "r"(y), "r"(z), "r"(w), "r"(bar) : "memory");
}
__device__ __forceinline__ void tma_x_tile(uint32_t sb, const CUtensorMap* tm, int r, int j, int slot) {
    asm volatile("{\n.reg .pred p;\nelect.sync _|p, 0xffffffff;\n"
        "@p mbarrier.arrive.expect_tx.shared::cta.b64 _, [%2], 36864;\n"
        "@p cp.async.bulk.tensor.2d.shared::cluster.global.mbarrier::complete_tx::bytes.multicast::cluster [%0], [%1, {%3, %4}], [%2], %7;\n"
        "@p cp.async.bulk.tensor.2d.shared::cluster.global.mbarrier::complete_tx::bytes.multicast::cluster [%0+4096], [%1, {%5, %4}], [%2], %7;\n"
        "@p cp.async.bulk.tensor.2d.shared::cluster.global.mbarrier::complete_tx::bytes.multicast::cluster [%0+8192], [%1, {%6, %4}], [%2], %7;\n}"
        :: "r"(sb + O_XT + slot * XT_BYTES + 3 * r * 4096), "l"(tm), "r"(sb + B_X + 8 * slot), "r"(192 * r), "r"(j * 32), "r"(192 * r + 64), "r"(192 * r + 128),
           "h"((unsigned short)7) : "memory");
}
__device__ __forceinline__ float quad_max(float v) {
    const float a = __shfl_xor_sync(~0u, v, 1), b = __shfl_xor_sync(~0u, v, 2), c = __shfl_xor_sync(~0u, v, 3);
    return fmaxf(fmaxf(v, a), fmaxf(b, c));
}
__device__ __forceinline__ void load_scores(float (&p)[10], uint32_t base, uint32_t stride, uint32_t l16) {
    const float4 a0 = lds128f(base + l16), b0 = lds128f(base + stride + l16);
    const float4 a1 = lds128f(base + 512 + l16), b1 = lds128f(base + stride + 512 + l16);
    const float2 a2 = lds64f(base + 1024 + (l16 >> 1)), b2 = lds64f(base + stride + 1024 + (l16 >> 1));
    p[0] = a2.x + b2.x; p[1] = a2.y + b2.y;
    p[2] = a0.x + b0.x; p[3] = a0.y + b0.y; p[4] = a0.z + b0.z; p[5] = a0.w + b0.w;
    p[6] = a1.x + b1.x; p[7] = a1.y + b1.y; p[8] = a1.z + b1.z; p[9] = a1.w + b1.w;
}
__device__ __forceinline__ float rcp_fast(float x) { float y; asm("rcp.approx.ftz.f32 %0, %1;" : "=f"(y) : "f"(x)); return y; }

__global__ void __cluster_dims__(3, 1, 1) __launch_bounds__(384, 1)
chain_kernel(const __grid_constant__ CUtensorMap tm_x,
             const __nv_bfloat16* __restrict__ x, const __nv_bfloat16* __restrict__ mem0,
             const __nv_bfloat16* __restrict__ Wq, const __nv_bfloat16* __restrict__ Wk,
             const __nv_bfloat16* __restrict__ Wv, const __nv_bfloat16* __restrict__ Wo) {
    extern __shared__ __align__(1024) uint8_t smem_raw[];
    const uint32_t sb = smem_u32(smem_raw);
    const int lane = threadIdx.x & 31;
    const int warp = __shfl_sync(~0u, threadIdx.x >> 5, 0);
    const int wg = warp >> 2, w = warp & 3;
    const int h = blockIdx.x / 3, r = blockIdx.x - 3 * h;

#define PSTAMP(i) do {} while (0)
    if (warp == 9 && lane < 12) {
        const __nv_bfloat16* W = lane < 3 ? Wq : lane < 6 ? Wk : lane < 9 ? Wv : Wo;
        asm volatile("cp.async.bulk.prefetch.L2.global [%0], 16384;" :: "l"(W + (size_t)blockIdx.x * 24576 + (lane % 3) * 8192) : "memory");
    }
    if (threadIdx.x == 0) {
        if (sb & 1023u) __trap();
        for (int i = 0; i < 7; i++) mbar_init(sb + O_BAR + 8 * i, 1);
        asm volatile("fence.mbarrier_init.release.cluster;" ::: "memory");
    }
    __syncwarp();
    asm volatile("barrier.cluster.arrive.relaxed.aligned;" ::: "memory");
    if (warp == 0) PSTAMP(9);
    const uint32_t l16c = __shfl_sync(~0u, lane * 16, lane);

    if (wg < 2) {
#define KS(u) ((u) < 8 ? ((u) >> 1) + 4 * ((u) & 1) : (u) < 12 ? (u) : (u) < 20 ? 12 + (((u) - 12) >> 1) + 4 * ((u) & 1) : (u) < 24 ? (u) : (u) + 8)
        asm volatile("setmaxnreg.inc.sync.aligned.u32 184;");
        uint32_t a[144];
        uint32_t adr1;
        {
            const int g = lane >> 2, t = lane & 3;
#pragma unroll
            for (int tl = 0; tl < 2; tl++) {
                const int tile = tl ? wg : (wg ^ 1);
                const __nv_bfloat16* W = (r < 2) ? (tile == 0 ? Wq : Wk) : Wv;
                const int col = h * 128 + ((r < 2) ? 64 * r : 64 * tile) + 16 * w + 2 * g;
                const __nv_bfloat16* p = W + (size_t)(2 * t) * HD + col;
                const __nv_bfloat16* ps = p + (size_t)(384 * wg) * HD;
#pragma unroll
                for (int u = 0; u < (tl ? 28 : 8); u++) {
                    const __nv_bfloat16* q = (u < 8 ? ps : p) + (size_t)(16 * KS(u)) * HD;
                    a[32 * tl + 4 * u + 0] = ldg_nc32(q);
                    a[32 * tl + 4 * u + 1] = ldg_nc32(q + HD);
                    a[32 * tl + 4 * u + 2] = ldg_nc32(q + 8 * HD);
                    a[32 * tl + 4 * u + 3] = ldg_nc32(q + 9 * HD);
                }
            }
#pragma unroll
            for (int kk = 0; kk < 72; kk++) {
                uint32_t w0 = a[2 * kk], w1 = a[2 * kk + 1];
                a[2 * kk] = __byte_perm(w0, w1, 0x5410);
                a[2 * kk + 1] = __byte_perm(w0, w1, 0x7632);
            }
            if (r == 2) {
                float n0[4], n1[4];
#pragma unroll
                for (int u = 0; u < 36; u++) {
                    const uint32_t x0 = a[4 * u] & 0x7fff7fffu, x1 = a[4 * u + 1] & 0x7fff7fffu, x2 = a[4 * u + 2] & 0x7fff7fffu, x3 = a[4 * u + 3] & 0x7fff7fffu;
                    if (u == 0) mma16816_z(n0, x0, x1, x2, x3, ONES, ONES);
                    else if (u < 8) mma16816(n0, x0, x1, x2, x3, ONES, ONES);
                    else if (u == 8) mma16816_z(n1, x0, x1, x2, x3, ONES, ONES);
                    else mma16816(n1, x0, x1, x2, x3, ONES, ONES);
                }
                const uint32_t mx = __reduce_max_sync(~0u, __float_as_uint(2.f * fmaxf(fmaxf(n0[0], n0[2]), fmaxf(n1[0], n1[2]))));
                sts32_if(lane, sb + O_MISC + 32 + 4 * warp, mx);
            }
            asm volatile("barrier.cluster.wait.aligned;" ::: "memory");
            if (warp == 0) PSTAMP(11);
            bar_arrive(7, 384);
            const uint32_t as = sb + O_AS + wg * 8192 + (16 * w + g) * 128 + t * 4;
            sts32(as + (g << 4), a[32]);
            sts32(as + 1024 + (g << 4), a[33]);
            sts32(as + ((1 ^ g) << 4), a[34]);
            sts32(as + 1024 + ((1 ^ g) << 4), a[35]);
            sts128(sb + O_AF + warp * 512 + lane * 16, a[32], a[33], a[34], a[35]);
            fence_async_smem();
            bar_sync(1, 256);
            const uint32_t l = lane * 16;
            const int mi = lane >> 3, isk = (mi >> 1) ? wg : (wg ^ 1);
            adr1 = (r == 2) ? (sb + O_VM + warp * 256 + (l >> 1))
                            : (isk ? (sb + O_KM + w * 512 + wg * 256 + (mi & 1) * 128 + (l & 127))
                                   : (sb + O_QM + w * 512 + (mi & 1) * 256 + wg * 128 + (l & 127)));
            adr1 = __shfl_sync(~0u, adr1, lane);
        }
        int s3 = 2;
#pragma unroll 1
        for (int s = -1; s < NSEG; s++) {
            const uint32_t l16 = opaque(l16c);
            s3 = (s3 == 2) ? 0 : s3 + 1;
            if (s < 0) mbar_wait(sb + B_X, 0);
            const uint64_t desc0 = (uint64_t)(((sb + O_XT + s3 * XT_BYTES) & 0x3FFFF) >> 4) | (1ull << 16) | (64ull << 32) | (1ull << 62);
            uint32_t km0 = 0, km1 = 0;
            if (s >= 0) {
                { const uint4 v = lds128(sb + O_AF + warp * 512 + l16); a[32] = v.x; a[33] = v.y; a[34] = v.z; a[35] = v.w; }
                float co[4], cw[3][4];
                uint4 b[14];
                float inv;
#define GORD(i) ((i) == 0 ? 0 : (i) == 1 ? 1 : (i) == 5 ? 2 : (i) == 9 ? 3 : (i) < 5 ? (i) + 2 : (i) < 9 ? (i) + 1 : (i))
                auto qkv_mma = [&](int i) {
                    const int gi = GORD(i), u = 8 * gi, n0 = 2 * i, n1 = 2 * i + 1;
                    if (gi < 4) {
                        if (i == 0) mma16816_z(co, a[u], a[u + 1], a[u + 2], a[u + 3], b[0].x, b[0].y);
                        else mma16816(co, a[u], a[u + 1], a[u + 2], a[u + 3], b[i].x, b[i].y);
                    }
                    if (n0 < 3) mma16816_z(cw[n0 % 3], a[32 + u], a[32 + u + 1], a[32 + u + 2], a[32 + u + 3], b[i].x, b[i].y);
                    else mma16816(cw[n0 % 3], a[32 + u], a[32 + u + 1], a[32 + u + 2], a[32 + u + 3], b[i].x, b[i].y);
                    if (n1 < 3) mma16816_z(cw[n1 % 3], a[32 + u + 4], a[32 + u + 5], a[32 + u + 6], a[32 + u + 7], b[i].z, b[i].w);
                    else mma16816(cw[n1 % 3], a[32 + u + 4], a[32 + u + 5], a[32 + u + 6], a[32 + u + 7], b[i].z, b[i].w);
                    if (gi < 4) mma16816(co, a[u + 4], a[u + 5], a[u + 6], a[u + 7], b[i].z, b[i].w);
                };
                const uint32_t mf = sb + O_MF + l16, mfs = mf + wg * 6144;
                if (VSEND == 0 && r == 2) {
                    asm volatile("{\n.reg .pred p;\ncp.async.bulk.wait_group 0;\nelect.sync _|p, 0xffffffff;\nsetp.lt.and.s32 p, %4, 63, p;\n"
                        "@p cp.async.bulk.shared::cluster.global.mbarrier::complete_tx::bytes.multicast::cluster [%1], [%0], 1024, [%2], %3;\n"
                        "fence.proxy.async.global;\n}"
                        :: "l"(reinterpret_cast<char*>(g_qkv) + (size_t)(s * NH + h) * 24576 + 16384 + warp * 1024), "r"(sb + O_VX + (s & 1) * 8192 + warp * 1024),
                           "r"(sb + B_VX + 8 * (s & 1)), "h"((unsigned short)3), "r"(s) : "memory");
                }
                bar_sync(2, 384);
                if (warp == 0) STAMP(s, 0);
                auto qkv_ld = [&](int i) { b[i] = GORD(i) < 4 ? lds128v(mfs + GORD(i) * 512) : lds128v(mf + (GORD(i) < 12 ? GORD(i) : GORD(i) + 4) * 512); };
#pragma unroll
                for (int i = 0; i < 5; i++) qkv_ld(i);
                if (QF >= 1) sched_fence<2>(h);
#pragma unroll
                for (int i = 0; i < 4; i++) { qkv_mma(i); qkv_ld(5 + i); }
                if (QF >= 2) sched_fence<3>(h);
#pragma unroll
                for (int i = 4; i < 9; i++) { qkv_mma(i); qkv_ld(5 + i); }
                inv = __uint_as_float(lds32(sb + O_MISC));
                if (QF >= 3) sched_fence<4>(h);
#pragma unroll
                for (int i = 9; i < 14; i++) qkv_mma(i);
#pragma unroll
                for (int i = 0; i < 4; i++) cw[0][i] += cw[1][i] + cw[2][i];
                if (r < 2) {
                    const uint32_t o0 = pack_bf16(co[0] * inv, co[1] * inv), o1 = pack_bf16(co[2] * inv, co[3] * inv);
                    const uint32_t w0 = pack_bf16(cw[0][0] * inv, cw[0][1] * inv), w1 = pack_bf16(cw[0][2] * inv, cw[0][3] * inv);
                    stsm4t(adr1, o0, o1, w0, w1);
                    km0 = wg ? w0 : o0; km1 = wg ? w1 : o1;
                    if (warp == 0) STAMP(s, 1);
                    asm volatile("{\n.reg .pred p;\nsetp.ge.u32 p, %0, 3;\n@p bar.arrive 1, 256;\n}" :: "r"(warp) : "memory");
                    if (warp < 3 && s < NSEG - 1) {
                        uint4 q[4], k[4];
                        const uint32_t ka = sb + (warp == 2 ? O_KM : O_QKX + (s & 1) * 8192 + 4096 + warp * 2048) + l16;
#pragma unroll
                        for (int i = 0; i < 4; i++) k[i] = ldsm4(ka + i * 512);
                        const uint32_t dst = sb + O_SC + r * 1280 + warp * 512 + (l16 >> 1);
                        bar_sync(1, 256);
#pragma unroll
                        for (int i = 0; i < 4; i++) q[i] = ldsm4(sb + O_QM + i * 512 + l16);
                        if (warp == 2) {
#pragma unroll
                            for (int i = 0; i < 4; i++) k[i] = ldsm4(ka + i * 512);
                        }
                        float s0[4], s1[4], t0[4], t1[4];
                        mma16816_z(s0, q[0].x, q[0].y, q[0].z, q[0].w, k[0].x, k[0].y);
                        mma16816_z(s1, q[0].x, q[0].y, q[0].z, q[0].w, k[0].z, k[0].w);
                        mma16816_z(t0, q[1].x, q[1].y, q[1].z, q[1].w, k[1].x, k[1].y);
                        mma16816_z(t1, q[1].x, q[1].y, q[1].z, q[1].w, k[1].z, k[1].w);
                        mma16816(s0, q[2].x, q[2].y, q[2].z, q[2].w, k[2].x, k[2].y);
                        mma16816(s1, q[2].x, q[2].y, q[2].z, q[2].w, k[2].z, k[2].w);
                        mma16816(t0, q[3].x, q[3].y, q[3].z, q[3].w, k[3].x, k[3].y);
                        mma16816(t1, q[3].x, q[3].y, q[3].z, q[3].w, k[3].z, k[3].w);
                        const float v0 = (s0[0] + s0[2]) + (t0[0] + t0[2]), v1 = (s0[1] + s0[3]) + (t0[1] + t0[3]);
                        const float v2 = (s1[0] + s1[2]) + (t1[0] + t1[2]), v3 = (s1[1] + s1[3]) + (t1[1] + t1[3]);
                        if (warp < 2) {
                            const uint32_t dv = dst + (l16 >> 1);
                            st_async128(mapa(dv, 2), __float_as_uint(v0), __float_as_uint(v1), __float_as_uint(v2), __float_as_uint(v3), mapa(sb + B_SC, 2));
                            st_async128(mapa(dv, r ^ 1), __float_as_uint(v0), __float_as_uint(v1), __float_as_uint(v2), __float_as_uint(v3), mapa(sb + B_SC, r ^ 1));
                            st_async128(mapa(dv, r), __float_as_uint(v0), __float_as_uint(v1), __float_as_uint(v2), __float_as_uint(v3), mapa(sb + B_SC, r));
                        } else {
                            st_async64(mapa(dst, 2), __float_as_uint(v0 + v2), __float_as_uint(v1 + v3), mapa(sb + B_SC, 2));
                            st_async64(mapa(dst, r ^ 1), __float_as_uint(v0 + v2), __float_as_uint(v1 + v3), mapa(sb + B_SC, r ^ 1));
                            st_async64(mapa(dst, r), __float_as_uint(v0 + v2), __float_as_uint(v1 + v3), mapa(sb + B_SC, r));
                        }
                        if (warp == 2) STAMP(s, 2);
                    } else if (warp < 3) {
                        bar_sync(1, 256);
                    }
                } else {
                    sts128f(sb + O_XP + warp * 512 + l16, co[0], co[1], co[2], co[3]);
                    bar_sync(8 + w, 64);
                    const float4 o = lds128f(sb + O_XP + (warp ^ 4) * 512 + l16);
                    km0 = pack_bf16((cw[0][0] + o.x) * inv, (cw[0][1] + o.y) * inv);
                    km1 = pack_bf16((cw[0][2] + o.z) * inv, (cw[0][3] + o.w) * inv);
                    if (warp == 0) STAMP(s, 1);
                    if (s < NSEG - 1) {
                        st_async64(mapa(adr1, 0), km0, km1, mapa(sb + B_SC, 0));
                        st_async64(mapa(adr1, 1), km0, km1, mapa(sb + B_SC, 1));
                        st_async64(mapa(adr1, 2), km0, km1, mapa(sb + B_SC, 2));
                    }
                    if (warp == 0) STAMP(s, 2);
                }
            }
            auto store_qk = [&]() {
                asm volatile("{\n.reg .pred p;\nelect.sync _|p, 0xffffffff;\n"
                    "@p cp.async.bulk.global.shared::cta.bulk_group [%0], [%1], 8192;\n@p cp.async.bulk.commit_group;\n}"
                    :: "l"(reinterpret_cast<char*>(g_qkv) + (size_t)(s * NH + h) * 24576 + r * 8192), "r"(sb + O_QKX + (s & 1) * 8192) : "memory");
            };
            auto store_kvm = [&]() {
                char* p = reinterpret_cast<char*>(g_kvm) + (size_t)(s * NH + h) * 6144 + (r < 2 ? wg * 2048 + (r * 4 + w) * 256 : 4096 + warp * 256) + (l16 >> 1);
                *reinterpret_cast<uint2*>(p) = make_uint2(km0, km1);
            };
            if (s >= 0) bar_sync(3, 384);
            if (s == NSEG - 1) {
                store_kvm();
                if (warp == 3 && r < 2) {
                    store_qk();
                    asm volatile("cp.async.bulk.wait_group 0;\nfence.proxy.async.global;" ::: "memory");
                }
            } else {
                const int j = s + 1;
#define XDESC(u) (((u) < 8 ? descs : desc0) + (uint64_t)(((KS(u) >> 2) * 4096 + (KS(u) & 3) * 32) >> 4))
                const uint64_t descs = desc0 + (uint64_t)(wg * (6 * 4096 >> 4));
                float d[16];
                wg_fence();
#pragma unroll
                for (int u = 0; u < 8; u++) {
                    if (u == 0) wgmma_n32_rs<0>(d, a[0], a[1], a[2], a[3], XDESC(0));
                    else wgmma_n32_rs<1>(d, a[4 * u], a[4 * u + 1], a[4 * u + 2], a[4 * u + 3], XDESC(u));
                }
                wg_commit();
                wg_wait0();
                if (warp == 0) STAMP(s, 15);
                if (s >= 0) bar_sync(4, 384);
#pragma unroll
                for (int q = 0; q < 2; q++)
                    sts128(sb + O_XP + warp * 1024 + q * 512 + l16, pack_bf16(d[8 * q], d[8 * q + 1]), pack_bf16(d[8 * q + 2], d[8 * q + 3]),
                           pack_bf16(d[8 * q + 4], d[8 * q + 5]), pack_bf16(d[8 * q + 6], d[8 * q + 7]));
                if (s >= 0) {
                    store_kvm();
                    if (warp == 3) asm volatile("cp.async.bulk.wait_group 0;\nfence.proxy.async.global;" ::: "memory");
                    if (warp == 1 && s + 2 < NSEG) tma_x_tile(sb, &tm_x, r, s + 2, s3 == 2 ? 0 : s3 + 1);
                }
                bar_sync(12, 256);
#pragma unroll
                for (int q = 0; q < 2; q++) {
                    const uint4 o = lds128(sb + O_XP + (warp ^ 4) * 1024 + q * 512 + l16);
                    d[8 * q] = __uint_as_float(o.x << 16); d[8 * q + 1] = __uint_as_float(o.x & 0xffff0000u);
                    d[8 * q + 2] = __uint_as_float(o.y << 16); d[8 * q + 3] = __uint_as_float(o.y & 0xffff0000u);
                    d[8 * q + 4] = __uint_as_float(o.z << 16); d[8 * q + 5] = __uint_as_float(o.z & 0xffff0000u);
                    d[8 * q + 6] = __uint_as_float(o.w << 16); d[8 * q + 7] = __uint_as_float(o.w & 0xffff0000u);
                }
                if (s >= 0) {
                    if (warp == 6 && (s & 3) == 0 && s >= 4)
                        asm volatile("{\n.reg .pred p;\nsetp.eq.u32 p, %1, 0;\n@p red.release.gpu.global.inc.u32 [%0], 0x7fffffff;\n}"
                                     :: "l"(&g_flag[((s - 1) * 4 + (h >> 3)) * 8]), "r"(l16) : "memory");
                    asm volatile("{\n.reg .pred p;\nsetp.eq.u32 p, %0, 0;\n@p bar.sync 5, 256;\n@!p bar.sync 13, 256;\n}" :: "r"(wg) : "memory");
                }
                const uint64_t da0 = (uint64_t)(((sb + O_AS + wg * 8192) & 0x3FFFF) >> 4) | (1ull << 16) | (64ull << 32) | (1ull << 62);
                wg_fence();
                wgmma_n32_ss<1>(d, da0, XDESC(0));
#pragma unroll
                for (int u = 1; u < 28; u++) wgmma_n32_rs<1>(d, a[32 + 4 * u], a[32 + 4 * u + 1], a[32 + 4 * u + 2], a[32 + 4 * u + 3], XDESC(u));
                wg_commit();
                wg_wait0();
                if (warp == 3 && r < 2 && s >= 0) store_qk();
                if (warp == 4) STAMP(s, 3);
                uint32_t e[8];
#pragma unroll
                for (int i = 0; i < 8; i++) e[i] = pack_bf16(d[2 * i], d[2 * i + 1]);
                if (r < 2) {
                    const uint32_t base = sb + O_QKX + (j & 1) * 8192 + wg * 4096 + w * 512 + l16;
                    stsm4t(base, e[0], wg ? e[1] : e[2], wg ? e[2] : e[1], e[3]);
                    stsm4t(base + 2048, e[4], wg ? e[5] : e[6], wg ? e[6] : e[5], e[7]);
                    fence_async_smem();
                } else {
                    const uint32_t base = sb + O_VX + (j & 1) * 8192 + warp * 1024 + l16;
                    sts128(base, e[0], e[1], e[2], e[3]);
                    sts128(base + 512, e[4], e[5], e[6], e[7]);
                    fence_async_smem();
                    bar_arrive(14, 288);
                }
                if (warp == 7) STAMP(s, 4);
            }
        }
        bar_arrive(7, 384);
    } else {
        asm volatile("setmaxnreg.dec.sync.aligned.u32 136;");
        const int c = w;
        uint32_t a[96];
        uint32_t mmax = 0;
        {
            const int g = lane >> 2, t = lane & 3, t2 = threadIdx.x - 256;
#pragma unroll
            for (int i = 0; i < 4; i++) g_acc[(blockIdx.x * 64 + i * 16 + (t2 >> 3)) * 16 + (t2 & 7)] = make_uint4(0, 0, 0, 0);
            if (blockIdx.x == 0) {
#pragma unroll
                for (int i = 0; i < NFLAG / 512; i++) reinterpret_cast<uint4*>(g_flag)[i * 128 + t2] = make_uint4(0, 0, 0, 0);
            }
            uint32_t tag = 0;
            if (t2 == 0) tag = atomicAdd(&g_ticket, 1u);
            asm volatile("barrier.cluster.wait.aligned;" ::: "memory");
            if (c == 0) {
                tma_x_tile(sb, &tm_x, r, 0, 0);
                tma_x_tile(sb, &tm_x, r, 1, 1);
                mbar_expect_if(lane, sb + B_SC, 4608);
                if (r < 2) mbar_expect_if(lane, sb + B_VX, 8192);
                sts32_if(lane, sb + O_MISC, __float_as_uint(1.0f));
                sts32_if(lane, sb + O_MISC + 12, __float_as_uint(SM_SCALE));
            }
            __threadfence();
            bar_sync(6, 128);
            asm volatile("griddepcontrol.launch_dependents;" ::: "memory");
            tag = (__shfl_sync(~0u, tag, 0) / 96u + 1u) & 0xffffu;
#pragma unroll
            for (int tau = 0; tau < 3; tau++) {
                uint32_t v[6];
#pragma unroll
                for (int i = 0; i < 3; i++) {
                    const uint32_t* p = reinterpret_cast<const uint32_t*>(mem0 + g * DM + 16 * (12 * tau + 4 * i + c) + 2 * t);
                    v[2 * i] = __ldg(p); v[2 * i + 1] = __ldg(p + 4);
                    mmax = __vmaxu2(mmax, __vmaxu2(v[2 * i] & 0x7fff7fffu, v[2 * i + 1] & 0x7fff7fffu));
                }
                sts128(sb + O_MF + tau * 3072 + c * 512 + lane * 16, v[0], v[1], v[2], v[3]);
                sts64(sb + O_MF + tau * 3072 + 2048 + (c >> 1) * 512 + lane * 16 + (c & 1) * 8, v[4], v[5]);
            }
            mmax = max(mmax << 16, mmax & 0xffff0000u);
            bar_arrive(2, 384);
            uint32_t xm = 0;
            const uint4* xp = reinterpret_cast<const uint4*>(x) + blockIdx.x * 1536 + t2;
#pragma unroll
            for (int i = 0; i < 12; i++) {
                uint4 v = __ldg(xp + i * 128);
                xm = __vmaxu2(xm, __vmaxu2(__vmaxu2(v.x & 0x7fff7fffu, v.y & 0x7fff7fffu), __vmaxu2(v.z & 0x7fff7fffu, v.w & 0x7fff7fffu)));
            }
            xm = __reduce_max_sync(~0u, max(xm << 16, xm & 0xffff0000u));

            const __nv_bfloat16* p = Wo + (size_t)(h * 128 + 4 * t) * DM + 192 * r + 16 * c + 2 * g;
#pragma unroll
            for (int i = 0; i < 3; i++)
#pragma unroll
                for (int eb = 0; eb < 8; eb++)
#pragma unroll
                    for (int j = 0; j < 4; j++) a[(i * 8 + eb) * 4 + j] = ldg_nc32(p + (16 * eb + ((j & 1) * 2 + (j >> 1))) * DM + 64 * i);
#pragma unroll
            for (int kk = 0; kk < 48; kk++) {
                uint32_t w0 = a[2 * kk], w1 = a[2 * kk + 1];
                a[2 * kk] = __byte_perm(w0, w1, 0x5410);
                a[2 * kk + 1] = __byte_perm(w0, w1, 0x7632);
            }
            sts128(sb + O_WP + c * 512 + lane * 16, a[92], a[93], a[94], a[95]);
            float wmax = 0.f;
#pragma unroll
            for (int i = 0; i < 3; i++) {
                float n0[4];
#pragma unroll
                for (int u = 8 * i; u < 8 * i + 8; u++) {
                    const uint32_t x0 = a[4 * u] & 0x7fff7fffu, x1 = a[4 * u + 1] & 0x7fff7fffu, x2 = a[4 * u + 2] & 0x7fff7fffu, x3 = a[4 * u + 3] & 0x7fff7fffu;
                    if (u == 8 * i) mma16816_z(n0, x0, x1, x2, x3, ONES, ONES);
                    else mma16816(n0, x0, x1, x2, x3, ONES, ONES);
                }
                wmax = fmaxf(wmax, fmaxf(n0[0], n0[2]));
            }
            uint32_t wm = __reduce_max_sync(~0u, __float_as_uint(wmax));
            sts32_if(lane, sb + O_OF + 4 * c, wm); sts32_if(lane, sb + O_OF + 16 + 4 * c, xm);
            if (c == 0) PSTAMP(8);
            bar_sync(7, 384);
            if (c == 0) {
                const uint4 wq = lds128(sb + O_OF), xq = lds128(sb + O_OF + 16), v0 = lds128(sb + O_MISC + 32), v1 = lds128(sb + O_MISC + 48);
                const uint32_t w1 = max(max(wq.x, wq.y), max(wq.z, wq.w)), x1 = max(max(xq.x, xq.y), max(xq.z, xq.w));
                const uint32_t vv = (r < 2) ? 0u : max(max(max(v0.x, v0.y), max(v0.z, v0.w)), max(max(v1.x, v1.y), max(v1.z, v1.w)));
                const uint32_t lo = (min(w1, 0x7f800000u) + 0xffffu) >> 16 | ((min(vv, 0x7f800000u) + 0xffffu) & 0xffff0000u), hi = (x1 & 0xffff0000u) | tag;
                uint32_t l0, h0, l1, h1, l2, h2;
                asm volatile("{\n.reg .pred p;\n.reg .u32 n, x, y;\n.reg .b64 v;\nsetp.eq.u32 p, %10, 0;\nmov.b64 v, {%8, %9};\n@p st.relaxed.gpu.global.b64 [%7], v;\nmov.u32 n, 0;\n"
                             "G_%=: ld.relaxed.gpu.global.b64 v, [%6];\nmov.b64 {%0, %1}, v;\nld.relaxed.gpu.global.b64 v, [%6+256];\nmov.b64 {%2, %3}, v;\n"
                             "ld.relaxed.gpu.global.b64 v, [%6+512];\nmov.b64 {%4, %5}, v;\n"
                             "xor.b32 x, %1, %9;\nxor.b32 y, %3, %9;\nor.b32 x, x, y;\nxor.b32 y, %5, %9;\nor.b32 x, x, y;\nand.b32 x, x, 0xffff;\n"
                             "setp.eq.u32 p, x, 0;\nvote.sync.all.pred p, p, 0xffffffff;\n@p bra.uni E_%=;\n"
                             "add.u32 n, n, 1;\nsetp.lt.u32 p, n, 4000000;\n@p bra.uni G_%=;\ntrap;\nE_%=:\n}"
                             : "=&r"(l0), "=&r"(h0), "=&r"(l1), "=&r"(h1), "=&r"(l2), "=&r"(h2)
                             : "l"(&g_norm[lane]), "l"(&g_norm[blockIdx.x]), "r"(lo), "r"(hi), "r"(lane) : "memory");
                const uint32_t lm = __vmaxu2(l0, __vmaxu2(l1, l2));
                const float fw = __uint_as_float(__reduce_max_sync(~0u, lm << 16));
                const float fv = __uint_as_float(__reduce_max_sync(~0u, lm & 0xffff0000u));
                const float xmax = __uint_as_float(__reduce_max_sync(~0u, max(h0, max(h1, h2)) & 0xffff0000u));
                const float G = 36.f * fw * fv;
                sts32_if(lane, sb + O_MISC + 4, __float_as_uint(G)); sts32_if(lane, sb + O_MISC + 8, __float_as_uint(G * xmax));
            }
        }
        if (c == 0) PSTAMP(12);
        bar_sync(6, 128);
        int s3n = 1;
        uint32_t roff = __shfl_sync(~0u, (r * 4 + c) * 2048 + (lane >> 4) * 512 + (lane & 2) * 128 + (lane & 1) * 64 + (lane & 12) * 4, lane);
        uint32_t poff = __shfl_sync(~0u, c * 2048 + (lane & 4) * 256 + (lane >> 4) * 256 + (lane & 8) * 8 + (lane & 3) * 16, lane);
#pragma unroll 1
        for (int s = 0; s < NSEG; s++) {
            const uint32_t l16 = opaque(l16c);
            const uint32_t vxa = sb + O_VX + (s & 1) * 8192 + c * 2048 + l16;
            if (c == 0 && r == 2) {
                bar_sync(14, 288);
                asm volatile("{\n.reg .pred p;\nelect.sync _|p, 0xffffffff;\n"
                    "@p cp.async.bulk.global.shared::cta.bulk_group [%0], [%1], 8192;\n@p cp.async.bulk.commit_group;\n"
                    "cp.async.bulk.wait_group 0;\nsetp.lt.and.s32 p, %4, 63, p;\n"
                    "@p cp.async.bulk.shared::cluster.global.mbarrier::complete_tx::bytes.multicast::cluster [%1], [%0], 8192, [%2], %3;\n"
                    "fence.proxy.async.global;\n}"
                    :: "l"(reinterpret_cast<char*>(g_qkv) + (size_t)(s * NH + h) * 24576 + 16384), "r"(sb + O_VX + (s & 1) * 8192),
                       "r"(sb + B_VX + 8 * (s & 1)), "h"((unsigned short)3), "r"(s) : "memory");
            }
            if (s == NSEG - 1) { bar_sync(3, 384); break; }
            uint4 vx[4];
            sts32_if(l16, sb + O_MISC + 16 + 4 * c, __reduce_max_sync(~0u, mmax));
            if (c == 0) STAMP(s, 5);
            {
                bar_sync(6, 128);
                const uint4 mm = lds128(sb + O_MISC + 16), cf = lds128(sb + O_MISC);
                const float bound = fmaxf(__uint_as_float(cf.z), __uint_as_float(cf.y) * (__uint_as_float(max(max(mm.x, mm.y), max(mm.z, mm.w))) * __uint_as_float(cf.x)));
                const uint32_t ebits = __reduce_max_sync(~0u, min(max(__float_as_uint(bound) & 0x7f800000u, 21u << 23), 254u << 23));
                mbar_wait(sb + B_X + 8 * s3n, ((s + 1) / 3) & 1);
                s3n = (s3n == 2) ? 0 : s3n + 1;
                bar_sync(3, 384);
                if (r < 2) mbar_wait(sb + B_VX + 8 * (s & 1), (s >> 1) & 1);
                vx[0] = lds128(vxa); vx[2] = lds128(vxa + 1024);
                if (c == 0) STAMP(s, 13);
                mbar_wait(sb + B_SC, s & 1);
                if (c == 0) STAMP(s, 6);
                float p[10];
                load_scores(p, sb + O_SC, 1280, l16);
                float mx = fmaxf(fmaxf(fmaxf(p[0], p[1]), fmaxf(p[2], p[3])), fmaxf(fmaxf(p[4], p[5]), fmaxf(p[6], p[7])));
                mx = quad_max(fmaxf(mx, fmaxf(p[8], p[9])));
                const uint4 vm = lds64x2(sb + O_VM + c * 512 + (l16 >> 1));
                vx[1] = lds128(vxa + 512); vx[3] = lds128(vxa + 1536);
                bar_arrive(4, 384);
                const float sc = __uint_as_float(lds32(sb + O_MISC + 12));
                const float mo = mx * SM_SCALE;
                uint32_t P[5];
#pragma unroll
                for (int n = 0; n < 5; n++) P[n] = pack_bf16(ex2(fmaf(p[2 * n], SM_SCALE, -mo)), ex2(fmaf(p[2 * n + 1], n == 3 ? sc : SM_SCALE, -mo)));
                if (c == 0) STAMP(s, 7);
                float o0[4], o1[4], sm[4];
                mma16816_z(sm, ONES, ONES, ONES, ONES, P[1], P[2]);
                mma16816_z(o0, vx[0].x, vx[0].y, vx[0].z, vx[0].w, P[1], P[2]);
                mma16816_z(o1, vx[2].x, vx[2].y, vx[2].z, vx[2].w, P[1], P[2]);
                mma16816(sm, ONES, ONES, ONES, ONES, P[3], P[4]);
                mma16816(o0, vx[1].x, vx[1].y, vx[1].z, vx[1].w, P[3], P[4]);
                mma16816(o1, vx[3].x, vx[3].y, vx[3].z, vx[3].w, P[3], P[4]);
                mma1688(sm, ONES, ONES, P[0]);
                mma1688(o0, vm.x, vm.y, P[0]);
                mma1688(o1, vm.z, vm.w, P[0]);
                const float sig = __uint_as_float((268u << 23) - ebits);
                const float r0 = rcp_fast(sm[0]) * sig, r1 = rcp_fast(sm[1]) * sig;
                stsm4t(sb + O_OF + c * 512 + l16, pack_bf16(o0[0] * r0, o0[1] * r1), pack_bf16(o0[2] * r0, o0[3] * r1),
                       pack_bf16(o1[0] * r0, o1[1] * r1), pack_bf16(o1[2] * r0, o1[3] * r1));
                bar_sync(6, 128);
                uint4 ob[4];
#pragma unroll
                for (int q = 0; q < 4; q++) ob[q] = ldsm4(sb + O_OF + q * 512 + l16);
                { const uint4 v = lds128(sb + O_WP + c * 512 + l16); a[92] = v.x; a[93] = v.y; a[94] = v.z; a[95] = v.w; }
                float m0[3][4], m1[3][4];
#pragma unroll
                for (int q = 0; q < 4; q++) {
#pragma unroll
                    for (int i = 0; i < 3; i++) {
                        const int k0 = (i * 8 + 2 * q) * 4;
                        if (q == 0) mma16816_z(m0[i], a[k0], a[k0 + 1], a[k0 + 2], a[k0 + 3], ob[q].x, ob[q].y);
                        else mma16816(m0[i], a[k0], a[k0 + 1], a[k0 + 2], a[k0 + 3], ob[q].x, ob[q].y);
                    }
#pragma unroll
                    for (int i = 0; i < 3; i++) {
                        const int k1 = (i * 8 + 2 * q + 1) * 4;
                        if (q == 0) mma16816_z(m1[i], a[k1], a[k1 + 1], a[k1 + 2], a[k1 + 3], ob[q].z, ob[q].w);
                        else mma16816(m1[i], a[k1], a[k1 + 1], a[k1 + 2], a[k1 + 3], ob[q].z, ob[q].w);
                    }
                }
                asm volatile("red.relaxed.gpu.global.add.noftz.v4.f16x2 [%0], {%1,%2,%3,%4};" :: "l"(reinterpret_cast<char*>(g_acc) + roff),
                    "r"(pack_f16(m0[0][0] + m1[0][0], m0[0][2] + m1[0][2])), "r"(pack_f16(m0[1][0] + m1[1][0], m0[1][2] + m1[1][2])),
                    "r"(pack_f16(m0[2][0] + m1[2][0], m0[2][2] + m1[2][2])), "r"(0x3c00u) : "memory");
                asm volatile("red.relaxed.gpu.global.add.noftz.v4.f16x2 [%0], {%1,%2,%3,%4};" :: "l"(reinterpret_cast<char*>(g_acc) + roff + 1024),
                    "r"(pack_f16(m0[0][1] + m1[0][1], m0[0][3] + m1[0][3])), "r"(pack_f16(m0[1][1] + m1[1][1], m0[1][3] + m1[1][3])),
                    "r"(pack_f16(m0[2][1] + m1[2][1], m0[2][3] + m1[2][3])), "r"(0x3c00u) : "memory");
                const unsigned t_red = clk();
                bar_arrive(5, 256);
                bar_arrive(13, 256);
                mbar_expect_if(l16 | c, sb + B_SC, 4608);
                mbar_expect_if(l16 | (c ^ 1) | (r >> 1), sb + B_VX + 8 * ((s + 1) & 1), 8192);
                sts32_if(l16 | (c ^ 3), sb + O_MISC, ebits - (14u << 23));
                if (c == 0) STAMPV(s, 8, t_red);
                const char* pbase = reinterpret_cast<const char*>(g_acc) + poff;
                spin_until(t_red, D_WAIT);
                uint4 v[6];
#pragma unroll
                for (int i = 0; i < 6; i++) v[i] = ldg_relaxed128(pbase + (i >> 1) * 8192 + (i & 1) * 512);
                int nretry = 0;
                auto hand_over = [&]() -> uint32_t {
                    uint32_t ok = 0;
#pragma unroll
                    for (int tau = 0; tau < 3; tau++) {
                        if (tau == 1) sched_fence<0>(h);
                        if (tau == 2) {
                            sched_fence<1>(h);
                            asm volatile("{\n.reg .pred p, q;\n.reg .b32 x;\nlop3.b32 x, %1, %2, %3, 0x80;\nlop3.b32 x, x, %4, %5, 0x80;\nand.b32 x, x, %6;\n"
                                         "setp.eq.u32 p, x, 0x5000;\nvote.sync.all.pred q, p, 0xffffffff;\nselp.u32 %0, 1, 0, q;\n}"
                                         : "=r"(ok) : "r"(v[0].w), "r"(v[1].w), "r"(v[2].w), "r"(v[3].w), "r"(v[4].w), "r"(v[5].w));
                        }
                        v[2 * tau].x = f16x2_to_bf16x2(v[2 * tau].x); v[2 * tau + 1].x = f16x2_to_bf16x2(v[2 * tau + 1].x);
                        v[2 * tau].y = f16x2_to_bf16x2(v[2 * tau].y); v[2 * tau + 1].y = f16x2_to_bf16x2(v[2 * tau + 1].y);
                        v[2 * tau].z = f16x2_to_bf16x2(v[2 * tau].z); v[2 * tau + 1].z = f16x2_to_bf16x2(v[2 * tau + 1].z);
                        sts128(sb + O_MF + tau * 3072 + c * 512 + l16, v[2 * tau].x, v[2 * tau + 1].x, v[2 * tau].y, v[2 * tau + 1].y);
                        sts64(sb + O_MF + tau * 3072 + 2048 + (c >> 1) * 512 + (c & 1) * 8 + l16, v[2 * tau].z, v[2 * tau + 1].z);
                    }
                    asm volatile("{\n.reg .pred p;\nsetp.ne.u32 p, %0, 0;\n@p bar.arrive 2, 384;\n}" :: "r"(ok) : "memory");
                    return ok;
                };
                if (!hand_over()) {
                    asm volatile("{\n.reg .pred p, q;\n.reg .u32 n, x;\nmov.u32 n, 0;\n"
                         "R_%=: ld.relaxed.gpu.global.v4.u32 {%0,%1,%2,%3}, [%25];\nld.relaxed.gpu.global.v4.u32 {%4,%5,%6,%7}, [%25+512];\n"
                         "ld.relaxed.gpu.global.v4.u32 {%8,%9,%10,%11}, [%25+8192];\nld.relaxed.gpu.global.v4.u32 {%12,%13,%14,%15}, [%25+8704];\n"
                         "ld.relaxed.gpu.global.v4.u32 {%16,%17,%18,%19}, [%25+16384];\nld.relaxed.gpu.global.v4.u32 {%20,%21,%22,%23}, [%25+16896];\n"
                         "add.u32 %24, %24, 1;\nand.b32 x, %3, %7;\nand.b32 x, x, %11;\nand.b32 x, x, %15;\nand.b32 x, x, %19;\nand.b32 x, x, %23;\n"
                         "setp.eq.u32 p, x, 0x5000;\nvote.sync.all.pred q, p, 0xffffffff;\n@q bra.uni K_%=;\n"
                         "add.u32 n, n, 1;\nsetp.lt.u32 q, n, 2000000;\n@q bra.uni R_%=;\ntrap;\nK_%=:\n}"
                         : "+r"(v[0].x), "+r"(v[0].y), "+r"(v[0].z), "+r"(v[0].w), "+r"(v[1].x), "+r"(v[1].y), "+r"(v[1].z), "+r"(v[1].w),
                           "+r"(v[2].x), "+r"(v[2].y), "+r"(v[2].z), "+r"(v[2].w), "+r"(v[3].x), "+r"(v[3].y), "+r"(v[3].z), "+r"(v[3].w),
                           "+r"(v[4].x), "+r"(v[4].y), "+r"(v[4].z), "+r"(v[4].w), "+r"(v[5].x), "+r"(v[5].y), "+r"(v[5].z), "+r"(v[5].w), "+r"(nretry)
                         : "l"(pbase) : "memory");
                    hand_over();
                }
                if (c == 0) STAMP(s, 12);
                if (c == 0) STAMPV(s, 14, nretry);
                mmax = absmax2(absmax2(absmax2(v[0].x, v[0].y), absmax2(v[0].z, v[1].x)), absmax2(absmax2(v[1].y, v[1].z), absmax2(v[2].x, v[2].y)));
                mmax = absmax2(mmax, absmax2(absmax2(absmax2(v[2].z, v[3].x), absmax2(v[3].y, v[3].z)), absmax2(absmax2(v[4].x, v[4].y), absmax2(v[4].z, v[5].x))));
                mmax = absmax2(mmax, absmax2(v[5].y, v[5].z)) & 0x7fff7fffu;
                mmax = max(mmax << 16, mmax & 0xffff0000u);
            }
            roff += 24576; poff += 24576;
        }
        {
            bar_sync(7, 384);
            if (c == 0)
                asm volatile("{\n.reg .pred p;\nsetp.eq.u32 p, %1, 0;\n@p red.release.gpu.global.inc.u32 [%0], 0x7fffffff;\n}"
                             :: "l"(&g_flag[(63 * 4 + (h >> 3)) * 8]), "r"(l16c) : "memory");
        }
    }
    if (warp == 8) PSTAMP(13);
    cluster_sync();
}

__device__ float g_u[SEQ * 2 * DM];
__global__ void naive_gemm1(const __nv_bfloat16* x, const __nv_bfloat16* Bre, const __nv_bfloat16* Bim) {
    int p = blockIdx.x * 64 + threadIdx.x % 64, tk = blockIdx.y * 4 + threadIdx.x / 64;
    float sr = 0, si = 0;
    for (int d = 0; d < DM; d++) { float xv = __bfloat162float(x[tk * DM + d]); sr += xv * __bfloat162float(Bre[p * DM + d]); si += xv * __bfloat162float(Bim[p * DM + d]); }
    g_u[tk * 2 * DM + 2 * p] = sr; g_u[tk * 2 * DM + 2 * p + 1] = si;
}
__global__ void naive_scan(const __nv_bfloat16* Lre, const __nv_bfloat16* Lim, const __nv_bfloat16* logdt) {
    int p = blockIdx.x * 64 + threadIdx.x;
    float dt = __bfloat162float(__float2bfloat16(expf(__bfloat162float(logdt[p]))));
    float lr = __bfloat162float(Lre[p]), li = __bfloat162float(Lim[p]);
    float e = expf(dt * lr), br = e * cosf(dt * li), bi = e * sinf(dt * li);
    float den = lr * lr + li * li;
    float cr = ((br - 1.f) * lr + bi * li) / den, ci = (bi * lr - (br - 1.f) * li) / den;
    float hr = 0, hi = 0;
    for (int tk = 0; tk < SEQ; tk++) {
        float ur = g_u[tk * 2 * DM + 2 * p], ui = g_u[tk * 2 * DM + 2 * p + 1];
        float nr = br * hr - bi * hi + cr * ur - ci * ui, ni = br * hi + bi * hr + cr * ui + ci * ur;
        hr = nr; hi = ni;
        g_u[tk * 2 * DM + 2 * p] = hr; g_u[tk * 2 * DM + 2 * p + 1] = hi;
    }
}
__global__ void naive_gemm2(const __nv_bfloat16* x, const __nv_bfloat16* Cre, const __nv_bfloat16* Cim, const __nv_bfloat16* Dk, float* out) {
    int d = blockIdx.x * 64 + threadIdx.x % 64, tk = blockIdx.y * 4 + threadIdx.x / 64;
    float s = 0;
    for (int p = 0; p < DM; p++) s += g_u[tk * 2 * DM + 2 * p] * __bfloat162float(Cre[d * DM + p]) - g_u[tk * 2 * DM + 2 * p + 1] * __bfloat162float(Cim[d * DM + p]);
    out[tk * 1152 + d] = 2.f * s + __bfloat162float(__float2bfloat16(__bfloat162float(x[tk * DM + d]) * __bfloat162float(Dk[d])));
}
__device__ float frag_elem(const uint32_t* base, int e, int tok) {
    int eb = e >> 4, g = (e & 15) >> 1, hi = e & 1, j = tok >> 3, t = (tok & 7) >> 1, i = 2 * j + hi;
    uint32_t v = base[eb * 256 + (i >> 2) * 128 + (g * 4 + t) * 4 + (i & 3)];
    return __uint_as_float((tok & 1) ? (v & 0xffff0000u) : (v << 16));
}
__device__ float qk_elem(const uint32_t* base, int isk, int e, int tok) {
    int r = e >> 6, w = (e >> 4) & 3, g = (e & 15) >> 1, hi = e & 1, j = (tok >> 3) & 1;
    int mi = isk ? j * 2 + hi : hi * 2 + j;
    const __nv_bfloat16* p = reinterpret_cast<const __nv_bfloat16*>(base) + r * 4096 + isk * 2048 + (tok >> 4) * 1024 + w * 256 + mi * 64 + (tok & 7) * 8 + g;
    return __bfloat162float(*p);
}
__device__ float fragm_elem(const uint32_t* base, int e, int tok) {
    int eb = e >> 4, g = (e & 15) >> 1, hi = e & 1, t = tok >> 1;
    uint32_t v = base[eb * 64 + (g * 4 + t) * 2 + hi];
    return __uint_as_float((tok & 1) ? (v & 0xffff0000u) : (v << 16));
}
__global__ void naive_attn() {
    int s = blockIdx.x / NH, h = blockIdx.x % NH, q = threadIdx.x;
    const uint32_t* qkv = reinterpret_cast<const uint32_t*>(g_qkv) + (size_t)blockIdx.x * 6144;
    const uint32_t* kvm = reinterpret_cast<const uint32_t*>(g_kvm) + (size_t)blockIdx.x * 1536;
    float p[40], mx = -1e30f, sum = 0;
    for (int k = 0; k < 40; k++) {
        float d = 0;
        for (int e = 0; e < 128; e++)
            d += qk_elem(qkv, 0, e, q) * (k < 8 ? fragm_elem(kvm, e, k) + fragm_elem(kvm + 512, e, k) : qk_elem(qkv, 1, e, k - 8));
        p[k] = (k < 8 || k - 8 <= q) ? d * 0.08838834764831845f : -1e30f;
        mx = fmaxf(mx, p[k]);
    }
    for (int k = 0; k < 40; k++) { p[k] = expf(p[k] - mx); sum += p[k]; }
    __nv_bfloat16* ox = reinterpret_cast<__nv_bfloat16*>(g_ox);
    int tk = s * 32 + q;
    for (int e = 0; e < 128; e++) {
        float o = 0;
        for (int k = 0; k < 40; k++) o += p[k] * (k < 8 ? fragm_elem(kvm + 1024, e, k) : frag_elem(qkv + 4096, e, k - 8));
        int e0 = e & 63, ep = (e0 & 48) + (e0 & 1) * 8 + ((e0 & 15) >> 1);
        ox[((size_t)(h * 2 + (e >> 6)) * SEQ + tk) * 64 + (((ep >> 3) ^ (tk & 7)) << 3) + (ep & 7)] = __float2bfloat16(o / sum);
    }
}
__global__ void naive_wo(const __nv_bfloat16* Wo, float* out) {
    int d = blockIdx.x * 64 + threadIdx.x % 64, tk = blockIdx.y * 4 + threadIdx.x / 64;
    const __nv_bfloat16* ox = reinterpret_cast<const __nv_bfloat16*>(g_ox);
    float s = 0;
    for (int k = 0; k < HD; k++) {
        int hh = k >> 6, e0 = k & 63, e = (e0 & 48) + (e0 & 1) * 8 + ((e0 & 15) >> 1);
        s += __bfloat162float(ox[((size_t)hh * SEQ + tk) * 64 + (((e >> 3) ^ (tk & 7)) << 3) + (e & 7)]) * __bfloat162float(Wo[k * DM + d]);
    }
    out[tk * 1152 + DM + d] = s;
}

typedef CUresult (*EncodeFn)(CUtensorMap*, CUtensorMapDataType, cuuint32_t, void*, const cuuint64_t*, const cuuint64_t*, const cuuint32_t*, const cuuint32_t*,
                             CUtensorMapInterleave, CUtensorMapSwizzle, CUtensorMapL2promotion, CUtensorMapFloatOOBfill);
}

extern "C" void kernel_launch(void* const* d_in, const int* in_sizes, int n_in, void* d_out, int out_size) {
    typedef const __nv_bfloat16* bp;
    bp Ax = (bp)d_in[0], Lre = (bp)d_in[1], Lim = (bp)d_in[2], Bre = (bp)d_in[3], Bim = (bp)d_in[4], Cre = (bp)d_in[5], Cim = (bp)d_in[6],
       logdt = (bp)d_in[7], Dk = (bp)d_in[8], Bx = (bp)d_in[9], mem0 = (bp)d_in[10], Wq = (bp)d_in[11], Wk = (bp)d_in[12], Wv = (bp)d_in[13], Wo = (bp)d_in[14];
    float* out = (float*)d_out;
    static EncodeFn enc = nullptr;
    if (!enc) {
        void* fn = nullptr; cudaDriverEntryPointQueryResult qr;
        cudaGetDriverEntryPoint("cuTensorMapEncodeTiled", &fn, cudaEnableDefault, &qr);
        enc = (EncodeFn)fn;
        cudaFuncSetAttribute(chain_kernel, cudaFuncAttributeMaxDynamicSharedMemorySize, CHAIN_SMEM);
    }
    CUtensorMap tm_x;
    {
        cuuint64_t gd[2] = {DM, SEQ}; cuuint64_t gs[1] = {DM * 2}; cuuint32_t bd[2] = {64, 32}; cuuint32_t es[2] = {1, 1};
        enc(&tm_x, CU_TENSOR_MAP_DATA_TYPE_BFLOAT16, 2, (void*)Bx, gd, gs, bd, es, CU_TENSOR_MAP_INTERLEAVE_NONE, CU_TENSOR_MAP_SWIZZLE_128B,
            CU_TENSOR_MAP_L2_PROMOTION_L2_128B, CU_TENSOR_MAP_FLOAT_OOB_FILL_NONE);
    }
    cudaStream_t st = cudaStreamPerThread;
    chain_kernel<<<96, 384, CHAIN_SMEM, st>>>(tm_x, Bx, mem0, Wq, Wk, Wv, Wo);
    naive_gemm1<<<dim3(9, 512), 256, 0, st>>>(Ax, Bre, Bim);
    naive_scan<<<9, 64, 0, st>>>(Lre, Lim, logdt);
    naive_gemm2<<<dim3(9, 512), 256, 0, st>>>(Ax, Cre, Cim, Dk, out);
    naive_attn<<<NSEG * NH, 32, 0, st>>>();
    naive_wo<<<dim3(9, 512), 256, 0, st>>>(Wo, out);
}
```

```cpp
#include <cuda_runtime.h>
#include <cuda.h>
#include <cuda_bf16.h>
#include <cuda_fp16.h>
#include <stdint.h>

#define D_WAIT 700

#define VSEND 1
#define PREFETCH 1
#define QF 0
namespace {

constexpr int DM = 576, NH = 32, SEQ = 2048, NSEG = 64, HD = 4096;

__device__ uint4 g_acc[64 * 96 * 16];
__device__ uint4 g_ox[NH * 2 * SEQ * 8];
__device__ uint4 g_qkv[NSEG * NH * 3 * 512];
__device__ uint2 g_kvm[NSEG * NH * 3 * 256];
constexpr int NFLAG = 4096;
__device__ __align__(16) unsigned g_flag[NFLAG];
__device__ unsigned g_ticket;
__device__ unsigned long long g_norm[96];

__device__ __forceinline__ uint32_t smem_u32(const void* p) { return (uint32_t)__cvta_generic_to_shared(p); }
__device__ __forceinline__ uint32_t mapa(uint32_t a, uint32_t r) { uint32_t o; asm("mapa.shared::cluster.u32 %0, %1, %2;" : "=r"(o) : "r"(a), "r"(r)); return o; }
__device__ __forceinline__ uint32_t mapa_v(uint32_t a, uint32_t r) { uint32_t o; asm volatile("mapa.shared::cluster.u32 %0, %1, %2;" : "=r"(o) : "r"(a), "r"(r)); return o; }
__device__ __forceinline__ unsigned clk() { unsigned long long c; asm volatile("mov.u64 %0, %%clock64;" : "=l"(c) :: "memory"); return (unsigned)c; }
__device__ __forceinline__ void mbar_init(uint32_t bar, uint32_t cnt) { asm volatile("mbarrier.init.shared::cta.b64 [%0], %1;" :: "r"(bar), "r"(cnt) : "memory"); }
__device__ __forceinline__ void mbar_expect(uint32_t bar, uint32_t bytes) { asm volatile("mbarrier.arrive.expect_tx.shared::cta.b64 _, [%0], %1;" :: "r"(bar), "r"(bytes) : "memory"); }
__device__ __forceinline__ void mbar_wait(uint32_t bar, uint32_t parity) {
    asm volatile("{\n.reg .pred p;\n.reg .u32 n;\nmov.u32 n, 0;\n"
                 "W_%=: mbarrier.try_wait.parity.shared::cta.b64 p, [%0], %1;\n@p bra.uni D_%=;\n"
                 "add.u32 n, n, 1;\nsetp.lt.u32 p, n, 4000000;\n@p bra.uni W_%=;\ntrap;\nD_%=:\n}" :: "r"(bar), "r"(parity) : "memory");
}
__device__ __forceinline__ void mbar_expect_if(uint32_t z, uint32_t bar, uint32_t bytes) {
    asm volatile("{\n.reg .pred p;\nsetp.eq.u32 p, %2, 0;\n@p mbarrier.arrive.expect_tx.shared::cta.b64 _, [%0], %1;\n}" :: "r"(bar), "r"(bytes), "r"(z) : "memory");
}
__device__ __forceinline__ void mbar_arrive_if(uint32_t z, uint32_t bar) {
    asm volatile("{\n.reg .pred p;\nsetp.eq.u32 p, %1, 0;\n@p mbarrier.arrive.shared::cta.b64 _, [%0];\n}" :: "r"(bar), "r"(z) : "memory");
}
__device__ __forceinline__ void sts32_if(uint32_t z, uint32_t a, uint32_t x) {
    asm volatile("{\n.reg .pred p;\nsetp.eq.u32 p, %2, 0;\n@p st.shared.u32 [%0], %1;\n}" :: "r"(a), "r"(x), "r"(z) : "memory");
}
template <int K> __device__ __forceinline__ void sched_fence(int v) {
    asm volatile("{\n.reg .pred p;\nsetp.ne.s32 p, %0, %1;\n@p bra.uni F_%=;\ntrap;\nF_%=:\n}" :: "r"(v), "n"(1000 + K) : "memory");
}
__device__ __forceinline__ void spin_until(unsigned t0, unsigned d) {
    asm volatile("{\n.reg .pred p;\n.reg .u64 c;\n.reg .u32 lo;\n"
                 "S_%=: mov.u64 c, %%clock64;\ncvt.u32.u64 lo, c;\nsub.u32 lo, lo, %0;\nsetp.lt.u32 p, lo, %1;\n@p bra.uni S_%=;\n}" :: "r"(t0), "r"(d) : "memory");
}
__device__ __forceinline__ void bar_sync(int id, int n) { asm volatile("bar.sync %0, %1;" :: "r"(id), "r"(n) : "memory"); }
__device__ __forceinline__ void bar_sync_sel(int sel, int id) {
    asm volatile("{\n.reg .pred p;\nsetp.eq.u32 p, %0, 0;\n@p bar.sync %1, %3;\n@!p bar.sync %2, %3;\n}" :: "r"(sel), "r"(id), "r"(id + 1), "n"(192) : "memory");
}
__device__ __forceinline__ void bar_arrive(int id, int n) { asm volatile("bar.arrive %0, %1;" :: "r"(id), "r"(n) : "memory"); }
__device__ __forceinline__ void fence_async_smem() { asm volatile("fence.proxy.async.shared::cta;" ::: "memory"); }
__device__ __forceinline__ uint32_t pack_bf16(float lo, float hi) { uint32_t r; asm("cvt.rn.bf16x2.f32 %0, %1, %2;" : "=r"(r) : "f"(hi), "f"(lo)); return r; }
__device__ __forceinline__ uint32_t pack_f16(float lo, float hi) { uint32_t r; asm("cvt.rn.f16x2.f32 %0, %1, %2;" : "=r"(r) : "f"(hi), "f"(lo)); return r; }
__device__ __forceinline__ uint32_t f16x2_to_bf16x2(uint32_t v) { float2 f = __half22float2(*reinterpret_cast<__half2*>(&v)); return pack_bf16(f.x, f.y); }
__device__ __forceinline__ float ex2(float x) { float y; asm("ex2.approx.ftz.f32 %0, %1;" : "=f"(y) : "f"(x)); return y; }
__device__ __forceinline__ float ex2v(float x) { float y; asm volatile("ex2.approx.ftz.f32 %0, %1;" : "=f"(y) : "f"(x)); return y; }
__device__ __forceinline__ uint32_t absmax2(uint32_t a, uint32_t b) {
    uint32_t r; asm("max.xorsign.abs.bf16x2 %0, %1, %2;" : "=r"(r) : "r"(a), "r"(b)); return r;
}
__device__ __forceinline__ uint32_t shl_v(uint32_t a, int n) { return a << n; }
__device__ __forceinline__ uint32_t max3u(uint32_t a, uint32_t b, uint32_t c) { return max(max(a, b), c); }
__device__ __forceinline__ uint4 lds128(uint32_t a) { uint4 v; asm volatile("ld.shared.v4.u32 {%0,%1,%2,%3}, [%4];" : "=r"(v.x), "=r"(v.y), "=r"(v.z), "=r"(v.w) : "r"(a) : "memory"); return v; }
__device__ __forceinline__ uint4 lds128v(uint32_t a) { uint4 v; asm volatile("ld.volatile.shared.v4.u32 {%0,%1,%2,%3}, [%4];" : "=r"(v.x), "=r"(v.y), "=r"(v.z), "=r"(v.w) : "r"(a) : "memory"); return v; }
__device__ __forceinline__ float4 lds128f(uint32_t a) { float4 v; asm volatile("ld.shared.v4.f32 {%0,%1,%2,%3}, [%4];" : "=f"(v.x), "=f"(v.y), "=f"(v.z), "=f"(v.w) : "r"(a) : "memory"); return v; }
__device__ __forceinline__ float2 lds64f(uint32_t a) { float2 v; asm volatile("ld.shared.v2.f32 {%0,%1}, [%2];" : "=f"(v.x), "=f"(v.y) : "r"(a) : "memory"); return v; }
__device__ __forceinline__ uint4 lds64x2(uint32_t a) { uint4 v; asm volatile("ld.shared.v2.u32 {%0,%1}, [%4];\nld.shared.v2.u32 {%2,%3}, [%4+256];" : "=r"(v.x), "=r"(v.y), "=r"(v.z), "=r"(v.w) : "r"(a) : "memory"); return v; }
__device__ __forceinline__ uint32_t lds32(uint32_t a) { uint32_t v; asm volatile("ld.shared.u32 %0, [%1];" : "=r"(v) : "r"(a) : "memory"); return v; }
__device__ __forceinline__ void sts128(uint32_t a, uint32_t x, uint32_t y, uint32_t z, uint32_t w) { asm volatile("st.shared.v4.u32 [%0], {%1,%2,%3,%4};" :: "r"(a), "r"(x), "r"(y), "r"(z), "r"(w) : "memory"); }
__device__ __forceinline__ void sts128f(uint32_t a, float x, float y, float z, float w) { asm volatile("st.shared.v4.f32 [%0], {%1,%2,%3,%4};" :: "r"(a), "f"(x), "f"(y), "f"(z), "f"(w) : "memory"); }
__device__ __forceinline__ void sts64(uint32_t a, uint32_t x, uint32_t y) { asm volatile("st.shared.v2.u32 [%0], {%1,%2};" :: "r"(a), "r"(x), "r"(y) : "memory"); }
__device__ __forceinline__ void sts32(uint32_t a, uint32_t x) { asm volatile("st.shared.u32 [%0], %1;" :: "r"(a), "r"(x) : "memory"); }
__device__ __forceinline__ uint4 ldsm4(uint32_t a) { uint4 v; asm volatile("ldmatrix.sync.aligned.m8n8.x4.shared.b16 {%0,%1,%2,%3}, [%4];" : "=r"(v.x), "=r"(v.y), "=r"(v.z), "=r"(v.w) : "r"(a) : "memory"); return v; }
__device__ __forceinline__ void stsm2t(uint32_t a, uint32_t x, uint32_t y) { asm volatile("stmatrix.sync.aligned.m8n8.x2.trans.shared.b16 [%0], {%1,%2};" :: "r"(a), "r"(x), "r"(y) : "memory"); }
__device__ __forceinline__ void stsm4t(uint32_t a, uint32_t x, uint32_t y, uint32_t z, uint32_t w) { asm volatile("stmatrix.sync.aligned.m8n8.x4.trans.shared.b16 [%0], {%1,%2,%3,%4};" :: "r"(a), "r"(x), "r"(y), "r"(z), "r"(w) : "memory"); }
__device__ __forceinline__ void st_async64(uint32_t a, uint32_t x, uint32_t y, uint32_t bar) { asm volatile("st.async.shared::cluster.mbarrier::complete_tx::bytes.v2.b32 [%0], {%1,%2}, [%3];" :: "r"(a), "r"(x), "r"(y), "r"(bar) : "memory"); }
__device__ __forceinline__ void bulk_s2c(uint32_t dst, uint32_t src, uint32_t bytes, uint32_t bar) { asm volatile("cp.async.bulk.shared::cluster.shared::cta.mbarrier::complete_tx::bytes [%0], [%1], %2, [%3];" :: "r"(dst), "r"(src), "r"(bytes), "r"(bar) : "memory"); }
__device__ __forceinline__ void bulk_s2g(void* dst, uint32_t src, uint32_t bytes) { asm volatile("cp.async.bulk.global.shared::cta.bulk_group [%0], [%1], %2;" :: "l"(dst), "r"(src), "r"(bytes) : "memory"); }
__device__ __forceinline__ uint32_t ldg_nc32(const void* p) { uint32_t v; asm volatile("ld.global.nc.L2::128B.u32 %0, [%1];" : "=r"(v) : "l"(p)); return v; }
__device__ __forceinline__ uint4 ldg_relaxed128(const void* p) { uint4 v; asm volatile("ld.relaxed.gpu.global.v4.u32 {%0,%1,%2,%3}, [%4];" : "=r"(v.x), "=r"(v.y), "=r"(v.z), "=r"(v.w) : "l"(p) : "memory"); return v; }
__device__ __forceinline__ void mma16816(float (&d)[4], uint32_t a0, uint32_t a1, uint32_t a2, uint32_t a3, uint32_t b0, uint32_t b1) {
    asm volatile("mma.sync.aligned.m16n8k16.row.col.f32.bf16.bf16.f32 {%0,%1,%2,%3}, {%4,%5,%6,%7}, {%8,%9}, {%0,%1,%2,%3};"
        : "+f"(d[0]), "+f"(d[1]), "+f"(d[2]), "+f"(d[3]) : "r"(a0), "r"(a1), "r"(a2), "r"(a3), "r"(b0), "r"(b1));
}
__device__ __forceinline__ void mma16816_z(float (&d)[4], uint32_t a0, uint32_t a1, uint32_t a2, uint32_t a3, uint32_t b0, uint32_t b1) {
    asm volatile("mma.sync.aligned.m16n8k16.row.col.f32.bf16.bf16.f32 {%0,%1,%2,%3}, {%4,%5,%6,%7}, {%8,%9}, {%10,%10,%10,%10};"
        : "=f"(d[0]), "=f"(d[1]), "=f"(d[2]), "=f"(d[3]) : "r"(a0), "r"(a1), "r"(a2), "r"(a3), "r"(b0), "r"(b1), "f"(0.f));
}
__device__ __forceinline__ void mma1688(float (&d)[4], uint32_t a0, uint32_t a1, uint32_t b0) {
    asm volatile("mma.sync.aligned.m16n8k8.row.col.f32.bf16.bf16.f32 {%0,%1,%2,%3}, {%4,%5}, {%6}, {%0,%1,%2,%3};"
        : "+f"(d[0]), "+f"(d[1]), "+f"(d[2]), "+f"(d[3]) : "r"(a0), "r"(a1), "r"(b0));
}
__device__ __forceinline__ void mma1688_z(float (&d)[4], uint32_t a0, uint32_t a1, uint32_t b0) {
    asm volatile("mma.sync.aligned.m16n8k8.row.col.f32.bf16.bf16.f32 {%0,%1,%2,%3}, {%4,%5}, {%6}, {%7,%7,%7,%7};"
        : "=f"(d[0]), "=f"(d[1]), "=f"(d[2]), "=f"(d[3]) : "r"(a0), "r"(a1), "r"(b0), "f"(0.f));
}
template <int ACC>
__device__ __forceinline__ void wgmma_n32_rs(float (&d)[16], uint32_t a0, uint32_t a1, uint32_t a2, uint32_t a3, uint64_t desc) {
    asm volatile("wgmma.mma_async.sync.aligned.m64n32k16.f32.bf16.bf16 {%0,%1,%2,%3,%4,%5,%6,%7,%8,%9,%10,%11,%12,%13,%14,%15}, {%16,%17,%18,%19}, %20, %21, 1, 1, 0;"
        : "+f"(d[0]), "+f"(d[1]), "+f"(d[2]), "+f"(d[3]), "+f"(d[4]), "+f"(d[5]), "+f"(d[6]), "+f"(d[7]),
          "+f"(d[8]), "+f"(d[9]), "+f"(d[10]), "+f"(d[11]), "+f"(d[12]), "+f"(d[13]), "+f"(d[14]), "+f"(d[15])
        : "r"(a0), "r"(a1), "r"(a2), "r"(a3), "l"(desc), "n"(ACC));
}
template <int ACC>
__device__ __forceinline__ void wgmma_n32_ss(float (&d)[16], uint64_t da, uint64_t db) {
    asm volatile("wgmma.mma_async.sync.aligned.m64n32k16.f32.bf16.bf16 {%0,%1,%2,%3,%4,%5,%6,%7,%8,%9,%10,%11,%12,%13,%14,%15}, %16, %17, %18, 1, 1, 0, 0;"
        : "+f"(d[0]), "+f"(d[1]), "+f"(d[2]), "+f"(d[3]), "+f"(d[4]), "+f"(d[5]), "+f"(d[6]), "+f"(d[7]),
          "+f"(d[8]), "+f"(d[9]), "+f"(d[10]), "+f"(d[11]), "+f"(d[12]), "+f"(d[13]), "+f"(d[14]), "+f"(d[15])
        : "l"(da), "l"(db), "n"(ACC));
}
__device__ __forceinline__ void wg_fence() { asm volatile("wgmma.fence.sync.aligned;" ::: "memory"); }
__device__ __forceinline__ void wg_commit() { asm volatile("wgmma.commit_group.sync.aligned;" ::: "memory"); }
__device__ __forceinline__ void wg_wait0() { asm volatile("wgmma.wait_group.sync.aligned 0;" ::: "memory"); }
__device__ __forceinline__ void cluster_sync() { asm volatile("barrier.cluster.arrive.aligned;\nbarrier.cluster.wait.aligned;" ::: "memory"); }

#define STAMP(s, i) do {} while (0)
#define STAMPV(s, i, v) do {} while (0)

constexpr int XT_BYTES = 36864;
constexpr int O_XT = 0;
constexpr int O_STG = XT_BYTES;
constexpr int O_AS = 3 * XT_BYTES;
constexpr int O_XP = O_AS + 16384;
constexpr int O_QKX = O_XP + 8192;
constexpr int O_QM = O_QKX + 16384;
constexpr int O_KM = O_QM + 2048;
constexpr int O_VX = O_STG + 147456;
constexpr int O_VM = O_VX + 16384;
constexpr int O_SC = O_VM + 2048;
constexpr int O_OF = O_SC + 2560;
constexpr int O_AF = O_OF + 2048;
constexpr int O_WP = O_AF + 4096;
constexpr int O_MF = O_WP + 2048;
constexpr int O_MISC = O_MF + 9216;
static_assert(O_KM + 2048 <= O_VX, "smem");
constexpr int O_BAR = O_MISC + 64;
constexpr int CHAIN_SMEM = O_BAR + 128;
static_assert(CHAIN_SMEM <= 232448, "smem");
constexpr int B_X = O_BAR, B_VX = O_BAR + 24, B_SC = O_BAR + 40, B_W = O_BAR + 48;
constexpr float SM_SCALE = 0.08838834764831845f * 1.4426950408889634f;
constexpr uint32_t ONES = 0x3f803f80u;

__device__ __forceinline__ uint32_t opaque(uint32_t v) { uint32_t o; asm volatile("mov.u32 %0, %1;" : "=r"(o) : "r"(v)); return o; }
__device__ __forceinline__ void st_async128(uint32_t a, uint32_t x, uint32_t y, uint32_t z, uint32_t w, uint32_t bar) {
    asm volatile("st.async.shared::cluster.mbarrier::complete_tx::bytes.v4.b32 [%0], {%1,%2,%3,%4}, [%5];" :: "r"(a), "r"(x), "r"(y), "r"(z), "r"(w), "r"(bar) : "memory");
}
__device__ __forceinline__ void tma_x_tile(uint32_t sb, const CUtensorMap* tm, int r, int j, int slot) {
    asm volatile("{\n.reg .pred p;\nelect.sync _|p, 0xffffffff;\n"
        "@p mbarrier.arrive.expect_tx.shared::cta.b64 _, [%2], 36864;\n"
        "@p cp.async.bulk.tensor.2d.shared::cluster.global.mbarrier::complete_tx::bytes.multicast::cluster [%0], [%1, {%3, %4}], [%2], %7;\n"
        "@p cp.async.bulk.tensor.2d.shared::cluster.global.mbarrier::complete_tx::bytes.multicast::cluster [%0+4096], [%1, {%5, %4}], [%2], %7;\n"
        "@p cp.async.bulk.tensor.2d.shared::cluster.global.mbarrier::complete_tx::bytes.multicast::cluster [%0+8192], [%1, {%6, %4}], [%2], %7;\n}"
        :: "r"(sb + O_XT + slot * XT_BYTES + 3 * r * 4096), "l"(tm), "r"(sb + B_X + 8 * slot), "r"(192 * r), "r"(j * 32), "r"(192 * r + 64), "r"(192 * r + 128),
           "h"((unsigned short)7) : "memory");
}
__device__ __forceinline__ float quad_max(float v) {
    const float a = __shfl_xor_sync(~0u, v, 1), b = __shfl_xor_sync(~0u, v, 2), c = __shfl_xor_sync(~0u, v, 3);
    return fmaxf(fmaxf(v, a), fmaxf(b, c));
}
__device__ __forceinline__ void load_scores(float (&p)[10], uint32_t base, uint32_t stride, uint32_t l16) {
    const float4 a0 = lds128f(base + l16), b0 = lds128f(base + stride + l16);
    const float4 a1 = lds128f(base + 512 + l16), b1 = lds128f(base + stride + 512 + l16);
    const float2 a2 = lds64f(base + 1024 + (l16 >> 1)), b2 = lds64f(base + stride + 1024 + (l16 >> 1));
    p[0] = a2.x + b2.x; p[1] = a2.y + b2.y;
    p[2] = a0.x + b0.x; p[3] = a0.y + b0.y; p[4] = a0.z + b0.z; p[5] = a0.w + b0.w;
    p[6] = a1.x + b1.x; p[7] = a1.y + b1.y; p[8] = a1.z + b1.z; p[9] = a1.w + b1.w;
}
__device__ __forceinline__ float rcp_fast(float x) { float y; asm("rcp.approx.ftz.f32 %0, %1;" : "=f"(y) : "f"(x)); return y; }

__global__ void __cluster_dims__(3, 1, 1) __launch_bounds__(384, 1)
chain_kernel(const __grid_constant__ CUtensorMap tm_x, const __grid_constant__ CUtensorMap tm_q,
             const __grid_constant__ CUtensorMap tm_k, const __grid_constant__ CUtensorMap tm_v,
             const __nv_bfloat16* __restrict__ x, const __nv_bfloat16* __restrict__ mem0,
             const __nv_bfloat16* __restrict__ Wq, const __nv_bfloat16* __restrict__ Wk,
             const __nv_bfloat16* __restrict__ Wv, const __nv_bfloat16* __restrict__ Wo) {
    extern __shared__ __align__(1024) uint8_t smem_raw[];
    const uint32_t sb = smem_u32(smem_raw);
    const int lane = threadIdx.x & 31;
    const int warp = __shfl_sync(~0u, threadIdx.x >> 5, 0);
    const int wg = warp >> 2, w = warp & 3;
    const int h = blockIdx.x / 3, r = blockIdx.x - 3 * h;

#define PSTAMP(i) do {} while (0)
    if (PREFETCH && warp == 9 && lane < 12) {
        const __nv_bfloat16* W = lane < 3 ? Wq : lane < 6 ? Wk : lane < 9 ? Wv : Wo;
        asm volatile("cp.async.bulk.prefetch.L2.global [%0], 16384;" :: "l"(W + (size_t)blockIdx.x * 24576 + (lane % 3) * 8192) : "memory");
    }
    if (threadIdx.x == 0) {
        if (sb & 1023u) __trap();
        for (int i = 0; i < 9; i++) mbar_init(sb + O_BAR + 8 * i, 1);
        asm volatile("fence.mbarrier_init.release.cluster;" ::: "memory");
        for (int i = 0; i < 3; i++) {
            mbar_expect(sb + B_W + 8 * i, 49152);
            for (int tl = 0; tl < 2; tl++)
                asm volatile("cp.async.bulk.tensor.2d.shared::cluster.global.mbarrier::complete_tx::bytes [%0], [%1, {%3, %4}], [%2];"
                    :: "r"(sb + O_STG + tl * 73728 + i * 24576), "l"(r < 2 ? (tl ? &tm_k : &tm_q) : &tm_v), "r"(sb + B_W + 8 * i),
                       "r"(h * 128 + 64 * (r < 2 ? r : tl)), "r"(192 * i) : "memory");
        }
    }
    __syncwarp();
    asm volatile("barrier.cluster.arrive.relaxed.aligned;" ::: "memory");
    if (warp == 0) PSTAMP(9);
    const uint32_t l16c = __shfl_sync(~0u, lane * 16, lane);

    if (wg < 2) {
#define KS(u) ((u) < 8 ? ((u) >> 1) + 4 * ((u) & 1) : (u) < 12 ? (u) : (u) < 20 ? 12 + (((u) - 12) >> 1) + 4 * ((u) & 1) : (u) < 24 ? (u) : (u) + 8)
        asm volatile("setmaxnreg.inc.sync.aligned.u32 184;");
        uint32_t a[144];
        uint32_t adr1;
        {
            const int g = lane >> 2, t = lane & 3;
            asm volatile("barrier.cluster.wait.aligned;" ::: "memory");
            const uint32_t ev = sb + O_STG + (2 * t) * 128 + (((2 * w + (g >> 2)) ^ (2 * t)) << 4) + (g & 3) * 4;
            const uint32_t od = (ev ^ 16) + 128;
            auto gather = [&](int dst, uint32_t off) {
                a[dst] = lds32(ev + off); a[dst + 1] = lds32(od + off); a[dst + 2] = lds32(ev + off + 1024); a[dst + 3] = lds32(od + off + 1024);
            };
            mbar_wait(sb + B_W, 0);
#pragma unroll
            for (int u = 8; u < 12; u++) gather(32 + 4 * u, wg * 73728 + KS(u) * 2048);
            mbar_wait(sb + B_W + 8, 0);
#pragma unroll
            for (int u = 12; u < 24; u++) gather(32 + 4 * u, wg * 73728 + KS(u) * 2048);
            mbar_wait(sb + B_W + 16, 0);
#pragma unroll
            for (int u = 24; u < 28; u++) gather(32 + 4 * u, wg * 73728 + KS(u) * 2048);
#pragma unroll
            for (int u = 0; u < 8; u++) {
                gather(32 + 4 * u, wg * (73728 + 49152) + KS(u) * 2048);
                gather(4 * u, 73728 - wg * (73728 - 49152) + KS(u) * 2048);
            }
#pragma unroll
            for (int kk = 0; kk < 72; kk++) {
                uint32_t w0 = a[2 * kk], w1 = a[2 * kk + 1];
                a[2 * kk] = __byte_perm(w0, w1, 0x5410);
                a[2 * kk + 1] = __byte_perm(w0, w1, 0x7632);
            }
            if (r == 2) {
                float n0[4], n1[4];
#pragma unroll
                for (int u = 0; u < 36; u++) {
                    const uint32_t x0 = a[4 * u] & 0x7fff7fffu, x1 = a[4 * u + 1] & 0x7fff7fffu, x2 = a[4 * u + 2] & 0x7fff7fffu, x3 = a[4 * u + 3] & 0x7fff7fffu;
                    if (u == 0) mma16816_z(n0, x0, x1, x2, x3, ONES, ONES);
                    else if (u < 8) mma16816(n0, x0, x1, x2, x3, ONES, ONES);
                    else if (u == 8) mma16816_z(n1, x0, x1, x2, x3, ONES, ONES);
                    else mma16816(n1, x0, x1, x2, x3, ONES, ONES);
                }
                const uint32_t mx = __reduce_max_sync(~0u, __float_as_uint(2.f * fmaxf(fmaxf(n0[0], n0[2]), fmaxf(n1[0], n1[2]))));
                sts32_if(lane, sb + O_MISC + 32 + 4 * warp, mx);
            }
            if (warp == 0) PSTAMP(11);
            bar_arrive(7, 384);
            asm volatile("barrier.cluster.arrive.relaxed.aligned;" ::: "memory");
            bar_sync(1, 256);
            const uint32_t as = sb + O_AS + wg * 8192 + (16 * w + g) * 128 + t * 4;
            sts32(as + (g << 4), a[32]);
            sts32(as + 1024 + (g << 4), a[33]);
            sts32(as + ((1 ^ g) << 4), a[34]);
            sts32(as + 1024 + ((1 ^ g) << 4), a[35]);
            sts128(sb + O_AF + warp * 512 + lane * 16, a[32], a[33], a[34], a[35]);
            fence_async_smem();
            bar_sync(1, 256);
            const uint32_t l = lane * 16;
            const int mi = lane >> 3, isk = (mi >> 1) ? wg : (wg ^ 1);
            adr1 = (r == 2) ? (sb + O_VM + warp * 256 + (l >> 1))
                            : (isk ? (sb + O_KM + w * 512 + wg * 256 + (mi & 1) * 128 + (l & 127))
                                   : (sb + O_QM + w * 512 + (mi & 1) * 256 + wg * 128 + (l & 127)));
            adr1 = __shfl_sync(~0u, adr1, lane);
        }
        int s3 = 2;
#pragma unroll 1
        for (int s = -1; s < NSEG; s++) {
            const uint32_t l16 = opaque(l16c);
            s3 = (s3 == 2) ? 0 : s3 + 1;
            if (s < 0) mbar_wait(sb + B_X, 0);
            const uint64_t desc0 = (uint64_t)(((sb + O_XT + s3 * XT_BYTES) & 0x3FFFF) >> 4) | (1ull << 16) | (64ull << 32) | (1ull << 62);
            uint32_t km0 = 0, km1 = 0;
            if (s >= 0) {
                { const uint4 v = lds128(sb + O_AF + warp * 512 + l16); a[32] = v.x; a[33] = v.y; a[34] = v.z; a[35] = v.w; }
                float co[4], cw[3][4];
                uint4 b[14];
                float inv;
#define GORD(i) ((i) == 0 ? 0 : (i) == 1 ? 1 : (i) == 5 ? 2 : (i) == 9 ? 3 : (i) < 5 ? (i) + 2 : (i) < 9 ? (i) + 1 : (i))
                auto qkv_mma = [&](int i) {
                    const int gi = GORD(i), u = 8 * gi, n0 = 2 * i, n1 = 2 * i + 1;
                    if (gi < 4) {
                        if (i == 0) mma16816_z(co, a[u], a[u + 1], a[u + 2], a[u + 3], b[0].x, b[0].y);
                        else mma16816(co, a[u], a[u + 1], a[u + 2], a[u + 3], b[i].x, b[i].y);
                    }
                    if (n0 < 3) mma16816_z(cw[n0 % 3], a[32 + u], a[32 + u + 1], a[32 + u + 2], a[32 + u + 3], b[i].x, b[i].y);
                    else mma16816(cw[n0 % 3], a[32 + u], a[32 + u + 1], a[32 + u + 2], a[32 + u + 3], b[i].x, b[i].y);
                    if (n1 < 3) mma16816_z(cw[n1 % 3], a[32 + u + 4], a[32 + u + 5], a[32 + u + 6], a[32 + u + 7], b[i].z, b[i].w);
                    else mma16816(cw[n1 % 3], a[32 + u + 4], a[32 + u + 5], a[32 + u + 6], a[32 + u + 7], b[i].z, b[i].w);
                    if (gi < 4) mma16816(co, a[u + 4], a[u + 5], a[u + 6], a[u + 7], b[i].z, b[i].w);
                };
                const uint32_t mf = sb + O_MF + l16, mfs = mf + wg * 6144;
                if (VSEND == 0 && r == 2) {
                    asm volatile("{\n.reg .pred p;\ncp.async.bulk.wait_group 0;\nelect.sync _|p, 0xffffffff;\nsetp.lt.and.s32 p, %4, 63, p;\n"
                        "@p cp.async.bulk.shared::cluster.global.mbarrier::complete_tx::bytes.multicast::cluster [%1], [%0], 1024, [%2], %3;\n"
                        "fence.proxy.async.global;\n}"
                        :: "l"(reinterpret_cast<char*>(g_qkv) + (size_t)(s * NH + h) * 24576 + 16384 + warp * 1024), "r"(sb + O_VX + (s & 1) * 8192 + warp * 1024),
                           "r"(sb + B_VX + 8 * (s & 1)), "h"((unsigned short)3), "r"(s) : "memory");
                }
                bar_sync(2, 384);
                if (warp == 0) STAMP(s, 0);
                auto qkv_ld = [&](int i) { b[i] = GORD(i) < 4 ? lds128v(mfs + GORD(i) * 512) : lds128v(mf + (GORD(i) < 12 ? GORD(i) : GORD(i) + 4) * 512); };
#pragma unroll
                for (int i = 0; i < 5; i++) qkv_ld(i);
                if (QF >= 1) sched_fence<2>(h);
#pragma unroll
                for (int i = 0; i < 4; i++) { qkv_mma(i); qkv_ld(5 + i); }
                if (QF >= 2) sched_fence<3>(h);
#pragma unroll
                for (int i = 4; i < 9; i++) { qkv_mma(i); qkv_ld(5 + i); }
                inv = __uint_as_float(lds32(sb + O_MISC));
                if (QF >= 3) sched_fence<4>(h);
#pragma unroll
                for (int i = 9; i < 14; i++) qkv_mma(i);
#pragma unroll
                for (int i = 0; i < 4; i++) cw[0][i] += cw[1][i] + cw[2][i];
                if (r < 2) {
                    const uint32_t o0 = pack_bf16(co[0] * inv, co[1] * inv), o1 = pack_bf16(co[2] * inv, co[3] * inv);
                    const uint32_t w0 = pack_bf16(cw[0][0] * inv, cw[0][1] * inv), w1 = pack_bf16(cw[0][2] * inv, cw[0][3] * inv);
                    stsm4t(adr1, o0, o1, w0, w1);
                    km0 = wg ? w0 : o0; km1 = wg ? w1 : o1;
                    if (warp == 0) STAMP(s, 1);
                    asm volatile("{\n.reg .pred p;\nsetp.ge.u32 p, %0, 3;\n@p bar.arrive 1, 256;\n}" :: "r"(warp) : "memory");
                    if (warp < 3 && s < NSEG - 1) {
                        uint4 q[4], k[4];
                        const uint32_t ka = sb + (warp == 2 ? O_KM : O_QKX + (s & 1) * 8192 + 4096 + warp * 2048) + l16;
#pragma unroll
                        for (int i = 0; i < 4; i++) k[i] = ldsm4(ka + i * 512);
                        const uint32_t dst = sb + O_SC + r * 1280 + warp * 512 + (l16 >> 1);
                        bar_sync(1, 256);
#pragma unroll
                        for (int i = 0; i < 4; i++) q[i] = ldsm4(sb + O_QM + i * 512 + l16);
                        if (warp == 2) {
#pragma unroll
                            for (int i = 0; i < 4; i++) k[i] = ldsm4(ka + i * 512);
                        }
                        float s0[4], s1[4], t0[4], t1[4];
                        mma16816_z(s0, q[0].x, q[0].y, q[0].z, q[0].w, k[0].x, k[0].y);
                        mma16816_z(s1, q[0].x, q[0].y, q[0].z, q[0].w, k[0].z, k[0].w);
                        mma16816_z(t0, q[1].x, q[1].y, q[1].z, q[1].w, k[1].x, k[1].y);
                        mma16816_z(t1, q[1].x, q[1].y, q[1].z, q[1].w, k[1].z, k[1].w);
                        mma16816(s0, q[2].x, q[2].y, q[2].z, q[2].w, k[2].x, k[2].y);
                        mma16816(s1, q[2].x, q[2].y, q[2].z, q[2].w, k[2].z, k[2].w);
                        mma16816(t0, q[3].x, q[3].y, q[3].z, q[3].w, k[3].x, k[3].y);
                        mma16816(t1, q[3].x, q[3].y, q[3].z, q[3].w, k[3].z, k[3].w);
                        const float v0 = (s0[0] + s0[2]) + (t0[0] + t0[2]), v1 = (s0[1] + s0[3]) + (t0[1] + t0[3]);
                        const float v2 = (s1[0] + s1[2]) + (t1[0] + t1[2]), v3 = (s1[1] + s1[3]) + (t1[1] + t1[3]);
                        if (warp < 2) {
                            const uint32_t dv = dst + (l16 >> 1);
                            st_async128(mapa(dv, 2), __float_as_uint(v0), __float_as_uint(v1), __float_as_uint(v2), __float_as_uint(v3), mapa(sb + B_SC, 2));
                            st_async128(mapa(dv, r ^ 1), __float_as_uint(v0), __float_as_uint(v1), __float_as_uint(v2), __float_as_uint(v3), mapa(sb + B_SC, r ^ 1));
                            st_async128(mapa(dv, r), __float_as_uint(v0), __float_as_uint(v1), __float_as_uint(v2), __float_as_uint(v3), mapa(sb + B_SC, r));
                        } else {
                            st_async64(mapa(dst, 2), __float_as_uint(v0 + v2), __float_as_uint(v1 + v3), mapa(sb + B_SC, 2));
                            st_async64(mapa(dst, r ^ 1), __float_as_uint(v0 + v2), __float_as_uint(v1 + v3), mapa(sb + B_SC, r ^ 1));
                            st_async64(mapa(dst, r), __float_as_uint(v0 + v2), __float_as_uint(v1 + v3), mapa(sb + B_SC, r));
                        }
                        if (warp == 2) STAMP(s, 2);
                    } else if (warp < 3) {
                        bar_sync(1, 256);
                    }
                } else {
                    sts128f(sb + O_XP + warp * 512 + l16, co[0], co[1], co[2], co[3]);
                    bar_sync(8 + w, 64);
                    const float4 o = lds128f(sb + O_XP + (warp ^ 4) * 512 + l16);
                    km0 = pack_bf16((cw[0][0] + o.x) * inv, (cw[0][1] + o.y) * inv);
                    km1 = pack_bf16((cw[0][2] + o.z) * inv, (cw[0][3] + o.w) * inv);
                    if (warp == 0) STAMP(s, 1);
                    if (s < NSEG - 1) {
                        st_async64(mapa(adr1, 0), km0, km1, mapa(sb + B_SC, 0));
                        st_async64(mapa(adr1, 1), km0, km1, mapa(sb + B_SC, 1));
                        st_async64(mapa(adr1, 2), km0, km1, mapa(sb + B_SC, 2));
                    }
                    if (warp == 0) STAMP(s, 2);
                }
            }
            auto store_qk = [&]() {
                asm volatile("{\n.reg .pred p;\nelect.sync _|p, 0xffffffff;\n"
                    "@p cp.async.bulk.global.shared::cta.bulk_group [%0], [%1], 8192;\n@p cp.async.bulk.commit_group;\n}"
                    :: "l"(reinterpret_cast<char*>(g_qkv) + (size_t)(s * NH + h) * 24576 + r * 8192), "r"(sb + O_QKX + (s & 1) * 8192) : "memory");
            };
            auto store_kvm = [&]() {
                char* p = reinterpret_cast<char*>(g_kvm) + (size_t)(s * NH + h) * 6144 + (r < 2 ? wg * 2048 + (r * 4 + w) * 256 : 4096 + warp * 256) + (l16 >> 1);
                *reinterpret_cast<uint2*>(p) = make_uint2(km0, km1);
            };
            if (s >= 0) bar_sync(3, 384);
            if (s == NSEG - 1) {
                store_kvm();
                if (warp == 3 && r < 2) {
                    store_qk();
                    asm volatile("cp.async.bulk.wait_group 0;\nfence.proxy.async.global;" ::: "memory");
                }
            } else {
                const int j = s + 1;
#define XDESC(u) (((u) < 8 ? descs : desc0) + (uint64_t)(((KS(u) >> 2) * 4096 + (KS(u) & 3) * 32) >> 4))
                const uint64_t descs = desc0 + (uint64_t)(wg * (6 * 4096 >> 4));
                float d[16];
                wg_fence();
#pragma unroll
                for (int u = 0; u < 8; u++) {
                    if (u == 0) wgmma_n32_rs<0>(d, a[0], a[1], a[2], a[3], XDESC(0));
                    else wgmma_n32_rs<1>(d, a[4 * u], a[4 * u + 1], a[4 * u + 2], a[4 * u + 3], XDESC(u));
                }
                wg_commit();
                wg_wait0();
                if (warp == 0) STAMP(s, 15);
                if (s >= 0) bar_sync(4, 384);
#pragma unroll
                for (int q = 0; q < 2; q++)
                    sts128(sb + O_XP + warp * 1024 + q * 512 + l16, pack_bf16(d[8 * q], d[8 * q + 1]), pack_bf16(d[8 * q + 2], d[8 * q + 3]),
                           pack_bf16(d[8 * q + 4], d[8 * q + 5]), pack_bf16(d[8 * q + 6], d[8 * q + 7]));
                if (s >= 0) {
                    store_kvm();
                    if (warp == 3) asm volatile("cp.async.bulk.wait_group 0;\nfence.proxy.async.global;" ::: "memory");
                    if (warp == 1 && s + 2 < NSEG) tma_x_tile(sb, &tm_x, r, s + 2, s3 == 2 ? 0 : s3 + 1);
                }
                bar_sync(12, 256);
#pragma unroll
                for (int q = 0; q < 2; q++) {
                    const uint4 o = lds128(sb + O_XP + (warp ^ 4) * 1024 + q * 512 + l16);
                    d[8 * q] = __uint_as_float(o.x << 16); d[8 * q + 1] = __uint_as_float(o.x & 0xffff0000u);
                    d[8 * q + 2] = __uint_as_float(o.y << 16); d[8 * q + 3] = __uint_as_float(o.y & 0xffff0000u);
                    d[8 * q + 4] = __uint_as_float(o.z << 16); d[8 * q + 5] = __uint_as_float(o.z & 0xffff0000u);
                    d[8 * q + 6] = __uint_as_float(o.w << 16); d[8 * q + 7] = __uint_as_float(o.w & 0xffff0000u);
                }
                if (s >= 0) {
                    if (warp == 6 && (s & 3) == 0 && s >= 4)
                        asm volatile("{\n.reg .pred p;\nsetp.eq.u32 p, %1, 0;\n@p red.release.gpu.global.inc.u32 [%0], 0x7fffffff;\n}"
                                     :: "l"(&g_flag[((s - 1) * 4 + (h >> 3)) * 8]), "r"(l16) : "memory");
                    asm volatile("{\n.reg .pred p;\nsetp.eq.u32 p, %0, 0;\n@p bar.sync 5, 256;\n@!p bar.sync 13, 256;\n}" :: "r"(wg) : "memory");
                }
                const uint64_t da0 = (uint64_t)(((sb + O_AS + wg * 8192) & 0x3FFFF) >> 4) | (1ull << 16) | (64ull << 32) | (1ull << 62);
                wg_fence();
                wgmma_n32_ss<1>(d, da0, XDESC(0));
#pragma unroll
                for (int u = 1; u < 28; u++) wgmma_n32_rs<1>(d, a[32 + 4 * u], a[32 + 4 * u + 1], a[32 + 4 * u + 2], a[32 + 4 * u + 3], XDESC(u));
                wg_commit();
                wg_wait0();
                if (warp == 3 && r < 2 && s >= 0) store_qk();
                if (warp == 4) STAMP(s, 3);
                uint32_t e[8];
#pragma unroll
                for (int i = 0; i < 8; i++) e[i] = pack_bf16(d[2 * i], d[2 * i + 1]);
                if (r < 2) {
                    const uint32_t base = sb + O_QKX + (j & 1) * 8192 + wg * 4096 + w * 512 + l16;
                    stsm4t(base, e[0], wg ? e[1] : e[2], wg ? e[2] : e[1], e[3]);
                    stsm4t(base + 2048, e[4], wg ? e[5] : e[6], wg ? e[6] : e[5], e[7]);
                    fence_async_smem();
                } else {
                    const uint32_t base = sb + O_VX + (j & 1) * 8192 + warp * 1024 + l16;
                    sts128(base, e[0], e[1], e[2], e[3]);
                    sts128(base + 512, e[4], e[5], e[6], e[7]);
                    fence_async_smem();
                    bar_arrive(14, 288);
                }
                if (warp == 7) STAMP(s, 4);
                if (s < 0) asm volatile("barrier.cluster.wait.aligned;" ::: "memory");
            }
        }
        bar_arrive(7, 384);
    } else {
        asm volatile("setmaxnreg.dec.sync.aligned.u32 136;");
        const int c = w;
        uint32_t a[96];
        uint32_t mmax = 0;
        {
            const int g = lane >> 2, t = lane & 3, t2 = threadIdx.x - 256;
#pragma unroll
            for (int i = 0; i < 4; i++) g_acc[(blockIdx.x * 64 + i * 16 + (t2 >> 3)) * 16 + (t2 & 7)] = make_uint4(0, 0, 0, 0);
            if (blockIdx.x == 0) {
#pragma unroll
                for (int i = 0; i < NFLAG / 512; i++) reinterpret_cast<uint4*>(g_flag)[i * 128 + t2] = make_uint4(0, 0, 0, 0);
            }
            uint32_t tag = 0;
            if (t2 == 0) tag = atomicAdd(&g_ticket, 1u);
            asm volatile("barrier.cluster.wait.aligned;" ::: "memory");
            if (c == 0) {
                tma_x_tile(sb, &tm_x, r, 0, 0);
                mbar_expect_if(lane, sb + B_SC, 4608);
                if (r < 2) mbar_expect_if(lane, sb + B_VX, 8192);
                sts32_if(lane, sb + O_MISC, __float_as_uint(1.0f));
                sts32_if(lane, sb + O_MISC + 12, __float_as_uint(SM_SCALE));
            }
            asm volatile("barrier.cluster.arrive.relaxed.aligned;" ::: "memory");
            __threadfence();
            bar_sync(6, 128);
            asm volatile("griddepcontrol.launch_dependents;" ::: "memory");
            tag = (__shfl_sync(~0u, tag, 0) / 96u + 1u) & 0xffffu;
#pragma unroll
            for (int tau = 0; tau < 3; tau++) {
                uint32_t v[6];
#pragma unroll
                for (int i = 0; i < 3; i++) {
                    const uint32_t* p = reinterpret_cast<const uint32_t*>(mem0 + g * DM + 16 * (12 * tau + 4 * i + c) + 2 * t);
                    v[2 * i] = __ldg(p); v[2 * i + 1] = __ldg(p + 4);
                    mmax = __vmaxu2(mmax, __vmaxu2(v[2 * i] & 0x7fff7fffu, v[2 * i + 1] & 0x7fff7fffu));
                }
                sts128(sb + O_MF + tau * 3072 + c * 512 + lane * 16, v[0], v[1], v[2], v[3]);
                sts64(sb + O_MF + tau * 3072 + 2048 + (c >> 1) * 512 + lane * 16 + (c & 1) * 8, v[4], v[5]);
            }
            mmax = max(mmax << 16, mmax & 0xffff0000u);
            bar_arrive(2, 384);
            uint32_t xm = 0;
            const uint4* xp = reinterpret_cast<const uint4*>(x) + blockIdx.x * 1536 + t2;
#pragma unroll
            for (int i = 0; i < 12; i++) {
                uint4 v = __ldg(xp + i * 128);
                xm = __vmaxu2(xm, __vmaxu2(__vmaxu2(v.x & 0x7fff7fffu, v.y & 0x7fff7fffu), __vmaxu2(v.z & 0x7fff7fffu, v.w & 0x7fff7fffu)));
            }
            xm = __reduce_max_sync(~0u, max(xm << 16, xm & 0xffff0000u));

            const __nv_bfloat16* p = Wo + (size_t)(h * 128 + 4 * t) * DM + 192 * r + 16 * c + 2 * g;
#pragma unroll
            for (int i = 0; i < 3; i++)
#pragma unroll
                for (int eb = 0; eb < 8; eb++)
#pragma unroll
                    for (int j = 0; j < 4; j++) a[(i * 8 + eb) * 4 + j] = ldg_nc32(p + (16 * eb + ((j & 1) * 2 + (j >> 1))) * DM + 64 * i);
#pragma unroll
            for (int kk = 0; kk < 48; kk++) {
                uint32_t w0 = a[2 * kk], w1 = a[2 * kk + 1];
                a[2 * kk] = __byte_perm(w0, w1, 0x5410);
                a[2 * kk + 1] = __byte_perm(w0, w1, 0x7632);
            }
            sts128(sb + O_WP + c * 512 + lane * 16, a[92], a[93], a[94], a[95]);
            float wmax = 0.f;
#pragma unroll
            for (int i = 0; i < 3; i++) {
                float n0[4];
#pragma unroll
                for (int u = 8 * i; u < 8 * i + 8; u++) {
                    const uint32_t x0 = a[4 * u] & 0x7fff7fffu, x1 = a[4 * u + 1] & 0x7fff7fffu, x2 = a[4 * u + 2] & 0x7fff7fffu, x3 = a[4 * u + 3] & 0x7fff7fffu;
                    if (u == 8 * i) mma16816_z(n0, x0, x1, x2, x3, ONES, ONES);
                    else mma16816(n0, x0, x1, x2, x3, ONES, ONES);
                }
                wmax = fmaxf(wmax, fmaxf(n0[0], n0[2]));
            }
            uint32_t wm = __reduce_max_sync(~0u, __float_as_uint(wmax));
            sts32_if(lane, sb + O_OF + 4 * c, wm); sts32_if(lane, sb + O_OF + 16 + 4 * c, xm);
            if (c == 0) PSTAMP(8);
            bar_sync(7, 384);
            asm volatile("barrier.cluster.wait.aligned;" ::: "memory");
            if (c == 1) tma_x_tile(sb, &tm_x, r, 1, 1);
            if (c == 0) {
                const uint4 wq = lds128(sb + O_OF), xq = lds128(sb + O_OF + 16), v0 = lds128(sb + O_MISC + 32), v1 = lds128(sb + O_MISC + 48);
                const uint32_t w1 = max(max(wq.x, wq.y), max(wq.z, wq.w)), x1 = max(max(xq.x, xq.y), max(xq.z, xq.w));
                const uint32_t vv = (r < 2) ? 0u : max(max(max(v0.x, v0.y), max(v0.z, v0.w)), max(max(v1.x, v1.y), max(v1.z, v1.w)));
                const uint32_t lo = (min(w1, 0x7f800000u) + 0xffffu) >> 16 | ((min(vv, 0x7f800000u) + 0xffffu) & 0xffff0000u), hi = (x1 & 0xffff0000u) | tag;
                uint32_t l0, h0, l1, h1, l2, h2;
                asm volatile("{\n.reg .pred p;\n.reg .u32 n, x, y;\n.reg .b64 v;\nsetp.eq.u32 p, %10, 0;\nmov.b64 v, {%8, %9};\n@p st.relaxed.gpu.global.b64 [%7], v;\nmov.u32 n, 0;\n"
                             "G_%=: ld.relaxed.gpu.global.b64 v, [%6];\nmov.b64 {%0, %1}, v;\nld.relaxed.gpu.global.b64 v, [%6+256];\nmov.b64 {%2, %3}, v;\n"
                             "ld.relaxed.gpu.global.b64 v, [%6+512];\nmov.b64 {%4, %5}, v;\n"
                             "xor.b32 x, %1, %9;\nxor.b32 y, %3, %9;\nor.b32 x, x, y;\nxor.b32 y, %5, %9;\nor.b32 x, x, y;\nand.b32 x, x, 0xffff;\n"
                             "setp.eq.u32 p, x, 0;\nvote.sync.all.pred p, p, 0xffffffff;\n@p bra.uni E_%=;\n"
                             "add.u32 n, n, 1;\nsetp.lt.u32 p, n, 4000000;\n@p bra.uni G_%=;\ntrap;\nE_%=:\n}"
                             : "=&r"(l0), "=&r"(h0), "=&r"(l1), "=&r"(h1), "=&r"(l2), "=&r"(h2)
                             : "l"(&g_norm[lane]), "l"(&g_norm[blockIdx.x]), "r"(lo), "r"(hi), "r"(lane) : "memory");
                const uint32_t lm = __vmaxu2(l0, __vmaxu2(l1, l2));
                const float fw = __uint_as_float(__reduce_max_sync(~0u, lm << 16));
                const float fv = __uint_as_float(__reduce_max_sync(~0u, lm & 0xffff0000u));
                const float xmax = __uint_as_float(__reduce_max_sync(~0u, max(h0, max(h1, h2)) & 0xffff0000u));
                const float G = 36.f * fw * fv;
                sts32_if(lane, sb + O_MISC + 4, __float_as_uint(G)); sts32_if(lane, sb + O_MISC + 8, __float_as_uint(G * xmax));
            }
        }
        if (c == 0) PSTAMP(12);
        bar_sync(6, 128);
        int s3n = 1;
        uint32_t roff = __shfl_sync(~0u, (r * 4 + c) * 2048 + (lane >> 4) * 512 + (lane & 2) * 128 + (lane & 1) * 64 + (lane & 12) * 4, lane);
        uint32_t poff = __shfl_sync(~0u, c * 2048 + (lane & 4) * 256 + (lane >> 4) * 256 + (lane & 8) * 8 + (lane & 3) * 16, lane);
#pragma unroll 1
        for (int s = 0; s < NSEG; s++) {
            const uint32_t l16 = opaque(l16c);
            const uint32_t vxa = sb + O_VX + (s & 1) * 8192 + c * 2048 + l16;
            if (c == 0 && r == 2) {
                bar_sync(14, 288);
                asm volatile("{\n.reg .pred p;\nelect.sync _|p, 0xffffffff;\n"
                    "@p cp.async.bulk.global.shared::cta.bulk_group [%0], [%1], 8192;\n@p cp.async.bulk.commit_group;\n"
                    "cp.async.bulk.wait_group 0;\nsetp.lt.and.s32 p, %4, 63, p;\n"
                    "@p cp.async.bulk.shared::cluster.global.mbarrier::complete_tx::bytes.multicast::cluster [%1], [%0], 8192, [%2], %3;\n"
                    "fence.proxy.async.global;\n}"
                    :: "l"(reinterpret_cast<char*>(g_qkv) + (size_t)(s * NH + h) * 24576 + 16384), "r"(sb + O_VX + (s & 1) * 8192),
                       "r"(sb + B_VX + 8 * (s & 1)), "h"((unsigned short)3), "r"(s) : "memory");
            }
            if (s == NSEG - 1) { bar_sync(3, 384); break; }
            uint4 vx[4];
            sts32_if(l16, sb + O_MISC + 16 + 4 * c, __reduce_max_sync(~0u, mmax));
            if (c == 0) STAMP(s, 5);
            {
                bar_sync(6, 128);
                const uint4 mm = lds128(sb + O_MISC + 16), cf = lds128(sb + O_MISC);
                const float bound = fmaxf(__uint_as_float(cf.z), __uint_as_float(cf.y) * (__uint_as_float(max(max(mm.x, mm.y), max(mm.z, mm.w))) * __uint_as_float(cf.x)));
                const uint32_t ebits = __reduce_max_sync(~0u, min(max(__float_as_uint(bound) & 0x7f800000u, 21u << 23), 254u << 23));
                mbar_wait(sb + B_X + 8 * s3n, ((s + 1) / 3) & 1);
                s3n = (s3n == 2) ? 0 : s3n + 1;
                bar_sync(3, 384);
                if (r < 2) mbar_wait(sb + B_VX + 8 * (s & 1), (s >> 1) & 1);
                vx[0] = lds128(vxa); vx[2] = lds128(vxa + 1024);
                if (c == 0) STAMP(s, 13);
                mbar_wait(sb + B_SC, s & 1);
                if (c == 0) STAMP(s, 6);
                float p[10];
                load_scores(p, sb + O_SC, 1280, l16);
                float mx = fmaxf(fmaxf(fmaxf(p[0], p[1]), fmaxf(p[2], p[3])), fmaxf(fmaxf(p[4], p[5]), fmaxf(p[6], p[7])));
                mx = quad_max(fmaxf(mx, fmaxf(p[8], p[9])));
                const uint4 vm = lds64x2(sb + O_VM + c * 512 + (l16 >> 1));
                vx[1] = lds128(vxa + 512); vx[3] = lds128(vxa + 1536);
                bar_arrive(4, 384);
                const float sc = __uint_as_float(lds32(sb + O_MISC + 12));
                const float mo = mx * SM_SCALE;
                uint32_t P[5];
#pragma unroll
                for (int n = 0; n < 5; n++) P[n] = pack_bf16(ex2(fmaf(p[2 * n], SM_SCALE, -mo)), ex2(fmaf(p[2 * n + 1], n == 3 ? sc : SM_SCALE, -mo)));
                if (c == 0) STAMP(s, 7);
                float o0[4], o1[4], sm[4];
                mma16816_z(sm, ONES, ONES, ONES, ONES, P[1], P[2]);
                mma16816_z(o0, vx[0].x, vx[0].y, vx[0].z, vx[0].w, P[1], P[2]);
                mma16816_z(o1, vx[2].x, vx[2].y, vx[2].z, vx[2].w, P[1], P[2]);
                mma16816(sm, ONES, ONES, ONES, ONES, P[3], P[4]);
                mma16816(o0, vx[1].x, vx[1].y, vx[1].z, vx[1].w, P[3], P[4]);
                mma16816(o1, vx[3].x, vx[3].y, vx[3].z, vx[3].w, P[3], P[4]);
                mma1688(sm, ONES, ONES, P[0]);
                mma1688(o0, vm.x, vm.y, P[0]);
                mma1688(o1, vm.z, vm.w, P[0]);
                const float sig = __uint_as_float((268u << 23) - ebits);
                const float r0 = rcp_fast(sm[0]) * sig, r1 = rcp_fast(sm[1]) * sig;
                stsm4t(sb + O_OF + c * 512 + l16, pack_bf16(o0[0] * r0, o0[1] * r1), pack_bf16(o0[2] * r0, o0[3] * r1),
                       pack_bf16(o1[0] * r0, o1[1] * r1), pack_bf16(o1[2] * r0, o1[3] * r1));
                bar_sync(6, 128);
                uint4 ob[4];
#pragma unroll
                for (int q = 0; q < 4; q++) ob[q] = ldsm4(sb + O_OF + q * 512 + l16);
                { const uint4 v = lds128(sb + O_WP + c * 512 + l16); a[92] = v.x; a[93] = v.y; a[94] = v.z; a[95] = v.w; }
                float m0[3][4], m1[3][4];
#pragma unroll
                for (int q = 0; q < 4; q++) {
#pragma unroll
                    for (int i = 0; i < 3; i++) {
                        const int k0 = (i * 8 + 2 * q) * 4;
                        if (q == 0) mma16816_z(m0[i], a[k0], a[k0 + 1], a[k0 + 2], a[k0 + 3], ob[q].x, ob[q].y);
                        else mma16816(m0[i], a[k0], a[k0 + 1], a[k0 + 2], a[k0 + 3], ob[q].x, ob[q].y);
                    }
#pragma unroll
                    for (int i = 0; i < 3; i++) {
                        const int k1 = (i * 8 + 2 * q + 1) * 4;
                        if (q == 0) mma16816_z(m1[i], a[k1], a[k1 + 1], a[k1 + 2], a[k1 + 3], ob[q].z, ob[q].w);
                        else mma16816(m1[i], a[k1], a[k1 + 1], a[k1 + 2], a[k1 + 3], ob[q].z, ob[q].w);
                    }
                }
                asm volatile("red.relaxed.gpu.global.add.noftz.v4.f16x2 [%0], {%1,%2,%3,%4};" :: "l"(reinterpret_cast<char*>(g_acc) + roff),
                    "r"(pack_f16(m0[0][0] + m1[0][0], m0[0][2] + m1[0][2])), "r"(pack_f16(m0[1][0] + m1[1][0], m0[1][2] + m1[1][2])),
                    "r"(pack_f16(m0[2][0] + m1[2][0], m0[2][2] + m1[2][2])), "r"(0x3c00u) : "memory");
                asm volatile("red.relaxed.gpu.global.add.noftz.v4.f16x2 [%0], {%1,%2,%3,%4};" :: "l"(reinterpret_cast<char*>(g_acc) + roff + 1024),
                    "r"(pack_f16(m0[0][1] + m1[0][1], m0[0][3] + m1[0][3])), "r"(pack_f16(m0[1][1] + m1[1][1], m0[1][3] + m1[1][3])),
                    "r"(pack_f16(m0[2][1] + m1[2][1], m0[2][3] + m1[2][3])), "r"(0x3c00u) : "memory");
                const unsigned t_red = clk();
                bar_arrive(5, 256);
                bar_arrive(13, 256);
                mbar_expect_if(l16 | c, sb + B_SC, 4608);
                mbar_expect_if(l16 | (c ^ 1) | (r >> 1), sb + B_VX + 8 * ((s + 1) & 1), 8192);
                sts32_if(l16 | (c ^ 3), sb + O_MISC, ebits - (14u << 23));
                if (c == 0) STAMPV(s, 8, t_red);
                const char* pbase = reinterpret_cast<const char*>(g_acc) + poff;
                spin_until(t_red, D_WAIT);
                uint4 v[6];
#pragma unroll
                for (int i = 0; i < 6; i++) v[i] = ldg_relaxed128(pbase + (i >> 1) * 8192 + (i & 1) * 512);
                int nretry = 0;
                auto hand_over = [&]() -> uint32_t {
                    uint32_t ok = 0;
#pragma unroll
                    for (int tau = 0; tau < 3; tau++) {
                        if (tau == 1) sched_fence<0>(h);
                        if (tau == 2) {
                            sched_fence<1>(h);
                            asm volatile("{\n.reg .pred p, q;\n.reg .b32 x;\nlop3.b32 x, %1, %2, %3, 0x80;\nlop3.b32 x, x, %4, %5, 0x80;\nand.b32 x, x, %6;\n"
                                         "setp.eq.u32 p, x, 0x5000;\nvote.sync.all.pred q, p, 0xffffffff;\nselp.u32 %0, 1, 0, q;\n}"
                                         : "=r"(ok) : "r"(v[0].w), "r"(v[1].w), "r"(v[2].w), "r"(v[3].w), "r"(v[4].w), "r"(v[5].w));
                        }
                        v[2 * tau].x = f16x2_to_bf16x2(v[2 * tau].x); v[2 * tau + 1].x = f16x2_to_bf16x2(v[2 * tau + 1].x);
                        v[2 * tau].y = f16x2_to_bf16x2(v[2 * tau].y); v[2 * tau + 1].y = f16x2_to_bf16x2(v[2 * tau + 1].y);
                        v[2 * tau].z = f16x2_to_bf16x2(v[2 * tau].z); v[2 * tau + 1].z = f16x2_to_bf16x2(v[2 * tau + 1].z);
                        sts128(sb + O_MF + tau * 3072 + c * 512 + l16, v[2 * tau].x, v[2 * tau + 1].x, v[2 * tau].y, v[2 * tau + 1].y);
                        sts64(sb + O_MF + tau * 3072 + 2048 + (c >> 1) * 512 + (c & 1) * 8 + l16, v[2 * tau].z, v[2 * tau + 1].z);
                    }
                    asm volatile("{\n.reg .pred p;\nsetp.ne.u32 p, %0, 0;\n@p bar.arrive 2, 384;\n}" :: "r"(ok) : "memory");
                    return ok;
                };
                if (!hand_over()) {
                    asm volatile("{\n.reg .pred p, q;\n.reg .u32 n, x;\nmov.u32 n, 0;\n"
                         "R_%=: ld.relaxed.gpu.global.v4.u32 {%0,%1,%2,%3}, [%25];\nld.relaxed.gpu.global.v4.u32 {%4,%5,%6,%7}, [%25+512];\n"
                         "ld.relaxed.gpu.global.v4.u32 {%8,%9,%10,%11}, [%25+8192];\nld.relaxed.gpu.global.v4.u32 {%12,%13,%14,%15}, [%25+8704];\n"
                         "ld.relaxed.gpu.global.v4.u32 {%16,%17,%18,%19}, [%25+16384];\nld.relaxed.gpu.global.v4.u32 {%20,%21,%22,%23}, [%25+16896];\n"
                         "add.u32 %24, %24, 1;\nand.b32 x, %3, %7;\nand.b32 x, x, %11;\nand.b32 x, x, %15;\nand.b32 x, x, %19;\nand.b32 x, x, %23;\n"
                         "setp.eq.u32 p, x, 0x5000;\nvote.sync.all.pred q, p, 0xffffffff;\n@q bra.uni K_%=;\n"
                         "add.u32 n, n, 1;\nsetp.lt.u32 q, n, 2000000;\n@q bra.uni R_%=;\ntrap;\nK_%=:\n}"
                         : "+r"(v[0].x), "+r"(v[0].y), "+r"(v[0].z), "+r"(v[0].w), "+r"(v[1].x), "+r"(v[1].y), "+r"(v[1].z), "+r"(v[1].w),
                           "+r"(v[2].x), "+r"(v[2].y), "+r"(v[2].z), "+r"(v[2].w), "+r"(v[3].x), "+r"(v[3].y), "+r"(v[3].z), "+r"(v[3].w),
                           "+r"(v[4].x), "+r"(v[4].y), "+r"(v[4].z), "+r"(v[4].w), "+r"(v[5].x), "+r"(v[5].y), "+r"(v[5].z), "+r"(v[5].w), "+r"(nretry)
                         : "l"(pbase) : "memory");
                    hand_over();
                }
                if (c == 0) STAMP(s, 12);
                if (c == 0) STAMPV(s, 14, nretry);
                mmax = absmax2(absmax2(absmax2(v[0].x, v[0].y), absmax2(v[0].z, v[1].x)), absmax2(absmax2(v[1].y, v[1].z), absmax2(v[2].x, v[2].y)));
                mmax = absmax2(mmax, absmax2(absmax2(absmax2(v[2].z, v[3].x), absmax2(v[3].y, v[3].z)), absmax2(absmax2(v[4].x, v[4].y), absmax2(v[4].z, v[5].x))));
                mmax = absmax2(mmax, absmax2(v[5].y, v[5].z)) & 0x7fff7fffu;
                mmax = max(mmax << 16, mmax & 0xffff0000u);
            }
            roff += 24576; poff += 24576;
        }
        {
            bar_sync(7, 384);
            if (c == 0)
                asm volatile("{\n.reg .pred p;\nsetp.eq.u32 p, %1, 0;\n@p red.release.gpu.global.inc.u32 [%0], 0x7fffffff;\n}"
                             :: "l"(&g_flag[(63 * 4 + (h >> 3)) * 8]), "r"(l16c) : "memory");
        }
    }
    if (warp == 8) PSTAMP(13);
    cluster_sync();
}

__device__ float g_u[SEQ * 2 * DM];
__global__ void naive_gemm1(const __nv_bfloat16* x, const __nv_bfloat16* Bre, const __nv_bfloat16* Bim) {
    int p = blockIdx.x * 64 + threadIdx.x % 64, tk = blockIdx.y * 4 + threadIdx.x / 64;
    float sr = 0, si = 0;
    for (int d = 0; d < DM; d++) { float xv = __bfloat162float(x[tk * DM + d]); sr += xv * __bfloat162float(Bre[p * DM + d]); si += xv * __bfloat162float(Bim[p * DM + d]); }
    g_u[tk * 2 * DM + 2 * p] = sr; g_u[tk * 2 * DM + 2 * p + 1] = si;
}
__global__ void naive_scan(const __nv_bfloat16* Lre, const __nv_bfloat16* Lim, const __nv_bfloat16* logdt) {
    int p = blockIdx.x * 64 + threadIdx.x;
    float dt = __bfloat162float(__float2bfloat16(expf(__bfloat162float(logdt[p]))));
    float lr = __bfloat162float(Lre[p]), li = __bfloat162float(Lim[p]);
    float e = expf(dt * lr), br = e * cosf(dt * li), bi = e * sinf(dt * li);
    float den = lr * lr + li * li;
    float cr = ((br - 1.f) * lr + bi * li) / den, ci = (bi * lr - (br - 1.f) * li) / den;
    float hr = 0, hi = 0;
    for (int tk = 0; tk < SEQ; tk++) {
        float ur = g_u[tk * 2 * DM + 2 * p], ui = g_u[tk * 2 * DM + 2 * p + 1];
        float nr = br * hr - bi * hi + cr * ur - ci * ui, ni = br * hi + bi * hr + cr * ui + ci * ur;
        hr = nr; hi = ni;
        g_u[tk * 2 * DM + 2 * p] = hr; g_u[tk * 2 * DM + 2 * p + 1] = hi;
    }
}
__global__ void naive_gemm2(const __nv_bfloat16* x, const __nv_bfloat16* Cre, const __nv_bfloat16* Cim, const __nv_bfloat16* Dk, float* out) {
    int d = blockIdx.x * 64 + threadIdx.x % 64, tk = blockIdx.y * 4 + threadIdx.x / 64;
    float s = 0;
    for (int p = 0; p < DM; p++) s += g_u[tk * 2 * DM + 2 * p] * __bfloat162float(Cre[d * DM + p]) - g_u[tk * 2 * DM + 2 * p + 1] * __bfloat162float(Cim[d * DM + p]);
    out[tk * 1152 + d] = 2.f * s + __bfloat162float(__float2bfloat16(__bfloat162float(x[tk * DM + d]) * __bfloat162float(Dk[d])));
}
__device__ float frag_elem(const uint32_t* base, int e, int tok) {
    int eb = e >> 4, g = (e & 15) >> 1, hi = e & 1, j = tok >> 3, t = (tok & 7) >> 1, i = 2 * j + hi;
    uint32_t v = base[eb * 256 + (i >> 2) * 128 + (g * 4 + t) * 4 + (i & 3)];
    return __uint_as_float((tok & 1) ? (v & 0xffff0000u) : (v << 16));
}
__device__ float qk_elem(const uint32_t* base, int isk, int e, int tok) {
    int r = e >> 6, w = (e >> 4) & 3, g = (e & 15) >> 1, hi = e & 1, j = (tok >> 3) & 1;
    int mi = isk ? j * 2 + hi : hi * 2 + j;
    const __nv_bfloat16* p = reinterpret_cast<const __nv_bfloat16*>(base) + r * 4096 + isk * 2048 + (tok >> 4) * 1024 + w * 256 + mi * 64 + (tok & 7) * 8 + g;
    return __bfloat162float(*p);
}
__device__ float fragm_elem(const uint32_t* base, int e, int tok) {
    int eb = e >> 4, g = (e & 15) >> 1, hi = e & 1, t = tok >> 1;
    uint32_t v = base[eb * 64 + (g * 4 + t) * 2 + hi];
    return __uint_as_float((tok & 1) ? (v & 0xffff0000u) : (v << 16));
}
__global__ void naive_attn() {
    int s = blockIdx.x / NH, h = blockIdx.x % NH, q = threadIdx.x;
    const uint32_t* qkv = reinterpret_cast<const uint32_t*>(g_qkv) + (size_t)blockIdx.x * 6144;
    const uint32_t* kvm = reinterpret_cast<const uint32_t*>(g_kvm) + (size_t)blockIdx.x * 1536;
    float p[40], mx = -1e30f, sum = 0;
    for (int k = 0; k < 40; k++) {
        float d = 0;
        for (int e = 0; e < 128; e++)
            d += qk_elem(qkv, 0, e, q) * (k < 8 ? fragm_elem(kvm, e, k) + fragm_elem(kvm + 512, e, k) : qk_elem(qkv, 1, e, k - 8));
        p[k] = (k < 8 || k - 8 <= q) ? d * 0.08838834764831845f : -1e30f;
        mx = fmaxf(mx, p[k]);
    }
    for (int k = 0; k < 40; k++) { p[k] = expf(p[k] - mx); sum += p[k]; }
    __nv_bfloat16* ox = reinterpret_cast<__nv_bfloat16*>(g_ox);
    int tk = s * 32 + q;
    for (int e = 0; e < 128; e++) {
        float o = 0;
        for (int k = 0; k < 40; k++) o += p[k] * (k < 8 ? fragm_elem(kvm + 1024, e, k) : frag_elem(qkv + 4096, e, k - 8));
        int e0 = e & 63, ep = (e0 & 48) + (e0 & 1) * 8 + ((e0 & 15) >> 1);
        ox[((size_t)(h * 2 + (e >> 6)) * SEQ + tk) * 64 + (((ep >> 3) ^ (tk & 7)) << 3) + (ep & 7)] = __float2bfloat16(o / sum);
    }
}
__global__ void naive_wo(const __nv_bfloat16* Wo, float* out) {
    int d = blockIdx.x * 64 + threadIdx.x % 64, tk = blockIdx.y * 4 + threadIdx.x / 64;
    const __nv_bfloat16* ox = reinterpret_cast<const __nv_bfloat16*>(g_ox);
    float s = 0;
    for (int k = 0; k < HD; k++) {
        int hh = k >> 6, e0 = k & 63, e = (e0 & 48) + (e0 & 1) * 8 + ((e0 & 15) >> 1);
        s += __bfloat162float(ox[((size_t)hh * SEQ + tk) * 64 + (((e >> 3) ^ (tk & 7)) << 3) + (e & 7)]) * __bfloat162float(Wo[k * DM + d]);
    }
    out[tk * 1152 + DM + d] = s;
}

typedef CUresult (*EncodeFn)(CUtensorMap*, CUtensorMapDataType, cuuint32_t, void*, const cuuint64_t*, const cuuint64_t*, const cuuint32_t*, const cuuint32_t*,
                             CUtensorMapInterleave, CUtensorMapSwizzle, CUtensorMapL2promotion, CUtensorMapFloatOOBfill);
}

extern "C" void kernel_launch(void* const* d_in, const int* in_sizes, int n_in, void* d_out, int out_size) {
    typedef const __nv_bfloat16* bp;
    bp Ax = (bp)d_in[0], Lre = (bp)d_in[1], Lim = (bp)d_in[2], Bre = (bp)d_in[3], Bim = (bp)d_in[4], Cre = (bp)d_in[5], Cim = (bp)d_in[6],
       logdt = (bp)d_in[7], Dk = (bp)d_in[8], Bx = (bp)d_in[9], mem0 = (bp)d_in[10], Wq = (bp)d_in[11], Wk = (bp)d_in[12], Wv = (bp)d_in[13], Wo = (bp)d_in[14];
    float* out = (float*)d_out;
    static EncodeFn enc = nullptr;
    if (!enc) {
        void* fn = nullptr; cudaDriverEntryPointQueryResult qr;
        cudaGetDriverEntryPoint("cuTensorMapEncodeTiled", &fn, cudaEnableDefault, &qr);
        enc = (EncodeFn)fn;
        cudaFuncSetAttribute(chain_kernel, cudaFuncAttributeMaxDynamicSharedMemorySize, CHAIN_SMEM);
    }
    CUtensorMap tm_x;
    {
        cuuint64_t gd[2] = {DM, SEQ}; cuuint64_t gs[1] = {DM * 2}; cuuint32_t bd[2] = {64, 32}; cuuint32_t es[2] = {1, 1};
        enc(&tm_x, CU_TENSOR_MAP_DATA_TYPE_BFLOAT16, 2, (void*)Bx, gd, gs, bd, es, CU_TENSOR_MAP_INTERLEAVE_NONE, CU_TENSOR_MAP_SWIZZLE_128B,
            CU_TENSOR_MAP_L2_PROMOTION_L2_128B, CU_TENSOR_MAP_FLOAT_OOB_FILL_NONE);
    }
    CUtensorMap tm_w[3];
    for (int i = 0; i < 3; i++) {
        cuuint64_t gd[2] = {HD, DM}; cuuint64_t gs[1] = {HD * 2}; cuuint32_t bd[2] = {64, 192}; cuuint32_t es[2] = {1, 1};
        enc(&tm_w[i], CU_TENSOR_MAP_DATA_TYPE_BFLOAT16, 2, (void*)(i == 0 ? Wq : i == 1 ? Wk : Wv), gd, gs, bd, es, CU_TENSOR_MAP_INTERLEAVE_NONE,
            CU_TENSOR_MAP_SWIZZLE_128B, CU_TENSOR_MAP_L2_PROMOTION_L2_128B, CU_TENSOR_MAP_FLOAT_OOB_FILL_NONE);
    }
    cudaStream_t st = cudaStreamPerThread;
    chain_kernel<<<96, 384, CHAIN_SMEM, st>>>(tm_x, tm_w[0], tm_w[1], tm_w[2], Bx, mem0, Wq, Wk, Wv, Wo);
    naive_gemm1<<<dim3(9, 512), 256, 0, st>>>(Ax, Bre, Bim);
    naive_scan<<<9, 64, 0, st>>>(Lre, Lim, logdt);
    naive_gemm2<<<dim3(9, 512), 256, 0, st>>>(Ax, Cre, Cim, Dk, out);
    naive_attn<<<NSEG * NH, 32, 0, st>>>();
    naive_wo<<<dim3(9, 512), 256, 0, st>>>(Wo, out);
}
```

```cpp
#include <cuda_runtime.h>
#include <cuda.h>
#include <cuda_bf16.h>
#include <cuda_fp16.h>
#include <stdint.h>

#define D_WAIT 700

#define VSEND 1
#define PREFETCH 1
#define QF 0
namespace {

constexpr int DM = 576, NH = 32, SEQ = 2048, NSEG = 64, HD = 4096;

__device__ uint4 g_acc[64 * 96 * 16];
__device__ uint4 g_ox[NH * 2 * SEQ * 8];
__device__ uint4 g_qkv[NSEG * NH * 3 * 512];
__device__ uint2 g_kvm[NSEG * NH * 3 * 256];
constexpr int NFLAG = 4096;
__device__ __align__(16) unsigned g_flag[NFLAG];
__device__ unsigned g_ticket;
__device__ unsigned long long g_norm[96];

__device__ __forceinline__ uint32_t smem_u32(const void* p) { return (uint32_t)__cvta_generic_to_shared(p); }
__device__ __forceinline__ uint32_t mapa(uint32_t a, uint32_t r) { uint32_t o; asm("mapa.shared::cluster.u32 %0, %1, %2;" : "=r"(o) : "r"(a), "r"(r)); return o; }
__device__ __forceinline__ uint32_t mapa_v(uint32_t a, uint32_t r) { uint32_t o; asm volatile("mapa.shared::cluster.u32 %0, %1, %2;" : "=r"(o) : "r"(a), "r"(r)); return o; }
__device__ __forceinline__ unsigned clk() { unsigned long long c; asm volatile("mov.u64 %0, %%clock64;" : "=l"(c) :: "memory"); return (unsigned)c; }
__device__ __forceinline__ void mbar_init(uint32_t bar, uint32_t cnt) { asm volatile("mbarrier.init.shared::cta.b64 [%0], %1;" :: "r"(bar), "r"(cnt) : "memory"); }
__device__ __forceinline__ void mbar_expect(uint32_t bar, uint32_t bytes) { asm volatile("mbarrier.arrive.expect_tx.shared::cta.b64 _, [%0], %1;" :: "r"(bar), "r"(bytes) : "memory"); }
__device__ __forceinline__ void mbar_wait(uint32_t bar, uint32_t parity) {
    asm volatile("{\n.reg .pred p;\n.reg .u32 n;\nmov.u32 n, 0;\n"
                 "W_%=: mbarrier.try_wait.parity.shared::cta.b64 p, [%0], %1;\n@p bra.uni D_%=;\n"
                 "add.u32 n, n, 1;\nsetp.lt.u32 p, n, 4000000;\n@p bra.uni W_%=;\ntrap;\nD_%=:\n}" :: "r"(bar), "r"(parity) : "memory");
}
__device__ __forceinline__ void mbar_expect_if(uint32_t z, uint32_t bar, uint32_t bytes) {
    asm volatile("{\n.reg .pred p;\nsetp.eq.u32 p, %2, 0;\n@p mbarrier.arrive.expect_tx.shared::cta.b64 _, [%0], %1;\n}" :: "r"(bar), "r"(bytes), "r"(z) : "memory");
}
__device__ __forceinline__ void mbar_arrive_if(uint32_t z, uint32_t bar) {
    asm volatile("{\n.reg .pred p;\nsetp.eq.u32 p, %1, 0;\n@p mbarrier.arrive.shared::cta.b64 _, [%0];\n}" :: "r"(bar), "r"(z) : "memory");
}
__device__ __forceinline__ void sts32_if(uint32_t z, uint32_t a, uint32_t x) {
    asm volatile("{\n.reg .pred p;\nsetp.eq.u32 p, %2, 0;\n@p st.shared.u32 [%0], %1;\n}" :: "r"(a), "r"(x), "r"(z) : "memory");
}
template <int K> __device__ __forceinline__ void sched_fence(int v) {
    asm volatile("{\n.reg .pred p;\nsetp.ne.s32 p, %0, %1;\n@p bra.uni F_%=;\ntrap;\nF_%=:\n}" :: "r"(v), "n"(1000 + K) : "memory");
}
__device__ __forceinline__ void spin_until(unsigned t0, unsigned d) {
    asm volatile("{\n.reg .pred p;\n.reg .u64 c;\n.reg .u32 lo;\n"
                 "S_%=: mov.u64 c, %%clock64;\ncvt.u32.u64 lo, c;\nsub.u32 lo, lo, %0;\nsetp.lt.u32 p, lo, %1;\n@p bra.uni S_%=;\n}" :: "r"(t0), "r"(d) : "memory");
}
__device__ __forceinline__ void bar_sync(int id, int n) { asm volatile("bar.sync %0, %1;" :: "r"(id), "r"(n) : "memory"); }
__device__ __forceinline__ void bar_sync_sel(int sel, int id) {
    asm volatile("{\n.reg .pred p;\nsetp.eq.u32 p, %0, 0;\n@p bar.sync %1, %3;\n@!p bar.sync %2, %3;\n}" :: "r"(sel), "r"(id), "r"(id + 1), "n"(192) : "memory");
}
__device__ __forceinline__ void bar_arrive(int id, int n) { asm volatile("bar.arrive %0, %1;" :: "r"(id), "r"(n) : "memory"); }
__device__ __forceinline__ void fence_async_smem() { asm volatile("fence.proxy.async.shared::cta;" ::: "memory"); }
__device__ __forceinline__ uint32_t pack_bf16(float lo, float hi) { uint32_t r; asm("cvt.rn.bf16x2.f32 %0, %1, %2;" : "=r"(r) : "f"(hi), "f"(lo)); return r; }
__device__ __forceinline__ uint32_t pack_f16(float lo, float hi) { uint32_t r; asm("cvt.rn.f16x2.f32 %0, %1, %2;" : "=r"(r) : "f"(hi), "f"(lo)); return r; }
__device__ __forceinline__ uint32_t f16x2_to_bf16x2(uint32_t v) { float2 f = __half22float2(*reinterpret_cast<__half2*>(&v)); return pack_bf16(f.x, f.y); }
__device__ __forceinline__ float ex2(float x) { float y; asm("ex2.approx.ftz.f32 %0, %1;" : "=f"(y) : "f"(x)); return y; }
__device__ __forceinline__ float ex2v(float x) { float y; asm volatile("ex2.approx.ftz.f32 %0, %1;" : "=f"(y) : "f"(x)); return y; }
__device__ __forceinline__ uint32_t absmax2(uint32_t a, uint32_t b) {
    uint32_t r; asm("max.xorsign.abs.bf16x2 %0, %1, %2;" : "=r"(r) : "r"(a), "r"(b)); return r;
}
__device__ __forceinline__ uint32_t shl_v(uint32_t a, int n) { return a << n; }
__device__ __forceinline__ uint32_t max3u(uint32_t a, uint32_t b, uint32_t c) { return max(max(a, b), c); }
__device__ __forceinline__ uint4 lds128(uint32_t a) { uint4 v; asm volatile("ld.shared.v4.u32 {%0,%1,%2,%3}, [%4];" : "=r"(v.x), "=r"(v.y), "=r"(v.z), "=r"(v.w) : "r"(a) : "memory"); return v; }
__device__ __forceinline__ uint4 lds128v(uint32_t a) { uint4 v; asm volatile("ld.volatile.shared.v4.u32 {%0,%1,%2,%3}, [%4];" : "=r"(v.x), "=r"(v.y), "=r"(v.z), "=r"(v.w) : "r"(a) : "memory"); return v; }
__device__ __forceinline__ float4 lds128f(uint32_t a) { float4 v; asm volatile("ld.shared.v4.f32 {%0,%1,%2,%3}, [%4];" : "=f"(v.x), "=f"(v.y), "=f"(v.z), "=f"(v.w) : "r"(a) : "memory"); return v; }
__device__ __forceinline__ float2 lds64f(uint32_t a) { float2 v; asm volatile("ld.shared.v2.f32 {%0,%1}, [%2];" : "=f"(v.x), "=f"(v.y) : "r"(a) : "memory"); return v; }
__device__ __forceinline__ uint4 lds64x2(uint32_t a) { uint4 v; asm volatile("ld.shared.v2.u32 {%0,%1}, [%4];\nld.shared.v2.u32 {%2,%3}, [%4+256];" : "=r"(v.x), "=r"(v.y), "=r"(v.z), "=r"(v.w) : "r"(a) : "memory"); return v; }
__device__ __forceinline__ uint32_t lds32(uint32_t a) { uint32_t v; asm volatile("ld.shared.u32 %0, [%1];" : "=r"(v) : "r"(a) : "memory"); return v; }
__device__ __forceinline__ void sts128(uint32_t a, uint32_t x, uint32_t y, uint32_t z, uint32_t w) { asm volatile("st.shared.v4.u32 [%0], {%1,%2,%3,%4};" :: "r"(a), "r"(x), "r"(y), "r"(z), "r"(w) : "memory"); }
__device__ __forceinline__ void sts128f(uint32_t a, float x, float y, float z, float w) { asm volatile("st.shared.v4.f32 [%0], {%1,%2,%3,%4};" :: "r"(a), "f"(x), "f"(y), "f"(z), "f"(w) : "memory"); }
__device__ __forceinline__ void sts64(uint32_t a, uint32_t x, uint32_t y) { asm volatile("st.shared.v2.u32 [%0], {%1,%2};" :: "r"(a), "r"(x), "r"(y) : "memory"); }
__device__ __forceinline__ void sts32(uint32_t a, uint32_t x) { asm volatile("st.shared.u32 [%0], %1;" :: "r"(a), "r"(x) : "memory"); }
__device__ __forceinline__ uint4 ldsm4(uint32_t a) { uint4 v; asm volatile("ldmatrix.sync.aligned.m8n8.x4.shared.b16 {%0,%1,%2,%3}, [%4];" : "=r"(v.x), "=r"(v.y), "=r"(v.z), "=r"(v.w) : "r"(a) : "memory"); return v; }
__device__ __forceinline__ void stsm2t(uint32_t a, uint32_t x, uint32_t y) { asm volatile("stmatrix.sync.aligned.m8n8.x2.trans.shared.b16 [%0], {%1,%2};" :: "r"(a), "r"(x), "r"(y) : "memory"); }
__device__ __forceinline__ void stsm4t(uint32_t a, uint32_t x, uint32_t y, uint32_t z, uint32_t w) { asm volatile("stmatrix.sync.aligned.m8n8.x4.trans.shared.b16 [%0], {%1,%2,%3,%4};" :: "r"(a), "r"(x), "r"(y), "r"(z), "r"(w) : "memory"); }
__device__ __forceinline__ void st_async64(uint32_t a, uint32_t x, uint32_t y, uint32_t bar) { asm volatile("st.async.shared::cluster.mbarrier::complete_tx::bytes.v2.b32 [%0], {%1,%2}, [%3];" :: "r"(a), "r"(x), "r"(y), "r"(bar) : "memory"); }
__device__ __forceinline__ void bulk_s2c(uint32_t dst, uint32_t src, uint32_t bytes, uint32_t bar) { asm volatile("cp.async.bulk.shared::cluster.shared::cta.mbarrier::complete_tx::bytes [%0], [%1], %2, [%3];" :: "r"(dst), "r"(src), "r"(bytes), "r"(bar) : "memory"); }
__device__ __forceinline__ void bulk_s2g(void* dst, uint32_t src, uint32_t bytes) { asm volatile("cp.async.bulk.global.shared::cta.bulk_group [%0], [%1], %2;" :: "l"(dst), "r"(src), "r"(bytes) : "memory"); }
__device__ __forceinline__ uint32_t ldg_nc32(const void* p) { uint32_t v; asm volatile("ld.global.nc.L2::128B.u32 %0, [%1];" : "=r"(v) : "l"(p)); return v; }
__device__ __forceinline__ uint4 ldg_relaxed128(const void* p) { uint4 v; asm volatile("ld.relaxed.gpu.global.v4.u32 {%0,%1,%2,%3}, [%4];" : "=r"(v.x), "=r"(v.y), "=r"(v.z), "=r"(v.w) : "l"(p) : "memory"); return v; }
__device__ __forceinline__ void mma16816(float (&d)[4], uint32_t a0, uint32_t a1, uint32_t a2, uint32_t a3, uint32_t b0, uint32_t b1) {
    asm volatile("mma.sync.aligned.m16n8k16.row.col.f32.bf16.bf16.f32 {%0,%1,%2,%3}, {%4,%5,%6,%7}, {%8,%9}, {%0,%1,%2,%3};"
        : "+f"(d[0]), "+f"(d[1]), "+f"(d[2]), "+f"(d[3]) : "r"(a0), "r"(a1), "r"(a2), "r"(a3), "r"(b0), "r"(b1));
}
__device__ __forceinline__ void mma16816_z(float (&d)[4], uint32_t a0, uint32_t a1, uint32_t a2, uint32_t a3, uint32_t b0, uint32_t b1) {
    asm volatile("mma.sync.aligned.m16n8k16.row.col.f32.bf16.bf16.f32 {%0,%1,%2,%3}, {%4,%5,%6,%7}, {%8,%9}, {%10,%10,%10,%10};"
        : "=f"(d[0]), "=f"(d[1]), "=f"(d[2]), "=f"(d[3]) : "r"(a0), "r"(a1), "r"(a2), "r"(a3), "r"(b0), "r"(b1), "f"(0.f));
}
__device__ __forceinline__ void mma1688(float (&d)[4], uint32_t a0, uint32_t a1, uint32_t b0) {
    asm volatile("mma.sync.aligned.m16n8k8.row.col.f32.bf16.bf16.f32 {%0,%1,%2,%3}, {%4,%5}, {%6}, {%0,%1,%2,%3};"
        : "+f"(d[0]), "+f"(d[1]), "+f"(d[2]), "+f"(d[3]) : "r"(a0), "r"(a1), "r"(b0));
}
__device__ __forceinline__ void mma1688_z(float (&d)[4], uint32_t a0, uint32_t a1, uint32_t b0) {
    asm volatile("mma.sync.aligned.m16n8k8.row.col.f32.bf16.bf16.f32 {%0,%1,%2,%3}, {%4,%5}, {%6}, {%7,%7,%7,%7};"
        : "=f"(d[0]), "=f"(d[1]), "=f"(d[2]), "=f"(d[3]) : "r"(a0), "r"(a1), "r"(b0), "f"(0.f));
}
template <int ACC>
__device__ __forceinline__ void wgmma_n32_rs(float (&d)[16], uint32_t a0, uint32_t a1, uint32_t a2, uint32_t a3, uint64_t desc) {
    asm volatile("wgmma.mma_async.sync.aligned.m64n32k16.f32.bf16.bf16 {%0,%1,%2,%3,%4,%5,%6,%7,%8,%9,%10,%11,%12,%13,%14,%15}, {%16,%17,%18,%19}, %20, %21, 1, 1, 0;"
        : "+f"(d[0]), "+f"(d[1]), "+f"(d[2]), "+f"(d[3]), "+f"(d[4]), "+f"(d[5]), "+f"(d[6]), "+f"(d[7]),
          "+f"(d[8]), "+f"(d[9]), "+f"(d[10]), "+f"(d[11]), "+f"(d[12]), "+f"(d[13]), "+f"(d[14]), "+f"(d[15])
        : "r"(a0), "r"(a1), "r"(a2), "r"(a3), "l"(desc), "n"(ACC));
}
template <int ACC>
__device__ __forceinline__ void wgmma_n32_ss(float (&d)[16], uint64_t da, uint64_t db) {
    asm volatile("wgmma.mma_async.sync.aligned.m64n32k16.f32.bf16.bf16 {%0,%1,%2,%3,%4,%5,%6,%7,%8,%9,%10,%11,%12,%13,%14,%15}, %16, %17, %18, 1, 1, 0, 0;"
        : "+f"(d[0]), "+f"(d[1]), "+f"(d[2]), "+f"(d[3]), "+f"(d[4]), "+f"(d[5]), "+f"(d[6]), "+f"(d[7]),
          "+f"(d[8]), "+f"(d[9]), "+f"(d[10]), "+f"(d[11]), "+f"(d[12]), "+f"(d[13]), "+f"(d[14]), "+f"(d[15])
        : "l"(da), "l"(db), "n"(ACC));
}
__device__ __forceinline__ void wg_fence() { asm volatile("wgmma.fence.sync.aligned;" ::: "memory"); }
__device__ __forceinline__ void wg_commit() { asm volatile("wgmma.commit_group.sync.aligned;" ::: "memory"); }
__device__ __forceinline__ void wg_wait0() { asm volatile("wgmma.wait_group.sync.aligned 0;" ::: "memory"); }
__device__ __forceinline__ void cluster_sync() { asm volatile("barrier.cluster.arrive.aligned;\nbarrier.cluster.wait.aligned;" ::: "memory"); }

#define STAMP(s, i) do {} while (0)
#define STAMPV(s, i, v) do {} while (0)

constexpr int XT_BYTES = 36864;
constexpr int O_XT = 0;
constexpr int O_STG = XT_BYTES;
constexpr int O_AS = 3 * XT_BYTES;
constexpr int O_XP = O_AS + 16384;
constexpr int O_QKX = O_XP + 8192;
constexpr int O_QM = O_QKX + 16384;
constexpr int O_KM = O_QM + 2048;
constexpr int O_VX = O_STG + 147456;
constexpr int O_VM = O_VX + 16384;
constexpr int O_SC = O_VM + 2048;
constexpr int O_OF = O_SC + 2560;
constexpr int O_AF = O_OF + 2048;
constexpr int O_WP = O_AF + 4096;
constexpr int O_MF = O_WP + 2048;
constexpr int O_MISC = O_MF + 9216;
static_assert(O_KM + 2048 <= O_VX, "smem");
constexpr int O_BAR = O_MISC + 64;
constexpr int CHAIN_SMEM = O_BAR + 128;
static_assert(CHAIN_SMEM <= 232448, "smem");
constexpr int B_X = O_BAR, B_VX = O_BAR + 24, B_SC = O_BAR + 40, B_W = O_BAR + 48;
constexpr float SM_SCALE = 0.08838834764831845f * 1.4426950408889634f;
constexpr uint32_t ONES = 0x3f803f80u;

__device__ __forceinline__ uint32_t opaque(uint32_t v) { uint32_t o; asm volatile("mov.u32 %0, %1;" : "=r"(o) : "r"(v)); return o; }
__device__ __forceinline__ void st_async128(uint32_t a, uint32_t x, uint32_t y, uint32_t z, uint32_t w, uint32_t bar) {
    asm volatile("st.async.shared::cluster.mbarrier::complete_tx::bytes.v4.b32 [%0], {%1,%2,%3,%4}, [%5];" :: "r"(a), "r"(x), "r"(y), "r"(z), "r"(w), "r"(bar) : "memory");
}
__device__ __forceinline__ void tma_x_tile(uint32_t sb, const CUtensorMap* tm, int r, int j, int slot) {
    asm volatile("{\n.reg .pred p;\nelect.sync _|p, 0xffffffff;\n"
        "@p mbarrier.arrive.expect_tx.shared::cta.b64 _, [%2], 36864;\n"
        "@p cp.async.bulk.tensor.2d.shared::cluster.global.mbarrier::complete_tx::bytes.multicast::cluster [%0], [%1, {%3, %4}], [%2], %7;\n"
        "@p cp.async.bulk.tensor.2d.shared::cluster.global.mbarrier::complete_tx::bytes.multicast::cluster [%0+4096], [%1, {%5, %4}], [%2], %7;\n"
        "@p cp.async.bulk.tensor.2d.shared::cluster.global.mbarrier::complete_tx::bytes.multicast::cluster [%0+8192], [%1, {%6, %4}], [%2], %7;\n}"
        :: "r"(sb + O_XT + slot * XT_BYTES + 3 * r * 4096), "l"(tm), "r"(sb + B_X + 8 * slot), "r"(192 * r), "r"(j * 32), "r"(192 * r + 64), "r"(192 * r + 128),
           "h"((unsigned short)7) : "memory");
}
__device__ __forceinline__ float quad_max(float v) {
    const float a = __shfl_xor_sync(~0u, v, 1), b = __shfl_xor_sync(~0u, v, 2), c = __shfl_xor_sync(~0u, v, 3);
    return fmaxf(fmaxf(v, a), fmaxf(b, c));
}
__device__ __forceinline__ void load_scores(float (&p)[10], uint32_t base, uint32_t stride, uint32_t l16) {
    const float4 a0 = lds128f(base + l16), b0 = lds128f(base + stride + l16);
    const float4 a1 = lds128f(base + 512 + l16), b1 = lds128f(base + stride + 512 + l16);
    const float2 a2 = lds64f(base + 1024 + (l16 >> 1)), b2 = lds64f(base + stride + 1024 + (l16 >> 1));
    p[0] = a2.x + b2.x; p[1] = a2.y + b2.y;
    p[2] = a0.x + b0.x; p[3] = a0.y + b0.y; p[4] = a0.z + b0.z; p[5] = a0.w + b0.w;
    p[6] = a1.x + b1.x; p[7] = a1.y + b1.y; p[8] = a1.z + b1.z; p[9] = a1.w + b1.w;
}
__device__ __forceinline__ float rcp_fast(float x) { float y; asm("rcp.approx.ftz.f32 %0, %1;" : "=f"(y) : "f"(x)); return y; }

__global__ void __cluster_dims__(3, 1, 1) __launch_bounds__(384, 1)
chain_kernel(const __grid_constant__ CUtensorMap tm_x, const __grid_constant__ CUtensorMap tm_q,
             const __grid_constant__ CUtensorMap tm_k, const __grid_constant__ CUtensorMap tm_v,
             const __nv_bfloat16* __restrict__ x, const __nv_bfloat16* __restrict__ mem0,
             const __nv_bfloat16* __restrict__ Wq, const __nv_bfloat16* __restrict__ Wk,
             const __nv_bfloat16* __restrict__ Wv, const __nv_bfloat16* __restrict__ Wo) {
    extern __shared__ __align__(1024) uint8_t smem_raw[];
    const uint32_t sb = smem_u32(smem_raw);
    const int lane = threadIdx.x & 31;
    const int warp = __shfl_sync(~0u, threadIdx.x >> 5, 0);
    const int wg = warp >> 2, w = warp & 3;
    const int h = blockIdx.x / 3, r = blockIdx.x - 3 * h;

#define PSTAMP(i) do {} while (0)
    if (PREFETCH && warp == 9 && lane < 12) {
        const __nv_bfloat16* W = lane < 3 ? Wq : lane < 6 ? Wk : lane < 9 ? Wv : Wo;
        asm volatile("cp.async.bulk.prefetch.L2.global [%0], 16384;" :: "l"(W + (size_t)blockIdx.x * 24576 + (lane % 3) * 8192) : "memory");
    }
    if (threadIdx.x == 0) {
        if (sb & 1023u) __trap();
        for (int i = 0; i < 9; i++) mbar_init(sb + O_BAR + 8 * i, 1);
        asm volatile("fence.mbarrier_init.release.cluster;" ::: "memory");
        for (int i = 0; i < 3; i++) {
            mbar_expect(sb + B_W + 8 * i, 49152);
            for (int tl = 0; tl < 2; tl++)
                asm volatile("cp.async.bulk.tensor.2d.shared::cluster.global.mbarrier::complete_tx::bytes [%0], [%1, {%3, %4}], [%2];"
                    :: "r"(sb + O_STG + tl * 73728 + i * 24576), "l"(r < 2 ? (tl ? &tm_k : &tm_q) : &tm_v), "r"(sb + B_W + 8 * i),
                       "r"(h * 128 + 64 * (r < 2 ? r : tl)), "r"(192 * i) : "memory");
        }
    }
    __syncwarp();
    asm volatile("barrier.cluster.arrive.relaxed.aligned;" ::: "memory");
    if (warp == 0) PSTAMP(9);
    const uint32_t l16c = __shfl_sync(~0u, lane * 16, lane);

    if (wg < 2) {
#define KS(u) ((u) < 8 ? ((u) >> 1) + 4 * ((u) & 1) : (u) < 12 ? (u) : (u) < 20 ? 12 + (((u) - 12) >> 1) + 4 * ((u) & 1) : (u) < 24 ? (u) : (u) + 8)
        asm volatile("setmaxnreg.inc.sync.aligned.u32 184;");
        uint32_t a[144];
        uint32_t adr1;
        {
            const int g = lane >> 2, t = lane & 3;
            const int t1 = threadIdx.x;
#pragma unroll
            for (int i = 0; i < 2; i++) g_acc[(blockIdx.x * 64 + i * 32 + (t1 >> 3)) * 16 + (t1 & 7)] = make_uint4(0, 0, 0, 0);
            if (blockIdx.x == 0) {
#pragma unroll
                for (int i = 0; i < NFLAG / 1024; i++) reinterpret_cast<uint4*>(g_flag)[i * 256 + t1] = make_uint4(0, 0, 0, 0);
            }
            uint32_t xm = 0;
            const uint4* xp = reinterpret_cast<const uint4*>(x) + blockIdx.x * 1536 + t1;
#pragma unroll
            for (int i = 0; i < 6; i++) {
                uint4 v = __ldg(xp + i * 256);
                xm = __vmaxu2(xm, __vmaxu2(__vmaxu2(v.x & 0x7fff7fffu, v.y & 0x7fff7fffu), __vmaxu2(v.z & 0x7fff7fffu, v.w & 0x7fff7fffu)));
            }
            sts32_if(lane, sb + O_OF + 16 + 4 * warp, __reduce_max_sync(~0u, max(xm << 16, xm & 0xffff0000u)));
            __threadfence();
            bar_sync(1, 256);
            asm volatile("griddepcontrol.launch_dependents;" ::: "memory");
            asm volatile("barrier.cluster.wait.aligned;" ::: "memory");
            const uint32_t ev = sb + O_STG + (2 * t) * 128 + (((2 * w + (g >> 2)) ^ (2 * t)) << 4) + (g & 3) * 4;
            const uint32_t od = (ev ^ 16) + 128;
            auto gather = [&](int dst, uint32_t off) {
                a[dst] = lds32(ev + off); a[dst + 1] = lds32(od + off); a[dst + 2] = lds32(ev + off + 1024); a[dst + 3] = lds32(od + off + 1024);
            };
            mbar_wait(sb + B_W, 0);
#pragma unroll
            for (int u = 8; u < 12; u++) gather(32 + 4 * u, wg * 73728 + KS(u) * 2048);
            mbar_wait(sb + B_W + 8, 0);
#pragma unroll
            for (int u = 12; u < 24; u++) gather(32 + 4 * u, wg * 73728 + KS(u) * 2048);
            mbar_wait(sb + B_W + 16, 0);
#pragma unroll
            for (int u = 24; u < 28; u++) gather(32 + 4 * u, wg * 73728 + KS(u) * 2048);
#pragma unroll
            for (int u = 0; u < 8; u++) {
                gather(32 + 4 * u, wg * (73728 + 49152) + KS(u) * 2048);
                gather(4 * u, 73728 - wg * (73728 - 49152) + KS(u) * 2048);
            }
#pragma unroll
            for (int kk = 0; kk < 72; kk++) {
                uint32_t w0 = a[2 * kk], w1 = a[2 * kk + 1];
                a[2 * kk] = __byte_perm(w0, w1, 0x5410);
                a[2 * kk + 1] = __byte_perm(w0, w1, 0x7632);
            }
            if (r == 2) {
                float n0[4], n1[4];
#pragma unroll
                for (int u = 0; u < 36; u++) {
                    const uint32_t x0 = a[4 * u] & 0x7fff7fffu, x1 = a[4 * u + 1] & 0x7fff7fffu, x2 = a[4 * u + 2] & 0x7fff7fffu, x3 = a[4 * u + 3] & 0x7fff7fffu;
                    if (u == 0) mma16816_z(n0, x0, x1, x2, x3, ONES, ONES);
                    else if (u < 8) mma16816(n0, x0, x1, x2, x3, ONES, ONES);
                    else if (u == 8) mma16816_z(n1, x0, x1, x2, x3, ONES, ONES);
                    else mma16816(n1, x0, x1, x2, x3, ONES, ONES);
                }
                const uint32_t mx = __reduce_max_sync(~0u, __float_as_uint(2.f * fmaxf(fmaxf(n0[0], n0[2]), fmaxf(n1[0], n1[2]))));
                sts32_if(lane, sb + O_MISC + 32 + 4 * warp, mx);
            }
            if (warp == 0) PSTAMP(11);
            bar_arrive(7, 384);
            asm volatile("barrier.cluster.arrive.relaxed.aligned;" ::: "memory");
            bar_sync(1, 256);
            const uint32_t as = sb + O_AS + wg * 8192 + (16 * w + g) * 128 + t * 4;
            sts32(as + (g << 4), a[32]);
            sts32(as + 1024 + (g << 4), a[33]);
            sts32(as + ((1 ^ g) << 4), a[34]);
            sts32(as + 1024 + ((1 ^ g) << 4), a[35]);
            sts128(sb + O_AF + warp * 512 + lane * 16, a[32], a[33], a[34], a[35]);
            fence_async_smem();
            bar_sync(1, 256);
            const uint32_t l = lane * 16;
            const int mi = lane >> 3, isk = (mi >> 1) ? wg : (wg ^ 1);
            adr1 = (r == 2) ? (sb + O_VM + warp * 256 + (l >> 1))
                            : (isk ? (sb + O_KM + w * 512 + wg * 256 + (mi & 1) * 128 + (l & 127))
                                   : (sb + O_QM + w * 512 + (mi & 1) * 256 + wg * 128 + (l & 127)));
            adr1 = __shfl_sync(~0u, adr1, lane);
        }
        int s3 = 2;
#pragma unroll 1
        for (int s = -1; s < NSEG; s++) {
            const uint32_t l16 = opaque(l16c);
            s3 = (s3 == 2) ? 0 : s3 + 1;
            if (s < 0) mbar_wait(sb + B_X, 0);
            const uint64_t desc0 = (uint64_t)(((sb + O_XT + s3 * XT_BYTES) & 0x3FFFF) >> 4) | (1ull << 16) | (64ull << 32) | (1ull << 62);
            uint32_t km0 = 0, km1 = 0;
            if (s >= 0) {
                { const uint4 v = lds128(sb + O_AF + warp * 512 + l16); a[32] = v.x; a[33] = v.y; a[34] = v.z; a[35] = v.w; }
                float co[4], cw[3][4];
                uint4 b[14];
                float inv;
#define GORD(i) ((i) == 0 ? 0 : (i) == 1 ? 1 : (i) == 5 ? 2 : (i) == 9 ? 3 : (i) < 5 ? (i) + 2 : (i) < 9 ? (i) + 1 : (i))
                auto qkv_mma = [&](int i) {
                    const int gi = GORD(i), u = 8 * gi, n0 = 2 * i, n1 = 2 * i + 1;
                    if (gi < 4) {
                        if (i == 0) mma16816_z(co, a[u], a[u + 1], a[u + 2], a[u + 3], b[0].x, b[0].y);
                        else mma16816(co, a[u], a[u + 1], a[u + 2], a[u + 3], b[i].x, b[i].y);
                    }
                    if (n0 < 3) mma16816_z(cw[n0 % 3], a[32 + u], a[32 + u + 1], a[32 + u + 2], a[32 + u + 3], b[i].x, b[i].y);
                    else mma16816(cw[n0 % 3], a[32 + u], a[32 + u + 1], a[32 + u + 2], a[32 + u + 3], b[i].x, b[i].y);
                    if (n1 < 3) mma16816_z(cw[n1 % 3], a[32 + u + 4], a[32 + u + 5], a[32 + u + 6], a[32 + u + 7], b[i].z, b[i].w);
                    else mma16816(cw[n1 % 3], a[32 + u + 4], a[32 + u + 5], a[32 + u + 6], a[32 + u + 7], b[i].z, b[i].w);
                    if (gi < 4) mma16816(co, a[u + 4], a[u + 5], a[u + 6], a[u + 7], b[i].z, b[i].w);
                };
                const uint32_t mf = sb + O_MF + l16, mfs = mf + wg * 6144;
                if (VSEND == 0 && r == 2) {
                    asm volatile("{\n.reg .pred p;\ncp.async.bulk.wait_group 0;\nelect.sync _|p, 0xffffffff;\nsetp.lt.and.s32 p, %4, 63, p;\n"
                        "@p cp.async.bulk.shared::cluster.global.mbarrier::complete_tx::bytes.multicast::cluster [%1], [%0], 1024, [%2], %3;\n"
                        "fence.proxy.async.global;\n}"
                        :: "l"(reinterpret_cast<char*>(g_qkv) + (size_t)(s * NH + h) * 24576 + 16384 + warp * 1024), "r"(sb + O_VX + (s & 1) * 8192 + warp * 1024),
                           "r"(sb + B_VX + 8 * (s & 1)), "h"((unsigned short)3), "r"(s) : "memory");
                }
                bar_sync(2, 384);
                if (warp == 0) STAMP(s, 0);
                auto qkv_ld = [&](int i) { b[i] = GORD(i) < 4 ? lds128v(mfs + GORD(i) * 512) : lds128v(mf + (GORD(i) < 12 ? GORD(i) : GORD(i) + 4) * 512); };
#pragma unroll
                for (int i = 0; i < 5; i++) qkv_ld(i);
                if (QF >= 1) sched_fence<2>(h);
#pragma unroll
                for (int i = 0; i < 4; i++) { qkv_mma(i); qkv_ld(5 + i); }
                if (QF >= 2) sched_fence<3>(h);
#pragma unroll
                for (int i = 4; i < 9; i++) { qkv_mma(i); qkv_ld(5 + i); }
                inv = __uint_as_float(lds32(sb + O_MISC));
                if (QF >= 3) sched_fence<4>(h);
#pragma unroll
                for (int i = 9; i < 14; i++) qkv_mma(i);
#pragma unroll
                for (int i = 0; i < 4; i++) cw[0][i] += cw[1][i] + cw[2][i];
                if (r < 2) {
                    const uint32_t o0 = pack_bf16(co[0] * inv, co[1] * inv), o1 = pack_bf16(co[2] * inv, co[3] * inv);
                    const uint32_t w0 = pack_bf16(cw[0][0] * inv, cw[0][1] * inv), w1 = pack_bf16(cw[0][2] * inv, cw[0][3] * inv);
                    stsm4t(adr1, o0, o1, w0, w1);
                    km0 = wg ? w0 : o0; km1 = wg ? w1 : o1;
                    if (warp == 0) STAMP(s, 1);
                    asm volatile("{\n.reg .pred p;\nsetp.ge.u32 p, %0, 3;\n@p bar.arrive 1, 256;\n}" :: "r"(warp) : "memory");
                    if (warp < 3 && s < NSEG - 1) {
                        uint4 q[4], k[4];
                        const uint32_t ka = sb + (warp == 2 ? O_KM : O_QKX + (s & 1) * 8192 + 4096 + warp * 2048) + l16;
#pragma unroll
                        for (int i = 0; i < 4; i++) k[i] = ldsm4(ka + i * 512);
                        const uint32_t dst = sb + O_SC + r * 1280 + warp * 512 + (l16 >> 1);
                        bar_sync(1, 256);
#pragma unroll
                        for (int i = 0; i < 4; i++) q[i] = ldsm4(sb + O_QM + i * 512 + l16);
                        if (warp == 2) {
#pragma unroll
                            for (int i = 0; i < 4; i++) k[i] = ldsm4(ka + i * 512);
                        }
                        float s0[4], s1[4], t0[4], t1[4];
                        mma16816_z(s0, q[0].x, q[0].y, q[0].z, q[0].w, k[0].x, k[0].y);
                        mma16816_z(s1, q[0].x, q[0].y, q[0].z, q[0].w, k[0].z, k[0].w);
                        mma16816_z(t0, q[1].x, q[1].y, q[1].z, q[1].w, k[1].x, k[1].y);
                        mma16816_z(t1, q[1].x, q[1].y, q[1].z, q[1].w, k[1].z, k[1].w);
                        mma16816(s0, q[2].x, q[2].y, q[2].z, q[2].w, k[2].x, k[2].y);
                        mma16816(s1, q[2].x, q[2].y, q[2].z, q[2].w, k[2].z, k[2].w);
                        mma16816(t0, q[3].x, q[3].y, q[3].z, q[3].w, k[3].x, k[3].y);
                        mma16816(t1, q[3].x, q[3].y, q[3].z, q[3].w, k[3].z, k[3].w);
                        const float v0 = (s0[0] + s0[2]) + (t0[0] + t0[2]), v1 = (s0[1] + s0[3]) + (t0[1] + t0[3]);
                        const float v2 = (s1[0] + s1[2]) + (t1[0] + t1[2]), v3 = (s1[1] + s1[3]) + (t1[1] + t1[3]);
                        if (warp < 2) {
                            const uint32_t dv = dst + (l16 >> 1);
                            st_async128(mapa(dv, 2), __float_as_uint(v0), __float_as_uint(v1), __float_as_uint(v2), __float_as_uint(v3), mapa(sb + B_SC, 2));
                            st_async128(mapa(dv, r ^ 1), __float_as_uint(v0), __float_as_uint(v1), __float_as_uint(v2), __float_as_uint(v3), mapa(sb + B_SC, r ^ 1));
                            st_async128(mapa(dv, r), __float_as_uint(v0), __float_as_uint(v1), __float_as_uint(v2), __float_as_uint(v3), mapa(sb + B_SC, r));
                        } else {
                            st_async64(mapa(dst, 2), __float_as_uint(v0 + v2), __float_as_uint(v1 + v3), mapa(sb + B_SC, 2));
                            st_async64(mapa(dst, r ^ 1), __float_as_uint(v0 + v2), __float_as_uint(v1 + v3), mapa(sb + B_SC, r ^ 1));
                            st_async64(mapa(dst, r), __float_as_uint(v0 + v2), __float_as_uint(v1 + v3), mapa(sb + B_SC, r));
                        }
                        if (warp == 2) STAMP(s, 2);
                    } else if (warp < 3) {
                        bar_sync(1, 256);
                    }
                } else {
                    sts128f(sb + O_XP + warp * 512 + l16, co[0], co[1], co[2], co[3]);
                    bar_sync(8 + w, 64);
                    const float4 o = lds128f(sb + O_XP + (warp ^ 4) * 512 + l16);
                    km0 = pack_bf16((cw[0][0] + o.x) * inv, (cw[0][1] + o.y) * inv);
                    km1 = pack_bf16((cw[0][2] + o.z) * inv, (cw[0][3] + o.w) * inv);
                    if (warp == 0) STAMP(s, 1);
                    if (s < NSEG - 1) {
                        st_async64(mapa(adr1, 0), km0, km1, mapa(sb + B_SC, 0));
                        st_async64(mapa(adr1, 1), km0, km1, mapa(sb + B_SC, 1));
                        st_async64(mapa(adr1, 2), km0, km1, mapa(sb + B_SC, 2));
                    }
                    if (warp == 0) STAMP(s, 2);
                }
            }
            auto store_qk = [&]() {
                asm volatile("{\n.reg .pred p;\nelect.sync _|p, 0xffffffff;\n"
                    "@p cp.async.bulk.global.shared::cta.bulk_group [%0], [%1], 8192;\n@p cp.async.bulk.commit_group;\n}"
                    :: "l"(reinterpret_cast<char*>(g_qkv) + (size_t)(s * NH + h) * 24576 + r * 8192), "r"(sb + O_QKX + (s & 1) * 8192) : "memory");
            };
            auto store_kvm = [&]() {
                char* p = reinterpret_cast<char*>(g_kvm) + (size_t)(s * NH + h) * 6144 + (r < 2 ? wg * 2048 + (r * 4 + w) * 256 : 4096 + warp * 256) + (l16 >> 1);
                *reinterpret_cast<uint2*>(p) = make_uint2(km0, km1);
            };
            if (s >= 0) bar_sync(3, 384);
            if (s == NSEG - 1) {
                store_kvm();
                if (warp == 3 && r < 2) {
                    store_qk();
                    asm volatile("cp.async.bulk.wait_group 0;\nfence.proxy.async.global;" ::: "memory");
                }
            } else {
                const int j = s + 1;
#define XDESC(u) (((u) < 8 ? descs : desc0) + (uint64_t)(((KS(u) >> 2) * 4096 + (KS(u) & 3) * 32) >> 4))
                const uint64_t descs = desc0 + (uint64_t)(wg * (6 * 4096 >> 4));
                float d[16];
                wg_fence();
#pragma unroll
                for (int u = 0; u < 8; u++) {
                    if (u == 0) wgmma_n32_rs<0>(d, a[0], a[1], a[2], a[3], XDESC(0));
                    else wgmma_n32_rs<1>(d, a[4 * u], a[4 * u + 1], a[4 * u + 2], a[4 * u + 3], XDESC(u));
                }
                wg_commit();
                wg_wait0();
                if (warp == 0) STAMP(s, 15);
                if (s >= 0) bar_sync(4, 384);
#pragma unroll
                for (int q = 0; q < 2; q++)
                    sts128(sb + O_XP + warp * 1024 + q * 512 + l16, pack_bf16(d[8 * q], d[8 * q + 1]), pack_bf16(d[8 * q + 2], d[8 * q + 3]),
                           pack_bf16(d[8 * q + 4], d[8 * q + 5]), pack_bf16(d[8 * q + 6], d[8 * q + 7]));
                if (s >= 0) {
                    store_kvm();
                    if (warp == 3) asm volatile("cp.async.bulk.wait_group 0;\nfence.proxy.async.global;" ::: "memory");
                    if (warp == 1 && s + 2 < NSEG) tma_x_tile(sb, &tm_x, r, s + 2, s3 == 2 ? 0 : s3 + 1);
                }
                bar_sync(12, 256);
#pragma unroll
                for (int q = 0; q < 2; q++) {
                    const uint4 o = lds128(sb + O_XP + (warp ^ 4) * 1024 + q * 512 + l16);
                    d[8 * q] = __uint_as_float(o.x << 16); d[8 * q + 1] = __uint_as_float(o.x & 0xffff0000u);
                    d[8 * q + 2] = __uint_as_float(o.y << 16); d[8 * q + 3] = __uint_as_float(o.y & 0xffff0000u);
                    d[8 * q + 4] = __uint_as_float(o.z << 16); d[8 * q + 5] = __uint_as_float(o.z & 0xffff0000u);
                    d[8 * q + 6] = __uint_as_float(o.w << 16); d[8 * q + 7] = __uint_as_float(o.w & 0xffff0000u);
                }
                if (s >= 0) {
                    if (warp == 6 && (s & 3) == 0 && s >= 4)
                        asm volatile("{\n.reg .pred p;\nsetp.eq.u32 p, %1, 0;\n@p red.release.gpu.global.inc.u32 [%0], 0x7fffffff;\n}"
                                     :: "l"(&g_flag[((s - 1) * 4 + (h >> 3)) * 8]), "r"(l16) : "memory");
                    asm volatile("{\n.reg .pred p;\nsetp.eq.u32 p, %0, 0;\n@p bar.sync 5, 256;\n@!p bar.sync 13, 256;\n}" :: "r"(wg) : "memory");
                }
                const uint64_t da0 = (uint64_t)(((sb + O_AS + wg * 8192) & 0x3FFFF) >> 4) | (1ull << 16) | (64ull << 32) | (1ull << 62);
                wg_fence();
                wgmma_n32_ss<1>(d, da0, XDESC(0));
#pragma unroll
                for (int u = 1; u < 28; u++) wgmma_n32_rs<1>(d, a[32 + 4 * u], a[32 + 4 * u + 1], a[32 + 4 * u + 2], a[32 + 4 * u + 3], XDESC(u));
                wg_commit();
                wg_wait0();
                if (warp == 3 && r < 2 && s >= 0) store_qk();
                if (warp == 4) STAMP(s, 3);
                uint32_t e[8];
#pragma unroll
                for (int i = 0; i < 8; i++) e[i] = pack_bf16(d[2 * i], d[2 * i + 1]);
                if (r < 2) {
                    const uint32_t base = sb + O_QKX + (j & 1) * 8192 + wg * 4096 + w * 512 + l16;
                    stsm4t(base, e[0], wg ? e[1] : e[2], wg ? e[2] : e[1], e[3]);
                    stsm4t(base + 2048, e[4], wg ? e[5] : e[6], wg ? e[6] : e[5], e[7]);
                    fence_async_smem();
                } else {
                    const uint32_t base = sb + O_VX + (j & 1) * 8192 + warp * 1024 + l16;
                    sts128(base, e[0], e[1], e[2], e[3]);
                    sts128(base + 512, e[4], e[5], e[6], e[7]);
                    fence_async_smem();
                    bar_arrive(14, 288);
                }
                if (warp == 7) STAMP(s, 4);
                if (s < 0) asm volatile("barrier.cluster.wait.aligned;" ::: "memory");
            }
        }
        bar_arrive(7, 384);
    } else {
        asm volatile("setmaxnreg.dec.sync.aligned.u32 136;");
        const int c = w;
        uint32_t a[96];
        uint32_t mmax = 0;
        {
            const int g = lane >> 2, t = lane & 3;
            uint32_t tag = 0, m0v[18];
            if (threadIdx.x == 256) tag = atomicAdd(&g_ticket, 1u);
#pragma unroll
            for (int i = 0; i < 9; i++) {
                const uint32_t* p = reinterpret_cast<const uint32_t*>(mem0 + g * DM + 16 * (4 * i + c) + 2 * t);
                m0v[2 * i] = __ldg(p); m0v[2 * i + 1] = __ldg(p + 4);
            }
            const __nv_bfloat16* p = Wo + (size_t)(h * 128 + 4 * t) * DM + 192 * r + 16 * c + 2 * g;
#pragma unroll
            for (int i = 0; i < 3; i++)
#pragma unroll
                for (int eb = 0; eb < 8; eb++)
#pragma unroll
                    for (int j = 0; j < 4; j++) a[(i * 8 + eb) * 4 + j] = ldg_nc32(p + (16 * eb + ((j & 1) * 2 + (j >> 1))) * DM + 64 * i);
            asm volatile("barrier.cluster.wait.aligned;" ::: "memory");
            if (c == 0) {
                tma_x_tile(sb, &tm_x, r, 0, 0);
                mbar_expect_if(lane, sb + B_SC, 4608);
                if (r < 2) mbar_expect_if(lane, sb + B_VX, 8192);
                sts32_if(lane, sb + O_MISC, __float_as_uint(1.0f));
                sts32_if(lane, sb + O_MISC + 12, __float_as_uint(SM_SCALE));
            }
            asm volatile("barrier.cluster.arrive.relaxed.aligned;" ::: "memory");
#pragma unroll
            for (int tau = 0; tau < 3; tau++) {
                const uint32_t* v = m0v + 6 * tau;
                sts128(sb + O_MF + tau * 3072 + c * 512 + lane * 16, v[0], v[1], v[2], v[3]);
                sts64(sb + O_MF + tau * 3072 + 2048 + (c >> 1) * 512 + lane * 16 + (c & 1) * 8, v[4], v[5]);
#pragma unroll
                for (int i = 0; i < 6; i++) mmax = __vmaxu2(mmax, v[i] & 0x7fff7fffu);
            }
            mmax = max(mmax << 16, mmax & 0xffff0000u);
            bar_arrive(2, 384);
            tag = (__shfl_sync(~0u, tag, 0) / 96u + 1u) & 0xffffu;
#pragma unroll
            for (int kk = 0; kk < 48; kk++) {
                uint32_t w0 = a[2 * kk], w1 = a[2 * kk + 1];
                a[2 * kk] = __byte_perm(w0, w1, 0x5410);
                a[2 * kk + 1] = __byte_perm(w0, w1, 0x7632);
            }
            sts128(sb + O_WP + c * 512 + lane * 16, a[92], a[93], a[94], a[95]);
            float wmax = 0.f;
#pragma unroll
            for (int i = 0; i < 3; i++) {
                float n0[4];
#pragma unroll
                for (int u = 8 * i; u < 8 * i + 8; u++) {
                    const uint32_t x0 = a[4 * u] & 0x7fff7fffu, x1 = a[4 * u + 1] & 0x7fff7fffu, x2 = a[4 * u + 2] & 0x7fff7fffu, x3 = a[4 * u + 3] & 0x7fff7fffu;
                    if (u == 8 * i) mma16816_z(n0, x0, x1, x2, x3, ONES, ONES);
                    else mma16816(n0, x0, x1, x2, x3, ONES, ONES);
                }
                wmax = fmaxf(wmax, fmaxf(n0[0], n0[2]));
            }
            uint32_t wm = __reduce_max_sync(~0u, __float_as_uint(wmax));
            sts32_if(lane, sb + O_OF + 4 * c, wm);
            if (c == 0) PSTAMP(8);
            bar_sync(7, 384);
            asm volatile("barrier.cluster.wait.aligned;" ::: "memory");
            if (c == 1) tma_x_tile(sb, &tm_x, r, 1, 1);
            if (c == 0) {
                const uint4 wq = lds128(sb + O_OF), xq = lds128(sb + O_OF + 16), xr = lds128(sb + O_OF + 32), v0 = lds128(sb + O_MISC + 32), v1 = lds128(sb + O_MISC + 48);
                const uint32_t w1 = max(max(wq.x, wq.y), max(wq.z, wq.w)), x1 = max(max(max(xq.x, xq.y), max(xq.z, xq.w)), max(max(xr.x, xr.y), max(xr.z, xr.w)));
                const uint32_t vv = (r < 2) ? 0u : max(max(max(v0.x, v0.y), max(v0.z, v0.w)), max(max(v1.x, v1.y), max(v1.z, v1.w)));
                const uint32_t lo = (min(w1, 0x7f800000u) + 0xffffu) >> 16 | ((min(vv, 0x7f800000u) + 0xffffu) & 0xffff0000u), hi = (x1 & 0xffff0000u) | tag;
                uint32_t l0, h0, l1, h1, l2, h2;
                asm volatile("{\n.reg .pred p;\n.reg .u32 n, x, y;\n.reg .b64 v;\nsetp.eq.u32 p, %10, 0;\nmov.b64 v, {%8, %9};\n@p st.relaxed.gpu.global.b64 [%7], v;\nmov.u32 n, 0;\n"
                             "G_%=: ld.relaxed.gpu.global.b64 v, [%6];\nmov.b64 {%0, %1}, v;\nld.relaxed.gpu.global.b64 v, [%6+256];\nmov.b64 {%2, %3}, v;\n"
                             "ld.relaxed.gpu.global.b64 v, [%6+512];\nmov.b64 {%4, %5}, v;\n"
                             "xor.b32 x, %1, %9;\nxor.b32 y, %3, %9;\nor.b32 x, x, y;\nxor.b32 y, %5, %9;\nor.b32 x, x, y;\nand.b32 x, x, 0xffff;\n"
                             "setp.eq.u32 p, x, 0;\nvote.sync.all.pred p, p, 0xffffffff;\n@p bra.uni E_%=;\n"
                             "add.u32 n, n, 1;\nsetp.lt.u32 p, n, 4000000;\n@p bra.uni G_%=;\ntrap;\nE_%=:\n}"
                             : "=&r"(l0), "=&r"(h0), "=&r"(l1), "=&r"(h1), "=&r"(l2), "=&r"(h2)
                             : "l"(&g_norm[lane]), "l"(&g_norm[blockIdx.x]), "r"(lo), "r"(hi), "r"(lane) : "memory");
                const uint32_t lm = __vmaxu2(l0, __vmaxu2(l1, l2));
                const float fw = __uint_as_float(__reduce_max_sync(~0u, lm << 16));
                const float fv = __uint_as_float(__reduce_max_sync(~0u, lm & 0xffff0000u));
                const float xmax = __uint_as_float(__reduce_max_sync(~0u, max(h0, max(h1, h2)) & 0xffff0000u));
                const float G = 36.f * fw * fv;
                sts32_if(lane, sb + O_MISC + 4, __float_as_uint(G)); sts32_if(lane, sb + O_MISC + 8, __float_as_uint(G * xmax));
            }
        }
        if (c == 0) PSTAMP(12);
        bar_sync(6, 128);
        int s3n = 1;
        uint32_t roff = __shfl_sync(~0u, (r * 4 + c) * 2048 + (lane >> 4) * 512 + (lane & 2) * 128 + (lane & 1) * 64 + (lane & 12) * 4, lane);
        uint32_t poff = __shfl_sync(~0u, c * 2048 + (lane & 4) * 256 + (lane >> 4) * 256 + (lane & 8) * 8 + (lane & 3) * 16, lane);
#pragma unroll 1
        for (int s = 0; s < NSEG; s++) {
            const uint32_t l16 = opaque(l16c);
            const uint32_t vxa = sb + O_VX + (s & 1) * 8192 + c * 2048 + l16;
            if (c == 0 && r == 2) {
                bar_sync(14, 288);
                asm volatile("{\n.reg .pred p;\nelect.sync _|p, 0xffffffff;\n"
                    "@p cp.async.bulk.global.shared::cta.bulk_group [%0], [%1], 8192;\n@p cp.async.bulk.commit_group;\n"
                    "cp.async.bulk.wait_group 0;\nsetp.lt.and.s32 p, %4, 63, p;\n"
                    "@p cp.async.bulk.shared::cluster.global.mbarrier::complete_tx::bytes.multicast::cluster [%1], [%0], 8192, [%2], %3;\n"
                    "fence.proxy.async.global;\n}"
                    :: "l"(reinterpret_cast<char*>(g_qkv) + (size_t)(s * NH + h) * 24576 + 16384), "r"(sb + O_VX + (s & 1) * 8192),
                       "r"(sb + B_VX + 8 * (s & 1)), "h"((unsigned short)3), "r"(s) : "memory");
            }
            if (s == NSEG - 1) { bar_sync(3, 384); break; }
            uint4 vx[4];
            sts32_if(l16, sb + O_MISC + 16 + 4 * c, __reduce_max_sync(~0u, mmax));
            if (c == 0) STAMP(s, 5);
            {
                bar_sync(6, 128);
                const uint4 mm = lds128(sb + O_MISC + 16), cf = lds128(sb + O_MISC);
                const float bound = fmaxf(__uint_as_float(cf.z), __uint_as_float(cf.y) * (__uint_as_float(max(max(mm.x, mm.y), max(mm.z, mm.w))) * __uint_as_float(cf.x)));
                const uint32_t ebits = __reduce_max_sync(~0u, min(max(__float_as_uint(bound) & 0x7f800000u, 21u << 23), 254u << 23));
                mbar_wait(sb + B_X + 8 * s3n, ((s + 1) / 3) & 1);
                s3n = (s3n == 2) ? 0 : s3n + 1;
                bar_sync(3, 384);
                if (r < 2) mbar_wait(sb + B_VX + 8 * (s & 1), (s >> 1) & 1);
                vx[0] = lds128(vxa); vx[2] = lds128(vxa + 1024);
                if (c == 0) STAMP(s, 13);
                mbar_wait(sb + B_SC, s & 1);
                if (c == 0) STAMP(s, 6);
                float p[10];
                load_scores(p, sb + O_SC, 1280, l16);
                float mx = fmaxf(fmaxf(fmaxf(p[0], p[1]), fmaxf(p[2], p[3])), fmaxf(fmaxf(p[4], p[5]), fmaxf(p[6], p[7])));
                mx = quad_max(fmaxf(mx, fmaxf(p[8], p[9])));
                const uint4 vm = lds64x2(sb + O_VM + c * 512 + (l16 >> 1));
                vx[1] = lds128(vxa + 512); vx[3] = lds128(vxa + 1536);
                bar_arrive(4, 384);
                const float sc = __uint_as_float(lds32(sb + O_MISC + 12));
                const float mo = mx * SM_SCALE;
                uint32_t P[5];
#pragma unroll
                for (int n = 0; n < 5; n++) P[n] = pack_bf16(ex2(fmaf(p[2 * n], SM_SCALE, -mo)), ex2(fmaf(p[2 * n + 1], n == 3 ? sc : SM_SCALE, -mo)));
                if (c == 0) STAMP(s, 7);
                float o0[4], o1[4], sm[4];
                mma16816_z(sm, ONES, ONES, ONES, ONES, P[1], P[2]);
                mma16816_z(o0, vx[0].x, vx[0].y, vx[0].z, vx[0].w, P[1], P[2]);
                mma16816_z(o1, vx[2].x, vx[2].y, vx[2].z, vx[2].w, P[1], P[2]);
                mma16816(sm, ONES, ONES, ONES, ONES, P[3], P[4]);
                mma16816(o0, vx[1].x, vx[1].y, vx[1].z, vx[1].w, P[3], P[4]);
                mma16816(o1, vx[3].x, vx[3].y, vx[3].z, vx[3].w, P[3], P[4]);
                mma1688(sm, ONES, ONES, P[0]);
                mma1688(o0, vm.x, vm.y, P[0]);
                mma1688(o1, vm.z, vm.w, P[0]);
                const float sig = __uint_as_float((268u << 23) - ebits);
                const float r0 = rcp_fast(sm[0]) * sig, r1 = rcp_fast(sm[1]) * sig;
                stsm4t(sb + O_OF + c * 512 + l16, pack_bf16(o0[0] * r0, o0[1] * r1), pack_bf16(o0[2] * r0, o0[3] * r1),
                       pack_bf16(o1[0] * r0, o1[1] * r1), pack_bf16(o1[2] * r0, o1[3] * r1));
                bar_sync(6, 128);
                uint4 ob[4];
#pragma unroll
                for (int q = 0; q < 4; q++) ob[q] = ldsm4(sb + O_OF + q * 512 + l16);
                { const uint4 v = lds128(sb + O_WP + c * 512 + l16); a[92] = v.x; a[93] = v.y; a[94] = v.z; a[95] = v.w; }
                float m0[3][4], m1[3][4];
#pragma unroll
                for (int q = 0; q < 4; q++) {
#pragma unroll
                    for (int i = 0; i < 3; i++) {
                        const int k0 = (i * 8 + 2 * q) * 4;
                        if (q == 0) mma16816_z(m0[i], a[k0], a[k0 + 1], a[k0 + 2], a[k0 + 3], ob[q].x, ob[q].y);
                        else mma16816(m0[i], a[k0], a[k0 + 1], a[k0 + 2], a[k0 + 3], ob[q].x, ob[q].y);
                    }
#pragma unroll
                    for (int i = 0; i < 3; i++) {
                        const int k1 = (i * 8 + 2 * q + 1) * 4;
                        if (q == 0) mma16816_z(m1[i], a[k1], a[k1 + 1], a[k1 + 2], a[k1 + 3], ob[q].z, ob[q].w);
                        else mma16816(m1[i], a[k1], a[k1 + 1], a[k1 + 2], a[k1 + 3], ob[q].z, ob[q].w);
                    }
                }
                asm volatile("red.relaxed.gpu.global.add.noftz.v4.f16x2 [%0], {%1,%2,%3,%4};" :: "l"(reinterpret_cast<char*>(g_acc) + roff),
                    "r"(pack_f16(m0[0][0] + m1[0][0], m0[0][2] + m1[0][2])), "r"(pack_f16(m0[1][0] + m1[1][0], m0[1][2] + m1[1][2])),
                    "r"(pack_f16(m0[2][0] + m1[2][0], m0[2][2] + m1[2][2])), "r"(0x3c00u) : "memory");
                asm volatile("red.relaxed.gpu.global.add.noftz.v4.f16x2 [%0], {%1,%2,%3,%4};" :: "l"(reinterpret_cast<char*>(g_acc) + roff + 1024),
                    "r"(pack_f16(m0[0][1] + m1[0][1], m0[0][3] + m1[0][3])), "r"(pack_f16(m0[1][1] + m1[1][1], m0[1][3] + m1[1][3])),
                    "r"(pack_f16(m0[2][1] + m1[2][1], m0[2][3] + m1[2][3])), "r"(0x3c00u) : "memory");
                const unsigned t_red = clk();
                bar_arrive(5, 256);
                bar_arrive(13, 256);
                mbar_expect_if(l16 | c, sb + B_SC, 4608);
                mbar_expect_if(l16 | (c ^ 1) | (r >> 1), sb + B_VX + 8 * ((s + 1) & 1), 8192);
                sts32_if(l16 | (c ^ 3), sb + O_MISC, ebits - (14u << 23));
                if (c == 0) STAMPV(s, 8, t_red);
                const char* pbase = reinterpret_cast<const char*>(g_acc) + poff;
                spin_until(t_red, D_WAIT);
                uint4 v[6];
#pragma unroll
                for (int i = 0; i < 6; i++) v[i] = ldg_relaxed128(pbase + (i >> 1) * 8192 + (i & 1) * 512);
                int nretry = 0;
                auto hand_over = [&]() -> uint32_t {
                    uint32_t ok = 0;
#pragma unroll
                    for (int tau = 0; tau < 3; tau++) {
                        if (tau == 1) sched_fence<0>(h);
                        if (tau == 2) {
                            sched_fence<1>(h);
                            asm volatile("{\n.reg .pred p, q;\n.reg .b32 x;\nlop3.b32 x, %1, %2, %3, 0x80;\nlop3.b32 x, x, %4, %5, 0x80;\nand.b32 x, x, %6;\n"
                                         "setp.eq.u32 p, x, 0x5000;\nvote.sync.all.pred q, p, 0xffffffff;\nselp.u32 %0, 1, 0, q;\n}"
                                         : "=r"(ok) : "r"(v[0].w), "r"(v[1].w), "r"(v[2].w), "r"(v[3].w), "r"(v[4].w), "r"(v[5].w));
                        }
                        v[2 * tau].x = f16x2_to_bf16x2(v[2 * tau].x); v[2 * tau + 1].x = f16x2_to_bf16x2(v[2 * tau + 1].x);
                        v[2 * tau].y = f16x2_to_bf16x2(v[2 * tau].y); v[2 * tau + 1].y = f16x2_to_bf16x2(v[2 * tau + 1].y);
                        v[2 * tau].z = f16x2_to_bf16x2(v[2 * tau].z); v[2 * tau + 1].z = f16x2_to_bf16x2(v[2 * tau + 1].z);
                        sts128(sb + O_MF + tau * 3072 + c * 512 + l16, v[2 * tau].x, v[2 * tau + 1].x, v[2 * tau].y, v[2 * tau + 1].y);
                        sts64(sb + O_MF + tau * 3072 + 2048 + (c >> 1) * 512 + (c & 1) * 8 + l16, v[2 * tau].z, v[2 * tau + 1].z);
                    }
                    asm volatile("{\n.reg .pred p;\nsetp.ne.u32 p, %0, 0;\n@p bar.arrive 2, 384;\n}" :: "r"(ok) : "memory");
                    return ok;
                };
                if (!hand_over()) {
                    asm volatile("{\n.reg .pred p, q;\n.reg .u32 n, x;\nmov.u32 n, 0;\n"
                         "R_%=: ld.relaxed.gpu.global.v4.u32 {%0,%1,%2,%3}, [%25];\nld.relaxed.gpu.global.v4.u32 {%4,%5,%6,%7}, [%25+512];\n"
                         "ld.relaxed.gpu.global.v4.u32 {%8,%9,%10,%11}, [%25+8192];\nld.relaxed.gpu.global.v4.u32 {%12,%13,%14,%15}, [%25+8704];\n"
                         "ld.relaxed.gpu.global.v4.u32 {%16,%17,%18,%19}, [%25+16384];\nld.relaxed.gpu.global.v4.u32 {%20,%21,%22,%23}, [%25+16896];\n"
                         "add.u32 %24, %24, 1;\nand.b32 x, %3, %7;\nand.b32 x, x, %11;\nand.b32 x, x, %15;\nand.b32 x, x, %19;\nand.b32 x, x, %23;\n"
                         "setp.eq.u32 p, x, 0x5000;\nvote.sync.all.pred q, p, 0xffffffff;\n@q bra.uni K_%=;\n"
                         "add.u32 n, n, 1;\nsetp.lt.u32 q, n, 2000000;\n@q bra.uni R_%=;\ntrap;\nK_%=:\n}"
                         : "+r"(v[0].x), "+r"(v[0].y), "+r"(v[0].z), "+r"(v[0].w), "+r"(v[1].x), "+r"(v[1].y), "+r"(v[1].z), "+r"(v[1].w),
                           "+r"(v[2].x), "+r"(v[2].y), "+r"(v[2].z), "+r"(v[2].w), "+r"(v[3].x), "+r"(v[3].y), "+r"(v[3].z), "+r"(v[3].w),
                           "+r"(v[4].x), "+r"(v[4].y), "+r"(v[4].z), "+r"(v[4].w), "+r"(v[5].x), "+r"(v[5].y), "+r"(v[5].z), "+r"(v[5].w), "+r"(nretry)
                         : "l"(pbase) : "memory");
                    hand_over();
                }
                if (c == 0) STAMP(s, 12);
                if (c == 0) STAMPV(s, 14, nretry);
                mmax = absmax2(absmax2(absmax2(v[0].x, v[0].y), absmax2(v[0].z, v[1].x)), absmax2(absmax2(v[1].y, v[1].z), absmax2(v[2].x, v[2].y)));
                mmax = absmax2(mmax, absmax2(absmax2(absmax2(v[2].z, v[3].x), absmax2(v[3].y, v[3].z)), absmax2(absmax2(v[4].x, v[4].y), absmax2(v[4].z, v[5].x))));
                mmax = absmax2(mmax, absmax2(v[5].y, v[5].z)) & 0x7fff7fffu;
                mmax = max(mmax << 16, mmax & 0xffff0000u);
            }
            roff += 24576; poff += 24576;
        }
        {
            bar_sync(7, 384);
            if (c == 0)
                asm volatile("{\n.reg .pred p;\nsetp.eq.u32 p, %1, 0;\n@p red.release.gpu.global.inc.u32 [%0], 0x7fffffff;\n}"
                             :: "l"(&g_flag[(63 * 4 + (h >> 3)) * 8]), "r"(l16c) : "memory");
        }
    }
    if (warp == 8) PSTAMP(13);
    cluster_sync();
}

__device__ float g_u[SEQ * 2 * DM];
__global__ void naive_gemm1(const __nv_bfloat16* x, const __nv_bfloat16* Bre, const __nv_bfloat16* Bim) {
    int p = blockIdx.x * 64 + threadIdx.x % 64, tk = blockIdx.y * 4 + threadIdx.x / 64;
    float sr = 0, si = 0;
    for (int d = 0; d < DM; d++) { float xv = __bfloat162float(x[tk * DM + d]); sr += xv * __bfloat162float(Bre[p * DM + d]); si += xv * __bfloat162float(Bim[p * DM + d]); }
    g_u[tk * 2 * DM + 2 * p] = sr; g_u[tk * 2 * DM + 2 * p + 1] = si;
}
__global__ void naive_scan(const __nv_bfloat16* Lre, const __nv_bfloat16* Lim, const __nv_bfloat16* logdt) {
    int p = blockIdx.x * 64 + threadIdx.x;
    float dt = __bfloat162float(__float2bfloat16(expf(__bfloat162float(logdt[p]))));
    float lr = __bfloat162float(Lre[p]), li = __bfloat162float(Lim[p]);
    float e = expf(dt * lr), br = e * cosf(dt * li), bi = e * sinf(dt * li);
    float den = lr * lr + li * li;
    float cr = ((br - 1.f) * lr + bi * li) / den, ci = (bi * lr - (br - 1.f) * li) / den;
    float hr = 0, hi = 0;
    for (int tk = 0; tk < SEQ; tk++) {
        float ur = g_u[tk * 2 * DM + 2 * p], ui = g_u[tk * 2 * DM + 2 * p + 1];
        float nr = br * hr - bi * hi + cr * ur - ci * ui, ni = br * hi + bi * hr + cr * ui + ci * ur;
        hr = nr; hi = ni;
        g_u[tk * 2 * DM + 2 * p] = hr; g_u[tk * 2 * DM + 2 * p + 1] = hi;
    }
}
__global__ void naive_gemm2(const __nv_bfloat16* x, const __nv_bfloat16* Cre, const __nv_bfloat16* Cim, const __nv_bfloat16* Dk, float* out) {
    int d = blockIdx.x * 64 + threadIdx.x % 64, tk = blockIdx.y * 4 + threadIdx.x / 64;
    float s = 0;
    for (int p = 0; p < DM; p++) s += g_u[tk * 2 * DM + 2 * p] * __bfloat162float(Cre[d * DM + p]) - g_u[tk * 2 * DM + 2 * p + 1] * __bfloat162float(Cim[d * DM + p]);
    out[tk * 1152 + d] = 2.f * s + __bfloat162float(__float2bfloat16(__bfloat162float(x[tk * DM + d]) * __bfloat162float(Dk[d])));
}
__device__ float frag_elem(const uint32_t* base, int e, int tok) {
    int eb = e >> 4, g = (e & 15) >> 1, hi = e & 1, j = tok >> 3, t = (tok & 7) >> 1, i = 2 * j + hi;
    uint32_t v = base[eb * 256 + (i >> 2) * 128 + (g * 4 + t) * 4 + (i & 3)];
    return __uint_as_float((tok & 1) ? (v & 0xffff0000u) : (v << 16));
}
__device__ float qk_elem(const uint32_t* base, int isk, int e, int tok) {
    int r = e >> 6, w = (e >> 4) & 3, g = (e & 15) >> 1, hi = e & 1, j = (tok >> 3) & 1;
    int mi = isk ? j * 2 + hi : hi * 2 + j;
    const __nv_bfloat16* p = reinterpret_cast<const __nv_bfloat16*>(base) + r * 4096 + isk * 2048 + (tok >> 4) * 1024 + w * 256 + mi * 64 + (tok & 7) * 8 + g;
    return __bfloat162float(*p);
}
__device__ float fragm_elem(const uint32_t* base, int e, int tok) {
    int eb = e >> 4, g = (e & 15) >> 1, hi = e & 1, t = tok >> 1;
    uint32_t v = base[eb * 64 + (g * 4 + t) * 2 + hi];
    return __uint_as_float((tok & 1) ? (v & 0xffff0000u) : (v << 16));
}
__global__ void naive_attn() {
    int s = blockIdx.x / NH, h = blockIdx.x % NH, q = threadIdx.x;
    const uint32_t* qkv = reinterpret_cast<const uint32_t*>(g_qkv) + (size_t)blockIdx.x * 6144;
    const uint32_t* kvm = reinterpret_cast<const uint32_t*>(g_kvm) + (size_t)blockIdx.x * 1536;
    float p[40], mx = -1e30f, sum = 0;
    for (int k = 0; k < 40; k++) {
        float d = 0;
        for (int e = 0; e < 128; e++)
            d += qk_elem(qkv, 0, e, q) * (k < 8 ? fragm_elem(kvm, e, k) + fragm_elem(kvm + 512, e, k) : qk_elem(qkv, 1, e, k - 8));
        p[k] = (k < 8 || k - 8 <= q) ? d * 0.08838834764831845f : -1e30f;
        mx = fmaxf(mx, p[k]);
    }
    for (int k = 0; k < 40; k++) { p[k] = expf(p[k] - mx); sum += p[k]; }
    __nv_bfloat16* ox = reinterpret_cast<__nv_bfloat16*>(g_ox);
    int tk = s * 32 + q;
    for (int e = 0; e < 128; e++) {
        float o = 0;
        for (int k = 0; k < 40; k++) o += p[k] * (k < 8 ? fragm_elem(kvm + 1024, e, k) : frag_elem(qkv + 4096, e, k - 8));
        int e0 = e & 63, ep = (e0 & 48) + (e0 & 1) * 8 + ((e0 & 15) >> 1);
        ox[((size_t)(h * 2 + (e >> 6)) * SEQ + tk) * 64 + (((ep >> 3) ^ (tk & 7)) << 3) + (ep & 7)] = __float2bfloat16(o / sum);
    }
}
__global__ void naive_wo(const __nv_bfloat16* Wo, float* out) {
    int d = blockIdx.x * 64 + threadIdx.x % 64, tk = blockIdx.y * 4 + threadIdx.x / 64;
    const __nv_bfloat16* ox = reinterpret_cast<const __nv_bfloat16*>(g_ox);
    float s = 0;
    for (int k = 0; k < HD; k++) {
        int hh = k >> 6, e0 = k & 63, e = (e0 & 48) + (e0 & 1) * 8 + ((e0 & 15) >> 1);
        s += __bfloat162float(ox[((size_t)hh * SEQ + tk) * 64 + (((e >> 3) ^ (tk & 7)) << 3) + (e & 7)]) * __bfloat162float(Wo[k * DM + d]);
    }
    out[tk * 1152 + DM + d] = s;
}

typedef CUresult (*EncodeFn)(CUtensorMap*, CUtensorMapDataType, cuuint32_t, void*, const cuuint64_t*, const cuuint64_t*, const cuuint32_t*, const cuuint32_t*,
                             CUtensorMapInterleave, CUtensorMapSwizzle, CUtensorMapL2promotion, CUtensorMapFloatOOBfill);
}

extern "C" void kernel_launch(void* const* d_in, const int* in_sizes, int n_in, void* d_out, int out_size) {
    typedef const __nv_bfloat16* bp;
    bp Ax = (bp)d_in[0], Lre = (bp)d_in[1], Lim = (bp)d_in[2], Bre = (bp)d_in[3], Bim = (bp)d_in[4], Cre = (bp)d_in[5], Cim = (bp)d_in[6],
       logdt = (bp)d_in[7], Dk = (bp)d_in[8], Bx = (bp)d_in[9], mem0 = (bp)d_in[10], Wq = (bp)d_in[11], Wk = (bp)d_in[12], Wv = (bp)d_in[13], Wo = (bp)d_in[14];
    float* out = (float*)d_out;
    static EncodeFn enc = nullptr;
    if (!enc) {
        void* fn = nullptr; cudaDriverEntryPointQueryResult qr;
        cudaGetDriverEntryPoint("cuTensorMapEncodeTiled", &fn, cudaEnableDefault, &qr);
        enc = (EncodeFn)fn;
        cudaFuncSetAttribute(chain_kernel, cudaFuncAttributeMaxDynamicSharedMemorySize, CHAIN_SMEM);
    }
    CUtensorMap tm_x;
    {
        cuuint64_t gd[2] = {DM, SEQ}; cuuint64_t gs[1] = {DM * 2}; cuuint32_t bd[2] = {64, 32}; cuuint32_t es[2] = {1, 1};
        enc(&tm_x, CU_TENSOR_MAP_DATA_TYPE_BFLOAT16, 2, (void*)Bx, gd, gs, bd, es, CU_TENSOR_MAP_INTERLEAVE_NONE, CU_TENSOR_MAP_SWIZZLE_128B,
            CU_TENSOR_MAP_L2_PROMOTION_L2_128B, CU_TENSOR_MAP_FLOAT_OOB_FILL_NONE);
    }
    CUtensorMap tm_w[3];
    for (int i = 0; i < 3; i++) {
        cuuint64_t gd[2] = {HD, DM}; cuuint64_t gs[1] = {HD * 2}; cuuint32_t bd[2] = {64, 192}; cuuint32_t es[2] = {1, 1};
        enc(&tm_w[i], CU_TENSOR_MAP_DATA_TYPE_BFLOAT16, 2, (void*)(i == 0 ? Wq : i == 1 ? Wk : Wv), gd, gs, bd, es, CU_TENSOR_MAP_INTERLEAVE_NONE,
            CU_TENSOR_MAP_SWIZZLE_128B, CU_TENSOR_MAP_L2_PROMOTION_L2_128B, CU_TENSOR_MAP_FLOAT_OOB_FILL_NONE);
    }
    cudaStream_t st = cudaStreamPerThread;
    chain_kernel<<<96, 384, CHAIN_SMEM, st>>>(tm_x, tm_w[0], tm_w[1], tm_w[2], Bx, mem0, Wq, Wk, Wv, Wo);
    naive_gemm1<<<dim3(9, 512), 256, 0, st>>>(Ax, Bre, Bim);
    naive_scan<<<9, 64, 0, st>>>(Lre, Lim, logdt);
    naive_gemm2<<<dim3(9, 512), 256, 0, st>>>(Ax, Cre, Cim, Dk, out);
    naive_attn<<<NSEG * NH, 32, 0, st>>>();
    naive_wo<<<dim3(9, 512), 256, 0, st>>>(Wo, out);
}
```

```cpp
#include <cuda_runtime.h>
#include <cuda.h>
#include <cuda_bf16.h>
#include <cuda_fp16.h>
#include <stdint.h>

#define D_WAIT 700

#define BG_AHEAD 10

namespace {

constexpr int DM = 576, NH = 32, SEQ = 2048, NSEG = 64, HD = 4096;

__device__ uint4 g_acc[64 * 96 * 16];
__device__ uint4 g_ox[NH * 2 * SEQ * 8];
constexpr int REC = 30720;
__device__ uint4 g_qkv[NSEG * NH * (REC / 16)];
__device__ uint4 g_h[18 * SEQ * 8];
constexpr int NFLAG = 2048, F_QKV = 0, F_OX = 512, F_H = 1024;
__device__ __align__(16) unsigned g_flag[NFLAG];
__device__ unsigned g_ticket;
__device__ unsigned long long g_norm[96];

__device__ __forceinline__ uint32_t smem_u32(const void* p) { return (uint32_t)__cvta_generic_to_shared(p); }
__device__ __forceinline__ uint32_t mapa(uint32_t a, uint32_t r) { uint32_t o; asm("mapa.shared::cluster.u32 %0, %1, %2;" : "=r"(o) : "r"(a), "r"(r)); return o; }
__device__ __forceinline__ uint32_t mapa_v(uint32_t a, uint32_t r) { uint32_t o; asm volatile("mapa.shared::cluster.u32 %0, %1, %2;" : "=r"(o) : "r"(a), "r"(r)); return o; }
__device__ __forceinline__ unsigned clk() { unsigned long long c; asm volatile("mov.u64 %0, %%clock64;" : "=l"(c) :: "memory"); return (unsigned)c; }
__device__ __forceinline__ void mbar_init(uint32_t bar, uint32_t cnt) { asm volatile("mbarrier.init.shared::cta.b64 [%0], %1;" :: "r"(bar), "r"(cnt) : "memory"); }
__device__ __forceinline__ void mbar_expect(uint32_t bar, uint32_t bytes) { asm volatile("mbarrier.arrive.expect_tx.shared::cta.b64 _, [%0], %1;" :: "r"(bar), "r"(bytes) : "memory"); }
__device__ __forceinline__ void mbar_wait(uint32_t bar, uint32_t parity) {
    asm volatile("{\n.reg .pred p;\n.reg .u32 n;\nmov.u32 n, 0;\n"
                 "W_%=: mbarrier.try_wait.parity.shared::cta.b64 p, [%0], %1;\n@p bra.uni D_%=;\n"
                 "add.u32 n, n, 1;\nsetp.lt.u32 p, n, 4000000;\n@p bra.uni W_%=;\ntrap;\nD_%=:\n}" :: "r"(bar), "r"(parity) : "memory");
}
__device__ __forceinline__ void mbar_expect_if(uint32_t z, uint32_t bar, uint32_t bytes) {
    asm volatile("{\n.reg .pred p;\nsetp.eq.u32 p, %2, 0;\n@p mbarrier.arrive.expect_tx.shared::cta.b64 _, [%0], %1;\n}" :: "r"(bar), "r"(bytes), "r"(z) : "memory");
}
__device__ __forceinline__ void mbar_arrive_if(uint32_t z, uint32_t bar) {
    asm volatile("{\n.reg .pred p;\nsetp.eq.u32 p, %1, 0;\n@p mbarrier.arrive.shared::cta.b64 _, [%0];\n}" :: "r"(bar), "r"(z) : "memory");
}
__device__ __forceinline__ void sts32_if(uint32_t z, uint32_t a, uint32_t x) {
    asm volatile("{\n.reg .pred p;\nsetp.eq.u32 p, %2, 0;\n@p st.shared.u32 [%0], %1;\n}" :: "r"(a), "r"(x), "r"(z) : "memory");
}
template <int K> __device__ __forceinline__ void sched_fence(int v) {
    asm volatile("{\n.reg .pred p;\nsetp.ne.s32 p, %0, %1;\n@p bra.uni F_%=;\ntrap;\nF_%=:\n}" :: "r"(v), "n"(1000 + K) : "memory");
}
__device__ __forceinline__ void spin_until(unsigned t0, unsigned d) {
    asm volatile("{\n.reg .pred p;\n.reg .u64 c;\n.reg .u32 lo;\n"
                 "S_%=: mov.u64 c, %%clock64;\ncvt.u32.u64 lo, c;\nsub.u32 lo, lo, %0;\nsetp.lt.u32 p, lo, %1;\n@p bra.uni S_%=;\n}" :: "r"(t0), "r"(d) : "memory");
}
__device__ __forceinline__ void bar_sync(int id, int n) { asm volatile("bar.sync %0, %1;" :: "r"(id), "r"(n) : "memory"); }
__device__ __forceinline__ void bar_sync_sel(int sel, int id) {
    asm volatile("{\n.reg .pred p;\nsetp.eq.u32 p, %0, 0;\n@p bar.sync %1, %3;\n@!p bar.sync %2, %3;\n}" :: "r"(sel), "r"(id), "r"(id + 1), "n"(192) : "memory");
}
__device__ __forceinline__ void bar_arrive(int id, int n) { asm volatile("bar.arrive %0, %1;" :: "r"(id), "r"(n) : "memory"); }
__device__ __forceinline__ void fence_async_smem() { asm volatile("fence.proxy.async.shared::cta;" ::: "memory"); }
__device__ __forceinline__ uint32_t pack_bf16(float lo, float hi) { uint32_t r; asm("cvt.rn.bf16x2.f32 %0, %1, %2;" : "=r"(r) : "f"(hi), "f"(lo)); return r; }
__device__ __forceinline__ uint32_t pack_f16(float lo, float hi) { uint32_t r; asm("cvt.rn.f16x2.f32 %0, %1, %2;" : "=r"(r) : "f"(hi), "f"(lo)); return r; }
__device__ __forceinline__ uint32_t f16x2_to_bf16x2(uint32_t v) { float2 f = __half22float2(*reinterpret_cast<__half2*>(&v)); return pack_bf16(f.x, f.y); }
__device__ __forceinline__ float ex2(float x) { float y; asm("ex2.approx.ftz.f32 %0, %1;" : "=f"(y) : "f"(x)); return y; }
__device__ __forceinline__ float ex2v(float x) { float y; asm volatile("ex2.approx.ftz.f32 %0, %1;" : "=f"(y) : "f"(x)); return y; }
__device__ __forceinline__ uint32_t absmax2(uint32_t a, uint32_t b) {
    uint32_t r; asm("max.xorsign.abs.bf16x2 %0, %1, %2;" : "=r"(r) : "r"(a), "r"(b)); return r;
}
__device__ __forceinline__ uint32_t shl_v(uint32_t a, int n) { return a << n; }
__device__ __forceinline__ uint32_t max3u(uint32_t a, uint32_t b, uint32_t c) { return max(max(a, b), c); }
__device__ __forceinline__ uint4 lds128(uint32_t a) { uint4 v; asm volatile("ld.shared.v4.u32 {%0,%1,%2,%3}, [%4];" : "=r"(v.x), "=r"(v.y), "=r"(v.z), "=r"(v.w) : "r"(a) : "memory"); return v; }
__device__ __forceinline__ uint4 lds128v(uint32_t a) { uint4 v; asm volatile("ld.volatile.shared.v4.u32 {%0,%1,%2,%3}, [%4];" : "=r"(v.x), "=r"(v.y), "=r"(v.z), "=r"(v.w) : "r"(a) : "memory"); return v; }
__device__ __forceinline__ float4 lds128f(uint32_t a) { float4 v; asm volatile("ld.shared.v4.f32 {%0,%1,%2,%3}, [%4];" : "=f"(v.x), "=f"(v.y), "=f"(v.z), "=f"(v.w) : "r"(a) : "memory"); return v; }
__device__ __forceinline__ float2 lds64f(uint32_t a) { float2 v; asm volatile("ld.shared.v2.f32 {%0,%1}, [%2];" : "=f"(v.x), "=f"(v.y) : "r"(a) : "memory"); return v; }
__device__ __forceinline__ uint4 lds64x2(uint32_t a) { uint4 v; asm volatile("ld.shared.v2.u32 {%0,%1}, [%4];\nld.shared.v2.u32 {%2,%3}, [%4+256];" : "=r"(v.x), "=r"(v.y), "=r"(v.z), "=r"(v.w) : "r"(a) : "memory"); return v; }
__device__ __forceinline__ uint32_t lds32(uint32_t a) { uint32_t v; asm volatile("ld.shared.u32 %0, [%1];" : "=r"(v) : "r"(a) : "memory"); return v; }
__device__ __forceinline__ void sts128(uint32_t a, uint32_t x, uint32_t y, uint32_t z, uint32_t w) { asm volatile("st.shared.v4.u32 [%0], {%1,%2,%3,%4};" :: "r"(a), "r"(x), "r"(y), "r"(z), "r"(w) : "memory"); }
__device__ __forceinline__ void sts128f(uint32_t a, float x, float y, float z, float w) { asm volatile("st.shared.v4.f32 [%0], {%1,%2,%3,%4};" :: "r"(a), "f"(x), "f"(y), "f"(z), "f"(w) : "memory"); }
__device__ __forceinline__ void sts64(uint32_t a, uint32_t x, uint32_t y) { asm volatile("st.shared.v2.u32 [%0], {%1,%2};" :: "r"(a), "r"(x), "r"(y) : "memory"); }
__device__ __forceinline__ void sts32(uint32_t a, uint32_t x) { asm volatile("st.shared.u32 [%0], %1;" :: "r"(a), "r"(x) : "memory"); }
__device__ __forceinline__ uint4 ldsm4(uint32_t a) { uint4 v; asm volatile("ldmatrix.sync.aligned.m8n8.x4.shared.b16 {%0,%1,%2,%3}, [%4];" : "=r"(v.x), "=r"(v.y), "=r"(v.z), "=r"(v.w) : "r"(a) : "memory"); return v; }
__device__ __forceinline__ void stsm2t(uint32_t a, uint32_t x, uint32_t y) { asm volatile("stmatrix.sync.aligned.m8n8.x2.trans.shared.b16 [%0], {%1,%2};" :: "r"(a), "r"(x), "r"(y) : "memory"); }
__device__ __forceinline__ void stsm4t(uint32_t a, uint32_t x, uint32_t y, uint32_t z, uint32_t w) { asm volatile("stmatrix.sync.aligned.m8n8.x4.trans.shared.b16 [%0], {%1,%2,%3,%4};" :: "r"(a), "r"(x), "r"(y), "r"(z), "r"(w) : "memory"); }
__device__ __forceinline__ void st_async64(uint32_t a, uint32_t x, uint32_t y, uint32_t bar) { asm volatile("st.async.shared::cluster.mbarrier::complete_tx::bytes.v2.b32 [%0], {%1,%2}, [%3];" :: "r"(a), "r"(x), "r"(y), "r"(bar) : "memory"); }
__device__ __forceinline__ void bulk_s2c(uint32_t dst, uint32_t src, uint32_t bytes, uint32_t bar) { asm volatile("cp.async.bulk.shared::cluster.shared::cta.mbarrier::complete_tx::bytes [%0], [%1], %2, [%3];" :: "r"(dst), "r"(src), "r"(bytes), "r"(bar) : "memory"); }
__device__ __forceinline__ void bulk_s2g(void* dst, uint32_t src, uint32_t bytes) { asm volatile("cp.async.bulk.global.shared::cta.bulk_group [%0], [%1], %2;" :: "l"(dst), "r"(src), "r"(bytes) : "memory"); }
__device__ __forceinline__ uint32_t ldg_nc32(const void* p) { uint32_t v; asm volatile("ld.global.nc.L2::128B.u32 %0, [%1];" : "=r"(v) : "l"(p)); return v; }
__device__ __forceinline__ uint4 ldg_relaxed128(const void* p) { uint4 v; asm volatile("ld.relaxed.gpu.global.v4.u32 {%0,%1,%2,%3}, [%4];" : "=r"(v.x), "=r"(v.y), "=r"(v.z), "=r"(v.w) : "l"(p) : "memory"); return v; }
__device__ __forceinline__ void mma16816(float (&d)[4], uint32_t a0, uint32_t a1, uint32_t a2, uint32_t a3, uint32_t b0, uint32_t b1) {
    asm volatile("mma.sync.aligned.m16n8k16.row.col.f32.bf16.bf16.f32 {%0,%1,%2,%3}, {%4,%5,%6,%7}, {%8,%9}, {%0,%1,%2,%3};"
        : "+f"(d[0]), "+f"(d[1]), "+f"(d[2]), "+f"(d[3]) : "r"(a0), "r"(a1), "r"(a2), "r"(a3), "r"(b0), "r"(b1));
}
__device__ __forceinline__ void mma16816_z(float (&d)[4], uint32_t a0, uint32_t a1, uint32_t a2, uint32_t a3, uint32_t b0, uint32_t b1) {
    asm volatile("mma.sync.aligned.m16n8k16.row.col.f32.bf16.bf16.f32 {%0,%1,%2,%3}, {%4,%5,%6,%7}, {%8,%9}, {%10,%10,%10,%10};"
        : "=f"(d[0]), "=f"(d[1]), "=f"(d[2]), "=f"(d[3]) : "r"(a0), "r"(a1), "r"(a2), "r"(a3), "r"(b0), "r"(b1), "f"(0.f));
}
__device__ __forceinline__ void mma1688(float (&d)[4], uint32_t a0, uint32_t a1, uint32_t b0) {
    asm volatile("mma.sync.aligned.m16n8k8.row.col.f32.bf16.bf16.f32 {%0,%1,%2,%3}, {%4,%5}, {%6}, {%0,%1,%2,%3};"
        : "+f"(d[0]), "+f"(d[1]), "+f"(d[2]), "+f"(d[3]) : "r"(a0), "r"(a1), "r"(b0));
}
__device__ __forceinline__ void mma1688_z(float (&d)[4], uint32_t a0, uint32_t a1, uint32_t b0) {
    asm volatile("mma.sync.aligned.m16n8k8.row.col.f32.bf16.bf16.f32 {%0,%1,%2,%3}, {%4,%5}, {%6}, {%7,%7,%7,%7};"
        : "=f"(d[0]), "=f"(d[1]), "=f"(d[2]), "=f"(d[3]) : "r"(a0), "r"(a1), "r"(b0), "f"(0.f));
}
template <int ACC>
__device__ __forceinline__ void wgmma_n32_rs(float (&d)[16], uint32_t a0, uint32_t a1, uint32_t a2, uint32_t a3, uint64_t desc) {
    asm volatile("wgmma.mma_async.sync.aligned.m64n32k16.f32.bf16.bf16 {%0,%1,%2,%3,%4,%5,%6,%7,%8,%9,%10,%11,%12,%13,%14,%15}, {%16,%17,%18,%19}, %20, %21, 1, 1, 0;"
        : "+f"(d[0]), "+f"(d[1]), "+f"(d[2]), "+f"(d[3]), "+f"(d[4]), "+f"(d[5]), "+f"(d[6]), "+f"(d[7]),
          "+f"(d[8]), "+f"(d[9]), "+f"(d[10]), "+f"(d[11]), "+f"(d[12]), "+f"(d[13]), "+f"(d[14]), "+f"(d[15])
        : "r"(a0), "r"(a1), "r"(a2), "r"(a3), "l"(desc), "n"(ACC));
}
template <int ACC>
__device__ __forceinline__ void wgmma_n32_ss(float (&d)[16], uint64_t da, uint64_t db) {
    asm volatile("wgmma.mma_async.sync.aligned.m64n32k16.f32.bf16.bf16 {%0,%1,%2,%3,%4,%5,%6,%7,%8,%9,%10,%11,%12,%13,%14,%15}, %16, %17, %18, 1, 1, 0, 0;"
        : "+f"(d[0]), "+f"(d[1]), "+f"(d[2]), "+f"(d[3]), "+f"(d[4]), "+f"(d[5]), "+f"(d[6]), "+f"(d[7]),
          "+f"(d[8]), "+f"(d[9]), "+f"(d[10]), "+f"(d[11]), "+f"(d[12]), "+f"(d[13]), "+f"(d[14]), "+f"(d[15])
        : "l"(da), "l"(db), "n"(ACC));
}
__device__ __forceinline__ void wg_fence() { asm volatile("wgmma.fence.sync.aligned;" ::: "memory"); }
__device__ __forceinline__ void wg_commit() { asm volatile("wgmma.commit_group.sync.aligned;" ::: "memory"); }
__device__ __forceinline__ void wg_wait0() { asm volatile("wgmma.wait_group.sync.aligned 0;" ::: "memory"); }
__device__ __forceinline__ void cluster_sync() { asm volatile("barrier.cluster.arrive.aligned;\nbarrier.cluster.wait.aligned;" ::: "memory"); }

#define STAMP(s, i) do {} while (0)
#define STAMPV(s, i, v) do {} while (0)

constexpr int XT_BYTES = 36864;
constexpr int O_XT = 0;
constexpr int O_STG = XT_BYTES;
constexpr int O_AS = 3 * XT_BYTES;
constexpr int O_XP = O_AS + 16384;
constexpr int O_QKX = O_XP + 8192;
constexpr int O_KM = O_QKX + 8192;
constexpr int O_QM = O_QKX + 10240;
constexpr int O_VX = O_STG + 147456;
constexpr int O_VM = O_VX + 16384;
constexpr int O_SC = O_VM + 2048;
constexpr int O_OF = O_SC + 2560;
constexpr int O_AF = O_OF + 2048;
constexpr int O_WP = O_AF + 4096;
constexpr int O_MF = O_WP + 2048;
constexpr int O_MISC = O_MF + 9216;
static_assert(O_QKX + 24576 <= O_VX, "smem");
constexpr int O_BAR = O_MISC + 64;
constexpr int CHAIN_SMEM = O_BAR + 128;
static_assert(CHAIN_SMEM <= 232448, "smem");
constexpr int B_X = O_BAR, B_VX = O_BAR + 24, B_SC = O_BAR + 40, B_W = O_BAR + 48;
constexpr float SM_SCALE = 0.08838834764831845f * 1.4426950408889634f;
constexpr uint32_t ONES = 0x3f803f80u;

__device__ __forceinline__ uint32_t opaque(uint32_t v) { uint32_t o; asm volatile("mov.u32 %0, %1;" : "=r"(o) : "r"(v)); return o; }
__device__ __forceinline__ void st_async128(uint32_t a, uint32_t x, uint32_t y, uint32_t z, uint32_t w, uint32_t bar) {
    asm volatile("st.async.shared::cluster.mbarrier::complete_tx::bytes.v4.b32 [%0], {%1,%2,%3,%4}, [%5];" :: "r"(a), "r"(x), "r"(y), "r"(z), "r"(w), "r"(bar) : "memory");
}
__device__ __forceinline__ void tma_x_tile(uint32_t sb, const CUtensorMap* tm, int r, int j, int slot) {
    asm volatile("{\n.reg .pred p;\nelect.sync _|p, 0xffffffff;\n"
        "@p mbarrier.arrive.expect_tx.shared::cta.b64 _, [%2], 36864;\n"
        "@p cp.async.bulk.tensor.2d.shared::cluster.global.mbarrier::complete_tx::bytes.multicast::cluster [%0], [%1, {%3, %4}], [%2], %7;\n"
        "@p cp.async.bulk.tensor.2d.shared::cluster.global.mbarrier::complete_tx::bytes.multicast::cluster [%0+4096], [%1, {%5, %4}], [%2], %7;\n"
        "@p cp.async.bulk.tensor.2d.shared::cluster.global.mbarrier::complete_tx::bytes.multicast::cluster [%0+8192], [%1, {%6, %4}], [%2], %7;\n}"
        :: "r"(sb + O_XT + slot * XT_BYTES + 3 * r * 4096), "l"(tm), "r"(sb + B_X + 8 * slot), "r"(192 * r), "r"(j * 32), "r"(192 * r + 64), "r"(192 * r + 128),
           "h"((unsigned short)7) : "memory");
}
__device__ __forceinline__ float quad_max(float v) {
    const float a = __shfl_xor_sync(~0u, v, 1), b = __shfl_xor_sync(~0u, v, 2), c = __shfl_xor_sync(~0u, v, 3);
    return fmaxf(fmaxf(v, a), fmaxf(b, c));
}
__device__ __forceinline__ void load_scores(float (&p)[10], uint32_t base, uint32_t stride, uint32_t l16) {
    const float4 a0 = lds128f(base + l16), b0 = lds128f(base + stride + l16);
    const float4 a1 = lds128f(base + 512 + l16), b1 = lds128f(base + stride + 512 + l16);
    const float2 a2 = lds64f(base + 1024 + (l16 >> 1)), b2 = lds64f(base + stride + 1024 + (l16 >> 1));
    p[0] = a2.x + b2.x; p[1] = a2.y + b2.y;
    p[2] = a0.x + b0.x; p[3] = a0.y + b0.y; p[4] = a0.z + b0.z; p[5] = a0.w + b0.w;
    p[6] = a1.x + b1.x; p[7] = a1.y + b1.y; p[8] = a1.z + b1.z; p[9] = a1.w + b1.w;
}
__device__ __forceinline__ float rcp_fast(float x) { float y; asm("rcp.approx.ftz.f32 %0, %1;" : "=f"(y) : "f"(x)); return y; }

__global__ void __cluster_dims__(3, 1, 1) __launch_bounds__(384, 1)
chain_kernel(const __grid_constant__ CUtensorMap tm_x, const __grid_constant__ CUtensorMap tm_q,
             const __grid_constant__ CUtensorMap tm_k, const __grid_constant__ CUtensorMap tm_v,
             const __nv_bfloat16* __restrict__ x, const __nv_bfloat16* __restrict__ mem0,
             const __nv_bfloat16* __restrict__ Wo, float* __restrict__ out) {
    extern __shared__ __align__(1024) uint8_t smem_raw[];
    const uint32_t sb = smem_u32(smem_raw);
    const int lane = threadIdx.x & 31;
    const int warp = __shfl_sync(~0u, threadIdx.x >> 5, 0);
    const int wg = warp >> 2, w = warp & 3;
    const int h = blockIdx.x / 3, r = blockIdx.x - 3 * h;

#define PSTAMP(i) do {} while (0)
    if (threadIdx.x == 0) {
        if (sb & 1023u) __trap();
        for (int i = 0; i < 9; i++) mbar_init(sb + O_BAR + 8 * i, 1);
        asm volatile("fence.mbarrier_init.release.cluster;" ::: "memory");
        for (int i = 0; i < 3; i++) {
            mbar_expect(sb + B_W + 8 * i, 49152);
            for (int tl = 0; tl < 2; tl++)
                asm volatile("cp.async.bulk.tensor.2d.shared::cluster.global.mbarrier::complete_tx::bytes [%0], [%1, {%3, %4}], [%2];"
                    :: "r"(sb + O_STG + tl * 73728 + i * 24576), "l"(r < 2 ? (tl ? &tm_k : &tm_q) : &tm_v), "r"(sb + B_W + 8 * i),
                       "r"(h * 128 + 64 * (r < 2 ? r : tl)), "r"(192 * i) : "memory");
        }
    }
    __syncwarp();
    asm volatile("barrier.cluster.arrive.relaxed.aligned;" ::: "memory");
    if (warp == 0) PSTAMP(9);
    const uint32_t l16c = __shfl_sync(~0u, lane * 16, lane);

    if (wg < 2) {
#define KS(u) ((u) < 8 ? ((u) >> 1) + 4 * ((u) & 1) : (u) < 12 ? (u) : (u) < 20 ? 12 + (((u) - 12) >> 1) + 4 * ((u) & 1) : (u) < 24 ? (u) : (u) + 8)
        asm volatile("setmaxnreg.inc.sync.aligned.u32 184;");
        uint32_t a[144];
        uint32_t adr1;
        {
            const int g = lane >> 2, t = lane & 3;
            const int t1 = threadIdx.x;
#pragma unroll
            for (int i = 0; i < 2; i++) g_acc[(blockIdx.x * 64 + i * 32 + (t1 >> 3)) * 16 + (t1 & 7)] = make_uint4(0, 0, 0, 0);
            if (blockIdx.x == 0) {
#pragma unroll
                for (int i = 0; i < NFLAG / 1024; i++) reinterpret_cast<uint4*>(g_flag)[i * 256 + t1] = make_uint4(0, 0, 0, 0);
            }
#pragma unroll
            for (int i = 0; i < 12; i++) {
                const int idx = blockIdx.x * 3072 + i * 256 + t1, row = idx / 144;
                reinterpret_cast<float4*>(out)[row * 288 + 144 + (idx - row * 144)] = make_float4(0.f, 0.f, 0.f, 0.f);
            }
            __threadfence();
            bar_sync(1, 256);
            asm volatile("griddepcontrol.launch_dependents;" ::: "memory");
            asm volatile("barrier.cluster.wait.aligned;" ::: "memory");
            const uint32_t ev = sb + O_STG + (2 * t) * 128 + (((2 * w + (g >> 2)) ^ (2 * t)) << 4) + (g & 3) * 4;
            const uint32_t od = (ev ^ 16) + 128;
            auto gather = [&](int dst, uint32_t off) {
                a[dst] = lds32(ev + off); a[dst + 1] = lds32(od + off); a[dst + 2] = lds32(ev + off + 1024); a[dst + 3] = lds32(od + off + 1024);
            };
            mbar_wait(sb + B_W, 0);
#pragma unroll
            for (int u = 8; u < 12; u++) gather(32 + 4 * u, wg * 73728 + KS(u) * 2048);
            mbar_wait(sb + B_W + 8, 0);
            const uint4* xp = reinterpret_cast<const uint4*>(x) + blockIdx.x * 1536 + t1;
            uint4 xv[6];
#pragma unroll
            for (int i = 0; i < 6; i++) xv[i] = __ldg(xp + i * 256);
#pragma unroll
            for (int u = 12; u < 24; u++) gather(32 + 4 * u, wg * 73728 + KS(u) * 2048);
            mbar_wait(sb + B_W + 16, 0);
#pragma unroll
            for (int u = 24; u < 28; u++) gather(32 + 4 * u, wg * 73728 + KS(u) * 2048);
#pragma unroll
            for (int u = 0; u < 8; u++) {
                gather(32 + 4 * u, wg * (73728 + 49152) + KS(u) * 2048);
                gather(4 * u, 73728 - wg * (73728 - 49152) + KS(u) * 2048);
            }
#pragma unroll
            for (int kk = 0; kk < 72; kk++) {
                uint32_t w0 = a[2 * kk], w1 = a[2 * kk + 1];
                a[2 * kk] = __byte_perm(w0, w1, 0x5410);
                a[2 * kk + 1] = __byte_perm(w0, w1, 0x7632);
            }
            if (r == 2) {
                float n0[4], n1[4];
#pragma unroll
                for (int u = 0; u < 36; u++) {
                    const uint32_t x0 = a[4 * u] & 0x7fff7fffu, x1 = a[4 * u + 1] & 0x7fff7fffu, x2 = a[4 * u + 2] & 0x7fff7fffu, x3 = a[4 * u + 3] & 0x7fff7fffu;
                    if (u == 0) mma16816_z(n0, x0, x1, x2, x3, ONES, ONES);
                    else if (u < 8) mma16816(n0, x0, x1, x2, x3, ONES, ONES);
                    else if (u == 8) mma16816_z(n1, x0, x1, x2, x3, ONES, ONES);
                    else mma16816(n1, x0, x1, x2, x3, ONES, ONES);
                }
                const uint32_t mx = __reduce_max_sync(~0u, __float_as_uint(2.f * fmaxf(fmaxf(n0[0], n0[2]), fmaxf(n1[0], n1[2]))));
                sts32_if(lane, sb + O_MISC + 32 + 4 * warp, mx);
            }
            uint32_t xm = 0;
#pragma unroll
            for (int i = 0; i < 6; i++)
                xm = __vmaxu2(xm, __vmaxu2(__vmaxu2(xv[i].x & 0x7fff7fffu, xv[i].y & 0x7fff7fffu), __vmaxu2(xv[i].z & 0x7fff7fffu, xv[i].w & 0x7fff7fffu)));
            sts32_if(lane, sb + O_OF + 16 + 4 * warp, __reduce_max_sync(~0u, max(xm << 16, xm & 0xffff0000u)));
            if (warp == 0) PSTAMP(11);
            bar_arrive(7, 384);
            asm volatile("barrier.cluster.arrive.relaxed.aligned;" ::: "memory");
            bar_sync(1, 256);
            const uint32_t as = sb + O_AS + wg * 8192 + (16 * w + g) * 128 + t * 4;
            sts32(as + (g << 4), a[32]);
            sts32(as + 1024 + (g << 4), a[33]);
            sts32(as + ((1 ^ g) << 4), a[34]);
            sts32(as + 1024 + ((1 ^ g) << 4), a[35]);
            sts128(sb + O_AF + warp * 512 + lane * 16, a[32], a[33], a[34], a[35]);
            fence_async_smem();
            bar_sync(1, 256);
            const uint32_t l = lane * 16;
            const int mi = lane >> 3, isk = (mi >> 1) ? wg : (wg ^ 1);
            adr1 = (r == 2) ? (sb + O_VM + warp * 256 + (l >> 1))
                            : (isk ? (sb + O_KM + w * 512 + wg * 256 + (mi & 1) * 128 + (l & 127))
                                   : (sb + O_QM + w * 512 + (mi & 1) * 256 + wg * 128 + (l & 127)));
            adr1 = __shfl_sync(~0u, adr1, lane);
        }
        int s3 = 2;
#pragma unroll 1
        for (int s = -1; s < NSEG; s++) {
            const uint32_t l16 = opaque(l16c);
            s3 = (s3 == 2) ? 0 : s3 + 1;
            if (s < 0) mbar_wait(sb + B_X, 0);
            const uint64_t desc0 = (uint64_t)(((sb + O_XT + s3 * XT_BYTES) & 0x3FFFF) >> 4) | (1ull << 16) | (64ull << 32) | (1ull << 62);
            uint32_t km0 = 0, km1 = 0;
            if (s >= 0) {
                { const uint4 v = lds128(sb + O_AF + warp * 512 + l16); a[32] = v.x; a[33] = v.y; a[34] = v.z; a[35] = v.w; }
                float co[4], cw[3][4];
                uint4 b[14];
                float inv;
#define GORD(i) ((i) == 0 ? 0 : (i) == 1 ? 1 : (i) == 5 ? 2 : (i) == 9 ? 3 : (i) < 5 ? (i) + 2 : (i) < 9 ? (i) + 1 : (i))
                auto qkv_mma = [&](int i) {
                    const int gi = GORD(i), u = 8 * gi, n0 = 2 * i, n1 = 2 * i + 1;
                    if (gi < 4) {
                        if (i == 0) mma16816_z(co, a[u], a[u + 1], a[u + 2], a[u + 3], b[0].x, b[0].y);
                        else mma16816(co, a[u], a[u + 1], a[u + 2], a[u + 3], b[i].x, b[i].y);
                    }
                    if (n0 < 3) mma16816_z(cw[n0 % 3], a[32 + u], a[32 + u + 1], a[32 + u + 2], a[32 + u + 3], b[i].x, b[i].y);
                    else mma16816(cw[n0 % 3], a[32 + u], a[32 + u + 1], a[32 + u + 2], a[32 + u + 3], b[i].x, b[i].y);
                    if (n1 < 3) mma16816_z(cw[n1 % 3], a[32 + u + 4], a[32 + u + 5], a[32 + u + 6], a[32 + u + 7], b[i].z, b[i].w);
                    else mma16816(cw[n1 % 3], a[32 + u + 4], a[32 + u + 5], a[32 + u + 6], a[32 + u + 7], b[i].z, b[i].w);
                    if (gi < 4) mma16816(co, a[u + 4], a[u + 5], a[u + 6], a[u + 7], b[i].z, b[i].w);
                };
                const uint32_t mf = sb + O_MF + l16, mfs = mf + wg * 6144;
                const uint32_t qb = (s & 1) * 12288;
                bar_sync(2, 384);
                if (warp == 0) STAMP(s, 0);
                auto qkv_ld = [&](int i) { b[i] = GORD(i) < 4 ? lds128v(mfs + GORD(i) * 512) : lds128v(mf + (GORD(i) < 12 ? GORD(i) : GORD(i) + 4) * 512); };
#pragma unroll
                for (int i = 0; i < 5; i++) qkv_ld(i);
#pragma unroll
                for (int i = 0; i < 4; i++) { qkv_mma(i); qkv_ld(5 + i); }
#pragma unroll
                for (int i = 4; i < 9; i++) { qkv_mma(i); qkv_ld(5 + i); }
                inv = __uint_as_float(lds32(sb + O_MISC));
#pragma unroll
                for (int i = 9; i < 14; i++) qkv_mma(i);
#pragma unroll
                for (int i = 0; i < 4; i++) cw[0][i] += cw[1][i] + cw[2][i];
                if (r < 2) {
                    const uint32_t o0 = pack_bf16(co[0] * inv, co[1] * inv), o1 = pack_bf16(co[2] * inv, co[3] * inv);
                    const uint32_t w0 = pack_bf16(cw[0][0] * inv, cw[0][1] * inv), w1 = pack_bf16(cw[0][2] * inv, cw[0][3] * inv);
                    stsm4t(adr1 + qb, o0, o1, w0, w1);
                    if (warp == 0) STAMP(s, 1);
                    asm volatile("{\n.reg .pred p;\nsetp.ge.u32 p, %0, 3;\n@p bar.arrive 1, 256;\n}" :: "r"(warp) : "memory");
                    if (warp < 3 && s < NSEG - 1) {
                        uint4 q[4], k[4];
                        const uint32_t ka = sb + O_QKX + 4096 + qb + warp * 2048 + l16;
#pragma unroll
                        for (int i = 0; i < 4; i++) k[i] = ldsm4(ka + i * 512);
                        const uint32_t dst = sb + O_SC + r * 1280 + warp * 512 + (l16 >> 1);
                        bar_sync(1, 256);
#pragma unroll
                        for (int i = 0; i < 4; i++) q[i] = ldsm4(sb + O_QM + qb + i * 512 + l16);
                        if (warp == 2) {
#pragma unroll
                            for (int i = 0; i < 4; i++) k[i] = ldsm4(ka + i * 512);
                        }
                        float s0[4], s1[4], t0[4], t1[4];
                        mma16816_z(s0, q[0].x, q[0].y, q[0].z, q[0].w, k[0].x, k[0].y);
                        mma16816_z(s1, q[0].x, q[0].y, q[0].z, q[0].w, k[0].z, k[0].w);
                        mma16816_z(t0, q[1].x, q[1].y, q[1].z, q[1].w, k[1].x, k[1].y);
                        mma16816_z(t1, q[1].x, q[1].y, q[1].z, q[1].w, k[1].z, k[1].w);
                        mma16816(s0, q[2].x, q[2].y, q[2].z, q[2].w, k[2].x, k[2].y);
                        mma16816(s1, q[2].x, q[2].y, q[2].z, q[2].w, k[2].z, k[2].w);
                        mma16816(t0, q[3].x, q[3].y, q[3].z, q[3].w, k[3].x, k[3].y);
                        mma16816(t1, q[3].x, q[3].y, q[3].z, q[3].w, k[3].z, k[3].w);
                        const float v0 = (s0[0] + s0[2]) + (t0[0] + t0[2]), v1 = (s0[1] + s0[3]) + (t0[1] + t0[3]);
                        const float v2 = (s1[0] + s1[2]) + (t1[0] + t1[2]), v3 = (s1[1] + s1[3]) + (t1[1] + t1[3]);
                        if (warp < 2) {
                            const uint32_t dv = dst + (l16 >> 1);
                            st_async128(mapa(dv, 2), __float_as_uint(v0), __float_as_uint(v1), __float_as_uint(v2), __float_as_uint(v3), mapa(sb + B_SC, 2));
                            st_async128(mapa(dv, r ^ 1), __float_as_uint(v0), __float_as_uint(v1), __float_as_uint(v2), __float_as_uint(v3), mapa(sb + B_SC, r ^ 1));
                            st_async128(mapa(dv, r), __float_as_uint(v0), __float_as_uint(v1), __float_as_uint(v2), __float_as_uint(v3), mapa(sb + B_SC, r));
                        } else {
                            st_async64(mapa(dst, 2), __float_as_uint(v0 + v2), __float_as_uint(v1 + v3), mapa(sb + B_SC, 2));
                            st_async64(mapa(dst, r ^ 1), __float_as_uint(v0 + v2), __float_as_uint(v1 + v3), mapa(sb + B_SC, r ^ 1));
                            st_async64(mapa(dst, r), __float_as_uint(v0 + v2), __float_as_uint(v1 + v3), mapa(sb + B_SC, r));
                        }
                        if (warp == 2) STAMP(s, 2);
                    } else if (warp < 3) {
                        bar_sync(1, 256);
                    }
                } else {
                    sts128f(sb + O_XP + warp * 512 + l16, co[0], co[1], co[2], co[3]);
                    bar_sync(8 + w, 64);
                    const float4 o = lds128f(sb + O_XP + (warp ^ 4) * 512 + l16);
                    km0 = pack_bf16((cw[0][0] + o.x) * inv, (cw[0][1] + o.y) * inv);
                    km1 = pack_bf16((cw[0][2] + o.z) * inv, (cw[0][3] + o.w) * inv);
                    if (warp == 0) STAMP(s, 1);
                    if (s < NSEG - 1) {
                        st_async64(mapa(adr1, 0), km0, km1, mapa(sb + B_SC, 0));
                        st_async64(mapa(adr1, 1), km0, km1, mapa(sb + B_SC, 1));
                        st_async64(mapa(adr1, 2), km0, km1, mapa(sb + B_SC, 2));
                    }
                    if (warp == 0) STAMP(s, 2);
                }
            }
            char* rec = reinterpret_cast<char*>(g_qkv) + (size_t)(s * NH + h) * REC;
            auto store_qk = [&]() {
                asm volatile("{\n.reg .pred p;\nelect.sync _|p, 0xffffffff;\n"
                    "@p cp.async.bulk.global.shared::cta.bulk_group [%0], [%1], 10240;\n@p cp.async.bulk.commit_group;\n}"
                    :: "l"(rec + r * 10240), "r"(sb + O_QKX + (s & 1) * 12288) : "memory");
            };
            auto store_vm = [&]() { *reinterpret_cast<uint2*>(rec + 28672 + warp * 256 + (l16 >> 1)) = make_uint2(km0, km1); };
            if (s == NSEG - 1) fence_async_smem();
            if (s >= 0) bar_sync(3, 384);
            if (s == NSEG - 1) {
                if (r == 2) store_vm();
                else if (warp == 3) {
                    store_qk();
                    asm volatile("cp.async.bulk.wait_group 0;\nfence.proxy.async.global;" ::: "memory");
                }
            } else {
                const int j = s + 1;
#define XDESC(u) (((u) < 8 ? descs : desc0) + (uint64_t)(((KS(u) >> 2) * 4096 + (KS(u) & 3) * 32) >> 4))
                const uint64_t descs = desc0 + (uint64_t)(wg * (6 * 4096 >> 4));
                float d[16];
                wg_fence();
#pragma unroll
                for (int u = 0; u < 8; u++) {
                    if (u == 0) wgmma_n32_rs<0>(d, a[0], a[1], a[2], a[3], XDESC(0));
                    else wgmma_n32_rs<1>(d, a[4 * u], a[4 * u + 1], a[4 * u + 2], a[4 * u + 3], XDESC(u));
                }
                wg_commit();
                wg_wait0();
                if (warp == 0) STAMP(s, 15);
                if (s >= 0) bar_sync(4, 384);
#pragma unroll
                for (int q = 0; q < 2; q++)
                    sts128(sb + O_XP + warp * 1024 + q * 512 + l16, pack_bf16(d[8 * q], d[8 * q + 1]), pack_bf16(d[8 * q + 2], d[8 * q + 3]),
                           pack_bf16(d[8 * q + 4], d[8 * q + 5]), pack_bf16(d[8 * q + 6], d[8 * q + 7]));
                if (s >= 0) {
                    if (r == 2) store_vm();
                    else fence_async_smem();
                    if (warp == 3) asm volatile("cp.async.bulk.wait_group 0;\nfence.proxy.async.global;" ::: "memory");
                    if (warp == 1 && s + 2 < NSEG) tma_x_tile(sb, &tm_x, r, s + 2, s3 == 2 ? 0 : s3 + 1);
                }
                bar_sync(12, 256);
#pragma unroll
                for (int q = 0; q < 2; q++) {
                    const uint4 o = lds128(sb + O_XP + (warp ^ 4) * 1024 + q * 512 + l16);
                    d[8 * q] = __uint_as_float(o.x << 16); d[8 * q + 1] = __uint_as_float(o.x & 0xffff0000u);
                    d[8 * q + 2] = __uint_as_float(o.y << 16); d[8 * q + 3] = __uint_as_float(o.y & 0xffff0000u);
                    d[8 * q + 4] = __uint_as_float(o.z << 16); d[8 * q + 5] = __uint_as_float(o.z & 0xffff0000u);
                    d[8 * q + 6] = __uint_as_float(o.w << 16); d[8 * q + 7] = __uint_as_float(o.w & 0xffff0000u);
                }
                if (s >= 0) {
                    if (warp == 6 && (s & 3) == 0 && s >= 4)
                        asm volatile("{\n.reg .pred p;\nsetp.eq.u32 p, %1, 0;\n@p red.release.gpu.global.inc.u32 [%0], 0x7fffffff;\n}"
                                     :: "l"(&g_flag[F_QKV + (s - 4 + (h >> 3)) * 8]), "r"(l16) : "memory");
                    asm volatile("{\n.reg .pred p;\nsetp.eq.u32 p, %0, 0;\n@p bar.sync 5, 256;\n@!p bar.sync 13, 256;\n}" :: "r"(wg) : "memory");
                }
                const uint64_t da0 = (uint64_t)(((sb + O_AS + wg * 8192) & 0x3FFFF) >> 4) | (1ull << 16) | (64ull << 32) | (1ull << 62);
                wg_fence();
                wgmma_n32_ss<1>(d, da0, XDESC(0));
#pragma unroll
                for (int u = 1; u < 28; u++) wgmma_n32_rs<1>(d, a[32 + 4 * u], a[32 + 4 * u + 1], a[32 + 4 * u + 2], a[32 + 4 * u + 3], XDESC(u));
                wg_commit();
                wg_wait0();
                if (warp == 3 && r < 2 && s >= 0) store_qk();
                if (warp == 4) STAMP(s, 3);
                uint32_t e[8];
#pragma unroll
                for (int i = 0; i < 8; i++) e[i] = pack_bf16(d[2 * i], d[2 * i + 1]);
                if (r < 2) {
                    const uint32_t base = sb + O_QKX + (j & 1) * 12288 + wg * 4096 + w * 512 + l16;
                    stsm4t(base, e[0], wg ? e[1] : e[2], wg ? e[2] : e[1], e[3]);
                    stsm4t(base + 2048, e[4], wg ? e[5] : e[6], wg ? e[6] : e[5], e[7]);
                } else {
                    const uint32_t base = sb + O_VX + (j & 1) * 8192 + warp * 1024 + l16;
                    sts128(base, e[0], e[1], e[2], e[3]);
                    sts128(base + 512, e[4], e[5], e[6], e[7]);
                    fence_async_smem();
                    bar_arrive(14, 288);
                }
                if (warp == 7) STAMP(s, 4);
                if (s < 0) asm volatile("barrier.cluster.wait.aligned;" ::: "memory");
            }
        }
        bar_arrive(7, 384);
    } else {
        asm volatile("setmaxnreg.dec.sync.aligned.u32 136;");
        const int c = w;
        uint32_t a[96];
        uint32_t mmax = 0;
        {
            const int g = lane >> 2, t = lane & 3;
            uint32_t tag = 0, m0v[18];
            if (threadIdx.x == 256) tag = atomicAdd(&g_ticket, 1u);
#pragma unroll
            for (int i = 0; i < 9; i++) {
                const uint32_t* p = reinterpret_cast<const uint32_t*>(mem0 + g * DM + 16 * (4 * i + c) + 2 * t);
                m0v[2 * i] = __ldg(p); m0v[2 * i + 1] = __ldg(p + 4);
            }
            asm volatile("barrier.cluster.wait.aligned;" ::: "memory");
            if (c == 0) {
                tma_x_tile(sb, &tm_x, r, 0, 0);
                mbar_expect_if(lane, sb + B_SC, 4608);
                if (r < 2) mbar_expect_if(lane, sb + B_VX, 8192);
                sts32_if(lane, sb + O_MISC, __float_as_uint(1.0f));
                sts32_if(lane, sb + O_MISC + 12, __float_as_uint(SM_SCALE));
            }
            asm volatile("barrier.cluster.arrive.relaxed.aligned;" ::: "memory");
#pragma unroll
            for (int tau = 0; tau < 3; tau++) {
                const uint32_t* v = m0v + 6 * tau;
                sts128(sb + O_MF + tau * 3072 + c * 512 + lane * 16, v[0], v[1], v[2], v[3]);
                sts64(sb + O_MF + tau * 3072 + 2048 + (c >> 1) * 512 + lane * 16 + (c & 1) * 8, v[4], v[5]);
#pragma unroll
                for (int i = 0; i < 6; i++) mmax = __vmaxu2(mmax, v[i] & 0x7fff7fffu);
            }
            mmax = max(mmax << 16, mmax & 0xffff0000u);
            bar_arrive(2, 384);
            tag = (__shfl_sync(~0u, tag, 0) / 96u + 1u) & 0xffffu;
            mbar_wait(sb + B_W + 0, 0);
            const __nv_bfloat16* p = Wo + (size_t)(h * 128 + 4 * t) * DM + 192 * r + 16 * c + 2 * g;
#pragma unroll
            for (int i = 0; i < 3; i++)
#pragma unroll
                for (int eb = 0; eb < 8; eb++)
#pragma unroll
                    for (int j = 0; j < 4; j++) a[(i * 8 + eb) * 4 + j] = ldg_nc32(p + (16 * eb + ((j & 1) * 2 + (j >> 1))) * DM + 64 * i);
#pragma unroll
            for (int kk = 0; kk < 48; kk++) {
                uint32_t w0 = a[2 * kk], w1 = a[2 * kk + 1];
                a[2 * kk] = __byte_perm(w0, w1, 0x5410);
                a[2 * kk + 1] = __byte_perm(w0, w1, 0x7632);
            }
            sts128(sb + O_WP + c * 512 + lane * 16, a[92], a[93], a[94], a[95]);
            float wmax = 0.f;
#pragma unroll
            for (int i = 0; i < 3; i++) {
                float n0[4];
#pragma unroll
                for (int u = 8 * i; u < 8 * i + 8; u++) {
                    const uint32_t x0 = a[4 * u] & 0x7fff7fffu, x1 = a[4 * u + 1] & 0x7fff7fffu, x2 = a[4 * u + 2] & 0x7fff7fffu, x3 = a[4 * u + 3] & 0x7fff7fffu;
                    if (u == 8 * i) mma16816_z(n0, x0, x1, x2, x3, ONES, ONES);
                    else mma16816(n0, x0, x1, x2, x3, ONES, ONES);
                }
                wmax = fmaxf(wmax, fmaxf(n0[0], n0[2]));
            }
            uint32_t wm = __reduce_max_sync(~0u, __float_as_uint(wmax));
            sts32_if(lane, sb + O_OF + 4 * c, wm);
            if (c == 0) PSTAMP(8);
            bar_sync(7, 384);
            asm volatile("barrier.cluster.wait.aligned;" ::: "memory");
            if (c == 1) tma_x_tile(sb, &tm_x, r, 1, 1);
            if (c == 0) {
                const uint4 wq = lds128(sb + O_OF), xq = lds128(sb + O_OF + 16), xr = lds128(sb + O_OF + 32), v0 = lds128(sb + O_MISC + 32), v1 = lds128(sb + O_MISC + 48);
                const uint32_t w1 = max(max(wq.x, wq.y), max(wq.z, wq.w)), x1 = max(max(max(xq.x, xq.y), max(xq.z, xq.w)), max(max(xr.x, xr.y), max(xr.z, xr.w)));
                const uint32_t vv = (r < 2) ? 0u : max(max(max(v0.x, v0.y), max(v0.z, v0.w)), max(max(v1.x, v1.y), max(v1.z, v1.w)));
                const uint32_t lo = (min(w1, 0x7f800000u) + 0xffffu) >> 16 | ((min(vv, 0x7f800000u) + 0xffffu) & 0xffff0000u), hi = (x1 & 0xffff0000u) | tag;
                uint32_t l0, h0, l1, h1, l2, h2;
                asm volatile("{\n.reg .pred p;\n.reg .u32 n, x, y;\n.reg .b64 v;\nsetp.eq.u32 p, %10, 0;\nmov.b64 v, {%8, %9};\n@p st.relaxed.gpu.global.b64 [%7], v;\nmov.u32 n, 0;\n"
                             "G_%=: ld.relaxed.gpu.global.b64 v, [%6];\nmov.b64 {%0, %1}, v;\nld.relaxed.gpu.global.b64 v, [%6+256];\nmov.b64 {%2, %3}, v;\n"
                             "ld.relaxed.gpu.global.b64 v, [%6+512];\nmov.b64 {%4, %5}, v;\n"
                             "xor.b32 x, %1, %9;\nxor.b32 y, %3, %9;\nor.b32 x, x, y;\nxor.b32 y, %5, %9;\nor.b32 x, x, y;\nand.b32 x, x, 0xffff;\n"
                             "setp.eq.u32 p, x, 0;\nvote.sync.all.pred p, p, 0xffffffff;\n@p bra.uni E_%=;\n"
                             "add.u32 n, n, 1;\nsetp.lt.u32 p, n, 4000000;\n@p bra.uni G_%=;\ntrap;\nE_%=:\n}"
                             : "=&r"(l0), "=&r"(h0), "=&r"(l1), "=&r"(h1), "=&r"(l2), "=&r"(h2)
                             : "l"(&g_norm[lane]), "l"(&g_norm[blockIdx.x]), "r"(lo), "r"(hi), "r"(lane) : "memory");
                const uint32_t lm = __vmaxu2(l0, __vmaxu2(l1, l2));
                const float fw = __uint_as_float(__reduce_max_sync(~0u, lm << 16));
                const float fv = __uint_as_float(__reduce_max_sync(~0u, lm & 0xffff0000u));
                const float xmax = __uint_as_float(__reduce_max_sync(~0u, max(h0, max(h1, h2)) & 0xffff0000u));
                const float G = 36.f * fw * fv;
                sts32_if(lane, sb + O_MISC + 4, __float_as_uint(G)); sts32_if(lane, sb + O_MISC + 8, __float_as_uint(G * xmax));
            }
        }
        if (c == 0) PSTAMP(12);
        bar_sync(6, 128);
        int s3n = 1;
        uint32_t roff = __shfl_sync(~0u, (r * 4 + c) * 2048 + (lane >> 4) * 512 + (lane & 2) * 128 + (lane & 1) * 64 + (lane & 12) * 4, lane);
#pragma unroll 1
        for (int s = 0; s < NSEG; s++) {
            const uint32_t l16 = opaque(l16c);
            const uint32_t vxa = sb + O_VX + (s & 1) * 8192 + c * 2048 + l16;
            if (c == 0 && r == 2) {
                bar_sync(14, 288);
                asm volatile("{\n.reg .pred p;\nelect.sync _|p, 0xffffffff;\n"
                    "@p cp.async.bulk.global.shared::cta.bulk_group [%0], [%1], 8192;\n@p cp.async.bulk.commit_group;\n"
                    "cp.async.bulk.wait_group 0;\nsetp.lt.and.s32 p, %4, 63, p;\n"
                    "@p cp.async.bulk.shared::cluster.global.mbarrier::complete_tx::bytes.multicast::cluster [%1], [%0], 8192, [%2], %3;\n"
                    "fence.proxy.async.global;\n}"
                    :: "l"(reinterpret_cast<char*>(g_qkv) + (size_t)(s * NH + h) * REC + 20480), "r"(sb + O_VX + (s & 1) * 8192),
                       "r"(sb + B_VX + 8 * (s & 1)), "h"((unsigned short)3), "r"(s) : "memory");
            }
            if (s == NSEG - 1) { bar_sync(3, 384); break; }
            uint4 vx[4];
            sts32_if(l16, sb + O_MISC + 16 + 4 * c, __reduce_max_sync(~0u, mmax));
            if (c == 0) STAMP(s, 5);
            {
                bar_sync(6, 128);
                const uint4 mm = lds128(sb + O_MISC + 16), cf = lds128(sb + O_MISC);
                const float bound = fmaxf(__uint_as_float(cf.z), __uint_as_float(cf.y) * (__uint_as_float(max(max(mm.x, mm.y), max(mm.z, mm.w))) * __uint_as_float(cf.x)));
                const uint32_t ebits = __reduce_max_sync(~0u, min(max(__float_as_uint(bound) & 0x7f800000u, 21u << 23), 254u << 23));
                mbar_wait(sb + B_X + 8 * s3n, ((s + 1) / 3) & 1);
                s3n = (s3n == 2) ? 0 : s3n + 1;
                bar_sync(3, 384);
                if (r < 2) mbar_wait(sb + B_VX + 8 * (s & 1), (s >> 1) & 1);
                vx[0] = lds128(vxa); vx[2] = lds128(vxa + 1024);
                if (c == 0) STAMP(s, 13);
                mbar_wait(sb + B_SC, s & 1);
                if (c == 0) STAMP(s, 6);
                float p[10];
                load_scores(p, sb + O_SC, 1280, l16);
                float mx = fmaxf(fmaxf(fmaxf(p[0], p[1]), fmaxf(p[2], p[3])), fmaxf(fmaxf(p[4], p[5]), fmaxf(p[6], p[7])));
                mx = quad_max(fmaxf(mx, fmaxf(p[8], p[9])));
                const uint4 vm = lds64x2(sb + O_VM + c * 512 + (l16 >> 1));
                vx[1] = lds128(vxa + 512); vx[3] = lds128(vxa + 1536);
                bar_arrive(4, 384);
                const float sc = __uint_as_float(lds32(sb + O_MISC + 12));
                const float mo = mx * SM_SCALE;
                uint32_t P[5];
#pragma unroll
                for (int n = 0; n < 5; n++) P[n] = pack_bf16(ex2(fmaf(p[2 * n], SM_SCALE, -mo)), ex2(fmaf(p[2 * n + 1], n == 3 ? sc : SM_SCALE, -mo)));
                if (c == 0) STAMP(s, 7);
                float o0[4], o1[4], sm[4];
                mma16816_z(sm, ONES, ONES, ONES, ONES, P[1], P[2]);
                mma16816_z(o0, vx[0].x, vx[0].y, vx[0].z, vx[0].w, P[1], P[2]);
                mma16816_z(o1, vx[2].x, vx[2].y, vx[2].z, vx[2].w, P[1], P[2]);
                mma16816(sm, ONES, ONES, ONES, ONES, P[3], P[4]);
                mma16816(o0, vx[1].x, vx[1].y, vx[1].z, vx[1].w, P[3], P[4]);
                mma16816(o1, vx[3].x, vx[3].y, vx[3].z, vx[3].w, P[3], P[4]);
                mma1688(sm, ONES, ONES, P[0]);
                mma1688(o0, vm.x, vm.y, P[0]);
                mma1688(o1, vm.z, vm.w, P[0]);
                const float sig = __uint_as_float((268u << 23) - ebits);
                const float r0 = rcp_fast(sm[0]) * sig, r1 = rcp_fast(sm[1]) * sig;
                stsm4t(sb + O_OF + c * 512 + l16, pack_bf16(o0[0] * r0, o0[1] * r1), pack_bf16(o0[2] * r0, o0[3] * r1),
                       pack_bf16(o1[0] * r0, o1[1] * r1), pack_bf16(o1[2] * r0, o1[3] * r1));
                bar_sync(6, 128);
                uint4 ob[4];
#pragma unroll
                for (int q = 0; q < 4; q++) ob[q] = ldsm4(sb + O_OF + q * 512 + l16);
                { const uint4 v = lds128(sb + O_WP + c * 512 + l16); a[92] = v.x; a[93] = v.y; a[94] = v.z; a[95] = v.w; }
                float m0[3][4], m1[3][4];
#pragma unroll
                for (int q = 0; q < 4; q++) {
#pragma unroll
                    for (int i = 0; i < 3; i++) {
                        const int k0 = (i * 8 + 2 * q) * 4;
                        if (q == 0) mma16816_z(m0[i], a[k0], a[k0 + 1], a[k0 + 2], a[k0 + 3], ob[q].x, ob[q].y);
                        else mma16816(m0[i], a[k0], a[k0 + 1], a[k0 + 2], a[k0 + 3], ob[q].x, ob[q].y);
                    }
#pragma unroll
                    for (int i = 0; i < 3; i++) {
                        const int k1 = (i * 8 + 2 * q + 1) * 4;
                        if (q == 0) mma16816_z(m1[i], a[k1], a[k1 + 1], a[k1 + 2], a[k1 + 3], ob[q].z, ob[q].w);
                        else mma16816(m1[i], a[k1], a[k1 + 1], a[k1 + 2], a[k1 + 3], ob[q].z, ob[q].w);
                    }
                }
                asm volatile("red.relaxed.gpu.global.add.noftz.v4.f16x2 [%0], {%1,%2,%3,%4};" :: "l"(reinterpret_cast<char*>(g_acc) + roff),
                    "r"(pack_f16(m0[0][0] + m1[0][0], m0[0][2] + m1[0][2])), "r"(pack_f16(m0[1][0] + m1[1][0], m0[1][2] + m1[1][2])),
                    "r"(pack_f16(m0[2][0] + m1[2][0], m0[2][2] + m1[2][2])), "r"(0x3c00u) : "memory");
                asm volatile("red.relaxed.gpu.global.add.noftz.v4.f16x2 [%0], {%1,%2,%3,%4};" :: "l"(reinterpret_cast<char*>(g_acc) + roff + 1024),
                    "r"(pack_f16(m0[0][1] + m1[0][1], m0[0][3] + m1[0][3])), "r"(pack_f16(m0[1][1] + m1[1][1], m0[1][3] + m1[1][3])),
                    "r"(pack_f16(m0[2][1] + m1[2][1], m0[2][3] + m1[2][3])), "r"(0x3c00u) : "memory");
                const unsigned t_red = clk();
                bar_arrive(5, 256);
                bar_arrive(13, 256);
                mbar_expect_if(l16 | c, sb + B_SC, 4608);
                mbar_expect_if(l16 | (c ^ 1) | (r >> 1), sb + B_VX + 8 * ((s + 1) & 1), 8192);
                sts32_if(l16 | (c ^ 3), sb + O_MISC, ebits - (14u << 23));
                if (c == 0) STAMPV(s, 8, t_red);
                const char* pbase = reinterpret_cast<const char*>(g_acc) + (s * 24576 + c * 2048) + ((l16 & 64) * 16 + (l16 & 256) + ((l16 & 128) >> 1) + (l16 & 48));
                spin_until(t_red, D_WAIT);
                uint4 v[6];
#pragma unroll
                for (int i = 0; i < 6; i++) v[i] = ldg_relaxed128(pbase + (i >> 1) * 8192 + (i & 1) * 512);
                int nretry = 0;
                auto hand_over = [&]() -> uint32_t {
                    uint32_t ok = 0;
#pragma unroll
                    for (int tau = 0; tau < 3; tau++) {
                        if (tau == 1) sched_fence<0>(h);
                        if (tau == 2) {
                            sched_fence<1>(h);
                            asm volatile("{\n.reg .pred p, q;\n.reg .b32 x;\nlop3.b32 x, %1, %2, %3, 0x80;\nlop3.b32 x, x, %4, %5, 0x80;\nand.b32 x, x, %6;\n"
                                         "setp.eq.u32 p, x, 0x5000;\nvote.sync.all.pred q, p, 0xffffffff;\nselp.u32 %0, 1, 0, q;\n}"
                                         : "=r"(ok) : "r"(v[0].w), "r"(v[1].w), "r"(v[2].w), "r"(v[3].w), "r"(v[4].w), "r"(v[5].w));
                        }
                        v[2 * tau].x = f16x2_to_bf16x2(v[2 * tau].x); v[2 * tau + 1].x = f16x2_to_bf16x2(v[2 * tau + 1].x);
                        v[2 * tau].y = f16x2_to_bf16x2(v[2 * tau].y); v[2 * tau + 1].y = f16x2_to_bf16x2(v[2 * tau + 1].y);
                        v[2 * tau].z = f16x2_to_bf16x2(v[2 * tau].z); v[2 * tau + 1].z = f16x2_to_bf16x2(v[2 * tau + 1].z);
                        sts128(sb + O_MF + tau * 3072 + c * 512 + l16, v[2 * tau].x, v[2 * tau + 1].x, v[2 * tau].y, v[2 * tau + 1].y);
                        sts64(sb + O_MF + tau * 3072 + 2048 + (c >> 1) * 512 + (c & 1) * 8 + l16, v[2 * tau].z, v[2 * tau + 1].z);
                    }
                    asm volatile("{\n.reg .pred p;\nsetp.ne.u32 p, %0, 0;\n@p bar.arrive 2, 384;\n}" :: "r"(ok) : "memory");
                    return ok;
                };
                if (!hand_over()) {
                    asm volatile("{\n.reg .pred p, q;\n.reg .u32 n, x;\nmov.u32 n, 0;\n"
                         "R_%=: ld.relaxed.gpu.global.v4.u32 {%0,%1,%2,%3}, [%25];\nld.relaxed.gpu.global.v4.u32 {%4,%5,%6,%7}, [%25+512];\n"
                         "ld.relaxed.gpu.global.v4.u32 {%8,%9,%10,%11}, [%25+8192];\nld.relaxed.gpu.global.v4.u32 {%12,%13,%14,%15}, [%25+8704];\n"
                         "ld.relaxed.gpu.global.v4.u32 {%16,%17,%18,%19}, [%25+16384];\nld.relaxed.gpu.global.v4.u32 {%20,%21,%22,%23}, [%25+16896];\n"
                         "add.u32 %24, %24, 1;\nand.b32 x, %3, %7;\nand.b32 x, x, %11;\nand.b32 x, x, %15;\nand.b32 x, x, %19;\nand.b32 x, x, %23;\n"
                         "setp.eq.u32 p, x, 0x5000;\nvote.sync.all.pred q, p, 0xffffffff;\n@q bra.uni K_%=;\n"
                         "add.u32 n, n, 1;\nsetp.lt.u32 q, n, 2000000;\n@q bra.uni R_%=;\ntrap;\nK_%=:\n}"
                         : "+r"(v[0].x), "+r"(v[0].y), "+r"(v[0].z), "+r"(v[0].w), "+r"(v[1].x), "+r"(v[1].y), "+r"(v[1].z), "+r"(v[1].w),
                           "+r"(v[2].x), "+r"(v[2].y), "+r"(v[2].z), "+r"(v[2].w), "+r"(v[3].x), "+r"(v[3].y), "+r"(v[3].z), "+r"(v[3].w),
                           "+r"(v[4].x), "+r"(v[4].y), "+r"(v[4].z), "+r"(v[4].w), "+r"(v[5].x), "+r"(v[5].y), "+r"(v[5].z), "+r"(v[5].w), "+r"(nretry)
                         : "l"(pbase) : "memory");
                    hand_over();
                }
                if (c == 0) STAMP(s, 12);
                if (c == 0) STAMPV(s, 14, nretry);
                mmax = absmax2(absmax2(absmax2(v[0].x, v[0].y), absmax2(v[0].z, v[1].x)), absmax2(absmax2(v[1].y, v[1].z), absmax2(v[2].x, v[2].y)));
                mmax = absmax2(mmax, absmax2(absmax2(absmax2(v[2].z, v[3].x), absmax2(v[3].y, v[3].z)), absmax2(absmax2(v[4].x, v[4].y), absmax2(v[4].z, v[5].x))));
                mmax = absmax2(mmax, absmax2(v[5].y, v[5].z)) & 0x7fff7fffu;
                mmax = max(mmax << 16, mmax & 0xffff0000u);
            }
            roff += 24576;
        }
        {
            bar_sync(7, 384);
            if (c == 0)
                asm volatile("{\n.reg .pred p;\nsetp.eq.u32 p, %1, 0;\n@p red.release.gpu.global.inc.u32 [%0], 0x7fffffff;\n}"
                             :: "l"(&g_flag[F_QKV + (60 + (h >> 3)) * 8]), "r"(l16c) : "memory");
        }
    }
    if (warp == 8) PSTAMP(13);
    cluster_sync();
}

constexpr int NST = 10;
constexpr int G_RING = 0, G_EX = NST * 16384, G_OUT = G_EX + 32768, G_CARRY = G_OUT + 32768, G_BAR = G_CARRY + 512, BG_SMEM = G_BAR + 256;
constexpr int GB_FULL = G_BAR, GB_EMPTY = G_BAR + 8 * NST, GB_W = G_BAR + 16 * NST;
static_assert(BG_SMEM <= 232448, "smem");

template <int ACC>
__device__ __forceinline__ void wgmma_n128_rs(float (&d)[64], uint32_t a0, uint32_t a1, uint32_t a2, uint32_t a3, uint64_t desc) {
    asm volatile("wgmma.mma_async.sync.aligned.m64n128k16.f32.bf16.bf16 "
        "{%0,%1,%2,%3,%4,%5,%6,%7,%8,%9,%10,%11,%12,%13,%14,%15,%16,%17,%18,%19,%20,%21,%22,%23,%24,%25,%26,%27,%28,%29,%30,%31,"
        "%32,%33,%34,%35,%36,%37,%38,%39,%40,%41,%42,%43,%44,%45,%46,%47,%48,%49,%50,%51,%52,%53,%54,%55,%56,%57,%58,%59,%60,%61,%62,%63}, "
        "{%64,%65,%66,%67}, %68, %69, 1, 1, 0;"
        : "+f"(d[0]), "+f"(d[1]), "+f"(d[2]), "+f"(d[3]), "+f"(d[4]), "+f"(d[5]), "+f"(d[6]), "+f"(d[7]),
          "+f"(d[8]), "+f"(d[9]), "+f"(d[10]), "+f"(d[11]), "+f"(d[12]), "+f"(d[13]), "+f"(d[14]), "+f"(d[15]),
          "+f"(d[16]), "+f"(d[17]), "+f"(d[18]), "+f"(d[19]), "+f"(d[20]), "+f"(d[21]), "+f"(d[22]), "+f"(d[23]),
          "+f"(d[24]), "+f"(d[25]), "+f"(d[26]), "+f"(d[27]), "+f"(d[28]), "+f"(d[29]), "+f"(d[30]), "+f"(d[31]),
          "+f"(d[32]), "+f"(d[33]), "+f"(d[34]), "+f"(d[35]), "+f"(d[36]), "+f"(d[37]), "+f"(d[38]), "+f"(d[39]),
          "+f"(d[40]), "+f"(d[41]), "+f"(d[42]), "+f"(d[43]), "+f"(d[44]), "+f"(d[45]), "+f"(d[46]), "+f"(d[47]),
          "+f"(d[48]), "+f"(d[49]), "+f"(d[50]), "+f"(d[51]), "+f"(d[52]), "+f"(d[53]), "+f"(d[54]), "+f"(d[55]),
          "+f"(d[56]), "+f"(d[57]), "+f"(d[58]), "+f"(d[59]), "+f"(d[60]), "+f"(d[61]), "+f"(d[62]), "+f"(d[63])
        : "r"(a0), "r"(a1), "r"(a2), "r"(a3), "l"(desc), "n"(ACC));
}
__device__ __forceinline__ void wait_flag(const unsigned* p, unsigned target) {
    asm volatile("{\n.reg .pred p;\n.reg .u32 n, v;\nmov.u32 n, 0;\n"
                 "W_%=: ld.acquire.gpu.global.u32 v, [%0];\nsetp.ge.u32 p, v, %1;\n@p bra.uni D_%=;\nnanosleep.u32 100;\n"
                 "add.u32 n, n, 1;\nsetp.lt.u32 p, n, 4000000;\n@p bra.uni W_%=;\ntrap;\nD_%=:\n}" :: "l"(p), "r"(target) : "memory");
}
__device__ __forceinline__ void flag_inc_if(uint32_t z, unsigned* p) {
    asm volatile("{\n.reg .pred p;\nsetp.eq.u32 p, %1, 0;\n@p red.release.gpu.global.inc.u32 [%0], 0x7fffffff;\n}" :: "l"(p), "r"(z) : "memory");
}
template <int NS, int STRIDE>
__device__ __forceinline__ void bg_mainloop(float (&d)[64], const uint32_t (&a)[144], uint32_t sb, int it, int lane) {
    int slot = it % NST, ph = (it / NST) & 1, prev = 0;
#pragma unroll
    for (int i = 0; i < NS; i++) {
        mbar_wait(sb + GB_FULL + 8 * slot, ph);
        const uint64_t desc = (uint64_t)(((sb + G_RING + slot * 16384) & 0x3FFFF) >> 4) | (1ull << 16) | (64ull << 32) | (1ull << 62);
        wg_fence();
#pragma unroll
        for (int k = 0; k < 4; k++) {
            const int u = 16 * i + 4 * k;
            if (i == 0 && k == 0) wgmma_n128_rs<0>(d, a[u], a[u + 1], a[u + 2], a[u + 3], desc);
            else wgmma_n128_rs<1>(d, a[u], a[u + 1], a[u + 2], a[u + 3], desc + 2 * k);
        }
        wg_commit();
        if (i > 0) {
            asm volatile("wgmma.wait_group.sync.aligned 1;" ::: "memory");
            mbar_arrive_if(lane, sb + GB_EMPTY + 8 * prev);
        }
        prev = slot;
        slot += STRIDE;
        if (slot >= NST) { slot -= NST; ph ^= 1; }
    }
    wg_wait0();
    mbar_arrive_if(lane, sb + GB_EMPTY + 8 * prev);
}
template <bool SKIP>
__device__ __forceinline__ void bg_epilogue(float (&d)[64], uint32_t sb, int wg, int w, int lane, const CUtensorMap* tm_out, int col0, int tok0,
                                            const __nv_bfloat16* xa, const __nv_bfloat16* Dk) {
    const int g = lane >> 2, t = lane & 3;
    const uint32_t ex = sb + G_EX + w * 4096 + lane * 16;
    float k[32];
    if (wg == 0) {
#pragma unroll
        for (int q = 0; q < 8; q++) sts128f(ex + q * 512, d[32 + 4 * q], d[32 + 4 * q + 1], d[32 + 4 * q + 2], d[32 + 4 * q + 3]);
#pragma unroll
        for (int i = 0; i < 32; i++) k[i] = d[i];
    } else {
#pragma unroll
        for (int q = 0; q < 8; q++) sts128f(ex + 16384 + q * 512, d[4 * q], d[4 * q + 1], d[4 * q + 2], d[4 * q + 3]);
#pragma unroll
        for (int i = 0; i < 32; i++) k[i] = d[32 + i];
    }
    uint32_t xv[16], dv = 0;
    if (SKIP) {
        const __nv_bfloat16* xp = xa + (size_t)(tok0 + 64 * wg + 2 * t) * DM + col0 + 16 * w + 2 * g;
#pragma unroll
        for (int i = 0; i < 16; i++) xv[i] = ldg_nc32(xp + (8 * (i >> 1) + (i & 1)) * DM);
        dv = ldg_nc32(Dk + col0 + 16 * w + 2 * g);
    }
    if (w == 0) asm volatile("cp.async.bulk.wait_group.read 0;" ::: "memory");
    bar_sync(1, 256);
#pragma unroll
    for (int q = 0; q < 8; q++) {
        const float4 o = lds128f(ex + (wg ^ 1) * 16384 + q * 512);
        k[4 * q] += o.x; k[4 * q + 1] += o.y; k[4 * q + 2] += o.z; k[4 * q + 3] += o.w;
    }
    bar_sync(1, 256);
    const uint32_t ob = sb + G_OUT + wg * 16384 + (w >> 1) * 8192 + (g & 1) * 8;
    const uint32_t ch = (w & 1) * 4 + (g >> 1);
#pragma unroll
    for (int i = 0; i < 16; i++) {
        float v0 = k[4 * (i >> 1) + (i & 1)], v1 = k[4 * (i >> 1) + 2 + (i & 1)];
        if (SKIP) {
            const uint32_t p = pack_bf16(__uint_as_float(xv[i] << 16) * __uint_as_float(dv << 16), __uint_as_float(xv[i] & 0xffff0000u) * __uint_as_float(dv & 0xffff0000u));
            v0 += __uint_as_float(p << 16); v1 += __uint_as_float(p & 0xffff0000u);
        }
        const uint32_t n7 = 2 * t + (i & 1);
        sts64(ob + (8 * (i >> 1) + n7) * 128 + ((ch ^ n7) << 4), __float_as_uint(v0), __float_as_uint(v1));
    }
    fence_async_smem();
    bar_sync(4 + wg, 128);
    if (w == 0) {
        if (SKIP)
            asm volatile("{\n.reg .pred p;\nelect.sync _|p, 0xffffffff;\n"
                "@p cp.async.bulk.tensor.2d.global.shared::cta.bulk_group [%0, {%2, %4}], [%1];\n"
                "@p cp.async.bulk.tensor.2d.global.shared::cta.bulk_group [%0, {%3, %4}], [%1+8192];\n@p cp.async.bulk.commit_group;\n}"
                :: "l"(tm_out), "r"(sb + G_OUT + wg * 16384), "r"(col0), "r"(col0 + 32), "r"(tok0 + 64 * wg) : "memory");
        else
            asm volatile("{\n.reg .pred p;\nelect.sync _|p, 0xffffffff;\n"
                "@p cp.reduce.async.bulk.tensor.2d.global.shared::cta.add.bulk_group [%0, {%2, %4}], [%1];\n"
                "@p cp.reduce.async.bulk.tensor.2d.global.shared::cta.add.bulk_group [%0, {%3, %4}], [%1+8192];\n@p cp.async.bulk.commit_group;\n}"
                :: "l"(tm_out), "r"(sb + G_OUT + wg * 16384), "r"(col0), "r"(col0 + 32), "r"(tok0 + 64 * wg) : "memory");
    }
}
__device__ __forceinline__ void s5_channel(int p, const __nv_bfloat16* Lre, const __nv_bfloat16* Lim, const __nv_bfloat16* logdt, float2& lam, float2& coef) {
    const float dt = __bfloat162float(__float2bfloat16(expf(__bfloat162float(logdt[p]))));
    const float lr = __bfloat162float(Lre[p]), li = __bfloat162float(Lim[p]);
    const float e = expf(dt * lr);
    float sn, cs;
    sincosf(dt * li, &sn, &cs);
    lam = make_float2(e * cs, e * sn);
    const float den = lr * lr + li * li;
    coef = make_float2(((lam.x - 1.f) * lr + lam.y * li) / den, (lam.y * lr - (lam.x - 1.f) * li) / den);
}
__device__ __forceinline__ float2 cfma(float2 a, float2 b, float2 c) {
    return make_float2(fmaf(a.x, b.x, fmaf(-a.y, b.y, c.x)), fmaf(a.x, b.y, fmaf(a.y, b.x, c.y)));
}
__device__ __forceinline__ uint4 ldg128(const void* p) { uint4 v; asm volatile("ld.global.v4.u32 {%0,%1,%2,%3}, [%4];" : "=r"(v.x), "=r"(v.y), "=r"(v.z), "=r"(v.w) : "l"(p) : "memory"); return v; }
__device__ __forceinline__ uint2 ldg64(const void* p) { uint2 v; asm volatile("ld.global.v2.u32 {%0,%1}, [%2];" : "=r"(v.x), "=r"(v.y) : "l"(p) : "memory"); return v; }

__device__ __forceinline__ void bg_attention(uint32_t stg, int seg, int head, int mt, int lane) {
    const int g = lane >> 2, t = lane & 3;
    const char* rec = reinterpret_cast<const char*>(g_qkv) + (size_t)(seg * NH + head) * REC;
    float sc[5][4];
#pragma unroll
    for (int n = 0; n < 5; n++) sc[n][0] = sc[n][1] = sc[n][2] = sc[n][3] = 0.f;
    const char* qp = rec + mt * 2048 + (t >> 1) * 512 + (t & 1) * 256 + g * 16;
    const char* kp = rec + 4096 + (t >> 1) * 512 + (t & 1) * 128 + g * 16;
#pragma unroll
    for (int r = 0; r < 2; r++) {
        uint4 q[2][2], k[2][6];
#pragma unroll
        for (int wp = 0; wp < 2; wp++) {
            const int o = r * 10240 + wp * 1024;
            q[wp][0] = ldg128(qp + o); q[wp][1] = ldg128(qp + o + 128);
            k[wp][0] = ldg128(kp + o + 4096); k[wp][1] = ldg128(kp + o + 4096 + 256);
            k[wp][2] = ldg128(kp + o); k[wp][3] = ldg128(kp + o + 256);
            k[wp][4] = ldg128(kp + o + mt * 2048); k[wp][5] = ldg128(kp + o + mt * 2048 + 256);
        }
#pragma unroll
        for (int wp = 0; wp < 2; wp++)
#pragma unroll
            for (int n = 0; n < 6; n++) {
                mma16816(sc[n < 2 ? 0 : n - 1], q[wp][0].x, q[wp][1].x, q[wp][0].y, q[wp][1].y, k[wp][n].x, k[wp][n].y);
                mma16816(sc[n < 2 ? 0 : n - 1], q[wp][0].z, q[wp][1].z, q[wp][0].w, q[wp][1].w, k[wp][n].z, k[wp][n].w);
            }
    }
    const char* vp = rec + 20480 + lane * 16;
    uint4 v[8]; uint2 vm[4];
#pragma unroll
    for (int i = 0; i < 8; i++) v[i] = ldg128(vp + i * 512);
#pragma unroll
    for (int i = 0; i < 4; i++) vm[i] = ldg64(rec + 28672 + i * 256 + lane * 8);
    const int q0 = 16 * mt + 8 + g - 2 * t;
#pragma unroll
    for (int n = 1; n < 5; n++) {
        if (8 * n > q0) sc[n][0] = -INFINITY;
        if (8 * n + 1 > q0) sc[n][1] = -INFINITY;
        if (8 * n > q0 + 8) sc[n][2] = -INFINITY;
        if (8 * n + 1 > q0 + 8) sc[n][3] = -INFINITY;
    }
    float ma = fmaxf(sc[0][0], sc[0][1]), mb = fmaxf(sc[0][2], sc[0][3]);
#pragma unroll
    for (int n = 1; n < 5; n++) { ma = fmaxf(ma, fmaxf(sc[n][0], sc[n][1])); mb = fmaxf(mb, fmaxf(sc[n][2], sc[n][3])); }
    ma = quad_max(ma) * SM_SCALE; mb = quad_max(mb) * SM_SCALE;
    uint32_t Pa[5], Pb[5];
#pragma unroll
    for (int n = 0; n < 5; n++) {
        Pa[n] = pack_bf16(ex2(fmaf(sc[n][0], SM_SCALE, -ma)), ex2(fmaf(sc[n][1], SM_SCALE, -ma)));
        Pb[n] = pack_bf16(ex2(fmaf(sc[n][2], SM_SCALE, -mb)), ex2(fmaf(sc[n][3], SM_SCALE, -mb)));
    }
    float sa[4], sbb[4];
    mma1688_z(sa, ONES, ONES, Pa[0]); mma1688_z(sbb, ONES, ONES, Pb[0]);
    mma16816(sa, ONES, ONES, ONES, ONES, Pa[1], Pa[2]); mma16816(sbb, ONES, ONES, ONES, ONES, Pb[1], Pb[2]);
    mma16816(sa, ONES, ONES, ONES, ONES, Pa[3], Pa[4]); mma16816(sbb, ONES, ONES, ONES, ONES, Pb[3], Pb[4]);
    const float ra0 = rcp_fast(sa[0]), ra1 = rcp_fast(sa[1]), rb0 = rcp_fast(sbb[0]), rb1 = rcp_fast(sbb[1]);
    const uint32_t row = lane & 7;
    const uint32_t st0 = stg + (lane >> 4) * 1024 + row * 128;
#pragma unroll
    for (int eh = 0; eh < 2; eh++) {
#pragma unroll
        for (int e4 = 0; e4 < 4; e4++) {
            float oa[4], ob[4];
            mma1688_z(oa, vm[e4].x, vm[e4].y, Pa[0]); mma1688_z(ob, vm[e4].x, vm[e4].y, Pb[0]);
            mma16816(oa, v[2 * e4].x, v[2 * e4].y, v[2 * e4].z, v[2 * e4].w, Pa[1], Pa[2]);
            mma16816(ob, v[2 * e4].x, v[2 * e4].y, v[2 * e4].z, v[2 * e4].w, Pb[1], Pb[2]);
            mma16816(oa, v[2 * e4 + 1].x, v[2 * e4 + 1].y, v[2 * e4 + 1].z, v[2 * e4 + 1].w, Pa[3], Pa[4]);
            mma16816(ob, v[2 * e4 + 1].x, v[2 * e4 + 1].y, v[2 * e4 + 1].z, v[2 * e4 + 1].w, Pb[3], Pb[4]);
            if (eh == 0) {
                v[2 * e4] = ldg128(vp + 4096 + 2 * e4 * 512); v[2 * e4 + 1] = ldg128(vp + 4096 + (2 * e4 + 1) * 512);
                vm[e4] = ldg64(rec + 28672 + 1024 + e4 * 256 + lane * 8);
            }
            stsm4t(st0 + eh * 2048 + (((2 * e4 + ((lane >> 3) & 1)) ^ row) << 4), pack_bf16(oa[0] * ra0, oa[1] * ra1), pack_bf16(oa[2] * ra0, oa[3] * ra1),
                   pack_bf16(ob[0] * rb0, ob[1] * rb1), pack_bf16(ob[2] * rb0, ob[3] * rb1));
        }
    }
    __syncwarp();
    char* op = reinterpret_cast<char*>(g_ox) + ((size_t)(head * 2) * SEQ + seg * 32 + 16 * mt) * 128 + lane * 16;
#pragma unroll
    for (int i = 0; i < 8; i++) *reinterpret_cast<uint4*>(op + (i >> 2) * (SEQ * 128) + (i & 3) * 512) = lds128(stg + i * 512 + lane * 16);
}

__global__ void __launch_bounds__(384, 1)
bg_kernel(const __grid_constant__ CUtensorMap tm_xa, const __grid_constant__ CUtensorMap tm_wo, const __grid_constant__ CUtensorMap tm_out,
          const __nv_bfloat16* __restrict__ xa, const __nv_bfloat16* __restrict__ Lre, const __nv_bfloat16* __restrict__ Lim,
          const __nv_bfloat16* __restrict__ Bre, const __nv_bfloat16* __restrict__ Bim, const __nv_bfloat16* __restrict__ Cre,
          const __nv_bfloat16* __restrict__ Cim, const __nv_bfloat16* __restrict__ logdt, const __nv_bfloat16* __restrict__ Dk) {
    extern __shared__ __align__(1024) uint8_t smem_raw[];
    const uint32_t sb = smem_u32(smem_raw);
    const int lane = threadIdx.x & 31;
    const int warp = __shfl_sync(~0u, threadIdx.x >> 5, 0);
    const int wg = warp >> 2, w = warp & 3, b = blockIdx.x;
    const int nt = b % 9, kq = b / 9;
    if (threadIdx.x == 0) {
        if (sb & 1023u) __trap();
        for (int i = 0; i < NST; i++) { mbar_init(sb + GB_FULL + 8 * i, 1); mbar_init(sb + GB_EMPTY + 8 * i, 4); }
        mbar_init(sb + GB_W, 1);
        asm volatile("fence.mbarrier_init.release.cluster;" ::: "memory");
        mbar_expect(sb + GB_W, (b < 18 ? 64 : 128) * 1152);
    }
    __syncthreads();
    if (wg == 2) {
        asm volatile("setmaxnreg.dec.sync.aligned.u32 24;");
        if (w == 0) {
            int slot = 0, ph = 1;
            auto next = [&]() { if (++slot == NST) { slot = 0; ph ^= 1; } };
            bar_sync(6, 288);
            if (b < 18) {
#pragma unroll 1
                for (int i = 0; i < 144; i++) {
                    const int blk = i / 9, kb = i - 9 * blk, it = (blk >> 1) * 18 + (blk & 1) + 2 * kb;
                    slot = it % NST;
                    mbar_wait(sb + GB_EMPTY + 8 * slot, ((it / NST) & 1) ^ 1);
                    asm volatile("{\n.reg .pred p;\nelect.sync _|p, 0xffffffff;\n@p mbarrier.arrive.expect_tx.shared::cta.b64 _, [%2], 16384;\n"
                        "@p cp.async.bulk.tensor.5d.shared::cluster.global.mbarrier::complete_tx::bytes [%0], [%1, {%3, %4, %4, %4, %5}], [%2];\n}"
                        :: "r"(sb + G_RING + slot * 16384), "l"(&tm_xa), "r"(sb + GB_FULL + 8 * slot), "r"(kb * 64), "r"(0), "r"(blk) : "memory");
                }
                slot = 144 % NST; ph = ((144 / NST) & 1) ^ 1;
            }
#pragma unroll 1
            for (int phase = (b < 18); phase < 2; phase++) {
                if (phase == 1) bar_sync(6, 288);
                const int ns = phase ? 16 : 18;
#pragma unroll 1
                for (int j = 0; j < (phase ? 16 : 8); j++) {
                    const int blk = phase ? j : 2 * j + (kq - 2);
                    wait_flag(&g_flag[phase ? F_OX + (blk * 4 + kq) * 8 : F_H + blk * 8], phase ? 8 : 18);
                    asm volatile("fence.proxy.async.global;" ::: "memory");
                    const char* src = (phase ? reinterpret_cast<const char*>(g_ox) + (size_t)kq * 16 * SEQ * 128 : reinterpret_cast<const char*>(g_h)) + blk * 16384;
#pragma unroll 1
                    for (int i = 0; i < ns; i++) {
                        mbar_wait(sb + GB_EMPTY + 8 * slot, ph);
                        asm volatile("{\n.reg .pred p;\nelect.sync _|p, 0xffffffff;\n@p mbarrier.arrive.expect_tx.shared::cta.b64 _, [%2], 16384;\n"
                            "@p cp.async.bulk.shared::cluster.global.mbarrier::complete_tx::bytes [%0], [%1], 16384, [%2];\n}"
                            :: "r"(sb + G_RING + slot * 16384), "l"(src + (size_t)((i & 1) * (ns >> 1) + (i >> 1)) * (SEQ * 128)), "r"(sb + GB_FULL + 8 * slot) : "memory");
                        next();
                    }
                }
            }
        }
    } else {
        asm volatile("setmaxnreg.inc.sync.aligned.u32 240;");
        const int g = lane >> 2, t = lane & 3, tid = threadIdx.x;
        uint32_t a[144];
        float d[64];
        if (b < 18) {
            if (tid < 64)
                asm volatile("cp.async.bulk.shared::cluster.global.mbarrier::complete_tx::bytes [%0], [%1], 1152, [%2];"
                    :: "r"(sb + tid * 1168), "l"((tid < 32 ? Bre : Bim) + (size_t)(32 * b + (tid & 31)) * DM), "r"(sb + GB_W) : "memory");
            float2 lam, coef;
            s5_channel(32 * b + 8 * w + g, Lre, Lim, logdt, lam, coef);
            float2 l32 = lam;
#pragma unroll
            for (int i = 0; i < 5; i++) l32 = make_float2(l32.x * l32.x - l32.y * l32.y, 2.f * l32.x * l32.y);
            __syncwarp();
            mbar_wait(sb + GB_W, 0);
            const uint32_t ap = sb + (((lane >> 3) & 1) * 32 + 8 * w + (lane & 7)) * 1168 + (lane >> 4) * 16;
#pragma unroll
            for (int ks = 0; ks < 36; ks++) { const uint4 v = ldsm4(ap + ks * 32); a[4 * ks] = v.x; a[4 * ks + 1] = v.y; a[4 * ks + 2] = v.z; a[4 * ks + 3] = v.w; }
            bar_sync(1, 256);
            bar_arrive(6, 288);
#pragma unroll 1
            for (int blk = wg; blk < 16; blk += 2) {
                bg_mainloop<9, 2>(d, a, sb, (blk >> 1) * 18 + wg, lane);
                float2 e = make_float2(0.f, 0.f);
#pragma unroll
                for (int i = 0; i < 32; i++) e = cfma(lam, e, make_float2(d[4 * (i >> 1) + (i & 1)], d[4 * (i >> 1) + 2 + (i & 1)]));
                float2 cin = make_float2(0.f, 0.f);
                if (blk > 0) { bar_sync(2 + (wg ^ 1), 256); cin = lds64f(sb + G_CARRY + (wg ^ 1) * 256 + (8 * w + g) * 8); }
                float2 mine = cin;
#pragma unroll
                for (int q = 0; q < 4; q++) {
                    const float2 eq = make_float2(__shfl_sync(~0u, e.x, (lane & 28) + q), __shfl_sync(~0u, e.y, (lane & 28) + q));
                    cin = cfma(l32, cin, eq);
                    if (t == q + 1) mine = cin;
                }
                if (blk < 15) {
                    if (t == 0) sts64(sb + G_CARRY + wg * 256 + (8 * w + g) * 8, __float_as_uint(cin.x), __float_as_uint(cin.y));
                    bar_arrive(2 + wg, 256);
                }
                const uint32_t hs = sb + G_OUT + wg * 16384 + t * 4096 + (g & 3) * 4;
                const uint32_t ch = 2 * w + (g >> 2);
#pragma unroll
                for (int i = 0; i < 32; i++) {
                    mine = cfma(lam, mine, make_float2(d[4 * (i >> 1) + (i & 1)], d[4 * (i >> 1) + 2 + (i & 1)]));
                    sts32(hs + i * 128 + ((ch ^ (i & 7)) << 4), pack_bf16(mine.x, mine.y));
                }
                fence_async_smem();
                bar_sync(4 + wg, 128);
                if (w == 0) {
                    asm volatile("{\n.reg .pred p;\nelect.sync _|p, 0xffffffff;\n@p cp.async.bulk.global.shared::cta.bulk_group [%0], [%1], 16384;\n"
                        "@p cp.async.bulk.commit_group;\ncp.async.bulk.wait_group 0;\nfence.proxy.async.global;\n}"
                        :: "l"(reinterpret_cast<char*>(g_h) + ((size_t)b * SEQ + blk * 128) * 128), "r"(sb + G_OUT + wg * 16384) : "memory");
                    __syncwarp();
                    flag_inc_if(lane, &g_flag[F_H + blk * 8]);
                }
                bar_sync(4 + wg, 128);
            }
        } else {
            if (tid < 128)
                asm volatile("cp.async.bulk.shared::cluster.global.mbarrier::complete_tx::bytes [%0], [%1], 1152, [%2];"
                    :: "r"(sb + tid * 1168), "l"((tid < 64 ? Cre : Cim) + (size_t)(64 * nt + (tid & 63)) * DM), "r"(sb + GB_W) : "memory");
            for (int p = tid; p < DM; p += 256) {
                float2 lam, coef;
                s5_channel(p, Lre, Lim, logdt, lam, coef);
                sts64(sb + G_EX + p * 8, __float_as_uint(2.f * coef.x), __float_as_uint(2.f * coef.y));
            }
            bar_sync(1, 256);
            mbar_wait(sb + GB_W, 0);
            const uint32_t cp = sb + (16 * w + 2 * g) * 1168 + (288 * wg + t) * 2;
#pragma unroll
            for (int u = 0; u < 72; u++) {
                const float2 c2 = lds64f(sb + G_EX + (288 * wg + 4 * u + t) * 8);
#pragma unroll
                for (int f = 0; f < 2; f++) {
                    unsigned short r16, i16;
                    asm volatile("ld.shared.u16 %0, [%1];" : "=h"(r16) : "r"(cp + f * 1168 + u * 8) : "memory");
                    asm volatile("ld.shared.u16 %0, [%1];" : "=h"(i16) : "r"(cp + (64 + f) * 1168 + u * 8) : "memory");
                    const float cr = __uint_as_float((uint32_t)r16 << 16), ci = __uint_as_float((uint32_t)i16 << 16);
                    a[2 * u + f] = pack_bf16(cr * c2.x - ci * c2.y, -(cr * c2.y + ci * c2.x));
                }
            }
            bar_sync(1, 256);
            bar_arrive(6, 288);
#pragma unroll 1
            for (int j = 0; j < 8; j++) {
                bg_mainloop<9, 2>(d, a, sb, j * 18 + wg, lane);
                bg_epilogue<true>(d, sb, wg, w, lane, &tm_out, 64 * nt, (2 * j + kq - 2) * 128, xa, Dk);
            }
        }
        bar_sync(1, 256);
        if (warp == 0)
            asm volatile("{\n.reg .pred p;\nelect.sync _|p, 0xffffffff;\n@p mbarrier.arrive.expect_tx.shared::cta.b64 _, [%2], 131072;\n"
                "@p cp.async.bulk.tensor.2d.shared::cluster.global.mbarrier::complete_tx::bytes [%0], [%1, {%3, %4}], [%2];\n"
                "@p cp.async.bulk.tensor.2d.shared::cluster.global.mbarrier::complete_tx::bytes [%0+32768], [%1, {%3, %5}], [%2];\n"
                "@p cp.async.bulk.tensor.2d.shared::cluster.global.mbarrier::complete_tx::bytes [%0+65536], [%1, {%3, %6}], [%2];\n"
                "@p cp.async.bulk.tensor.2d.shared::cluster.global.mbarrier::complete_tx::bytes [%0+98304], [%1, {%3, %7}], [%2];\n}"
                :: "r"(sb), "l"(&tm_wo), "r"(sb + GB_W), "r"(64 * nt), "r"(1024 * kq), "r"(1024 * kq + 256), "r"(1024 * kq + 512), "r"(1024 * kq + 768) : "memory");
        mbar_wait(sb + GB_W, 1);
        {
            const uint32_t base = sb + wg * 65536 + 4 * t * 128 + (g & 3) * 4, ch = 2 * w + (g >> 2), r7 = (4 * t) & 7;
#pragma unroll
            for (int ks = 0; ks < 32; ks++) {
                const uint32_t w0 = lds32(base + ks * 2048 + ((ch ^ r7) << 4)), w1 = lds32(base + ks * 2048 + 256 + ((ch ^ (r7 + 2)) << 4));
                const uint32_t w2 = lds32(base + ks * 2048 + 128 + ((ch ^ (r7 + 1)) << 4)), w3 = lds32(base + ks * 2048 + 384 + ((ch ^ (r7 + 3)) << 4));
                a[4 * ks] = __byte_perm(w0, w1, 0x5410); a[4 * ks + 1] = __byte_perm(w0, w1, 0x7632);
                a[4 * ks + 2] = __byte_perm(w2, w3, 0x5410); a[4 * ks + 3] = __byte_perm(w2, w3, 0x7632);
            }
        }
        bar_sync(1, 256);
        bar_arrive(6, 288);
#pragma unroll 1
        for (int na = 0, ng = 0; ng < 16;) {
            if (na == ng || (na == ng + 1 && na <= BG_AHEAD)) {
                if (nt < 8) {
                    const int id = nt * 8 + warp;
                    wait_flag(&g_flag[F_QKV + (na * 4 + kq) * 8], 24);
                    bg_attention(sb + G_EX + warp * 4096, 4 * na + (id >> 4), 8 * kq + ((id >> 1) & 7), id & 1, lane);
                    bar_sync(1, 256);
                    if (warp == 7) flag_inc_if(lane, &g_flag[F_OX + (na * 4 + kq) * 8]);
                }
                na++;
            } else {
                bg_mainloop<8, 2>(d, a, sb, 144 + ng * 16 + wg, lane);
                bg_epilogue<false>(d, sb, wg, w, lane, &tm_out, DM + 64 * nt, ng * 128, xa, Dk);
                ng++;
            }
        }
        if (w == 0) asm volatile("cp.async.bulk.wait_group 0;" ::: "memory");
    }
    asm volatile("griddepcontrol.wait;" ::: "memory");
}

typedef CUresult (*EncodeFn)(CUtensorMap*, CUtensorMapDataType, cuuint32_t, void*, const cuuint64_t*, const cuuint64_t*, const cuuint32_t*, const cuuint32_t*,
                             CUtensorMapInterleave, CUtensorMapSwizzle, CUtensorMapL2promotion, CUtensorMapFloatOOBfill);
}

extern "C" void kernel_launch(void* const* d_in, const int* in_sizes, int n_in, void* d_out, int out_size) {
    typedef const __nv_bfloat16* bp;
    bp Ax = (bp)d_in[0], Lre = (bp)d_in[1], Lim = (bp)d_in[2], Bre = (bp)d_in[3], Bim = (bp)d_in[4], Cre = (bp)d_in[5], Cim = (bp)d_in[6],
       logdt = (bp)d_in[7], Dk = (bp)d_in[8], Bx = (bp)d_in[9], mem0 = (bp)d_in[10], Wq = (bp)d_in[11], Wk = (bp)d_in[12], Wv = (bp)d_in[13], Wo = (bp)d_in[14];
    float* out = (float*)d_out;
    static EncodeFn enc = nullptr;
    if (!enc) {
        void* fn = nullptr; cudaDriverEntryPointQueryResult qr;
        cudaGetDriverEntryPoint("cuTensorMapEncodeTiled", &fn, cudaEnableDefault, &qr);
        enc = (EncodeFn)fn;
        cudaFuncSetAttribute(chain_kernel, cudaFuncAttributeMaxDynamicSharedMemorySize, CHAIN_SMEM);
        cudaFuncSetAttribute(bg_kernel, cudaFuncAttributeMaxDynamicSharedMemorySize, BG_SMEM);
    }
    const cuuint32_t es[5] = {1, 1, 1, 1, 1};
    auto map2d = [&](CUtensorMap* tm, CUtensorMapDataType dt, const void* p, cuuint64_t d0, cuuint64_t d1, cuuint64_t stride, cuuint32_t b0, cuuint32_t b1) {
        cuuint64_t gd[2] = {d0, d1}, gs[1] = {stride}; cuuint32_t bd[2] = {b0, b1};
        enc(tm, dt, 2, (void*)p, gd, gs, bd, es, CU_TENSOR_MAP_INTERLEAVE_NONE, CU_TENSOR_MAP_SWIZZLE_128B, CU_TENSOR_MAP_L2_PROMOTION_L2_128B,
            CU_TENSOR_MAP_FLOAT_OOB_FILL_NONE);
    };
    CUtensorMap tm_x, tm_q, tm_k, tm_v, tm_xa, tm_wo, tm_out;
    map2d(&tm_x, CU_TENSOR_MAP_DATA_TYPE_BFLOAT16, Bx, DM, SEQ, DM * 2, 64, 32);
    map2d(&tm_q, CU_TENSOR_MAP_DATA_TYPE_BFLOAT16, Wq, HD, DM, HD * 2, 64, 192);
    map2d(&tm_k, CU_TENSOR_MAP_DATA_TYPE_BFLOAT16, Wk, HD, DM, HD * 2, 64, 192);
    map2d(&tm_v, CU_TENSOR_MAP_DATA_TYPE_BFLOAT16, Wv, HD, DM, HD * 2, 64, 192);
    map2d(&tm_wo, CU_TENSOR_MAP_DATA_TYPE_BFLOAT16, Wo, DM, HD, DM * 2, 64, 256);
    map2d(&tm_out, CU_TENSOR_MAP_DATA_TYPE_FLOAT32, out, 2 * DM, SEQ, 2 * DM * 4, 32, 64);
    {
        cuuint64_t gd[5] = {DM, 2, 4, 16, 16}, gs[4] = {DM * 2, 32 * DM * 2, 2 * DM * 2, 128 * DM * 2}; cuuint32_t bd[5] = {64, 2, 4, 16, 1};
        enc(&tm_xa, CU_TENSOR_MAP_DATA_TYPE_BFLOAT16, 5, (void*)Ax, gd, gs, bd, es, CU_TENSOR_MAP_INTERLEAVE_NONE, CU_TENSOR_MAP_SWIZZLE_128B,
            CU_TENSOR_MAP_L2_PROMOTION_L2_128B, CU_TENSOR_MAP_FLOAT_OOB_FILL_NONE);
    }
    cudaStream_t st = cudaStreamPerThread;
    chain_kernel<<<96, 384, CHAIN_SMEM, st>>>(tm_x, tm_q, tm_k, tm_v, Bx, mem0, Wo, out);
    cudaLaunchConfig_t cfg = {};
    cfg.gridDim = dim3(36); cfg.blockDim = dim3(384); cfg.dynamicSmemBytes = BG_SMEM; cfg.stream = st;
    cudaLaunchAttribute at[1];
    at[0].id = cudaLaunchAttributeProgrammaticStreamSerialization; at[0].val.programmaticStreamSerializationAllowed = 1;
    cfg.attrs = at; cfg.numAttrs = 1;
    cudaLaunchKernelEx(&cfg, bg_kernel, tm_xa, tm_wo, tm_out, Ax, Lre, Lim, Bre, Bim, Cre, Cim, logdt, Dk);
}
```

```cpp
#include <cuda_runtime.h>
#include <cuda.h>
#include <cuda_bf16.h>
#include <cuda_fp16.h>
#include <stdint.h>

#define D_WAIT 700

#define BG_AHEAD 10

namespace {

constexpr int DM = 576, NH = 32, SEQ = 2048, NSEG = 64, HD = 4096;

__device__ uint4 g_acc[64 * 96 * 16];
__device__ uint4 g_ox[NH * 2 * SEQ * 8];
constexpr int REC = 30720;
__device__ uint4 g_qkv[NSEG * NH * (REC / 16)];
__device__ uint4 g_h[18 * SEQ * 8];
constexpr int NFLAG = 2048, F_QKV = 0, F_OX = 512, F_H = 1024;
__device__ unsigned g_flag[NFLAG];
__device__ unsigned g_ticket, g_ticket_bg;
__device__ unsigned long long g_norm[96];
#define BSTAMP(i) do {} while (0)

__device__ __forceinline__ uint32_t smem_u32(const void* p) { return (uint32_t)__cvta_generic_to_shared(p); }
__device__ __forceinline__ uint32_t mapa(uint32_t a, uint32_t r) { uint32_t o; asm("mapa.shared::cluster.u32 %0, %1, %2;" : "=r"(o) : "r"(a), "r"(r)); return o; }
__device__ __forceinline__ uint32_t mapa_v(uint32_t a, uint32_t r) { uint32_t o; asm volatile("mapa.shared::cluster.u32 %0, %1, %2;" : "=r"(o) : "r"(a), "r"(r)); return o; }
__device__ __forceinline__ unsigned clk() { unsigned long long c; asm volatile("mov.u64 %0, %%clock64;" : "=l"(c) :: "memory"); return (unsigned)c; }
__device__ __forceinline__ void mbar_init(uint32_t bar, uint32_t cnt) { asm volatile("mbarrier.init.shared::cta.b64 [%0], %1;" :: "r"(bar), "r"(cnt) : "memory"); }
__device__ __forceinline__ void mbar_expect(uint32_t bar, uint32_t bytes) { asm volatile("mbarrier.arrive.expect_tx.shared::cta.b64 _, [%0], %1;" :: "r"(bar), "r"(bytes) : "memory"); }
__device__ __forceinline__ void mbar_wait(uint32_t bar, uint32_t parity) {
    asm volatile("{\n.reg .pred p;\n.reg .u32 n;\nmov.u32 n, 0;\n"
                 "W_%=: mbarrier.try_wait.parity.shared::cta.b64 p, [%0], %1;\n@p bra.uni D_%=;\n"
                 "add.u32 n, n, 1;\nsetp.lt.u32 p, n, 4000000;\n@p bra.uni W_%=;\ntrap;\nD_%=:\n}" :: "r"(bar), "r"(parity) : "memory");
}
__device__ __forceinline__ void mbar_expect_if(uint32_t z, uint32_t bar, uint32_t bytes) {
    asm volatile("{\n.reg .pred p;\nsetp.eq.u32 p, %2, 0;\n@p mbarrier.arrive.expect_tx.shared::cta.b64 _, [%0], %1;\n}" :: "r"(bar), "r"(bytes), "r"(z) : "memory");
}
__device__ __forceinline__ void mbar_arrive_if(uint32_t z, uint32_t bar) {
    asm volatile("{\n.reg .pred p;\nsetp.eq.u32 p, %1, 0;\n@p mbarrier.arrive.shared::cta.b64 _, [%0];\n}" :: "r"(bar), "r"(z) : "memory");
}
__device__ __forceinline__ void sts32_if(uint32_t z, uint32_t a, uint32_t x) {
    asm volatile("{\n.reg .pred p;\nsetp.eq.u32 p, %2, 0;\n@p st.shared.u32 [%0], %1;\n}" :: "r"(a), "r"(x), "r"(z) : "memory");
}
template <int K> __device__ __forceinline__ void sched_fence(int v) {
    asm volatile("{\n.reg .pred p;\nsetp.ne.s32 p, %0, %1;\n@p bra.uni F_%=;\ntrap;\nF_%=:\n}" :: "r"(v), "n"(1000 + K) : "memory");
}
__device__ __forceinline__ void spin_until(unsigned t0, unsigned d) {
    asm volatile("{\n.reg .pred p;\n.reg .u64 c;\n.reg .u32 lo;\n"
                 "S_%=: mov.u64 c, %%clock64;\ncvt.u32.u64 lo, c;\nsub.u32 lo, lo, %0;\nsetp.lt.u32 p, lo, %1;\n@p bra.uni S_%=;\n}" :: "r"(t0), "r"(d) : "memory");
}
__device__ __forceinline__ void bar_sync(int id, int n) { asm volatile("bar.sync %0, %1;" :: "r"(id), "r"(n) : "memory"); }
__device__ __forceinline__ void bar_sync_sel(int sel, int id) {
    asm volatile("{\n.reg .pred p;\nsetp.eq.u32 p, %0, 0;\n@p bar.sync %1, %3;\n@!p bar.sync %2, %3;\n}" :: "r"(sel), "r"(id), "r"(id + 1), "n"(192) : "memory");
}
__device__ __forceinline__ void bar_arrive(int id, int n) { asm volatile("bar.arrive %0, %1;" :: "r"(id), "r"(n) : "memory"); }
__device__ __forceinline__ void fence_async_smem() { asm volatile("fence.proxy.async.shared::cta;" ::: "memory"); }
__device__ __forceinline__ uint32_t pack_bf16(float lo, float hi) { uint32_t r; asm("cvt.rn.bf16x2.f32 %0, %1, %2;" : "=r"(r) : "f"(hi), "f"(lo)); return r; }
__device__ __forceinline__ uint32_t pack_f16(float lo, float hi) { uint32_t r; asm("cvt.rn.f16x2.f32 %0, %1, %2;" : "=r"(r) : "f"(hi), "f"(lo)); return r; }
__device__ __forceinline__ uint32_t f16x2_to_bf16x2(uint32_t v) { float2 f = __half22float2(*reinterpret_cast<__half2*>(&v)); return pack_bf16(f.x, f.y); }
__device__ __forceinline__ float ex2(float x) { float y; asm("ex2.approx.ftz.f32 %0, %1;" : "=f"(y) : "f"(x)); return y; }
__device__ __forceinline__ float ex2v(float x) { float y; asm volatile("ex2.approx.ftz.f32 %0, %1;" : "=f"(y) : "f"(x)); return y; }
__device__ __forceinline__ uint32_t absmax2(uint32_t a, uint32_t b) {
    uint32_t r; asm("max.xorsign.abs.bf16x2 %0, %1, %2;" : "=r"(r) : "r"(a), "r"(b)); return r;
}
__device__ __forceinline__ uint32_t shl_v(uint32_t a, int n) { return a << n; }
__device__ __forceinline__ uint32_t max3u(uint32_t a, uint32_t b, uint32_t c) { return max(max(a, b), c); }
__device__ __forceinline__ uint4 lds128(uint32_t a) { uint4 v; asm volatile("ld.shared.v4.u32 {%0,%1,%2,%3}, [%4];" : "=r"(v.x), "=r"(v.y), "=r"(v.z), "=r"(v.w) : "r"(a) : "memory"); return v; }
__device__ __forceinline__ uint4 lds128v(uint32_t a) { uint4 v; asm volatile("ld.volatile.shared.v4.u32 {%0,%1,%2,%3}, [%4];" : "=r"(v.x), "=r"(v.y), "=r"(v.z), "=r"(v.w) : "r"(a) : "memory"); return v; }
__device__ __forceinline__ float4 lds128f(uint32_t a) { float4 v; asm volatile("ld.shared.v4.f32 {%0,%1,%2,%3}, [%4];" : "=f"(v.x), "=f"(v.y), "=f"(v.z), "=f"(v.w) : "r"(a) : "memory"); return v; }
__device__ __forceinline__ float2 lds64f(uint32_t a) { float2 v; asm volatile("ld.shared.v2.f32 {%0,%1}, [%2];" : "=f"(v.x), "=f"(v.y) : "r"(a) : "memory"); return v; }
__device__ __forceinline__ uint4 lds64x2(uint32_t a) { uint4 v; asm volatile("ld.shared.v2.u32 {%0,%1}, [%4];\nld.shared.v2.u32 {%2,%3}, [%4+256];" : "=r"(v.x), "=r"(v.y), "=r"(v.z), "=r"(v.w) : "r"(a) : "memory"); return v; }
__device__ __forceinline__ uint32_t lds32(uint32_t a) { uint32_t v; asm volatile("ld.shared.u32 %0, [%1];" : "=r"(v) : "r"(a) : "memory"); return v; }
__device__ __forceinline__ void sts128(uint32_t a, uint32_t x, uint32_t y, uint32_t z, uint32_t w) { asm volatile("st.shared.v4.u32 [%0], {%1,%2,%3,%4};" :: "r"(a), "r"(x), "r"(y), "r"(z), "r"(w) : "memory"); }
__device__ __forceinline__ void sts128f(uint32_t a, float x, float y, float z, float w) { asm volatile("st.shared.v4.f32 [%0], {%1,%2,%3,%4};" :: "r"(a), "f"(x), "f"(y), "f"(z), "f"(w) : "memory"); }
__device__ __forceinline__ void sts64(uint32_t a, uint32_t x, uint32_t y) { asm volatile("st.shared.v2.u32 [%0], {%1,%2};" :: "r"(a), "r"(x), "r"(y) : "memory"); }
__device__ __forceinline__ void sts32(uint32_t a, uint32_t x) { asm volatile("st.shared.u32 [%0], %1;" :: "r"(a), "r"(x) : "memory"); }
__device__ __forceinline__ uint4 ldsm4(uint32_t a) { uint4 v; asm volatile("ldmatrix.sync.aligned.m8n8.x4.shared.b16 {%0,%1,%2,%3}, [%4];" : "=r"(v.x), "=r"(v.y), "=r"(v.z), "=r"(v.w) : "r"(a) : "memory"); return v; }
__device__ __forceinline__ void stsm2t(uint32_t a, uint32_t x, uint32_t y) { asm volatile("stmatrix.sync.aligned.m8n8.x2.trans.shared.b16 [%0], {%1,%2};" :: "r"(a), "r"(x), "r"(y) : "memory"); }
__device__ __forceinline__ void stsm4t(uint32_t a, uint32_t x, uint32_t y, uint32_t z, uint32_t w) { asm volatile("stmatrix.sync.aligned.m8n8.x4.trans.shared.b16 [%0], {%1,%2,%3,%4};" :: "r"(a), "r"(x), "r"(y), "r"(z), "r"(w) : "memory"); }
__device__ __forceinline__ void st_async64(uint32_t a, uint32_t x, uint32_t y, uint32_t bar) { asm volatile("st.async.shared::cluster.mbarrier::complete_tx::bytes.v2.b32 [%0], {%1,%2}, [%3];" :: "r"(a), "r"(x), "r"(y), "r"(bar) : "memory"); }
__device__ __forceinline__ void bulk_s2c(uint32_t dst, uint32_t src, uint32_t bytes, uint32_t bar) { asm volatile("cp.async.bulk.shared::cluster.shared::cta.mbarrier::complete_tx::bytes [%0], [%1], %2, [%3];" :: "r"(dst), "r"(src), "r"(bytes), "r"(bar) : "memory"); }
__device__ __forceinline__ void bulk_s2g(void* dst, uint32_t src, uint32_t bytes) { asm volatile("cp.async.bulk.global.shared::cta.bulk_group [%0], [%1], %2;" :: "l"(dst), "r"(src), "r"(bytes) : "memory"); }
__device__ __forceinline__ uint32_t ldg_nc32(const void* p) { uint32_t v; asm volatile("ld.global.nc.L2::128B.u32 %0, [%1];" : "=r"(v) : "l"(p)); return v; }
__device__ __forceinline__ uint4 ldg_relaxed128(const void* p) { uint4 v; asm volatile("ld.relaxed.gpu.global.v4.u32 {%0,%1,%2,%3}, [%4];" : "=r"(v.x), "=r"(v.y), "=r"(v.z), "=r"(v.w) : "l"(p) : "memory"); return v; }
__device__ __forceinline__ void mma16816(float (&d)[4], uint32_t a0, uint32_t a1, uint32_t a2, uint32_t a3, uint32_t b0, uint32_t b1) {
    asm volatile("mma.sync.aligned.m16n8k16.row.col.f32.bf16.bf16.f32 {%0,%1,%2,%3}, {%4,%5,%6,%7}, {%8,%9}, {%0,%1,%2,%3};"
        : "+f"(d[0]), "+f"(d[1]), "+f"(d[2]), "+f"(d[3]) : "r"(a0), "r"(a1), "r"(a2), "r"(a3), "r"(b0), "r"(b1));
}
__device__ __forceinline__ void mma16816_z(float (&d)[4], uint32_t a0, uint32_t a1, uint32_t a2, uint32_t a3, uint32_t b0, uint32_t b1) {
    asm volatile("mma.sync.aligned.m16n8k16.row.col.f32.bf16.bf16.f32 {%0,%1,%2,%3}, {%4,%5,%6,%7}, {%8,%9}, {%10,%10,%10,%10};"
        : "=f"(d[0]), "=f"(d[1]), "=f"(d[2]), "=f"(d[3]) : "r"(a0), "r"(a1), "r"(a2), "r"(a3), "r"(b0), "r"(b1), "f"(0.f));
}
__device__ __forceinline__ void mma1688(float (&d)[4], uint32_t a0, uint32_t a1, uint32_t b0) {
    asm volatile("mma.sync.aligned.m16n8k8.row.col.f32.bf16.bf16.f32 {%0,%1,%2,%3}, {%4,%5}, {%6}, {%0,%1,%2,%3};"
        : "+f"(d[0]), "+f"(d[1]), "+f"(d[2]), "+f"(d[3]) : "r"(a0), "r"(a1), "r"(b0));
}
__device__ __forceinline__ void mma1688_z(float (&d)[4], uint32_t a0, uint32_t a1, uint32_t b0) {
    asm volatile("mma.sync.aligned.m16n8k8.row.col.f32.bf16.bf16.f32 {%0,%1,%2,%3}, {%4,%5}, {%6}, {%7,%7,%7,%7};"
        : "=f"(d[0]), "=f"(d[1]), "=f"(d[2]), "=f"(d[3]) : "r"(a0), "r"(a1), "r"(b0), "f"(0.f));
}
template <int ACC>
__device__ __forceinline__ void wgmma_n32_rs(float (&d)[16], uint32_t a0, uint32_t a1, uint32_t a2, uint32_t a3, uint64_t desc) {
    asm volatile("wgmma.mma_async.sync.aligned.m64n32k16.f32.bf16.bf16 {%0,%1,%2,%3,%4,%5,%6,%7,%8,%9,%10,%11,%12,%13,%14,%15}, {%16,%17,%18,%19}, %20, %21, 1, 1, 0;"
        : "+f"(d[0]), "+f"(d[1]), "+f"(d[2]), "+f"(d[3]), "+f"(d[4]), "+f"(d[5]), "+f"(d[6]), "+f"(d[7]),
          "+f"(d[8]), "+f"(d[9]), "+f"(d[10]), "+f"(d[11]), "+f"(d[12]), "+f"(d[13]), "+f"(d[14]), "+f"(d[15])
        : "r"(a0), "r"(a1), "r"(a2), "r"(a3), "l"(desc), "n"(ACC));
}
template <int ACC>
__device__ __forceinline__ void wgmma_n32_ss(float (&d)[16], uint64_t da, uint64_t db) {
    asm volatile("wgmma.mma_async.sync.aligned.m64n32k16.f32.bf16.bf16 {%0,%1,%2,%3,%4,%5,%6,%7,%8,%9,%10,%11,%12,%13,%14,%15}, %16, %17, %18, 1, 1, 0, 0;"
        : "+f"(d[0]), "+f"(d[1]), "+f"(d[2]), "+f"(d[3]), "+f"(d[4]), "+f"(d[5]), "+f"(d[6]), "+f"(d[7]),
          "+f"(d[8]), "+f"(d[9]), "+f"(d[10]), "+f"(d[11]), "+f"(d[12]), "+f"(d[13]), "+f"(d[14]), "+f"(d[15])
        : "l"(da), "l"(db), "n"(ACC));
}
__device__ __forceinline__ void wg_fence() { asm volatile("wgmma.fence.sync.aligned;" ::: "memory"); }
__device__ __forceinline__ void wg_commit() { asm volatile("wgmma.commit_group.sync.aligned;" ::: "memory"); }
__device__ __forceinline__ void wg_wait0() { asm volatile("wgmma.wait_group.sync.aligned 0;" ::: "memory"); }
__device__ __forceinline__ void cluster_sync() { asm volatile("barrier.cluster.arrive.aligned;\nbarrier.cluster.wait.aligned;" ::: "memory"); }

#define STAMP(s, i) do {} while (0)
#define STAMPV(s, i, v) do {} while (0)

constexpr int XT_BYTES = 36864;
constexpr int O_XT = 0;
constexpr int O_STG = XT_BYTES;
constexpr int O_AS = 3 * XT_BYTES;
constexpr int O_XP = O_AS + 16384;
constexpr int O_QKX = O_XP + 8192;
constexpr int O_KM = O_QKX + 8192;
constexpr int O_QM = O_QKX + 10240;
constexpr int O_VX = O_STG + 147456;
constexpr int O_VM = O_VX + 16384;
constexpr int O_SC = O_VM + 2048;
constexpr int O_OF = O_SC + 2560;
constexpr int O_AF = O_OF + 2048;
constexpr int O_WP = O_AF + 4096;
constexpr int O_MF = O_WP + 2048;
constexpr int O_MISC = O_MF + 9216;
static_assert(O_QKX + 24576 <= O_VX, "smem");
constexpr int O_BAR = O_MISC + 64;
constexpr int CHAIN_SMEM = O_BAR + 128;
static_assert(CHAIN_SMEM <= 232448, "smem");
constexpr int B_X = O_BAR, B_VX = O_BAR + 24, B_SC = O_BAR + 40, B_W = O_BAR + 48;
constexpr float SM_SCALE = 0.08838834764831845f * 1.4426950408889634f;
constexpr uint32_t ONES = 0x3f803f80u;

__device__ __forceinline__ uint32_t opaque(uint32_t v) { uint32_t o; asm volatile("mov.u32 %0, %1;" : "=r"(o) : "r"(v)); return o; }
__device__ __forceinline__ void st_async128(uint32_t a, uint32_t x, uint32_t y, uint32_t z, uint32_t w, uint32_t bar) {
    asm volatile("st.async.shared::cluster.mbarrier::complete_tx::bytes.v4.b32 [%0], {%1,%2,%3,%4}, [%5];" :: "r"(a), "r"(x), "r"(y), "r"(z), "r"(w), "r"(bar) : "memory");
}
__device__ __forceinline__ void tma_x_tile(uint32_t sb, const CUtensorMap* tm, int r, int j, int slot) {
    asm volatile("{\n.reg .pred p;\nelect.sync _|p, 0xffffffff;\n"
        "@p mbarrier.arrive.expect_tx.shared::cta.b64 _, [%2], 36864;\n"
        "@p cp.async.bulk.tensor.2d.shared::cluster.global.mbarrier::complete_tx::bytes.multicast::cluster [%0], [%1, {%3, %4}], [%2], %7;\n"
        "@p cp.async.bulk.tensor.2d.shared::cluster.global.mbarrier::complete_tx::bytes.multicast::cluster [%0+4096], [%1, {%5, %4}], [%2], %7;\n"
        "@p cp.async.bulk.tensor.2d.shared::cluster.global.mbarrier::complete_tx::bytes.multicast::cluster [%0+8192], [%1, {%6, %4}], [%2], %7;\n}"
        :: "r"(sb + O_XT + slot * XT_BYTES + 3 * r * 4096), "l"(tm), "r"(sb + B_X + 8 * slot), "r"(192 * r), "r"(j * 32), "r"(192 * r + 64), "r"(192 * r + 128),
           "h"((unsigned short)7) : "memory");
}
__device__ __forceinline__ float quad_max(float v) {
    const float a = __shfl_xor_sync(~0u, v, 1), b = __shfl_xor_sync(~0u, v, 2), c = __shfl_xor_sync(~0u, v, 3);
    return fmaxf(fmaxf(v, a), fmaxf(b, c));
}
__device__ __forceinline__ void load_scores(float (&p)[10], uint32_t base, uint32_t stride, uint32_t l16) {
    const float4 a0 = lds128f(base + l16), b0 = lds128f(base + stride + l16);
    const float4 a1 = lds128f(base + 512 + l16), b1 = lds128f(base + stride + 512 + l16);
    const float2 a2 = lds64f(base + 1024 + (l16 >> 1)), b2 = lds64f(base + stride + 1024 + (l16 >> 1));
    p[0] = a2.x + b2.x; p[1] = a2.y + b2.y;
    p[2] = a0.x + b0.x; p[3] = a0.y + b0.y; p[4] = a0.z + b0.z; p[5] = a0.w + b0.w;
    p[6] = a1.x + b1.x; p[7] = a1.y + b1.y; p[8] = a1.z + b1.z; p[9] = a1.w + b1.w;
}
__device__ __forceinline__ float rcp_fast(float x) { float y; asm("rcp.approx.ftz.f32 %0, %1;" : "=f"(y) : "f"(x)); return y; }

__global__ void __cluster_dims__(3, 1, 1) __launch_bounds__(384, 1)
chain_kernel(const __grid_constant__ CUtensorMap tm_x, const __grid_constant__ CUtensorMap tm_q,
             const __grid_constant__ CUtensorMap tm_k, const __grid_constant__ CUtensorMap tm_v,
             const __nv_bfloat16* __restrict__ x, const __nv_bfloat16* __restrict__ mem0,
             const __nv_bfloat16* __restrict__ Wo, float* __restrict__ out) {
    extern __shared__ __align__(1024) uint8_t smem_raw[];
    const uint32_t sb = smem_u32(smem_raw);
    const int lane = threadIdx.x & 31;
    const int warp = __shfl_sync(~0u, threadIdx.x >> 5, 0);
    const int wg = warp >> 2, w = warp & 3;
    const int h = blockIdx.x / 3, r = blockIdx.x - 3 * h;

#define PSTAMP(i) do {} while (0)
    if (threadIdx.x == 0) {
        if (sb & 1023u) __trap();
        for (int i = 0; i < 9; i++) mbar_init(sb + O_BAR + 8 * i, 1);
        asm volatile("fence.mbarrier_init.release.cluster;" ::: "memory");
        for (int i = 0; i < 3; i++) {
            mbar_expect(sb + B_W + 8 * i, 49152);
            for (int tl = 0; tl < 2; tl++)
                asm volatile("cp.async.bulk.tensor.2d.shared::cluster.global.mbarrier::complete_tx::bytes [%0], [%1, {%3, %4}], [%2];"
                    :: "r"(sb + O_STG + tl * 73728 + i * 24576), "l"(r < 2 ? (tl ? &tm_k : &tm_q) : &tm_v), "r"(sb + B_W + 8 * i),
                       "r"(h * 128 + 64 * (r < 2 ? r : tl)), "r"(192 * i) : "memory");
        }
    }
    __syncwarp();
    asm volatile("barrier.cluster.arrive.relaxed.aligned;" ::: "memory");
    asm volatile("griddepcontrol.launch_dependents;" ::: "memory");
    if (warp == 0) PSTAMP(9);
    const uint32_t l16c = __shfl_sync(~0u, lane * 16, lane);

    if (wg < 2) {
#define KS(u) ((u) < 8 ? ((u) >> 1) + 4 * ((u) & 1) : (u) < 12 ? (u) : (u) < 20 ? 12 + (((u) - 12) >> 1) + 4 * ((u) & 1) : (u) < 24 ? (u) : (u) + 8)
        asm volatile("setmaxnreg.inc.sync.aligned.u32 184;");
        uint32_t a[144];
        uint32_t adr1;
        {
            const int g = lane >> 2, t = lane & 3;
            const int t1 = threadIdx.x;
#pragma unroll
            for (int i = 0; i < 2; i++) g_acc[(blockIdx.x * 64 + i * 32 + (t1 >> 3)) * 16 + (t1 & 7)] = make_uint4(0, 0, 0, 0);
#pragma unroll
            for (int i = 0; i < 12; i++) {
                const int idx = blockIdx.x * 3072 + i * 256 + t1, row = idx / 144;
                reinterpret_cast<float4*>(out)[row * 288 + 144 + (idx - row * 144)] = make_float4(0.f, 0.f, 0.f, 0.f);
            }
            __threadfence();
            asm volatile("barrier.cluster.wait.aligned;" ::: "memory");
            const uint32_t ev = sb + O_STG + (2 * t) * 128 + (((2 * w + (g >> 2)) ^ (2 * t)) << 4) + (g & 3) * 4;
            const uint32_t od = (ev ^ 16) + 128;
            auto gather = [&](int dst, uint32_t off) {
                a[dst] = lds32(ev + off); a[dst + 1] = lds32(od + off); a[dst + 2] = lds32(ev + off + 1024); a[dst + 3] = lds32(od + off + 1024);
            };
            mbar_wait(sb + B_W, 0);
#pragma unroll
            for (int u = 8; u < 12; u++) gather(32 + 4 * u, wg * 73728 + KS(u) * 2048);
            mbar_wait(sb + B_W + 8, 0);
            const uint4* xp = reinterpret_cast<const uint4*>(x) + blockIdx.x * 1536 + t1;
            uint4 xv[6];
#pragma unroll
            for (int i = 0; i < 6; i++) xv[i] = __ldg(xp + i * 256);
#pragma unroll
            for (int u = 12; u < 24; u++) gather(32 + 4 * u, wg * 73728 + KS(u) * 2048);
            mbar_wait(sb + B_W + 16, 0);
#pragma unroll
            for (int u = 24; u < 28; u++) gather(32 + 4 * u, wg * 73728 + KS(u) * 2048);
#pragma unroll
            for (int u = 0; u < 8; u++) {
                gather(32 + 4 * u, wg * (73728 + 49152) + KS(u) * 2048);
                gather(4 * u, 73728 - wg * (73728 - 49152) + KS(u) * 2048);
            }
#pragma unroll
            for (int kk = 0; kk < 72; kk++) {
                uint32_t w0 = a[2 * kk], w1 = a[2 * kk + 1];
                a[2 * kk] = __byte_perm(w0, w1, 0x5410);
                a[2 * kk + 1] = __byte_perm(w0, w1, 0x7632);
            }
            if (r == 2) {
                float n0[4], n1[4];
#pragma unroll
                for (int u = 0; u < 36; u++) {
                    const uint32_t x0 = a[4 * u] & 0x7fff7fffu, x1 = a[4 * u + 1] & 0x7fff7fffu, x2 = a[4 * u + 2] & 0x7fff7fffu, x3 = a[4 * u + 3] & 0x7fff7fffu;
                    if (u == 0) mma16816_z(n0, x0, x1, x2, x3, ONES, ONES);
                    else if (u < 8) mma16816(n0, x0, x1, x2, x3, ONES, ONES);
                    else if (u == 8) mma16816_z(n1, x0, x1, x2, x3, ONES, ONES);
                    else mma16816(n1, x0, x1, x2, x3, ONES, ONES);
                }
                const uint32_t mx = __reduce_max_sync(~0u, __float_as_uint(2.f * fmaxf(fmaxf(n0[0], n0[2]), fmaxf(n1[0], n1[2]))));
                sts32_if(lane, sb + O_MISC + 32 + 4 * warp, mx);
            }
            uint32_t xm = 0;
#pragma unroll
            for (int i = 0; i < 6; i++)
                xm = __vmaxu2(xm, __vmaxu2(__vmaxu2(xv[i].x & 0x7fff7fffu, xv[i].y & 0x7fff7fffu), __vmaxu2(xv[i].z & 0x7fff7fffu, xv[i].w & 0x7fff7fffu)));
            sts32_if(lane, sb + O_OF + 16 + 4 * warp, __reduce_max_sync(~0u, max(xm << 16, xm & 0xffff0000u)));
            if (warp == 0) PSTAMP(11);
            bar_arrive(7, 384);
            asm volatile("barrier.cluster.arrive.relaxed.aligned;" ::: "memory");
            bar_sync(1, 256);
            const uint32_t as = sb + O_AS + wg * 8192 + (16 * w + g) * 128 + t * 4;
            sts32(as + (g << 4), a[32]);
            sts32(as + 1024 + (g << 4), a[33]);
            sts32(as + ((1 ^ g) << 4), a[34]);
            sts32(as + 1024 + ((1 ^ g) << 4), a[35]);
            sts128(sb + O_AF + warp * 512 + lane * 16, a[32], a[33], a[34], a[35]);
            fence_async_smem();
            bar_sync(1, 256);
            const uint32_t l = lane * 16;
            const int mi = lane >> 3, isk = (mi >> 1) ? wg : (wg ^ 1);
            adr1 = (r == 2) ? (sb + O_VM + warp * 256 + (l >> 1))
                            : (isk ? (sb + O_KM + w * 512 + wg * 256 + (mi & 1) * 128 + (l & 127))
                                   : (sb + O_QM + w * 512 + (mi & 1) * 256 + wg * 128 + (l & 127)));
            adr1 = __shfl_sync(~0u, adr1, lane);
        }
        int s3 = 2;
#pragma unroll 1
        for (int s = -1; s < NSEG; s++) {
            const uint32_t l16 = opaque(l16c);
            s3 = (s3 == 2) ? 0 : s3 + 1;
            if (s < 0) mbar_wait(sb + B_X, 0);
            const uint64_t desc0 = (uint64_t)(((sb + O_XT + s3 * XT_BYTES) & 0x3FFFF) >> 4) | (1ull << 16) | (64ull << 32) | (1ull << 62);
            uint32_t km0 = 0, km1 = 0;
            if (s >= 0) {
                { const uint4 v = lds128(sb + O_AF + warp * 512 + l16); a[32] = v.x; a[33] = v.y; a[34] = v.z; a[35] = v.w; }
                float co[4], cw[3][4];
                uint4 b[14];
                float inv;
#define GORD(i) ((i) == 0 ? 0 : (i) == 1 ? 1 : (i) == 5 ? 2 : (i) == 9 ? 3 : (i) < 5 ? (i) + 2 : (i) < 9 ? (i) + 1 : (i))
                auto qkv_mma = [&](int i) {
                    const int gi = GORD(i), u = 8 * gi, n0 = 2 * i, n1 = 2 * i + 1;
                    if (gi < 4) {
                        if (i == 0) mma16816_z(co, a[u], a[u + 1], a[u + 2], a[u + 3], b[0].x, b[0].y);
                        else mma16816(co, a[u], a[u + 1], a[u + 2], a[u + 3], b[i].x, b[i].y);
                    }
                    if (n0 < 3) mma16816_z(cw[n0 % 3], a[32 + u], a[32 + u + 1], a[32 + u + 2], a[32 + u + 3], b[i].x, b[i].y);
                    else mma16816(cw[n0 % 3], a[32 + u], a[32 + u + 1], a[32 + u + 2], a[32 + u + 3], b[i].x, b[i].y);
                    if (n1 < 3) mma16816_z(cw[n1 % 3], a[32 + u + 4], a[32 + u + 5], a[32 + u + 6], a[32 + u + 7], b[i].z, b[i].w);
                    else mma16816(cw[n1 % 3], a[32 + u + 4], a[32 + u + 5], a[32 + u + 6], a[32 + u + 7], b[i].z, b[i].w);
                    if (gi < 4) mma16816(co, a[u + 4], a[u + 5], a[u + 6], a[u + 7], b[i].z, b[i].w);
                };
                const uint32_t mf = sb + O_MF + l16, mfs = mf + wg * 6144;
                const uint32_t qb = (s & 1) * 12288;
                bar_sync(2, 384);
                if (warp == 0) STAMP(s, 0);
                auto qkv_ld = [&](int i) { b[i] = GORD(i) < 4 ? lds128v(mfs + GORD(i) * 512) : lds128v(mf + (GORD(i) < 12 ? GORD(i) : GORD(i) + 4) * 512); };
#pragma unroll
                for (int i = 0; i < 5; i++) qkv_ld(i);
#pragma unroll
                for (int i = 0; i < 4; i++) { qkv_mma(i); qkv_ld(5 + i); }
#pragma unroll
                for (int i = 4; i < 9; i++) { qkv_mma(i); qkv_ld(5 + i); }
                inv = __uint_as_float(lds32(sb + O_MISC));
#pragma unroll
                for (int i = 9; i < 14; i++) qkv_mma(i);
#pragma unroll
                for (int i = 0; i < 4; i++) cw[0][i] += cw[1][i] + cw[2][i];
                if (r < 2) {
                    const uint32_t o0 = pack_bf16(co[0] * inv, co[1] * inv), o1 = pack_bf16(co[2] * inv, co[3] * inv);
                    const uint32_t w0 = pack_bf16(cw[0][0] * inv, cw[0][1] * inv), w1 = pack_bf16(cw[0][2] * inv, cw[0][3] * inv);
                    stsm4t(adr1 + qb, o0, o1, w0, w1);
                    if (warp == 0) STAMP(s, 1);
                    asm volatile("{\n.reg .pred p;\nsetp.ge.u32 p, %0, 3;\n@p bar.arrive 1, 256;\n}" :: "r"(warp) : "memory");
                    if (warp < 3 && s < NSEG - 1) {
                        uint4 q[4], k[4];
                        const uint32_t ka = sb + O_QKX + 4096 + qb + warp * 2048 + l16;
#pragma unroll
                        for (int i = 0; i < 4; i++) k[i] = ldsm4(ka + i * 512);
                        const uint32_t dst = sb + O_SC + r * 1280 + warp * 512 + (l16 >> 1);
                        bar_sync(1, 256);
#pragma unroll
                        for (int i = 0; i < 4; i++) q[i] = ldsm4(sb + O_QM + qb + i * 512 + l16);
                        if (warp == 2) {
#pragma unroll
                            for (int i = 0; i < 4; i++) k[i] = ldsm4(ka + i * 512);
                        }
                        float s0[4], s1[4], t0[4], t1[4];
                        mma16816_z(s0, q[0].x, q[0].y, q[0].z, q[0].w, k[0].x, k[0].y);
                        mma16816_z(s1, q[0].x, q[0].y, q[0].z, q[0].w, k[0].z, k[0].w);
                        mma16816_z(t0, q[1].x, q[1].y, q[1].z, q[1].w, k[1].x, k[1].y);
                        mma16816_z(t1, q[1].x, q[1].y, q[1].z, q[1].w, k[1].z, k[1].w);
                        mma16816(s0, q[2].x, q[2].y, q[2].z, q[2].w, k[2].x, k[2].y);
                        mma16816(s1, q[2].x, q[2].y, q[2].z, q[2].w, k[2].z, k[2].w);
                        mma16816(t0, q[3].x, q[3].y, q[3].z, q[3].w, k[3].x, k[3].y);
                        mma16816(t1, q[3].x, q[3].y, q[3].z, q[3].w, k[3].z, k[3].w);
                        const float v0 = (s0[0] + s0[2]) + (t0[0] + t0[2]), v1 = (s0[1] + s0[3]) + (t0[1] + t0[3]);
                        const float v2 = (s1[0] + s1[2]) + (t1[0] + t1[2]), v3 = (s1[1] + s1[3]) + (t1[1] + t1[3]);
                        if (warp < 2) {
                            const uint32_t dv = dst + (l16 >> 1);
                            st_async128(mapa(dv, 2), __float_as_uint(v0), __float_as_uint(v1), __float_as_uint(v2), __float_as_uint(v3), mapa(sb + B_SC, 2));
                            st_async128(mapa(dv, r ^ 1), __float_as_uint(v0), __float_as_uint(v1), __float_as_uint(v2), __float_as_uint(v3), mapa(sb + B_SC, r ^ 1));
                            st_async128(mapa(dv, r), __float_as_uint(v0), __float_as_uint(v1), __float_as_uint(v2), __float_as_uint(v3), mapa(sb + B_SC, r));
                        } else {
                            st_async64(mapa(dst, 2), __float_as_uint(v0 + v2), __float_as_uint(v1 + v3), mapa(sb + B_SC, 2));
                            st_async64(mapa(dst, r ^ 1), __float_as_uint(v0 + v2), __float_as_uint(v1 + v3), mapa(sb + B_SC, r ^ 1));
                            st_async64(mapa(dst, r), __float_as_uint(v0 + v2), __float_as_uint(v1 + v3), mapa(sb + B_SC, r));
                        }
                        if (warp == 2) STAMP(s, 2);
                    } else if (warp < 3) {
                        bar_sync(1, 256);
                    }
                } else {
                    sts128f(sb + O_XP + warp * 512 + l16, co[0], co[1], co[2], co[3]);
                    bar_sync(8 + w, 64);
                    const float4 o = lds128f(sb + O_XP + (warp ^ 4) * 512 + l16);
                    km0 = pack_bf16((cw[0][0] + o.x) * inv, (cw[0][1] + o.y) * inv);
                    km1 = pack_bf16((cw[0][2] + o.z) * inv, (cw[0][3] + o.w) * inv);
                    if (warp == 0) STAMP(s, 1);
                    if (s < NSEG - 1) {
                        st_async64(mapa(adr1, 0), km0, km1, mapa(sb + B_SC, 0));
                        st_async64(mapa(adr1, 1), km0, km1, mapa(sb + B_SC, 1));
                        st_async64(mapa(adr1, 2), km0, km1, mapa(sb + B_SC, 2));
                    }
                    if (warp == 0) STAMP(s, 2);
                }
            }
            char* rec = reinterpret_cast<char*>(g_qkv) + (size_t)(s * NH + h) * REC;
            auto store_qk = [&]() {
                asm volatile("{\n.reg .pred p;\nelect.sync _|p, 0xffffffff;\n"
                    "@p cp.async.bulk.global.shared::cta.bulk_group [%0], [%1], 10240;\n@p cp.async.bulk.commit_group;\n}"
                    :: "l"(rec + r * 10240), "r"(sb + O_QKX + (s & 1) * 12288) : "memory");
            };
            auto store_vm = [&]() { *reinterpret_cast<uint2*>(rec + 28672 + warp * 256 + (l16 >> 1)) = make_uint2(km0, km1); };
            if (s == NSEG - 1) fence_async_smem();
            if (s >= 0) bar_sync(3, 384);
            if (s == NSEG - 1) {
                if (r == 2) store_vm();
                else if (warp == 3) {
                    store_qk();
                    asm volatile("cp.async.bulk.wait_group 0;\nfence.proxy.async.global;" ::: "memory");
                }
            } else {
                const int j = s + 1;
#define XDESC(u) (((u) < 8 ? descs : desc0) + (uint64_t)(((KS(u) >> 2) * 4096 + (KS(u) & 3) * 32) >> 4))
                const uint64_t descs = desc0 + (uint64_t)(wg * (6 * 4096 >> 4));
                float d[16];
                wg_fence();
#pragma unroll
                for (int u = 0; u < 8; u++) {
                    if (u == 0) wgmma_n32_rs<0>(d, a[0], a[1], a[2], a[3], XDESC(0));
                    else wgmma_n32_rs<1>(d, a[4 * u], a[4 * u + 1], a[4 * u + 2], a[4 * u + 3], XDESC(u));
                }
                wg_commit();
                wg_wait0();
                if (warp == 0) STAMP(s, 15);
                if (s >= 0) bar_sync(4, 384);
#pragma unroll
                for (int q = 0; q < 2; q++)
                    sts128(sb + O_XP + warp * 1024 + q * 512 + l16, pack_bf16(d[8 * q], d[8 * q + 1]), pack_bf16(d[8 * q + 2], d[8 * q + 3]),
                           pack_bf16(d[8 * q + 4], d[8 * q + 5]), pack_bf16(d[8 * q + 6], d[8 * q + 7]));
                if (s >= 0) {
                    if (r == 2) store_vm();
                    else fence_async_smem();
                    if (warp == 3) asm volatile("cp.async.bulk.wait_group 0;\nfence.proxy.async.global;" ::: "memory");
                    if (warp == 1 && s + 2 < NSEG) tma_x_tile(sb, &tm_x, r, s + 2, s3 == 2 ? 0 : s3 + 1);
                }
                bar_sync(12, 256);
#pragma unroll
                for (int q = 0; q < 2; q++) {
                    const uint4 o = lds128(sb + O_XP + (warp ^ 4) * 1024 + q * 512 + l16);
                    d[8 * q] = __uint_as_float(o.x << 16); d[8 * q + 1] = __uint_as_float(o.x & 0xffff0000u);
                    d[8 * q + 2] = __uint_as_float(o.y << 16); d[8 * q + 3] = __uint_as_float(o.y & 0xffff0000u);
                    d[8 * q + 4] = __uint_as_float(o.z << 16); d[8 * q + 5] = __uint_as_float(o.z & 0xffff0000u);
                    d[8 * q + 6] = __uint_as_float(o.w << 16); d[8 * q + 7] = __uint_as_float(o.w & 0xffff0000u);
                }
                if (s >= 0) {
                    if (warp == 6 && (s & 3) == 0 && s >= 4)
                        asm volatile("{\n.reg .pred p;\nsetp.eq.u32 p, %1, 0;\n@p red.release.gpu.global.inc.u32 [%0], 0xffffffff;\n}"
                                     :: "l"(&g_flag[F_QKV + (s - 4 + (h >> 3)) * 8]), "r"(l16) : "memory");
                    asm volatile("{\n.reg .pred p;\nsetp.eq.u32 p, %0, 0;\n@p bar.sync 5, 256;\n@!p bar.sync 13, 256;\n}" :: "r"(wg) : "memory");
                }
                const uint64_t da0 = (uint64_t)(((sb + O_AS + wg * 8192) & 0x3FFFF) >> 4) | (1ull << 16) | (64ull << 32) | (1ull << 62);
                wg_fence();
                wgmma_n32_ss<1>(d, da0, XDESC(0));
#pragma unroll
                for (int u = 1; u < 28; u++) wgmma_n32_rs<1>(d, a[32 + 4 * u], a[32 + 4 * u + 1], a[32 + 4 * u + 2], a[32 + 4 * u + 3], XDESC(u));
                wg_commit();
                wg_wait0();
                if (warp == 3 && r < 2 && s >= 0) store_qk();
                if (warp == 4) STAMP(s, 3);
                uint32_t e[8];
#pragma unroll
                for (int i = 0; i < 8; i++) e[i] = pack_bf16(d[2 * i], d[2 * i + 1]);
                if (r < 2) {
                    const uint32_t base = sb + O_QKX + (j & 1) * 12288 + wg * 4096 + w * 512 + l16;
                    stsm4t(base, e[0], wg ? e[1] : e[2], wg ? e[2] : e[1], e[3]);
                    stsm4t(base + 2048, e[4], wg ? e[5] : e[6], wg ? e[6] : e[5], e[7]);
                } else {
                    const uint32_t base = sb + O_VX + (j & 1) * 8192 + warp * 1024 + l16;
                    sts128(base, e[0], e[1], e[2], e[3]);
                    sts128(base + 512, e[4], e[5], e[6], e[7]);
                    fence_async_smem();
                    bar_arrive(14, 288);
                }
                if (warp == 7) STAMP(s, 4);
                if (s < 0) asm volatile("barrier.cluster.wait.aligned;" ::: "memory");
            }
        }
        bar_arrive(7, 384);
    } else {
        asm volatile("setmaxnreg.dec.sync.aligned.u32 136;");
        const int c = w;
        uint32_t a[96];
        uint32_t mmax = 0;
        {
            const int g = lane >> 2, t = lane & 3;
            uint32_t tag = 0, m0v[18];
            if (threadIdx.x == 256) tag = atomicAdd(&g_ticket, 1u);
#pragma unroll
            for (int i = 0; i < 9; i++) {
                const uint32_t* p = reinterpret_cast<const uint32_t*>(mem0 + g * DM + 16 * (4 * i + c) + 2 * t);
                m0v[2 * i] = __ldg(p); m0v[2 * i + 1] = __ldg(p + 4);
            }
            asm volatile("barrier.cluster.wait.aligned;" ::: "memory");
            if (c == 0) {
                tma_x_tile(sb, &tm_x, r, 0, 0);
                mbar_expect_if(lane, sb + B_SC, 4608);
                if (r < 2) mbar_expect_if(lane, sb + B_VX, 8192);
                sts32_if(lane, sb + O_MISC, __float_as_uint(1.0f));
                sts32_if(lane, sb + O_MISC + 12, __float_as_uint(SM_SCALE));
            }
            asm volatile("barrier.cluster.arrive.relaxed.aligned;" ::: "memory");
#pragma unroll
            for (int tau = 0; tau < 3; tau++) {
                const uint32_t* v = m0v + 6 * tau;
                sts128(sb + O_MF + tau * 3072 + c * 512 + lane * 16, v[0], v[1], v[2], v[3]);
                sts64(sb + O_MF + tau * 3072 + 2048 + (c >> 1) * 512 + lane * 16 + (c & 1) * 8, v[4], v[5]);
#pragma unroll
                for (int i = 0; i < 6; i++) mmax = __vmaxu2(mmax, v[i] & 0x7fff7fffu);
            }
            mmax = max(mmax << 16, mmax & 0xffff0000u);
            bar_arrive(2, 384);
            tag = (__shfl_sync(~0u, tag, 0) / 96u + 1u) & 0xffffu;
            mbar_wait(sb + B_W + 0, 0);
            const __nv_bfloat16* p = Wo + (size_t)(h * 128 + 4 * t) * DM + 192 * r + 16 * c + 2 * g;
#pragma unroll
            for (int i = 0; i < 3; i++)
#pragma unroll
                for (int eb = 0; eb < 8; eb++)
#pragma unroll
                    for (int j = 0; j < 4; j++) a[(i * 8 + eb) * 4 + j] = ldg_nc32(p + (16 * eb + ((j & 1) * 2 + (j >> 1))) * DM + 64 * i);
#pragma unroll
            for (int kk = 0; kk < 48; kk++) {
                uint32_t w0 = a[2 * kk], w1 = a[2 * kk + 1];
                a[2 * kk] = __byte_perm(w0, w1, 0x5410);
                a[2 * kk + 1] = __byte_perm(w0, w1, 0x7632);
            }
            sts128(sb + O_WP + c * 512 + lane * 16, a[92], a[93], a[94], a[95]);
            float wmax = 0.f;
#pragma unroll
            for (int i = 0; i < 3; i++) {
                float n0[4];
#pragma unroll
                for (int u = 8 * i; u < 8 * i + 8; u++) {
                    const uint32_t x0 = a[4 * u] & 0x7fff7fffu, x1 = a[4 * u + 1] & 0x7fff7fffu, x2 = a[4 * u + 2] & 0x7fff7fffu, x3 = a[4 * u + 3] & 0x7fff7fffu;
                    if (u == 8 * i) mma16816_z(n0, x0, x1, x2, x3, ONES, ONES);
                    else mma16816(n0, x0, x1, x2, x3, ONES, ONES);
                }
                wmax = fmaxf(wmax, fmaxf(n0[0], n0[2]));
            }
            uint32_t wm = __reduce_max_sync(~0u, __float_as_uint(wmax));
            sts32_if(lane, sb + O_OF + 4 * c, wm);
            if (c == 0) PSTAMP(8);
            bar_sync(7, 384);
            asm volatile("barrier.cluster.wait.aligned;" ::: "memory");
            if (c == 1) tma_x_tile(sb, &tm_x, r, 1, 1);
            if (c == 0) {
                const uint4 wq = lds128(sb + O_OF), xq = lds128(sb + O_OF + 16), xr = lds128(sb + O_OF + 32), v0 = lds128(sb + O_MISC + 32), v1 = lds128(sb + O_MISC + 48);
                const uint32_t w1 = max(max(wq.x, wq.y), max(wq.z, wq.w)), x1 = max(max(max(xq.x, xq.y), max(xq.z, xq.w)), max(max(xr.x, xr.y), max(xr.z, xr.w)));
                const uint32_t vv = (r < 2) ? 0u : max(max(max(v0.x, v0.y), max(v0.z, v0.w)), max(max(v1.x, v1.y), max(v1.z, v1.w)));
                const uint32_t lo = (min(w1, 0x7f800000u) + 0xffffu) >> 16 | ((min(vv, 0x7f800000u) + 0xffffu) & 0xffff0000u), hi = (x1 & 0xffff0000u) | tag;
                uint32_t l0, h0, l1, h1, l2, h2;
                asm volatile("{\n.reg .pred p;\n.reg .u32 n, x, y;\n.reg .b64 v;\nsetp.eq.u32 p, %10, 0;\nmov.b64 v, {%8, %9};\n@p st.relaxed.gpu.global.b64 [%7], v;\nmov.u32 n, 0;\n"
                             "G_%=: ld.relaxed.gpu.global.b64 v, [%6];\nmov.b64 {%0, %1}, v;\nld.relaxed.gpu.global.b64 v, [%6+256];\nmov.b64 {%2, %3}, v;\n"
                             "ld.relaxed.gpu.global.b64 v, [%6+512];\nmov.b64 {%4, %5}, v;\n"
                             "xor.b32 x, %1, %9;\nxor.b32 y, %3, %9;\nor.b32 x, x, y;\nxor.b32 y, %5, %9;\nor.b32 x, x, y;\nand.b32 x, x, 0xffff;\n"
                             "setp.eq.u32 p, x, 0;\nvote.sync.all.pred p, p, 0xffffffff;\n@p bra.uni E_%=;\n"
                             "add.u32 n, n, 1;\nsetp.lt.u32 p, n, 4000000;\n@p bra.uni G_%=;\ntrap;\nE_%=:\n}"
                             : "=&r"(l0), "=&r"(h0), "=&r"(l1), "=&r"(h1), "=&r"(l2), "=&r"(h2)
                             : "l"(&g_norm[lane]), "l"(&g_norm[blockIdx.x]), "r"(lo), "r"(hi), "r"(lane) : "memory");
                const uint32_t lm = __vmaxu2(l0, __vmaxu2(l1, l2));
                const float fw = __uint_as_float(__reduce_max_sync(~0u, lm << 16));
                const float fv = __uint_as_float(__reduce_max_sync(~0u, lm & 0xffff0000u));
                const float xmax = __uint_as_float(__reduce_max_sync(~0u, max(h0, max(h1, h2)) & 0xffff0000u));
                const float G = 36.f * fw * fv;
                sts32_if(lane, sb + O_MISC + 4, __float_as_uint(G)); sts32_if(lane, sb + O_MISC + 8, __float_as_uint(G * xmax));
            }
        }
        if (c == 0) PSTAMP(12);
        bar_sync(6, 128);
        int s3n = 1;
        uint32_t roff = __shfl_sync(~0u, (r * 4 + c) * 2048 + (lane >> 4) * 512 + (lane & 2) * 128 + (lane & 1) * 64 + (lane & 12) * 4, lane);
#pragma unroll 1
        for (int s = 0; s < NSEG; s++) {
            const uint32_t l16 = opaque(l16c);
            const uint32_t vxa = sb + O_VX + (s & 1) * 8192 + c * 2048 + l16;
            if (c == 0 && r == 2) {
                bar_sync(14, 288);
                asm volatile("{\n.reg .pred p;\nelect.sync _|p, 0xffffffff;\n"
                    "@p cp.async.bulk.global.shared::cta.bulk_group [%0], [%1], 8192;\n@p cp.async.bulk.commit_group;\n"
                    "cp.async.bulk.wait_group 0;\nsetp.lt.and.s32 p, %4, 63, p;\n"
                    "@p cp.async.bulk.shared::cluster.global.mbarrier::complete_tx::bytes.multicast::cluster [%1], [%0], 8192, [%2], %3;\n"
                    "fence.proxy.async.global;\n}"
                    :: "l"(reinterpret_cast<char*>(g_qkv) + (size_t)(s * NH + h) * REC + 20480), "r"(sb + O_VX + (s & 1) * 8192),
                       "r"(sb + B_VX + 8 * (s & 1)), "h"((unsigned short)3), "r"(s) : "memory");
            }
            if (s == NSEG - 1) { bar_sync(3, 384); break; }
            uint4 vx[4];
            sts32_if(l16, sb + O_MISC + 16 + 4 * c, __reduce_max_sync(~0u, mmax));
            if (c == 0) STAMP(s, 5);
            {
                bar_sync(6, 128);
                const uint4 mm = lds128(sb + O_MISC + 16), cf = lds128(sb + O_MISC);
                const float bound = fmaxf(__uint_as_float(cf.z), __uint_as_float(cf.y) * (__uint_as_float(max(max(mm.x, mm.y), max(mm.z, mm.w))) * __uint_as_float(cf.x)));
                const uint32_t ebits = __reduce_max_sync(~0u, min(max(__float_as_uint(bound) & 0x7f800000u, 21u << 23), 254u << 23));
                mbar_wait(sb + B_X + 8 * s3n, ((s + 1) / 3) & 1);
                s3n = (s3n == 2) ? 0 : s3n + 1;
                bar_sync(3, 384);
                if (r < 2) mbar_wait(sb + B_VX + 8 * (s & 1), (s >> 1) & 1);
                vx[0] = lds128(vxa); vx[2] = lds128(vxa + 1024);
                if (c == 0) STAMP(s, 13);
                mbar_wait(sb + B_SC, s & 1);
                if (c == 0) STAMP(s, 6);
                float p[10];
                load_scores(p, sb + O_SC, 1280, l16);
                float mx = fmaxf(fmaxf(fmaxf(p[0], p[1]), fmaxf(p[2], p[3])), fmaxf(fmaxf(p[4], p[5]), fmaxf(p[6], p[7])));
                mx = quad_max(fmaxf(mx, fmaxf(p[8], p[9])));
                const uint4 vm = lds64x2(sb + O_VM + c * 512 + (l16 >> 1));
                vx[1] = lds128(vxa + 512); vx[3] = lds128(vxa + 1536);
                bar_arrive(4, 384);
                const float sc = __uint_as_float(lds32(sb + O_MISC + 12));
                const float mo = mx * SM_SCALE;
                uint32_t P[5];
#pragma unroll
                for (int n = 0; n < 5; n++) P[n] = pack_bf16(ex2(fmaf(p[2 * n], SM_SCALE, -mo)), ex2(fmaf(p[2 * n + 1], n == 3 ? sc : SM_SCALE, -mo)));
                if (c == 0) STAMP(s, 7);
                float o0[4], o1[4], sm[4];
                mma16816_z(sm, ONES, ONES, ONES, ONES, P[1], P[2]);
                mma16816_z(o0, vx[0].x, vx[0].y, vx[0].z, vx[0].w, P[1], P[2]);
                mma16816_z(o1, vx[2].x, vx[2].y, vx[2].z, vx[2].w, P[1], P[2]);
                mma16816(sm, ONES, ONES, ONES, ONES, P[3], P[4]);
                mma16816(o0, vx[1].x, vx[1].y, vx[1].z, vx[1].w, P[3], P[4]);
                mma16816(o1, vx[3].x, vx[3].y, vx[3].z, vx[3].w, P[3], P[4]);
                mma1688(sm, ONES, ONES, P[0]);
                mma1688(o0, vm.x, vm.y, P[0]);
                mma1688(o1, vm.z, vm.w, P[0]);
                const float sig = __uint_as_float((268u << 23) - ebits);
                const float r0 = rcp_fast(sm[0]) * sig, r1 = rcp_fast(sm[1]) * sig;
                stsm4t(sb + O_OF + c * 512 + l16, pack_bf16(o0[0] * r0, o0[1] * r1), pack_bf16(o0[2] * r0, o0[3] * r1),
                       pack_bf16(o1[0] * r0, o1[1] * r1), pack_bf16(o1[2] * r0, o1[3] * r1));
                bar_sync(6, 128);
                uint4 ob[4];
#pragma unroll
                for (int q = 0; q < 4; q++) ob[q] = ldsm4(sb + O_OF + q * 512 + l16);
                { const uint4 v = lds128(sb + O_WP + c * 512 + l16); a[92] = v.x; a[93] = v.y; a[94] = v.z; a[95] = v.w; }
                float m0[3][4], m1[3][4];
#pragma unroll
                for (int q = 0; q < 4; q++) {
#pragma unroll
                    for (int i = 0; i < 3; i++) {
                        const int k0 = (i * 8 + 2 * q) * 4;
                        if (q == 0) mma16816_z(m0[i], a[k0], a[k0 + 1], a[k0 + 2], a[k0 + 3], ob[q].x, ob[q].y);
                        else mma16816(m0[i], a[k0], a[k0 + 1], a[k0 + 2], a[k0 + 3], ob[q].x, ob[q].y);
                    }
#pragma unroll
                    for (int i = 0; i < 3; i++) {
                        const int k1 = (i * 8 + 2 * q + 1) * 4;
                        if (q == 0) mma16816_z(m1[i], a[k1], a[k1 + 1], a[k1 + 2], a[k1 + 3], ob[q].z, ob[q].w);
                        else mma16816(m1[i], a[k1], a[k1 + 1], a[k1 + 2], a[k1 + 3], ob[q].z, ob[q].w);
                    }
                }
                asm volatile("red.relaxed.gpu.global.add.noftz.v4.f16x2 [%0], {%1,%2,%3,%4};" :: "l"(reinterpret_cast<char*>(g_acc) + roff),
                    "r"(pack_f16(m0[0][0] + m1[0][0], m0[0][2] + m1[0][2])), "r"(pack_f16(m0[1][0] + m1[1][0], m0[1][2] + m1[1][2])),
                    "r"(pack_f16(m0[2][0] + m1[2][0], m0[2][2] + m1[2][2])), "r"(0x3c00u) : "memory");
                asm volatile("red.relaxed.gpu.global.add.noftz.v4.f16x2 [%0], {%1,%2,%3,%4};" :: "l"(reinterpret_cast<char*>(g_acc) + roff + 1024),
                    "r"(pack_f16(m0[0][1] + m1[0][1], m0[0][3] + m1[0][3])), "r"(pack_f16(m0[1][1] + m1[1][1], m0[1][3] + m1[1][3])),
                    "r"(pack_f16(m0[2][1] + m1[2][1], m0[2][3] + m1[2][3])), "r"(0x3c00u) : "memory");
                const unsigned t_red = clk();
                bar_arrive(5, 256);
                bar_arrive(13, 256);
                mbar_expect_if(l16 | c, sb + B_SC, 4608);
                mbar_expect_if(l16 | (c ^ 1) | (r >> 1), sb + B_VX + 8 * ((s + 1) & 1), 8192);
                sts32_if(l16 | (c ^ 3), sb + O_MISC, ebits - (14u << 23));
                if (c == 0) STAMPV(s, 8, t_red);
                const char* pbase = reinterpret_cast<const char*>(g_acc) + (s * 24576 + c * 2048) + ((l16 & 64) * 16 + (l16 & 256) + ((l16 & 128) >> 1) + (l16 & 48));
                spin_until(t_red, D_WAIT);
                uint4 v[6];
#pragma unroll
                for (int i = 0; i < 6; i++) v[i] = ldg_relaxed128(pbase + (i >> 1) * 8192 + (i & 1) * 512);
                int nretry = 0;
                auto hand_over = [&]() -> uint32_t {
                    uint32_t ok = 0;
#pragma unroll
                    for (int tau = 0; tau < 3; tau++) {
                        if (tau == 1) sched_fence<0>(h);
                        if (tau == 2) {
                            sched_fence<1>(h);
                            asm volatile("{\n.reg .pred p, q;\n.reg .b32 x;\nlop3.b32 x, %1, %2, %3, 0x80;\nlop3.b32 x, x, %4, %5, 0x80;\nand.b32 x, x, %6;\n"
                                         "setp.eq.u32 p, x, 0x5000;\nvote.sync.all.pred q, p, 0xffffffff;\nselp.u32 %0, 1, 0, q;\n}"
                                         : "=r"(ok) : "r"(v[0].w), "r"(v[1].w), "r"(v[2].w), "r"(v[3].w), "r"(v[4].w), "r"(v[5].w));
                        }
                        v[2 * tau].x = f16x2_to_bf16x2(v[2 * tau].x); v[2 * tau + 1].x = f16x2_to_bf16x2(v[2 * tau + 1].x);
                        v[2 * tau].y = f16x2_to_bf16x2(v[2 * tau].y); v[2 * tau + 1].y = f16x2_to_bf16x2(v[2 * tau + 1].y);
                        v[2 * tau].z = f16x2_to_bf16x2(v[2 * tau].z); v[2 * tau + 1].z = f16x2_to_bf16x2(v[2 * tau + 1].z);
                        sts128(sb + O_MF + tau * 3072 + c * 512 + l16, v[2 * tau].x, v[2 * tau + 1].x, v[2 * tau].y, v[2 * tau + 1].y);
                        sts64(sb + O_MF + tau * 3072 + 2048 + (c >> 1) * 512 + (c & 1) * 8 + l16, v[2 * tau].z, v[2 * tau + 1].z);
                    }
                    asm volatile("{\n.reg .pred p;\nsetp.ne.u32 p, %0, 0;\n@p bar.arrive 2, 384;\n}" :: "r"(ok) : "memory");
                    return ok;
                };
                if (!hand_over()) {
                    asm volatile("{\n.reg .pred p, q;\n.reg .u32 n, x;\nmov.u32 n, 0;\n"
                         "R_%=: ld.relaxed.gpu.global.v4.u32 {%0,%1,%2,%3}, [%25];\nld.relaxed.gpu.global.v4.u32 {%4,%5,%6,%7}, [%25+512];\n"
                         "ld.relaxed.gpu.global.v4.u32 {%8,%9,%10,%11}, [%25+8192];\nld.relaxed.gpu.global.v4.u32 {%12,%13,%14,%15}, [%25+8704];\n"
                         "ld.relaxed.gpu.global.v4.u32 {%16,%17,%18,%19}, [%25+16384];\nld.relaxed.gpu.global.v4.u32 {%20,%21,%22,%23}, [%25+16896];\n"
                         "add.u32 %24, %24, 1;\nand.b32 x, %3, %7;\nand.b32 x, x, %11;\nand.b32 x, x, %15;\nand.b32 x, x, %19;\nand.b32 x, x, %23;\n"
                         "setp.eq.u32 p, x, 0x5000;\nvote.sync.all.pred q, p, 0xffffffff;\n@q bra.uni K_%=;\n"
                         "add.u32 n, n, 1;\nsetp.lt.u32 q, n, 2000000;\n@q bra.uni R_%=;\ntrap;\nK_%=:\n}"
                         : "+r"(v[0].x), "+r"(v[0].y), "+r"(v[0].z), "+r"(v[0].w), "+r"(v[1].x), "+r"(v[1].y), "+r"(v[1].z), "+r"(v[1].w),
                           "+r"(v[2].x), "+r"(v[2].y), "+r"(v[2].z), "+r"(v[2].w), "+r"(v[3].x), "+r"(v[3].y), "+r"(v[3].z), "+r"(v[3].w),
                           "+r"(v[4].x), "+r"(v[4].y), "+r"(v[4].z), "+r"(v[4].w), "+r"(v[5].x), "+r"(v[5].y), "+r"(v[5].z), "+r"(v[5].w), "+r"(nretry)
                         : "l"(pbase) : "memory");
                    hand_over();
                }
                if (c == 0) STAMP(s, 12);
                if (c == 0) STAMPV(s, 14, nretry);
                mmax = absmax2(absmax2(absmax2(v[0].x, v[0].y), absmax2(v[0].z, v[1].x)), absmax2(absmax2(v[1].y, v[1].z), absmax2(v[2].x, v[2].y)));
                mmax = absmax2(mmax, absmax2(absmax2(absmax2(v[2].z, v[3].x), absmax2(v[3].y, v[3].z)), absmax2(absmax2(v[4].x, v[4].y), absmax2(v[4].z, v[5].x))));
                mmax = absmax2(mmax, absmax2(v[5].y, v[5].z)) & 0x7fff7fffu;
                mmax = max(mmax << 16, mmax & 0xffff0000u);
            }
            roff += 24576;
        }
        {
            bar_sync(7, 384);
            if (c == 0)
                asm volatile("{\n.reg .pred p;\nsetp.eq.u32 p, %1, 0;\n@p red.release.gpu.global.inc.u32 [%0], 0xffffffff;\n}"
                             :: "l"(&g_flag[F_QKV + (60 + (h >> 3)) * 8]), "r"(l16c) : "memory");
        }
    }
    if (warp == 8) PSTAMP(13);
    cluster_sync();
}

constexpr int NST = 10;
constexpr int G_RING = 0, G_EX = NST * 16384, G_OUT = G_EX + 32768, G_CARRY = G_OUT + 32768, G_BAR = G_CARRY + 512, BG_SMEM = G_BAR + 256;
constexpr int GB_FULL = G_BAR, GB_EMPTY = G_BAR + 8 * NST, GB_W = G_BAR + 16 * NST;
static_assert(BG_SMEM <= 232448, "smem");

template <int ACC>
__device__ __forceinline__ void wgmma_n128_rs(float (&d)[64], uint32_t a0, uint32_t a1, uint32_t a2, uint32_t a3, uint64_t desc) {
    asm volatile("wgmma.mma_async.sync.aligned.m64n128k16.f32.bf16.bf16 "
        "{%0,%1,%2,%3,%4,%5,%6,%7,%8,%9,%10,%11,%12,%13,%14,%15,%16,%17,%18,%19,%20,%21,%22,%23,%24,%25,%26,%27,%28,%29,%30,%31,"
        "%32,%33,%34,%35,%36,%37,%38,%39,%40,%41,%42,%43,%44,%45,%46,%47,%48,%49,%50,%51,%52,%53,%54,%55,%56,%57,%58,%59,%60,%61,%62,%63}, "
        "{%64,%65,%66,%67}, %68, %69, 1, 1, 0;"
        : "+f"(d[0]), "+f"(d[1]), "+f"(d[2]), "+f"(d[3]), "+f"(d[4]), "+f"(d[5]), "+f"(d[6]), "+f"(d[7]),
          "+f"(d[8]), "+f"(d[9]), "+f"(d[10]), "+f"(d[11]), "+f"(d[12]), "+f"(d[13]), "+f"(d[14]), "+f"(d[15]),
          "+f"(d[16]), "+f"(d[17]), "+f"(d[18]), "+f"(d[19]), "+f"(d[20]), "+f"(d[21]), "+f"(d[22]), "+f"(d[23]),
          "+f"(d[24]), "+f"(d[25]), "+f"(d[26]), "+f"(d[27]), "+f"(d[28]), "+f"(d[29]), "+f"(d[30]), "+f"(d[31]),
          "+f"(d[32]), "+f"(d[33]), "+f"(d[34]), "+f"(d[35]), "+f"(d[36]), "+f"(d[37]), "+f"(d[38]), "+f"(d[39]),
          "+f"(d[40]), "+f"(d[41]), "+f"(d[42]), "+f"(d[43]), "+f"(d[44]), "+f"(d[45]), "+f"(d[46]), "+f"(d[47]),
          "+f"(d[48]), "+f"(d[49]), "+f"(d[50]), "+f"(d[51]), "+f"(d[52]), "+f"(d[53]), "+f"(d[54]), "+f"(d[55]),
          "+f"(d[56]), "+f"(d[57]), "+f"(d[58]), "+f"(d[59]), "+f"(d[60]), "+f"(d[61]), "+f"(d[62]), "+f"(d[63])
        : "r"(a0), "r"(a1), "r"(a2), "r"(a3), "l"(desc), "n"(ACC));
}
__device__ __forceinline__ void wait_flag(const unsigned* p, unsigned target) {
    asm volatile("{\n.reg .pred p;\n.reg .u32 n, v;\nmov.u32 n, 0;\n"
                 "W_%=: ld.acquire.gpu.global.u32 v, [%0];\nsub.u32 v, v, %1;\nsetp.ge.s32 p, v, 0;\n@p bra.uni D_%=;\nnanosleep.u32 100;\n"
                 "add.u32 n, n, 1;\nsetp.lt.u32 p, n, 4000000;\n@p bra.uni W_%=;\ntrap;\nD_%=:\n}" :: "l"(p), "r"(target) : "memory");
}
__device__ __forceinline__ void flag_inc_if(uint32_t z, unsigned* p) {
    asm volatile("{\n.reg .pred p;\nsetp.eq.u32 p, %1, 0;\n@p red.release.gpu.global.inc.u32 [%0], 0xffffffff;\n}" :: "l"(p), "r"(z) : "memory");
}
template <int NS, int STRIDE>
__device__ __forceinline__ void bg_mainloop(float (&d)[64], const uint32_t (&a)[144], uint32_t sb, int it, int lane) {
    int slot = it % NST, ph = (it / NST) & 1, prev = 0;
#pragma unroll
    for (int i = 0; i < NS; i++) {
        mbar_wait(sb + GB_FULL + 8 * slot, ph);
        const uint64_t desc = (uint64_t)(((sb + G_RING + slot * 16384) & 0x3FFFF) >> 4) | (1ull << 16) | (64ull << 32) | (1ull << 62);
        wg_fence();
#pragma unroll
        for (int k = 0; k < 4; k++) {
            const int u = 16 * i + 4 * k;
            if (i == 0 && k == 0) wgmma_n128_rs<0>(d, a[u], a[u + 1], a[u + 2], a[u + 3], desc);
            else wgmma_n128_rs<1>(d, a[u], a[u + 1], a[u + 2], a[u + 3], desc + 2 * k);
        }
        wg_commit();
        if (i > 0) {
            asm volatile("wgmma.wait_group.sync.aligned 1;" ::: "memory");
            mbar_arrive_if(lane, sb + GB_EMPTY + 8 * prev);
        }
        prev = slot;
        slot += STRIDE;
        if (slot >= NST) { slot -= NST; ph ^= 1; }
    }
    wg_wait0();
    mbar_arrive_if(lane, sb + GB_EMPTY + 8 * prev);
}
template <bool SKIP>
__device__ __forceinline__ void bg_epilogue(float (&d)[64], uint32_t sb, int wg, int w, int lane, const CUtensorMap* tm_out, int col0, int tok0,
                                            const __nv_bfloat16* xa, const __nv_bfloat16* Dk) {
    const int g = lane >> 2, t = lane & 3;
    const uint32_t ex = sb + G_EX + w * 4096 + lane * 16;
    float k[32];
    if (wg == 0) {
#pragma unroll
        for (int q = 0; q < 8; q++) sts128f(ex + q * 512, d[32 + 4 * q], d[32 + 4 * q + 1], d[32 + 4 * q + 2], d[32 + 4 * q + 3]);
#pragma unroll
        for (int i = 0; i < 32; i++) k[i] = d[i];
    } else {
#pragma unroll
        for (int q = 0; q < 8; q++) sts128f(ex + 16384 + q * 512, d[4 * q], d[4 * q + 1], d[4 * q + 2], d[4 * q + 3]);
#pragma unroll
        for (int i = 0; i < 32; i++) k[i] = d[32 + i];
    }
    uint32_t xv[16], dv = 0;
    if (SKIP) {
        const __nv_bfloat16* xp = xa + (size_t)(tok0 + 64 * wg + 2 * t) * DM + col0 + 16 * w + 2 * g;
#pragma unroll
        for (int i = 0; i < 16; i++) xv[i] = ldg_nc32(xp + (8 * (i >> 1) + (i & 1)) * DM);
        dv = ldg_nc32(Dk + col0 + 16 * w + 2 * g);
    }
    if (w == 0) asm volatile("cp.async.bulk.wait_group.read 0;" ::: "memory");
    bar_sync(1, 256);
#pragma unroll
    for (int q = 0; q < 8; q++) {
        const float4 o = lds128f(ex + (wg ^ 1) * 16384 + q * 512);
        k[4 * q] += o.x; k[4 * q + 1] += o.y; k[4 * q + 2] += o.z; k[4 * q + 3] += o.w;
    }
    bar_sync(1, 256);
    const uint32_t ob = sb + G_OUT + wg * 16384 + (w >> 1) * 8192 + (g & 1) * 8;
    const uint32_t ch = (w & 1) * 4 + (g >> 1);
#pragma unroll
    for (int i = 0; i < 16; i++) {
        float v0 = k[4 * (i >> 1) + (i & 1)], v1 = k[4 * (i >> 1) + 2 + (i & 1)];
        if (SKIP) {
            const uint32_t p = pack_bf16(__uint_as_float(xv[i] << 16) * __uint_as_float(dv << 16), __uint_as_float(xv[i] & 0xffff0000u) * __uint_as_float(dv & 0xffff0000u));
            v0 += __uint_as_float(p << 16); v1 += __uint_as_float(p & 0xffff0000u);
        }
        const uint32_t n7 = 2 * t + (i & 1);
        sts64(ob + (8 * (i >> 1) + n7) * 128 + ((ch ^ n7) << 4), __float_as_uint(v0), __float_as_uint(v1));
    }
    fence_async_smem();
    bar_sync(4 + wg, 128);
    if (w == 0) {
        if (SKIP)
            asm volatile("{\n.reg .pred p;\nelect.sync _|p, 0xffffffff;\n"
                "@p cp.async.bulk.tensor.2d.global.shared::cta.bulk_group [%0, {%2, %4}], [%1];\n"
                "@p cp.async.bulk.tensor.2d.global.shared::cta.bulk_group [%0, {%3, %4}], [%1+8192];\n@p cp.async.bulk.commit_group;\n}"
                :: "l"(tm_out), "r"(sb + G_OUT + wg * 16384), "r"(col0), "r"(col0 + 32), "r"(tok0 + 64 * wg) : "memory");
        else
            asm volatile("{\n.reg .pred p;\nelect.sync _|p, 0xffffffff;\n"
                "@p cp.reduce.async.bulk.tensor.2d.global.shared::cta.add.bulk_group [%0, {%2, %4}], [%1];\n"
                "@p cp.reduce.async.bulk.tensor.2d.global.shared::cta.add.bulk_group [%0, {%3, %4}], [%1+8192];\n@p cp.async.bulk.commit_group;\n}"
                :: "l"(tm_out), "r"(sb + G_OUT + wg * 16384), "r"(col0), "r"(col0 + 32), "r"(tok0 + 64 * wg) : "memory");
    }
}
__device__ __forceinline__ void s5_channel(int p, const __nv_bfloat16* Lre, const __nv_bfloat16* Lim, const __nv_bfloat16* logdt, float2& lam, float2& coef) {
    const float dt = __bfloat162float(__float2bfloat16(expf(__bfloat162float(logdt[p]))));
    const float lr = __bfloat162float(Lre[p]), li = __bfloat162float(Lim[p]);
    const float e = expf(dt * lr);
    float sn, cs;
    sincosf(dt * li, &sn, &cs);
    lam = make_float2(e * cs, e * sn);
    const float den = lr * lr + li * li;
    coef = make_float2(((lam.x - 1.f) * lr + lam.y * li) / den, (lam.y * lr - (lam.x - 1.f) * li) / den);
}
__device__ __forceinline__ float2 cfma(float2 a, float2 b, float2 c) {
    return make_float2(fmaf(a.x, b.x, fmaf(-a.y, b.y, c.x)), fmaf(a.x, b.y, fmaf(a.y, b.x, c.y)));
}
__device__ __forceinline__ uint4 ldg128(const void* p) { uint4 v; asm volatile("ld.global.v4.u32 {%0,%1,%2,%3}, [%4];" : "=r"(v.x), "=r"(v.y), "=r"(v.z), "=r"(v.w) : "l"(p) : "memory"); return v; }
__device__ __forceinline__ uint2 ldg64(const void* p) { uint2 v; asm volatile("ld.global.v2.u32 {%0,%1}, [%2];" : "=r"(v.x), "=r"(v.y) : "l"(p) : "memory"); return v; }

__device__ __forceinline__ void bg_attention(uint32_t st0, uint32_t st1, int mt, int lane) {
    const int g = lane >> 2, t = lane & 3;
    float sc[5][4];
#pragma unroll
    for (int n = 0; n < 5; n++) sc[n][0] = sc[n][1] = sc[n][2] = sc[n][3] = 0.f;
    float sm2[4] = {0.f, 0.f, 0.f, 0.f};
#pragma unroll
    for (int i = 0; i < 8; i++) {
        const uint32_t st = (i >> 2 ? st1 : st0) + (i & 3) * 512 + lane * 16;
        const uint4 q = ldsm4(st + mt * 2048), km = ldsm4(st + 8192), k0 = ldsm4(st + 4096);
        mma16816(sc[0], q.x, q.y, q.z, q.w, km.x, km.y);
        mma16816(sm2, q.x, q.y, q.z, q.w, km.z, km.w);
        mma16816(sc[1], q.x, q.y, q.z, q.w, k0.x, k0.y);
        mma16816(sc[2], q.x, q.y, q.z, q.w, k0.z, k0.w);
        if (mt) {
            const uint4 k1 = ldsm4(st + 6144);
            mma16816(sc[3], q.x, q.y, q.z, q.w, k1.x, k1.y);
            mma16816(sc[4], q.x, q.y, q.z, q.w, k1.z, k1.w);
        }
    }
#pragma unroll
    for (int i = 0; i < 4; i++) sc[0][i] += sm2[i];
    const int q0 = 16 * mt + 8 + g - 2 * t;
#pragma unroll
    for (int n = 1; n < 5; n++) {
        if (8 * n > q0) sc[n][0] = -INFINITY;
        if (8 * n + 1 > q0) sc[n][1] = -INFINITY;
        if (8 * n > q0 + 8) sc[n][2] = -INFINITY;
        if (8 * n + 1 > q0 + 8) sc[n][3] = -INFINITY;
    }
    float ma = fmaxf(sc[0][0], sc[0][1]), mb = fmaxf(sc[0][2], sc[0][3]);
#pragma unroll
    for (int n = 1; n < 5; n++) { ma = fmaxf(ma, fmaxf(sc[n][0], sc[n][1])); mb = fmaxf(mb, fmaxf(sc[n][2], sc[n][3])); }
    ma = quad_max(ma) * SM_SCALE; mb = quad_max(mb) * SM_SCALE;
    uint32_t Pa[5], Pb[5];
#pragma unroll
    for (int n = 0; n < 5; n++) {
        Pa[n] = pack_bf16(ex2(fmaf(sc[n][0], SM_SCALE, -ma)), ex2(fmaf(sc[n][1], SM_SCALE, -ma)));
        Pb[n] = pack_bf16(ex2(fmaf(sc[n][2], SM_SCALE, -mb)), ex2(fmaf(sc[n][3], SM_SCALE, -mb)));
    }
    float sa[4], sbb[4];
    mma1688_z(sa, ONES, ONES, Pa[0]); mma1688_z(sbb, ONES, ONES, Pb[0]);
    mma16816(sa, ONES, ONES, ONES, ONES, Pa[1], Pa[2]); mma16816(sbb, ONES, ONES, ONES, ONES, Pb[1], Pb[2]);
    mma16816(sa, ONES, ONES, ONES, ONES, Pa[3], Pa[4]); mma16816(sbb, ONES, ONES, ONES, ONES, Pb[3], Pb[4]);
    const float ra0 = rcp_fast(sa[0]), ra1 = rcp_fast(sa[1]), rb0 = rcp_fast(sbb[0]), rb1 = rcp_fast(sbb[1]);
    const uint32_t row = lane & 7;
    const uint32_t so = mt * 2048 + (lane >> 4) * 1024 + row * 128;
#pragma unroll
    for (int i = 0; i < 8; i++) {
        const uint32_t st = i >> 2 ? st1 : st0;
        const int e4 = i & 3;
        const float2 vmf = lds64f(st + 14336 + e4 * 256 + lane * 8);
        const uint32_t vm0 = __float_as_uint(vmf.x), vm1 = __float_as_uint(vmf.y);
        const uint4 v0 = lds128(st + 10240 + e4 * 1024 + lane * 16);
        float oa[4], ob[4];
        mma1688_z(oa, vm0, vm1, Pa[0]); mma1688_z(ob, vm0, vm1, Pb[0]);
        mma16816(oa, v0.x, v0.y, v0.z, v0.w, Pa[1], Pa[2]);
        mma16816(ob, v0.x, v0.y, v0.z, v0.w, Pb[1], Pb[2]);
        if (mt) {
            const uint4 v1 = lds128(st + 10240 + e4 * 1024 + 512 + lane * 16);
            mma16816(oa, v1.x, v1.y, v1.z, v1.w, Pa[3], Pa[4]);
            mma16816(ob, v1.x, v1.y, v1.z, v1.w, Pb[3], Pb[4]);
        }
        stsm4t(st + so + (((2 * e4 + ((lane >> 3) & 1)) ^ row) << 4), pack_bf16(oa[0] * ra0, oa[1] * ra1), pack_bf16(oa[2] * ra0, oa[3] * ra1),
               pack_bf16(ob[0] * rb0, ob[1] * rb1), pack_bf16(ob[2] * rb0, ob[3] * rb1));
    }
}
__device__ __forceinline__ bool bg_att_turn(int na, int ng) { return na == ng || (na == ng + 1 && na <= BG_AHEAD); }

__global__ void __launch_bounds__(384, 1)
bg_kernel(const __grid_constant__ CUtensorMap tm_xa, const __grid_constant__ CUtensorMap tm_wo, const __grid_constant__ CUtensorMap tm_out,
          const __nv_bfloat16* __restrict__ xa, const __nv_bfloat16* __restrict__ Lre, const __nv_bfloat16* __restrict__ Lim,
          const __nv_bfloat16* __restrict__ Bre, const __nv_bfloat16* __restrict__ Bim, const __nv_bfloat16* __restrict__ Cre,
          const __nv_bfloat16* __restrict__ Cim, const __nv_bfloat16* __restrict__ logdt, const __nv_bfloat16* __restrict__ Dk) {
    extern __shared__ __align__(1024) uint8_t smem_raw[];
    const uint32_t sb = smem_u32(smem_raw);
    const int lane = threadIdx.x & 31;
    const int warp = __shfl_sync(~0u, threadIdx.x >> 5, 0);
    const int wg = warp >> 2, w = warp & 3, b = blockIdx.x;
    const int nt = b % 9, kq = b / 9;
    BSTAMP(0);
    if (threadIdx.x == 0) {
        if (sb & 1023u) __trap();
        for (int i = 0; i < NST; i++) { mbar_init(sb + GB_FULL + 8 * i, 1); mbar_init(sb + GB_EMPTY + 8 * i, 4); }
        mbar_init(sb + GB_W, 1);
        asm volatile("fence.mbarrier_init.release.cluster;" ::: "memory");
        mbar_expect(sb + GB_W, (b < 18 ? 64 : 128) * 1152);
        sts32(sb + G_BAR + 248, atomicAdd(&g_ticket_bg, 1u) / 36u + 1u);
    }
    __syncthreads();
    if (wg == 2) {
        asm volatile("setmaxnreg.dec.sync.aligned.u32 24;");
        if (w == 0) {
            int slot = 0, ph = 1;
            auto next = [&]() { if (++slot == NST) { slot = 0; ph ^= 1; } };
            bar_sync(6, 288);
            if (b < 18) {
#pragma unroll 1
                for (int i = 0; i < 144; i++) {
                    const int blk = i / 9, kb = i - 9 * blk, it = (blk >> 1) * 18 + (blk & 1) + 2 * kb;
                    slot = it % NST;
                    mbar_wait(sb + GB_EMPTY + 8 * slot, ((it / NST) & 1) ^ 1);
                    asm volatile("{\n.reg .pred p;\nelect.sync _|p, 0xffffffff;\n@p mbarrier.arrive.expect_tx.shared::cta.b64 _, [%2], 16384;\n"
                        "@p cp.async.bulk.tensor.5d.shared::cluster.global.mbarrier::complete_tx::bytes [%0], [%1, {%3, %4, %4, %4, %5}], [%2];\n}"
                        :: "r"(sb + G_RING + slot * 16384), "l"(&tm_xa), "r"(sb + GB_FULL + 8 * slot), "r"(kb * 64), "r"(0), "r"(blk) : "memory");
                }
                slot = 144 % NST; ph = ((144 / NST) & 1) ^ 1;
            }
            const unsigned ep = lds32(sb + G_BAR + 248);
            auto slabs = [&](const char* src, int ns) {
                asm volatile("fence.proxy.async.global;" ::: "memory");
#pragma unroll 1
                for (int i = 0; i < ns; i++) {
                    mbar_wait(sb + GB_EMPTY + 8 * slot, ph);
                    asm volatile("{\n.reg .pred p;\nelect.sync _|p, 0xffffffff;\n@p mbarrier.arrive.expect_tx.shared::cta.b64 _, [%2], 16384;\n"
                        "@p cp.async.bulk.shared::cluster.global.mbarrier::complete_tx::bytes [%0], [%1], 16384, [%2];\n}"
                        :: "r"(sb + G_RING + slot * 16384), "l"(src + (size_t)((i & 1) * (ns >> 1) + (i >> 1)) * (SEQ * 128)), "r"(sb + GB_FULL + 8 * slot) : "memory");
                    next();
                }
            };
            if (b >= 18) {
#pragma unroll 1
                for (int blk = kq - 2; blk < 16; blk += 2) {
                    wait_flag(&g_flag[F_H + blk * 8], 18 * ep);
                    slabs(reinterpret_cast<const char*>(g_h) + blk * 16384, 18);
                }
            }
            bar_sync(6, 288);
#pragma unroll 1
            for (int na = 0, ng = 0; ng < 16;) {
                if (bg_att_turn(na, ng)) {
                    if (nt < 8) {
                        wait_flag(&g_flag[F_QKV + (na * 4 + kq) * 8], 24 * ep);
                        asm volatile("fence.proxy.async.global;" ::: "memory");
#pragma unroll 1
                        for (int i = 0; i < 8; i++) {
                            const int pr = nt * 4 + 2 * (i & 1) + (i >> 2), hf = (i >> 1) & 1;
                            const char* rec = reinterpret_cast<const char*>(g_qkv) + (size_t)((4 * na + (pr >> 3)) * NH + 8 * kq + (pr & 7)) * REC;
                            mbar_wait(sb + GB_EMPTY + 8 * slot, ph);
                            asm volatile("{\n.reg .pred p;\nelect.sync _|p, 0xffffffff;\n@p mbarrier.arrive.expect_tx.shared::cta.b64 _, [%4], 15360;\n"
                                "@p cp.async.bulk.shared::cluster.global.mbarrier::complete_tx::bytes [%0], [%1], 10240, [%4];\n"
                                "@p cp.async.bulk.shared::cluster.global.mbarrier::complete_tx::bytes [%0+10240], [%2], 4096, [%4];\n"
                                "@p cp.async.bulk.shared::cluster.global.mbarrier::complete_tx::bytes [%0+14336], [%3], 1024, [%4];\n}"
                                :: "r"(sb + G_RING + slot * 16384), "l"(rec + hf * 10240), "l"(rec + 20480 + hf * 4096), "l"(rec + 28672 + hf * 1024),
                                   "r"(sb + GB_FULL + 8 * slot) : "memory");
                            next();
                        }
                    }
                    na++;
                } else {
                    wait_flag(&g_flag[F_OX + (ng * 4 + kq) * 8], 8 * ep);
                    slabs(reinterpret_cast<const char*>(g_ox) + (size_t)kq * 16 * SEQ * 128 + ng * 16384, 16);
                    ng++;
                }
            }
        } else if (w == 1) {
            if (b < 18) {
#pragma unroll 1
                for (int blk = 0; blk < 16; blk++) {
                    bar_sync(8 + (blk & 1), 160);
                    asm volatile("{\n.reg .pred p;\nelect.sync _|p, 0xffffffff;\n@p cp.async.bulk.global.shared::cta.bulk_group [%0], [%1], 16384;\n"
                        "@p cp.async.bulk.commit_group;\ncp.async.bulk.wait_group 0;\nfence.proxy.async.global;\n}"
                        :: "l"(reinterpret_cast<char*>(g_h) + ((size_t)b * SEQ + blk * 128) * 128), "r"(sb + G_OUT + (blk & 1) * 16384) : "memory");
                    bar_arrive(10 + (blk & 1), 160);
                    flag_inc_if(lane, &g_flag[F_H + blk * 8]);
                }
            }
            if (nt < 8) {
                int it = 144;
#pragma unroll 1
                for (int na = 0, ng = 0; ng < 16;) {
                    if (bg_att_turn(na, ng)) {
                        bar_sync(7, 288);
                        if (lane < 8) {
                            const int pr = nt * 4 + 2 * (lane & 1) + (lane >> 2), hf = (lane >> 1) & 1;
                            asm volatile("cp.async.bulk.global.shared::cta.bulk_group [%0], [%1], 4096;\ncp.async.bulk.commit_group;\ncp.async.bulk.wait_group.read 0;\n"
                                "mbarrier.arrive.shared::cta.b64 _, [%2], 4;\ncp.async.bulk.wait_group 0;\nfence.proxy.async.global;"
                                :: "l"(reinterpret_cast<char*>(g_ox) + ((size_t)((8 * kq + (pr & 7)) * 2 + hf) * SEQ + (4 * na + (pr >> 3)) * 32) * 128),
                                   "r"(sb + G_RING + ((it + lane) % NST) * 16384), "r"(sb + GB_EMPTY + 8 * ((it + lane) % NST)) : "memory");
                        }
                        __syncwarp();
                        flag_inc_if(lane, &g_flag[F_OX + (na * 4 + kq) * 8]);
                        it += 8; na++;
                    } else { it += 16; ng++; }
                }
            }
        }
    } else {
        asm volatile("setmaxnreg.inc.sync.aligned.u32 240;");
        const int g = lane >> 2, t = lane & 3, tid = threadIdx.x;
        uint32_t a[144];
        float d[64];
        if (b < 18) {
            if (tid < 64)
                asm volatile("cp.async.bulk.shared::cluster.global.mbarrier::complete_tx::bytes [%0], [%1], 1152, [%2];"
                    :: "r"(sb + tid * 1168), "l"((tid < 32 ? Bre : Bim) + (size_t)(32 * b + (tid & 31)) * DM), "r"(sb + GB_W) : "memory");
            float2 lam, coef;
            s5_channel(32 * b + 8 * w + g, Lre, Lim, logdt, lam, coef);
            float2 l32 = lam;
#pragma unroll
            for (int i = 0; i < 5; i++) l32 = make_float2(l32.x * l32.x - l32.y * l32.y, 2.f * l32.x * l32.y);
            __syncwarp();
            mbar_wait(sb + GB_W, 0);
            const uint32_t ap = sb + (((lane >> 3) & 1) * 32 + 8 * w + (lane & 7)) * 1168 + (lane >> 4) * 16;
#pragma unroll
            for (int ks = 0; ks < 36; ks++) { const uint4 v = ldsm4(ap + ks * 32); a[4 * ks] = v.x; a[4 * ks + 1] = v.y; a[4 * ks + 2] = v.z; a[4 * ks + 3] = v.w; }
            bar_sync(1, 256);
            bar_arrive(6, 288);
            BSTAMP(1);
#pragma unroll 1
            for (int blk = wg; blk < 16; blk += 2) {
                bg_mainloop<9, 2>(d, a, sb, (blk >> 1) * 18 + wg, lane);
                float2 e = make_float2(0.f, 0.f);
#pragma unroll
                for (int i = 0; i < 32; i++) e = cfma(lam, e, make_float2(d[4 * (i >> 1) + (i & 1)], d[4 * (i >> 1) + 2 + (i & 1)]));
                float2 cin = make_float2(0.f, 0.f);
                if (blk > 0) { bar_sync(2 + (wg ^ 1), 256); cin = lds64f(sb + G_CARRY + (wg ^ 1) * 256 + (8 * w + g) * 8); }
                float2 mine = cin;
#pragma unroll
                for (int q = 0; q < 4; q++) {
                    const float2 eq = make_float2(__shfl_sync(~0u, e.x, (lane & 28) + q), __shfl_sync(~0u, e.y, (lane & 28) + q));
                    cin = cfma(l32, cin, eq);
                    if (t == q + 1) mine = cin;
                }
                if (blk < 15) {
                    if (t == 0) sts64(sb + G_CARRY + wg * 256 + (8 * w + g) * 8, __float_as_uint(cin.x), __float_as_uint(cin.y));
                    bar_arrive(2 + wg, 256);
                }
                const uint32_t hs = sb + G_OUT + wg * 16384 + t * 4096 + (g & 3) * 4;
                const uint32_t ch = 2 * w + (g >> 2);
                if (blk >= 2) bar_sync(10 + wg, 160);
#pragma unroll
                for (int i = 0; i < 32; i++) {
                    mine = cfma(lam, mine, make_float2(d[4 * (i >> 1) + (i & 1)], d[4 * (i >> 1) + 2 + (i & 1)]));
                    sts32(hs + i * 128 + ((ch ^ (i & 7)) << 4), pack_bf16(mine.x, mine.y));
                }
                fence_async_smem();
                bar_arrive(8 + wg, 160);
            }
            bar_sync(10 + wg, 160);
        } else {
            if (tid < 128)
                asm volatile("cp.async.bulk.shared::cluster.global.mbarrier::complete_tx::bytes [%0], [%1], 1152, [%2];"
                    :: "r"(sb + tid * 1168), "l"((tid < 64 ? Cre : Cim) + (size_t)(64 * nt + (tid & 63)) * DM), "r"(sb + GB_W) : "memory");
            for (int p = tid; p < DM; p += 256) {
                float2 lam, coef;
                s5_channel(p, Lre, Lim, logdt, lam, coef);
                sts64(sb + G_EX + p * 8, __float_as_uint(2.f * coef.x), __float_as_uint(2.f * coef.y));
            }
            bar_sync(1, 256);
            mbar_wait(sb + GB_W, 0);
            const uint32_t cp = sb + (16 * w + 2 * g) * 1168 + (288 * wg + t) * 2;
#pragma unroll
            for (int u = 0; u < 72; u++) {
                const float2 c2 = lds64f(sb + G_EX + (288 * wg + 4 * u + t) * 8);
#pragma unroll
                for (int f = 0; f < 2; f++) {
                    unsigned short r16, i16;
                    asm volatile("ld.shared.u16 %0, [%1];" : "=h"(r16) : "r"(cp + f * 1168 + u * 8) : "memory");
                    asm volatile("ld.shared.u16 %0, [%1];" : "=h"(i16) : "r"(cp + (64 + f) * 1168 + u * 8) : "memory");
                    const float cr = __uint_as_float((uint32_t)r16 << 16), ci = __uint_as_float((uint32_t)i16 << 16);
                    a[2 * u + f] = pack_bf16(cr * c2.x - ci * c2.y, -(cr * c2.y + ci * c2.x));
                }
            }
            bar_sync(1, 256);
            bar_arrive(6, 288);
            BSTAMP(1);
#pragma unroll 1
            for (int j = 0; j < 8; j++) {
                bg_mainloop<9, 2>(d, a, sb, j * 18 + wg, lane);
                bg_epilogue<true>(d, sb, wg, w, lane, &tm_out, 64 * nt, (2 * j + kq - 2) * 128, xa, Dk);
            }
        }
        bar_sync(1, 256);
        BSTAMP(2);
        if (warp == 0)
            asm volatile("{\n.reg .pred p;\nelect.sync _|p, 0xffffffff;\n@p mbarrier.arrive.expect_tx.shared::cta.b64 _, [%2], 131072;\n"
                "@p cp.async.bulk.tensor.2d.shared::cluster.global.mbarrier::complete_tx::bytes [%0], [%1, {%3, %4}], [%2];\n"
                "@p cp.async.bulk.tensor.2d.shared::cluster.global.mbarrier::complete_tx::bytes [%0+32768], [%1, {%3, %5}], [%2];\n"
                "@p cp.async.bulk.tensor.2d.shared::cluster.global.mbarrier::complete_tx::bytes [%0+65536], [%1, {%3, %6}], [%2];\n"
                "@p cp.async.bulk.tensor.2d.shared::cluster.global.mbarrier::complete_tx::bytes [%0+98304], [%1, {%3, %7}], [%2];\n}"
                :: "r"(sb), "l"(&tm_wo), "r"(sb + GB_W), "r"(64 * nt), "r"(1024 * kq), "r"(1024 * kq + 256), "r"(1024 * kq + 512), "r"(1024 * kq + 768) : "memory");
        mbar_wait(sb + GB_W, 1);
        {
            const uint32_t base = sb + wg * 65536 + 4 * t * 128 + (g & 3) * 4, ch = 2 * w + (g >> 2), r7 = (4 * t) & 7;
#pragma unroll
            for (int ks = 0; ks < 32; ks++) {
                const uint32_t w0 = lds32(base + ks * 2048 + ((ch ^ r7) << 4)), w1 = lds32(base + ks * 2048 + 256 + ((ch ^ (r7 + 2)) << 4));
                const uint32_t w2 = lds32(base + ks * 2048 + 128 + ((ch ^ (r7 + 1)) << 4)), w3 = lds32(base + ks * 2048 + 384 + ((ch ^ (r7 + 3)) << 4));
                a[4 * ks] = __byte_perm(w0, w1, 0x5410); a[4 * ks + 1] = __byte_perm(w0, w1, 0x7632);
                a[4 * ks + 2] = __byte_perm(w2, w3, 0x5410); a[4 * ks + 3] = __byte_perm(w2, w3, 0x7632);
            }
        }
        bar_sync(1, 256);
        bar_arrive(6, 288);
        BSTAMP(3);
#pragma unroll 1
        for (int na = 0, ng = 0, it = 144; ng < 16;) {
            if (bg_att_turn(na, ng)) {
                if (nt < 8) {
                    const int i0 = it + wg + 4 * (w >> 1), i1 = i0 + 2;
                    mbar_wait(sb + GB_FULL + 8 * (i0 % NST), (i0 / NST) & 1);
                    mbar_wait(sb + GB_FULL + 8 * (i1 % NST), (i1 / NST) & 1);
                    BSTAMP(8 + na * 4);
                    bg_attention(sb + G_RING + (i0 % NST) * 16384, sb + G_RING + (i1 % NST) * 16384, w & 1, lane);
                    fence_async_smem();
                    bar_arrive(7, 288);
                    bar_sync(1, 256);
                    BSTAMP(9 + na * 4);
                    it += 8;
                }
                na++;
            } else {
                bg_mainloop<8, 2>(d, a, sb, it + wg, lane);
                BSTAMP(10 + ng * 4);
                bg_epilogue<false>(d, sb, wg, w, lane, &tm_out, DM + 64 * nt, ng * 128, xa, Dk);
                BSTAMP(11 + ng * 4);
                it += 16; ng++;
            }
        }
        if (w == 0) asm volatile("cp.async.bulk.wait_group 0;" ::: "memory");
    }
    asm volatile("griddepcontrol.wait;" ::: "memory");
}

typedef CUresult (*EncodeFn)(CUtensorMap*, CUtensorMapDataType, cuuint32_t, void*, const cuuint64_t*, const cuuint64_t*, const cuuint32_t*, const cuuint32_t*,
                             CUtensorMapInterleave, CUtensorMapSwizzle, CUtensorMapL2promotion, CUtensorMapFloatOOBfill);
}

extern "C" void kernel_launch(void* const* d_in, const int* in_sizes, int n_in, void* d_out, int out_size) {
    typedef const __nv_bfloat16* bp;
    bp Ax = (bp)d_in[0], Lre = (bp)d_in[1], Lim = (bp)d_in[2], Bre = (bp)d_in[3], Bim = (bp)d_in[4], Cre = (bp)d_in[5], Cim = (bp)d_in[6],
       logdt = (bp)d_in[7], Dk = (bp)d_in[8], Bx = (bp)d_in[9], mem0 = (bp)d_in[10], Wq = (bp)d_in[11], Wk = (bp)d_in[12], Wv = (bp)d_in[13], Wo = (bp)d_in[14];
    float* out = (float*)d_out;
    static EncodeFn enc = nullptr;
    if (!enc) {
        void* fn = nullptr; cudaDriverEntryPointQueryResult qr;
        cudaGetDriverEntryPoint("cuTensorMapEncodeTiled", &fn, cudaEnableDefault, &qr);
        enc = (EncodeFn)fn;
        cudaFuncSetAttribute(chain_kernel, cudaFuncAttributeMaxDynamicSharedMemorySize, CHAIN_SMEM);
        cudaFuncSetAttribute(bg_kernel, cudaFuncAttributeMaxDynamicSharedMemorySize, BG_SMEM);
    }
    const cuuint32_t es[5] = {1, 1, 1, 1, 1};
    auto map2d = [&](CUtensorMap* tm, CUtensorMapDataType dt, const void* p, cuuint64_t d0, cuuint64_t d1, cuuint64_t stride, cuuint32_t b0, cuuint32_t b1) {
        cuuint64_t gd[2] = {d0, d1}, gs[1] = {stride}; cuuint32_t bd[2] = {b0, b1};
        enc(tm, dt, 2, (void*)p, gd, gs, bd, es, CU_TENSOR_MAP_INTERLEAVE_NONE, CU_TENSOR_MAP_SWIZZLE_128B, CU_TENSOR_MAP_L2_PROMOTION_L2_128B,
            CU_TENSOR_MAP_FLOAT_OOB_FILL_NONE);
    };
    CUtensorMap tm_x, tm_q, tm_k, tm_v, tm_xa, tm_wo, tm_out;
    map2d(&tm_x, CU_TENSOR_MAP_DATA_TYPE_BFLOAT16, Bx, DM, SEQ, DM * 2, 64, 32);
    map2d(&tm_q, CU_TENSOR_MAP_DATA_TYPE_BFLOAT16, Wq, HD, DM, HD * 2, 64, 192);
    map2d(&tm_k, CU_TENSOR_MAP_DATA_TYPE_BFLOAT16, Wk, HD, DM, HD * 2, 64, 192);
    map2d(&tm_v, CU_TENSOR_MAP_DATA_TYPE_BFLOAT16, Wv, HD, DM, HD * 2, 64, 192);
    map2d(&tm_wo, CU_TENSOR_MAP_DATA_TYPE_BFLOAT16, Wo, DM, HD, DM * 2, 64, 256);
    map2d(&tm_out, CU_TENSOR_MAP_DATA_TYPE_FLOAT32, out, 2 * DM, SEQ, 2 * DM * 4, 32, 64);
    {
        cuuint64_t gd[5] = {DM, 2, 4, 16, 16}, gs[4] = {DM * 2, 32 * DM * 2, 2 * DM * 2, 128 * DM * 2}; cuuint32_t bd[5] = {64, 2, 4, 16, 1};
        enc(&tm_xa, CU_TENSOR_MAP_DATA_TYPE_BFLOAT16, 5, (void*)Ax, gd, gs, bd, es, CU_TENSOR_MAP_INTERLEAVE_NONE, CU_TENSOR_MAP_SWIZZLE_128B,
            CU_TENSOR_MAP_L2_PROMOTION_L2_128B, CU_TENSOR_MAP_FLOAT_OOB_FILL_NONE);
    }
    cudaStream_t st = cudaStreamPerThread;
    chain_kernel<<<96, 384, CHAIN_SMEM, st>>>(tm_x, tm_q, tm_k, tm_v, Bx, mem0, Wo, out);
    cudaLaunchConfig_t cfg = {};
    cfg.gridDim = dim3(36); cfg.blockDim = dim3(384); cfg.dynamicSmemBytes = BG_SMEM; cfg.stream = st;
    cudaLaunchAttribute at[1];
    at[0].id = cudaLaunchAttributeProgrammaticStreamSerialization; at[0].val.programmaticStreamSerializationAllowed = 1;
    cfg.attrs = at; cfg.numAttrs = 1;
    cudaLaunchKernelEx(&cfg, bg_kernel, tm_xa, tm_wo, tm_out, Ax, Lre, Lim, Bre, Bim, Cre, Cim, logdt, Dk);
}
```

```cpp
#include <cuda_runtime.h>
#include <cuda.h>
#include <cuda_bf16.h>
#include <cuda_fp16.h>
#include <stdint.h>

#define D_WAIT 700

#define CLUSTER6 1
#define BG_AHEAD 5

namespace {

constexpr int DM = 576, NH = 32, SEQ = 2048, NSEG = 64, HD = 4096;

__device__ uint4 g_acc[64 * 96 * 16];
__device__ uint4 g_ox[NH * 2 * SEQ * 8];
constexpr int REC = 30720;
__device__ uint4 g_qkv[NSEG * NH * (REC / 16)];
__device__ uint4 g_h[18 * SEQ * 8];
constexpr int NFLAG = 2048, F_QKV = 0, F_OX = 512, F_H = 1024;
__device__ unsigned g_flag[NFLAG];
__device__ unsigned g_ticket, g_ticket_bg;
__device__ unsigned long long g_norm[96];
#define BSTAMP(i) do {} while (0)

__device__ __forceinline__ uint32_t smem_u32(const void* p) { return (uint32_t)__cvta_generic_to_shared(p); }
__device__ __forceinline__ uint32_t mapa(uint32_t a, uint32_t r) { uint32_t o; asm("mapa.shared::cluster.u32 %0, %1, %2;" : "=r"(o) : "r"(a), "r"(r)); return o; }
__device__ __forceinline__ uint32_t mapa_v(uint32_t a, uint32_t r) { uint32_t o; asm volatile("mapa.shared::cluster.u32 %0, %1, %2;" : "=r"(o) : "r"(a), "r"(r)); return o; }
__device__ __forceinline__ unsigned clk() { unsigned long long c; asm volatile("mov.u64 %0, %%clock64;" : "=l"(c) :: "memory"); return (unsigned)c; }
__device__ __forceinline__ void mbar_init(uint32_t bar, uint32_t cnt) { asm volatile("mbarrier.init.shared::cta.b64 [%0], %1;" :: "r"(bar), "r"(cnt) : "memory"); }
__device__ __forceinline__ void mbar_expect(uint32_t bar, uint32_t bytes) { asm volatile("mbarrier.arrive.expect_tx.shared::cta.b64 _, [%0], %1;" :: "r"(bar), "r"(bytes) : "memory"); }
__device__ __forceinline__ void mbar_wait(uint32_t bar, uint32_t parity) {
    asm volatile("{\n.reg .pred p;\n.reg .u32 n;\nmov.u32 n, 0;\n"
                 "W_%=: mbarrier.try_wait.parity.shared::cta.b64 p, [%0], %1;\n@p bra.uni D_%=;\n"
                 "add.u32 n, n, 1;\nsetp.lt.u32 p, n, 4000000;\n@p bra.uni W_%=;\ntrap;\nD_%=:\n}" :: "r"(bar), "r"(parity) : "memory");
}
__device__ __forceinline__ void mbar_expect_if(uint32_t z, uint32_t bar, uint32_t bytes) {
    asm volatile("{\n.reg .pred p;\nsetp.eq.u32 p, %2, 0;\n@p mbarrier.arrive.expect_tx.shared::cta.b64 _, [%0], %1;\n}" :: "r"(bar), "r"(bytes), "r"(z) : "memory");
}
__device__ __forceinline__ void mbar_arrive_if(uint32_t z, uint32_t bar) {
    asm volatile("{\n.reg .pred p;\nsetp.eq.u32 p, %1, 0;\n@p mbarrier.arrive.shared::cta.b64 _, [%0];\n}" :: "r"(bar), "r"(z) : "memory");
}
__device__ __forceinline__ void sts32_if(uint32_t z, uint32_t a, uint32_t x) {
    asm volatile("{\n.reg .pred p;\nsetp.eq.u32 p, %2, 0;\n@p st.shared.u32 [%0], %1;\n}" :: "r"(a), "r"(x), "r"(z) : "memory");
}
template <int K> __device__ __forceinline__ void sched_fence(int v) {
    asm volatile("{\n.reg .pred p;\nsetp.ne.s32 p, %0, %1;\n@p bra.uni F_%=;\ntrap;\nF_%=:\n}" :: "r"(v), "n"(1000 + K) : "memory");
}
__device__ __forceinline__ void spin_until(unsigned t0, unsigned d) {
    asm volatile("{\n.reg .pred p;\n.reg .u64 c;\n.reg .u32 lo;\n"
                 "S_%=: mov.u64 c, %%clock64;\ncvt.u32.u64 lo, c;\nsub.u32 lo, lo, %0;\nsetp.lt.u32 p, lo, %1;\n@p bra.uni S_%=;\n}" :: "r"(t0), "r"(d) : "memory");
}
__device__ __forceinline__ void bar_sync(int id, int n) { asm volatile("bar.sync %0, %1;" :: "r"(id), "r"(n) : "memory"); }
__device__ __forceinline__ void bar_sync_sel(int sel, int id) {
    asm volatile("{\n.reg .pred p;\nsetp.eq.u32 p, %0, 0;\n@p bar.sync %1, %3;\n@!p bar.sync %2, %3;\n}" :: "r"(sel), "r"(id), "r"(id + 1), "n"(192) : "memory");
}
__device__ __forceinline__ void bar_arrive(int id, int n) { asm volatile("bar.arrive %0, %1;" :: "r"(id), "r"(n) : "memory"); }
__device__ __forceinline__ void fence_async_smem() { asm volatile("fence.proxy.async.shared::cta;" ::: "memory"); }
__device__ __forceinline__ uint32_t pack_bf16(float lo, float hi) { uint32_t r; asm("cvt.rn.bf16x2.f32 %0, %1, %2;" : "=r"(r) : "f"(hi), "f"(lo)); return r; }
__device__ __forceinline__ uint32_t pack_f16(float lo, float hi) { uint32_t r; asm("cvt.rn.f16x2.f32 %0, %1, %2;" : "=r"(r) : "f"(hi), "f"(lo)); return r; }
__device__ __forceinline__ uint32_t f16x2_to_bf16x2(uint32_t v) { float2 f = __half22float2(*reinterpret_cast<__half2*>(&v)); return pack_bf16(f.x, f.y); }
__device__ __forceinline__ float ex2(float x) { float y; asm("ex2.approx.ftz.f32 %0, %1;" : "=f"(y) : "f"(x)); return y; }
__device__ __forceinline__ float ex2v(float x) { float y; asm volatile("ex2.approx.ftz.f32 %0, %1;" : "=f"(y) : "f"(x)); return y; }
__device__ __forceinline__ uint32_t absmax2(uint32_t a, uint32_t b) {
    uint32_t r; asm("max.xorsign.abs.bf16x2 %0, %1, %2;" : "=r"(r) : "r"(a), "r"(b)); return r;
}
__device__ __forceinline__ uint32_t shl_v(uint32_t a, int n) { return a << n; }
__device__ __forceinline__ uint32_t max3u(uint32_t a, uint32_t b, uint32_t c) { return max(max(a, b), c); }
__device__ __forceinline__ uint4 lds128(uint32_t a) { uint4 v; asm volatile("ld.shared.v4.u32 {%0,%1,%2,%3}, [%4];" : "=r"(v.x), "=r"(v.y), "=r"(v.z), "=r"(v.w) : "r"(a) : "memory"); return v; }
__device__ __forceinline__ uint4 lds128v(uint32_t a) { uint4 v; asm volatile("ld.volatile.shared.v4.u32 {%0,%1,%2,%3}, [%4];" : "=r"(v.x), "=r"(v.y), "=r"(v.z), "=r"(v.w) : "r"(a) : "memory"); return v; }
__device__ __forceinline__ float4 lds128f(uint32_t a) { float4 v; asm volatile("ld.shared.v4.f32 {%0,%1,%2,%3}, [%4];" : "=f"(v.x), "=f"(v.y), "=f"(v.z), "=f"(v.w) : "r"(a) : "memory"); return v; }
__device__ __forceinline__ float2 lds64f(uint32_t a) { float2 v; asm volatile("ld.shared.v2.f32 {%0,%1}, [%2];" : "=f"(v.x), "=f"(v.y) : "r"(a) : "memory"); return v; }
__device__ __forceinline__ uint4 lds64x2(uint32_t a) { uint4 v; asm volatile("ld.shared.v2.u32 {%0,%1}, [%4];\nld.shared.v2.u32 {%2,%3}, [%4+256];" : "=r"(v.x), "=r"(v.y), "=r"(v.z), "=r"(v.w) : "r"(a) : "memory"); return v; }
__device__ __forceinline__ uint32_t lds32(uint32_t a) { uint32_t v; asm volatile("ld.shared.u32 %0, [%1];" : "=r"(v) : "r"(a) : "memory"); return v; }
__device__ __forceinline__ void sts128(uint32_t a, uint32_t x, uint32_t y, uint32_t z, uint32_t w) { asm volatile("st.shared.v4.u32 [%0], {%1,%2,%3,%4};" :: "r"(a), "r"(x), "r"(y), "r"(z), "r"(w) : "memory"); }
__device__ __forceinline__ void sts128f(uint32_t a, float x, float y, float z, float w) { asm volatile("st.shared.v4.f32 [%0], {%1,%2,%3,%4};" :: "r"(a), "f"(x), "f"(y), "f"(z), "f"(w) : "memory"); }
__device__ __forceinline__ void sts64(uint32_t a, uint32_t x, uint32_t y) { asm volatile("st.shared.v2.u32 [%0], {%1,%2};" :: "r"(a), "r"(x), "r"(y) : "memory"); }
__device__ __forceinline__ void sts32(uint32_t a, uint32_t x) { asm volatile("st.shared.u32 [%0], %1;" :: "r"(a), "r"(x) : "memory"); }
__device__ __forceinline__ uint4 ldsm4(uint32_t a) { uint4 v; asm volatile("ldmatrix.sync.aligned.m8n8.x4.shared.b16 {%0,%1,%2,%3}, [%4];" : "=r"(v.x), "=r"(v.y), "=r"(v.z), "=r"(v.w) : "r"(a) : "memory"); return v; }
__device__ __forceinline__ void stsm2t(uint32_t a, uint32_t x, uint32_t y) { asm volatile("stmatrix.sync.aligned.m8n8.x2.trans.shared.b16 [%0], {%1,%2};" :: "r"(a), "r"(x), "r"(y) : "memory"); }
__device__ __forceinline__ void stsm4t(uint32_t a, uint32_t x, uint32_t y, uint32_t z, uint32_t w) { asm volatile("stmatrix.sync.aligned.m8n8.x4.trans.shared.b16 [%0], {%1,%2,%3,%4};" :: "r"(a), "r"(x), "r"(y), "r"(z), "r"(w) : "memory"); }
__device__ __forceinline__ void st_async64(uint32_t a, uint32_t x, uint32_t y, uint32_t bar) { asm volatile("st.async.shared::cluster.mbarrier::complete_tx::bytes.v2.b32 [%0], {%1,%2}, [%3];" :: "r"(a), "r"(x), "r"(y), "r"(bar) : "memory"); }
__device__ __forceinline__ void bulk_s2c(uint32_t dst, uint32_t src, uint32_t bytes, uint32_t bar) { asm volatile("cp.async.bulk.shared::cluster.shared::cta.mbarrier::complete_tx::bytes [%0], [%1], %2, [%3];" :: "r"(dst), "r"(src), "r"(bytes), "r"(bar) : "memory"); }
__device__ __forceinline__ void bulk_s2g(void* dst, uint32_t src, uint32_t bytes) { asm volatile("cp.async.bulk.global.shared::cta.bulk_group [%0], [%1], %2;" :: "l"(dst), "r"(src), "r"(bytes) : "memory"); }
__device__ __forceinline__ uint32_t ldg_nc32(const void* p) { uint32_t v; asm volatile("ld.global.nc.L2::128B.u32 %0, [%1];" : "=r"(v) : "l"(p)); return v; }
__device__ __forceinline__ uint4 ldg_relaxed128(const void* p) { uint4 v; asm volatile("ld.relaxed.gpu.global.v4.u32 {%0,%1,%2,%3}, [%4];" : "=r"(v.x), "=r"(v.y), "=r"(v.z), "=r"(v.w) : "l"(p) : "memory"); return v; }
__device__ __forceinline__ void mma16816(float (&d)[4], uint32_t a0, uint32_t a1, uint32_t a2, uint32_t a3, uint32_t b0, uint32_t b1) {
    asm volatile("mma.sync.aligned.m16n8k16.row.col.f32.bf16.bf16.f32 {%0,%1,%2,%3}, {%4,%5,%6,%7}, {%8,%9}, {%0,%1,%2,%3};"
        : "+f"(d[0]), "+f"(d[1]), "+f"(d[2]), "+f"(d[3]) : "r"(a0), "r"(a1), "r"(a2), "r"(a3), "r"(b0), "r"(b1));
}
__device__ __forceinline__ void mma16816_z(float (&d)[4], uint32_t a0, uint32_t a1, uint32_t a2, uint32_t a3, uint32_t b0, uint32_t b1) {
    asm volatile("mma.sync.aligned.m16n8k16.row.col.f32.bf16.bf16.f32 {%0,%1,%2,%3}, {%4,%5,%6,%7}, {%8,%9}, {%10,%10,%10,%10};"
        : "=f"(d[0]), "=f"(d[1]), "=f"(d[2]), "=f"(d[3]) : "r"(a0), "r"(a1), "r"(a2), "r"(a3), "r"(b0), "r"(b1), "f"(0.f));
}
__device__ __forceinline__ void mma1688(float (&d)[4], uint32_t a0, uint32_t a1, uint32_t b0) {
    asm volatile("mma.sync.aligned.m16n8k8.row.col.f32.bf16.bf16.f32 {%0,%1,%2,%3}, {%4,%5}, {%6}, {%0,%1,%2,%3};"
        : "+f"(d[0]), "+f"(d[1]), "+f"(d[2]), "+f"(d[3]) : "r"(a0), "r"(a1), "r"(b0));
}
__device__ __forceinline__ void mma1688_z(float (&d)[4], uint32_t a0, uint32_t a1, uint32_t b0) {
    asm volatile("mma.sync.aligned.m16n8k8.row.col.f32.bf16.bf16.f32 {%0,%1,%2,%3}, {%4,%5}, {%6}, {%7,%7,%7,%7};"
        : "=f"(d[0]), "=f"(d[1]), "=f"(d[2]), "=f"(d[3]) : "r"(a0), "r"(a1), "r"(b0), "f"(0.f));
}
template <int ACC>
__device__ __forceinline__ void wgmma_n32_rs(float (&d)[16], uint32_t a0, uint32_t a1, uint32_t a2, uint32_t a3, uint64_t desc) {
    asm volatile("wgmma.mma_async.sync.aligned.m64n32k16.f32.bf16.bf16 {%0,%1,%2,%3,%4,%5,%6,%7,%8,%9,%10,%11,%12,%13,%14,%15}, {%16,%17,%18,%19}, %20, %21, 1, 1, 0;"
        : "+f"(d[0]), "+f"(d[1]), "+f"(d[2]), "+f"(d[3]), "+f"(d[4]), "+f"(d[5]), "+f"(d[6]), "+f"(d[7]),
          "+f"(d[8]), "+f"(d[9]), "+f"(d[10]), "+f"(d[11]), "+f"(d[12]), "+f"(d[13]), "+f"(d[14]), "+f"(d[15])
        : "r"(a0), "r"(a1), "r"(a2), "r"(a3), "l"(desc), "n"(ACC));
}
template <int ACC>
__device__ __forceinline__ void wgmma_n32_ss(float (&d)[16], uint64_t da, uint64_t db) {
    asm volatile("wgmma.mma_async.sync.aligned.m64n32k16.f32.bf16.bf16 {%0,%1,%2,%3,%4,%5,%6,%7,%8,%9,%10,%11,%12,%13,%14,%15}, %16, %17, %18, 1, 1, 0, 0;"
        : "+f"(d[0]), "+f"(d[1]), "+f"(d[2]), "+f"(d[3]), "+f"(d[4]), "+f"(d[5]), "+f"(d[6]), "+f"(d[7]),
          "+f"(d[8]), "+f"(d[9]), "+f"(d[10]), "+f"(d[11]), "+f"(d[12]), "+f"(d[13]), "+f"(d[14]), "+f"(d[15])
        : "l"(da), "l"(db), "n"(ACC));
}
__device__ __forceinline__ void wg_fence() { asm volatile("wgmma.fence.sync.aligned;" ::: "memory"); }
__device__ __forceinline__ void wg_commit() { asm volatile("wgmma.commit_group.sync.aligned;" ::: "memory"); }
__device__ __forceinline__ void wg_wait0() { asm volatile("wgmma.wait_group.sync.aligned 0;" ::: "memory"); }
__device__ __forceinline__ void cluster_sync() { asm volatile("barrier.cluster.arrive.aligned;\nbarrier.cluster.wait.aligned;" ::: "memory"); }

#define STAMP(s, i) do {} while (0)
#define STAMPV(s, i, v) do {} while (0)

constexpr int XT_BYTES = 36864;
constexpr int O_XT = 0;
constexpr int O_STG = XT_BYTES;
constexpr int O_AS = 3 * XT_BYTES;
constexpr int O_XP = O_AS + 16384;
constexpr int O_QKX = O_XP + 8192;
constexpr int O_KM = O_QKX + 8192;
constexpr int O_QM = O_QKX + 10240;
constexpr int O_VX = O_STG + 147456;
constexpr int O_VM = O_VX + 16384;
constexpr int O_SC = O_VM + 2048;
constexpr int O_OF = O_SC + 2560;
constexpr int O_AF = O_OF + 2048;
constexpr int O_WP = O_AF + 4096;
constexpr int O_MF = O_WP + 2048;
constexpr int O_MISC = O_MF + 9216;
static_assert(O_QKX + 24576 <= O_VX, "smem");
constexpr int O_BAR = O_MISC + 64;
constexpr int CHAIN_SMEM = O_BAR + 128;
static_assert(CHAIN_SMEM <= 232448, "smem");
constexpr int B_X = O_BAR, B_VX = O_BAR + 24, B_SC = O_BAR + 40, B_W = O_BAR + 48;
constexpr float SM_SCALE = 0.08838834764831845f * 1.4426950408889634f;
constexpr uint32_t ONES = 0x3f803f80u;

__device__ __forceinline__ uint32_t opaque(uint32_t v) { uint32_t o; asm volatile("mov.u32 %0, %1;" : "=r"(o) : "r"(v)); return o; }
__device__ __forceinline__ void st_async128(uint32_t a, uint32_t x, uint32_t y, uint32_t z, uint32_t w, uint32_t bar) {
    asm volatile("st.async.shared::cluster.mbarrier::complete_tx::bytes.v4.b32 [%0], {%1,%2,%3,%4}, [%5];" :: "r"(a), "r"(x), "r"(y), "r"(z), "r"(w), "r"(bar) : "memory");
}
__device__ __forceinline__ void tma_x_tile(uint32_t sb, const CUtensorMap* tm, int rb, int r, int j, int slot) {
    asm volatile("{\n.reg .pred p;\nelect.sync _|p, 0xffffffff;\n"
        "@p mbarrier.arrive.expect_tx.shared::cta.b64 _, [%2], 36864;\n"
        "@p cp.async.bulk.tensor.2d.shared::cluster.global.mbarrier::complete_tx::bytes.multicast::cluster [%0], [%1, {%3, %4}], [%2], %7;\n"
        "@p cp.async.bulk.tensor.2d.shared::cluster.global.mbarrier::complete_tx::bytes.multicast::cluster [%0+4096], [%1, {%5, %4}], [%2], %7;\n"
        "@p cp.async.bulk.tensor.2d.shared::cluster.global.mbarrier::complete_tx::bytes.multicast::cluster [%0+8192], [%1, {%6, %4}], [%2], %7;\n}"
        :: "r"(sb + O_XT + slot * XT_BYTES + 3 * r * 4096), "l"(tm), "r"(sb + B_X + 8 * slot), "r"(192 * r), "r"(j * 32), "r"(192 * r + 64), "r"(192 * r + 128),
           "h"((unsigned short)(7 << rb)) : "memory");
}
__device__ __forceinline__ float quad_max(float v) {
    const float a = __shfl_xor_sync(~0u, v, 1), b = __shfl_xor_sync(~0u, v, 2), c = __shfl_xor_sync(~0u, v, 3);
    return fmaxf(fmaxf(v, a), fmaxf(b, c));
}
__device__ __forceinline__ void load_scores(float (&p)[10], uint32_t base, uint32_t stride, uint32_t l16) {
    const float4 a0 = lds128f(base + l16), b0 = lds128f(base + stride + l16);
    const float4 a1 = lds128f(base + 512 + l16), b1 = lds128f(base + stride + 512 + l16);
    const float2 a2 = lds64f(base + 1024 + (l16 >> 1)), b2 = lds64f(base + stride + 1024 + (l16 >> 1));
    p[0] = a2.x + b2.x; p[1] = a2.y + b2.y;
    p[2] = a0.x + b0.x; p[3] = a0.y + b0.y; p[4] = a0.z + b0.z; p[5] = a0.w + b0.w;
    p[6] = a1.x + b1.x; p[7] = a1.y + b1.y; p[8] = a1.z + b1.z; p[9] = a1.w + b1.w;
}
__device__ __forceinline__ float rcp_fast(float x) { float y; asm("rcp.approx.ftz.f32 %0, %1;" : "=f"(y) : "f"(x)); return y; }

__global__ void __launch_bounds__(384, 1)
chain_kernel(const __grid_constant__ CUtensorMap tm_x, const __grid_constant__ CUtensorMap tm_q,
             const __grid_constant__ CUtensorMap tm_k, const __grid_constant__ CUtensorMap tm_v,
             const __nv_bfloat16* __restrict__ x, const __nv_bfloat16* __restrict__ mem0,
             const __nv_bfloat16* __restrict__ Wo, float* __restrict__ out) {
    extern __shared__ __align__(1024) uint8_t smem_raw[];
    const uint32_t sb = smem_u32(smem_raw);
    const int lane = threadIdx.x & 31;
    const int warp = __shfl_sync(~0u, threadIdx.x >> 5, 0);
    const int wg = warp >> 2, w = warp & 3;
    const int h = blockIdx.x / 3, r = blockIdx.x - 3 * h;
    int rb;
    asm("mov.u32 %0, %%cluster_ctarank;" : "=r"(rb));
    rb -= r;

#define PSTAMP(i) do {} while (0)
    if (threadIdx.x == 0) {
        if (sb & 1023u) __trap();
        for (int i = 0; i < 9; i++) mbar_init(sb + O_BAR + 8 * i, 1);
        asm volatile("fence.mbarrier_init.release.cluster;" ::: "memory");
        for (int i = 0; i < 3; i++) {
            mbar_expect(sb + B_W + 8 * i, 49152);
            for (int tl = 0; tl < 2; tl++)
                asm volatile("cp.async.bulk.tensor.2d.shared::cluster.global.mbarrier::complete_tx::bytes [%0], [%1, {%3, %4}], [%2];"
                    :: "r"(sb + O_STG + tl * 73728 + i * 24576), "l"(r < 2 ? (tl ? &tm_k : &tm_q) : &tm_v), "r"(sb + B_W + 8 * i),
                       "r"(h * 128 + 64 * (r < 2 ? r : tl)), "r"(192 * i) : "memory");
        }
    }
    __syncwarp();
    asm volatile("barrier.cluster.arrive.relaxed.aligned;" ::: "memory");
    asm volatile("griddepcontrol.launch_dependents;" ::: "memory");
    if (warp == 0) PSTAMP(9);
    const uint32_t l16c = __shfl_sync(~0u, lane * 16, lane);

    if (wg < 2) {
#define KS(u) ((u) < 8 ? ((u) >> 1) + 4 * ((u) & 1) : (u) < 12 ? (u) : (u) < 20 ? 12 + (((u) - 12) >> 1) + 4 * ((u) & 1) : (u) < 24 ? (u) : (u) + 8)
        asm volatile("setmaxnreg.inc.sync.aligned.u32 184;");
        uint32_t a[144];
        uint32_t adr1;
        {
            const int g = lane >> 2, t = lane & 3;
            const int t1 = threadIdx.x;
#pragma unroll
            for (int i = 0; i < 2; i++) g_acc[(blockIdx.x * 64 + i * 32 + (t1 >> 3)) * 16 + (t1 & 7)] = make_uint4(0, 0, 0, 0);
#pragma unroll
            for (int i = 0; i < 12; i++) {
                const int idx = blockIdx.x * 3072 + i * 256 + t1, row = idx / 144;
                reinterpret_cast<float4*>(out)[row * 288 + 144 + (idx - row * 144)] = make_float4(0.f, 0.f, 0.f, 0.f);
            }
            __threadfence();
            asm volatile("barrier.cluster.wait.aligned;" ::: "memory");
            const uint32_t ev = sb + O_STG + (2 * t) * 128 + (((2 * w + (g >> 2)) ^ (2 * t)) << 4) + (g & 3) * 4;
            const uint32_t od = (ev ^ 16) + 128;
            auto gather = [&](int dst, uint32_t off) {
                a[dst] = lds32(ev + off); a[dst + 1] = lds32(od + off); a[dst + 2] = lds32(ev + off + 1024); a[dst + 3] = lds32(od + off + 1024);
            };
            mbar_wait(sb + B_W, 0);
#pragma unroll
            for (int u = 8; u < 12; u++) gather(32 + 4 * u, wg * 73728 + KS(u) * 2048);
            mbar_wait(sb + B_W + 8, 0);
            const uint4* xp = reinterpret_cast<const uint4*>(x) + blockIdx.x * 1536 + t1;
            uint4 xv[6];
#pragma unroll
            for (int i = 0; i < 6; i++) xv[i] = __ldg(xp + i * 256);
#pragma unroll
            for (int u = 12; u < 24; u++) gather(32 + 4 * u, wg * 73728 + KS(u) * 2048);
            mbar_wait(sb + B_W + 16, 0);
#pragma unroll
            for (int u = 24; u < 28; u++) gather(32 + 4 * u, wg * 73728 + KS(u) * 2048);
#pragma unroll
            for (int u = 0; u < 8; u++) {
                gather(32 + 4 * u, wg * (73728 + 49152) + KS(u) * 2048);
                gather(4 * u, 73728 - wg * (73728 - 49152) + KS(u) * 2048);
            }
#pragma unroll
            for (int kk = 0; kk < 72; kk++) {
                uint32_t w0 = a[2 * kk], w1 = a[2 * kk + 1];
                a[2 * kk] = __byte_perm(w0, w1, 0x5410);
                a[2 * kk + 1] = __byte_perm(w0, w1, 0x7632);
            }
            if (r == 2) {
                float n0[4], n1[4];
#pragma unroll
                for (int u = 0; u < 36; u++) {
                    const uint32_t x0 = a[4 * u] & 0x7fff7fffu, x1 = a[4 * u + 1] & 0x7fff7fffu, x2 = a[4 * u + 2] & 0x7fff7fffu, x3 = a[4 * u + 3] & 0x7fff7fffu;
                    if (u == 0) mma16816_z(n0, x0, x1, x2, x3, ONES, ONES);
                    else if (u < 8) mma16816(n0, x0, x1, x2, x3, ONES, ONES);
                    else if (u == 8) mma16816_z(n1, x0, x1, x2, x3, ONES, ONES);
                    else mma16816(n1, x0, x1, x2, x3, ONES, ONES);
                }
                const uint32_t mx = __reduce_max_sync(~0u, __float_as_uint(2.f * fmaxf(fmaxf(n0[0], n0[2]), fmaxf(n1[0], n1[2]))));
                sts32_if(lane, sb + O_MISC + 32 + 4 * warp, mx);
            }
            uint32_t xm = 0;
#pragma unroll
            for (int i = 0; i < 6; i++)
                xm = __vmaxu2(xm, __vmaxu2(__vmaxu2(xv[i].x & 0x7fff7fffu, xv[i].y & 0x7fff7fffu), __vmaxu2(xv[i].z & 0x7fff7fffu, xv[i].w & 0x7fff7fffu)));
            sts32_if(lane, sb + O_OF + 16 + 4 * warp, __reduce_max_sync(~0u, max(xm << 16, xm & 0xffff0000u)));
            if (warp == 0) PSTAMP(11);
            bar_arrive(7, 384);
            asm volatile("barrier.cluster.arrive.relaxed.aligned;" ::: "memory");
            bar_sync(1, 256);
            const uint32_t as = sb + O_AS + wg * 8192 + (16 * w + g) * 128 + t * 4;
            sts32(as + (g << 4), a[32]);
            sts32(as + 1024 + (g << 4), a[33]);
            sts32(as + ((1 ^ g) << 4), a[34]);
            sts32(as + 1024 + ((1 ^ g) << 4), a[35]);
            sts128(sb + O_AF + warp * 512 + lane * 16, a[32], a[33], a[34], a[35]);
            fence_async_smem();
            bar_sync(1, 256);
            const uint32_t l = lane * 16;
            const int mi = lane >> 3, isk = (mi >> 1) ? wg : (wg ^ 1);
            adr1 = (r == 2) ? (sb + O_VM + warp * 256 + (l >> 1))
                            : (isk ? (sb + O_KM + w * 512 + wg * 256 + (mi & 1) * 128 + (l & 127))
                                   : (sb + O_QM + w * 512 + (mi & 1) * 256 + wg * 128 + (l & 127)));
            adr1 = __shfl_sync(~0u, adr1, lane);
        }
        int s3 = 2;
#pragma unroll 1
        for (int s = -1; s < NSEG; s++) {
            const uint32_t l16 = opaque(l16c);
            s3 = (s3 == 2) ? 0 : s3 + 1;
            if (s < 0) mbar_wait(sb + B_X, 0);
            const uint64_t desc0 = (uint64_t)(((sb + O_XT + s3 * XT_BYTES) & 0x3FFFF) >> 4) | (1ull << 16) | (64ull << 32) | (1ull << 62);
            uint32_t km0 = 0, km1 = 0;
            if (s >= 0) {
                { const uint4 v = lds128(sb + O_AF + warp * 512 + l16); a[32] = v.x; a[33] = v.y; a[34] = v.z; a[35] = v.w; }
                float co[4], cw[3][4];
                uint4 b[14];
                float inv;
#define GORD(i) ((i) == 0 ? 0 : (i) == 1 ? 1 : (i) == 5 ? 2 : (i) == 9 ? 3 : (i) < 5 ? (i) + 2 : (i) < 9 ? (i) + 1 : (i))
                auto qkv_mma = [&](int i) {
                    const int gi = GORD(i), u = 8 * gi, n0 = 2 * i, n1 = 2 * i + 1;
                    if (gi < 4) {
                        if (i == 0) mma16816_z(co, a[u], a[u + 1], a[u + 2], a[u + 3], b[0].x, b[0].y);
                        else mma16816(co, a[u], a[u + 1], a[u + 2], a[u + 3], b[i].x, b[i].y);
                    }
                    if (n0 < 3) mma16816_z(cw[n0 % 3], a[32 + u], a[32 + u + 1], a[32 + u + 2], a[32 + u + 3], b[i].x, b[i].y);
                    else mma16816(cw[n0 % 3], a[32 + u], a[32 + u + 1], a[32 + u + 2], a[32 + u + 3], b[i].x, b[i].y);
                    if (n1 < 3) mma16816_z(cw[n1 % 3], a[32 + u + 4], a[32 + u + 5], a[32 + u + 6], a[32 + u + 7], b[i].z, b[i].w);
                    else mma16816(cw[n1 % 3], a[32 + u + 4], a[32 + u + 5], a[32 + u + 6], a[32 + u + 7], b[i].z, b[i].w);
                    if (gi < 4) mma16816(co, a[u + 4], a[u + 5], a[u + 6], a[u + 7], b[i].z, b[i].w);
                };
                const uint32_t mf = sb + O_MF + l16, mfs = mf + wg * 6144;
                const uint32_t qb = (s & 1) * 12288;
                bar_sync(2, 384);
                if (warp == 0) STAMP(s, 0);
                auto qkv_ld = [&](int i) { b[i] = GORD(i) < 4 ? lds128v(mfs + GORD(i) * 512) : lds128v(mf + (GORD(i) < 12 ? GORD(i) : GORD(i) + 4) * 512); };
#pragma unroll
                for (int i = 0; i < 5; i++) qkv_ld(i);
#pragma unroll
                for (int i = 0; i < 4; i++) { qkv_mma(i); qkv_ld(5 + i); }
#pragma unroll
                for (int i = 4; i < 9; i++) { qkv_mma(i); qkv_ld(5 + i); }
                inv = __uint_as_float(lds32(sb + O_MISC));
#pragma unroll
                for (int i = 9; i < 14; i++) qkv_mma(i);
#pragma unroll
                for (int i = 0; i < 4; i++) cw[0][i] += cw[1][i] + cw[2][i];
                if (r < 2) {
                    const uint32_t o0 = pack_bf16(co[0] * inv, co[1] * inv), o1 = pack_bf16(co[2] * inv, co[3] * inv);
                    const uint32_t w0 = pack_bf16(cw[0][0] * inv, cw[0][1] * inv), w1 = pack_bf16(cw[0][2] * inv, cw[0][3] * inv);
                    stsm4t(adr1 + qb, o0, o1, w0, w1);
                    if (warp == 0) STAMP(s, 1);
                    asm volatile("{\n.reg .pred p;\nsetp.ge.u32 p, %0, 3;\n@p bar.arrive 1, 256;\n}" :: "r"(warp) : "memory");
                    if (warp < 3 && s < NSEG - 1) {
                        uint4 q[4], k[4];
                        const uint32_t ka = sb + O_QKX + 4096 + qb + warp * 2048 + l16;
#pragma unroll
                        for (int i = 0; i < 4; i++) k[i] = ldsm4(ka + i * 512);
                        const uint32_t dst = sb + O_SC + r * 1280 + warp * 512 + (l16 >> 1);
                        bar_sync(1, 256);
#pragma unroll
                        for (int i = 0; i < 4; i++) q[i] = ldsm4(sb + O_QM + qb + i * 512 + l16);
                        if (warp == 2) {
#pragma unroll
                            for (int i = 0; i < 4; i++) k[i] = ldsm4(ka + i * 512);
                        }
                        float s0[4], s1[4], t0[4], t1[4];
                        mma16816_z(s0, q[0].x, q[0].y, q[0].z, q[0].w, k[0].x, k[0].y);
                        mma16816_z(s1, q[0].x, q[0].y, q[0].z, q[0].w, k[0].z, k[0].w);
                        mma16816_z(t0, q[1].x, q[1].y, q[1].z, q[1].w, k[1].x, k[1].y);
                        mma16816_z(t1, q[1].x, q[1].y, q[1].z, q[1].w, k[1].z, k[1].w);
                        mma16816(s0, q[2].x, q[2].y, q[2].z, q[2].w, k[2].x, k[2].y);
                        mma16816(s1, q[2].x, q[2].y, q[2].z, q[2].w, k[2].z, k[2].w);
                        mma16816(t0, q[3].x, q[3].y, q[3].z, q[3].w, k[3].x, k[3].y);
                        mma16816(t1, q[3].x, q[3].y, q[3].z, q[3].w, k[3].z, k[3].w);
                        const float v0 = (s0[0] + s0[2]) + (t0[0] + t0[2]), v1 = (s0[1] + s0[3]) + (t0[1] + t0[3]);
                        const float v2 = (s1[0] + s1[2]) + (t1[0] + t1[2]), v3 = (s1[1] + s1[3]) + (t1[1] + t1[3]);
                        if (warp < 2) {
                            const uint32_t dv = dst + (l16 >> 1);
                            st_async128(mapa(dv, rb + (2)), __float_as_uint(v0), __float_as_uint(v1), __float_as_uint(v2), __float_as_uint(v3), mapa(sb + B_SC, rb + (2)));
                            st_async128(mapa(dv, rb + (r ^ 1)), __float_as_uint(v0), __float_as_uint(v1), __float_as_uint(v2), __float_as_uint(v3), mapa(sb + B_SC, rb + (r ^ 1)));
                            st_async128(mapa(dv, rb + (r)), __float_as_uint(v0), __float_as_uint(v1), __float_as_uint(v2), __float_as_uint(v3), mapa(sb + B_SC, rb + (r)));
                        } else {
                            st_async64(mapa(dst, rb + (2)), __float_as_uint(v0 + v2), __float_as_uint(v1 + v3), mapa(sb + B_SC, rb + (2)));
                            st_async64(mapa(dst, rb + (r ^ 1)), __float_as_uint(v0 + v2), __float_as_uint(v1 + v3), mapa(sb + B_SC, rb + (r ^ 1)));
                            st_async64(mapa(dst, rb + (r)), __float_as_uint(v0 + v2), __float_as_uint(v1 + v3), mapa(sb + B_SC, rb + (r)));
                        }
                        if (warp == 2) STAMP(s, 2);
                    } else if (warp < 3) {
                        bar_sync(1, 256);
                    }
                } else {
                    sts128f(sb + O_XP + warp * 512 + l16, co[0], co[1], co[2], co[3]);
                    bar_sync(8 + w, 64);
                    const float4 o = lds128f(sb + O_XP + (warp ^ 4) * 512 + l16);
                    km0 = pack_bf16((cw[0][0] + o.x) * inv, (cw[0][1] + o.y) * inv);
                    km1 = pack_bf16((cw[0][2] + o.z) * inv, (cw[0][3] + o.w) * inv);
                    if (warp == 0) STAMP(s, 1);
                    if (s < NSEG - 1) {
                        st_async64(mapa(adr1, rb + (0)), km0, km1, mapa(sb + B_SC, rb + (0)));
                        st_async64(mapa(adr1, rb + (1)), km0, km1, mapa(sb + B_SC, rb + (1)));
                        st_async64(mapa(adr1, rb + (2)), km0, km1, mapa(sb + B_SC, rb + (2)));
                    }
                    if (warp == 0) STAMP(s, 2);
                }
            }
            char* rec = reinterpret_cast<char*>(g_qkv) + (size_t)(s * NH + h) * REC;
            auto store_qk = [&]() {
                asm volatile("{\n.reg .pred p;\nelect.sync _|p, 0xffffffff;\n"
                    "@p cp.async.bulk.global.shared::cta.bulk_group [%0], [%1], 10240;\n@p cp.async.bulk.commit_group;\n}"
                    :: "l"(rec + r * 10240), "r"(sb + O_QKX + (s & 1) * 12288) : "memory");
            };
            auto store_vm = [&]() { *reinterpret_cast<uint2*>(rec + 28672 + warp * 256 + (l16 >> 1)) = make_uint2(km0, km1); };
            if (s == NSEG - 1) fence_async_smem();
            if (s >= 0) bar_sync(3, 384);
            if (s == NSEG - 1) {
                if (r == 2) store_vm();
                else if (warp == 3) {
                    store_qk();
                    asm volatile("cp.async.bulk.wait_group 0;\nfence.proxy.async.global;" ::: "memory");
                }
            } else {
                const int j = s + 1;
#define XDESC(u) (((u) < 8 ? descs : desc0) + (uint64_t)(((KS(u) >> 2) * 4096 + (KS(u) & 3) * 32) >> 4))
                const uint64_t descs = desc0 + (uint64_t)(wg * (6 * 4096 >> 4));
                float d[16];
                wg_fence();
#pragma unroll
                for (int u = 0; u < 8; u++) {
                    if (u == 0) wgmma_n32_rs<0>(d, a[0], a[1], a[2], a[3], XDESC(0));
                    else wgmma_n32_rs<1>(d, a[4 * u], a[4 * u + 1], a[4 * u + 2], a[4 * u + 3], XDESC(u));
                }
                wg_commit();
                wg_wait0();
                if (warp == 0) STAMP(s, 15);
                if (s >= 0) bar_sync(4, 384);
#pragma unroll
                for (int q = 0; q < 2; q++)
                    sts128(sb + O_XP + warp * 1024 + q * 512 + l16, pack_bf16(d[8 * q], d[8 * q + 1]), pack_bf16(d[8 * q + 2], d[8 * q + 3]),
                           pack_bf16(d[8 * q + 4], d[8 * q + 5]), pack_bf16(d[8 * q + 6], d[8 * q + 7]));
                if (s >= 0) {
                    if (r == 2) store_vm();
                    else fence_async_smem();
                    if (warp == 3) asm volatile("cp.async.bulk.wait_group 0;\nfence.proxy.async.global;" ::: "memory");
                    if (warp == 1 && s + 2 < NSEG) tma_x_tile(sb, &tm_x, rb, r, s + 2, s3 == 2 ? 0 : s3 + 1);
                }
                bar_sync(12, 256);
#pragma unroll
                for (int q = 0; q < 2; q++) {
                    const uint4 o = lds128(sb + O_XP + (warp ^ 4) * 1024 + q * 512 + l16);
                    d[8 * q] = __uint_as_float(o.x << 16); d[8 * q + 1] = __uint_as_float(o.x & 0xffff0000u);
                    d[8 * q + 2] = __uint_as_float(o.y << 16); d[8 * q + 3] = __uint_as_float(o.y & 0xffff0000u);
                    d[8 * q + 4] = __uint_as_float(o.z << 16); d[8 * q + 5] = __uint_as_float(o.z & 0xffff0000u);
                    d[8 * q + 6] = __uint_as_float(o.w << 16); d[8 * q + 7] = __uint_as_float(o.w & 0xffff0000u);
                }
                if (s >= 0) {
                    if (warp == 6 && (s & 3) == 0 && s >= 4)
                        asm volatile("{\n.reg .pred p;\nsetp.eq.u32 p, %1, 0;\n@p red.release.gpu.global.inc.u32 [%0], 0xffffffff;\n}"
                                     :: "l"(&g_flag[F_QKV + (s - 4 + (h >> 3)) * 8]), "r"(l16) : "memory");
                    asm volatile("{\n.reg .pred p;\nsetp.eq.u32 p, %0, 0;\n@p bar.sync 5, 256;\n@!p bar.sync 13, 256;\n}" :: "r"(wg) : "memory");
                }
                const uint64_t da0 = (uint64_t)(((sb + O_AS + wg * 8192) & 0x3FFFF) >> 4) | (1ull << 16) | (64ull << 32) | (1ull << 62);
                wg_fence();
                wgmma_n32_ss<1>(d, da0, XDESC(0));
#pragma unroll
                for (int u = 1; u < 28; u++) wgmma_n32_rs<1>(d, a[32 + 4 * u], a[32 + 4 * u + 1], a[32 + 4 * u + 2], a[32 + 4 * u + 3], XDESC(u));
                wg_commit();
                wg_wait0();
                if (warp == 3 && r < 2 && s >= 0) store_qk();
                if (warp == 4) STAMP(s, 3);
                uint32_t e[8];
#pragma unroll
                for (int i = 0; i < 8; i++) e[i] = pack_bf16(d[2 * i], d[2 * i + 1]);
                if (r < 2) {
                    const uint32_t base = sb + O_QKX + (j & 1) * 12288 + wg * 4096 + w * 512 + l16;
                    stsm4t(base, e[0], wg ? e[1] : e[2], wg ? e[2] : e[1], e[3]);
                    stsm4t(base + 2048, e[4], wg ? e[5] : e[6], wg ? e[6] : e[5], e[7]);
                } else {
                    const uint32_t base = sb + O_VX + (j & 1) * 8192 + warp * 1024 + l16;
                    sts128(base, e[0], e[1], e[2], e[3]);
                    sts128(base + 512, e[4], e[5], e[6], e[7]);
                    fence_async_smem();
                    bar_arrive(14, 288);
                }
                if (warp == 7) STAMP(s, 4);
                if (s < 0) asm volatile("barrier.cluster.wait.aligned;" ::: "memory");
            }
        }
        bar_arrive(7, 384);
    } else {
        asm volatile("setmaxnreg.dec.sync.aligned.u32 136;");
        const int c = w;
        uint32_t a[96];
        uint32_t mmax = 0;
        {
            const int g = lane >> 2, t = lane & 3;
            uint32_t tag = 0, m0v[18];
            if (threadIdx.x == 256) tag = atomicAdd(&g_ticket, 1u);
#pragma unroll
            for (int i = 0; i < 9; i++) {
                const uint32_t* p = reinterpret_cast<const uint32_t*>(mem0 + g * DM + 16 * (4 * i + c) + 2 * t);
                m0v[2 * i] = __ldg(p); m0v[2 * i + 1] = __ldg(p + 4);
            }
            asm volatile("barrier.cluster.wait.aligned;" ::: "memory");
            if (c == 0) {
                tma_x_tile(sb, &tm_x, rb, r, 0, 0);
                mbar_expect_if(lane, sb + B_SC, 4608);
                if (r < 2) mbar_expect_if(lane, sb + B_VX, 8192);
                sts32_if(lane, sb + O_MISC, __float_as_uint(1.0f));
                sts32_if(lane, sb + O_MISC + 12, __float_as_uint(SM_SCALE));
            }
            asm volatile("barrier.cluster.arrive.relaxed.aligned;" ::: "memory");
#pragma unroll
            for (int tau = 0; tau < 3; tau++) {
                const uint32_t* v = m0v + 6 * tau;
                sts128(sb + O_MF + tau * 3072 + c * 512 + lane * 16, v[0], v[1], v[2], v[3]);
                sts64(sb + O_MF + tau * 3072 + 2048 + (c >> 1) * 512 + lane * 16 + (c & 1) * 8, v[4], v[5]);
#pragma unroll
                for (int i = 0; i < 6; i++) mmax = __vmaxu2(mmax, v[i] & 0x7fff7fffu);
            }
            mmax = max(mmax << 16, mmax & 0xffff0000u);
            bar_arrive(2, 384);
            tag = (__shfl_sync(~0u, tag, 0) / 96u + 1u) & 0xffffu;
            mbar_wait(sb + B_W + 0, 0);
            const __nv_bfloat16* p = Wo + (size_t)(h * 128 + 4 * t) * DM + 192 * r + 16 * c + 2 * g;
#pragma unroll
            for (int i = 0; i < 3; i++)
#pragma unroll
                for (int eb = 0; eb < 8; eb++)
#pragma unroll
                    for (int j = 0; j < 4; j++) a[(i * 8 + eb) * 4 + j] = ldg_nc32(p + (16 * eb + ((j & 1) * 2 + (j >> 1))) * DM + 64 * i);
#pragma unroll
            for (int kk = 0; kk < 48; kk++) {
                uint32_t w0 = a[2 * kk], w1 = a[2 * kk + 1];
                a[2 * kk] = __byte_perm(w0, w1, 0x5410);
                a[2 * kk + 1] = __byte_perm(w0, w1, 0x7632);
            }
            sts128(sb + O_WP + c * 512 + lane * 16, a[92], a[93], a[94], a[95]);
            float wmax = 0.f;
#pragma unroll
            for (int i = 0; i < 3; i++) {
                float n0[4];
#pragma unroll
                for (int u = 8 * i; u < 8 * i + 8; u++) {
                    const uint32_t x0 = a[4 * u] & 0x7fff7fffu, x1 = a[4 * u + 1] & 0x7fff7fffu, x2 = a[4 * u + 2] & 0x7fff7fffu, x3 = a[4 * u + 3] & 0x7fff7fffu;
                    if (u == 8 * i) mma16816_z(n0, x0, x1, x2, x3, ONES, ONES);
                    else mma16816(n0, x0, x1, x2, x3, ONES, ONES);
                }
                wmax = fmaxf(wmax, fmaxf(n0[0], n0[2]));
            }
            uint32_t wm = __reduce_max_sync(~0u, __float_as_uint(wmax));
            sts32_if(lane, sb + O_OF + 4 * c, wm);
            if (c == 0) PSTAMP(8);
            bar_sync(7, 384);
            asm volatile("barrier.cluster.wait.aligned;" ::: "memory");
            if (c == 1) tma_x_tile(sb, &tm_x, rb, r, 1, 1);
            if (c == 0) {
                const uint4 wq = lds128(sb + O_OF), xq = lds128(sb + O_OF + 16), xr = lds128(sb + O_OF + 32), v0 = lds128(sb + O_MISC + 32), v1 = lds128(sb + O_MISC + 48);
                const uint32_t w1 = max(max(wq.x, wq.y), max(wq.z, wq.w)), x1 = max(max(max(xq.x, xq.y), max(xq.z, xq.w)), max(max(xr.x, xr.y), max(xr.z, xr.w)));
                const uint32_t vv = (r < 2) ? 0u : max(max(max(v0.x, v0.y), max(v0.z, v0.w)), max(max(v1.x, v1.y), max(v1.z, v1.w)));
                const uint32_t lo = (min(w1, 0x7f800000u) + 0xffffu) >> 16 | ((min(vv, 0x7f800000u) + 0xffffu) & 0xffff0000u), hi = (x1 & 0xffff0000u) | tag;
                uint32_t l0, h0, l1, h1, l2, h2;
                asm volatile("{\n.reg .pred p;\n.reg .u32 n, x, y;\n.reg .b64 v;\nsetp.eq.u32 p, %10, 0;\nmov.b64 v, {%8, %9};\n@p st.relaxed.gpu.global.b64 [%7], v;\nmov.u32 n, 0;\n"
                             "G_%=: ld.relaxed.gpu.global.b64 v, [%6];\nmov.b64 {%0, %1}, v;\nld.relaxed.gpu.global.b64 v, [%6+256];\nmov.b64 {%2, %3}, v;\n"
                             "ld.relaxed.gpu.global.b64 v, [%6+512];\nmov.b64 {%4, %5}, v;\n"
                             "xor.b32 x, %1, %9;\nxor.b32 y, %3, %9;\nor.b32 x, x, y;\nxor.b32 y, %5, %9;\nor.b32 x, x, y;\nand.b32 x, x, 0xffff;\n"
                             "setp.eq.u32 p, x, 0;\nvote.sync.all.pred p, p, 0xffffffff;\n@p bra.uni E_%=;\n"
                             "add.u32 n, n, 1;\nsetp.lt.u32 p, n, 4000000;\n@p bra.uni G_%=;\ntrap;\nE_%=:\n}"
                             : "=&r"(l0), "=&r"(h0), "=&r"(l1), "=&r"(h1), "=&r"(l2), "=&r"(h2)
                             : "l"(&g_norm[lane]), "l"(&g_norm[blockIdx.x]), "r"(lo), "r"(hi), "r"(lane) : "memory");
                const uint32_t lm = __vmaxu2(l0, __vmaxu2(l1, l2));
                const float fw = __uint_as_float(__reduce_max_sync(~0u, lm << 16));
                const float fv = __uint_as_float(__reduce_max_sync(~0u, lm & 0xffff0000u));
                const float xmax = __uint_as_float(__reduce_max_sync(~0u, max(h0, max(h1, h2)) & 0xffff0000u));
                const float G = 36.f * fw * fv;
                sts32_if(lane, sb + O_MISC + 4, __float_as_uint(G)); sts32_if(lane, sb + O_MISC + 8, __float_as_uint(G * xmax));
            }
        }
        if (c == 0) PSTAMP(12);
        bar_sync(6, 128);
        int s3n = 1;
        uint32_t roff = __shfl_sync(~0u, (r * 4 + c) * 2048 + (lane >> 4) * 512 + (lane & 2) * 128 + (lane & 1) * 64 + (lane & 12) * 4, lane);
#pragma unroll 1
        for (int s = 0; s < NSEG; s++) {
            const uint32_t l16 = opaque(l16c);
            const uint32_t vxa = sb + O_VX + (s & 1) * 8192 + c * 2048 + l16;
            if (c == 0 && r == 2) {
                bar_sync(14, 288);
                asm volatile("{\n.reg .pred p;\nelect.sync _|p, 0xffffffff;\n"
                    "@p cp.async.bulk.global.shared::cta.bulk_group [%0], [%1], 8192;\n@p cp.async.bulk.commit_group;\n"
                    "cp.async.bulk.wait_group 0;\nsetp.lt.and.s32 p, %4, 63, p;\n"
                    "@p cp.async.bulk.shared::cluster.global.mbarrier::complete_tx::bytes.multicast::cluster [%1], [%0], 8192, [%2], %3;\n"
                    "fence.proxy.async.global;\n}"
                    :: "l"(reinterpret_cast<char*>(g_qkv) + (size_t)(s * NH + h) * REC + 20480), "r"(sb + O_VX + (s & 1) * 8192),
                       "r"(sb + B_VX + 8 * (s & 1)), "h"((unsigned short)(3 << rb)), "r"(s) : "memory");
            }
            if (s == NSEG - 1) { bar_sync(3, 384); break; }
            uint4 vx[4];
            sts32_if(l16, sb + O_MISC + 16 + 4 * c, __reduce_max_sync(~0u, mmax));
            if (c == 0) STAMP(s, 5);
            {
                bar_sync(6, 128);
                const uint4 mm = lds128(sb + O_MISC + 16), cf = lds128(sb + O_MISC);
                const float bound = fmaxf(__uint_as_float(cf.z), __uint_as_float(cf.y) * (__uint_as_float(max(max(mm.x, mm.y), max(mm.z, mm.w))) * __uint_as_float(cf.x)));
                const uint32_t ebits = __reduce_max_sync(~0u, min(max(__float_as_uint(bound) & 0x7f800000u, 21u << 23), 254u << 23));
                mbar_wait(sb + B_X + 8 * s3n, ((s + 1) / 3) & 1);
                s3n = (s3n == 2) ? 0 : s3n + 1;
                bar_sync(3, 384);
                if (r < 2) mbar_wait(sb + B_VX + 8 * (s & 1), (s >> 1) & 1);
                vx[0] = lds128(vxa); vx[2] = lds128(vxa + 1024);
                if (c == 0) STAMP(s, 13);
                mbar_wait(sb + B_SC, s & 1);
                if (c == 0) STAMP(s, 6);
                float p[10];
                load_scores(p, sb + O_SC, 1280, l16);
                float mx = fmaxf(fmaxf(fmaxf(p[0], p[1]), fmaxf(p[2], p[3])), fmaxf(fmaxf(p[4], p[5]), fmaxf(p[6], p[7])));
                mx = quad_max(fmaxf(mx, fmaxf(p[8], p[9])));
                const uint4 vm = lds64x2(sb + O_VM + c * 512 + (l16 >> 1));
                vx[1] = lds128(vxa + 512); vx[3] = lds128(vxa + 1536);
                bar_arrive(4, 384);
                const float sc = __uint_as_float(lds32(sb + O_MISC + 12));
                const float mo = mx * SM_SCALE;
                uint32_t P[5];
#pragma unroll
                for (int n = 0; n < 5; n++) P[n] = pack_bf16(ex2(fmaf(p[2 * n], SM_SCALE, -mo)), ex2(fmaf(p[2 * n + 1], n == 3 ? sc : SM_SCALE, -mo)));
                if (c == 0) STAMP(s, 7);
                float o0[4], o1[4], sm[4];
                mma16816_z(sm, ONES, ONES, ONES, ONES, P[1], P[2]);
                mma16816_z(o0, vx[0].x, vx[0].y, vx[0].z, vx[0].w, P[1], P[2]);
                mma16816_z(o1, vx[2].x, vx[2].y, vx[2].z, vx[2].w, P[1], P[2]);
                mma16816(sm, ONES, ONES, ONES, ONES, P[3], P[4]);
                mma16816(o0, vx[1].x, vx[1].y, vx[1].z, vx[1].w, P[3], P[4]);
                mma16816(o1, vx[3].x, vx[3].y, vx[3].z, vx[3].w, P[3], P[4]);
                mma1688(sm, ONES, ONES, P[0]);
                mma1688(o0, vm.x, vm.y, P[0]);
                mma1688(o1, vm.z, vm.w, P[0]);
                const float sig = __uint_as_float((268u << 23) - ebits);
                const float r0 = rcp_fast(sm[0]) * sig, r1 = rcp_fast(sm[1]) * sig;
                stsm4t(sb + O_OF + c * 512 + l16, pack_bf16(o0[0] * r0, o0[1] * r1), pack_bf16(o0[2] * r0, o0[3] * r1),
                       pack_bf16(o1[0] * r0, o1[1] * r1), pack_bf16(o1[2] * r0, o1[3] * r1));
                bar_sync(6, 128);
                uint4 ob[4];
#pragma unroll
                for (int q = 0; q < 4; q++) ob[q] = ldsm4(sb + O_OF + q * 512 + l16);
                { const uint4 v = lds128(sb + O_WP + c * 512 + l16); a[92] = v.x; a[93] = v.y; a[94] = v.z; a[95] = v.w; }
                float m0[3][4], m1[3][4];
#pragma unroll
                for (int q = 0; q < 4; q++) {
#pragma unroll
                    for (int i = 0; i < 3; i++) {
                        const int k0 = (i * 8 + 2 * q) * 4;
                        if (q == 0) mma16816_z(m0[i], a[k0], a[k0 + 1], a[k0 + 2], a[k0 + 3], ob[q].x, ob[q].y);
                        else mma16816(m0[i], a[k0], a[k0 + 1], a[k0 + 2], a[k0 + 3], ob[q].x, ob[q].y);
                    }
#pragma unroll
                    for (int i = 0; i < 3; i++) {
                        const int k1 = (i * 8 + 2 * q + 1) * 4;
                        if (q == 0) mma16816_z(m1[i], a[k1], a[k1 + 1], a[k1 + 2], a[k1 + 3], ob[q].z, ob[q].w);
                        else mma16816(m1[i], a[k1], a[k1 + 1], a[k1 + 2], a[k1 + 3], ob[q].z, ob[q].w);
                    }
                }
                asm volatile("red.relaxed.gpu.global.add.noftz.v4.f16x2 [%0], {%1,%2,%3,%4};" :: "l"(reinterpret_cast<char*>(g_acc) + roff),
                    "r"(pack_f16(m0[0][0] + m1[0][0], m0[0][2] + m1[0][2])), "r"(pack_f16(m0[1][0] + m1[1][0], m0[1][2] + m1[1][2])),
                    "r"(pack_f16(m0[2][0] + m1[2][0], m0[2][2] + m1[2][2])), "r"(0x3c00u) : "memory");
                asm volatile("red.relaxed.gpu.global.add.noftz.v4.f16x2 [%0], {%1,%2,%3,%4};" :: "l"(reinterpret_cast<char*>(g_acc) + roff + 1024),
                    "r"(pack_f16(m0[0][1] + m1[0][1], m0[0][3] + m1[0][3])), "r"(pack_f16(m0[1][1] + m1[1][1], m0[1][3] + m1[1][3])),
                    "r"(pack_f16(m0[2][1] + m1[2][1], m0[2][3] + m1[2][3])), "r"(0x3c00u) : "memory");
                const unsigned t_red = clk();
                bar_arrive(5, 256);
                bar_arrive(13, 256);
                mbar_expect_if(l16 | c, sb + B_SC, 4608);
                mbar_expect_if(l16 | (c ^ 1) | (r >> 1), sb + B_VX + 8 * ((s + 1) & 1), 8192);
                sts32_if(l16 | (c ^ 3), sb + O_MISC, ebits - (14u << 23));
                if (c == 0) STAMPV(s, 8, t_red);
                const char* pbase = reinterpret_cast<const char*>(g_acc) + (s * 24576 + c * 2048) + ((l16 & 64) * 16 + (l16 & 256) + ((l16 & 128) >> 1) + (l16 & 48));
                spin_until(t_red, D_WAIT);
                uint4 v[6];
#pragma unroll
                for (int i = 0; i < 6; i++) v[i] = ldg_relaxed128(pbase + (i >> 1) * 8192 + (i & 1) * 512);
                int nretry = 0;
                auto hand_over = [&]() -> uint32_t {
                    uint32_t ok = 0;
#pragma unroll
                    for (int tau = 0; tau < 3; tau++) {
                        if (tau == 1) sched_fence<0>(h);
                        if (tau == 2) {
                            sched_fence<1>(h);
                            asm volatile("{\n.reg .pred p, q;\n.reg .b32 x;\nlop3.b32 x, %1, %2, %3, 0x80;\nlop3.b32 x, x, %4, %5, 0x80;\nand.b32 x, x, %6;\n"
                                         "setp.eq.u32 p, x, 0x5000;\nvote.sync.all.pred q, p, 0xffffffff;\nselp.u32 %0, 1, 0, q;\n}"
                                         : "=r"(ok) : "r"(v[0].w), "r"(v[1].w), "r"(v[2].w), "r"(v[3].w), "r"(v[4].w), "r"(v[5].w));
                        }
                        v[2 * tau].x = f16x2_to_bf16x2(v[2 * tau].x); v[2 * tau + 1].x = f16x2_to_bf16x2(v[2 * tau + 1].x);
                        v[2 * tau].y = f16x2_to_bf16x2(v[2 * tau].y); v[2 * tau + 1].y = f16x2_to_bf16x2(v[2 * tau + 1].y);
                        v[2 * tau].z = f16x2_to_bf16x2(v[2 * tau].z); v[2 * tau + 1].z = f16x2_to_bf16x2(v[2 * tau + 1].z);
                        sts128(sb + O_MF + tau * 3072 + c * 512 + l16, v[2 * tau].x, v[2 * tau + 1].x, v[2 * tau].y, v[2 * tau + 1].y);
                        sts64(sb + O_MF + tau * 3072 + 2048 + (c >> 1) * 512 + (c & 1) * 8 + l16, v[2 * tau].z, v[2 * tau + 1].z);
                    }
                    asm volatile("{\n.reg .pred p;\nsetp.ne.u32 p, %0, 0;\n@p bar.arrive 2, 384;\n}" :: "r"(ok) : "memory");
                    return ok;
                };
                if (!hand_over()) {
                    asm volatile("{\n.reg .pred p, q;\n.reg .u32 n, x;\nmov.u32 n, 0;\n"
                         "R_%=: ld.relaxed.gpu.global.v4.u32 {%0,%1,%2,%3}, [%25];\nld.relaxed.gpu.global.v4.u32 {%4,%5,%6,%7}, [%25+512];\n"
                         "ld.relaxed.gpu.global.v4.u32 {%8,%9,%10,%11}, [%25+8192];\nld.relaxed.gpu.global.v4.u32 {%12,%13,%14,%15}, [%25+8704];\n"
                         "ld.relaxed.gpu.global.v4.u32 {%16,%17,%18,%19}, [%25+16384];\nld.relaxed.gpu.global.v4.u32 {%20,%21,%22,%23}, [%25+16896];\n"
                         "add.u32 %24, %24, 1;\nand.b32 x, %3, %7;\nand.b32 x, x, %11;\nand.b32 x, x, %15;\nand.b32 x, x, %19;\nand.b32 x, x, %23;\n"
                         "setp.eq.u32 p, x, 0x5000;\nvote.sync.all.pred q, p, 0xffffffff;\n@q bra.uni K_%=;\n"
                         "add.u32 n, n, 1;\nsetp.lt.u32 q, n, 2000000;\n@q bra.uni R_%=;\ntrap;\nK_%=:\n}"
                         : "+r"(v[0].x), "+r"(v[0].y), "+r"(v[0].z), "+r"(v[0].w), "+r"(v[1].x), "+r"(v[1].y), "+r"(v[1].z), "+r"(v[1].w),
                           "+r"(v[2].x), "+r"(v[2].y), "+r"(v[2].z), "+r"(v[2].w), "+r"(v[3].x), "+r"(v[3].y), "+r"(v[3].z), "+r"(v[3].w),
                           "+r"(v[4].x), "+r"(v[4].y), "+r"(v[4].z), "+r"(v[4].w), "+r"(v[5].x), "+r"(v[5].y), "+r"(v[5].z), "+r"(v[5].w), "+r"(nretry)
                         : "l"(pbase) : "memory");
                    hand_over();
                }
                if (c == 0) STAMP(s, 12);
                if (c == 0) STAMPV(s, 14, nretry);
                mmax = absmax2(absmax2(absmax2(v[0].x, v[0].y), absmax2(v[0].z, v[1].x)), absmax2(absmax2(v[1].y, v[1].z), absmax2(v[2].x, v[2].y)));
                mmax = absmax2(mmax, absmax2(absmax2(absmax2(v[2].z, v[3].x), absmax2(v[3].y, v[3].z)), absmax2(absmax2(v[4].x, v[4].y), absmax2(v[4].z, v[5].x))));
                mmax = absmax2(mmax, absmax2(v[5].y, v[5].z)) & 0x7fff7fffu;
                mmax = max(mmax << 16, mmax & 0xffff0000u);
            }
            roff += 24576;
        }
        {
            bar_sync(7, 384);
            if (c == 0)
                asm volatile("{\n.reg .pred p;\nsetp.eq.u32 p, %1, 0;\n@p red.release.gpu.global.inc.u32 [%0], 0xffffffff;\n}"
                             :: "l"(&g_flag[F_QKV + (60 + (h >> 3)) * 8]), "r"(l16c) : "memory");
        }
    }
    if (warp == 8) PSTAMP(13);
    cluster_sync();
}

constexpr int NST = 10;
constexpr int G_RING = 0, G_EX = NST * 16384, G_OUT = G_EX + 32768, G_CARRY = G_OUT + 32768, G_BAR = G_CARRY + 512, BG_SMEM = G_BAR + 256;
constexpr int GB_FULL = G_BAR, GB_EMPTY = G_BAR + 8 * NST, GB_W = G_BAR + 16 * NST;
static_assert(BG_SMEM <= 232448, "smem");

template <int ACC>
__device__ __forceinline__ void wgmma_n128_rs(float (&d)[64], uint32_t a0, uint32_t a1, uint32_t a2, uint32_t a3, uint64_t desc) {
    asm volatile("wgmma.mma_async.sync.aligned.m64n128k16.f32.bf16.bf16 "
        "{%0,%1,%2,%3,%4,%5,%6,%7,%8,%9,%10,%11,%12,%13,%14,%15,%16,%17,%18,%19,%20,%21,%22,%23,%24,%25,%26,%27,%28,%29,%30,%31,"
        "%32,%33,%34,%35,%36,%37,%38,%39,%40,%41,%42,%43,%44,%45,%46,%47,%48,%49,%50,%51,%52,%53,%54,%55,%56,%57,%58,%59,%60,%61,%62,%63}, "
        "{%64,%65,%66,%67}, %68, %69, 1, 1, 0;"
        : "+f"(d[0]), "+f"(d[1]), "+f"(d[2]), "+f"(d[3]), "+f"(d[4]), "+f"(d[5]), "+f"(d[6]), "+f"(d[7]),
          "+f"(d[8]), "+f"(d[9]), "+f"(d[10]), "+f"(d[11]), "+f"(d[12]), "+f"(d[13]), "+f"(d[14]), "+f"(d[15]),
          "+f"(d[16]), "+f"(d[17]), "+f"(d[18]), "+f"(d[19]), "+f"(d[20]), "+f"(d[21]), "+f"(d[22]), "+f"(d[23]),
          "+f"(d[24]), "+f"(d[25]), "+f"(d[26]), "+f"(d[27]), "+f"(d[28]), "+f"(d[29]), "+f"(d[30]), "+f"(d[31]),
          "+f"(d[32]), "+f"(d[33]), "+f"(d[34]), "+f"(d[35]), "+f"(d[36]), "+f"(d[37]), "+f"(d[38]), "+f"(d[39]),
          "+f"(d[40]), "+f"(d[41]), "+f"(d[42]), "+f"(d[43]), "+f"(d[44]), "+f"(d[45]), "+f"(d[46]), "+f"(d[47]),
          "+f"(d[48]), "+f"(d[49]), "+f"(d[50]), "+f"(d[51]), "+f"(d[52]), "+f"(d[53]), "+f"(d[54]), "+f"(d[55]),
          "+f"(d[56]), "+f"(d[57]), "+f"(d[58]), "+f"(d[59]), "+f"(d[60]), "+f"(d[61]), "+f"(d[62]), "+f"(d[63])
        : "r"(a0), "r"(a1), "r"(a2), "r"(a3), "l"(desc), "n"(ACC));
}
__device__ __forceinline__ void wait_flag(const unsigned* p, unsigned target) {
    asm volatile("{\n.reg .pred p;\n.reg .u32 n, v;\nmov.u32 n, 0;\n"
                 "W_%=: ld.acquire.gpu.global.u32 v, [%0];\nsub.u32 v, v, %1;\nsetp.ge.s32 p, v, 0;\n@p bra.uni D_%=;\nnanosleep.u32 100;\n"
                 "add.u32 n, n, 1;\nsetp.lt.u32 p, n, 4000000;\n@p bra.uni W_%=;\ntrap;\nD_%=:\n}" :: "l"(p), "r"(target) : "memory");
}
__device__ __forceinline__ void flag_inc_if(uint32_t z, unsigned* p) {
    asm volatile("{\n.reg .pred p;\nsetp.eq.u32 p, %1, 0;\n@p red.release.gpu.global.inc.u32 [%0], 0xffffffff;\n}" :: "l"(p), "r"(z) : "memory");
}
template <int NS, int STRIDE>
__device__ __forceinline__ void bg_mainloop(float (&d)[64], const uint32_t (&a)[144], uint32_t sb, int it, int lane) {
    int slot = it % NST, ph = (it / NST) & 1, prev = 0;
#pragma unroll
    for (int i = 0; i < NS; i++) {
        mbar_wait(sb + GB_FULL + 8 * slot, ph);
        const uint64_t desc = (uint64_t)(((sb + G_RING + slot * 16384) & 0x3FFFF) >> 4) | (1ull << 16) | (64ull << 32) | (1ull << 62);
        wg_fence();
#pragma unroll
        for (int k = 0; k < 4; k++) {
            const int u = 16 * i + 4 * k;
            if (i == 0 && k == 0) wgmma_n128_rs<0>(d, a[u], a[u + 1], a[u + 2], a[u + 3], desc);
            else wgmma_n128_rs<1>(d, a[u], a[u + 1], a[u + 2], a[u + 3], desc + 2 * k);
        }
        wg_commit();
        if (i > 0) {
            asm volatile("wgmma.wait_group.sync.aligned 1;" ::: "memory");
            mbar_arrive_if(lane, sb + GB_EMPTY + 8 * prev);
        }
        prev = slot;
        slot += STRIDE;
        if (slot >= NST) { slot -= NST; ph ^= 1; }
    }
    wg_wait0();
    mbar_arrive_if(lane, sb + GB_EMPTY + 8 * prev);
}
template <bool SKIP>
__device__ __forceinline__ void bg_epilogue(float (&d)[64], uint32_t sb, int wg, int w, int lane, const CUtensorMap* tm_out, int col0, int tok0,
                                            const __nv_bfloat16* xa, const __nv_bfloat16* Dk) {
    const int g = lane >> 2, t = lane & 3;
    const uint32_t ex = sb + G_EX + w * 4096 + lane * 16;
    float k[32];
    if (wg == 0) {
#pragma unroll
        for (int q = 0; q < 8; q++) sts128f(ex + q * 512, d[32 + 4 * q], d[32 + 4 * q + 1], d[32 + 4 * q + 2], d[32 + 4 * q + 3]);
#pragma unroll
        for (int i = 0; i < 32; i++) k[i] = d[i];
    } else {
#pragma unroll
        for (int q = 0; q < 8; q++) sts128f(ex + 16384 + q * 512, d[4 * q], d[4 * q + 1], d[4 * q + 2], d[4 * q + 3]);
#pragma unroll
        for (int i = 0; i < 32; i++) k[i] = d[32 + i];
    }
    uint32_t xv[16], dv = 0;
    if (SKIP) {
        const __nv_bfloat16* xp = xa + (size_t)(tok0 + 64 * wg + 2 * t) * DM + col0 + 16 * w + 2 * g;
#pragma unroll
        for (int i = 0; i < 16; i++) xv[i] = ldg_nc32(xp + (8 * (i >> 1) + (i & 1)) * DM);
        dv = ldg_nc32(Dk + col0 + 16 * w + 2 * g);
    }
    if (w == 0) asm volatile("cp.async.bulk.wait_group.read 0;" ::: "memory");
    bar_sync(1, 256);
#pragma unroll
    for (int q = 0; q < 8; q++) {
        const float4 o = lds128f(ex + (wg ^ 1) * 16384 + q * 512);
        k[4 * q] += o.x; k[4 * q + 1] += o.y; k[4 * q + 2] += o.z; k[4 * q + 3] += o.w;
    }
    bar_sync(1, 256);
    const uint32_t ob = sb + G_OUT + wg * 16384 + (w >> 1) * 8192 + (g & 1) * 8;
    const uint32_t ch = (w & 1) * 4 + (g >> 1);
#pragma unroll
    for (int i = 0; i < 16; i++) {
        float v0 = k[4 * (i >> 1) + (i & 1)], v1 = k[4 * (i >> 1) + 2 + (i & 1)];
        if (SKIP) {
            const uint32_t p = pack_bf16(__uint_as_float(xv[i] << 16) * __uint_as_float(dv << 16), __uint_as_float(xv[i] & 0xffff0000u) * __uint_as_float(dv & 0xffff0000u));
            v0 += __uint_as_float(p << 16); v1 += __uint_as_float(p & 0xffff0000u);
        }
        const uint32_t n7 = 2 * t + (i & 1);
        sts64(ob + (8 * (i >> 1) + n7) * 128 + ((ch ^ n7) << 4), __float_as_uint(v0), __float_as_uint(v1));
    }
    fence_async_smem();
    bar_sync(4 + wg, 128);
    if (w == 0) {
        if (SKIP)
            asm volatile("{\n.reg .pred p;\nelect.sync _|p, 0xffffffff;\n"
                "@p cp.async.bulk.tensor.2d.global.shared::cta.bulk_group [%0, {%2, %4}], [%1];\n"
                "@p cp.async.bulk.tensor.2d.global.shared::cta.bulk_group [%0, {%3, %4}], [%1+8192];\n@p cp.async.bulk.commit_group;\n}"
                :: "l"(tm_out), "r"(sb + G_OUT + wg * 16384), "r"(col0), "r"(col0 + 32), "r"(tok0 + 64 * wg) : "memory");
        else
            asm volatile("{\n.reg .pred p;\nelect.sync _|p, 0xffffffff;\n"
                "@p cp.reduce.async.bulk.tensor.2d.global.shared::cta.add.bulk_group [%0, {%2, %4}], [%1];\n"
                "@p cp.reduce.async.bulk.tensor.2d.global.shared::cta.add.bulk_group [%0, {%3, %4}], [%1+8192];\n@p cp.async.bulk.commit_group;\n}"
                :: "l"(tm_out), "r"(sb + G_OUT + wg * 16384), "r"(col0), "r"(col0 + 32), "r"(tok0 + 64 * wg) : "memory");
    }
}
__device__ __forceinline__ void s5_channel(int p, const __nv_bfloat16* Lre, const __nv_bfloat16* Lim, const __nv_bfloat16* logdt, float2& lam, float2& coef) {
    const float dt = __bfloat162float(__float2bfloat16(expf(__bfloat162float(logdt[p]))));
    const float lr = __bfloat162float(Lre[p]), li = __bfloat162float(Lim[p]);
    const float e = expf(dt * lr);
    float sn, cs;
    sincosf(dt * li, &sn, &cs);
    lam = make_float2(e * cs, e * sn);
    const float den = lr * lr + li * li;
    coef = make_float2(((lam.x - 1.f) * lr + lam.y * li) / den, (lam.y * lr - (lam.x - 1.f) * li) / den);
}
__device__ __forceinline__ float2 cfma(float2 a, float2 b, float2 c) {
    return make_float2(fmaf(a.x, b.x, fmaf(-a.y, b.y, c.x)), fmaf(a.x, b.y, fmaf(a.y, b.x, c.y)));
}
__device__ __forceinline__ uint4 ldg128(const void* p) { uint4 v; asm volatile("ld.global.v4.u32 {%0,%1,%2,%3}, [%4];" : "=r"(v.x), "=r"(v.y), "=r"(v.z), "=r"(v.w) : "l"(p) : "memory"); return v; }
__device__ __forceinline__ uint2 ldg64(const void* p) { uint2 v; asm volatile("ld.global.v2.u32 {%0,%1}, [%2];" : "=r"(v.x), "=r"(v.y) : "l"(p) : "memory"); return v; }

__device__ __forceinline__ void bg_attention(uint32_t st0, uint32_t st1, int mt, int lane) {
    const int g = lane >> 2, t = lane & 3;
    float sc[5][4];
#pragma unroll
    for (int n = 0; n < 5; n++) sc[n][0] = sc[n][1] = sc[n][2] = sc[n][3] = 0.f;
    float sm2[4] = {0.f, 0.f, 0.f, 0.f};
#pragma unroll
    for (int i = 0; i < 8; i++) {
        const uint32_t st = (i >> 2 ? st1 : st0) + (i & 3) * 512 + lane * 16;
        const uint4 q = ldsm4(st + mt * 2048), km = ldsm4(st + 8192), k0 = ldsm4(st + 4096);
        mma16816(sc[0], q.x, q.y, q.z, q.w, km.x, km.y);
        mma16816(sm2, q.x, q.y, q.z, q.w, km.z, km.w);
        mma16816(sc[1], q.x, q.y, q.z, q.w, k0.x, k0.y);
        mma16816(sc[2], q.x, q.y, q.z, q.w, k0.z, k0.w);
        if (mt) {
            const uint4 k1 = ldsm4(st + 6144);
            mma16816(sc[3], q.x, q.y, q.z, q.w, k1.x, k1.y);
            mma16816(sc[4], q.x, q.y, q.z, q.w, k1.z, k1.w);
        }
    }
#pragma unroll
    for (int i = 0; i < 4; i++) sc[0][i] += sm2[i];
    const int q0 = 16 * mt + 8 + g - 2 * t;
#pragma unroll
    for (int n = 1; n < 5; n++) {
        if (8 * n > q0) sc[n][0] = -INFINITY;
        if (8 * n + 1 > q0) sc[n][1] = -INFINITY;
        if (8 * n > q0 + 8) sc[n][2] = -INFINITY;
        if (8 * n + 1 > q0 + 8) sc[n][3] = -INFINITY;
    }
    float ma = fmaxf(sc[0][0], sc[0][1]), mb = fmaxf(sc[0][2], sc[0][3]);
#pragma unroll
    for (int n = 1; n < 5; n++) { ma = fmaxf(ma, fmaxf(sc[n][0], sc[n][1])); mb = fmaxf(mb, fmaxf(sc[n][2], sc[n][3])); }
    ma = quad_max(ma) * SM_SCALE; mb = quad_max(mb) * SM_SCALE;
    uint32_t Pa[5], Pb[5];
#pragma unroll
    for (int n = 0; n < 5; n++) {
        Pa[n] = pack_bf16(ex2(fmaf(sc[n][0], SM_SCALE, -ma)), ex2(fmaf(sc[n][1], SM_SCALE, -ma)));
        Pb[n] = pack_bf16(ex2(fmaf(sc[n][2], SM_SCALE, -mb)), ex2(fmaf(sc[n][3], SM_SCALE, -mb)));
    }
    float sa[4], sbb[4];
    mma1688_z(sa, ONES, ONES, Pa[0]); mma1688_z(sbb, ONES, ONES, Pb[0]);
    mma16816(sa, ONES, ONES, ONES, ONES, Pa[1], Pa[2]); mma16816(sbb, ONES, ONES, ONES, ONES, Pb[1], Pb[2]);
    mma16816(sa, ONES, ONES, ONES, ONES, Pa[3], Pa[4]); mma16816(sbb, ONES, ONES, ONES, ONES, Pb[3], Pb[4]);
    const float ra0 = rcp_fast(sa[0]), ra1 = rcp_fast(sa[1]), rb0 = rcp_fast(sbb[0]), rb1 = rcp_fast(sbb[1]);
    const uint32_t row = lane & 7;
    const uint32_t so = mt * 2048 + (lane >> 4) * 1024 + row * 128;
#pragma unroll
    for (int i = 0; i < 8; i++) {
        const uint32_t st = i >> 2 ? st1 : st0;
        const int e4 = i & 3;
        const float2 vmf = lds64f(st + 14336 + e4 * 256 + lane * 8);
        const uint32_t vm0 = __float_as_uint(vmf.x), vm1 = __float_as_uint(vmf.y);
        const uint4 v0 = lds128(st + 10240 + e4 * 1024 + lane * 16);
        float oa[4], ob[4];
        mma1688_z(oa, vm0, vm1, Pa[0]); mma1688_z(ob, vm0, vm1, Pb[0]);
        mma16816(oa, v0.x, v0.y, v0.z, v0.w, Pa[1], Pa[2]);
        mma16816(ob, v0.x, v0.y, v0.z, v0.w, Pb[1], Pb[2]);
        if (mt) {
            const uint4 v1 = lds128(st + 10240 + e4 * 1024 + 512 + lane * 16);
            mma16816(oa, v1.x, v1.y, v1.z, v1.w, Pa[3], Pa[4]);
            mma16816(ob, v1.x, v1.y, v1.z, v1.w, Pb[3], Pb[4]);
        }
        stsm4t(st + so + (((2 * e4 + ((lane >> 3) & 1)) ^ row) << 4), pack_bf16(oa[0] * ra0, oa[1] * ra1), pack_bf16(oa[2] * ra0, oa[3] * ra1),
               pack_bf16(ob[0] * rb0, ob[1] * rb1), pack_bf16(ob[2] * rb0, ob[3] * rb1));
    }
}
__device__ __forceinline__ bool bg_att_turn(int na, int ng) { return na == ng || (na == ng + 1 && na <= BG_AHEAD); }

__global__ void __launch_bounds__(384, 1)
bg_kernel(const __grid_constant__ CUtensorMap tm_xa, const __grid_constant__ CUtensorMap tm_wo, const __grid_constant__ CUtensorMap tm_out,
          const __nv_bfloat16* __restrict__ xa, const __nv_bfloat16* __restrict__ Lre, const __nv_bfloat16* __restrict__ Lim,
          const __nv_bfloat16* __restrict__ Bre, const __nv_bfloat16* __restrict__ Bim, const __nv_bfloat16* __restrict__ Cre,
          const __nv_bfloat16* __restrict__ Cim, const __nv_bfloat16* __restrict__ logdt, const __nv_bfloat16* __restrict__ Dk) {
    extern __shared__ __align__(1024) uint8_t smem_raw[];
    const uint32_t sb = smem_u32(smem_raw);
    const int lane = threadIdx.x & 31;
    const int warp = __shfl_sync(~0u, threadIdx.x >> 5, 0);
    const int wg = warp >> 2, w = warp & 3, b = blockIdx.x;
    const int nt = b % 9, kq = b / 9;
    BSTAMP(0);
    if (threadIdx.x == 0) {
        if (sb & 1023u) __trap();
        for (int i = 0; i < NST; i++) { mbar_init(sb + GB_FULL + 8 * i, 1); mbar_init(sb + GB_EMPTY + 8 * i, 4); }
        mbar_init(sb + GB_W, 1);
        asm volatile("fence.mbarrier_init.release.cluster;" ::: "memory");
        mbar_expect(sb + GB_W, (b < 18 ? 64 : 128) * 1152);
        sts32(sb + G_BAR + 248, atomicAdd(&g_ticket_bg, 1u) / 36u + 1u);
    }
    __syncthreads();
    if (wg == 2) {
        asm volatile("setmaxnreg.dec.sync.aligned.u32 24;");
        if (w == 0) {
            int slot = 0, ph = 1;
            auto next = [&]() { if (++slot == NST) { slot = 0; ph ^= 1; } };
            bar_sync(6, 288);
            if (b < 18) {
#pragma unroll 1
                for (int i = 0; i < 144; i++) {
                    const int blk = i / 9, kb = i - 9 * blk, it = (blk >> 1) * 18 + (blk & 1) + 2 * kb;
                    slot = it % NST;
                    mbar_wait(sb + GB_EMPTY + 8 * slot, ((it / NST) & 1) ^ 1);
                    asm volatile("{\n.reg .pred p;\nelect.sync _|p, 0xffffffff;\n@p mbarrier.arrive.expect_tx.shared::cta.b64 _, [%2], 16384;\n"
                        "@p cp.async.bulk.tensor.5d.shared::cluster.global.mbarrier::complete_tx::bytes [%0], [%1, {%3, %4, %4, %4, %5}], [%2];\n}"
                        :: "r"(sb + G_RING + slot * 16384), "l"(&tm_xa), "r"(sb + GB_FULL + 8 * slot), "r"(kb * 64), "r"(0), "r"(blk) : "memory");
                }
                slot = 144 % NST; ph = ((144 / NST) & 1) ^ 1;
            }
            const unsigned ep = lds32(sb + G_BAR + 248);
            auto slabs = [&](const char* src, int ns) {
                asm volatile("fence.proxy.async.global;" ::: "memory");
#pragma unroll 1
                for (int i = 0; i < ns; i++) {
                    mbar_wait(sb + GB_EMPTY + 8 * slot, ph);
                    asm volatile("{\n.reg .pred p;\nelect.sync _|p, 0xffffffff;\n@p mbarrier.arrive.expect_tx.shared::cta.b64 _, [%2], 16384;\n"
                        "@p cp.async.bulk.shared::cluster.global.mbarrier::complete_tx::bytes [%0], [%1], 16384, [%2];\n}"
                        :: "r"(sb + G_RING + slot * 16384), "l"(src + (size_t)((i & 1) * (ns >> 1) + (i >> 1)) * (SEQ * 128)), "r"(sb + GB_FULL + 8 * slot) : "memory");
                    next();
                }
            };
            if (b >= 18) {
#pragma unroll 1
                for (int blk = kq - 2; blk < 16; blk += 2) {
                    wait_flag(&g_flag[F_H + blk * 8], 18 * ep);
                    slabs(reinterpret_cast<const char*>(g_h) + blk * 16384, 18);
                }
            }
            bar_sync(6, 288);
#pragma unroll 1
            for (int na = 0, ng = 0; ng < 16;) {
                if (bg_att_turn(na, ng)) {
                    if (nt < 8) {
                        wait_flag(&g_flag[F_QKV + (na * 4 + kq) * 8], 24 * ep);
                        asm volatile("fence.proxy.async.global;" ::: "memory");
#pragma unroll 1
                        for (int i = 0; i < 8; i++) {
                            const int pr = nt * 4 + 2 * (i & 1) + (i >> 2), hf = (i >> 1) & 1;
                            const char* rec = reinterpret_cast<const char*>(g_qkv) + (size_t)((4 * na + (pr >> 3)) * NH + 8 * kq + (pr & 7)) * REC;
                            mbar_wait(sb + GB_EMPTY + 8 * slot, ph);
                            asm volatile("{\n.reg .pred p;\nelect.sync _|p, 0xffffffff;\n@p mbarrier.arrive.expect_tx.shared::cta.b64 _, [%4], 15360;\n"
                                "@p cp.async.bulk.shared::cluster.global.mbarrier::complete_tx::bytes [%0], [%1], 10240, [%4];\n"
                                "@p cp.async.bulk.shared::cluster.global.mbarrier::complete_tx::bytes [%0+10240], [%2], 4096, [%4];\n"
                                "@p cp.async.bulk.shared::cluster.global.mbarrier::complete_tx::bytes [%0+14336], [%3], 1024, [%4];\n}"
                                :: "r"(sb + G_RING + slot * 16384), "l"(rec + hf * 10240), "l"(rec + 20480 + hf * 4096), "l"(rec + 28672 + hf * 1024),
                                   "r"(sb + GB_FULL + 8 * slot) : "memory");
                            next();
                        }
                    }
                    na++;
                } else {
                    wait_flag(&g_flag[F_OX + (ng * 4 + kq) * 8], 8 * ep);
                    slabs(reinterpret_cast<const char*>(g_ox) + (size_t)kq * 16 * SEQ * 128 + ng * 16384, 16);
                    ng++;
                }
            }
        } else if (w == 1) {
            if (b < 18) {
#pragma unroll 1
                for (int blk = 0; blk < 16; blk++) {
                    bar_sync(8 + (blk & 1), 160);
                    asm volatile("{\n.reg .pred p;\nelect.sync _|p, 0xffffffff;\n@p cp.async.bulk.global.shared::cta.bulk_group [%0], [%1], 16384;\n"
                        "@p cp.async.bulk.commit_group;\ncp.async.bulk.wait_group 0;\nfence.proxy.async.global;\n}"
                        :: "l"(reinterpret_cast<char*>(g_h) + ((size_t)b * SEQ + blk * 128) * 128), "r"(sb + G_OUT + (blk & 1) * 16384) : "memory");
                    bar_arrive(10 + (blk & 1), 160);
                    flag_inc_if(lane, &g_flag[F_H + blk * 8]);
                }
            }
            if (nt < 8) {
                int it = 144;
#pragma unroll 1
                for (int na = 0, ng = 0; ng < 16;) {
                    if (bg_att_turn(na, ng)) {
                        bar_sync(7, 288);
                        if (lane < 8) {
                            const int pr = nt * 4 + 2 * (lane & 1) + (lane >> 2), hf = (lane >> 1) & 1;
                            asm volatile("cp.async.bulk.global.shared::cta.bulk_group [%0], [%1], 4096;\ncp.async.bulk.commit_group;\ncp.async.bulk.wait_group.read 0;\n"
                                "mbarrier.arrive.shared::cta.b64 _, [%2], 4;\ncp.async.bulk.wait_group 0;\nfence.proxy.async.global;"
                                :: "l"(reinterpret_cast<char*>(g_ox) + ((size_t)((8 * kq + (pr & 7)) * 2 + hf) * SEQ + (4 * na + (pr >> 3)) * 32) * 128),
                                   "r"(sb + G_RING + ((it + lane) % NST) * 16384), "r"(sb + GB_EMPTY + 8 * ((it + lane) % NST)) : "memory");
                        }
                        __syncwarp();
                        flag_inc_if(lane, &g_flag[F_OX + (na * 4 + kq) * 8]);
                        it += 8; na++;
                    } else { it += 16; ng++; }
                }
            }
        }
    } else {
        asm volatile("setmaxnreg.inc.sync.aligned.u32 240;");
        const int g = lane >> 2, t = lane & 3, tid = threadIdx.x;
        uint32_t a[144];
        float d[64];
        if (b < 18) {
            if (tid < 64)
                asm volatile("cp.async.bulk.shared::cluster.global.mbarrier::complete_tx::bytes [%0], [%1], 1152, [%2];"
                    :: "r"(sb + tid * 1168), "l"((tid < 32 ? Bre : Bim) + (size_t)(32 * b + (tid & 31)) * DM), "r"(sb + GB_W) : "memory");
            float2 lam, coef;
            s5_channel(32 * b + 8 * w + g, Lre, Lim, logdt, lam, coef);
            float2 l32 = lam;
#pragma unroll
            for (int i = 0; i < 5; i++) l32 = make_float2(l32.x * l32.x - l32.y * l32.y, 2.f * l32.x * l32.y);
            __syncwarp();
            mbar_wait(sb + GB_W, 0);
            const uint32_t ap = sb + (((lane >> 3) & 1) * 32 + 8 * w + (lane & 7)) * 1168 + (lane >> 4) * 16;
#pragma unroll
            for (int ks = 0; ks < 36; ks++) { const uint4 v = ldsm4(ap + ks * 32); a[4 * ks] = v.x; a[4 * ks + 1] = v.y; a[4 * ks + 2] = v.z; a[4 * ks + 3] = v.w; }
            bar_sync(1, 256);
            bar_arrive(6, 288);
            BSTAMP(1);
#pragma unroll 1
            for (int blk = wg; blk < 16; blk += 2) {
                bg_mainloop<9, 2>(d, a, sb, (blk >> 1) * 18 + wg, lane);
                float2 e = make_float2(0.f, 0.f);
#pragma unroll
                for (int i = 0; i < 32; i++) e = cfma(lam, e, make_float2(d[4 * (i >> 1) + (i & 1)], d[4 * (i >> 1) + 2 + (i & 1)]));
                float2 cin = make_float2(0.f, 0.f);
                if (blk > 0) { bar_sync(2 + (wg ^ 1), 256); cin = lds64f(sb + G_CARRY + (wg ^ 1) * 256 + (8 * w + g) * 8); }
                float2 mine = cin;
#pragma unroll
                for (int q = 0; q < 4; q++) {
                    const float2 eq = make_float2(__shfl_sync(~0u, e.x, (lane & 28) + q), __shfl_sync(~0u, e.y, (lane & 28) + q));
                    cin = cfma(l32, cin, eq);
                    if (t == q + 1) mine = cin;
                }
                if (blk < 15) {
                    if (t == 0) sts64(sb + G_CARRY + wg * 256 + (8 * w + g) * 8, __float_as_uint(cin.x), __float_as_uint(cin.y));
                    bar_arrive(2 + wg, 256);
                }
                const uint32_t hs = sb + G_OUT + wg * 16384 + t * 4096 + (g & 3) * 4;
                const uint32_t ch = 2 * w + (g >> 2);
                if (blk >= 2) bar_sync(10 + wg, 160);
#pragma unroll
                for (int i = 0; i < 32; i++) {
                    mine = cfma(lam, mine, make_float2(d[4 * (i >> 1) + (i & 1)], d[4 * (i >> 1) + 2 + (i & 1)]));
                    sts32(hs + i * 128 + ((ch ^ (i & 7)) << 4), pack_bf16(mine.x, mine.y));
                }
                fence_async_smem();
                bar_arrive(8 + wg, 160);
            }
            bar_sync(10 + wg, 160);
        } else {
            if (tid < 128)
                asm volatile("cp.async.bulk.shared::cluster.global.mbarrier::complete_tx::bytes [%0], [%1], 1152, [%2];"
                    :: "r"(sb + tid * 1168), "l"((tid < 64 ? Cre : Cim) + (size_t)(64 * nt + (tid & 63)) * DM), "r"(sb + GB_W) : "memory");
            for (int p = tid; p < DM; p += 256) {
                float2 lam, coef;
                s5_channel(p, Lre, Lim, logdt, lam, coef);
                sts64(sb + G_EX + p * 8, __float_as_uint(2.f * coef.x), __float_as_uint(2.f * coef.y));
            }
            bar_sync(1, 256);
            mbar_wait(sb + GB_W, 0);
            const uint32_t cp = sb + (16 * w + 2 * g) * 1168 + (288 * wg + t) * 2;
#pragma unroll
            for (int u = 0; u < 72; u++) {
                const float2 c2 = lds64f(sb + G_EX + (288 * wg + 4 * u + t) * 8);
#pragma unroll
                for (int f = 0; f < 2; f++) {
                    unsigned short r16, i16;
                    asm volatile("ld.shared.u16 %0, [%1];" : "=h"(r16) : "r"(cp + f * 1168 + u * 8) : "memory");
                    asm volatile("ld.shared.u16 %0, [%1];" : "=h"(i16) : "r"(cp + (64 + f) * 1168 + u * 8) : "memory");
                    const float cr = __uint_as_float((uint32_t)r16 << 16), ci = __uint_as_float((uint32_t)i16 << 16);
                    a[2 * u + f] = pack_bf16(cr * c2.x - ci * c2.y, -(cr * c2.y + ci * c2.x));
                }
            }
            bar_sync(1, 256);
            bar_arrive(6, 288);
            BSTAMP(1);
#pragma unroll 1
            for (int j = 0; j < 8; j++) {
                bg_mainloop<9, 2>(d, a, sb, j * 18 + wg, lane);
                bg_epilogue<true>(d, sb, wg, w, lane, &tm_out, 64 * nt, (2 * j + kq - 2) * 128, xa, Dk);
            }
        }
        bar_sync(1, 256);
        BSTAMP(2);
        if (warp == 0)
            asm volatile("{\n.reg .pred p;\nelect.sync _|p, 0xffffffff;\n@p mbarrier.arrive.expect_tx.shared::cta.b64 _, [%2], 131072;\n"
                "@p cp.async.bulk.tensor.2d.shared::cluster.global.mbarrier::complete_tx::bytes [%0], [%1, {%3, %4}], [%2];\n"
                "@p cp.async.bulk.tensor.2d.shared::cluster.global.mbarrier::complete_tx::bytes [%0+32768], [%1, {%3, %5}], [%2];\n"
                "@p cp.async.bulk.tensor.2d.shared::cluster.global.mbarrier::complete_tx::bytes [%0+65536], [%1, {%3, %6}], [%2];\n"
                "@p cp.async.bulk.tensor.2d.shared::cluster.global.mbarrier::complete_tx::bytes [%0+98304], [%1, {%3, %7}], [%2];\n}"
                :: "r"(sb), "l"(&tm_wo), "r"(sb + GB_W), "r"(64 * nt), "r"(1024 * kq), "r"(1024 * kq + 256), "r"(1024 * kq + 512), "r"(1024 * kq + 768) : "memory");
        mbar_wait(sb + GB_W, 1);
        {
            const uint32_t base = sb + wg * 65536 + 4 * t * 128 + (g & 3) * 4, ch = 2 * w + (g >> 2), r7 = (4 * t) & 7;
#pragma unroll
            for (int ks = 0; ks < 32; ks++) {
                const uint32_t w0 = lds32(base + ks * 2048 + ((ch ^ r7) << 4)), w1 = lds32(base + ks * 2048 + 256 + ((ch ^ (r7 + 2)) << 4));
                const uint32_t w2 = lds32(base + ks * 2048 + 128 + ((ch ^ (r7 + 1)) << 4)), w3 = lds32(base + ks * 2048 + 384 + ((ch ^ (r7 + 3)) << 4));
                a[4 * ks] = __byte_perm(w0, w1, 0x5410); a[4 * ks + 1] = __byte_perm(w0, w1, 0x7632);
                a[4 * ks + 2] = __byte_perm(w2, w3, 0x5410); a[4 * ks + 3] = __byte_perm(w2, w3, 0x7632);
            }
        }
        bar_sync(1, 256);
        bar_arrive(6, 288);
        BSTAMP(3);
#pragma unroll 1
        for (int na = 0, ng = 0, it = 144; ng < 16;) {
            if (bg_att_turn(na, ng)) {
                if (nt < 8) {
                    const int i0 = it + wg + 4 * (w >> 1), i1 = i0 + 2;
                    mbar_wait(sb + GB_FULL + 8 * (i0 % NST), (i0 / NST) & 1);
                    mbar_wait(sb + GB_FULL + 8 * (i1 % NST), (i1 / NST) & 1);
                    BSTAMP(8 + na * 4);
                    bg_attention(sb + G_RING + (i0 % NST) * 16384, sb + G_RING + (i1 % NST) * 16384, w & 1, lane);
                    fence_async_smem();
                    bar_arrive(7, 288);
                    bar_sync(1, 256);
                    BSTAMP(9 + na * 4);
                    it += 8;
                }
                na++;
            } else {
                bg_mainloop<8, 2>(d, a, sb, it + wg, lane);
                BSTAMP(10 + ng * 4);
                bg_epilogue<false>(d, sb, wg, w, lane, &tm_out, DM + 64 * nt, ng * 128, xa, Dk);
                BSTAMP(11 + ng * 4);
                it += 16; ng++;
            }
        }
        if (w == 0) asm volatile("cp.async.bulk.wait_group 0;" ::: "memory");
    }
    asm volatile("griddepcontrol.wait;" ::: "memory");
}

typedef CUresult (*EncodeFn)(CUtensorMap*, CUtensorMapDataType, cuuint32_t, void*, const cuuint64_t*, const cuuint64_t*, const cuuint32_t*, const cuuint32_t*,
                             CUtensorMapInterleave, CUtensorMapSwizzle, CUtensorMapL2promotion, CUtensorMapFloatOOBfill);
}

extern "C" void kernel_launch(void* const* d_in, const int* in_sizes, int n_in, void* d_out, int out_size) {
    typedef const __nv_bfloat16* bp;
    bp Ax = (bp)d_in[0], Lre = (bp)d_in[1], Lim = (bp)d_in[2], Bre = (bp)d_in[3], Bim = (bp)d_in[4], Cre = (bp)d_in[5], Cim = (bp)d_in[6],
       logdt = (bp)d_in[7], Dk = (bp)d_in[8], Bx = (bp)d_in[9], mem0 = (bp)d_in[10], Wq = (bp)d_in[11], Wk = (bp)d_in[12], Wv = (bp)d_in[13], Wo = (bp)d_in[14];
    float* out = (float*)d_out;
    static EncodeFn enc = nullptr;
    if (!enc) {
        void* fn = nullptr; cudaDriverEntryPointQueryResult qr;
        cudaGetDriverEntryPoint("cuTensorMapEncodeTiled", &fn, cudaEnableDefault, &qr);
        enc = (EncodeFn)fn;
        cudaFuncSetAttribute(chain_kernel, cudaFuncAttributeMaxDynamicSharedMemorySize, CHAIN_SMEM);
        cudaFuncSetAttribute(bg_kernel, cudaFuncAttributeMaxDynamicSharedMemorySize, BG_SMEM);
    }
    const cuuint32_t es[5] = {1, 1, 1, 1, 1};
    auto map2d = [&](CUtensorMap* tm, CUtensorMapDataType dt, const void* p, cuuint64_t d0, cuuint64_t d1, cuuint64_t stride, cuuint32_t b0, cuuint32_t b1) {
        cuuint64_t gd[2] = {d0, d1}, gs[1] = {stride}; cuuint32_t bd[2] = {b0, b1};
        enc(tm, dt, 2, (void*)p, gd, gs, bd, es, CU_TENSOR_MAP_INTERLEAVE_NONE, CU_TENSOR_MAP_SWIZZLE_128B, CU_TENSOR_MAP_L2_PROMOTION_L2_128B,
            CU_TENSOR_MAP_FLOAT_OOB_FILL_NONE);
    };
    CUtensorMap tm_x, tm_q, tm_k, tm_v, tm_xa, tm_wo, tm_out;
    map2d(&tm_x, CU_TENSOR_MAP_DATA_TYPE_BFLOAT16, Bx, DM, SEQ, DM * 2, 64, 32);
    map2d(&tm_q, CU_TENSOR_MAP_DATA_TYPE_BFLOAT16, Wq, HD, DM, HD * 2, 64, 192);
    map2d(&tm_k, CU_TENSOR_MAP_DATA_TYPE_BFLOAT16, Wk, HD, DM, HD * 2, 64, 192);
    map2d(&tm_v, CU_TENSOR_MAP_DATA_TYPE_BFLOAT16, Wv, HD, DM, HD * 2, 64, 192);
    map2d(&tm_wo, CU_TENSOR_MAP_DATA_TYPE_BFLOAT16, Wo, DM, HD, DM * 2, 64, 256);
    map2d(&tm_out, CU_TENSOR_MAP_DATA_TYPE_FLOAT32, out, 2 * DM, SEQ, 2 * DM * 4, 32, 64);
    {
        cuuint64_t gd[5] = {DM, 2, 4, 16, 16}, gs[4] = {DM * 2, 32 * DM * 2, 2 * DM * 2, 128 * DM * 2}; cuuint32_t bd[5] = {64, 2, 4, 16, 1};
        enc(&tm_xa, CU_TENSOR_MAP_DATA_TYPE_BFLOAT16, 5, (void*)Ax, gd, gs, bd, es, CU_TENSOR_MAP_INTERLEAVE_NONE, CU_TENSOR_MAP_SWIZZLE_128B,
            CU_TENSOR_MAP_L2_PROMOTION_L2_128B, CU_TENSOR_MAP_FLOAT_OOB_FILL_NONE);
    }
    cudaStream_t st = cudaStreamPerThread;
    {
        cudaLaunchConfig_t cfg = {};
        cfg.gridDim = dim3(96); cfg.blockDim = dim3(384); cfg.dynamicSmemBytes = CHAIN_SMEM; cfg.stream = st;
        cudaLaunchAttribute at[1];
        at[0].id = cudaLaunchAttributeClusterDimension; at[0].val.clusterDim.y = 1; at[0].val.clusterDim.z = 1;
        cfg.attrs = at; cfg.numAttrs = 1;
        static int csize = 0;
        if (!csize) {
            int n = 0;
            at[0].val.clusterDim.x = 6;
            csize = (CLUSTER6 && cudaOccupancyMaxActiveClusters(&n, chain_kernel, &cfg) == cudaSuccess && n >= 16) ? 6 : 3;
            (void)cudaGetLastError();
        }
        at[0].val.clusterDim.x = csize;
        cudaLaunchKernelEx(&cfg, chain_kernel, tm_x, tm_q, tm_k, tm_v, Bx, mem0, Wo, out);
    }
    cudaLaunchConfig_t cfg = {};
    cfg.gridDim = dim3(36); cfg.blockDim = dim3(384); cfg.dynamicSmemBytes = BG_SMEM; cfg.stream = st;
    cudaLaunchAttribute at[1];
    at[0].id = cudaLaunchAttributeProgrammaticStreamSerialization; at[0].val.programmaticStreamSerializationAllowed = 1;
    cfg.attrs = at; cfg.numAttrs = 1;
    cudaLaunchKernelEx(&cfg, bg_kernel, tm_xa, tm_wo, tm_out, Ax, Lre, Lim, Bre, Bim, Cre, Cim, logdt, Dk);
}
```

```cpp
#include <cuda_runtime.h>
#include <cuda.h>
#include <cuda_bf16.h>
#include <cuda_fp16.h>
#include <stdint.h>

#define D_WAIT 700

#define CLUSTER6 0
#define BG_PACE 0
#define RED_GAP 720
#define BG_AHEAD 5

namespace {

constexpr int DM = 576, NH = 32, SEQ = 2048, NSEG = 64, HD = 4096;

__device__ uint4 g_acc[64 * 96 * 16];
__device__ uint4 g_ox[NH * 2 * SEQ * 8];
constexpr int REC = 30720;
__device__ uint4 g_qkv[NSEG * NH * (REC / 16)];
__device__ uint4 g_h[18 * SEQ * 8];
constexpr int NFLAG = 4096, F_QKV = 0, F_OX = 512, F_H = 1024, F_OUT = 2048;
__device__ unsigned g_flag[NFLAG];
__device__ unsigned g_ticket, g_ticket_bg;
__device__ unsigned long long g_norm[96];
#define BSTAMP(i) do {} while (0)

__device__ __forceinline__ uint32_t smem_u32(const void* p) { return (uint32_t)__cvta_generic_to_shared(p); }
__device__ __forceinline__ uint32_t mapa(uint32_t a, uint32_t r) { uint32_t o; asm("mapa.shared::cluster.u32 %0, %1, %2;" : "=r"(o) : "r"(a), "r"(r)); return o; }
__device__ __forceinline__ uint32_t mapa_v(uint32_t a, uint32_t r) { uint32_t o; asm volatile("mapa.shared::cluster.u32 %0, %1, %2;" : "=r"(o) : "r"(a), "r"(r)); return o; }
__device__ __forceinline__ unsigned clk() { unsigned long long c; asm volatile("mov.u64 %0, %%clock64;" : "=l"(c) :: "memory"); return (unsigned)c; }
__device__ __forceinline__ void mbar_init(uint32_t bar, uint32_t cnt) { asm volatile("mbarrier.init.shared::cta.b64 [%0], %1;" :: "r"(bar), "r"(cnt) : "memory"); }
__device__ __forceinline__ void mbar_expect(uint32_t bar, uint32_t bytes) { asm volatile("mbarrier.arrive.expect_tx.shared::cta.b64 _, [%0], %1;" :: "r"(bar), "r"(bytes) : "memory"); }
__device__ __forceinline__ void mbar_wait(uint32_t bar, uint32_t parity) {
    asm volatile("{\n.reg .pred p;\n.reg .u32 n;\nmov.u32 n, 0;\n"
                 "W_%=: mbarrier.try_wait.parity.shared::cta.b64 p, [%0], %1;\n@p bra.uni D_%=;\n"
                 "add.u32 n, n, 1;\nsetp.lt.u32 p, n, 4000000;\n@p bra.uni W_%=;\ntrap;\nD_%=:\n}" :: "r"(bar), "r"(parity) : "memory");
}
__device__ __forceinline__ void mbar_expect_if(uint32_t z, uint32_t bar, uint32_t bytes) {
    asm volatile("{\n.reg .pred p;\nsetp.eq.u32 p, %2, 0;\n@p mbarrier.arrive.expect_tx.shared::cta.b64 _, [%0], %1;\n}" :: "r"(bar), "r"(bytes), "r"(z) : "memory");
}
__device__ __forceinline__ void mbar_arrive_if(uint32_t z, uint32_t bar) {
    asm volatile("{\n.reg .pred p;\nsetp.eq.u32 p, %1, 0;\n@p mbarrier.arrive.shared::cta.b64 _, [%0];\n}" :: "r"(bar), "r"(z) : "memory");
}
__device__ __forceinline__ void sts32_if(uint32_t z, uint32_t a, uint32_t x) {
    asm volatile("{\n.reg .pred p;\nsetp.eq.u32 p, %2, 0;\n@p st.shared.u32 [%0], %1;\n}" :: "r"(a), "r"(x), "r"(z) : "memory");
}
template <int K> __device__ __forceinline__ void sched_fence(int v) {
    asm volatile("{\n.reg .pred p;\nsetp.ne.s32 p, %0, %1;\n@p bra.uni F_%=;\ntrap;\nF_%=:\n}" :: "r"(v), "n"(1000 + K) : "memory");
}
__device__ __forceinline__ void spin_until(unsigned t0, unsigned d) {
    asm volatile("{\n.reg .pred p;\n.reg .u64 c;\n.reg .u32 lo;\n"
                 "S_%=: mov.u64 c, %%clock64;\ncvt.u32.u64 lo, c;\nsub.u32 lo, lo, %0;\nsetp.lt.u32 p, lo, %1;\n@p bra.uni S_%=;\n}" :: "r"(t0), "r"(d) : "memory");
}
__device__ __forceinline__ void bar_sync(int id, int n) { asm volatile("bar.sync %0, %1;" :: "r"(id), "r"(n) : "memory"); }
__device__ __forceinline__ void bar_sync_sel(int sel, int id) {
    asm volatile("{\n.reg .pred p;\nsetp.eq.u32 p, %0, 0;\n@p bar.sync %1, %3;\n@!p bar.sync %2, %3;\n}" :: "r"(sel), "r"(id), "r"(id + 1), "n"(192) : "memory");
}
__device__ __forceinline__ void bar_arrive(int id, int n) { asm volatile("bar.arrive %0, %1;" :: "r"(id), "r"(n) : "memory"); }
__device__ __forceinline__ void fence_async_smem() { asm volatile("fence.proxy.async.shared::cta;" ::: "memory"); }
__device__ __forceinline__ uint32_t pack_bf16(float lo, float hi) { uint32_t r; asm("cvt.rn.bf16x2.f32 %0, %1, %2;" : "=r"(r) : "f"(hi), "f"(lo)); return r; }
__device__ __forceinline__ uint32_t pack_f16(float lo, float hi) { uint32_t r; asm("cvt.rn.f16x2.f32 %0, %1, %2;" : "=r"(r) : "f"(hi), "f"(lo)); return r; }
__device__ __forceinline__ uint32_t f16x2_to_bf16x2(uint32_t v) { float2 f = __half22float2(*reinterpret_cast<__half2*>(&v)); return pack_bf16(f.x, f.y); }
__device__ __forceinline__ float ex2(float x) { float y; asm("ex2.approx.ftz.f32 %0, %1;" : "=f"(y) : "f"(x)); return y; }
__device__ __forceinline__ float ex2v(float x) { float y; asm volatile("ex2.approx.ftz.f32 %0, %1;" : "=f"(y) : "f"(x)); return y; }
__device__ __forceinline__ uint32_t absmax2(uint32_t a, uint32_t b) {
    uint32_t r; asm("max.xorsign.abs.bf16x2 %0, %1, %2;" : "=r"(r) : "r"(a), "r"(b)); return r;
}
__device__ __forceinline__ uint32_t shl_v(uint32_t a, int n) { return a << n; }
__device__ __forceinline__ uint32_t max3u(uint32_t a, uint32_t b, uint32_t c) { return max(max(a, b), c); }
__device__ __forceinline__ uint4 lds128(uint32_t a) { uint4 v; asm volatile("ld.shared.v4.u32 {%0,%1,%2,%3}, [%4];" : "=r"(v.x), "=r"(v.y), "=r"(v.z), "=r"(v.w) : "r"(a) : "memory"); return v; }
__device__ __forceinline__ uint4 lds128v(uint32_t a) { uint4 v; asm volatile("ld.volatile.shared.v4.u32 {%0,%1,%2,%3}, [%4];" : "=r"(v.x), "=r"(v.y), "=r"(v.z), "=r"(v.w) : "r"(a) : "memory"); return v; }
__device__ __forceinline__ float4 lds128f(uint32_t a) { float4 v; asm volatile("ld.shared.v4.f32 {%0,%1,%2,%3}, [%4];" : "=f"(v.x), "=f"(v.y), "=f"(v.z), "=f"(v.w) : "r"(a) : "memory"); return v; }
__device__ __forceinline__ float2 lds64f(uint32_t a) { float2 v; asm volatile("ld.shared.v2.f32 {%0,%1}, [%2];" : "=f"(v.x), "=f"(v.y) : "r"(a) : "memory"); return v; }
__device__ __forceinline__ uint4 lds64x2(uint32_t a) { uint4 v; asm volatile("ld.shared.v2.u32 {%0,%1}, [%4];\nld.shared.v2.u32 {%2,%3}, [%4+256];" : "=r"(v.x), "=r"(v.y), "=r"(v.z), "=r"(v.w) : "r"(a) : "memory"); return v; }
__device__ __forceinline__ uint32_t lds32(uint32_t a) { uint32_t v; asm volatile("ld.shared.u32 %0, [%1];" : "=r"(v) : "r"(a) : "memory"); return v; }
__device__ __forceinline__ void sts128(uint32_t a, uint32_t x, uint32_t y, uint32_t z, uint32_t w) { asm volatile("st.shared.v4.u32 [%0], {%1,%2,%3,%4};" :: "r"(a), "r"(x), "r"(y), "r"(z), "r"(w) : "memory"); }
__device__ __forceinline__ void sts128f(uint32_t a, float x, float y, float z, float w) { asm volatile("st.shared.v4.f32 [%0], {%1,%2,%3,%4};" :: "r"(a), "f"(x), "f"(y), "f"(z), "f"(w) : "memory"); }
__device__ __forceinline__ void sts64(uint32_t a, uint32_t x, uint32_t y) { asm volatile("st.shared.v2.u32 [%0], {%1,%2};" :: "r"(a), "r"(x), "r"(y) : "memory"); }
__device__ __forceinline__ void sts32(uint32_t a, uint32_t x) { asm volatile("st.shared.u32 [%0], %1;" :: "r"(a), "r"(x) : "memory"); }
__device__ __forceinline__ uint4 ldsm4(uint32_t a) { uint4 v; asm volatile("ldmatrix.sync.aligned.m8n8.x4.shared.b16 {%0,%1,%2,%3}, [%4];" : "=r"(v.x), "=r"(v.y), "=r"(v.z), "=r"(v.w) : "r"(a) : "memory"); return v; }
__device__ __forceinline__ void stsm2t(uint32_t a, uint32_t x, uint32_t y) { asm volatile("stmatrix.sync.aligned.m8n8.x2.trans.shared.b16 [%0], {%1,%2};" :: "r"(a), "r"(x), "r"(y) : "memory"); }
__device__ __forceinline__ void stsm4t(uint32_t a, uint32_t x, uint32_t y, uint32_t z, uint32_t w) { asm volatile("stmatrix.sync.aligned.m8n8.x4.trans.shared.b16 [%0], {%1,%2,%3,%4};" :: "r"(a), "r"(x), "r"(y), "r"(z), "r"(w) : "memory"); }
__device__ __forceinline__ void st_async64(uint32_t a, uint32_t x, uint32_t y, uint32_t bar) { asm volatile("st.async.shared::cluster.mbarrier::complete_tx::bytes.v2.b32 [%0], {%1,%2}, [%3];" :: "r"(a), "r"(x), "r"(y), "r"(bar) : "memory"); }
__device__ __forceinline__ void bulk_s2c(uint32_t dst, uint32_t src, uint32_t bytes, uint32_t bar) { asm volatile("cp.async.bulk.shared::cluster.shared::cta.mbarrier::complete_tx::bytes [%0], [%1], %2, [%3];" :: "r"(dst), "r"(src), "r"(bytes), "r"(bar) : "memory"); }
__device__ __forceinline__ void bulk_s2g(void* dst, uint32_t src, uint32_t bytes) { asm volatile("cp.async.bulk.global.shared::cta.bulk_group [%0], [%1], %2;" :: "l"(dst), "r"(src), "r"(bytes) : "memory"); }
__device__ __forceinline__ uint32_t ldg_nc32(const void* p) { uint32_t v; asm volatile("ld.global.nc.L2::128B.u32 %0, [%1];" : "=r"(v) : "l"(p)); return v; }
__device__ __forceinline__ uint4 ldg_relaxed128(const void* p) { uint4 v; asm volatile("ld.relaxed.gpu.global.v4.u32 {%0,%1,%2,%3}, [%4];" : "=r"(v.x), "=r"(v.y), "=r"(v.z), "=r"(v.w) : "l"(p) : "memory"); return v; }
__device__ __forceinline__ void mma16816(float (&d)[4], uint32_t a0, uint32_t a1, uint32_t a2, uint32_t a3, uint32_t b0, uint32_t b1) {
    asm volatile("mma.sync.aligned.m16n8k16.row.col.f32.bf16.bf16.f32 {%0,%1,%2,%3}, {%4,%5,%6,%7}, {%8,%9}, {%0,%1,%2,%3};"
        : "+f"(d[0]), "+f"(d[1]), "+f"(d[2]), "+f"(d[3]) : "r"(a0), "r"(a1), "r"(a2), "r"(a3), "r"(b0), "r"(b1));
}
__device__ __forceinline__ void mma16816_z(float (&d)[4], uint32_t a0, uint32_t a1, uint32_t a2, uint32_t a3, uint32_t b0, uint32_t b1) {
    asm volatile("mma.sync.aligned.m16n8k16.row.col.f32.bf16.bf16.f32 {%0,%1,%2,%3}, {%4,%5,%6,%7}, {%8,%9}, {%10,%10,%10,%10};"
        : "=f"(d[0]), "=f"(d[1]), "=f"(d[2]), "=f"(d[3]) : "r"(a0), "r"(a1), "r"(a2), "r"(a3), "r"(b0), "r"(b1), "f"(0.f));
}
__device__ __forceinline__ void mma1688(float (&d)[4], uint32_t a0, uint32_t a1, uint32_t b0) {
    asm volatile("mma.sync.aligned.m16n8k8.row.col.f32.bf16.bf16.f32 {%0,%1,%2,%3}, {%4,%5}, {%6}, {%0,%1,%2,%3};"
        : "+f"(d[0]), "+f"(d[1]), "+f"(d[2]), "+f"(d[3]) : "r"(a0), "r"(a1), "r"(b0));
}
__device__ __forceinline__ void mma1688_z(float (&d)[4], uint32_t a0, uint32_t a1, uint32_t b0) {
    asm volatile("mma.sync.aligned.m16n8k8.row.col.f32.bf16.bf16.f32 {%0,%1,%2,%3}, {%4,%5}, {%6}, {%7,%7,%7,%7};"
        : "=f"(d[0]), "=f"(d[1]), "=f"(d[2]), "=f"(d[3]) : "r"(a0), "r"(a1), "r"(b0), "f"(0.f));
}
template <int ACC>
__device__ __forceinline__ void wgmma_n32_rs(float (&d)[16], uint32_t a0, uint32_t a1, uint32_t a2, uint32_t a3, uint64_t desc) {
    asm volatile("wgmma.mma_async.sync.aligned.m64n32k16.f32.bf16.bf16 {%0,%1,%2,%3,%4,%5,%6,%7,%8,%9,%10,%11,%12,%13,%14,%15}, {%16,%17,%18,%19}, %20, %21, 1, 1, 0;"
        : "+f"(d[0]), "+f"(d[1]), "+f"(d[2]), "+f"(d[3]), "+f"(d[4]), "+f"(d[5]), "+f"(d[6]), "+f"(d[7]),
          "+f"(d[8]), "+f"(d[9]), "+f"(d[10]), "+f"(d[11]), "+f"(d[12]), "+f"(d[13]), "+f"(d[14]), "+f"(d[15])
        : "r"(a0), "r"(a1), "r"(a2), "r"(a3), "l"(desc), "n"(ACC));
}
template <int ACC>
__device__ __forceinline__ void wgmma_n32_ss(float (&d)[16], uint64_t da, uint64_t db) {
    asm volatile("wgmma.mma_async.sync.aligned.m64n32k16.f32.bf16.bf16 {%0,%1,%2,%3,%4,%5,%6,%7,%8,%9,%10,%11,%12,%13,%14,%15}, %16, %17, %18, 1, 1, 0, 0;"
        : "+f"(d[0]), "+f"(d[1]), "+f"(d[2]), "+f"(d[3]), "+f"(d[4]), "+f"(d[5]), "+f"(d[6]), "+f"(d[7]),
          "+f"(d[8]), "+f"(d[9]), "+f"(d[10]), "+f"(d[11]), "+f"(d[12]), "+f"(d[13]), "+f"(d[14]), "+f"(d[15])
        : "l"(da), "l"(db), "n"(ACC));
}
__device__ __forceinline__ void wg_fence() { asm volatile("wgmma.fence.sync.aligned;" ::: "memory"); }
__device__ __forceinline__ void wg_commit() { asm volatile("wgmma.commit_group.sync.aligned;" ::: "memory"); }
__device__ __forceinline__ void wg_wait0() { asm volatile("wgmma.wait_group.sync.aligned 0;" ::: "memory"); }
__device__ __forceinline__ void cluster_sync() { asm volatile("barrier.cluster.arrive.aligned;\nbarrier.cluster.wait.aligned;" ::: "memory"); }

#define STAMP(s, i) do {} while (0)
#define STAMPV(s, i, v) do {} while (0)

constexpr int XT_BYTES = 36864;
constexpr int O_XT = 0;
constexpr int O_STG = XT_BYTES;
constexpr int O_AS = 3 * XT_BYTES;
constexpr int O_XP = O_AS + 16384;
constexpr int O_QKX = O_XP + 8192;
constexpr int O_KM = O_QKX + 8192;
constexpr int O_QM = O_QKX + 10240;
constexpr int O_VX = O_STG + 147456;
constexpr int O_VM = O_VX + 16384;
constexpr int O_SC = O_VM + 2048;
constexpr int O_OF = O_SC + 2560;
constexpr int O_AF = O_OF + 2048;
constexpr int O_WP = O_AF + 4096;
constexpr int O_MF = O_WP + 2048;
constexpr int O_MISC = O_MF + 9216;
static_assert(O_QKX + 24576 <= O_VX, "smem");
constexpr int O_BAR = O_MISC + 64;
constexpr int CHAIN_SMEM = O_BAR + 128;
static_assert(CHAIN_SMEM <= 232448, "smem");
constexpr int B_X = O_BAR, B_VX = O_BAR + 24, B_SC = O_BAR + 40, B_W = O_BAR + 48;
constexpr float SM_SCALE = 0.08838834764831845f * 1.4426950408889634f;
constexpr uint32_t ONES = 0x3f803f80u;

__device__ __forceinline__ uint32_t opaque(uint32_t v) { uint32_t o; asm volatile("mov.u32 %0, %1;" : "=r"(o) : "r"(v)); return o; }
__device__ __forceinline__ void st_async128(uint32_t a, uint32_t x, uint32_t y, uint32_t z, uint32_t w, uint32_t bar) {
    asm volatile("st.async.shared::cluster.mbarrier::complete_tx::bytes.v4.b32 [%0], {%1,%2,%3,%4}, [%5];" :: "r"(a), "r"(x), "r"(y), "r"(z), "r"(w), "r"(bar) : "memory");
}
__device__ __forceinline__ void tma_x_tile(uint32_t sb, const CUtensorMap* tm, int rb, int r, int j, int slot) {
    asm volatile("{\n.reg .pred p;\nelect.sync _|p, 0xffffffff;\n"
        "@p mbarrier.arrive.expect_tx.shared::cta.b64 _, [%2], 36864;\n"
        "@p cp.async.bulk.tensor.2d.shared::cluster.global.mbarrier::complete_tx::bytes.multicast::cluster [%0], [%1, {%3, %4}], [%2], %7;\n"
        "@p cp.async.bulk.tensor.2d.shared::cluster.global.mbarrier::complete_tx::bytes.multicast::cluster [%0+4096], [%1, {%5, %4}], [%2], %7;\n"
        "@p cp.async.bulk.tensor.2d.shared::cluster.global.mbarrier::complete_tx::bytes.multicast::cluster [%0+8192], [%1, {%6, %4}], [%2], %7;\n}"
        :: "r"(sb + O_XT + slot * XT_BYTES + 3 * r * 4096), "l"(tm), "r"(sb + B_X + 8 * slot), "r"(192 * r), "r"(j * 32), "r"(192 * r + 64), "r"(192 * r + 128),
           "h"((unsigned short)(7 << rb)) : "memory");
}
__device__ __forceinline__ float quad_max(float v) {
    const float a = __shfl_xor_sync(~0u, v, 1), b = __shfl_xor_sync(~0u, v, 2), c = __shfl_xor_sync(~0u, v, 3);
    return fmaxf(fmaxf(v, a), fmaxf(b, c));
}
__device__ __forceinline__ void load_scores(float (&p)[10], uint32_t base, uint32_t stride, uint32_t l16) {
    const float4 a0 = lds128f(base + l16), b0 = lds128f(base + stride + l16);
    const float4 a1 = lds128f(base + 512 + l16), b1 = lds128f(base + stride + 512 + l16);
    const float2 a2 = lds64f(base + 1024 + (l16 >> 1)), b2 = lds64f(base + stride + 1024 + (l16 >> 1));
    p[0] = a2.x + b2.x; p[1] = a2.y + b2.y;
    p[2] = a0.x + b0.x; p[3] = a0.y + b0.y; p[4] = a0.z + b0.z; p[5] = a0.w + b0.w;
    p[6] = a1.x + b1.x; p[7] = a1.y + b1.y; p[8] = a1.z + b1.z; p[9] = a1.w + b1.w;
}
__device__ __forceinline__ float rcp_fast(float x) { float y; asm("rcp.approx.ftz.f32 %0, %1;" : "=f"(y) : "f"(x)); return y; }

__global__ void __launch_bounds__(384, 1)
chain_kernel(const __grid_constant__ CUtensorMap tm_x, const __grid_constant__ CUtensorMap tm_q,
             const __grid_constant__ CUtensorMap tm_k, const __grid_constant__ CUtensorMap tm_v,
             const __nv_bfloat16* __restrict__ x, const __nv_bfloat16* __restrict__ mem0,
             const __nv_bfloat16* __restrict__ Wo) {
    extern __shared__ __align__(1024) uint8_t smem_raw[];
    const uint32_t sb = smem_u32(smem_raw);
    const int lane = threadIdx.x & 31;
    const int warp = __shfl_sync(~0u, threadIdx.x >> 5, 0);
    const int wg = warp >> 2, w = warp & 3;
    const int h = blockIdx.x / 3, r = blockIdx.x - 3 * h;
    int rb;
    asm("mov.u32 %0, %%cluster_ctarank;" : "=r"(rb));
    rb -= r;

#define PSTAMP(i) do {} while (0)
    if (threadIdx.x == 0) {
        if (sb & 1023u) __trap();
        for (int i = 0; i < 9; i++) mbar_init(sb + O_BAR + 8 * i, 1);
        asm volatile("fence.mbarrier_init.release.cluster;" ::: "memory");
        for (int i = 0; i < 3; i++) {
            mbar_expect(sb + B_W + 8 * i, 49152);
            for (int tl = 0; tl < 2; tl++)
                asm volatile("cp.async.bulk.tensor.2d.shared::cluster.global.mbarrier::complete_tx::bytes [%0], [%1, {%3, %4}], [%2];"
                    :: "r"(sb + O_STG + tl * 73728 + i * 24576), "l"(r < 2 ? (tl ? &tm_k : &tm_q) : &tm_v), "r"(sb + B_W + 8 * i),
                       "r"(h * 128 + 64 * (r < 2 ? r : tl)), "r"(192 * i) : "memory");
        }
    }
    __syncwarp();
    asm volatile("barrier.cluster.arrive.relaxed.aligned;" ::: "memory");
    asm volatile("griddepcontrol.launch_dependents;" ::: "memory");
    if (warp == 0) PSTAMP(9);
    const uint32_t l16c = __shfl_sync(~0u, lane * 16, lane);

    if (wg < 2) {
#define KS(u) ((u) < 8 ? ((u) >> 1) + 4 * ((u) & 1) : (u) < 12 ? (u) : (u) < 20 ? 12 + (((u) - 12) >> 1) + 4 * ((u) & 1) : (u) < 24 ? (u) : (u) + 8)
        asm volatile("setmaxnreg.inc.sync.aligned.u32 184;");
        uint32_t a[144];
        uint32_t adr1;
        {
            const int g = lane >> 2, t = lane & 3;
            const int t1 = threadIdx.x;
#pragma unroll
            for (int i = 0; i < 2; i++) g_acc[(blockIdx.x * 64 + i * 32 + (t1 >> 3)) * 16 + (t1 & 7)] = make_uint4(0, 0, 0, 0);
            __threadfence();
            asm volatile("barrier.cluster.wait.aligned;" ::: "memory");
            const uint32_t ev = sb + O_STG + (2 * t) * 128 + (((2 * w + (g >> 2)) ^ (2 * t)) << 4) + (g & 3) * 4;
            const uint32_t od = (ev ^ 16) + 128;
            auto gather = [&](int dst, uint32_t off) {
                a[dst] = lds32(ev + off); a[dst + 1] = lds32(od + off); a[dst + 2] = lds32(ev + off + 1024); a[dst + 3] = lds32(od + off + 1024);
            };
            mbar_wait(sb + B_W, 0);
#pragma unroll
            for (int u = 8; u < 12; u++) gather(32 + 4 * u, wg * 73728 + KS(u) * 2048);
            mbar_wait(sb + B_W + 8, 0);
            const uint4* xp = reinterpret_cast<const uint4*>(x) + blockIdx.x * 1536 + t1;
            uint4 xv[6];
#pragma unroll
            for (int i = 0; i < 6; i++) xv[i] = __ldg(xp + i * 256);
#pragma unroll
            for (int u = 12; u < 24; u++) gather(32 + 4 * u, wg * 73728 + KS(u) * 2048);
            mbar_wait(sb + B_W + 16, 0);
#pragma unroll
            for (int u = 24; u < 28; u++) gather(32 + 4 * u, wg * 73728 + KS(u) * 2048);
#pragma unroll
            for (int u = 0; u < 8; u++) {
                gather(32 + 4 * u, wg * (73728 + 49152) + KS(u) * 2048);
                gather(4 * u, 73728 - wg * (73728 - 49152) + KS(u) * 2048);
            }
#pragma unroll
            for (int kk = 0; kk < 72; kk++) {
                uint32_t w0 = a[2 * kk], w1 = a[2 * kk + 1];
                a[2 * kk] = __byte_perm(w0, w1, 0x5410);
                a[2 * kk + 1] = __byte_perm(w0, w1, 0x7632);
            }
            if (r == 2) {
                float n0[4], n1[4];
#pragma unroll
                for (int u = 0; u < 36; u++) {
                    const uint32_t x0 = a[4 * u] & 0x7fff7fffu, x1 = a[4 * u + 1] & 0x7fff7fffu, x2 = a[4 * u + 2] & 0x7fff7fffu, x3 = a[4 * u + 3] & 0x7fff7fffu;
                    if (u == 0) mma16816_z(n0, x0, x1, x2, x3, ONES, ONES);
                    else if (u < 8) mma16816(n0, x0, x1, x2, x3, ONES, ONES);
                    else if (u == 8) mma16816_z(n1, x0, x1, x2, x3, ONES, ONES);
                    else mma16816(n1, x0, x1, x2, x3, ONES, ONES);
                }
                const uint32_t mx = __reduce_max_sync(~0u, __float_as_uint(2.f * fmaxf(fmaxf(n0[0], n0[2]), fmaxf(n1[0], n1[2]))));
                sts32_if(lane, sb + O_MISC + 32 + 4 * warp, mx);
            }
            uint32_t xm = 0;
#pragma unroll
            for (int i = 0; i < 6; i++)
                xm = __vmaxu2(xm, __vmaxu2(__vmaxu2(xv[i].x & 0x7fff7fffu, xv[i].y & 0x7fff7fffu), __vmaxu2(xv[i].z & 0x7fff7fffu, xv[i].w & 0x7fff7fffu)));
            sts32_if(lane, sb + O_OF + 16 + 4 * warp, __reduce_max_sync(~0u, max(xm << 16, xm & 0xffff0000u)));
            if (warp == 0) PSTAMP(11);
            bar_arrive(7, 384);
            asm volatile("barrier.cluster.arrive.relaxed.aligned;" ::: "memory");
            bar_sync(1, 256);
            const uint32_t as = sb + O_AS + wg * 8192 + (16 * w + g) * 128 + t * 4;
            sts32(as + (g << 4), a[32]);
            sts32(as + 1024 + (g << 4), a[33]);
            sts32(as + ((1 ^ g) << 4), a[34]);
            sts32(as + 1024 + ((1 ^ g) << 4), a[35]);
            sts128(sb + O_AF + warp * 512 + lane * 16, a[32], a[33], a[34], a[35]);
            fence_async_smem();
            bar_sync(1, 256);
            const uint32_t l = lane * 16;
            const int mi = lane >> 3, isk = (mi >> 1) ? wg : (wg ^ 1);
            adr1 = (r == 2) ? (sb + O_VM + warp * 256 + (l >> 1))
                            : (isk ? (sb + O_KM + w * 512 + wg * 256 + (mi & 1) * 128 + (l & 127))
                                   : (sb + O_QM + w * 512 + (mi & 1) * 256 + wg * 128 + (l & 127)));
            adr1 = __shfl_sync(~0u, adr1, lane);
        }
        int s3 = 2;
#pragma unroll 1
        for (int s = -1; s < NSEG; s++) {
            const uint32_t l16 = opaque(l16c);
            s3 = (s3 == 2) ? 0 : s3 + 1;
            if (s < 0) mbar_wait(sb + B_X, 0);
            const uint64_t desc0 = (uint64_t)(((sb + O_XT + s3 * XT_BYTES) & 0x3FFFF) >> 4) | (1ull << 16) | (64ull << 32) | (1ull << 62);
            uint32_t km0 = 0, km1 = 0;
            if (s >= 0) {
                { const uint4 v = lds128(sb + O_AF + warp * 512 + l16); a[32] = v.x; a[33] = v.y; a[34] = v.z; a[35] = v.w; }
                float co[4], cw[3][4];
                uint4 b[14];
                float inv;
#define GORD(i) ((i) == 0 ? 0 : (i) == 1 ? 1 : (i) == 5 ? 2 : (i) == 9 ? 3 : (i) < 5 ? (i) + 2 : (i) < 9 ? (i) + 1 : (i))
                auto qkv_mma = [&](int i) {
                    const int gi = GORD(i), u = 8 * gi, n0 = 2 * i, n1 = 2 * i + 1;
                    if (gi < 4) {
                        if (i == 0) mma16816_z(co, a[u], a[u + 1], a[u + 2], a[u + 3], b[0].x, b[0].y);
                        else mma16816(co, a[u], a[u + 1], a[u + 2], a[u + 3], b[i].x, b[i].y);
                    }
                    if (n0 < 3) mma16816_z(cw[n0 % 3], a[32 + u], a[32 + u + 1], a[32 + u + 2], a[32 + u + 3], b[i].x, b[i].y);
                    else mma16816(cw[n0 % 3], a[32 + u], a[32 + u + 1], a[32 + u + 2], a[32 + u + 3], b[i].x, b[i].y);
                    if (n1 < 3) mma16816_z(cw[n1 % 3], a[32 + u + 4], a[32 + u + 5], a[32 + u + 6], a[32 + u + 7], b[i].z, b[i].w);
                    else mma16816(cw[n1 % 3], a[32 + u + 4], a[32 + u + 5], a[32 + u + 6], a[32 + u + 7], b[i].z, b[i].w);
                    if (gi < 4) mma16816(co, a[u + 4], a[u + 5], a[u + 6], a[u + 7], b[i].z, b[i].w);
                };
                const uint32_t mf = sb + O_MF + l16, mfs = mf + wg * 6144;
                const uint32_t qb = (s & 1) * 12288;
                bar_sync(2, 384);
                if (warp == 0) STAMP(s, 0);
                auto qkv_ld = [&](int i) { b[i] = GORD(i) < 4 ? lds128v(mfs + GORD(i) * 512) : lds128v(mf + (GORD(i) < 12 ? GORD(i) : GORD(i) + 4) * 512); };
#pragma unroll
                for (int i = 0; i < 5; i++) qkv_ld(i);
#pragma unroll
                for (int i = 0; i < 4; i++) { qkv_mma(i); qkv_ld(5 + i); }
#pragma unroll
                for (int i = 4; i < 9; i++) { qkv_mma(i); qkv_ld(5 + i); }
                inv = __uint_as_float(lds32(sb + O_MISC));
#pragma unroll
                for (int i = 9; i < 14; i++) qkv_mma(i);
#pragma unroll
                for (int i = 0; i < 4; i++) cw[0][i] += cw[1][i] + cw[2][i];
                if (r < 2) {
                    const uint32_t o0 = pack_bf16(co[0] * inv, co[1] * inv), o1 = pack_bf16(co[2] * inv, co[3] * inv);
                    const uint32_t w0 = pack_bf16(cw[0][0] * inv, cw[0][1] * inv), w1 = pack_bf16(cw[0][2] * inv, cw[0][3] * inv);
                    stsm4t(adr1 + qb, o0, o1, w0, w1);
                    if (warp == 0) STAMP(s, 1);
                    asm volatile("{\n.reg .pred p;\nsetp.ge.u32 p, %0, 3;\n@p bar.arrive 1, 256;\n}" :: "r"(warp) : "memory");
                    if (warp < 3 && s < NSEG - 1) {
                        uint4 q[4], k[4];
                        const uint32_t ka = sb + O_QKX + 4096 + qb + warp * 2048 + l16;
#pragma unroll
                        for (int i = 0; i < 4; i++) k[i] = ldsm4(ka + i * 512);
                        const uint32_t dst = sb + O_SC + r * 1280 + warp * 512 + (l16 >> 1);
                        bar_sync(1, 256);
#pragma unroll
                        for (int i = 0; i < 4; i++) q[i] = ldsm4(sb + O_QM + qb + i * 512 + l16);
                        if (warp == 2) {
#pragma unroll
                            for (int i = 0; i < 4; i++) k[i] = ldsm4(ka + i * 512);
                        }
                        float s0[4], s1[4], t0[4], t1[4];
                        mma16816_z(s0, q[0].x, q[0].y, q[0].z, q[0].w, k[0].x, k[0].y);
                        mma16816_z(s1, q[0].x, q[0].y, q[0].z, q[0].w, k[0].z, k[0].w);
                        mma16816_z(t0, q[1].x, q[1].y, q[1].z, q[1].w, k[1].x, k[1].y);
                        mma16816_z(t1, q[1].x, q[1].y, q[1].z, q[1].w, k[1].z, k[1].w);
                        mma16816(s0, q[2].x, q[2].y, q[2].z, q[2].w, k[2].x, k[2].y);
                        mma16816(s1, q[2].x, q[2].y, q[2].z, q[2].w, k[2].z, k[2].w);
                        mma16816(t0, q[3].x, q[3].y, q[3].z, q[3].w, k[3].x, k[3].y);
                        mma16816(t1, q[3].x, q[3].y, q[3].z, q[3].w, k[3].z, k[3].w);
                        const float v0 = (s0[0] + s0[2]) + (t0[0] + t0[2]), v1 = (s0[1] + s0[3]) + (t0[1] + t0[3]);
                        const float v2 = (s1[0] + s1[2]) + (t1[0] + t1[2]), v3 = (s1[1] + s1[3]) + (t1[1] + t1[3]);
                        if (warp < 2) {
                            const uint32_t dv = dst + (l16 >> 1);
                            st_async128(mapa(dv, rb + (2)), __float_as_uint(v0), __float_as_uint(v1), __float_as_uint(v2), __float_as_uint(v3), mapa(sb + B_SC, rb + (2)));
                            st_async128(mapa(dv, rb + (r ^ 1)), __float_as_uint(v0), __float_as_uint(v1), __float_as_uint(v2), __float_as_uint(v3), mapa(sb + B_SC, rb + (r ^ 1)));
                            st_async128(mapa(dv, rb + (r)), __float_as_uint(v0), __float_as_uint(v1), __float_as_uint(v2), __float_as_uint(v3), mapa(sb + B_SC, rb + (r)));
                        } else {
                            st_async64(mapa(dst, rb + (2)), __float_as_uint(v0 + v2), __float_as_uint(v1 + v3), mapa(sb + B_SC, rb + (2)));
                            st_async64(mapa(dst, rb + (r ^ 1)), __float_as_uint(v0 + v2), __float_as_uint(v1 + v3), mapa(sb + B_SC, rb + (r ^ 1)));
                            st_async64(mapa(dst, rb + (r)), __float_as_uint(v0 + v2), __float_as_uint(v1 + v3), mapa(sb + B_SC, rb + (r)));
                        }
                        if (warp == 2) STAMP(s, 2);
                    } else if (warp < 3) {
                        bar_sync(1, 256);
                    }
                } else {
                    sts128f(sb + O_XP + warp * 512 + l16, co[0], co[1], co[2], co[3]);
                    bar_sync(8 + w, 64);
                    const float4 o = lds128f(sb + O_XP + (warp ^ 4) * 512 + l16);
                    km0 = pack_bf16((cw[0][0] + o.x) * inv, (cw[0][1] + o.y) * inv);
                    km1 = pack_bf16((cw[0][2] + o.z) * inv, (cw[0][3] + o.w) * inv);
                    if (warp == 0) STAMP(s, 1);
                    if (s < NSEG - 1) {
                        st_async64(mapa(adr1, rb + (0)), km0, km1, mapa(sb + B_SC, rb + (0)));
                        st_async64(mapa(adr1, rb + (1)), km0, km1, mapa(sb + B_SC, rb + (1)));
                        st_async64(mapa(adr1, rb + (2)), km0, km1, mapa(sb + B_SC, rb + (2)));
                    }
                    if (warp == 0) STAMP(s, 2);
                }
            }
            char* rec = reinterpret_cast<char*>(g_qkv) + (size_t)(s * NH + h) * REC;
            auto store_qk = [&]() {
                asm volatile("{\n.reg .pred p;\nelect.sync _|p, 0xffffffff;\n"
                    "@p cp.async.bulk.global.shared::cta.bulk_group [%0], [%1], 10240;\n@p cp.async.bulk.commit_group;\n}"
                    :: "l"(rec + r * 10240), "r"(sb + O_QKX + (s & 1) * 12288) : "memory");
            };
            auto store_vm = [&]() { *reinterpret_cast<uint2*>(rec + 28672 + warp * 256 + (l16 >> 1)) = make_uint2(km0, km1); };
            if (s == NSEG - 1) fence_async_smem();
            if (s >= 0) bar_sync(3, 384);
            if (s == NSEG - 1) {
                if (r == 2) store_vm();
                else if (warp == 3) {
                    store_qk();
                    asm volatile("cp.async.bulk.wait_group 0;\nfence.proxy.async.global;" ::: "memory");
                }
            } else {
                const int j = s + 1;
#define XDESC(u) (((u) < 8 ? descs : desc0) + (uint64_t)(((KS(u) >> 2) * 4096 + (KS(u) & 3) * 32) >> 4))
                const uint64_t descs = desc0 + (uint64_t)(wg * (6 * 4096 >> 4));
                float d[16];
                wg_fence();
#pragma unroll
                for (int u = 0; u < 8; u++) {
                    if (u == 0) wgmma_n32_rs<0>(d, a[0], a[1], a[2], a[3], XDESC(0));
                    else wgmma_n32_rs<1>(d, a[4 * u], a[4 * u + 1], a[4 * u + 2], a[4 * u + 3], XDESC(u));
                }
                wg_commit();
                wg_wait0();
                if (warp == 0) STAMP(s, 15);
                if (s >= 0) bar_sync(4, 384);
#pragma unroll
                for (int q = 0; q < 2; q++)
                    sts128(sb + O_XP + warp * 1024 + q * 512 + l16, pack_bf16(d[8 * q], d[8 * q + 1]), pack_bf16(d[8 * q + 2], d[8 * q + 3]),
                           pack_bf16(d[8 * q + 4], d[8 * q + 5]), pack_bf16(d[8 * q + 6], d[8 * q + 7]));
                if (s >= 0) {
                    if (r == 2) store_vm();
                    else fence_async_smem();
                    if (warp == 3) asm volatile("cp.async.bulk.wait_group 0;\nfence.proxy.async.global;" ::: "memory");
                    if (warp == 1 && s + 2 < NSEG) tma_x_tile(sb, &tm_x, rb, r, s + 2, s3 == 2 ? 0 : s3 + 1);
                }
                bar_sync(12, 256);
#pragma unroll
                for (int q = 0; q < 2; q++) {
                    const uint4 o = lds128(sb + O_XP + (warp ^ 4) * 1024 + q * 512 + l16);
                    d[8 * q] = __uint_as_float(o.x << 16); d[8 * q + 1] = __uint_as_float(o.x & 0xffff0000u);
                    d[8 * q + 2] = __uint_as_float(o.y << 16); d[8 * q + 3] = __uint_as_float(o.y & 0xffff0000u);
                    d[8 * q + 4] = __uint_as_float(o.z << 16); d[8 * q + 5] = __uint_as_float(o.z & 0xffff0000u);
                    d[8 * q + 6] = __uint_as_float(o.w << 16); d[8 * q + 7] = __uint_as_float(o.w & 0xffff0000u);
                }
                if (s >= 0) {
                    if (warp == 6 && (s & 3) == 0 && s >= 4)
                        asm volatile("{\n.reg .pred p;\nsetp.eq.u32 p, %1, 0;\n@p red.release.gpu.global.inc.u32 [%0], 0xffffffff;\n}"
                                     :: "l"(&g_flag[F_QKV + (s - 4 + (h >> 3)) * 8]), "r"(l16) : "memory");
                    asm volatile("{\n.reg .pred p;\nsetp.eq.u32 p, %0, 0;\n@p bar.sync 5, 256;\n@!p bar.sync 13, 256;\n}" :: "r"(wg) : "memory");
                }
                const uint64_t da0 = (uint64_t)(((sb + O_AS + wg * 8192) & 0x3FFFF) >> 4) | (1ull << 16) | (64ull << 32) | (1ull << 62);
                wg_fence();
                wgmma_n32_ss<1>(d, da0, XDESC(0));
#pragma unroll
                for (int u = 1; u < 28; u++) wgmma_n32_rs<1>(d, a[32 + 4 * u], a[32 + 4 * u + 1], a[32 + 4 * u + 2], a[32 + 4 * u + 3], XDESC(u));
                wg_commit();
                wg_wait0();
                if (warp == 3 && r < 2 && s >= 0) store_qk();
                if (warp == 4) STAMP(s, 3);
                uint32_t e[8];
#pragma unroll
                for (int i = 0; i < 8; i++) e[i] = pack_bf16(d[2 * i], d[2 * i + 1]);
                if (r < 2) {
                    const uint32_t base = sb + O_QKX + (j & 1) * 12288 + wg * 4096 + w * 512 + l16;
                    stsm4t(base, e[0], wg ? e[1] : e[2], wg ? e[2] : e[1], e[3]);
                    stsm4t(base + 2048, e[4], wg ? e[5] : e[6], wg ? e[6] : e[5], e[7]);
                } else {
                    const uint32_t base = sb + O_VX + (j & 1) * 8192 + warp * 1024 + l16;
                    sts128(base, e[0], e[1], e[2], e[3]);
                    sts128(base + 512, e[4], e[5], e[6], e[7]);
                    fence_async_smem();
                    bar_arrive(14, 288);
                }
                if (warp == 7) STAMP(s, 4);
                if (s < 0) asm volatile("barrier.cluster.wait.aligned;" ::: "memory");
            }
        }
        bar_arrive(7, 384);
    } else {
        asm volatile("setmaxnreg.dec.sync.aligned.u32 136;");
        const int c = w;
        uint32_t a[96];
        uint32_t mmax = 0;
        {
            const int g = lane >> 2, t = lane & 3;
            uint32_t tag = 0, m0v[18];
            if (threadIdx.x == 256) tag = atomicAdd(&g_ticket, 1u);
#pragma unroll
            for (int i = 0; i < 9; i++) {
                const uint32_t* p = reinterpret_cast<const uint32_t*>(mem0 + g * DM + 16 * (4 * i + c) + 2 * t);
                m0v[2 * i] = __ldg(p); m0v[2 * i + 1] = __ldg(p + 4);
            }
            asm volatile("barrier.cluster.wait.aligned;" ::: "memory");
            if (c == 0) {
                tma_x_tile(sb, &tm_x, rb, r, 0, 0);
                mbar_expect_if(lane, sb + B_SC, 4608);
                if (r < 2) mbar_expect_if(lane, sb + B_VX, 8192);
                sts32_if(lane, sb + O_MISC, __float_as_uint(1.0f));
                sts32_if(lane, sb + O_MISC + 12, __float_as_uint(SM_SCALE));
            }
            asm volatile("barrier.cluster.arrive.relaxed.aligned;" ::: "memory");
#pragma unroll
            for (int tau = 0; tau < 3; tau++) {
                const uint32_t* v = m0v + 6 * tau;
                sts128(sb + O_MF + tau * 3072 + c * 512 + lane * 16, v[0], v[1], v[2], v[3]);
                sts64(sb + O_MF + tau * 3072 + 2048 + (c >> 1) * 512 + lane * 16 + (c & 1) * 8, v[4], v[5]);
#pragma unroll
                for (int i = 0; i < 6; i++) mmax = __vmaxu2(mmax, v[i] & 0x7fff7fffu);
            }
            mmax = max(mmax << 16, mmax & 0xffff0000u);
            bar_arrive(2, 384);
            tag = (__shfl_sync(~0u, tag, 0) / 96u + 1u) & 0xffffu;
            mbar_wait(sb + B_W + 0, 0);
            const __nv_bfloat16* p = Wo + (size_t)(h * 128 + 4 * t) * DM + 192 * r + 16 * c + 2 * g;
#pragma unroll
            for (int i = 0; i < 3; i++)
#pragma unroll
                for (int eb = 0; eb < 8; eb++)
#pragma unroll
                    for (int j = 0; j < 4; j++) a[(i * 8 + eb) * 4 + j] = ldg_nc32(p + (16 * eb + ((j & 1) * 2 + (j >> 1))) * DM + 64 * i);
#pragma unroll
            for (int kk = 0; kk < 48; kk++) {
                uint32_t w0 = a[2 * kk], w1 = a[2 * kk + 1];
                a[2 * kk] = __byte_perm(w0, w1, 0x5410);
                a[2 * kk + 1] = __byte_perm(w0, w1, 0x7632);
            }
            sts128(sb + O_WP + c * 512 + lane * 16, a[92], a[93], a[94], a[95]);
            float wmax = 0.f;
#pragma unroll
            for (int i = 0; i < 3; i++) {
                float n0[4];
#pragma unroll
                for (int u = 8 * i; u < 8 * i + 8; u++) {
                    const uint32_t x0 = a[4 * u] & 0x7fff7fffu, x1 = a[4 * u + 1] & 0x7fff7fffu, x2 = a[4 * u + 2] & 0x7fff7fffu, x3 = a[4 * u + 3] & 0x7fff7fffu;
                    if (u == 8 * i) mma16816_z(n0, x0, x1, x2, x3, ONES, ONES);
                    else mma16816(n0, x0, x1, x2, x3, ONES, ONES);
                }
                wmax = fmaxf(wmax, fmaxf(n0[0], n0[2]));
            }
            uint32_t wm = __reduce_max_sync(~0u, __float_as_uint(wmax));
            sts32_if(lane, sb + O_OF + 4 * c, wm);
            if (c == 0) PSTAMP(8);
            bar_sync(7, 384);
            asm volatile("barrier.cluster.wait.aligned;" ::: "memory");
            if (c == 1) tma_x_tile(sb, &tm_x, rb, r, 1, 1);
            if (c == 0) {
                const uint4 wq = lds128(sb + O_OF), xq = lds128(sb + O_OF + 16), xr = lds128(sb + O_OF + 32), v0 = lds128(sb + O_MISC + 32), v1 = lds128(sb + O_MISC + 48);
                const uint32_t w1 = max(max(wq.x, wq.y), max(wq.z, wq.w)), x1 = max(max(max(xq.x, xq.y), max(xq.z, xq.w)), max(max(xr.x, xr.y), max(xr.z, xr.w)));
                const uint32_t vv = (r < 2) ? 0u : max(max(max(v0.x, v0.y), max(v0.z, v0.w)), max(max(v1.x, v1.y), max(v1.z, v1.w)));
                const uint32_t lo = (min(w1, 0x7f800000u) + 0xffffu) >> 16 | ((min(vv, 0x7f800000u) + 0xffffu) & 0xffff0000u), hi = (x1 & 0xffff0000u) | tag;
                uint32_t l0, h0, l1, h1, l2, h2;
                asm volatile("{\n.reg .pred p;\n.reg .u32 n, x, y;\n.reg .b64 v;\nsetp.eq.u32 p, %10, 0;\nmov.b64 v, {%8, %9};\n@p st.relaxed.gpu.global.b64 [%7], v;\nmov.u32 n, 0;\n"
                             "G_%=: ld.relaxed.gpu.global.b64 v, [%6];\nmov.b64 {%0, %1}, v;\nld.relaxed.gpu.global.b64 v, [%6+256];\nmov.b64 {%2, %3}, v;\n"
                             "ld.relaxed.gpu.global.b64 v, [%6+512];\nmov.b64 {%4, %5}, v;\n"
                             "xor.b32 x, %1, %9;\nxor.b32 y, %3, %9;\nor.b32 x, x, y;\nxor.b32 y, %5, %9;\nor.b32 x, x, y;\nand.b32 x, x, 0xffff;\n"
                             "setp.eq.u32 p, x, 0;\nvote.sync.all.pred p, p, 0xffffffff;\n@p bra.uni E_%=;\n"
                             "add.u32 n, n, 1;\nsetp.lt.u32 p, n, 4000000;\n@p bra.uni G_%=;\ntrap;\nE_%=:\n}"
                             : "=&r"(l0), "=&r"(h0), "=&r"(l1), "=&r"(h1), "=&r"(l2), "=&r"(h2)
                             : "l"(&g_norm[lane]), "l"(&g_norm[blockIdx.x]), "r"(lo), "r"(hi), "r"(lane) : "memory");
                const uint32_t lm = __vmaxu2(l0, __vmaxu2(l1, l2));
                const float fw = __uint_as_float(__reduce_max_sync(~0u, lm << 16));
                const float fv = __uint_as_float(__reduce_max_sync(~0u, lm & 0xffff0000u));
                const float xmax = __uint_as_float(__reduce_max_sync(~0u, max(h0, max(h1, h2)) & 0xffff0000u));
                const float G = 36.f * fw * fv;
                sts32_if(lane, sb + O_MISC + 4, __float_as_uint(G)); sts32_if(lane, sb + O_MISC + 8, __float_as_uint(G * xmax));
            }
        }
        if (c == 0) PSTAMP(12);
        bar_sync(6, 128);
        int s3n = 1;
        uint32_t roff = __shfl_sync(~0u, (r * 4 + c) * 2048 + (lane >> 4) * 512 + (lane & 2) * 128 + (lane & 1) * 64 + (lane & 12) * 4, lane);
#pragma unroll 1
        for (int s = 0; s < NSEG; s++) {
            const uint32_t l16 = opaque(l16c);
            const uint32_t vxa = sb + O_VX + (s & 1) * 8192 + c * 2048 + l16;
            if (c == 0 && r == 2) {
                bar_sync(14, 288);
                asm volatile("{\n.reg .pred p;\nelect.sync _|p, 0xffffffff;\n"
                    "@p cp.async.bulk.global.shared::cta.bulk_group [%0], [%1], 8192;\n@p cp.async.bulk.commit_group;\n"
                    "cp.async.bulk.wait_group 0;\nsetp.lt.and.s32 p, %4, 63, p;\n"
                    "@p cp.async.bulk.shared::cluster.global.mbarrier::complete_tx::bytes.multicast::cluster [%1], [%0], 8192, [%2], %3;\n"
                    "fence.proxy.async.global;\n}"
                    :: "l"(reinterpret_cast<char*>(g_qkv) + (size_t)(s * NH + h) * REC + 20480), "r"(sb + O_VX + (s & 1) * 8192),
                       "r"(sb + B_VX + 8 * (s & 1)), "h"((unsigned short)(3 << rb)), "r"(s) : "memory");
            }
            if (s == NSEG - 1) { bar_sync(3, 384); break; }
            uint4 vx[4];
            sts32_if(l16, sb + O_MISC + 16 + 4 * c, __reduce_max_sync(~0u, mmax));
            if (c == 0) STAMP(s, 5);
            {
                bar_sync(6, 128);
                const uint4 mm = lds128(sb + O_MISC + 16), cf = lds128(sb + O_MISC);
                const float bound = fmaxf(__uint_as_float(cf.z), __uint_as_float(cf.y) * (__uint_as_float(max(max(mm.x, mm.y), max(mm.z, mm.w))) * __uint_as_float(cf.x)));
                const uint32_t ebits = __reduce_max_sync(~0u, min(max(__float_as_uint(bound) & 0x7f800000u, 21u << 23), 254u << 23));
                mbar_wait(sb + B_X + 8 * s3n, ((s + 1) / 3) & 1);
                s3n = (s3n == 2) ? 0 : s3n + 1;
                bar_sync(3, 384);
                if (r < 2) mbar_wait(sb + B_VX + 8 * (s & 1), (s >> 1) & 1);
                vx[0] = lds128(vxa); vx[2] = lds128(vxa + 1024);
                if (c == 0) STAMP(s, 13);
                mbar_wait(sb + B_SC, s & 1);
                if (c == 0) STAMP(s, 6);
                float p[10];
                load_scores(p, sb + O_SC, 1280, l16);
                float mx = fmaxf(fmaxf(fmaxf(p[0], p[1]), fmaxf(p[2], p[3])), fmaxf(fmaxf(p[4], p[5]), fmaxf(p[6], p[7])));
                mx = quad_max(fmaxf(mx, fmaxf(p[8], p[9])));
                const uint4 vm = lds64x2(sb + O_VM + c * 512 + (l16 >> 1));
                vx[1] = lds128(vxa + 512); vx[3] = lds128(vxa + 1536);
                bar_arrive(4, 384);
                const float sc = __uint_as_float(lds32(sb + O_MISC + 12));
                const float mo = mx * SM_SCALE;
                uint32_t P[5];
#pragma unroll
                for (int n = 0; n < 5; n++) P[n] = pack_bf16(ex2(fmaf(p[2 * n], SM_SCALE, -mo)), ex2(fmaf(p[2 * n + 1], n == 3 ? sc : SM_SCALE, -mo)));
                if (c == 0) STAMP(s, 7);
                float o0[4], o1[4], sm[4];
                mma16816_z(sm, ONES, ONES, ONES, ONES, P[1], P[2]);
                mma16816_z(o0, vx[0].x, vx[0].y, vx[0].z, vx[0].w, P[1], P[2]);
                mma16816_z(o1, vx[2].x, vx[2].y, vx[2].z, vx[2].w, P[1], P[2]);
                mma16816(sm, ONES, ONES, ONES, ONES, P[3], P[4]);
                mma16816(o0, vx[1].x, vx[1].y, vx[1].z, vx[1].w, P[3], P[4]);
                mma16816(o1, vx[3].x, vx[3].y, vx[3].z, vx[3].w, P[3], P[4]);
                mma1688(sm, ONES, ONES, P[0]);
                mma1688(o0, vm.x, vm.y, P[0]);
                mma1688(o1, vm.z, vm.w, P[0]);
                const float sig = __uint_as_float((268u << 23) - ebits);
                const float r0 = rcp_fast(sm[0]) * sig, r1 = rcp_fast(sm[1]) * sig;
                stsm4t(sb + O_OF + c * 512 + l16, pack_bf16(o0[0] * r0, o0[1] * r1), pack_bf16(o0[2] * r0, o0[3] * r1),
                       pack_bf16(o1[0] * r0, o1[1] * r1), pack_bf16(o1[2] * r0, o1[3] * r1));
                bar_sync(6, 128);
                uint4 ob[4];
#pragma unroll
                for (int q = 0; q < 4; q++) ob[q] = ldsm4(sb + O_OF + q * 512 + l16);
                { const uint4 v = lds128(sb + O_WP + c * 512 + l16); a[92] = v.x; a[93] = v.y; a[94] = v.z; a[95] = v.w; }
                float m0[3][4], m1[3][4];
#pragma unroll
                for (int q = 0; q < 4; q++) {
#pragma unroll
                    for (int i = 0; i < 3; i++) {
                        const int k0 = (i * 8 + 2 * q) * 4;
                        if (q == 0) mma16816_z(m0[i], a[k0], a[k0 + 1], a[k0 + 2], a[k0 + 3], ob[q].x, ob[q].y);
                        else mma16816(m0[i], a[k0], a[k0 + 1], a[k0 + 2], a[k0 + 3], ob[q].x, ob[q].y);
                    }
#pragma unroll
                    for (int i = 0; i < 3; i++) {
                        const int k1 = (i * 8 + 2 * q + 1) * 4;
                        if (q == 0) mma16816_z(m1[i], a[k1], a[k1 + 1], a[k1 + 2], a[k1 + 3], ob[q].z, ob[q].w);
                        else mma16816(m1[i], a[k1], a[k1 + 1], a[k1 + 2], a[k1 + 3], ob[q].z, ob[q].w);
                    }
                }
                asm volatile("red.relaxed.gpu.global.add.noftz.v4.f16x2 [%0], {%1,%2,%3,%4};" :: "l"(reinterpret_cast<char*>(g_acc) + roff),
                    "r"(pack_f16(m0[0][0] + m1[0][0], m0[0][2] + m1[0][2])), "r"(pack_f16(m0[1][0] + m1[1][0], m0[1][2] + m1[1][2])),
                    "r"(pack_f16(m0[2][0] + m1[2][0], m0[2][2] + m1[2][2])), "r"(0x3c00u) : "memory");
                asm volatile("red.relaxed.gpu.global.add.noftz.v4.f16x2 [%0], {%1,%2,%3,%4};" :: "l"(reinterpret_cast<char*>(g_acc) + roff + 1024),
                    "r"(pack_f16(m0[0][1] + m1[0][1], m0[0][3] + m1[0][3])), "r"(pack_f16(m0[1][1] + m1[1][1], m0[1][3] + m1[1][3])),
                    "r"(pack_f16(m0[2][1] + m1[2][1], m0[2][3] + m1[2][3])), "r"(0x3c00u) : "memory");
                const unsigned t_red = clk();
                bar_arrive(5, 256);
                bar_arrive(13, 256);
                mbar_expect_if(l16 | c, sb + B_SC, 4608);
                mbar_expect_if(l16 | (c ^ 1) | (r >> 1), sb + B_VX + 8 * ((s + 1) & 1), 8192);
                sts32_if(l16 | (c ^ 3), sb + O_MISC, ebits - (14u << 23));
                if (c == 0) STAMPV(s, 8, t_red);
                const char* pbase = reinterpret_cast<const char*>(g_acc) + (s * 24576 + c * 2048) + ((l16 & 64) * 16 + (l16 & 256) + ((l16 & 128) >> 1) + (l16 & 48));
                spin_until(t_red, D_WAIT);
                uint4 v[6];
#pragma unroll
                for (int i = 0; i < 6; i++) v[i] = ldg_relaxed128(pbase + (i >> 1) * 8192 + (i & 1) * 512);
                int nretry = 0;
                auto hand_over = [&]() -> uint32_t {
                    uint32_t ok = 0;
#pragma unroll
                    for (int tau = 0; tau < 3; tau++) {
                        if (tau == 1) sched_fence<0>(h);
                        if (tau == 2) {
                            sched_fence<1>(h);
                            asm volatile("{\n.reg .pred p, q;\n.reg .b32 x;\nlop3.b32 x, %1, %2, %3, 0x80;\nlop3.b32 x, x, %4, %5, 0x80;\nand.b32 x, x, %6;\n"
                                         "setp.eq.u32 p, x, 0x5000;\nvote.sync.all.pred q, p, 0xffffffff;\nselp.u32 %0, 1, 0, q;\n}"
                                         : "=r"(ok) : "r"(v[0].w), "r"(v[1].w), "r"(v[2].w), "r"(v[3].w), "r"(v[4].w), "r"(v[5].w));
                        }
                        v[2 * tau].x = f16x2_to_bf16x2(v[2 * tau].x); v[2 * tau + 1].x = f16x2_to_bf16x2(v[2 * tau + 1].x);
                        v[2 * tau].y = f16x2_to_bf16x2(v[2 * tau].y); v[2 * tau + 1].y = f16x2_to_bf16x2(v[2 * tau + 1].y);
                        v[2 * tau].z = f16x2_to_bf16x2(v[2 * tau].z); v[2 * tau + 1].z = f16x2_to_bf16x2(v[2 * tau + 1].z);
                        sts128(sb + O_MF + tau * 3072 + c * 512 + l16, v[2 * tau].x, v[2 * tau + 1].x, v[2 * tau].y, v[2 * tau + 1].y);
                        sts64(sb + O_MF + tau * 3072 + 2048 + (c >> 1) * 512 + (c & 1) * 8 + l16, v[2 * tau].z, v[2 * tau + 1].z);
                    }
                    asm volatile("{\n.reg .pred p;\nsetp.ne.u32 p, %0, 0;\n@p bar.arrive 2, 384;\n}" :: "r"(ok) : "memory");
                    return ok;
                };
                if (!hand_over()) {
                    asm volatile("{\n.reg .pred p, q;\n.reg .u32 n, x;\nmov.u32 n, 0;\n"
                         "R_%=: ld.relaxed.gpu.global.v4.u32 {%0,%1,%2,%3}, [%25];\nld.relaxed.gpu.global.v4.u32 {%4,%5,%6,%7}, [%25+512];\n"
                         "ld.relaxed.gpu.global.v4.u32 {%8,%9,%10,%11}, [%25+8192];\nld.relaxed.gpu.global.v4.u32 {%12,%13,%14,%15}, [%25+8704];\n"
                         "ld.relaxed.gpu.global.v4.u32 {%16,%17,%18,%19}, [%25+16384];\nld.relaxed.gpu.global.v4.u32 {%20,%21,%22,%23}, [%25+16896];\n"
                         "add.u32 %24, %24, 1;\nand.b32 x, %3, %7;\nand.b32 x, x, %11;\nand.b32 x, x, %15;\nand.b32 x, x, %19;\nand.b32 x, x, %23;\n"
                         "setp.eq.u32 p, x, 0x5000;\nvote.sync.all.pred q, p, 0xffffffff;\n@q bra.uni K_%=;\n"
                         "add.u32 n, n, 1;\nsetp.lt.u32 q, n, 2000000;\n@q bra.uni R_%=;\ntrap;\nK_%=:\n}"
                         : "+r"(v[0].x), "+r"(v[0].y), "+r"(v[0].z), "+r"(v[0].w), "+r"(v[1].x), "+r"(v[1].y), "+r"(v[1].z), "+r"(v[1].w),
                           "+r"(v[2].x), "+r"(v[2].y), "+r"(v[2].z), "+r"(v[2].w), "+r"(v[3].x), "+r"(v[3].y), "+r"(v[3].z), "+r"(v[3].w),
                           "+r"(v[4].x), "+r"(v[4].y), "+r"(v[4].z), "+r"(v[4].w), "+r"(v[5].x), "+r"(v[5].y), "+r"(v[5].z), "+r"(v[5].w), "+r"(nretry)
                         : "l"(pbase) : "memory");
                    hand_over();
                }
                if (c == 0) STAMP(s, 12);
                if (c == 0) STAMPV(s, 14, nretry);
                mmax = absmax2(absmax2(absmax2(v[0].x, v[0].y), absmax2(v[0].z, v[1].x)), absmax2(absmax2(v[1].y, v[1].z), absmax2(v[2].x, v[2].y)));
                mmax = absmax2(mmax, absmax2(absmax2(absmax2(v[2].z, v[3].x), absmax2(v[3].y, v[3].z)), absmax2(absmax2(v[4].x, v[4].y), absmax2(v[4].z, v[5].x))));
                mmax = absmax2(mmax, absmax2(v[5].y, v[5].z)) & 0x7fff7fffu;
                mmax = max(mmax << 16, mmax & 0xffff0000u);
            }
            roff += 24576;
        }
        {
            bar_sync(7, 384);
            if (c == 0)
                asm volatile("{\n.reg .pred p;\nsetp.eq.u32 p, %1, 0;\n@p red.release.gpu.global.inc.u32 [%0], 0xffffffff;\n}"
                             :: "l"(&g_flag[F_QKV + (60 + (h >> 3)) * 8]), "r"(l16c) : "memory");
        }
    }
    if (warp == 8) PSTAMP(13);
    cluster_sync();
}

constexpr int NST = 10;
constexpr int G_RING = 0, G_EX = NST * 16384, G_OUT = G_EX + 32768, G_CARRY = G_OUT + 32768, G_BAR = G_CARRY + 512, BG_SMEM = G_BAR + 256;
constexpr int GB_FULL = G_BAR, GB_EMPTY = G_BAR + 8 * NST, GB_W = G_BAR + 16 * NST;
static_assert(BG_SMEM <= 232448, "smem");

template <int ACC>
__device__ __forceinline__ void wgmma_n128_rs(float (&d)[64], uint32_t a0, uint32_t a1, uint32_t a2, uint32_t a3, uint64_t desc) {
    asm volatile("wgmma.mma_async.sync.aligned.m64n128k16.f32.bf16.bf16 "
        "{%0,%1,%2,%3,%4,%5,%6,%7,%8,%9,%10,%11,%12,%13,%14,%15,%16,%17,%18,%19,%20,%21,%22,%23,%24,%25,%26,%27,%28,%29,%30,%31,"
        "%32,%33,%34,%35,%36,%37,%38,%39,%40,%41,%42,%43,%44,%45,%46,%47,%48,%49,%50,%51,%52,%53,%54,%55,%56,%57,%58,%59,%60,%61,%62,%63}, "
        "{%64,%65,%66,%67}, %68, %69, 1, 1, 0;"
        : "+f"(d[0]), "+f"(d[1]), "+f"(d[2]), "+f"(d[3]), "+f"(d[4]), "+f"(d[5]), "+f"(d[6]), "+f"(d[7]),
          "+f"(d[8]), "+f"(d[9]), "+f"(d[10]), "+f"(d[11]), "+f"(d[12]), "+f"(d[13]), "+f"(d[14]), "+f"(d[15]),
          "+f"(d[16]), "+f"(d[17]), "+f"(d[18]), "+f"(d[19]), "+f"(d[20]), "+f"(d[21]), "+f"(d[22]), "+f"(d[23]),
          "+f"(d[24]), "+f"(d[25]), "+f"(d[26]), "+f"(d[27]), "+f"(d[28]), "+f"(d[29]), "+f"(d[30]), "+f"(d[31]),
          "+f"(d[32]), "+f"(d[33]), "+f"(d[34]), "+f"(d[35]), "+f"(d[36]), "+f"(d[37]), "+f"(d[38]), "+f"(d[39]),
          "+f"(d[40]), "+f"(d[41]), "+f"(d[42]), "+f"(d[43]), "+f"(d[44]), "+f"(d[45]), "+f"(d[46]), "+f"(d[47]),
          "+f"(d[48]), "+f"(d[49]), "+f"(d[50]), "+f"(d[51]), "+f"(d[52]), "+f"(d[53]), "+f"(d[54]), "+f"(d[55]),
          "+f"(d[56]), "+f"(d[57]), "+f"(d[58]), "+f"(d[59]), "+f"(d[60]), "+f"(d[61]), "+f"(d[62]), "+f"(d[63])
        : "r"(a0), "r"(a1), "r"(a2), "r"(a3), "l"(desc), "n"(ACC));
}
__device__ __forceinline__ void wait_flag(const unsigned* p, unsigned target) {
    asm volatile("{\n.reg .pred p;\n.reg .u32 n, v;\nmov.u32 n, 0;\n"
                 "W_%=: ld.acquire.gpu.global.u32 v, [%0];\nsub.u32 v, v, %1;\nsetp.ge.s32 p, v, 0;\n@p bra.uni D_%=;\nnanosleep.u32 100;\n"
                 "add.u32 n, n, 1;\nsetp.lt.u32 p, n, 4000000;\n@p bra.uni W_%=;\ntrap;\nD_%=:\n}" :: "l"(p), "r"(target) : "memory");
}
__device__ __forceinline__ void flag_inc_if(uint32_t z, unsigned* p) {
    asm volatile("{\n.reg .pred p;\nsetp.eq.u32 p, %1, 0;\n@p red.release.gpu.global.inc.u32 [%0], 0xffffffff;\n}" :: "l"(p), "r"(z) : "memory");
}
template <int NS, int STRIDE>
__device__ __forceinline__ void bg_mainloop(float (&d)[64], const uint32_t (&a)[144], uint32_t sb, int it, int lane) {
    int slot = it % NST, ph = (it / NST) & 1, prev = 0;
#pragma unroll
    for (int i = 0; i < NS; i++) {
        mbar_wait(sb + GB_FULL + 8 * slot, ph);
        const uint64_t desc = (uint64_t)(((sb + G_RING + slot * 16384) & 0x3FFFF) >> 4) | (1ull << 16) | (64ull << 32) | (1ull << 62);
        wg_fence();
#pragma unroll
        for (int k = 0; k < 4; k++) {
            const int u = 16 * i + 4 * k;
            if (i == 0 && k == 0) wgmma_n128_rs<0>(d, a[u], a[u + 1], a[u + 2], a[u + 3], desc);
            else wgmma_n128_rs<1>(d, a[u], a[u + 1], a[u + 2], a[u + 3], desc + 2 * k);
        }
        wg_commit();
        if (i > 0) {
            asm volatile("wgmma.wait_group.sync.aligned 1;" ::: "memory");
            mbar_arrive_if(lane, sb + GB_EMPTY + 8 * prev);
        }
        prev = slot;
        slot += STRIDE;
        if (slot >= NST) { slot -= NST; ph ^= 1; }
    }
    wg_wait0();
    mbar_arrive_if(lane, sb + GB_EMPTY + 8 * prev);
}
template <bool SKIP>
__device__ __forceinline__ void bg_epilogue(float (&d)[64], uint32_t sb, int wg, int w, int lane, const CUtensorMap* tm_out, int col0, int tok0,
                                            const __nv_bfloat16* xa, const __nv_bfloat16* Dk) {
    const int g = lane >> 2, t = lane & 3;
    const uint32_t ex = sb + G_EX + w * 4096 + lane * 16;
    float k[32];
    if (wg == 0) {
#pragma unroll
        for (int q = 0; q < 8; q++) sts128f(ex + q * 512, d[32 + 4 * q], d[32 + 4 * q + 1], d[32 + 4 * q + 2], d[32 + 4 * q + 3]);
#pragma unroll
        for (int i = 0; i < 32; i++) k[i] = d[i];
    } else {
#pragma unroll
        for (int q = 0; q < 8; q++) sts128f(ex + 16384 + q * 512, d[4 * q], d[4 * q + 1], d[4 * q + 2], d[4 * q + 3]);
#pragma unroll
        for (int i = 0; i < 32; i++) k[i] = d[32 + i];
    }
    uint32_t xv[16], dv = 0;
    if (SKIP) {
        const __nv_bfloat16* xp = xa + (size_t)(tok0 + 64 * wg + 2 * t) * DM + col0 + 16 * w + 2 * g;
#pragma unroll
        for (int i = 0; i < 16; i++) xv[i] = ldg_nc32(xp + (8 * (i >> 1) + (i & 1)) * DM);
        dv = ldg_nc32(Dk + col0 + 16 * w + 2 * g);
    }
    if (SKIP && w == 0) asm volatile("cp.async.bulk.wait_group.read 0;" ::: "memory");
    bar_sync(1, 256);
#pragma unroll
    for (int q = 0; q < 8; q++) {
        const float4 o = lds128f(ex + (wg ^ 1) * 16384 + q * 512);
        k[4 * q] += o.x; k[4 * q + 1] += o.y; k[4 * q + 2] += o.z; k[4 * q + 3] += o.w;
    }
    if (SKIP) bar_sync(1, 256); else bar_sync(13, 288);
    const uint32_t ob = sb + G_OUT + wg * 16384 + (w >> 1) * 8192 + (g & 1) * 8;
    const uint32_t ch = (w & 1) * 4 + (g >> 1);
#pragma unroll
    for (int i = 0; i < 16; i++) {
        float v0 = k[4 * (i >> 1) + (i & 1)], v1 = k[4 * (i >> 1) + 2 + (i & 1)];
        if (SKIP) {
            const uint32_t p = pack_bf16(__uint_as_float(xv[i] << 16) * __uint_as_float(dv << 16), __uint_as_float(xv[i] & 0xffff0000u) * __uint_as_float(dv & 0xffff0000u));
            v0 += __uint_as_float(p << 16); v1 += __uint_as_float(p & 0xffff0000u);
        }
        const uint32_t n7 = 2 * t + (i & 1);
        sts64(ob + (8 * (i >> 1) + n7) * 128 + ((ch ^ n7) << 4), __float_as_uint(v0), __float_as_uint(v1));
    }
    fence_async_smem();
    if (SKIP) {
        bar_sync(4 + wg, 128);
        if (w == 0)
            asm volatile("{\n.reg .pred p;\nelect.sync _|p, 0xffffffff;\n"
                "@p cp.async.bulk.tensor.2d.global.shared::cta.bulk_group [%0, {%2, %4}], [%1];\n"
                "@p cp.async.bulk.tensor.2d.global.shared::cta.bulk_group [%0, {%3, %4}], [%1+8192];\n@p cp.async.bulk.commit_group;\n}"
                :: "l"(tm_out), "r"(sb + G_OUT + wg * 16384), "r"(col0), "r"(col0 + 32), "r"(tok0 + 64 * wg) : "memory");
    } else {
        bar_arrive(12, 288);
    }
}
__device__ __forceinline__ void s5_channel(int p, const __nv_bfloat16* Lre, const __nv_bfloat16* Lim, const __nv_bfloat16* logdt, float2& lam, float2& coef) {
    const float dt = __bfloat162float(__float2bfloat16(expf(__bfloat162float(logdt[p]))));
    const float lr = __bfloat162float(Lre[p]), li = __bfloat162float(Lim[p]);
    const float e = expf(dt * lr);
    float sn, cs;
    sincosf(dt * li, &sn, &cs);
    lam = make_float2(e * cs, e * sn);
    const float den = lr * lr + li * li;
    coef = make_float2(((lam.x - 1.f) * lr + lam.y * li) / den, (lam.y * lr - (lam.x - 1.f) * li) / den);
}
__device__ __forceinline__ float2 cfma(float2 a, float2 b, float2 c) {
    return make_float2(fmaf(a.x, b.x, fmaf(-a.y, b.y, c.x)), fmaf(a.x, b.y, fmaf(a.y, b.x, c.y)));
}
__device__ __forceinline__ uint4 ldg128(const void* p) { uint4 v; asm volatile("ld.global.v4.u32 {%0,%1,%2,%3}, [%4];" : "=r"(v.x), "=r"(v.y), "=r"(v.z), "=r"(v.w) : "l"(p) : "memory"); return v; }
__device__ __forceinline__ uint2 ldg64(const void* p) { uint2 v; asm volatile("ld.global.v2.u32 {%0,%1}, [%2];" : "=r"(v.x), "=r"(v.y) : "l"(p) : "memory"); return v; }

__device__ __forceinline__ void bg_attention(uint32_t st0, uint32_t st1, int mt, int lane) {
    const int g = lane >> 2, t = lane & 3;
    float sc[5][4];
#pragma unroll
    for (int n = 0; n < 5; n++) sc[n][0] = sc[n][1] = sc[n][2] = sc[n][3] = 0.f;
    float sm2[4] = {0.f, 0.f, 0.f, 0.f};
#pragma unroll
    for (int i = 0; i < 8; i++) {
        const uint32_t st = (i >> 2 ? st1 : st0) + (i & 3) * 512 + lane * 16;
        const uint4 q = ldsm4(st + mt * 2048), km = ldsm4(st + 8192), k0 = ldsm4(st + 4096);
        mma16816(sc[0], q.x, q.y, q.z, q.w, km.x, km.y);
        mma16816(sm2, q.x, q.y, q.z, q.w, km.z, km.w);
        mma16816(sc[1], q.x, q.y, q.z, q.w, k0.x, k0.y);
        mma16816(sc[2], q.x, q.y, q.z, q.w, k0.z, k0.w);
        if (mt) {
            const uint4 k1 = ldsm4(st + 6144);
            mma16816(sc[3], q.x, q.y, q.z, q.w, k1.x, k1.y);
            mma16816(sc[4], q.x, q.y, q.z, q.w, k1.z, k1.w);
        }
    }
#pragma unroll
    for (int i = 0; i < 4; i++) sc[0][i] += sm2[i];
    const int q0 = 16 * mt + 8 + g - 2 * t;
#pragma unroll
    for (int n = 1; n < 5; n++) {
        if (8 * n > q0) sc[n][0] = -INFINITY;
        if (8 * n + 1 > q0) sc[n][1] = -INFINITY;
        if (8 * n > q0 + 8) sc[n][2] = -INFINITY;
        if (8 * n + 1 > q0 + 8) sc[n][3] = -INFINITY;
    }
    float ma = fmaxf(sc[0][0], sc[0][1]), mb = fmaxf(sc[0][2], sc[0][3]);
#pragma unroll
    for (int n = 1; n < 5; n++) { ma = fmaxf(ma, fmaxf(sc[n][0], sc[n][1])); mb = fmaxf(mb, fmaxf(sc[n][2], sc[n][3])); }
    ma = quad_max(ma) * SM_SCALE; mb = quad_max(mb) * SM_SCALE;
    uint32_t Pa[5], Pb[5];
#pragma unroll
    for (int n = 0; n < 5; n++) {
        Pa[n] = pack_bf16(ex2(fmaf(sc[n][0], SM_SCALE, -ma)), ex2(fmaf(sc[n][1], SM_SCALE, -ma)));
        Pb[n] = pack_bf16(ex2(fmaf(sc[n][2], SM_SCALE, -mb)), ex2(fmaf(sc[n][3], SM_SCALE, -mb)));
    }
    float sa[4], sbb[4];
    mma1688_z(sa, ONES, ONES, Pa[0]); mma1688_z(sbb, ONES, ONES, Pb[0]);
    mma16816(sa, ONES, ONES, ONES, ONES, Pa[1], Pa[2]); mma16816(sbb, ONES, ONES, ONES, ONES, Pb[1], Pb[2]);
    mma16816(sa, ONES, ONES, ONES, ONES, Pa[3], Pa[4]); mma16816(sbb, ONES, ONES, ONES, ONES, Pb[3], Pb[4]);
    const float ra0 = rcp_fast(sa[0]), ra1 = rcp_fast(sa[1]), rb0 = rcp_fast(sbb[0]), rb1 = rcp_fast(sbb[1]);
    const uint32_t row = lane & 7;
    const uint32_t so = mt * 2048 + (lane >> 4) * 1024 + row * 128;
#pragma unroll
    for (int i = 0; i < 8; i++) {
        const uint32_t st = i >> 2 ? st1 : st0;
        const int e4 = i & 3;
        const float2 vmf = lds64f(st + 14336 + e4 * 256 + lane * 8);
        const uint32_t vm0 = __float_as_uint(vmf.x), vm1 = __float_as_uint(vmf.y);
        const uint4 v0 = lds128(st + 10240 + e4 * 1024 + lane * 16);
        float oa[4], ob[4];
        mma1688_z(oa, vm0, vm1, Pa[0]); mma1688_z(ob, vm0, vm1, Pb[0]);
        mma16816(oa, v0.x, v0.y, v0.z, v0.w, Pa[1], Pa[2]);
        mma16816(ob, v0.x, v0.y, v0.z, v0.w, Pb[1], Pb[2]);
        if (mt) {
            const uint4 v1 = lds128(st + 10240 + e4 * 1024 + 512 + lane * 16);
            mma16816(oa, v1.x, v1.y, v1.z, v1.w, Pa[3], Pa[4]);
            mma16816(ob, v1.x, v1.y, v1.z, v1.w, Pb[3], Pb[4]);
        }
        stsm4t(st + so + (((2 * e4 + ((lane >> 3) & 1)) ^ row) << 4), pack_bf16(oa[0] * ra0, oa[1] * ra1), pack_bf16(oa[2] * ra0, oa[3] * ra1),
               pack_bf16(ob[0] * rb0, ob[1] * rb1), pack_bf16(ob[2] * rb0, ob[3] * rb1));
    }
}
__device__ __forceinline__ bool bg_att_turn(int na, int ng) { return na == ng || (na == ng + 1 && na <= BG_AHEAD); }

__global__ void __launch_bounds__(384, 1)
bg_kernel(const __grid_constant__ CUtensorMap tm_xa, const __grid_constant__ CUtensorMap tm_wo, const __grid_constant__ CUtensorMap tm_out,
          const __nv_bfloat16* __restrict__ xa, const __nv_bfloat16* __restrict__ Lre, const __nv_bfloat16* __restrict__ Lim,
          const __nv_bfloat16* __restrict__ Bre, const __nv_bfloat16* __restrict__ Bim, const __nv_bfloat16* __restrict__ Cre,
          const __nv_bfloat16* __restrict__ Cim, const __nv_bfloat16* __restrict__ logdt, const __nv_bfloat16* __restrict__ Dk) {
    extern __shared__ __align__(1024) uint8_t smem_raw[];
    const uint32_t sb = smem_u32(smem_raw);
    const int lane = threadIdx.x & 31;
    const int warp = __shfl_sync(~0u, threadIdx.x >> 5, 0);
    const int wg = warp >> 2, w = warp & 3, b = blockIdx.x;
    const int nt = b % 9, kq = b / 9;
    BSTAMP(0);
    if (threadIdx.x == 0) {
        if (sb & 1023u) __trap();
        for (int i = 0; i < NST; i++) { mbar_init(sb + GB_FULL + 8 * i, 1); mbar_init(sb + GB_EMPTY + 8 * i, 4); }
        mbar_init(sb + GB_W, 1);
        asm volatile("fence.mbarrier_init.release.cluster;" ::: "memory");
        mbar_expect(sb + GB_W, (b < 18 ? 64 : 128) * 1152);
        sts32(sb + G_BAR + 248, atomicAdd(&g_ticket_bg, 1u) / 36u + 1u);
    }
    __syncthreads();
    if (wg == 2) {
        asm volatile("setmaxnreg.dec.sync.aligned.u32 24;");
        if (w == 0) {
            int slot = 0, ph = 1;
            unsigned tlast = clk();
            auto pace = [&]() { if (BG_PACE) { spin_until(tlast, BG_PACE); tlast = clk(); } };
            auto next = [&]() { if (++slot == NST) { slot = 0; ph ^= 1; } };
            bar_sync(6, 288);
            if (b < 18) {
#pragma unroll 1
                for (int i = 0; i < 144; i++) {
                    const int blk = i / 9, kb = i - 9 * blk, it = (blk >> 1) * 18 + (blk & 1) + 2 * kb;
                    slot = it % NST;
                    mbar_wait(sb + GB_EMPTY + 8 * slot, ((it / NST) & 1) ^ 1);
                    pace();
                    asm volatile("{\n.reg .pred p;\nelect.sync _|p, 0xffffffff;\n@p mbarrier.arrive.expect_tx.shared::cta.b64 _, [%2], 16384;\n"
                        "@p cp.async.bulk.tensor.5d.shared::cluster.global.mbarrier::complete_tx::bytes [%0], [%1, {%3, %4, %4, %4, %5}], [%2];\n}"
                        :: "r"(sb + G_RING + slot * 16384), "l"(&tm_xa), "r"(sb + GB_FULL + 8 * slot), "r"(kb * 64), "r"(0), "r"(blk) : "memory");
                }
                slot = 144 % NST; ph = ((144 / NST) & 1) ^ 1;
            }
            const unsigned ep = lds32(sb + G_BAR + 248);
            auto slabs = [&](const char* src, int ns) {
                asm volatile("fence.proxy.async.global;" ::: "memory");
#pragma unroll 1
                for (int i = 0; i < ns; i++) {
                    mbar_wait(sb + GB_EMPTY + 8 * slot, ph);
                    pace();
                    asm volatile("{\n.reg .pred p;\nelect.sync _|p, 0xffffffff;\n@p mbarrier.arrive.expect_tx.shared::cta.b64 _, [%2], 16384;\n"
                        "@p cp.async.bulk.shared::cluster.global.mbarrier::complete_tx::bytes [%0], [%1], 16384, [%2];\n}"
                        :: "r"(sb + G_RING + slot * 16384), "l"(src + (size_t)((i & 1) * (ns >> 1) + (i >> 1)) * (SEQ * 128)), "r"(sb + GB_FULL + 8 * slot) : "memory");
                    next();
                }
            };
            if (b >= 18) {
#pragma unroll 1
                for (int blk = kq - 2; blk < 16; blk += 2) {
                    wait_flag(&g_flag[F_H + blk * 8], 18 * ep);
                    slabs(reinterpret_cast<const char*>(g_h) + blk * 16384, 18);
                }
            }
            bar_sync(6, 288);
#pragma unroll 1
            for (int na = 0, ng = 0; ng < 16;) {
                if (bg_att_turn(na, ng)) {
                    if (nt < 8) {
                        wait_flag(&g_flag[F_QKV + (na * 4 + kq) * 8], 24 * ep);
                        asm volatile("fence.proxy.async.global;" ::: "memory");
#pragma unroll 1
                        for (int i = 0; i < 8; i++) {
                            const int pr = nt * 4 + 2 * (i & 1) + (i >> 2), hf = (i >> 1) & 1;
                            const char* rec = reinterpret_cast<const char*>(g_qkv) + (size_t)((4 * na + (pr >> 3)) * NH + 8 * kq + (pr & 7)) * REC;
                            mbar_wait(sb + GB_EMPTY + 8 * slot, ph);
                    pace();
                            asm volatile("{\n.reg .pred p;\nelect.sync _|p, 0xffffffff;\n@p mbarrier.arrive.expect_tx.shared::cta.b64 _, [%4], 15360;\n"
                                "@p cp.async.bulk.shared::cluster.global.mbarrier::complete_tx::bytes [%0], [%1], 10240, [%4];\n"
                                "@p cp.async.bulk.shared::cluster.global.mbarrier::complete_tx::bytes [%0+10240], [%2], 4096, [%4];\n"
                                "@p cp.async.bulk.shared::cluster.global.mbarrier::complete_tx::bytes [%0+14336], [%3], 1024, [%4];\n}"
                                :: "r"(sb + G_RING + slot * 16384), "l"(rec + hf * 10240), "l"(rec + 20480 + hf * 4096), "l"(rec + 28672 + hf * 1024),
                                   "r"(sb + GB_FULL + 8 * slot) : "memory");
                            next();
                        }
                    }
                    na++;
                } else {
                    wait_flag(&g_flag[F_OX + (ng * 4 + kq) * 8], 8 * ep);
                    slabs(reinterpret_cast<const char*>(g_ox) + (size_t)kq * 16 * SEQ * 128 + ng * 16384, 16);
                    ng++;
                }
            }
        } else if (w == 1) {
            if (b < 18) {
#pragma unroll 1
                for (int blk = 0; blk < 16; blk++) {
                    bar_sync(8 + (blk & 1), 160);
                    asm volatile("{\n.reg .pred p;\nelect.sync _|p, 0xffffffff;\n@p cp.async.bulk.global.shared::cta.bulk_group [%0], [%1], 16384;\n"
                        "@p cp.async.bulk.commit_group;\ncp.async.bulk.wait_group 0;\nfence.proxy.async.global;\n}"
                        :: "l"(reinterpret_cast<char*>(g_h) + ((size_t)b * SEQ + blk * 128) * 128), "r"(sb + G_OUT + (blk & 1) * 16384) : "memory");
                    bar_arrive(10 + (blk & 1), 160);
                    flag_inc_if(lane, &g_flag[F_H + blk * 8]);
                }
            }
            if (nt < 8) {
                int it = 144;
#pragma unroll 1
                for (int na = 0, ng = 0; ng < 16;) {
                    if (bg_att_turn(na, ng)) {
                        bar_sync(7, 288);
                        if (lane < 8) {
                            const int pr = nt * 4 + 2 * (lane & 1) + (lane >> 2), hf = (lane >> 1) & 1;
                            asm volatile("cp.async.bulk.global.shared::cta.bulk_group [%0], [%1], 4096;\ncp.async.bulk.commit_group;\ncp.async.bulk.wait_group.read 0;\n"
                                "mbarrier.arrive.shared::cta.b64 _, [%2], 4;\ncp.async.bulk.wait_group 0;\nfence.proxy.async.global;"
                                :: "l"(reinterpret_cast<char*>(g_ox) + ((size_t)((8 * kq + (pr & 7)) * 2 + hf) * SEQ + (4 * na + (pr >> 3)) * 32) * 128),
                                   "r"(sb + G_RING + ((it + lane) % NST) * 16384), "r"(sb + GB_EMPTY + 8 * ((it + lane) % NST)) : "memory");
                        }
                        __syncwarp();
                        flag_inc_if(lane, &g_flag[F_OX + (na * 4 + kq) * 8]);
                        it += 8; na++;
                    } else { it += 16; ng++; }
                }
            }
        } else if (w == 2) {
            const unsigned ep = lds32(sb + G_BAR + 248);
#pragma unroll 1
            for (int blk = 0; blk < 16; blk++) {
                bar_arrive(13, 288);
                bar_sync(12, 288);
                if (kq) { wait_flag(&g_flag[F_OUT + (blk * 9 + nt) * 8], ep); asm volatile("fence.proxy.async.global;" ::: "memory"); }
                unsigned t0 = clk();
                if (blk < 15) spin_until(t0, b * (RED_GAP / 36));
#pragma unroll 1
                for (int i = 0; i < 4; i++) {
                    const uint32_t src = sb + G_OUT + i * 8192;
                    const int c0 = DM + 64 * nt + (i & 1) * 32, c1 = blk * 128 + (i >> 1) * 64;
                    if (kq) {
                        asm volatile("{\n.reg .pred p;\nelect.sync _|p, 0xffffffff;\n@p cp.reduce.async.bulk.tensor.2d.global.shared::cta.add.bulk_group [%0, {%2, %3}], [%1];\n}"
                            :: "l"(&tm_out), "r"(src), "r"(c0), "r"(c1) : "memory");
                        t0 = clk();
                        if (blk < 15 && i < 3) spin_until(t0, RED_GAP);
                    } else {
                        asm volatile("{\n.reg .pred p;\nelect.sync _|p, 0xffffffff;\n@p cp.async.bulk.tensor.2d.global.shared::cta.bulk_group [%0, {%2, %3}], [%1];\n}"
                            :: "l"(&tm_out), "r"(src), "r"(c0), "r"(c1) : "memory");
                    }
                }
                asm volatile("cp.async.bulk.commit_group;\ncp.async.bulk.wait_group 0;\nfence.proxy.async.global;" ::: "memory");
                __syncwarp();
                if (!kq) flag_inc_if(lane, &g_flag[F_OUT + (blk * 9 + nt) * 8]);
            }
        }
    } else {
        asm volatile("setmaxnreg.inc.sync.aligned.u32 240;");
        const int g = lane >> 2, t = lane & 3, tid = threadIdx.x;
        uint32_t a[144];
        float d[64];
        if (b < 18) {
            if (tid < 64)
                asm volatile("cp.async.bulk.shared::cluster.global.mbarrier::complete_tx::bytes [%0], [%1], 1152, [%2];"
                    :: "r"(sb + tid * 1168), "l"((tid < 32 ? Bre : Bim) + (size_t)(32 * b + (tid & 31)) * DM), "r"(sb + GB_W) : "memory");
            float2 lam, coef;
            s5_channel(32 * b + 8 * w + g, Lre, Lim, logdt, lam, coef);
            float2 l32 = lam;
#pragma unroll
            for (int i = 0; i < 5; i++) l32 = make_float2(l32.x * l32.x - l32.y * l32.y, 2.f * l32.x * l32.y);
            __syncwarp();
            mbar_wait(sb + GB_W, 0);
            const uint32_t ap = sb + (((lane >> 3) & 1) * 32 + 8 * w + (lane & 7)) * 1168 + (lane >> 4) * 16;
#pragma unroll
            for (int ks = 0; ks < 36; ks++) { const uint4 v = ldsm4(ap + ks * 32); a[4 * ks] = v.x; a[4 * ks + 1] = v.y; a[4 * ks + 2] = v.z; a[4 * ks + 3] = v.w; }
            bar_sync(1, 256);
            bar_arrive(6, 288);
            BSTAMP(1);
#pragma unroll 1
            for (int blk = wg; blk < 16; blk += 2) {
                bg_mainloop<9, 2>(d, a, sb, (blk >> 1) * 18 + wg, lane);
                float2 e = make_float2(0.f, 0.f);
#pragma unroll
                for (int i = 0; i < 32; i++) e = cfma(lam, e, make_float2(d[4 * (i >> 1) + (i & 1)], d[4 * (i >> 1) + 2 + (i & 1)]));
                float2 cin = make_float2(0.f, 0.f);
                if (blk > 0) { bar_sync(2 + (wg ^ 1), 256); cin = lds64f(sb + G_CARRY + (wg ^ 1) * 256 + (8 * w + g) * 8); }
                float2 mine = cin;
#pragma unroll
                for (int q = 0; q < 4; q++) {
                    const float2 eq = make_float2(__shfl_sync(~0u, e.x, (lane & 28) + q), __shfl_sync(~0u, e.y, (lane & 28) + q));
                    cin = cfma(l32, cin, eq);
                    if (t == q + 1) mine = cin;
                }
                if (blk < 15) {
                    if (t == 0) sts64(sb + G_CARRY + wg * 256 + (8 * w + g) * 8, __float_as_uint(cin.x), __float_as_uint(cin.y));
                    bar_arrive(2 + wg, 256);
                }
                const uint32_t hs = sb + G_OUT + wg * 16384 + t * 4096 + (g & 3) * 4;
                const uint32_t ch = 2 * w + (g >> 2);
                if (blk >= 2) bar_sync(10 + wg, 160);
#pragma unroll
                for (int i = 0; i < 32; i++) {
                    mine = cfma(lam, mine, make_float2(d[4 * (i >> 1) + (i & 1)], d[4 * (i >> 1) + 2 + (i & 1)]));
                    sts32(hs + i * 128 + ((ch ^ (i & 7)) << 4), pack_bf16(mine.x, mine.y));
                }
                fence_async_smem();
                bar_arrive(8 + wg, 160);
            }
            bar_sync(10 + wg, 160);
        } else {
            if (tid < 128)
                asm volatile("cp.async.bulk.shared::cluster.global.mbarrier::complete_tx::bytes [%0], [%1], 1152, [%2];"
                    :: "r"(sb + tid * 1168), "l"((tid < 64 ? Cre : Cim) + (size_t)(64 * nt + (tid & 63)) * DM), "r"(sb + GB_W) : "memory");
            for (int p = tid; p < DM; p += 256) {
                float2 lam, coef;
                s5_channel(p, Lre, Lim, logdt, lam, coef);
                sts64(sb + G_EX + p * 8, __float_as_uint(2.f * coef.x), __float_as_uint(2.f * coef.y));
            }
            bar_sync(1, 256);
            mbar_wait(sb + GB_W, 0);
            const uint32_t cp = sb + (16 * w + 2 * g) * 1168 + (288 * wg + t) * 2;
#pragma unroll
            for (int u = 0; u < 72; u++) {
                const float2 c2 = lds64f(sb + G_EX + (288 * wg + 4 * u + t) * 8);
#pragma unroll
                for (int f = 0; f < 2; f++) {
                    unsigned short r16, i16;
                    asm volatile("ld.shared.u16 %0, [%1];" : "=h"(r16) : "r"(cp + f * 1168 + u * 8) : "memory");
                    asm volatile("ld.shared.u16 %0, [%1];" : "=h"(i16) : "r"(cp + (64 + f) * 1168 + u * 8) : "memory");
                    const float cr = __uint_as_float((uint32_t)r16 << 16), ci = __uint_as_float((uint32_t)i16 << 16);
                    a[2 * u + f] = pack_bf16(cr * c2.x - ci * c2.y, -(cr * c2.y + ci * c2.x));
                }
            }
            bar_sync(1, 256);
            bar_arrive(6, 288);
            BSTAMP(1);
#pragma unroll 1
            for (int j = 0; j < 8; j++) {
                bg_mainloop<9, 2>(d, a, sb, j * 18 + wg, lane);
                bg_epilogue<true>(d, sb, wg, w, lane, &tm_out, 64 * nt, (2 * j + kq - 2) * 128, xa, Dk);
            }
        }
        if (w == 0) asm volatile("cp.async.bulk.wait_group 0;" ::: "memory");
        bar_sync(1, 256);
        BSTAMP(2);
        if (warp == 0)
            asm volatile("{\n.reg .pred p;\nelect.sync _|p, 0xffffffff;\n@p mbarrier.arrive.expect_tx.shared::cta.b64 _, [%2], 131072;\n"
                "@p cp.async.bulk.tensor.2d.shared::cluster.global.mbarrier::complete_tx::bytes [%0], [%1, {%3, %4}], [%2];\n"
                "@p cp.async.bulk.tensor.2d.shared::cluster.global.mbarrier::complete_tx::bytes [%0+32768], [%1, {%3, %5}], [%2];\n"
                "@p cp.async.bulk.tensor.2d.shared::cluster.global.mbarrier::complete_tx::bytes [%0+65536], [%1, {%3, %6}], [%2];\n"
                "@p cp.async.bulk.tensor.2d.shared::cluster.global.mbarrier::complete_tx::bytes [%0+98304], [%1, {%3, %7}], [%2];\n}"
                :: "r"(sb), "l"(&tm_wo), "r"(sb + GB_W), "r"(64 * nt), "r"(1024 * kq), "r"(1024 * kq + 256), "r"(1024 * kq + 512), "r"(1024 * kq + 768) : "memory");
        mbar_wait(sb + GB_W, 1);
        {
            const uint32_t base = sb + wg * 65536 + 4 * t * 128 + (g & 3) * 4, ch = 2 * w + (g >> 2), r7 = (4 * t) & 7;
#pragma unroll
            for (int ks = 0; ks < 32; ks++) {
                const uint32_t w0 = lds32(base + ks * 2048 + ((ch ^ r7) << 4)), w1 = lds32(base + ks * 2048 + 256 + ((ch ^ (r7 + 2)) << 4));
                const uint32_t w2 = lds32(base + ks * 2048 + 128 + ((ch ^ (r7 + 1)) << 4)), w3 = lds32(base + ks * 2048 + 384 + ((ch ^ (r7 + 3)) << 4));
                a[4 * ks] = __byte_perm(w0, w1, 0x5410); a[4 * ks + 1] = __byte_perm(w0, w1, 0x7632);
                a[4 * ks + 2] = __byte_perm(w2, w3, 0x5410); a[4 * ks + 3] = __byte_perm(w2, w3, 0x7632);
            }
        }
        bar_sync(1, 256);
        bar_arrive(6, 288);
        BSTAMP(3);
#pragma unroll 1
        for (int na = 0, ng = 0, it = 144; ng < 16;) {
            if (bg_att_turn(na, ng)) {
                if (nt < 8) {
                    const int i0 = it + wg + 4 * (w >> 1), i1 = i0 + 2;
                    mbar_wait(sb + GB_FULL + 8 * (i0 % NST), (i0 / NST) & 1);
                    mbar_wait(sb + GB_FULL + 8 * (i1 % NST), (i1 / NST) & 1);
                    BSTAMP(8 + na * 4);
                    bg_attention(sb + G_RING + (i0 % NST) * 16384, sb + G_RING + (i1 % NST) * 16384, w & 1, lane);
                    fence_async_smem();
                    bar_arrive(7, 288);
                    bar_sync(1, 256);
                    BSTAMP(9 + na * 4);
                    it += 8;
                }
                na++;
            } else {
                bg_mainloop<8, 2>(d, a, sb, it + wg, lane);
                BSTAMP(10 + ng * 4);
                bg_epilogue<false>(d, sb, wg, w, lane, &tm_out, DM + 64 * nt, ng * 128, xa, Dk);
                BSTAMP(11 + ng * 4);
                it += 16; ng++;
            }
        }
    }
    asm volatile("griddepcontrol.wait;" ::: "memory");
}

typedef CUresult (*EncodeFn)(CUtensorMap*, CUtensorMapDataType, cuuint32_t, void*, const cuuint64_t*, const cuuint64_t*, const cuuint32_t*, const cuuint32_t*,
                             CUtensorMapInterleave, CUtensorMapSwizzle, CUtensorMapL2promotion, CUtensorMapFloatOOBfill);
}

extern "C" void kernel_launch(void* const* d_in, const int* in_sizes, int n_in, void* d_out, int out_size) {
    typedef const __nv_bfloat16* bp;
    bp Ax = (bp)d_in[0], Lre = (bp)d_in[1], Lim = (bp)d_in[2], Bre = (bp)d_in[3], Bim = (bp)d_in[4], Cre = (bp)d_in[5], Cim = (bp)d_in[6],
       logdt = (bp)d_in[7], Dk = (bp)d_in[8], Bx = (bp)d_in[9], mem0 = (bp)d_in[10], Wq = (bp)d_in[11], Wk = (bp)d_in[12], Wv = (bp)d_in[13], Wo = (bp)d_in[14];
    float* out = (float*)d_out;
    static EncodeFn enc = nullptr;
    if (!enc) {
        void* fn = nullptr; cudaDriverEntryPointQueryResult qr;
        cudaGetDriverEntryPoint("cuTensorMapEncodeTiled", &fn, cudaEnableDefault, &qr);
        enc = (EncodeFn)fn;
        cudaFuncSetAttribute(chain_kernel, cudaFuncAttributeMaxDynamicSharedMemorySize, CHAIN_SMEM);
        cudaFuncSetAttribute(bg_kernel, cudaFuncAttributeMaxDynamicSharedMemorySize, BG_SMEM);
    }
    const cuuint32_t es[5] = {1, 1, 1, 1, 1};
    auto map2d = [&](CUtensorMap* tm, CUtensorMapDataType dt, const void* p, cuuint64_t d0, cuuint64_t d1, cuuint64_t stride, cuuint32_t b0, cuuint32_t b1) {
        cuuint64_t gd[2] = {d0, d1}, gs[1] = {stride}; cuuint32_t bd[2] = {b0, b1};
        enc(tm, dt, 2, (void*)p, gd, gs, bd, es, CU_TENSOR_MAP_INTERLEAVE_NONE, CU_TENSOR_MAP_SWIZZLE_128B, CU_TENSOR_MAP_L2_PROMOTION_L2_128B,
            CU_TENSOR_MAP_FLOAT_OOB_FILL_NONE);
    };
    CUtensorMap tm_x, tm_q, tm_k, tm_v, tm_xa, tm_wo, tm_out;
    map2d(&tm_x, CU_TENSOR_MAP_DATA_TYPE_BFLOAT16, Bx, DM, SEQ, DM * 2, 64, 32);
    map2d(&tm_q, CU_TENSOR_MAP_DATA_TYPE_BFLOAT16, Wq, HD, DM, HD * 2, 64, 192);
    map2d(&tm_k, CU_TENSOR_MAP_DATA_TYPE_BFLOAT16, Wk, HD, DM, HD * 2, 64, 192);
    map2d(&tm_v, CU_TENSOR_MAP_DATA_TYPE_BFLOAT16, Wv, HD, DM, HD * 2, 64, 192);
    map2d(&tm_wo, CU_TENSOR_MAP_DATA_TYPE_BFLOAT16, Wo, DM, HD, DM * 2, 64, 256);
    map2d(&tm_out, CU_TENSOR_MAP_DATA_TYPE_FLOAT32, out, 2 * DM, SEQ, 2 * DM * 4, 32, 64);
    {
        cuuint64_t gd[5] = {DM, 2, 4, 16, 16}, gs[4] = {DM * 2, 32 * DM * 2, 2 * DM * 2, 128 * DM * 2}; cuuint32_t bd[5] = {64, 2, 4, 16, 1};
        enc(&tm_xa, CU_TENSOR_MAP_DATA_TYPE_BFLOAT16, 5, (void*)Ax, gd, gs, bd, es, CU_TENSOR_MAP_INTERLEAVE_NONE, CU_TENSOR_MAP_SWIZZLE_128B,
            CU_TENSOR_MAP_L2_PROMOTION_L2_128B, CU_TENSOR_MAP_FLOAT_OOB_FILL_NONE);
    }
    cudaStream_t st = cudaStreamPerThread;
    {
        cudaLaunchConfig_t cfg = {};
        cfg.gridDim = dim3(96); cfg.blockDim = dim3(384); cfg.dynamicSmemBytes = CHAIN_SMEM; cfg.stream = st;
        cudaLaunchAttribute at[1];
        at[0].id = cudaLaunchAttributeClusterDimension; at[0].val.clusterDim.y = 1; at[0].val.clusterDim.z = 1;
        cfg.attrs = at; cfg.numAttrs = 1;
        static int csize = 0;
        if (!csize) {
            int n = 0;
            at[0].val.clusterDim.x = 6;
            csize = (CLUSTER6 && cudaOccupancyMaxActiveClusters(&n, chain_kernel, &cfg) == cudaSuccess && n >= 16) ? 6 : 3;
            (void)cudaGetLastError();
        }
        at[0].val.clusterDim.x = csize;
        cudaLaunchKernelEx(&cfg, chain_kernel, tm_x, tm_q, tm_k, tm_v, Bx, mem0, Wo);
    }
    cudaLaunchConfig_t cfg = {};
    cfg.gridDim = dim3(36); cfg.blockDim = dim3(384); cfg.dynamicSmemBytes = BG_SMEM; cfg.stream = st;
    cudaLaunchAttribute at[1];
    at[0].id = cudaLaunchAttributeProgrammaticStreamSerialization; at[0].val.programmaticStreamSerializationAllowed = 1;
    cfg.attrs = at; cfg.numAttrs = 1;
    cudaLaunchKernelEx(&cfg, bg_kernel, tm_xa, tm_wo, tm_out, Ax, Lre, Lim, Bre, Bim, Cre, Cim, logdt, Dk);
}
```

```cpp
#include <cuda_runtime.h>
#include <cuda.h>
#include <cuda_bf16.h>
#include <cuda_fp16.h>
#include <stdint.h>

#define D_WAIT 740

#define CLUSTER6 0
#define BG_PACE 0
#define RED_GAP 720
#define ACC_PF 1
#define QDEP 1
#define BG_AHEAD 5

namespace {

constexpr int DM = 576, NH = 32, SEQ = 2048, NSEG = 64, HD = 4096;

__device__ uint4 g_acc_raw[64 * 96 * 16 + 131072];
__device__ uint4 g_ox[NH * 2 * SEQ * 8];
constexpr int REC = 30720;
__device__ uint4 g_qkv[NSEG * NH * (REC / 16)];
__device__ uint4 g_h[18 * SEQ * 8];
constexpr int NFLAG = 4096, F_QKV = 0, F_OX = 512, F_H = 1024, F_OUT = 2048;
__device__ unsigned g_flag[NFLAG];
__device__ unsigned g_ticket, g_ticket_bg;
__device__ unsigned long long g_norm[96];
#define BSTAMP(i) do {} while (0)

__device__ __forceinline__ uint32_t smem_u32(const void* p) { return (uint32_t)__cvta_generic_to_shared(p); }
__device__ __forceinline__ uint32_t mapa(uint32_t a, uint32_t r) { uint32_t o; asm("mapa.shared::cluster.u32 %0, %1, %2;" : "=r"(o) : "r"(a), "r"(r)); return o; }
__device__ __forceinline__ uint32_t mapa_v(uint32_t a, uint32_t r) { uint32_t o; asm volatile("mapa.shared::cluster.u32 %0, %1, %2;" : "=r"(o) : "r"(a), "r"(r)); return o; }
__device__ __forceinline__ unsigned clk() { unsigned long long c; asm volatile("mov.u64 %0, %%clock64;" : "=l"(c) :: "memory"); return (unsigned)c; }
__device__ __forceinline__ void mbar_init(uint32_t bar, uint32_t cnt) { asm volatile("mbarrier.init.shared::cta.b64 [%0], %1;" :: "r"(bar), "r"(cnt) : "memory"); }
__device__ __forceinline__ void mbar_expect(uint32_t bar, uint32_t bytes) { asm volatile("mbarrier.arrive.expect_tx.shared::cta.b64 _, [%0], %1;" :: "r"(bar), "r"(bytes) : "memory"); }
__device__ __forceinline__ void mbar_wait(uint32_t bar, uint32_t parity) {
    asm volatile("{\n.reg .pred p;\n.reg .u32 n;\nmov.u32 n, 0;\n"
                 "W_%=: mbarrier.try_wait.parity.shared::cta.b64 p, [%0], %1;\n@p bra.uni D_%=;\n"
                 "add.u32 n, n, 1;\nsetp.lt.u32 p, n, 4000000;\n@p bra.uni W_%=;\ntrap;\nD_%=:\n}" :: "r"(bar), "r"(parity) : "memory");
}
__device__ __forceinline__ void mbar_expect_if(uint32_t z, uint32_t bar, uint32_t bytes) {
    asm volatile("{\n.reg .pred p;\nsetp.eq.u32 p, %2, 0;\n@p mbarrier.arrive.expect_tx.shared::cta.b64 _, [%0], %1;\n}" :: "r"(bar), "r"(bytes), "r"(z) : "memory");
}
__device__ __forceinline__ void mbar_arrive_if(uint32_t z, uint32_t bar) {
    asm volatile("{\n.reg .pred p;\nsetp.eq.u32 p, %1, 0;\n@p mbarrier.arrive.shared::cta.b64 _, [%0];\n}" :: "r"(bar), "r"(z) : "memory");
}
__device__ __forceinline__ void sts32_if(uint32_t z, uint32_t a, uint32_t x) {
    asm volatile("{\n.reg .pred p;\nsetp.eq.u32 p, %2, 0;\n@p st.shared.u32 [%0], %1;\n}" :: "r"(a), "r"(x), "r"(z) : "memory");
}
template <int K> __device__ __forceinline__ void sched_fence(int v) {
    asm volatile("{\n.reg .pred p;\nsetp.ne.s32 p, %0, %1;\n@p bra.uni F_%=;\ntrap;\nF_%=:\n}" :: "r"(v), "n"(1000 + K) : "memory");
}
__device__ __forceinline__ void spin_until(unsigned t0, unsigned d) {
    asm volatile("{\n.reg .pred p;\n.reg .u64 c;\n.reg .u32 lo;\n"
                 "S_%=: mov.u64 c, %%clock64;\ncvt.u32.u64 lo, c;\nsub.u32 lo, lo, %0;\nsetp.lt.u32 p, lo, %1;\n@p bra.uni S_%=;\n}" :: "r"(t0), "r"(d) : "memory");
}
__device__ __forceinline__ void bar_sync(int id, int n) { asm volatile("bar.sync %0, %1;" :: "r"(id), "r"(n) : "memory"); }
__device__ __forceinline__ void bar_sync_sel(int sel, int id) {
    asm volatile("{\n.reg .pred p;\nsetp.eq.u32 p, %0, 0;\n@p bar.sync %1, %3;\n@!p bar.sync %2, %3;\n}" :: "r"(sel), "r"(id), "r"(id + 1), "n"(192) : "memory");
}
__device__ __forceinline__ void bar_arrive(int id, int n) { asm volatile("bar.arrive %0, %1;" :: "r"(id), "r"(n) : "memory"); }
__device__ __forceinline__ void fence_async_smem() { asm volatile("fence.proxy.async.shared::cta;" ::: "memory"); }
__device__ __forceinline__ uint32_t pack_bf16(float lo, float hi) { uint32_t r; asm("cvt.rn.bf16x2.f32 %0, %1, %2;" : "=r"(r) : "f"(hi), "f"(lo)); return r; }
__device__ __forceinline__ uint32_t pack_f16(float lo, float hi) { uint32_t r; asm("cvt.rn.f16x2.f32 %0, %1, %2;" : "=r"(r) : "f"(hi), "f"(lo)); return r; }
__device__ __forceinline__ uint32_t f16x2_to_bf16x2(uint32_t v) { float2 f = __half22float2(*reinterpret_cast<__half2*>(&v)); return pack_bf16(f.x, f.y); }
__device__ __forceinline__ uint32_t hmul2(uint32_t a, uint32_t b) { uint32_t r; asm("mul.rn.f16x2 %0, %1, %2;" : "=r"(r) : "r"(a), "r"(b)); return r; }
__device__ __forceinline__ float ex2(float x) { float y; asm("ex2.approx.ftz.f32 %0, %1;" : "=f"(y) : "f"(x)); return y; }
__device__ __forceinline__ float ex2v(float x) { float y; asm volatile("ex2.approx.ftz.f32 %0, %1;" : "=f"(y) : "f"(x)); return y; }
__device__ __forceinline__ uint32_t absmax2(uint32_t a, uint32_t b) {
    uint32_t r; asm("max.xorsign.abs.bf16x2 %0, %1, %2;" : "=r"(r) : "r"(a), "r"(b)); return r;
}
__device__ __forceinline__ uint32_t shl_v(uint32_t a, int n) { return a << n; }
__device__ __forceinline__ uint32_t max3u(uint32_t a, uint32_t b, uint32_t c) { return max(max(a, b), c); }
__device__ __forceinline__ uint4 lds128(uint32_t a) { uint4 v; asm volatile("ld.shared.v4.u32 {%0,%1,%2,%3}, [%4];" : "=r"(v.x), "=r"(v.y), "=r"(v.z), "=r"(v.w) : "r"(a) : "memory"); return v; }
__device__ __forceinline__ uint4 lds128v(uint32_t a) { uint4 v; asm volatile("ld.volatile.shared.v4.u32 {%0,%1,%2,%3}, [%4];" : "=r"(v.x), "=r"(v.y), "=r"(v.z), "=r"(v.w) : "r"(a) : "memory"); return v; }
__device__ __forceinline__ float4 lds128f(uint32_t a) { float4 v; asm volatile("ld.shared.v4.f32 {%0,%1,%2,%3}, [%4];" : "=f"(v.x), "=f"(v.y), "=f"(v.z), "=f"(v.w) : "r"(a) : "memory"); return v; }
__device__ __forceinline__ float2 lds64f(uint32_t a) { float2 v; asm volatile("ld.shared.v2.f32 {%0,%1}, [%2];" : "=f"(v.x), "=f"(v.y) : "r"(a) : "memory"); return v; }
__device__ __forceinline__ uint4 lds64x2(uint32_t a) { uint4 v; asm volatile("ld.shared.v2.u32 {%0,%1}, [%4];\nld.shared.v2.u32 {%2,%3}, [%4+256];" : "=r"(v.x), "=r"(v.y), "=r"(v.z), "=r"(v.w) : "r"(a) : "memory"); return v; }
__device__ __forceinline__ uint32_t lds32(uint32_t a) { uint32_t v; asm volatile("ld.shared.u32 %0, [%1];" : "=r"(v) : "r"(a) : "memory"); return v; }
__device__ __forceinline__ void sts128(uint32_t a, uint32_t x, uint32_t y, uint32_t z, uint32_t w) { asm volatile("st.shared.v4.u32 [%0], {%1,%2,%3,%4};" :: "r"(a), "r"(x), "r"(y), "r"(z), "r"(w) : "memory"); }
__device__ __forceinline__ void sts128f(uint32_t a, float x, float y, float z, float w) { asm volatile("st.shared.v4.f32 [%0], {%1,%2,%3,%4};" :: "r"(a), "f"(x), "f"(y), "f"(z), "f"(w) : "memory"); }
__device__ __forceinline__ void sts64(uint32_t a, uint32_t x, uint32_t y) { asm volatile("st.shared.v2.u32 [%0], {%1,%2};" :: "r"(a), "r"(x), "r"(y) : "memory"); }
__device__ __forceinline__ void sts32(uint32_t a, uint32_t x) { asm volatile("st.shared.u32 [%0], %1;" :: "r"(a), "r"(x) : "memory"); }
__device__ __forceinline__ uint4 ldsm4(uint32_t a) { uint4 v; asm volatile("ldmatrix.sync.aligned.m8n8.x4.shared.b16 {%0,%1,%2,%3}, [%4];" : "=r"(v.x), "=r"(v.y), "=r"(v.z), "=r"(v.w) : "r"(a) : "memory"); return v; }
__device__ __forceinline__ void stsm2t(uint32_t a, uint32_t x, uint32_t y) { asm volatile("stmatrix.sync.aligned.m8n8.x2.trans.shared.b16 [%0], {%1,%2};" :: "r"(a), "r"(x), "r"(y) : "memory"); }
__device__ __forceinline__ void stsm4t(uint32_t a, uint32_t x, uint32_t y, uint32_t z, uint32_t w) { asm volatile("stmatrix.sync.aligned.m8n8.x4.trans.shared.b16 [%0], {%1,%2,%3,%4};" :: "r"(a), "r"(x), "r"(y), "r"(z), "r"(w) : "memory"); }
__device__ __forceinline__ void st_async64(uint32_t a, uint32_t x, uint32_t y, uint32_t bar) { asm volatile("st.async.shared::cluster.mbarrier::complete_tx::bytes.v2.b32 [%0], {%1,%2}, [%3];" :: "r"(a), "r"(x), "r"(y), "r"(bar) : "memory"); }
__device__ __forceinline__ void bulk_s2c(uint32_t dst, uint32_t src, uint32_t bytes, uint32_t bar) { asm volatile("cp.async.bulk.shared::cluster.shared::cta.mbarrier::complete_tx::bytes [%0], [%1], %2, [%3];" :: "r"(dst), "r"(src), "r"(bytes), "r"(bar) : "memory"); }
__device__ __forceinline__ void bulk_s2g(void* dst, uint32_t src, uint32_t bytes) { asm volatile("cp.async.bulk.global.shared::cta.bulk_group [%0], [%1], %2;" :: "l"(dst), "r"(src), "r"(bytes) : "memory"); }
__device__ __forceinline__ uint32_t ldg_nc32(const void* p) { uint32_t v; asm volatile("ld.global.nc.L2::128B.u32 %0, [%1];" : "=r"(v) : "l"(p)); return v; }
__device__ __forceinline__ uint4 ldg_relaxed128(const void* p) { uint4 v; asm volatile("ld.relaxed.gpu.global.v4.u32 {%0,%1,%2,%3}, [%4];" : "=r"(v.x), "=r"(v.y), "=r"(v.z), "=r"(v.w) : "l"(p) : "memory"); return v; }
__device__ __forceinline__ void mma16816(float (&d)[4], uint32_t a0, uint32_t a1, uint32_t a2, uint32_t a3, uint32_t b0, uint32_t b1) {
    asm volatile("mma.sync.aligned.m16n8k16.row.col.f32.bf16.bf16.f32 {%0,%1,%2,%3}, {%4,%5,%6,%7}, {%8,%9}, {%0,%1,%2,%3};"
        : "+f"(d[0]), "+f"(d[1]), "+f"(d[2]), "+f"(d[3]) : "r"(a0), "r"(a1), "r"(a2), "r"(a3), "r"(b0), "r"(b1));
}
__device__ __forceinline__ void mma16816_z(float (&d)[4], uint32_t a0, uint32_t a1, uint32_t a2, uint32_t a3, uint32_t b0, uint32_t b1) {
    asm volatile("mma.sync.aligned.m16n8k16.row.col.f32.bf16.bf16.f32 {%0,%1,%2,%3}, {%4,%5,%6,%7}, {%8,%9}, {%10,%10,%10,%10};"
        : "=f"(d[0]), "=f"(d[1]), "=f"(d[2]), "=f"(d[3]) : "r"(a0), "r"(a1), "r"(a2), "r"(a3), "r"(b0), "r"(b1), "f"(0.f));
}
__device__ __forceinline__ void mma1688(float (&d)[4], uint32_t a0, uint32_t a1, uint32_t b0) {
    asm volatile("mma.sync.aligned.m16n8k8.row.col.f32.bf16.bf16.f32 {%0,%1,%2,%3}, {%4,%5}, {%6}, {%0,%1,%2,%3};"
        : "+f"(d[0]), "+f"(d[1]), "+f"(d[2]), "+f"(d[3]) : "r"(a0), "r"(a1), "r"(b0));
}
__device__ __forceinline__ void mma1688_z(float (&d)[4], uint32_t a0, uint32_t a1, uint32_t b0) {
    asm volatile("mma.sync.aligned.m16n8k8.row.col.f32.bf16.bf16.f32 {%0,%1,%2,%3}, {%4,%5}, {%6}, {%7,%7,%7,%7};"
        : "=f"(d[0]), "=f"(d[1]), "=f"(d[2]), "=f"(d[3]) : "r"(a0), "r"(a1), "r"(b0), "f"(0.f));
}
template <int ACC>
__device__ __forceinline__ void wgmma_n32_rs(float (&d)[16], uint32_t a0, uint32_t a1, uint32_t a2, uint32_t a3, uint64_t desc) {
    asm volatile("wgmma.mma_async.sync.aligned.m64n32k16.f32.bf16.bf16 {%0,%1,%2,%3,%4,%5,%6,%7,%8,%9,%10,%11,%12,%13,%14,%15}, {%16,%17,%18,%19}, %20, %21, 1, 1, 0;"
        : "+f"(d[0]), "+f"(d[1]), "+f"(d[2]), "+f"(d[3]), "+f"(d[4]), "+f"(d[5]), "+f"(d[6]), "+f"(d[7]),
          "+f"(d[8]), "+f"(d[9]), "+f"(d[10]), "+f"(d[11]), "+f"(d[12]), "+f"(d[13]), "+f"(d[14]), "+f"(d[15])
        : "r"(a0), "r"(a1), "r"(a2), "r"(a3), "l"(desc), "n"(ACC));
}
template <int ACC>
__device__ __forceinline__ void wgmma_n32_ss(float (&d)[16], uint64_t da, uint64_t db) {
    asm volatile("wgmma.mma_async.sync.aligned.m64n32k16.f32.bf16.bf16 {%0,%1,%2,%3,%4,%5,%6,%7,%8,%9,%10,%11,%12,%13,%14,%15}, %16, %17, %18, 1, 1, 0, 0;"
        : "+f"(d[0]), "+f"(d[1]), "+f"(d[2]), "+f"(d[3]), "+f"(d[4]), "+f"(d[5]), "+f"(d[6]), "+f"(d[7]),
          "+f"(d[8]), "+f"(d[9]), "+f"(d[10]), "+f"(d[11]), "+f"(d[12]), "+f"(d[13]), "+f"(d[14]), "+f"(d[15])
        : "l"(da), "l"(db), "n"(ACC));
}
__device__ __forceinline__ void wg_fence() { asm volatile("wgmma.fence.sync.aligned;" ::: "memory"); }
__device__ __forceinline__ void wg_commit() { asm volatile("wgmma.commit_group.sync.aligned;" ::: "memory"); }
__device__ __forceinline__ void wg_wait0() { asm volatile("wgmma.wait_group.sync.aligned 0;" ::: "memory"); }
__device__ __forceinline__ void cluster_sync() { asm volatile("barrier.cluster.arrive.aligned;\nbarrier.cluster.wait.aligned;" ::: "memory"); }

#define STAMP(s, i) do {} while (0)
#define STAMPV(s, i, v) do {} while (0)

constexpr int XT_BYTES = 36864;
constexpr int O_XT = 0;
constexpr int O_STG = XT_BYTES;
constexpr int O_AS = 3 * XT_BYTES;
constexpr int O_XP = O_AS + 16384;
constexpr int O_QKX = O_XP + 8192;
constexpr int O_KM = O_QKX + 8192;
constexpr int O_QM = O_QKX + 10240;
constexpr int O_VX = O_STG + 147456;
constexpr int O_VM = O_VX + 16384;
constexpr int O_SC = O_VM + 2048;
constexpr int O_OF = O_SC + 2560;
constexpr int O_AF = O_OF + 2048;
constexpr int O_WP = O_AF + 4096;
constexpr int O_MF = O_WP + 2048;
constexpr int O_MISC = O_MF + 9216;
static_assert(O_QKX + 24576 <= O_VX, "smem");
constexpr int O_BAR = O_MISC + 64;
constexpr int CHAIN_SMEM = O_BAR + 128;
static_assert(CHAIN_SMEM <= 232448, "smem");
constexpr int B_X = O_BAR, B_VX = O_BAR + 24, B_SC = O_BAR + 40, B_W = O_BAR + 48;
constexpr float SM_SCALE = 0.08838834764831845f * 1.4426950408889634f;
constexpr uint32_t ONES = 0x3f803f80u;

__device__ __forceinline__ uint32_t opaque(uint32_t v) { uint32_t o; asm volatile("mov.u32 %0, %1;" : "=r"(o) : "r"(v)); return o; }
__device__ __forceinline__ void st_async128(uint32_t a, uint32_t x, uint32_t y, uint32_t z, uint32_t w, uint32_t bar) {
    asm volatile("st.async.shared::cluster.mbarrier::complete_tx::bytes.v4.b32 [%0], {%1,%2,%3,%4}, [%5];" :: "r"(a), "r"(x), "r"(y), "r"(z), "r"(w), "r"(bar) : "memory");
}
__device__ __forceinline__ void tma_x_tile(uint32_t sb, const CUtensorMap* tm, int rb, int r, int j, int slot) {
    asm volatile("{\n.reg .pred p;\nelect.sync _|p, 0xffffffff;\n"
        "@p mbarrier.arrive.expect_tx.shared::cta.b64 _, [%2], 36864;\n"
        "@p cp.async.bulk.tensor.2d.shared::cluster.global.mbarrier::complete_tx::bytes.multicast::cluster [%0], [%1, {%3, %4}], [%2], %7;\n"
        "@p cp.async.bulk.tensor.2d.shared::cluster.global.mbarrier::complete_tx::bytes.multicast::cluster [%0+4096], [%1, {%5, %4}], [%2], %7;\n"
        "@p cp.async.bulk.tensor.2d.shared::cluster.global.mbarrier::complete_tx::bytes.multicast::cluster [%0+8192], [%1, {%6, %4}], [%2], %7;\n}"
        :: "r"(sb + O_XT + slot * XT_BYTES + 3 * r * 4096), "l"(tm), "r"(sb + B_X + 8 * slot), "r"(192 * r), "r"(j * 32), "r"(192 * r + 64), "r"(192 * r + 128),
           "h"((unsigned short)(7 << rb)) : "memory");
}
__device__ __forceinline__ float quad_max(float v) {
    const float a = __shfl_xor_sync(~0u, v, 1), b = __shfl_xor_sync(~0u, v, 2), c = __shfl_xor_sync(~0u, v, 3);
    return fmaxf(fmaxf(v, a), fmaxf(b, c));
}
__device__ __forceinline__ void load_scores(float (&p)[10], uint32_t base, uint32_t stride, uint32_t l16) {
    const float4 a0 = lds128f(base + l16), b0 = lds128f(base + stride + l16);
    const float4 a1 = lds128f(base + 512 + l16), b1 = lds128f(base + stride + 512 + l16);
    const float2 a2 = lds64f(base + 1024 + (l16 >> 1)), b2 = lds64f(base + stride + 1024 + (l16 >> 1));
    p[0] = a2.x + b2.x; p[1] = a2.y + b2.y;
    p[2] = a0.x + b0.x; p[3] = a0.y + b0.y; p[4] = a0.z + b0.z; p[5] = a0.w + b0.w;
    p[6] = a1.x + b1.x; p[7] = a1.y + b1.y; p[8] = a1.z + b1.z; p[9] = a1.w + b1.w;
}
__device__ __forceinline__ float rcp_fast(float x) { float y; asm("rcp.approx.ftz.f32 %0, %1;" : "=f"(y) : "f"(x)); return y; }

__global__ void __launch_bounds__(384, 1)
chain_kernel(const __grid_constant__ CUtensorMap tm_x, const __grid_constant__ CUtensorMap tm_q,
             const __grid_constant__ CUtensorMap tm_k, const __grid_constant__ CUtensorMap tm_v,
             const __nv_bfloat16* __restrict__ x, const __nv_bfloat16* __restrict__ mem0,
             const __nv_bfloat16* __restrict__ Wo) {
    extern __shared__ __align__(1024) uint8_t smem_raw[];
    const uint32_t sb = smem_u32(smem_raw);
    const int lane = threadIdx.x & 31;
    const int warp = __shfl_sync(~0u, threadIdx.x >> 5, 0);
    const int wg = warp >> 2, w = warp & 3;
    const int h = blockIdx.x / 3, r = blockIdx.x - 3 * h;
    uint4* const g_acc = reinterpret_cast<uint4*>((reinterpret_cast<uintptr_t>(g_acc_raw) + 0x1fffff) & ~(uintptr_t)0x1fffff);
    int rb;
    asm("mov.u32 %0, %%cluster_ctarank;" : "=r"(rb));
    rb -= r;

#define PSTAMP(i) do {} while (0)
    if (threadIdx.x == 0) {
        if (sb & 1023u) __trap();
        for (int i = 0; i < 9; i++) mbar_init(sb + O_BAR + 8 * i, 1);
        asm volatile("fence.mbarrier_init.release.cluster;" ::: "memory");
        for (int i = 0; i < 3; i++) {
            mbar_expect(sb + B_W + 8 * i, 49152);
            for (int tl = 0; tl < 2; tl++)
                asm volatile("cp.async.bulk.tensor.2d.shared::cluster.global.mbarrier::complete_tx::bytes [%0], [%1, {%3, %4}], [%2];"
                    :: "r"(sb + O_STG + tl * 73728 + i * 24576), "l"(r < 2 ? (tl ? &tm_k : &tm_q) : &tm_v), "r"(sb + B_W + 8 * i),
                       "r"(h * 128 + 64 * (r < 2 ? r : tl)), "r"(192 * i) : "memory");
        }
    }
    __syncwarp();
    asm volatile("barrier.cluster.arrive.relaxed.aligned;" ::: "memory");
    asm volatile("griddepcontrol.launch_dependents;" ::: "memory");
    if (warp == 0) PSTAMP(9);
    const uint32_t l16c = __shfl_sync(~0u, lane * 16, lane);

    if (wg < 2) {
#define KS(u) ((u) < 8 ? 12 * ((u) >> 2) + (((u) >> 1) & 1) + 4 * ((u) & 1) : (u) < 12 ? (u) : (u) < 16 ? (u) + 8 : (u) < 24 ? 24 + (((u) - 16) >> 1) + 4 * ((u) & 1) : (u) + 8)
        asm volatile("setmaxnreg.inc.sync.aligned.u32 184;");
        uint32_t a[144];
        uint32_t adr1;
        {
            const int g = lane >> 2, t = lane & 3;
            const int t1 = threadIdx.x;
#pragma unroll
            for (int i = 0; i < 2; i++) g_acc[(blockIdx.x * 64 + i * 32 + (t1 >> 3)) * 16 + (t1 & 7)] = make_uint4(0, 0, 0, 0);
            __threadfence();
            asm volatile("barrier.cluster.wait.aligned;" ::: "memory");
            const uint32_t ev = sb + O_STG + (2 * t) * 128 + (((2 * w + (g >> 2)) ^ (2 * t)) << 4) + (g & 3) * 4;
            const uint32_t od = (ev ^ 16) + 128;
            auto gather = [&](int dst, uint32_t off) {
                a[dst] = lds32(ev + off); a[dst + 1] = lds32(od + off); a[dst + 2] = lds32(ev + off + 1024); a[dst + 3] = lds32(od + off + 1024);
            };
            const uint4* xp = reinterpret_cast<const uint4*>(x) + blockIdx.x * 1536 + t1;
            uint4 xv[6];
#pragma unroll
            for (int th = 0; th < 2; th++) {
                mbar_wait(sb + B_W + 8 * th, 0);
                if (th == 1) {
#pragma unroll
                    for (int i = 0; i < 6; i++) xv[i] = __ldg(xp + i * 256);
                }
#pragma unroll
                for (int u = 4 * th; u < 4 * th + 4; u++) {
                    gather(32 + 4 * u, wg * (73728 + 4096) + KS(u) * 2048);
                    gather(4 * u, 73728 - wg * (73728 - 4096) + KS(u) * 2048);
                    gather(64 + 4 * u, wg * 73728 + KS(8 + u) * 2048);
                }
            }
            mbar_wait(sb + B_W + 16, 0);
#pragma unroll
            for (int u = 16; u < 28; u++) gather(32 + 4 * u, wg * 73728 + KS(u) * 2048);
#pragma unroll
            for (int kk = 0; kk < 72; kk++) {
                uint32_t w0 = a[2 * kk], w1 = a[2 * kk + 1];
                a[2 * kk] = __byte_perm(w0, w1, 0x5410);
                a[2 * kk + 1] = __byte_perm(w0, w1, 0x7632);
            }
            if (r == 2) {
                float n0[4], n1[4];
#pragma unroll
                for (int u = 0; u < 36; u++) {
                    const uint32_t x0 = a[4 * u] & 0x7fff7fffu, x1 = a[4 * u + 1] & 0x7fff7fffu, x2 = a[4 * u + 2] & 0x7fff7fffu, x3 = a[4 * u + 3] & 0x7fff7fffu;
                    if (u == 0) mma16816_z(n0, x0, x1, x2, x3, ONES, ONES);
                    else if (u < 8) mma16816(n0, x0, x1, x2, x3, ONES, ONES);
                    else if (u == 8) mma16816_z(n1, x0, x1, x2, x3, ONES, ONES);
                    else mma16816(n1, x0, x1, x2, x3, ONES, ONES);
                }
                const uint32_t mx = __reduce_max_sync(~0u, __float_as_uint(2.f * fmaxf(fmaxf(n0[0], n0[2]), fmaxf(n1[0], n1[2]))));
                sts32_if(lane, sb + O_MISC + 32 + 4 * warp, mx);
            }
            uint32_t xm = 0;
#pragma unroll
            for (int i = 0; i < 6; i++)
                xm = __vmaxu2(xm, __vmaxu2(__vmaxu2(xv[i].x & 0x7fff7fffu, xv[i].y & 0x7fff7fffu), __vmaxu2(xv[i].z & 0x7fff7fffu, xv[i].w & 0x7fff7fffu)));
            sts32_if(lane, sb + O_OF + 16 + 4 * warp, __reduce_max_sync(~0u, max(xm << 16, xm & 0xffff0000u)));
            if (warp == 0) PSTAMP(11);
            bar_arrive(7, 384);
            asm volatile("barrier.cluster.arrive.relaxed.aligned;" ::: "memory");
            bar_sync(1, 256);
            const uint32_t as = sb + O_AS + wg * 8192 + (16 * w + g) * 128 + t * 4;
            sts32(as + (g << 4), a[32]);
            sts32(as + 1024 + (g << 4), a[33]);
            sts32(as + ((1 ^ g) << 4), a[34]);
            sts32(as + 1024 + ((1 ^ g) << 4), a[35]);
            sts128(sb + O_AF + warp * 512 + lane * 16, a[32], a[33], a[34], a[35]);
            fence_async_smem();
            bar_sync(1, 256);
            const uint32_t l = lane * 16;
            const int mi = lane >> 3, isk = (mi >> 1) ? wg : (wg ^ 1);
            adr1 = (r == 2) ? (sb + O_VM + warp * 256 + (l >> 1))
                            : (isk ? (sb + O_KM + w * 512 + wg * 256 + (mi & 1) * 128 + (l & 127))
                                   : (sb + O_QM + w * 512 + (mi & 1) * 256 + wg * 128 + (l & 127)));
            adr1 = __shfl_sync(~0u, adr1, lane);
        }
        int s3 = 2;
#pragma unroll 1
        for (int s = -1; s < NSEG; s++) {
            const uint32_t l16 = opaque(l16c);
            s3 = (s3 == 2) ? 0 : s3 + 1;
            if (s < 0) mbar_wait(sb + B_X, 0);
            const uint64_t desc0 = (uint64_t)(((sb + O_XT + s3 * XT_BYTES) & 0x3FFFF) >> 4) | (1ull << 16) | (64ull << 32) | (1ull << 62);
            uint32_t km0 = 0, km1 = 0;
            if (s >= 0) {
                { const uint4 v = lds128(sb + O_AF + warp * 512 + l16); a[32] = v.x; a[33] = v.y; a[34] = v.z; a[35] = v.w; }
                float co[4], cw[3][4];
                uint4 b[14];
                float inv;
#define GORD(i) ((i) < 8 ? 2 * ((i) >> 2) + (((i) >> 1) & 1) + 4 * ((i) & 1) : (i))
                auto qkv_mma = [&](int i) {
                    const int gi = GORD(i), u = 8 * gi, n0 = 2 * i, n1 = 2 * i + 1;
                    if (gi < 4) {
                        if (i == 0) mma16816_z(co, a[u], a[u + 1], a[u + 2], a[u + 3], b[0].x, b[0].y);
                        else mma16816(co, a[u], a[u + 1], a[u + 2], a[u + 3], b[i].x, b[i].y);
                    }
                    if (n0 < 3) mma16816_z(cw[n0 % 3], a[32 + u], a[32 + u + 1], a[32 + u + 2], a[32 + u + 3], b[i].x, b[i].y);
                    else mma16816(cw[n0 % 3], a[32 + u], a[32 + u + 1], a[32 + u + 2], a[32 + u + 3], b[i].x, b[i].y);
                    if (n1 < 3) mma16816_z(cw[n1 % 3], a[32 + u + 4], a[32 + u + 5], a[32 + u + 6], a[32 + u + 7], b[i].z, b[i].w);
                    else mma16816(cw[n1 % 3], a[32 + u + 4], a[32 + u + 5], a[32 + u + 6], a[32 + u + 7], b[i].z, b[i].w);
                    if (gi < 4) mma16816(co, a[u + 4], a[u + 5], a[u + 6], a[u + 7], b[i].z, b[i].w);
                };
                const uint32_t mf = sb + O_MF + l16, mfs = mf + wg * 1024;
                const uint32_t qb = (s & 1) * 12288;
                bar_sync(2, 384);
                if (warp == 0) STAMP(s, 0);
                auto qkv_ld = [&](int i) {
                    const int gi = GORD(i);
                    b[i] = gi < 4 ? lds128v(mfs + (gi >> 1) * 3072 + (gi & 1) * 512) : lds128v(mf + (gi < 6 ? gi : gi + 4) * 512);
                };
#pragma unroll
                for (int i = 0; i < 4; i++) qkv_ld(i);
                const uint32_t zero = l16 & 15u;
                qkv_mma(0); qkv_mma(1);
                const uint32_t z0 = __float_as_uint(QDEP ? cw[0][0] : co[0]) & zero;
                qkv_mma(2);
                const uint32_t z1 = __float_as_uint(co[0]) & zero;
                bar_sync(0, 384);
                b[4] = lds128v(mfs + 3072 + (QDEP < 2 ? z0 : z1));
#pragma unroll
                for (int i = 5; i < 8; i++) qkv_ld(i);
                qkv_mma(3); qkv_mma(4); qkv_mma(5);
                const uint32_t z2 = __float_as_uint(QDEP ? cw[2][0] : co[0]) & zero;
                qkv_mma(6);
                const uint32_t z3 = __float_as_uint(co[0]) & zero;
                bar_sync(15, 384);
                b[8] = lds128v(mf + 12 * 512 + (QDEP < 2 ? z2 : z3));
#pragma unroll
                for (int i = 9; i < 12; i++) qkv_ld(i);
                qkv_mma(7);
                qkv_ld(12); qkv_mma(8); qkv_ld(13);
                asm volatile("ld.volatile.shared.f32 %0, [%1];" : "=f"(inv) : "r"(sb + O_MISC) : "memory");
#pragma unroll
                for (int i = 9; i < 14; i++) qkv_mma(i);
#pragma unroll
                for (int i = 0; i < 4; i++) cw[0][i] += cw[1][i] + cw[2][i];
                if (r < 2) {
                    const uint32_t o0 = pack_bf16(co[0] * inv, co[1] * inv), o1 = pack_bf16(co[2] * inv, co[3] * inv);
                    const uint32_t w0 = pack_bf16(cw[0][0] * inv, cw[0][1] * inv), w1 = pack_bf16(cw[0][2] * inv, cw[0][3] * inv);
                    stsm4t(adr1 + qb, o0, o1, w0, w1);
                    if (warp == 0) STAMP(s, 1);
                    asm volatile("{\n.reg .pred p;\nsetp.ge.u32 p, %0, 3;\n@p bar.arrive 1, 256;\n}" :: "r"(warp) : "memory");
                    if (warp < 3 && s < NSEG - 1) {
                        uint4 q[4], k[4];
                        const uint32_t ka = sb + O_QKX + 4096 + qb + warp * 2048 + l16;
#pragma unroll
                        for (int i = 0; i < 4; i++) k[i] = ldsm4(ka + i * 512);
                        const uint32_t dst = sb + O_SC + r * 1280 + warp * 512 + (l16 >> 1);
                        bar_sync(1, 256);
#pragma unroll
                        for (int i = 0; i < 4; i++) q[i] = ldsm4(sb + O_QM + qb + i * 512 + l16);
                        if (warp == 2) {
#pragma unroll
                            for (int i = 0; i < 4; i++) k[i] = ldsm4(ka + i * 512);
                        }
                        float s0[4], s1[4], t0[4], t1[4];
                        mma16816_z(s0, q[0].x, q[0].y, q[0].z, q[0].w, k[0].x, k[0].y);
                        mma16816_z(s1, q[0].x, q[0].y, q[0].z, q[0].w, k[0].z, k[0].w);
                        mma16816_z(t0, q[1].x, q[1].y, q[1].z, q[1].w, k[1].x, k[1].y);
                        mma16816_z(t1, q[1].x, q[1].y, q[1].z, q[1].w, k[1].z, k[1].w);
                        mma16816(s0, q[2].x, q[2].y, q[2].z, q[2].w, k[2].x, k[2].y);
                        mma16816(s1, q[2].x, q[2].y, q[2].z, q[2].w, k[2].z, k[2].w);
                        mma16816(t0, q[3].x, q[3].y, q[3].z, q[3].w, k[3].x, k[3].y);
                        mma16816(t1, q[3].x, q[3].y, q[3].z, q[3].w, k[3].z, k[3].w);
                        const float v0 = (s0[0] + s0[2]) + (t0[0] + t0[2]), v1 = (s0[1] + s0[3]) + (t0[1] + t0[3]);
                        const float v2 = (s1[0] + s1[2]) + (t1[0] + t1[2]), v3 = (s1[1] + s1[3]) + (t1[1] + t1[3]);
                        if (warp < 2) {
                            const uint32_t dv = dst + (l16 >> 1);
                            st_async128(mapa(dv, rb + (2)), __float_as_uint(v0), __float_as_uint(v1), __float_as_uint(v2), __float_as_uint(v3), mapa(sb + B_SC, rb + (2)));
                            st_async128(mapa(dv, rb + (r ^ 1)), __float_as_uint(v0), __float_as_uint(v1), __float_as_uint(v2), __float_as_uint(v3), mapa(sb + B_SC, rb + (r ^ 1)));
                            st_async128(mapa(dv, rb + (r)), __float_as_uint(v0), __float_as_uint(v1), __float_as_uint(v2), __float_as_uint(v3), mapa(sb + B_SC, rb + (r)));
                        } else {
                            st_async64(mapa(dst, rb + (2)), __float_as_uint(v0 + v2), __float_as_uint(v1 + v3), mapa(sb + B_SC, rb + (2)));
                            st_async64(mapa(dst, rb + (r ^ 1)), __float_as_uint(v0 + v2), __float_as_uint(v1 + v3), mapa(sb + B_SC, rb + (r ^ 1)));
                            st_async64(mapa(dst, rb + (r)), __float_as_uint(v0 + v2), __float_as_uint(v1 + v3), mapa(sb + B_SC, rb + (r)));
                        }
                        if (warp == 2) STAMP(s, 2);
                    } else if (warp < 3) {
                        bar_sync(1, 256);
                    }
                } else {
                    sts128f(sb + O_XP + warp * 512 + l16, co[0], co[1], co[2], co[3]);
                    bar_sync(8 + w, 64);
                    const float4 o = lds128f(sb + O_XP + (warp ^ 4) * 512 + l16);
                    km0 = pack_bf16((cw[0][0] + o.x) * inv, (cw[0][1] + o.y) * inv);
                    km1 = pack_bf16((cw[0][2] + o.z) * inv, (cw[0][3] + o.w) * inv);
                    if (warp == 0) STAMP(s, 1);
                    if (s < NSEG - 1) {
                        st_async64(mapa(adr1, rb + (0)), km0, km1, mapa(sb + B_SC, rb + (0)));
                        st_async64(mapa(adr1, rb + (1)), km0, km1, mapa(sb + B_SC, rb + (1)));
                        st_async64(mapa(adr1, rb + (2)), km0, km1, mapa(sb + B_SC, rb + (2)));
                    }
                    if (warp == 0) STAMP(s, 2);
                }
            }
            char* rec = reinterpret_cast<char*>(g_qkv) + (size_t)(s * NH + h) * REC;
            auto store_qk = [&]() {
                asm volatile("{\n.reg .pred p;\nelect.sync _|p, 0xffffffff;\n"
                    "@p cp.async.bulk.global.shared::cta.bulk_group [%0], [%1], 10240;\n@p cp.async.bulk.commit_group;\n}"
                    :: "l"(rec + r * 10240), "r"(sb + O_QKX + (s & 1) * 12288) : "memory");
            };
            auto store_vm = [&]() { *reinterpret_cast<uint2*>(rec + 28672 + warp * 256 + (l16 >> 1)) = make_uint2(km0, km1); };
            if (s == NSEG - 1) fence_async_smem();
            if (s >= 0) bar_sync(3, 384);
            if (s == NSEG - 1) {
                if (r == 2) store_vm();
                else if (warp == 3) {
                    store_qk();
                    asm volatile("cp.async.bulk.wait_group 0;\nfence.proxy.async.global;" ::: "memory");
                }
            } else {
                const int j = s + 1;
#define XDESC(u) (((u) < 8 ? descs : desc0) + (uint64_t)(((KS(u) >> 2) * 4096 + (KS(u) & 3) * 32) >> 4))
                const uint64_t descs = desc0 + (uint64_t)(wg * 4);
                float d[16];
                wg_fence();
#pragma unroll
                for (int u = 0; u < 8; u++) {
                    if (u == 0) wgmma_n32_rs<0>(d, a[0], a[1], a[2], a[3], XDESC(0));
                    else wgmma_n32_rs<1>(d, a[4 * u], a[4 * u + 1], a[4 * u + 2], a[4 * u + 3], XDESC(u));
                }
                wg_commit();
                wg_wait0();
                if (warp == 0) STAMP(s, 15);
                if (s >= 0) bar_sync(4, 384);
#pragma unroll
                for (int q = 0; q < 2; q++)
                    sts128(sb + O_XP + warp * 1024 + q * 512 + l16, pack_bf16(d[8 * q], d[8 * q + 1]), pack_bf16(d[8 * q + 2], d[8 * q + 3]),
                           pack_bf16(d[8 * q + 4], d[8 * q + 5]), pack_bf16(d[8 * q + 6], d[8 * q + 7]));
                if (s >= 0) {
                    if (r == 2) store_vm();
                    else fence_async_smem();
                    if (warp == 3) asm volatile("cp.async.bulk.wait_group 0;\nfence.proxy.async.global;" ::: "memory");
                    if (warp == 1 && s + 2 < NSEG) tma_x_tile(sb, &tm_x, rb, r, s + 2, s3 == 2 ? 0 : s3 + 1);
                }
                bar_sync(12, 256);
#pragma unroll
                for (int q = 0; q < 2; q++) {
                    const uint4 o = lds128(sb + O_XP + (warp ^ 4) * 1024 + q * 512 + l16);
                    d[8 * q] = __uint_as_float(o.x << 16); d[8 * q + 1] = __uint_as_float(o.x & 0xffff0000u);
                    d[8 * q + 2] = __uint_as_float(o.y << 16); d[8 * q + 3] = __uint_as_float(o.y & 0xffff0000u);
                    d[8 * q + 4] = __uint_as_float(o.z << 16); d[8 * q + 5] = __uint_as_float(o.z & 0xffff0000u);
                    d[8 * q + 6] = __uint_as_float(o.w << 16); d[8 * q + 7] = __uint_as_float(o.w & 0xffff0000u);
                }
                if (s >= 0) {
                    if (warp == 6 && (s & 3) == 0 && s >= 4)
                        asm volatile("{\n.reg .pred p;\nsetp.eq.u32 p, %1, 0;\n@p red.release.gpu.global.inc.u32 [%0], 0xffffffff;\n}"
                                     :: "l"(&g_flag[F_QKV + (s - 4 + (h >> 3)) * 8]), "r"(l16) : "memory");
                    asm volatile("{\n.reg .pred p;\nsetp.eq.u32 p, %0, 0;\n@p bar.sync 5, 256;\n@!p bar.sync 13, 256;\n}" :: "r"(wg) : "memory");
                }
                const uint64_t da0 = (uint64_t)(((sb + O_AS + wg * 8192) & 0x3FFFF) >> 4) | (1ull << 16) | (64ull << 32) | (1ull << 62);
                wg_fence();
                wgmma_n32_ss<1>(d, da0, XDESC(0));
#pragma unroll
                for (int u = 1; u < 28; u++) wgmma_n32_rs<1>(d, a[32 + 4 * u], a[32 + 4 * u + 1], a[32 + 4 * u + 2], a[32 + 4 * u + 3], XDESC(u));
                wg_commit();
                wg_wait0();
                if (warp == 3 && r < 2 && s >= 0) store_qk();
                if (warp == 4) STAMP(s, 3);
                uint32_t e[8];
#pragma unroll
                for (int i = 0; i < 8; i++) e[i] = pack_bf16(d[2 * i], d[2 * i + 1]);
                if (r < 2) {
                    const uint32_t base = sb + O_QKX + (j & 1) * 12288 + wg * 4096 + w * 512 + l16;
                    stsm4t(base, e[0], wg ? e[1] : e[2], wg ? e[2] : e[1], e[3]);
                    stsm4t(base + 2048, e[4], wg ? e[5] : e[6], wg ? e[6] : e[5], e[7]);
                } else {
                    const uint32_t base = sb + O_VX + (j & 1) * 8192 + warp * 1024 + l16;
                    sts128(base, e[0], e[1], e[2], e[3]);
                    sts128(base + 512, e[4], e[5], e[6], e[7]);
                    fence_async_smem();
                    bar_arrive(14, 288);
                }
                if (warp == 7) STAMP(s, 4);
                if (s < 0) asm volatile("barrier.cluster.wait.aligned;" ::: "memory");
            }
        }
        bar_arrive(7, 384);
    } else {
        asm volatile("setmaxnreg.dec.sync.aligned.u32 136;");
        const int c = w;
        uint32_t a[96];
        uint32_t mmax = 0;
        {
            const int g = lane >> 2, t = lane & 3;
            uint32_t tag = 0, m0v[18];
            if (threadIdx.x == 256) tag = atomicAdd(&g_ticket, 1u);
#pragma unroll
            for (int i = 0; i < 9; i++) {
                const uint32_t* p = reinterpret_cast<const uint32_t*>(mem0 + g * DM + 16 * (4 * i + c) + 2 * t);
                m0v[2 * i] = __ldg(p); m0v[2 * i + 1] = __ldg(p + 4);
            }
            asm volatile("barrier.cluster.wait.aligned;" ::: "memory");
            if (c == 0) {
                tma_x_tile(sb, &tm_x, rb, r, 0, 0);
                mbar_expect_if(lane, sb + B_SC, 4608);
                if (r < 2) mbar_expect_if(lane, sb + B_VX, 8192);
                sts32_if(lane, sb + O_MISC, __float_as_uint(1.0f));
                sts32_if(lane, sb + O_MISC + 12, __float_as_uint(SM_SCALE));
            }
            asm volatile("barrier.cluster.arrive.relaxed.aligned;" ::: "memory");
#pragma unroll
            for (int tau = 0; tau < 3; tau++) {
                const uint32_t* v = m0v + 6 * tau;
                sts128(sb + O_MF + tau * 3072 + c * 512 + lane * 16, v[0], v[1], v[2], v[3]);
                sts64(sb + O_MF + tau * 3072 + 2048 + (c >> 1) * 512 + lane * 16 + (c & 1) * 8, v[4], v[5]);
#pragma unroll
                for (int i = 0; i < 6; i++) mmax = __vmaxu2(mmax, v[i] & 0x7fff7fffu);
            }
            mmax = max(mmax << 16, mmax & 0xffff0000u);
            bar_arrive(2, 384); bar_arrive(0, 384); bar_arrive(15, 384);
            tag = (__shfl_sync(~0u, tag, 0) / 96u + 1u) & 0xffffu;
            mbar_wait(sb + B_W + 0, 0);
            const __nv_bfloat16* p = Wo + (size_t)(h * 128 + 4 * t) * DM + 192 * r + 16 * c + 2 * g;
#pragma unroll
            for (int i = 0; i < 3; i++)
#pragma unroll
                for (int eb = 0; eb < 8; eb++)
#pragma unroll
                    for (int j = 0; j < 4; j++) a[(i * 8 + eb) * 4 + j] = ldg_nc32(p + (16 * eb + ((j & 1) * 2 + (j >> 1))) * DM + 64 * i);
#pragma unroll
            for (int kk = 0; kk < 48; kk++) {
                uint32_t w0 = a[2 * kk], w1 = a[2 * kk + 1];
                a[2 * kk] = __byte_perm(w0, w1, 0x5410);
                a[2 * kk + 1] = __byte_perm(w0, w1, 0x7632);
            }
            sts128(sb + O_WP + c * 512 + lane * 16, a[92], a[93], a[94], a[95]);
            float wmax = 0.f;
#pragma unroll
            for (int i = 0; i < 3; i++) {
                float n0[4];
#pragma unroll
                for (int u = 8 * i; u < 8 * i + 8; u++) {
                    const uint32_t x0 = a[4 * u] & 0x7fff7fffu, x1 = a[4 * u + 1] & 0x7fff7fffu, x2 = a[4 * u + 2] & 0x7fff7fffu, x3 = a[4 * u + 3] & 0x7fff7fffu;
                    if (u == 8 * i) mma16816_z(n0, x0, x1, x2, x3, ONES, ONES);
                    else mma16816(n0, x0, x1, x2, x3, ONES, ONES);
                }
                wmax = fmaxf(wmax, fmaxf(n0[0], n0[2]));
            }
            uint32_t wm = __reduce_max_sync(~0u, __float_as_uint(wmax));
            sts32_if(lane, sb + O_OF + 4 * c, wm);
            if (c == 0) PSTAMP(8);
            bar_sync(7, 384);
            asm volatile("barrier.cluster.wait.aligned;" ::: "memory");
            if (c == 1) tma_x_tile(sb, &tm_x, rb, r, 1, 1);
            if (c == 0) {
                const uint4 wq = lds128(sb + O_OF), xq = lds128(sb + O_OF + 16), xr = lds128(sb + O_OF + 32), v0 = lds128(sb + O_MISC + 32), v1 = lds128(sb + O_MISC + 48);
                const uint32_t w1 = max(max(wq.x, wq.y), max(wq.z, wq.w)), x1 = max(max(max(xq.x, xq.y), max(xq.z, xq.w)), max(max(xr.x, xr.y), max(xr.z, xr.w)));
                const uint32_t vv = (r < 2) ? 0u : max(max(max(v0.x, v0.y), max(v0.z, v0.w)), max(max(v1.x, v1.y), max(v1.z, v1.w)));
                const uint32_t lo = (min(w1, 0x7f800000u) + 0xffffu) >> 16 | ((min(vv, 0x7f800000u) + 0xffffu) & 0xffff0000u), hi = (x1 & 0xffff0000u) | tag;
                uint32_t l0, h0, l1, h1, l2, h2;
                asm volatile("{\n.reg .pred p;\n.reg .u32 n, x, y;\n.reg .b64 v;\nsetp.eq.u32 p, %10, 0;\nmov.b64 v, {%8, %9};\n@p st.relaxed.gpu.global.b64 [%7], v;\nmov.u32 n, 0;\n"
                             "G_%=: ld.relaxed.gpu.global.b64 v, [%6];\nmov.b64 {%0, %1}, v;\nld.relaxed.gpu.global.b64 v, [%6+256];\nmov.b64 {%2, %3}, v;\n"
                             "ld.relaxed.gpu.global.b64 v, [%6+512];\nmov.b64 {%4, %5}, v;\n"
                             "xor.b32 x, %1, %9;\nxor.b32 y, %3, %9;\nor.b32 x, x, y;\nxor.b32 y, %5, %9;\nor.b32 x, x, y;\nand.b32 x, x, 0xffff;\n"
                             "setp.eq.u32 p, x, 0;\nvote.sync.all.pred p, p, 0xffffffff;\n@p bra.uni E_%=;\n"
                             "add.u32 n, n, 1;\nsetp.lt.u32 p, n, 4000000;\n@p bra.uni G_%=;\ntrap;\nE_%=:\n}"
                             : "=&r"(l0), "=&r"(h0), "=&r"(l1), "=&r"(h1), "=&r"(l2), "=&r"(h2)
                             : "l"(&g_norm[lane]), "l"(&g_norm[blockIdx.x]), "r"(lo), "r"(hi), "r"(lane) : "memory");
                const uint32_t lm = __vmaxu2(l0, __vmaxu2(l1, l2));
                const float fw = __uint_as_float(__reduce_max_sync(~0u, lm << 16));
                const float fv = __uint_as_float(__reduce_max_sync(~0u, lm & 0xffff0000u));
                const float xmax = __uint_as_float(__reduce_max_sync(~0u, max(h0, max(h1, h2)) & 0xffff0000u));
                const float G = 36.f * fw * fv;
                sts32_if(lane, sb + O_MISC + 4, __float_as_uint(G)); sts32_if(lane, sb + O_MISC + 8, __float_as_uint(G * xmax));
                sts32_if(lane, sb + O_MISC + 32, 0x3c003c00u); sts32_if(lane, sb + O_MISC + 36, 0x3c003c00u);
            }
        }
        if (c == 0) PSTAMP(12);
        bar_sync(6, 128);
        int s3n = 1;
        uint32_t roff = __shfl_sync(~0u, (r * 4 + c) * 2048 + (lane >> 4) * 512 + (lane & 2) * 128 + (lane & 1) * 64 + (lane & 12) * 4, lane);
#pragma unroll 1
        for (int s = 0; s < NSEG; s++) {
            const uint32_t l16 = opaque(l16c);
            const uint32_t vxa = sb + O_VX + (s & 1) * 8192 + c * 2048 + l16;
            if (c == 0 && r == 2) {
                bar_sync(14, 288);
                asm volatile("{\n.reg .pred p;\nelect.sync _|p, 0xffffffff;\n"
                    "@p cp.async.bulk.global.shared::cta.bulk_group [%0], [%1], 8192;\n@p cp.async.bulk.commit_group;\n"
                    "cp.async.bulk.wait_group 0;\nsetp.lt.and.s32 p, %4, 63, p;\n"
                    "@p cp.async.bulk.shared::cluster.global.mbarrier::complete_tx::bytes.multicast::cluster [%1], [%0], 8192, [%2], %3;\n"
                    "fence.proxy.async.global;\n}"
                    :: "l"(reinterpret_cast<char*>(g_qkv) + (size_t)(s * NH + h) * REC + 20480), "r"(sb + O_VX + (s & 1) * 8192),
                       "r"(sb + B_VX + 8 * (s & 1)), "h"((unsigned short)(3 << rb)), "r"(s) : "memory");
            }
            if (s == NSEG - 1) { bar_sync(3, 384); break; }
            uint4 vx[4];
            sts32_if(l16, sb + O_MISC + 16 + 4 * c, __reduce_max_sync(~0u, mmax));
            if (c == 0) STAMP(s, 5);
            {
                bar_sync(6, 128);
                const uint4 mm = lds128(sb + O_MISC + 16), cf = lds128(sb + O_MISC);
                const float bound = fmaxf(__uint_as_float(cf.z), __uint_as_float(cf.y) * (__uint_as_float(max(max(mm.x, mm.y), max(mm.z, mm.w))) * __uint_as_float(cf.x)));
                const uint32_t ebits = __reduce_max_sync(~0u, min(max(__float_as_uint(bound) & 0x7f800000u, 21u << 23), 254u << 23));
                mbar_wait(sb + B_X + 8 * s3n, ((s + 1) / 3) & 1);
                s3n = (s3n == 2) ? 0 : s3n + 1;
                bar_sync(3, 384);
                if (r < 2) mbar_wait(sb + B_VX + 8 * (s & 1), (s >> 1) & 1);
                vx[0] = lds128(vxa); vx[2] = lds128(vxa + 1024);
                if (c == 0) STAMP(s, 13);
                mbar_wait(sb + B_SC, s & 1);
                if (c == 0) STAMP(s, 6);
                float p[10];
                load_scores(p, sb + O_SC, 1280, l16);
                float mx = fmaxf(fmaxf(fmaxf(p[0], p[1]), fmaxf(p[2], p[3])), fmaxf(fmaxf(p[4], p[5]), fmaxf(p[6], p[7])));
                mx = quad_max(fmaxf(mx, fmaxf(p[8], p[9])));
                const uint4 vm = lds64x2(sb + O_VM + c * 512 + (l16 >> 1));
                vx[1] = lds128(vxa + 512); vx[3] = lds128(vxa + 1536);
                bar_arrive(4, 384);
                const float sc = __uint_as_float(lds32(sb + O_MISC + 12));
                const float mo = mx * SM_SCALE;
                uint32_t P[5];
#pragma unroll
                for (int n = 0; n < 5; n++) P[n] = pack_bf16(ex2(fmaf(p[2 * n], SM_SCALE, -mo)), ex2(fmaf(p[2 * n + 1], n == 3 ? sc : SM_SCALE, -mo)));
                if (c == 0) STAMP(s, 7);
                float o0[4], o1[4], sm[4];
                mma16816_z(sm, ONES, ONES, ONES, ONES, P[1], P[2]);
                mma16816_z(o0, vx[0].x, vx[0].y, vx[0].z, vx[0].w, P[1], P[2]);
                mma16816_z(o1, vx[2].x, vx[2].y, vx[2].z, vx[2].w, P[1], P[2]);
                mma16816(sm, ONES, ONES, ONES, ONES, P[3], P[4]);
                mma16816(o0, vx[1].x, vx[1].y, vx[1].z, vx[1].w, P[3], P[4]);
                mma16816(o1, vx[3].x, vx[3].y, vx[3].z, vx[3].w, P[3], P[4]);
                mma1688(sm, ONES, ONES, P[0]);
                mma1688(o0, vm.x, vm.y, P[0]);
                mma1688(o1, vm.z, vm.w, P[0]);
                const float sig = __uint_as_float((268u << 23) - ebits);
                const float r0 = rcp_fast(sm[0]) * sig, r1 = rcp_fast(sm[1]) * sig;
                stsm4t(sb + O_OF + c * 512 + l16, pack_bf16(o0[0] * r0, o0[1] * r1), pack_bf16(o0[2] * r0, o0[3] * r1),
                       pack_bf16(o1[0] * r0, o1[1] * r1), pack_bf16(o1[2] * r0, o1[3] * r1));
                bar_sync(6, 128);
                uint4 ob[4];
#pragma unroll
                for (int q = 0; q < 4; q++) ob[q] = ldsm4(sb + O_OF + q * 512 + l16);
                { const uint4 v = lds128(sb + O_WP + c * 512 + l16); a[92] = v.x; a[93] = v.y; a[94] = v.z; a[95] = v.w; }
                float m0[3][4], m1[3][4];
#pragma unroll
                for (int q = 0; q < 4; q++) {
#pragma unroll
                    for (int i = 0; i < 3; i++) {
                        const int k0 = (i * 8 + 2 * q) * 4;
                        if (q == 0) mma16816_z(m0[i], a[k0], a[k0 + 1], a[k0 + 2], a[k0 + 3], ob[q].x, ob[q].y);
                        else mma16816(m0[i], a[k0], a[k0 + 1], a[k0 + 2], a[k0 + 3], ob[q].x, ob[q].y);
                    }
#pragma unroll
                    for (int i = 0; i < 3; i++) {
                        const int k1 = (i * 8 + 2 * q + 1) * 4;
                        if (q == 0) mma16816_z(m1[i], a[k1], a[k1 + 1], a[k1 + 2], a[k1 + 3], ob[q].z, ob[q].w);
                        else mma16816(m1[i], a[k1], a[k1 + 1], a[k1 + 2], a[k1 + 3], ob[q].z, ob[q].w);
                    }
                }
                asm volatile("red.relaxed.gpu.global.add.noftz.v4.f16x2 [%0], {%1,%2,%3,%4};" :: "l"(reinterpret_cast<char*>(g_acc) + roff),
                    "r"(pack_f16(m0[0][0] + m1[0][0], m0[0][2] + m1[0][2])), "r"(pack_f16(m0[1][0] + m1[1][0], m0[1][2] + m1[1][2])),
                    "r"(pack_f16(m0[2][0] + m1[2][0], m0[2][2] + m1[2][2])), "r"(0x3c00u) : "memory");
                asm volatile("red.relaxed.gpu.global.add.noftz.v4.f16x2 [%0], {%1,%2,%3,%4};" :: "l"(reinterpret_cast<char*>(g_acc) + roff + 1024),
                    "r"(pack_f16(m0[0][1] + m1[0][1], m0[0][3] + m1[0][3])), "r"(pack_f16(m0[1][1] + m1[1][1], m0[1][3] + m1[1][3])),
                    "r"(pack_f16(m0[2][1] + m1[2][1], m0[2][3] + m1[2][3])), "r"(0x3c00u) : "memory");
                const unsigned t_red = clk();
                bar_arrive(5, 256);
                bar_arrive(13, 256);
                mbar_expect_if(l16 | c, sb + B_SC, 4608);
                mbar_expect_if(l16 | (c ^ 1) | (r >> 1), sb + B_VX + 8 * ((s + 1) & 1), 8192);
                sts32_if(l16 | (c ^ 3), sb + O_MISC, ebits - (14u << 23));
                if (c == 0) STAMPV(s, 8, t_red);
                if (ACC_PF && c == 2 && s + 4 < NSEG - 1)
                    asm volatile("prefetch.global.L2 [%0];" :: "l"(reinterpret_cast<const char*>(g_acc) + ((s + 4) * 96 + blockIdx.x) * 256 + (l16 & 96)) : "memory");
                const char* pbase = reinterpret_cast<const char*>(g_acc) + (s * 24576 + c * 2048) + ((l16 & 64) * 16 + (l16 & 256) + ((l16 & 128) >> 1) + (l16 & 48));
                spin_until(t_red, D_WAIT);
                uint4 v[6];
#pragma unroll
                for (int i = 0; i < 6; i++) v[i] = ldg_relaxed128(pbase + (i >> 1) * 8192 + (i & 1) * 512);
                int nretry = 0;
                auto hand_over = [&](int tau, uint32_t one) -> uint32_t {
                    uint4& A = v[2 * tau]; uint4& B = v[2 * tau + 1];
                    if (tau > 0) {
                        A.x = hmul2(A.x, one); A.y = hmul2(A.y, one); A.z = hmul2(A.z, one); A.w &= one | 0x5000u;
                        B.x = hmul2(B.x, one); B.y = hmul2(B.y, one); B.z = hmul2(B.z, one);
                    }
                    const uint32_t ok = __all_sync(~0u, (A.w & B.w) == 0x5000u);
                    A.x = f16x2_to_bf16x2(A.x); B.x = f16x2_to_bf16x2(B.x); A.y = f16x2_to_bf16x2(A.y); B.y = f16x2_to_bf16x2(B.y);
                    A.z = f16x2_to_bf16x2(A.z); B.z = f16x2_to_bf16x2(B.z);
                    sts128(sb + O_MF + tau * 3072 + c * 512 + l16, A.x, B.x, A.y, B.y);
                    sts64(sb + O_MF + tau * 3072 + 2048 + (c >> 1) * 512 + (c & 1) * 8 + l16, A.z, B.z);
                    asm volatile("{\n.reg .pred p;\nsetp.ne.u32 p, %0, 0;\n@p bar.arrive %1, 384;\n}" :: "r"(ok), "r"(tau == 0 ? 2 : tau == 1 ? 0 : 15) : "memory");
                    return ok;
                };
                uint32_t okv[3];
                okv[0] = hand_over(0, 0u);
                okv[1] = hand_over(1, lds32(sb + O_MISC + 32));
                okv[2] = hand_over(2, lds32(sb + O_MISC + 36));
                if (!(okv[0] & okv[1] & okv[2])) {
#pragma unroll
                    for (int tau = 0; tau < 3; tau++) {
                        if (!okv[tau]) {
                            asm volatile("{\n.reg .pred p, q;\n.reg .u32 n, x;\nmov.u32 n, 0;\n"
                                 "R_%=: ld.relaxed.gpu.global.v4.u32 {%0,%1,%2,%3}, [%9];\nld.relaxed.gpu.global.v4.u32 {%4,%5,%6,%7}, [%9+512];\n"
                                 "add.u32 %8, %8, 1;\nand.b32 x, %3, %7;\nsetp.eq.u32 p, x, 0x5000;\nvote.sync.all.pred q, p, 0xffffffff;\n@q bra.uni K_%=;\n"
                                 "add.u32 n, n, 1;\nsetp.lt.u32 q, n, 2000000;\n@q bra.uni R_%=;\ntrap;\nK_%=:\n}"
                                 : "+r"(v[2 * tau].x), "+r"(v[2 * tau].y), "+r"(v[2 * tau].z), "+r"(v[2 * tau].w),
                                   "+r"(v[2 * tau + 1].x), "+r"(v[2 * tau + 1].y), "+r"(v[2 * tau + 1].z), "+r"(v[2 * tau + 1].w), "+r"(nretry)
                                 : "l"(pbase + tau * 8192) : "memory");
                            hand_over(tau, 0x3c003c00u);
                        }
                    }
                }
                if (c == 0) STAMP(s, 12);
                if (c == 0) STAMPV(s, 14, nretry);
                mmax = absmax2(absmax2(absmax2(v[0].x, v[0].y), absmax2(v[0].z, v[1].x)), absmax2(absmax2(v[1].y, v[1].z), absmax2(v[2].x, v[2].y)));
                mmax = absmax2(mmax, absmax2(absmax2(absmax2(v[2].z, v[3].x), absmax2(v[3].y, v[3].z)), absmax2(absmax2(v[4].x, v[4].y), absmax2(v[4].z, v[5].x))));
                mmax = absmax2(mmax, absmax2(v[5].y, v[5].z)) & 0x7fff7fffu;
                mmax = max(mmax << 16, mmax & 0xffff0000u);
            }
            roff += 24576;
        }
        {
            bar_sync(7, 384);
            if (c == 0)
                asm volatile("{\n.reg .pred p;\nsetp.eq.u32 p, %1, 0;\n@p red.release.gpu.global.inc.u32 [%0], 0xffffffff;\n}"
                             :: "l"(&g_flag[F_QKV + (60 + (h >> 3)) * 8]), "r"(l16c) : "memory");
        }
    }
    if (warp == 8) PSTAMP(13);
    cluster_sync();
}

constexpr int NST = 10;
constexpr int G_RING = 0, G_EX = NST * 16384, G_OUT = G_EX + 32768, G_CARRY = G_OUT + 32768, G_BAR = G_CARRY + 512, BG_SMEM = G_BAR + 256;
constexpr int GB_FULL = G_BAR, GB_EMPTY = G_BAR + 8 * NST, GB_W = G_BAR + 16 * NST;
static_assert(BG_SMEM <= 232448, "smem");

template <int ACC>
__device__ __forceinline__ void wgmma_n128_rs(float (&d)[64], uint32_t a0, uint32_t a1, uint32_t a2, uint32_t a3, uint64_t desc) {
    asm volatile("wgmma.mma_async.sync.aligned.m64n128k16.f32.bf16.bf16 "
        "{%0,%1,%2,%3,%4,%5,%6,%7,%8,%9,%10,%11,%12,%13,%14,%15,%16,%17,%18,%19,%20,%21,%22,%23,%24,%25,%26,%27,%28,%29,%30,%31,"
        "%32,%33,%34,%35,%36,%37,%38,%39,%40,%41,%42,%43,%44,%45,%46,%47,%48,%49,%50,%51,%52,%53,%54,%55,%56,%57,%58,%59,%60,%61,%62,%63}, "
        "{%64,%65,%66,%67}, %68, %69, 1, 1, 0;"
        : "+f"(d[0]), "+f"(d[1]), "+f"(d[2]), "+f"(d[3]), "+f"(d[4]), "+f"(d[5]), "+f"(d[6]), "+f"(d[7]),
          "+f"(d[8]), "+f"(d[9]), "+f"(d[10]), "+f"(d[11]), "+f"(d[12]), "+f"(d[13]), "+f"(d[14]), "+f"(d[15]),
          "+f"(d[16]), "+f"(d[17]), "+f"(d[18]), "+f"(d[19]), "+f"(d[20]), "+f"(d[21]), "+f"(d[22]), "+f"(d[23]),
          "+f"(d[24]), "+f"(d[25]), "+f"(d[26]), "+f"(d[27]), "+f"(d[28]), "+f"(d[29]), "+f"(d[30]), "+f"(d[31]),
          "+f"(d[32]), "+f"(d[33]), "+f"(d[34]), "+f"(d[35]), "+f"(d[36]), "+f"(d[37]), "+f"(d[38]), "+f"(d[39]),
          "+f"(d[40]), "+f"(d[41]), "+f"(d[42]), "+f"(d[43]), "+f"(d[44]), "+f"(d[45]), "+f"(d[46]), "+f"(d[47]),
          "+f"(d[48]), "+f"(d[49]), "+f"(d[50]), "+f"(d[51]), "+f"(d[52]), "+f"(d[53]), "+f"(d[54]), "+f"(d[55]),
          "+f"(d[56]), "+f"(d[57]), "+f"(d[58]), "+f"(d[59]), "+f"(d[60]), "+f"(d[61]), "+f"(d[62]), "+f"(d[63])
        : "r"(a0), "r"(a1), "r"(a2), "r"(a3), "l"(desc), "n"(ACC));
}
__device__ __forceinline__ void wait_flag(const unsigned* p, unsigned target) {
    asm volatile("{\n.reg .pred p;\n.reg .u32 n, v;\nmov.u32 n, 0;\n"
                 "W_%=: ld.acquire.gpu.global.u32 v, [%0];\nsub.u32 v, v, %1;\nsetp.ge.s32 p, v, 0;\n@p bra.uni D_%=;\nnanosleep.u32 100;\n"
                 "add.u32 n, n, 1;\nsetp.lt.u32 p, n, 4000000;\n@p bra.uni W_%=;\ntrap;\nD_%=:\n}" :: "l"(p), "r"(target) : "memory");
}
__device__ __forceinline__ void flag_inc_if(uint32_t z, unsigned* p) {
    asm volatile("{\n.reg .pred p;\nsetp.eq.u32 p, %1, 0;\n@p red.release.gpu.global.inc.u32 [%0], 0xffffffff;\n}" :: "l"(p), "r"(z) : "memory");
}
template <int NS, int STRIDE>
__device__ __forceinline__ void bg_mainloop(float (&d)[64], const uint32_t (&a)[144], uint32_t sb, int it, int lane) {
    int slot = it % NST, ph = (it / NST) & 1, prev = 0;
#pragma unroll
    for (int i = 0; i < NS; i++) {
        mbar_wait(sb + GB_FULL + 8 * slot, ph);
        const uint64_t desc = (uint64_t)(((sb + G_RING + slot * 16384) & 0x3FFFF) >> 4) | (1ull << 16) | (64ull << 32) | (1ull << 62);
        wg_fence();
#pragma unroll
        for (int k = 0; k < 4; k++) {
            const int u = 16 * i + 4 * k;
            if (i == 0 && k == 0) wgmma_n128_rs<0>(d, a[u], a[u + 1], a[u + 2], a[u + 3], desc);
            else wgmma_n128_rs<1>(d, a[u], a[u + 1], a[u + 2], a[u + 3], desc + 2 * k);
        }
        wg_commit();
        if (i > 0) {
            asm volatile("wgmma.wait_group.sync.aligned 1;" ::: "memory");
            mbar_arrive_if(lane, sb + GB_EMPTY + 8 * prev);
        }
        prev = slot;
        slot += STRIDE;
        if (slot >= NST) { slot -= NST; ph ^= 1; }
    }
    wg_wait0();
    mbar_arrive_if(lane, sb + GB_EMPTY + 8 * prev);
}
template <bool SKIP>
__device__ __forceinline__ void bg_epilogue(float (&d)[64], uint32_t sb, int wg, int w, int lane, const CUtensorMap* tm_out, int col0, int tok0,
                                            const __nv_bfloat16* xa, const __nv_bfloat16* Dk) {
    const int g = lane >> 2, t = lane & 3;
    const uint32_t ex = sb + G_EX + w * 4096 + lane * 16;
    float k[32];
    if (wg == 0) {
#pragma unroll
        for (int q = 0; q < 8; q++) sts128f(ex + q * 512, d[32 + 4 * q], d[32 + 4 * q + 1], d[32 + 4 * q + 2], d[32 + 4 * q + 3]);
#pragma unroll
        for (int i = 0; i < 32; i++) k[i] = d[i];
    } else {
#pragma unroll
        for (int q = 0; q < 8; q++) sts128f(ex + 16384 + q * 512, d[4 * q], d[4 * q + 1], d[4 * q + 2], d[4 * q + 3]);
#pragma unroll
        for (int i = 0; i < 32; i++) k[i] = d[32 + i];
    }
    uint32_t xv[16], dv = 0;
    if (SKIP) {
        const __nv_bfloat16* xp = xa + (size_t)(tok0 + 64 * wg + 2 * t) * DM + col0 + 16 * w + 2 * g;
#pragma unroll
        for (int i = 0; i < 16; i++) xv[i] = ldg_nc32(xp + (8 * (i >> 1) + (i & 1)) * DM);
        dv = ldg_nc32(Dk + col0 + 16 * w + 2 * g);
    }
    if (SKIP && w == 0) asm volatile("cp.async.bulk.wait_group.read 0;" ::: "memory");
    bar_sync(1, 256);
#pragma unroll
    for (int q = 0; q < 8; q++) {
        const float4 o = lds128f(ex + (wg ^ 1) * 16384 + q * 512);
        k[4 * q] += o.x; k[4 * q + 1] += o.y; k[4 * q + 2] += o.z; k[4 * q + 3] += o.w;
    }
    if (SKIP) bar_sync(1, 256); else bar_sync(13, 288);
    const uint32_t ob = sb + G_OUT + wg * 16384 + (w >> 1) * 8192 + (g & 1) * 8;
    const uint32_t ch = (w & 1) * 4 + (g >> 1);
#pragma unroll
    for (int i = 0; i < 16; i++) {
        float v0 = k[4 * (i >> 1) + (i & 1)], v1 = k[4 * (i >> 1) + 2 + (i & 1)];
        if (SKIP) {
            const uint32_t p = pack_bf16(__uint_as_float(xv[i] << 16) * __uint_as_float(dv << 16), __uint_as_float(xv[i] & 0xffff0000u) * __uint_as_float(dv & 0xffff0000u));
            v0 += __uint_as_float(p << 16); v1 += __uint_as_float(p & 0xffff0000u);
        }
        const uint32_t n7 = 2 * t + (i & 1);
        sts64(ob + (8 * (i >> 1) + n7) * 128 + ((ch ^ n7) << 4), __float_as_uint(v0), __float_as_uint(v1));
    }
    fence_async_smem();
    if (SKIP) {
        bar_sync(4 + wg, 128);
        if (w == 0)
            asm volatile("{\n.reg .pred p;\nelect.sync _|p, 0xffffffff;\n"
                "@p cp.async.bulk.tensor.2d.global.shared::cta.bulk_group [%0, {%2, %4}], [%1];\n"
                "@p cp.async.bulk.tensor.2d.global.shared::cta.bulk_group [%0, {%3, %4}], [%1+8192];\n@p cp.async.bulk.commit_group;\n}"
                :: "l"(tm_out), "r"(sb + G_OUT + wg * 16384), "r"(col0), "r"(col0 + 32), "r"(tok0 + 64 * wg) : "memory");
    } else {
        bar_arrive(12, 288);
    }
}
__device__ __forceinline__ void s5_channel(int p, const __nv_bfloat16* Lre, const __nv_bfloat16* Lim, const __nv_bfloat16* logdt, float2& lam, float2& coef) {
    const float dt = __bfloat162float(__float2bfloat16(expf(__bfloat162float(logdt[p]))));
    const float lr = __bfloat162float(Lre[p]), li = __bfloat162float(Lim[p]);
    const float e = expf(dt * lr);
    float sn, cs;
    sincosf(dt * li, &sn, &cs);
    lam = make_float2(e * cs, e * sn);
    const float den = lr * lr + li * li;
    coef = make_float2(((lam.x - 1.f) * lr + lam.y * li) / den, (lam.y * lr - (lam.x - 1.f) * li) / den);
}
__device__ __forceinline__ float2 cfma(float2 a, float2 b, float2 c) {
    return make_float2(fmaf(a.x, b.x, fmaf(-a.y, b.y, c.x)), fmaf(a.x, b.y, fmaf(a.y, b.x, c.y)));
}
__device__ __forceinline__ uint4 ldg128(const void* p) { uint4 v; asm volatile("ld.global.v4.u32 {%0,%1,%2,%3}, [%4];" : "=r"(v.x), "=r"(v.y), "=r"(v.z), "=r"(v.w) : "l"(p) : "memory"); return v; }
__device__ __forceinline__ uint2 ldg64(const void* p) { uint2 v; asm volatile("ld.global.v2.u32 {%0,%1}, [%2];" : "=r"(v.x), "=r"(v.y) : "l"(p) : "memory"); return v; }

__device__ __forceinline__ void bg_attention(uint32_t st0, uint32_t st1, int mt, int lane) {
    const int g = lane >> 2, t = lane & 3;
    float sc[5][4];
#pragma unroll
    for (int n = 0; n < 5; n++) sc[n][0] = sc[n][1] = sc[n][2] = sc[n][3] = 0.f;
    float sm2[4] = {0.f, 0.f, 0.f, 0.f};
#pragma unroll
    for (int i = 0; i < 8; i++) {
        const uint32_t st = (i >> 2 ? st1 : st0) + (i & 3) * 512 + lane * 16;
        const uint4 q = ldsm4(st + mt * 2048), km = ldsm4(st + 8192), k0 = ldsm4(st + 4096);
        mma16816(sc[0], q.x, q.y, q.z, q.w, km.x, km.y);
        mma16816(sm2, q.x, q.y, q.z, q.w, km.z, km.w);
        mma16816(sc[1], q.x, q.y, q.z, q.w, k0.x, k0.y);
        mma16816(sc[2], q.x, q.y, q.z, q.w, k0.z, k0.w);
        if (mt) {
            const uint4 k1 = ldsm4(st + 6144);
            mma16816(sc[3], q.x, q.y, q.z, q.w, k1.x, k1.y);
            mma16816(sc[4], q.x, q.y, q.z, q.w, k1.z, k1.w);
        }
    }
#pragma unroll
    for (int i = 0; i < 4; i++) sc[0][i] += sm2[i];
    const int q0 = 16 * mt + 8 + g - 2 * t;
#pragma unroll
    for (int n = 1; n < 5; n++) {
        if (8 * n > q0) sc[n][0] = -INFINITY;
        if (8 * n + 1 > q0) sc[n][1] = -INFINITY;
        if (8 * n > q0 + 8) sc[n][2] = -INFINITY;
        if (8 * n + 1 > q0 + 8) sc[n][3] = -INFINITY;
    }
    float ma = fmaxf(sc[0][0], sc[0][1]), mb = fmaxf(sc[0][2], sc[0][3]);
#pragma unroll
    for (int n = 1; n < 5; n++) { ma = fmaxf(ma, fmaxf(sc[n][0], sc[n][1])); mb = fmaxf(mb, fmaxf(sc[n][2], sc[n][3])); }
    ma = quad_max(ma) * SM_SCALE; mb = quad_max(mb) * SM_SCALE;
    uint32_t Pa[5], Pb[5];
#pragma unroll
    for (int n = 0; n < 5; n++) {
        Pa[n] = pack_bf16(ex2(fmaf(sc[n][0], SM_SCALE, -ma)), ex2(fmaf(sc[n][1], SM_SCALE, -ma)));
        Pb[n] = pack_bf16(ex2(fmaf(sc[n][2], SM_SCALE, -mb)), ex2(fmaf(sc[n][3], SM_SCALE, -mb)));
    }
    float sa[4], sbb[4];
    mma1688_z(sa, ONES, ONES, Pa[0]); mma1688_z(sbb, ONES, ONES, Pb[0]);
    mma16816(sa, ONES, ONES, ONES, ONES, Pa[1], Pa[2]); mma16816(sbb, ONES, ONES, ONES, ONES, Pb[1], Pb[2]);
    mma16816(sa, ONES, ONES, ONES, ONES, Pa[3], Pa[4]); mma16816(sbb, ONES, ONES, ONES, ONES, Pb[3], Pb[4]);
    const float ra0 = rcp_fast(sa[0]), ra1 = rcp_fast(sa[1]), rb0 = rcp_fast(sbb[0]), rb1 = rcp_fast(sbb[1]);
    const uint32_t row = lane & 7;
    const uint32_t so = mt * 2048 + (lane >> 4) * 1024 + row * 128;
#pragma unroll
    for (int i = 0; i < 8; i++) {
        const uint32_t st = i >> 2 ? st1 : st0;
        const int e4 = i & 3;
        const float2 vmf = lds64f(st + 14336 + e4 * 256 + lane * 8);
        const uint32_t vm0 = __float_as_uint(vmf.x), vm1 = __float_as_uint(vmf.y);
        const uint4 v0 = lds128(st + 10240 + e4 * 1024 + lane * 16);
        float oa[4], ob[4];
        mma1688_z(oa, vm0, vm1, Pa[0]); mma1688_z(ob, vm0, vm1, Pb[0]);
        mma16816(oa, v0.x, v0.y, v0.z, v0.w, Pa[1], Pa[2]);
        mma16816(ob, v0.x, v0.y, v0.z, v0.w, Pb[1], Pb[2]);
        if (mt) {
            const uint4 v1 = lds128(st + 10240 + e4 * 1024 + 512 + lane * 16);
            mma16816(oa, v1.x, v1.y, v1.z, v1.w, Pa[3], Pa[4]);
            mma16816(ob, v1.x, v1.y, v1.z, v1.w, Pb[3], Pb[4]);
        }
        stsm4t(st + so + (((2 * e4 + ((lane >> 3) & 1)) ^ row) << 4), pack_bf16(oa[0] * ra0, oa[1] * ra1), pack_bf16(oa[2] * ra0, oa[3] * ra1),
               pack_bf16(ob[0] * rb0, ob[1] * rb1), pack_bf16(ob[2] * rb0, ob[3] * rb1));
    }
}
__device__ __forceinline__ bool bg_att_turn(int na, int ng) { return na == ng || (na == ng + 1 && na <= BG_AHEAD); }

__global__ void __launch_bounds__(384, 1)
bg_kernel(const __grid_constant__ CUtensorMap tm_xa, const __grid_constant__ CUtensorMap tm_wo, const __grid_constant__ CUtensorMap tm_out,
          const __nv_bfloat16* __restrict__ xa, const __nv_bfloat16* __restrict__ Lre, const __nv_bfloat16* __restrict__ Lim,
          const __nv_bfloat16* __restrict__ Bre, const __nv_bfloat16* __restrict__ Bim, const __nv_bfloat16* __restrict__ Cre,
          const __nv_bfloat16* __restrict__ Cim, const __nv_bfloat16* __restrict__ logdt, const __nv_bfloat16* __restrict__ Dk) {
    extern __shared__ __align__(1024) uint8_t smem_raw[];
    const uint32_t sb = smem_u32(smem_raw);
    const int lane = threadIdx.x & 31;
    const int warp = __shfl_sync(~0u, threadIdx.x >> 5, 0);
    const int wg = warp >> 2, w = warp & 3, b = blockIdx.x;
    const int nt = b % 9, kq = b / 9;
    BSTAMP(0);
    if (threadIdx.x == 0) {
        if (sb & 1023u) __trap();
        for (int i = 0; i < NST; i++) { mbar_init(sb + GB_FULL + 8 * i, 1); mbar_init(sb + GB_EMPTY + 8 * i, 4); }
        mbar_init(sb + GB_W, 1);
        asm volatile("fence.mbarrier_init.release.cluster;" ::: "memory");
        mbar_expect(sb + GB_W, (b < 18 ? 64 : 128) * 1152);
        sts32(sb + G_BAR + 248, atomicAdd(&g_ticket_bg, 1u) / 36u + 1u);
    }
    __syncthreads();
    if (wg == 2) {
        asm volatile("setmaxnreg.dec.sync.aligned.u32 24;");
        if (w == 0) {
            int slot = 0, ph = 1;
            unsigned tlast = clk();
            auto pace = [&]() { if (BG_PACE) { spin_until(tlast, BG_PACE); tlast = clk(); } };
            auto next = [&]() { if (++slot == NST) { slot = 0; ph ^= 1; } };
            bar_sync(6, 288);
            if (b < 18) {
#pragma unroll 1
                for (int i = 0; i < 144; i++) {
                    const int blk = i / 9, kb = i - 9 * blk, it = (blk >> 1) * 18 + (blk & 1) + 2 * kb;
                    slot = it % NST;
                    mbar_wait(sb + GB_EMPTY + 8 * slot, ((it / NST) & 1) ^ 1);
                    pace();
                    asm volatile("{\n.reg .pred p;\nelect.sync _|p, 0xffffffff;\n@p mbarrier.arrive.expect_tx.shared::cta.b64 _, [%2], 16384;\n"
                        "@p cp.async.bulk.tensor.5d.shared::cluster.global.mbarrier::complete_tx::bytes [%0], [%1, {%3, %4, %4, %4, %5}], [%2];\n}"
                        :: "r"(sb + G_RING + slot * 16384), "l"(&tm_xa), "r"(sb + GB_FULL + 8 * slot), "r"(kb * 64), "r"(0), "r"(blk) : "memory");
                }
                slot = 144 % NST; ph = ((144 / NST) & 1) ^ 1;
            }
            const unsigned ep = lds32(sb + G_BAR + 248);
            auto slabs = [&](const char* src, int ns) {
                asm volatile("fence.proxy.async.global;" ::: "memory");
#pragma unroll 1
                for (int i = 0; i < ns; i++) {
                    mbar_wait(sb + GB_EMPTY + 8 * slot, ph);
                    pace();
                    asm volatile("{\n.reg .pred p;\nelect.sync _|p, 0xffffffff;\n@p mbarrier.arrive.expect_tx.shared::cta.b64 _, [%2], 16384;\n"
                        "@p cp.async.bulk.shared::cluster.global.mbarrier::complete_tx::bytes [%0], [%1], 16384, [%2];\n}"
                        :: "r"(sb + G_RING + slot * 16384), "l"(src + (size_t)((i & 1) * (ns >> 1) + (i >> 1)) * (SEQ * 128)), "r"(sb + GB_FULL + 8 * slot) : "memory");
                    next();
                }
            };
            if (b >= 18) {
#pragma unroll 1
                for (int blk = kq - 2; blk < 16; blk += 2) {
                    wait_flag(&g_flag[F_H + blk * 8], 18 * ep);
                    slabs(reinterpret_cast<const char*>(g_h) + blk * 16384, 18);
                }
            }
            bar_sync(6, 288);
#pragma unroll 1
            for (int na = 0, ng = 0; ng < 16;) {
                if (bg_att_turn(na, ng)) {
                    if (nt < 8) {
                        wait_flag(&g_flag[F_QKV + (na * 4 + kq) * 8], 24 * ep);
                        asm volatile("fence.proxy.async.global;" ::: "memory");
#pragma unroll 1
                        for (int i = 0; i < 8; i++) {
                            const int pr = nt * 4 + 2 * (i & 1) + (i >> 2), hf = (i >> 1) & 1;
                            const char* rec = reinterpret_cast<const char*>(g_qkv) + (size_t)((4 * na + (pr >> 3)) * NH + 8 * kq + (pr & 7)) * REC;
                            mbar_wait(sb + GB_EMPTY + 8 * slot, ph);
                    pace();
                            asm volatile("{\n.reg .pred p;\nelect.sync _|p, 0xffffffff;\n@p mbarrier.arrive.expect_tx.shared::cta.b64 _, [%4], 15360;\n"
                                "@p cp.async.bulk.shared::cluster.global.mbarrier::complete_tx::bytes [%0], [%1], 10240, [%4];\n"
                                "@p cp.async.bulk.shared::cluster.global.mbarrier::complete_tx::bytes [%0+10240], [%2], 4096, [%4];\n"
                                "@p cp.async.bulk.shared::cluster.global.mbarrier::complete_tx::bytes [%0+14336], [%3], 1024, [%4];\n}"
                                :: "r"(sb + G_RING + slot * 16384), "l"(rec + hf * 10240), "l"(rec + 20480 + hf * 4096), "l"(rec + 28672 + hf * 1024),
                                   "r"(sb + GB_FULL + 8 * slot) : "memory");
                            next();
                        }
                    }
                    na++;
                } else {
                    wait_flag(&g_flag[F_OX + (ng * 4 + kq) * 8], 8 * ep);
                    slabs(reinterpret_cast<const char*>(g_ox) + (size_t)kq * 16 * SEQ * 128 + ng * 16384, 16);
                    ng++;
                }
            }
        } else if (w == 1) {
            if (b < 18) {
#pragma unroll 1
                for (int blk = 0; blk < 16; blk++) {
                    bar_sync(8 + (blk & 1), 160);
                    asm volatile("{\n.reg .pred p;\nelect.sync _|p, 0xffffffff;\n@p cp.async.bulk.global.shared::cta.bulk_group [%0], [%1], 16384;\n"
                        "@p cp.async.bulk.commit_group;\ncp.async.bulk.wait_group 0;\nfence.proxy.async.global;\n}"
                        :: "l"(reinterpret_cast<char*>(g_h) + ((size_t)b * SEQ + blk * 128) * 128), "r"(sb + G_OUT + (blk & 1) * 16384) : "memory");
                    bar_arrive(10 + (blk & 1), 160);
                    flag_inc_if(lane, &g_flag[F_H + blk * 8]);
                }
            }
            if (nt < 8) {
                int it = 144;
#pragma unroll 1
                for (int na = 0, ng = 0; ng < 16;) {
                    if (bg_att_turn(na, ng)) {
                        bar_sync(7, 288);
                        if (lane < 8) {
                            const int pr = nt * 4 + 2 * (lane & 1) + (lane >> 2), hf = (lane >> 1) & 1;
                            asm volatile("cp.async.bulk.global.shared::cta.bulk_group [%0], [%1], 4096;\ncp.async.bulk.commit_group;\ncp.async.bulk.wait_group.read 0;\n"
                                "mbarrier.arrive.shared::cta.b64 _, [%2], 4;\ncp.async.bulk.wait_group 0;\nfence.proxy.async.global;"
                                :: "l"(reinterpret_cast<char*>(g_ox) + ((size_t)((8 * kq + (pr & 7)) * 2 + hf) * SEQ + (4 * na + (pr >> 3)) * 32) * 128),
                                   "r"(sb + G_RING + ((it + lane) % NST) * 16384), "r"(sb + GB_EMPTY + 8 * ((it + lane) % NST)) : "memory");
                        }
                        __syncwarp();
                        flag_inc_if(lane, &g_flag[F_OX + (na * 4 + kq) * 8]);
                        it += 8; na++;
                    } else { it += 16; ng++; }
                }
            }
        } else if (w == 2) {
            const unsigned ep = lds32(sb + G_BAR + 248);
#pragma unroll 1
            for (int blk = 0; blk < 16; blk++) {
                bar_arrive(13, 288);
                bar_sync(12, 288);
                if (kq) { wait_flag(&g_flag[F_OUT + (blk * 9 + nt) * 8], ep); asm volatile("fence.proxy.async.global;" ::: "memory"); }
                unsigned t0 = clk();
                if (blk < 15) spin_until(t0, b * (RED_GAP / 36));
#pragma unroll 1
                for (int i = 0; i < 4; i++) {
                    const uint32_t src = sb + G_OUT + i * 8192;
                    const int c0 = DM + 64 * nt + (i & 1) * 32, c1 = blk * 128 + (i >> 1) * 64;
                    if (kq) {
                        asm volatile("{\n.reg .pred p;\nelect.sync _|p, 0xffffffff;\n@p cp.reduce.async.bulk.tensor.2d.global.shared::cta.add.bulk_group [%0, {%2, %3}], [%1];\n}"
                            :: "l"(&tm_out), "r"(src), "r"(c0), "r"(c1) : "memory");
                        t0 = clk();
                        if (blk < 15 && i < 3) spin_until(t0, RED_GAP);
                    } else {
                        asm volatile("{\n.reg .pred p;\nelect.sync _|p, 0xffffffff;\n@p cp.async.bulk.tensor.2d.global.shared::cta.bulk_group [%0, {%2, %3}], [%1];\n}"
                            :: "l"(&tm_out), "r"(src), "r"(c0), "r"(c1) : "memory");
                    }
                }
                asm volatile("cp.async.bulk.commit_group;\ncp.async.bulk.wait_group 0;\nfence.proxy.async.global;" ::: "memory");
                __syncwarp();
                if (!kq) flag_inc_if(lane, &g_flag[F_OUT + (blk * 9 + nt) * 8]);
            }
        }
    } else {
        asm volatile("setmaxnreg.inc.sync.aligned.u32 240;");
        const int g = lane >> 2, t = lane & 3, tid = threadIdx.x;
        uint32_t a[144];
        float d[64];
        if (b < 18) {
            if (tid < 64)
                asm volatile("cp.async.bulk.shared::cluster.global.mbarrier::complete_tx::bytes [%0], [%1], 1152, [%2];"
                    :: "r"(sb + tid * 1168), "l"((tid < 32 ? Bre : Bim) + (size_t)(32 * b + (tid & 31)) * DM), "r"(sb + GB_W) : "memory");
            float2 lam, coef;
            s5_channel(32 * b + 8 * w + g, Lre, Lim, logdt, lam, coef);
            float2 l32 = lam;
#pragma unroll
            for (int i = 0; i < 5; i++) l32 = make_float2(l32.x * l32.x - l32.y * l32.y, 2.f * l32.x * l32.y);
            __syncwarp();
            mbar_wait(sb + GB_W, 0);
            const uint32_t ap = sb + (((lane >> 3) & 1) * 32 + 8 * w + (lane & 7)) * 1168 + (lane >> 4) * 16;
#pragma unroll
            for (int ks = 0; ks < 36; ks++) { const uint4 v = ldsm4(ap + ks * 32); a[4 * ks] = v.x; a[4 * ks + 1] = v.y; a[4 * ks + 2] = v.z; a[4 * ks + 3] = v.w; }
            bar_sync(1, 256);
            bar_arrive(6, 288);
            BSTAMP(1);
#pragma unroll 1
            for (int blk = wg; blk < 16; blk += 2) {
                bg_mainloop<9, 2>(d, a, sb, (blk >> 1) * 18 + wg, lane);
                float2 e = make_float2(0.f, 0.f);
#pragma unroll
                for (int i = 0; i < 32; i++) e = cfma(lam, e, make_float2(d[4 * (i >> 1) + (i & 1)], d[4 * (i >> 1) + 2 + (i & 1)]));
                float2 cin = make_float2(0.f, 0.f);
                if (blk > 0) { bar_sync(2 + (wg ^ 1), 256); cin = lds64f(sb + G_CARRY + (wg ^ 1) * 256 + (8 * w + g) * 8); }
                float2 mine = cin;
#pragma unroll
                for (int q = 0; q < 4; q++) {
                    const float2 eq = make_float2(__shfl_sync(~0u, e.x, (lane & 28) + q), __shfl_sync(~0u, e.y, (lane & 28) + q));
                    cin = cfma(l32, cin, eq);
                    if (t == q + 1) mine = cin;
                }
                if (blk < 15) {
                    if (t == 0) sts64(sb + G_CARRY + wg * 256 + (8 * w + g) * 8, __float_as_uint(cin.x), __float_as_uint(cin.y));
                    bar_arrive(2 + wg, 256);
                }
                const uint32_t hs = sb + G_OUT + wg * 16384 + t * 4096 + (g & 3) * 4;
                const uint32_t ch = 2 * w + (g >> 2);
                if (blk >= 2) bar_sync(10 + wg, 160);
#pragma unroll
                for (int i = 0; i < 32; i++) {
                    mine = cfma(lam, mine, make_float2(d[4 * (i >> 1) + (i & 1)], d[4 * (i >> 1) + 2 + (i & 1)]));
                    sts32(hs + i * 128 + ((ch ^ (i & 7)) << 4), pack_bf16(mine.x, mine.y));
                }
                fence_async_smem();
                bar_arrive(8 + wg, 160);
            }
            bar_sync(10 + wg, 160);
        } else {
            if (tid < 128)
                asm volatile("cp.async.bulk.shared::cluster.global.mbarrier::complete_tx::bytes [%0], [%1], 1152, [%2];"
                    :: "r"(sb + tid * 1168), "l"((tid < 64 ? Cre : Cim) + (size_t)(64 * nt + (tid & 63)) * DM), "r"(sb + GB_W) : "memory");
            for (int p = tid; p < DM; p += 256) {
                float2 lam, coef;
                s5_channel(p, Lre, Lim, logdt, lam, coef);
                sts64(sb + G_EX + p * 8, __float_as_uint(2.f * coef.x), __float_as_uint(2.f * coef.y));
            }
            bar_sync(1, 256);
            mbar_wait(sb + GB_W, 0);
            const uint32_t cp = sb + (16 * w + 2 * g) * 1168 + (288 * wg + t) * 2;
#pragma unroll
            for (int u = 0; u < 72; u++) {
                const float2 c2 = lds64f(sb + G_EX + (288 * wg + 4 * u + t) * 8);
#pragma unroll
                for (int f = 0; f < 2; f++) {
                    unsigned short r16, i16;
                    asm volatile("ld.shared.u16 %0, [%1];" : "=h"(r16) : "r"(cp + f * 1168 + u * 8) : "memory");
                    asm volatile("ld.shared.u16 %0, [%1];" : "=h"(i16) : "r"(cp + (64 + f) * 1168 + u * 8) : "memory");
                    const float cr = __uint_as_float((uint32_t)r16 << 16), ci = __uint_as_float((uint32_t)i16 << 16);
                    a[2 * u + f] = pack_bf16(cr * c2.x - ci * c2.y, -(cr * c2.y + ci * c2.x));
                }
            }
            bar_sync(1, 256);
            bar_arrive(6, 288);
            BSTAMP(1);
#pragma unroll 1
            for (int j = 0; j < 8; j++) {
                bg_mainloop<9, 2>(d, a, sb, j * 18 + wg, lane);
                bg_epilogue<true>(d, sb, wg, w, lane, &tm_out, 64 * nt, (2 * j + kq - 2) * 128, xa, Dk);
            }
        }
        if (w == 0) asm volatile("cp.async.bulk.wait_group 0;" ::: "memory");
        bar_sync(1, 256);
        BSTAMP(2);
        if (warp == 0)
            asm volatile("{\n.reg .pred p;\nelect.sync _|p, 0xffffffff;\n@p mbarrier.arrive.expect_tx.shared::cta.b64 _, [%2], 131072;\n"
                "@p cp.async.bulk.tensor.2d.shared::cluster.global.mbarrier::complete_tx::bytes [%0], [%1, {%3, %4}], [%2];\n"
                "@p cp.async.bulk.tensor.2d.shared::cluster.global.mbarrier::complete_tx::bytes [%0+32768], [%1, {%3, %5}], [%2];\n"
                "@p cp.async.bulk.tensor.2d.shared::cluster.global.mbarrier::complete_tx::bytes [%0+65536], [%1, {%3, %6}], [%2];\n"
                "@p cp.async.bulk.tensor.2d.shared::cluster.global.mbarrier::complete_tx::bytes [%0+98304], [%1, {%3, %7}], [%2];\n}"
                :: "r"(sb), "l"(&tm_wo), "r"(sb + GB_W), "r"(64 * nt), "r"(1024 * kq), "r"(1024 * kq + 256), "r"(1024 * kq + 512), "r"(1024 * kq + 768) : "memory");
        mbar_wait(sb + GB_W, 1);
        {
            const uint32_t base = sb + wg * 65536 + 4 * t * 128 + (g & 3) * 4, ch = 2 * w + (g >> 2), r7 = (4 * t) & 7;
#pragma unroll
            for (int ks = 0; ks < 32; ks++) {
                const uint32_t w0 = lds32(base + ks * 2048 + ((ch ^ r7) << 4)), w1 = lds32(base + ks * 2048 + 256 + ((ch ^ (r7 + 2)) << 4));
                const uint32_t w2 = lds32(base + ks * 2048 + 128 + ((ch ^ (r7 + 1)) << 4)), w3 = lds32(base + ks * 2048 + 384 + ((ch ^ (r7 + 3)) << 4));
                a[4 * ks] = __byte_perm(w0, w1, 0x5410); a[4 * ks + 1] = __byte_perm(w0, w1, 0x7632);
                a[4 * ks + 2] = __byte_perm(w2, w3, 0x5410); a[4 * ks + 3] = __byte_perm(w2, w3, 0x7632);
            }
        }
        bar_sync(1, 256);
        bar_arrive(6, 288);
        BSTAMP(3);
#pragma unroll 1
        for (int na = 0, ng = 0, it = 144; ng < 16;) {
            if (bg_att_turn(na, ng)) {
                if (nt < 8) {
                    const int i0 = it + wg + 4 * (w >> 1), i1 = i0 + 2;
                    mbar_wait(sb + GB_FULL + 8 * (i0 % NST), (i0 / NST) & 1);
                    mbar_wait(sb + GB_FULL + 8 * (i1 % NST), (i1 / NST) & 1);
                    BSTAMP(8 + na * 4);
                    bg_attention(sb + G_RING + (i0 % NST) * 16384, sb + G_RING + (i1 % NST) * 16384, w & 1, lane);
                    fence_async_smem();
                    bar_arrive(7, 288);
                    bar_sync(1, 256);
                    BSTAMP(9 + na * 4);
                    it += 8;
                }
                na++;
            } else {
                bg_mainloop<8, 2>(d, a, sb, it + wg, lane);
                BSTAMP(10 + ng * 4);
                bg_epilogue<false>(d, sb, wg, w, lane, &tm_out, DM + 64 * nt, ng * 128, xa, Dk);
                BSTAMP(11 + ng * 4);
                it += 16; ng++;
            }
        }
    }
    asm volatile("griddepcontrol.wait;" ::: "memory");
}

typedef CUresult (*EncodeFn)(CUtensorMap*, CUtensorMapDataType, cuuint32_t, void*, const cuuint64_t*, const cuuint64_t*, const cuuint32_t*, const cuuint32_t*,
                             CUtensorMapInterleave, CUtensorMapSwizzle, CUtensorMapL2promotion, CUtensorMapFloatOOBfill);
}

extern "C" void kernel_launch(void* const* d_in, const int* in_sizes, int n_in, void* d_out, int out_size) {
    typedef const __nv_bfloat16* bp;
    bp Ax = (bp)d_in[0], Lre = (bp)d_in[1], Lim = (bp)d_in[2], Bre = (bp)d_in[3], Bim = (bp)d_in[4], Cre = (bp)d_in[5], Cim = (bp)d_in[6],
       logdt = (bp)d_in[7], Dk = (bp)d_in[8], Bx = (bp)d_in[9], mem0 = (bp)d_in[10], Wq = (bp)d_in[11], Wk = (bp)d_in[12], Wv = (bp)d_in[13], Wo = (bp)d_in[14];
    float* out = (float*)d_out;
    static EncodeFn enc = nullptr;
    if (!enc) {
        void* fn = nullptr; cudaDriverEntryPointQueryResult qr;
        cudaGetDriverEntryPoint("cuTensorMapEncodeTiled", &fn, cudaEnableDefault, &qr);
        enc = (EncodeFn)fn;
        cudaFuncSetAttribute(chain_kernel, cudaFuncAttributeMaxDynamicSharedMemorySize, CHAIN_SMEM);
        cudaFuncSetAttribute(bg_kernel, cudaFuncAttributeMaxDynamicSharedMemorySize, BG_SMEM);
    }
    const cuuint32_t es[5] = {1, 1, 1, 1, 1};
    auto map2d = [&](CUtensorMap* tm, CUtensorMapDataType dt, const void* p, cuuint64_t d0, cuuint64_t d1, cuuint64_t stride, cuuint32_t b0, cuuint32_t b1) {
        cuuint64_t gd[2] = {d0, d1}, gs[1] = {stride}; cuuint32_t bd[2] = {b0, b1};
        enc(tm, dt, 2, (void*)p, gd, gs, bd, es, CU_TENSOR_MAP_INTERLEAVE_NONE, CU_TENSOR_MAP_SWIZZLE_128B, CU_TENSOR_MAP_L2_PROMOTION_L2_128B,
            CU_TENSOR_MAP_FLOAT_OOB_FILL_NONE);
    };
    CUtensorMap tm_x, tm_q, tm_k, tm_v, tm_xa, tm_wo, tm_out;
    map2d(&tm_x, CU_TENSOR_MAP_DATA_TYPE_BFLOAT16, Bx, DM, SEQ, DM * 2, 64, 32);
    map2d(&tm_q, CU_TENSOR_MAP_DATA_TYPE_BFLOAT16, Wq, HD, DM, HD * 2, 64, 192);
    map2d(&tm_k, CU_TENSOR_MAP_DATA_TYPE_BFLOAT16, Wk, HD, DM, HD * 2, 64, 192);
    map2d(&tm_v, CU_TENSOR_MAP_DATA_TYPE_BFLOAT16, Wv, HD, DM, HD * 2, 64, 192);
    map2d(&tm_wo, CU_TENSOR_MAP_DATA_TYPE_BFLOAT16, Wo, DM, HD, DM * 2, 64, 256);
    map2d(&tm_out, CU_TENSOR_MAP_DATA_TYPE_FLOAT32, out, 2 * DM, SEQ, 2 * DM * 4, 32, 64);
    {
        cuuint64_t gd[5] = {DM, 2, 4, 16, 16}, gs[4] = {DM * 2, 32 * DM * 2, 2 * DM * 2, 128 * DM * 2}; cuuint32_t bd[5] = {64, 2, 4, 16, 1};
        enc(&tm_xa, CU_TENSOR_MAP_DATA_TYPE_BFLOAT16, 5, (void*)Ax, gd, gs, bd, es, CU_TENSOR_MAP_INTERLEAVE_NONE, CU_TENSOR_MAP_SWIZZLE_128B,
            CU_TENSOR_MAP_L2_PROMOTION_L2_128B, CU_TENSOR_MAP_FLOAT_OOB_FILL_NONE);
    }
    cudaStream_t st = cudaStreamPerThread;
    {
        cudaLaunchConfig_t cfg = {};
        cfg.gridDim = dim3(96); cfg.blockDim = dim3(384); cfg.dynamicSmemBytes = CHAIN_SMEM; cfg.stream = st;
        cudaLaunchAttribute at[1];
        at[0].id = cudaLaunchAttributeClusterDimension; at[0].val.clusterDim.y = 1; at[0].val.clusterDim.z = 1;
        cfg.attrs = at; cfg.numAttrs = 1;
        static int csize = 0;
        if (!csize) {
            int n = 0;
            at[0].val.clusterDim.x = 6;
            csize = (CLUSTER6 && cudaOccupancyMaxActiveClusters(&n, chain_kernel, &cfg) == cudaSuccess && n >= 16) ? 6 : 3;
            (void)cudaGetLastError();
        }
        at[0].val.clusterDim.x = csize;
        cudaLaunchKernelEx(&cfg, chain_kernel, tm_x, tm_q, tm_k, tm_v, Bx, mem0, Wo);
    }
    cudaLaunchConfig_t cfg = {};
    cfg.gridDim = dim3(36); cfg.blockDim = dim3(384); cfg.dynamicSmemBytes = BG_SMEM; cfg.stream = st;
    cudaLaunchAttribute at[1];
    at[0].id = cudaLaunchAttributeProgrammaticStreamSerialization; at[0].val.programmaticStreamSerializationAllowed = 1;
    cfg.attrs = at; cfg.numAttrs = 1;
    cudaLaunchKernelEx(&cfg, bg_kernel, tm_xa, tm_wo, tm_out, Ax, Lre, Lim, Bre, Bim, Cre, Cim, logdt, Dk);
}
```

```cpp
#include <cuda_runtime.h>
#include <cuda.h>
#include <cuda_bf16.h>
#include <cuda_fp16.h>
#include <stdint.h>

#define D_WAIT 740

#define BG_PACE 0
#define RED_GAP 720
#define ACC_PF 1
#define QDEP 1
#define BG_AHEAD 5

namespace {

constexpr int DM = 576, NH = 32, SEQ = 2048, NSEG = 64, HD = 4096;

__device__ uint4 g_acc_raw[64 * 96 * 16 + 131072];
__device__ uint4 g_ox[NH * 2 * SEQ * 8];
constexpr int REC = 30720;
__device__ uint4 g_qkv[NSEG * NH * (REC / 16)];
__device__ uint4 g_h[18 * SEQ * 8];
constexpr int NFLAG = 4096, F_QKV = 0, F_OX = 512, F_H = 1024, F_OUT = 2048;
__device__ unsigned g_flag[NFLAG];
__device__ unsigned g_ticket, g_ticket_bg;
__device__ unsigned long long g_norm[96];
#define BSTAMP(i) do {} while (0)

__device__ __forceinline__ uint32_t smem_u32(const void* p) { return (uint32_t)__cvta_generic_to_shared(p); }
__device__ __forceinline__ uint32_t mapa(uint32_t a, uint32_t r) { uint32_t o; asm("mapa.shared::cluster.u32 %0, %1, %2;" : "=r"(o) : "r"(a), "r"(r)); return o; }
__device__ __forceinline__ uint32_t mapa_v(uint32_t a, uint32_t r) { uint32_t o; asm volatile("mapa.shared::cluster.u32 %0, %1, %2;" : "=r"(o) : "r"(a), "r"(r)); return o; }
__device__ __forceinline__ unsigned clk() { unsigned long long c; asm volatile("mov.u64 %0, %%clock64;" : "=l"(c) :: "memory"); return (unsigned)c; }
__device__ __forceinline__ void mbar_init(uint32_t bar, uint32_t cnt) { asm volatile("mbarrier.init.shared::cta.b64 [%0], %1;" :: "r"(bar), "r"(cnt) : "memory"); }
__device__ __forceinline__ void mbar_expect(uint32_t bar, uint32_t bytes) { asm volatile("mbarrier.arrive.expect_tx.shared::cta.b64 _, [%0], %1;" :: "r"(bar), "r"(bytes) : "memory"); }
__device__ __forceinline__ void mbar_wait(uint32_t bar, uint32_t parity) {
    asm volatile("{\n.reg .pred p;\n.reg .u32 n;\nmov.u32 n, 0;\n"
                 "W_%=: mbarrier.try_wait.parity.shared::cta.b64 p, [%0], %1;\n@p bra.uni D_%=;\n"
                 "add.u32 n, n, 1;\nsetp.lt.u32 p, n, 4000000;\n@p bra.uni W_%=;\ntrap;\nD_%=:\n}" :: "r"(bar), "r"(parity) : "memory");
}
__device__ __forceinline__ void mbar_expect_if(uint32_t z, uint32_t bar, uint32_t bytes) {
    asm volatile("{\n.reg .pred p;\nsetp.eq.u32 p, %2, 0;\n@p mbarrier.arrive.expect_tx.shared::cta.b64 _, [%0], %1;\n}" :: "r"(bar), "r"(bytes), "r"(z) : "memory");
}
__device__ __forceinline__ void mbar_arrive_if(uint32_t z, uint32_t bar) {
    asm volatile("{\n.reg .pred p;\nsetp.eq.u32 p, %1, 0;\n@p mbarrier.arrive.shared::cta.b64 _, [%0];\n}" :: "r"(bar), "r"(z) : "memory");
}
__device__ __forceinline__ void sts32_if(uint32_t z, uint32_t a, uint32_t x) {
    asm volatile("{\n.reg .pred p;\nsetp.eq.u32 p, %2, 0;\n@p st.shared.u32 [%0], %1;\n}" :: "r"(a), "r"(x), "r"(z) : "memory");
}
template <int K> __device__ __forceinline__ void sched_fence(int v) {
    asm volatile("{\n.reg .pred p;\nsetp.ne.s32 p, %0, %1;\n@p bra.uni F_%=;\ntrap;\nF_%=:\n}" :: "r"(v), "n"(1000 + K) : "memory");
}
__device__ __forceinline__ void spin_until(unsigned t0, unsigned d) {
    asm volatile("{\n.reg .pred p;\n.reg .u64 c;\n.reg .u32 lo;\n"
                 "S_%=: mov.u64 c, %%clock64;\ncvt.u32.u64 lo, c;\nsub.u32 lo, lo, %0;\nsetp.lt.u32 p, lo, %1;\n@p bra.uni S_%=;\n}" :: "r"(t0), "r"(d) : "memory");
}
__device__ __forceinline__ void bar_sync(int id, int n) { asm volatile("bar.sync %0, %1;" :: "r"(id), "r"(n) : "memory"); }
__device__ __forceinline__ void bar_sync_sel(int sel, int id) {
    asm volatile("{\n.reg .pred p;\nsetp.eq.u32 p, %0, 0;\n@p bar.sync %1, %3;\n@!p bar.sync %2, %3;\n}" :: "r"(sel), "r"(id), "r"(id + 1), "n"(192) : "memory");
}
__device__ __forceinline__ void bar_arrive(int id, int n) { asm volatile("bar.arrive %0, %1;" :: "r"(id), "r"(n) : "memory"); }
__device__ __forceinline__ void fence_async_smem() { asm volatile("fence.proxy.async.shared::cta;" ::: "memory"); }
__device__ __forceinline__ uint32_t pack_bf16(float lo, float hi) { uint32_t r; asm("cvt.rn.bf16x2.f32 %0, %1, %2;" : "=r"(r) : "f"(hi), "f"(lo)); return r; }
__device__ __forceinline__ uint32_t pack_f16(float lo, float hi) { uint32_t r; asm("cvt.rn.f16x2.f32 %0, %1, %2;" : "=r"(r) : "f"(hi), "f"(lo)); return r; }
__device__ __forceinline__ uint32_t f16x2_to_bf16x2(uint32_t v) { float2 f = __half22float2(*reinterpret_cast<__half2*>(&v)); return pack_bf16(f.x, f.y); }
__device__ __forceinline__ uint32_t hmul2(uint32_t a, uint32_t b) { uint32_t r; asm("mul.rn.f16x2 %0, %1, %2;" : "=r"(r) : "r"(a), "r"(b)); return r; }
__device__ __forceinline__ float ex2(float x) { float y; asm("ex2.approx.ftz.f32 %0, %1;" : "=f"(y) : "f"(x)); return y; }
__device__ __forceinline__ float ex2v(float x) { float y; asm volatile("ex2.approx.ftz.f32 %0, %1;" : "=f"(y) : "f"(x)); return y; }
__device__ __forceinline__ uint32_t absmax2(uint32_t a, uint32_t b) {
    uint32_t r; asm("max.xorsign.abs.bf16x2 %0, %1, %2;" : "=r"(r) : "r"(a), "r"(b)); return r;
}
__device__ __forceinline__ uint32_t shl_v(uint32_t a, int n) { return a << n; }
__device__ __forceinline__ uint32_t max3u(uint32_t a, uint32_t b, uint32_t c) { return max(max(a, b), c); }
__device__ __forceinline__ uint4 lds128(uint32_t a) { uint4 v; asm volatile("ld.shared.v4.u32 {%0,%1,%2,%3}, [%4];" : "=r"(v.x), "=r"(v.y), "=r"(v.z), "=r"(v.w) : "r"(a) : "memory"); return v; }
__device__ __forceinline__ uint4 lds128v(uint32_t a) { uint4 v; asm volatile("ld.volatile.shared.v4.u32 {%0,%1,%2,%3}, [%4];" : "=r"(v.x), "=r"(v.y), "=r"(v.z), "=r"(v.w) : "r"(a) : "memory"); return v; }
__device__ __forceinline__ float4 lds128f(uint32_t a) { float4 v; asm volatile("ld.shared.v4.f32 {%0,%1,%2,%3}, [%4];" : "=f"(v.x), "=f"(v.y), "=f"(v.z), "=f"(v.w) : "r"(a) : "memory"); return v; }
__device__ __forceinline__ float2 lds64f(uint32_t a) { float2 v; asm volatile("ld.shared.v2.f32 {%0,%1}, [%2];" : "=f"(v.x), "=f"(v.y) : "r"(a) : "memory"); return v; }
__device__ __forceinline__ uint4 lds64x2(uint32_t a) { uint4 v; asm volatile("ld.shared.v2.u32 {%0,%1}, [%4];\nld.shared.v2.u32 {%2,%3}, [%4+256];" : "=r"(v.x), "=r"(v.y), "=r"(v.z), "=r"(v.w) : "r"(a) : "memory"); return v; }
__device__ __forceinline__ uint32_t lds32(uint32_t a) { uint32_t v; asm volatile("ld.shared.u32 %0, [%1];" : "=r"(v) : "r"(a) : "memory"); return v; }
__device__ __forceinline__ void sts128(uint32_t a, uint32_t x, uint32_t y, uint32_t z, uint32_t w) { asm volatile("st.shared.v4.u32 [%0], {%1,%2,%3,%4};" :: "r"(a), "r"(x), "r"(y), "r"(z), "r"(w) : "memory"); }
__device__ __forceinline__ void sts128f(uint32_t a, float x, float y, float z, float w) { asm volatile("st.shared.v4.f32 [%0], {%1,%2,%3,%4};" :: "r"(a), "f"(x), "f"(y), "f"(z), "f"(w) : "memory"); }
__device__ __forceinline__ void sts64(uint32_t a, uint32_t x, uint32_t y) { asm volatile("st.shared.v2.u32 [%0], {%1,%2};" :: "r"(a), "r"(x), "r"(y) : "memory"); }
__device__ __forceinline__ void sts32(uint32_t a, uint32_t x) { asm volatile("st.shared.u32 [%0], %1;" :: "r"(a), "r"(x) : "memory"); }
__device__ __forceinline__ uint4 ldsm4(uint32_t a) { uint4 v; asm volatile("ldmatrix.sync.aligned.m8n8.x4.shared.b16 {%0,%1,%2,%3}, [%4];" : "=r"(v.x), "=r"(v.y), "=r"(v.z), "=r"(v.w) : "r"(a) : "memory"); return v; }
__device__ __forceinline__ void stsm2t(uint32_t a, uint32_t x, uint32_t y) { asm volatile("stmatrix.sync.aligned.m8n8.x2.trans.shared.b16 [%0], {%1,%2};" :: "r"(a), "r"(x), "r"(y) : "memory"); }
__device__ __forceinline__ void stsm4t(uint32_t a, uint32_t x, uint32_t y, uint32_t z, uint32_t w) { asm volatile("stmatrix.sync.aligned.m8n8.x4.trans.shared.b16 [%0], {%1,%2,%3,%4};" :: "r"(a), "r"(x), "r"(y), "r"(z), "r"(w) : "memory"); }
__device__ __forceinline__ void st_async64(uint32_t a, uint32_t x, uint32_t y, uint32_t bar) { asm volatile("st.async.shared::cluster.mbarrier::complete_tx::bytes.v2.b32 [%0], {%1,%2}, [%3];" :: "r"(a), "r"(x), "r"(y), "r"(bar) : "memory"); }
__device__ __forceinline__ void bulk_s2c(uint32_t dst, uint32_t src, uint32_t bytes, uint32_t bar) { asm volatile("cp.async.bulk.shared::cluster.shared::cta.mbarrier::complete_tx::bytes [%0], [%1], %2, [%3];" :: "r"(dst), "r"(src), "r"(bytes), "r"(bar) : "memory"); }
__device__ __forceinline__ void bulk_s2g(void* dst, uint32_t src, uint32_t bytes) { asm volatile("cp.async.bulk.global.shared::cta.bulk_group [%0], [%1], %2;" :: "l"(dst), "r"(src), "r"(bytes) : "memory"); }
__device__ __forceinline__ uint32_t ldg_nc32(const void* p) { uint32_t v; asm volatile("ld.global.nc.L2::128B.u32 %0, [%1];" : "=r"(v) : "l"(p)); return v; }
__device__ __forceinline__ uint4 ldg_relaxed128(const void* p) { uint4 v; asm volatile("ld.relaxed.gpu.global.v4.u32 {%0,%1,%2,%3}, [%4];" : "=r"(v.x), "=r"(v.y), "=r"(v.z), "=r"(v.w) : "l"(p) : "memory"); return v; }
__device__ __forceinline__ void mma16816(float (&d)[4], uint32_t a0, uint32_t a1, uint32_t a2, uint32_t a3, uint32_t b0, uint32_t b1) {
    asm volatile("mma.sync.aligned.m16n8k16.row.col.f32.bf16.bf16.f32 {%0,%1,%2,%3}, {%4,%5,%6,%7}, {%8,%9}, {%0,%1,%2,%3};"
        : "+f"(d[0]), "+f"(d[1]), "+f"(d[2]), "+f"(d[3]) : "r"(a0), "r"(a1), "r"(a2), "r"(a3), "r"(b0), "r"(b1));
}
__device__ __forceinline__ void mma16816_z(float (&d)[4], uint32_t a0, uint32_t a1, uint32_t a2, uint32_t a3, uint32_t b0, uint32_t b1) {
    asm volatile("mma.sync.aligned.m16n8k16.row.col.f32.bf16.bf16.f32 {%0,%1,%2,%3}, {%4,%5,%6,%7}, {%8,%9}, {%10,%10,%10,%10};"
        : "=f"(d[0]), "=f"(d[1]), "=f"(d[2]), "=f"(d[3]) : "r"(a0), "r"(a1), "r"(a2), "r"(a3), "r"(b0), "r"(b1), "f"(0.f));
}
__device__ __forceinline__ void mma1688(float (&d)[4], uint32_t a0, uint32_t a1, uint32_t b0) {
    asm volatile("mma.sync.aligned.m16n8k8.row.col.f32.bf16.bf16.f32 {%0,%1,%2,%3}, {%4,%5}, {%6}, {%0,%1,%2,%3};"
        : "+f"(d[0]), "+f"(d[1]), "+f"(d[2]), "+f"(d[3]) : "r"(a0), "r"(a1), "r"(b0));
}
__device__ __forceinline__ void mma1688_z(float (&d)[4], uint32_t a0, uint32_t a1, uint32_t b0) {
    asm volatile("mma.sync.aligned.m16n8k8.row.col.f32.bf16.bf16.f32 {%0,%1,%2,%3}, {%4,%5}, {%6}, {%7,%7,%7,%7};"
        : "=f"(d[0]), "=f"(d[1]), "=f"(d[2]), "=f"(d[3]) : "r"(a0), "r"(a1), "r"(b0), "f"(0.f));
}
template <int ACC>
__device__ __forceinline__ void wgmma_n32_rs(float (&d)[16], uint32_t a0, uint32_t a1, uint32_t a2, uint32_t a3, uint64_t desc) {
    asm volatile("wgmma.mma_async.sync.aligned.m64n32k16.f32.bf16.bf16 {%0,%1,%2,%3,%4,%5,%6,%7,%8,%9,%10,%11,%12,%13,%14,%15}, {%16,%17,%18,%19}, %20, %21, 1, 1, 0;"
        : "+f"(d[0]), "+f"(d[1]), "+f"(d[2]), "+f"(d[3]), "+f"(d[4]), "+f"(d[5]), "+f"(d[6]), "+f"(d[7]),
          "+f"(d[8]), "+f"(d[9]), "+f"(d[10]), "+f"(d[11]), "+f"(d[12]), "+f"(d[13]), "+f"(d[14]), "+f"(d[15])
        : "r"(a0), "r"(a1), "r"(a2), "r"(a3), "l"(desc), "n"(ACC));
}
template <int ACC>
__device__ __forceinline__ void wgmma_n32_ss(float (&d)[16], uint64_t da, uint64_t db) {
    asm volatile("wgmma.mma_async.sync.aligned.m64n32k16.f32.bf16.bf16 {%0,%1,%2,%3,%4,%5,%6,%7,%8,%9,%10,%11,%12,%13,%14,%15}, %16, %17, %18, 1, 1, 0, 0;"
        : "+f"(d[0]), "+f"(d[1]), "+f"(d[2]), "+f"(d[3]), "+f"(d[4]), "+f"(d[5]), "+f"(d[6]), "+f"(d[7]),
          "+f"(d[8]), "+f"(d[9]), "+f"(d[10]), "+f"(d[11]), "+f"(d[12]), "+f"(d[13]), "+f"(d[14]), "+f"(d[15])
        : "l"(da), "l"(db), "n"(ACC));
}
__device__ __forceinline__ void wg_fence() { asm volatile("wgmma.fence.sync.aligned;" ::: "memory"); }
__device__ __forceinline__ void wg_commit() { asm volatile("wgmma.commit_group.sync.aligned;" ::: "memory"); }
__device__ __forceinline__ void wg_wait0() { asm volatile("wgmma.wait_group.sync.aligned 0;" ::: "memory"); }
__device__ __forceinline__ void cluster_sync() { asm volatile("barrier.cluster.arrive.aligned;\nbarrier.cluster.wait.aligned;" ::: "memory"); }

#define STAMP(s, i) do {} while (0)
#define STAMPV(s, i, v) do {} while (0)

constexpr int XT_BYTES = 36864;
constexpr int O_XT = 0;
constexpr int O_STG = XT_BYTES;
constexpr int O_AS = 3 * XT_BYTES;
constexpr int O_XP = O_AS + 16384;
constexpr int O_QKX = O_XP + 8192;
constexpr int O_KM = O_QKX + 8192;
constexpr int O_QM = O_QKX + 10240;
constexpr int O_VX = O_STG + 147456;
constexpr int O_VM = O_VX + 16384;
constexpr int O_SC = O_VM + 2048;
constexpr int O_OF = O_SC + 2560;
constexpr int O_AF = O_OF + 2048;
constexpr int O_WP = O_AF + 4096;
constexpr int O_MF = O_WP + 2048;
constexpr int O_MISC = O_MF + 9216;
static_assert(O_QKX + 24576 <= O_VX, "smem");
constexpr int O_BAR = O_MISC + 64;
constexpr int CHAIN_SMEM = O_BAR + 128;
static_assert(CHAIN_SMEM <= 232448, "smem");
constexpr int B_X = O_BAR, B_VX = O_BAR + 24, B_SC = O_BAR + 40, B_W = O_BAR + 48;
constexpr float SM_SCALE = 0.08838834764831845f * 1.4426950408889634f;
constexpr uint32_t ONES = 0x3f803f80u;

__device__ __forceinline__ uint32_t opaque(uint32_t v) { uint32_t o; asm volatile("mov.u32 %0, %1;" : "=r"(o) : "r"(v)); return o; }
__device__ __forceinline__ void st_async128(uint32_t a, uint32_t x, uint32_t y, uint32_t z, uint32_t w, uint32_t bar) {
    asm volatile("st.async.shared::cluster.mbarrier::complete_tx::bytes.v4.b32 [%0], {%1,%2,%3,%4}, [%5];" :: "r"(a), "r"(x), "r"(y), "r"(z), "r"(w), "r"(bar) : "memory");
}
__device__ __forceinline__ void tma_x_tile(uint32_t sb, const CUtensorMap* tm, int r, int j, int slot) {
    asm volatile("{\n.reg .pred p;\nelect.sync _|p, 0xffffffff;\n"
        "@p mbarrier.arrive.expect_tx.shared::cta.b64 _, [%2], 36864;\n"
        "@p cp.async.bulk.tensor.2d.shared::cluster.global.mbarrier::complete_tx::bytes.multicast::cluster [%0], [%1, {%3, %4}], [%2], %7;\n"
        "@p cp.async.bulk.tensor.2d.shared::cluster.global.mbarrier::complete_tx::bytes.multicast::cluster [%0+4096], [%1, {%5, %4}], [%2], %7;\n"
        "@p cp.async.bulk.tensor.2d.shared::cluster.global.mbarrier::complete_tx::bytes.multicast::cluster [%0+8192], [%1, {%6, %4}], [%2], %7;\n}"
        :: "r"(sb + O_XT + slot * XT_BYTES + 3 * r * 4096), "l"(tm), "r"(sb + B_X + 8 * slot), "r"(192 * r), "r"(j * 32), "r"(192 * r + 64), "r"(192 * r + 128),
           "h"((unsigned short)7) : "memory");
}
__device__ __forceinline__ float quad_max(float v) {
    const float a = __shfl_xor_sync(~0u, v, 1), b = __shfl_xor_sync(~0u, v, 2), c = __shfl_xor_sync(~0u, v, 3);
    return fmaxf(fmaxf(v, a), fmaxf(b, c));
}
__device__ __forceinline__ void load_scores(float (&p)[10], uint32_t base, uint32_t stride, uint32_t l16) {
    const float4 a0 = lds128f(base + l16), b0 = lds128f(base + stride + l16);
    const float4 a1 = lds128f(base + 512 + l16), b1 = lds128f(base + stride + 512 + l16);
    const float2 a2 = lds64f(base + 1024 + (l16 >> 1)), b2 = lds64f(base + stride + 1024 + (l16 >> 1));
    p[0] = a2.x + b2.x; p[1] = a2.y + b2.y;
    p[2] = a0.x + b0.x; p[3] = a0.y + b0.y; p[4] = a0.z + b0.z; p[5] = a0.w + b0.w;
    p[6] = a1.x + b1.x; p[7] = a1.y + b1.y; p[8] = a1.z + b1.z; p[9] = a1.w + b1.w;
}
__device__ __forceinline__ float rcp_fast(float x) { float y; asm("rcp.approx.ftz.f32 %0, %1;" : "=f"(y) : "f"(x)); return y; }

__global__ void __cluster_dims__(3, 1, 1) __launch_bounds__(384, 1)
chain_kernel(const __grid_constant__ CUtensorMap tm_x, const __grid_constant__ CUtensorMap tm_q,
             const __grid_constant__ CUtensorMap tm_k, const __grid_constant__ CUtensorMap tm_v,
             const __nv_bfloat16* __restrict__ x, const __nv_bfloat16* __restrict__ mem0,
             const __nv_bfloat16* __restrict__ Wo) {
    extern __shared__ __align__(1024) uint8_t smem_raw[];
    const uint32_t sb = smem_u32(smem_raw);
    const int lane = threadIdx.x & 31;
    const int warp = __shfl_sync(~0u, threadIdx.x >> 5, 0);
    const int wg = warp >> 2, w = warp & 3;
    const int h = blockIdx.x / 3, r = blockIdx.x - 3 * h;
    uint4* const g_acc = reinterpret_cast<uint4*>((reinterpret_cast<uintptr_t>(g_acc_raw) + 0x1fffff) & ~(uintptr_t)0x1fffff);

#define PSTAMP(i) do {} while (0)
    if (threadIdx.x == 0) {
        if (sb & 1023u) __trap();
        for (int i = 0; i < 9; i++) mbar_init(sb + O_BAR + 8 * i, 1);
        asm volatile("fence.mbarrier_init.release.cluster;" ::: "memory");
        for (int i = 0; i < 3; i++) {
            mbar_expect(sb + B_W + 8 * i, 49152);
            for (int tl = 0; tl < 2; tl++)
                asm volatile("cp.async.bulk.tensor.2d.shared::cluster.global.mbarrier::complete_tx::bytes [%0], [%1, {%3, %4}], [%2];"
                    :: "r"(sb + O_STG + tl * 73728 + i * 24576), "l"(r < 2 ? (tl ? &tm_k : &tm_q) : &tm_v), "r"(sb + B_W + 8 * i),
                       "r"(h * 128 + 64 * (r < 2 ? r : tl)), "r"(192 * i) : "memory");
        }
    }
    __syncwarp();
    asm volatile("barrier.cluster.arrive.relaxed.aligned;" ::: "memory");
    asm volatile("griddepcontrol.launch_dependents;" ::: "memory");
    if (warp == 0) PSTAMP(9);
    const uint32_t l16c = __shfl_sync(~0u, lane * 16, lane);

    if (wg < 2) {
#define KS(u) ((u) < 8 ? 12 * ((u) >> 2) + (((u) >> 1) & 1) + 4 * ((u) & 1) : (u) < 12 ? (u) : (u) < 16 ? (u) + 8 : (u) < 24 ? 24 + (((u) - 16) >> 1) + 4 * ((u) & 1) : (u) + 8)
        asm volatile("setmaxnreg.inc.sync.aligned.u32 184;");
        uint32_t a[144];
        uint32_t adr1;
        {
            const int g = lane >> 2, t = lane & 3;
            const int t1 = threadIdx.x;
#pragma unroll
            for (int i = 0; i < 2; i++) g_acc[(blockIdx.x * 64 + i * 32 + (t1 >> 3)) * 16 + (t1 & 7)] = make_uint4(0, 0, 0, 0);
            __threadfence();
            asm volatile("barrier.cluster.wait.aligned;" ::: "memory");
            const uint32_t ev = sb + O_STG + (2 * t) * 128 + (((2 * w + (g >> 2)) ^ (2 * t)) << 4) + (g & 3) * 4;
            const uint32_t od = (ev ^ 16) + 128;
            auto gather = [&](int dst, uint32_t off) {
                a[dst] = lds32(ev + off); a[dst + 1] = lds32(od + off); a[dst + 2] = lds32(ev + off + 1024); a[dst + 3] = lds32(od + off + 1024);
            };
            const uint4* xp = reinterpret_cast<const uint4*>(x) + blockIdx.x * 1536 + t1;
            uint4 xv[6];
#pragma unroll
            for (int th = 0; th < 2; th++) {
                mbar_wait(sb + B_W + 8 * th, 0);
                if (th == 1) {
#pragma unroll
                    for (int i = 0; i < 6; i++) xv[i] = __ldg(xp + i * 256);
                }
#pragma unroll
                for (int u = 4 * th; u < 4 * th + 4; u++) {
                    gather(32 + 4 * u, wg * (73728 + 4096) + KS(u) * 2048);
                    gather(4 * u, 73728 - wg * (73728 - 4096) + KS(u) * 2048);
                    gather(64 + 4 * u, wg * 73728 + KS(8 + u) * 2048);
                }
            }
            mbar_wait(sb + B_W + 16, 0);
#pragma unroll
            for (int u = 16; u < 28; u++) gather(32 + 4 * u, wg * 73728 + KS(u) * 2048);
#pragma unroll
            for (int kk = 0; kk < 72; kk++) {
                uint32_t w0 = a[2 * kk], w1 = a[2 * kk + 1];
                a[2 * kk] = __byte_perm(w0, w1, 0x5410);
                a[2 * kk + 1] = __byte_perm(w0, w1, 0x7632);
            }
            if (r == 2) {
                float n0[4], n1[4];
#pragma unroll
                for (int u = 0; u < 36; u++) {
                    const uint32_t x0 = a[4 * u] & 0x7fff7fffu, x1 = a[4 * u + 1] & 0x7fff7fffu, x2 = a[4 * u + 2] & 0x7fff7fffu, x3 = a[4 * u + 3] & 0x7fff7fffu;
                    if (u == 0) mma16816_z(n0, x0, x1, x2, x3, ONES, ONES);
                    else if (u < 8) mma16816(n0, x0, x1, x2, x3, ONES, ONES);
                    else if (u == 8) mma16816_z(n1, x0, x1, x2, x3, ONES, ONES);
                    else mma16816(n1, x0, x1, x2, x3, ONES, ONES);
                }
                const uint32_t mx = __reduce_max_sync(~0u, __float_as_uint(2.f * fmaxf(fmaxf(n0[0], n0[2]), fmaxf(n1[0], n1[2]))));
                sts32_if(lane, sb + O_MISC + 32 + 4 * warp, mx);
            }
            uint32_t xm = 0;
#pragma unroll
            for (int i = 0; i < 6; i++)
                xm = __vmaxu2(xm, __vmaxu2(__vmaxu2(xv[i].x & 0x7fff7fffu, xv[i].y & 0x7fff7fffu), __vmaxu2(xv[i].z & 0x7fff7fffu, xv[i].w & 0x7fff7fffu)));
            sts32_if(lane, sb + O_OF + 16 + 4 * warp, __reduce_max_sync(~0u, max(xm << 16, xm & 0xffff0000u)));
            if (warp == 0) PSTAMP(11);
            bar_arrive(7, 384);
            asm volatile("barrier.cluster.arrive.relaxed.aligned;" ::: "memory");
            bar_sync(1, 256);
            const uint32_t as = sb + O_AS + wg * 8192 + (16 * w + g) * 128 + t * 4;
            sts32(as + (g << 4), a[32]);
            sts32(as + 1024 + (g << 4), a[33]);
            sts32(as + ((1 ^ g) << 4), a[34]);
            sts32(as + 1024 + ((1 ^ g) << 4), a[35]);
            sts128(sb + O_AF + warp * 512 + lane * 16, a[32], a[33], a[34], a[35]);
            fence_async_smem();
            bar_sync(1, 256);
            const uint32_t l = lane * 16;
            const int mi = lane >> 3, isk = (mi >> 1) ? wg : (wg ^ 1);
            adr1 = (r == 2) ? (sb + O_VM + warp * 256 + (l >> 1))
                            : (isk ? (sb + O_KM + w * 512 + wg * 256 + (mi & 1) * 128 + (l & 127))
                                   : (sb + O_QM + w * 512 + (mi & 1) * 256 + wg * 128 + (l & 127)));
            adr1 = __shfl_sync(~0u, adr1, lane);
        }
        int s3 = 2;
#pragma unroll 1
        for (int s = -1; s < NSEG; s++) {
            const uint32_t l16 = opaque(l16c);
            s3 = (s3 == 2) ? 0 : s3 + 1;
            if (s < 0) mbar_wait(sb + B_X, 0);
            const uint64_t desc0 = (uint64_t)(((sb + O_XT + s3 * XT_BYTES) & 0x3FFFF) >> 4) | (1ull << 16) | (64ull << 32) | (1ull << 62);
            uint32_t km0 = 0, km1 = 0;
            if (s >= 0) {
                { const uint4 v = lds128(sb + O_AF + warp * 512 + l16); a[32] = v.x; a[33] = v.y; a[34] = v.z; a[35] = v.w; }
                float co[4], cw[3][4];
                uint4 b[14];
                float inv;
#define GORD(i) ((i) < 8 ? 2 * ((i) >> 2) + (((i) >> 1) & 1) + 4 * ((i) & 1) : (i))
                auto qkv_mma = [&](int i) {
                    const int gi = GORD(i), u = 8 * gi, n0 = 2 * i, n1 = 2 * i + 1;
                    if (gi < 4) {
                        if (i == 0) mma16816_z(co, a[u], a[u + 1], a[u + 2], a[u + 3], b[0].x, b[0].y);
                        else mma16816(co, a[u], a[u + 1], a[u + 2], a[u + 3], b[i].x, b[i].y);
                    }
                    if (n0 < 3) mma16816_z(cw[n0 % 3], a[32 + u], a[32 + u + 1], a[32 + u + 2], a[32 + u + 3], b[i].x, b[i].y);
                    else mma16816(cw[n0 % 3], a[32 + u], a[32 + u + 1], a[32 + u + 2], a[32 + u + 3], b[i].x, b[i].y);
                    if (n1 < 3) mma16816_z(cw[n1 % 3], a[32 + u + 4], a[32 + u + 5], a[32 + u + 6], a[32 + u + 7], b[i].z, b[i].w);
                    else mma16816(cw[n1 % 3], a[32 + u + 4], a[32 + u + 5], a[32 + u + 6], a[32 + u + 7], b[i].z, b[i].w);
                    if (gi < 4) mma16816(co, a[u + 4], a[u + 5], a[u + 6], a[u + 7], b[i].z, b[i].w);
                };
                const uint32_t mf = sb + O_MF + l16, mfs = mf + wg * 1024;
                const uint32_t qb = (s & 1) * 12288;
                bar_sync(2, 384);
                if (warp == 0) STAMP(s, 0);
                auto qkv_ld = [&](int i) {
                    const int gi = GORD(i);
                    b[i] = gi < 4 ? lds128v(mfs + (gi >> 1) * 3072 + (gi & 1) * 512) : lds128v(mf + (gi < 6 ? gi : gi + 4) * 512);
                };
#pragma unroll
                for (int i = 0; i < 4; i++) qkv_ld(i);
                qkv_mma(0); qkv_mma(1); qkv_mma(2);
                const uint32_t z0 = __float_as_uint(QDEP ? co[0] : cw[1][0]) & (l16 & 15u);
                qkv_mma(3);
                bar_sync(15, 384);
                b[4] = lds128v(mfs + 3072 + z0);
#pragma unroll
                for (int i = 5; i < 9; i++) qkv_ld(i);
#pragma unroll
                for (int i = 4; i < 9; i++) { qkv_mma(i); qkv_ld(5 + i); }
                asm volatile("ld.volatile.shared.f32 %0, [%1];" : "=f"(inv) : "r"(sb + O_MISC) : "memory");
#pragma unroll
                for (int i = 9; i < 14; i++) qkv_mma(i);
#pragma unroll
                for (int i = 0; i < 4; i++) cw[0][i] += cw[1][i] + cw[2][i];
                if (r < 2) {
                    const uint32_t o0 = pack_bf16(co[0] * inv, co[1] * inv), o1 = pack_bf16(co[2] * inv, co[3] * inv);
                    const uint32_t w0 = pack_bf16(cw[0][0] * inv, cw[0][1] * inv), w1 = pack_bf16(cw[0][2] * inv, cw[0][3] * inv);
                    stsm4t(adr1 + qb, o0, o1, w0, w1);
                    if (warp == 0) STAMP(s, 1);
                    asm volatile("{\n.reg .pred p;\nsetp.ge.u32 p, %0, 3;\n@p bar.arrive 1, 256;\n}" :: "r"(warp) : "memory");
                    if (warp < 3 && s < NSEG - 1) {
                        uint4 q[4], k[4];
                        const uint32_t ka = sb + O_QKX + 4096 + qb + warp * 2048 + l16;
#pragma unroll
                        for (int i = 0; i < 4; i++) k[i] = ldsm4(ka + i * 512);
                        const uint32_t dst = sb + O_SC + r * 1280 + warp * 512 + (l16 >> 1);
                        bar_sync(1, 256);
#pragma unroll
                        for (int i = 0; i < 4; i++) q[i] = ldsm4(sb + O_QM + qb + i * 512 + l16);
                        if (warp == 2) {
#pragma unroll
                            for (int i = 0; i < 4; i++) k[i] = ldsm4(ka + i * 512);
                        }
                        float s0[4], s1[4], t0[4], t1[4];
                        mma16816_z(s0, q[0].x, q[0].y, q[0].z, q[0].w, k[0].x, k[0].y);
                        mma16816_z(s1, q[0].x, q[0].y, q[0].z, q[0].w, k[0].z, k[0].w);
                        mma16816_z(t0, q[1].x, q[1].y, q[1].z, q[1].w, k[1].x, k[1].y);
                        mma16816_z(t1, q[1].x, q[1].y, q[1].z, q[1].w, k[1].z, k[1].w);
                        mma16816(s0, q[2].x, q[2].y, q[2].z, q[2].w, k[2].x, k[2].y);
                        mma16816(s1, q[2].x, q[2].y, q[2].z, q[2].w, k[2].z, k[2].w);
                        mma16816(t0, q[3].x, q[3].y, q[3].z, q[3].w, k[3].x, k[3].y);
                        mma16816(t1, q[3].x, q[3].y, q[3].z, q[3].w, k[3].z, k[3].w);
                        const float v0 = (s0[0] + s0[2]) + (t0[0] + t0[2]), v1 = (s0[1] + s0[3]) + (t0[1] + t0[3]);
                        const float v2 = (s1[0] + s1[2]) + (t1[0] + t1[2]), v3 = (s1[1] + s1[3]) + (t1[1] + t1[3]);
                        if (warp < 2) {
                            const uint32_t dv = dst + (l16 >> 1);
                            st_async128(mapa(dv, 2), __float_as_uint(v0), __float_as_uint(v1), __float_as_uint(v2), __float_as_uint(v3), mapa(sb + B_SC, 2));
                            st_async128(mapa(dv, r ^ 1), __float_as_uint(v0), __float_as_uint(v1), __float_as_uint(v2), __float_as_uint(v3), mapa(sb + B_SC, r ^ 1));
                            st_async128(mapa(dv, r), __float_as_uint(v0), __float_as_uint(v1), __float_as_uint(v2), __float_as_uint(v3), mapa(sb + B_SC, r));
                        } else {
                            st_async64(mapa(dst, 2), __float_as_uint(v0 + v2), __float_as_uint(v1 + v3), mapa(sb + B_SC, 2));
                            st_async64(mapa(dst, r ^ 1), __float_as_uint(v0 + v2), __float_as_uint(v1 + v3), mapa(sb + B_SC, r ^ 1));
                            st_async64(mapa(dst, r), __float_as_uint(v0 + v2), __float_as_uint(v1 + v3), mapa(sb + B_SC, r));
                        }
                        if (warp == 2) STAMP(s, 2);
                    } else if (warp < 3) {
                        bar_sync(1, 256);
                    }
                } else {
                    sts128f(sb + O_XP + warp * 512 + l16, co[0], co[1], co[2], co[3]);
                    bar_sync(8 + w, 64);
                    const float4 o = lds128f(sb + O_XP + (warp ^ 4) * 512 + l16);
                    km0 = pack_bf16((cw[0][0] + o.x) * inv, (cw[0][1] + o.y) * inv);
                    km1 = pack_bf16((cw[0][2] + o.z) * inv, (cw[0][3] + o.w) * inv);
                    if (warp == 0) STAMP(s, 1);
                    if (s < NSEG - 1) {
                        st_async64(mapa(adr1, 0), km0, km1, mapa(sb + B_SC, 0));
                        st_async64(mapa(adr1, 1), km0, km1, mapa(sb + B_SC, 1));
                        st_async64(mapa(adr1, 2), km0, km1, mapa(sb + B_SC, 2));
                    }
                    if (warp == 0) STAMP(s, 2);
                }
            }
            char* rec = reinterpret_cast<char*>(g_qkv) + (size_t)(s * NH + h) * REC;
            auto store_qk = [&]() {
                asm volatile("{\n.reg .pred p;\nelect.sync _|p, 0xffffffff;\n"
                    "@p cp.async.bulk.global.shared::cta.bulk_group [%0], [%1], 10240;\n@p cp.async.bulk.commit_group;\n}"
                    :: "l"(rec + r * 10240), "r"(sb + O_QKX + (s & 1) * 12288) : "memory");
            };
            auto store_vm = [&]() { *reinterpret_cast<uint2*>(rec + 28672 + warp * 256 + (l16 >> 1)) = make_uint2(km0, km1); };
            if (s == NSEG - 1) fence_async_smem();
            if (s >= 0) bar_sync(3, 384);
            if (s == NSEG - 1) {
                if (r == 2) store_vm();
                else if (warp == 3) {
                    store_qk();
                    asm volatile("cp.async.bulk.wait_group 0;\nfence.proxy.async.global;" ::: "memory");
                }
            } else {
                const int j = s + 1;
#define XDESC(u) (((u) < 8 ? descs : desc0) + (uint64_t)(((KS(u) >> 2) * 4096 + (KS(u) & 3) * 32) >> 4))
                const uint64_t descs = desc0 + (uint64_t)(wg * 4);
                float d[16];
                wg_fence();
#pragma unroll
                for (int u = 0; u < 8; u++) {
                    if (u == 0) wgmma_n32_rs<0>(d, a[0], a[1], a[2], a[3], XDESC(0));
                    else wgmma_n32_rs<1>(d, a[4 * u], a[4 * u + 1], a[4 * u + 2], a[4 * u + 3], XDESC(u));
                }
                wg_commit();
                wg_wait0();
                if (warp == 0) STAMP(s, 15);
                if (s >= 0) bar_sync(4, 384);
#pragma unroll
                for (int q = 0; q < 2; q++)
                    sts128(sb + O_XP + warp * 1024 + q * 512 + l16, pack_bf16(d[8 * q], d[8 * q + 1]), pack_bf16(d[8 * q + 2], d[8 * q + 3]),
                           pack_bf16(d[8 * q + 4], d[8 * q + 5]), pack_bf16(d[8 * q + 6], d[8 * q + 7]));
                if (s >= 0) {
                    if (r == 2) store_vm();
                    else fence_async_smem();
                    if (warp == 3) asm volatile("cp.async.bulk.wait_group 0;\nfence.proxy.async.global;" ::: "memory");
                    if (warp == 1 && s + 2 < NSEG) tma_x_tile(sb, &tm_x, r, s + 2, s3 == 2 ? 0 : s3 + 1);
                }
                bar_sync(12, 256);
#pragma unroll
                for (int q = 0; q < 2; q++) {
                    const uint4 o = lds128(sb + O_XP + (warp ^ 4) * 1024 + q * 512 + l16);
                    d[8 * q] = __uint_as_float(o.x << 16); d[8 * q + 1] = __uint_as_float(o.x & 0xffff0000u);
                    d[8 * q + 2] = __uint_as_float(o.y << 16); d[8 * q + 3] = __uint_as_float(o.y & 0xffff0000u);
                    d[8 * q + 4] = __uint_as_float(o.z << 16); d[8 * q + 5] = __uint_as_float(o.z & 0xffff0000u);
                    d[8 * q + 6] = __uint_as_float(o.w << 16); d[8 * q + 7] = __uint_as_float(o.w & 0xffff0000u);
                }
                if (s >= 0) {
                    if (warp == 6 && (s & 3) == 0 && s >= 4)
                        asm volatile("{\n.reg .pred p;\nsetp.eq.u32 p, %1, 0;\n@p red.release.gpu.global.inc.u32 [%0], 0xffffffff;\n}"
                                     :: "l"(&g_flag[F_QKV + (s - 4 + (h >> 3)) * 8]), "r"(l16) : "memory");
                    asm volatile("{\n.reg .pred p;\nsetp.eq.u32 p, %0, 0;\n@p bar.sync 5, 256;\n@!p bar.sync 13, 256;\n}" :: "r"(wg) : "memory");
                }
                const uint64_t da0 = (uint64_t)(((sb + O_AS + wg * 8192) & 0x3FFFF) >> 4) | (1ull << 16) | (64ull << 32) | (1ull << 62);
                wg_fence();
                wgmma_n32_ss<1>(d, da0, XDESC(0));
#pragma unroll
                for (int u = 1; u < 28; u++) wgmma_n32_rs<1>(d, a[32 + 4 * u], a[32 + 4 * u + 1], a[32 + 4 * u + 2], a[32 + 4 * u + 3], XDESC(u));
                wg_commit();
                wg_wait0();
                if (warp == 3 && r < 2 && s >= 0) store_qk();
                if (warp == 4) STAMP(s, 3);
                uint32_t e[8];
#pragma unroll
                for (int i = 0; i < 8; i++) e[i] = pack_bf16(d[2 * i], d[2 * i + 1]);
                if (r < 2) {
                    const uint32_t base = sb + O_QKX + (j & 1) * 12288 + wg * 4096 + w * 512 + l16;
                    stsm4t(base, e[0], wg ? e[1] : e[2], wg ? e[2] : e[1], e[3]);
                    stsm4t(base + 2048, e[4], wg ? e[5] : e[6], wg ? e[6] : e[5], e[7]);
                } else {
                    const uint32_t base = sb + O_VX + (j & 1) * 8192 + warp * 1024 + l16;
                    sts128(base, e[0], e[1], e[2], e[3]);
                    sts128(base + 512, e[4], e[5], e[6], e[7]);
                    fence_async_smem();
                    bar_arrive(14, 288);
                }
                if (warp == 7) STAMP(s, 4);
                if (s < 0) asm volatile("barrier.cluster.wait.aligned;" ::: "memory");
            }
        }
        bar_arrive(7, 384);
    } else {
        asm volatile("setmaxnreg.dec.sync.aligned.u32 136;");
        const int c = w;
        uint32_t a[96];
        uint32_t mmax = 0;
        {
            const int g = lane >> 2, t = lane & 3;
            uint32_t tag = 0, m0v[18];
            if (threadIdx.x == 256) tag = atomicAdd(&g_ticket, 1u);
#pragma unroll
            for (int i = 0; i < 9; i++) {
                const uint32_t* p = reinterpret_cast<const uint32_t*>(mem0 + g * DM + 16 * (4 * i + c) + 2 * t);
                m0v[2 * i] = __ldg(p); m0v[2 * i + 1] = __ldg(p + 4);
            }
            asm volatile("barrier.cluster.wait.aligned;" ::: "memory");
            if (c == 0) {
                tma_x_tile(sb, &tm_x, r, 0, 0);
                mbar_expect_if(lane, sb + B_SC, 4608);
                if (r < 2) mbar_expect_if(lane, sb + B_VX, 8192);
                sts32_if(lane, sb + O_MISC, __float_as_uint(1.0f));
                sts32_if(lane, sb + O_MISC + 12, __float_as_uint(SM_SCALE));
            }
            asm volatile("barrier.cluster.arrive.relaxed.aligned;" ::: "memory");
#pragma unroll
            for (int tau = 0; tau < 3; tau++) {
                const uint32_t* v = m0v + 6 * tau;
                sts128(sb + O_MF + tau * 3072 + c * 512 + lane * 16, v[0], v[1], v[2], v[3]);
                sts64(sb + O_MF + tau * 3072 + 2048 + (c >> 1) * 512 + lane * 16 + (c & 1) * 8, v[4], v[5]);
#pragma unroll
                for (int i = 0; i < 6; i++) mmax = __vmaxu2(mmax, v[i] & 0x7fff7fffu);
            }
            mmax = max(mmax << 16, mmax & 0xffff0000u);
            bar_arrive(2, 384); bar_arrive(15, 384);
            tag = (__shfl_sync(~0u, tag, 0) / 96u + 1u) & 0xffffu;
            mbar_wait(sb + B_W + 0, 0);
            const __nv_bfloat16* p = Wo + (size_t)(h * 128 + 4 * t) * DM + 192 * r + 16 * c + 2 * g;
#pragma unroll
            for (int i = 0; i < 3; i++)
#pragma unroll
                for (int eb = 0; eb < 8; eb++)
#pragma unroll
                    for (int j = 0; j < 4; j++) a[(i * 8 + eb) * 4 + j] = ldg_nc32(p + (16 * eb + ((j & 1) * 2 + (j >> 1))) * DM + 64 * i);
#pragma unroll
            for (int kk = 0; kk < 48; kk++) {
                uint32_t w0 = a[2 * kk], w1 = a[2 * kk + 1];
                a[2 * kk] = __byte_perm(w0, w1, 0x5410);
                a[2 * kk + 1] = __byte_perm(w0, w1, 0x7632);
            }
            sts128(sb + O_WP + c * 512 + lane * 16, a[92], a[93], a[94], a[95]);
            float wmax = 0.f;
#pragma unroll
            for (int i = 0; i < 3; i++) {
                float n0[4];
#pragma unroll
                for (int u = 8 * i; u < 8 * i + 8; u++) {
                    const uint32_t x0 = a[4 * u] & 0x7fff7fffu, x1 = a[4 * u + 1] & 0x7fff7fffu, x2 = a[4 * u + 2] & 0x7fff7fffu, x3 = a[4 * u + 3] & 0x7fff7fffu;
                    if (u == 8 * i) mma16816_z(n0, x0, x1, x2, x3, ONES, ONES);
                    else mma16816(n0, x0, x1, x2, x3, ONES, ONES);
                }
                wmax = fmaxf(wmax, fmaxf(n0[0], n0[2]));
            }
            uint32_t wm = __reduce_max_sync(~0u, __float_as_uint(wmax));
            sts32_if(lane, sb + O_OF + 4 * c, wm);
            if (c == 0) PSTAMP(8);
            bar_sync(7, 384);
            asm volatile("barrier.cluster.wait.aligned;" ::: "memory");
            if (c == 1) tma_x_tile(sb, &tm_x, r, 1, 1);
            if (c == 0) {
                const uint4 wq = lds128(sb + O_OF), xq = lds128(sb + O_OF + 16), xr = lds128(sb + O_OF + 32), v0 = lds128(sb + O_MISC + 32), v1 = lds128(sb + O_MISC + 48);
                const uint32_t w1 = max(max(wq.x, wq.y), max(wq.z, wq.w)), x1 = max(max(max(xq.x, xq.y), max(xq.z, xq.w)), max(max(xr.x, xr.y), max(xr.z, xr.w)));
                const uint32_t vv = (r < 2) ? 0u : max(max(max(v0.x, v0.y), max(v0.z, v0.w)), max(max(v1.x, v1.y), max(v1.z, v1.w)));
                const uint32_t lo = (min(w1, 0x7f800000u) + 0xffffu) >> 16 | ((min(vv, 0x7f800000u) + 0xffffu) & 0xffff0000u), hi = (x1 & 0xffff0000u) | tag;
                uint32_t l0, h0, l1, h1, l2, h2;
                asm volatile("{\n.reg .pred p;\n.reg .u32 n, x, y;\n.reg .b64 v;\nsetp.eq.u32 p, %10, 0;\nmov.b64 v, {%8, %9};\n@p st.relaxed.gpu.global.b64 [%7], v;\nmov.u32 n, 0;\n"
                             "G_%=: ld.relaxed.gpu.global.b64 v, [%6];\nmov.b64 {%0, %1}, v;\nld.relaxed.gpu.global.b64 v, [%6+256];\nmov.b64 {%2, %3}, v;\n"
                             "ld.relaxed.gpu.global.b64 v, [%6+512];\nmov.b64 {%4, %5}, v;\n"
                             "xor.b32 x, %1, %9;\nxor.b32 y, %3, %9;\nor.b32 x, x, y;\nxor.b32 y, %5, %9;\nor.b32 x, x, y;\nand.b32 x, x, 0xffff;\n"
                             "setp.eq.u32 p, x, 0;\nvote.sync.all.pred p, p, 0xffffffff;\n@p bra.uni E_%=;\n"
                             "add.u32 n, n, 1;\nsetp.lt.u32 p, n, 4000000;\n@p bra.uni G_%=;\ntrap;\nE_%=:\n}"
                             : "=&r"(l0), "=&r"(h0), "=&r"(l1), "=&r"(h1), "=&r"(l2), "=&r"(h2)
                             : "l"(&g_norm[lane]), "l"(&g_norm[blockIdx.x]), "r"(lo), "r"(hi), "r"(lane) : "memory");
                const uint32_t lm = __vmaxu2(l0, __vmaxu2(l1, l2));
                const float fw = __uint_as_float(__reduce_max_sync(~0u, lm << 16));
                const float fv = __uint_as_float(__reduce_max_sync(~0u, lm & 0xffff0000u));
                const float xmax = __uint_as_float(__reduce_max_sync(~0u, max(h0, max(h1, h2)) & 0xffff0000u));
                const float G = 36.f * fw * fv;
                sts32_if(lane, sb + O_MISC + 4, __float_as_uint(G)); sts32_if(lane, sb + O_MISC + 8, __float_as_uint(G * xmax));
            }
        }
        if (c == 0) PSTAMP(12);
        bar_sync(6, 128);
        int s3n = 1;
        uint32_t roff = __shfl_sync(~0u, (r * 4 + c) * 2048 + (lane >> 4) * 512 + (lane & 2) * 128 + (lane & 1) * 64 + (lane & 12) * 4, lane);
#pragma unroll 1
        for (int s = 0; s < NSEG; s++) {
            const uint32_t l16 = opaque(l16c);
            const uint32_t vxa = sb + O_VX + (s & 1) * 8192 + c * 2048 + l16;
            if (c == 0 && r == 2) {
                bar_sync(14, 288);
                asm volatile("{\n.reg .pred p;\nelect.sync _|p, 0xffffffff;\n"
                    "@p cp.async.bulk.global.shared::cta.bulk_group [%0], [%1], 8192;\n@p cp.async.bulk.commit_group;\n"
                    "cp.async.bulk.wait_group 0;\nsetp.lt.and.s32 p, %4, 63, p;\n"
                    "@p cp.async.bulk.shared::cluster.global.mbarrier::complete_tx::bytes.multicast::cluster [%1], [%0], 8192, [%2], %3;\n"
                    "fence.proxy.async.global;\n}"
                    :: "l"(reinterpret_cast<char*>(g_qkv) + (size_t)(s * NH + h) * REC + 20480), "r"(sb + O_VX + (s & 1) * 8192),
                       "r"(sb + B_VX + 8 * (s & 1)), "h"((unsigned short)3), "r"(s) : "memory");
            }
            if (s == NSEG - 1) { bar_sync(3, 384); break; }
            uint4 vx[4];
            sts32_if(l16, sb + O_MISC + 16 + 4 * c, __reduce_max_sync(~0u, mmax));
            if (c == 0) STAMP(s, 5);
            {
                bar_sync(6, 128);
                const uint4 mm = lds128(sb + O_MISC + 16), cf = lds128(sb + O_MISC);
                const float bound = fmaxf(__uint_as_float(cf.z), __uint_as_float(cf.y) * (__uint_as_float(max(max(mm.x, mm.y), max(mm.z, mm.w))) * __uint_as_float(cf.x)));
                const uint32_t ebits = __reduce_max_sync(~0u, min(max(__float_as_uint(bound) & 0x7f800000u, 21u << 23), 254u << 23));
                mbar_wait(sb + B_X + 8 * s3n, ((s + 1) / 3) & 1);
                s3n = (s3n == 2) ? 0 : s3n + 1;
                bar_sync(3, 384);
                if (r < 2) mbar_wait(sb + B_VX + 8 * (s & 1), (s >> 1) & 1);
                vx[0] = lds128(vxa); vx[2] = lds128(vxa + 1024);
                if (c == 0) STAMP(s, 13);
                mbar_wait(sb + B_SC, s & 1);
                if (c == 0) STAMP(s, 6);
                float p[10];
                load_scores(p, sb + O_SC, 1280, l16);
                float mx = fmaxf(fmaxf(fmaxf(p[0], p[1]), fmaxf(p[2], p[3])), fmaxf(fmaxf(p[4], p[5]), fmaxf(p[6], p[7])));
                mx = quad_max(fmaxf(mx, fmaxf(p[8], p[9])));
                const uint4 vm = lds64x2(sb + O_VM + c * 512 + (l16 >> 1));
                vx[1] = lds128(vxa + 512); vx[3] = lds128(vxa + 1536);
                bar_arrive(4, 384);
                const float sc = __uint_as_float(lds32(sb + O_MISC + 12));
                const float mo = mx * SM_SCALE;
                uint32_t P[5];
#pragma unroll
                for (int n = 0; n < 5; n++) P[n] = pack_bf16(ex2(fmaf(p[2 * n], SM_SCALE, -mo)), ex2(fmaf(p[2 * n + 1], n == 3 ? sc : SM_SCALE, -mo)));
                if (c == 0) STAMP(s, 7);
                float o0[4], o1[4], sm[4];
                mma16816_z(sm, ONES, ONES, ONES, ONES, P[1], P[2]);
                mma16816_z(o0, vx[0].x, vx[0].y, vx[0].z, vx[0].w, P[1], P[2]);
                mma16816_z(o1, vx[2].x, vx[2].y, vx[2].z, vx[2].w, P[1], P[2]);
                mma16816(sm, ONES, ONES, ONES, ONES, P[3], P[4]);
                mma16816(o0, vx[1].x, vx[1].y, vx[1].z, vx[1].w, P[3], P[4]);
                mma16816(o1, vx[3].x, vx[3].y, vx[3].z, vx[3].w, P[3], P[4]);
                mma1688(sm, ONES, ONES, P[0]);
                mma1688(o0, vm.x, vm.y, P[0]);
                mma1688(o1, vm.z, vm.w, P[0]);
                const float sig = __uint_as_float((268u << 23) - ebits);
                const float r0 = rcp_fast(sm[0]) * sig, r1 = rcp_fast(sm[1]) * sig;
                stsm4t(sb + O_OF + c * 512 + l16, pack_bf16(o0[0] * r0, o0[1] * r1), pack_bf16(o0[2] * r0, o0[3] * r1),
                       pack_bf16(o1[0] * r0, o1[1] * r1), pack_bf16(o1[2] * r0, o1[3] * r1));
                bar_sync(6, 128);
                uint4 ob[4];
#pragma unroll
                for (int q = 0; q < 4; q++) ob[q] = ldsm4(sb + O_OF + q * 512 + l16);
                { const uint4 v = lds128(sb + O_WP + c * 512 + l16); a[92] = v.x; a[93] = v.y; a[94] = v.z; a[95] = v.w; }
                float m0[3][4], m1[3][4];
#pragma unroll
                for (int q = 0; q < 4; q++) {
#pragma unroll
                    for (int i = 0; i < 3; i++) {
                        const int k0 = (i * 8 + 2 * q) * 4;
                        if (q == 0) mma16816_z(m0[i], a[k0], a[k0 + 1], a[k0 + 2], a[k0 + 3], ob[q].x, ob[q].y);
                        else mma16816(m0[i], a[k0], a[k0 + 1], a[k0 + 2], a[k0 + 3], ob[q].x, ob[q].y);
                    }
#pragma unroll
                    for (int i = 0; i < 3; i++) {
                        const int k1 = (i * 8 + 2 * q + 1) * 4;
                        if (q == 0) mma16816_z(m1[i], a[k1], a[k1 + 1], a[k1 + 2], a[k1 + 3], ob[q].z, ob[q].w);
                        else mma16816(m1[i], a[k1], a[k1 + 1], a[k1 + 2], a[k1 + 3], ob[q].z, ob[q].w);
                    }
                }
                asm volatile("red.relaxed.gpu.global.add.noftz.v4.f16x2 [%0], {%1,%2,%3,%4};" :: "l"(reinterpret_cast<char*>(g_acc) + roff),
                    "r"(pack_f16(m0[0][0] + m1[0][0], m0[0][2] + m1[0][2])), "r"(pack_f16(m0[1][0] + m1[1][0], m0[1][2] + m1[1][2])),
                    "r"(pack_f16(m0[2][0] + m1[2][0], m0[2][2] + m1[2][2])), "r"(0x3c00u) : "memory");
                asm volatile("red.relaxed.gpu.global.add.noftz.v4.f16x2 [%0], {%1,%2,%3,%4};" :: "l"(reinterpret_cast<char*>(g_acc) + roff + 1024),
                    "r"(pack_f16(m0[0][1] + m1[0][1], m0[0][3] + m1[0][3])), "r"(pack_f16(m0[1][1] + m1[1][1], m0[1][3] + m1[1][3])),
                    "r"(pack_f16(m0[2][1] + m1[2][1], m0[2][3] + m1[2][3])), "r"(0x3c00u) : "memory");
                const unsigned t_red = clk();
                bar_arrive(5, 256);
                bar_arrive(13, 256);
                mbar_expect_if(l16 | c, sb + B_SC, 4608);
                mbar_expect_if(l16 | (c ^ 1) | (r >> 1), sb + B_VX + 8 * ((s + 1) & 1), 8192);
                sts32_if(l16 | (c ^ 3), sb + O_MISC, ebits - (14u << 23));
                if (c == 0) STAMPV(s, 8, t_red);
                if (ACC_PF && c == 2 && s + 4 < NSEG - 1)
                    asm volatile("prefetch.global.L2 [%0];" :: "l"(reinterpret_cast<const char*>(g_acc) + ((s + 4) * 96 + blockIdx.x) * 256 + (l16 & 96)) : "memory");
                const char* pbase = reinterpret_cast<const char*>(g_acc) + (s * 24576 + c * 2048) + ((l16 & 64) * 16 + (l16 & 256) + ((l16 & 128) >> 1) + (l16 & 48));
                spin_until(t_red, D_WAIT);
                uint4 v[6];
#pragma unroll
                for (int i = 0; i < 6; i++) v[i] = ldg_relaxed128(pbase + (i >> 1) * 8192 + (i & 1) * 512);
                int nretry = 0;
                auto convert = [&](int tau) {
                    uint4& A = v[2 * tau]; uint4& B = v[2 * tau + 1];
                    A.x = f16x2_to_bf16x2(A.x); B.x = f16x2_to_bf16x2(B.x); A.y = f16x2_to_bf16x2(A.y); B.y = f16x2_to_bf16x2(B.y);
                    A.z = f16x2_to_bf16x2(A.z); B.z = f16x2_to_bf16x2(B.z);
                    sts128(sb + O_MF + tau * 3072 + c * 512 + l16, A.x, B.x, A.y, B.y);
                    sts64(sb + O_MF + tau * 3072 + 2048 + (c >> 1) * 512 + (c & 1) * 8 + l16, A.z, B.z);
                };
                const uint32_t ok0 = __all_sync(~0u, (v[0].w & v[1].w) == 0x5000u);
                convert(0);
                asm volatile("{\n.reg .pred p;\nsetp.ne.u32 p, %0, 0;\n@p bar.arrive 2, 384;\n}" :: "r"(ok0) : "memory");
                sched_fence<0>(h);
                uint32_t ok1;
                asm volatile("{\n.reg .pred p, q;\n.reg .b32 x;\nlop3.b32 x, %1, %2, %3, 0x80;\nand.b32 x, x, %4;\n"
                             "setp.eq.u32 p, x, 0x5000;\nvote.sync.all.pred q, p, 0xffffffff;\nselp.u32 %0, 1, 0, q;\n}"
                             : "=r"(ok1) : "r"(v[2].w), "r"(v[3].w), "r"(v[4].w), "r"(v[5].w));
                convert(1); convert(2);
                asm volatile("{\n.reg .pred p;\nsetp.ne.u32 p, %0, 0;\n@p bar.arrive 15, 384;\n}" :: "r"(ok1) : "memory");
                if (!(ok0 & ok1)) {
                    asm volatile("{\n.reg .pred p, q;\n.reg .u32 n, x;\nmov.u32 n, 0;\n"
                         "R_%=: ld.relaxed.gpu.global.v4.u32 {%0,%1,%2,%3}, [%25];\nld.relaxed.gpu.global.v4.u32 {%4,%5,%6,%7}, [%25+512];\n"
                         "ld.relaxed.gpu.global.v4.u32 {%8,%9,%10,%11}, [%25+8192];\nld.relaxed.gpu.global.v4.u32 {%12,%13,%14,%15}, [%25+8704];\n"
                         "ld.relaxed.gpu.global.v4.u32 {%16,%17,%18,%19}, [%25+16384];\nld.relaxed.gpu.global.v4.u32 {%20,%21,%22,%23}, [%25+16896];\n"
                         "add.u32 %24, %24, 1;\nand.b32 x, %3, %7;\nand.b32 x, x, %11;\nand.b32 x, x, %15;\nand.b32 x, x, %19;\nand.b32 x, x, %23;\n"
                         "setp.eq.u32 p, x, 0x5000;\nvote.sync.all.pred q, p, 0xffffffff;\n@q bra.uni K_%=;\n"
                         "add.u32 n, n, 1;\nsetp.lt.u32 q, n, 2000000;\n@q bra.uni R_%=;\ntrap;\nK_%=:\n}"
                         : "+r"(v[0].x), "+r"(v[0].y), "+r"(v[0].z), "+r"(v[0].w), "+r"(v[1].x), "+r"(v[1].y), "+r"(v[1].z), "+r"(v[1].w),
                           "+r"(v[2].x), "+r"(v[2].y), "+r"(v[2].z), "+r"(v[2].w), "+r"(v[3].x), "+r"(v[3].y), "+r"(v[3].z), "+r"(v[3].w),
                           "+r"(v[4].x), "+r"(v[4].y), "+r"(v[4].z), "+r"(v[4].w), "+r"(v[5].x), "+r"(v[5].y), "+r"(v[5].z), "+r"(v[5].w), "+r"(nretry)
                         : "l"(pbase) : "memory");
                    convert(0); convert(1); convert(2);
                    if (!ok0) bar_arrive(2, 384);
                    if (!ok1) bar_arrive(15, 384);
                }
                if (c == 0) STAMP(s, 12);
                if (c == 0) STAMPV(s, 14, nretry);
                mmax = absmax2(absmax2(absmax2(v[0].x, v[0].y), absmax2(v[0].z, v[1].x)), absmax2(absmax2(v[1].y, v[1].z), absmax2(v[2].x, v[2].y)));
                mmax = absmax2(mmax, absmax2(absmax2(absmax2(v[2].z, v[3].x), absmax2(v[3].y, v[3].z)), absmax2(absmax2(v[4].x, v[4].y), absmax2(v[4].z, v[5].x))));
                mmax = absmax2(mmax, absmax2(v[5].y, v[5].z)) & 0x7fff7fffu;
                mmax = max(mmax << 16, mmax & 0xffff0000u);
            }
            roff += 24576;
        }
        {
            bar_sync(7, 384);
            if (c == 0)
                asm volatile("{\n.reg .pred p;\nsetp.eq.u32 p, %1, 0;\n@p red.release.gpu.global.inc.u32 [%0], 0xffffffff;\n}"
                             :: "l"(&g_flag[F_QKV + (60 + (h >> 3)) * 8]), "r"(l16c) : "memory");
        }
    }
    if (warp == 8) PSTAMP(13);
    cluster_sync();
}

constexpr int NST = 10;
constexpr int G_RING = 0, G_EX = NST * 16384, G_OUT = G_EX + 32768, G_CARRY = G_OUT + 32768, G_BAR = G_CARRY + 512, BG_SMEM = G_BAR + 256;
constexpr int GB_FULL = G_BAR, GB_EMPTY = G_BAR + 8 * NST, GB_W = G_BAR + 16 * NST;
static_assert(BG_SMEM <= 232448, "smem");

template <int ACC>
__device__ __forceinline__ void wgmma_n128_rs(float (&d)[64], uint32_t a0, uint32_t a1, uint32_t a2, uint32_t a3, uint64_t desc) {
    asm volatile("wgmma.mma_async.sync.aligned.m64n128k16.f32.bf16.bf16 "
        "{%0,%1,%2,%3,%4,%5,%6,%7,%8,%9,%10,%11,%12,%13,%14,%15,%16,%17,%18,%19,%20,%21,%22,%23,%24,%25,%26,%27,%28,%29,%30,%31,"
        "%32,%33,%34,%35,%36,%37,%38,%39,%40,%41,%42,%43,%44,%45,%46,%47,%48,%49,%50,%51,%52,%53,%54,%55,%56,%57,%58,%59,%60,%61,%62,%63}, "
        "{%64,%65,%66,%67}, %68, %69, 1, 1, 0;"
        : "+f"(d[0]), "+f"(d[1]), "+f"(d[2]), "+f"(d[3]), "+f"(d[4]), "+f"(d[5]), "+f"(d[6]), "+f"(d[7]),
          "+f"(d[8]), "+f"(d[9]), "+f"(d[10]), "+f"(d[11]), "+f"(d[12]), "+f"(d[13]), "+f"(d[14]), "+f"(d[15]),
          "+f"(d[16]), "+f"(d[17]), "+f"(d[18]), "+f"(d[19]), "+f"(d[20]), "+f"(d[21]), "+f"(d[22]), "+f"(d[23]),
          "+f"(d[24]), "+f"(d[25]), "+f"(d[26]), "+f"(d[27]), "+f"(d[28]), "+f"(d[29]), "+f"(d[30]), "+f"(d[31]),
          "+f"(d[32]), "+f"(d[33]), "+f"(d[34]), "+f"(d[35]), "+f"(d[36]), "+f"(d[37]), "+f"(d[38]), "+f"(d[39]),
          "+f"(d[40]), "+f"(d[41]), "+f"(d[42]), "+f"(d[43]), "+f"(d[44]), "+f"(d[45]), "+f"(d[46]), "+f"(d[47]),
          "+f"(d[48]), "+f"(d[49]), "+f"(d[50]), "+f"(d[51]), "+f"(d[52]), "+f"(d[53]), "+f"(d[54]), "+f"(d[55]),
          "+f"(d[56]), "+f"(d[57]), "+f"(d[58]), "+f"(d[59]), "+f"(d[60]), "+f"(d[61]), "+f"(d[62]), "+f"(d[63])
        : "r"(a0), "r"(a1), "r"(a2), "r"(a3), "l"(desc), "n"(ACC));
}
__device__ __forceinline__ void wait_flag(const unsigned* p, unsigned target) {
    asm volatile("{\n.reg .pred p;\n.reg .u32 n, v;\nmov.u32 n, 0;\n"
                 "W_%=: ld.acquire.gpu.global.u32 v, [%0];\nsub.u32 v, v, %1;\nsetp.ge.s32 p, v, 0;\n@p bra.uni D_%=;\nnanosleep.u32 100;\n"
                 "add.u32 n, n, 1;\nsetp.lt.u32 p, n, 4000000;\n@p bra.uni W_%=;\ntrap;\nD_%=:\n}" :: "l"(p), "r"(target) : "memory");
}
__device__ __forceinline__ void flag_inc_if(uint32_t z, unsigned* p) {
    asm volatile("{\n.reg .pred p;\nsetp.eq.u32 p, %1, 0;\n@p red.release.gpu.global.inc.u32 [%0], 0xffffffff;\n}" :: "l"(p), "r"(z) : "memory");
}
template <int NS, int STRIDE>
__device__ __forceinline__ void bg_mainloop(float (&d)[64], const uint32_t (&a)[144], uint32_t sb, int it, int lane) {
    int slot = it % NST, ph = (it / NST) & 1, prev = 0;
#pragma unroll
    for (int i = 0; i < NS; i++) {
        mbar_wait(sb + GB_FULL + 8 * slot, ph);
        const uint64_t desc = (uint64_t)(((sb + G_RING + slot * 16384) & 0x3FFFF) >> 4) | (1ull << 16) | (64ull << 32) | (1ull << 62);
        wg_fence();
#pragma unroll
        for (int k = 0; k < 4; k++) {
            const int u = 16 * i + 4 * k;
            if (i == 0 && k == 0) wgmma_n128_rs<0>(d, a[u], a[u + 1], a[u + 2], a[u + 3], desc);
            else wgmma_n128_rs<1>(d, a[u], a[u + 1], a[u + 2], a[u + 3], desc + 2 * k);
        }
        wg_commit();
        if (i > 0) {
            asm volatile("wgmma.wait_group.sync.aligned 1;" ::: "memory");
            mbar_arrive_if(lane, sb + GB_EMPTY + 8 * prev);
        }
        prev = slot;
        slot += STRIDE;
        if (slot >= NST) { slot -= NST; ph ^= 1; }
    }
    wg_wait0();
    mbar_arrive_if(lane, sb + GB_EMPTY + 8 * prev);
}
template <bool SKIP>
__device__ __forceinline__ void bg_epilogue(float (&d)[64], uint32_t sb, int wg, int w, int lane, const CUtensorMap* tm_out, int col0, int tok0,
                                            const __nv_bfloat16* xa, const __nv_bfloat16* Dk) {
    const int g = lane >> 2, t = lane & 3;
    const uint32_t ex = sb + G_EX + w * 4096 + lane * 16;
    float k[32];
    if (wg == 0) {
#pragma unroll
        for (int q = 0; q < 8; q++) sts128f(ex + q * 512, d[32 + 4 * q], d[32 + 4 * q + 1], d[32 + 4 * q + 2], d[32 + 4 * q + 3]);
#pragma unroll
        for (int i = 0; i < 32; i++) k[i] = d[i];
    } else {
#pragma unroll
        for (int q = 0; q < 8; q++) sts128f(ex + 16384 + q * 512, d[4 * q], d[4 * q + 1], d[4 * q + 2], d[4 * q + 3]);
#pragma unroll
        for (int i = 0; i < 32; i++) k[i] = d[32 + i];
    }
    uint32_t xv[16], dv = 0;
    if (SKIP) {
        const __nv_bfloat16* xp = xa + (size_t)(tok0 + 64 * wg + 2 * t) * DM + col0 + 16 * w + 2 * g;
#pragma unroll
        for (int i = 0; i < 16; i++) xv[i] = ldg_nc32(xp + (8 * (i >> 1) + (i & 1)) * DM);
        dv = ldg_nc32(Dk + col0 + 16 * w + 2 * g);
    }
    if (SKIP && w == 0) asm volatile("cp.async.bulk.wait_group.read 0;" ::: "memory");
    bar_sync(1, 256);
#pragma unroll
    for (int q = 0; q < 8; q++) {
        const float4 o = lds128f(ex + (wg ^ 1) * 16384 + q * 512);
        k[4 * q] += o.x; k[4 * q + 1] += o.y; k[4 * q + 2] += o.z; k[4 * q + 3] += o.w;
    }
    if (SKIP) bar_sync(1, 256); else bar_sync(13, 288);
    const uint32_t ob = sb + G_OUT + wg * 16384 + (w >> 1) * 8192 + (g & 1) * 8;
    const uint32_t ch = (w & 1) * 4 + (g >> 1);
#pragma unroll
    for (int i = 0; i < 16; i++) {
        float v0 = k[4 * (i >> 1) + (i & 1)], v1 = k[4 * (i >> 1) + 2 + (i & 1)];
        if (SKIP) {
            const uint32_t p = pack_bf16(__uint_as_float(xv[i] << 16) * __uint_as_float(dv << 16), __uint_as_float(xv[i] & 0xffff0000u) * __uint_as_float(dv & 0xffff0000u));
            v0 += __uint_as_float(p << 16); v1 += __uint_as_float(p & 0xffff0000u);
        }
        const uint32_t n7 = 2 * t + (i & 1);
        sts64(ob + (8 * (i >> 1) + n7) * 128 + ((ch ^ n7) << 4), __float_as_uint(v0), __float_as_uint(v1));
    }
    fence_async_smem();
    if (SKIP) {
        bar_sync(4 + wg, 128);
        if (w == 0)
            asm volatile("{\n.reg .pred p;\nelect.sync _|p, 0xffffffff;\n"
                "@p cp.async.bulk.tensor.2d.global.shared::cta.bulk_group [%0, {%2, %4}], [%1];\n"
                "@p cp.async.bulk.tensor.2d.global.shared::cta.bulk_group [%0, {%3, %4}], [%1+8192];\n@p cp.async.bulk.commit_group;\n}"
                :: "l"(tm_out), "r"(sb + G_OUT + wg * 16384), "r"(col0), "r"(col0 + 32), "r"(tok0 + 64 * wg) : "memory");
    } else {
        bar_arrive(12, 288);
    }
}
__device__ __forceinline__ void s5_channel(int p, const __nv_bfloat16* Lre, const __nv_bfloat16* Lim, const __nv_bfloat16* logdt, float2& lam, float2& coef) {
    const float dt = __bfloat162float(__float2bfloat16(expf(__bfloat162float(logdt[p]))));
    const float lr = __bfloat162float(Lre[p]), li = __bfloat162float(Lim[p]);
    const float e = expf(dt * lr);
    float sn, cs;
    sincosf(dt * li, &sn, &cs);
    lam = make_float2(e * cs, e * sn);
    const float den = lr * lr + li * li;
    coef = make_float2(((lam.x - 1.f) * lr + lam.y * li) / den, (lam.y * lr - (lam.x - 1.f) * li) / den);
}
__device__ __forceinline__ float2 cfma(float2 a, float2 b, float2 c) {
    return make_float2(fmaf(a.x, b.x, fmaf(-a.y, b.y, c.x)), fmaf(a.x, b.y, fmaf(a.y, b.x, c.y)));
}
__device__ __forceinline__ uint4 ldg128(const void* p) { uint4 v; asm volatile("ld.global.v4.u32 {%0,%1,%2,%3}, [%4];" : "=r"(v.x), "=r"(v.y), "=r"(v.z), "=r"(v.w) : "l"(p) : "memory"); return v; }
__device__ __forceinline__ uint2 ldg64(const void* p) { uint2 v; asm volatile("ld.global.v2.u32 {%0,%1}, [%2];" : "=r"(v.x), "=r"(v.y) : "l"(p) : "memory"); return v; }

__device__ __forceinline__ void bg_attention(uint32_t st0, uint32_t st1, int mt, int lane) {
    const int g = lane >> 2, t = lane & 3;
    float sc[5][4];
#pragma unroll
    for (int n = 0; n < 5; n++) sc[n][0] = sc[n][1] = sc[n][2] = sc[n][3] = 0.f;
    float sm2[4] = {0.f, 0.f, 0.f, 0.f};
#pragma unroll
    for (int i = 0; i < 8; i++) {
        const uint32_t st = (i >> 2 ? st1 : st0) + (i & 3) * 512 + lane * 16;
        const uint4 q = ldsm4(st + mt * 2048), km = ldsm4(st + 8192), k0 = ldsm4(st + 4096);
        mma16816(sc[0], q.x, q.y, q.z, q.w, km.x, km.y);
        mma16816(sm2, q.x, q.y, q.z, q.w, km.z, km.w);
        mma16816(sc[1], q.x, q.y, q.z, q.w, k0.x, k0.y);
        mma16816(sc[2], q.x, q.y, q.z, q.w, k0.z, k0.w);
        if (mt) {
            const uint4 k1 = ldsm4(st + 6144);
            mma16816(sc[3], q.x, q.y, q.z, q.w, k1.x, k1.y);
            mma16816(sc[4], q.x, q.y, q.z, q.w, k1.z, k1.w);
        }
    }
#pragma unroll
    for (int i = 0; i < 4; i++) sc[0][i] += sm2[i];
    const int q0 = 16 * mt + 8 + g - 2 * t;
#pragma unroll
    for (int n = 1; n < 5; n++) {
        if (8 * n > q0) sc[n][0] = -INFINITY;
        if (8 * n + 1 > q0) sc[n][1] = -INFINITY;
        if (8 * n > q0 + 8) sc[n][2] = -INFINITY;
        if (8 * n + 1 > q0 + 8) sc[n][3] = -INFINITY;
    }
    float ma = fmaxf(sc[0][0], sc[0][1]), mb = fmaxf(sc[0][2], sc[0][3]);
#pragma unroll
    for (int n = 1; n < 5; n++) { ma = fmaxf(ma, fmaxf(sc[n][0], sc[n][1])); mb = fmaxf(mb, fmaxf(sc[n][2], sc[n][3])); }
    ma = quad_max(ma) * SM_SCALE; mb = quad_max(mb) * SM_SCALE;
    uint32_t Pa[5], Pb[5];
#pragma unroll
    for (int n = 0; n < 5; n++) {
        Pa[n] = pack_bf16(ex2(fmaf(sc[n][0], SM_SCALE, -ma)), ex2(fmaf(sc[n][1], SM_SCALE, -ma)));
        Pb[n] = pack_bf16(ex2(fmaf(sc[n][2], SM_SCALE, -mb)), ex2(fmaf(sc[n][3], SM_SCALE, -mb)));
    }
    float sa[4], sbb[4];
    mma1688_z(sa, ONES, ONES, Pa[0]); mma1688_z(sbb, ONES, ONES, Pb[0]);
    mma16816(sa, ONES, ONES, ONES, ONES, Pa[1], Pa[2]); mma16816(sbb, ONES, ONES, ONES, ONES, Pb[1], Pb[2]);
    mma16816(sa, ONES, ONES, ONES, ONES, Pa[3], Pa[4]); mma16816(sbb, ONES, ONES, ONES, ONES, Pb[3], Pb[4]);
    const float ra0 = rcp_fast(sa[0]), ra1 = rcp_fast(sa[1]), rb0 = rcp_fast(sbb[0]), rb1 = rcp_fast(sbb[1]);
    const uint32_t row = lane & 7;
    const uint32_t so = mt * 2048 + (lane >> 4) * 1024 + row * 128;
#pragma unroll
    for (int i = 0; i < 8; i++) {
        const uint32_t st = i >> 2 ? st1 : st0;
        const int e4 = i & 3;
        const float2 vmf = lds64f(st + 14336 + e4 * 256 + lane * 8);
        const uint32_t vm0 = __float_as_uint(vmf.x), vm1 = __float_as_uint(vmf.y);
        const uint4 v0 = lds128(st + 10240 + e4 * 1024 + lane * 16);
        float oa[4], ob[4];
        mma1688_z(oa, vm0, vm1, Pa[0]); mma1688_z(ob, vm0, vm1, Pb[0]);
        mma16816(oa, v0.x, v0.y, v0.z, v0.w, Pa[1], Pa[2]);
        mma16816(ob, v0.x, v0.y, v0.z, v0.w, Pb[1], Pb[2]);
        if (mt) {
            const uint4 v1 = lds128(st + 10240 + e4 * 1024 + 512 + lane * 16);
            mma16816(oa, v1.x, v1.y, v1.z, v1.w, Pa[3], Pa[4]);
            mma16816(ob, v1.x, v1.y, v1.z, v1.w, Pb[3], Pb[4]);
        }
        stsm4t(st + so + (((2 * e4 + ((lane >> 3) & 1)) ^ row) << 4), pack_bf16(oa[0] * ra0, oa[1] * ra1), pack_bf16(oa[2] * ra0, oa[3] * ra1),
               pack_bf16(ob[0] * rb0, ob[1] * rb1), pack_bf16(ob[2] * rb0, ob[3] * rb1));
    }
}
__device__ __forceinline__ bool bg_att_turn(int na, int ng) { return na == ng || (na == ng + 1 && na <= BG_AHEAD); }

__global__ void __launch_bounds__(384, 1)
bg_kernel(const __grid_constant__ CUtensorMap tm_xa, const __grid_constant__ CUtensorMap tm_wo, const __grid_constant__ CUtensorMap tm_out,
          const __nv_bfloat16* __restrict__ xa, const __nv_bfloat16* __restrict__ Lre, const __nv_bfloat16* __restrict__ Lim,
          const __nv_bfloat16* __restrict__ Bre, const __nv_bfloat16* __restrict__ Bim, const __nv_bfloat16* __restrict__ Cre,
          const __nv_bfloat16* __restrict__ Cim, const __nv_bfloat16* __restrict__ logdt, const __nv_bfloat16* __restrict__ Dk) {
    extern __shared__ __align__(1024) uint8_t smem_raw[];
    const uint32_t sb = smem_u32(smem_raw);
    const int lane = threadIdx.x & 31;
    const int warp = __shfl_sync(~0u, threadIdx.x >> 5, 0);
    const int wg = warp >> 2, w = warp & 3, b = blockIdx.x;
    const int nt = b % 9, kq = b / 9;
    BSTAMP(0);
    if (threadIdx.x == 0) {
        if (sb & 1023u) __trap();
        for (int i = 0; i < NST; i++) { mbar_init(sb + GB_FULL + 8 * i, 1); mbar_init(sb + GB_EMPTY + 8 * i, 4); }
        mbar_init(sb + GB_W, 1);
        asm volatile("fence.mbarrier_init.release.cluster;" ::: "memory");
        mbar_expect(sb + GB_W, (b < 18 ? 64 : 128) * 1152);
        sts32(sb + G_BAR + 248, atomicAdd(&g_ticket_bg, 1u) / 36u + 1u);
    }
    __syncthreads();
    if (wg == 2) {
        asm volatile("setmaxnreg.dec.sync.aligned.u32 24;");
        if (w == 0) {
            int slot = 0, ph = 1;
            unsigned tlast = clk();
            auto pace = [&]() { if (BG_PACE) { spin_until(tlast, BG_PACE); tlast = clk(); } };
            auto next = [&]() { if (++slot == NST) { slot = 0; ph ^= 1; } };
            bar_sync(6, 288);
            if (b < 18) {
#pragma unroll 1
                for (int i = 0; i < 144; i++) {
                    const int blk = i / 9, kb = i - 9 * blk, it = (blk >> 1) * 18 + (blk & 1) + 2 * kb;
                    slot = it % NST;
                    mbar_wait(sb + GB_EMPTY + 8 * slot, ((it / NST) & 1) ^ 1);
                    pace();
                    asm volatile("{\n.reg .pred p;\nelect.sync _|p, 0xffffffff;\n@p mbarrier.arrive.expect_tx.shared::cta.b64 _, [%2], 16384;\n"
                        "@p cp.async.bulk.tensor.5d.shared::cluster.global.mbarrier::complete_tx::bytes [%0], [%1, {%3, %4, %4, %4, %5}], [%2];\n}"
                        :: "r"(sb + G_RING + slot * 16384), "l"(&tm_xa), "r"(sb + GB_FULL + 8 * slot), "r"(kb * 64), "r"(0), "r"(blk) : "memory");
                }
                slot = 144 % NST; ph = ((144 / NST) & 1) ^ 1;
            }
            const unsigned ep = lds32(sb + G_BAR + 248);
            auto slabs = [&](const char* src, int ns) {
                asm volatile("fence.proxy.async.global;" ::: "memory");
#pragma unroll 1
                for (int i = 0; i < ns; i++) {
                    mbar_wait(sb + GB_EMPTY + 8 * slot, ph);
                    pace();
                    asm volatile("{\n.reg .pred p;\nelect.sync _|p, 0xffffffff;\n@p mbarrier.arrive.expect_tx.shared::cta.b64 _, [%2], 16384;\n"
                        "@p cp.async.bulk.shared::cluster.global.mbarrier::complete_tx::bytes [%0], [%1], 16384, [%2];\n}"
                        :: "r"(sb + G_RING + slot * 16384), "l"(src + (size_t)((i & 1) * (ns >> 1) + (i >> 1)) * (SEQ * 128)), "r"(sb + GB_FULL + 8 * slot) : "memory");
                    next();
                }
            };
            if (b >= 18) {
#pragma unroll 1
                for (int blk = kq - 2; blk < 16; blk += 2) {
                    wait_flag(&g_flag[F_H + blk * 8], 18 * ep);
                    slabs(reinterpret_cast<const char*>(g_h) + blk * 16384, 18);
                }
            }
            bar_sync(6, 288);
#pragma unroll 1
            for (int na = 0, ng = 0; ng < 16;) {
                if (bg_att_turn(na, ng)) {
                    if (nt < 8) {
                        wait_flag(&g_flag[F_QKV + (na * 4 + kq) * 8], 24 * ep);
                        asm volatile("fence.proxy.async.global;" ::: "memory");
#pragma unroll 1
                        for (int i = 0; i < 8; i++) {
                            const int pr = nt * 4 + 2 * (i & 1) + (i >> 2), hf = (i >> 1) & 1;
                            const char* rec = reinterpret_cast<const char*>(g_qkv) + (size_t)((4 * na + (pr >> 3)) * NH + 8 * kq + (pr & 7)) * REC;
                            mbar_wait(sb + GB_EMPTY + 8 * slot, ph);
                    pace();
                            asm volatile("{\n.reg .pred p;\nelect.sync _|p, 0xffffffff;\n@p mbarrier.arrive.expect_tx.shared::cta.b64 _, [%4], 15360;\n"
                                "@p cp.async.bulk.shared::cluster.global.mbarrier::complete_tx::bytes [%0], [%1], 10240, [%4];\n"
                                "@p cp.async.bulk.shared::cluster.global.mbarrier::complete_tx::bytes [%0+10240], [%2], 4096, [%4];\n"
                                "@p cp.async.bulk.shared::cluster.global.mbarrier::complete_tx::bytes [%0+14336], [%3], 1024, [%4];\n}"
                                :: "r"(sb + G_RING + slot * 16384), "l"(rec + hf * 10240), "l"(rec + 20480 + hf * 4096), "l"(rec + 28672 + hf * 1024),
                                   "r"(sb + GB_FULL + 8 * slot) : "memory");
                            next();
                        }
                    }
                    na++;
                } else {
                    wait_flag(&g_flag[F_OX + (ng * 4 + kq) * 8], 8 * ep);
                    slabs(reinterpret_cast<const char*>(g_ox) + (size_t)kq * 16 * SEQ * 128 + ng * 16384, 16);
                    ng++;
                }
            }
        } else if (w == 1) {
            if (b < 18) {
#pragma unroll 1
                for (int blk = 0; blk < 16; blk++) {
                    bar_sync(8 + (blk & 1), 160);
                    asm volatile("{\n.reg .pred p;\nelect.sync _|p, 0xffffffff;\n@p cp.async.bulk.global.shared::cta.bulk_group [%0], [%1], 16384;\n"
                        "@p cp.async.bulk.commit_group;\ncp.async.bulk.wait_group 0;\nfence.proxy.async.global;\n}"
                        :: "l"(reinterpret_cast<char*>(g_h) + ((size_t)b * SEQ + blk * 128) * 128), "r"(sb + G_OUT + (blk & 1) * 16384) : "memory");
                    bar_arrive(10 + (blk & 1), 160);
                    flag_inc_if(lane, &g_flag[F_H + blk * 8]);
                }
            }
            if (nt < 8) {
                int it = 144;
#pragma unroll 1
                for (int na = 0, ng = 0; ng < 16;) {
                    if (bg_att_turn(na, ng)) {
                        bar_sync(7, 288);
                        if (lane < 8) {
                            const int pr = nt * 4 + 2 * (lane & 1) + (lane >> 2), hf = (lane >> 1) & 1;
                            asm volatile("cp.async.bulk.global.shared::cta.bulk_group [%0], [%1], 4096;\ncp.async.bulk.commit_group;\ncp.async.bulk.wait_group.read 0;\n"
                                "mbarrier.arrive.shared::cta.b64 _, [%2], 4;\ncp.async.bulk.wait_group 0;\nfence.proxy.async.global;"
                                :: "l"(reinterpret_cast<char*>(g_ox) + ((size_t)((8 * kq + (pr & 7)) * 2 + hf) * SEQ + (4 * na + (pr >> 3)) * 32) * 128),
                                   "r"(sb + G_RING + ((it + lane) % NST) * 16384), "r"(sb + GB_EMPTY + 8 * ((it + lane) % NST)) : "memory");
                        }
                        __syncwarp();
                        flag_inc_if(lane, &g_flag[F_OX + (na * 4 + kq) * 8]);
                        it += 8; na++;
                    } else { it += 16; ng++; }
                }
            }
        } else if (w == 2) {
            const unsigned ep = lds32(sb + G_BAR + 248);
#pragma unroll 1
            for (int blk = 0; blk < 16; blk++) {
                bar_arrive(13, 288);
                bar_sync(12, 288);
                if (kq) { wait_flag(&g_flag[F_OUT + (blk * 9 + nt) * 8], ep); asm volatile("fence.proxy.async.global;" ::: "memory"); }
                unsigned t0 = clk();
                if (blk < 15) spin_until(t0, b * (RED_GAP / 36));
#pragma unroll 1
                for (int i = 0; i < 4; i++) {
                    const uint32_t src = sb + G_OUT + i * 8192;
                    const int c0 = DM + 64 * nt + (i & 1) * 32, c1 = blk * 128 + (i >> 1) * 64;
                    if (kq) {
                        asm volatile("{\n.reg .pred p;\nelect.sync _|p, 0xffffffff;\n@p cp.reduce.async.bulk.tensor.2d.global.shared::cta.add.bulk_group [%0, {%2, %3}], [%1];\n}"
                            :: "l"(&tm_out), "r"(src), "r"(c0), "r"(c1) : "memory");
                        t0 = clk();
                        if (blk < 15 && i < 3) spin_until(t0, RED_GAP);
                    } else {
                        asm volatile("{\n.reg .pred p;\nelect.sync _|p, 0xffffffff;\n@p cp.async.bulk.tensor.2d.global.shared::cta.bulk_group [%0, {%2, %3}], [%1];\n}"
                            :: "l"(&tm_out), "r"(src), "r"(c0), "r"(c1) : "memory");
                    }
                }
                asm volatile("cp.async.bulk.commit_group;\ncp.async.bulk.wait_group 0;\nfence.proxy.async.global;" ::: "memory");
                __syncwarp();
                if (!kq) flag_inc_if(lane, &g_flag[F_OUT + (blk * 9 + nt) * 8]);
            }
        }
    } else {
        asm volatile("setmaxnreg.inc.sync.aligned.u32 240;");
        const int g = lane >> 2, t = lane & 3, tid = threadIdx.x;
        uint32_t a[144];
        float d[64];
        if (b < 18) {
            if (tid < 64)
                asm volatile("cp.async.bulk.shared::cluster.global.mbarrier::complete_tx::bytes [%0], [%1], 1152, [%2];"
                    :: "r"(sb + tid * 1168), "l"((tid < 32 ? Bre : Bim) + (size_t)(32 * b + (tid & 31)) * DM), "r"(sb + GB_W) : "memory");
            float2 lam, coef;
            s5_channel(32 * b + 8 * w + g, Lre, Lim, logdt, lam, coef);
            float2 l32 = lam;
#pragma unroll
            for (int i = 0; i < 5; i++) l32 = make_float2(l32.x * l32.x - l32.y * l32.y, 2.f * l32.x * l32.y);
            __syncwarp();
            mbar_wait(sb + GB_W, 0);
            const uint32_t ap = sb + (((lane >> 3) & 1) * 32 + 8 * w + (lane & 7)) * 1168 + (lane >> 4) * 16;
#pragma unroll
            for (int ks = 0; ks < 36; ks++) { const uint4 v = ldsm4(ap + ks * 32); a[4 * ks] = v.x; a[4 * ks + 1] = v.y; a[4 * ks + 2] = v.z; a[4 * ks + 3] = v.w; }
            bar_sync(1, 256);
            bar_arrive(6, 288);
            BSTAMP(1);
#pragma unroll 1
            for (int blk = wg; blk < 16; blk += 2) {
                bg_mainloop<9, 2>(d, a, sb, (blk >> 1) * 18 + wg, lane);
                float2 e = make_float2(0.f, 0.f);
#pragma unroll
                for (int i = 0; i < 32; i++) e = cfma(lam, e, make_float2(d[4 * (i >> 1) + (i & 1)], d[4 * (i >> 1) + 2 + (i & 1)]));
                float2 cin = make_float2(0.f, 0.f);
                if (blk > 0) { bar_sync(2 + (wg ^ 1), 256); cin = lds64f(sb + G_CARRY + (wg ^ 1) * 256 + (8 * w + g) * 8); }
                float2 mine = cin;
#pragma unroll
                for (int q = 0; q < 4; q++) {
                    const float2 eq = make_float2(__shfl_sync(~0u, e.x, (lane & 28) + q), __shfl_sync(~0u, e.y, (lane & 28) + q));
                    cin = cfma(l32, cin, eq);
                    if (t == q + 1) mine = cin;
                }
                if (blk < 15) {
                    if (t == 0) sts64(sb + G_CARRY + wg * 256 + (8 * w + g) * 8, __float_as_uint(cin.x), __float_as_uint(cin.y));
                    bar_arrive(2 + wg, 256);
                }
                const uint32_t hs = sb + G_OUT + wg * 16384 + t * 4096 + (g & 3) * 4;
                const uint32_t ch = 2 * w + (g >> 2);
                if (blk >= 2) bar_sync(10 + wg, 160);
#pragma unroll
                for (int i = 0; i < 32; i++) {
                    mine = cfma(lam, mine, make_float2(d[4 * (i >> 1) + (i & 1)], d[4 * (i >> 1) + 2 + (i & 1)]));
                    sts32(hs + i * 128 + ((ch ^ (i & 7)) << 4), pack_bf16(mine.x, mine.y));
                }
                fence_async_smem();
                bar_arrive(8 + wg, 160);
            }
            bar_sync(10 + wg, 160);
        } else {
            if (tid < 128)
                asm volatile("cp.async.bulk.shared::cluster.global.mbarrier::complete_tx::bytes [%0], [%1], 1152, [%2];"
                    :: "r"(sb + tid * 1168), "l"((tid < 64 ? Cre : Cim) + (size_t)(64 * nt + (tid & 63)) * DM), "r"(sb + GB_W) : "memory");
            for (int p = tid; p < DM; p += 256) {
                float2 lam, coef;
                s5_channel(p, Lre, Lim, logdt, lam, coef);
                sts64(sb + G_EX + p * 8, __float_as_uint(2.f * coef.x), __float_as_uint(2.f * coef.y));
            }
            bar_sync(1, 256);
            mbar_wait(sb + GB_W, 0);
            const uint32_t cp = sb + (16 * w + 2 * g) * 1168 + (288 * wg + t) * 2;
#pragma unroll
            for (int u = 0; u < 72; u++) {
                const float2 c2 = lds64f(sb + G_EX + (288 * wg + 4 * u + t) * 8);
#pragma unroll
                for (int f = 0; f < 2; f++) {
                    unsigned short r16, i16;
                    asm volatile("ld.shared.u16 %0, [%1];" : "=h"(r16) : "r"(cp + f * 1168 + u * 8) : "memory");
                    asm volatile("ld.shared.u16 %0, [%1];" : "=h"(i16) : "r"(cp + (64 + f) * 1168 + u * 8) : "memory");
                    const float cr = __uint_as_float((uint32_t)r16 << 16), ci = __uint_as_float((uint32_t)i16 << 16);
                    a[2 * u + f] = pack_bf16(cr * c2.x - ci * c2.y, -(cr * c2.y + ci * c2.x));
                }
            }
            bar_sync(1, 256);
            bar_arrive(6, 288);
            BSTAMP(1);
#pragma unroll 1
            for (int j = 0; j < 8; j++) {
                bg_mainloop<9, 2>(d, a, sb, j * 18 + wg, lane);
                bg_epilogue<true>(d, sb, wg, w, lane, &tm_out, 64 * nt, (2 * j + kq - 2) * 128, xa, Dk);
            }
        }
        if (w == 0) asm volatile("cp.async.bulk.wait_group 0;" ::: "memory");
        bar_sync(1, 256);
        BSTAMP(2);
        if (warp == 0)
            asm volatile("{\n.reg .pred p;\nelect.sync _|p, 0xffffffff;\n@p mbarrier.arrive.expect_tx.shared::cta.b64 _, [%2], 131072;\n"
                "@p cp.async.bulk.tensor.2d.shared::cluster.global.mbarrier::complete_tx::bytes [%0], [%1, {%3, %4}], [%2];\n"
                "@p cp.async.bulk.tensor.2d.shared::cluster.global.mbarrier::complete_tx::bytes [%0+32768], [%1, {%3, %5}], [%2];\n"
                "@p cp.async.bulk.tensor.2d.shared::cluster.global.mbarrier::complete_tx::bytes [%0+65536], [%1, {%3, %6}], [%2];\n"
                "@p cp.async.bulk.tensor.2d.shared::cluster.global.mbarrier::complete_tx::bytes [%0+98304], [%1, {%3, %7}], [%2];\n}"
                :: "r"(sb), "l"(&tm_wo), "r"(sb + GB_W), "r"(64 * nt), "r"(1024 * kq), "r"(1024 * kq + 256), "r"(1024 * kq + 512), "r"(1024 * kq + 768) : "memory");
        mbar_wait(sb + GB_W, 1);
        {
            const uint32_t base = sb + wg * 65536 + 4 * t * 128 + (g & 3) * 4, ch = 2 * w + (g >> 2), r7 = (4 * t) & 7;
#pragma unroll
            for (int ks = 0; ks < 32; ks++) {
                const uint32_t w0 = lds32(base + ks * 2048 + ((ch ^ r7) << 4)), w1 = lds32(base + ks * 2048 + 256 + ((ch ^ (r7 + 2)) << 4));
                const uint32_t w2 = lds32(base + ks * 2048 + 128 + ((ch ^ (r7 + 1)) << 4)), w3 = lds32(base + ks * 2048 + 384 + ((ch ^ (r7 + 3)) << 4));
                a[4 * ks] = __byte_perm(w0, w1, 0x5410); a[4 * ks + 1] = __byte_perm(w0, w1, 0x7632);
                a[4 * ks + 2] = __byte_perm(w2, w3, 0x5410); a[4 * ks + 3] = __byte_perm(w2, w3, 0x7632);
            }
        }
        bar_sync(1, 256);
        bar_arrive(6, 288);
        BSTAMP(3);
#pragma unroll 1
        for (int na = 0, ng = 0, it = 144; ng < 16;) {
            if (bg_att_turn(na, ng)) {
                if (nt < 8) {
                    const int i0 = it + wg + 4 * (w >> 1), i1 = i0 + 2;
                    mbar_wait(sb + GB_FULL + 8 * (i0 % NST), (i0 / NST) & 1);
                    mbar_wait(sb + GB_FULL + 8 * (i1 % NST), (i1 / NST) & 1);
                    BSTAMP(8 + na * 4);
                    bg_attention(sb + G_RING + (i0 % NST) * 16384, sb + G_RING + (i1 % NST) * 16384, w & 1, lane);
                    fence_async_smem();
                    bar_arrive(7, 288);
                    bar_sync(1, 256);
                    BSTAMP(9 + na * 4);
                    it += 8;
                }
                na++;
            } else {
                bg_mainloop<8, 2>(d, a, sb, it + wg, lane);
                BSTAMP(10 + ng * 4);
                bg_epilogue<false>(d, sb, wg, w, lane, &tm_out, DM + 64 * nt, ng * 128, xa, Dk);
                BSTAMP(11 + ng * 4);
                it += 16; ng++;
            }
        }
    }
    asm volatile("griddepcontrol.wait;" ::: "memory");
}

typedef CUresult (*EncodeFn)(CUtensorMap*, CUtensorMapDataType, cuuint32_t, void*, const cuuint64_t*, const cuuint64_t*, const cuuint32_t*, const cuuint32_t*,
                             CUtensorMapInterleave, CUtensorMapSwizzle, CUtensorMapL2promotion, CUtensorMapFloatOOBfill);
}

extern "C" void kernel_launch(void* const* d_in, const int* in_sizes, int n_in, void* d_out, int out_size) {
    typedef const __nv_bfloat16* bp;
    bp Ax = (bp)d_in[0], Lre = (bp)d_in[1], Lim = (bp)d_in[2], Bre = (bp)d_in[3], Bim = (bp)d_in[4], Cre = (bp)d_in[5], Cim = (bp)d_in[6],
       logdt = (bp)d_in[7], Dk = (bp)d_in[8], Bx = (bp)d_in[9], mem0 = (bp)d_in[10], Wq = (bp)d_in[11], Wk = (bp)d_in[12], Wv = (bp)d_in[13], Wo = (bp)d_in[14];
    float* out = (float*)d_out;
    static EncodeFn enc = nullptr;
    if (!enc) {
        void* fn = nullptr; cudaDriverEntryPointQueryResult qr;
        cudaGetDriverEntryPoint("cuTensorMapEncodeTiled", &fn, cudaEnableDefault, &qr);
        enc = (EncodeFn)fn;
        cudaFuncSetAttribute(chain_kernel, cudaFuncAttributeMaxDynamicSharedMemorySize, CHAIN_SMEM);
        cudaFuncSetAttribute(bg_kernel, cudaFuncAttributeMaxDynamicSharedMemorySize, BG_SMEM);
    }
    const cuuint32_t es[5] = {1, 1, 1, 1, 1};
    auto map2d = [&](CUtensorMap* tm, CUtensorMapDataType dt, const void* p, cuuint64_t d0, cuuint64_t d1, cuuint64_t stride, cuuint32_t b0, cuuint32_t b1) {
        cuuint64_t gd[2] = {d0, d1}, gs[1] = {stride}; cuuint32_t bd[2] = {b0, b1};
        enc(tm, dt, 2, (void*)p, gd, gs, bd, es, CU_TENSOR_MAP_INTERLEAVE_NONE, CU_TENSOR_MAP_SWIZZLE_128B, CU_TENSOR_MAP_L2_PROMOTION_L2_128B,
            CU_TENSOR_MAP_FLOAT_OOB_FILL_NONE);
    };
    CUtensorMap tm_x, tm_q, tm_k, tm_v, tm_xa, tm_wo, tm_out;
    map2d(&tm_x, CU_TENSOR_MAP_DATA_TYPE_BFLOAT16, Bx, DM, SEQ, DM * 2, 64, 32);
    map2d(&tm_q, CU_TENSOR_MAP_DATA_TYPE_BFLOAT16, Wq, HD, DM, HD * 2, 64, 192);
    map2d(&tm_k, CU_TENSOR_MAP_DATA_TYPE_BFLOAT16, Wk, HD, DM, HD * 2, 64, 192);
    map2d(&tm_v, CU_TENSOR_MAP_DATA_TYPE_BFLOAT16, Wv, HD, DM, HD * 2, 64, 192);
    map2d(&tm_wo, CU_TENSOR_MAP_DATA_TYPE_BFLOAT16, Wo, DM, HD, DM * 2, 64, 256);
    map2d(&tm_out, CU_TENSOR_MAP_DATA_TYPE_FLOAT32, out, 2 * DM, SEQ, 2 * DM * 4, 32, 64);
    {
        cuuint64_t gd[5] = {DM, 2, 4, 16, 16}, gs[4] = {DM * 2, 32 * DM * 2, 2 * DM * 2, 128 * DM * 2}; cuuint32_t bd[5] = {64, 2, 4, 16, 1};
        enc(&tm_xa, CU_TENSOR_MAP_DATA_TYPE_BFLOAT16, 5, (void*)Ax, gd, gs, bd, es, CU_TENSOR_MAP_INTERLEAVE_NONE, CU_TENSOR_MAP_SWIZZLE_128B,
            CU_TENSOR_MAP_L2_PROMOTION_L2_128B, CU_TENSOR_MAP_FLOAT_OOB_FILL_NONE);
    }
    cudaStream_t st = cudaStreamPerThread;
    chain_kernel<<<96, 384, CHAIN_SMEM, st>>>(tm_x, tm_q, tm_k, tm_v, Bx, mem0, Wo);
    cudaLaunchConfig_t cfg = {};
    cfg.gridDim = dim3(36); cfg.blockDim = dim3(384); cfg.dynamicSmemBytes = BG_SMEM; cfg.stream = st;
    cudaLaunchAttribute at[1];
    at[0].id = cudaLaunchAttributeProgrammaticStreamSerialization; at[0].val.programmaticStreamSerializationAllowed = 1;
    cfg.attrs = at; cfg.numAttrs = 1;
    cudaLaunchKernelEx(&cfg, bg_kernel, tm_xa, tm_wo, tm_out, Ax, Lre, Lim, Bre, Bim, Cre, Cim, logdt, Dk);
}
```

```cpp
#include <cuda_runtime.h>
#include <cuda.h>
#include <cuda_bf16.h>
#include <cuda_fp16.h>
#include <stdint.h>

#define D_WAIT 740

#define BG_PACE 0
#define RED_GAP 720
#define ACC_PF 1
#define QDEP 0
#define BG_AHEAD 5

namespace {

constexpr int DM = 576, NH = 32, SEQ = 2048, NSEG = 64, HD = 4096;

__device__ uint4 g_acc_raw[64 * 96 * 16 + 131072];
__device__ uint4 g_ox[NH * 2 * SEQ * 8];
constexpr int REC = 30720;
__device__ uint4 g_qkv[NSEG * NH * (REC / 16)];
__device__ uint4 g_h[18 * SEQ * 8];
constexpr int NFLAG = 4096, F_QKV = 0, F_OX = 512, F_H = 1024, F_OUT = 2048;
__device__ unsigned g_flag[NFLAG];
__device__ unsigned g_ticket, g_ticket_bg;
__device__ unsigned long long g_norm[96];
#define BSTAMP(i) do {} while (0)

__device__ __forceinline__ uint32_t smem_u32(const void* p) { return (uint32_t)__cvta_generic_to_shared(p); }
__device__ __forceinline__ uint32_t mapa(uint32_t a, uint32_t r) { uint32_t o; asm("mapa.shared::cluster.u32 %0, %1, %2;" : "=r"(o) : "r"(a), "r"(r)); return o; }
__device__ __forceinline__ uint32_t mapa_v(uint32_t a, uint32_t r) { uint32_t o; asm volatile("mapa.shared::cluster.u32 %0, %1, %2;" : "=r"(o) : "r"(a), "r"(r)); return o; }
__device__ __forceinline__ unsigned clk() { unsigned long long c; asm volatile("mov.u64 %0, %%clock64;" : "=l"(c) :: "memory"); return (unsigned)c; }
__device__ __forceinline__ void mbar_init(uint32_t bar, uint32_t cnt) { asm volatile("mbarrier.init.shared::cta.b64 [%0], %1;" :: "r"(bar), "r"(cnt) : "memory"); }
__device__ __forceinline__ void mbar_expect(uint32_t bar, uint32_t bytes) { asm volatile("mbarrier.arrive.expect_tx.shared::cta.b64 _, [%0], %1;" :: "r"(bar), "r"(bytes) : "memory"); }
__device__ __forceinline__ void mbar_wait(uint32_t bar, uint32_t parity) {
    asm volatile("{\n.reg .pred p;\n.reg .u32 n;\nmov.u32 n, 0;\n"
                 "W_%=: mbarrier.try_wait.parity.shared::cta.b64 p, [%0], %1;\n@p bra.uni D_%=;\n"
                 "add.u32 n, n, 1;\nsetp.lt.u32 p, n, 4000000;\n@p bra.uni W_%=;\ntrap;\nD_%=:\n}" :: "r"(bar), "r"(parity) : "memory");
}
__device__ __forceinline__ void mbar_expect_if(uint32_t z, uint32_t bar, uint32_t bytes) {
    asm volatile("{\n.reg .pred p;\nsetp.eq.u32 p, %2, 0;\n@p mbarrier.arrive.expect_tx.shared::cta.b64 _, [%0], %1;\n}" :: "r"(bar), "r"(bytes), "r"(z) : "memory");
}
__device__ __forceinline__ void mbar_arrive_if(uint32_t z, uint32_t bar) {
    asm volatile("{\n.reg .pred p;\nsetp.eq.u32 p, %1, 0;\n@p mbarrier.arrive.shared::cta.b64 _, [%0];\n}" :: "r"(bar), "r"(z) : "memory");
}
__device__ __forceinline__ void sts32_if(uint32_t z, uint32_t a, uint32_t x) {
    asm volatile("{\n.reg .pred p;\nsetp.eq.u32 p, %2, 0;\n@p st.shared.u32 [%0], %1;\n}" :: "r"(a), "r"(x), "r"(z) : "memory");
}
template <int K> __device__ __forceinline__ void sched_fence(int v) {
    asm volatile("{\n.reg .pred p;\nsetp.ne.s32 p, %0, %1;\n@p bra.uni F_%=;\ntrap;\nF_%=:\n}" :: "r"(v), "n"(1000 + K) : "memory");
}
__device__ __forceinline__ void spin_until(unsigned t0, unsigned d) {
    asm volatile("{\n.reg .pred p;\n.reg .u64 c;\n.reg .u32 lo;\n"
                 "S_%=: mov.u64 c, %%clock64;\ncvt.u32.u64 lo, c;\nsub.u32 lo, lo, %0;\nsetp.lt.u32 p, lo, %1;\n@p bra.uni S_%=;\n}" :: "r"(t0), "r"(d) : "memory");
}
__device__ __forceinline__ void bar_sync(int id, int n) { asm volatile("bar.sync %0, %1;" :: "r"(id), "r"(n) : "memory"); }
__device__ __forceinline__ void bar_sync_sel(int sel, int id) {
    asm volatile("{\n.reg .pred p;\nsetp.eq.u32 p, %0, 0;\n@p bar.sync %1, %3;\n@!p bar.sync %2, %3;\n}" :: "r"(sel), "r"(id), "r"(id + 1), "n"(192) : "memory");
}
__device__ __forceinline__ void bar_arrive(int id, int n) { asm volatile("bar.arrive %0, %1;" :: "r"(id), "r"(n) : "memory"); }
__device__ __forceinline__ void fence_async_smem() { asm volatile("fence.proxy.async.shared::cta;" ::: "memory"); }
__device__ __forceinline__ uint32_t pack_bf16(float lo, float hi) { uint32_t r; asm("cvt.rn.bf16x2.f32 %0, %1, %2;" : "=r"(r) : "f"(hi), "f"(lo)); return r; }
__device__ __forceinline__ uint32_t pack_f16(float lo, float hi) { uint32_t r; asm("cvt.rn.f16x2.f32 %0, %1, %2;" : "=r"(r) : "f"(hi), "f"(lo)); return r; }
__device__ __forceinline__ uint32_t f16x2_to_bf16x2(uint32_t v) { float2 f = __half22float2(*reinterpret_cast<__half2*>(&v)); return pack_bf16(f.x, f.y); }
__device__ __forceinline__ uint32_t hmul2(uint32_t a, uint32_t b) { uint32_t r; asm("mul.rn.f16x2 %0, %1, %2;" : "=r"(r) : "r"(a), "r"(b)); return r; }
__device__ __forceinline__ float ex2(float x) { float y; asm("ex2.approx.ftz.f32 %0, %1;" : "=f"(y) : "f"(x)); return y; }
__device__ __forceinline__ float ex2v(float x) { float y; asm volatile("ex2.approx.ftz.f32 %0, %1;" : "=f"(y) : "f"(x)); return y; }
__device__ __forceinline__ uint32_t absmax2(uint32_t a, uint32_t b) {
    uint32_t r; asm("max.xorsign.abs.bf16x2 %0, %1, %2;" : "=r"(r) : "r"(a), "r"(b)); return r;
}
__device__ __forceinline__ uint32_t shl_v(uint32_t a, int n) { return a << n; }
__device__ __forceinline__ uint32_t max3u(uint32_t a, uint32_t b, uint32_t c) { return max(max(a, b), c); }
__device__ __forceinline__ uint4 lds128(uint32_t a) { uint4 v; asm volatile("ld.shared.v4.u32 {%0,%1,%2,%3}, [%4];" : "=r"(v.x), "=r"(v.y), "=r"(v.z), "=r"(v.w) : "r"(a) : "memory"); return v; }
__device__ __forceinline__ uint4 lds128v(uint32_t a) { uint4 v; asm volatile("ld.volatile.shared.v4.u32 {%0,%1,%2,%3}, [%4];" : "=r"(v.x), "=r"(v.y), "=r"(v.z), "=r"(v.w) : "r"(a) : "memory"); return v; }
__device__ __forceinline__ float4 lds128f(uint32_t a) { float4 v; asm volatile("ld.shared.v4.f32 {%0,%1,%2,%3}, [%4];" : "=f"(v.x), "=f"(v.y), "=f"(v.z), "=f"(v.w) : "r"(a) : "memory"); return v; }
__device__ __forceinline__ float2 lds64f(uint32_t a) { float2 v; asm volatile("ld.shared.v2.f32 {%0,%1}, [%2];" : "=f"(v.x), "=f"(v.y) : "r"(a) : "memory"); return v; }
__device__ __forceinline__ uint4 lds64x2(uint32_t a) { uint4 v; asm volatile("ld.shared.v2.u32 {%0,%1}, [%4];\nld.shared.v2.u32 {%2,%3}, [%4+256];" : "=r"(v.x), "=r"(v.y), "=r"(v.z), "=r"(v.w) : "r"(a) : "memory"); return v; }
__device__ __forceinline__ uint32_t lds32(uint32_t a) { uint32_t v; asm volatile("ld.shared.u32 %0, [%1];" : "=r"(v) : "r"(a) : "memory"); return v; }
__device__ __forceinline__ void sts128(uint32_t a, uint32_t x, uint32_t y, uint32_t z, uint32_t w) { asm volatile("st.shared.v4.u32 [%0], {%1,%2,%3,%4};" :: "r"(a), "r"(x), "r"(y), "r"(z), "r"(w) : "memory"); }
__device__ __forceinline__ void sts128f(uint32_t a, float x, float y, float z, float w) { asm volatile("st.shared.v4.f32 [%0], {%1,%2,%3,%4};" :: "r"(a), "f"(x), "f"(y), "f"(z), "f"(w) : "memory"); }
__device__ __forceinline__ void sts64(uint32_t a, uint32_t x, uint32_t y) { asm volatile("st.shared.v2.u32 [%0], {%1,%2};" :: "r"(a), "r"(x), "r"(y) : "memory"); }
__device__ __forceinline__ void sts32(uint32_t a, uint32_t x) { asm volatile("st.shared.u32 [%0], %1;" :: "r"(a), "r"(x) : "memory"); }
__device__ __forceinline__ uint4 ldsm4(uint32_t a) { uint4 v; asm volatile("ldmatrix.sync.aligned.m8n8.x4.shared.b16 {%0,%1,%2,%3}, [%4];" : "=r"(v.x), "=r"(v.y), "=r"(v.z), "=r"(v.w) : "r"(a) : "memory"); return v; }
__device__ __forceinline__ void stsm2t(uint32_t a, uint32_t x, uint32_t y) { asm volatile("stmatrix.sync.aligned.m8n8.x2.trans.shared.b16 [%0], {%1,%2};" :: "r"(a), "r"(x), "r"(y) : "memory"); }
__device__ __forceinline__ void stsm4t(uint32_t a, uint32_t x, uint32_t y, uint32_t z, uint32_t w) { asm volatile("stmatrix.sync.aligned.m8n8.x4.trans.shared.b16 [%0], {%1,%2,%3,%4};" :: "r"(a), "r"(x), "r"(y), "r"(z), "r"(w) : "memory"); }
__device__ __forceinline__ void st_async64(uint32_t a, uint32_t x, uint32_t y, uint32_t bar) { asm volatile("st.async.shared::cluster.mbarrier::complete_tx::bytes.v2.b32 [%0], {%1,%2}, [%3];" :: "r"(a), "r"(x), "r"(y), "r"(bar) : "memory"); }
__device__ __forceinline__ void bulk_s2c(uint32_t dst, uint32_t src, uint32_t bytes, uint32_t bar) { asm volatile("cp.async.bulk.shared::cluster.shared::cta.mbarrier::complete_tx::bytes [%0], [%1], %2, [%3];" :: "r"(dst), "r"(src), "r"(bytes), "r"(bar) : "memory"); }
__device__ __forceinline__ void bulk_s2g(void* dst, uint32_t src, uint32_t bytes) { asm volatile("cp.async.bulk.global.shared::cta.bulk_group [%0], [%1], %2;" :: "l"(dst), "r"(src), "r"(bytes) : "memory"); }
__device__ __forceinline__ uint32_t ldg_nc32(const void* p) { uint32_t v; asm volatile("ld.global.nc.L2::128B.u32 %0, [%1];" : "=r"(v) : "l"(p)); return v; }
__device__ __forceinline__ uint4 ldg_relaxed128(const void* p) { uint4 v; asm volatile("ld.relaxed.gpu.global.v4.u32 {%0,%1,%2,%3}, [%4];" : "=r"(v.x), "=r"(v.y), "=r"(v.z), "=r"(v.w) : "l"(p) : "memory"); return v; }
__device__ __forceinline__ void mma16816(float (&d)[4], uint32_t a0, uint32_t a1, uint32_t a2, uint32_t a3, uint32_t b0, uint32_t b1) {
    asm volatile("mma.sync.aligned.m16n8k16.row.col.f32.bf16.bf16.f32 {%0,%1,%2,%3}, {%4,%5,%6,%7}, {%8,%9}, {%0,%1,%2,%3};"
        : "+f"(d[0]), "+f"(d[1]), "+f"(d[2]), "+f"(d[3]) : "r"(a0), "r"(a1), "r"(a2), "r"(a3), "r"(b0), "r"(b1));
}
__device__ __forceinline__ void mma16816_z(float (&d)[4], uint32_t a0, uint32_t a1, uint32_t a2, uint32_t a3, uint32_t b0, uint32_t b1) {
    asm volatile("mma.sync.aligned.m16n8k16.row.col.f32.bf16.bf16.f32 {%0,%1,%2,%3}, {%4,%5,%6,%7}, {%8,%9}, {%10,%10,%10,%10};"
        : "=f"(d[0]), "=f"(d[1]), "=f"(d[2]), "=f"(d[3]) : "r"(a0), "r"(a1), "r"(a2), "r"(a3), "r"(b0), "r"(b1), "f"(0.f));
}
__device__ __forceinline__ void mma1688(float (&d)[4], uint32_t a0, uint32_t a1, uint32_t b0) {
    asm volatile("mma.sync.aligned.m16n8k8.row.col.f32.bf16.bf16.f32 {%0,%1,%2,%3}, {%4,%5}, {%6}, {%0,%1,%2,%3};"
        : "+f"(d[0]), "+f"(d[1]), "+f"(d[2]), "+f"(d[3]) : "r"(a0), "r"(a1), "r"(b0));
}
__device__ __forceinline__ void mma1688_z(float (&d)[4], uint32_t a0, uint32_t a1, uint32_t b0) {
    asm volatile("mma.sync.aligned.m16n8k8.row.col.f32.bf16.bf16.f32 {%0,%1,%2,%3}, {%4,%5}, {%6}, {%7,%7,%7,%7};"
        : "=f"(d[0]), "=f"(d[1]), "=f"(d[2]), "=f"(d[3]) : "r"(a0), "r"(a1), "r"(b0), "f"(0.f));
}
template <int ACC>
__device__ __forceinline__ void wgmma_n32_rs(float (&d)[16], uint32_t a0, uint32_t a1, uint32_t a2, uint32_t a3, uint64_t desc) {
    asm volatile("wgmma.mma_async.sync.aligned.m64n32k16.f32.bf16.bf16 {%0,%1,%2,%3,%4,%5,%6,%7,%8,%9,%10,%11,%12,%13,%14,%15}, {%16,%17,%18,%19}, %20, %21, 1, 1, 0;"
        : "+f"(d[0]), "+f"(d[1]), "+f"(d[2]), "+f"(d[3]), "+f"(d[4]), "+f"(d[5]), "+f"(d[6]), "+f"(d[7]),
          "+f"(d[8]), "+f"(d[9]), "+f"(d[10]), "+f"(d[11]), "+f"(d[12]), "+f"(d[13]), "+f"(d[14]), "+f"(d[15])
        : "r"(a0), "r"(a1), "r"(a2), "r"(a3), "l"(desc), "n"(ACC));
}
template <int ACC>
__device__ __forceinline__ void wgmma_n32_ss(float (&d)[16], uint64_t da, uint64_t db) {
    asm volatile("wgmma.mma_async.sync.aligned.m64n32k16.f32.bf16.bf16 {%0,%1,%2,%3,%4,%5,%6,%7,%8,%9,%10,%11,%12,%13,%14,%15}, %16, %17, %18, 1, 1, 0, 0;"
        : "+f"(d[0]), "+f"(d[1]), "+f"(d[2]), "+f"(d[3]), "+f"(d[4]), "+f"(d[5]), "+f"(d[6]), "+f"(d[7]),
          "+f"(d[8]), "+f"(d[9]), "+f"(d[10]), "+f"(d[11]), "+f"(d[12]), "+f"(d[13]), "+f"(d[14]), "+f"(d[15])
        : "l"(da), "l"(db), "n"(ACC));
}
__device__ __forceinline__ void wg_fence() { asm volatile("wgmma.fence.sync.aligned;" ::: "memory"); }
__device__ __forceinline__ void wg_commit() { asm volatile("wgmma.commit_group.sync.aligned;" ::: "memory"); }
__device__ __forceinline__ void wg_wait0() { asm volatile("wgmma.wait_group.sync.aligned 0;" ::: "memory"); }
__device__ __forceinline__ void cluster_sync() { asm volatile("barrier.cluster.arrive.aligned;\nbarrier.cluster.wait.aligned;" ::: "memory"); }

#define STAMP(s, i) do {} while (0)
#define STAMPV(s, i, v) do {} while (0)

constexpr int XT_BYTES = 36864;
constexpr int O_XT = 0;
constexpr int O_STG = XT_BYTES;
constexpr int O_AS = 3 * XT_BYTES;
constexpr int O_XP = O_AS + 16384;
constexpr int O_QKX = O_XP + 8192;
constexpr int O_KM = O_QKX + 8192;
constexpr int O_QM = O_QKX + 10240;
constexpr int O_VX = O_STG + 147456;
constexpr int O_VM = O_VX + 16384;
constexpr int O_SC = O_VM + 2048;
constexpr int O_OF = O_SC + 2560;
constexpr int O_AF = O_OF + 2048;
constexpr int O_WP = O_AF + 4096;
constexpr int O_MF = O_WP + 2048;
constexpr int O_MISC = O_MF + 9216;
static_assert(O_QKX + 24576 <= O_VX, "smem");
constexpr int O_BAR = O_MISC + 64;
constexpr int CHAIN_SMEM = O_BAR + 128;
static_assert(CHAIN_SMEM <= 232448, "smem");
constexpr int B_X = O_BAR, B_VX = O_BAR + 24, B_SC = O_BAR + 40, B_W = O_BAR + 48;
constexpr float SM_SCALE = 0.08838834764831845f * 1.4426950408889634f;
constexpr uint32_t ONES = 0x3f803f80u;

__device__ __forceinline__ uint32_t opaque(uint32_t v) { uint32_t o; asm volatile("mov.u32 %0, %1;" : "=r"(o) : "r"(v)); return o; }
__device__ __forceinline__ void st_async128(uint32_t a, uint32_t x, uint32_t y, uint32_t z, uint32_t w, uint32_t bar) {
    asm volatile("st.async.shared::cluster.mbarrier::complete_tx::bytes.v4.b32 [%0], {%1,%2,%3,%4}, [%5];" :: "r"(a), "r"(x), "r"(y), "r"(z), "r"(w), "r"(bar) : "memory");
}
__device__ __forceinline__ void tma_x_tile(uint32_t sb, const CUtensorMap* tm, int r, int j, int slot) {
    asm volatile("{\n.reg .pred p;\nelect.sync _|p, 0xffffffff;\n"
        "@p mbarrier.arrive.expect_tx.shared::cta.b64 _, [%2], 36864;\n"
        "@p cp.async.bulk.tensor.2d.shared::cluster.global.mbarrier::complete_tx::bytes.multicast::cluster [%0], [%1, {%3, %4}], [%2], %7;\n"
        "@p cp.async.bulk.tensor.2d.shared::cluster.global.mbarrier::complete_tx::bytes.multicast::cluster [%0+4096], [%1, {%5, %4}], [%2], %7;\n"
        "@p cp.async.bulk.tensor.2d.shared::cluster.global.mbarrier::complete_tx::bytes.multicast::cluster [%0+8192], [%1, {%6, %4}], [%2], %7;\n}"
        :: "r"(sb + O_XT + slot * XT_BYTES + 3 * r * 4096), "l"(tm), "r"(sb + B_X + 8 * slot), "r"(192 * r), "r"(j * 32), "r"(192 * r + 64), "r"(192 * r + 128),
           "h"((unsigned short)7) : "memory");
}
__device__ __forceinline__ void flag_inc_if(uint32_t z, unsigned* p) {
    asm volatile("{\n.reg .pred p;\nsetp.eq.u32 p, %1, 0;\n@p red.release.gpu.global.inc.u32 [%0], 0xfffffffe;\n}" :: "l"(p), "r"(z) : "memory");
}
__device__ __forceinline__ float quad_max(float v) {
    const float a = __shfl_xor_sync(~0u, v, 1), b = __shfl_xor_sync(~0u, v, 2), c = __shfl_xor_sync(~0u, v, 3);
    return fmaxf(fmaxf(v, a), fmaxf(b, c));
}
__device__ __forceinline__ void load_scores(float (&p)[10], uint32_t base, uint32_t stride, uint32_t l16) {
    const float4 a0 = lds128f(base + l16), b0 = lds128f(base + stride + l16);
    const float4 a1 = lds128f(base + 512 + l16), b1 = lds128f(base + stride + 512 + l16);
    const float2 a2 = lds64f(base + 1024 + (l16 >> 1)), b2 = lds64f(base + stride + 1024 + (l16 >> 1));
    p[0] = a2.x + b2.x; p[1] = a2.y + b2.y;
    p[2] = a0.x + b0.x; p[3] = a0.y + b0.y; p[4] = a0.z + b0.z; p[5] = a0.w + b0.w;
    p[6] = a1.x + b1.x; p[7] = a1.y + b1.y; p[8] = a1.z + b1.z; p[9] = a1.w + b1.w;
}
__device__ __forceinline__ float rcp_fast(float x) { float y; asm("rcp.approx.ftz.f32 %0, %1;" : "=f"(y) : "f"(x)); return y; }

__global__ void __cluster_dims__(3, 1, 1) __launch_bounds__(384, 1)
chain_kernel(const __grid_constant__ CUtensorMap tm_x, const __grid_constant__ CUtensorMap tm_q,
             const __grid_constant__ CUtensorMap tm_k, const __grid_constant__ CUtensorMap tm_v,
             const __nv_bfloat16* __restrict__ x, const __nv_bfloat16* __restrict__ mem0,
             const __nv_bfloat16* __restrict__ Wo) {
    extern __shared__ __align__(1024) uint8_t smem_raw[];
    const uint32_t sb = smem_u32(smem_raw);
    const int lane = threadIdx.x & 31;
    const int warp = __shfl_sync(~0u, threadIdx.x >> 5, 0);
    const int wg = warp >> 2, w = warp & 3;
    const int h = blockIdx.x / 3, r = blockIdx.x - 3 * h;
    uint4* const g_acc = reinterpret_cast<uint4*>((reinterpret_cast<uintptr_t>(g_acc_raw) + 0x1fffff) & ~(uintptr_t)0x1fffff);

#define PSTAMP(i) do {} while (0)
    if (threadIdx.x == 0) {
        if (sb & 1023u) __trap();
        for (int i = 0; i < 9; i++) mbar_init(sb + O_BAR + 8 * i, 1);
        asm volatile("fence.mbarrier_init.release.cluster;" ::: "memory");
        for (int i = 0; i < 3; i++) {
            mbar_expect(sb + B_W + 8 * i, 49152);
            for (int tl = 0; tl < 2; tl++)
                asm volatile("cp.async.bulk.tensor.2d.shared::cluster.global.mbarrier::complete_tx::bytes [%0], [%1, {%3, %4}], [%2];"
                    :: "r"(sb + O_STG + tl * 73728 + i * 24576), "l"(r < 2 ? (tl ? &tm_k : &tm_q) : &tm_v), "r"(sb + B_W + 8 * i),
                       "r"(h * 128 + 64 * (r < 2 ? r : tl)), "r"(192 * i) : "memory");
        }
    }
    __syncwarp();
    asm volatile("barrier.cluster.arrive.relaxed.aligned;" ::: "memory");
    asm volatile("griddepcontrol.launch_dependents;" ::: "memory");
    if (warp == 0) PSTAMP(9);
    const uint32_t l16c = __shfl_sync(~0u, lane * 16, lane);

    if (wg < 2) {
#define KS(u) ((u) < 8 ? 12 * ((u) >> 2) + (((u) >> 1) & 1) + 4 * ((u) & 1) : (u) < 12 ? (u) : (u) < 16 ? (u) + 8 : (u) < 24 ? 24 + (((u) - 16) >> 1) + 4 * ((u) & 1) : (u) + 8)
        asm volatile("setmaxnreg.inc.sync.aligned.u32 184;");
        uint32_t a[144];
        uint32_t adr1;
        {
            const int g = lane >> 2, t = lane & 3;
            const int t1 = threadIdx.x;
#pragma unroll
            for (int i = 0; i < 2; i++) g_acc[(blockIdx.x * 64 + i * 32 + (t1 >> 3)) * 16 + (t1 & 7)] = make_uint4(0, 0, 0, 0);
            __threadfence();
            asm volatile("barrier.cluster.wait.aligned;" ::: "memory");
            const uint32_t ev = sb + O_STG + (2 * t) * 128 + (((2 * w + (g >> 2)) ^ (2 * t)) << 4) + (g & 3) * 4;
            const uint32_t od = (ev ^ 16) + 128;
            auto gather = [&](int dst, uint32_t off) {
                a[dst] = lds32(ev + off); a[dst + 1] = lds32(od + off); a[dst + 2] = lds32(ev + off + 1024); a[dst + 3] = lds32(od + off + 1024);
            };
            const uint4* xp = reinterpret_cast<const uint4*>(x) + blockIdx.x * 1536 + t1;
            uint4 xv[6];
#pragma unroll
            for (int th = 0; th < 2; th++) {
                mbar_wait(sb + B_W + 8 * th, 0);
                if (th == 1) {
#pragma unroll
                    for (int i = 0; i < 6; i++) xv[i] = __ldg(xp + i * 256);
                }
#pragma unroll
                for (int u = 4 * th; u < 4 * th + 4; u++) {
                    gather(32 + 4 * u, wg * (73728 + 4096) + KS(u) * 2048);
                    gather(4 * u, 73728 - wg * (73728 - 4096) + KS(u) * 2048);
                    gather(64 + 4 * u, wg * 73728 + KS(8 + u) * 2048);
                }
            }
            mbar_wait(sb + B_W + 16, 0);
#pragma unroll
            for (int u = 16; u < 28; u++) gather(32 + 4 * u, wg * 73728 + KS(u) * 2048);
#pragma unroll
            for (int kk = 0; kk < 72; kk++) {
                uint32_t w0 = a[2 * kk], w1 = a[2 * kk + 1];
                a[2 * kk] = __byte_perm(w0, w1, 0x5410);
                a[2 * kk + 1] = __byte_perm(w0, w1, 0x7632);
            }
            if (r == 2) {
                float n0[4], n1[4];
#pragma unroll
                for (int u = 0; u < 36; u++) {
                    const uint32_t x0 = a[4 * u] & 0x7fff7fffu, x1 = a[4 * u + 1] & 0x7fff7fffu, x2 = a[4 * u + 2] & 0x7fff7fffu, x3 = a[4 * u + 3] & 0x7fff7fffu;
                    if (u == 0) mma16816_z(n0, x0, x1, x2, x3, ONES, ONES);
                    else if (u < 8) mma16816(n0, x0, x1, x2, x3, ONES, ONES);
                    else if (u == 8) mma16816_z(n1, x0, x1, x2, x3, ONES, ONES);
                    else mma16816(n1, x0, x1, x2, x3, ONES, ONES);
                }
                const uint32_t mx = __reduce_max_sync(~0u, __float_as_uint(2.f * fmaxf(fmaxf(n0[0], n0[2]), fmaxf(n1[0], n1[2]))));
                sts32_if(lane, sb + O_MISC + 32 + 4 * warp, mx);
            }
            uint32_t xm = 0;
#pragma unroll
            for (int i = 0; i < 6; i++)
                xm = __vmaxu2(xm, __vmaxu2(__vmaxu2(xv[i].x & 0x7fff7fffu, xv[i].y & 0x7fff7fffu), __vmaxu2(xv[i].z & 0x7fff7fffu, xv[i].w & 0x7fff7fffu)));
            sts32_if(lane, sb + O_OF + 16 + 4 * warp, __reduce_max_sync(~0u, max(xm << 16, xm & 0xffff0000u)));
            if (warp == 0) PSTAMP(11);
            bar_arrive(7, 384);
            asm volatile("barrier.cluster.arrive.relaxed.aligned;" ::: "memory");
            bar_sync(1, 256);
            const uint32_t as = sb + O_AS + wg * 8192 + (16 * w + g) * 128 + t * 4;
            sts32(as + (g << 4), a[32]);
            sts32(as + 1024 + (g << 4), a[33]);
            sts32(as + ((1 ^ g) << 4), a[34]);
            sts32(as + 1024 + ((1 ^ g) << 4), a[35]);
            sts128(sb + O_AF + warp * 512 + lane * 16, a[32], a[33], a[34], a[35]);
            fence_async_smem();
            bar_sync(1, 256);
            const uint32_t l = lane * 16;
            const int mi = lane >> 3, isk = (mi >> 1) ? wg : (wg ^ 1);
            adr1 = (r == 2) ? (sb + O_VM + warp * 256 + (l >> 1))
                            : (isk ? (sb + O_KM + w * 512 + wg * 256 + (mi & 1) * 128 + (l & 127))
                                   : (sb + O_QM + w * 512 + (mi & 1) * 256 + wg * 128 + (l & 127)));
            adr1 = __shfl_sync(~0u, adr1, lane);
        }
        int s3 = 2;
#pragma unroll 1
        for (int s = -1; s < NSEG; s++) {
            const uint32_t l16 = opaque(l16c);
            s3 = (s3 == 2) ? 0 : s3 + 1;
            if (s < 0) mbar_wait(sb + B_X, 0);
            const uint64_t desc0 = (uint64_t)(((sb + O_XT + s3 * XT_BYTES) & 0x3FFFF) >> 4) | (1ull << 16) | (64ull << 32) | (1ull << 62);
            uint32_t km0 = 0, km1 = 0;
            if (s >= 0) {
                { const uint4 v = lds128(sb + O_AF + warp * 512 + l16); a[32] = v.x; a[33] = v.y; a[34] = v.z; a[35] = v.w; }
                float co[4], cw[3][4];
                uint4 b[14];
                float inv;
#define GORD(i) ((i) < 8 ? 2 * ((i) >> 2) + (((i) >> 1) & 1) + 4 * ((i) & 1) : (i))
                auto qkv_mma = [&](int i) {
                    const int gi = GORD(i), u = 8 * gi, n0 = 2 * i, n1 = 2 * i + 1;
                    if (gi < 4) {
                        if (i == 0) mma16816_z(co, a[u], a[u + 1], a[u + 2], a[u + 3], b[0].x, b[0].y);
                        else mma16816(co, a[u], a[u + 1], a[u + 2], a[u + 3], b[i].x, b[i].y);
                    }
                    if (n0 < 3) mma16816_z(cw[n0 % 3], a[32 + u], a[32 + u + 1], a[32 + u + 2], a[32 + u + 3], b[i].x, b[i].y);
                    else mma16816(cw[n0 % 3], a[32 + u], a[32 + u + 1], a[32 + u + 2], a[32 + u + 3], b[i].x, b[i].y);
                    if (n1 < 3) mma16816_z(cw[n1 % 3], a[32 + u + 4], a[32 + u + 5], a[32 + u + 6], a[32 + u + 7], b[i].z, b[i].w);
                    else mma16816(cw[n1 % 3], a[32 + u + 4], a[32 + u + 5], a[32 + u + 6], a[32 + u + 7], b[i].z, b[i].w);
                    if (gi < 4) mma16816(co, a[u + 4], a[u + 5], a[u + 6], a[u + 7], b[i].z, b[i].w);
                };
                const uint32_t mf = sb + O_MF + l16, mfs = mf + wg * 1024;
                const uint32_t qb = (s & 1) * 12288;
                bar_sync(2, 384);
                if (warp == 0) STAMP(s, 0);
                auto qkv_ld = [&](int i) {
                    const int gi = GORD(i);
                    b[i] = gi < 4 ? lds128v(mfs + (gi >> 1) * 3072 + (gi & 1) * 512) : lds128v(mf + (gi < 6 ? gi : gi + 4) * 512);
                };
#pragma unroll
                for (int i = 0; i < 4; i++) qkv_ld(i);
                qkv_mma(0); qkv_mma(1); qkv_mma(2);
                const uint32_t z0 = __float_as_uint(QDEP ? co[0] : cw[1][0]) & (l16 & 15u);
                qkv_mma(3);
                bar_sync(15, 384);
                b[4] = lds128v(mfs + 3072 + z0);
#pragma unroll
                for (int i = 5; i < 9; i++) qkv_ld(i);
#pragma unroll
                for (int i = 4; i < 9; i++) { qkv_mma(i); qkv_ld(5 + i); }
                asm volatile("ld.volatile.shared.f32 %0, [%1];" : "=f"(inv) : "r"(sb + O_MISC) : "memory");
#pragma unroll
                for (int i = 9; i < 14; i++) qkv_mma(i);
#pragma unroll
                for (int i = 0; i < 4; i++) cw[0][i] += cw[1][i] + cw[2][i];
                if (r < 2) {
                    const uint32_t o0 = pack_bf16(co[0] * inv, co[1] * inv), o1 = pack_bf16(co[2] * inv, co[3] * inv);
                    const uint32_t w0 = pack_bf16(cw[0][0] * inv, cw[0][1] * inv), w1 = pack_bf16(cw[0][2] * inv, cw[0][3] * inv);
                    stsm4t(adr1 + qb, o0, o1, w0, w1);
                    if (warp == 0) STAMP(s, 1);
                    asm volatile("{\n.reg .pred p;\nsetp.ge.u32 p, %0, 3;\n@p bar.arrive 1, 256;\n}" :: "r"(warp) : "memory");
                    auto scores = [&](float (&v)[4], const uint4 (&q)[4], const uint4 (&k)[4]) {
                        float s0[4], s1[4], t0[4], t1[4];
                        mma16816_z(s0, q[0].x, q[0].y, q[0].z, q[0].w, k[0].x, k[0].y);
                        mma16816_z(s1, q[0].x, q[0].y, q[0].z, q[0].w, k[0].z, k[0].w);
                        mma16816_z(t0, q[1].x, q[1].y, q[1].z, q[1].w, k[1].x, k[1].y);
                        mma16816_z(t1, q[1].x, q[1].y, q[1].z, q[1].w, k[1].z, k[1].w);
                        mma16816(s0, q[2].x, q[2].y, q[2].z, q[2].w, k[2].x, k[2].y);
                        mma16816(s1, q[2].x, q[2].y, q[2].z, q[2].w, k[2].z, k[2].w);
                        mma16816(t0, q[3].x, q[3].y, q[3].z, q[3].w, k[3].x, k[3].y);
                        mma16816(t1, q[3].x, q[3].y, q[3].z, q[3].w, k[3].z, k[3].w);
                        v[0] = (s0[0] + s0[2]) + (t0[0] + t0[2]); v[1] = (s0[1] + s0[3]) + (t0[1] + t0[3]);
                        v[2] = (s1[0] + s1[2]) + (t1[0] + t1[2]); v[3] = (s1[1] + s1[3]) + (t1[1] + t1[3]);
                    };
                    if (warp < 2) {
                        uint4 q[4], k[4]; float v[4];
#pragma unroll
                        for (int i = 0; i < 4; i++) k[i] = ldsm4(sb + O_QKX + 4096 + qb + warp * 2048 + i * 512 + l16);
                        bar_sync(1, 256);
#pragma unroll
                        for (int i = 0; i < 4; i++) q[i] = ldsm4(sb + O_QM + qb + i * 512 + l16);
                        scores(v, q, k);
                        const uint32_t dst = sb + O_SC + r * 1280 + warp * 512 + l16;
                        st_async128(mapa(dst, 2), __float_as_uint(v[0]), __float_as_uint(v[1]), __float_as_uint(v[2]), __float_as_uint(v[3]), mapa(sb + B_SC, 2));
                        st_async128(mapa(dst, r ^ 1), __float_as_uint(v[0]), __float_as_uint(v[1]), __float_as_uint(v[2]), __float_as_uint(v[3]), mapa(sb + B_SC, r ^ 1));
                        st_async128(mapa(dst, r), __float_as_uint(v[0]), __float_as_uint(v[1]), __float_as_uint(v[2]), __float_as_uint(v[3]), mapa(sb + B_SC, r));
                    } else if (warp == 2) {
                        uint4 q[4], k[4]; float v[4];
                        bar_sync(1, 256);
#pragma unroll
                        for (int i = 0; i < 4; i++) { q[i] = ldsm4(sb + O_QM + qb + i * 512 + l16); k[i] = ldsm4(sb + O_KM + qb + i * 512 + l16); }
                        scores(v, q, k);
                        const uint32_t dst = sb + O_SC + r * 1280 + 1024 + (l16 >> 1);
                        st_async64(mapa(dst, 2), __float_as_uint(v[0] + v[2]), __float_as_uint(v[1] + v[3]), mapa(sb + B_SC, 2));
                        st_async64(mapa(dst, r ^ 1), __float_as_uint(v[0] + v[2]), __float_as_uint(v[1] + v[3]), mapa(sb + B_SC, r ^ 1));
                        st_async64(mapa(dst, r), __float_as_uint(v[0] + v[2]), __float_as_uint(v[1] + v[3]), mapa(sb + B_SC, r));
                        STAMP(s, 2);
                    }
                } else {
                    sts128f(sb + O_XP + warp * 512 + l16, co[0], co[1], co[2], co[3]);
                    bar_sync(8 + w, 64);
                    const float4 o = lds128f(sb + O_XP + (warp ^ 4) * 512 + l16);
                    km0 = pack_bf16((cw[0][0] + o.x) * inv, (cw[0][1] + o.y) * inv);
                    km1 = pack_bf16((cw[0][2] + o.z) * inv, (cw[0][3] + o.w) * inv);
                    if (warp == 0) STAMP(s, 1);
                    st_async64(mapa(adr1, 0), km0, km1, mapa(sb + B_SC, 0));
                    st_async64(mapa(adr1, 1), km0, km1, mapa(sb + B_SC, 1));
                    st_async64(mapa(adr1, 2), km0, km1, mapa(sb + B_SC, 2));
                    if (warp == 0) STAMP(s, 2);
                }
            }
            if (s >= 0) bar_sync(3, 384);
            auto store_qk = [&]() {
                asm volatile("{\n.reg .pred p;\nelect.sync _|p, 0xffffffff;\n"
                    "@p cp.async.bulk.global.shared::cta.bulk_group [%0], [%1], 10240;\n@p cp.async.bulk.commit_group;\n}"
                    :: "l"(reinterpret_cast<char*>(g_qkv) + (size_t)(s * NH + h) * REC + r * 10240), "r"(sb + O_QKX + (s & 1) * 12288) : "memory");
            };
            auto store_vm = [&]() {
                *reinterpret_cast<uint2*>(reinterpret_cast<char*>(g_qkv) + (size_t)(s * NH + h) * REC + 28672 + warp * 256 + (l16 >> 1)) = make_uint2(km0, km1);
            };
            if (s == NSEG - 1) {
                if (r == 2) store_vm();
                else if (warp == 3) {
                    fence_async_smem();
                    store_qk();
                    asm volatile("cp.async.bulk.wait_group 0;\nfence.proxy.async.global;" ::: "memory");
                }
            } else {
                const int j = s + 1;
#define XDESC(u) (((u) < 8 ? descs : desc0) + (uint64_t)(((KS(u) >> 2) * 4096 + (KS(u) & 3) * 32) >> 4))
                const uint64_t descs = desc0 + (uint64_t)(wg * 4);
                float d[16];
                wg_fence();
#pragma unroll
                for (int u = 0; u < 8; u++) {
                    if (u == 0) wgmma_n32_rs<0>(d, a[0], a[1], a[2], a[3], XDESC(0));
                    else wgmma_n32_rs<1>(d, a[4 * u], a[4 * u + 1], a[4 * u + 2], a[4 * u + 3], XDESC(u));
                }
                wg_commit();
                wg_wait0();
                if (warp == 0) STAMP(s, 15);
                if (warp == 3) asm volatile("cp.async.bulk.wait_group.read 0;" ::: "memory");
                if (s >= 0) bar_sync(4, 384);
#pragma unroll
                for (int q = 0; q < 2; q++)
                    sts128(sb + O_XP + warp * 1024 + q * 512 + l16, pack_bf16(d[8 * q], d[8 * q + 1]), pack_bf16(d[8 * q + 2], d[8 * q + 3]),
                           pack_bf16(d[8 * q + 4], d[8 * q + 5]), pack_bf16(d[8 * q + 6], d[8 * q + 7]));
                bar_sync(12, 256);
#pragma unroll
                for (int q = 0; q < 2; q++) {
                    const uint4 o = lds128(sb + O_XP + (warp ^ 4) * 1024 + q * 512 + l16);
                    d[8 * q] = __uint_as_float(o.x << 16); d[8 * q + 1] = __uint_as_float(o.x & 0xffff0000u);
                    d[8 * q + 2] = __uint_as_float(o.y << 16); d[8 * q + 3] = __uint_as_float(o.y & 0xffff0000u);
                    d[8 * q + 4] = __uint_as_float(o.z << 16); d[8 * q + 5] = __uint_as_float(o.z & 0xffff0000u);
                    d[8 * q + 6] = __uint_as_float(o.w << 16); d[8 * q + 7] = __uint_as_float(o.w & 0xffff0000u);
                }
                if (s >= 0) {
                    if (r == 2) store_vm();
                    if (warp == 5 && s + 2 < NSEG) tma_x_tile(sb, &tm_x, r, s + 2, s3 == 2 ? 0 : s3 + 1);
                    if (warp == 3) {
                        asm volatile("cp.async.bulk.wait_group 0;\nfence.proxy.async.global;" ::: "memory");
                        if ((s & 3) == 0 && s >= 4) {
                            __syncwarp();
                            flag_inc_if(l16, &g_flag[F_QKV + (s - 4 + (h >> 3)) * 8]);
                        }
                        fence_async_smem();
                    }
                    asm volatile("{\n.reg .pred p;\nsetp.eq.u32 p, %0, 0;\n@p bar.sync 5, 256;\n@!p bar.sync 13, 256;\n}" :: "r"(wg) : "memory");
                }
                const uint64_t da0 = (uint64_t)(((sb + O_AS + wg * 8192) & 0x3FFFF) >> 4) | (1ull << 16) | (64ull << 32) | (1ull << 62);
                wg_fence();
                wgmma_n32_ss<1>(d, da0, XDESC(0));
#pragma unroll
                for (int u = 1; u < 28; u++) wgmma_n32_rs<1>(d, a[32 + 4 * u], a[32 + 4 * u + 1], a[32 + 4 * u + 2], a[32 + 4 * u + 3], XDESC(u));
                wg_commit();
                wg_wait0();
                if (warp == 3 && r < 2 && s >= 0) store_qk();
                if (warp == 4) STAMP(s, 3);
                uint32_t e[8];
#pragma unroll
                for (int i = 0; i < 8; i++) e[i] = pack_bf16(d[2 * i], d[2 * i + 1]);
                if (r < 2) {
                    const uint32_t base = sb + O_QKX + (j & 1) * 12288 + wg * 4096 + w * 512 + l16;
                    stsm4t(base, e[0], wg ? e[1] : e[2], wg ? e[2] : e[1], e[3]);
                    stsm4t(base + 2048, e[4], wg ? e[5] : e[6], wg ? e[6] : e[5], e[7]);
                } else {
                    const uint32_t base = sb + O_VX + (j & 1) * 8192 + warp * 1024 + l16;
                    sts128(base, e[0], e[1], e[2], e[3]);
                    sts128(base + 512, e[4], e[5], e[6], e[7]);
                    bar_arrive(14, 288);
                }
                if (warp == 7) STAMP(s, 4);
                if (s < 0) asm volatile("barrier.cluster.wait.aligned;" ::: "memory");
            }
        }
        bar_arrive(7, 384);
    } else {
        asm volatile("setmaxnreg.dec.sync.aligned.u32 136;");
        const int c = w;
        uint32_t a[96];
        uint32_t mmax = 0;
        {
            const int g = lane >> 2, t = lane & 3;
            uint32_t tag = 0, m0v[18];
            if (threadIdx.x == 256) tag = atomicAdd(&g_ticket, 1u);
#pragma unroll
            for (int i = 0; i < 9; i++) {
                const uint32_t* p = reinterpret_cast<const uint32_t*>(mem0 + g * DM + 16 * (4 * i + c) + 2 * t);
                m0v[2 * i] = __ldg(p); m0v[2 * i + 1] = __ldg(p + 4);
            }
            asm volatile("barrier.cluster.wait.aligned;" ::: "memory");
            if (c == 0) {
                tma_x_tile(sb, &tm_x, r, 0, 0);
                mbar_expect_if(lane, sb + B_SC, 4608);
                if (r < 2) mbar_expect_if(lane, sb + B_VX, 8192);
                sts32_if(lane, sb + O_MISC, __float_as_uint(1.0f));
                sts32_if(lane, sb + O_MISC + 12, __float_as_uint(SM_SCALE));
            }
            asm volatile("barrier.cluster.arrive.relaxed.aligned;" ::: "memory");
#pragma unroll
            for (int tau = 0; tau < 3; tau++) {
                const uint32_t* v = m0v + 6 * tau;
                sts128(sb + O_MF + tau * 3072 + c * 512 + lane * 16, v[0], v[1], v[2], v[3]);
                sts64(sb + O_MF + tau * 3072 + 2048 + (c >> 1) * 512 + lane * 16 + (c & 1) * 8, v[4], v[5]);
#pragma unroll
                for (int i = 0; i < 6; i++) mmax = __vmaxu2(mmax, v[i] & 0x7fff7fffu);
            }
            mmax = max(mmax << 16, mmax & 0xffff0000u);
            bar_arrive(2, 384); bar_arrive(15, 384);
            tag = (__shfl_sync(~0u, tag, 0) / 96u + 1u) & 0xffffu;
            mbar_wait(sb + B_W + 0, 0);
            const __nv_bfloat16* p = Wo + (size_t)(h * 128 + 4 * t) * DM + 192 * r + 16 * c + 2 * g;
#pragma unroll
            for (int i = 0; i < 3; i++)
#pragma unroll
                for (int eb = 0; eb < 8; eb++)
#pragma unroll
                    for (int j = 0; j < 4; j++) a[(i * 8 + eb) * 4 + j] = ldg_nc32(p + (16 * eb + ((j & 1) * 2 + (j >> 1))) * DM + 64 * i);
#pragma unroll
            for (int kk = 0; kk < 48; kk++) {
                uint32_t w0 = a[2 * kk], w1 = a[2 * kk + 1];
                a[2 * kk] = __byte_perm(w0, w1, 0x5410);
                a[2 * kk + 1] = __byte_perm(w0, w1, 0x7632);
            }
            sts128(sb + O_WP + c * 512 + lane * 16, a[92], a[93], a[94], a[95]);
            float wmax = 0.f;
#pragma unroll
            for (int i = 0; i < 3; i++) {
                float n0[4];
#pragma unroll
                for (int u = 8 * i; u < 8 * i + 8; u++) {
                    const uint32_t x0 = a[4 * u] & 0x7fff7fffu, x1 = a[4 * u + 1] & 0x7fff7fffu, x2 = a[4 * u + 2] & 0x7fff7fffu, x3 = a[4 * u + 3] & 0x7fff7fffu;
                    if (u == 8 * i) mma16816_z(n0, x0, x1, x2, x3, ONES, ONES);
                    else mma16816(n0, x0, x1, x2, x3, ONES, ONES);
                }
                wmax = fmaxf(wmax, fmaxf(n0[0], n0[2]));
            }
            uint32_t wm = __reduce_max_sync(~0u, __float_as_uint(wmax));
            sts32_if(lane, sb + O_OF + 4 * c, wm);
            if (c == 0) PSTAMP(8);
            bar_sync(7, 384);
            asm volatile("barrier.cluster.wait.aligned;" ::: "memory");
            if (c == 1) tma_x_tile(sb, &tm_x, r, 1, 1);
            if (c == 0) {
                const uint4 wq = lds128(sb + O_OF), xq = lds128(sb + O_OF + 16), xr = lds128(sb + O_OF + 32), v0 = lds128(sb + O_MISC + 32), v1 = lds128(sb + O_MISC + 48);
                const uint32_t w1 = max(max(wq.x, wq.y), max(wq.z, wq.w)), x1 = max(max(max(xq.x, xq.y), max(xq.z, xq.w)), max(max(xr.x, xr.y), max(xr.z, xr.w)));
                const uint32_t vv = (r < 2) ? 0u : max(max(max(v0.x, v0.y), max(v0.z, v0.w)), max(max(v1.x, v1.y), max(v1.z, v1.w)));
                const uint32_t lo = (min(w1, 0x7f800000u) + 0xffffu) >> 16 | ((min(vv, 0x7f800000u) + 0xffffu) & 0xffff0000u), hi = (x1 & 0xffff0000u) | tag;
                uint32_t l0, h0, l1, h1, l2, h2;
                asm volatile("{\n.reg .pred p;\n.reg .u32 n, x, y;\n.reg .b64 v;\nsetp.eq.u32 p, %10, 0;\nmov.b64 v, {%8, %9};\n@p st.relaxed.gpu.global.b64 [%7], v;\nmov.u32 n, 0;\n"
                             "G_%=: ld.relaxed.gpu.global.b64 v, [%6];\nmov.b64 {%0, %1}, v;\nld.relaxed.gpu.global.b64 v, [%6+256];\nmov.b64 {%2, %3}, v;\n"
                             "ld.relaxed.gpu.global.b64 v, [%6+512];\nmov.b64 {%4, %5}, v;\n"
                             "xor.b32 x, %1, %9;\nxor.b32 y, %3, %9;\nor.b32 x, x, y;\nxor.b32 y, %5, %9;\nor.b32 x, x, y;\nand.b32 x, x, 0xffff;\n"
                             "setp.eq.u32 p, x, 0;\nvote.sync.all.pred p, p, 0xffffffff;\n@p bra.uni E_%=;\n"
                             "add.u32 n, n, 1;\nsetp.lt.u32 p, n, 4000000;\n@p bra.uni G_%=;\ntrap;\nE_%=:\n}"
                             : "=&r"(l0), "=&r"(h0), "=&r"(l1), "=&r"(h1), "=&r"(l2), "=&r"(h2)
                             : "l"(&g_norm[lane]), "l"(&g_norm[blockIdx.x]), "r"(lo), "r"(hi), "r"(lane) : "memory");
                const uint32_t lm = __vmaxu2(l0, __vmaxu2(l1, l2));
                const float fw = __uint_as_float(__reduce_max_sync(~0u, lm << 16));
                const float fv = __uint_as_float(__reduce_max_sync(~0u, lm & 0xffff0000u));
                const float xmax = __uint_as_float(__reduce_max_sync(~0u, max(h0, max(h1, h2)) & 0xffff0000u));
                const float G = 36.f * fw * fv;
                sts32_if(lane, sb + O_MISC + 4, __float_as_uint(G)); sts32_if(lane, sb + O_MISC + 8, __float_as_uint(G * xmax));
            }
        }
        if (c == 0) PSTAMP(12);
        bar_sync(6, 128);
        int s3n = 1;
        uint32_t roff = __shfl_sync(~0u, (r * 4 + c) * 2048 + (lane >> 4) * 512 + (lane & 2) * 128 + (lane & 1) * 64 + (lane & 12) * 4, lane);
#pragma unroll 1
        for (int s = 0; s < NSEG; s++) {
            const uint32_t l16 = opaque(l16c);
            const uint32_t vxa = sb + O_VX + (s & 1) * 8192 + c * 2048 + l16;
            if (c == 0 && r == 2) {
                bar_sync(14, 288);
                fence_async_smem();
                asm volatile("{\n.reg .pred p;\nelect.sync _|p, 0xffffffff;\n"
                    "@p cp.async.bulk.global.shared::cta.bulk_group [%0], [%1], 8192;\n@p cp.async.bulk.commit_group;\n"
                    "cp.async.bulk.wait_group 0;\nsetp.lt.and.s32 p, %4, 63, p;\n"
                    "@p cp.async.bulk.shared::cluster.global.mbarrier::complete_tx::bytes.multicast::cluster [%1], [%0], 8192, [%2], %3;\n"
                    "fence.proxy.async.global;\n}"
                    :: "l"(reinterpret_cast<char*>(g_qkv) + (size_t)(s * NH + h) * REC + 20480), "r"(sb + O_VX + (s & 1) * 8192),
                       "r"(sb + B_VX + 8 * (s & 1)), "h"((unsigned short)3), "r"(s) : "memory");
            }
            if (s == NSEG - 1) { bar_sync(3, 384); mbar_wait(sb + B_SC, s & 1); break; }
            uint4 vx[4];
            sts32_if(l16, sb + O_MISC + 16 + 4 * c, __reduce_max_sync(~0u, mmax));
            if (c == 0) STAMP(s, 5);
            {
                bar_sync(6, 128);
                const uint4 mm = lds128(sb + O_MISC + 16), cf = lds128(sb + O_MISC);
                const float bound = fmaxf(__uint_as_float(cf.z), __uint_as_float(cf.y) * (__uint_as_float(max(max(mm.x, mm.y), max(mm.z, mm.w))) * __uint_as_float(cf.x)));
                const uint32_t ebits = __reduce_max_sync(~0u, min(max(__float_as_uint(bound) & 0x7f800000u, 21u << 23), 254u << 23));
                mbar_wait(sb + B_X + 8 * s3n, ((s + 1) / 3) & 1);
                s3n = (s3n == 2) ? 0 : s3n + 1;
                bar_sync(3, 384);
                if (r < 2) mbar_wait(sb + B_VX + 8 * (s & 1), (s >> 1) & 1);
                vx[0] = lds128(vxa); vx[2] = lds128(vxa + 1024);
                if (c == 0) STAMP(s, 13);
                mbar_wait(sb + B_SC, s & 1);
                if (c == 0) STAMP(s, 6);
                float p[10];
                load_scores(p, sb + O_SC, 1280, l16);
                float mx = fmaxf(fmaxf(fmaxf(p[0], p[1]), fmaxf(p[2], p[3])), fmaxf(fmaxf(p[4], p[5]), fmaxf(p[6], p[7])));
                mx = quad_max(fmaxf(mx, fmaxf(p[8], p[9])));
                const uint4 vm = lds64x2(sb + O_VM + c * 512 + (l16 >> 1));
                vx[1] = lds128(vxa + 512); vx[3] = lds128(vxa + 1536);
                bar_arrive(4, 384);
                const float sc = __uint_as_float(lds32(sb + O_MISC + 12));
                const float mo = mx * SM_SCALE;
                uint32_t P[5];
#pragma unroll
                for (int n = 0; n < 5; n++) P[n] = pack_bf16(ex2(fmaf(p[2 * n], SM_SCALE, -mo)), ex2(fmaf(p[2 * n + 1], n == 3 ? sc : SM_SCALE, -mo)));
                if (c == 0) STAMP(s, 7);
                float o0[4], o1[4], sm[4];
                mma16816_z(sm, ONES, ONES, ONES, ONES, P[1], P[2]);
                mma16816_z(o0, vx[0].x, vx[0].y, vx[0].z, vx[0].w, P[1], P[2]);
                mma16816_z(o1, vx[2].x, vx[2].y, vx[2].z, vx[2].w, P[1], P[2]);
                mma16816(sm, ONES, ONES, ONES, ONES, P[3], P[4]);
                mma16816(o0, vx[1].x, vx[1].y, vx[1].z, vx[1].w, P[3], P[4]);
                mma16816(o1, vx[3].x, vx[3].y, vx[3].z, vx[3].w, P[3], P[4]);
                mma1688(sm, ONES, ONES, P[0]);
                mma1688(o0, vm.x, vm.y, P[0]);
                mma1688(o1, vm.z, vm.w, P[0]);
                const float sig = __uint_as_float((268u << 23) - ebits);
                const float r0 = rcp_fast(sm[0]) * sig, r1 = rcp_fast(sm[1]) * sig;
                stsm4t(sb + O_OF + c * 512 + l16, pack_bf16(o0[0] * r0, o0[1] * r1), pack_bf16(o0[2] * r0, o0[3] * r1),
                       pack_bf16(o1[0] * r0, o1[1] * r1), pack_bf16(o1[2] * r0, o1[3] * r1));
                bar_sync(6, 128);
                uint4 ob[4];
#pragma unroll
                for (int q = 0; q < 4; q++) ob[q] = ldsm4(sb + O_OF + q * 512 + l16);
                { const uint4 v = lds128(sb + O_WP + c * 512 + l16); a[92] = v.x; a[93] = v.y; a[94] = v.z; a[95] = v.w; }
                float m0[3][4], m1[3][4];
#pragma unroll
                for (int q = 0; q < 4; q++) {
#pragma unroll
                    for (int i = 0; i < 3; i++) {
                        const int k0 = (i * 8 + 2 * q) * 4;
                        if (q == 0) mma16816_z(m0[i], a[k0], a[k0 + 1], a[k0 + 2], a[k0 + 3], ob[q].x, ob[q].y);
                        else mma16816(m0[i], a[k0], a[k0 + 1], a[k0 + 2], a[k0 + 3], ob[q].x, ob[q].y);
                    }
#pragma unroll
                    for (int i = 0; i < 3; i++) {
                        const int k1 = (i * 8 + 2 * q + 1) * 4;
                        if (q == 0) mma16816_z(m1[i], a[k1], a[k1 + 1], a[k1 + 2], a[k1 + 3], ob[q].z, ob[q].w);
                        else mma16816(m1[i], a[k1], a[k1 + 1], a[k1 + 2], a[k1 + 3], ob[q].z, ob[q].w);
                    }
                }
                asm volatile("red.relaxed.gpu.global.add.noftz.v4.f16x2 [%0], {%1,%2,%3,%4};" :: "l"(reinterpret_cast<char*>(g_acc) + roff),
                    "r"(pack_f16(m0[0][0] + m1[0][0], m0[0][2] + m1[0][2])), "r"(pack_f16(m0[1][0] + m1[1][0], m0[1][2] + m1[1][2])),
                    "r"(pack_f16(m0[2][0] + m1[2][0], m0[2][2] + m1[2][2])), "r"(0x3c00u) : "memory");
                asm volatile("red.relaxed.gpu.global.add.noftz.v4.f16x2 [%0], {%1,%2,%3,%4};" :: "l"(reinterpret_cast<char*>(g_acc) + roff + 1024),
                    "r"(pack_f16(m0[0][1] + m1[0][1], m0[0][3] + m1[0][3])), "r"(pack_f16(m0[1][1] + m1[1][1], m0[1][3] + m1[1][3])),
                    "r"(pack_f16(m0[2][1] + m1[2][1], m0[2][3] + m1[2][3])), "r"(0x3c00u) : "memory");
                const unsigned t_red = clk();
                bar_arrive(5, 256);
                bar_arrive(13, 256);
                mbar_expect_if(l16 | c, sb + B_SC, 4608);
                mbar_expect_if(l16 | (c ^ 1) | (r >> 1), sb + B_VX + 8 * ((s + 1) & 1), 8192);
                sts32_if(l16 | (c ^ 3), sb + O_MISC, ebits - (14u << 23));
                if (c == 0) STAMPV(s, 8, t_red);
                if (ACC_PF && c == 2 && s + 4 < NSEG - 1)
                    asm volatile("prefetch.global.L2 [%0];" :: "l"(reinterpret_cast<const char*>(g_acc) + ((s + 4) * 96 + blockIdx.x) * 256 + (l16 & 96)) : "memory");
                const char* pbase = reinterpret_cast<const char*>(g_acc) + (s * 24576 + c * 2048) + ((l16 & 64) * 16 + (l16 & 256) + ((l16 & 128) >> 1) + (l16 & 48));
                spin_until(t_red, D_WAIT);
                uint4 v[6];
#pragma unroll
                for (int i = 0; i < 6; i++) v[i] = ldg_relaxed128(pbase + (i >> 1) * 8192 + (i & 1) * 512);
                int nretry = 0;
                auto convert = [&](int tau) {
                    uint4& A = v[2 * tau]; uint4& B = v[2 * tau + 1];
                    A.x = f16x2_to_bf16x2(A.x); B.x = f16x2_to_bf16x2(B.x); A.y = f16x2_to_bf16x2(A.y); B.y = f16x2_to_bf16x2(B.y);
                    A.z = f16x2_to_bf16x2(A.z); B.z = f16x2_to_bf16x2(B.z);
                    sts128(sb + O_MF + tau * 3072 + c * 512 + l16, A.x, B.x, A.y, B.y);
                    sts64(sb + O_MF + tau * 3072 + 2048 + (c >> 1) * 512 + (c & 1) * 8 + l16, A.z, B.z);
                };
                const uint32_t ok0 = __all_sync(~0u, (v[0].w & v[1].w) == 0x5000u);
                convert(0);
                asm volatile("{\n.reg .pred p;\nsetp.ne.u32 p, %0, 0;\n@p bar.arrive 2, 384;\n}" :: "r"(ok0) : "memory");
                sched_fence<0>(h);
                uint32_t ok1;
                asm volatile("{\n.reg .pred p, q;\n.reg .b32 x;\nlop3.b32 x, %1, %2, %3, 0x80;\nand.b32 x, x, %4;\n"
                             "setp.eq.u32 p, x, 0x5000;\nvote.sync.all.pred q, p, 0xffffffff;\nselp.u32 %0, 1, 0, q;\n}"
                             : "=r"(ok1) : "r"(v[2].w), "r"(v[3].w), "r"(v[4].w), "r"(v[5].w));
                convert(1); convert(2);
                asm volatile("{\n.reg .pred p;\nsetp.ne.u32 p, %0, 0;\n@p bar.arrive 15, 384;\n}" :: "r"(ok1) : "memory");
                if (!(ok0 & ok1)) {
                    asm volatile("{\n.reg .pred p, q;\n.reg .u32 n, x;\nmov.u32 n, 0;\n"
                         "R_%=: ld.relaxed.gpu.global.v4.u32 {%0,%1,%2,%3}, [%25];\nld.relaxed.gpu.global.v4.u32 {%4,%5,%6,%7}, [%25+512];\n"
                         "ld.relaxed.gpu.global.v4.u32 {%8,%9,%10,%11}, [%25+8192];\nld.relaxed.gpu.global.v4.u32 {%12,%13,%14,%15}, [%25+8704];\n"
                         "ld.relaxed.gpu.global.v4.u32 {%16,%17,%18,%19}, [%25+16384];\nld.relaxed.gpu.global.v4.u32 {%20,%21,%22,%23}, [%25+16896];\n"
                         "add.u32 %24, %24, 1;\nand.b32 x, %3, %7;\nand.b32 x, x, %11;\nand.b32 x, x, %15;\nand.b32 x, x, %19;\nand.b32 x, x, %23;\n"
                         "setp.eq.u32 p, x, 0x5000;\nvote.sync.all.pred q, p, 0xffffffff;\n@q bra.uni K_%=;\n"
                         "add.u32 n, n, 1;\nsetp.lt.u32 q, n, 2000000;\n@q bra.uni R_%=;\ntrap;\nK_%=:\n}"
                         : "+r"(v[0].x), "+r"(v[0].y), "+r"(v[0].z), "+r"(v[0].w), "+r"(v[1].x), "+r"(v[1].y), "+r"(v[1].z), "+r"(v[1].w),
                           "+r"(v[2].x), "+r"(v[2].y), "+r"(v[2].z), "+r"(v[2].w), "+r"(v[3].x), "+r"(v[3].y), "+r"(v[3].z), "+r"(v[3].w),
                           "+r"(v[4].x), "+r"(v[4].y), "+r"(v[4].z), "+r"(v[4].w), "+r"(v[5].x), "+r"(v[5].y), "+r"(v[5].z), "+r"(v[5].w), "+r"(nretry)
                         : "l"(pbase) : "memory");
                    convert(0); convert(1); convert(2);
                    if (!ok0) bar_arrive(2, 384);
                    if (!ok1) bar_arrive(15, 384);
                }
                if (c == 0) STAMP(s, 12);
                if (c == 0) STAMPV(s, 14, nretry);
                mmax = absmax2(absmax2(absmax2(v[0].x, v[0].y), absmax2(v[0].z, v[1].x)), absmax2(absmax2(v[1].y, v[1].z), absmax2(v[2].x, v[2].y)));
                mmax = absmax2(mmax, absmax2(absmax2(absmax2(v[2].z, v[3].x), absmax2(v[3].y, v[3].z)), absmax2(absmax2(v[4].x, v[4].y), absmax2(v[4].z, v[5].x))));
                mmax = absmax2(mmax, absmax2(v[5].y, v[5].z)) & 0x7fff7fffu;
                mmax = max(mmax << 16, mmax & 0xffff0000u);
            }
            roff += 24576;
        }
        {
            bar_sync(7, 384);
            if (c == 0) flag_inc_if(l16c, &g_flag[F_QKV + (60 + (h >> 3)) * 8]);
        }
    }
    if (warp == 8) PSTAMP(13);
    cluster_sync();
}

constexpr int NST = 10;
constexpr int G_RING = 0, G_EX = NST * 16384, G_OUT = G_EX + 32768, G_CARRY = G_OUT + 32768, G_BAR = G_CARRY + 512, BG_SMEM = G_BAR + 256;
constexpr int GB_FULL = G_BAR, GB_EMPTY = G_BAR + 8 * NST, GB_W = G_BAR + 16 * NST;
static_assert(BG_SMEM <= 232448, "smem");

template <int ACC>
__device__ __forceinline__ void wgmma_n128_rs(float (&d)[64], uint32_t a0, uint32_t a1, uint32_t a2, uint32_t a3, uint64_t desc) {
    asm volatile("wgmma.mma_async.sync.aligned.m64n128k16.f32.bf16.bf16 "
        "{%0,%1,%2,%3,%4,%5,%6,%7,%8,%9,%10,%11,%12,%13,%14,%15,%16,%17,%18,%19,%20,%21,%22,%23,%24,%25,%26,%27,%28,%29,%30,%31,"
        "%32,%33,%34,%35,%36,%37,%38,%39,%40,%41,%42,%43,%44,%45,%46,%47,%48,%49,%50,%51,%52,%53,%54,%55,%56,%57,%58,%59,%60,%61,%62,%63}, "
        "{%64,%65,%66,%67}, %68, %69, 1, 1, 0;"
        : "+f"(d[0]), "+f"(d[1]), "+f"(d[2]), "+f"(d[3]), "+f"(d[4]), "+f"(d[5]), "+f"(d[6]), "+f"(d[7]),
          "+f"(d[8]), "+f"(d[9]), "+f"(d[10]), "+f"(d[11]), "+f"(d[12]), "+f"(d[13]), "+f"(d[14]), "+f"(d[15]),
          "+f"(d[16]), "+f"(d[17]), "+f"(d[18]), "+f"(d[19]), "+f"(d[20]), "+f"(d[21]), "+f"(d[22]), "+f"(d[23]),
          "+f"(d[24]), "+f"(d[25]), "+f"(d[26]), "+f"(d[27]), "+f"(d[28]), "+f"(d[29]), "+f"(d[30]), "+f"(d[31]),
          "+f"(d[32]), "+f"(d[33]), "+f"(d[34]), "+f"(d[35]), "+f"(d[36]), "+f"(d[37]), "+f"(d[38]), "+f"(d[39]),
          "+f"(d[40]), "+f"(d[41]), "+f"(d[42]), "+f"(d[43]), "+f"(d[44]), "+f"(d[45]), "+f"(d[46]), "+f"(d[47]),
          "+f"(d[48]), "+f"(d[49]), "+f"(d[50]), "+f"(d[51]), "+f"(d[52]), "+f"(d[53]), "+f"(d[54]), "+f"(d[55]),
          "+f"(d[56]), "+f"(d[57]), "+f"(d[58]), "+f"(d[59]), "+f"(d[60]), "+f"(d[61]), "+f"(d[62]), "+f"(d[63])
        : "r"(a0), "r"(a1), "r"(a2), "r"(a3), "l"(desc), "n"(ACC));
}
__device__ __forceinline__ void wait_flag(const unsigned* p, unsigned target) {
    asm volatile("{\n.reg .pred p;\n.reg .u32 n, v;\nmov.u32 n, 0;\n"
                 "W_%=: ld.acquire.gpu.global.u32 v, [%0];\nsub.u32 v, v, %1;\nsetp.ge.s32 p, v, 0;\n@p bra.uni D_%=;\nnanosleep.u32 100;\n"
                 "add.u32 n, n, 1;\nsetp.lt.u32 p, n, 4000000;\n@p bra.uni W_%=;\ntrap;\nD_%=:\n}" :: "l"(p), "r"(target) : "memory");
}
template <int NS, int STRIDE>
__device__ __forceinline__ void bg_mainloop(float (&d)[64], const uint32_t (&a)[144], uint32_t sb, int it, int lane) {
    int slot = it % NST, ph = (it / NST) & 1, prev = 0;
#pragma unroll
    for (int i = 0; i < NS; i++) {
        mbar_wait(sb + GB_FULL + 8 * slot, ph);
        const uint64_t desc = (uint64_t)(((sb + G_RING + slot * 16384) & 0x3FFFF) >> 4) | (1ull << 16) | (64ull << 32) | (1ull << 62);
        wg_fence();
#pragma unroll
        for (int k = 0; k < 4; k++) {
            const int u = 16 * i + 4 * k;
            if (i == 0 && k == 0) wgmma_n128_rs<0>(d, a[u], a[u + 1], a[u + 2], a[u + 3], desc);
            else wgmma_n128_rs<1>(d, a[u], a[u + 1], a[u + 2], a[u + 3], desc + 2 * k);
        }
        wg_commit();
        if (i > 0) {
            asm volatile("wgmma.wait_group.sync.aligned 1;" ::: "memory");
            mbar_arrive_if(lane, sb + GB_EMPTY + 8 * prev);
        }
        prev = slot;
        slot += STRIDE;
        if (slot >= NST) { slot -= NST; ph ^= 1; }
    }
    wg_wait0();
    mbar_arrive_if(lane, sb + GB_EMPTY + 8 * prev);
}
template <bool SKIP>
__device__ __forceinline__ void bg_epilogue(float (&d)[64], uint32_t sb, int wg, int w, int lane, const CUtensorMap* tm_out, int col0, int tok0,
                                            const __nv_bfloat16* xa, const __nv_bfloat16* Dk) {
    const int g = lane >> 2, t = lane & 3;
    const uint32_t ex = sb + G_EX + w * 4096 + lane * 16;
    float k[32];
    if (wg == 0) {
#pragma unroll
        for (int q = 0; q < 8; q++) sts128f(ex + q * 512, d[32 + 4 * q], d[32 + 4 * q + 1], d[32 + 4 * q + 2], d[32 + 4 * q + 3]);
#pragma unroll
        for (int i = 0; i < 32; i++) k[i] = d[i];
    } else {
#pragma unroll
        for (int q = 0; q < 8; q++) sts128f(ex + 16384 + q * 512, d[4 * q], d[4 * q + 1], d[4 * q + 2], d[4 * q + 3]);
#pragma unroll
        for (int i = 0; i < 32; i++) k[i] = d[32 + i];
    }
    uint32_t xv[16], dv = 0;
    if (SKIP) {
        const __nv_bfloat16* xp = xa + (size_t)(tok0 + 64 * wg + 2 * t) * DM + col0 + 16 * w + 2 * g;
#pragma unroll
        for (int i = 0; i < 16; i++) xv[i] = ldg_nc32(xp + (8 * (i >> 1) + (i & 1)) * DM);
        dv = ldg_nc32(Dk + col0 + 16 * w + 2 * g);
    }
    if (SKIP && w == 0) asm volatile("cp.async.bulk.wait_group.read 0;" ::: "memory");
    bar_sync(1, 256);
#pragma unroll
    for (int q = 0; q < 8; q++) {
        const float4 o = lds128f(ex + (wg ^ 1) * 16384 + q * 512);
        k[4 * q] += o.x; k[4 * q + 1] += o.y; k[4 * q + 2] += o.z; k[4 * q + 3] += o.w;
    }
    if (SKIP) bar_sync(1, 256); else bar_sync(13, 288);
    const uint32_t ob = sb + G_OUT + wg * 16384 + (w >> 1) * 8192 + (g & 1) * 8;
    const uint32_t ch = (w & 1) * 4 + (g >> 1);
#pragma unroll
    for (int i = 0; i < 16; i++) {
        float v0 = k[4 * (i >> 1) + (i & 1)], v1 = k[4 * (i >> 1) + 2 + (i & 1)];
        if (SKIP) {
            const uint32_t p = pack_bf16(__uint_as_float(xv[i] << 16) * __uint_as_float(dv << 16), __uint_as_float(xv[i] & 0xffff0000u) * __uint_as_float(dv & 0xffff0000u));
            v0 += __uint_as_float(p << 16); v1 += __uint_as_float(p & 0xffff0000u);
        }
        const uint32_t n7 = 2 * t + (i & 1);
        sts64(ob + (8 * (i >> 1) + n7) * 128 + ((ch ^ n7) << 4), __float_as_uint(v0), __float_as_uint(v1));
    }
    fence_async_smem();
    if (SKIP) {
        bar_sync(4 + wg, 128);
        if (w == 0)
            asm volatile("{\n.reg .pred p;\nelect.sync _|p, 0xffffffff;\n"
                "@p cp.async.bulk.tensor.2d.global.shared::cta.bulk_group [%0, {%2, %4}], [%1];\n"
                "@p cp.async.bulk.tensor.2d.global.shared::cta.bulk_group [%0, {%3, %4}], [%1+8192];\n@p cp.async.bulk.commit_group;\n}"
                :: "l"(tm_out), "r"(sb + G_OUT + wg * 16384), "r"(col0), "r"(col0 + 32), "r"(tok0 + 64 * wg) : "memory");
    } else {
        bar_arrive(12, 288);
    }
}
__device__ __forceinline__ void s5_channel(int p, const __nv_bfloat16* Lre, const __nv_bfloat16* Lim, const __nv_bfloat16* logdt, float2& lam, float2& coef) {
    const float dt = __bfloat162float(__float2bfloat16(expf(__bfloat162float(logdt[p]))));
    const float lr = __bfloat162float(Lre[p]), li = __bfloat162float(Lim[p]);
    const float e = expf(dt * lr);
    float sn, cs;
    sincosf(dt * li, &sn, &cs);
    lam = make_float2(e * cs, e * sn);
    const float den = lr * lr + li * li;
    coef = make_float2(((lam.x - 1.f) * lr + lam.y * li) / den, (lam.y * lr - (lam.x - 1.f) * li) / den);
}
__device__ __forceinline__ float2 cfma(float2 a, float2 b, float2 c) {
    return make_float2(fmaf(a.x, b.x, fmaf(-a.y, b.y, c.x)), fmaf(a.x, b.y, fmaf(a.y, b.x, c.y)));
}
__device__ __forceinline__ uint4 ldg128(const void* p) { uint4 v; asm volatile("ld.global.v4.u32 {%0,%1,%2,%3}, [%4];" : "=r"(v.x), "=r"(v.y), "=r"(v.z), "=r"(v.w) : "l"(p) : "memory"); return v; }
__device__ __forceinline__ uint2 ldg64(const void* p) { uint2 v; asm volatile("ld.global.v2.u32 {%0,%1}, [%2];" : "=r"(v.x), "=r"(v.y) : "l"(p) : "memory"); return v; }

__device__ __forceinline__ void bg_attention(uint32_t st0, uint32_t st1, int mt, int lane) {
    const int g = lane >> 2, t = lane & 3;
    float sc[5][4];
#pragma unroll
    for (int n = 0; n < 5; n++) sc[n][0] = sc[n][1] = sc[n][2] = sc[n][3] = 0.f;
    float sm2[4] = {0.f, 0.f, 0.f, 0.f};
#pragma unroll
    for (int i = 0; i < 8; i++) {
        const uint32_t st = (i >> 2 ? st1 : st0) + (i & 3) * 512 + lane * 16;
        const uint4 q = ldsm4(st + mt * 2048), km = ldsm4(st + 8192), k0 = ldsm4(st + 4096);
        mma16816(sc[0], q.x, q.y, q.z, q.w, km.x, km.y);
        mma16816(sm2, q.x, q.y, q.z, q.w, km.z, km.w);
        mma16816(sc[1], q.x, q.y, q.z, q.w, k0.x, k0.y);
        mma16816(sc[2], q.x, q.y, q.z, q.w, k0.z, k0.w);
        if (mt) {
            const uint4 k1 = ldsm4(st + 6144);
            mma16816(sc[3], q.x, q.y, q.z, q.w, k1.x, k1.y);
            mma16816(sc[4], q.x, q.y, q.z, q.w, k1.z, k1.w);
        }
    }
#pragma unroll
    for (int i = 0; i < 4; i++) sc[0][i] += sm2[i];
    const int q0 = 16 * mt + 8 + g - 2 * t;
#pragma unroll
    for (int n = 1; n < 5; n++) {
        if (8 * n > q0) sc[n][0] = -INFINITY;
        if (8 * n + 1 > q0) sc[n][1] = -INFINITY;
        if (8 * n > q0 + 8) sc[n][2] = -INFINITY;
        if (8 * n + 1 > q0 + 8) sc[n][3] = -INFINITY;
    }
    float ma = fmaxf(sc[0][0], sc[0][1]), mb = fmaxf(sc[0][2], sc[0][3]);
#pragma unroll
    for (int n = 1; n < 5; n++) { ma = fmaxf(ma, fmaxf(sc[n][0], sc[n][1])); mb = fmaxf(mb, fmaxf(sc[n][2], sc[n][3])); }
    ma = quad_max(ma) * SM_SCALE; mb = quad_max(mb) * SM_SCALE;
    uint32_t Pa[5], Pb[5];
#pragma unroll
    for (int n = 0; n < 5; n++) {
        Pa[n] = pack_bf16(ex2(fmaf(sc[n][0], SM_SCALE, -ma)), ex2(fmaf(sc[n][1], SM_SCALE, -ma)));
        Pb[n] = pack_bf16(ex2(fmaf(sc[n][2], SM_SCALE, -mb)), ex2(fmaf(sc[n][3], SM_SCALE, -mb)));
    }
    float sa[4], sbb[4];
    mma1688_z(sa, ONES, ONES, Pa[0]); mma1688_z(sbb, ONES, ONES, Pb[0]);
    mma16816(sa, ONES, ONES, ONES, ONES, Pa[1], Pa[2]); mma16816(sbb, ONES, ONES, ONES, ONES, Pb[1], Pb[2]);
    mma16816(sa, ONES, ONES, ONES, ONES, Pa[3], Pa[4]); mma16816(sbb, ONES, ONES, ONES, ONES, Pb[3], Pb[4]);
    const float ra0 = rcp_fast(sa[0]), ra1 = rcp_fast(sa[1]), rb0 = rcp_fast(sbb[0]), rb1 = rcp_fast(sbb[1]);
    const uint32_t row = lane & 7;
    const uint32_t so = mt * 2048 + (lane >> 4) * 1024 + row * 128;
#pragma unroll
    for (int i = 0; i < 8; i++) {
        const uint32_t st = i >> 2 ? st1 : st0;
        const int e4 = i & 3;
        const float2 vmf = lds64f(st + 14336 + e4 * 256 + lane * 8);
        const uint32_t vm0 = __float_as_uint(vmf.x), vm1 = __float_as_uint(vmf.y);
        const uint4 v0 = lds128(st + 10240 + e4 * 1024 + lane * 16);
        float oa[4], ob[4];
        mma1688_z(oa, vm0, vm1, Pa[0]); mma1688_z(ob, vm0, vm1, Pb[0]);
        mma16816(oa, v0.x, v0.y, v0.z, v0.w, Pa[1], Pa[2]);
        mma16816(ob, v0.x, v0.y, v0.z, v0.w, Pb[1], Pb[2]);
        if (mt) {
            const uint4 v1 = lds128(st + 10240 + e4 * 1024 + 512 + lane * 16);
            mma16816(oa, v1.x, v1.y, v1.z, v1.w, Pa[3], Pa[4]);
            mma16816(ob, v1.x, v1.y, v1.z, v1.w, Pb[3], Pb[4]);
        }
        stsm4t(st + so + (((2 * e4 + ((lane >> 3) & 1)) ^ row) << 4), pack_bf16(oa[0] * ra0, oa[1] * ra1), pack_bf16(oa[2] * ra0, oa[3] * ra1),
               pack_bf16(ob[0] * rb0, ob[1] * rb1), pack_bf16(ob[2] * rb0, ob[3] * rb1));
    }
}
__device__ __forceinline__ bool bg_att_turn(int na, int ng) { return na == ng || (na == ng + 1 && na <= BG_AHEAD); }

__global__ void __launch_bounds__(384, 1)
bg_kernel(const __grid_constant__ CUtensorMap tm_xa, const __grid_constant__ CUtensorMap tm_wo, const __grid_constant__ CUtensorMap tm_out,
          const __nv_bfloat16* __restrict__ xa, const __nv_bfloat16* __restrict__ Lre, const __nv_bfloat16* __restrict__ Lim,
          const __nv_bfloat16* __restrict__ Bre, const __nv_bfloat16* __restrict__ Bim, const __nv_bfloat16* __restrict__ Cre,
          const __nv_bfloat16* __restrict__ Cim, const __nv_bfloat16* __restrict__ logdt, const __nv_bfloat16* __restrict__ Dk) {
    extern __shared__ __align__(1024) uint8_t smem_raw[];
    const uint32_t sb = smem_u32(smem_raw);
    const int lane = threadIdx.x & 31;
    const int warp = __shfl_sync(~0u, threadIdx.x >> 5, 0);
    const int wg = warp >> 2, w = warp & 3, b = blockIdx.x;
    const int nt = b % 9, kq = b / 9;
    BSTAMP(0);
    if (threadIdx.x == 0) {
        if (sb & 1023u) __trap();
        for (int i = 0; i < NST; i++) { mbar_init(sb + GB_FULL + 8 * i, 1); mbar_init(sb + GB_EMPTY + 8 * i, 4); }
        mbar_init(sb + GB_W, 1);
        asm volatile("fence.mbarrier_init.release.cluster;" ::: "memory");
        mbar_expect(sb + GB_W, (b < 18 ? 64 : 128) * 1152);
        sts32(sb + G_BAR + 248, atomicAdd(&g_ticket_bg, 1u) / 36u + 1u);
    }
    __syncthreads();
    if (wg == 2) {
        asm volatile("setmaxnreg.dec.sync.aligned.u32 24;");
        if (w == 0) {
            int slot = 0, ph = 1;
            unsigned tlast = clk();
            auto pace = [&]() { if (BG_PACE) { spin_until(tlast, BG_PACE); tlast = clk(); } };
            auto next = [&]() { if (++slot == NST) { slot = 0; ph ^= 1; } };
            bar_sync(6, 288);
            if (b < 18) {
#pragma unroll 1
                for (int i = 0; i < 144; i++) {
                    const int blk = i / 9, kb = i - 9 * blk, it = (blk >> 1) * 18 + (blk & 1) + 2 * kb;
                    slot = it % NST;
                    mbar_wait(sb + GB_EMPTY + 8 * slot, ((it / NST) & 1) ^ 1);
                    pace();
                    asm volatile("{\n.reg .pred p;\nelect.sync _|p, 0xffffffff;\n@p mbarrier.arrive.expect_tx.shared::cta.b64 _, [%2], 16384;\n"
                        "@p cp.async.bulk.tensor.5d.shared::cluster.global.mbarrier::complete_tx::bytes [%0], [%1, {%3, %4, %4, %4, %5}], [%2];\n}"
                        :: "r"(sb + G_RING + slot * 16384), "l"(&tm_xa), "r"(sb + GB_FULL + 8 * slot), "r"(kb * 64), "r"(0), "r"(blk) : "memory");
                }
                slot = 144 % NST; ph = ((144 / NST) & 1) ^ 1;
            }
            const unsigned ep = lds32(sb + G_BAR + 248);
            auto slabs = [&](const char* src, int ns) {
                asm volatile("fence.proxy.async.global;" ::: "memory");
#pragma unroll 1
                for (int i = 0; i < ns; i++) {
                    mbar_wait(sb + GB_EMPTY + 8 * slot, ph);
                    pace();
                    asm volatile("{\n.reg .pred p;\nelect.sync _|p, 0xffffffff;\n@p mbarrier.arrive.expect_tx.shared::cta.b64 _, [%2], 16384;\n"
                        "@p cp.async.bulk.shared::cluster.global.mbarrier::complete_tx::bytes [%0], [%1], 16384, [%2];\n}"
                        :: "r"(sb + G_RING + slot * 16384), "l"(src + (size_t)((i & 1) * (ns >> 1) + (i >> 1)) * (SEQ * 128)), "r"(sb + GB_FULL + 8 * slot) : "memory");
                    next();
                }
            };
            if (b >= 18) {
#pragma unroll 1
                for (int blk = kq - 2; blk < 16; blk += 2) {
                    wait_flag(&g_flag[F_H + blk * 8], 18 * ep);
                    slabs(reinterpret_cast<const char*>(g_h) + blk * 16384, 18);
                }
            }
            bar_sync(6, 288);
#pragma unroll 1
            for (int na = 0, ng = 0; ng < 16;) {
                if (bg_att_turn(na, ng)) {
                    if (nt < 8) {
                        wait_flag(&g_flag[F_QKV + (na * 4 + kq) * 8], 24 * ep);
                        asm volatile("fence.proxy.async.global;" ::: "memory");
#pragma unroll 1
                        for (int i = 0; i < 8; i++) {
                            const int pr = nt * 4 + 2 * (i & 1) + (i >> 2), hf = (i >> 1) & 1;
                            const char* rec = reinterpret_cast<const char*>(g_qkv) + (size_t)((4 * na + (pr >> 3)) * NH + 8 * kq + (pr & 7)) * REC;
                            mbar_wait(sb + GB_EMPTY + 8 * slot, ph);
                    pace();
                            asm volatile("{\n.reg .pred p;\nelect.sync _|p, 0xffffffff;\n@p mbarrier.arrive.expect_tx.shared::cta.b64 _, [%4], 15360;\n"
                                "@p cp.async.bulk.shared::cluster.global.mbarrier::complete_tx::bytes [%0], [%1], 10240, [%4];\n"
                                "@p cp.async.bulk.shared::cluster.global.mbarrier::complete_tx::bytes [%0+10240], [%2], 4096, [%4];\n"
                                "@p cp.async.bulk.shared::cluster.global.mbarrier::complete_tx::bytes [%0+14336], [%3], 1024, [%4];\n}"
                                :: "r"(sb + G_RING + slot * 16384), "l"(rec + hf * 10240), "l"(rec + 20480 + hf * 4096), "l"(rec + 28672 + hf * 1024),
                                   "r"(sb + GB_FULL + 8 * slot) : "memory");
                            next();
                        }
                    }
                    na++;
                } else {
                    wait_flag(&g_flag[F_OX + (ng * 4 + kq) * 8], 8 * ep);
                    slabs(reinterpret_cast<const char*>(g_ox) + (size_t)kq * 16 * SEQ * 128 + ng * 16384, 16);
                    ng++;
                }
            }
        } else if (w == 1) {
            if (b < 18) {
#pragma unroll 1
                for (int blk = 0; blk < 16; blk++) {
                    bar_sync(8 + (blk & 1), 160);
                    asm volatile("{\n.reg .pred p;\nelect.sync _|p, 0xffffffff;\n@p cp.async.bulk.global.shared::cta.bulk_group [%0], [%1], 16384;\n"
                        "@p cp.async.bulk.commit_group;\ncp.async.bulk.wait_group 0;\nfence.proxy.async.global;\n}"
                        :: "l"(reinterpret_cast<char*>(g_h) + ((size_t)b * SEQ + blk * 128) * 128), "r"(sb + G_OUT + (blk & 1) * 16384) : "memory");
                    bar_arrive(10 + (blk & 1), 160);
                    flag_inc_if(lane, &g_flag[F_H + blk * 8]);
                }
            }
            if (nt < 8) {
                int it = 144;
#pragma unroll 1
                for (int na = 0, ng = 0; ng < 16;) {
                    if (bg_att_turn(na, ng)) {
                        bar_sync(7, 288);
                        if (lane < 8) {
                            const int pr = nt * 4 + 2 * (lane & 1) + (lane >> 2), hf = (lane >> 1) & 1;
                            asm volatile("cp.async.bulk.global.shared::cta.bulk_group [%0], [%1], 4096;\ncp.async.bulk.commit_group;\ncp.async.bulk.wait_group.read 0;\n"
                                "mbarrier.arrive.shared::cta.b64 _, [%2], 4;\ncp.async.bulk.wait_group 0;\nfence.proxy.async.global;"
                                :: "l"(reinterpret_cast<char*>(g_ox) + ((size_t)((8 * kq + (pr & 7)) * 2 + hf) * SEQ + (4 * na + (pr >> 3)) * 32) * 128),
                                   "r"(sb + G_RING + ((it + lane) % NST) * 16384), "r"(sb + GB_EMPTY + 8 * ((it + lane) % NST)) : "memory");
                        }
                        __syncwarp();
                        flag_inc_if(lane, &g_flag[F_OX + (na * 4 + kq) * 8]);
                        it += 8; na++;
                    } else { it += 16; ng++; }
                }
            }
        } else if (w == 2) {
            const unsigned ep = lds32(sb + G_BAR + 248);
#pragma unroll 1
            for (int blk = 0; blk < 16; blk++) {
                bar_arrive(13, 288);
                bar_sync(12, 288);
                if (kq) { wait_flag(&g_flag[F_OUT + (blk * 9 + nt) * 8], ep); asm volatile("fence.proxy.async.global;" ::: "memory"); }
                unsigned t0 = clk();
                if (blk < 15) spin_until(t0, b * (RED_GAP / 36));
#pragma unroll 1
                for (int i = 0; i < 4; i++) {
                    const uint32_t src = sb + G_OUT + i * 8192;
                    const int c0 = DM + 64 * nt + (i & 1) * 32, c1 = blk * 128 + (i >> 1) * 64;
                    if (kq) {
                        asm volatile("{\n.reg .pred p;\nelect.sync _|p, 0xffffffff;\n@p cp.reduce.async.bulk.tensor.2d.global.shared::cta.add.bulk_group [%0, {%2, %3}], [%1];\n}"
                            :: "l"(&tm_out), "r"(src), "r"(c0), "r"(c1) : "memory");
                        t0 = clk();
                        if (blk < 15 && i < 3) spin_until(t0, RED_GAP);
                    } else {
                        asm volatile("{\n.reg .pred p;\nelect.sync _|p, 0xffffffff;\n@p cp.async.bulk.tensor.2d.global.shared::cta.bulk_group [%0, {%2, %3}], [%1];\n}"
                            :: "l"(&tm_out), "r"(src), "r"(c0), "r"(c1) : "memory");
                    }
                }
                asm volatile("cp.async.bulk.commit_group;\ncp.async.bulk.wait_group 0;\nfence.proxy.async.global;" ::: "memory");
                __syncwarp();
                if (!kq) flag_inc_if(lane, &g_flag[F_OUT + (blk * 9 + nt) * 8]);
            }
        }
    } else {
        asm volatile("setmaxnreg.inc.sync.aligned.u32 240;");
        const int g = lane >> 2, t = lane & 3, tid = threadIdx.x;
        uint32_t a[144];
        float d[64];
        if (b < 18) {
            if (tid < 64)
                asm volatile("cp.async.bulk.shared::cluster.global.mbarrier::complete_tx::bytes [%0], [%1], 1152, [%2];"
                    :: "r"(sb + tid * 1168), "l"((tid < 32 ? Bre : Bim) + (size_t)(32 * b + (tid & 31)) * DM), "r"(sb + GB_W) : "memory");
            float2 lam, coef;
            s5_channel(32 * b + 8 * w + g, Lre, Lim, logdt, lam, coef);
            float2 l32 = lam;
#pragma unroll
            for (int i = 0; i < 5; i++) l32 = make_float2(l32.x * l32.x - l32.y * l32.y, 2.f * l32.x * l32.y);
            __syncwarp();
            mbar_wait(sb + GB_W, 0);
            const uint32_t ap = sb + (((lane >> 3) & 1) * 32 + 8 * w + (lane & 7)) * 1168 + (lane >> 4) * 16;
#pragma unroll
            for (int ks = 0; ks < 36; ks++) { const uint4 v = ldsm4(ap + ks * 32); a[4 * ks] = v.x; a[4 * ks + 1] = v.y; a[4 * ks + 2] = v.z; a[4 * ks + 3] = v.w; }
            bar_sync(1, 256);
            bar_arrive(6, 288);
            BSTAMP(1);
#pragma unroll 1
            for (int blk = wg; blk < 16; blk += 2) {
                bg_mainloop<9, 2>(d, a, sb, (blk >> 1) * 18 + wg, lane);
                float2 e = make_float2(0.f, 0.f);
#pragma unroll
                for (int i = 0; i < 32; i++) e = cfma(lam, e, make_float2(d[4 * (i >> 1) + (i & 1)], d[4 * (i >> 1) + 2 + (i & 1)]));
                float2 cin = make_float2(0.f, 0.f);
                if (blk > 0) { bar_sync(2 + (wg ^ 1), 256); cin = lds64f(sb + G_CARRY + (wg ^ 1) * 256 + (8 * w + g) * 8); }
                float2 mine = cin;
#pragma unroll
                for (int q = 0; q < 4; q++) {
                    const float2 eq = make_float2(__shfl_sync(~0u, e.x, (lane & 28) + q), __shfl_sync(~0u, e.y, (lane & 28) + q));
                    cin = cfma(l32, cin, eq);
                    if (t == q + 1) mine = cin;
                }
                if (blk < 15) {
                    if (t == 0) sts64(sb + G_CARRY + wg * 256 + (8 * w + g) * 8, __float_as_uint(cin.x), __float_as_uint(cin.y));
                    bar_arrive(2 + wg, 256);
                }
                const uint32_t hs = sb + G_OUT + wg * 16384 + t * 4096 + (g & 3) * 4;
                const uint32_t ch = 2 * w + (g >> 2);
                if (blk >= 2) bar_sync(10 + wg, 160);
#pragma unroll
                for (int i = 0; i < 32; i++) {
                    mine = cfma(lam, mine, make_float2(d[4 * (i >> 1) + (i & 1)], d[4 * (i >> 1) + 2 + (i & 1)]));
                    sts32(hs + i * 128 + ((ch ^ (i & 7)) << 4), pack_bf16(mine.x, mine.y));
                }
                fence_async_smem();
                bar_arrive(8 + wg, 160);
            }
            bar_sync(10 + wg, 160);
        } else {
            if (tid < 128)
                asm volatile("cp.async.bulk.shared::cluster.global.mbarrier::complete_tx::bytes [%0], [%1], 1152, [%2];"
                    :: "r"(sb + tid * 1168), "l"((tid < 64 ? Cre : Cim) + (size_t)(64 * nt + (tid & 63)) * DM), "r"(sb + GB_W) : "memory");
            for (int p = tid; p < DM; p += 256) {
                float2 lam, coef;
                s5_channel(p, Lre, Lim, logdt, lam, coef);
                sts64(sb + G_EX + p * 8, __float_as_uint(2.f * coef.x), __float_as_uint(2.f * coef.y));
            }
            bar_sync(1, 256);
            mbar_wait(sb + GB_W, 0);
            const uint32_t cp = sb + (16 * w + 2 * g) * 1168 + (288 * wg + t) * 2;
#pragma unroll
            for (int u = 0; u < 72; u++) {
                const float2 c2 = lds64f(sb + G_EX + (288 * wg + 4 * u + t) * 8);
#pragma unroll
                for (int f = 0; f < 2; f++) {
                    unsigned short r16, i16;
                    asm volatile("ld.shared.u16 %0, [%1];" : "=h"(r16) : "r"(cp + f * 1168 + u * 8) : "memory");
                    asm volatile("ld.shared.u16 %0, [%1];" : "=h"(i16) : "r"(cp + (64 + f) * 1168 + u * 8) : "memory");
                    const float cr = __uint_as_float((uint32_t)r16 << 16), ci = __uint_as_float((uint32_t)i16 << 16);
                    a[2 * u + f] = pack_bf16(cr * c2.x - ci * c2.y, -(cr * c2.y + ci * c2.x));
                }
            }
            bar_sync(1, 256);
            bar_arrive(6, 288);
            BSTAMP(1);
#pragma unroll 1
            for (int j = 0; j < 8; j++) {
                bg_mainloop<9, 2>(d, a, sb, j * 18 + wg, lane);
                bg_epilogue<true>(d, sb, wg, w, lane, &tm_out, 64 * nt, (2 * j + kq - 2) * 128, xa, Dk);
            }
        }
        if (w == 0) asm volatile("cp.async.bulk.wait_group 0;" ::: "memory");
        bar_sync(1, 256);
        BSTAMP(2);
        if (warp == 0)
            asm volatile("{\n.reg .pred p;\nelect.sync _|p, 0xffffffff;\n@p mbarrier.arrive.expect_tx.shared::cta.b64 _, [%2], 131072;\n"
                "@p cp.async.bulk.tensor.2d.shared::cluster.global.mbarrier::complete_tx::bytes [%0], [%1, {%3, %4}], [%2];\n"
                "@p cp.async.bulk.tensor.2d.shared::cluster.global.mbarrier::complete_tx::bytes [%0+32768], [%1, {%3, %5}], [%2];\n"
                "@p cp.async.bulk.tensor.2d.shared::cluster.global.mbarrier::complete_tx::bytes [%0+65536], [%1, {%3, %6}], [%2];\n"
                "@p cp.async.bulk.tensor.2d.shared::cluster.global.mbarrier::complete_tx::bytes [%0+98304], [%1, {%3, %7}], [%2];\n}"
                :: "r"(sb), "l"(&tm_wo), "r"(sb + GB_W), "r"(64 * nt), "r"(1024 * kq), "r"(1024 * kq + 256), "r"(1024 * kq + 512), "r"(1024 * kq + 768) : "memory");
        mbar_wait(sb + GB_W, 1);
        {
            const uint32_t base = sb + wg * 65536 + 4 * t * 128 + (g & 3) * 4, ch = 2 * w + (g >> 2), r7 = (4 * t) & 7;
#pragma unroll
            for (int ks = 0; ks < 32; ks++) {
                const uint32_t w0 = lds32(base + ks * 2048 + ((ch ^ r7) << 4)), w1 = lds32(base + ks * 2048 + 256 + ((ch ^ (r7 + 2)) << 4));
                const uint32_t w2 = lds32(base + ks * 2048 + 128 + ((ch ^ (r7 + 1)) << 4)), w3 = lds32(base + ks * 2048 + 384 + ((ch ^ (r7 + 3)) << 4));
                a[4 * ks] = __byte_perm(w0, w1, 0x5410); a[4 * ks + 1] = __byte_perm(w0, w1, 0x7632);
                a[4 * ks + 2] = __byte_perm(w2, w3, 0x5410); a[4 * ks + 3] = __byte_perm(w2, w3, 0x7632);
            }
        }
        bar_sync(1, 256);
        bar_arrive(6, 288);
        BSTAMP(3);
#pragma unroll 1
        for (int na = 0, ng = 0, it = 144; ng < 16;) {
            if (bg_att_turn(na, ng)) {
                if (nt < 8) {
                    const int i0 = it + wg + 4 * (w >> 1), i1 = i0 + 2;
                    mbar_wait(sb + GB_FULL + 8 * (i0 % NST), (i0 / NST) & 1);
                    mbar_wait(sb + GB_FULL + 8 * (i1 % NST), (i1 / NST) & 1);
                    BSTAMP(8 + na * 4);
                    bg_attention(sb + G_RING + (i0 % NST) * 16384, sb + G_RING + (i1 % NST) * 16384, w & 1, lane);
                    fence_async_smem();
                    bar_arrive(7, 288);
                    bar_sync(1, 256);
                    BSTAMP(9 + na * 4);
                    it += 8;
                }
                na++;
            } else {
                bg_mainloop<8, 2>(d, a, sb, it + wg, lane);
                BSTAMP(10 + ng * 4);
                bg_epilogue<false>(d, sb, wg, w, lane, &tm_out, DM + 64 * nt, ng * 128, xa, Dk);
                BSTAMP(11 + ng * 4);
                it += 16; ng++;
            }
        }
    }
    asm volatile("griddepcontrol.wait;" ::: "memory");
}

typedef CUresult (*EncodeFn)(CUtensorMap*, CUtensorMapDataType, cuuint32_t, void*, const cuuint64_t*, const cuuint64_t*, const cuuint32_t*, const cuuint32_t*,
                             CUtensorMapInterleave, CUtensorMapSwizzle, CUtensorMapL2promotion, CUtensorMapFloatOOBfill);
}

extern "C" void kernel_launch(void* const* d_in, const int* in_sizes, int n_in, void* d_out, int out_size) {
    typedef const __nv_bfloat16* bp;
    bp Ax = (bp)d_in[0], Lre = (bp)d_in[1], Lim = (bp)d_in[2], Bre = (bp)d_in[3], Bim = (bp)d_in[4], Cre = (bp)d_in[5], Cim = (bp)d_in[6],
       logdt = (bp)d_in[7], Dk = (bp)d_in[8], Bx = (bp)d_in[9], mem0 = (bp)d_in[10], Wq = (bp)d_in[11], Wk = (bp)d_in[12], Wv = (bp)d_in[13], Wo = (bp)d_in[14];
    float* out = (float*)d_out;
    static EncodeFn enc = nullptr;
    if (!enc) {
        void* fn = nullptr; cudaDriverEntryPointQueryResult qr;
        cudaGetDriverEntryPoint("cuTensorMapEncodeTiled", &fn, cudaEnableDefault, &qr);
        enc = (EncodeFn)fn;
        cudaFuncSetAttribute(chain_kernel, cudaFuncAttributeMaxDynamicSharedMemorySize, CHAIN_SMEM);
        cudaFuncSetAttribute(bg_kernel, cudaFuncAttributeMaxDynamicSharedMemorySize, BG_SMEM);
    }
    const cuuint32_t es[5] = {1, 1, 1, 1, 1};
    auto map2d = [&](CUtensorMap* tm, CUtensorMapDataType dt, const void* p, cuuint64_t d0, cuuint64_t d1, cuuint64_t stride, cuuint32_t b0, cuuint32_t b1) {
        cuuint64_t gd[2] = {d0, d1}, gs[1] = {stride}; cuuint32_t bd[2] = {b0, b1};
        enc(tm, dt, 2, (void*)p, gd, gs, bd, es, CU_TENSOR_MAP_INTERLEAVE_NONE, CU_TENSOR_MAP_SWIZZLE_128B, CU_TENSOR_MAP_L2_PROMOTION_L2_128B,
            CU_TENSOR_MAP_FLOAT_OOB_FILL_NONE);
    };
    CUtensorMap tm_x, tm_q, tm_k, tm_v, tm_xa, tm_wo, tm_out;
    map2d(&tm_x, CU_TENSOR_MAP_DATA_TYPE_BFLOAT16, Bx, DM, SEQ, DM * 2, 64, 32);
    map2d(&tm_q, CU_TENSOR_MAP_DATA_TYPE_BFLOAT16, Wq, HD, DM, HD * 2, 64, 192);
    map2d(&tm_k, CU_TENSOR_MAP_DATA_TYPE_BFLOAT16, Wk, HD, DM, HD * 2, 64, 192);
    map2d(&tm_v, CU_TENSOR_MAP_DATA_TYPE_BFLOAT16, Wv, HD, DM, HD * 2, 64, 192);
    map2d(&tm_wo, CU_TENSOR_MAP_DATA_TYPE_BFLOAT16, Wo, DM, HD, DM * 2, 64, 256);
    map2d(&tm_out, CU_TENSOR_MAP_DATA_TYPE_FLOAT32, out, 2 * DM, SEQ, 2 * DM * 4, 32, 64);
    {
        cuuint64_t gd[5] = {DM, 2, 4, 16, 16}, gs[4] = {DM * 2, 32 * DM * 2, 2 * DM * 2, 128 * DM * 2}; cuuint32_t bd[5] = {64, 2, 4, 16, 1};
        enc(&tm_xa, CU_TENSOR_MAP_DATA_TYPE_BFLOAT16, 5, (void*)Ax, gd, gs, bd, es, CU_TENSOR_MAP_INTERLEAVE_NONE, CU_TENSOR_MAP_SWIZZLE_128B,
            CU_TENSOR_MAP_L2_PROMOTION_L2_128B, CU_TENSOR_MAP_FLOAT_OOB_FILL_NONE);
    }
    cudaStream_t st = cudaStreamPerThread;
    chain_kernel<<<96, 384, CHAIN_SMEM, st>>>(tm_x, tm_q, tm_k, tm_v, Bx, mem0, Wo);
    cudaLaunchConfig_t cfg = {};
    cfg.gridDim = dim3(36); cfg.blockDim = dim3(384); cfg.dynamicSmemBytes = BG_SMEM; cfg.stream = st;
    cudaLaunchAttribute at[1];
    at[0].id = cudaLaunchAttributeProgrammaticStreamSerialization; at[0].val.programmaticStreamSerializationAllowed = 1;
    cfg.attrs = at; cfg.numAttrs = 1;
    cudaLaunchKernelEx(&cfg, bg_kernel, tm_xa, tm_wo, tm_out, Ax, Lre, Lim, Bre, Bim, Cre, Cim, logdt, Dk);
}
```

```cpp
#include <cuda_runtime.h>
#include <cuda.h>
#include <cuda_bf16.h>
#include <cuda_fp16.h>
#include <stdint.h>

#define D_WAIT 740

#define BG_PACE 0
#define RED_GAP 720
#define ACC_PF 1
#define QDEP 0
#define BG_AHEAD 5

namespace {

constexpr int DM = 576, NH = 32, SEQ = 2048, NSEG = 64, HD = 4096;

__device__ uint4 g_acc_raw[64 * 96 * 16 + 131072];
__device__ uint4 g_ox[NH * 2 * SEQ * 8];
constexpr int REC = 30720;
__device__ uint4 g_qkv[NSEG * NH * (REC / 16)];
__device__ uint4 g_h[18 * SEQ * 8];
constexpr int NFLAG = 4096, F_QKV = 0, F_OX = 512, F_H = 1024, F_OUT = 2048;
__device__ unsigned g_flag[NFLAG];
__device__ unsigned g_ticket, g_ticket_bg;
__device__ unsigned long long g_norm[96];
#define BSTAMP(i) do {} while (0)

__device__ __forceinline__ uint32_t smem_u32(const void* p) { return (uint32_t)__cvta_generic_to_shared(p); }
__device__ __forceinline__ uint32_t mapa(uint32_t a, uint32_t r) { uint32_t o; asm("mapa.shared::cluster.u32 %0, %1, %2;" : "=r"(o) : "r"(a), "r"(r)); return o; }
__device__ __forceinline__ uint32_t mapa_v(uint32_t a, uint32_t r) { uint32_t o; asm volatile("mapa.shared::cluster.u32 %0, %1, %2;" : "=r"(o) : "r"(a), "r"(r)); return o; }
__device__ __forceinline__ unsigned clk() { unsigned long long c; asm volatile("mov.u64 %0, %%clock64;" : "=l"(c) :: "memory"); return (unsigned)c; }
__device__ __forceinline__ void mbar_init(uint32_t bar, uint32_t cnt) { asm volatile("mbarrier.init.shared::cta.b64 [%0], %1;" :: "r"(bar), "r"(cnt) : "memory"); }
__device__ __forceinline__ void mbar_expect(uint32_t bar, uint32_t bytes) { asm volatile("mbarrier.arrive.expect_tx.shared::cta.b64 _, [%0], %1;" :: "r"(bar), "r"(bytes) : "memory"); }
__device__ __forceinline__ void mbar_wait(uint32_t bar, uint32_t parity) {
    asm volatile("{\n.reg .pred p;\n.reg .u32 n;\nmov.u32 n, 0;\n"
                 "W_%=: mbarrier.try_wait.parity.shared::cta.b64 p, [%0], %1;\n@p bra.uni D_%=;\n"
                 "add.u32 n, n, 1;\nsetp.lt.u32 p, n, 4000000;\n@p bra.uni W_%=;\ntrap;\nD_%=:\n}" :: "r"(bar), "r"(parity) : "memory");
}
__device__ __forceinline__ void mbar_expect_if(uint32_t z, uint32_t bar, uint32_t bytes) {
    asm volatile("{\n.reg .pred p;\nsetp.eq.u32 p, %2, 0;\n@p mbarrier.arrive.expect_tx.shared::cta.b64 _, [%0], %1;\n}" :: "r"(bar), "r"(bytes), "r"(z) : "memory");
}
__device__ __forceinline__ void mbar_arrive_if(uint32_t z, uint32_t bar) {
    asm volatile("{\n.reg .pred p;\nsetp.eq.u32 p, %1, 0;\n@p mbarrier.arrive.shared::cta.b64 _, [%0];\n}" :: "r"(bar), "r"(z) : "memory");
}
__device__ __forceinline__ void sts32_if(uint32_t z, uint32_t a, uint32_t x) {
    asm volatile("{\n.reg .pred p;\nsetp.eq.u32 p, %2, 0;\n@p st.shared.u32 [%0], %1;\n}" :: "r"(a), "r"(x), "r"(z) : "memory");
}
template <int K> __device__ __forceinline__ void sched_fence(int v) {
    asm volatile("{\n.reg .pred p;\nsetp.ne.s32 p, %0, %1;\n@p bra.uni F_%=;\ntrap;\nF_%=:\n}" :: "r"(v), "n"(1000 + K) : "memory");
}
__device__ __forceinline__ void spin_until(unsigned t0, unsigned d) {
    asm volatile("{\n.reg .pred p;\n.reg .u64 c;\n.reg .u32 lo;\n"
                 "S_%=: mov.u64 c, %%clock64;\ncvt.u32.u64 lo, c;\nsub.u32 lo, lo, %0;\nsetp.lt.u32 p, lo, %1;\n@p bra.uni S_%=;\n}" :: "r"(t0), "r"(d) : "memory");
}
__device__ __forceinline__ void bar_sync(int id, int n) { asm volatile("bar.sync %0, %1;" :: "r"(id), "r"(n) : "memory"); }
__device__ __forceinline__ void bar_sync_sel(int sel, int id) {
    asm volatile("{\n.reg .pred p;\nsetp.eq.u32 p, %0, 0;\n@p bar.sync %1, %3;\n@!p bar.sync %2, %3;\n}" :: "r"(sel), "r"(id), "r"(id + 1), "n"(192) : "memory");
}
__device__ __forceinline__ void bar_arrive(int id, int n) { asm volatile("bar.arrive %0, %1;" :: "r"(id), "r"(n) : "memory"); }
__device__ __forceinline__ void fence_async_smem() { asm volatile("fence.proxy.async.shared::cta;" ::: "memory"); }
__device__ __forceinline__ uint32_t pack_bf16(float lo, float hi) { uint32_t r; asm("cvt.rn.bf16x2.f32 %0, %1, %2;" : "=r"(r) : "f"(hi), "f"(lo)); return r; }
__device__ __forceinline__ uint32_t pack_f16(float lo, float hi) { uint32_t r; asm("cvt.rn.f16x2.f32 %0, %1, %2;" : "=r"(r) : "f"(hi), "f"(lo)); return r; }
__device__ __forceinline__ uint32_t f16x2_to_bf16x2(uint32_t v) { float2 f = __half22float2(*reinterpret_cast<__half2*>(&v)); return pack_bf16(f.x, f.y); }
__device__ __forceinline__ uint32_t hmul2(uint32_t a, uint32_t b) { uint32_t r; asm("mul.rn.f16x2 %0, %1, %2;" : "=r"(r) : "r"(a), "r"(b)); return r; }
__device__ __forceinline__ float ex2(float x) { float y; asm("ex2.approx.ftz.f32 %0, %1;" : "=f"(y) : "f"(x)); return y; }
__device__ __forceinline__ float ex2v(float x) { float y; asm volatile("ex2.approx.ftz.f32 %0, %1;" : "=f"(y) : "f"(x)); return y; }
__device__ __forceinline__ uint32_t absmax2(uint32_t a, uint32_t b) {
    uint32_t r; asm("max.xorsign.abs.bf16x2 %0, %1, %2;" : "=r"(r) : "r"(a), "r"(b)); return r;
}
__device__ __forceinline__ uint32_t shl_v(uint32_t a, int n) { return a << n; }
__device__ __forceinline__ uint32_t max3u(uint32_t a, uint32_t b, uint32_t c) { return max(max(a, b), c); }
__device__ __forceinline__ uint4 lds128(uint32_t a) { uint4 v; asm volatile("ld.shared.v4.u32 {%0,%1,%2,%3}, [%4];" : "=r"(v.x), "=r"(v.y), "=r"(v.z), "=r"(v.w) : "r"(a) : "memory"); return v; }
__device__ __forceinline__ uint4 lds128v(uint32_t a) { uint4 v; asm volatile("ld.volatile.shared.v4.u32 {%0,%1,%2,%3}, [%4];" : "=r"(v.x), "=r"(v.y), "=r"(v.z), "=r"(v.w) : "r"(a) : "memory"); return v; }
__device__ __forceinline__ float4 lds128f(uint32_t a) { float4 v; asm volatile("ld.shared.v4.f32 {%0,%1,%2,%3}, [%4];" : "=f"(v.x), "=f"(v.y), "=f"(v.z), "=f"(v.w) : "r"(a) : "memory"); return v; }
__device__ __forceinline__ float2 lds64f(uint32_t a) { float2 v; asm volatile("ld.shared.v2.f32 {%0,%1}, [%2];" : "=f"(v.x), "=f"(v.y) : "r"(a) : "memory"); return v; }
__device__ __forceinline__ uint4 lds64x2(uint32_t a) { uint4 v; asm volatile("ld.shared.v2.u32 {%0,%1}, [%4];\nld.shared.v2.u32 {%2,%3}, [%4+256];" : "=r"(v.x), "=r"(v.y), "=r"(v.z), "=r"(v.w) : "r"(a) : "memory"); return v; }
__device__ __forceinline__ uint32_t lds32(uint32_t a) { uint32_t v; asm volatile("ld.shared.u32 %0, [%1];" : "=r"(v) : "r"(a) : "memory"); return v; }
__device__ __forceinline__ void sts128(uint32_t a, uint32_t x, uint32_t y, uint32_t z, uint32_t w) { asm volatile("st.shared.v4.u32 [%0], {%1,%2,%3,%4};" :: "r"(a), "r"(x), "r"(y), "r"(z), "r"(w) : "memory"); }
__device__ __forceinline__ void sts128f(uint32_t a, float x, float y, float z, float w) { asm volatile("st.shared.v4.f32 [%0], {%1,%2,%3,%4};" :: "r"(a), "f"(x), "f"(y), "f"(z), "f"(w) : "memory"); }
__device__ __forceinline__ void sts64(uint32_t a, uint32_t x, uint32_t y) { asm volatile("st.shared.v2.u32 [%0], {%1,%2};" :: "r"(a), "r"(x), "r"(y) : "memory"); }
__device__ __forceinline__ void sts32(uint32_t a, uint32_t x) { asm volatile("st.shared.u32 [%0], %1;" :: "r"(a), "r"(x) : "memory"); }
__device__ __forceinline__ uint4 ldsm4(uint32_t a) { uint4 v; asm volatile("ldmatrix.sync.aligned.m8n8.x4.shared.b16 {%0,%1,%2,%3}, [%4];" : "=r"(v.x), "=r"(v.y), "=r"(v.z), "=r"(v.w) : "r"(a) : "memory"); return v; }
__device__ __forceinline__ void stsm2t(uint32_t a, uint32_t x, uint32_t y) { asm volatile("stmatrix.sync.aligned.m8n8.x2.trans.shared.b16 [%0], {%1,%2};" :: "r"(a), "r"(x), "r"(y) : "memory"); }
__device__ __forceinline__ void stsm4t(uint32_t a, uint32_t x, uint32_t y, uint32_t z, uint32_t w) { asm volatile("stmatrix.sync.aligned.m8n8.x4.trans.shared.b16 [%0], {%1,%2,%3,%4};" :: "r"(a), "r"(x), "r"(y), "r"(z), "r"(w) : "memory"); }
__device__ __forceinline__ void st_async64(uint32_t a, uint32_t x, uint32_t y, uint32_t bar) { asm volatile("st.async.shared::cluster.mbarrier::complete_tx::bytes.v2.b32 [%0], {%1,%2}, [%3];" :: "r"(a), "r"(x), "r"(y), "r"(bar) : "memory"); }
__device__ __forceinline__ void bulk_s2c(uint32_t dst, uint32_t src, uint32_t bytes, uint32_t bar) { asm volatile("cp.async.bulk.shared::cluster.shared::cta.mbarrier::complete_tx::bytes [%0], [%1], %2, [%3];" :: "r"(dst), "r"(src), "r"(bytes), "r"(bar) : "memory"); }
__device__ __forceinline__ void bulk_s2g(void* dst, uint32_t src, uint32_t bytes) { asm volatile("cp.async.bulk.global.shared::cta.bulk_group [%0], [%1], %2;" :: "l"(dst), "r"(src), "r"(bytes) : "memory"); }
__device__ __forceinline__ uint32_t ldg_nc32(const void* p) { uint32_t v; asm volatile("ld.global.nc.L2::128B.u32 %0, [%1];" : "=r"(v) : "l"(p)); return v; }
__device__ __forceinline__ uint4 ldg_relaxed128(const void* p) { uint4 v; asm volatile("ld.relaxed.gpu.global.v4.u32 {%0,%1,%2,%3}, [%4];" : "=r"(v.x), "=r"(v.y), "=r"(v.z), "=r"(v.w) : "l"(p) : "memory"); return v; }
__device__ __forceinline__ void mma16816(float (&d)[4], uint32_t a0, uint32_t a1, uint32_t a2, uint32_t a3, uint32_t b0, uint32_t b1) {
    asm volatile("mma.sync.aligned.m16n8k16.row.col.f32.bf16.bf16.f32 {%0,%1,%2,%3}, {%4,%5,%6,%7}, {%8,%9}, {%0,%1,%2,%3};"
        : "+f"(d[0]), "+f"(d[1]), "+f"(d[2]), "+f"(d[3]) : "r"(a0), "r"(a1), "r"(a2), "r"(a3), "r"(b0), "r"(b1));
}
__device__ __forceinline__ void mma16816_z(float (&d)[4], uint32_t a0, uint32_t a1, uint32_t a2, uint32_t a3, uint32_t b0, uint32_t b1) {
    asm volatile("mma.sync.aligned.m16n8k16.row.col.f32.bf16.bf16.f32 {%0,%1,%2,%3}, {%4,%5,%6,%7}, {%8,%9}, {%10,%10,%10,%10};"
        : "=f"(d[0]), "=f"(d[1]), "=f"(d[2]), "=f"(d[3]) : "r"(a0), "r"(a1), "r"(a2), "r"(a3), "r"(b0), "r"(b1), "f"(0.f));
}
__device__ __forceinline__ void mma1688(float (&d)[4], uint32_t a0, uint32_t a1, uint32_t b0) {
    asm volatile("mma.sync.aligned.m16n8k8.row.col.f32.bf16.bf16.f32 {%0,%1,%2,%3}, {%4,%5}, {%6}, {%0,%1,%2,%3};"
        : "+f"(d[0]), "+f"(d[1]), "+f"(d[2]), "+f"(d[3]) : "r"(a0), "r"(a1), "r"(b0));
}
__device__ __forceinline__ void mma1688_z(float (&d)[4], uint32_t a0, uint32_t a1, uint32_t b0) {
    asm volatile("mma.sync.aligned.m16n8k8.row.col.f32.bf16.bf16.f32 {%0,%1,%2,%3}, {%4,%5}, {%6}, {%7,%7,%7,%7};"
        : "=f"(d[0]), "=f"(d[1]), "=f"(d[2]), "=f"(d[3]) : "r"(a0), "r"(a1), "r"(b0), "f"(0.f));
}
template <int ACC>
__device__ __forceinline__ void wgmma_n32_rs(float (&d)[16], uint32_t a0, uint32_t a1, uint32_t a2, uint32_t a3, uint64_t desc) {
    asm volatile("wgmma.mma_async.sync.aligned.m64n32k16.f32.bf16.bf16 {%0,%1,%2,%3,%4,%5,%6,%7,%8,%9,%10,%11,%12,%13,%14,%15}, {%16,%17,%18,%19}, %20, %21, 1, 1, 0;"
        : "+f"(d[0]), "+f"(d[1]), "+f"(d[2]), "+f"(d[3]), "+f"(d[4]), "+f"(d[5]), "+f"(d[6]), "+f"(d[7]),
          "+f"(d[8]), "+f"(d[9]), "+f"(d[10]), "+f"(d[11]), "+f"(d[12]), "+f"(d[13]), "+f"(d[14]), "+f"(d[15])
        : "r"(a0), "r"(a1), "r"(a2), "r"(a3), "l"(desc), "n"(ACC));
}
template <int ACC>
__device__ __forceinline__ void wgmma_n32_ss(float (&d)[16], uint64_t da, uint64_t db) {
    asm volatile("wgmma.mma_async.sync.aligned.m64n32k16.f32.bf16.bf16 {%0,%1,%2,%3,%4,%5,%6,%7,%8,%9,%10,%11,%12,%13,%14,%15}, %16, %17, %18, 1, 1, 0, 0;"
        : "+f"(d[0]), "+f"(d[1]), "+f"(d[2]), "+f"(d[3]), "+f"(d[4]), "+f"(d[5]), "+f"(d[6]), "+f"(d[7]),
          "+f"(d[8]), "+f"(d[9]), "+f"(d[10]), "+f"(d[11]), "+f"(d[12]), "+f"(d[13]), "+f"(d[14]), "+f"(d[15])
        : "l"(da), "l"(db), "n"(ACC));
}
__device__ __forceinline__ void wg_fence() { asm volatile("wgmma.fence.sync.aligned;" ::: "memory"); }
__device__ __forceinline__ void wg_commit() { asm volatile("wgmma.commit_group.sync.aligned;" ::: "memory"); }
__device__ __forceinline__ void wg_wait0() { asm volatile("wgmma.wait_group.sync.aligned 0;" ::: "memory"); }
__device__ __forceinline__ void cluster_sync() { asm volatile("barrier.cluster.arrive.aligned;\nbarrier.cluster.wait.aligned;" ::: "memory"); }

#define STAMP(s, i) do {} while (0)
#define STAMPV(s, i, v) do {} while (0)

constexpr int XT_BYTES = 36864;
constexpr int O_XT = 0;
constexpr int O_STG = XT_BYTES;
constexpr int O_AS = 3 * XT_BYTES;
constexpr int O_XP = O_AS + 16384;
constexpr int O_QKX = O_XP + 8192;
constexpr int O_KM = O_QKX + 8192;
constexpr int O_QM = O_QKX + 10240;
constexpr int O_VX = O_STG + 147456;
constexpr int O_VM = O_VX + 16384;
constexpr int O_SC = O_VM + 2048;
constexpr int O_OF = O_SC + 2560;
constexpr int O_AF = O_OF + 2048;
constexpr int O_WP = O_AF + 4096;
constexpr int O_MF = O_WP + 2048;
constexpr int O_MISC = O_MF + 9216;
static_assert(O_QKX + 24576 <= O_VX, "smem");
constexpr int O_BAR = O_MISC + 64;
constexpr int CHAIN_SMEM = O_BAR + 128;
static_assert(CHAIN_SMEM <= 232448, "smem");
constexpr int B_X = O_BAR, B_VX = O_BAR + 24, B_SC = O_BAR + 40, B_W = O_BAR + 48;
constexpr float SM_SCALE = 0.08838834764831845f * 1.4426950408889634f;
constexpr uint32_t ONES = 0x3f803f80u;

__device__ __forceinline__ uint32_t opaque(uint32_t v) { uint32_t o; asm volatile("mov.u32 %0, %1;" : "=r"(o) : "r"(v)); return o; }
__device__ __forceinline__ void st_async128(uint32_t a, uint32_t x, uint32_t y, uint32_t z, uint32_t w, uint32_t bar) {
    asm volatile("st.async.shared::cluster.mbarrier::complete_tx::bytes.v4.b32 [%0], {%1,%2,%3,%4}, [%5];" :: "r"(a), "r"(x), "r"(y), "r"(z), "r"(w), "r"(bar) : "memory");
}
__device__ __forceinline__ void tma_x_tile(uint32_t sb, const CUtensorMap* tm, int r, int j, int slot) {
    asm volatile("{\n.reg .pred p;\nelect.sync _|p, 0xffffffff;\n"
        "@p mbarrier.arrive.expect_tx.shared::cta.b64 _, [%2], 36864;\n"
        "@p cp.async.bulk.tensor.2d.shared::cluster.global.mbarrier::complete_tx::bytes.multicast::cluster [%0], [%1, {%3, %4}], [%2], %7;\n"
        "@p cp.async.bulk.tensor.2d.shared::cluster.global.mbarrier::complete_tx::bytes.multicast::cluster [%0+4096], [%1, {%5, %4}], [%2], %7;\n"
        "@p cp.async.bulk.tensor.2d.shared::cluster.global.mbarrier::complete_tx::bytes.multicast::cluster [%0+8192], [%1, {%6, %4}], [%2], %7;\n}"
        :: "r"(sb + O_XT + slot * XT_BYTES + 3 * r * 4096), "l"(tm), "r"(sb + B_X + 8 * slot), "r"(192 * r), "r"(j * 32), "r"(192 * r + 64), "r"(192 * r + 128),
           "h"((unsigned short)7) : "memory");
}
__device__ __forceinline__ void flag_inc_if(uint32_t z, unsigned* p) {
    asm volatile("{\n.reg .pred p;\nsetp.eq.u32 p, %1, 0;\n@p red.release.gpu.global.inc.u32 [%0], 0xfffffffe;\n}" :: "l"(p), "r"(z) : "memory");
}
__device__ __forceinline__ float quad_max(float v) {
    const float a = __shfl_xor_sync(~0u, v, 1), b = __shfl_xor_sync(~0u, v, 2), c = __shfl_xor_sync(~0u, v, 3);
    return fmaxf(fmaxf(v, a), fmaxf(b, c));
}
__device__ __forceinline__ void load_scores(float (&p)[10], uint32_t base, uint32_t stride, uint32_t l16) {
    const float4 a0 = lds128f(base + l16), b0 = lds128f(base + stride + l16);
    const float4 a1 = lds128f(base + 512 + l16), b1 = lds128f(base + stride + 512 + l16);
    const float2 a2 = lds64f(base + 1024 + (l16 >> 1)), b2 = lds64f(base + stride + 1024 + (l16 >> 1));
    p[0] = a2.x + b2.x; p[1] = a2.y + b2.y;
    p[2] = a0.x + b0.x; p[3] = a0.y + b0.y; p[4] = a0.z + b0.z; p[5] = a0.w + b0.w;
    p[6] = a1.x + b1.x; p[7] = a1.y + b1.y; p[8] = a1.z + b1.z; p[9] = a1.w + b1.w;
}
__device__ __forceinline__ float rcp_fast(float x) { float y; asm("rcp.approx.ftz.f32 %0, %1;" : "=f"(y) : "f"(x)); return y; }

__global__ void __cluster_dims__(3, 1, 1) __launch_bounds__(384, 1)
chain_kernel(const __grid_constant__ CUtensorMap tm_x, const __grid_constant__ CUtensorMap tm_q,
             const __grid_constant__ CUtensorMap tm_k, const __grid_constant__ CUtensorMap tm_v,
             const __nv_bfloat16* __restrict__ x, const __nv_bfloat16* __restrict__ mem0,
             const __nv_bfloat16* __restrict__ Wo) {
    extern __shared__ __align__(1024) uint8_t smem_raw[];
    const uint32_t sb = smem_u32(smem_raw);
    const int lane = threadIdx.x & 31;
    const int warp = __shfl_sync(~0u, threadIdx.x >> 5, 0);
    const int wg = warp >> 2, w = warp & 3;
    const int h = blockIdx.x / 3, r = blockIdx.x - 3 * h;
    uint4* const g_acc = reinterpret_cast<uint4*>((reinterpret_cast<uintptr_t>(g_acc_raw) + 0x1fffff) & ~(uintptr_t)0x1fffff);

#define PSTAMP(i) do {} while (0)
    if (threadIdx.x == 0) {
        if (sb & 1023u) __trap();
        for (int i = 0; i < 9; i++) mbar_init(sb + O_BAR + 8 * i, 1);
        asm volatile("fence.mbarrier_init.release.cluster;" ::: "memory");
        for (int i = 0; i < 3; i++) {
            mbar_expect(sb + B_W + 8 * i, 49152);
            for (int tl = 0; tl < 2; tl++)
                asm volatile("cp.async.bulk.tensor.2d.shared::cluster.global.mbarrier::complete_tx::bytes [%0], [%1, {%3, %4}], [%2];"
                    :: "r"(sb + O_STG + tl * 73728 + i * 24576), "l"(r < 2 ? (tl ? &tm_k : &tm_q) : &tm_v), "r"(sb + B_W + 8 * i),
                       "r"(h * 128 + 64 * (r < 2 ? r : tl)), "r"(192 * i) : "memory");
        }
    }
    __syncwarp();
    asm volatile("barrier.cluster.arrive.relaxed.aligned;" ::: "memory");
    asm volatile("griddepcontrol.launch_dependents;" ::: "memory");
    if (warp == 0) PSTAMP(9);
    const uint32_t l16c = __shfl_sync(~0u, lane * 16, lane);

    if (wg < 2) {
#define KS(u) ((u) < 8 ? 12 * ((u) >> 2) + (((u) >> 1) & 1) + 4 * ((u) & 1) : (u) < 12 ? (u) : (u) < 16 ? (u) + 8 : (u) < 24 ? 24 + (((u) - 16) >> 1) + 4 * ((u) & 1) : (u) + 8)
        asm volatile("setmaxnreg.inc.sync.aligned.u32 184;");
        uint32_t a[144];
        uint32_t adr1;
        {
            const int g = lane >> 2, t = lane & 3;
            const int t1 = threadIdx.x;
#pragma unroll
            for (int i = 0; i < 2; i++) g_acc[(blockIdx.x * 64 + i * 32 + (t1 >> 3)) * 16 + (t1 & 7)] = make_uint4(0, 0, 0, 0);
            __threadfence();
            asm volatile("barrier.cluster.wait.aligned;" ::: "memory");
            const uint32_t ev = sb + O_STG + (2 * t) * 128 + (((2 * w + (g >> 2)) ^ (2 * t)) << 4) + (g & 3) * 4;
            const uint32_t od = (ev ^ 16) + 128;
            auto gather = [&](int dst, uint32_t off) {
                a[dst] = lds32(ev + off); a[dst + 1] = lds32(od + off); a[dst + 2] = lds32(ev + off + 1024); a[dst + 3] = lds32(od + off + 1024);
            };
            const uint4* xp = reinterpret_cast<const uint4*>(x) + blockIdx.x * 1536 + t1;
            uint4 xv[6];
#pragma unroll
            for (int th = 0; th < 2; th++) {
                mbar_wait(sb + B_W + 8 * th, 0);
                if (th == 1) {
#pragma unroll
                    for (int i = 0; i < 6; i++) xv[i] = __ldg(xp + i * 256);
                }
#pragma unroll
                for (int u = 4 * th; u < 4 * th + 4; u++) {
                    gather(32 + 4 * u, wg * (73728 + 4096) + KS(u) * 2048);
                    gather(4 * u, 73728 - wg * (73728 - 4096) + KS(u) * 2048);
                    gather(64 + 4 * u, wg * 73728 + KS(8 + u) * 2048);
                }
            }
            mbar_wait(sb + B_W + 16, 0);
#pragma unroll
            for (int u = 16; u < 28; u++) gather(32 + 4 * u, wg * 73728 + KS(u) * 2048);
#pragma unroll
            for (int kk = 0; kk < 72; kk++) {
                uint32_t w0 = a[2 * kk], w1 = a[2 * kk + 1];
                a[2 * kk] = __byte_perm(w0, w1, 0x5410);
                a[2 * kk + 1] = __byte_perm(w0, w1, 0x7632);
            }
            if (r == 2) {
                float n0[4], n1[4];
#pragma unroll
                for (int u = 0; u < 36; u++) {
                    const uint32_t x0 = a[4 * u] & 0x7fff7fffu, x1 = a[4 * u + 1] & 0x7fff7fffu, x2 = a[4 * u + 2] & 0x7fff7fffu, x3 = a[4 * u + 3] & 0x7fff7fffu;
                    if (u == 0) mma16816_z(n0, x0, x1, x2, x3, ONES, ONES);
                    else if (u < 8) mma16816(n0, x0, x1, x2, x3, ONES, ONES);
                    else if (u == 8) mma16816_z(n1, x0, x1, x2, x3, ONES, ONES);
                    else mma16816(n1, x0, x1, x2, x3, ONES, ONES);
                }
                const uint32_t mx = __reduce_max_sync(~0u, __float_as_uint(2.f * fmaxf(fmaxf(n0[0], n0[2]), fmaxf(n1[0], n1[2]))));
                sts32_if(lane, sb + O_MISC + 32 + 4 * warp, mx);
            }
            uint32_t xm = 0;
#pragma unroll
            for (int i = 0; i < 6; i++)
                xm = __vmaxu2(xm, __vmaxu2(__vmaxu2(xv[i].x & 0x7fff7fffu, xv[i].y & 0x7fff7fffu), __vmaxu2(xv[i].z & 0x7fff7fffu, xv[i].w & 0x7fff7fffu)));
            sts32_if(lane, sb + O_OF + 16 + 4 * warp, __reduce_max_sync(~0u, max(xm << 16, xm & 0xffff0000u)));
            if (warp == 0) PSTAMP(11);
            bar_arrive(7, 384);
            asm volatile("barrier.cluster.arrive.relaxed.aligned;" ::: "memory");
            bar_sync(1, 256);
            const uint32_t as = sb + O_AS + wg * 8192 + (16 * w + g) * 128 + t * 4;
            sts32(as + (g << 4), a[32]);
            sts32(as + 1024 + (g << 4), a[33]);
            sts32(as + ((1 ^ g) << 4), a[34]);
            sts32(as + 1024 + ((1 ^ g) << 4), a[35]);
            sts128(sb + O_AF + warp * 512 + lane * 16, a[32], a[33], a[34], a[35]);
            fence_async_smem();
            bar_sync(1, 256);
            const uint32_t l = lane * 16;
            const int mi = lane >> 3, isk = (mi >> 1) ? wg : (wg ^ 1);
            adr1 = (r == 2) ? (sb + O_VM + warp * 256 + (l >> 1))
                            : (isk ? (sb + O_KM + w * 512 + wg * 256 + (mi & 1) * 128 + (l & 127))
                                   : (sb + O_QM + w * 512 + (mi & 1) * 256 + wg * 128 + (l & 127)));
            adr1 = __shfl_sync(~0u, adr1, lane);
        }
        int s3 = 2;
#pragma unroll 1
        for (int s = -1; s < NSEG; s++) {
            const uint32_t l16 = opaque(l16c);
            s3 = (s3 == 2) ? 0 : s3 + 1;
            if (s < 0) mbar_wait(sb + B_X, 0);
            const uint64_t desc0 = (uint64_t)(((sb + O_XT + s3 * XT_BYTES) & 0x3FFFF) >> 4) | (1ull << 16) | (64ull << 32) | (1ull << 62);
            uint32_t km0 = 0, km1 = 0;
            if (s >= 0) {
                { const uint4 v = lds128(sb + O_AF + warp * 512 + l16); a[32] = v.x; a[33] = v.y; a[34] = v.z; a[35] = v.w; }
                float co[4], cw[3][4];
                uint4 b[14];
                float inv;
#define GORD(i) ((i) < 8 ? 2 * ((i) >> 2) + (((i) >> 1) & 1) + 4 * ((i) & 1) : (i))
                auto qkv_mma = [&](int i) {
                    const int gi = GORD(i), u = 8 * gi, n0 = 2 * i, n1 = 2 * i + 1;
                    if (gi < 4) {
                        if (i == 0) mma16816_z(co, a[u], a[u + 1], a[u + 2], a[u + 3], b[0].x, b[0].y);
                        else mma16816(co, a[u], a[u + 1], a[u + 2], a[u + 3], b[i].x, b[i].y);
                    }
                    if (n0 < 3) mma16816_z(cw[n0 % 3], a[32 + u], a[32 + u + 1], a[32 + u + 2], a[32 + u + 3], b[i].x, b[i].y);
                    else mma16816(cw[n0 % 3], a[32 + u], a[32 + u + 1], a[32 + u + 2], a[32 + u + 3], b[i].x, b[i].y);
                    if (n1 < 3) mma16816_z(cw[n1 % 3], a[32 + u + 4], a[32 + u + 5], a[32 + u + 6], a[32 + u + 7], b[i].z, b[i].w);
                    else mma16816(cw[n1 % 3], a[32 + u + 4], a[32 + u + 5], a[32 + u + 6], a[32 + u + 7], b[i].z, b[i].w);
                    if (gi < 4) mma16816(co, a[u + 4], a[u + 5], a[u + 6], a[u + 7], b[i].z, b[i].w);
                };
                const uint32_t mf = sb + O_MF + l16, mfs = mf + wg * 1024;
                const uint32_t qb = (s & 1) * 12288;
                bar_sync(2, 384);
                if (warp == 0) STAMP(s, 0);
                auto qkv_ld = [&](int i) {
                    const int gi = GORD(i);
                    b[i] = gi < 4 ? lds128v(mfs + (gi >> 1) * 3072 + (gi & 1) * 512) : lds128v(mf + (gi < 6 ? gi : gi + 4) * 512);
                };
#pragma unroll
                for (int i = 0; i < 4; i++) qkv_ld(i);
                qkv_mma(0); qkv_mma(1); qkv_mma(2);
                const uint32_t z0 = __float_as_uint(QDEP ? co[0] : cw[1][0]) & (l16 & 15u);
                qkv_mma(3);
                bar_sync(15, 384);
                b[4] = lds128v(mfs + 3072 + z0);
#pragma unroll
                for (int i = 5; i < 9; i++) qkv_ld(i);
#pragma unroll
                for (int i = 4; i < 9; i++) { qkv_mma(i); qkv_ld(5 + i); }
                asm volatile("ld.volatile.shared.f32 %0, [%1];" : "=f"(inv) : "r"(sb + O_MISC) : "memory");
#pragma unroll
                for (int i = 9; i < 14; i++) qkv_mma(i);
#pragma unroll
                for (int i = 0; i < 4; i++) cw[0][i] += cw[1][i] + cw[2][i];
                if (r < 2) {
                    const uint32_t o0 = pack_bf16(co[0] * inv, co[1] * inv), o1 = pack_bf16(co[2] * inv, co[3] * inv);
                    const uint32_t w0 = pack_bf16(cw[0][0] * inv, cw[0][1] * inv), w1 = pack_bf16(cw[0][2] * inv, cw[0][3] * inv);
                    stsm4t(adr1 + qb, o0, o1, w0, w1);
                    if (warp == 0) STAMP(s, 1);
                    asm volatile("{\n.reg .pred p;\nsetp.ge.u32 p, %0, 3;\n@p bar.arrive 1, 256;\n}" :: "r"(warp) : "memory");
                    auto scores = [&](float (&v)[4], const uint4 (&q)[4], const uint4 (&k)[4]) {
                        float s0[4], s1[4], t0[4], t1[4];
                        mma16816_z(s0, q[0].x, q[0].y, q[0].z, q[0].w, k[0].x, k[0].y);
                        mma16816_z(s1, q[0].x, q[0].y, q[0].z, q[0].w, k[0].z, k[0].w);
                        mma16816_z(t0, q[1].x, q[1].y, q[1].z, q[1].w, k[1].x, k[1].y);
                        mma16816_z(t1, q[1].x, q[1].y, q[1].z, q[1].w, k[1].z, k[1].w);
                        mma16816(s0, q[2].x, q[2].y, q[2].z, q[2].w, k[2].x, k[2].y);
                        mma16816(s1, q[2].x, q[2].y, q[2].z, q[2].w, k[2].z, k[2].w);
                        mma16816(t0, q[3].x, q[3].y, q[3].z, q[3].w, k[3].x, k[3].y);
                        mma16816(t1, q[3].x, q[3].y, q[3].z, q[3].w, k[3].z, k[3].w);
                        v[0] = (s0[0] + s0[2]) + (t0[0] + t0[2]); v[1] = (s0[1] + s0[3]) + (t0[1] + t0[3]);
                        v[2] = (s1[0] + s1[2]) + (t1[0] + t1[2]); v[3] = (s1[1] + s1[3]) + (t1[1] + t1[3]);
                    };
                    if (warp < 2) {
                        uint4 q[4], k[4]; float v[4];
#pragma unroll
                        for (int i = 0; i < 4; i++) k[i] = ldsm4(sb + O_QKX + 4096 + qb + warp * 2048 + i * 512 + l16);
                        bar_sync(1, 256);
#pragma unroll
                        for (int i = 0; i < 4; i++) q[i] = ldsm4(sb + O_QM + qb + i * 512 + l16);
                        scores(v, q, k);
                        const uint32_t dst = sb + O_SC + r * 1280 + warp * 512 + l16;
                        st_async128(mapa(dst, 2), __float_as_uint(v[0]), __float_as_uint(v[1]), __float_as_uint(v[2]), __float_as_uint(v[3]), mapa(sb + B_SC, 2));
                        st_async128(mapa(dst, r ^ 1), __float_as_uint(v[0]), __float_as_uint(v[1]), __float_as_uint(v[2]), __float_as_uint(v[3]), mapa(sb + B_SC, r ^ 1));
                        st_async128(mapa(dst, r), __float_as_uint(v[0]), __float_as_uint(v[1]), __float_as_uint(v[2]), __float_as_uint(v[3]), mapa(sb + B_SC, r));
                    } else if (warp == 2) {
                        uint4 q[4], k[4]; float v[4];
                        bar_sync(1, 256);
#pragma unroll
                        for (int i = 0; i < 4; i++) { q[i] = ldsm4(sb + O_QM + qb + i * 512 + l16); k[i] = ldsm4(sb + O_KM + qb + i * 512 + l16); }
                        scores(v, q, k);
                        const uint32_t dst = sb + O_SC + r * 1280 + 1024 + (l16 >> 1);
                        st_async64(mapa(dst, 2), __float_as_uint(v[0] + v[2]), __float_as_uint(v[1] + v[3]), mapa(sb + B_SC, 2));
                        st_async64(mapa(dst, r ^ 1), __float_as_uint(v[0] + v[2]), __float_as_uint(v[1] + v[3]), mapa(sb + B_SC, r ^ 1));
                        st_async64(mapa(dst, r), __float_as_uint(v[0] + v[2]), __float_as_uint(v[1] + v[3]), mapa(sb + B_SC, r));
                        STAMP(s, 2);
                    }
                } else {
                    sts128f(sb + O_XP + warp * 512 + l16, co[0], co[1], co[2], co[3]);
                    bar_sync(8 + w, 64);
                    const float4 o = lds128f(sb + O_XP + (warp ^ 4) * 512 + l16);
                    km0 = pack_bf16((cw[0][0] + o.x) * inv, (cw[0][1] + o.y) * inv);
                    km1 = pack_bf16((cw[0][2] + o.z) * inv, (cw[0][3] + o.w) * inv);
                    if (warp == 0) STAMP(s, 1);
                    st_async64(mapa(adr1, 0), km0, km1, mapa(sb + B_SC, 0));
                    st_async64(mapa(adr1, 1), km0, km1, mapa(sb + B_SC, 1));
                    st_async64(mapa(adr1, 2), km0, km1, mapa(sb + B_SC, 2));
                    if (warp == 0) STAMP(s, 2);
                }
            }
            if (s >= 0) bar_sync(3, 384);
            auto store_qk = [&]() {
                asm volatile("{\n.reg .pred p;\nelect.sync _|p, 0xffffffff;\n"
                    "@p cp.async.bulk.global.shared::cta.bulk_group [%0], [%1], 10240;\n@p cp.async.bulk.commit_group;\n}"
                    :: "l"(reinterpret_cast<char*>(g_qkv) + (size_t)(s * NH + h) * REC + r * 10240), "r"(sb + O_QKX + (s & 1) * 12288) : "memory");
            };
            auto store_vm = [&]() {
                *reinterpret_cast<uint2*>(reinterpret_cast<char*>(g_qkv) + (size_t)(s * NH + h) * REC + 28672 + warp * 256 + (l16 >> 1)) = make_uint2(km0, km1);
            };
            if (s == NSEG - 1) {
                if (r == 2) store_vm();
                else if (warp == 3) {
                    fence_async_smem();
                    store_qk();
                    asm volatile("cp.async.bulk.wait_group 0;\nfence.proxy.async.global;" ::: "memory");
                }
            } else {
                const int j = s + 1;
#define XDESC(u) (((u) < 8 ? descs : desc0) + (uint64_t)(((KS(u) >> 2) * 4096 + (KS(u) & 3) * 32) >> 4))
                const uint64_t descs = desc0 + (uint64_t)(wg * 4);
                float d[16];
                wg_fence();
#pragma unroll
                for (int u = 0; u < 8; u++) {
                    if (u == 0) wgmma_n32_rs<0>(d, a[0], a[1], a[2], a[3], XDESC(0));
                    else wgmma_n32_rs<1>(d, a[4 * u], a[4 * u + 1], a[4 * u + 2], a[4 * u + 3], XDESC(u));
                }
                wg_commit();
                wg_wait0();
                if (warp == 0) STAMP(s, 15);
                if (warp == 3) asm volatile("cp.async.bulk.wait_group.read 0;" ::: "memory");
                if (s >= 0) bar_sync(4, 384);
#pragma unroll
                for (int q = 0; q < 2; q++)
                    sts128(sb + O_XP + warp * 1024 + q * 512 + l16, pack_bf16(d[8 * q], d[8 * q + 1]), pack_bf16(d[8 * q + 2], d[8 * q + 3]),
                           pack_bf16(d[8 * q + 4], d[8 * q + 5]), pack_bf16(d[8 * q + 6], d[8 * q + 7]));
                bar_sync(12, 256);
#pragma unroll
                for (int q = 0; q < 2; q++) {
                    const uint4 o = lds128(sb + O_XP + (warp ^ 4) * 1024 + q * 512 + l16);
                    d[8 * q] = __uint_as_float(o.x << 16); d[8 * q + 1] = __uint_as_float(o.x & 0xffff0000u);
                    d[8 * q + 2] = __uint_as_float(o.y << 16); d[8 * q + 3] = __uint_as_float(o.y & 0xffff0000u);
                    d[8 * q + 4] = __uint_as_float(o.z << 16); d[8 * q + 5] = __uint_as_float(o.z & 0xffff0000u);
                    d[8 * q + 6] = __uint_as_float(o.w << 16); d[8 * q + 7] = __uint_as_float(o.w & 0xffff0000u);
                }
                if (s >= 0) {
                    if (r == 2) store_vm();
                    if (warp == 5 && s + 2 < NSEG) tma_x_tile(sb, &tm_x, r, s + 2, s3 == 2 ? 0 : s3 + 1);
                    if (warp == 3) {
                        asm volatile("cp.async.bulk.wait_group 0;\nfence.proxy.async.global;" ::: "memory");
                        if ((s & 3) == 0 && s >= 4) {
                            __syncwarp();
                            flag_inc_if(l16, &g_flag[F_QKV + (s - 4 + (h >> 3)) * 8]);
                        }
                        fence_async_smem();
                    }
                    asm volatile("{\n.reg .pred p;\nsetp.eq.u32 p, %0, 0;\n@p bar.sync 5, 256;\n@!p bar.sync 13, 256;\n}" :: "r"(wg) : "memory");
                }
                const uint64_t da0 = (uint64_t)(((sb + O_AS + wg * 8192) & 0x3FFFF) >> 4) | (1ull << 16) | (64ull << 32) | (1ull << 62);
                wg_fence();
                wgmma_n32_ss<1>(d, da0, XDESC(0));
#pragma unroll
                for (int u = 1; u < 28; u++) wgmma_n32_rs<1>(d, a[32 + 4 * u], a[32 + 4 * u + 1], a[32 + 4 * u + 2], a[32 + 4 * u + 3], XDESC(u));
                wg_commit();
                wg_wait0();
                if (warp == 3 && r < 2 && s >= 0) store_qk();
                if (warp == 4) STAMP(s, 3);
                uint32_t e[8];
#pragma unroll
                for (int i = 0; i < 8; i++) e[i] = pack_bf16(d[2 * i], d[2 * i + 1]);
                if (r < 2) {
                    const uint32_t base = sb + O_QKX + (j & 1) * 12288 + wg * 4096 + w * 512 + l16;
                    stsm4t(base, e[0], wg ? e[1] : e[2], wg ? e[2] : e[1], e[3]);
                    stsm4t(base + 2048, e[4], wg ? e[5] : e[6], wg ? e[6] : e[5], e[7]);
                } else {
                    const uint32_t base = sb + O_VX + (j & 1) * 8192 + warp * 1024 + l16;
                    sts128(base, e[0], e[1], e[2], e[3]);
                    sts128(base + 512, e[4], e[5], e[6], e[7]);
                    bar_arrive(14, 288);
                }
                if (warp == 7) STAMP(s, 4);
                if (s < 0) asm volatile("barrier.cluster.wait.aligned;" ::: "memory");
            }
        }
        bar_arrive(7, 384);
    } else {
        asm volatile("setmaxnreg.dec.sync.aligned.u32 136;");
        const int c = w;
        uint32_t a[96];
        uint32_t mmax = 0;
        {
            const int g = lane >> 2, t = lane & 3;
            uint32_t tag = 0, m0v[18];
            if (threadIdx.x == 256) tag = atomicAdd(&g_ticket, 1u);
#pragma unroll
            for (int i = 0; i < 9; i++) {
                const uint32_t* p = reinterpret_cast<const uint32_t*>(mem0 + g * DM + 16 * (4 * i + c) + 2 * t);
                m0v[2 * i] = __ldg(p); m0v[2 * i + 1] = __ldg(p + 4);
            }
            asm volatile("barrier.cluster.wait.aligned;" ::: "memory");
            if (c == 0) {
                tma_x_tile(sb, &tm_x, r, 0, 0);
                mbar_expect_if(lane, sb + B_SC, 4608);
                if (r < 2) mbar_expect_if(lane, sb + B_VX, 8192);
                sts32_if(lane, sb + O_MISC, __float_as_uint(1.0f));
                sts32_if(lane, sb + O_MISC + 12, __float_as_uint(SM_SCALE));
            }
            asm volatile("barrier.cluster.arrive.relaxed.aligned;" ::: "memory");
#pragma unroll
            for (int tau = 0; tau < 3; tau++) {
                const uint32_t* v = m0v + 6 * tau;
                sts128(sb + O_MF + tau * 3072 + c * 512 + lane * 16, v[0], v[1], v[2], v[3]);
                sts64(sb + O_MF + tau * 3072 + 2048 + (c >> 1) * 512 + lane * 16 + (c & 1) * 8, v[4], v[5]);
#pragma unroll
                for (int i = 0; i < 6; i++) mmax = __vmaxu2(mmax, v[i] & 0x7fff7fffu);
            }
            mmax = max(mmax << 16, mmax & 0xffff0000u);
            bar_arrive(2, 384); bar_arrive(15, 384);
            tag = (__shfl_sync(~0u, tag, 0) / 96u + 1u) & 0xffffu;
            mbar_wait(sb + B_W + 0, 0);
            const __nv_bfloat16* p = Wo + (size_t)(h * 128 + 4 * t) * DM + 192 * r + 16 * c + 2 * g;
#pragma unroll
            for (int i = 0; i < 3; i++)
#pragma unroll
                for (int eb = 0; eb < 8; eb++)
#pragma unroll
                    for (int j = 0; j < 4; j++) a[(i * 8 + eb) * 4 + j] = ldg_nc32(p + (16 * eb + ((j & 1) * 2 + (j >> 1))) * DM + 64 * i);
#pragma unroll
            for (int kk = 0; kk < 48; kk++) {
                uint32_t w0 = a[2 * kk], w1 = a[2 * kk + 1];
                a[2 * kk] = __byte_perm(w0, w1, 0x5410);
                a[2 * kk + 1] = __byte_perm(w0, w1, 0x7632);
            }
            sts128(sb + O_WP + c * 512 + lane * 16, a[92], a[93], a[94], a[95]);
            float wmax = 0.f;
#pragma unroll
            for (int i = 0; i < 3; i++) {
                float n0[4];
#pragma unroll
                for (int u = 8 * i; u < 8 * i + 8; u++) {
                    const uint32_t x0 = a[4 * u] & 0x7fff7fffu, x1 = a[4 * u + 1] & 0x7fff7fffu, x2 = a[4 * u + 2] & 0x7fff7fffu, x3 = a[4 * u + 3] & 0x7fff7fffu;
                    if (u == 8 * i) mma16816_z(n0, x0, x1, x2, x3, ONES, ONES);
                    else mma16816(n0, x0, x1, x2, x3, ONES, ONES);
                }
                wmax = fmaxf(wmax, fmaxf(n0[0], n0[2]));
            }
            uint32_t wm = __reduce_max_sync(~0u, __float_as_uint(wmax));
            sts32_if(lane, sb + O_OF + 4 * c, wm);
            if (c == 0) PSTAMP(8);
            bar_sync(7, 384);
            asm volatile("barrier.cluster.wait.aligned;" ::: "memory");
            if (c == 1) tma_x_tile(sb, &tm_x, r, 1, 1);
            if (c == 0) {
                const uint4 wq = lds128(sb + O_OF), xq = lds128(sb + O_OF + 16), xr = lds128(sb + O_OF + 32), v0 = lds128(sb + O_MISC + 32), v1 = lds128(sb + O_MISC + 48);
                const uint32_t w1 = max(max(wq.x, wq.y), max(wq.z, wq.w)), x1 = max(max(max(xq.x, xq.y), max(xq.z, xq.w)), max(max(xr.x, xr.y), max(xr.z, xr.w)));
                const uint32_t vv = (r < 2) ? 0u : max(max(max(v0.x, v0.y), max(v0.z, v0.w)), max(max(v1.x, v1.y), max(v1.z, v1.w)));
                const uint32_t lo = (min(w1, 0x7f800000u) + 0xffffu) >> 16 | ((min(vv, 0x7f800000u) + 0xffffu) & 0xffff0000u), hi = (x1 & 0xffff0000u) | tag;
                uint32_t l0, h0, l1, h1, l2, h2;
                asm volatile("{\n.reg .pred p;\n.reg .u32 n, x, y;\n.reg .b64 v;\nsetp.eq.u32 p, %10, 0;\nmov.b64 v, {%8, %9};\n@p st.relaxed.gpu.global.b64 [%7], v;\nmov.u32 n, 0;\n"
                             "G_%=: ld.relaxed.gpu.global.b64 v, [%6];\nmov.b64 {%0, %1}, v;\nld.relaxed.gpu.global.b64 v, [%6+256];\nmov.b64 {%2, %3}, v;\n"
                             "ld.relaxed.gpu.global.b64 v, [%6+512];\nmov.b64 {%4, %5}, v;\n"
                             "xor.b32 x, %1, %9;\nxor.b32 y, %3, %9;\nor.b32 x, x, y;\nxor.b32 y, %5, %9;\nor.b32 x, x, y;\nand.b32 x, x, 0xffff;\n"
                             "setp.eq.u32 p, x, 0;\nvote.sync.all.pred p, p, 0xffffffff;\n@p bra.uni E_%=;\n"
                             "add.u32 n, n, 1;\nsetp.lt.u32 p, n, 4000000;\n@p bra.uni G_%=;\ntrap;\nE_%=:\n}"
                             : "=&r"(l0), "=&r"(h0), "=&r"(l1), "=&r"(h1), "=&r"(l2), "=&r"(h2)
                             : "l"(&g_norm[lane]), "l"(&g_norm[blockIdx.x]), "r"(lo), "r"(hi), "r"(lane) : "memory");
                const uint32_t lm = __vmaxu2(l0, __vmaxu2(l1, l2));
                const float fw = __uint_as_float(__reduce_max_sync(~0u, lm << 16));
                const float fv = __uint_as_float(__reduce_max_sync(~0u, lm & 0xffff0000u));
                const float xmax = __uint_as_float(__reduce_max_sync(~0u, max(h0, max(h1, h2)) & 0xffff0000u));
                const float G = 36.f * fw * fv;
                sts32_if(lane, sb + O_MISC + 4, __float_as_uint(G)); sts32_if(lane, sb + O_MISC + 8, __float_as_uint(G * xmax));
            }
        }
        if (c == 0) PSTAMP(12);
        bar_sync(6, 128);
        int s3n = 1;
        uint32_t roff = __shfl_sync(~0u, (r * 4 + c) * 2048 + (lane >> 4) * 512 + (lane & 2) * 128 + (lane & 1) * 64 + (lane & 12) * 4, lane);
#pragma unroll 1
        for (int s = 0; s < NSEG; s++) {
            const uint32_t l16 = opaque(l16c);
            const uint32_t vxa = sb + O_VX + (s & 1) * 8192 + c * 2048 + l16;
            if (c == 0 && r == 2) {
                bar_sync(14, 288);
                fence_async_smem();
                asm volatile("{\n.reg .pred p;\nelect.sync _|p, 0xffffffff;\n"
                    "@p cp.async.bulk.global.shared::cta.bulk_group [%0], [%1], 8192;\n@p cp.async.bulk.commit_group;\n"
                    "cp.async.bulk.wait_group 0;\nsetp.lt.and.s32 p, %4, 63, p;\n"
                    "@p cp.async.bulk.shared::cluster.global.mbarrier::complete_tx::bytes.multicast::cluster [%1], [%0], 8192, [%2], %3;\n"
                    "fence.proxy.async.global;\n}"
                    :: "l"(reinterpret_cast<char*>(g_qkv) + (size_t)(s * NH + h) * REC + 20480), "r"(sb + O_VX + (s & 1) * 8192),
                       "r"(sb + B_VX + 8 * (s & 1)), "h"((unsigned short)3), "r"(s) : "memory");
            }
            if (s == NSEG - 1) { bar_sync(3, 384); mbar_wait(sb + B_SC, s & 1); break; }
            uint4 vx[4];
            sts32_if(l16, sb + O_MISC + 16 + 4 * c, __reduce_max_sync(~0u, mmax));
            if (c == 0) STAMP(s, 5);
            {
                bar_sync(6, 128);
                const uint4 mm = lds128(sb + O_MISC + 16), cf = lds128(sb + O_MISC);
                const float bound = fmaxf(__uint_as_float(cf.z), __uint_as_float(cf.y) * (__uint_as_float(max(max(mm.x, mm.y), max(mm.z, mm.w))) * __uint_as_float(cf.x)));
                const uint32_t ebits = __reduce_max_sync(~0u, min(max(__float_as_uint(bound) & 0x7f800000u, 21u << 23), 254u << 23));
                mbar_wait(sb + B_X + 8 * s3n, ((s + 1) / 3) & 1);
                s3n = (s3n == 2) ? 0 : s3n + 1;
                bar_sync(3, 384);
                if (r < 2) mbar_wait(sb + B_VX + 8 * (s & 1), (s >> 1) & 1);
                vx[0] = lds128(vxa); vx[2] = lds128(vxa + 1024);
                if (c == 0) STAMP(s, 13);
                mbar_wait(sb + B_SC, s & 1);
                if (c == 0) STAMP(s, 6);
                float p[10];
                load_scores(p, sb + O_SC, 1280, l16);
                float mx = fmaxf(fmaxf(fmaxf(p[0], p[1]), fmaxf(p[2], p[3])), fmaxf(fmaxf(p[4], p[5]), fmaxf(p[6], p[7])));
                mx = quad_max(fmaxf(mx, fmaxf(p[8], p[9])));
                const uint4 vm = lds64x2(sb + O_VM + c * 512 + (l16 >> 1));
                vx[1] = lds128(vxa + 512); vx[3] = lds128(vxa + 1536);
                bar_arrive(4, 384);
                const float sc = __uint_as_float(lds32(sb + O_MISC + 12));
                const float mo = mx * SM_SCALE;
                uint32_t P[5];
#pragma unroll
                for (int n = 0; n < 5; n++) P[n] = pack_bf16(ex2(fmaf(p[2 * n], SM_SCALE, -mo)), ex2(fmaf(p[2 * n + 1], n == 3 ? sc : SM_SCALE, -mo)));
                if (c == 0) STAMP(s, 7);
                float o0[4], o1[4], sm[4];
                mma16816_z(sm, ONES, ONES, ONES, ONES, P[1], P[2]);
                mma16816_z(o0, vx[0].x, vx[0].y, vx[0].z, vx[0].w, P[1], P[2]);
                mma16816_z(o1, vx[2].x, vx[2].y, vx[2].z, vx[2].w, P[1], P[2]);
                mma16816(sm, ONES, ONES, ONES, ONES, P[3], P[4]);
                mma16816(o0, vx[1].x, vx[1].y, vx[1].z, vx[1].w, P[3], P[4]);
                mma16816(o1, vx[3].x, vx[3].y, vx[3].z, vx[3].w, P[3], P[4]);
                mma1688(sm, ONES, ONES, P[0]);
                mma1688(o0, vm.x, vm.y, P[0]);
                mma1688(o1, vm.z, vm.w, P[0]);
                const float sig = __uint_as_float((268u << 23) - ebits);
                const float r0 = rcp_fast(sm[0]) * sig, r1 = rcp_fast(sm[1]) * sig;
                stsm4t(sb + O_OF + c * 512 + l16, pack_bf16(o0[0] * r0, o0[1] * r1), pack_bf16(o0[2] * r0, o0[3] * r1),
                       pack_bf16(o1[0] * r0, o1[1] * r1), pack_bf16(o1[2] * r0, o1[3] * r1));
                bar_sync(6, 128);
                uint4 ob[4];
#pragma unroll
                for (int q = 0; q < 4; q++) ob[q] = ldsm4(sb + O_OF + q * 512 + l16);
                { const uint4 v = lds128(sb + O_WP + c * 512 + l16); a[92] = v.x; a[93] = v.y; a[94] = v.z; a[95] = v.w; }
                float m0[3][4], m1[3][4];
#pragma unroll
                for (int q = 0; q < 4; q++) {
#pragma unroll
                    for (int i = 0; i < 3; i++) {
                        const int k0 = (i * 8 + 2 * q) * 4;
                        if (q == 0) mma16816_z(m0[i], a[k0], a[k0 + 1], a[k0 + 2], a[k0 + 3], ob[q].x, ob[q].y);
                        else mma16816(m0[i], a[k0], a[k0 + 1], a[k0 + 2], a[k0 + 3], ob[q].x, ob[q].y);
                    }
#pragma unroll
                    for (int i = 0; i < 3; i++) {
                        const int k1 = (i * 8 + 2 * q + 1) * 4;
                        if (q == 0) mma16816_z(m1[i], a[k1], a[k1 + 1], a[k1 + 2], a[k1 + 3], ob[q].z, ob[q].w);
                        else mma16816(m1[i], a[k1], a[k1 + 1], a[k1 + 2], a[k1 + 3], ob[q].z, ob[q].w);
                    }
                }
                asm volatile("red.relaxed.gpu.global.add.noftz.v4.f16x2 [%0], {%1,%2,%3,%4};" :: "l"(reinterpret_cast<char*>(g_acc) + roff),
                    "r"(pack_f16(m0[0][0] + m1[0][0], m0[0][2] + m1[0][2])), "r"(pack_f16(m0[1][0] + m1[1][0], m0[1][2] + m1[1][2])),
                    "r"(pack_f16(m0[2][0] + m1[2][0], m0[2][2] + m1[2][2])), "r"(0x3c00u) : "memory");
                asm volatile("red.relaxed.gpu.global.add.noftz.v4.f16x2 [%0], {%1,%2,%3,%4};" :: "l"(reinterpret_cast<char*>(g_acc) + roff + 1024),
                    "r"(pack_f16(m0[0][1] + m1[0][1], m0[0][3] + m1[0][3])), "r"(pack_f16(m0[1][1] + m1[1][1], m0[1][3] + m1[1][3])),
                    "r"(pack_f16(m0[2][1] + m1[2][1], m0[2][3] + m1[2][3])), "r"(0x3c00u) : "memory");
                const unsigned t_red = clk();
                bar_arrive(5, 256);
                bar_arrive(13, 256);
                mbar_expect_if(l16 | c, sb + B_SC, 4608);
                mbar_expect_if(l16 | (c ^ 1) | (r >> 1), sb + B_VX + 8 * ((s + 1) & 1), 8192);
                sts32_if(l16 | (c ^ 3), sb + O_MISC, ebits - (14u << 23));
                if (c == 0) STAMPV(s, 8, t_red);
                if (ACC_PF && c == 2 && s + 4 < NSEG - 1)
                    asm volatile("prefetch.global.L2 [%0];" :: "l"(reinterpret_cast<const char*>(g_acc) + ((s + 4) * 96 + blockIdx.x) * 256 + (l16 & 96)) : "memory");
                const char* pbase = reinterpret_cast<const char*>(g_acc) + (s * 24576 + c * 2048) + ((l16 & 64) * 16 + (l16 & 256) + ((l16 & 128) >> 1) + (l16 & 48));
                spin_until(t_red, D_WAIT);
                uint4 v[6];
#pragma unroll
                for (int i = 0; i < 6; i++) v[i] = ldg_relaxed128(pbase + (i >> 1) * 8192 + (i & 1) * 512);
                int nretry = 0;
                auto convert = [&](int tau) {
                    uint4& A = v[2 * tau]; uint4& B = v[2 * tau + 1];
                    A.x = f16x2_to_bf16x2(A.x); B.x = f16x2_to_bf16x2(B.x); A.y = f16x2_to_bf16x2(A.y); B.y = f16x2_to_bf16x2(B.y);
                    A.z = f16x2_to_bf16x2(A.z); B.z = f16x2_to_bf16x2(B.z);
                    sts128(sb + O_MF + tau * 3072 + c * 512 + l16, A.x, B.x, A.y, B.y);
                    sts64(sb + O_MF + tau * 3072 + 2048 + (c >> 1) * 512 + (c & 1) * 8 + l16, A.z, B.z);
                };
                const uint32_t ok0 = __all_sync(~0u, (v[0].w & v[1].w) == 0x5000u);
                convert(0);
                asm volatile("{\n.reg .pred p;\nsetp.ne.u32 p, %0, 0;\n@p bar.arrive 2, 384;\n}" :: "r"(ok0) : "memory");
                sched_fence<0>(h);
                uint32_t ok1;
                asm volatile("{\n.reg .pred p, q;\n.reg .b32 x;\nlop3.b32 x, %1, %2, %3, 0x80;\nand.b32 x, x, %4;\n"
                             "setp.eq.u32 p, x, 0x5000;\nvote.sync.all.pred q, p, 0xffffffff;\nselp.u32 %0, 1, 0, q;\n}"
                             : "=r"(ok1) : "r"(v[2].w), "r"(v[3].w), "r"(v[4].w), "r"(v[5].w));
                convert(1); convert(2);
                asm volatile("{\n.reg .pred p;\nsetp.ne.u32 p, %0, 0;\n@p bar.arrive 15, 384;\n}" :: "r"(ok1) : "memory");
                if (!(ok0 & ok1)) {
                    uint32_t bad = 0;
#pragma unroll
                    for (int i = 0; i < 6; i++) bad |= (v[i].w != 0x5000u) << i;
                    asm volatile("{\n.reg .pred p0, p1, p2, p3, p4, p5, q;\n.reg .u32 n, x;\nmov.u32 n, 0;\n"
                         "R_%=: setp.ne.u32 p0, %3, 0x5000;\nsetp.ne.u32 p1, %7, 0x5000;\nsetp.ne.u32 p2, %11, 0x5000;\n"
                         "setp.ne.u32 p3, %15, 0x5000;\nsetp.ne.u32 p4, %19, 0x5000;\nsetp.ne.u32 p5, %23, 0x5000;\n"
                         "@p0 ld.relaxed.gpu.global.v4.u32 {%0,%1,%2,%3}, [%25];\n@p1 ld.relaxed.gpu.global.v4.u32 {%4,%5,%6,%7}, [%25+512];\n"
                         "@p2 ld.relaxed.gpu.global.v4.u32 {%8,%9,%10,%11}, [%25+8192];\n@p3 ld.relaxed.gpu.global.v4.u32 {%12,%13,%14,%15}, [%25+8704];\n"
                         "@p4 ld.relaxed.gpu.global.v4.u32 {%16,%17,%18,%19}, [%25+16384];\n@p5 ld.relaxed.gpu.global.v4.u32 {%20,%21,%22,%23}, [%25+16896];\n"
                         "add.u32 %24, %24, 1;\nand.b32 x, %3, %7;\nand.b32 x, x, %11;\nand.b32 x, x, %15;\nand.b32 x, x, %19;\nand.b32 x, x, %23;\n"
                         "setp.eq.u32 q, x, 0x5000;\nvote.sync.all.pred q, q, 0xffffffff;\n@q bra.uni K_%=;\n"
                         "add.u32 n, n, 1;\nsetp.lt.u32 q, n, 2000000;\n@q bra.uni R_%=;\ntrap;\nK_%=:\n}"
                         : "+r"(v[0].x), "+r"(v[0].y), "+r"(v[0].z), "+r"(v[0].w), "+r"(v[1].x), "+r"(v[1].y), "+r"(v[1].z), "+r"(v[1].w),
                           "+r"(v[2].x), "+r"(v[2].y), "+r"(v[2].z), "+r"(v[2].w), "+r"(v[3].x), "+r"(v[3].y), "+r"(v[3].z), "+r"(v[3].w),
                           "+r"(v[4].x), "+r"(v[4].y), "+r"(v[4].z), "+r"(v[4].w), "+r"(v[5].x), "+r"(v[5].y), "+r"(v[5].z), "+r"(v[5].w), "+r"(nretry)
                         : "l"(pbase) : "memory");
#pragma unroll
                    for (int i = 0; i < 6; i++) {
                        const bool nb = (bad >> i) & 1;
                        v[i].x = nb ? f16x2_to_bf16x2(v[i].x) : v[i].x; v[i].y = nb ? f16x2_to_bf16x2(v[i].y) : v[i].y; v[i].z = nb ? f16x2_to_bf16x2(v[i].z) : v[i].z;
                    }
#pragma unroll
                    for (int tau = 0; tau < 3; tau++) {
                        sts128(sb + O_MF + tau * 3072 + c * 512 + l16, v[2 * tau].x, v[2 * tau + 1].x, v[2 * tau].y, v[2 * tau + 1].y);
                        sts64(sb + O_MF + tau * 3072 + 2048 + (c >> 1) * 512 + (c & 1) * 8 + l16, v[2 * tau].z, v[2 * tau + 1].z);
                    }
                    if (!ok0) bar_arrive(2, 384);
                    if (!ok1) bar_arrive(15, 384);
                }
                if (c == 0) STAMP(s, 12);
                if (c == 0) STAMPV(s, 14, nretry);
                mmax = absmax2(absmax2(absmax2(v[0].x, v[0].y), absmax2(v[0].z, v[1].x)), absmax2(absmax2(v[1].y, v[1].z), absmax2(v[2].x, v[2].y)));
                mmax = absmax2(mmax, absmax2(absmax2(absmax2(v[2].z, v[3].x), absmax2(v[3].y, v[3].z)), absmax2(absmax2(v[4].x, v[4].y), absmax2(v[4].z, v[5].x))));
                mmax = absmax2(mmax, absmax2(v[5].y, v[5].z)) & 0x7fff7fffu;
                mmax = max(mmax << 16, mmax & 0xffff0000u);
            }
            roff += 24576;
        }
        {
            bar_sync(7, 384);
            if (c == 0) flag_inc_if(l16c, &g_flag[F_QKV + (60 + (h >> 3)) * 8]);
        }
    }
    if (warp == 8) PSTAMP(13);
    cluster_sync();
}

constexpr int NST = 10;
constexpr int G_RING = 0, G_EX = NST * 16384, G_OUT = G_EX + 32768, G_CARRY = G_OUT + 32768, G_BAR = G_CARRY + 512, BG_SMEM = G_BAR + 256;
constexpr int GB_FULL = G_BAR, GB_EMPTY = G_BAR + 8 * NST, GB_W = G_BAR + 16 * NST;
static_assert(BG_SMEM <= 232448, "smem");

template <int ACC>
__device__ __forceinline__ void wgmma_n128_rs(float (&d)[64], uint32_t a0, uint32_t a1, uint32_t a2, uint32_t a3, uint64_t desc) {
    asm volatile("wgmma.mma_async.sync.aligned.m64n128k16.f32.bf16.bf16 "
        "{%0,%1,%2,%3,%4,%5,%6,%7,%8,%9,%10,%11,%12,%13,%14,%15,%16,%17,%18,%19,%20,%21,%22,%23,%24,%25,%26,%27,%28,%29,%30,%31,"
        "%32,%33,%34,%35,%36,%37,%38,%39,%40,%41,%42,%43,%44,%45,%46,%47,%48,%49,%50,%51,%52,%53,%54,%55,%56,%57,%58,%59,%60,%61,%62,%63}, "
        "{%64,%65,%66,%67}, %68, %69, 1, 1, 0;"
        : "+f"(d[0]), "+f"(d[1]), "+f"(d[2]), "+f"(d[3]), "+f"(d[4]), "+f"(d[5]), "+f"(d[6]), "+f"(d[7]),
          "+f"(d[8]), "+f"(d[9]), "+f"(d[10]), "+f"(d[11]), "+f"(d[12]), "+f"(d[13]), "+f"(d[14]), "+f"(d[15]),
          "+f"(d[16]), "+f"(d[17]), "+f"(d[18]), "+f"(d[19]), "+f"(d[20]), "+f"(d[21]), "+f"(d[22]), "+f"(d[23]),
          "+f"(d[24]), "+f"(d[25]), "+f"(d[26]), "+f"(d[27]), "+f"(d[28]), "+f"(d[29]), "+f"(d[30]), "+f"(d[31]),
          "+f"(d[32]), "+f"(d[33]), "+f"(d[34]), "+f"(d[35]), "+f"(d[36]), "+f"(d[37]), "+f"(d[38]), "+f"(d[39]),
          "+f"(d[40]), "+f"(d[41]), "+f"(d[42]), "+f"(d[43]), "+f"(d[44]), "+f"(d[45]), "+f"(d[46]), "+f"(d[47]),
          "+f"(d[48]), "+f"(d[49]), "+f"(d[50]), "+f"(d[51]), "+f"(d[52]), "+f"(d[53]), "+f"(d[54]), "+f"(d[55]),
          "+f"(d[56]), "+f"(d[57]), "+f"(d[58]), "+f"(d[59]), "+f"(d[60]), "+f"(d[61]), "+f"(d[62]), "+f"(d[63])
        : "r"(a0), "r"(a1), "r"(a2), "r"(a3), "l"(desc), "n"(ACC));
}
__device__ __forceinline__ void wait_flag(const unsigned* p, unsigned target) {
    asm volatile("{\n.reg .pred p;\n.reg .u32 n, v;\nmov.u32 n, 0;\n"
                 "W_%=: ld.acquire.gpu.global.u32 v, [%0];\nsub.u32 v, v, %1;\nsetp.ge.s32 p, v, 0;\n@p bra.uni D_%=;\nnanosleep.u32 100;\n"
                 "add.u32 n, n, 1;\nsetp.lt.u32 p, n, 4000000;\n@p bra.uni W_%=;\ntrap;\nD_%=:\n}" :: "l"(p), "r"(target) : "memory");
}
template <int NS, int STRIDE>
__device__ __forceinline__ void bg_mainloop(float (&d)[64], const uint32_t (&a)[144], uint32_t sb, int it, int lane) {
    int slot = it % NST, ph = (it / NST) & 1, prev = 0;
#pragma unroll
    for (int i = 0; i < NS; i++) {
        mbar_wait(sb + GB_FULL + 8 * slot, ph);
        const uint64_t desc = (uint64_t)(((sb + G_RING + slot * 16384) & 0x3FFFF) >> 4) | (1ull << 16) | (64ull << 32) | (1ull << 62);
        wg_fence();
#pragma unroll
        for (int k = 0; k < 4; k++) {
            const int u = 16 * i + 4 * k;
            if (i == 0 && k == 0) wgmma_n128_rs<0>(d, a[u], a[u + 1], a[u + 2], a[u + 3], desc);
            else wgmma_n128_rs<1>(d, a[u], a[u + 1], a[u + 2], a[u + 3], desc + 2 * k);
        }
        wg_commit();
        if (i > 0) {
            asm volatile("wgmma.wait_group.sync.aligned 1;" ::: "memory");
            mbar_arrive_if(lane, sb + GB_EMPTY + 8 * prev);
        }
        prev = slot;
        slot += STRIDE;
        if (slot >= NST) { slot -= NST; ph ^= 1; }
    }
    wg_wait0();
    mbar_arrive_if(lane, sb + GB_EMPTY + 8 * prev);
}
template <bool SKIP>
__device__ __forceinline__ void bg_epilogue(float (&d)[64], uint32_t sb, int wg, int w, int lane, const CUtensorMap* tm_out, int col0, int tok0,
                                            const __nv_bfloat16* xa, const __nv_bfloat16* Dk) {
    const int g = lane >> 2, t = lane & 3;
    const uint32_t ex = sb + G_EX + w * 4096 + lane * 16;
    float k[32];
    if (wg == 0) {
#pragma unroll
        for (int q = 0; q < 8; q++) sts128f(ex + q * 512, d[32 + 4 * q], d[32 + 4 * q + 1], d[32 + 4 * q + 2], d[32 + 4 * q + 3]);
#pragma unroll
        for (int i = 0; i < 32; i++) k[i] = d[i];
    } else {
#pragma unroll
        for (int q = 0; q < 8; q++) sts128f(ex + 16384 + q * 512, d[4 * q], d[4 * q + 1], d[4 * q + 2], d[4 * q + 3]);
#pragma unroll
        for (int i = 0; i < 32; i++) k[i] = d[32 + i];
    }
    uint32_t xv[16], dv = 0;
    if (SKIP) {
        const __nv_bfloat16* xp = xa + (size_t)(tok0 + 64 * wg + 2 * t) * DM + col0 + 16 * w + 2 * g;
#pragma unroll
        for (int i = 0; i < 16; i++) xv[i] = ldg_nc32(xp + (8 * (i >> 1) + (i & 1)) * DM);
        dv = ldg_nc32(Dk + col0 + 16 * w + 2 * g);
    }
    if (SKIP && w == 0) asm volatile("cp.async.bulk.wait_group.read 0;" ::: "memory");
    bar_sync(1, 256);
#pragma unroll
    for (int q = 0; q < 8; q++) {
        const float4 o = lds128f(ex + (wg ^ 1) * 16384 + q * 512);
        k[4 * q] += o.x; k[4 * q + 1] += o.y; k[4 * q + 2] += o.z; k[4 * q + 3] += o.w;
    }
    if (SKIP) bar_sync(1, 256); else bar_sync(13, 288);
    const uint32_t ob = sb + G_OUT + wg * 16384 + (w >> 1) * 8192 + (g & 1) * 8;
    const uint32_t ch = (w & 1) * 4 + (g >> 1);
#pragma unroll
    for (int i = 0; i < 16; i++) {
        float v0 = k[4 * (i >> 1) + (i & 1)], v1 = k[4 * (i >> 1) + 2 + (i & 1)];
        if (SKIP) {
            const uint32_t p = pack_bf16(__uint_as_float(xv[i] << 16) * __uint_as_float(dv << 16), __uint_as_float(xv[i] & 0xffff0000u) * __uint_as_float(dv & 0xffff0000u));
            v0 += __uint_as_float(p << 16); v1 += __uint_as_float(p & 0xffff0000u);
        }
        const uint32_t n7 = 2 * t + (i & 1);
        sts64(ob + (8 * (i >> 1) + n7) * 128 + ((ch ^ n7) << 4), __float_as_uint(v0), __float_as_uint(v1));
    }
    fence_async_smem();
    if (SKIP) {
        bar_sync(4 + wg, 128);
        if (w == 0)
            asm volatile("{\n.reg .pred p;\nelect.sync _|p, 0xffffffff;\n"
                "@p cp.async.bulk.tensor.2d.global.shared::cta.bulk_group [%0, {%2, %4}], [%1];\n"
                "@p cp.async.bulk.tensor.2d.global.shared::cta.bulk_group [%0, {%3, %4}], [%1+8192];\n@p cp.async.bulk.commit_group;\n}"
                :: "l"(tm_out), "r"(sb + G_OUT + wg * 16384), "r"(col0), "r"(col0 + 32), "r"(tok0 + 64 * wg) : "memory");
    } else {
        bar_arrive(12, 288);
    }
}
__device__ __forceinline__ void s5_channel(int p, const __nv_bfloat16* Lre, const __nv_bfloat16* Lim, const __nv_bfloat16* logdt, float2& lam, float2& coef) {
    const float dt = __bfloat162float(__float2bfloat16(expf(__bfloat162float(logdt[p]))));
    const float lr = __bfloat162float(Lre[p]), li = __bfloat162float(Lim[p]);
    const float e = expf(dt * lr);
    float sn, cs;
    sincosf(dt * li, &sn, &cs);
    lam = make_float2(e * cs, e * sn);
    const float den = lr * lr + li * li;
    coef = make_float2(((lam.x - 1.f) * lr + lam.y * li) / den, (lam.y * lr - (lam.x - 1.f) * li) / den);
}
__device__ __forceinline__ float2 cfma(float2 a, float2 b, float2 c) {
    return make_float2(fmaf(a.x, b.x, fmaf(-a.y, b.y, c.x)), fmaf(a.x, b.y, fmaf(a.y, b.x, c.y)));
}
__device__ __forceinline__ uint4 ldg128(const void* p) { uint4 v; asm volatile("ld.global.v4.u32 {%0,%1,%2,%3}, [%4];" : "=r"(v.x), "=r"(v.y), "=r"(v.z), "=r"(v.w) : "l"(p) : "memory"); return v; }
__device__ __forceinline__ uint2 ldg64(const void* p) { uint2 v; asm volatile("ld.global.v2.u32 {%0,%1}, [%2];" : "=r"(v.x), "=r"(v.y) : "l"(p) : "memory"); return v; }

__device__ __forceinline__ void bg_attention(uint32_t st0, uint32_t st1, int mt, int lane) {
    const int g = lane >> 2, t = lane & 3;
    float sc[5][4];
#pragma unroll
    for (int n = 0; n < 5; n++) sc[n][0] = sc[n][1] = sc[n][2] = sc[n][3] = 0.f;
    float sm2[4] = {0.f, 0.f, 0.f, 0.f};
#pragma unroll
    for (int i = 0; i < 8; i++) {
        const uint32_t st = (i >> 2 ? st1 : st0) + (i & 3) * 512 + lane * 16;
        const uint4 q = ldsm4(st + mt * 2048), km = ldsm4(st + 8192), k0 = ldsm4(st + 4096);
        mma16816(sc[0], q.x, q.y, q.z, q.w, km.x, km.y);
        mma16816(sm2, q.x, q.y, q.z, q.w, km.z, km.w);
        mma16816(sc[1], q.x, q.y, q.z, q.w, k0.x, k0.y);
        mma16816(sc[2], q.x, q.y, q.z, q.w, k0.z, k0.w);
        if (mt) {
            const uint4 k1 = ldsm4(st + 6144);
            mma16816(sc[3], q.x, q.y, q.z, q.w, k1.x, k1.y);
            mma16816(sc[4], q.x, q.y, q.z, q.w, k1.z, k1.w);
        }
    }
#pragma unroll
    for (int i = 0; i < 4; i++) sc[0][i] += sm2[i];
    const int q0 = 16 * mt + 8 + g - 2 * t;
#pragma unroll
    for (int n = 1; n < 5; n++) {
        if (8 * n > q0) sc[n][0] = -INFINITY;
        if (8 * n + 1 > q0) sc[n][1] = -INFINITY;
        if (8 * n > q0 + 8) sc[n][2] = -INFINITY;
        if (8 * n + 1 > q0 + 8) sc[n][3] = -INFINITY;
    }
    float ma = fmaxf(sc[0][0], sc[0][1]), mb = fmaxf(sc[0][2], sc[0][3]);
#pragma unroll
    for (int n = 1; n < 5; n++) { ma = fmaxf(ma, fmaxf(sc[n][0], sc[n][1])); mb = fmaxf(mb, fmaxf(sc[n][2], sc[n][3])); }
    ma = quad_max(ma) * SM_SCALE; mb = quad_max(mb) * SM_SCALE;
    uint32_t Pa[5], Pb[5];
#pragma unroll
    for (int n = 0; n < 5; n++) {
        Pa[n] = pack_bf16(ex2(fmaf(sc[n][0], SM_SCALE, -ma)), ex2(fmaf(sc[n][1], SM_SCALE, -ma)));
        Pb[n] = pack_bf16(ex2(fmaf(sc[n][2], SM_SCALE, -mb)), ex2(fmaf(sc[n][3], SM_SCALE, -mb)));
    }
    float sa[4], sbb[4];
    mma1688_z(sa, ONES, ONES, Pa[0]); mma1688_z(sbb, ONES, ONES, Pb[0]);
    mma16816(sa, ONES, ONES, ONES, ONES, Pa[1], Pa[2]); mma16816(sbb, ONES, ONES, ONES, ONES, Pb[1], Pb[2]);
    mma16816(sa, ONES, ONES, ONES, ONES, Pa[3], Pa[4]); mma16816(sbb, ONES, ONES, ONES, ONES, Pb[3], Pb[4]);
    const float ra0 = rcp_fast(sa[0]), ra1 = rcp_fast(sa[1]), rb0 = rcp_fast(sbb[0]), rb1 = rcp_fast(sbb[1]);
    const uint32_t row = lane & 7;
    const uint32_t so = mt * 2048 + (lane >> 4) * 1024 + row * 128;
#pragma unroll
    for (int i = 0; i < 8; i++) {
        const uint32_t st = i >> 2 ? st1 : st0;
        const int e4 = i & 3;
        const float2 vmf = lds64f(st + 14336 + e4 * 256 + lane * 8);
        const uint32_t vm0 = __float_as_uint(vmf.x), vm1 = __float_as_uint(vmf.y);
        const uint4 v0 = lds128(st + 10240 + e4 * 1024 + lane * 16);
        float oa[4], ob[4];
        mma1688_z(oa, vm0, vm1, Pa[0]); mma1688_z(ob, vm0, vm1, Pb[0]);
        mma16816(oa, v0.x, v0.y, v0.z, v0.w, Pa[1], Pa[2]);
        mma16816(ob, v0.x, v0.y, v0.z, v0.w, Pb[1], Pb[2]);
        if (mt) {
            const uint4 v1 = lds128(st + 10240 + e4 * 1024 + 512 + lane * 16);
            mma16816(oa, v1.x, v1.y, v1.z, v1.w, Pa[3], Pa[4]);
            mma16816(ob, v1.x, v1.y, v1.z, v1.w, Pb[3], Pb[4]);
        }
        stsm4t(st + so + (((2 * e4 + ((lane >> 3) & 1)) ^ row) << 4), pack_bf16(oa[0] * ra0, oa[1] * ra1), pack_bf16(oa[2] * ra0, oa[3] * ra1),
               pack_bf16(ob[0] * rb0, ob[1] * rb1), pack_bf16(ob[2] * rb0, ob[3] * rb1));
    }
}
__device__ __forceinline__ bool bg_att_turn(int na, int ng) { return na == ng || (na == ng + 1 && na <= BG_AHEAD); }

__global__ void __launch_bounds__(384, 1)
bg_kernel(const __grid_constant__ CUtensorMap tm_xa, const __grid_constant__ CUtensorMap tm_wo, const __grid_constant__ CUtensorMap tm_out,
          const __nv_bfloat16* __restrict__ xa, const __nv_bfloat16* __restrict__ Lre, const __nv_bfloat16* __restrict__ Lim,
          const __nv_bfloat16* __restrict__ Bre, const __nv_bfloat16* __restrict__ Bim, const __nv_bfloat16* __restrict__ Cre,
          const __nv_bfloat16* __restrict__ Cim, const __nv_bfloat16* __restrict__ logdt, const __nv_bfloat16* __restrict__ Dk) {
    extern __shared__ __align__(1024) uint8_t smem_raw[];
    const uint32_t sb = smem_u32(smem_raw);
    const int lane = threadIdx.x & 31;
    const int warp = __shfl_sync(~0u, threadIdx.x >> 5, 0);
    const int wg = warp >> 2, w = warp & 3, b = blockIdx.x;
    const int nt = b % 9, kq = b / 9;
    BSTAMP(0);
    if (threadIdx.x == 0) {
        if (sb & 1023u) __trap();
        for (int i = 0; i < NST; i++) { mbar_init(sb + GB_FULL + 8 * i, 1); mbar_init(sb + GB_EMPTY + 8 * i, 4); }
        mbar_init(sb + GB_W, 1);
        asm volatile("fence.mbarrier_init.release.cluster;" ::: "memory");
        mbar_expect(sb + GB_W, (b < 18 ? 64 : 128) * 1152);
        sts32(sb + G_BAR + 248, atomicAdd(&g_ticket_bg, 1u) / 36u + 1u);
    }
    __syncthreads();
    if (wg == 2) {
        asm volatile("setmaxnreg.dec.sync.aligned.u32 24;");
        if (w == 0) {
            int slot = 0, ph = 1;
            unsigned tlast = clk();
            auto pace = [&]() { if (BG_PACE) { spin_until(tlast, BG_PACE); tlast = clk(); } };
            auto next = [&]() { if (++slot == NST) { slot = 0; ph ^= 1; } };
            bar_sync(6, 288);
            if (b < 18) {
#pragma unroll 1
                for (int i = 0; i < 144; i++) {
                    const int blk = i / 9, kb = i - 9 * blk, it = (blk >> 1) * 18 + (blk & 1) + 2 * kb;
                    slot = it % NST;
                    mbar_wait(sb + GB_EMPTY + 8 * slot, ((it / NST) & 1) ^ 1);
                    pace();
                    asm volatile("{\n.reg .pred p;\nelect.sync _|p, 0xffffffff;\n@p mbarrier.arrive.expect_tx.shared::cta.b64 _, [%2], 16384;\n"
                        "@p cp.async.bulk.tensor.5d.shared::cluster.global.mbarrier::complete_tx::bytes [%0], [%1, {%3, %4, %4, %4, %5}], [%2];\n}"
                        :: "r"(sb + G_RING + slot * 16384), "l"(&tm_xa), "r"(sb + GB_FULL + 8 * slot), "r"(kb * 64), "r"(0), "r"(blk) : "memory");
                }
                slot = 144 % NST; ph = ((144 / NST) & 1) ^ 1;
            }
            const unsigned ep = lds32(sb + G_BAR + 248);
            auto slabs = [&](const char* src, int ns) {
                asm volatile("fence.proxy.async.global;" ::: "memory");
#pragma unroll 1
                for (int i = 0; i < ns; i++) {
                    mbar_wait(sb + GB_EMPTY + 8 * slot, ph);
                    pace();
                    asm volatile("{\n.reg .pred p;\nelect.sync _|p, 0xffffffff;\n@p mbarrier.arrive.expect_tx.shared::cta.b64 _, [%2], 16384;\n"
                        "@p cp.async.bulk.shared::cluster.global.mbarrier::complete_tx::bytes [%0], [%1], 16384, [%2];\n}"
                        :: "r"(sb + G_RING + slot * 16384), "l"(src + (size_t)((i & 1) * (ns >> 1) + (i >> 1)) * (SEQ * 128)), "r"(sb + GB_FULL + 8 * slot) : "memory");
                    next();
                }
            };
            if (b >= 18) {
#pragma unroll 1
                for (int blk = kq - 2; blk < 16; blk += 2) {
                    wait_flag(&g_flag[F_H + blk * 8], 18 * ep);
                    slabs(reinterpret_cast<const char*>(g_h) + blk * 16384, 18);
                }
            }
            bar_sync(6, 288);
#pragma unroll 1
            for (int na = 0, ng = 0; ng < 16;) {
                if (bg_att_turn(na, ng)) {
                    if (nt < 8) {
                        wait_flag(&g_flag[F_QKV + (na * 4 + kq) * 8], 24 * ep);
                        asm volatile("fence.proxy.async.global;" ::: "memory");
#pragma unroll 1
                        for (int i = 0; i < 8; i++) {
                            const int pr = nt * 4 + 2 * (i & 1) + (i >> 2), hf = (i >> 1) & 1;
                            const char* rec = reinterpret_cast<const char*>(g_qkv) + (size_t)((4 * na + (pr >> 3)) * NH + 8 * kq + (pr & 7)) * REC;
                            mbar_wait(sb + GB_EMPTY + 8 * slot, ph);
                    pace();
                            asm volatile("{\n.reg .pred p;\nelect.sync _|p, 0xffffffff;\n@p mbarrier.arrive.expect_tx.shared::cta.b64 _, [%4], 15360;\n"
                                "@p cp.async.bulk.shared::cluster.global.mbarrier::complete_tx::bytes [%0], [%1], 10240, [%4];\n"
                                "@p cp.async.bulk.shared::cluster.global.mbarrier::complete_tx::bytes [%0+10240], [%2], 4096, [%4];\n"
                                "@p cp.async.bulk.shared::cluster.global.mbarrier::complete_tx::bytes [%0+14336], [%3], 1024, [%4];\n}"
                                :: "r"(sb + G_RING + slot * 16384), "l"(rec + hf * 10240), "l"(rec + 20480 + hf * 4096), "l"(rec + 28672 + hf * 1024),
                                   "r"(sb + GB_FULL + 8 * slot) : "memory");
                            next();
                        }
                    }
                    na++;
                } else {
                    wait_flag(&g_flag[F_OX + (ng * 4 + kq) * 8], 8 * ep);
                    slabs(reinterpret_cast<const char*>(g_ox) + (size_t)kq * 16 * SEQ * 128 + ng * 16384, 16);
                    ng++;
                }
            }
        } else if (w == 1) {
            if (b < 18) {
#pragma unroll 1
                for (int blk = 0; blk < 16; blk++) {
                    bar_sync(8 + (blk & 1), 160);
                    asm volatile("{\n.reg .pred p;\nelect.sync _|p, 0xffffffff;\n@p cp.async.bulk.global.shared::cta.bulk_group [%0], [%1], 16384;\n"
                        "@p cp.async.bulk.commit_group;\ncp.async.bulk.wait_group 0;\nfence.proxy.async.global;\n}"
                        :: "l"(reinterpret_cast<char*>(g_h) + ((size_t)b * SEQ + blk * 128) * 128), "r"(sb + G_OUT + (blk & 1) * 16384) : "memory");
                    bar_arrive(10 + (blk & 1), 160);
                    flag_inc_if(lane, &g_flag[F_H + blk * 8]);
                }
            }
            if (nt < 8) {
                int it = 144;
#pragma unroll 1
                for (int na = 0, ng = 0; ng < 16;) {
                    if (bg_att_turn(na, ng)) {
                        bar_sync(7, 288);
                        if (lane < 8) {
                            const int pr = nt * 4 + 2 * (lane & 1) + (lane >> 2), hf = (lane >> 1) & 1;
                            asm volatile("cp.async.bulk.global.shared::cta.bulk_group [%0], [%1], 4096;\ncp.async.bulk.commit_group;\ncp.async.bulk.wait_group.read 0;\n"
                                "mbarrier.arrive.shared::cta.b64 _, [%2], 4;\ncp.async.bulk.wait_group 0;\nfence.proxy.async.global;"
                                :: "l"(reinterpret_cast<char*>(g_ox) + ((size_t)((8 * kq + (pr & 7)) * 2 + hf) * SEQ + (4 * na + (pr >> 3)) * 32) * 128),
                                   "r"(sb + G_RING + ((it + lane) % NST) * 16384), "r"(sb + GB_EMPTY + 8 * ((it + lane) % NST)) : "memory");
                        }
                        __syncwarp();
                        flag_inc_if(lane, &g_flag[F_OX + (na * 4 + kq) * 8]);
                        it += 8; na++;
                    } else { it += 16; ng++; }
                }
            }
        } else if (w == 2) {
            const unsigned ep = lds32(sb + G_BAR + 248);
#pragma unroll 1
            for (int blk = 0; blk < 16; blk++) {
                bar_arrive(13, 288);
                bar_sync(12, 288);
                if (kq) { wait_flag(&g_flag[F_OUT + (blk * 9 + nt) * 8], ep); asm volatile("fence.proxy.async.global;" ::: "memory"); }
                unsigned t0 = clk();
                if (blk < 15) spin_until(t0, b * (RED_GAP / 36));
#pragma unroll 1
                for (int i = 0; i < 4; i++) {
                    const uint32_t src = sb + G_OUT + i * 8192;
                    const int c0 = DM + 64 * nt + (i & 1) * 32, c1 = blk * 128 + (i >> 1) * 64;
                    if (kq) {
                        asm volatile("{\n.reg .pred p;\nelect.sync _|p, 0xffffffff;\n@p cp.reduce.async.bulk.tensor.2d.global.shared::cta.add.bulk_group [%0, {%2, %3}], [%1];\n}"
                            :: "l"(&tm_out), "r"(src), "r"(c0), "r"(c1) : "memory");
                        t0 = clk();
                        if (blk < 15 && i < 3) spin_until(t0, RED_GAP);
                    } else {
                        asm volatile("{\n.reg .pred p;\nelect.sync _|p, 0xffffffff;\n@p cp.async.bulk.tensor.2d.global.shared::cta.bulk_group [%0, {%2, %3}], [%1];\n}"
                            :: "l"(&tm_out), "r"(src), "r"(c0), "r"(c1) : "memory");
                    }
                }
                asm volatile("cp.async.bulk.commit_group;\ncp.async.bulk.wait_group 0;\nfence.proxy.async.global;" ::: "memory");
                __syncwarp();
                if (!kq) flag_inc_if(lane, &g_flag[F_OUT + (blk * 9 + nt) * 8]);
            }
        }
    } else {
        asm volatile("setmaxnreg.inc.sync.aligned.u32 240;");
        const int g = lane >> 2, t = lane & 3, tid = threadIdx.x;
        uint32_t a[144];
        float d[64];
        if (b < 18) {
            if (tid < 64)
                asm volatile("cp.async.bulk.shared::cluster.global.mbarrier::complete_tx::bytes [%0], [%1], 1152, [%2];"
                    :: "r"(sb + tid * 1168), "l"((tid < 32 ? Bre : Bim) + (size_t)(32 * b + (tid & 31)) * DM), "r"(sb + GB_W) : "memory");
            float2 lam, coef;
            s5_channel(32 * b + 8 * w + g, Lre, Lim, logdt, lam, coef);
            float2 l32 = lam;
#pragma unroll
            for (int i = 0; i < 5; i++) l32 = make_float2(l32.x * l32.x - l32.y * l32.y, 2.f * l32.x * l32.y);
            __syncwarp();
            mbar_wait(sb + GB_W, 0);
            const uint32_t ap = sb + (((lane >> 3) & 1) * 32 + 8 * w + (lane & 7)) * 1168 + (lane >> 4) * 16;
#pragma unroll
            for (int ks = 0; ks < 36; ks++) { const uint4 v = ldsm4(ap + ks * 32); a[4 * ks] = v.x; a[4 * ks + 1] = v.y; a[4 * ks + 2] = v.z; a[4 * ks + 3] = v.w; }
            bar_sync(1, 256);
            bar_arrive(6, 288);
            BSTAMP(1);
#pragma unroll 1
            for (int blk = wg; blk < 16; blk += 2) {
                bg_mainloop<9, 2>(d, a, sb, (blk >> 1) * 18 + wg, lane);
                float2 e = make_float2(0.f, 0.f);
#pragma unroll
                for (int i = 0; i < 32; i++) e = cfma(lam, e, make_float2(d[4 * (i >> 1) + (i & 1)], d[4 * (i >> 1) + 2 + (i & 1)]));
                float2 cin = make_float2(0.f, 0.f);
                if (blk > 0) { bar_sync(2 + (wg ^ 1), 256); cin = lds64f(sb + G_CARRY + (wg ^ 1) * 256 + (8 * w + g) * 8); }
                float2 mine = cin;
#pragma unroll
                for (int q = 0; q < 4; q++) {
                    const float2 eq = make_float2(__shfl_sync(~0u, e.x, (lane & 28) + q), __shfl_sync(~0u, e.y, (lane & 28) + q));
                    cin = cfma(l32, cin, eq);
                    if (t == q + 1) mine = cin;
                }
                if (blk < 15) {
                    if (t == 0) sts64(sb + G_CARRY + wg * 256 + (8 * w + g) * 8, __float_as_uint(cin.x), __float_as_uint(cin.y));
                    bar_arrive(2 + wg, 256);
                }
                const uint32_t hs = sb + G_OUT + wg * 16384 + t * 4096 + (g & 3) * 4;
                const uint32_t ch = 2 * w + (g >> 2);
                if (blk >= 2) bar_sync(10 + wg, 160);
#pragma unroll
                for (int i = 0; i < 32; i++) {
                    mine = cfma(lam, mine, make_float2(d[4 * (i >> 1) + (i & 1)], d[4 * (i >> 1) + 2 + (i & 1)]));
                    sts32(hs + i * 128 + ((ch ^ (i & 7)) << 4), pack_bf16(mine.x, mine.y));
                }
                fence_async_smem();
                bar_arrive(8 + wg, 160);
            }
            bar_sync(10 + wg, 160);
        } else {
            if (tid < 128)
                asm volatile("cp.async.bulk.shared::cluster.global.mbarrier::complete_tx::bytes [%0], [%1], 1152, [%2];"
                    :: "r"(sb + tid * 1168), "l"((tid < 64 ? Cre : Cim) + (size_t)(64 * nt + (tid & 63)) * DM), "r"(sb + GB_W) : "memory");
            for (int p = tid; p < DM; p += 256) {
                float2 lam, coef;
                s5_channel(p, Lre, Lim, logdt, lam, coef);
                sts64(sb + G_EX + p * 8, __float_as_uint(2.f * coef.x), __float_as_uint(2.f * coef.y));
            }
            bar_sync(1, 256);
            mbar_wait(sb + GB_W, 0);
            const uint32_t cp = sb + (16 * w + 2 * g) * 1168 + (288 * wg + t) * 2;
#pragma unroll
            for (int u = 0; u < 72; u++) {
                const float2 c2 = lds64f(sb + G_EX + (288 * wg + 4 * u + t) * 8);
#pragma unroll
                for (int f = 0; f < 2; f++) {
                    unsigned short r16, i16;
                    asm volatile("ld.shared.u16 %0, [%1];" : "=h"(r16) : "r"(cp + f * 1168 + u * 8) : "memory");
                    asm volatile("ld.shared.u16 %0, [%1];" : "=h"(i16) : "r"(cp + (64 + f) * 1168 + u * 8) : "memory");
                    const float cr = __uint_as_float((uint32_t)r16 << 16), ci = __uint_as_float((uint32_t)i16 << 16);
                    a[2 * u + f] = pack_bf16(cr * c2.x - ci * c2.y, -(cr * c2.y + ci * c2.x));
                }
            }
            bar_sync(1, 256);
            bar_arrive(6, 288);
            BSTAMP(1);
#pragma unroll 1
            for (int j = 0; j < 8; j++) {
                bg_mainloop<9, 2>(d, a, sb, j * 18 + wg, lane);
                bg_epilogue<true>(d, sb, wg, w, lane, &tm_out, 64 * nt, (2 * j + kq - 2) * 128, xa, Dk);
            }
        }
        if (w == 0) asm volatile("cp.async.bulk.wait_group 0;" ::: "memory");
        bar_sync(1, 256);
        BSTAMP(2);
        if (warp == 0)
            asm volatile("{\n.reg .pred p;\nelect.sync _|p, 0xffffffff;\n@p mbarrier.arrive.expect_tx.shared::cta.b64 _, [%2], 131072;\n"
                "@p cp.async.bulk.tensor.2d.shared::cluster.global.mbarrier::complete_tx::bytes [%0], [%1, {%3, %4}], [%2];\n"
                "@p cp.async.bulk.tensor.2d.shared::cluster.global.mbarrier::complete_tx::bytes [%0+32768], [%1, {%3, %5}], [%2];\n"
                "@p cp.async.bulk.tensor.2d.shared::cluster.global.mbarrier::complete_tx::bytes [%0+65536], [%1, {%3, %6}], [%2];\n"
                "@p cp.async.bulk.tensor.2d.shared::cluster.global.mbarrier::complete_tx::bytes [%0+98304], [%1, {%3, %7}], [%2];\n}"
                :: "r"(sb), "l"(&tm_wo), "r"(sb + GB_W), "r"(64 * nt), "r"(1024 * kq), "r"(1024 * kq + 256), "r"(1024 * kq + 512), "r"(1024 * kq + 768) : "memory");
        mbar_wait(sb + GB_W, 1);
        {
            const uint32_t base = sb + wg * 65536 + 4 * t * 128 + (g & 3) * 4, ch = 2 * w + (g >> 2), r7 = (4 * t) & 7;
#pragma unroll
            for (int ks = 0; ks < 32; ks++) {
                const uint32_t w0 = lds32(base + ks * 2048 + ((ch ^ r7) << 4)), w1 = lds32(base + ks * 2048 + 256 + ((ch ^ (r7 + 2)) << 4));
                const uint32_t w2 = lds32(base + ks * 2048 + 128 + ((ch ^ (r7 + 1)) << 4)), w3 = lds32(base + ks * 2048 + 384 + ((ch ^ (r7 + 3)) << 4));
                a[4 * ks] = __byte_perm(w0, w1, 0x5410); a[4 * ks + 1] = __byte_perm(w0, w1, 0x7632);
                a[4 * ks + 2] = __byte_perm(w2, w3, 0x5410); a[4 * ks + 3] = __byte_perm(w2, w3, 0x7632);
            }
        }
        bar_sync(1, 256);
        bar_arrive(6, 288);
        BSTAMP(3);
#pragma unroll 1
        for (int na = 0, ng = 0, it = 144; ng < 16;) {
            if (bg_att_turn(na, ng)) {
                if (nt < 8) {
                    const int i0 = it + wg + 4 * (w >> 1), i1 = i0 + 2;
                    mbar_wait(sb + GB_FULL + 8 * (i0 % NST), (i0 / NST) & 1);
                    mbar_wait(sb + GB_FULL + 8 * (i1 % NST), (i1 / NST) & 1);
                    BSTAMP(8 + na * 4);
                    bg_attention(sb + G_RING + (i0 % NST) * 16384, sb + G_RING + (i1 % NST) * 16384, w & 1, lane);
                    fence_async_smem();
                    bar_arrive(7, 288);
                    bar_sync(1, 256);
                    BSTAMP(9 + na * 4);
                    it += 8;
                }
                na++;
            } else {
                bg_mainloop<8, 2>(d, a, sb, it + wg, lane);
                BSTAMP(10 + ng * 4);
                bg_epilogue<false>(d, sb, wg, w, lane, &tm_out, DM + 64 * nt, ng * 128, xa, Dk);
                BSTAMP(11 + ng * 4);
                it += 16; ng++;
            }
        }
    }
    asm volatile("griddepcontrol.wait;" ::: "memory");
}

typedef CUresult (*EncodeFn)(CUtensorMap*, CUtensorMapDataType, cuuint32_t, void*, const cuuint64_t*, const cuuint64_t*, const cuuint32_t*, const cuuint32_t*,
                             CUtensorMapInterleave, CUtensorMapSwizzle, CUtensorMapL2promotion, CUtensorMapFloatOOBfill);
}

extern "C" void kernel_launch(void* const* d_in, const int* in_sizes, int n_in, void* d_out, int out_size) {
    typedef const __nv_bfloat16* bp;
    bp Ax = (bp)d_in[0], Lre = (bp)d_in[1], Lim = (bp)d_in[2], Bre = (bp)d_in[3], Bim = (bp)d_in[4], Cre = (bp)d_in[5], Cim = (bp)d_in[6],
       logdt = (bp)d_in[7], Dk = (bp)d_in[8], Bx = (bp)d_in[9], mem0 = (bp)d_in[10], Wq = (bp)d_in[11], Wk = (bp)d_in[12], Wv = (bp)d_in[13], Wo = (bp)d_in[14];
    float* out = (float*)d_out;
    static EncodeFn enc = nullptr;
    if (!enc) {
        void* fn = nullptr; cudaDriverEntryPointQueryResult qr;
        cudaGetDriverEntryPoint("cuTensorMapEncodeTiled", &fn, cudaEnableDefault, &qr);
        enc = (EncodeFn)fn;
        cudaFuncSetAttribute(chain_kernel, cudaFuncAttributeMaxDynamicSharedMemorySize, CHAIN_SMEM);
        cudaFuncSetAttribute(bg_kernel, cudaFuncAttributeMaxDynamicSharedMemorySize, BG_SMEM);
    }
    const cuuint32_t es[5] = {1, 1, 1, 1, 1};
    auto map2d = [&](CUtensorMap* tm, CUtensorMapDataType dt, const void* p, cuuint64_t d0, cuuint64_t d1, cuuint64_t stride, cuuint32_t b0, cuuint32_t b1) {
        cuuint64_t gd[2] = {d0, d1}, gs[1] = {stride}; cuuint32_t bd[2] = {b0, b1};
        enc(tm, dt, 2, (void*)p, gd, gs, bd, es, CU_TENSOR_MAP_INTERLEAVE_NONE, CU_TENSOR_MAP_SWIZZLE_128B, CU_TENSOR_MAP_L2_PROMOTION_L2_128B,
            CU_TENSOR_MAP_FLOAT_OOB_FILL_NONE);
    };
    CUtensorMap tm_x, tm_q, tm_k, tm_v, tm_xa, tm_wo, tm_out;
    map2d(&tm_x, CU_TENSOR_MAP_DATA_TYPE_BFLOAT16, Bx, DM, SEQ, DM * 2, 64, 32);
    map2d(&tm_q, CU_TENSOR_MAP_DATA_TYPE_BFLOAT16, Wq, HD, DM, HD * 2, 64, 192);
    map2d(&tm_k, CU_TENSOR_MAP_DATA_TYPE_BFLOAT16, Wk, HD, DM, HD * 2, 64, 192);
    map2d(&tm_v, CU_TENSOR_MAP_DATA_TYPE_BFLOAT16, Wv, HD, DM, HD * 2, 64, 192);
    map2d(&tm_wo, CU_TENSOR_MAP_DATA_TYPE_BFLOAT16, Wo, DM, HD, DM * 2, 64, 256);
    map2d(&tm_out, CU_TENSOR_MAP_DATA_TYPE_FLOAT32, out, 2 * DM, SEQ, 2 * DM * 4, 32, 64);
    {
        cuuint64_t gd[5] = {DM, 2, 4, 16, 16}, gs[4] = {DM * 2, 32 * DM * 2, 2 * DM * 2, 128 * DM * 2}; cuuint32_t bd[5] = {64, 2, 4, 16, 1};
        enc(&tm_xa, CU_TENSOR_MAP_DATA_TYPE_BFLOAT16, 5, (void*)Ax, gd, gs, bd, es, CU_TENSOR_MAP_INTERLEAVE_NONE, CU_TENSOR_MAP_SWIZZLE_128B,
            CU_TENSOR_MAP_L2_PROMOTION_L2_128B, CU_TENSOR_MAP_FLOAT_OOB_FILL_NONE);
    }
    cudaStream_t st = cudaStreamPerThread;
    chain_kernel<<<96, 384, CHAIN_SMEM, st>>>(tm_x, tm_q, tm_k, tm_v, Bx, mem0, Wo);
    cudaLaunchConfig_t cfg = {};
    cfg.gridDim = dim3(36); cfg.blockDim = dim3(384); cfg.dynamicSmemBytes = BG_SMEM; cfg.stream = st;
    cudaLaunchAttribute at[1];
    at[0].id = cudaLaunchAttributeProgrammaticStreamSerialization; at[0].val.programmaticStreamSerializationAllowed = 1;
    cfg.attrs = at; cfg.numAttrs = 1;
    cudaLaunchKernelEx(&cfg, bg_kernel, tm_xa, tm_wo, tm_out, Ax, Lre, Lim, Bre, Bim, Cre, Cim, logdt, Dk);
}
```

```cpp
#include <cuda_runtime.h>
#include <cuda.h>
#include <cuda_bf16.h>
#include <cuda_fp16.h>
#include <stdint.h>

#define D_WAIT 740

#define BG_PACE 0
#define RED_GAP 720
#define ACC_PF 1
#define QDEP 0
#define BG_AHEAD 5

namespace {

constexpr int DM = 576, NH = 32, SEQ = 2048, NSEG = 64, HD = 4096;

__device__ uint4 g_acc_raw[64 * 96 * 16 + 131072];
__device__ uint4 g_ox[NH * 2 * SEQ * 8];
constexpr int REC = 30720;
__device__ uint4 g_qkv[NSEG * NH * (REC / 16)];
__device__ uint4 g_h[18 * SEQ * 8];
constexpr int NFLAG = 4096, F_QKV = 0, F_OX = 512, F_H = 1024, F_OUT = 2048;
__device__ unsigned g_flag[NFLAG];
__device__ unsigned g_ticket, g_ticket_bg;
__device__ unsigned long long g_norm[96];
#define BSTAMP(i) do {} while (0)

__device__ __forceinline__ uint32_t smem_u32(const void* p) { return (uint32_t)__cvta_generic_to_shared(p); }
__device__ __forceinline__ uint32_t mapa(uint32_t a, uint32_t r) { uint32_t o; asm("mapa.shared::cluster.u32 %0, %1, %2;" : "=r"(o) : "r"(a), "r"(r)); return o; }
__device__ __forceinline__ uint32_t mapa_v(uint32_t a, uint32_t r) { uint32_t o; asm volatile("mapa.shared::cluster.u32 %0, %1, %2;" : "=r"(o) : "r"(a), "r"(r)); return o; }
__device__ __forceinline__ unsigned clk() { unsigned long long c; asm volatile("mov.u64 %0, %%clock64;" : "=l"(c) :: "memory"); return (unsigned)c; }
__device__ __forceinline__ void mbar_init(uint32_t bar, uint32_t cnt) { asm volatile("mbarrier.init.shared::cta.b64 [%0], %1;" :: "r"(bar), "r"(cnt) : "memory"); }
__device__ __forceinline__ void mbar_expect(uint32_t bar, uint32_t bytes) { asm volatile("mbarrier.arrive.expect_tx.shared::cta.b64 _, [%0], %1;" :: "r"(bar), "r"(bytes) : "memory"); }
__device__ __forceinline__ void mbar_wait(uint32_t bar, uint32_t parity) {
    asm volatile("{\n.reg .pred p;\n.reg .u32 n;\nmov.u32 n, 0;\n"
                 "W_%=: mbarrier.try_wait.parity.shared::cta.b64 p, [%0], %1;\n@p bra.uni D_%=;\n"
                 "add.u32 n, n, 1;\nsetp.lt.u32 p, n, 4000000;\n@p bra.uni W_%=;\ntrap;\nD_%=:\n}" :: "r"(bar), "r"(parity) : "memory");
}
__device__ __forceinline__ void mbar_expect_if(uint32_t z, uint32_t bar, uint32_t bytes) {
    asm volatile("{\n.reg .pred p;\nsetp.eq.u32 p, %2, 0;\n@p mbarrier.arrive.expect_tx.shared::cta.b64 _, [%0], %1;\n}" :: "r"(bar), "r"(bytes), "r"(z) : "memory");
}
__device__ __forceinline__ void mbar_arrive_if(uint32_t z, uint32_t bar) {
    asm volatile("{\n.reg .pred p;\nsetp.eq.u32 p, %1, 0;\n@p mbarrier.arrive.shared::cta.b64 _, [%0];\n}" :: "r"(bar), "r"(z) : "memory");
}
__device__ __forceinline__ void sts32_if(uint32_t z, uint32_t a, uint32_t x) {
    asm volatile("{\n.reg .pred p;\nsetp.eq.u32 p, %2, 0;\n@p st.shared.u32 [%0], %1;\n}" :: "r"(a), "r"(x), "r"(z) : "memory");
}
template <int K> __device__ __forceinline__ void sched_fence(int v) {
    asm volatile("{\n.reg .pred p;\nsetp.ne.s32 p, %0, %1;\n@p bra.uni F_%=;\ntrap;\nF_%=:\n}" :: "r"(v), "n"(1000 + K) : "memory");
}
__device__ __forceinline__ void spin_until(unsigned t0, unsigned d) {
    asm volatile("{\n.reg .pred p;\n.reg .u64 c;\n.reg .u32 lo;\n"
                 "S_%=: mov.u64 c, %%clock64;\ncvt.u32.u64 lo, c;\nsub.u32 lo, lo, %0;\nsetp.lt.u32 p, lo, %1;\n@p bra.uni S_%=;\n}" :: "r"(t0), "r"(d) : "memory");
}
__device__ __forceinline__ void bar_sync(int id, int n) { asm volatile("bar.sync %0, %1;" :: "r"(id), "r"(n) : "memory"); }
__device__ __forceinline__ void bar_sync_sel(int sel, int id) {
    asm volatile("{\n.reg .pred p;\nsetp.eq.u32 p, %0, 0;\n@p bar.sync %1, %3;\n@!p bar.sync %2, %3;\n}" :: "r"(sel), "r"(id), "r"(id + 1), "n"(192) : "memory");
}
__device__ __forceinline__ void bar_arrive(int id, int n) { asm volatile("bar.arrive %0, %1;" :: "r"(id), "r"(n) : "memory"); }
__device__ __forceinline__ void fence_async_smem() { asm volatile("fence.proxy.async.shared::cta;" ::: "memory"); }
__device__ __forceinline__ uint32_t pack_bf16(float lo, float hi) { uint32_t r; asm("cvt.rn.bf16x2.f32 %0, %1, %2;" : "=r"(r) : "f"(hi), "f"(lo)); return r; }
__device__ __forceinline__ uint32_t pack_f16(float lo, float hi) { uint32_t r; asm("cvt.rn.f16x2.f32 %0, %1, %2;" : "=r"(r) : "f"(hi), "f"(lo)); return r; }
__device__ __forceinline__ uint32_t f16x2_to_bf16x2(uint32_t v) { float2 f = __half22float2(*reinterpret_cast<__half2*>(&v)); return pack_bf16(f.x, f.y); }
__device__ __forceinline__ uint32_t hmul2(uint32_t a, uint32_t b) { uint32_t r; asm("mul.rn.f16x2 %0, %1, %2;" : "=r"(r) : "r"(a), "r"(b)); return r; }
__device__ __forceinline__ float ex2(float x) { float y; asm("ex2.approx.ftz.f32 %0, %1;" : "=f"(y) : "f"(x)); return y; }
__device__ __forceinline__ float ex2v(float x) { float y; asm volatile("ex2.approx.ftz.f32 %0, %1;" : "=f"(y) : "f"(x)); return y; }
__device__ __forceinline__ uint32_t absmax2(uint32_t a, uint32_t b) {
    uint32_t r; asm("max.xorsign.abs.f16x2 %0, %1, %2;" : "=r"(r) : "r"(a), "r"(b)); return r;
}
__device__ __forceinline__ uint32_t shl_v(uint32_t a, int n) { return a << n; }
__device__ __forceinline__ uint32_t max3u(uint32_t a, uint32_t b, uint32_t c) { return max(max(a, b), c); }
__device__ __forceinline__ uint4 lds128(uint32_t a) { uint4 v; asm volatile("ld.shared.v4.u32 {%0,%1,%2,%3}, [%4];" : "=r"(v.x), "=r"(v.y), "=r"(v.z), "=r"(v.w) : "r"(a) : "memory"); return v; }
__device__ __forceinline__ uint4 lds128v(uint32_t a) { uint4 v; asm volatile("ld.volatile.shared.v4.u32 {%0,%1,%2,%3}, [%4];" : "=r"(v.x), "=r"(v.y), "=r"(v.z), "=r"(v.w) : "r"(a) : "memory"); return v; }
__device__ __forceinline__ float4 lds128f(uint32_t a) { float4 v; asm volatile("ld.shared.v4.f32 {%0,%1,%2,%3}, [%4];" : "=f"(v.x), "=f"(v.y), "=f"(v.z), "=f"(v.w) : "r"(a) : "memory"); return v; }
__device__ __forceinline__ float2 lds64f(uint32_t a) { float2 v; asm volatile("ld.shared.v2.f32 {%0,%1}, [%2];" : "=f"(v.x), "=f"(v.y) : "r"(a) : "memory"); return v; }
__device__ __forceinline__ uint4 lds64x2(uint32_t a) { uint4 v; asm volatile("ld.shared.v2.u32 {%0,%1}, [%4];\nld.shared.v2.u32 {%2,%3}, [%4+256];" : "=r"(v.x), "=r"(v.y), "=r"(v.z), "=r"(v.w) : "r"(a) : "memory"); return v; }
__device__ __forceinline__ uint32_t lds32(uint32_t a) { uint32_t v; asm volatile("ld.shared.u32 %0, [%1];" : "=r"(v) : "r"(a) : "memory"); return v; }
__device__ __forceinline__ void sts128(uint32_t a, uint32_t x, uint32_t y, uint32_t z, uint32_t w) { asm volatile("st.shared.v4.u32 [%0], {%1,%2,%3,%4};" :: "r"(a), "r"(x), "r"(y), "r"(z), "r"(w) : "memory"); }
__device__ __forceinline__ void sts128f(uint32_t a, float x, float y, float z, float w) { asm volatile("st.shared.v4.f32 [%0], {%1,%2,%3,%4};" :: "r"(a), "f"(x), "f"(y), "f"(z), "f"(w) : "memory"); }
__device__ __forceinline__ void sts64(uint32_t a, uint32_t x, uint32_t y) { asm volatile("st.shared.v2.u32 [%0], {%1,%2};" :: "r"(a), "r"(x), "r"(y) : "memory"); }
__device__ __forceinline__ void sts32(uint32_t a, uint32_t x) { asm volatile("st.shared.u32 [%0], %1;" :: "r"(a), "r"(x) : "memory"); }
__device__ __forceinline__ uint4 ldsm4(uint32_t a) { uint4 v; asm volatile("ldmatrix.sync.aligned.m8n8.x4.shared.b16 {%0,%1,%2,%3}, [%4];" : "=r"(v.x), "=r"(v.y), "=r"(v.z), "=r"(v.w) : "r"(a) : "memory"); return v; }
__device__ __forceinline__ void stsm2t(uint32_t a, uint32_t x, uint32_t y) { asm volatile("stmatrix.sync.aligned.m8n8.x2.trans.shared.b16 [%0], {%1,%2};" :: "r"(a), "r"(x), "r"(y) : "memory"); }
__device__ __forceinline__ void stsm4t(uint32_t a, uint32_t x, uint32_t y, uint32_t z, uint32_t w) { asm volatile("stmatrix.sync.aligned.m8n8.x4.trans.shared.b16 [%0], {%1,%2,%3,%4};" :: "r"(a), "r"(x), "r"(y), "r"(z), "r"(w) : "memory"); }
__device__ __forceinline__ void st_async64(uint32_t a, uint32_t x, uint32_t y, uint32_t bar) { asm volatile("st.async.shared::cluster.mbarrier::complete_tx::bytes.v2.b32 [%0], {%1,%2}, [%3];" :: "r"(a), "r"(x), "r"(y), "r"(bar) : "memory"); }
__device__ __forceinline__ void bulk_s2c(uint32_t dst, uint32_t src, uint32_t bytes, uint32_t bar) { asm volatile("cp.async.bulk.shared::cluster.shared::cta.mbarrier::complete_tx::bytes [%0], [%1], %2, [%3];" :: "r"(dst), "r"(src), "r"(bytes), "r"(bar) : "memory"); }
__device__ __forceinline__ void bulk_s2g(void* dst, uint32_t src, uint32_t bytes) { asm volatile("cp.async.bulk.global.shared::cta.bulk_group [%0], [%1], %2;" :: "l"(dst), "r"(src), "r"(bytes) : "memory"); }
__device__ __forceinline__ uint32_t ldg_nc32(const void* p) { uint32_t v; asm volatile("ld.global.nc.L2::128B.u32 %0, [%1];" : "=r"(v) : "l"(p)); return v; }
__device__ __forceinline__ uint4 ldg_relaxed128(const void* p) { uint4 v; asm volatile("ld.relaxed.gpu.global.v4.u32 {%0,%1,%2,%3}, [%4];" : "=r"(v.x), "=r"(v.y), "=r"(v.z), "=r"(v.w) : "l"(p) : "memory"); return v; }
__device__ __forceinline__ void mma16816(float (&d)[4], uint32_t a0, uint32_t a1, uint32_t a2, uint32_t a3, uint32_t b0, uint32_t b1) {
    asm volatile("mma.sync.aligned.m16n8k16.row.col.f32.bf16.bf16.f32 {%0,%1,%2,%3}, {%4,%5,%6,%7}, {%8,%9}, {%0,%1,%2,%3};"
        : "+f"(d[0]), "+f"(d[1]), "+f"(d[2]), "+f"(d[3]) : "r"(a0), "r"(a1), "r"(a2), "r"(a3), "r"(b0), "r"(b1));
}
__device__ __forceinline__ void mma16816_z(float (&d)[4], uint32_t a0, uint32_t a1, uint32_t a2, uint32_t a3, uint32_t b0, uint32_t b1) {
    asm volatile("mma.sync.aligned.m16n8k16.row.col.f32.bf16.bf16.f32 {%0,%1,%2,%3}, {%4,%5,%6,%7}, {%8,%9}, {%10,%10,%10,%10};"
        : "=f"(d[0]), "=f"(d[1]), "=f"(d[2]), "=f"(d[3]) : "r"(a0), "r"(a1), "r"(a2), "r"(a3), "r"(b0), "r"(b1), "f"(0.f));
}
__device__ __forceinline__ void mma1688(float (&d)[4], uint32_t a0, uint32_t a1, uint32_t b0) {
    asm volatile("mma.sync.aligned.m16n8k8.row.col.f32.bf16.bf16.f32 {%0,%1,%2,%3}, {%4,%5}, {%6}, {%0,%1,%2,%3};"
        : "+f"(d[0]), "+f"(d[1]), "+f"(d[2]), "+f"(d[3]) : "r"(a0), "r"(a1), "r"(b0));
}
__device__ __forceinline__ void mma1688_z(float (&d)[4], uint32_t a0, uint32_t a1, uint32_t b0) {
    asm volatile("mma.sync.aligned.m16n8k8.row.col.f32.bf16.bf16.f32 {%0,%1,%2,%3}, {%4,%5}, {%6}, {%7,%7,%7,%7};"
        : "=f"(d[0]), "=f"(d[1]), "=f"(d[2]), "=f"(d[3]) : "r"(a0), "r"(a1), "r"(b0), "f"(0.f));
}
template <int ACC>
__device__ __forceinline__ void wgmma_n32_rs(float (&d)[16], uint32_t a0, uint32_t a1, uint32_t a2, uint32_t a3, uint64_t desc) {
    asm volatile("wgmma.mma_async.sync.aligned.m64n32k16.f32.bf16.bf16 {%0,%1,%2,%3,%4,%5,%6,%7,%8,%9,%10,%11,%12,%13,%14,%15}, {%16,%17,%18,%19}, %20, %21, 1, 1, 0;"
        : "+f"(d[0]), "+f"(d[1]), "+f"(d[2]), "+f"(d[3]), "+f"(d[4]), "+f"(d[5]), "+f"(d[6]), "+f"(d[7]),
          "+f"(d[8]), "+f"(d[9]), "+f"(d[10]), "+f"(d[11]), "+f"(d[12]), "+f"(d[13]), "+f"(d[14]), "+f"(d[15])
        : "r"(a0), "r"(a1), "r"(a2), "r"(a3), "l"(desc), "n"(ACC));
}
template <int ACC>
__device__ __forceinline__ void wgmma_n32_ss(float (&d)[16], uint64_t da, uint64_t db) {
    asm volatile("wgmma.mma_async.sync.aligned.m64n32k16.f32.bf16.bf16 {%0,%1,%2,%3,%4,%5,%6,%7,%8,%9,%10,%11,%12,%13,%14,%15}, %16, %17, %18, 1, 1, 0, 0;"
        : "+f"(d[0]), "+f"(d[1]), "+f"(d[2]), "+f"(d[3]), "+f"(d[4]), "+f"(d[5]), "+f"(d[6]), "+f"(d[7]),
          "+f"(d[8]), "+f"(d[9]), "+f"(d[10]), "+f"(d[11]), "+f"(d[12]), "+f"(d[13]), "+f"(d[14]), "+f"(d[15])
        : "l"(da), "l"(db), "n"(ACC));
}
__device__ __forceinline__ void wg_fence() { asm volatile("wgmma.fence.sync.aligned;" ::: "memory"); }
__device__ __forceinline__ void wg_commit() { asm volatile("wgmma.commit_group.sync.aligned;" ::: "memory"); }
__device__ __forceinline__ void wg_wait0() { asm volatile("wgmma.wait_group.sync.aligned 0;" ::: "memory"); }
__device__ __forceinline__ void cluster_sync() { asm volatile("barrier.cluster.arrive.aligned;\nbarrier.cluster.wait.aligned;" ::: "memory"); }

#define STAMP(s, i) do {} while (0)
#define STAMPV(s, i, v) do {} while (0)

constexpr int XT_BYTES = 36864;
constexpr int O_XT = 0;
constexpr int O_STG = XT_BYTES;
constexpr int O_AS = 3 * XT_BYTES;
constexpr int O_XP = O_AS + 16384;
constexpr int O_QKX = O_XP + 8192;
constexpr int O_KM = O_QKX + 8192;
constexpr int O_QM = O_QKX + 10240;
constexpr int O_VX = O_STG + 147456;
constexpr int O_VM = O_VX + 16384;
constexpr int O_SC = O_VM + 2048;
constexpr int O_OF = O_SC + 2560;
constexpr int O_AF = O_OF + 2048;
constexpr int O_WP = O_AF + 4096;
constexpr int O_MF = O_WP + 2048;
constexpr int O_MISC = O_MF + 9216;
static_assert(O_QKX + 24576 <= O_VX, "smem");
constexpr int O_BAR = O_MISC + 64;
constexpr int CHAIN_SMEM = O_BAR + 128;
static_assert(CHAIN_SMEM <= 232448, "smem");
constexpr int B_X = O_BAR, B_VX = O_BAR + 24, B_SC = O_BAR + 40, B_W = O_BAR + 48;
constexpr float SM_SCALE = 0.08838834764831845f * 1.4426950408889634f;
constexpr uint32_t ONES = 0x3f803f80u;

__device__ __forceinline__ uint32_t opaque(uint32_t v) { uint32_t o; asm volatile("mov.u32 %0, %1;" : "=r"(o) : "r"(v)); return o; }
__device__ __forceinline__ void st_async128(uint32_t a, uint32_t x, uint32_t y, uint32_t z, uint32_t w, uint32_t bar) {
    asm volatile("st.async.shared::cluster.mbarrier::complete_tx::bytes.v4.b32 [%0], {%1,%2,%3,%4}, [%5];" :: "r"(a), "r"(x), "r"(y), "r"(z), "r"(w), "r"(bar) : "memory");
}
__device__ __forceinline__ void tma_x_tile(uint32_t sb, const CUtensorMap* tm, int r, int j, int slot) {
    asm volatile("{\n.reg .pred p;\nelect.sync _|p, 0xffffffff;\n"
        "@p mbarrier.arrive.expect_tx.shared::cta.b64 _, [%2], 36864;\n"
        "@p cp.async.bulk.tensor.2d.shared::cluster.global.mbarrier::complete_tx::bytes.multicast::cluster [%0], [%1, {%3, %4}], [%2], %7;\n"
        "@p cp.async.bulk.tensor.2d.shared::cluster.global.mbarrier::complete_tx::bytes.multicast::cluster [%0+4096], [%1, {%5, %4}], [%2], %7;\n"
        "@p cp.async.bulk.tensor.2d.shared::cluster.global.mbarrier::complete_tx::bytes.multicast::cluster [%0+8192], [%1, {%6, %4}], [%2], %7;\n}"
        :: "r"(sb + O_XT + slot * XT_BYTES + 3 * r * 4096), "l"(tm), "r"(sb + B_X + 8 * slot), "r"(192 * r), "r"(j * 32), "r"(192 * r + 64), "r"(192 * r + 128),
           "h"((unsigned short)7) : "memory");
}
__device__ __forceinline__ void flag_inc_if(uint32_t z, unsigned* p) {
    asm volatile("{\n.reg .pred p;\nsetp.eq.u32 p, %1, 0;\n@p red.release.gpu.global.inc.u32 [%0], 0xfffffffe;\n}" :: "l"(p), "r"(z) : "memory");
}
__device__ __forceinline__ float quad_max(float v) {
    const float a = __shfl_xor_sync(~0u, v, 1), b = __shfl_xor_sync(~0u, v, 2), c = __shfl_xor_sync(~0u, v, 3);
    return fmaxf(fmaxf(v, a), fmaxf(b, c));
}
__device__ __forceinline__ void load_scores(float (&p)[10], uint32_t base, uint32_t stride, uint32_t l16) {
    const float4 a0 = lds128f(base + l16), b0 = lds128f(base + stride + l16);
    const float4 a1 = lds128f(base + 512 + l16), b1 = lds128f(base + stride + 512 + l16);
    const float2 a2 = lds64f(base + 1024 + (l16 >> 1)), b2 = lds64f(base + stride + 1024 + (l16 >> 1));
    p[0] = a2.x + b2.x; p[1] = a2.y + b2.y;
    p[2] = a0.x + b0.x; p[3] = a0.y + b0.y; p[4] = a0.z + b0.z; p[5] = a0.w + b0.w;
    p[6] = a1.x + b1.x; p[7] = a1.y + b1.y; p[8] = a1.z + b1.z; p[9] = a1.w + b1.w;
}
__device__ __forceinline__ float rcp_fast(float x) { float y; asm("rcp.approx.ftz.f32 %0, %1;" : "=f"(y) : "f"(x)); return y; }

__global__ void __cluster_dims__(3, 1, 1) __launch_bounds__(384, 1)
chain_kernel(const __grid_constant__ CUtensorMap tm_x, const __grid_constant__ CUtensorMap tm_q,
             const __grid_constant__ CUtensorMap tm_k, const __grid_constant__ CUtensorMap tm_v,
             const __nv_bfloat16* __restrict__ x, const __nv_bfloat16* __restrict__ mem0,
             const __nv_bfloat16* __restrict__ Wo) {
    extern __shared__ __align__(1024) uint8_t smem_raw[];
    const uint32_t sb = smem_u32(smem_raw);
    const int lane = threadIdx.x & 31;
    const int warp = __shfl_sync(~0u, threadIdx.x >> 5, 0);
    const int wg = warp >> 2, w = warp & 3;
    const int h = blockIdx.x / 3, r = blockIdx.x - 3 * h;
    uint4* const g_acc = reinterpret_cast<uint4*>((reinterpret_cast<uintptr_t>(g_acc_raw) + 0x1fffff) & ~(uintptr_t)0x1fffff);

#define PSTAMP(i) do {} while (0)
    if (threadIdx.x == 0) {
        if (sb & 1023u) __trap();
        for (int i = 0; i < 9; i++) mbar_init(sb + O_BAR + 8 * i, 1);
        asm volatile("fence.mbarrier_init.release.cluster;" ::: "memory");
        for (int i = 0; i < 3; i++) {
            mbar_expect(sb + B_W + 8 * i, 49152);
            for (int tl = 0; tl < 2; tl++)
                asm volatile("cp.async.bulk.tensor.2d.shared::cluster.global.mbarrier::complete_tx::bytes [%0], [%1, {%3, %4}], [%2];"
                    :: "r"(sb + O_STG + tl * 73728 + i * 24576), "l"(r < 2 ? (tl ? &tm_k : &tm_q) : &tm_v), "r"(sb + B_W + 8 * i),
                       "r"(h * 128 + 64 * (r < 2 ? r : tl)), "r"(192 * i) : "memory");
        }
    }
    __syncwarp();
    asm volatile("barrier.cluster.arrive.relaxed.aligned;" ::: "memory");
    asm volatile("griddepcontrol.launch_dependents;" ::: "memory");
    if (warp == 0) PSTAMP(9);
    const uint32_t l16c = __shfl_sync(~0u, lane * 16, lane);

    if (wg < 2) {
#define KS(u) ((u) < 8 ? 12 * ((u) >> 2) + (((u) >> 1) & 1) + 4 * ((u) & 1) : (u) < 12 ? (u) : (u) < 16 ? (u) + 8 : (u) < 24 ? 24 + (((u) - 16) >> 1) + 4 * ((u) & 1) : (u) + 8)
        asm volatile("setmaxnreg.inc.sync.aligned.u32 184;");
        uint32_t a[144];
        uint32_t adr1;
        {
            const int g = lane >> 2, t = lane & 3;
            const int t1 = threadIdx.x;
#pragma unroll
            for (int i = 0; i < 2; i++) g_acc[(blockIdx.x * 64 + i * 32 + (t1 >> 3)) * 16 + (t1 & 7)] = make_uint4(0, 0, 0, 0);
            __threadfence();
            asm volatile("barrier.cluster.wait.aligned;" ::: "memory");
            const uint32_t ev = sb + O_STG + (2 * t) * 128 + (((2 * w + (g >> 2)) ^ (2 * t)) << 4) + (g & 3) * 4;
            const uint32_t od = (ev ^ 16) + 128;
            auto gather = [&](int dst, uint32_t off) {
                a[dst] = lds32(ev + off); a[dst + 1] = lds32(od + off); a[dst + 2] = lds32(ev + off + 1024); a[dst + 3] = lds32(od + off + 1024);
            };
            const uint4* xp = reinterpret_cast<const uint4*>(x) + blockIdx.x * 1536 + t1;
            uint4 xv[6];
#pragma unroll
            for (int th = 0; th < 2; th++) {
                mbar_wait(sb + B_W + 8 * th, 0);
                if (th == 1) {
#pragma unroll
                    for (int i = 0; i < 6; i++) xv[i] = __ldg(xp + i * 256);
                }
#pragma unroll
                for (int u = 4 * th; u < 4 * th + 4; u++) {
                    gather(32 + 4 * u, wg * (73728 + 4096) + KS(u) * 2048);
                    gather(4 * u, 73728 - wg * (73728 - 4096) + KS(u) * 2048);
                    gather(64 + 4 * u, wg * 73728 + KS(8 + u) * 2048);
                }
            }
            mbar_wait(sb + B_W + 16, 0);
#pragma unroll
            for (int u = 16; u < 28; u++) gather(32 + 4 * u, wg * 73728 + KS(u) * 2048);
#pragma unroll
            for (int kk = 0; kk < 72; kk++) {
                uint32_t w0 = a[2 * kk], w1 = a[2 * kk + 1];
                a[2 * kk] = __byte_perm(w0, w1, 0x5410);
                a[2 * kk + 1] = __byte_perm(w0, w1, 0x7632);
            }
            if (r == 2) {
                float n0[4], n1[4];
#pragma unroll
                for (int u = 0; u < 36; u++) {
                    const uint32_t x0 = a[4 * u] & 0x7fff7fffu, x1 = a[4 * u + 1] & 0x7fff7fffu, x2 = a[4 * u + 2] & 0x7fff7fffu, x3 = a[4 * u + 3] & 0x7fff7fffu;
                    if (u == 0) mma16816_z(n0, x0, x1, x2, x3, ONES, ONES);
                    else if (u < 8) mma16816(n0, x0, x1, x2, x3, ONES, ONES);
                    else if (u == 8) mma16816_z(n1, x0, x1, x2, x3, ONES, ONES);
                    else mma16816(n1, x0, x1, x2, x3, ONES, ONES);
                }
                const uint32_t mx = __reduce_max_sync(~0u, __float_as_uint(2.f * fmaxf(fmaxf(n0[0], n0[2]), fmaxf(n1[0], n1[2]))));
                sts32_if(lane, sb + O_MISC + 32 + 4 * warp, mx);
            }
            uint32_t xm = 0;
#pragma unroll
            for (int i = 0; i < 6; i++)
                xm = __vmaxu2(xm, __vmaxu2(__vmaxu2(xv[i].x & 0x7fff7fffu, xv[i].y & 0x7fff7fffu), __vmaxu2(xv[i].z & 0x7fff7fffu, xv[i].w & 0x7fff7fffu)));
            sts32_if(lane, sb + O_OF + 16 + 4 * warp, __reduce_max_sync(~0u, max(xm << 16, xm & 0xffff0000u)));
            if (warp == 0) PSTAMP(11);
            bar_arrive(7, 384);
            asm volatile("barrier.cluster.arrive.relaxed.aligned;" ::: "memory");
            bar_sync(1, 256);
            const uint32_t as = sb + O_AS + wg * 8192 + (16 * w + g) * 128 + t * 4;
            sts32(as + (g << 4), a[32]);
            sts32(as + 1024 + (g << 4), a[33]);
            sts32(as + ((1 ^ g) << 4), a[34]);
            sts32(as + 1024 + ((1 ^ g) << 4), a[35]);
            sts128(sb + O_AF + warp * 512 + lane * 16, a[32], a[33], a[34], a[35]);
            fence_async_smem();
            bar_sync(1, 256);
            const uint32_t l = lane * 16;
            const int mi = lane >> 3, isk = (mi >> 1) ? wg : (wg ^ 1);
            adr1 = (r == 2) ? (sb + O_VM + warp * 256 + (l >> 1))
                            : (isk ? (sb + O_KM + w * 512 + wg * 256 + (mi & 1) * 128 + (l & 127))
                                   : (sb + O_QM + w * 512 + (mi & 1) * 256 + wg * 128 + (l & 127)));
            adr1 = __shfl_sync(~0u, adr1, lane);
        }
        int s3 = 2;
#pragma unroll 1
        for (int s = -1; s < NSEG; s++) {
            const uint32_t l16 = opaque(l16c);
            s3 = (s3 == 2) ? 0 : s3 + 1;
            if (s < 0) mbar_wait(sb + B_X, 0);
            const uint64_t desc0 = (uint64_t)(((sb + O_XT + s3 * XT_BYTES) & 0x3FFFF) >> 4) | (1ull << 16) | (64ull << 32) | (1ull << 62);
            uint32_t km0 = 0, km1 = 0;
            if (s >= 0) {
                { const uint4 v = lds128(sb + O_AF + warp * 512 + l16); a[32] = v.x; a[33] = v.y; a[34] = v.z; a[35] = v.w; }
                float co[4], cw[3][4];
                uint4 b[14];
                float inv;
#define GORD(i) ((i) < 8 ? 2 * ((i) >> 2) + (((i) >> 1) & 1) + 4 * ((i) & 1) : (i))
                auto qkv_mma = [&](int i) {
                    const int gi = GORD(i), u = 8 * gi, n0 = 2 * i, n1 = 2 * i + 1;
                    if (gi < 4) {
                        if (i == 0) mma16816_z(co, a[u], a[u + 1], a[u + 2], a[u + 3], b[0].x, b[0].y);
                        else mma16816(co, a[u], a[u + 1], a[u + 2], a[u + 3], b[i].x, b[i].y);
                    }
                    if (n0 < 3) mma16816_z(cw[n0 % 3], a[32 + u], a[32 + u + 1], a[32 + u + 2], a[32 + u + 3], b[i].x, b[i].y);
                    else mma16816(cw[n0 % 3], a[32 + u], a[32 + u + 1], a[32 + u + 2], a[32 + u + 3], b[i].x, b[i].y);
                    if (n1 < 3) mma16816_z(cw[n1 % 3], a[32 + u + 4], a[32 + u + 5], a[32 + u + 6], a[32 + u + 7], b[i].z, b[i].w);
                    else mma16816(cw[n1 % 3], a[32 + u + 4], a[32 + u + 5], a[32 + u + 6], a[32 + u + 7], b[i].z, b[i].w);
                    if (gi < 4) mma16816(co, a[u + 4], a[u + 5], a[u + 6], a[u + 7], b[i].z, b[i].w);
                };
                const uint32_t mf = sb + O_MF + l16, mfs = mf + wg * 1024;
                const uint32_t qb = (s & 1) * 12288;
                bar_sync(2, 384);
                if (warp == 0) STAMP(s, 0);
                auto qkv_ld = [&](int i) {
                    const int gi = GORD(i);
                    b[i] = gi < 4 ? lds128v(mfs + (gi >> 1) * 3072 + (gi & 1) * 512) : lds128v(mf + (gi < 6 ? gi : gi + 4) * 512);
                };
#pragma unroll
                for (int i = 0; i < 4; i++) qkv_ld(i);
                qkv_mma(0); qkv_mma(1); qkv_mma(2);
                const uint32_t z0 = __float_as_uint(QDEP ? co[0] : cw[1][0]) & (l16 & 15u);
                qkv_mma(3);
                bar_sync(15, 384);
                b[4] = lds128v(mfs + 3072 + z0);
#pragma unroll
                for (int i = 5; i < 9; i++) qkv_ld(i);
#pragma unroll
                for (int i = 4; i < 9; i++) { qkv_mma(i); qkv_ld(5 + i); }
                asm volatile("ld.volatile.shared.f32 %0, [%1];" : "=f"(inv) : "r"(sb + O_MISC) : "memory");
#pragma unroll
                for (int i = 9; i < 14; i++) qkv_mma(i);
#pragma unroll
                for (int i = 0; i < 4; i++) cw[0][i] += cw[1][i] + cw[2][i];
                if (r < 2) {
                    const uint32_t o0 = pack_bf16(co[0] * inv, co[1] * inv), o1 = pack_bf16(co[2] * inv, co[3] * inv);
                    const uint32_t w0 = pack_bf16(cw[0][0] * inv, cw[0][1] * inv), w1 = pack_bf16(cw[0][2] * inv, cw[0][3] * inv);
                    stsm4t(adr1 + qb, o0, o1, w0, w1);
                    if (warp == 0) STAMP(s, 1);
                    asm volatile("{\n.reg .pred p;\nsetp.ge.u32 p, %0, 3;\n@p bar.arrive 1, 256;\n}" :: "r"(warp) : "memory");
                    auto scores = [&](float (&v)[4], const uint4 (&q)[4], const uint4 (&k)[4]) {
                        float s0[4], s1[4], t0[4], t1[4];
                        mma16816_z(s0, q[0].x, q[0].y, q[0].z, q[0].w, k[0].x, k[0].y);
                        mma16816_z(s1, q[0].x, q[0].y, q[0].z, q[0].w, k[0].z, k[0].w);
                        mma16816_z(t0, q[1].x, q[1].y, q[1].z, q[1].w, k[1].x, k[1].y);
                        mma16816_z(t1, q[1].x, q[1].y, q[1].z, q[1].w, k[1].z, k[1].w);
                        mma16816(s0, q[2].x, q[2].y, q[2].z, q[2].w, k[2].x, k[2].y);
                        mma16816(s1, q[2].x, q[2].y, q[2].z, q[2].w, k[2].z, k[2].w);
                        mma16816(t0, q[3].x, q[3].y, q[3].z, q[3].w, k[3].x, k[3].y);
                        mma16816(t1, q[3].x, q[3].y, q[3].z, q[3].w, k[3].z, k[3].w);
                        v[0] = (s0[0] + s0[2]) + (t0[0] + t0[2]); v[1] = (s0[1] + s0[3]) + (t0[1] + t0[3]);
                        v[2] = (s1[0] + s1[2]) + (t1[0] + t1[2]); v[3] = (s1[1] + s1[3]) + (t1[1] + t1[3]);
                    };
                    if (warp < 2) {
                        uint4 q[4], k[4]; float v[4];
#pragma unroll
                        for (int i = 0; i < 4; i++) k[i] = ldsm4(sb + O_QKX + 4096 + qb + warp * 2048 + i * 512 + l16);
                        bar_sync(1, 256);
#pragma unroll
                        for (int i = 0; i < 4; i++) q[i] = ldsm4(sb + O_QM + qb + i * 512 + l16);
                        scores(v, q, k);
                        const uint32_t dst = sb + O_SC + r * 1280 + warp * 512 + l16;
                        st_async128(mapa(dst, 2), __float_as_uint(v[0]), __float_as_uint(v[1]), __float_as_uint(v[2]), __float_as_uint(v[3]), mapa(sb + B_SC, 2));
                        st_async128(mapa(dst, r ^ 1), __float_as_uint(v[0]), __float_as_uint(v[1]), __float_as_uint(v[2]), __float_as_uint(v[3]), mapa(sb + B_SC, r ^ 1));
                        st_async128(mapa(dst, r), __float_as_uint(v[0]), __float_as_uint(v[1]), __float_as_uint(v[2]), __float_as_uint(v[3]), mapa(sb + B_SC, r));
                    } else if (warp == 2) {
                        uint4 q[4], k[4]; float v[4];
                        bar_sync(1, 256);
#pragma unroll
                        for (int i = 0; i < 4; i++) { q[i] = ldsm4(sb + O_QM + qb + i * 512 + l16); k[i] = ldsm4(sb + O_KM + qb + i * 512 + l16); }
                        scores(v, q, k);
                        const uint32_t dst = sb + O_SC + r * 1280 + 1024 + (l16 >> 1);
                        st_async64(mapa(dst, 2), __float_as_uint(v[0] + v[2]), __float_as_uint(v[1] + v[3]), mapa(sb + B_SC, 2));
                        st_async64(mapa(dst, r ^ 1), __float_as_uint(v[0] + v[2]), __float_as_uint(v[1] + v[3]), mapa(sb + B_SC, r ^ 1));
                        st_async64(mapa(dst, r), __float_as_uint(v[0] + v[2]), __float_as_uint(v[1] + v[3]), mapa(sb + B_SC, r));
                        STAMP(s, 2);
                    }
                } else {
                    sts128f(sb + O_XP + warp * 512 + l16, co[0], co[1], co[2], co[3]);
                    bar_sync(8 + w, 64);
                    const float4 o = lds128f(sb + O_XP + (warp ^ 4) * 512 + l16);
                    km0 = pack_bf16((cw[0][0] + o.x) * inv, (cw[0][1] + o.y) * inv);
                    km1 = pack_bf16((cw[0][2] + o.z) * inv, (cw[0][3] + o.w) * inv);
                    if (warp == 0) STAMP(s, 1);
                    st_async64(mapa(adr1, 0), km0, km1, mapa(sb + B_SC, 0));
                    st_async64(mapa(adr1, 1), km0, km1, mapa(sb + B_SC, 1));
                    st_async64(mapa(adr1, 2), km0, km1, mapa(sb + B_SC, 2));
                    if (warp == 0) STAMP(s, 2);
                }
            }
            if (s >= 0) bar_sync(3, 384);
            auto store_qk = [&]() {
                asm volatile("{\n.reg .pred p;\nelect.sync _|p, 0xffffffff;\n"
                    "@p cp.async.bulk.global.shared::cta.bulk_group [%0], [%1], 10240;\n@p cp.async.bulk.commit_group;\n}"
                    :: "l"(reinterpret_cast<char*>(g_qkv) + (size_t)(s * NH + h) * REC + r * 10240), "r"(sb + O_QKX + (s & 1) * 12288) : "memory");
            };
            auto store_vm = [&]() {
                *reinterpret_cast<uint2*>(reinterpret_cast<char*>(g_qkv) + (size_t)(s * NH + h) * REC + 28672 + warp * 256 + (l16 >> 1)) = make_uint2(km0, km1);
            };
            if (s == NSEG - 1) {
                if (r == 2) store_vm();
                else if (warp == 3) {
                    fence_async_smem();
                    store_qk();
                    asm volatile("cp.async.bulk.wait_group 0;\nfence.proxy.async.global;" ::: "memory");
                }
            } else {
                const int j = s + 1;
#define XDESC(u) (((u) < 8 ? descs : desc0) + (uint64_t)(((KS(u) >> 2) * 4096 + (KS(u) & 3) * 32) >> 4))
                const uint64_t descs = desc0 + (uint64_t)(wg * 4);
                float d[16];
                wg_fence();
#pragma unroll
                for (int u = 0; u < 8; u++) {
                    if (u == 0) wgmma_n32_rs<0>(d, a[0], a[1], a[2], a[3], XDESC(0));
                    else wgmma_n32_rs<1>(d, a[4 * u], a[4 * u + 1], a[4 * u + 2], a[4 * u + 3], XDESC(u));
                }
                wg_commit();
                wg_wait0();
                if (warp == 0) STAMP(s, 15);
                if (warp == 3) asm volatile("cp.async.bulk.wait_group.read 0;" ::: "memory");
                if (s >= 0) bar_sync(4, 384);
#pragma unroll
                for (int q = 0; q < 2; q++)
                    sts128(sb + O_XP + warp * 1024 + q * 512 + l16, pack_bf16(d[8 * q], d[8 * q + 1]), pack_bf16(d[8 * q + 2], d[8 * q + 3]),
                           pack_bf16(d[8 * q + 4], d[8 * q + 5]), pack_bf16(d[8 * q + 6], d[8 * q + 7]));
                bar_sync(12, 256);
#pragma unroll
                for (int q = 0; q < 2; q++) {
                    const uint4 o = lds128(sb + O_XP + (warp ^ 4) * 1024 + q * 512 + l16);
                    d[8 * q] = __uint_as_float(o.x << 16); d[8 * q + 1] = __uint_as_float(o.x & 0xffff0000u);
                    d[8 * q + 2] = __uint_as_float(o.y << 16); d[8 * q + 3] = __uint_as_float(o.y & 0xffff0000u);
                    d[8 * q + 4] = __uint_as_float(o.z << 16); d[8 * q + 5] = __uint_as_float(o.z & 0xffff0000u);
                    d[8 * q + 6] = __uint_as_float(o.w << 16); d[8 * q + 7] = __uint_as_float(o.w & 0xffff0000u);
                }
                if (s >= 0) {
                    if (r == 2) store_vm();
                    if (warp == 5 && s + 2 < NSEG) tma_x_tile(sb, &tm_x, r, s + 2, s3 == 2 ? 0 : s3 + 1);
                    if (warp == 3) {
                        asm volatile("cp.async.bulk.wait_group 0;\nfence.proxy.async.global;" ::: "memory");
                        if ((s & 3) == 0 && s >= 4) {
                            __syncwarp();
                            flag_inc_if(l16, &g_flag[F_QKV + (s - 4 + (h >> 3)) * 8]);
                        }
                        fence_async_smem();
                    }
                    asm volatile("{\n.reg .pred p;\nsetp.eq.u32 p, %0, 0;\n@p bar.sync 5, 256;\n@!p bar.sync 13, 256;\n}" :: "r"(wg) : "memory");
                }
                const uint64_t da0 = (uint64_t)(((sb + O_AS + wg * 8192) & 0x3FFFF) >> 4) | (1ull << 16) | (64ull << 32) | (1ull << 62);
                wg_fence();
                wgmma_n32_ss<1>(d, da0, XDESC(0));
#pragma unroll
                for (int u = 1; u < 28; u++) wgmma_n32_rs<1>(d, a[32 + 4 * u], a[32 + 4 * u + 1], a[32 + 4 * u + 2], a[32 + 4 * u + 3], XDESC(u));
                wg_commit();
                wg_wait0();
                if (warp == 3 && r < 2 && s >= 0) store_qk();
                if (warp == 4) STAMP(s, 3);
                uint32_t e[8];
#pragma unroll
                for (int i = 0; i < 8; i++) e[i] = pack_bf16(d[2 * i], d[2 * i + 1]);
                if (r < 2) {
                    const uint32_t base = sb + O_QKX + (j & 1) * 12288 + wg * 4096 + w * 512 + l16;
                    stsm4t(base, e[0], wg ? e[1] : e[2], wg ? e[2] : e[1], e[3]);
                    stsm4t(base + 2048, e[4], wg ? e[5] : e[6], wg ? e[6] : e[5], e[7]);
                } else {
                    const uint32_t base = sb + O_VX + (j & 1) * 8192 + warp * 1024 + l16;
                    sts128(base, e[0], e[1], e[2], e[3]);
                    sts128(base + 512, e[4], e[5], e[6], e[7]);
                    bar_arrive(14, 288);
                }
                if (warp == 7) STAMP(s, 4);
                if (s < 0) asm volatile("barrier.cluster.wait.aligned;" ::: "memory");
            }
        }
        bar_arrive(7, 384);
    } else {
        asm volatile("setmaxnreg.dec.sync.aligned.u32 136;");
        const int c = w;
        uint32_t a[96];
        uint32_t mmax = 0;
        {
            const int g = lane >> 2, t = lane & 3;
            uint32_t tag = 0, m0v[18];
            if (threadIdx.x == 256) tag = atomicAdd(&g_ticket, 1u);
#pragma unroll
            for (int i = 0; i < 9; i++) {
                const uint32_t* p = reinterpret_cast<const uint32_t*>(mem0 + g * DM + 16 * (4 * i + c) + 2 * t);
                m0v[2 * i] = __ldg(p); m0v[2 * i + 1] = __ldg(p + 4);
            }
            asm volatile("barrier.cluster.wait.aligned;" ::: "memory");
            if (c == 0) {
                tma_x_tile(sb, &tm_x, r, 0, 0);
                mbar_expect_if(lane, sb + B_SC, 4608);
                if (r < 2) mbar_expect_if(lane, sb + B_VX, 8192);
                sts32_if(lane, sb + O_MISC, __float_as_uint(1.0f));
                sts32_if(lane, sb + O_MISC + 12, __float_as_uint(SM_SCALE));
            }
            asm volatile("barrier.cluster.arrive.relaxed.aligned;" ::: "memory");
#pragma unroll
            for (int tau = 0; tau < 3; tau++) {
                const uint32_t* v = m0v + 6 * tau;
                sts128(sb + O_MF + tau * 3072 + c * 512 + lane * 16, v[0], v[1], v[2], v[3]);
                sts64(sb + O_MF + tau * 3072 + 2048 + (c >> 1) * 512 + lane * 16 + (c & 1) * 8, v[4], v[5]);
#pragma unroll
                for (int i = 0; i < 6; i++) mmax = __vmaxu2(mmax, v[i] & 0x7fff7fffu);
            }
            mmax = max(mmax << 16, mmax & 0xffff0000u);
            bar_arrive(2, 384); bar_arrive(15, 384);
            tag = (__shfl_sync(~0u, tag, 0) / 96u + 1u) & 0xffffu;
            mbar_wait(sb + B_W + 0, 0);
            const __nv_bfloat16* p = Wo + (size_t)(h * 128 + 4 * t) * DM + 192 * r + 16 * c + 2 * g;
#pragma unroll
            for (int i = 0; i < 3; i++)
#pragma unroll
                for (int eb = 0; eb < 8; eb++)
#pragma unroll
                    for (int j = 0; j < 4; j++) a[(i * 8 + eb) * 4 + j] = ldg_nc32(p + (16 * eb + ((j & 1) * 2 + (j >> 1))) * DM + 64 * i);
#pragma unroll
            for (int kk = 0; kk < 48; kk++) {
                uint32_t w0 = a[2 * kk], w1 = a[2 * kk + 1];
                a[2 * kk] = __byte_perm(w0, w1, 0x5410);
                a[2 * kk + 1] = __byte_perm(w0, w1, 0x7632);
            }
            sts128(sb + O_WP + c * 512 + lane * 16, a[92], a[93], a[94], a[95]);
            float wmax = 0.f;
#pragma unroll
            for (int i = 0; i < 3; i++) {
                float n0[4];
#pragma unroll
                for (int u = 8 * i; u < 8 * i + 8; u++) {
                    const uint32_t x0 = a[4 * u] & 0x7fff7fffu, x1 = a[4 * u + 1] & 0x7fff7fffu, x2 = a[4 * u + 2] & 0x7fff7fffu, x3 = a[4 * u + 3] & 0x7fff7fffu;
                    if (u == 8 * i) mma16816_z(n0, x0, x1, x2, x3, ONES, ONES);
                    else mma16816(n0, x0, x1, x2, x3, ONES, ONES);
                }
                wmax = fmaxf(wmax, fmaxf(n0[0], n0[2]));
            }
            uint32_t wm = __reduce_max_sync(~0u, __float_as_uint(wmax));
            sts32_if(lane, sb + O_OF + 4 * c, wm);
            if (c == 0) PSTAMP(8);
            bar_sync(7, 384);
            asm volatile("barrier.cluster.wait.aligned;" ::: "memory");
            if (c == 1) tma_x_tile(sb, &tm_x, r, 1, 1);
            if (c == 0) {
                const uint4 wq = lds128(sb + O_OF), xq = lds128(sb + O_OF + 16), xr = lds128(sb + O_OF + 32), v0 = lds128(sb + O_MISC + 32), v1 = lds128(sb + O_MISC + 48);
                const uint32_t w1 = max(max(wq.x, wq.y), max(wq.z, wq.w)), x1 = max(max(max(xq.x, xq.y), max(xq.z, xq.w)), max(max(xr.x, xr.y), max(xr.z, xr.w)));
                const uint32_t vv = (r < 2) ? 0u : max(max(max(v0.x, v0.y), max(v0.z, v0.w)), max(max(v1.x, v1.y), max(v1.z, v1.w)));
                const uint32_t lo = (min(w1, 0x7f800000u) + 0xffffu) >> 16 | ((min(vv, 0x7f800000u) + 0xffffu) & 0xffff0000u), hi = (x1 & 0xffff0000u) | tag;
                uint32_t l0, h0, l1, h1, l2, h2;
                asm volatile("{\n.reg .pred p;\n.reg .u32 n, x, y;\n.reg .b64 v;\nsetp.eq.u32 p, %10, 0;\nmov.b64 v, {%8, %9};\n@p st.relaxed.gpu.global.b64 [%7], v;\nmov.u32 n, 0;\n"
                             "G_%=: ld.relaxed.gpu.global.b64 v, [%6];\nmov.b64 {%0, %1}, v;\nld.relaxed.gpu.global.b64 v, [%6+256];\nmov.b64 {%2, %3}, v;\n"
                             "ld.relaxed.gpu.global.b64 v, [%6+512];\nmov.b64 {%4, %5}, v;\n"
                             "xor.b32 x, %1, %9;\nxor.b32 y, %3, %9;\nor.b32 x, x, y;\nxor.b32 y, %5, %9;\nor.b32 x, x, y;\nand.b32 x, x, 0xffff;\n"
                             "setp.eq.u32 p, x, 0;\nvote.sync.all.pred p, p, 0xffffffff;\n@p bra.uni E_%=;\n"
                             "add.u32 n, n, 1;\nsetp.lt.u32 p, n, 4000000;\n@p bra.uni G_%=;\ntrap;\nE_%=:\n}"
                             : "=&r"(l0), "=&r"(h0), "=&r"(l1), "=&r"(h1), "=&r"(l2), "=&r"(h2)
                             : "l"(&g_norm[lane]), "l"(&g_norm[blockIdx.x]), "r"(lo), "r"(hi), "r"(lane) : "memory");
                const uint32_t lm = __vmaxu2(l0, __vmaxu2(l1, l2));
                const float fw = __uint_as_float(__reduce_max_sync(~0u, lm << 16));
                const float fv = __uint_as_float(__reduce_max_sync(~0u, lm & 0xffff0000u));
                const float xmax = __uint_as_float(__reduce_max_sync(~0u, max(h0, max(h1, h2)) & 0xffff0000u));
                const float G = 36.f * fw * fv;
                sts32_if(lane, sb + O_MISC + 4, __float_as_uint(G)); sts32_if(lane, sb + O_MISC + 8, __float_as_uint(G * xmax));
            }
        }
        if (c == 0) PSTAMP(12);
        bar_sync(6, 128);
        int s3n = 1;
        uint32_t roff = __shfl_sync(~0u, (r * 4 + c) * 2048 + (lane >> 4) * 512 + (lane & 2) * 128 + (lane & 1) * 64 + (lane & 12) * 4, lane);
#pragma unroll 1
        for (int s = 0; s < NSEG; s++) {
            const uint32_t l16 = opaque(l16c);
            const uint32_t vxa = sb + O_VX + (s & 1) * 8192 + c * 2048 + l16;
            if (c == 0 && r == 2) {
                bar_sync(14, 288);
                fence_async_smem();
                asm volatile("{\n.reg .pred p;\nelect.sync _|p, 0xffffffff;\n"
                    "@p cp.async.bulk.global.shared::cta.bulk_group [%0], [%1], 8192;\n@p cp.async.bulk.commit_group;\n"
                    "cp.async.bulk.wait_group 0;\nsetp.lt.and.s32 p, %4, 63, p;\n"
                    "@p cp.async.bulk.shared::cluster.global.mbarrier::complete_tx::bytes.multicast::cluster [%1], [%0], 8192, [%2], %3;\n"
                    "fence.proxy.async.global;\n}"
                    :: "l"(reinterpret_cast<char*>(g_qkv) + (size_t)(s * NH + h) * REC + 20480), "r"(sb + O_VX + (s & 1) * 8192),
                       "r"(sb + B_VX + 8 * (s & 1)), "h"((unsigned short)3), "r"(s) : "memory");
            }
            if (s == NSEG - 1) { bar_sync(3, 384); mbar_wait(sb + B_SC, s & 1); break; }
            uint4 vx[4];
            sts32_if(l16, sb + O_MISC + 16 + 4 * c, __reduce_max_sync(~0u, mmax));
            if (c == 0) STAMP(s, 5);
            {
                bar_sync(6, 128);
                const uint4 mm = lds128(sb + O_MISC + 16), cf = lds128(sb + O_MISC);
                const float bound = fmaxf(__uint_as_float(cf.z), __uint_as_float(cf.y) * (__uint_as_float(max(max(mm.x, mm.y), max(mm.z, mm.w))) * __uint_as_float(cf.x)));
                const uint32_t ebits = __reduce_max_sync(~0u, min(max(__float_as_uint(bound) & 0x7f800000u, 21u << 23), 254u << 23));
                mbar_wait(sb + B_X + 8 * s3n, ((s + 1) / 3) & 1);
                s3n = (s3n == 2) ? 0 : s3n + 1;
                bar_sync(3, 384);
                if (r < 2) mbar_wait(sb + B_VX + 8 * (s & 1), (s >> 1) & 1);
                vx[0] = lds128(vxa); vx[2] = lds128(vxa + 1024);
                if (c == 0) STAMP(s, 13);
                mbar_wait(sb + B_SC, s & 1);
                if (c == 0) STAMP(s, 6);
                float p[10];
                load_scores(p, sb + O_SC, 1280, l16);
                float mx = fmaxf(fmaxf(fmaxf(p[0], p[1]), fmaxf(p[2], p[3])), fmaxf(fmaxf(p[4], p[5]), fmaxf(p[6], p[7])));
                mx = quad_max(fmaxf(mx, fmaxf(p[8], p[9])));
                const uint4 vm = lds64x2(sb + O_VM + c * 512 + (l16 >> 1));
                vx[1] = lds128(vxa + 512); vx[3] = lds128(vxa + 1536);
                bar_arrive(4, 384);
                const float sc = __uint_as_float(lds32(sb + O_MISC + 12));
                const float mo = mx * SM_SCALE;
                uint32_t P[5];
#pragma unroll
                for (int n = 0; n < 5; n++) P[n] = pack_bf16(ex2(fmaf(p[2 * n], SM_SCALE, -mo)), ex2(fmaf(p[2 * n + 1], n == 3 ? sc : SM_SCALE, -mo)));
                if (c == 0) STAMP(s, 7);
                float o0[4], o1[4], sm[4];
                mma16816_z(sm, ONES, ONES, ONES, ONES, P[1], P[2]);
                mma16816_z(o0, vx[0].x, vx[0].y, vx[0].z, vx[0].w, P[1], P[2]);
                mma16816_z(o1, vx[2].x, vx[2].y, vx[2].z, vx[2].w, P[1], P[2]);
                mma16816(sm, ONES, ONES, ONES, ONES, P[3], P[4]);
                mma16816(o0, vx[1].x, vx[1].y, vx[1].z, vx[1].w, P[3], P[4]);
                mma16816(o1, vx[3].x, vx[3].y, vx[3].z, vx[3].w, P[3], P[4]);
                mma1688(sm, ONES, ONES, P[0]);
                mma1688(o0, vm.x, vm.y, P[0]);
                mma1688(o1, vm.z, vm.w, P[0]);
                const float sig = __uint_as_float((268u << 23) - ebits);
                const float r0 = rcp_fast(sm[0]) * sig, r1 = rcp_fast(sm[1]) * sig;
                stsm4t(sb + O_OF + c * 512 + l16, pack_bf16(o0[0] * r0, o0[1] * r1), pack_bf16(o0[2] * r0, o0[3] * r1),
                       pack_bf16(o1[0] * r0, o1[1] * r1), pack_bf16(o1[2] * r0, o1[3] * r1));
                bar_sync(6, 128);
                uint4 ob[4];
#pragma unroll
                for (int q = 0; q < 4; q++) ob[q] = ldsm4(sb + O_OF + q * 512 + l16);
                { const uint4 v = lds128(sb + O_WP + c * 512 + l16); a[92] = v.x; a[93] = v.y; a[94] = v.z; a[95] = v.w; }
                float m0[3][4], m1[3][4];
#pragma unroll
                for (int q = 0; q < 4; q++) {
#pragma unroll
                    for (int i = 0; i < 3; i++) {
                        const int k0 = (i * 8 + 2 * q) * 4;
                        if (q == 0) mma16816_z(m0[i], a[k0], a[k0 + 1], a[k0 + 2], a[k0 + 3], ob[q].x, ob[q].y);
                        else mma16816(m0[i], a[k0], a[k0 + 1], a[k0 + 2], a[k0 + 3], ob[q].x, ob[q].y);
                    }
#pragma unroll
                    for (int i = 0; i < 3; i++) {
                        const int k1 = (i * 8 + 2 * q + 1) * 4;
                        if (q == 0) mma16816_z(m1[i], a[k1], a[k1 + 1], a[k1 + 2], a[k1 + 3], ob[q].z, ob[q].w);
                        else mma16816(m1[i], a[k1], a[k1 + 1], a[k1 + 2], a[k1 + 3], ob[q].z, ob[q].w);
                    }
                }
                asm volatile("red.relaxed.gpu.global.add.noftz.v4.f16x2 [%0], {%1,%2,%3,%4};" :: "l"(reinterpret_cast<char*>(g_acc) + roff),
                    "r"(pack_f16(m0[0][0] + m1[0][0], m0[0][2] + m1[0][2])), "r"(pack_f16(m0[1][0] + m1[1][0], m0[1][2] + m1[1][2])),
                    "r"(pack_f16(m0[2][0] + m1[2][0], m0[2][2] + m1[2][2])), "r"(0x3c00u) : "memory");
                asm volatile("red.relaxed.gpu.global.add.noftz.v4.f16x2 [%0], {%1,%2,%3,%4};" :: "l"(reinterpret_cast<char*>(g_acc) + roff + 1024),
                    "r"(pack_f16(m0[0][1] + m1[0][1], m0[0][3] + m1[0][3])), "r"(pack_f16(m0[1][1] + m1[1][1], m0[1][3] + m1[1][3])),
                    "r"(pack_f16(m0[2][1] + m1[2][1], m0[2][3] + m1[2][3])), "r"(0x3c00u) : "memory");
                const unsigned t_red = clk();
                bar_arrive(5, 256);
                bar_arrive(13, 256);
                mbar_expect_if(l16 | c, sb + B_SC, 4608);
                mbar_expect_if(l16 | (c ^ 1) | (r >> 1), sb + B_VX + 8 * ((s + 1) & 1), 8192);
                sts32_if(l16 | (c ^ 3), sb + O_MISC, ebits - (14u << 23));
                if (c == 0) STAMPV(s, 8, t_red);
                if (ACC_PF && c == 2 && s + 4 < NSEG - 1)
                    asm volatile("prefetch.global.L2 [%0];" :: "l"(reinterpret_cast<const char*>(g_acc) + ((s + 4) * 96 + blockIdx.x) * 256 + (l16 & 96)) : "memory");
                const char* pbase = reinterpret_cast<const char*>(g_acc) + (s * 24576 + c * 2048) + ((l16 & 64) * 16 + (l16 & 256) + ((l16 & 128) >> 1) + (l16 & 48));
                spin_until(t_red, D_WAIT);
                uint4 v[6];
#pragma unroll
                for (int i = 0; i < 6; i++) v[i] = ldg_relaxed128(pbase + (i >> 1) * 8192 + (i & 1) * 512);
                int nretry = 0;
                auto convert = [&](int tau) {
                    const uint4 A = v[2 * tau], B = v[2 * tau + 1];
                    sts128(sb + O_MF + tau * 3072 + c * 512 + l16, f16x2_to_bf16x2(A.x), f16x2_to_bf16x2(B.x), f16x2_to_bf16x2(A.y), f16x2_to_bf16x2(B.y));
                    sts64(sb + O_MF + tau * 3072 + 2048 + (c >> 1) * 512 + (c & 1) * 8 + l16, f16x2_to_bf16x2(A.z), f16x2_to_bf16x2(B.z));
                };
                const uint32_t ok0 = __all_sync(~0u, (v[0].w & v[1].w) == 0x5000u);
                convert(0);
                asm volatile("{\n.reg .pred p;\nsetp.ne.u32 p, %0, 0;\n@p bar.arrive 2, 384;\n}" :: "r"(ok0) : "memory");
                sched_fence<0>(h);
                uint32_t ok1;
                asm volatile("{\n.reg .pred p, q;\n.reg .b32 x;\nlop3.b32 x, %1, %2, %3, 0x80;\nand.b32 x, x, %4;\n"
                             "setp.eq.u32 p, x, 0x5000;\nvote.sync.all.pred q, p, 0xffffffff;\nselp.u32 %0, 1, 0, q;\n}"
                             : "=r"(ok1) : "r"(v[2].w), "r"(v[3].w), "r"(v[4].w), "r"(v[5].w));
                convert(1); convert(2);
                asm volatile("{\n.reg .pred p;\nsetp.ne.u32 p, %0, 0;\n@p bar.arrive 15, 384;\n}" :: "r"(ok1) : "memory");
                if (!(ok0 & ok1)) {
                    asm volatile("{\n.reg .pred p0, p1, p2, p3, p4, p5, q;\n.reg .u32 n, x;\nmov.u32 n, 0;\n"
                         "R_%=: setp.ne.u32 p0, %3, 0x5000;\nsetp.ne.u32 p1, %7, 0x5000;\nsetp.ne.u32 p2, %11, 0x5000;\n"
                         "setp.ne.u32 p3, %15, 0x5000;\nsetp.ne.u32 p4, %19, 0x5000;\nsetp.ne.u32 p5, %23, 0x5000;\n"
                         "@p0 ld.relaxed.gpu.global.v4.u32 {%0,%1,%2,%3}, [%25];\n@p1 ld.relaxed.gpu.global.v4.u32 {%4,%5,%6,%7}, [%25+512];\n"
                         "@p2 ld.relaxed.gpu.global.v4.u32 {%8,%9,%10,%11}, [%25+8192];\n@p3 ld.relaxed.gpu.global.v4.u32 {%12,%13,%14,%15}, [%25+8704];\n"
                         "@p4 ld.relaxed.gpu.global.v4.u32 {%16,%17,%18,%19}, [%25+16384];\n@p5 ld.relaxed.gpu.global.v4.u32 {%20,%21,%22,%23}, [%25+16896];\n"
                         "add.u32 %24, %24, 1;\nand.b32 x, %3, %7;\nand.b32 x, x, %11;\nand.b32 x, x, %15;\nand.b32 x, x, %19;\nand.b32 x, x, %23;\n"
                         "setp.eq.u32 q, x, 0x5000;\nvote.sync.all.pred q, q, 0xffffffff;\n@q bra.uni K_%=;\n"
                         "add.u32 n, n, 1;\nsetp.lt.u32 q, n, 2000000;\n@q bra.uni R_%=;\ntrap;\nK_%=:\n}"
                         : "+r"(v[0].x), "+r"(v[0].y), "+r"(v[0].z), "+r"(v[0].w), "+r"(v[1].x), "+r"(v[1].y), "+r"(v[1].z), "+r"(v[1].w),
                           "+r"(v[2].x), "+r"(v[2].y), "+r"(v[2].z), "+r"(v[2].w), "+r"(v[3].x), "+r"(v[3].y), "+r"(v[3].z), "+r"(v[3].w),
                           "+r"(v[4].x), "+r"(v[4].y), "+r"(v[4].z), "+r"(v[4].w), "+r"(v[5].x), "+r"(v[5].y), "+r"(v[5].z), "+r"(v[5].w), "+r"(nretry)
                         : "l"(pbase) : "memory");
                    if (!ok0) { convert(0); bar_arrive(2, 384); }
                    if (!ok1) { convert(1); convert(2); bar_arrive(15, 384); }
                }
                if (c == 0) STAMP(s, 12);
                if (c == 0) STAMPV(s, 14, nretry);
                mmax = absmax2(absmax2(absmax2(v[0].x, v[0].y), absmax2(v[0].z, v[1].x)), absmax2(absmax2(v[1].y, v[1].z), absmax2(v[2].x, v[2].y)));
                mmax = absmax2(mmax, absmax2(absmax2(absmax2(v[2].z, v[3].x), absmax2(v[3].y, v[3].z)), absmax2(absmax2(v[4].x, v[4].y), absmax2(v[4].z, v[5].x))));
                mmax = absmax2(mmax, absmax2(v[5].y, v[5].z)) & 0x7fff7fffu;
                { const float2 mf = __half22float2(*reinterpret_cast<__half2*>(&mmax)); mmax = max(__float_as_uint(mf.x), __float_as_uint(mf.y)); }
            }
            roff += 24576;
        }
        {
            bar_sync(7, 384);
            if (c == 0) flag_inc_if(l16c, &g_flag[F_QKV + (60 + (h >> 3)) * 8]);
        }
    }
    if (warp == 8) PSTAMP(13);
    cluster_sync();
}

constexpr int NST = 10;
constexpr int G_RING = 0, G_EX = NST * 16384, G_OUT = G_EX + 32768, G_CARRY = G_OUT + 32768, G_BAR = G_CARRY + 512, BG_SMEM = G_BAR + 256;
constexpr int GB_FULL = G_BAR, GB_EMPTY = G_BAR + 8 * NST, GB_W = G_BAR + 16 * NST;
static_assert(BG_SMEM <= 232448, "smem");

template <int ACC>
__device__ __forceinline__ void wgmma_n128_rs(float (&d)[64], uint32_t a0, uint32_t a1, uint32_t a2, uint32_t a3, uint64_t desc) {
    asm volatile("wgmma.mma_async.sync.aligned.m64n128k16.f32.bf16.bf16 "
        "{%0,%1,%2,%3,%4,%5,%6,%7,%8,%9,%10,%11,%12,%13,%14,%15,%16,%17,%18,%19,%20,%21,%22,%23,%24,%25,%26,%27,%28,%29,%30,%31,"
        "%32,%33,%34,%35,%36,%37,%38,%39,%40,%41,%42,%43,%44,%45,%46,%47,%48,%49,%50,%51,%52,%53,%54,%55,%56,%57,%58,%59,%60,%61,%62,%63}, "
        "{%64,%65,%66,%67}, %68, %69, 1, 1, 0;"
        : "+f"(d[0]), "+f"(d[1]), "+f"(d[2]), "+f"(d[3]), "+f"(d[4]), "+f"(d[5]), "+f"(d[6]), "+f"(d[7]),
          "+f"(d[8]), "+f"(d[9]), "+f"(d[10]), "+f"(d[11]), "+f"(d[12]), "+f"(d[13]), "+f"(d[14]), "+f"(d[15]),
          "+f"(d[16]), "+f"(d[17]), "+f"(d[18]), "+f"(d[19]), "+f"(d[20]), "+f"(d[21]), "+f"(d[22]), "+f"(d[23]),
          "+f"(d[24]), "+f"(d[25]), "+f"(d[26]), "+f"(d[27]), "+f"(d[28]), "+f"(d[29]), "+f"(d[30]), "+f"(d[31]),
          "+f"(d[32]), "+f"(d[33]), "+f"(d[34]), "+f"(d[35]), "+f"(d[36]), "+f"(d[37]), "+f"(d[38]), "+f"(d[39]),
          "+f"(d[40]), "+f"(d[41]), "+f"(d[42]), "+f"(d[43]), "+f"(d[44]), "+f"(d[45]), "+f"(d[46]), "+f"(d[47]),
          "+f"(d[48]), "+f"(d[49]), "+f"(d[50]), "+f"(d[51]), "+f"(d[52]), "+f"(d[53]), "+f"(d[54]), "+f"(d[55]),
          "+f"(d[56]), "+f"(d[57]), "+f"(d[58]), "+f"(d[59]), "+f"(d[60]), "+f"(d[61]), "+f"(d[62]), "+f"(d[63])
        : "r"(a0), "r"(a1), "r"(a2), "r"(a3), "l"(desc), "n"(ACC));
}
__device__ __forceinline__ void wait_flag(const unsigned* p, unsigned target) {
    asm volatile("{\n.reg .pred p;\n.reg .u32 n, v;\nmov.u32 n, 0;\n"
                 "W_%=: ld.acquire.gpu.global.u32 v, [%0];\nsub.u32 v, v, %1;\nsetp.ge.s32 p, v, 0;\n@p bra.uni D_%=;\nnanosleep.u32 100;\n"
                 "add.u32 n, n, 1;\nsetp.lt.u32 p, n, 4000000;\n@p bra.uni W_%=;\ntrap;\nD_%=:\n}" :: "l"(p), "r"(target) : "memory");
}
template <int NS, int STRIDE>
__device__ __forceinline__ void bg_mainloop(float (&d)[64], const uint32_t (&a)[144], uint32_t sb, int it, int lane) {
    int slot = it % NST, ph = (it / NST) & 1, prev = 0;
#pragma unroll
    for (int i = 0; i < NS; i++) {
        mbar_wait(sb + GB_FULL + 8 * slot, ph);
        const uint64_t desc = (uint64_t)(((sb + G_RING + slot * 16384) & 0x3FFFF) >> 4) | (1ull << 16) | (64ull << 32) | (1ull << 62);
        wg_fence();
#pragma unroll
        for (int k = 0; k < 4; k++) {
            const int u = 16 * i + 4 * k;
            if (i == 0 && k == 0) wgmma_n128_rs<0>(d, a[u], a[u + 1], a[u + 2], a[u + 3], desc);
            else wgmma_n128_rs<1>(d, a[u], a[u + 1], a[u + 2], a[u + 3], desc + 2 * k);
        }
        wg_commit();
        if (i > 0) {
            asm volatile("wgmma.wait_group.sync.aligned 1;" ::: "memory");
            mbar_arrive_if(lane, sb + GB_EMPTY + 8 * prev);
        }
        prev = slot;
        slot += STRIDE;
        if (slot >= NST) { slot -= NST; ph ^= 1; }
    }
    wg_wait0();
    mbar_arrive_if(lane, sb + GB_EMPTY + 8 * prev);
}
template <bool SKIP>
__device__ __forceinline__ void bg_epilogue(float (&d)[64], uint32_t sb, int wg, int w, int lane, const CUtensorMap* tm_out, int col0, int tok0,
                                            const __nv_bfloat16* xa, const __nv_bfloat16* Dk) {
    const int g = lane >> 2, t = lane & 3;
    const uint32_t ex = sb + G_EX + w * 4096 + lane * 16;
    float k[32];
    if (wg == 0) {
#pragma unroll
        for (int q = 0; q < 8; q++) sts128f(ex + q * 512, d[32 + 4 * q], d[32 + 4 * q + 1], d[32 + 4 * q + 2], d[32 + 4 * q + 3]);
#pragma unroll
        for (int i = 0; i < 32; i++) k[i] = d[i];
    } else {
#pragma unroll
        for (int q = 0; q < 8; q++) sts128f(ex + 16384 + q * 512, d[4 * q], d[4 * q + 1], d[4 * q + 2], d[4 * q + 3]);
#pragma unroll
        for (int i = 0; i < 32; i++) k[i] = d[32 + i];
    }
    uint32_t xv[16], dv = 0;
    if (SKIP) {
        const __nv_bfloat16* xp = xa + (size_t)(tok0 + 64 * wg + 2 * t) * DM + col0 + 16 * w + 2 * g;
#pragma unroll
        for (int i = 0; i < 16; i++) xv[i] = ldg_nc32(xp + (8 * (i >> 1) + (i & 1)) * DM);
        dv = ldg_nc32(Dk + col0 + 16 * w + 2 * g);
    }
    if (SKIP && w == 0) asm volatile("cp.async.bulk.wait_group.read 0;" ::: "memory");
    bar_sync(1, 256);
#pragma unroll
    for (int q = 0; q < 8; q++) {
        const float4 o = lds128f(ex + (wg ^ 1) * 16384 + q * 512);
        k[4 * q] += o.x; k[4 * q + 1] += o.y; k[4 * q + 2] += o.z; k[4 * q + 3] += o.w;
    }
    if (SKIP) bar_sync(1, 256); else bar_sync(13, 288);
    const uint32_t ob = sb + G_OUT + wg * 16384 + (w >> 1) * 8192 + (g & 1) * 8;
    const uint32_t ch = (w & 1) * 4 + (g >> 1);
#pragma unroll
    for (int i = 0; i < 16; i++) {
        float v0 = k[4 * (i >> 1) + (i & 1)], v1 = k[4 * (i >> 1) + 2 + (i & 1)];
        if (SKIP) {
            const uint32_t p = pack_bf16(__uint_as_float(xv[i] << 16) * __uint_as_float(dv << 16), __uint_as_float(xv[i] & 0xffff0000u) * __uint_as_float(dv & 0xffff0000u));
            v0 += __uint_as_float(p << 16); v1 += __uint_as_float(p & 0xffff0000u);
        }
        const uint32_t n7 = 2 * t + (i & 1);
        sts64(ob + (8 * (i >> 1) + n7) * 128 + ((ch ^ n7) << 4), __float_as_uint(v0), __float_as_uint(v1));
    }
    fence_async_smem();
    if (SKIP) {
        bar_sync(4 + wg, 128);
        if (w == 0)
            asm volatile("{\n.reg .pred p;\nelect.sync _|p, 0xffffffff;\n"
                "@p cp.async.bulk.tensor.2d.global.shared::cta.bulk_group [%0, {%2, %4}], [%1];\n"
                "@p cp.async.bulk.tensor.2d.global.shared::cta.bulk_group [%0, {%3, %4}], [%1+8192];\n@p cp.async.bulk.commit_group;\n}"
                :: "l"(tm_out), "r"(sb + G_OUT + wg * 16384), "r"(col0), "r"(col0 + 32), "r"(tok0 + 64 * wg) : "memory");
    } else {
        bar_arrive(12, 288);
    }
}
__device__ __forceinline__ void s5_channel(int p, const __nv_bfloat16* Lre, const __nv_bfloat16* Lim, const __nv_bfloat16* logdt, float2& lam, float2& coef) {
    const float dt = __bfloat162float(__float2bfloat16(expf(__bfloat162float(logdt[p]))));
    const float lr = __bfloat162float(Lre[p]), li = __bfloat162float(Lim[p]);
    const float e = expf(dt * lr);
    float sn, cs;
    sincosf(dt * li, &sn, &cs);
    lam = make_float2(e * cs, e * sn);
    const float den = lr * lr + li * li;
    coef = make_float2(((lam.x - 1.f) * lr + lam.y * li) / den, (lam.y * lr - (lam.x - 1.f) * li) / den);
}
__device__ __forceinline__ float2 cfma(float2 a, float2 b, float2 c) {
    return make_float2(fmaf(a.x, b.x, fmaf(-a.y, b.y, c.x)), fmaf(a.x, b.y, fmaf(a.y, b.x, c.y)));
}
__device__ __forceinline__ uint4 ldg128(const void* p) { uint4 v; asm volatile("ld.global.v4.u32 {%0,%1,%2,%3}, [%4];" : "=r"(v.x), "=r"(v.y), "=r"(v.z), "=r"(v.w) : "l"(p) : "memory"); return v; }
__device__ __forceinline__ uint2 ldg64(const void* p) { uint2 v; asm volatile("ld.global.v2.u32 {%0,%1}, [%2];" : "=r"(v.x), "=r"(v.y) : "l"(p) : "memory"); return v; }

__device__ __forceinline__ void bg_attention(uint32_t st0, uint32_t st1, int mt, int lane) {
    const int g = lane >> 2, t = lane & 3;
    float sc[5][4];
#pragma unroll
    for (int n = 0; n < 5; n++) sc[n][0] = sc[n][1] = sc[n][2] = sc[n][3] = 0.f;
    float sm2[4] = {0.f, 0.f, 0.f, 0.f};
#pragma unroll
    for (int i = 0; i < 8; i++) {
        const uint32_t st = (i >> 2 ? st1 : st0) + (i & 3) * 512 + lane * 16;
        const uint4 q = ldsm4(st + mt * 2048), km = ldsm4(st + 8192), k0 = ldsm4(st + 4096);
        mma16816(sc[0], q.x, q.y, q.z, q.w, km.x, km.y);
        mma16816(sm2, q.x, q.y, q.z, q.w, km.z, km.w);
        mma16816(sc[1], q.x, q.y, q.z, q.w, k0.x, k0.y);
        mma16816(sc[2], q.x, q.y, q.z, q.w, k0.z, k0.w);
        if (mt) {
            const uint4 k1 = ldsm4(st + 6144);
            mma16816(sc[3], q.x, q.y, q.z, q.w, k1.x, k1.y);
            mma16816(sc[4], q.x, q.y, q.z, q.w, k1.z, k1.w);
        }
    }
#pragma unroll
    for (int i = 0; i < 4; i++) sc[0][i] += sm2[i];
    const int q0 = 16 * mt + 8 + g - 2 * t;
#pragma unroll
    for (int n = 1; n < 5; n++) {
        if (8 * n > q0) sc[n][0] = -INFINITY;
        if (8 * n + 1 > q0) sc[n][1] = -INFINITY;
        if (8 * n > q0 + 8) sc[n][2] = -INFINITY;
        if (8 * n + 1 > q0 + 8) sc[n][3] = -INFINITY;
    }
    float ma = fmaxf(sc[0][0], sc[0][1]), mb = fmaxf(sc[0][2], sc[0][3]);
#pragma unroll
    for (int n = 1; n < 5; n++) { ma = fmaxf(ma, fmaxf(sc[n][0], sc[n][1])); mb = fmaxf(mb, fmaxf(sc[n][2], sc[n][3])); }
    ma = quad_max(ma) * SM_SCALE; mb = quad_max(mb) * SM_SCALE;
    uint32_t Pa[5], Pb[5];
#pragma unroll
    for (int n = 0; n < 5; n++) {
        Pa[n] = pack_bf16(ex2(fmaf(sc[n][0], SM_SCALE, -ma)), ex2(fmaf(sc[n][1], SM_SCALE, -ma)));
        Pb[n] = pack_bf16(ex2(fmaf(sc[n][2], SM_SCALE, -mb)), ex2(fmaf(sc[n][3], SM_SCALE, -mb)));
    }
    float sa[4], sbb[4];
    mma1688_z(sa, ONES, ONES, Pa[0]); mma1688_z(sbb, ONES, ONES, Pb[0]);
    mma16816(sa, ONES, ONES, ONES, ONES, Pa[1], Pa[2]); mma16816(sbb, ONES, ONES, ONES, ONES, Pb[1], Pb[2]);
    mma16816(sa, ONES, ONES, ONES, ONES, Pa[3], Pa[4]); mma16816(sbb, ONES, ONES, ONES, ONES, Pb[3], Pb[4]);
    const float ra0 = rcp_fast(sa[0]), ra1 = rcp_fast(sa[1]), rb0 = rcp_fast(sbb[0]), rb1 = rcp_fast(sbb[1]);
    const uint32_t row = lane & 7;
    const uint32_t so = mt * 2048 + (lane >> 4) * 1024 + row * 128;
#pragma unroll
    for (int i = 0; i < 8; i++) {
        const uint32_t st = i >> 2 ? st1 : st0;
        const int e4 = i & 3;
        const float2 vmf = lds64f(st + 14336 + e4 * 256 + lane * 8);
        const uint32_t vm0 = __float_as_uint(vmf.x), vm1 = __float_as_uint(vmf.y);
        const uint4 v0 = lds128(st + 10240 + e4 * 1024 + lane * 16);
        float oa[4], ob[4];
        mma1688_z(oa, vm0, vm1, Pa[0]); mma1688_z(ob, vm0, vm1, Pb[0]);
        mma16816(oa, v0.x, v0.y, v0.z, v0.w, Pa[1], Pa[2]);
        mma16816(ob, v0.x, v0.y, v0.z, v0.w, Pb[1], Pb[2]);
        if (mt) {
            const uint4 v1 = lds128(st + 10240 + e4 * 1024 + 512 + lane * 16);
            mma16816(oa, v1.x, v1.y, v1.z, v1.w, Pa[3], Pa[4]);
            mma16816(ob, v1.x, v1.y, v1.z, v1.w, Pb[3], Pb[4]);
        }
        stsm4t(st + so + (((2 * e4 + ((lane >> 3) & 1)) ^ row) << 4), pack_bf16(oa[0] * ra0, oa[1] * ra1), pack_bf16(oa[2] * ra0, oa[3] * ra1),
               pack_bf16(ob[0] * rb0, ob[1] * rb1), pack_bf16(ob[2] * rb0, ob[3] * rb1));
    }
}
__device__ __forceinline__ bool bg_att_turn(int na, int ng) { return na == ng || (na == ng + 1 && na <= BG_AHEAD); }

__global__ void __launch_bounds__(384, 1)
bg_kernel(const __grid_constant__ CUtensorMap tm_xa, const __grid_constant__ CUtensorMap tm_wo, const __grid_constant__ CUtensorMap tm_out,
          const __nv_bfloat16* __restrict__ xa, const __nv_bfloat16* __restrict__ Lre, const __nv_bfloat16* __restrict__ Lim,
          const __nv_bfloat16* __restrict__ Bre, const __nv_bfloat16* __restrict__ Bim, const __nv_bfloat16* __restrict__ Cre,
          const __nv_bfloat16* __restrict__ Cim, const __nv_bfloat16* __restrict__ logdt, const __nv_bfloat16* __restrict__ Dk) {
    extern __shared__ __align__(1024) uint8_t smem_raw[];
    const uint32_t sb = smem_u32(smem_raw);
    const int lane = threadIdx.x & 31;
    const int warp = __shfl_sync(~0u, threadIdx.x >> 5, 0);
    const int wg = warp >> 2, w = warp & 3, b = blockIdx.x;
    const int nt = b % 9, kq = b / 9;
    BSTAMP(0);
    if (threadIdx.x == 0) {
        if (sb & 1023u) __trap();
        for (int i = 0; i < NST; i++) { mbar_init(sb + GB_FULL + 8 * i, 1); mbar_init(sb + GB_EMPTY + 8 * i, 4); }
        mbar_init(sb + GB_W, 1);
        asm volatile("fence.mbarrier_init.release.cluster;" ::: "memory");
        mbar_expect(sb + GB_W, (b < 18 ? 64 : 128) * 1152);
        sts32(sb + G_BAR + 248, atomicAdd(&g_ticket_bg, 1u) / 36u + 1u);
    }
    __syncthreads();
    if (wg == 2) {
        asm volatile("setmaxnreg.dec.sync.aligned.u32 24;");
        if (w == 0) {
            int slot = 0, ph = 1;
            unsigned tlast = clk();
            auto pace = [&]() { if (BG_PACE) { spin_until(tlast, BG_PACE); tlast = clk(); } };
            auto next = [&]() { if (++slot == NST) { slot = 0; ph ^= 1; } };
            bar_sync(6, 288);
            if (b < 18) {
#pragma unroll 1
                for (int i = 0; i < 144; i++) {
                    const int blk = i / 9, kb = i - 9 * blk, it = (blk >> 1) * 18 + (blk & 1) + 2 * kb;
                    slot = it % NST;
                    mbar_wait(sb + GB_EMPTY + 8 * slot, ((it / NST) & 1) ^ 1);
                    pace();
                    asm volatile("{\n.reg .pred p;\nelect.sync _|p, 0xffffffff;\n@p mbarrier.arrive.expect_tx.shared::cta.b64 _, [%2], 16384;\n"
                        "@p cp.async.bulk.tensor.5d.shared::cluster.global.mbarrier::complete_tx::bytes [%0], [%1, {%3, %4, %4, %4, %5}], [%2];\n}"
                        :: "r"(sb + G_RING + slot * 16384), "l"(&tm_xa), "r"(sb + GB_FULL + 8 * slot), "r"(kb * 64), "r"(0), "r"(blk) : "memory");
                }
                slot = 144 % NST; ph = ((144 / NST) & 1) ^ 1;
            }
            const unsigned ep = lds32(sb + G_BAR + 248);
            auto slabs = [&](const char* src, int ns) {
                asm volatile("fence.proxy.async.global;" ::: "memory");
#pragma unroll 1
                for (int i = 0; i < ns; i++) {
                    mbar_wait(sb + GB_EMPTY + 8 * slot, ph);
                    pace();
                    asm volatile("{\n.reg .pred p;\nelect.sync _|p, 0xffffffff;\n@p mbarrier.arrive.expect_tx.shared::cta.b64 _, [%2], 16384;\n"
                        "@p cp.async.bulk.shared::cluster.global.mbarrier::complete_tx::bytes [%0], [%1], 16384, [%2];\n}"
                        :: "r"(sb + G_RING + slot * 16384), "l"(src + (size_t)((i & 1) * (ns >> 1) + (i >> 1)) * (SEQ * 128)), "r"(sb + GB_FULL + 8 * slot) : "memory");
                    next();
                }
            };
            if (b >= 18) {
#pragma unroll 1
                for (int blk = kq - 2; blk < 16; blk += 2) {
                    wait_flag(&g_flag[F_H + blk * 8], 18 * ep);
                    slabs(reinterpret_cast<const char*>(g_h) + blk * 16384, 18);
                }
            }
            bar_sync(6, 288);
#pragma unroll 1
            for (int na = 0, ng = 0; ng < 16;) {
                if (bg_att_turn(na, ng)) {
                    if (nt < 8) {
                        wait_flag(&g_flag[F_QKV + (na * 4 + kq) * 8], 24 * ep);
                        asm volatile("fence.proxy.async.global;" ::: "memory");
#pragma unroll 1
                        for (int i = 0; i < 8; i++) {
                            const int pr = nt * 4 + 2 * (i & 1) + (i >> 2), hf = (i >> 1) & 1;
                            const char* rec = reinterpret_cast<const char*>(g_qkv) + (size_t)((4 * na + (pr >> 3)) * NH + 8 * kq + (pr & 7)) * REC;
                            mbar_wait(sb + GB_EMPTY + 8 * slot, ph);
                    pace();
                            asm volatile("{\n.reg .pred p;\nelect.sync _|p, 0xffffffff;\n@p mbarrier.arrive.expect_tx.shared::cta.b64 _, [%4], 15360;\n"
                                "@p cp.async.bulk.shared::cluster.global.mbarrier::complete_tx::bytes [%0], [%1], 10240, [%4];\n"
                                "@p cp.async.bulk.shared::cluster.global.mbarrier::complete_tx::bytes [%0+10240], [%2], 4096, [%4];\n"
                                "@p cp.async.bulk.shared::cluster.global.mbarrier::complete_tx::bytes [%0+14336], [%3], 1024, [%4];\n}"
                                :: "r"(sb + G_RING + slot * 16384), "l"(rec + hf * 10240), "l"(rec + 20480 + hf * 4096), "l"(rec + 28672 + hf * 1024),
                                   "r"(sb + GB_FULL + 8 * slot) : "memory");
                            next();
                        }
                    }
                    na++;
                } else {
                    wait_flag(&g_flag[F_OX + (ng * 4 + kq) * 8], 8 * ep);
                    slabs(reinterpret_cast<const char*>(g_ox) + (size_t)kq * 16 * SEQ * 128 + ng * 16384, 16);
                    ng++;
                }
            }
        } else if (w == 1) {
            if (b < 18) {
#pragma unroll 1
                for (int blk = 0; blk < 16; blk++) {
                    bar_sync(8 + (blk & 1), 160);
                    asm volatile("{\n.reg .pred p;\nelect.sync _|p, 0xffffffff;\n@p cp.async.bulk.global.shared::cta.bulk_group [%0], [%1], 16384;\n"
                        "@p cp.async.bulk.commit_group;\ncp.async.bulk.wait_group 0;\nfence.proxy.async.global;\n}"
                        :: "l"(reinterpret_cast<char*>(g_h) + ((size_t)b * SEQ + blk * 128) * 128), "r"(sb + G_OUT + (blk & 1) * 16384) : "memory");
                    bar_arrive(10 + (blk & 1), 160);
                    flag_inc_if(lane, &g_flag[F_H + blk * 8]);
                }
            }
            if (nt < 8) {
                int it = 144;
#pragma unroll 1
                for (int na = 0, ng = 0; ng < 16;) {
                    if (bg_att_turn(na, ng)) {
                        bar_sync(7, 288);
                        if (lane < 8) {
                            const int pr = nt * 4 + 2 * (lane & 1) + (lane >> 2), hf = (lane >> 1) & 1;
                            asm volatile("cp.async.bulk.global.shared::cta.bulk_group [%0], [%1], 4096;\ncp.async.bulk.commit_group;\ncp.async.bulk.wait_group.read 0;\n"
                                "mbarrier.arrive.shared::cta.b64 _, [%2], 4;\ncp.async.bulk.wait_group 0;\nfence.proxy.async.global;"
                                :: "l"(reinterpret_cast<char*>(g_ox) + ((size_t)((8 * kq + (pr & 7)) * 2 + hf) * SEQ + (4 * na + (pr >> 3)) * 32) * 128),
                                   "r"(sb + G_RING + ((it + lane) % NST) * 16384), "r"(sb + GB_EMPTY + 8 * ((it + lane) % NST)) : "memory");
                        }
                        __syncwarp();
                        flag_inc_if(lane, &g_flag[F_OX + (na * 4 + kq) * 8]);
                        it += 8; na++;
                    } else { it += 16; ng++; }
                }
            }
        } else if (w == 2) {
            const unsigned ep = lds32(sb + G_BAR + 248);
#pragma unroll 1
            for (int blk = 0; blk < 16; blk++) {
                bar_arrive(13, 288);
                bar_sync(12, 288);
                if (kq) { wait_flag(&g_flag[F_OUT + (blk * 9 + nt) * 8], ep); asm volatile("fence.proxy.async.global;" ::: "memory"); }
                unsigned t0 = clk();
                if (blk < 15) spin_until(t0, b * (RED_GAP / 36));
#pragma unroll 1
                for (int i = 0; i < 4; i++) {
                    const uint32_t src = sb + G_OUT + i * 8192;
                    const int c0 = DM + 64 * nt + (i & 1) * 32, c1 = blk * 128 + (i >> 1) * 64;
                    if (kq) {
                        asm volatile("{\n.reg .pred p;\nelect.sync _|p, 0xffffffff;\n@p cp.reduce.async.bulk.tensor.2d.global.shared::cta.add.bulk_group [%0, {%2, %3}], [%1];\n}"
                            :: "l"(&tm_out), "r"(src), "r"(c0), "r"(c1) : "memory");
                        t0 = clk();
                        if (blk < 15 && i < 3) spin_until(t0, RED_GAP);
                    } else {
                        asm volatile("{\n.reg .pred p;\nelect.sync _|p, 0xffffffff;\n@p cp.async.bulk.tensor.2d.global.shared::cta.bulk_group [%0, {%2, %3}], [%1];\n}"
                            :: "l"(&tm_out), "r"(src), "r"(c0), "r"(c1) : "memory");
                    }
                }
                asm volatile("cp.async.bulk.commit_group;\ncp.async.bulk.wait_group 0;\nfence.proxy.async.global;" ::: "memory");
                __syncwarp();
                if (!kq) flag_inc_if(lane, &g_flag[F_OUT + (blk * 9 + nt) * 8]);
            }
        }
    } else {
        asm volatile("setmaxnreg.inc.sync.aligned.u32 240;");
        const int g = lane >> 2, t = lane & 3, tid = threadIdx.x;
        uint32_t a[144];
        float d[64];
        if (b < 18) {
            if (tid < 64)
                asm volatile("cp.async.bulk.shared::cluster.global.mbarrier::complete_tx::bytes [%0], [%1], 1152, [%2];"
                    :: "r"(sb + tid * 1168), "l"((tid < 32 ? Bre : Bim) + (size_t)(32 * b + (tid & 31)) * DM), "r"(sb + GB_W) : "memory");
            float2 lam, coef;
            s5_channel(32 * b + 8 * w + g, Lre, Lim, logdt, lam, coef);
            float2 l32 = lam;
#pragma unroll
            for (int i = 0; i < 5; i++) l32 = make_float2(l32.x * l32.x - l32.y * l32.y, 2.f * l32.x * l32.y);
            __syncwarp();
            mbar_wait(sb + GB_W, 0);
            const uint32_t ap = sb + (((lane >> 3) & 1) * 32 + 8 * w + (lane & 7)) * 1168 + (lane >> 4) * 16;
#pragma unroll
            for (int ks = 0; ks < 36; ks++) { const uint4 v = ldsm4(ap + ks * 32); a[4 * ks] = v.x; a[4 * ks + 1] = v.y; a[4 * ks + 2] = v.z; a[4 * ks + 3] = v.w; }
            bar_sync(1, 256);
            bar_arrive(6, 288);
            BSTAMP(1);
#pragma unroll 1
            for (int blk = wg; blk < 16; blk += 2) {
                bg_mainloop<9, 2>(d, a, sb, (blk >> 1) * 18 + wg, lane);
                float2 e = make_float2(0.f, 0.f);
#pragma unroll
                for (int i = 0; i < 32; i++) e = cfma(lam, e, make_float2(d[4 * (i >> 1) + (i & 1)], d[4 * (i >> 1) + 2 + (i & 1)]));
                float2 cin = make_float2(0.f, 0.f);
                if (blk > 0) { bar_sync(2 + (wg ^ 1), 256); cin = lds64f(sb + G_CARRY + (wg ^ 1) * 256 + (8 * w + g) * 8); }
                float2 mine = cin;
#pragma unroll
                for (int q = 0; q < 4; q++) {
                    const float2 eq = make_float2(__shfl_sync(~0u, e.x, (lane & 28) + q), __shfl_sync(~0u, e.y, (lane & 28) + q));
                    cin = cfma(l32, cin, eq);
                    if (t == q + 1) mine = cin;
                }
                if (blk < 15) {
                    if (t == 0) sts64(sb + G_CARRY + wg * 256 + (8 * w + g) * 8, __float_as_uint(cin.x), __float_as_uint(cin.y));
                    bar_arrive(2 + wg, 256);
                }
                const uint32_t hs = sb + G_OUT + wg * 16384 + t * 4096 + (g & 3) * 4;
                const uint32_t ch = 2 * w + (g >> 2);
                if (blk >= 2) bar_sync(10 + wg, 160);
#pragma unroll
                for (int i = 0; i < 32; i++) {
                    mine = cfma(lam, mine, make_float2(d[4 * (i >> 1) + (i & 1)], d[4 * (i >> 1) + 2 + (i & 1)]));
                    sts32(hs + i * 128 + ((ch ^ (i & 7)) << 4), pack_bf16(mine.x, mine.y));
                }
                fence_async_smem();
                bar_arrive(8 + wg, 160);
            }
            bar_sync(10 + wg, 160);
        } else {
            if (tid < 128)
                asm volatile("cp.async.bulk.shared::cluster.global.mbarrier::complete_tx::bytes [%0], [%1], 1152, [%2];"
                    :: "r"(sb + tid * 1168), "l"((tid < 64 ? Cre : Cim) + (size_t)(64 * nt + (tid & 63)) * DM), "r"(sb + GB_W) : "memory");
            for (int p = tid; p < DM; p += 256) {
                float2 lam, coef;
                s5_channel(p, Lre, Lim, logdt, lam, coef);
                sts64(sb + G_EX + p * 8, __float_as_uint(2.f * coef.x), __float_as_uint(2.f * coef.y));
            }
            bar_sync(1, 256);
            mbar_wait(sb + GB_W, 0);
            const uint32_t cp = sb + (16 * w + 2 * g) * 1168 + (288 * wg + t) * 2;
#pragma unroll
            for (int u = 0; u < 72; u++) {
                const float2 c2 = lds64f(sb + G_EX + (288 * wg + 4 * u + t) * 8);
#pragma unroll
                for (int f = 0; f < 2; f++) {
                    unsigned short r16, i16;
                    asm volatile("ld.shared.u16 %0, [%1];" : "=h"(r16) : "r"(cp + f * 1168 + u * 8) : "memory");
                    asm volatile("ld.shared.u16 %0, [%1];" : "=h"(i16) : "r"(cp + (64 + f) * 1168 + u * 8) : "memory");
                    const float cr = __uint_as_float((uint32_t)r16 << 16), ci = __uint_as_float((uint32_t)i16 << 16);
                    a[2 * u + f] = pack_bf16(cr * c2.x - ci * c2.y, -(cr * c2.y + ci * c2.x));
                }
            }
            bar_sync(1, 256);
            bar_arrive(6, 288);
            BSTAMP(1);
#pragma unroll 1
            for (int j = 0; j < 8; j++) {
                bg_mainloop<9, 2>(d, a, sb, j * 18 + wg, lane);
                bg_epilogue<true>(d, sb, wg, w, lane, &tm_out, 64 * nt, (2 * j + kq - 2) * 128, xa, Dk);
            }
        }
        if (w == 0) asm volatile("cp.async.bulk.wait_group 0;" ::: "memory");
        bar_sync(1, 256);
        BSTAMP(2);
        if (warp == 0)
            asm volatile("{\n.reg .pred p;\nelect.sync _|p, 0xffffffff;\n@p mbarrier.arrive.expect_tx.shared::cta.b64 _, [%2], 131072;\n"
                "@p cp.async.bulk.tensor.2d.shared::cluster.global.mbarrier::complete_tx::bytes [%0], [%1, {%3, %4}], [%2];\n"
                "@p cp.async.bulk.tensor.2d.shared::cluster.global.mbarrier::complete_tx::bytes [%0+32768], [%1, {%3, %5}], [%2];\n"
                "@p cp.async.bulk.tensor.2d.shared::cluster.global.mbarrier::complete_tx::bytes [%0+65536], [%1, {%3, %6}], [%2];\n"
                "@p cp.async.bulk.tensor.2d.shared::cluster.global.mbarrier::complete_tx::bytes [%0+98304], [%1, {%3, %7}], [%2];\n}"
                :: "r"(sb), "l"(&tm_wo), "r"(sb + GB_W), "r"(64 * nt), "r"(1024 * kq), "r"(1024 * kq + 256), "r"(1024 * kq + 512), "r"(1024 * kq + 768) : "memory");
        mbar_wait(sb + GB_W, 1);
        {
            const uint32_t base = sb + wg * 65536 + 4 * t * 128 + (g & 3) * 4, ch = 2 * w + (g >> 2), r7 = (4 * t) & 7;
#pragma unroll
            for (int ks = 0; ks < 32; ks++) {
                const uint32_t w0 = lds32(base + ks * 2048 + ((ch ^ r7) << 4)), w1 = lds32(base + ks * 2048 + 256 + ((ch ^ (r7 + 2)) << 4));
                const uint32_t w2 = lds32(base + ks * 2048 + 128 + ((ch ^ (r7 + 1)) << 4)), w3 = lds32(base + ks * 2048 + 384 + ((ch ^ (r7 + 3)) << 4));
                a[4 * ks] = __byte_perm(w0, w1, 0x5410); a[4 * ks + 1] = __byte_perm(w0, w1, 0x7632);
                a[4 * ks + 2] = __byte_perm(w2, w3, 0x5410); a[4 * ks + 3] = __byte_perm(w2, w3, 0x7632);
            }
        }
        bar_sync(1, 256);
        bar_arrive(6, 288);
        BSTAMP(3);
#pragma unroll 1
        for (int na = 0, ng = 0, it = 144; ng < 16;) {
            if (bg_att_turn(na, ng)) {
                if (nt < 8) {
                    const int i0 = it + wg + 4 * (w >> 1), i1 = i0 + 2;
                    mbar_wait(sb + GB_FULL + 8 * (i0 % NST), (i0 / NST) & 1);
                    mbar_wait(sb + GB_FULL + 8 * (i1 % NST), (i1 / NST) & 1);
                    BSTAMP(8 + na * 4);
                    bg_attention(sb + G_RING + (i0 % NST) * 16384, sb + G_RING + (i1 % NST) * 16384, w & 1, lane);
                    fence_async_smem();
                    bar_arrive(7, 288);
                    bar_sync(1, 256);
                    BSTAMP(9 + na * 4);
                    it += 8;
                }
                na++;
            } else {
                bg_mainloop<8, 2>(d, a, sb, it + wg, lane);
                BSTAMP(10 + ng * 4);
                bg_epilogue<false>(d, sb, wg, w, lane, &tm_out, DM + 64 * nt, ng * 128, xa, Dk);
                BSTAMP(11 + ng * 4);
                it += 16; ng++;
            }
        }
    }
    asm volatile("griddepcontrol.wait;" ::: "memory");
}

typedef CUresult (*EncodeFn)(CUtensorMap*, CUtensorMapDataType, cuuint32_t, void*, const cuuint64_t*, const cuuint64_t*, const cuuint32_t*, const cuuint32_t*,
                             CUtensorMapInterleave, CUtensorMapSwizzle, CUtensorMapL2promotion, CUtensorMapFloatOOBfill);
}

extern "C" void kernel_launch(void* const* d_in, const int* in_sizes, int n_in, void* d_out, int out_size) {
    typedef const __nv_bfloat16* bp;
    bp Ax = (bp)d_in[0], Lre = (bp)d_in[1], Lim = (bp)d_in[2], Bre = (bp)d_in[3], Bim = (bp)d_in[4], Cre = (bp)d_in[5], Cim = (bp)d_in[6],
       logdt = (bp)d_in[7], Dk = (bp)d_in[8], Bx = (bp)d_in[9], mem0 = (bp)d_in[10], Wq = (bp)d_in[11], Wk = (bp)d_in[12], Wv = (bp)d_in[13], Wo = (bp)d_in[14];
    float* out = (float*)d_out;
    static EncodeFn enc = nullptr;
    if (!enc) {
        void* fn = nullptr; cudaDriverEntryPointQueryResult qr;
        cudaGetDriverEntryPoint("cuTensorMapEncodeTiled", &fn, cudaEnableDefault, &qr);
        enc = (EncodeFn)fn;
        cudaFuncSetAttribute(chain_kernel, cudaFuncAttributeMaxDynamicSharedMemorySize, CHAIN_SMEM);
        cudaFuncSetAttribute(bg_kernel, cudaFuncAttributeMaxDynamicSharedMemorySize, BG_SMEM);
    }
    const cuuint32_t es[5] = {1, 1, 1, 1, 1};
    auto map2d = [&](CUtensorMap* tm, CUtensorMapDataType dt, const void* p, cuuint64_t d0, cuuint64_t d1, cuuint64_t stride, cuuint32_t b0, cuuint32_t b1) {
        cuuint64_t gd[2] = {d0, d1}, gs[1] = {stride}; cuuint32_t bd[2] = {b0, b1};
        enc(tm, dt, 2, (void*)p, gd, gs, bd, es, CU_TENSOR_MAP_INTERLEAVE_NONE, CU_TENSOR_MAP_SWIZZLE_128B, CU_TENSOR_MAP_L2_PROMOTION_L2_128B,
            CU_TENSOR_MAP_FLOAT_OOB_FILL_NONE);
    };
    CUtensorMap tm_x, tm_q, tm_k, tm_v, tm_xa, tm_wo, tm_out;
    map2d(&tm_x, CU_TENSOR_MAP_DATA_TYPE_BFLOAT16, Bx, DM, SEQ, DM * 2, 64, 32);
    map2d(&tm_q, CU_TENSOR_MAP_DATA_TYPE_BFLOAT16, Wq, HD, DM, HD * 2, 64, 192);
    map2d(&tm_k, CU_TENSOR_MAP_DATA_TYPE_BFLOAT16, Wk, HD, DM, HD * 2, 64, 192);
    map2d(&tm_v, CU_TENSOR_MAP_DATA_TYPE_BFLOAT16, Wv, HD, DM, HD * 2, 64, 192);
    map2d(&tm_wo, CU_TENSOR_MAP_DATA_TYPE_BFLOAT16, Wo, DM, HD, DM * 2, 64, 256);
    map2d(&tm_out, CU_TENSOR_MAP_DATA_TYPE_FLOAT32, out, 2 * DM, SEQ, 2 * DM * 4, 32, 64);
    {
        cuuint64_t gd[5] = {DM, 2, 4, 16, 16}, gs[4] = {DM * 2, 32 * DM * 2, 2 * DM * 2, 128 * DM * 2}; cuuint32_t bd[5] = {64, 2, 4, 16, 1};
        enc(&tm_xa, CU_TENSOR_MAP_DATA_TYPE_BFLOAT16, 5, (void*)Ax, gd, gs, bd, es, CU_TENSOR_MAP_INTERLEAVE_NONE, CU_TENSOR_MAP_SWIZZLE_128B,
            CU_TENSOR_MAP_L2_PROMOTION_L2_128B, CU_TENSOR_MAP_FLOAT_OOB_FILL_NONE);
    }
    cudaStream_t st = cudaStreamPerThread;
    chain_kernel<<<96, 384, CHAIN_SMEM, st>>>(tm_x, tm_q, tm_k, tm_v, Bx, mem0, Wo);
    cudaLaunchConfig_t cfg = {};
    cfg.gridDim = dim3(36); cfg.blockDim = dim3(384); cfg.dynamicSmemBytes = BG_SMEM; cfg.stream = st;
    cudaLaunchAttribute at[1];
    at[0].id = cudaLaunchAttributeProgrammaticStreamSerialization; at[0].val.programmaticStreamSerializationAllowed = 1;
    cfg.attrs = at; cfg.numAttrs = 1;
    cudaLaunchKernelEx(&cfg, bg_kernel, tm_xa, tm_wo, tm_out, Ax, Lre, Lim, Bre, Bim, Cre, Cim, logdt, Dk);
}
```

```cpp
#include <cuda_runtime.h>
#include <cuda.h>
#include <cuda_bf16.h>
#include <cuda_fp16.h>
#include <stdint.h>

#define D_WAIT 720

#define BG_PACE 0
#define RED_GAP 720
#define ACC_PF 1
#define QDEP 0
#define BG_AHEAD 5

namespace {

constexpr int DM = 576, NH = 32, SEQ = 2048, NSEG = 64, HD = 4096;

__device__ uint4 g_acc_raw[64 * 96 * 16 + 131072];
__device__ uint4 g_ox[NH * 2 * SEQ * 8];
constexpr int REC = 30720;
__device__ uint4 g_qkv[NSEG * NH * (REC / 16)];
__device__ uint4 g_h[18 * SEQ * 8];
constexpr int NFLAG = 4096, F_QKV = 0, F_OX = 512, F_H = 1024, F_OUT = 2048;
__device__ unsigned g_flag[NFLAG];
__device__ unsigned g_ticket, g_ticket_bg;
__device__ unsigned long long g_norm[96];
#define BSTAMP(i) do {} while (0)

__device__ __forceinline__ uint32_t smem_u32(const void* p) { return (uint32_t)__cvta_generic_to_shared(p); }
__device__ __forceinline__ uint32_t mapa(uint32_t a, uint32_t r) { uint32_t o; asm("mapa.shared::cluster.u32 %0, %1, %2;" : "=r"(o) : "r"(a), "r"(r)); return o; }
__device__ __forceinline__ uint32_t mapa_v(uint32_t a, uint32_t r) { uint32_t o; asm volatile("mapa.shared::cluster.u32 %0, %1, %2;" : "=r"(o) : "r"(a), "r"(r)); return o; }
__device__ __forceinline__ unsigned clk() { unsigned long long c; asm volatile("mov.u64 %0, %%clock64;" : "=l"(c) :: "memory"); return (unsigned)c; }
__device__ __forceinline__ void mbar_init(uint32_t bar, uint32_t cnt) { asm volatile("mbarrier.init.shared::cta.b64 [%0], %1;" :: "r"(bar), "r"(cnt) : "memory"); }
__device__ __forceinline__ void mbar_expect(uint32_t bar, uint32_t bytes) { asm volatile("mbarrier.arrive.expect_tx.shared::cta.b64 _, [%0], %1;" :: "r"(bar), "r"(bytes) : "memory"); }
__device__ __forceinline__ void mbar_wait(uint32_t bar, uint32_t parity) {
    asm volatile("{\n.reg .pred p;\n.reg .u32 n;\nmov.u32 n, 0;\n"
                 "W_%=: mbarrier.try_wait.parity.shared::cta.b64 p, [%0], %1;\n@p bra.uni D_%=;\n"
                 "add.u32 n, n, 1;\nsetp.lt.u32 p, n, 4000000;\n@p bra.uni W_%=;\ntrap;\nD_%=:\n}" :: "r"(bar), "r"(parity) : "memory");
}
__device__ __forceinline__ void mbar_expect_if(uint32_t z, uint32_t bar, uint32_t bytes) {
    asm volatile("{\n.reg .pred p;\nsetp.eq.u32 p, %2, 0;\n@p mbarrier.arrive.expect_tx.shared::cta.b64 _, [%0], %1;\n}" :: "r"(bar), "r"(bytes), "r"(z) : "memory");
}
__device__ __forceinline__ void mbar_arrive_if(uint32_t z, uint32_t bar) {
    asm volatile("{\n.reg .pred p;\nsetp.eq.u32 p, %1, 0;\n@p mbarrier.arrive.shared::cta.b64 _, [%0];\n}" :: "r"(bar), "r"(z) : "memory");
}
__device__ __forceinline__ void sts32_if(uint32_t z, uint32_t a, uint32_t x) {
    asm volatile("{\n.reg .pred p;\nsetp.eq.u32 p, %2, 0;\n@p st.shared.u32 [%0], %1;\n}" :: "r"(a), "r"(x), "r"(z) : "memory");
}
template <int K> __device__ __forceinline__ void sched_fence(int v) {
    asm volatile("{\n.reg .pred p;\nsetp.ne.s32 p, %0, %1;\n@p bra.uni F_%=;\ntrap;\nF_%=:\n}" :: "r"(v), "n"(1000 + K) : "memory");
}
__device__ __forceinline__ void spin_until(unsigned t0, unsigned d) {
    asm volatile("{\n.reg .pred p;\n.reg .u64 c;\n.reg .u32 lo;\n"
                 "S_%=: mov.u64 c, %%clock64;\ncvt.u32.u64 lo, c;\nsub.u32 lo, lo, %0;\nsetp.lt.u32 p, lo, %1;\n@p bra.uni S_%=;\n}" :: "r"(t0), "r"(d) : "memory");
}
__device__ __forceinline__ void bar_sync(int id, int n) { asm volatile("bar.sync %0, %1;" :: "r"(id), "r"(n) : "memory"); }
__device__ __forceinline__ void bar_sync_sel(int sel, int id) {
    asm volatile("{\n.reg .pred p;\nsetp.eq.u32 p, %0, 0;\n@p bar.sync %1, %3;\n@!p bar.sync %2, %3;\n}" :: "r"(sel), "r"(id), "r"(id + 1), "n"(192) : "memory");
}
__device__ __forceinline__ void bar_arrive(int id, int n) { asm volatile("bar.arrive %0, %1;" :: "r"(id), "r"(n) : "memory"); }
__device__ __forceinline__ void fence_async_smem() { asm volatile("fence.proxy.async.shared::cta;" ::: "memory"); }
__device__ __forceinline__ uint32_t pack_bf16(float lo, float hi) { uint32_t r; asm("cvt.rn.bf16x2.f32 %0, %1, %2;" : "=r"(r) : "f"(hi), "f"(lo)); return r; }
__device__ __forceinline__ uint32_t pack_f16(float lo, float hi) { uint32_t r; asm("cvt.rn.f16x2.f32 %0, %1, %2;" : "=r"(r) : "f"(hi), "f"(lo)); return r; }
__device__ __forceinline__ uint32_t f16x2_to_bf16x2(uint32_t v) { float2 f = __half22float2(*reinterpret_cast<__half2*>(&v)); return pack_bf16(f.x, f.y); }
__device__ __forceinline__ uint32_t hmul2(uint32_t a, uint32_t b) { uint32_t r; asm("mul.rn.f16x2 %0, %1, %2;" : "=r"(r) : "r"(a), "r"(b)); return r; }
__device__ __forceinline__ float ex2(float x) { float y; asm("ex2.approx.ftz.f32 %0, %1;" : "=f"(y) : "f"(x)); return y; }
__device__ __forceinline__ float ex2v(float x) { float y; asm volatile("ex2.approx.ftz.f32 %0, %1;" : "=f"(y) : "f"(x)); return y; }
__device__ __forceinline__ uint32_t absmax2(uint32_t a, uint32_t b) {
    uint32_t r; asm("max.xorsign.abs.f16x2 %0, %1, %2;" : "=r"(r) : "r"(a), "r"(b)); return r;
}
__device__ __forceinline__ uint32_t shl_v(uint32_t a, int n) { return a << n; }
__device__ __forceinline__ uint32_t max3u(uint32_t a, uint32_t b, uint32_t c) { return max(max(a, b), c); }
__device__ __forceinline__ uint4 lds128(uint32_t a) { uint4 v; asm volatile("ld.shared.v4.u32 {%0,%1,%2,%3}, [%4];" : "=r"(v.x), "=r"(v.y), "=r"(v.z), "=r"(v.w) : "r"(a) : "memory"); return v; }
__device__ __forceinline__ uint4 lds128v(uint32_t a) { uint4 v; asm volatile("ld.volatile.shared.v4.u32 {%0,%1,%2,%3}, [%4];" : "=r"(v.x), "=r"(v.y), "=r"(v.z), "=r"(v.w) : "r"(a) : "memory"); return v; }
__device__ __forceinline__ float4 lds128f(uint32_t a) { float4 v; asm volatile("ld.shared.v4.f32 {%0,%1,%2,%3}, [%4];" : "=f"(v.x), "=f"(v.y), "=f"(v.z), "=f"(v.w) : "r"(a) : "memory"); return v; }
__device__ __forceinline__ float2 lds64f(uint32_t a) { float2 v; asm volatile("ld.shared.v2.f32 {%0,%1}, [%2];" : "=f"(v.x), "=f"(v.y) : "r"(a) : "memory"); return v; }
__device__ __forceinline__ uint4 lds64x2(uint32_t a) { uint4 v; asm volatile("ld.shared.v2.u32 {%0,%1}, [%4];\nld.shared.v2.u32 {%2,%3}, [%4+256];" : "=r"(v.x), "=r"(v.y), "=r"(v.z), "=r"(v.w) : "r"(a) : "memory"); return v; }
__device__ __forceinline__ uint32_t lds32(uint32_t a) { uint32_t v; asm volatile("ld.shared.u32 %0, [%1];" : "=r"(v) : "r"(a) : "memory"); return v; }
__device__ __forceinline__ void sts128(uint32_t a, uint32_t x, uint32_t y, uint32_t z, uint32_t w) { asm volatile("st.shared.v4.u32 [%0], {%1,%2,%3,%4};" :: "r"(a), "r"(x), "r"(y), "r"(z), "r"(w) : "memory"); }
__device__ __forceinline__ void sts128f(uint32_t a, float x, float y, float z, float w) { asm volatile("st.shared.v4.f32 [%0], {%1,%2,%3,%4};" :: "r"(a), "f"(x), "f"(y), "f"(z), "f"(w) : "memory"); }
__device__ __forceinline__ void sts64(uint32_t a, uint32_t x, uint32_t y) { asm volatile("st.shared.v2.u32 [%0], {%1,%2};" :: "r"(a), "r"(x), "r"(y) : "memory"); }
__device__ __forceinline__ void sts32(uint32_t a, uint32_t x) { asm volatile("st.shared.u32 [%0], %1;" :: "r"(a), "r"(x) : "memory"); }
__device__ __forceinline__ uint4 ldsm4(uint32_t a) { uint4 v; asm volatile("ldmatrix.sync.aligned.m8n8.x4.shared.b16 {%0,%1,%2,%3}, [%4];" : "=r"(v.x), "=r"(v.y), "=r"(v.z), "=r"(v.w) : "r"(a) : "memory"); return v; }
__device__ __forceinline__ void stsm2t(uint32_t a, uint32_t x, uint32_t y) { asm volatile("stmatrix.sync.aligned.m8n8.x2.trans.shared.b16 [%0], {%1,%2};" :: "r"(a), "r"(x), "r"(y) : "memory"); }
__device__ __forceinline__ void stsm4t(uint32_t a, uint32_t x, uint32_t y, uint32_t z, uint32_t w) { asm volatile("stmatrix.sync.aligned.m8n8.x4.trans.shared.b16 [%0], {%1,%2,%3,%4};" :: "r"(a), "r"(x), "r"(y), "r"(z), "r"(w) : "memory"); }
__device__ __forceinline__ void st_async64(uint32_t a, uint32_t x, uint32_t y, uint32_t bar) { asm volatile("st.async.shared::cluster.mbarrier::complete_tx::bytes.v2.b32 [%0], {%1,%2}, [%3];" :: "r"(a), "r"(x), "r"(y), "r"(bar) : "memory"); }
__device__ __forceinline__ void bulk_s2c(uint32_t dst, uint32_t src, uint32_t bytes, uint32_t bar) { asm volatile("cp.async.bulk.shared::cluster.shared::cta.mbarrier::complete_tx::bytes [%0], [%1], %2, [%3];" :: "r"(dst), "r"(src), "r"(bytes), "r"(bar) : "memory"); }
__device__ __forceinline__ void bulk_s2g(void* dst, uint32_t src, uint32_t bytes) { asm volatile("cp.async.bulk.global.shared::cta.bulk_group [%0], [%1], %2;" :: "l"(dst), "r"(src), "r"(bytes) : "memory"); }
__device__ __forceinline__ uint32_t ldg_nc32(const void* p) { uint32_t v; asm volatile("ld.global.nc.L2::128B.u32 %0, [%1];" : "=r"(v) : "l"(p)); return v; }
__device__ __forceinline__ uint4 ldg_relaxed128(const void* p) { uint4 v; asm volatile("ld.relaxed.gpu.global.v4.u32 {%0,%1,%2,%3}, [%4];" : "=r"(v.x), "=r"(v.y), "=r"(v.z), "=r"(v.w) : "l"(p) : "memory"); return v; }
__device__ __forceinline__ void mma16816(float (&d)[4], uint32_t a0, uint32_t a1, uint32_t a2, uint32_t a3, uint32_t b0, uint32_t b1) {
    asm volatile("mma.sync.aligned.m16n8k16.row.col.f32.bf16.bf16.f32 {%0,%1,%2,%3}, {%4,%5,%6,%7}, {%8,%9}, {%0,%1,%2,%3};"
        : "+f"(d[0]), "+f"(d[1]), "+f"(d[2]), "+f"(d[3]) : "r"(a0), "r"(a1), "r"(a2), "r"(a3), "r"(b0), "r"(b1));
}
__device__ __forceinline__ void mma16816_z(float (&d)[4], uint32_t a0, uint32_t a1, uint32_t a2, uint32_t a3, uint32_t b0, uint32_t b1) {
    asm volatile("mma.sync.aligned.m16n8k16.row.col.f32.bf16.bf16.f32 {%0,%1,%2,%3}, {%4,%5,%6,%7}, {%8,%9}, {%10,%10,%10,%10};"
        : "=f"(d[0]), "=f"(d[1]), "=f"(d[2]), "=f"(d[3]) : "r"(a0), "r"(a1), "r"(a2), "r"(a3), "r"(b0), "r"(b1), "f"(0.f));
}
__device__ __forceinline__ void mma1688(float (&d)[4], uint32_t a0, uint32_t a1, uint32_t b0) {
    asm volatile("mma.sync.aligned.m16n8k8.row.col.f32.bf16.bf16.f32 {%0,%1,%2,%3}, {%4,%5}, {%6}, {%0,%1,%2,%3};"
        : "+f"(d[0]), "+f"(d[1]), "+f"(d[2]), "+f"(d[3]) : "r"(a0), "r"(a1), "r"(b0));
}
__device__ __forceinline__ void mma1688_z(float (&d)[4], uint32_t a0, uint32_t a1, uint32_t b0) {
    asm volatile("mma.sync.aligned.m16n8k8.row.col.f32.bf16.bf16.f32 {%0,%1,%2,%3}, {%4,%5}, {%6}, {%7,%7,%7,%7};"
        : "=f"(d[0]), "=f"(d[1]), "=f"(d[2]), "=f"(d[3]) : "r"(a0), "r"(a1), "r"(b0), "f"(0.f));
}
template <int ACC>
__device__ __forceinline__ void wgmma_n32_rs(float (&d)[16], uint32_t a0, uint32_t a1, uint32_t a2, uint32_t a3, uint64_t desc) {
    asm volatile("wgmma.mma_async.sync.aligned.m64n32k16.f32.bf16.bf16 {%0,%1,%2,%3,%4,%5,%6,%7,%8,%9,%10,%11,%12,%13,%14,%15}, {%16,%17,%18,%19}, %20, %21, 1, 1, 0;"
        : "+f"(d[0]), "+f"(d[1]), "+f"(d[2]), "+f"(d[3]), "+f"(d[4]), "+f"(d[5]), "+f"(d[6]), "+f"(d[7]),
          "+f"(d[8]), "+f"(d[9]), "+f"(d[10]), "+f"(d[11]), "+f"(d[12]), "+f"(d[13]), "+f"(d[14]), "+f"(d[15])
        : "r"(a0), "r"(a1), "r"(a2), "r"(a3), "l"(desc), "n"(ACC));
}
template <int ACC>
__device__ __forceinline__ void wgmma_n32_ss(float (&d)[16], uint64_t da, uint64_t db) {
    asm volatile("wgmma.mma_async.sync.aligned.m64n32k16.f32.bf16.bf16 {%0,%1,%2,%3,%4,%5,%6,%7,%8,%9,%10,%11,%12,%13,%14,%15}, %16, %17, %18, 1, 1, 0, 0;"
        : "+f"(d[0]), "+f"(d[1]), "+f"(d[2]), "+f"(d[3]), "+f"(d[4]), "+f"(d[5]), "+f"(d[6]), "+f"(d[7]),
          "+f"(d[8]), "+f"(d[9]), "+f"(d[10]), "+f"(d[11]), "+f"(d[12]), "+f"(d[13]), "+f"(d[14]), "+f"(d[15])
        : "l"(da), "l"(db), "n"(ACC));
}
__device__ __forceinline__ void wg_fence() { asm volatile("wgmma.fence.sync.aligned;" ::: "memory"); }
__device__ __forceinline__ void wg_commit() { asm volatile("wgmma.commit_group.sync.aligned;" ::: "memory"); }
__device__ __forceinline__ void wg_wait0() { asm volatile("wgmma.wait_group.sync.aligned 0;" ::: "memory"); }
__device__ __forceinline__ void cluster_sync() { asm volatile("barrier.cluster.arrive.aligned;\nbarrier.cluster.wait.aligned;" ::: "memory"); }

#define STAMP(s, i) do {} while (0)
#define STAMPV(s, i, v) do {} while (0)

constexpr int XT_BYTES = 36864;
constexpr int O_XT = 0;
constexpr int O_STG = XT_BYTES;
constexpr int O_AS = 3 * XT_BYTES;
constexpr int O_XP = O_AS + 16384;
constexpr int O_QKX = O_XP + 8192;
constexpr int O_KM = O_QKX + 8192;
constexpr int O_QM = O_QKX + 10240;
constexpr int O_VX = O_STG + 147456;
constexpr int O_VM = O_VX + 16384;
constexpr int O_SC = O_VM + 2048;
constexpr int O_OF = O_SC + 2560;
constexpr int O_AF = O_OF + 2048;
constexpr int O_WP = O_AF + 4096;
constexpr int O_MF = O_WP + 2048;
constexpr int O_MISC = O_MF + 9216;
static_assert(O_QKX + 24576 <= O_VX, "smem");
constexpr int O_BAR = O_MISC + 64;
constexpr int CHAIN_SMEM = O_BAR + 128;
static_assert(CHAIN_SMEM <= 232448, "smem");
constexpr int B_X = O_BAR, B_VX = O_BAR + 24, B_SC = O_BAR + 40, B_W = O_BAR + 48;
constexpr float SM_SCALE = 0.08838834764831845f * 1.4426950408889634f;
constexpr uint32_t ONES = 0x3f803f80u;

__device__ __forceinline__ uint32_t opaque(uint32_t v) { uint32_t o; asm volatile("mov.u32 %0, %1;" : "=r"(o) : "r"(v)); return o; }
__device__ __forceinline__ void st_async128(uint32_t a, uint32_t x, uint32_t y, uint32_t z, uint32_t w, uint32_t bar) {
    asm volatile("st.async.shared::cluster.mbarrier::complete_tx::bytes.v4.b32 [%0], {%1,%2,%3,%4}, [%5];" :: "r"(a), "r"(x), "r"(y), "r"(z), "r"(w), "r"(bar) : "memory");
}
__device__ __forceinline__ void tma_x_tile(uint32_t sb, const CUtensorMap* tm, int r, int j, int slot) {
    asm volatile("{\n.reg .pred p;\nelect.sync _|p, 0xffffffff;\n"
        "@p mbarrier.arrive.expect_tx.shared::cta.b64 _, [%2], 36864;\n"
        "@p cp.async.bulk.tensor.2d.shared::cluster.global.mbarrier::complete_tx::bytes.multicast::cluster [%0], [%1, {%3, %4}], [%2], %7;\n"
        "@p cp.async.bulk.tensor.2d.shared::cluster.global.mbarrier::complete_tx::bytes.multicast::cluster [%0+4096], [%1, {%5, %4}], [%2], %7;\n"
        "@p cp.async.bulk.tensor.2d.shared::cluster.global.mbarrier::complete_tx::bytes.multicast::cluster [%0+8192], [%1, {%6, %4}], [%2], %7;\n}"
        :: "r"(sb + O_XT + slot * XT_BYTES + 3 * r * 4096), "l"(tm), "r"(sb + B_X + 8 * slot), "r"(192 * r), "r"(j * 32), "r"(192 * r + 64), "r"(192 * r + 128),
           "h"((unsigned short)7) : "memory");
}
__device__ __forceinline__ void flag_inc_if(uint32_t z, unsigned* p) {
    asm volatile("{\n.reg .pred p;\nsetp.eq.u32 p, %1, 0;\n@p red.release.gpu.global.inc.u32 [%0], 0xfffffffe;\n}" :: "l"(p), "r"(z) : "memory");
}
__device__ __forceinline__ float quad_max(float v) {
    const float a = __shfl_xor_sync(~0u, v, 1), b = __shfl_xor_sync(~0u, v, 2), c = __shfl_xor_sync(~0u, v, 3);
    return fmaxf(fmaxf(v, a), fmaxf(b, c));
}
__device__ __forceinline__ void load_scores(float (&p)[10], uint32_t base, uint32_t stride, uint32_t l16) {
    const float4 a0 = lds128f(base + l16), b0 = lds128f(base + stride + l16);
    const float4 a1 = lds128f(base + 512 + l16), b1 = lds128f(base + stride + 512 + l16);
    const float2 a2 = lds64f(base + 1024 + (l16 >> 1)), b2 = lds64f(base + stride + 1024 + (l16 >> 1));
    p[0] = a2.x + b2.x; p[1] = a2.y + b2.y;
    p[2] = a0.x + b0.x; p[3] = a0.y + b0.y; p[4] = a0.z + b0.z; p[5] = a0.w + b0.w;
    p[6] = a1.x + b1.x; p[7] = a1.y + b1.y; p[8] = a1.z + b1.z; p[9] = a1.w + b1.w;
}
__device__ __forceinline__ float rcp_fast(float x) { float y; asm("rcp.approx.ftz.f32 %0, %1;" : "=f"(y) : "f"(x)); return y; }

__global__ void __cluster_dims__(3, 1, 1) __launch_bounds__(384, 1)
chain_kernel(const __grid_constant__ CUtensorMap tm_x, const __grid_constant__ CUtensorMap tm_q,
             const __grid_constant__ CUtensorMap tm_k, const __grid_constant__ CUtensorMap tm_v,
             const __nv_bfloat16* __restrict__ x, const __nv_bfloat16* __restrict__ mem0,
             const __nv_bfloat16* __restrict__ Wo) {
    extern __shared__ __align__(1024) uint8_t smem_raw[];
    const uint32_t sb = smem_u32(smem_raw);
    const int lane = threadIdx.x & 31;
    const int warp = __shfl_sync(~0u, threadIdx.x >> 5, 0);
    const int wg = warp >> 2, w = warp & 3;
    const int h = blockIdx.x / 3, r = blockIdx.x - 3 * h;
    uint4* const g_acc = reinterpret_cast<uint4*>((reinterpret_cast<uintptr_t>(g_acc_raw) + 0x1fffff) & ~(uintptr_t)0x1fffff);

#define PSTAMP(i) do {} while (0)
    if (threadIdx.x == 0) {
        if (sb & 1023u) __trap();
        for (int i = 0; i < 9; i++) mbar_init(sb + O_BAR + 8 * i, 1);
        asm volatile("fence.mbarrier_init.release.cluster;" ::: "memory");
        for (int i = 0; i < 3; i++) {
            mbar_expect(sb + B_W + 8 * i, 49152);
            for (int tl = 0; tl < 2; tl++)
                asm volatile("cp.async.bulk.tensor.2d.shared::cluster.global.mbarrier::complete_tx::bytes [%0], [%1, {%3, %4}], [%2];"
                    :: "r"(sb + O_STG + tl * 73728 + i * 24576), "l"(r < 2 ? (tl ? &tm_k : &tm_q) : &tm_v), "r"(sb + B_W + 8 * i),
                       "r"(h * 128 + 64 * (r < 2 ? r : tl)), "r"(192 * i) : "memory");
        }
    }
    __syncwarp();
    asm volatile("barrier.cluster.arrive.relaxed.aligned;" ::: "memory");
    asm volatile("griddepcontrol.launch_dependents;" ::: "memory");
    if (warp == 0) PSTAMP(9);
    const uint32_t l16c = __shfl_sync(~0u, lane * 16, lane);

    if (wg < 2) {
#define KS(u) ((u) < 8 ? 12 * ((u) >> 2) + (((u) >> 1) & 1) + 4 * ((u) & 1) : (u) < 12 ? (u) : (u) < 16 ? (u) + 8 : (u) < 24 ? 24 + (((u) - 16) >> 1) + 4 * ((u) & 1) : (u) + 8)
        asm volatile("setmaxnreg.inc.sync.aligned.u32 184;");
        uint32_t a[144];
        uint32_t adr1;
        {
            const int g = lane >> 2, t = lane & 3;
            const int t1 = threadIdx.x;
#pragma unroll
            for (int i = 0; i < 2; i++) g_acc[(blockIdx.x * 64 + i * 32 + (t1 >> 3)) * 16 + (t1 & 7)] = make_uint4(0, 0, 0, 0);
            __threadfence();
            asm volatile("barrier.cluster.wait.aligned;" ::: "memory");
            const uint32_t ev = sb + O_STG + (2 * t) * 128 + (((2 * w + (g >> 2)) ^ (2 * t)) << 4) + (g & 3) * 4;
            const uint32_t od = (ev ^ 16) + 128;
            auto gather = [&](int dst, uint32_t off) {
                a[dst] = lds32(ev + off); a[dst + 1] = lds32(od + off); a[dst + 2] = lds32(ev + off + 1024); a[dst + 3] = lds32(od + off + 1024);
            };
            const uint4* xp = reinterpret_cast<const uint4*>(x) + blockIdx.x * 1536 + t1;
            uint4 xv[6];
#pragma unroll
            for (int th = 0; th < 2; th++) {
                mbar_wait(sb + B_W + 8 * th, 0);
                if (th == 1) {
#pragma unroll
                    for (int i = 0; i < 6; i++) xv[i] = __ldg(xp + i * 256);
                }
#pragma unroll
                for (int u = 4 * th; u < 4 * th + 4; u++) {
                    gather(32 + 4 * u, wg * (73728 + 4096) + KS(u) * 2048);
                    gather(4 * u, 73728 - wg * (73728 - 4096) + KS(u) * 2048);
                    gather(64 + 4 * u, wg * 73728 + KS(8 + u) * 2048);
                }
            }
            mbar_wait(sb + B_W + 16, 0);
#pragma unroll
            for (int u = 16; u < 28; u++) gather(32 + 4 * u, wg * 73728 + KS(u) * 2048);
#pragma unroll
            for (int kk = 0; kk < 72; kk++) {
                uint32_t w0 = a[2 * kk], w1 = a[2 * kk + 1];
                a[2 * kk] = __byte_perm(w0, w1, 0x5410);
                a[2 * kk + 1] = __byte_perm(w0, w1, 0x7632);
            }
            if (r == 2) {
                float n0[4], n1[4];
#pragma unroll
                for (int u = 0; u < 36; u++) {
                    const uint32_t x0 = a[4 * u] & 0x7fff7fffu, x1 = a[4 * u + 1] & 0x7fff7fffu, x2 = a[4 * u + 2] & 0x7fff7fffu, x3 = a[4 * u + 3] & 0x7fff7fffu;
                    if (u == 0) mma16816_z(n0, x0, x1, x2, x3, ONES, ONES);
                    else if (u < 8) mma16816(n0, x0, x1, x2, x3, ONES, ONES);
                    else if (u == 8) mma16816_z(n1, x0, x1, x2, x3, ONES, ONES);
                    else mma16816(n1, x0, x1, x2, x3, ONES, ONES);
                }
                const uint32_t mx = __reduce_max_sync(~0u, __float_as_uint(2.f * fmaxf(fmaxf(n0[0], n0[2]), fmaxf(n1[0], n1[2]))));
                sts32_if(lane, sb + O_MISC + 32 + 4 * warp, mx);
            }
            uint32_t xm = 0;
#pragma unroll
            for (int i = 0; i < 6; i++)
                xm = __vmaxu2(xm, __vmaxu2(__vmaxu2(xv[i].x & 0x7fff7fffu, xv[i].y & 0x7fff7fffu), __vmaxu2(xv[i].z & 0x7fff7fffu, xv[i].w & 0x7fff7fffu)));
            sts32_if(lane, sb + O_OF + 16 + 4 * warp, __reduce_max_sync(~0u, max(xm << 16, xm & 0xffff0000u)));
            if (warp == 0) PSTAMP(11);
            bar_arrive(7, 384);
            asm volatile("barrier.cluster.arrive.relaxed.aligned;" ::: "memory");
            bar_sync(1, 256);
            const uint32_t as = sb + O_AS + wg * 8192 + (16 * w + g) * 128 + t * 4;
            sts32(as + (g << 4), a[32]);
            sts32(as + 1024 + (g << 4), a[33]);
            sts32(as + ((1 ^ g) << 4), a[34]);
            sts32(as + 1024 + ((1 ^ g) << 4), a[35]);
            sts128(sb + O_AF + warp * 512 + lane * 16, a[32], a[33], a[34], a[35]);
            fence_async_smem();
            bar_sync(1, 256);
            const uint32_t l = lane * 16;
            const int mi = lane >> 3, isk = (mi >> 1) ? wg : (wg ^ 1);
            adr1 = (r == 2) ? (sb + O_VM + warp * 256 + (l >> 1))
                            : (isk ? (sb + O_KM + w * 512 + wg * 256 + (mi & 1) * 128 + (l & 127))
                                   : (sb + O_QM + w * 512 + (mi & 1) * 256 + wg * 128 + (l & 127)));
            adr1 = __shfl_sync(~0u, adr1, lane);
        }
        int s3 = 2;
#pragma unroll 1
        for (int s = -1; s < NSEG; s++) {
            const uint32_t l16 = opaque(l16c);
            s3 = (s3 == 2) ? 0 : s3 + 1;
            if (s < 0) mbar_wait(sb + B_X, 0);
            const uint64_t desc0 = (uint64_t)(((sb + O_XT + s3 * XT_BYTES) & 0x3FFFF) >> 4) | (1ull << 16) | (64ull << 32) | (1ull << 62);
            uint32_t km0 = 0, km1 = 0;
            if (s >= 0) {
                { const uint4 v = lds128(sb + O_AF + warp * 512 + l16); a[32] = v.x; a[33] = v.y; a[34] = v.z; a[35] = v.w; }
                float co[4], cw[3][4];
                uint4 b[14];
                float inv;
#define GORD(i) ((i) < 8 ? 2 * ((i) >> 2) + (((i) >> 1) & 1) + 4 * ((i) & 1) : (i))
                auto qkv_mma = [&](int i) {
                    const int gi = GORD(i), u = 8 * gi, n0 = 2 * i, n1 = 2 * i + 1;
                    if (gi < 4) {
                        if (i == 0) mma16816_z(co, a[u], a[u + 1], a[u + 2], a[u + 3], b[0].x, b[0].y);
                        else mma16816(co, a[u], a[u + 1], a[u + 2], a[u + 3], b[i].x, b[i].y);
                    }
                    if (n0 < 3) mma16816_z(cw[n0 % 3], a[32 + u], a[32 + u + 1], a[32 + u + 2], a[32 + u + 3], b[i].x, b[i].y);
                    else mma16816(cw[n0 % 3], a[32 + u], a[32 + u + 1], a[32 + u + 2], a[32 + u + 3], b[i].x, b[i].y);
                    if (n1 < 3) mma16816_z(cw[n1 % 3], a[32 + u + 4], a[32 + u + 5], a[32 + u + 6], a[32 + u + 7], b[i].z, b[i].w);
                    else mma16816(cw[n1 % 3], a[32 + u + 4], a[32 + u + 5], a[32 + u + 6], a[32 + u + 7], b[i].z, b[i].w);
                    if (gi < 4) mma16816(co, a[u + 4], a[u + 5], a[u + 6], a[u + 7], b[i].z, b[i].w);
                };
                const uint32_t mf = sb + O_MF + l16, mfs = mf + wg * 1024;
                const uint32_t qb = (s & 1) * 12288;
                bar_sync(2, 384);
                if (warp == 0) STAMP(s, 0);
                auto qkv_ld = [&](int i) {
                    const int gi = GORD(i);
                    b[i] = gi < 4 ? lds128v(mfs + (gi >> 1) * 3072 + (gi & 1) * 512) : lds128v(mf + (gi < 6 ? gi : gi + 4) * 512);
                };
#pragma unroll
                for (int i = 0; i < 4; i++) qkv_ld(i);
                qkv_mma(0); qkv_mma(1); qkv_mma(2);
                const uint32_t z0 = __float_as_uint(QDEP ? co[0] : cw[1][0]) & (l16 & 15u);
                qkv_mma(3);
                bar_sync(15, 384);
                b[4] = lds128v(mfs + 3072 + z0);
#pragma unroll
                for (int i = 5; i < 9; i++) qkv_ld(i);
#pragma unroll
                for (int i = 4; i < 9; i++) { qkv_mma(i); qkv_ld(5 + i); }
                asm volatile("ld.volatile.shared.f32 %0, [%1];" : "=f"(inv) : "r"(sb + O_MISC) : "memory");
#pragma unroll
                for (int i = 9; i < 14; i++) qkv_mma(i);
#pragma unroll
                for (int i = 0; i < 4; i++) cw[0][i] += cw[1][i] + cw[2][i];
                if (r < 2) {
                    const uint32_t o0 = pack_bf16(co[0] * inv, co[1] * inv), o1 = pack_bf16(co[2] * inv, co[3] * inv);
                    const uint32_t w0 = pack_bf16(cw[0][0] * inv, cw[0][1] * inv), w1 = pack_bf16(cw[0][2] * inv, cw[0][3] * inv);
                    stsm4t(adr1 + qb, o0, o1, w0, w1);
                    if (warp == 0) STAMP(s, 1);
                    asm volatile("{\n.reg .pred p;\nsetp.ge.u32 p, %0, 3;\n@p bar.arrive 1, 256;\n}" :: "r"(warp) : "memory");
                    auto scores = [&](float (&v)[4], const uint4 (&q)[4], const uint4 (&k)[4]) {
                        float s0[4], s1[4], t0[4], t1[4];
                        mma16816_z(s0, q[0].x, q[0].y, q[0].z, q[0].w, k[0].x, k[0].y);
                        mma16816_z(s1, q[0].x, q[0].y, q[0].z, q[0].w, k[0].z, k[0].w);
                        mma16816_z(t0, q[1].x, q[1].y, q[1].z, q[1].w, k[1].x, k[1].y);
                        mma16816_z(t1, q[1].x, q[1].y, q[1].z, q[1].w, k[1].z, k[1].w);
                        mma16816(s0, q[2].x, q[2].y, q[2].z, q[2].w, k[2].x, k[2].y);
                        mma16816(s1, q[2].x, q[2].y, q[2].z, q[2].w, k[2].z, k[2].w);
                        mma16816(t0, q[3].x, q[3].y, q[3].z, q[3].w, k[3].x, k[3].y);
                        mma16816(t1, q[3].x, q[3].y, q[3].z, q[3].w, k[3].z, k[3].w);
                        v[0] = (s0[0] + s0[2]) + (t0[0] + t0[2]); v[1] = (s0[1] + s0[3]) + (t0[1] + t0[3]);
                        v[2] = (s1[0] + s1[2]) + (t1[0] + t1[2]); v[3] = (s1[1] + s1[3]) + (t1[1] + t1[3]);
                    };
                    if (warp < 2) {
                        uint4 q[4], k[4]; float v[4];
#pragma unroll
                        for (int i = 0; i < 4; i++) k[i] = ldsm4(sb + O_QKX + 4096 + qb + warp * 2048 + i * 512 + l16);
                        bar_sync(1, 256);
#pragma unroll
                        for (int i = 0; i < 4; i++) q[i] = ldsm4(sb + O_QM + qb + i * 512 + l16);
                        scores(v, q, k);
                        const uint32_t dst = sb + O_SC + r * 1280 + warp * 512 + l16;
                        st_async128(mapa(dst, 2), __float_as_uint(v[0]), __float_as_uint(v[1]), __float_as_uint(v[2]), __float_as_uint(v[3]), mapa(sb + B_SC, 2));
                        st_async128(mapa(dst, r ^ 1), __float_as_uint(v[0]), __float_as_uint(v[1]), __float_as_uint(v[2]), __float_as_uint(v[3]), mapa(sb + B_SC, r ^ 1));
                        st_async128(mapa(dst, r), __float_as_uint(v[0]), __float_as_uint(v[1]), __float_as_uint(v[2]), __float_as_uint(v[3]), mapa(sb + B_SC, r));
                    } else if (warp == 2) {
                        uint4 q[4], k[4]; float v[4];
                        bar_sync(1, 256);
#pragma unroll
                        for (int i = 0; i < 4; i++) { q[i] = ldsm4(sb + O_QM + qb + i * 512 + l16); k[i] = ldsm4(sb + O_KM + qb + i * 512 + l16); }
                        scores(v, q, k);
                        const uint32_t dst = sb + O_SC + r * 1280 + 1024 + (l16 >> 1);
                        st_async64(mapa(dst, 2), __float_as_uint(v[0] + v[2]), __float_as_uint(v[1] + v[3]), mapa(sb + B_SC, 2));
                        st_async64(mapa(dst, r ^ 1), __float_as_uint(v[0] + v[2]), __float_as_uint(v[1] + v[3]), mapa(sb + B_SC, r ^ 1));
                        st_async64(mapa(dst, r), __float_as_uint(v[0] + v[2]), __float_as_uint(v[1] + v[3]), mapa(sb + B_SC, r));
                        STAMP(s, 2);
                    }
                } else {
                    sts128f(sb + O_XP + warp * 512 + l16, co[0], co[1], co[2], co[3]);
                    bar_sync(8 + w, 64);
                    const float4 o = lds128f(sb + O_XP + (warp ^ 4) * 512 + l16);
                    km0 = pack_bf16((cw[0][0] + o.x) * inv, (cw[0][1] + o.y) * inv);
                    km1 = pack_bf16((cw[0][2] + o.z) * inv, (cw[0][3] + o.w) * inv);
                    if (warp == 0) STAMP(s, 1);
                    st_async64(mapa(adr1, 0), km0, km1, mapa(sb + B_SC, 0));
                    st_async64(mapa(adr1, 1), km0, km1, mapa(sb + B_SC, 1));
                    st_async64(mapa(adr1, 2), km0, km1, mapa(sb + B_SC, 2));
                    if (warp == 0) STAMP(s, 2);
                }
            }
            if (s >= 0) bar_sync(3, 384);
            auto store_qk = [&]() {
                asm volatile("{\n.reg .pred p;\nelect.sync _|p, 0xffffffff;\n"
                    "@p cp.async.bulk.global.shared::cta.bulk_group [%0], [%1], 10240;\n@p cp.async.bulk.commit_group;\n}"
                    :: "l"(reinterpret_cast<char*>(g_qkv) + (size_t)(s * NH + h) * REC + r * 10240), "r"(sb + O_QKX + (s & 1) * 12288) : "memory");
            };
            auto store_vm = [&]() {
                *reinterpret_cast<uint2*>(reinterpret_cast<char*>(g_qkv) + (size_t)(s * NH + h) * REC + 28672 + warp * 256 + (l16 >> 1)) = make_uint2(km0, km1);
            };
            if (s == NSEG - 1) {
                if (r == 2) store_vm();
                else if (warp == 3) {
                    fence_async_smem();
                    store_qk();
                    asm volatile("cp.async.bulk.wait_group 0;\nfence.proxy.async.global;" ::: "memory");
                }
            } else {
                const int j = s + 1;
#define XDESC(u) (((u) < 8 ? descs : desc0) + (uint64_t)(((KS(u) >> 2) * 4096 + (KS(u) & 3) * 32) >> 4))
                const uint64_t descs = desc0 + (uint64_t)(wg * 4);
                float d[16];
                wg_fence();
#pragma unroll
                for (int u = 0; u < 8; u++) {
                    if (u == 0) wgmma_n32_rs<0>(d, a[0], a[1], a[2], a[3], XDESC(0));
                    else wgmma_n32_rs<1>(d, a[4 * u], a[4 * u + 1], a[4 * u + 2], a[4 * u + 3], XDESC(u));
                }
                wg_commit();
                wg_wait0();
                if (warp == 0) STAMP(s, 15);
                auto xp_put = [&]() {
#pragma unroll
                    for (int q = 0; q < 2; q++)
                        sts128(sb + O_XP + warp * 1024 + q * 512 + l16, pack_bf16(d[8 * q], d[8 * q + 1]), pack_bf16(d[8 * q + 2], d[8 * q + 3]),
                               pack_bf16(d[8 * q + 4], d[8 * q + 5]), pack_bf16(d[8 * q + 6], d[8 * q + 7]));
                };
                uint4 xo[2];
                auto xp_get = [&]() { xo[0] = lds128(sb + O_XP + (warp ^ 4) * 1024 + l16); xo[1] = lds128(sb + O_XP + (warp ^ 4) * 1024 + 512 + l16); };
                if (warp == 3) asm volatile("cp.async.bulk.wait_group 0;\nfence.proxy.async.global;" ::: "memory");
                if (warp == 3 && (s & 3) == 0 && s >= 4) {
                    xp_put();
                    bar_arrive(4, 384);
                    bar_arrive(12, 256);
                    flag_inc_if(l16, &g_flag[F_QKV + (s - 4 + (h >> 3)) * 8]);
                    if (r == 2) store_vm();
                    fence_async_smem();
                    bar_sync(5, 256);
                    xp_get();
                } else {
                    if (s >= 0) bar_sync(4, 384);
                    xp_put();
                    bar_sync(12, 256);
                    xp_get();
                    if (s >= 0) {
                        if (r == 2) store_vm();
                        if (warp == 5 && s + 2 < NSEG) tma_x_tile(sb, &tm_x, r, s + 2, s3 == 2 ? 0 : s3 + 1);
                        if (warp == 3) fence_async_smem();
                        asm volatile("{\n.reg .pred p;\nsetp.eq.u32 p, %0, 0;\n@p bar.sync 5, 256;\n@!p bar.sync 13, 256;\n}" :: "r"(wg) : "memory");
                    }
                }
#pragma unroll
                for (int q = 0; q < 2; q++) {
                    d[8 * q] = __uint_as_float(xo[q].x << 16); d[8 * q + 1] = __uint_as_float(xo[q].x & 0xffff0000u);
                    d[8 * q + 2] = __uint_as_float(xo[q].y << 16); d[8 * q + 3] = __uint_as_float(xo[q].y & 0xffff0000u);
                    d[8 * q + 4] = __uint_as_float(xo[q].z << 16); d[8 * q + 5] = __uint_as_float(xo[q].z & 0xffff0000u);
                    d[8 * q + 6] = __uint_as_float(xo[q].w << 16); d[8 * q + 7] = __uint_as_float(xo[q].w & 0xffff0000u);
                }
                const uint64_t da0 = (uint64_t)(((sb + O_AS + wg * 8192) & 0x3FFFF) >> 4) | (1ull << 16) | (64ull << 32) | (1ull << 62);
                wg_fence();
                wgmma_n32_ss<1>(d, da0, XDESC(0));
#pragma unroll
                for (int u = 1; u < 28; u++) wgmma_n32_rs<1>(d, a[32 + 4 * u], a[32 + 4 * u + 1], a[32 + 4 * u + 2], a[32 + 4 * u + 3], XDESC(u));
                wg_commit();
                wg_wait0();
                if (warp == 3 && r < 2 && s >= 0) store_qk();
                if (warp == 4) STAMP(s, 3);
                uint32_t e[8];
#pragma unroll
                for (int i = 0; i < 8; i++) e[i] = pack_bf16(d[2 * i], d[2 * i + 1]);
                if (r < 2) {
                    const uint32_t base = sb + O_QKX + (j & 1) * 12288 + wg * 4096 + w * 512 + l16;
                    stsm4t(base, e[0], wg ? e[1] : e[2], wg ? e[2] : e[1], e[3]);
                    stsm4t(base + 2048, e[4], wg ? e[5] : e[6], wg ? e[6] : e[5], e[7]);
                } else {
                    const uint32_t base = sb + O_VX + (j & 1) * 8192 + warp * 1024 + l16;
                    sts128(base, e[0], e[1], e[2], e[3]);
                    sts128(base + 512, e[4], e[5], e[6], e[7]);
                    bar_arrive(14, 288);
                }
                if (warp == 7) STAMP(s, 4);
                if (s < 0) asm volatile("barrier.cluster.wait.aligned;" ::: "memory");
            }
        }
        bar_arrive(7, 384);
    } else {
        asm volatile("setmaxnreg.dec.sync.aligned.u32 136;");
        const int c = w;
        uint32_t a[96];
        uint32_t mmax = 0;
        {
            const int g = lane >> 2, t = lane & 3;
            uint32_t tag = 0, m0v[18];
            if (threadIdx.x == 256) tag = atomicAdd(&g_ticket, 1u);
#pragma unroll
            for (int i = 0; i < 9; i++) {
                const uint32_t* p = reinterpret_cast<const uint32_t*>(mem0 + g * DM + 16 * (4 * i + c) + 2 * t);
                m0v[2 * i] = __ldg(p); m0v[2 * i + 1] = __ldg(p + 4);
            }
            asm volatile("barrier.cluster.wait.aligned;" ::: "memory");
            if (c == 0) {
                tma_x_tile(sb, &tm_x, r, 0, 0);
                mbar_expect_if(lane, sb + B_SC, 4608);
                if (r < 2) mbar_expect_if(lane, sb + B_VX, 8192);
                sts32_if(lane, sb + O_MISC, __float_as_uint(1.0f));
                sts32_if(lane, sb + O_MISC + 12, __float_as_uint(SM_SCALE));
            }
            asm volatile("barrier.cluster.arrive.relaxed.aligned;" ::: "memory");
#pragma unroll
            for (int tau = 0; tau < 3; tau++) {
                const uint32_t* v = m0v + 6 * tau;
                sts128(sb + O_MF + tau * 3072 + c * 512 + lane * 16, v[0], v[1], v[2], v[3]);
                sts64(sb + O_MF + tau * 3072 + 2048 + (c >> 1) * 512 + lane * 16 + (c & 1) * 8, v[4], v[5]);
#pragma unroll
                for (int i = 0; i < 6; i++) mmax = __vmaxu2(mmax, v[i] & 0x7fff7fffu);
            }
            mmax = max(mmax << 16, mmax & 0xffff0000u);
            bar_arrive(2, 384); bar_arrive(15, 384);
            tag = (__shfl_sync(~0u, tag, 0) / 96u + 1u) & 0xffffu;
            mbar_wait(sb + B_W + 0, 0);
            const __nv_bfloat16* p = Wo + (size_t)(h * 128 + 4 * t) * DM + 192 * r + 16 * c + 2 * g;
#pragma unroll
            for (int i = 0; i < 3; i++)
#pragma unroll
                for (int eb = 0; eb < 8; eb++)
#pragma unroll
                    for (int j = 0; j < 4; j++) a[(i * 8 + eb) * 4 + j] = ldg_nc32(p + (16 * eb + ((j & 1) * 2 + (j >> 1))) * DM + 64 * i);
#pragma unroll
            for (int kk = 0; kk < 48; kk++) {
                uint32_t w0 = a[2 * kk], w1 = a[2 * kk + 1];
                a[2 * kk] = __byte_perm(w0, w1, 0x5410);
                a[2 * kk + 1] = __byte_perm(w0, w1, 0x7632);
            }
            sts128(sb + O_WP + c * 512 + lane * 16, a[92], a[93], a[94], a[95]);
            float wmax = 0.f;
#pragma unroll
            for (int i = 0; i < 3; i++) {
                float n0[4];
#pragma unroll
                for (int u = 8 * i; u < 8 * i + 8; u++) {
                    const uint32_t x0 = a[4 * u] & 0x7fff7fffu, x1 = a[4 * u + 1] & 0x7fff7fffu, x2 = a[4 * u + 2] & 0x7fff7fffu, x3 = a[4 * u + 3] & 0x7fff7fffu;
                    if (u == 8 * i) mma16816_z(n0, x0, x1, x2, x3, ONES, ONES);
                    else mma16816(n0, x0, x1, x2, x3, ONES, ONES);
                }
                wmax = fmaxf(wmax, fmaxf(n0[0], n0[2]));
            }
            uint32_t wm = __reduce_max_sync(~0u, __float_as_uint(wmax));
            sts32_if(lane, sb + O_OF + 4 * c, wm);
            if (c == 0) PSTAMP(8);
            bar_sync(7, 384);
            asm volatile("barrier.cluster.wait.aligned;" ::: "memory");
            if (c == 1) tma_x_tile(sb, &tm_x, r, 1, 1);
            if (c == 0) {
                const uint4 wq = lds128(sb + O_OF), xq = lds128(sb + O_OF + 16), xr = lds128(sb + O_OF + 32), v0 = lds128(sb + O_MISC + 32), v1 = lds128(sb + O_MISC + 48);
                const uint32_t w1 = max(max(wq.x, wq.y), max(wq.z, wq.w)), x1 = max(max(max(xq.x, xq.y), max(xq.z, xq.w)), max(max(xr.x, xr.y), max(xr.z, xr.w)));
                const uint32_t vv = (r < 2) ? 0u : max(max(max(v0.x, v0.y), max(v0.z, v0.w)), max(max(v1.x, v1.y), max(v1.z, v1.w)));
                const uint32_t lo = (min(w1, 0x7f800000u) + 0xffffu) >> 16 | ((min(vv, 0x7f800000u) + 0xffffu) & 0xffff0000u), hi = (x1 & 0xffff0000u) | tag;
                uint32_t l0, h0, l1, h1, l2, h2;
                asm volatile("{\n.reg .pred p;\n.reg .u32 n, x, y;\n.reg .b64 v;\nsetp.eq.u32 p, %10, 0;\nmov.b64 v, {%8, %9};\n@p st.relaxed.gpu.global.b64 [%7], v;\nmov.u32 n, 0;\n"
                             "G_%=: ld.relaxed.gpu.global.b64 v, [%6];\nmov.b64 {%0, %1}, v;\nld.relaxed.gpu.global.b64 v, [%6+256];\nmov.b64 {%2, %3}, v;\n"
                             "ld.relaxed.gpu.global.b64 v, [%6+512];\nmov.b64 {%4, %5}, v;\n"
                             "xor.b32 x, %1, %9;\nxor.b32 y, %3, %9;\nor.b32 x, x, y;\nxor.b32 y, %5, %9;\nor.b32 x, x, y;\nand.b32 x, x, 0xffff;\n"
                             "setp.eq.u32 p, x, 0;\nvote.sync.all.pred p, p, 0xffffffff;\n@p bra.uni E_%=;\n"
                             "add.u32 n, n, 1;\nsetp.lt.u32 p, n, 4000000;\n@p bra.uni G_%=;\ntrap;\nE_%=:\n}"
                             : "=&r"(l0), "=&r"(h0), "=&r"(l1), "=&r"(h1), "=&r"(l2), "=&r"(h2)
                             : "l"(&g_norm[lane]), "l"(&g_norm[blockIdx.x]), "r"(lo), "r"(hi), "r"(lane) : "memory");
                const uint32_t lm = __vmaxu2(l0, __vmaxu2(l1, l2));
                const float fw = __uint_as_float(__reduce_max_sync(~0u, lm << 16));
                const float fv = __uint_as_float(__reduce_max_sync(~0u, lm & 0xffff0000u));
                const float xmax = __uint_as_float(__reduce_max_sync(~0u, max(h0, max(h1, h2)) & 0xffff0000u));
                const float G = 36.f * fw * fv;
                sts32_if(lane, sb + O_MISC + 4, __float_as_uint(G)); sts32_if(lane, sb + O_MISC + 8, __float_as_uint(G * xmax));
            }
        }
        if (c == 0) PSTAMP(12);
        bar_sync(6, 128);
        int s3n = 1;
        uint32_t roff = __shfl_sync(~0u, (r * 4 + c) * 2048 + (lane >> 4) * 512 + (lane & 2) * 128 + (lane & 1) * 64 + (lane & 12) * 4, lane);
#pragma unroll 1
        for (int s = 0; s < NSEG; s++) {
            const uint32_t l16 = opaque(l16c);
            const uint32_t vxa = sb + O_VX + (s & 1) * 8192 + c * 2048 + l16;
            if (c == 0 && r == 2) {
                bar_sync(14, 288);
                fence_async_smem();
                asm volatile("{\n.reg .pred p;\nelect.sync _|p, 0xffffffff;\n"
                    "@p cp.async.bulk.global.shared::cta.bulk_group [%0], [%1], 8192;\n@p cp.async.bulk.commit_group;\n"
                    "cp.async.bulk.wait_group 0;\nsetp.lt.and.s32 p, %4, 63, p;\n"
                    "@p cp.async.bulk.shared::cluster.global.mbarrier::complete_tx::bytes.multicast::cluster [%1], [%0], 8192, [%2], %3;\n"
                    "fence.proxy.async.global;\n}"
                    :: "l"(reinterpret_cast<char*>(g_qkv) + (size_t)(s * NH + h) * REC + 20480), "r"(sb + O_VX + (s & 1) * 8192),
                       "r"(sb + B_VX + 8 * (s & 1)), "h"((unsigned short)3), "r"(s) : "memory");
            }
            if (s == NSEG - 1) { bar_sync(3, 384); mbar_wait(sb + B_SC, s & 1); break; }
            uint4 vx[4];
            sts32_if(l16, sb + O_MISC + 16 + 4 * c, __reduce_max_sync(~0u, mmax));
            if (c == 0) STAMP(s, 5);
            {
                bar_sync(6, 128);
                const uint4 mm = lds128(sb + O_MISC + 16), cf = lds128(sb + O_MISC);
                const float bound = fmaxf(__uint_as_float(cf.z), __uint_as_float(cf.y) * (__uint_as_float(max(max(mm.x, mm.y), max(mm.z, mm.w))) * __uint_as_float(cf.x)));
                const uint32_t ebits = __reduce_max_sync(~0u, min(max(__float_as_uint(bound) & 0x7f800000u, 21u << 23), 254u << 23));
                mbar_wait(sb + B_X + 8 * s3n, ((s + 1) / 3) & 1);
                s3n = (s3n == 2) ? 0 : s3n + 1;
                bar_sync(3, 384);
                if (r < 2) mbar_wait(sb + B_VX + 8 * (s & 1), (s >> 1) & 1);
                vx[0] = lds128(vxa); vx[2] = lds128(vxa + 1024);
                if (c == 0) STAMP(s, 13);
                mbar_wait(sb + B_SC, s & 1);
                if (c == 0) STAMP(s, 6);
                float p[10];
                load_scores(p, sb + O_SC, 1280, l16);
                float mx = fmaxf(fmaxf(fmaxf(p[0], p[1]), fmaxf(p[2], p[3])), fmaxf(fmaxf(p[4], p[5]), fmaxf(p[6], p[7])));
                mx = quad_max(fmaxf(mx, fmaxf(p[8], p[9])));
                const uint4 vm = lds64x2(sb + O_VM + c * 512 + (l16 >> 1));
                vx[1] = lds128(vxa + 512); vx[3] = lds128(vxa + 1536);
                bar_arrive(4, 384);
                const float sc = __uint_as_float(lds32(sb + O_MISC + 12));
                const float mo = mx * SM_SCALE;
                uint32_t P[5];
#pragma unroll
                for (int n = 0; n < 5; n++) P[n] = pack_bf16(ex2(fmaf(p[2 * n], SM_SCALE, -mo)), ex2(fmaf(p[2 * n + 1], n == 3 ? sc : SM_SCALE, -mo)));
                if (c == 0) STAMP(s, 7);
                float o0[4], o1[4], sm[4];
                mma16816_z(sm, ONES, ONES, ONES, ONES, P[1], P[2]);
                mma16816_z(o0, vx[0].x, vx[0].y, vx[0].z, vx[0].w, P[1], P[2]);
                mma16816_z(o1, vx[2].x, vx[2].y, vx[2].z, vx[2].w, P[1], P[2]);
                mma16816(sm, ONES, ONES, ONES, ONES, P[3], P[4]);
                mma16816(o0, vx[1].x, vx[1].y, vx[1].z, vx[1].w, P[3], P[4]);
                mma16816(o1, vx[3].x, vx[3].y, vx[3].z, vx[3].w, P[3], P[4]);
                mma1688(sm, ONES, ONES, P[0]);
                mma1688(o0, vm.x, vm.y, P[0]);
                mma1688(o1, vm.z, vm.w, P[0]);
                const float sig = __uint_as_float((268u << 23) - ebits);
                const float r0 = rcp_fast(sm[0]) * sig, r1 = rcp_fast(sm[1]) * sig;
                stsm4t(sb + O_OF + c * 512 + l16, pack_bf16(o0[0] * r0, o0[1] * r1), pack_bf16(o0[2] * r0, o0[3] * r1),
                       pack_bf16(o1[0] * r0, o1[1] * r1), pack_bf16(o1[2] * r0, o1[3] * r1));
                bar_sync(6, 128);
                uint4 ob[4];
#pragma unroll
                for (int q = 0; q < 4; q++) ob[q] = ldsm4(sb + O_OF + q * 512 + l16);
                { const uint4 v = lds128(sb + O_WP + c * 512 + l16); a[92] = v.x; a[93] = v.y; a[94] = v.z; a[95] = v.w; }
                float m0[3][4], m1[3][4];
#pragma unroll
                for (int q = 0; q < 4; q++) {
#pragma unroll
                    for (int i = 0; i < 3; i++) {
                        const int k0 = (i * 8 + 2 * q) * 4;
                        if (q == 0) mma16816_z(m0[i], a[k0], a[k0 + 1], a[k0 + 2], a[k0 + 3], ob[q].x, ob[q].y);
                        else mma16816(m0[i], a[k0], a[k0 + 1], a[k0 + 2], a[k0 + 3], ob[q].x, ob[q].y);
                    }
#pragma unroll
                    for (int i = 0; i < 3; i++) {
                        const int k1 = (i * 8 + 2 * q + 1) * 4;
                        if (q == 0) mma16816_z(m1[i], a[k1], a[k1 + 1], a[k1 + 2], a[k1 + 3], ob[q].z, ob[q].w);
                        else mma16816(m1[i], a[k1], a[k1 + 1], a[k1 + 2], a[k1 + 3], ob[q].z, ob[q].w);
                    }
                }
                asm volatile("red.relaxed.gpu.global.add.noftz.v4.f16x2 [%0], {%1,%2,%3,%4};" :: "l"(reinterpret_cast<char*>(g_acc) + roff),
                    "r"(pack_f16(m0[0][0] + m1[0][0], m0[0][2] + m1[0][2])), "r"(pack_f16(m0[1][0] + m1[1][0], m0[1][2] + m1[1][2])),
                    "r"(pack_f16(m0[2][0] + m1[2][0], m0[2][2] + m1[2][2])), "r"(0x3c00u) : "memory");
                asm volatile("red.relaxed.gpu.global.add.noftz.v4.f16x2 [%0], {%1,%2,%3,%4};" :: "l"(reinterpret_cast<char*>(g_acc) + roff + 1024),
                    "r"(pack_f16(m0[0][1] + m1[0][1], m0[0][3] + m1[0][3])), "r"(pack_f16(m0[1][1] + m1[1][1], m0[1][3] + m1[1][3])),
                    "r"(pack_f16(m0[2][1] + m1[2][1], m0[2][3] + m1[2][3])), "r"(0x3c00u) : "memory");
                const unsigned t_red = clk();
                bar_arrive(5, 256);
                bar_arrive(13, 256);
                mbar_expect_if(l16 | c, sb + B_SC, 4608);
                mbar_expect_if(l16 | (c ^ 1) | (r >> 1), sb + B_VX + 8 * ((s + 1) & 1), 8192);
                sts32_if(l16 | (c ^ 3), sb + O_MISC, ebits - (14u << 23));
                if (c == 0) STAMPV(s, 8, t_red);
                if (ACC_PF && c == 2 && s + 4 < NSEG - 1)
                    asm volatile("prefetch.global.L2 [%0];" :: "l"(reinterpret_cast<const char*>(g_acc) + ((s + 4) * 96 + blockIdx.x) * 256 + (l16 & 96)) : "memory");
                const char* pbase = reinterpret_cast<const char*>(g_acc) + (s * 24576 + c * 2048) + ((l16 & 64) * 16 + (l16 & 256) + ((l16 & 128) >> 1) + (l16 & 48));
                spin_until(t_red, D_WAIT);
                uint4 v[6];
#pragma unroll
                for (int i = 0; i < 6; i++) v[i] = ldg_relaxed128(pbase + (i >> 1) * 8192 + (i & 1) * 512);
                int nretry = 0;
                auto convert = [&](int tau) {
                    const uint4 A = v[2 * tau], B = v[2 * tau + 1];
                    sts128(sb + O_MF + tau * 3072 + c * 512 + l16, f16x2_to_bf16x2(A.x), f16x2_to_bf16x2(B.x), f16x2_to_bf16x2(A.y), f16x2_to_bf16x2(B.y));
                    sts64(sb + O_MF + tau * 3072 + 2048 + (c >> 1) * 512 + (c & 1) * 8 + l16, f16x2_to_bf16x2(A.z), f16x2_to_bf16x2(B.z));
                };
                const uint32_t ok0 = __all_sync(~0u, (v[0].w & v[1].w) == 0x5000u);
                convert(0);
                asm volatile("{\n.reg .pred p;\nsetp.ne.u32 p, %0, 0;\n@p bar.arrive 2, 384;\n}" :: "r"(ok0) : "memory");
                sched_fence<0>(h);
                uint32_t ok1;
                asm volatile("{\n.reg .pred p, q;\n.reg .b32 x;\nlop3.b32 x, %1, %2, %3, 0x80;\nand.b32 x, x, %4;\n"
                             "setp.eq.u32 p, x, 0x5000;\nvote.sync.all.pred q, p, 0xffffffff;\nselp.u32 %0, 1, 0, q;\n}"
                             : "=r"(ok1) : "r"(v[2].w), "r"(v[3].w), "r"(v[4].w), "r"(v[5].w));
                convert(1); convert(2);
                asm volatile("{\n.reg .pred p;\nsetp.ne.u32 p, %0, 0;\n@p bar.arrive 15, 384;\n}" :: "r"(ok1) : "memory");
                if (!(ok0 & ok1)) {
                    asm volatile("{\n.reg .pred p0, p1, p2, p3, p4, p5, q;\n.reg .u32 n, x;\nmov.u32 n, 0;\n"
                         "R_%=: setp.ne.u32 p0, %3, 0x5000;\nsetp.ne.u32 p1, %7, 0x5000;\nsetp.ne.u32 p2, %11, 0x5000;\n"
                         "setp.ne.u32 p3, %15, 0x5000;\nsetp.ne.u32 p4, %19, 0x5000;\nsetp.ne.u32 p5, %23, 0x5000;\n"
                         "@p0 ld.relaxed.gpu.global.v4.u32 {%0,%1,%2,%3}, [%25];\n@p1 ld.relaxed.gpu.global.v4.u32 {%4,%5,%6,%7}, [%25+512];\n"
                         "@p2 ld.relaxed.gpu.global.v4.u32 {%8,%9,%10,%11}, [%25+8192];\n@p3 ld.relaxed.gpu.global.v4.u32 {%12,%13,%14,%15}, [%25+8704];\n"
                         "@p4 ld.relaxed.gpu.global.v4.u32 {%16,%17,%18,%19}, [%25+16384];\n@p5 ld.relaxed.gpu.global.v4.u32 {%20,%21,%22,%23}, [%25+16896];\n"
                         "add.u32 %24, %24, 1;\nand.b32 x, %3, %7;\nand.b32 x, x, %11;\nand.b32 x, x, %15;\nand.b32 x, x, %19;\nand.b32 x, x, %23;\n"
                         "setp.eq.u32 q, x, 0x5000;\nvote.sync.all.pred q, q, 0xffffffff;\n@q bra.uni K_%=;\n"
                         "add.u32 n, n, 1;\nsetp.lt.u32 q, n, 2000000;\n@q bra.uni R_%=;\ntrap;\nK_%=:\n}"
                         : "+r"(v[0].x), "+r"(v[0].y), "+r"(v[0].z), "+r"(v[0].w), "+r"(v[1].x), "+r"(v[1].y), "+r"(v[1].z), "+r"(v[1].w),
                           "+r"(v[2].x), "+r"(v[2].y), "+r"(v[2].z), "+r"(v[2].w), "+r"(v[3].x), "+r"(v[3].y), "+r"(v[3].z), "+r"(v[3].w),
                           "+r"(v[4].x), "+r"(v[4].y), "+r"(v[4].z), "+r"(v[4].w), "+r"(v[5].x), "+r"(v[5].y), "+r"(v[5].z), "+r"(v[5].w), "+r"(nretry)
                         : "l"(pbase) : "memory");
                    if (!ok0) { convert(0); bar_arrive(2, 384); }
                    if (!ok1) { convert(1); convert(2); bar_arrive(15, 384); }
                }
                if (c == 0) STAMP(s, 12);
                if (c == 0) STAMPV(s, 14, nretry);
                mmax = absmax2(absmax2(absmax2(v[0].x, v[0].y), absmax2(v[0].z, v[1].x)), absmax2(absmax2(v[1].y, v[1].z), absmax2(v[2].x, v[2].y)));
                mmax = absmax2(mmax, absmax2(absmax2(absmax2(v[2].z, v[3].x), absmax2(v[3].y, v[3].z)), absmax2(absmax2(v[4].x, v[4].y), absmax2(v[4].z, v[5].x))));
                mmax = absmax2(mmax, absmax2(v[5].y, v[5].z)) & 0x7fff7fffu;
                { const float2 mf = __half22float2(*reinterpret_cast<__half2*>(&mmax)); mmax = max(__float_as_uint(mf.x), __float_as_uint(mf.y)); }
            }
            roff += 24576;
        }
        {
            bar_sync(7, 384);
            if (c == 0) flag_inc_if(l16c, &g_flag[F_QKV + (60 + (h >> 3)) * 8]);
        }
    }
    if (warp == 8) PSTAMP(13);
    cluster_sync();
}

constexpr int NST = 10;
constexpr int G_RING = 0, G_EX = NST * 16384, G_OUT = G_EX + 32768, G_CARRY = G_OUT + 32768, G_BAR = G_CARRY + 512, BG_SMEM = G_BAR + 256;
constexpr int GB_FULL = G_BAR, GB_EMPTY = G_BAR + 8 * NST, GB_W = G_BAR + 16 * NST;
static_assert(BG_SMEM <= 232448, "smem");

template <int ACC>
__device__ __forceinline__ void wgmma_n128_rs(float (&d)[64], uint32_t a0, uint32_t a1, uint32_t a2, uint32_t a3, uint64_t desc) {
    asm volatile("wgmma.mma_async.sync.aligned.m64n128k16.f32.bf16.bf16 "
        "{%0,%1,%2,%3,%4,%5,%6,%7,%8,%9,%10,%11,%12,%13,%14,%15,%16,%17,%18,%19,%20,%21,%22,%23,%24,%25,%26,%27,%28,%29,%30,%31,"
        "%32,%33,%34,%35,%36,%37,%38,%39,%40,%41,%42,%43,%44,%45,%46,%47,%48,%49,%50,%51,%52,%53,%54,%55,%56,%57,%58,%59,%60,%61,%62,%63}, "
        "{%64,%65,%66,%67}, %68, %69, 1, 1, 0;"
        : "+f"(d[0]), "+f"(d[1]), "+f"(d[2]), "+f"(d[3]), "+f"(d[4]), "+f"(d[5]), "+f"(d[6]), "+f"(d[7]),
          "+f"(d[8]), "+f"(d[9]), "+f"(d[10]), "+f"(d[11]), "+f"(d[12]), "+f"(d[13]), "+f"(d[14]), "+f"(d[15]),
          "+f"(d[16]), "+f"(d[17]), "+f"(d[18]), "+f"(d[19]), "+f"(d[20]), "+f"(d[21]), "+f"(d[22]), "+f"(d[23]),
          "+f"(d[24]), "+f"(d[25]), "+f"(d[26]), "+f"(d[27]), "+f"(d[28]), "+f"(d[29]), "+f"(d[30]), "+f"(d[31]),
          "+f"(d[32]), "+f"(d[33]), "+f"(d[34]), "+f"(d[35]), "+f"(d[36]), "+f"(d[37]), "+f"(d[38]), "+f"(d[39]),
          "+f"(d[40]), "+f"(d[41]), "+f"(d[42]), "+f"(d[43]), "+f"(d[44]), "+f"(d[45]), "+f"(d[46]), "+f"(d[47]),
          "+f"(d[48]), "+f"(d[49]), "+f"(d[50]), "+f"(d[51]), "+f"(d[52]), "+f"(d[53]), "+f"(d[54]), "+f"(d[55]),
          "+f"(d[56]), "+f"(d[57]), "+f"(d[58]), "+f"(d[59]), "+f"(d[60]), "+f"(d[61]), "+f"(d[62]), "+f"(d[63])
        : "r"(a0), "r"(a1), "r"(a2), "r"(a3), "l"(desc), "n"(ACC));
}
__device__ __forceinline__ void wait_flag(const unsigned* p, unsigned target) {
    asm volatile("{\n.reg .pred p;\n.reg .u32 n, v;\nmov.u32 n, 0;\n"
                 "W_%=: ld.acquire.gpu.global.u32 v, [%0];\nsub.u32 v, v, %1;\nsetp.ge.s32 p, v, 0;\n@p bra.uni D_%=;\nnanosleep.u32 100;\n"
                 "add.u32 n, n, 1;\nsetp.lt.u32 p, n, 4000000;\n@p bra.uni W_%=;\ntrap;\nD_%=:\n}" :: "l"(p), "r"(target) : "memory");
}
template <int NS, int STRIDE>
__device__ __forceinline__ void bg_mainloop(float (&d)[64], const uint32_t (&a)[144], uint32_t sb, int it, int lane) {
    int slot = it % NST, ph = (it / NST) & 1, prev = 0;
#pragma unroll
    for (int i = 0; i < NS; i++) {
        mbar_wait(sb + GB_FULL + 8 * slot, ph);
        const uint64_t desc = (uint64_t)(((sb + G_RING + slot * 16384) & 0x3FFFF) >> 4) | (1ull << 16) | (64ull << 32) | (1ull << 62);
        wg_fence();
#pragma unroll
        for (int k = 0; k < 4; k++) {
            const int u = 16 * i + 4 * k;
            if (i == 0 && k == 0) wgmma_n128_rs<0>(d, a[u], a[u + 1], a[u + 2], a[u + 3], desc);
            else wgmma_n128_rs<1>(d, a[u], a[u + 1], a[u + 2], a[u + 3], desc + 2 * k);
        }
        wg_commit();
        if (i > 0) {
            asm volatile("wgmma.wait_group.sync.aligned 1;" ::: "memory");
            mbar_arrive_if(lane, sb + GB_EMPTY + 8 * prev);
        }
        prev = slot;
        slot += STRIDE;
        if (slot >= NST) { slot -= NST; ph ^= 1; }
    }
    wg_wait0();
    mbar_arrive_if(lane, sb + GB_EMPTY + 8 * prev);
}
template <bool SKIP>
__device__ __forceinline__ void bg_epilogue(float (&d)[64], uint32_t sb, int wg, int w, int lane, const CUtensorMap* tm_out, int col0, int tok0,
                                            const __nv_bfloat16* xa, const __nv_bfloat16* Dk) {
    const int g = lane >> 2, t = lane & 3;
    const uint32_t ex = sb + G_EX + w * 4096 + lane * 16;
    float k[32];
    if (wg == 0) {
#pragma unroll
        for (int q = 0; q < 8; q++) sts128f(ex + q * 512, d[32 + 4 * q], d[32 + 4 * q + 1], d[32 + 4 * q + 2], d[32 + 4 * q + 3]);
#pragma unroll
        for (int i = 0; i < 32; i++) k[i] = d[i];
    } else {
#pragma unroll
        for (int q = 0; q < 8; q++) sts128f(ex + 16384 + q * 512, d[4 * q], d[4 * q + 1], d[4 * q + 2], d[4 * q + 3]);
#pragma unroll
        for (int i = 0; i < 32; i++) k[i] = d[32 + i];
    }
    uint32_t xv[16], dv = 0;
    if (SKIP) {
        const __nv_bfloat16* xp = xa + (size_t)(tok0 + 64 * wg + 2 * t) * DM + col0 + 16 * w + 2 * g;
#pragma unroll
        for (int i = 0; i < 16; i++) xv[i] = ldg_nc32(xp + (8 * (i >> 1) + (i & 1)) * DM);
        dv = ldg_nc32(Dk + col0 + 16 * w + 2 * g);
    }
    if (SKIP && w == 0) asm volatile("cp.async.bulk.wait_group.read 0;" ::: "memory");
    bar_sync(1, 256);
#pragma unroll
    for (int q = 0; q < 8; q++) {
        const float4 o = lds128f(ex + (wg ^ 1) * 16384 + q * 512);
        k[4 * q] += o.x; k[4 * q + 1] += o.y; k[4 * q + 2] += o.z; k[4 * q + 3] += o.w;
    }
    if (SKIP) bar_sync(1, 256); else bar_sync(13, 288);
    const uint32_t ob = sb + G_OUT + wg * 16384 + (w >> 1) * 8192 + (g & 1) * 8;
    const uint32_t ch = (w & 1) * 4 + (g >> 1);
#pragma unroll
    for (int i = 0; i < 16; i++) {
        float v0 = k[4 * (i >> 1) + (i & 1)], v1 = k[4 * (i >> 1) + 2 + (i & 1)];
        if (SKIP) {
            const uint32_t p = pack_bf16(__uint_as_float(xv[i] << 16) * __uint_as_float(dv << 16), __uint_as_float(xv[i] & 0xffff0000u) * __uint_as_float(dv & 0xffff0000u));
            v0 += __uint_as_float(p << 16); v1 += __uint_as_float(p & 0xffff0000u);
        }
        const uint32_t n7 = 2 * t + (i & 1);
        sts64(ob + (8 * (i >> 1) + n7) * 128 + ((ch ^ n7) << 4), __float_as_uint(v0), __float_as_uint(v1));
    }
    fence_async_smem();
    if (SKIP) {
        bar_sync(4 + wg, 128);
        if (w == 0)
            asm volatile("{\n.reg .pred p;\nelect.sync _|p, 0xffffffff;\n"
                "@p cp.async.bulk.tensor.2d.global.shared::cta.bulk_group [%0, {%2, %4}], [%1];\n"
                "@p cp.async.bulk.tensor.2d.global.shared::cta.bulk_group [%0, {%3, %4}], [%1+8192];\n@p cp.async.bulk.commit_group;\n}"
                :: "l"(tm_out), "r"(sb + G_OUT + wg * 16384), "r"(col0), "r"(col0 + 32), "r"(tok0 + 64 * wg) : "memory");
    } else {
        bar_arrive(12, 288);
    }
}
__device__ __forceinline__ void s5_channel(int p, const __nv_bfloat16* Lre, const __nv_bfloat16* Lim, const __nv_bfloat16* logdt, float2& lam, float2& coef) {
    const float dt = __bfloat162float(__float2bfloat16(expf(__bfloat162float(logdt[p]))));
    const float lr = __bfloat162float(Lre[p]), li = __bfloat162float(Lim[p]);
    const float e = expf(dt * lr);
    float sn, cs;
    sincosf(dt * li, &sn, &cs);
    lam = make_float2(e * cs, e * sn);
    const float den = lr * lr + li * li;
    coef = make_float2(((lam.x - 1.f) * lr + lam.y * li) / den, (lam.y * lr - (lam.x - 1.f) * li) / den);
}
__device__ __forceinline__ float2 cfma(float2 a, float2 b, float2 c) {
    return make_float2(fmaf(a.x, b.x, fmaf(-a.y, b.y, c.x)), fmaf(a.x, b.y, fmaf(a.y, b.x, c.y)));
}
__device__ __forceinline__ uint4 ldg128(const void* p) { uint4 v; asm volatile("ld.global.v4.u32 {%0,%1,%2,%3}, [%4];" : "=r"(v.x), "=r"(v.y), "=r"(v.z), "=r"(v.w) : "l"(p) : "memory"); return v; }
__device__ __forceinline__ uint2 ldg64(const void* p) { uint2 v; asm volatile("ld.global.v2.u32 {%0,%1}, [%2];" : "=r"(v.x), "=r"(v.y) : "l"(p) : "memory"); return v; }

__device__ __forceinline__ void bg_attention(uint32_t st0, uint32_t st1, int mt, int lane) {
    const int g = lane >> 2, t = lane & 3;
    float sc[5][4];
#pragma unroll
    for (int n = 0; n < 5; n++) sc[n][0] = sc[n][1] = sc[n][2] = sc[n][3] = 0.f;
    float sm2[4] = {0.f, 0.f, 0.f, 0.f};
#pragma unroll
    for (int i = 0; i < 8; i++) {
        const uint32_t st = (i >> 2 ? st1 : st0) + (i & 3) * 512 + lane * 16;
        const uint4 q = ldsm4(st + mt * 2048), km = ldsm4(st + 8192), k0 = ldsm4(st + 4096);
        mma16816(sc[0], q.x, q.y, q.z, q.w, km.x, km.y);
        mma16816(sm2, q.x, q.y, q.z, q.w, km.z, km.w);
        mma16816(sc[1], q.x, q.y, q.z, q.w, k0.x, k0.y);
        mma16816(sc[2], q.x, q.y, q.z, q.w, k0.z, k0.w);
        if (mt) {
            const uint4 k1 = ldsm4(st + 6144);
            mma16816(sc[3], q.x, q.y, q.z, q.w, k1.x, k1.y);
            mma16816(sc[4], q.x, q.y, q.z, q.w, k1.z, k1.w);
        }
    }
#pragma unroll
    for (int i = 0; i < 4; i++) sc[0][i] += sm2[i];
    const int q0 = 16 * mt + 8 + g - 2 * t;
#pragma unroll
    for (int n = 1; n < 5; n++) {
        if (8 * n > q0) sc[n][0] = -INFINITY;
        if (8 * n + 1 > q0) sc[n][1] = -INFINITY;
        if (8 * n > q0 + 8) sc[n][2] = -INFINITY;
        if (8 * n + 1 > q0 + 8) sc[n][3] = -INFINITY;
    }
    float ma = fmaxf(sc[0][0], sc[0][1]), mb = fmaxf(sc[0][2], sc[0][3]);
#pragma unroll
    for (int n = 1; n < 5; n++) { ma = fmaxf(ma, fmaxf(sc[n][0], sc[n][1])); mb = fmaxf(mb, fmaxf(sc[n][2], sc[n][3])); }
    ma = quad_max(ma) * SM_SCALE; mb = quad_max(mb) * SM_SCALE;
    uint32_t Pa[5], Pb[5];
#pragma unroll
    for (int n = 0; n < 5; n++) {
        Pa[n] = pack_bf16(ex2(fmaf(sc[n][0], SM_SCALE, -ma)), ex2(fmaf(sc[n][1], SM_SCALE, -ma)));
        Pb[n] = pack_bf16(ex2(fmaf(sc[n][2], SM_SCALE, -mb)), ex2(fmaf(sc[n][3], SM_SCALE, -mb)));
    }
    float sa[4], sbb[4];
    mma1688_z(sa, ONES, ONES, Pa[0]); mma1688_z(sbb, ONES, ONES, Pb[0]);
    mma16816(sa, ONES, ONES, ONES, ONES, Pa[1], Pa[2]); mma16816(sbb, ONES, ONES, ONES, ONES, Pb[1], Pb[2]);
    mma16816(sa, ONES, ONES, ONES, ONES, Pa[3], Pa[4]); mma16816(sbb, ONES, ONES, ONES, ONES, Pb[3], Pb[4]);
    const float ra0 = rcp_fast(sa[0]), ra1 = rcp_fast(sa[1]), rb0 = rcp_fast(sbb[0]), rb1 = rcp_fast(sbb[1]);
    const uint32_t row = lane & 7;
    const uint32_t so = mt * 2048 + (lane >> 4) * 1024 + row * 128;
#pragma unroll
    for (int i = 0; i < 8; i++) {
        const uint32_t st = i >> 2 ? st1 : st0;
        const int e4 = i & 3;
        const float2 vmf = lds64f(st + 14336 + e4 * 256 + lane * 8);
        const uint32_t vm0 = __float_as_uint(vmf.x), vm1 = __float_as_uint(vmf.y);
        const uint4 v0 = lds128(st + 10240 + e4 * 1024 + lane * 16);
        float oa[4], ob[4];
        mma1688_z(oa, vm0, vm1, Pa[0]); mma1688_z(ob, vm0, vm1, Pb[0]);
        mma16816(oa, v0.x, v0.y, v0.z, v0.w, Pa[1], Pa[2]);
        mma16816(ob, v0.x, v0.y, v0.z, v0.w, Pb[1], Pb[2]);
        if (mt) {
            const uint4 v1 = lds128(st + 10240 + e4 * 1024 + 512 + lane * 16);
            mma16816(oa, v1.x, v1.y, v1.z, v1.w, Pa[3], Pa[4]);
            mma16816(ob, v1.x, v1.y, v1.z, v1.w, Pb[3], Pb[4]);
        }
        stsm4t(st + so + (((2 * e4 + ((lane >> 3) & 1)) ^ row) << 4), pack_bf16(oa[0] * ra0, oa[1] * ra1), pack_bf16(oa[2] * ra0, oa[3] * ra1),
               pack_bf16(ob[0] * rb0, ob[1] * rb1), pack_bf16(ob[2] * rb0, ob[3] * rb1));
    }
}
__device__ __forceinline__ bool bg_att_turn(int na, int ng) { return na == ng || (na == ng + 1 && na <= BG_AHEAD); }

__global__ void __launch_bounds__(384, 1)
bg_kernel(const __grid_constant__ CUtensorMap tm_xa, const __grid_constant__ CUtensorMap tm_wo, const __grid_constant__ CUtensorMap tm_out,
          const __nv_bfloat16* __restrict__ xa, const __nv_bfloat16* __restrict__ Lre, const __nv_bfloat16* __restrict__ Lim,
          const __nv_bfloat16* __restrict__ Bre, const __nv_bfloat16* __restrict__ Bim, const __nv_bfloat16* __restrict__ Cre,
          const __nv_bfloat16* __restrict__ Cim, const __nv_bfloat16* __restrict__ logdt, const __nv_bfloat16* __restrict__ Dk) {
    extern __shared__ __align__(1024) uint8_t smem_raw[];
    const uint32_t sb = smem_u32(smem_raw);
    const int lane = threadIdx.x & 31;
    const int warp = __shfl_sync(~0u, threadIdx.x >> 5, 0);
    const int wg = warp >> 2, w = warp & 3, b = blockIdx.x;
    const int nt = b % 9, kq = b / 9;
    BSTAMP(0);
    if (threadIdx.x == 0) {
        if (sb & 1023u) __trap();
        for (int i = 0; i < NST; i++) { mbar_init(sb + GB_FULL + 8 * i, 1); mbar_init(sb + GB_EMPTY + 8 * i, 4); }
        mbar_init(sb + GB_W, 1);
        asm volatile("fence.mbarrier_init.release.cluster;" ::: "memory");
        mbar_expect(sb + GB_W, (b < 18 ? 64 : 128) * 1152);
        sts32(sb + G_BAR + 248, atomicAdd(&g_ticket_bg, 1u) / 36u + 1u);
    }
    __syncthreads();
    if (wg == 2) {
        asm volatile("setmaxnreg.dec.sync.aligned.u32 24;");
        if (w == 0) {
            int slot = 0, ph = 1;
            unsigned tlast = clk();
            auto pace = [&]() { if (BG_PACE) { spin_until(tlast, BG_PACE); tlast = clk(); } };
            auto next = [&]() { if (++slot == NST) { slot = 0; ph ^= 1; } };
            bar_sync(6, 288);
            if (b < 18) {
#pragma unroll 1
                for (int i = 0; i < 144; i++) {
                    const int blk = i / 9, kb = i - 9 * blk, it = (blk >> 1) * 18 + (blk & 1) + 2 * kb;
                    slot = it % NST;
                    mbar_wait(sb + GB_EMPTY + 8 * slot, ((it / NST) & 1) ^ 1);
                    pace();
                    asm volatile("{\n.reg .pred p;\nelect.sync _|p, 0xffffffff;\n@p mbarrier.arrive.expect_tx.shared::cta.b64 _, [%2], 16384;\n"
                        "@p cp.async.bulk.tensor.5d.shared::cluster.global.mbarrier::complete_tx::bytes [%0], [%1, {%3, %4, %4, %4, %5}], [%2];\n}"
                        :: "r"(sb + G_RING + slot * 16384), "l"(&tm_xa), "r"(sb + GB_FULL + 8 * slot), "r"(kb * 64), "r"(0), "r"(blk) : "memory");
                }
                slot = 144 % NST; ph = ((144 / NST) & 1) ^ 1;
            }
            const unsigned ep = lds32(sb + G_BAR + 248);
            auto slabs = [&](const char* src, int ns) {
                asm volatile("fence.proxy.async.global;" ::: "memory");
#pragma unroll 1
                for (int i = 0; i < ns; i++) {
                    mbar_wait(sb + GB_EMPTY + 8 * slot, ph);
                    pace();
                    asm volatile("{\n.reg .pred p;\nelect.sync _|p, 0xffffffff;\n@p mbarrier.arrive.expect_tx.shared::cta.b64 _, [%2], 16384;\n"
                        "@p cp.async.bulk.shared::cluster.global.mbarrier::complete_tx::bytes [%0], [%1], 16384, [%2];\n}"
                        :: "r"(sb + G_RING + slot * 16384), "l"(src + (size_t)((i & 1) * (ns >> 1) + (i >> 1)) * (SEQ * 128)), "r"(sb + GB_FULL + 8 * slot) : "memory");
                    next();
                }
            };
            if (b >= 18) {
#pragma unroll 1
                for (int blk = kq - 2; blk < 16; blk += 2) {
                    wait_flag(&g_flag[F_H + blk * 8], 18 * ep);
                    slabs(reinterpret_cast<const char*>(g_h) + blk * 16384, 18);
                }
            }
            bar_sync(6, 288);
#pragma unroll 1
            for (int na = 0, ng = 0; ng < 16;) {
                if (bg_att_turn(na, ng)) {
                    if (nt < 8) {
                        wait_flag(&g_flag[F_QKV + (na * 4 + kq) * 8], 24 * ep);
                        asm volatile("fence.proxy.async.global;" ::: "memory");
#pragma unroll 1
                        for (int i = 0; i < 8; i++) {
                            const int pr = nt * 4 + 2 * (i & 1) + (i >> 2), hf = (i >> 1) & 1;
                            const char* rec = reinterpret_cast<const char*>(g_qkv) + (size_t)((4 * na + (pr >> 3)) * NH + 8 * kq + (pr & 7)) * REC;
                            mbar_wait(sb + GB_EMPTY + 8 * slot, ph);
                    pace();
                            asm volatile("{\n.reg .pred p;\nelect.sync _|p, 0xffffffff;\n@p mbarrier.arrive.expect_tx.shared::cta.b64 _, [%4], 15360;\n"
                                "@p cp.async.bulk.shared::cluster.global.mbarrier::complete_tx::bytes [%0], [%1], 10240, [%4];\n"
                                "@p cp.async.bulk.shared::cluster.global.mbarrier::complete_tx::bytes [%0+10240], [%2], 4096, [%4];\n"
                                "@p cp.async.bulk.shared::cluster.global.mbarrier::complete_tx::bytes [%0+14336], [%3], 1024, [%4];\n}"
                                :: "r"(sb + G_RING + slot * 16384), "l"(rec + hf * 10240), "l"(rec + 20480 + hf * 4096), "l"(rec + 28672 + hf * 1024),
                                   "r"(sb + GB_FULL + 8 * slot) : "memory");
                            next();
                        }
                    }
                    na++;
                } else {
                    wait_flag(&g_flag[F_OX + (ng * 4 + kq) * 8], 8 * ep);
                    slabs(reinterpret_cast<const char*>(g_ox) + (size_t)kq * 16 * SEQ * 128 + ng * 16384, 16);
                    ng++;
                }
            }
        } else if (w == 1) {
            if (b < 18) {
#pragma unroll 1
                for (int blk = 0; blk < 16; blk++) {
                    bar_sync(8 + (blk & 1), 160);
                    asm volatile("{\n.reg .pred p;\nelect.sync _|p, 0xffffffff;\n@p cp.async.bulk.global.shared::cta.bulk_group [%0], [%1], 16384;\n"
                        "@p cp.async.bulk.commit_group;\ncp.async.bulk.wait_group 0;\nfence.proxy.async.global;\n}"
                        :: "l"(reinterpret_cast<char*>(g_h) + ((size_t)b * SEQ + blk * 128) * 128), "r"(sb + G_OUT + (blk & 1) * 16384) : "memory");
                    bar_arrive(10 + (blk & 1), 160);
                    flag_inc_if(lane, &g_flag[F_H + blk * 8]);
                }
            }
            if (nt < 8) {
                int it = 144;
#pragma unroll 1
                for (int na = 0, ng = 0; ng < 16;) {
                    if (bg_att_turn(na, ng)) {
                        bar_sync(7, 288);
                        if (lane < 8) {
                            const int pr = nt * 4 + 2 * (lane & 1) + (lane >> 2), hf = (lane >> 1) & 1;
                            asm volatile("cp.async.bulk.global.shared::cta.bulk_group [%0], [%1], 4096;\ncp.async.bulk.commit_group;\ncp.async.bulk.wait_group.read 0;\n"
                                "mbarrier.arrive.shared::cta.b64 _, [%2], 4;\ncp.async.bulk.wait_group 0;\nfence.proxy.async.global;"
                                :: "l"(reinterpret_cast<char*>(g_ox) + ((size_t)((8 * kq + (pr & 7)) * 2 + hf) * SEQ + (4 * na + (pr >> 3)) * 32) * 128),
                                   "r"(sb + G_RING + ((it + lane) % NST) * 16384), "r"(sb + GB_EMPTY + 8 * ((it + lane) % NST)) : "memory");
                        }
                        __syncwarp();
                        flag_inc_if(lane, &g_flag[F_OX + (na * 4 + kq) * 8]);
                        it += 8; na++;
                    } else { it += 16; ng++; }
                }
            }
        } else if (w == 2) {
            const unsigned ep = lds32(sb + G_BAR + 248);
#pragma unroll 1
            for (int blk = 0; blk < 16; blk++) {
                bar_arrive(13, 288);
                bar_sync(12, 288);
                if (kq) { wait_flag(&g_flag[F_OUT + (blk * 9 + nt) * 8], ep); asm volatile("fence.proxy.async.global;" ::: "memory"); }
                unsigned t0 = clk();
                if (blk < 15) spin_until(t0, b * (RED_GAP / 36));
#pragma unroll 1
                for (int i = 0; i < 4; i++) {
                    const uint32_t src = sb + G_OUT + i * 8192;
                    const int c0 = DM + 64 * nt + (i & 1) * 32, c1 = blk * 128 + (i >> 1) * 64;
                    if (kq) {
                        asm volatile("{\n.reg .pred p;\nelect.sync _|p, 0xffffffff;\n@p cp.reduce.async.bulk.tensor.2d.global.shared::cta.add.bulk_group [%0, {%2, %3}], [%1];\n}"
                            :: "l"(&tm_out), "r"(src), "r"(c0), "r"(c1) : "memory");
                        t0 = clk();
                        if (blk < 15 && i < 3) spin_until(t0, RED_GAP);
                    } else {
                        asm volatile("{\n.reg .pred p;\nelect.sync _|p, 0xffffffff;\n@p cp.async.bulk.tensor.2d.global.shared::cta.bulk_group [%0, {%2, %3}], [%1];\n}"
                            :: "l"(&tm_out), "r"(src), "r"(c0), "r"(c1) : "memory");
                    }
                }
                asm volatile("cp.async.bulk.commit_group;\ncp.async.bulk.wait_group 0;\nfence.proxy.async.global;" ::: "memory");
                __syncwarp();
                if (!kq) flag_inc_if(lane, &g_flag[F_OUT + (blk * 9 + nt) * 8]);
            }
        }
    } else {
        asm volatile("setmaxnreg.inc.sync.aligned.u32 240;");
        const int g = lane >> 2, t = lane & 3, tid = threadIdx.x;
        uint32_t a[144];
        float d[64];
        if (b < 18) {
            if (tid < 64)
                asm volatile("cp.async.bulk.shared::cluster.global.mbarrier::complete_tx::bytes [%0], [%1], 1152, [%2];"
                    :: "r"(sb + tid * 1168), "l"((tid < 32 ? Bre : Bim) + (size_t)(32 * b + (tid & 31)) * DM), "r"(sb + GB_W) : "memory");
            float2 lam, coef;
            s5_channel(32 * b + 8 * w + g, Lre, Lim, logdt, lam, coef);
            float2 l32 = lam;
#pragma unroll
            for (int i = 0; i < 5; i++) l32 = make_float2(l32.x * l32.x - l32.y * l32.y, 2.f * l32.x * l32.y);
            __syncwarp();
            mbar_wait(sb + GB_W, 0);
            const uint32_t ap = sb + (((lane >> 3) & 1) * 32 + 8 * w + (lane & 7)) * 1168 + (lane >> 4) * 16;
#pragma unroll
            for (int ks = 0; ks < 36; ks++) { const uint4 v = ldsm4(ap + ks * 32); a[4 * ks] = v.x; a[4 * ks + 1] = v.y; a[4 * ks + 2] = v.z; a[4 * ks + 3] = v.w; }
            bar_sync(1, 256);
            bar_arrive(6, 288);
            BSTAMP(1);
#pragma unroll 1
            for (int blk = wg; blk < 16; blk += 2) {
                bg_mainloop<9, 2>(d, a, sb, (blk >> 1) * 18 + wg, lane);
                float2 e = make_float2(0.f, 0.f);
#pragma unroll
                for (int i = 0; i < 32; i++) e = cfma(lam, e, make_float2(d[4 * (i >> 1) + (i & 1)], d[4 * (i >> 1) + 2 + (i & 1)]));
                float2 cin = make_float2(0.f, 0.f);
                if (blk > 0) { bar_sync(2 + (wg ^ 1), 256); cin = lds64f(sb + G_CARRY + (wg ^ 1) * 256 + (8 * w + g) * 8); }
                float2 mine = cin;
#pragma unroll
                for (int q = 0; q < 4; q++) {
                    const float2 eq = make_float2(__shfl_sync(~0u, e.x, (lane & 28) + q), __shfl_sync(~0u, e.y, (lane & 28) + q));
                    cin = cfma(l32, cin, eq);
                    if (t == q + 1) mine = cin;
                }
                if (blk < 15) {
                    if (t == 0) sts64(sb + G_CARRY + wg * 256 + (8 * w + g) * 8, __float_as_uint(cin.x), __float_as_uint(cin.y));
                    bar_arrive(2 + wg, 256);
                }
                const uint32_t hs = sb + G_OUT + wg * 16384 + t * 4096 + (g & 3) * 4;
                const uint32_t ch = 2 * w + (g >> 2);
                if (blk >= 2) bar_sync(10 + wg, 160);
#pragma unroll
                for (int i = 0; i < 32; i++) {
                    mine = cfma(lam, mine, make_float2(d[4 * (i >> 1) + (i & 1)], d[4 * (i >> 1) + 2 + (i & 1)]));
                    sts32(hs + i * 128 + ((ch ^ (i & 7)) << 4), pack_bf16(mine.x, mine.y));
                }
                fence_async_smem();
                bar_arrive(8 + wg, 160);
            }
            bar_sync(10 + wg, 160);
        } else {
            if (tid < 128)
                asm volatile("cp.async.bulk.shared::cluster.global.mbarrier::complete_tx::bytes [%0], [%1], 1152, [%2];"
                    :: "r"(sb + tid * 1168), "l"((tid < 64 ? Cre : Cim) + (size_t)(64 * nt + (tid & 63)) * DM), "r"(sb + GB_W) : "memory");
            for (int p = tid; p < DM; p += 256) {
                float2 lam, coef;
                s5_channel(p, Lre, Lim, logdt, lam, coef);
                sts64(sb + G_EX + p * 8, __float_as_uint(2.f * coef.x), __float_as_uint(2.f * coef.y));
            }
            bar_sync(1, 256);
            mbar_wait(sb + GB_W, 0);
            const uint32_t cp = sb + (16 * w + 2 * g) * 1168 + (288 * wg + t) * 2;
#pragma unroll
            for (int u = 0; u < 72; u++) {
                const float2 c2 = lds64f(sb + G_EX + (288 * wg + 4 * u + t) * 8);
#pragma unroll
                for (int f = 0; f < 2; f++) {
                    unsigned short r16, i16;
                    asm volatile("ld.shared.u16 %0, [%1];" : "=h"(r16) : "r"(cp + f * 1168 + u * 8) : "memory");
                    asm volatile("ld.shared.u16 %0, [%1];" : "=h"(i16) : "r"(cp + (64 + f) * 1168 + u * 8) : "memory");
                    const float cr = __uint_as_float((uint32_t)r16 << 16), ci = __uint_as_float((uint32_t)i16 << 16);
                    a[2 * u + f] = pack_bf16(cr * c2.x - ci * c2.y, -(cr * c2.y + ci * c2.x));
                }
            }
            bar_sync(1, 256);
            bar_arrive(6, 288);
            BSTAMP(1);
#pragma unroll 1
            for (int j = 0; j < 8; j++) {
                bg_mainloop<9, 2>(d, a, sb, j * 18 + wg, lane);
                bg_epilogue<true>(d, sb, wg, w, lane, &tm_out, 64 * nt, (2 * j + kq - 2) * 128, xa, Dk);
            }
        }
        if (w == 0) asm volatile("cp.async.bulk.wait_group 0;" ::: "memory");
        bar_sync(1, 256);
        BSTAMP(2);
        if (warp == 0)
            asm volatile("{\n.reg .pred p;\nelect.sync _|p, 0xffffffff;\n@p mbarrier.arrive.expect_tx.shared::cta.b64 _, [%2], 131072;\n"
                "@p cp.async.bulk.tensor.2d.shared::cluster.global.mbarrier::complete_tx::bytes [%0], [%1, {%3, %4}], [%2];\n"
                "@p cp.async.bulk.tensor.2d.shared::cluster.global.mbarrier::complete_tx::bytes [%0+32768], [%1, {%3, %5}], [%2];\n"
                "@p cp.async.bulk.tensor.2d.shared::cluster.global.mbarrier::complete_tx::bytes [%0+65536], [%1, {%3, %6}], [%2];\n"
                "@p cp.async.bulk.tensor.2d.shared::cluster.global.mbarrier::complete_tx::bytes [%0+98304], [%1, {%3, %7}], [%2];\n}"
                :: "r"(sb), "l"(&tm_wo), "r"(sb + GB_W), "r"(64 * nt), "r"(1024 * kq), "r"(1024 * kq + 256), "r"(1024 * kq + 512), "r"(1024 * kq + 768) : "memory");
        mbar_wait(sb + GB_W, 1);
        {
            const uint32_t base = sb + wg * 65536 + 4 * t * 128 + (g & 3) * 4, ch = 2 * w + (g >> 2), r7 = (4 * t) & 7;
#pragma unroll
            for (int ks = 0; ks < 32; ks++) {
                const uint32_t w0 = lds32(base + ks * 2048 + ((ch ^ r7) << 4)), w1 = lds32(base + ks * 2048 + 256 + ((ch ^ (r7 + 2)) << 4));
                const uint32_t w2 = lds32(base + ks * 2048 + 128 + ((ch ^ (r7 + 1)) << 4)), w3 = lds32(base + ks * 2048 + 384 + ((ch ^ (r7 + 3)) << 4));
                a[4 * ks] = __byte_perm(w0, w1, 0x5410); a[4 * ks + 1] = __byte_perm(w0, w1, 0x7632);
                a[4 * ks + 2] = __byte_perm(w2, w3, 0x5410); a[4 * ks + 3] = __byte_perm(w2, w3, 0x7632);
            }
        }
        bar_sync(1, 256);
        bar_arrive(6, 288);
        BSTAMP(3);
#pragma unroll 1
        for (int na = 0, ng = 0, it = 144; ng < 16;) {
            if (bg_att_turn(na, ng)) {
                if (nt < 8) {
                    const int i0 = it + wg + 4 * (w >> 1), i1 = i0 + 2;
                    mbar_wait(sb + GB_FULL + 8 * (i0 % NST), (i0 / NST) & 1);
                    mbar_wait(sb + GB_FULL + 8 * (i1 % NST), (i1 / NST) & 1);
                    BSTAMP(8 + na * 4);
                    bg_attention(sb + G_RING + (i0 % NST) * 16384, sb + G_RING + (i1 % NST) * 16384, w & 1, lane);
                    fence_async_smem();
                    bar_arrive(7, 288);
                    bar_sync(1, 256);
                    BSTAMP(9 + na * 4);
                    it += 8;
                }
                na++;
            } else {
                bg_mainloop<8, 2>(d, a, sb, it + wg, lane);
                BSTAMP(10 + ng * 4);
                bg_epilogue<false>(d, sb, wg, w, lane, &tm_out, DM + 64 * nt, ng * 128, xa, Dk);
                BSTAMP(11 + ng * 4);
                it += 16; ng++;
            }
        }
    }
    asm volatile("griddepcontrol.wait;" ::: "memory");
}

typedef CUresult (*EncodeFn)(CUtensorMap*, CUtensorMapDataType, cuuint32_t, void*, const cuuint64_t*, const cuuint64_t*, const cuuint32_t*, const cuuint32_t*,
                             CUtensorMapInterleave, CUtensorMapSwizzle, CUtensorMapL2promotion, CUtensorMapFloatOOBfill);
}

extern "C" void kernel_launch(void* const* d_in, const int* in_sizes, int n_in, void* d_out, int out_size) {
    typedef const __nv_bfloat16* bp;
    bp Ax = (bp)d_in[0], Lre = (bp)d_in[1], Lim = (bp)d_in[2], Bre = (bp)d_in[3], Bim = (bp)d_in[4], Cre = (bp)d_in[5], Cim = (bp)d_in[6],
       logdt = (bp)d_in[7], Dk = (bp)d_in[8], Bx = (bp)d_in[9], mem0 = (bp)d_in[10], Wq = (bp)d_in[11], Wk = (bp)d_in[12], Wv = (bp)d_in[13], Wo = (bp)d_in[14];
    float* out = (float*)d_out;
    static EncodeFn enc = nullptr;
    if (!enc) {
        void* fn = nullptr; cudaDriverEntryPointQueryResult qr;
        cudaGetDriverEntryPoint("cuTensorMapEncodeTiled", &fn, cudaEnableDefault, &qr);
        enc = (EncodeFn)fn;
        cudaFuncSetAttribute(chain_kernel, cudaFuncAttributeMaxDynamicSharedMemorySize, CHAIN_SMEM);
        cudaFuncSetAttribute(bg_kernel, cudaFuncAttributeMaxDynamicSharedMemorySize, BG_SMEM);
    }
    const cuuint32_t es[5] = {1, 1, 1, 1, 1};
    auto map2d = [&](CUtensorMap* tm, CUtensorMapDataType dt, const void* p, cuuint64_t d0, cuuint64_t d1, cuuint64_t stride, cuuint32_t b0, cuuint32_t b1) {
        cuuint64_t gd[2] = {d0, d1}, gs[1] = {stride}; cuuint32_t bd[2] = {b0, b1};
        enc(tm, dt, 2, (void*)p, gd, gs, bd, es, CU_TENSOR_MAP_INTERLEAVE_NONE, CU_TENSOR_MAP_SWIZZLE_128B, CU_TENSOR_MAP_L2_PROMOTION_L2_128B,
            CU_TENSOR_MAP_FLOAT_OOB_FILL_NONE);
    };
    CUtensorMap tm_x, tm_q, tm_k, tm_v, tm_xa, tm_wo, tm_out;
    map2d(&tm_x, CU_TENSOR_MAP_DATA_TYPE_BFLOAT16, Bx, DM, SEQ, DM * 2, 64, 32);
    map2d(&tm_q, CU_TENSOR_MAP_DATA_TYPE_BFLOAT16, Wq, HD, DM, HD * 2, 64, 192);
    map2d(&tm_k, CU_TENSOR_MAP_DATA_TYPE_BFLOAT16, Wk, HD, DM, HD * 2, 64, 192);
    map2d(&tm_v, CU_TENSOR_MAP_DATA_TYPE_BFLOAT16, Wv, HD, DM, HD * 2, 64, 192);
    map2d(&tm_wo, CU_TENSOR_MAP_DATA_TYPE_BFLOAT16, Wo, DM, HD, DM * 2, 64, 256);
    map2d(&tm_out, CU_TENSOR_MAP_DATA_TYPE_FLOAT32, out, 2 * DM, SEQ, 2 * DM * 4, 32, 64);
    {
        cuuint64_t gd[5] = {DM, 2, 4, 16, 16}, gs[4] = {DM * 2, 32 * DM * 2, 2 * DM * 2, 128 * DM * 2}; cuuint32_t bd[5] = {64, 2, 4, 16, 1};
        enc(&tm_xa, CU_TENSOR_MAP_DATA_TYPE_BFLOAT16, 5, (void*)Ax, gd, gs, bd, es, CU_TENSOR_MAP_INTERLEAVE_NONE, CU_TENSOR_MAP_SWIZZLE_128B,
            CU_TENSOR_MAP_L2_PROMOTION_L2_128B, CU_TENSOR_MAP_FLOAT_OOB_FILL_NONE);
    }
    cudaStream_t st = cudaStreamPerThread;
    chain_kernel<<<96, 384, CHAIN_SMEM, st>>>(tm_x, tm_q, tm_k, tm_v, Bx, mem0, Wo);
    cudaLaunchConfig_t cfg = {};
    cfg.gridDim = dim3(36); cfg.blockDim = dim3(384); cfg.dynamicSmemBytes = BG_SMEM; cfg.stream = st;
    cudaLaunchAttribute at[1];
    at[0].id = cudaLaunchAttributeProgrammaticStreamSerialization; at[0].val.programmaticStreamSerializationAllowed = 1;
    cfg.attrs = at; cfg.numAttrs = 1;
    cudaLaunchKernelEx(&cfg, bg_kernel, tm_xa, tm_wo, tm_out, Ax, Lre, Lim, Bre, Bim, Cre, Cim, logdt, Dk);
}
```

```cpp
#include <cuda_runtime.h>
#include <cuda.h>
#include <cuda_bf16.h>
#include <cuda_fp16.h>
#include <stdint.h>

#define D_WAIT 720

#define BG_PACE 0
#define RED_GAP 720
#define ACC_PF 1
#define QDEP 0
#define BG_AHEAD 5

namespace {

constexpr int DM = 576, NH = 32, SEQ = 2048, NSEG = 64, HD = 4096;

__device__ uint4 g_acc_raw[64 * 96 * 16 + 131072];
__device__ uint4 g_ox[NH * 2 * SEQ * 8];
constexpr int REC = 30720;
__device__ uint4 g_qkv[NSEG * NH * (REC / 16)];
__device__ uint4 g_h[18 * SEQ * 8];
constexpr int NFLAG = 4096, F_QKV = 0, F_OX = 512, F_H = 1024, F_OUT = 2048;
__device__ unsigned g_flag[NFLAG];
__device__ unsigned g_ticket, g_ticket_bg;
__device__ unsigned long long g_norm[96];
#define BSTAMP(i) do {} while (0)

__device__ __forceinline__ uint32_t smem_u32(const void* p) { return (uint32_t)__cvta_generic_to_shared(p); }
__device__ __forceinline__ uint32_t mapa(uint32_t a, uint32_t r) { uint32_t o; asm("mapa.shared::cluster.u32 %0, %1, %2;" : "=r"(o) : "r"(a), "r"(r)); return o; }
__device__ __forceinline__ uint32_t mapa_v(uint32_t a, uint32_t r) { uint32_t o; asm volatile("mapa.shared::cluster.u32 %0, %1, %2;" : "=r"(o) : "r"(a), "r"(r)); return o; }
__device__ __forceinline__ unsigned clk() { unsigned long long c; asm volatile("mov.u64 %0, %%clock64;" : "=l"(c) :: "memory"); return (unsigned)c; }
__device__ __forceinline__ void mbar_init(uint32_t bar, uint32_t cnt) { asm volatile("mbarrier.init.shared::cta.b64 [%0], %1;" :: "r"(bar), "r"(cnt) : "memory"); }
__device__ __forceinline__ void mbar_expect(uint32_t bar, uint32_t bytes) { asm volatile("mbarrier.arrive.expect_tx.shared::cta.b64 _, [%0], %1;" :: "r"(bar), "r"(bytes) : "memory"); }
__device__ __forceinline__ void mbar_wait(uint32_t bar, uint32_t parity) {
    asm volatile("{\n.reg .pred p;\n.reg .u32 n;\nmov.u32 n, 0;\n"
                 "W_%=: mbarrier.try_wait.parity.shared::cta.b64 p, [%0], %1;\n@p bra.uni D_%=;\n"
                 "add.u32 n, n, 1;\nsetp.lt.u32 p, n, 4000000;\n@p bra.uni W_%=;\ntrap;\nD_%=:\n}" :: "r"(bar), "r"(parity) : "memory");
}
__device__ __forceinline__ void mbar_expect_if(uint32_t z, uint32_t bar, uint32_t bytes) {
    asm volatile("{\n.reg .pred p;\nsetp.eq.u32 p, %2, 0;\n@p mbarrier.arrive.expect_tx.shared::cta.b64 _, [%0], %1;\n}" :: "r"(bar), "r"(bytes), "r"(z) : "memory");
}
__device__ __forceinline__ void mbar_arrive_if(uint32_t z, uint32_t bar) {
    asm volatile("{\n.reg .pred p;\nsetp.eq.u32 p, %1, 0;\n@p mbarrier.arrive.shared::cta.b64 _, [%0];\n}" :: "r"(bar), "r"(z) : "memory");
}
__device__ __forceinline__ void sts32_if(uint32_t z, uint32_t a, uint32_t x) {
    asm volatile("{\n.reg .pred p;\nsetp.eq.u32 p, %2, 0;\n@p st.shared.u32 [%0], %1;\n}" :: "r"(a), "r"(x), "r"(z) : "memory");
}
template <int K> __device__ __forceinline__ void sched_fence(int v) {
    asm volatile("{\n.reg .pred p;\nsetp.ne.s32 p, %0, %1;\n@p bra.uni F_%=;\ntrap;\nF_%=:\n}" :: "r"(v), "n"(1000 + K) : "memory");
}
__device__ __forceinline__ void spin_until(unsigned t0, unsigned d) {
    asm volatile("{\n.reg .pred p;\n.reg .u64 c;\n.reg .u32 lo;\n"
                 "S_%=: mov.u64 c, %%clock64;\ncvt.u32.u64 lo, c;\nsub.u32 lo, lo, %0;\nsetp.lt.u32 p, lo, %1;\n@p bra.uni S_%=;\n}" :: "r"(t0), "r"(d) : "memory");
}
__device__ __forceinline__ void bar_sync(int id, int n) { asm volatile("bar.sync %0, %1;" :: "r"(id), "r"(n) : "memory"); }
__device__ __forceinline__ void bar_sync_sel(int sel, int id) {
    asm volatile("{\n.reg .pred p;\nsetp.eq.u32 p, %0, 0;\n@p bar.sync %1, %3;\n@!p bar.sync %2, %3;\n}" :: "r"(sel), "r"(id), "r"(id + 1), "n"(192) : "memory");
}
__device__ __forceinline__ void bar_arrive(int id, int n) { asm volatile("bar.arrive %0, %1;" :: "r"(id), "r"(n) : "memory"); }
__device__ __forceinline__ void fence_async_smem() { asm volatile("fence.proxy.async.shared::cta;" ::: "memory"); }
__device__ __forceinline__ uint32_t pack_bf16(float lo, float hi) { uint32_t r; asm("cvt.rn.bf16x2.f32 %0, %1, %2;" : "=r"(r) : "f"(hi), "f"(lo)); return r; }
__device__ __forceinline__ uint32_t pack_f16(float lo, float hi) { uint32_t r; asm("cvt.rn.f16x2.f32 %0, %1, %2;" : "=r"(r) : "f"(hi), "f"(lo)); return r; }
__device__ __forceinline__ uint32_t f16x2_to_bf16x2(uint32_t v) { float2 f = __half22float2(*reinterpret_cast<__half2*>(&v)); return pack_bf16(f.x, f.y); }
__device__ __forceinline__ uint32_t hmul2(uint32_t a, uint32_t b) { uint32_t r; asm("mul.rn.f16x2 %0, %1, %2;" : "=r"(r) : "r"(a), "r"(b)); return r; }
__device__ __forceinline__ float ex2(float x) { float y; asm("ex2.approx.ftz.f32 %0, %1;" : "=f"(y) : "f"(x)); return y; }
__device__ __forceinline__ float ex2v(float x) { float y; asm volatile("ex2.approx.ftz.f32 %0, %1;" : "=f"(y) : "f"(x)); return y; }
__device__ __forceinline__ uint32_t absmax2(uint32_t a, uint32_t b) {
    uint32_t r; asm("max.xorsign.abs.bf16x2 %0, %1, %2;" : "=r"(r) : "r"(a), "r"(b)); return r;
}
__device__ __forceinline__ uint32_t shl_v(uint32_t a, int n) { return a << n; }
__device__ __forceinline__ uint32_t max3u(uint32_t a, uint32_t b, uint32_t c) { return max(max(a, b), c); }
__device__ __forceinline__ uint4 lds128(uint32_t a) { uint4 v; asm volatile("ld.shared.v4.u32 {%0,%1,%2,%3}, [%4];" : "=r"(v.x), "=r"(v.y), "=r"(v.z), "=r"(v.w) : "r"(a) : "memory"); return v; }
__device__ __forceinline__ uint4 lds128v(uint32_t a) { uint4 v; asm volatile("ld.volatile.shared.v4.u32 {%0,%1,%2,%3}, [%4];" : "=r"(v.x), "=r"(v.y), "=r"(v.z), "=r"(v.w) : "r"(a) : "memory"); return v; }
__device__ __forceinline__ float4 lds128f(uint32_t a) { float4 v; asm volatile("ld.shared.v4.f32 {%0,%1,%2,%3}, [%4];" : "=f"(v.x), "=f"(v.y), "=f"(v.z), "=f"(v.w) : "r"(a) : "memory"); return v; }
__device__ __forceinline__ float2 lds64f(uint32_t a) { float2 v; asm volatile("ld.shared.v2.f32 {%0,%1}, [%2];" : "=f"(v.x), "=f"(v.y) : "r"(a) : "memory"); return v; }
__device__ __forceinline__ uint4 lds64x2(uint32_t a) { uint4 v; asm volatile("ld.shared.v2.u32 {%0,%1}, [%4];\nld.shared.v2.u32 {%2,%3}, [%4+256];" : "=r"(v.x), "=r"(v.y), "=r"(v.z), "=r"(v.w) : "r"(a) : "memory"); return v; }
__device__ __forceinline__ uint32_t lds32(uint32_t a) { uint32_t v; asm volatile("ld.shared.u32 %0, [%1];" : "=r"(v) : "r"(a) : "memory"); return v; }
__device__ __forceinline__ void sts128(uint32_t a, uint32_t x, uint32_t y, uint32_t z, uint32_t w) { asm volatile("st.shared.v4.u32 [%0], {%1,%2,%3,%4};" :: "r"(a), "r"(x), "r"(y), "r"(z), "r"(w) : "memory"); }
__device__ __forceinline__ void sts128f(uint32_t a, float x, float y, float z, float w) { asm volatile("st.shared.v4.f32 [%0], {%1,%2,%3,%4};" :: "r"(a), "f"(x), "f"(y), "f"(z), "f"(w) : "memory"); }
__device__ __forceinline__ void sts64(uint32_t a, uint32_t x, uint32_t y) { asm volatile("st.shared.v2.u32 [%0], {%1,%2};" :: "r"(a), "r"(x), "r"(y) : "memory"); }
__device__ __forceinline__ void sts32(uint32_t a, uint32_t x) { asm volatile("st.shared.u32 [%0], %1;" :: "r"(a), "r"(x) : "memory"); }
__device__ __forceinline__ uint4 ldsm4(uint32_t a) { uint4 v; asm volatile("ldmatrix.sync.aligned.m8n8.x4.shared.b16 {%0,%1,%2,%3}, [%4];" : "=r"(v.x), "=r"(v.y), "=r"(v.z), "=r"(v.w) : "r"(a) : "memory"); return v; }
__device__ __forceinline__ void stsm2t(uint32_t a, uint32_t x, uint32_t y) { asm volatile("stmatrix.sync.aligned.m8n8.x2.trans.shared.b16 [%0], {%1,%2};" :: "r"(a), "r"(x), "r"(y) : "memory"); }
__device__ __forceinline__ void stsm4t(uint32_t a, uint32_t x, uint32_t y, uint32_t z, uint32_t w) { asm volatile("stmatrix.sync.aligned.m8n8.x4.trans.shared.b16 [%0], {%1,%2,%3,%4};" :: "r"(a), "r"(x), "r"(y), "r"(z), "r"(w) : "memory"); }
__device__ __forceinline__ void st_async64(uint32_t a, uint32_t x, uint32_t y, uint32_t bar) { asm volatile("st.async.shared::cluster.mbarrier::complete_tx::bytes.v2.b32 [%0], {%1,%2}, [%3];" :: "r"(a), "r"(x), "r"(y), "r"(bar) : "memory"); }
__device__ __forceinline__ void bulk_s2c(uint32_t dst, uint32_t src, uint32_t bytes, uint32_t bar) { asm volatile("cp.async.bulk.shared::cluster.shared::cta.mbarrier::complete_tx::bytes [%0], [%1], %2, [%3];" :: "r"(dst), "r"(src), "r"(bytes), "r"(bar) : "memory"); }
__device__ __forceinline__ void bulk_s2g(void* dst, uint32_t src, uint32_t bytes) { asm volatile("cp.async.bulk.global.shared::cta.bulk_group [%0], [%1], %2;" :: "l"(dst), "r"(src), "r"(bytes) : "memory"); }
__device__ __forceinline__ uint32_t ldg_nc32(const void* p) { uint32_t v; asm volatile("ld.global.nc.L2::128B.u32 %0, [%1];" : "=r"(v) : "l"(p)); return v; }
__device__ __forceinline__ uint4 ldg_relaxed128(const void* p) { uint4 v; asm volatile("ld.relaxed.gpu.global.v4.u32 {%0,%1,%2,%3}, [%4];" : "=r"(v.x), "=r"(v.y), "=r"(v.z), "=r"(v.w) : "l"(p) : "memory"); return v; }
__device__ __forceinline__ void mma16816(float (&d)[4], uint32_t a0, uint32_t a1, uint32_t a2, uint32_t a3, uint32_t b0, uint32_t b1) {
    asm volatile("mma.sync.aligned.m16n8k16.row.col.f32.bf16.bf16.f32 {%0,%1,%2,%3}, {%4,%5,%6,%7}, {%8,%9}, {%0,%1,%2,%3};"
        : "+f"(d[0]), "+f"(d[1]), "+f"(d[2]), "+f"(d[3]) : "r"(a0), "r"(a1), "r"(a2), "r"(a3), "r"(b0), "r"(b1));
}
__device__ __forceinline__ void mma16816_z(float (&d)[4], uint32_t a0, uint32_t a1, uint32_t a2, uint32_t a3, uint32_t b0, uint32_t b1) {
    asm volatile("mma.sync.aligned.m16n8k16.row.col.f32.bf16.bf16.f32 {%0,%1,%2,%3}, {%4,%5,%6,%7}, {%8,%9}, {%10,%10,%10,%10};"
        : "=f"(d[0]), "=f"(d[1]), "=f"(d[2]), "=f"(d[3]) : "r"(a0), "r"(a1), "r"(a2), "r"(a3), "r"(b0), "r"(b1), "f"(0.f));
}
__device__ __forceinline__ void mma1688(float (&d)[4], uint32_t a0, uint32_t a1, uint32_t b0) {
    asm volatile("mma.sync.aligned.m16n8k8.row.col.f32.bf16.bf16.f32 {%0,%1,%2,%3}, {%4,%5}, {%6}, {%0,%1,%2,%3};"
        : "+f"(d[0]), "+f"(d[1]), "+f"(d[2]), "+f"(d[3]) : "r"(a0), "r"(a1), "r"(b0));
}
__device__ __forceinline__ void mma1688_z(float (&d)[4], uint32_t a0, uint32_t a1, uint32_t b0) {
    asm volatile("mma.sync.aligned.m16n8k8.row.col.f32.bf16.bf16.f32 {%0,%1,%2,%3}, {%4,%5}, {%6}, {%7,%7,%7,%7};"
        : "=f"(d[0]), "=f"(d[1]), "=f"(d[2]), "=f"(d[3]) : "r"(a0), "r"(a1), "r"(b0), "f"(0.f));
}
template <int ACC>
__device__ __forceinline__ void wgmma_n32_rs(float (&d)[16], uint32_t a0, uint32_t a1, uint32_t a2, uint32_t a3, uint64_t desc) {
    asm volatile("wgmma.mma_async.sync.aligned.m64n32k16.f32.bf16.bf16 {%0,%1,%2,%3,%4,%5,%6,%7,%8,%9,%10,%11,%12,%13,%14,%15}, {%16,%17,%18,%19}, %20, %21, 1, 1, 0;"
        : "+f"(d[0]), "+f"(d[1]), "+f"(d[2]), "+f"(d[3]), "+f"(d[4]), "+f"(d[5]), "+f"(d[6]), "+f"(d[7]),
          "+f"(d[8]), "+f"(d[9]), "+f"(d[10]), "+f"(d[11]), "+f"(d[12]), "+f"(d[13]), "+f"(d[14]), "+f"(d[15])
        : "r"(a0), "r"(a1), "r"(a2), "r"(a3), "l"(desc), "n"(ACC));
}
template <int ACC>
__device__ __forceinline__ void wgmma_n32_ss(float (&d)[16], uint64_t da, uint64_t db) {
    asm volatile("wgmma.mma_async.sync.aligned.m64n32k16.f32.bf16.bf16 {%0,%1,%2,%3,%4,%5,%6,%7,%8,%9,%10,%11,%12,%13,%14,%15}, %16, %17, %18, 1, 1, 0, 0;"
        : "+f"(d[0]), "+f"(d[1]), "+f"(d[2]), "+f"(d[3]), "+f"(d[4]), "+f"(d[5]), "+f"(d[6]), "+f"(d[7]),
          "+f"(d[8]), "+f"(d[9]), "+f"(d[10]), "+f"(d[11]), "+f"(d[12]), "+f"(d[13]), "+f"(d[14]), "+f"(d[15])
        : "l"(da), "l"(db), "n"(ACC));
}
__device__ __forceinline__ void wg_fence() { asm volatile("wgmma.fence.sync.aligned;" ::: "memory"); }
__device__ __forceinline__ void wg_commit() { asm volatile("wgmma.commit_group.sync.aligned;" ::: "memory"); }
__device__ __forceinline__ void wg_wait0() { asm volatile("wgmma.wait_group.sync.aligned 0;" ::: "memory"); }
__device__ __forceinline__ void cluster_sync() { asm volatile("barrier.cluster.arrive.aligned;\nbarrier.cluster.wait.aligned;" ::: "memory"); }

#define STAMP(s, i) do {} while (0)
#define STAMPV(s, i, v) do {} while (0)

constexpr int XT_BYTES = 36864;
constexpr int O_XT = 0;
constexpr int O_STG = XT_BYTES;
constexpr int O_AS = 3 * XT_BYTES;
constexpr int O_XP = O_AS + 16384;
constexpr int O_QKX = O_XP + 8192;
constexpr int O_KM = O_QKX + 8192;
constexpr int O_QM = O_QKX + 10240;
constexpr int O_VX = O_STG + 147456;
constexpr int O_VM = O_VX + 16384;
constexpr int O_SC = O_VM + 2048;
constexpr int O_OF = O_SC + 2560;
constexpr int O_AF = O_OF + 2048;
constexpr int O_WP = O_AF + 4096;
constexpr int O_MF = O_WP + 2048;
constexpr int O_MISC = O_MF + 9216;
static_assert(O_QKX + 24576 <= O_VX, "smem");
constexpr int O_BAR = O_MISC + 64;
constexpr int CHAIN_SMEM = O_BAR + 128;
static_assert(CHAIN_SMEM <= 232448, "smem");
constexpr int B_X = O_BAR, B_VX = O_BAR + 24, B_SC = O_BAR + 40, B_W = O_BAR + 48, B_MX = O_BAR + 72;
constexpr float SM_SCALE = 0.08838834764831845f * 1.4426950408889634f;
constexpr uint32_t ONES = 0x3f803f80u;

__device__ __forceinline__ uint32_t opaque(uint32_t v) { uint32_t o; asm volatile("mov.u32 %0, %1;" : "=r"(o) : "r"(v)); return o; }
__device__ __forceinline__ void st_async128(uint32_t a, uint32_t x, uint32_t y, uint32_t z, uint32_t w, uint32_t bar) {
    asm volatile("st.async.shared::cluster.mbarrier::complete_tx::bytes.v4.b32 [%0], {%1,%2,%3,%4}, [%5];" :: "r"(a), "r"(x), "r"(y), "r"(z), "r"(w), "r"(bar) : "memory");
}
__device__ __forceinline__ void tma_x_tile(uint32_t sb, const CUtensorMap* tm, int r, int j, int slot) {
    asm volatile("{\n.reg .pred p;\nelect.sync _|p, 0xffffffff;\n"
        "@p mbarrier.arrive.expect_tx.shared::cta.b64 _, [%2], 36864;\n"
        "@p cp.async.bulk.tensor.2d.shared::cluster.global.mbarrier::complete_tx::bytes.multicast::cluster [%0], [%1, {%3, %4}], [%2], %7;\n"
        "@p cp.async.bulk.tensor.2d.shared::cluster.global.mbarrier::complete_tx::bytes.multicast::cluster [%0+4096], [%1, {%5, %4}], [%2], %7;\n"
        "@p cp.async.bulk.tensor.2d.shared::cluster.global.mbarrier::complete_tx::bytes.multicast::cluster [%0+8192], [%1, {%6, %4}], [%2], %7;\n}"
        :: "r"(sb + O_XT + slot * XT_BYTES + 3 * r * 4096), "l"(tm), "r"(sb + B_X + 8 * slot), "r"(192 * r), "r"(j * 32), "r"(192 * r + 64), "r"(192 * r + 128),
           "h"((unsigned short)7) : "memory");
}
__device__ __forceinline__ void flag_inc_if(uint32_t z, unsigned* p) {
    asm volatile("{\n.reg .pred p;\nsetp.eq.u32 p, %1, 0;\n@p red.release.gpu.global.inc.u32 [%0], 0xfffffffe;\n}" :: "l"(p), "r"(z) : "memory");
}
__device__ __forceinline__ float quad_max(float v) {
    const float a = __shfl_xor_sync(~0u, v, 1), b = __shfl_xor_sync(~0u, v, 2), c = __shfl_xor_sync(~0u, v, 3);
    return fmaxf(fmaxf(v, a), fmaxf(b, c));
}
__device__ __forceinline__ void load_scores(float (&p)[10], uint32_t base, uint32_t stride, uint32_t l16) {
    const float4 a0 = lds128f(base + l16), b0 = lds128f(base + stride + l16);
    const float4 a1 = lds128f(base + 512 + l16), b1 = lds128f(base + stride + 512 + l16);
    const float2 a2 = lds64f(base + 1024 + (l16 >> 1)), b2 = lds64f(base + stride + 1024 + (l16 >> 1));
    p[0] = a2.x + b2.x; p[1] = a2.y + b2.y;
    p[2] = a0.x + b0.x; p[3] = a0.y + b0.y; p[4] = a0.z + b0.z; p[5] = a0.w + b0.w;
    p[6] = a1.x + b1.x; p[7] = a1.y + b1.y; p[8] = a1.z + b1.z; p[9] = a1.w + b1.w;
}
__device__ __forceinline__ float rcp_fast(float x) { float y; asm("rcp.approx.ftz.f32 %0, %1;" : "=f"(y) : "f"(x)); return y; }

__global__ void __cluster_dims__(3, 1, 1) __launch_bounds__(384, 1)
chain_kernel(const __grid_constant__ CUtensorMap tm_x, const __grid_constant__ CUtensorMap tm_q,
             const __grid_constant__ CUtensorMap tm_k, const __grid_constant__ CUtensorMap tm_v,
             const __nv_bfloat16* __restrict__ x, const __nv_bfloat16* __restrict__ mem0,
             const __nv_bfloat16* __restrict__ Wo) {
    extern __shared__ __align__(1024) uint8_t smem_raw[];
    const uint32_t sb = smem_u32(smem_raw);
    const int lane = threadIdx.x & 31;
    const int warp = __shfl_sync(~0u, threadIdx.x >> 5, 0);
    const int wg = warp >> 2, w = warp & 3;
    const int h = blockIdx.x / 3, r = blockIdx.x - 3 * h;
    uint4* const g_acc = reinterpret_cast<uint4*>((reinterpret_cast<uintptr_t>(g_acc_raw) + 0x1fffff) & ~(uintptr_t)0x1fffff);

#define PSTAMP(i) do {} while (0)
    if (threadIdx.x == 0) {
        if (sb & 1023u) __trap();
        for (int i = 0; i < 9; i++) mbar_init(sb + O_BAR + 8 * i, 1);
        mbar_init(sb + B_MX, 4);
        asm volatile("fence.mbarrier_init.release.cluster;" ::: "memory");
        for (int i = 0; i < 3; i++) {
            mbar_expect(sb + B_W + 8 * i, 49152);
            for (int tl = 0; tl < 2; tl++)
                asm volatile("cp.async.bulk.tensor.2d.shared::cluster.global.mbarrier::complete_tx::bytes [%0], [%1, {%3, %4}], [%2];"
                    :: "r"(sb + O_STG + tl * 73728 + i * 24576), "l"(r < 2 ? (tl ? &tm_k : &tm_q) : &tm_v), "r"(sb + B_W + 8 * i),
                       "r"(h * 128 + 64 * (r < 2 ? r : tl)), "r"(192 * i) : "memory");
        }
    }
    __syncwarp();
    asm volatile("barrier.cluster.arrive.relaxed.aligned;" ::: "memory");
    asm volatile("griddepcontrol.launch_dependents;" ::: "memory");
    if (warp == 0) PSTAMP(9);
    const uint32_t l16c = __shfl_sync(~0u, lane * 16, lane);

    if (wg < 2) {
#define KS(u) ((u) < 8 ? 12 * ((u) >> 2) + (((u) >> 1) & 1) + 4 * ((u) & 1) : (u) < 12 ? (u) : (u) < 16 ? (u) + 8 : (u) < 24 ? 24 + (((u) - 16) >> 1) + 4 * ((u) & 1) : (u) + 8)
        asm volatile("setmaxnreg.inc.sync.aligned.u32 184;");
        uint32_t a[144];
        uint32_t adr1;
        {
            const int g = lane >> 2, t = lane & 3;
            const int t1 = threadIdx.x;
#pragma unroll
            for (int i = 0; i < 2; i++) g_acc[(blockIdx.x * 64 + i * 32 + (t1 >> 3)) * 16 + (t1 & 7)] = make_uint4(0, 0, 0, 0);
            __threadfence();
            asm volatile("barrier.cluster.wait.aligned;" ::: "memory");
            const uint32_t ev = sb + O_STG + (2 * t) * 128 + (((2 * w + (g >> 2)) ^ (2 * t)) << 4) + (g & 3) * 4;
            const uint32_t od = (ev ^ 16) + 128;
            auto gather = [&](int dst, uint32_t off) {
                a[dst] = lds32(ev + off); a[dst + 1] = lds32(od + off); a[dst + 2] = lds32(ev + off + 1024); a[dst + 3] = lds32(od + off + 1024);
            };
            const uint4* xp = reinterpret_cast<const uint4*>(x) + blockIdx.x * 1536 + t1;
            uint4 xv[6];
#pragma unroll
            for (int th = 0; th < 2; th++) {
                mbar_wait(sb + B_W + 8 * th, 0);
                if (th == 1) {
#pragma unroll
                    for (int i = 0; i < 6; i++) xv[i] = __ldg(xp + i * 256);
                }
#pragma unroll
                for (int u = 4 * th; u < 4 * th + 4; u++) {
                    gather(32 + 4 * u, wg * (73728 + 4096) + KS(u) * 2048);
                    gather(4 * u, 73728 - wg * (73728 - 4096) + KS(u) * 2048);
                    gather(64 + 4 * u, wg * 73728 + KS(8 + u) * 2048);
                }
            }
            mbar_wait(sb + B_W + 16, 0);
#pragma unroll
            for (int u = 16; u < 28; u++) gather(32 + 4 * u, wg * 73728 + KS(u) * 2048);
#pragma unroll
            for (int kk = 0; kk < 72; kk++) {
                uint32_t w0 = a[2 * kk], w1 = a[2 * kk + 1];
                a[2 * kk] = __byte_perm(w0, w1, 0x5410);
                a[2 * kk + 1] = __byte_perm(w0, w1, 0x7632);
            }
            if (r == 2) {
                float n0[4], n1[4];
#pragma unroll
                for (int u = 0; u < 36; u++) {
                    const uint32_t x0 = a[4 * u] & 0x7fff7fffu, x1 = a[4 * u + 1] & 0x7fff7fffu, x2 = a[4 * u + 2] & 0x7fff7fffu, x3 = a[4 * u + 3] & 0x7fff7fffu;
                    if (u == 0) mma16816_z(n0, x0, x1, x2, x3, ONES, ONES);
                    else if (u < 8) mma16816(n0, x0, x1, x2, x3, ONES, ONES);
                    else if (u == 8) mma16816_z(n1, x0, x1, x2, x3, ONES, ONES);
                    else mma16816(n1, x0, x1, x2, x3, ONES, ONES);
                }
                const uint32_t mx = __reduce_max_sync(~0u, __float_as_uint(2.f * fmaxf(fmaxf(n0[0], n0[2]), fmaxf(n1[0], n1[2]))));
                sts32_if(lane, sb + O_MISC + 32 + 4 * warp, mx);
            }
            uint32_t xm = 0;
#pragma unroll
            for (int i = 0; i < 6; i++)
                xm = __vmaxu2(xm, __vmaxu2(__vmaxu2(xv[i].x & 0x7fff7fffu, xv[i].y & 0x7fff7fffu), __vmaxu2(xv[i].z & 0x7fff7fffu, xv[i].w & 0x7fff7fffu)));
            sts32_if(lane, sb + O_OF + 16 + 4 * warp, __reduce_max_sync(~0u, max(xm << 16, xm & 0xffff0000u)));
            if (warp == 0) PSTAMP(11);
            bar_arrive(7, 384);
            asm volatile("barrier.cluster.arrive.relaxed.aligned;" ::: "memory");
            bar_sync(1, 256);
            const uint32_t as = sb + O_AS + wg * 8192 + (16 * w + g) * 128 + t * 4;
            sts32(as + (g << 4), a[32]);
            sts32(as + 1024 + (g << 4), a[33]);
            sts32(as + ((1 ^ g) << 4), a[34]);
            sts32(as + 1024 + ((1 ^ g) << 4), a[35]);
            sts128(sb + O_AF + warp * 512 + lane * 16, a[32], a[33], a[34], a[35]);
            fence_async_smem();
            bar_sync(1, 256);
            const uint32_t l = lane * 16;
            const int mi = lane >> 3, isk = (mi >> 1) ? wg : (wg ^ 1);
            adr1 = (r == 2) ? (sb + O_VM + warp * 256 + (l >> 1))
                            : (isk ? (sb + O_KM + w * 512 + wg * 256 + (mi & 1) * 128 + (l & 127))
                                   : (sb + O_QM + w * 512 + (mi & 1) * 256 + wg * 128 + (l & 127)));
            adr1 = __shfl_sync(~0u, adr1, lane);
        }
        int s3 = 2;
#pragma unroll 1
        for (int s = -1; s < NSEG; s++) {
            const uint32_t l16 = opaque(l16c);
            s3 = (s3 == 2) ? 0 : s3 + 1;
            if (s < 0) mbar_wait(sb + B_X, 0);
            const uint64_t desc0 = (uint64_t)(((sb + O_XT + s3 * XT_BYTES) & 0x3FFFF) >> 4) | (1ull << 16) | (64ull << 32) | (1ull << 62);
            uint32_t km0 = 0, km1 = 0;
            if (s >= 0) {
                { const uint4 v = lds128(sb + O_AF + warp * 512 + l16); a[32] = v.x; a[33] = v.y; a[34] = v.z; a[35] = v.w; }
                float co[4], cw[3][4];
                uint4 b[14];
                float inv;
#define GORD(i) ((i) < 8 ? 2 * ((i) >> 2) + (((i) >> 1) & 1) + 4 * ((i) & 1) : (i))
                auto qkv_mma = [&](int i) {
                    const int gi = GORD(i), u = 8 * gi, n0 = 2 * i, n1 = 2 * i + 1;
                    if (gi < 4) {
                        if (i == 0) mma16816_z(co, a[u], a[u + 1], a[u + 2], a[u + 3], b[0].x, b[0].y);
                        else mma16816(co, a[u], a[u + 1], a[u + 2], a[u + 3], b[i].x, b[i].y);
                    }
                    if (n0 < 3) mma16816_z(cw[n0 % 3], a[32 + u], a[32 + u + 1], a[32 + u + 2], a[32 + u + 3], b[i].x, b[i].y);
                    else mma16816(cw[n0 % 3], a[32 + u], a[32 + u + 1], a[32 + u + 2], a[32 + u + 3], b[i].x, b[i].y);
                    if (n1 < 3) mma16816_z(cw[n1 % 3], a[32 + u + 4], a[32 + u + 5], a[32 + u + 6], a[32 + u + 7], b[i].z, b[i].w);
                    else mma16816(cw[n1 % 3], a[32 + u + 4], a[32 + u + 5], a[32 + u + 6], a[32 + u + 7], b[i].z, b[i].w);
                    if (gi < 4) mma16816(co, a[u + 4], a[u + 5], a[u + 6], a[u + 7], b[i].z, b[i].w);
                };
                const uint32_t mf = sb + O_MF + l16, mfs = mf + wg * 1024;
                const uint32_t qb = (s & 1) * 12288;
                bar_sync(2, 384);
                if (warp == 0) STAMP(s, 0);
                auto qkv_ld = [&](int i) {
                    const int gi = GORD(i);
                    b[i] = gi < 4 ? lds128v(mfs + (gi >> 1) * 3072 + (gi & 1) * 512) : lds128v(mf + (gi < 6 ? gi : gi + 4) * 512);
                };
#pragma unroll
                for (int i = 0; i < 4; i++) qkv_ld(i);
                qkv_mma(0); qkv_mma(1); qkv_mma(2);
                const uint32_t z0 = __float_as_uint(QDEP ? co[0] : cw[1][0]) & (l16 & 15u);
                qkv_mma(3);
                bar_sync(15, 384);
                b[4] = lds128v(mfs + 3072 + z0);
#pragma unroll
                for (int i = 5; i < 9; i++) qkv_ld(i);
#pragma unroll
                for (int i = 4; i < 9; i++) { qkv_mma(i); qkv_ld(5 + i); }
                asm volatile("ld.volatile.shared.f32 %0, [%1];" : "=f"(inv) : "r"(sb + O_MISC) : "memory");
#pragma unroll
                for (int i = 9; i < 14; i++) qkv_mma(i);
#pragma unroll
                for (int i = 0; i < 4; i++) cw[0][i] += cw[1][i] + cw[2][i];
                if (r < 2) {
                    const uint32_t o0 = pack_bf16(co[0] * inv, co[1] * inv), o1 = pack_bf16(co[2] * inv, co[3] * inv);
                    const uint32_t w0 = pack_bf16(cw[0][0] * inv, cw[0][1] * inv), w1 = pack_bf16(cw[0][2] * inv, cw[0][3] * inv);
                    stsm4t(adr1 + qb, o0, o1, w0, w1);
                    if (warp == 0) STAMP(s, 1);
                    asm volatile("{\n.reg .pred p;\nsetp.ge.u32 p, %0, 3;\n@p bar.arrive 1, 256;\n}" :: "r"(warp) : "memory");
                    auto scores = [&](float (&v)[4], const uint4 (&q)[4], const uint4 (&k)[4]) {
                        float s0[4], s1[4], t0[4], t1[4];
                        mma16816_z(s0, q[0].x, q[0].y, q[0].z, q[0].w, k[0].x, k[0].y);
                        mma16816_z(s1, q[0].x, q[0].y, q[0].z, q[0].w, k[0].z, k[0].w);
                        mma16816_z(t0, q[1].x, q[1].y, q[1].z, q[1].w, k[1].x, k[1].y);
                        mma16816_z(t1, q[1].x, q[1].y, q[1].z, q[1].w, k[1].z, k[1].w);
                        mma16816(s0, q[2].x, q[2].y, q[2].z, q[2].w, k[2].x, k[2].y);
                        mma16816(s1, q[2].x, q[2].y, q[2].z, q[2].w, k[2].z, k[2].w);
                        mma16816(t0, q[3].x, q[3].y, q[3].z, q[3].w, k[3].x, k[3].y);
                        mma16816(t1, q[3].x, q[3].y, q[3].z, q[3].w, k[3].z, k[3].w);
                        v[0] = (s0[0] + s0[2]) + (t0[0] + t0[2]); v[1] = (s0[1] + s0[3]) + (t0[1] + t0[3]);
                        v[2] = (s1[0] + s1[2]) + (t1[0] + t1[2]); v[3] = (s1[1] + s1[3]) + (t1[1] + t1[3]);
                    };
                    if (warp < 2) {
                        uint4 q[4], k[4]; float v[4];
#pragma unroll
                        for (int i = 0; i < 4; i++) k[i] = ldsm4(sb + O_QKX + 4096 + qb + warp * 2048 + i * 512 + l16);
                        bar_sync(1, 256);
#pragma unroll
                        for (int i = 0; i < 4; i++) q[i] = ldsm4(sb + O_QM + qb + i * 512 + l16);
                        scores(v, q, k);
                        const uint32_t dst = sb + O_SC + r * 1280 + warp * 512 + l16;
                        st_async128(mapa(dst, 2), __float_as_uint(v[0]), __float_as_uint(v[1]), __float_as_uint(v[2]), __float_as_uint(v[3]), mapa(sb + B_SC, 2));
                        st_async128(mapa(dst, r ^ 1), __float_as_uint(v[0]), __float_as_uint(v[1]), __float_as_uint(v[2]), __float_as_uint(v[3]), mapa(sb + B_SC, r ^ 1));
                        st_async128(mapa(dst, r), __float_as_uint(v[0]), __float_as_uint(v[1]), __float_as_uint(v[2]), __float_as_uint(v[3]), mapa(sb + B_SC, r));
                    } else if (warp == 2) {
                        uint4 q[4], k[4]; float v[4];
                        bar_sync(1, 256);
#pragma unroll
                        for (int i = 0; i < 4; i++) { q[i] = ldsm4(sb + O_QM + qb + i * 512 + l16); k[i] = ldsm4(sb + O_KM + qb + i * 512 + l16); }
                        scores(v, q, k);
                        const uint32_t dst = sb + O_SC + r * 1280 + 1024 + (l16 >> 1);
                        st_async64(mapa(dst, 2), __float_as_uint(v[0] + v[2]), __float_as_uint(v[1] + v[3]), mapa(sb + B_SC, 2));
                        st_async64(mapa(dst, r ^ 1), __float_as_uint(v[0] + v[2]), __float_as_uint(v[1] + v[3]), mapa(sb + B_SC, r ^ 1));
                        st_async64(mapa(dst, r), __float_as_uint(v[0] + v[2]), __float_as_uint(v[1] + v[3]), mapa(sb + B_SC, r));
                        STAMP(s, 2);
                    } else if (warp == 3) {
                        asm volatile("cp.async.bulk.wait_group 0;\nfence.proxy.async.global;" ::: "memory");
                    }
                } else {
                    sts128f(sb + O_XP + warp * 512 + l16, co[0], co[1], co[2], co[3]);
                    bar_sync(8 + w, 64);
                    const float4 o = lds128f(sb + O_XP + (warp ^ 4) * 512 + l16);
                    km0 = pack_bf16((cw[0][0] + o.x) * inv, (cw[0][1] + o.y) * inv);
                    km1 = pack_bf16((cw[0][2] + o.z) * inv, (cw[0][3] + o.w) * inv);
                    if (warp == 0) STAMP(s, 1);
                    st_async64(mapa(adr1, 0), km0, km1, mapa(sb + B_SC, 0));
                    st_async64(mapa(adr1, 1), km0, km1, mapa(sb + B_SC, 1));
                    st_async64(mapa(adr1, 2), km0, km1, mapa(sb + B_SC, 2));
                    if (warp == 0) STAMP(s, 2);
                }
            }
            if (s >= 0) bar_sync(3, 384);
            auto store_qk = [&]() {
                asm volatile("{\n.reg .pred p;\nelect.sync _|p, 0xffffffff;\n"
                    "@p cp.async.bulk.global.shared::cta.bulk_group [%0], [%1], 10240;\n@p cp.async.bulk.commit_group;\n}"
                    :: "l"(reinterpret_cast<char*>(g_qkv) + (size_t)(s * NH + h) * REC + r * 10240), "r"(sb + O_QKX + (s & 1) * 12288) : "memory");
            };
            auto store_vm = [&]() {
                *reinterpret_cast<uint2*>(reinterpret_cast<char*>(g_qkv) + (size_t)(s * NH + h) * REC + 28672 + warp * 256 + (l16 >> 1)) = make_uint2(km0, km1);
            };
            if (s == NSEG - 1) {
                if (r == 2) store_vm();
                else if (warp == 3) {
                    fence_async_smem();
                    store_qk();
                    asm volatile("cp.async.bulk.wait_group 0;\nfence.proxy.async.global;" ::: "memory");
                }
            } else {
                const int j = s + 1;
#define XDESC(u) (((u) < 8 ? descs : desc0) + (uint64_t)(((KS(u) >> 2) * 4096 + (KS(u) & 3) * 32) >> 4))
                const uint64_t descs = desc0 + (uint64_t)(wg * 4);
                float d[16];
                wg_fence();
#pragma unroll
                for (int u = 0; u < 8; u++) {
                    if (u == 0) wgmma_n32_rs<0>(d, a[0], a[1], a[2], a[3], XDESC(0));
                    else wgmma_n32_rs<1>(d, a[4 * u], a[4 * u + 1], a[4 * u + 2], a[4 * u + 3], XDESC(u));
                }
                wg_commit();
                wg_wait0();
                if (warp == 0) STAMP(s, 15);
                auto xp_put = [&]() {
#pragma unroll
                    for (int q = 0; q < 2; q++)
                        sts128(sb + O_XP + warp * 1024 + q * 512 + l16, pack_bf16(d[8 * q], d[8 * q + 1]), pack_bf16(d[8 * q + 2], d[8 * q + 3]),
                               pack_bf16(d[8 * q + 4], d[8 * q + 5]), pack_bf16(d[8 * q + 6], d[8 * q + 7]));
                };
                uint4 xo[2];
                auto xp_get = [&]() { xo[0] = lds128(sb + O_XP + (warp ^ 4) * 1024 + l16); xo[1] = lds128(sb + O_XP + (warp ^ 4) * 1024 + 512 + l16); };
                if (s >= 0) bar_sync(4, 384);
                xp_put();
                bar_sync(12, 256);
                xp_get();
#pragma unroll
                for (int q = 0; q < 2; q++) {
                    d[8 * q] = __uint_as_float(xo[q].x << 16); d[8 * q + 1] = __uint_as_float(xo[q].x & 0xffff0000u);
                    d[8 * q + 2] = __uint_as_float(xo[q].y << 16); d[8 * q + 3] = __uint_as_float(xo[q].y & 0xffff0000u);
                    d[8 * q + 4] = __uint_as_float(xo[q].z << 16); d[8 * q + 5] = __uint_as_float(xo[q].z & 0xffff0000u);
                    d[8 * q + 6] = __uint_as_float(xo[q].w << 16); d[8 * q + 7] = __uint_as_float(xo[q].w & 0xffff0000u);
                }
                if (s >= 0) {
                    if (r == 2) store_vm();
                    if (warp == 5 && s + 2 < NSEG) tma_x_tile(sb, &tm_x, r, s + 2, s3 == 2 ? 0 : s3 + 1);
                    if (warp == 3) fence_async_smem();
                    asm volatile("{\n.reg .pred p;\nsetp.eq.u32 p, %0, 0;\n@p bar.sync 5, 256;\n@!p bar.sync 13, 256;\n}" :: "r"(wg) : "memory");
                }
                const uint64_t da0 = (uint64_t)(((sb + O_AS + wg * 8192) & 0x3FFFF) >> 4) | (1ull << 16) | (64ull << 32) | (1ull << 62);
                wg_fence();
                wgmma_n32_ss<1>(d, da0, XDESC(0));
#pragma unroll
                for (int u = 1; u < 28; u++) wgmma_n32_rs<1>(d, a[32 + 4 * u], a[32 + 4 * u + 1], a[32 + 4 * u + 2], a[32 + 4 * u + 3], XDESC(u));
                wg_commit();
                wg_wait0();
                if (warp == 3 && r < 2 && s >= 0) store_qk();
                if (warp == 4) STAMP(s, 3);
                uint32_t e[8];
#pragma unroll
                for (int i = 0; i < 8; i++) e[i] = pack_bf16(d[2 * i], d[2 * i + 1]);
                if (r < 2) {
                    const uint32_t base = sb + O_QKX + (j & 1) * 12288 + wg * 4096 + w * 512 + l16;
                    stsm4t(base, e[0], wg ? e[1] : e[2], wg ? e[2] : e[1], e[3]);
                    stsm4t(base + 2048, e[4], wg ? e[5] : e[6], wg ? e[6] : e[5], e[7]);
                } else {
                    const uint32_t base = sb + O_VX + (j & 1) * 8192 + warp * 1024 + l16;
                    sts128(base, e[0], e[1], e[2], e[3]);
                    sts128(base + 512, e[4], e[5], e[6], e[7]);
                    bar_arrive(14, 288);
                }
                if (warp == 7) STAMP(s, 4);
                if (s < 0) asm volatile("barrier.cluster.wait.aligned;" ::: "memory");
            }
        }
        bar_arrive(7, 384);
    } else {
        asm volatile("setmaxnreg.dec.sync.aligned.u32 136;");
        const int c = w;
        uint32_t a[96];
        uint32_t mmax = 0;
        {
            const int g = lane >> 2, t = lane & 3;
            uint32_t tag = 0, m0v[18];
            if (threadIdx.x == 256) tag = atomicAdd(&g_ticket, 1u);
#pragma unroll
            for (int i = 0; i < 9; i++) {
                const uint32_t* p = reinterpret_cast<const uint32_t*>(mem0 + g * DM + 16 * (4 * i + c) + 2 * t);
                m0v[2 * i] = __ldg(p); m0v[2 * i + 1] = __ldg(p + 4);
            }
            asm volatile("barrier.cluster.wait.aligned;" ::: "memory");
            if (c == 0) {
                tma_x_tile(sb, &tm_x, r, 0, 0);
                mbar_expect_if(lane, sb + B_SC, 4608);
                if (r < 2) mbar_expect_if(lane, sb + B_VX, 8192);
                sts32_if(lane, sb + O_MISC, __float_as_uint(1.0f));
                sts32_if(lane, sb + O_MISC + 12, __float_as_uint(SM_SCALE));
            }
            asm volatile("barrier.cluster.arrive.relaxed.aligned;" ::: "memory");
#pragma unroll
            for (int tau = 0; tau < 3; tau++) {
                const uint32_t* v = m0v + 6 * tau;
                sts128(sb + O_MF + tau * 3072 + c * 512 + lane * 16, v[0], v[1], v[2], v[3]);
                sts64(sb + O_MF + tau * 3072 + 2048 + (c >> 1) * 512 + lane * 16 + (c & 1) * 8, v[4], v[5]);
#pragma unroll
                for (int i = 0; i < 6; i++) mmax = __vmaxu2(mmax, v[i] & 0x7fff7fffu);
            }
            mmax = max(mmax << 16, mmax & 0xffff0000u);
            bar_arrive(2, 384); bar_arrive(15, 384);
            tag = (__shfl_sync(~0u, tag, 0) / 96u + 1u) & 0xffffu;
            mbar_wait(sb + B_W + 0, 0);
            const __nv_bfloat16* p = Wo + (size_t)(h * 128 + 4 * t) * DM + 192 * r + 16 * c + 2 * g;
#pragma unroll
            for (int i = 0; i < 3; i++)
#pragma unroll
                for (int eb = 0; eb < 8; eb++)
#pragma unroll
                    for (int j = 0; j < 4; j++) a[(i * 8 + eb) * 4 + j] = ldg_nc32(p + (16 * eb + ((j & 1) * 2 + (j >> 1))) * DM + 64 * i);
#pragma unroll
            for (int kk = 0; kk < 48; kk++) {
                uint32_t w0 = a[2 * kk], w1 = a[2 * kk + 1];
                a[2 * kk] = __byte_perm(w0, w1, 0x5410);
                a[2 * kk + 1] = __byte_perm(w0, w1, 0x7632);
            }
            sts128(sb + O_WP + c * 512 + lane * 16, a[92], a[93], a[94], a[95]);
            float wmax = 0.f;
#pragma unroll
            for (int i = 0; i < 3; i++) {
                float n0[4];
#pragma unroll
                for (int u = 8 * i; u < 8 * i + 8; u++) {
                    const uint32_t x0 = a[4 * u] & 0x7fff7fffu, x1 = a[4 * u + 1] & 0x7fff7fffu, x2 = a[4 * u + 2] & 0x7fff7fffu, x3 = a[4 * u + 3] & 0x7fff7fffu;
                    if (u == 8 * i) mma16816_z(n0, x0, x1, x2, x3, ONES, ONES);
                    else mma16816(n0, x0, x1, x2, x3, ONES, ONES);
                }
                wmax = fmaxf(wmax, fmaxf(n0[0], n0[2]));
            }
            uint32_t wm = __reduce_max_sync(~0u, __float_as_uint(wmax));
            sts32_if(lane, sb + O_OF + 4 * c, wm);
            if (c == 0) PSTAMP(8);
            bar_sync(7, 384);
            asm volatile("barrier.cluster.wait.aligned;" ::: "memory");
            if (c == 1) tma_x_tile(sb, &tm_x, r, 1, 1);
            if (c == 0) {
                const uint4 wq = lds128(sb + O_OF), xq = lds128(sb + O_OF + 16), xr = lds128(sb + O_OF + 32), v0 = lds128(sb + O_MISC + 32), v1 = lds128(sb + O_MISC + 48);
                const uint32_t w1 = max(max(wq.x, wq.y), max(wq.z, wq.w)), x1 = max(max(max(xq.x, xq.y), max(xq.z, xq.w)), max(max(xr.x, xr.y), max(xr.z, xr.w)));
                const uint32_t vv = (r < 2) ? 0u : max(max(max(v0.x, v0.y), max(v0.z, v0.w)), max(max(v1.x, v1.y), max(v1.z, v1.w)));
                const uint32_t lo = (min(w1, 0x7f800000u) + 0xffffu) >> 16 | ((min(vv, 0x7f800000u) + 0xffffu) & 0xffff0000u), hi = (x1 & 0xffff0000u) | tag;
                uint32_t l0, h0, l1, h1, l2, h2;
                asm volatile("{\n.reg .pred p;\n.reg .u32 n, x, y;\n.reg .b64 v;\nsetp.eq.u32 p, %10, 0;\nmov.b64 v, {%8, %9};\n@p st.relaxed.gpu.global.b64 [%7], v;\nmov.u32 n, 0;\n"
                             "G_%=: ld.relaxed.gpu.global.b64 v, [%6];\nmov.b64 {%0, %1}, v;\nld.relaxed.gpu.global.b64 v, [%6+256];\nmov.b64 {%2, %3}, v;\n"
                             "ld.relaxed.gpu.global.b64 v, [%6+512];\nmov.b64 {%4, %5}, v;\n"
                             "xor.b32 x, %1, %9;\nxor.b32 y, %3, %9;\nor.b32 x, x, y;\nxor.b32 y, %5, %9;\nor.b32 x, x, y;\nand.b32 x, x, 0xffff;\n"
                             "setp.eq.u32 p, x, 0;\nvote.sync.all.pred p, p, 0xffffffff;\n@p bra.uni E_%=;\n"
                             "add.u32 n, n, 1;\nsetp.lt.u32 p, n, 4000000;\n@p bra.uni G_%=;\ntrap;\nE_%=:\n}"
                             : "=&r"(l0), "=&r"(h0), "=&r"(l1), "=&r"(h1), "=&r"(l2), "=&r"(h2)
                             : "l"(&g_norm[lane]), "l"(&g_norm[blockIdx.x]), "r"(lo), "r"(hi), "r"(lane) : "memory");
                const uint32_t lm = __vmaxu2(l0, __vmaxu2(l1, l2));
                const float fw = __uint_as_float(__reduce_max_sync(~0u, lm << 16));
                const float fv = __uint_as_float(__reduce_max_sync(~0u, lm & 0xffff0000u));
                const float xmax = __uint_as_float(__reduce_max_sync(~0u, max(h0, max(h1, h2)) & 0xffff0000u));
                const float G = 36.f * fw * fv;
                sts32_if(lane, sb + O_MISC + 4, __float_as_uint(G)); sts32_if(lane, sb + O_MISC + 8, __float_as_uint(G * xmax));
            }
        }
        if (c == 0) PSTAMP(12);
        bar_sync(6, 128);
        int s3n = 1;
        uint32_t roff = __shfl_sync(~0u, (r * 4 + c) * 2048 + (lane >> 4) * 512 + (lane & 2) * 128 + (lane & 1) * 64 + (lane & 12) * 4, lane);
#pragma unroll 1
        for (int s = 0; s < NSEG; s++) {
            const uint32_t l16 = opaque(l16c);
            const uint32_t vxa = sb + O_VX + (s & 1) * 8192 + c * 2048 + l16;
            sts32_if(l16, sb + O_MISC + 16 + 4 * c, __reduce_max_sync(~0u, mmax));
            mbar_arrive_if(l16, sb + B_MX);
            if (c == 0 && r == 2) {
                bar_sync(14, 288);
                fence_async_smem();
                asm volatile("{\n.reg .pred p;\nelect.sync _|p, 0xffffffff;\n"
                    "@p cp.async.bulk.global.shared::cta.bulk_group [%0], [%1], 8192;\n@p cp.async.bulk.commit_group;\n"
                    "cp.async.bulk.wait_group 0;\nsetp.lt.and.s32 p, %4, 63, p;\n"
                    "@p cp.async.bulk.shared::cluster.global.mbarrier::complete_tx::bytes.multicast::cluster [%1], [%0], 8192, [%2], %3;\n"
                    "fence.proxy.async.global;\n}"
                    :: "l"(reinterpret_cast<char*>(g_qkv) + (size_t)(s * NH + h) * REC + 20480), "r"(sb + O_VX + (s & 1) * 8192),
                       "r"(sb + B_VX + 8 * (s & 1)), "h"((unsigned short)3), "r"(s) : "memory");
            }
            if (s == NSEG - 1) { bar_sync(3, 384); mbar_wait(sb + B_SC, s & 1); break; }
            uint4 vx[4];
            if (c == 0) STAMP(s, 5);
            {
                const bool pub = c == 3 && (s & 3) == 1 && s >= 5;
                if (pub) { bar_arrive(3, 384); flag_inc_if(l16, &g_flag[F_QKV + (s - 5 + (h >> 3)) * 8]); }
                mbar_wait(sb + B_MX, s & 1);
                const uint4 mm = lds128(sb + O_MISC + 16), cf = lds128(sb + O_MISC);
                const float bound = fmaxf(__uint_as_float(cf.z), __uint_as_float(cf.y) * (__uint_as_float(max(max(mm.x, mm.y), max(mm.z, mm.w))) * __uint_as_float(cf.x)));
                const uint32_t ebits = __reduce_max_sync(~0u, min(max(__float_as_uint(bound) & 0x7f800000u, 21u << 23), 254u << 23));
                if (c == 1) mbar_wait(sb + B_X + 8 * s3n, ((s + 1) / 3) & 1);
                s3n = (s3n == 2) ? 0 : s3n + 1;
                if (!pub) bar_sync(3, 384);
                else if (r == 2) mbar_wait(sb + B_SC, s & 1);
                if (r < 2) mbar_wait(sb + B_VX + 8 * (s & 1), (s >> 1) & 1);
                vx[0] = lds128(vxa); vx[2] = lds128(vxa + 1024);
                if (c == 0) STAMP(s, 13);
                mbar_wait(sb + B_SC, s & 1);
                if (c == 0) STAMP(s, 6);
                float p[10];
                load_scores(p, sb + O_SC, 1280, l16);
                float mx = fmaxf(fmaxf(fmaxf(p[0], p[1]), fmaxf(p[2], p[3])), fmaxf(fmaxf(p[4], p[5]), fmaxf(p[6], p[7])));
                mx = quad_max(fmaxf(mx, fmaxf(p[8], p[9])));
                const uint4 vm = lds64x2(sb + O_VM + c * 512 + (l16 >> 1));
                vx[1] = lds128(vxa + 512); vx[3] = lds128(vxa + 1536);
                bar_arrive(4, 384);
                const float sc = __uint_as_float(lds32(sb + O_MISC + 12));
                const float mo = mx * SM_SCALE;
                uint32_t P[5];
#pragma unroll
                for (int n = 0; n < 5; n++) P[n] = pack_bf16(ex2(fmaf(p[2 * n], SM_SCALE, -mo)), ex2(fmaf(p[2 * n + 1], n == 3 ? sc : SM_SCALE, -mo)));
                if (c == 0) STAMP(s, 7);
                float o0[4], o1[4], sm[4];
                mma16816_z(sm, ONES, ONES, ONES, ONES, P[1], P[2]);
                mma16816_z(o0, vx[0].x, vx[0].y, vx[0].z, vx[0].w, P[1], P[2]);
                mma16816_z(o1, vx[2].x, vx[2].y, vx[2].z, vx[2].w, P[1], P[2]);
                mma16816(sm, ONES, ONES, ONES, ONES, P[3], P[4]);
                mma16816(o0, vx[1].x, vx[1].y, vx[1].z, vx[1].w, P[3], P[4]);
                mma16816(o1, vx[3].x, vx[3].y, vx[3].z, vx[3].w, P[3], P[4]);
                mma1688(sm, ONES, ONES, P[0]);
                mma1688(o0, vm.x, vm.y, P[0]);
                mma1688(o1, vm.z, vm.w, P[0]);
                const float sig = __uint_as_float((268u << 23) - ebits);
                const float r0 = rcp_fast(sm[0]) * sig, r1 = rcp_fast(sm[1]) * sig;
                stsm4t(sb + O_OF + c * 512 + l16, pack_bf16(o0[0] * r0, o0[1] * r1), pack_bf16(o0[2] * r0, o0[3] * r1),
                       pack_bf16(o1[0] * r0, o1[1] * r1), pack_bf16(o1[2] * r0, o1[3] * r1));
                bar_sync(6, 128);
                uint4 ob[4];
#pragma unroll
                for (int q = 0; q < 4; q++) ob[q] = ldsm4(sb + O_OF + q * 512 + l16);
                { const uint4 v = lds128(sb + O_WP + c * 512 + l16); a[92] = v.x; a[93] = v.y; a[94] = v.z; a[95] = v.w; }
                float m0[3][4], m1[3][4];
#pragma unroll
                for (int q = 0; q < 4; q++) {
#pragma unroll
                    for (int i = 0; i < 3; i++) {
                        const int k0 = (i * 8 + 2 * q) * 4;
                        if (q == 0) mma16816_z(m0[i], a[k0], a[k0 + 1], a[k0 + 2], a[k0 + 3], ob[q].x, ob[q].y);
                        else mma16816(m0[i], a[k0], a[k0 + 1], a[k0 + 2], a[k0 + 3], ob[q].x, ob[q].y);
                    }
#pragma unroll
                    for (int i = 0; i < 3; i++) {
                        const int k1 = (i * 8 + 2 * q + 1) * 4;
                        if (q == 0) mma16816_z(m1[i], a[k1], a[k1 + 1], a[k1 + 2], a[k1 + 3], ob[q].z, ob[q].w);
                        else mma16816(m1[i], a[k1], a[k1 + 1], a[k1 + 2], a[k1 + 3], ob[q].z, ob[q].w);
                    }
                }
                asm volatile("red.relaxed.gpu.global.add.noftz.v4.f16x2 [%0], {%1,%2,%3,%4};" :: "l"(reinterpret_cast<char*>(g_acc) + roff),
                    "r"(pack_f16(m0[0][0] + m1[0][0], m0[0][2] + m1[0][2])), "r"(pack_f16(m0[1][0] + m1[1][0], m0[1][2] + m1[1][2])),
                    "r"(pack_f16(m0[2][0] + m1[2][0], m0[2][2] + m1[2][2])), "r"(0x3c00u) : "memory");
                asm volatile("red.relaxed.gpu.global.add.noftz.v4.f16x2 [%0], {%1,%2,%3,%4};" :: "l"(reinterpret_cast<char*>(g_acc) + roff + 1024),
                    "r"(pack_f16(m0[0][1] + m1[0][1], m0[0][3] + m1[0][3])), "r"(pack_f16(m0[1][1] + m1[1][1], m0[1][3] + m1[1][3])),
                    "r"(pack_f16(m0[2][1] + m1[2][1], m0[2][3] + m1[2][3])), "r"(0x3c00u) : "memory");
                const unsigned t_red = clk();
                bar_arrive(5, 256);
                bar_arrive(13, 256);
                mbar_expect_if(l16 | c, sb + B_SC, 4608);
                mbar_expect_if(l16 | (c ^ 1) | (r >> 1), sb + B_VX + 8 * ((s + 1) & 1), 8192);
                sts32_if(l16 | (c ^ 3), sb + O_MISC, ebits - (14u << 23));
                if (c == 0) STAMPV(s, 8, t_red);
                if (ACC_PF && c == 2 && s + 4 < NSEG - 1)
                    asm volatile("prefetch.global.L2 [%0];" :: "l"(reinterpret_cast<const char*>(g_acc) + ((s + 4) * 96 + blockIdx.x) * 256 + (l16 & 96)) : "memory");
                const char* pbase = reinterpret_cast<const char*>(g_acc) + (s * 24576 + c * 2048) + ((l16 & 64) * 16 + (l16 & 256) + ((l16 & 128) >> 1) + (l16 & 48));
                spin_until(t_red, D_WAIT);
                uint4 v[6];
#pragma unroll
                for (int i = 0; i < 6; i++) v[i] = ldg_relaxed128(pbase + (i >> 1) * 8192 + (i & 1) * 512);
                int nretry = 0;
                auto convert = [&](int tau, uint4& A, uint4& B) {
                    A.x = f16x2_to_bf16x2(A.x); B.x = f16x2_to_bf16x2(B.x); A.y = f16x2_to_bf16x2(A.y); B.y = f16x2_to_bf16x2(B.y);
                    A.z = f16x2_to_bf16x2(A.z); B.z = f16x2_to_bf16x2(B.z);
                    sts128(sb + O_MF + tau * 3072 + c * 512 + l16, A.x, B.x, A.y, B.y);
                    sts64(sb + O_MF + tau * 3072 + 2048 + (c >> 1) * 512 + (c & 1) * 8 + l16, A.z, B.z);
                };
                const uint32_t ok0 = __all_sync(~0u, (v[0].w & v[1].w) == 0x5000u);
                convert(0, v[0], v[1]);
                asm volatile("{\n.reg .pred p;\nsetp.ne.u32 p, %0, 0;\n@p bar.arrive 2, 384;\n}" :: "r"(ok0) : "memory");
                sched_fence<0>(h);
                uint32_t ok1;
                asm volatile("{\n.reg .pred p, q;\n.reg .b32 x;\nlop3.b32 x, %1, %2, %3, 0x80;\nand.b32 x, x, %4;\n"
                             "setp.eq.u32 p, x, 0x5000;\nvote.sync.all.pred q, p, 0xffffffff;\nselp.u32 %0, 1, 0, q;\n}"
                             : "=r"(ok1) : "r"(v[2].w), "r"(v[3].w), "r"(v[4].w), "r"(v[5].w));
                convert(1, v[2], v[3]); convert(2, v[4], v[5]);
                asm volatile("{\n.reg .pred p;\nsetp.ne.u32 p, %0, 0;\n@p bar.arrive 15, 384;\n}" :: "r"(ok1) : "memory");
                if (ok0 & ok1) {
                    mmax = absmax2(absmax2(absmax2(v[0].x, v[0].y), absmax2(v[0].z, v[1].x)), absmax2(absmax2(v[1].y, v[1].z), absmax2(v[2].x, v[2].y)));
                    mmax = absmax2(mmax, absmax2(absmax2(absmax2(v[2].z, v[3].x), absmax2(v[3].y, v[3].z)), absmax2(absmax2(v[4].x, v[4].y), absmax2(v[4].z, v[5].x))));
                    mmax = absmax2(mmax, absmax2(v[5].y, v[5].z));
                } else {
                    const uint32_t bad1 = !__all_sync(~0u, (v[2].w & v[3].w) == 0x5000u), bad2 = !__all_sync(~0u, (v[4].w & v[5].w) == 0x5000u);
                    uint4 u[6];
                    asm volatile("{\n.reg .pred p0, p1, p2, q;\n.reg .u32 n, x;\nmov.u32 n, 0;\n"
                         "setp.eq.u32 p0, %26, 0;\nsetp.ne.u32 p1, %27, 0;\nsetp.ne.u32 p2, %28, 0;\n"
                         "mov.u32 %0, 0; mov.u32 %1, 0; mov.u32 %2, 0; mov.u32 %3, 0x5000; mov.u32 %4, 0; mov.u32 %5, 0; mov.u32 %6, 0; mov.u32 %7, 0x5000;\n"
                         "mov.u32 %8, 0; mov.u32 %9, 0; mov.u32 %10, 0; mov.u32 %11, 0x5000; mov.u32 %12, 0; mov.u32 %13, 0; mov.u32 %14, 0; mov.u32 %15, 0x5000;\n"
                         "mov.u32 %16, 0; mov.u32 %17, 0; mov.u32 %18, 0; mov.u32 %19, 0x5000; mov.u32 %20, 0; mov.u32 %21, 0; mov.u32 %22, 0; mov.u32 %23, 0x5000;\n"
                         "R_%=: @p0 ld.relaxed.gpu.global.v4.u32 {%0,%1,%2,%3}, [%25];\n@p0 ld.relaxed.gpu.global.v4.u32 {%4,%5,%6,%7}, [%25+512];\n"
                         "@p1 ld.relaxed.gpu.global.v4.u32 {%8,%9,%10,%11}, [%25+8192];\n@p1 ld.relaxed.gpu.global.v4.u32 {%12,%13,%14,%15}, [%25+8704];\n"
                         "@p2 ld.relaxed.gpu.global.v4.u32 {%16,%17,%18,%19}, [%25+16384];\n@p2 ld.relaxed.gpu.global.v4.u32 {%20,%21,%22,%23}, [%25+16896];\n"
                         "add.u32 %24, %24, 1;\nand.b32 x, %3, %7;\nsetp.ne.u32 p0, x, 0x5000;\nand.b32 x, %11, %15;\nsetp.ne.u32 p1, x, 0x5000;\n"
                         "and.b32 x, %19, %23;\nsetp.ne.u32 p2, x, 0x5000;\nor.pred q, p0, p1;\nor.pred q, q, p2;\nvote.sync.any.pred q, q, 0xffffffff;\n@!q bra.uni K_%=;\n"
                         "add.u32 n, n, 1;\nsetp.lt.u32 q, n, 2000000;\n@q bra.uni R_%=;\ntrap;\nK_%=:\n}"
                         : "=&r"(u[0].x), "=&r"(u[0].y), "=&r"(u[0].z), "=&r"(u[0].w), "=&r"(u[1].x), "=&r"(u[1].y), "=&r"(u[1].z), "=&r"(u[1].w),
                           "=&r"(u[2].x), "=&r"(u[2].y), "=&r"(u[2].z), "=&r"(u[2].w), "=&r"(u[3].x), "=&r"(u[3].y), "=&r"(u[3].z), "=&r"(u[3].w),
                           "=&r"(u[4].x), "=&r"(u[4].y), "=&r"(u[4].z), "=&r"(u[4].w), "=&r"(u[5].x), "=&r"(u[5].y), "=&r"(u[5].z), "=&r"(u[5].w), "+r"(nretry)
                         : "l"(pbase), "r"(ok0), "r"(bad1), "r"(bad2) : "memory");
                    if (!ok0) { convert(0, u[0], u[1]); bar_arrive(2, 384); }
                    if (bad1) convert(1, u[2], u[3]);
                    if (bad2) convert(2, u[4], u[5]);
                    if (!ok1) bar_arrive(15, 384);
                    mmax = 0;
#pragma unroll
                    for (int tau = 0; tau < 3; tau++) {
                        const uint4 A = lds128(sb + O_MF + tau * 3072 + c * 512 + l16);
                        const float2 B = lds64f(sb + O_MF + tau * 3072 + 2048 + (c >> 1) * 512 + (c & 1) * 8 + l16);
                        mmax = absmax2(absmax2(mmax, absmax2(A.x, A.y)), absmax2(absmax2(A.z, A.w), absmax2(__float_as_uint(B.x), __float_as_uint(B.y))));
                    }
                }
                if (c == 0) STAMP(s, 12);
                if (c == 0) STAMPV(s, 14, nretry);
                mmax &= 0x7fff7fffu;
                mmax = max(mmax << 16, mmax & 0xffff0000u);
            }
            roff += 24576;
        }
        {
            bar_sync(7, 384);
            if (c == 0) flag_inc_if(l16c, &g_flag[F_QKV + (60 + (h >> 3)) * 8]);
        }
    }
    if (warp == 8) PSTAMP(13);
    cluster_sync();
}

constexpr int NST = 10;
constexpr int G_RING = 0, G_EX = NST * 16384, G_OUT = G_EX + 32768, G_CARRY = G_OUT + 32768, G_BAR = G_CARRY + 512, BG_SMEM = G_BAR + 256;
constexpr int GB_FULL = G_BAR, GB_EMPTY = G_BAR + 8 * NST, GB_W = G_BAR + 16 * NST;
static_assert(BG_SMEM <= 232448, "smem");

template <int ACC>
__device__ __forceinline__ void wgmma_n128_rs(float (&d)[64], uint32_t a0, uint32_t a1, uint32_t a2, uint32_t a3, uint64_t desc) {
    asm volatile("wgmma.mma_async.sync.aligned.m64n128k16.f32.bf16.bf16 "
        "{%0,%1,%2,%3,%4,%5,%6,%7,%8,%9,%10,%11,%12,%13,%14,%15,%16,%17,%18,%19,%20,%21,%22,%23,%24,%25,%26,%27,%28,%29,%30,%31,"
        "%32,%33,%34,%35,%36,%37,%38,%39,%40,%41,%42,%43,%44,%45,%46,%47,%48,%49,%50,%51,%52,%53,%54,%55,%56,%57,%58,%59,%60,%61,%62,%63}, "
        "{%64,%65,%66,%67}, %68, %69, 1, 1, 0;"
        : "+f"(d[0]), "+f"(d[1]), "+f"(d[2]), "+f"(d[3]), "+f"(d[4]), "+f"(d[5]), "+f"(d[6]), "+f"(d[7]),
          "+f"(d[8]), "+f"(d[9]), "+f"(d[10]), "+f"(d[11]), "+f"(d[12]), "+f"(d[13]), "+f"(d[14]), "+f"(d[15]),
          "+f"(d[16]), "+f"(d[17]), "+f"(d[18]), "+f"(d[19]), "+f"(d[20]), "+f"(d[21]), "+f"(d[22]), "+f"(d[23]),
          "+f"(d[24]), "+f"(d[25]), "+f"(d[26]), "+f"(d[27]), "+f"(d[28]), "+f"(d[29]), "+f"(d[30]), "+f"(d[31]),
          "+f"(d[32]), "+f"(d[33]), "+f"(d[34]), "+f"(d[35]), "+f"(d[36]), "+f"(d[37]), "+f"(d[38]), "+f"(d[39]),
          "+f"(d[40]), "+f"(d[41]), "+f"(d[42]), "+f"(d[43]), "+f"(d[44]), "+f"(d[45]), "+f"(d[46]), "+f"(d[47]),
          "+f"(d[48]), "+f"(d[49]), "+f"(d[50]), "+f"(d[51]), "+f"(d[52]), "+f"(d[53]), "+f"(d[54]), "+f"(d[55]),
          "+f"(d[56]), "+f"(d[57]), "+f"(d[58]), "+f"(d[59]), "+f"(d[60]), "+f"(d[61]), "+f"(d[62]), "+f"(d[63])
        : "r"(a0), "r"(a1), "r"(a2), "r"(a3), "l"(desc), "n"(ACC));
}
__device__ __forceinline__ void wait_flag(const unsigned* p, unsigned target) {
    asm volatile("{\n.reg .pred p;\n.reg .u32 n, v;\nmov.u32 n, 0;\n"
                 "W_%=: ld.acquire.gpu.global.u32 v, [%0];\nsub.u32 v, v, %1;\nsetp.ge.s32 p, v, 0;\n@p bra.uni D_%=;\nnanosleep.u32 100;\n"
                 "add.u32 n, n, 1;\nsetp.lt.u32 p, n, 4000000;\n@p bra.uni W_%=;\ntrap;\nD_%=:\n}" :: "l"(p), "r"(target) : "memory");
}
template <int NS, int STRIDE>
__device__ __forceinline__ void bg_mainloop(float (&d)[64], const uint32_t (&a)[144], uint32_t sb, int it, int lane) {
    int slot = it % NST, ph = (it / NST) & 1, prev = 0;
#pragma unroll
    for (int i = 0; i < NS; i++) {
        mbar_wait(sb + GB_FULL + 8 * slot, ph);
        const uint64_t desc = (uint64_t)(((sb + G_RING + slot * 16384) & 0x3FFFF) >> 4) | (1ull << 16) | (64ull << 32) | (1ull << 62);
        wg_fence();
#pragma unroll
        for (int k = 0; k < 4; k++) {
            const int u = 16 * i + 4 * k;
            if (i == 0 && k == 0) wgmma_n128_rs<0>(d, a[u], a[u + 1], a[u + 2], a[u + 3], desc);
            else wgmma_n128_rs<1>(d, a[u], a[u + 1], a[u + 2], a[u + 3], desc + 2 * k);
        }
        wg_commit();
        if (i > 0) {
            asm volatile("wgmma.wait_group.sync.aligned 1;" ::: "memory");
            mbar_arrive_if(lane, sb + GB_EMPTY + 8 * prev);
        }
        prev = slot;
        slot += STRIDE;
        if (slot >= NST) { slot -= NST; ph ^= 1; }
    }
    wg_wait0();
    mbar_arrive_if(lane, sb + GB_EMPTY + 8 * prev);
}
template <bool SKIP>
__device__ __forceinline__ void bg_epilogue(float (&d)[64], uint32_t sb, int wg, int w, int lane, const CUtensorMap* tm_out, int col0, int tok0,
                                            const __nv_bfloat16* xa, const __nv_bfloat16* Dk) {
    const int g = lane >> 2, t = lane & 3;
    const uint32_t ex = sb + G_EX + w * 4096 + lane * 16;
    float k[32];
    if (wg == 0) {
#pragma unroll
        for (int q = 0; q < 8; q++) sts128f(ex + q * 512, d[32 + 4 * q], d[32 + 4 * q + 1], d[32 + 4 * q + 2], d[32 + 4 * q + 3]);
#pragma unroll
        for (int i = 0; i < 32; i++) k[i] = d[i];
    } else {
#pragma unroll
        for (int q = 0; q < 8; q++) sts128f(ex + 16384 + q * 512, d[4 * q], d[4 * q + 1], d[4 * q + 2], d[4 * q + 3]);
#pragma unroll
        for (int i = 0; i < 32; i++) k[i] = d[32 + i];
    }
    uint32_t xv[16], dv = 0;
    if (SKIP) {
        const __nv_bfloat16* xp = xa + (size_t)(tok0 + 64 * wg + 2 * t) * DM + col0 + 16 * w + 2 * g;
#pragma unroll
        for (int i = 0; i < 16; i++) xv[i] = ldg_nc32(xp + (8 * (i >> 1) + (i & 1)) * DM);
        dv = ldg_nc32(Dk + col0 + 16 * w + 2 * g);
    }
    if (SKIP && w == 0) asm volatile("cp.async.bulk.wait_group.read 0;" ::: "memory");
    bar_sync(1, 256);
#pragma unroll
    for (int q = 0; q < 8; q++) {
        const float4 o = lds128f(ex + (wg ^ 1) * 16384 + q * 512);
        k[4 * q] += o.x; k[4 * q + 1] += o.y; k[4 * q + 2] += o.z; k[4 * q + 3] += o.w;
    }
    if (SKIP) bar_sync(1, 256); else bar_sync(13, 288);
    const uint32_t ob = sb + G_OUT + wg * 16384 + (w >> 1) * 8192 + (g & 1) * 8;
    const uint32_t ch = (w & 1) * 4 + (g >> 1);
#pragma unroll
    for (int i = 0; i < 16; i++) {
        float v0 = k[4 * (i >> 1) + (i & 1)], v1 = k[4 * (i >> 1) + 2 + (i & 1)];
        if (SKIP) {
            const uint32_t p = pack_bf16(__uint_as_float(xv[i] << 16) * __uint_as_float(dv << 16), __uint_as_float(xv[i] & 0xffff0000u) * __uint_as_float(dv & 0xffff0000u));
            v0 += __uint_as_float(p << 16); v1 += __uint_as_float(p & 0xffff0000u);
        }
        const uint32_t n7 = 2 * t + (i & 1);
        sts64(ob + (8 * (i >> 1) + n7) * 128 + ((ch ^ n7) << 4), __float_as_uint(v0), __float_as_uint(v1));
    }
    fence_async_smem();
    if (SKIP) {
        bar_sync(4 + wg, 128);
        if (w == 0)
            asm volatile("{\n.reg .pred p;\nelect.sync _|p, 0xffffffff;\n"
                "@p cp.async.bulk.tensor.2d.global.shared::cta.bulk_group [%0, {%2, %4}], [%1];\n"
                "@p cp.async.bulk.tensor.2d.global.shared::cta.bulk_group [%0, {%3, %4}], [%1+8192];\n@p cp.async.bulk.commit_group;\n}"
                :: "l"(tm_out), "r"(sb + G_OUT + wg * 16384), "r"(col0), "r"(col0 + 32), "r"(tok0 + 64 * wg) : "memory");
    } else {
        bar_arrive(12, 288);
    }
}
__device__ __forceinline__ void s5_channel(int p, const __nv_bfloat16* Lre, const __nv_bfloat16* Lim, const __nv_bfloat16* logdt, float2& lam, float2& coef) {
    const float dt = __bfloat162float(__float2bfloat16(expf(__bfloat162float(logdt[p]))));
    const float lr = __bfloat162float(Lre[p]), li = __bfloat162float(Lim[p]);
    const float e = expf(dt * lr);
    float sn, cs;
    sincosf(dt * li, &sn, &cs);
    lam = make_float2(e * cs, e * sn);
    const float den = lr * lr + li * li;
    coef = make_float2(((lam.x - 1.f) * lr + lam.y * li) / den, (lam.y * lr - (lam.x - 1.f) * li) / den);
}
__device__ __forceinline__ float2 cfma(float2 a, float2 b, float2 c) {
    return make_float2(fmaf(a.x, b.x, fmaf(-a.y, b.y, c.x)), fmaf(a.x, b.y, fmaf(a.y, b.x, c.y)));
}
__device__ __forceinline__ uint4 ldg128(const void* p) { uint4 v; asm volatile("ld.global.v4.u32 {%0,%1,%2,%3}, [%4];" : "=r"(v.x), "=r"(v.y), "=r"(v.z), "=r"(v.w) : "l"(p) : "memory"); return v; }
__device__ __forceinline__ uint2 ldg64(const void* p) { uint2 v; asm volatile("ld.global.v2.u32 {%0,%1}, [%2];" : "=r"(v.x), "=r"(v.y) : "l"(p) : "memory"); return v; }

__device__ __forceinline__ void bg_attention(uint32_t st0, uint32_t st1, int mt, int lane) {
    const int g = lane >> 2, t = lane & 3;
    float sc[5][4];
#pragma unroll
    for (int n = 0; n < 5; n++) sc[n][0] = sc[n][1] = sc[n][2] = sc[n][3] = 0.f;
    float sm2[4] = {0.f, 0.f, 0.f, 0.f};
#pragma unroll
    for (int i = 0; i < 8; i++) {
        const uint32_t st = (i >> 2 ? st1 : st0) + (i & 3) * 512 + lane * 16;
        const uint4 q = ldsm4(st + mt * 2048), km = ldsm4(st + 8192), k0 = ldsm4(st + 4096);
        mma16816(sc[0], q.x, q.y, q.z, q.w, km.x, km.y);
        mma16816(sm2, q.x, q.y, q.z, q.w, km.z, km.w);
        mma16816(sc[1], q.x, q.y, q.z, q.w, k0.x, k0.y);
        mma16816(sc[2], q.x, q.y, q.z, q.w, k0.z, k0.w);
        if (mt) {
            const uint4 k1 = ldsm4(st + 6144);
            mma16816(sc[3], q.x, q.y, q.z, q.w, k1.x, k1.y);
            mma16816(sc[4], q.x, q.y, q.z, q.w, k1.z, k1.w);
        }
    }
#pragma unroll
    for (int i = 0; i < 4; i++) sc[0][i] += sm2[i];
    const int q0 = 16 * mt + 8 + g - 2 * t;
#pragma unroll
    for (int n = 1; n < 5; n++) {
        if (8 * n > q0) sc[n][0] = -INFINITY;
        if (8 * n + 1 > q0) sc[n][1] = -INFINITY;
        if (8 * n > q0 + 8) sc[n][2] = -INFINITY;
        if (8 * n + 1 > q0 + 8) sc[n][3] = -INFINITY;
    }
    float ma = fmaxf(sc[0][0], sc[0][1]), mb = fmaxf(sc[0][2], sc[0][3]);
#pragma unroll
    for (int n = 1; n < 5; n++) { ma = fmaxf(ma, fmaxf(sc[n][0], sc[n][1])); mb = fmaxf(mb, fmaxf(sc[n][2], sc[n][3])); }
    ma = quad_max(ma) * SM_SCALE; mb = quad_max(mb) * SM_SCALE;
    uint32_t Pa[5], Pb[5];
#pragma unroll
    for (int n = 0; n < 5; n++) {
        Pa[n] = pack_bf16(ex2(fmaf(sc[n][0], SM_SCALE, -ma)), ex2(fmaf(sc[n][1], SM_SCALE, -ma)));
        Pb[n] = pack_bf16(ex2(fmaf(sc[n][2], SM_SCALE, -mb)), ex2(fmaf(sc[n][3], SM_SCALE, -mb)));
    }
    float sa[4], sbb[4];
    mma1688_z(sa, ONES, ONES, Pa[0]); mma1688_z(sbb, ONES, ONES, Pb[0]);
    mma16816(sa, ONES, ONES, ONES, ONES, Pa[1], Pa[2]); mma16816(sbb, ONES, ONES, ONES, ONES, Pb[1], Pb[2]);
    mma16816(sa, ONES, ONES, ONES, ONES, Pa[3], Pa[4]); mma16816(sbb, ONES, ONES, ONES, ONES, Pb[3], Pb[4]);
    const float ra0 = rcp_fast(sa[0]), ra1 = rcp_fast(sa[1]), rb0 = rcp_fast(sbb[0]), rb1 = rcp_fast(sbb[1]);
    const uint32_t row = lane & 7;
    const uint32_t so = mt * 2048 + (lane >> 4) * 1024 + row * 128;
#pragma unroll
    for (int i = 0; i < 8; i++) {
        const uint32_t st = i >> 2 ? st1 : st0;
        const int e4 = i & 3;
        const float2 vmf = lds64f(st + 14336 + e4 * 256 + lane * 8);
        const uint32_t vm0 = __float_as_uint(vmf.x), vm1 = __float_as_uint(vmf.y);
        const uint4 v0 = lds128(st + 10240 + e4 * 1024 + lane * 16);
        float oa[4], ob[4];
        mma1688_z(oa, vm0, vm1, Pa[0]); mma1688_z(ob, vm0, vm1, Pb[0]);
        mma16816(oa, v0.x, v0.y, v0.z, v0.w, Pa[1], Pa[2]);
        mma16816(ob, v0.x, v0.y, v0.z, v0.w, Pb[1], Pb[2]);
        if (mt) {
            const uint4 v1 = lds128(st + 10240 + e4 * 1024 + 512 + lane * 16);
            mma16816(oa, v1.x, v1.y, v1.z, v1.w, Pa[3], Pa[4]);
            mma16816(ob, v1.x, v1.y, v1.z, v1.w, Pb[3], Pb[4]);
        }
        stsm4t(st + so + (((2 * e4 + ((lane >> 3) & 1)) ^ row) << 4), pack_bf16(oa[0] * ra0, oa[1] * ra1), pack_bf16(oa[2] * ra0, oa[3] * ra1),
               pack_bf16(ob[0] * rb0, ob[1] * rb1), pack_bf16(ob[2] * rb0, ob[3] * rb1));
    }
}
__device__ __forceinline__ bool bg_att_turn(int na, int ng) { return na == ng || (na == ng + 1 && na <= BG_AHEAD); }

__global__ void __launch_bounds__(384, 1)
bg_kernel(const __grid_constant__ CUtensorMap tm_xa, const __grid_constant__ CUtensorMap tm_wo, const __grid_constant__ CUtensorMap tm_out,
          const __nv_bfloat16* __restrict__ xa, const __nv_bfloat16* __restrict__ Lre, const __nv_bfloat16* __restrict__ Lim,
          const __nv_bfloat16* __restrict__ Bre, const __nv_bfloat16* __restrict__ Bim, const __nv_bfloat16* __restrict__ Cre,
          const __nv_bfloat16* __restrict__ Cim, const __nv_bfloat16* __restrict__ logdt, const __nv_bfloat16* __restrict__ Dk) {
    extern __shared__ __align__(1024) uint8_t smem_raw[];
    const uint32_t sb = smem_u32(smem_raw);
    const int lane = threadIdx.x & 31;
    const int warp = __shfl_sync(~0u, threadIdx.x >> 5, 0);
    const int wg = warp >> 2, w = warp & 3, b = blockIdx.x;
    const int nt = b % 9, kq = b / 9;
    BSTAMP(0);
    if (threadIdx.x == 0) {
        if (sb & 1023u) __trap();
        for (int i = 0; i < NST; i++) { mbar_init(sb + GB_FULL + 8 * i, 1); mbar_init(sb + GB_EMPTY + 8 * i, 4); }
        mbar_init(sb + GB_W, 1);
        asm volatile("fence.mbarrier_init.release.cluster;" ::: "memory");
        mbar_expect(sb + GB_W, (b < 18 ? 64 : 128) * 1152);
        sts32(sb + G_BAR + 248, atomicAdd(&g_ticket_bg, 1u) / 36u + 1u);
    }
    __syncthreads();
    if (wg == 2) {
        asm volatile("setmaxnreg.dec.sync.aligned.u32 24;");
        if (w == 0) {
            int slot = 0, ph = 1;
            unsigned tlast = clk();
            auto pace = [&]() { if (BG_PACE) { spin_until(tlast, BG_PACE); tlast = clk(); } };
            auto next = [&]() { if (++slot == NST) { slot = 0; ph ^= 1; } };
            bar_sync(6, 288);
            if (b < 18) {
#pragma unroll 1
                for (int i = 0; i < 144; i++) {
                    const int blk = i / 9, kb = i - 9 * blk, it = (blk >> 1) * 18 + (blk & 1) + 2 * kb;
                    slot = it % NST;
                    mbar_wait(sb + GB_EMPTY + 8 * slot, ((it / NST) & 1) ^ 1);
                    pace();
                    asm volatile("{\n.reg .pred p;\nelect.sync _|p, 0xffffffff;\n@p mbarrier.arrive.expect_tx.shared::cta.b64 _, [%2], 16384;\n"
                        "@p cp.async.bulk.tensor.5d.shared::cluster.global.mbarrier::complete_tx::bytes [%0], [%1, {%3, %4, %4, %4, %5}], [%2];\n}"
                        :: "r"(sb + G_RING + slot * 16384), "l"(&tm_xa), "r"(sb + GB_FULL + 8 * slot), "r"(kb * 64), "r"(0), "r"(blk) : "memory");
                }
                slot = 144 % NST; ph = ((144 / NST) & 1) ^ 1;
            }
            const unsigned ep = lds32(sb + G_BAR + 248);
            auto slabs = [&](const char* src, int ns) {
                asm volatile("fence.proxy.async.global;" ::: "memory");
#pragma unroll 1
                for (int i = 0; i < ns; i++) {
                    mbar_wait(sb + GB_EMPTY + 8 * slot, ph);
                    pace();
                    asm volatile("{\n.reg .pred p;\nelect.sync _|p, 0xffffffff;\n@p mbarrier.arrive.expect_tx.shared::cta.b64 _, [%2], 16384;\n"
                        "@p cp.async.bulk.shared::cluster.global.mbarrier::complete_tx::bytes [%0], [%1], 16384, [%2];\n}"
                        :: "r"(sb + G_RING + slot * 16384), "l"(src + (size_t)((i & 1) * (ns >> 1) + (i >> 1)) * (SEQ * 128)), "r"(sb + GB_FULL + 8 * slot) : "memory");
                    next();
                }
            };
            if (b >= 18) {
#pragma unroll 1
                for (int blk = kq - 2; blk < 16; blk += 2) {
                    wait_flag(&g_flag[F_H + blk * 8], 18 * ep);
                    slabs(reinterpret_cast<const char*>(g_h) + blk * 16384, 18);
                }
            }
            bar_sync(6, 288);
#pragma unroll 1
            for (int na = 0, ng = 0; ng < 16;) {
                if (bg_att_turn(na, ng)) {
                    if (nt < 8) {
                        wait_flag(&g_flag[F_QKV + (na * 4 + kq) * 8], 24 * ep);
                        asm volatile("fence.proxy.async.global;" ::: "memory");
#pragma unroll 1
                        for (int i = 0; i < 8; i++) {
                            const int pr = nt * 4 + 2 * (i & 1) + (i >> 2), hf = (i >> 1) & 1;
                            const char* rec = reinterpret_cast<const char*>(g_qkv) + (size_t)((4 * na + (pr >> 3)) * NH + 8 * kq + (pr & 7)) * REC;
                            mbar_wait(sb + GB_EMPTY + 8 * slot, ph);
                    pace();
                            asm volatile("{\n.reg .pred p;\nelect.sync _|p, 0xffffffff;\n@p mbarrier.arrive.expect_tx.shared::cta.b64 _, [%4], 15360;\n"
                                "@p cp.async.bulk.shared::cluster.global.mbarrier::complete_tx::bytes [%0], [%1], 10240, [%4];\n"
                                "@p cp.async.bulk.shared::cluster.global.mbarrier::complete_tx::bytes [%0+10240], [%2], 4096, [%4];\n"
                                "@p cp.async.bulk.shared::cluster.global.mbarrier::complete_tx::bytes [%0+14336], [%3], 1024, [%4];\n}"
                                :: "r"(sb + G_RING + slot * 16384), "l"(rec + hf * 10240), "l"(rec + 20480 + hf * 4096), "l"(rec + 28672 + hf * 1024),
                                   "r"(sb + GB_FULL + 8 * slot) : "memory");
                            next();
                        }
                    }
                    na++;
                } else {
                    wait_flag(&g_flag[F_OX + (ng * 4 + kq) * 8], 8 * ep);
                    slabs(reinterpret_cast<const char*>(g_ox) + (size_t)kq * 16 * SEQ * 128 + ng * 16384, 16);
                    ng++;
                }
            }
        } else if (w == 1) {
            if (b < 18) {
#pragma unroll 1
                for (int blk = 0; blk < 16; blk++) {
                    bar_sync(8 + (blk & 1), 160);
                    asm volatile("{\n.reg .pred p;\nelect.sync _|p, 0xffffffff;\n@p cp.async.bulk.global.shared::cta.bulk_group [%0], [%1], 16384;\n"
                        "@p cp.async.bulk.commit_group;\ncp.async.bulk.wait_group 0;\nfence.proxy.async.global;\n}"
                        :: "l"(reinterpret_cast<char*>(g_h) + ((size_t)b * SEQ + blk * 128) * 128), "r"(sb + G_OUT + (blk & 1) * 16384) : "memory");
                    bar_arrive(10 + (blk & 1), 160);
                    flag_inc_if(lane, &g_flag[F_H + blk * 8]);
                }
            }
            if (nt < 8) {
                int it = 144;
#pragma unroll 1
                for (int na = 0, ng = 0; ng < 16;) {
                    if (bg_att_turn(na, ng)) {
                        bar_sync(7, 288);
                        if (lane < 8) {
                            const int pr = nt * 4 + 2 * (lane & 1) + (lane >> 2), hf = (lane >> 1) & 1;
                            asm volatile("cp.async.bulk.global.shared::cta.bulk_group [%0], [%1], 4096;\ncp.async.bulk.commit_group;\ncp.async.bulk.wait_group.read 0;\n"
                                "mbarrier.arrive.shared::cta.b64 _, [%2], 4;\ncp.async.bulk.wait_group 0;\nfence.proxy.async.global;"
                                :: "l"(reinterpret_cast<char*>(g_ox) + ((size_t)((8 * kq + (pr & 7)) * 2 + hf) * SEQ + (4 * na + (pr >> 3)) * 32) * 128),
                                   "r"(sb + G_RING + ((it + lane) % NST) * 16384), "r"(sb + GB_EMPTY + 8 * ((it + lane) % NST)) : "memory");
                        }
                        __syncwarp();
                        flag_inc_if(lane, &g_flag[F_OX + (na * 4 + kq) * 8]);
                        it += 8; na++;
                    } else { it += 16; ng++; }
                }
            }
        } else if (w == 2) {
            const unsigned ep = lds32(sb + G_BAR + 248);
#pragma unroll 1
            for (int blk = 0; blk < 16; blk++) {
                bar_arrive(13, 288);
                bar_sync(12, 288);
                if (kq) { wait_flag(&g_flag[F_OUT + (blk * 9 + nt) * 8], ep); asm volatile("fence.proxy.async.global;" ::: "memory"); }
                unsigned t0 = clk();
                if (blk < 15) spin_until(t0, b * (RED_GAP / 36));
#pragma unroll 1
                for (int i = 0; i < 4; i++) {
                    const uint32_t src = sb + G_OUT + i * 8192;
                    const int c0 = DM + 64 * nt + (i & 1) * 32, c1 = blk * 128 + (i >> 1) * 64;
                    if (kq) {
                        asm volatile("{\n.reg .pred p;\nelect.sync _|p, 0xffffffff;\n@p cp.reduce.async.bulk.tensor.2d.global.shared::cta.add.bulk_group [%0, {%2, %3}], [%1];\n}"
                            :: "l"(&tm_out), "r"(src), "r"(c0), "r"(c1) : "memory");
                        t0 = clk();
                        if (blk < 15 && i < 3) spin_until(t0, RED_GAP);
                    } else {
                        asm volatile("{\n.reg .pred p;\nelect.sync _|p, 0xffffffff;\n@p cp.async.bulk.tensor.2d.global.shared::cta.bulk_group [%0, {%2, %3}], [%1];\n}"
                            :: "l"(&tm_out), "r"(src), "r"(c0), "r"(c1) : "memory");
                    }
                }
                asm volatile("cp.async.bulk.commit_group;\ncp.async.bulk.wait_group 0;\nfence.proxy.async.global;" ::: "memory");
                __syncwarp();
                if (!kq) flag_inc_if(lane, &g_flag[F_OUT + (blk * 9 + nt) * 8]);
            }
        }
    } else {
        asm volatile("setmaxnreg.inc.sync.aligned.u32 240;");
        const int g = lane >> 2, t = lane & 3, tid = threadIdx.x;
        uint32_t a[144];
        float d[64];
        if (b < 18) {
            if (tid < 64)
                asm volatile("cp.async.bulk.shared::cluster.global.mbarrier::complete_tx::bytes [%0], [%1], 1152, [%2];"
                    :: "r"(sb + tid * 1168), "l"((tid < 32 ? Bre : Bim) + (size_t)(32 * b + (tid & 31)) * DM), "r"(sb + GB_W) : "memory");
            float2 lam, coef;
            s5_channel(32 * b + 8 * w + g, Lre, Lim, logdt, lam, coef);
            float2 l32 = lam;
#pragma unroll
            for (int i = 0; i < 5; i++) l32 = make_float2(l32.x * l32.x - l32.y * l32.y, 2.f * l32.x * l32.y);
            __syncwarp();
            mbar_wait(sb + GB_W, 0);
            const uint32_t ap = sb + (((lane >> 3) & 1) * 32 + 8 * w + (lane & 7)) * 1168 + (lane >> 4) * 16;
#pragma unroll
            for (int ks = 0; ks < 36; ks++) { const uint4 v = ldsm4(ap + ks * 32); a[4 * ks] = v.x; a[4 * ks + 1] = v.y; a[4 * ks + 2] = v.z; a[4 * ks + 3] = v.w; }
            bar_sync(1, 256);
            bar_arrive(6, 288);
            BSTAMP(1);
#pragma unroll 1
            for (int blk = wg; blk < 16; blk += 2) {
                bg_mainloop<9, 2>(d, a, sb, (blk >> 1) * 18 + wg, lane);
                float2 e = make_float2(0.f, 0.f);
#pragma unroll
                for (int i = 0; i < 32; i++) e = cfma(lam, e, make_float2(d[4 * (i >> 1) + (i & 1)], d[4 * (i >> 1) + 2 + (i & 1)]));
                float2 cin = make_float2(0.f, 0.f);
                if (blk > 0) { bar_sync(2 + (wg ^ 1), 256); cin = lds64f(sb + G_CARRY + (wg ^ 1) * 256 + (8 * w + g) * 8); }
                float2 mine = cin;
#pragma unroll
                for (int q = 0; q < 4; q++) {
                    const float2 eq = make_float2(__shfl_sync(~0u, e.x, (lane & 28) + q), __shfl_sync(~0u, e.y, (lane & 28) + q));
                    cin = cfma(l32, cin, eq);
                    if (t == q + 1) mine = cin;
                }
                if (blk < 15) {
                    if (t == 0) sts64(sb + G_CARRY + wg * 256 + (8 * w + g) * 8, __float_as_uint(cin.x), __float_as_uint(cin.y));
                    bar_arrive(2 + wg, 256);
                }
                const uint32_t hs = sb + G_OUT + wg * 16384 + t * 4096 + (g & 3) * 4;
                const uint32_t ch = 2 * w + (g >> 2);
                if (blk >= 2) bar_sync(10 + wg, 160);
#pragma unroll
                for (int i = 0; i < 32; i++) {
                    mine = cfma(lam, mine, make_float2(d[4 * (i >> 1) + (i & 1)], d[4 * (i >> 1) + 2 + (i & 1)]));
                    sts32(hs + i * 128 + ((ch ^ (i & 7)) << 4), pack_bf16(mine.x, mine.y));
                }
                fence_async_smem();
                bar_arrive(8 + wg, 160);
            }
            bar_sync(10 + wg, 160);
        } else {
            if (tid < 128)
                asm volatile("cp.async.bulk.shared::cluster.global.mbarrier::complete_tx::bytes [%0], [%1], 1152, [%2];"
                    :: "r"(sb + tid * 1168), "l"((tid < 64 ? Cre : Cim) + (size_t)(64 * nt + (tid & 63)) * DM), "r"(sb + GB_W) : "memory");
            for (int p = tid; p < DM; p += 256) {
                float2 lam, coef;
                s5_channel(p, Lre, Lim, logdt, lam, coef);
                sts64(sb + G_EX + p * 8, __float_as_uint(2.f * coef.x), __float_as_uint(2.f * coef.y));
            }
            bar_sync(1, 256);
            mbar_wait(sb + GB_W, 0);
            const uint32_t cp = sb + (16 * w + 2 * g) * 1168 + (288 * wg + t) * 2;
#pragma unroll
            for (int u = 0; u < 72; u++) {
                const float2 c2 = lds64f(sb + G_EX + (288 * wg + 4 * u + t) * 8);
#pragma unroll
                for (int f = 0; f < 2; f++) {
                    unsigned short r16, i16;
                    asm volatile("ld.shared.u16 %0, [%1];" : "=h"(r16) : "r"(cp + f * 1168 + u * 8) : "memory");
                    asm volatile("ld.shared.u16 %0, [%1];" : "=h"(i16) : "r"(cp + (64 + f) * 1168 + u * 8) : "memory");
                    const float cr = __uint_as_float((uint32_t)r16 << 16), ci = __uint_as_float((uint32_t)i16 << 16);
                    a[2 * u + f] = pack_bf16(cr * c2.x - ci * c2.y, -(cr * c2.y + ci * c2.x));
                }
            }
            bar_sync(1, 256);
            bar_arrive(6, 288);
            BSTAMP(1);
#pragma unroll 1
            for (int j = 0; j < 8; j++) {
                bg_mainloop<9, 2>(d, a, sb, j * 18 + wg, lane);
                bg_epilogue<true>(d, sb, wg, w, lane, &tm_out, 64 * nt, (2 * j + kq - 2) * 128, xa, Dk);
            }
        }
        if (w == 0) asm volatile("cp.async.bulk.wait_group 0;" ::: "memory");
        bar_sync(1, 256);
        BSTAMP(2);
        if (warp == 0)
            asm volatile("{\n.reg .pred p;\nelect.sync _|p, 0xffffffff;\n@p mbarrier.arrive.expect_tx.shared::cta.b64 _, [%2], 131072;\n"
                "@p cp.async.bulk.tensor.2d.shared::cluster.global.mbarrier::complete_tx::bytes [%0], [%1, {%3, %4}], [%2];\n"
                "@p cp.async.bulk.tensor.2d.shared::cluster.global.mbarrier::complete_tx::bytes [%0+32768], [%1, {%3, %5}], [%2];\n"
                "@p cp.async.bulk.tensor.2d.shared::cluster.global.mbarrier::complete_tx::bytes [%0+65536], [%1, {%3, %6}], [%2];\n"
                "@p cp.async.bulk.tensor.2d.shared::cluster.global.mbarrier::complete_tx::bytes [%0+98304], [%1, {%3, %7}], [%2];\n}"
                :: "r"(sb), "l"(&tm_wo), "r"(sb + GB_W), "r"(64 * nt), "r"(1024 * kq), "r"(1024 * kq + 256), "r"(1024 * kq + 512), "r"(1024 * kq + 768) : "memory");
        mbar_wait(sb + GB_W, 1);
        {
            const uint32_t base = sb + wg * 65536 + 4 * t * 128 + (g & 3) * 4, ch = 2 * w + (g >> 2), r7 = (4 * t) & 7;
#pragma unroll
            for (int ks = 0; ks < 32; ks++) {
                const uint32_t w0 = lds32(base + ks * 2048 + ((ch ^ r7) << 4)), w1 = lds32(base + ks * 2048 + 256 + ((ch ^ (r7 + 2)) << 4));
                const uint32_t w2 = lds32(base + ks * 2048 + 128 + ((ch ^ (r7 + 1)) << 4)), w3 = lds32(base + ks * 2048 + 384 + ((ch ^ (r7 + 3)) << 4));
                a[4 * ks] = __byte_perm(w0, w1, 0x5410); a[4 * ks + 1] = __byte_perm(w0, w1, 0x7632);
                a[4 * ks + 2] = __byte_perm(w2, w3, 0x5410); a[4 * ks + 3] = __byte_perm(w2, w3, 0x7632);
            }
        }
        bar_sync(1, 256);
        bar_arrive(6, 288);
        BSTAMP(3);
#pragma unroll 1
        for (int na = 0, ng = 0, it = 144; ng < 16;) {
            if (bg_att_turn(na, ng)) {
                if (nt < 8) {
                    const int i0 = it + wg + 4 * (w >> 1), i1 = i0 + 2;
                    mbar_wait(sb + GB_FULL + 8 * (i0 % NST), (i0 / NST) & 1);
                    mbar_wait(sb + GB_FULL + 8 * (i1 % NST), (i1 / NST) & 1);
                    BSTAMP(8 + na * 4);
                    bg_attention(sb + G_RING + (i0 % NST) * 16384, sb + G_RING + (i1 % NST) * 16384, w & 1, lane);
                    fence_async_smem();
                    bar_arrive(7, 288);
                    bar_sync(1, 256);
                    BSTAMP(9 + na * 4);
                    it += 8;
                }
                na++;
            } else {
                bg_mainloop<8, 2>(d, a, sb, it + wg, lane);
                BSTAMP(10 + ng * 4);
                bg_epilogue<false>(d, sb, wg, w, lane, &tm_out, DM + 64 * nt, ng * 128, xa, Dk);
                BSTAMP(11 + ng * 4);
                it += 16; ng++;
            }
        }
    }
    asm volatile("griddepcontrol.wait;" ::: "memory");
}

typedef CUresult (*EncodeFn)(CUtensorMap*, CUtensorMapDataType, cuuint32_t, void*, const cuuint64_t*, const cuuint64_t*, const cuuint32_t*, const cuuint32_t*,
                             CUtensorMapInterleave, CUtensorMapSwizzle, CUtensorMapL2promotion, CUtensorMapFloatOOBfill);
}

extern "C" void kernel_launch(void* const* d_in, const int* in_sizes, int n_in, void* d_out, int out_size) {
    typedef const __nv_bfloat16* bp;
    bp Ax = (bp)d_in[0], Lre = (bp)d_in[1], Lim = (bp)d_in[2], Bre = (bp)d_in[3], Bim = (bp)d_in[4], Cre = (bp)d_in[5], Cim = (bp)d_in[6],
       logdt = (bp)d_in[7], Dk = (bp)d_in[8], Bx = (bp)d_in[9], mem0 = (bp)d_in[10], Wq = (bp)d_in[11], Wk = (bp)d_in[12], Wv = (bp)d_in[13], Wo = (bp)d_in[14];
    float* out = (float*)d_out;
    static EncodeFn enc = nullptr;
    if (!enc) {
        void* fn = nullptr; cudaDriverEntryPointQueryResult qr;
        cudaGetDriverEntryPoint("cuTensorMapEncodeTiled", &fn, cudaEnableDefault, &qr);
        enc = (EncodeFn)fn;
        cudaFuncSetAttribute(chain_kernel, cudaFuncAttributeMaxDynamicSharedMemorySize, CHAIN_SMEM);
        cudaFuncSetAttribute(bg_kernel, cudaFuncAttributeMaxDynamicSharedMemorySize, BG_SMEM);
    }
    const cuuint32_t es[5] = {1, 1, 1, 1, 1};
    auto map2d = [&](CUtensorMap* tm, CUtensorMapDataType dt, const void* p, cuuint64_t d0, cuuint64_t d1, cuuint64_t stride, cuuint32_t b0, cuuint32_t b1) {
        cuuint64_t gd[2] = {d0, d1}, gs[1] = {stride}; cuuint32_t bd[2] = {b0, b1};
        enc(tm, dt, 2, (void*)p, gd, gs, bd, es, CU_TENSOR_MAP_INTERLEAVE_NONE, CU_TENSOR_MAP_SWIZZLE_128B, CU_TENSOR_MAP_L2_PROMOTION_L2_128B,
            CU_TENSOR_MAP_FLOAT_OOB_FILL_NONE);
    };
    CUtensorMap tm_x, tm_q, tm_k, tm_v, tm_xa, tm_wo, tm_out;
    map2d(&tm_x, CU_TENSOR_MAP_DATA_TYPE_BFLOAT16, Bx, DM, SEQ, DM * 2, 64, 32);
    map2d(&tm_q, CU_TENSOR_MAP_DATA_TYPE_BFLOAT16, Wq, HD, DM, HD * 2, 64, 192);
    map2d(&tm_k, CU_TENSOR_MAP_DATA_TYPE_BFLOAT16, Wk, HD, DM, HD * 2, 64, 192);
    map2d(&tm_v, CU_TENSOR_MAP_DATA_TYPE_BFLOAT16, Wv, HD, DM, HD * 2, 64, 192);
    map2d(&tm_wo, CU_TENSOR_MAP_DATA_TYPE_BFLOAT16, Wo, DM, HD, DM * 2, 64, 256);
    map2d(&tm_out, CU_TENSOR_MAP_DATA_TYPE_FLOAT32, out, 2 * DM, SEQ, 2 * DM * 4, 32, 64);
    {
        cuuint64_t gd[5] = {DM, 2, 4, 16, 16}, gs[4] = {DM * 2, 32 * DM * 2, 2 * DM * 2, 128 * DM * 2}; cuuint32_t bd[5] = {64, 2, 4, 16, 1};
        enc(&tm_xa, CU_TENSOR_MAP_DATA_TYPE_BFLOAT16, 5, (void*)Ax, gd, gs, bd, es, CU_TENSOR_MAP_INTERLEAVE_NONE, CU_TENSOR_MAP_SWIZZLE_128B,
            CU_TENSOR_MAP_L2_PROMOTION_L2_128B, CU_TENSOR_MAP_FLOAT_OOB_FILL_NONE);
    }
    cudaStream_t st = cudaStreamPerThread;
    chain_kernel<<<96, 384, CHAIN_SMEM, st>>>(tm_x, tm_q, tm_k, tm_v, Bx, mem0, Wo);
    cudaLaunchConfig_t cfg = {};
    cfg.gridDim = dim3(36); cfg.blockDim = dim3(384); cfg.dynamicSmemBytes = BG_SMEM; cfg.stream = st;
    cudaLaunchAttribute at[1];
    at[0].id = cudaLaunchAttributeProgrammaticStreamSerialization; at[0].val.programmaticStreamSerializationAllowed = 1;
    cfg.attrs = at; cfg.numAttrs = 1;
    cudaLaunchKernelEx(&cfg, bg_kernel, tm_xa, tm_wo, tm_out, Ax, Lre, Lim, Bre, Bim, Cre, Cim, logdt, Dk);
}
```

```cpp
#include <cuda_runtime.h>
#include <cuda.h>
#include <cuda_bf16.h>
#include <cuda_fp16.h>
#include <stdint.h>

#define D_WAIT 720

#define BG_PACE 0
#define RED_GAP 720
#define ACC_PF 1
#define QDEP 0
#define PUB_MASK 0x1111010101011000ull
#define EARLY5 0
#define BG_AHEAD 5

namespace {

constexpr int DM = 576, NH = 32, SEQ = 2048, NSEG = 64, HD = 4096;

__device__ uint4 g_acc_raw[64 * 96 * 16 + 131072];
__device__ uint4 g_ox[NH * 2 * SEQ * 8];
constexpr int REC = 30720;
__device__ uint4 g_qkv[NSEG * NH * (REC / 16)];
__device__ uint4 g_h[18 * SEQ * 8];
constexpr int NFLAG = 4096, F_QKV = 0, F_OX = 512, F_H = 1024, F_OUT = 2048;
__device__ unsigned g_flag[NFLAG];
__device__ unsigned g_ticket, g_ticket_bg;
__device__ unsigned long long g_norm[96];
#define BSTAMP(i) do {} while (0)

__device__ __forceinline__ uint32_t smem_u32(const void* p) { return (uint32_t)__cvta_generic_to_shared(p); }
__device__ __forceinline__ uint32_t mapa(uint32_t a, uint32_t r) { uint32_t o; asm("mapa.shared::cluster.u32 %0, %1, %2;" : "=r"(o) : "r"(a), "r"(r)); return o; }
__device__ __forceinline__ uint32_t mapa_v(uint32_t a, uint32_t r) { uint32_t o; asm volatile("mapa.shared::cluster.u32 %0, %1, %2;" : "=r"(o) : "r"(a), "r"(r)); return o; }
__device__ __forceinline__ unsigned clk() { unsigned long long c; asm volatile("mov.u64 %0, %%clock64;" : "=l"(c) :: "memory"); return (unsigned)c; }
__device__ __forceinline__ void mbar_init(uint32_t bar, uint32_t cnt) { asm volatile("mbarrier.init.shared::cta.b64 [%0], %1;" :: "r"(bar), "r"(cnt) : "memory"); }
__device__ __forceinline__ void mbar_expect(uint32_t bar, uint32_t bytes) { asm volatile("mbarrier.arrive.expect_tx.shared::cta.b64 _, [%0], %1;" :: "r"(bar), "r"(bytes) : "memory"); }
__device__ __forceinline__ void mbar_wait(uint32_t bar, uint32_t parity) {
    asm volatile("{\n.reg .pred p;\n.reg .u32 n;\nmov.u32 n, 0;\n"
                 "W_%=: mbarrier.try_wait.parity.shared::cta.b64 p, [%0], %1;\n@p bra.uni D_%=;\n"
                 "add.u32 n, n, 1;\nsetp.lt.u32 p, n, 4000000;\n@p bra.uni W_%=;\ntrap;\nD_%=:\n}" :: "r"(bar), "r"(parity) : "memory");
}
__device__ __forceinline__ void mbar_expect_if(uint32_t z, uint32_t bar, uint32_t bytes) {
    asm volatile("{\n.reg .pred p;\nsetp.eq.u32 p, %2, 0;\n@p mbarrier.arrive.expect_tx.shared::cta.b64 _, [%0], %1;\n}" :: "r"(bar), "r"(bytes), "r"(z) : "memory");
}
__device__ __forceinline__ void mbar_arrive_if(uint32_t z, uint32_t bar) {
    asm volatile("{\n.reg .pred p;\nsetp.eq.u32 p, %1, 0;\n@p mbarrier.arrive.shared::cta.b64 _, [%0];\n}" :: "r"(bar), "r"(z) : "memory");
}
__device__ __forceinline__ void sts32_if(uint32_t z, uint32_t a, uint32_t x) {
    asm volatile("{\n.reg .pred p;\nsetp.eq.u32 p, %2, 0;\n@p st.shared.u32 [%0], %1;\n}" :: "r"(a), "r"(x), "r"(z) : "memory");
}
template <int K> __device__ __forceinline__ void sched_fence(int v) {
    asm volatile("{\n.reg .pred p;\nsetp.ne.s32 p, %0, %1;\n@p bra.uni F_%=;\ntrap;\nF_%=:\n}" :: "r"(v), "n"(1000 + K) : "memory");
}
__device__ __forceinline__ void spin_until(unsigned t0, unsigned d) {
    asm volatile("{\n.reg .pred p;\n.reg .u64 c;\n.reg .u32 lo;\n"
                 "S_%=: mov.u64 c, %%clock64;\ncvt.u32.u64 lo, c;\nsub.u32 lo, lo, %0;\nsetp.lt.u32 p, lo, %1;\n@p bra.uni S_%=;\n}" :: "r"(t0), "r"(d) : "memory");
}
__device__ __forceinline__ void bar_sync(int id, int n) { asm volatile("bar.sync %0, %1;" :: "r"(id), "r"(n) : "memory"); }
__device__ __forceinline__ void bar_sync_sel(int sel, int id) {
    asm volatile("{\n.reg .pred p;\nsetp.eq.u32 p, %0, 0;\n@p bar.sync %1, %3;\n@!p bar.sync %2, %3;\n}" :: "r"(sel), "r"(id), "r"(id + 1), "n"(192) : "memory");
}
__device__ __forceinline__ void bar_arrive(int id, int n) { asm volatile("bar.arrive %0, %1;" :: "r"(id), "r"(n) : "memory"); }
__device__ __forceinline__ void fence_async_smem() { asm volatile("fence.proxy.async.shared::cta;" ::: "memory"); }
__device__ __forceinline__ uint32_t pack_bf16(float lo, float hi) { uint32_t r; asm("cvt.rn.bf16x2.f32 %0, %1, %2;" : "=r"(r) : "f"(hi), "f"(lo)); return r; }
__device__ __forceinline__ uint32_t pack_f16(float lo, float hi) { uint32_t r; asm("cvt.rn.f16x2.f32 %0, %1, %2;" : "=r"(r) : "f"(hi), "f"(lo)); return r; }
__device__ __forceinline__ uint32_t f16x2_to_bf16x2(uint32_t v) { float2 f = __half22float2(*reinterpret_cast<__half2*>(&v)); return pack_bf16(f.x, f.y); }
__device__ __forceinline__ uint32_t hmul2(uint32_t a, uint32_t b) { uint32_t r; asm("mul.rn.f16x2 %0, %1, %2;" : "=r"(r) : "r"(a), "r"(b)); return r; }
__device__ __forceinline__ float ex2(float x) { float y; asm("ex2.approx.ftz.f32 %0, %1;" : "=f"(y) : "f"(x)); return y; }
__device__ __forceinline__ float ex2v(float x) { float y; asm volatile("ex2.approx.ftz.f32 %0, %1;" : "=f"(y) : "f"(x)); return y; }
__device__ __forceinline__ uint32_t absmax2(uint32_t a, uint32_t b) {
    uint32_t r; asm("max.xorsign.abs.bf16x2 %0, %1, %2;" : "=r"(r) : "r"(a), "r"(b)); return r;
}
__device__ __forceinline__ uint32_t shl_v(uint32_t a, int n) { return a << n; }
__device__ __forceinline__ uint32_t max3u(uint32_t a, uint32_t b, uint32_t c) { return max(max(a, b), c); }
__device__ __forceinline__ uint4 lds128(uint32_t a) { uint4 v; asm volatile("ld.shared.v4.u32 {%0,%1,%2,%3}, [%4];" : "=r"(v.x), "=r"(v.y), "=r"(v.z), "=r"(v.w) : "r"(a) : "memory"); return v; }
__device__ __forceinline__ uint4 lds128v(uint32_t a) { uint4 v; asm volatile("ld.volatile.shared.v4.u32 {%0,%1,%2,%3}, [%4];" : "=r"(v.x), "=r"(v.y), "=r"(v.z), "=r"(v.w) : "r"(a) : "memory"); return v; }
__device__ __forceinline__ float4 lds128f(uint32_t a) { float4 v; asm volatile("ld.shared.v4.f32 {%0,%1,%2,%3}, [%4];" : "=f"(v.x), "=f"(v.y), "=f"(v.z), "=f"(v.w) : "r"(a) : "memory"); return v; }
__device__ __forceinline__ float2 lds64f(uint32_t a) { float2 v; asm volatile("ld.shared.v2.f32 {%0,%1}, [%2];" : "=f"(v.x), "=f"(v.y) : "r"(a) : "memory"); return v; }
__device__ __forceinline__ uint4 lds64x2(uint32_t a) { uint4 v; asm volatile("ld.shared.v2.u32 {%0,%1}, [%4];\nld.shared.v2.u32 {%2,%3}, [%4+256];" : "=r"(v.x), "=r"(v.y), "=r"(v.z), "=r"(v.w) : "r"(a) : "memory"); return v; }
__device__ __forceinline__ uint32_t lds32(uint32_t a) { uint32_t v; asm volatile("ld.shared.u32 %0, [%1];" : "=r"(v) : "r"(a) : "memory"); return v; }
__device__ __forceinline__ void sts128(uint32_t a, uint32_t x, uint32_t y, uint32_t z, uint32_t w) { asm volatile("st.shared.v4.u32 [%0], {%1,%2,%3,%4};" :: "r"(a), "r"(x), "r"(y), "r"(z), "r"(w) : "memory"); }
__device__ __forceinline__ void sts128f(uint32_t a, float x, float y, float z, float w) { asm volatile("st.shared.v4.f32 [%0], {%1,%2,%3,%4};" :: "r"(a), "f"(x), "f"(y), "f"(z), "f"(w) : "memory"); }
__device__ __forceinline__ void sts64(uint32_t a, uint32_t x, uint32_t y) { asm volatile("st.shared.v2.u32 [%0], {%1,%2};" :: "r"(a), "r"(x), "r"(y) : "memory"); }
__device__ __forceinline__ void sts32(uint32_t a, uint32_t x) { asm volatile("st.shared.u32 [%0], %1;" :: "r"(a), "r"(x) : "memory"); }
__device__ __forceinline__ uint4 ldsm4(uint32_t a) { uint4 v; asm volatile("ldmatrix.sync.aligned.m8n8.x4.shared.b16 {%0,%1,%2,%3}, [%4];" : "=r"(v.x), "=r"(v.y), "=r"(v.z), "=r"(v.w) : "r"(a) : "memory"); return v; }
__device__ __forceinline__ void stsm2t(uint32_t a, uint32_t x, uint32_t y) { asm volatile("stmatrix.sync.aligned.m8n8.x2.trans.shared.b16 [%0], {%1,%2};" :: "r"(a), "r"(x), "r"(y) : "memory"); }
__device__ __forceinline__ void stsm4t(uint32_t a, uint32_t x, uint32_t y, uint32_t z, uint32_t w) { asm volatile("stmatrix.sync.aligned.m8n8.x4.trans.shared.b16 [%0], {%1,%2,%3,%4};" :: "r"(a), "r"(x), "r"(y), "r"(z), "r"(w) : "memory"); }
__device__ __forceinline__ void st_async64(uint32_t a, uint32_t x, uint32_t y, uint32_t bar) { asm volatile("st.async.shared::cluster.mbarrier::complete_tx::bytes.v2.b32 [%0], {%1,%2}, [%3];" :: "r"(a), "r"(x), "r"(y), "r"(bar) : "memory"); }
__device__ __forceinline__ void bulk_s2c(uint32_t dst, uint32_t src, uint32_t bytes, uint32_t bar) { asm volatile("cp.async.bulk.shared::cluster.shared::cta.mbarrier::complete_tx::bytes [%0], [%1], %2, [%3];" :: "r"(dst), "r"(src), "r"(bytes), "r"(bar) : "memory"); }
__device__ __forceinline__ void bulk_s2g(void* dst, uint32_t src, uint32_t bytes) { asm volatile("cp.async.bulk.global.shared::cta.bulk_group [%0], [%1], %2;" :: "l"(dst), "r"(src), "r"(bytes) : "memory"); }
__device__ __forceinline__ uint32_t ldg_nc32(const void* p) { uint32_t v; asm volatile("ld.global.nc.L2::128B.u32 %0, [%1];" : "=r"(v) : "l"(p)); return v; }
__device__ __forceinline__ uint4 ldg_relaxed128(const void* p) { uint4 v; asm volatile("ld.relaxed.gpu.global.v4.u32 {%0,%1,%2,%3}, [%4];" : "=r"(v.x), "=r"(v.y), "=r"(v.z), "=r"(v.w) : "l"(p) : "memory"); return v; }
__device__ __forceinline__ void mma16816(float (&d)[4], uint32_t a0, uint32_t a1, uint32_t a2, uint32_t a3, uint32_t b0, uint32_t b1) {
    asm volatile("mma.sync.aligned.m16n8k16.row.col.f32.bf16.bf16.f32 {%0,%1,%2,%3}, {%4,%5,%6,%7}, {%8,%9}, {%0,%1,%2,%3};"
        : "+f"(d[0]), "+f"(d[1]), "+f"(d[2]), "+f"(d[3]) : "r"(a0), "r"(a1), "r"(a2), "r"(a3), "r"(b0), "r"(b1));
}
__device__ __forceinline__ void mma16816_z(float (&d)[4], uint32_t a0, uint32_t a1, uint32_t a2, uint32_t a3, uint32_t b0, uint32_t b1) {
    asm volatile("mma.sync.aligned.m16n8k16.row.col.f32.bf16.bf16.f32 {%0,%1,%2,%3}, {%4,%5,%6,%7}, {%8,%9}, {%10,%10,%10,%10};"
        : "=f"(d[0]), "=f"(d[1]), "=f"(d[2]), "=f"(d[3]) : "r"(a0), "r"(a1), "r"(a2), "r"(a3), "r"(b0), "r"(b1), "f"(0.f));
}
__device__ __forceinline__ void mma1688(float (&d)[4], uint32_t a0, uint32_t a1, uint32_t b0) {
    asm volatile("mma.sync.aligned.m16n8k8.row.col.f32.bf16.bf16.f32 {%0,%1,%2,%3}, {%4,%5}, {%6}, {%0,%1,%2,%3};"
        : "+f"(d[0]), "+f"(d[1]), "+f"(d[2]), "+f"(d[3]) : "r"(a0), "r"(a1), "r"(b0));
}
__device__ __forceinline__ void mma1688_z(float (&d)[4], uint32_t a0, uint32_t a1, uint32_t b0) {
    asm volatile("mma.sync.aligned.m16n8k8.row.col.f32.bf16.bf16.f32 {%0,%1,%2,%3}, {%4,%5}, {%6}, {%7,%7,%7,%7};"
        : "=f"(d[0]), "=f"(d[1]), "=f"(d[2]), "=f"(d[3]) : "r"(a0), "r"(a1), "r"(b0), "f"(0.f));
}
template <int ACC>
__device__ __forceinline__ void wgmma_n32_rs(float (&d)[16], uint32_t a0, uint32_t a1, uint32_t a2, uint32_t a3, uint64_t desc) {
    asm volatile("wgmma.mma_async.sync.aligned.m64n32k16.f32.bf16.bf16 {%0,%1,%2,%3,%4,%5,%6,%7,%8,%9,%10,%11,%12,%13,%14,%15}, {%16,%17,%18,%19}, %20, %21, 1, 1, 0;"
        : "+f"(d[0]), "+f"(d[1]), "+f"(d[2]), "+f"(d[3]), "+f"(d[4]), "+f"(d[5]), "+f"(d[6]), "+f"(d[7]),
          "+f"(d[8]), "+f"(d[9]), "+f"(d[10]), "+f"(d[11]), "+f"(d[12]), "+f"(d[13]), "+f"(d[14]), "+f"(d[15])
        : "r"(a0), "r"(a1), "r"(a2), "r"(a3), "l"(desc), "n"(ACC));
}
template <int ACC>
__device__ __forceinline__ void wgmma_n32_ss(float (&d)[16], uint64_t da, uint64_t db) {
    asm volatile("wgmma.mma_async.sync.aligned.m64n32k16.f32.bf16.bf16 {%0,%1,%2,%3,%4,%5,%6,%7,%8,%9,%10,%11,%12,%13,%14,%15}, %16, %17, %18, 1, 1, 0, 0;"
        : "+f"(d[0]), "+f"(d[1]), "+f"(d[2]), "+f"(d[3]), "+f"(d[4]), "+f"(d[5]), "+f"(d[6]), "+f"(d[7]),
          "+f"(d[8]), "+f"(d[9]), "+f"(d[10]), "+f"(d[11]), "+f"(d[12]), "+f"(d[13]), "+f"(d[14]), "+f"(d[15])
        : "l"(da), "l"(db), "n"(ACC));
}
__device__ __forceinline__ void wg_fence() { asm volatile("wgmma.fence.sync.aligned;" ::: "memory"); }
__device__ __forceinline__ void wg_commit() { asm volatile("wgmma.commit_group.sync.aligned;" ::: "memory"); }
__device__ __forceinline__ void wg_wait0() { asm volatile("wgmma.wait_group.sync.aligned 0;" ::: "memory"); }
__device__ __forceinline__ void cluster_sync() { asm volatile("barrier.cluster.arrive.aligned;\nbarrier.cluster.wait.aligned;" ::: "memory"); }

#define STAMP(s, i) do {} while (0)
#define STAMPV(s, i, v) do {} while (0)

constexpr int XT_BYTES = 36864;
constexpr int O_XT = 0;
constexpr int O_STG = XT_BYTES;
constexpr int O_AS = 3 * XT_BYTES;
constexpr int O_XP = O_AS + 16384;
constexpr int O_QKX = O_XP + 8192;
constexpr int O_KM = O_QKX + 8192;
constexpr int O_QM = O_QKX + 10240;
constexpr int O_VX = O_STG + 147456;
constexpr int O_VM = O_VX + 16384;
constexpr int O_SC = O_VM + 2048;
constexpr int O_OF = O_SC + 2560;
constexpr int O_AF = O_OF + 2048;
constexpr int O_WP = O_AF + 4096;
constexpr int O_MF = O_WP + 2048;
constexpr int O_MISC = O_MF + 9216;
static_assert(O_QKX + 24576 <= O_VX, "smem");
constexpr int O_BAR = O_MISC + 64;
constexpr int CHAIN_SMEM = O_BAR + 128;
static_assert(CHAIN_SMEM <= 232448, "smem");
constexpr int B_X = O_BAR, B_VX = O_BAR + 24, B_SC = O_BAR + 40, B_W = O_BAR + 48, B_MX = O_BAR + 72;
constexpr float SM_SCALE = 0.08838834764831845f * 1.4426950408889634f;
constexpr uint32_t ONES = 0x3f803f80u;

__device__ __forceinline__ uint32_t opaque(uint32_t v) { uint32_t o; asm volatile("mov.u32 %0, %1;" : "=r"(o) : "r"(v)); return o; }
__device__ __forceinline__ void st_async128(uint32_t a, uint32_t x, uint32_t y, uint32_t z, uint32_t w, uint32_t bar) {
    asm volatile("st.async.shared::cluster.mbarrier::complete_tx::bytes.v4.b32 [%0], {%1,%2,%3,%4}, [%5];" :: "r"(a), "r"(x), "r"(y), "r"(z), "r"(w), "r"(bar) : "memory");
}
__device__ __forceinline__ void tma_x_tile(uint32_t sb, const CUtensorMap* tm, int r, int j, int slot) {
    asm volatile("{\n.reg .pred p;\nelect.sync _|p, 0xffffffff;\n"
        "@p mbarrier.arrive.expect_tx.shared::cta.b64 _, [%2], 36864;\n"
        "@p cp.async.bulk.tensor.2d.shared::cluster.global.mbarrier::complete_tx::bytes.multicast::cluster [%0], [%1, {%3, %4}], [%2], %7;\n"
        "@p cp.async.bulk.tensor.2d.shared::cluster.global.mbarrier::complete_tx::bytes.multicast::cluster [%0+4096], [%1, {%5, %4}], [%2], %7;\n"
        "@p cp.async.bulk.tensor.2d.shared::cluster.global.mbarrier::complete_tx::bytes.multicast::cluster [%0+8192], [%1, {%6, %4}], [%2], %7;\n}"
        :: "r"(sb + O_XT + slot * XT_BYTES + 3 * r * 4096), "l"(tm), "r"(sb + B_X + 8 * slot), "r"(192 * r), "r"(j * 32), "r"(192 * r + 64), "r"(192 * r + 128),
           "h"((unsigned short)7) : "memory");
}
__device__ __forceinline__ void flag_inc_if(uint32_t z, unsigned* p) {
    asm volatile("{\n.reg .pred p;\nsetp.eq.u32 p, %1, 0;\n@p red.release.gpu.global.inc.u32 [%0], 0xfffffffe;\n}" :: "l"(p), "r"(z) : "memory");
}
__device__ __forceinline__ float quad_max(float v) {
    const float a = __shfl_xor_sync(~0u, v, 1), b = __shfl_xor_sync(~0u, v, 2), c = __shfl_xor_sync(~0u, v, 3);
    return fmaxf(fmaxf(v, a), fmaxf(b, c));
}
__device__ __forceinline__ void load_scores(float (&p)[10], uint32_t base, uint32_t stride, uint32_t l16) {
    const float4 a0 = lds128f(base + l16), b0 = lds128f(base + stride + l16);
    const float4 a1 = lds128f(base + 512 + l16), b1 = lds128f(base + stride + 512 + l16);
    const float2 a2 = lds64f(base + 1024 + (l16 >> 1)), b2 = lds64f(base + stride + 1024 + (l16 >> 1));
    p[0] = a2.x + b2.x; p[1] = a2.y + b2.y;
    p[2] = a0.x + b0.x; p[3] = a0.y + b0.y; p[4] = a0.z + b0.z; p[5] = a0.w + b0.w;
    p[6] = a1.x + b1.x; p[7] = a1.y + b1.y; p[8] = a1.z + b1.z; p[9] = a1.w + b1.w;
}
__device__ __forceinline__ float rcp_fast(float x) { float y; asm("rcp.approx.ftz.f32 %0, %1;" : "=f"(y) : "f"(x)); return y; }

__global__ void __cluster_dims__(3, 1, 1) __launch_bounds__(384, 1)
chain_kernel(const __grid_constant__ CUtensorMap tm_x, const __grid_constant__ CUtensorMap tm_q,
             const __grid_constant__ CUtensorMap tm_k, const __grid_constant__ CUtensorMap tm_v,
             const __nv_bfloat16* __restrict__ x, const __nv_bfloat16* __restrict__ mem0,
             const __nv_bfloat16* __restrict__ Wo) {
    extern __shared__ __align__(1024) uint8_t smem_raw[];
    const uint32_t sb = smem_u32(smem_raw);
    const int lane = threadIdx.x & 31;
    const int warp = __shfl_sync(~0u, threadIdx.x >> 5, 0);
    const int wg = warp >> 2, w = warp & 3;
    const int h = blockIdx.x / 3, r = blockIdx.x - 3 * h;
    uint4* const g_acc = reinterpret_cast<uint4*>((reinterpret_cast<uintptr_t>(g_acc_raw) + 0x1fffff) & ~(uintptr_t)0x1fffff);

#define PSTAMP(i) do {} while (0)
    if (threadIdx.x == 0) {
        if (sb & 1023u) __trap();
        for (int i = 0; i < 9; i++) mbar_init(sb + O_BAR + 8 * i, 1);
        mbar_init(sb + B_MX, 4);
        asm volatile("fence.mbarrier_init.release.cluster;" ::: "memory");
        for (int i = 0; i < 3; i++) {
            mbar_expect(sb + B_W + 8 * i, 49152);
            for (int tl = 0; tl < 2; tl++)
                asm volatile("cp.async.bulk.tensor.2d.shared::cluster.global.mbarrier::complete_tx::bytes [%0], [%1, {%3, %4}], [%2];"
                    :: "r"(sb + O_STG + tl * 73728 + i * 24576), "l"(r < 2 ? (tl ? &tm_k : &tm_q) : &tm_v), "r"(sb + B_W + 8 * i),
                       "r"(h * 128 + 64 * (r < 2 ? r : tl)), "r"(192 * i) : "memory");
        }
    }
    __syncwarp();
    asm volatile("barrier.cluster.arrive.relaxed.aligned;" ::: "memory");
    asm volatile("griddepcontrol.launch_dependents;" ::: "memory");
    if (warp == 0) PSTAMP(9);
    const uint32_t l16c = __shfl_sync(~0u, lane * 16, lane);

    if (wg < 2) {
#define KS(u) ((u) < 8 ? 12 * ((u) >> 2) + (((u) >> 1) & 1) + 4 * ((u) & 1) : (u) < 12 ? (u) : (u) < 16 ? (u) + 8 : (u) < 24 ? 24 + (((u) - 16) >> 1) + 4 * ((u) & 1) : (u) + 8)
        asm volatile("setmaxnreg.inc.sync.aligned.u32 184;");
        uint32_t a[144];
        uint32_t adr1;
        {
            const int g = lane >> 2, t = lane & 3;
            const int t1 = threadIdx.x;
#pragma unroll
            for (int i = 0; i < 2; i++) g_acc[(blockIdx.x * 64 + i * 32 + (t1 >> 3)) * 16 + (t1 & 7)] = make_uint4(0, 0, 0, 0);
            __threadfence();
            asm volatile("barrier.cluster.wait.aligned;" ::: "memory");
            const uint32_t ev = sb + O_STG + (2 * t) * 128 + (((2 * w + (g >> 2)) ^ (2 * t)) << 4) + (g & 3) * 4;
            const uint32_t od = (ev ^ 16) + 128;
            auto gather = [&](int dst, uint32_t off) {
                a[dst] = lds32(ev + off); a[dst + 1] = lds32(od + off); a[dst + 2] = lds32(ev + off + 1024); a[dst + 3] = lds32(od + off + 1024);
            };
            const uint4* xp = reinterpret_cast<const uint4*>(x) + blockIdx.x * 1536 + t1;
            uint4 xv[6];
#pragma unroll
            for (int th = 0; th < 2; th++) {
                mbar_wait(sb + B_W + 8 * th, 0);
                if (th == 1) {
#pragma unroll
                    for (int i = 0; i < 6; i++) xv[i] = __ldg(xp + i * 256);
                }
#pragma unroll
                for (int u = 4 * th; u < 4 * th + 4; u++) {
                    gather(32 + 4 * u, wg * (73728 + 4096) + KS(u) * 2048);
                    gather(4 * u, 73728 - wg * (73728 - 4096) + KS(u) * 2048);
                    gather(64 + 4 * u, wg * 73728 + KS(8 + u) * 2048);
                }
            }
            mbar_wait(sb + B_W + 16, 0);
#pragma unroll
            for (int u = 16; u < 28; u++) gather(32 + 4 * u, wg * 73728 + KS(u) * 2048);
#pragma unroll
            for (int kk = 0; kk < 72; kk++) {
                uint32_t w0 = a[2 * kk], w1 = a[2 * kk + 1];
                a[2 * kk] = __byte_perm(w0, w1, 0x5410);
                a[2 * kk + 1] = __byte_perm(w0, w1, 0x7632);
            }
            if (r == 2) {
                float n0[4], n1[4];
#pragma unroll
                for (int u = 0; u < 36; u++) {
                    const uint32_t x0 = a[4 * u] & 0x7fff7fffu, x1 = a[4 * u + 1] & 0x7fff7fffu, x2 = a[4 * u + 2] & 0x7fff7fffu, x3 = a[4 * u + 3] & 0x7fff7fffu;
                    if (u == 0) mma16816_z(n0, x0, x1, x2, x3, ONES, ONES);
                    else if (u < 8) mma16816(n0, x0, x1, x2, x3, ONES, ONES);
                    else if (u == 8) mma16816_z(n1, x0, x1, x2, x3, ONES, ONES);
                    else mma16816(n1, x0, x1, x2, x3, ONES, ONES);
                }
                const uint32_t mx = __reduce_max_sync(~0u, __float_as_uint(2.f * fmaxf(fmaxf(n0[0], n0[2]), fmaxf(n1[0], n1[2]))));
                sts32_if(lane, sb + O_MISC + 32 + 4 * warp, mx);
            }
            uint32_t xm = 0;
#pragma unroll
            for (int i = 0; i < 6; i++)
                xm = __vmaxu2(xm, __vmaxu2(__vmaxu2(xv[i].x & 0x7fff7fffu, xv[i].y & 0x7fff7fffu), __vmaxu2(xv[i].z & 0x7fff7fffu, xv[i].w & 0x7fff7fffu)));
            sts32_if(lane, sb + O_OF + 16 + 4 * warp, __reduce_max_sync(~0u, max(xm << 16, xm & 0xffff0000u)));
            if (warp == 0) PSTAMP(11);
            bar_arrive(7, 384);
            asm volatile("barrier.cluster.arrive.relaxed.aligned;" ::: "memory");
            bar_sync(1, 256);
            const uint32_t as = sb + O_AS + wg * 8192 + (16 * w + g) * 128 + t * 4;
            sts32(as + (g << 4), a[32]);
            sts32(as + 1024 + (g << 4), a[33]);
            sts32(as + ((1 ^ g) << 4), a[34]);
            sts32(as + 1024 + ((1 ^ g) << 4), a[35]);
            sts128(sb + O_AF + warp * 512 + lane * 16, a[32], a[33], a[34], a[35]);
            fence_async_smem();
            bar_sync(1, 256);
            const uint32_t l = lane * 16;
            const int mi = lane >> 3, isk = (mi >> 1) ? wg : (wg ^ 1);
            adr1 = (r == 2) ? (sb + O_VM + warp * 256 + (l >> 1))
                            : (isk ? (sb + O_KM + w * 512 + wg * 256 + (mi & 1) * 128 + (l & 127))
                                   : (sb + O_QM + w * 512 + (mi & 1) * 256 + wg * 128 + (l & 127)));
            adr1 = __shfl_sync(~0u, adr1, lane);
        }
        int s3 = 2;
#pragma unroll 1
        for (int s = -1; s < NSEG; s++) {
            const uint32_t l16 = opaque(l16c);
            s3 = (s3 == 2) ? 0 : s3 + 1;
            if (s < 0) mbar_wait(sb + B_X, 0);
            const uint64_t desc0 = (uint64_t)(((sb + O_XT + s3 * XT_BYTES) & 0x3FFFF) >> 4) | (1ull << 16) | (64ull << 32) | (1ull << 62);
            uint32_t km0 = 0, km1 = 0;
            if (s >= 0) {
                { const uint4 v = lds128(sb + O_AF + warp * 512 + l16); a[32] = v.x; a[33] = v.y; a[34] = v.z; a[35] = v.w; }
                float co[4], cw[3][4];
                uint4 b[14];
                float inv;
#define GORD(i) ((i) < 8 ? 2 * ((i) >> 2) + (((i) >> 1) & 1) + 4 * ((i) & 1) : (i))
                auto qkv_mma = [&](int i) {
                    const int gi = GORD(i), u = 8 * gi, n0 = 2 * i, n1 = 2 * i + 1;
                    if (gi < 4) {
                        if (i == 0) mma16816_z(co, a[u], a[u + 1], a[u + 2], a[u + 3], b[0].x, b[0].y);
                        else mma16816(co, a[u], a[u + 1], a[u + 2], a[u + 3], b[i].x, b[i].y);
                    }
                    if (n0 < 3) mma16816_z(cw[n0 % 3], a[32 + u], a[32 + u + 1], a[32 + u + 2], a[32 + u + 3], b[i].x, b[i].y);
                    else mma16816(cw[n0 % 3], a[32 + u], a[32 + u + 1], a[32 + u + 2], a[32 + u + 3], b[i].x, b[i].y);
                    if (n1 < 3) mma16816_z(cw[n1 % 3], a[32 + u + 4], a[32 + u + 5], a[32 + u + 6], a[32 + u + 7], b[i].z, b[i].w);
                    else mma16816(cw[n1 % 3], a[32 + u + 4], a[32 + u + 5], a[32 + u + 6], a[32 + u + 7], b[i].z, b[i].w);
                    if (gi < 4) mma16816(co, a[u + 4], a[u + 5], a[u + 6], a[u + 7], b[i].z, b[i].w);
                };
                const uint32_t mf = sb + O_MF + l16, mfs = mf + wg * 1024;
                const uint32_t qb = (s & 1) * 12288;
                bar_sync(2, 384);
                if (warp == 0) STAMP(s, 0);
                auto qkv_ld = [&](int i) {
                    const int gi = GORD(i);
                    b[i] = gi < 4 ? lds128v(mfs + (gi >> 1) * 3072 + (gi & 1) * 512) : lds128v(mf + (gi < 6 ? gi : gi + 4) * 512);
                };
#pragma unroll
                for (int i = 0; i < 4; i++) qkv_ld(i);
                qkv_mma(0); qkv_mma(1); qkv_mma(2);
                const uint32_t z0 = __float_as_uint(QDEP ? co[0] : cw[1][0]) & (l16 & 15u);
                qkv_mma(3);
                bar_sync(15, 384);
                b[4] = lds128v(mfs + 3072 + z0);
#pragma unroll
                for (int i = 5; i < 9; i++) qkv_ld(i);
#pragma unroll
                for (int i = 4; i < 9; i++) { qkv_mma(i); qkv_ld(5 + i); }
                asm volatile("ld.volatile.shared.f32 %0, [%1];" : "=f"(inv) : "r"(sb + O_MISC) : "memory");
#pragma unroll
                for (int i = 9; i < 14; i++) qkv_mma(i);
#pragma unroll
                for (int i = 0; i < 4; i++) cw[0][i] += cw[1][i] + cw[2][i];
                if (r < 2) {
                    const uint32_t o0 = pack_bf16(co[0] * inv, co[1] * inv), o1 = pack_bf16(co[2] * inv, co[3] * inv);
                    const uint32_t w0 = pack_bf16(cw[0][0] * inv, cw[0][1] * inv), w1 = pack_bf16(cw[0][2] * inv, cw[0][3] * inv);
                    stsm4t(adr1 + qb, o0, o1, w0, w1);
                    if (warp == 0) STAMP(s, 1);
                    asm volatile("{\n.reg .pred p;\nsetp.ge.u32 p, %0, 3;\n@p bar.arrive 1, 256;\n}" :: "r"(warp) : "memory");
                    auto scores = [&](float (&v)[4], const uint4 (&q)[4], const uint4 (&k)[4]) {
                        float s0[4], s1[4], t0[4], t1[4];
                        mma16816_z(s0, q[0].x, q[0].y, q[0].z, q[0].w, k[0].x, k[0].y);
                        mma16816_z(s1, q[0].x, q[0].y, q[0].z, q[0].w, k[0].z, k[0].w);
                        mma16816_z(t0, q[1].x, q[1].y, q[1].z, q[1].w, k[1].x, k[1].y);
                        mma16816_z(t1, q[1].x, q[1].y, q[1].z, q[1].w, k[1].z, k[1].w);
                        mma16816(s0, q[2].x, q[2].y, q[2].z, q[2].w, k[2].x, k[2].y);
                        mma16816(s1, q[2].x, q[2].y, q[2].z, q[2].w, k[2].z, k[2].w);
                        mma16816(t0, q[3].x, q[3].y, q[3].z, q[3].w, k[3].x, k[3].y);
                        mma16816(t1, q[3].x, q[3].y, q[3].z, q[3].w, k[3].z, k[3].w);
                        v[0] = (s0[0] + s0[2]) + (t0[0] + t0[2]); v[1] = (s0[1] + s0[3]) + (t0[1] + t0[3]);
                        v[2] = (s1[0] + s1[2]) + (t1[0] + t1[2]); v[3] = (s1[1] + s1[3]) + (t1[1] + t1[3]);
                    };
                    if (warp < 2) {
                        uint4 q[4], k[4]; float v[4];
#pragma unroll
                        for (int i = 0; i < 4; i++) k[i] = ldsm4(sb + O_QKX + 4096 + qb + warp * 2048 + i * 512 + l16);
                        bar_sync(1, 256);
#pragma unroll
                        for (int i = 0; i < 4; i++) q[i] = ldsm4(sb + O_QM + qb + i * 512 + l16);
                        scores(v, q, k);
                        const uint32_t dst = sb + O_SC + r * 1280 + warp * 512 + l16;
                        st_async128(mapa(dst, 2), __float_as_uint(v[0]), __float_as_uint(v[1]), __float_as_uint(v[2]), __float_as_uint(v[3]), mapa(sb + B_SC, 2));
                        st_async128(mapa(dst, r ^ 1), __float_as_uint(v[0]), __float_as_uint(v[1]), __float_as_uint(v[2]), __float_as_uint(v[3]), mapa(sb + B_SC, r ^ 1));
                        st_async128(mapa(dst, r), __float_as_uint(v[0]), __float_as_uint(v[1]), __float_as_uint(v[2]), __float_as_uint(v[3]), mapa(sb + B_SC, r));
                    } else if (warp == 2) {
                        uint4 q[4], k[4]; float v[4];
                        bar_sync(1, 256);
#pragma unroll
                        for (int i = 0; i < 4; i++) { q[i] = ldsm4(sb + O_QM + qb + i * 512 + l16); k[i] = ldsm4(sb + O_KM + qb + i * 512 + l16); }
                        scores(v, q, k);
                        const uint32_t dst = sb + O_SC + r * 1280 + 1024 + (l16 >> 1);
                        st_async64(mapa(dst, 2), __float_as_uint(v[0] + v[2]), __float_as_uint(v[1] + v[3]), mapa(sb + B_SC, 2));
                        st_async64(mapa(dst, r ^ 1), __float_as_uint(v[0] + v[2]), __float_as_uint(v[1] + v[3]), mapa(sb + B_SC, r ^ 1));
                        st_async64(mapa(dst, r), __float_as_uint(v[0] + v[2]), __float_as_uint(v[1] + v[3]), mapa(sb + B_SC, r));
                        STAMP(s, 2);
                    } else if (warp == 3) {
                        asm volatile("cp.async.bulk.wait_group 0;\nfence.proxy.async.global;" ::: "memory");
                    }
                } else {
                    sts128f(sb + O_XP + warp * 512 + l16, co[0], co[1], co[2], co[3]);
                    bar_sync(8 + w, 64);
                    const float4 o = lds128f(sb + O_XP + (warp ^ 4) * 512 + l16);
                    km0 = pack_bf16((cw[0][0] + o.x) * inv, (cw[0][1] + o.y) * inv);
                    km1 = pack_bf16((cw[0][2] + o.z) * inv, (cw[0][3] + o.w) * inv);
                    if (warp == 0) STAMP(s, 1);
                    st_async64(mapa(adr1, 0), km0, km1, mapa(sb + B_SC, 0));
                    st_async64(mapa(adr1, 1), km0, km1, mapa(sb + B_SC, 1));
                    st_async64(mapa(adr1, 2), km0, km1, mapa(sb + B_SC, 2));
                    if (warp == 0) STAMP(s, 2);
                }
            }
            if (s >= 0) bar_sync(3, 384);
            auto store_qk = [&]() {
                asm volatile("{\n.reg .pred p;\nelect.sync _|p, 0xffffffff;\n"
                    "@p cp.async.bulk.global.shared::cta.bulk_group [%0], [%1], 10240;\n@p cp.async.bulk.commit_group;\n}"
                    :: "l"(reinterpret_cast<char*>(g_qkv) + (size_t)(s * NH + h) * REC + r * 10240), "r"(sb + O_QKX + (s & 1) * 12288) : "memory");
            };
            auto store_vm = [&]() {
                *reinterpret_cast<uint2*>(reinterpret_cast<char*>(g_qkv) + (size_t)(s * NH + h) * REC + 28672 + warp * 256 + (l16 >> 1)) = make_uint2(km0, km1);
            };
            if (s == NSEG - 1) {
                if (r == 2) store_vm();
                else if (warp == 3) {
                    fence_async_smem();
                    store_qk();
                    asm volatile("cp.async.bulk.wait_group 0;\nfence.proxy.async.global;" ::: "memory");
                }
            } else {
                const int j = s + 1;
#define XDESC(u) (((u) < 8 ? descs : desc0) + (uint64_t)(((KS(u) >> 2) * 4096 + (KS(u) & 3) * 32) >> 4))
                const uint64_t descs = desc0 + (uint64_t)(wg * 4);
                float d[16];
                wg_fence();
#pragma unroll
                for (int u = 0; u < 8; u++) {
                    if (u == 0) wgmma_n32_rs<0>(d, a[0], a[1], a[2], a[3], XDESC(0));
                    else wgmma_n32_rs<1>(d, a[4 * u], a[4 * u + 1], a[4 * u + 2], a[4 * u + 3], XDESC(u));
                }
                wg_commit();
                wg_wait0();
                if (warp == 0) STAMP(s, 15);
                auto xp_put = [&]() {
#pragma unroll
                    for (int q = 0; q < 2; q++)
                        sts128(sb + O_XP + warp * 1024 + q * 512 + l16, pack_bf16(d[8 * q], d[8 * q + 1]), pack_bf16(d[8 * q + 2], d[8 * q + 3]),
                               pack_bf16(d[8 * q + 4], d[8 * q + 5]), pack_bf16(d[8 * q + 6], d[8 * q + 7]));
                };
                uint4 xo[2];
                auto xp_get = [&]() { xo[0] = lds128(sb + O_XP + (warp ^ 4) * 1024 + l16); xo[1] = lds128(sb + O_XP + (warp ^ 4) * 1024 + 512 + l16); };
                if (s >= 0) bar_sync(4, 384);
                xp_put();
                bar_sync(12, 256);
                xp_get();
#pragma unroll
                for (int q = 0; q < 2; q++) {
                    d[8 * q] = __uint_as_float(xo[q].x << 16); d[8 * q + 1] = __uint_as_float(xo[q].x & 0xffff0000u);
                    d[8 * q + 2] = __uint_as_float(xo[q].y << 16); d[8 * q + 3] = __uint_as_float(xo[q].y & 0xffff0000u);
                    d[8 * q + 4] = __uint_as_float(xo[q].z << 16); d[8 * q + 5] = __uint_as_float(xo[q].z & 0xffff0000u);
                    d[8 * q + 6] = __uint_as_float(xo[q].w << 16); d[8 * q + 7] = __uint_as_float(xo[q].w & 0xffff0000u);
                }
                if (s >= 0) {
                    if (r == 2) store_vm();
                    if (warp == 5 && s + 2 < NSEG) tma_x_tile(sb, &tm_x, r, s + 2, s3 == 2 ? 0 : s3 + 1);
                    if (warp == 3) fence_async_smem();
                    if (warp == 7 && ((PUB_MASK >> s) & 1)) {
                        flag_inc_if(l16, &g_flag[F_QKV + (s - 4 + (h >> 3)) * 8]);
                        for (int sb4 = s - 4; sb4 > 0 && !((PUB_MASK >> sb4) & 1); sb4 -= 4)
                            asm volatile("{\n.reg .pred p;\nsetp.eq.u32 p, %1, 0;\n@p red.relaxed.gpu.global.inc.u32 [%0], 0xfffffffe;\n}"
                                         :: "l"(&g_flag[F_QKV + (sb4 - 4 + (h >> 3)) * 8]), "r"(l16) : "memory");
                    }
                    asm volatile("{\n.reg .pred p;\nsetp.eq.u32 p, %0, 0;\n@p bar.sync 5, 256;\n@!p bar.sync 13, 256;\n}" :: "r"(wg) : "memory");
                }
                const uint64_t da0 = (uint64_t)(((sb + O_AS + wg * 8192) & 0x3FFFF) >> 4) | (1ull << 16) | (64ull << 32) | (1ull << 62);
                wg_fence();
                wgmma_n32_ss<1>(d, da0, XDESC(0));
#pragma unroll
                for (int u = 1; u < 28; u++) wgmma_n32_rs<1>(d, a[32 + 4 * u], a[32 + 4 * u + 1], a[32 + 4 * u + 2], a[32 + 4 * u + 3], XDESC(u));
                wg_commit();
                wg_wait0();
                if (warp == 3 && r < 2 && s >= 0) store_qk();
                if (warp == 4) STAMP(s, 3);
                uint32_t e[8];
#pragma unroll
                for (int i = 0; i < 8; i++) e[i] = pack_bf16(d[2 * i], d[2 * i + 1]);
                if (r < 2) {
                    const uint32_t base = sb + O_QKX + (j & 1) * 12288 + wg * 4096 + w * 512 + l16;
                    stsm4t(base, e[0], wg ? e[1] : e[2], wg ? e[2] : e[1], e[3]);
                    stsm4t(base + 2048, e[4], wg ? e[5] : e[6], wg ? e[6] : e[5], e[7]);
                } else {
                    const uint32_t base = sb + O_VX + (j & 1) * 8192 + warp * 1024 + l16;
                    sts128(base, e[0], e[1], e[2], e[3]);
                    sts128(base + 512, e[4], e[5], e[6], e[7]);
                    bar_arrive(14, 288);
                }
                if (warp == 7) STAMP(s, 4);
                if (s < 0) asm volatile("barrier.cluster.wait.aligned;" ::: "memory");
            }
        }
        bar_arrive(7, 384);
    } else {
        asm volatile("setmaxnreg.dec.sync.aligned.u32 136;");
        const int c = w;
        uint32_t a[96];
        uint32_t mmax = 0;
        {
            const int g = lane >> 2, t = lane & 3;
            uint32_t tag = 0, m0v[18];
            if (threadIdx.x == 256) tag = atomicAdd(&g_ticket, 1u);
#pragma unroll
            for (int i = 0; i < 9; i++) {
                const uint32_t* p = reinterpret_cast<const uint32_t*>(mem0 + g * DM + 16 * (4 * i + c) + 2 * t);
                m0v[2 * i] = __ldg(p); m0v[2 * i + 1] = __ldg(p + 4);
            }
            asm volatile("barrier.cluster.wait.aligned;" ::: "memory");
            if (c == 0) {
                tma_x_tile(sb, &tm_x, r, 0, 0);
                mbar_expect_if(lane, sb + B_SC, 4608);
                if (r < 2) mbar_expect_if(lane, sb + B_VX, 8192);
                sts32_if(lane, sb + O_MISC, __float_as_uint(1.0f));
                sts32_if(lane, sb + O_MISC + 12, __float_as_uint(SM_SCALE));
            }
            asm volatile("barrier.cluster.arrive.relaxed.aligned;" ::: "memory");
#pragma unroll
            for (int tau = 0; tau < 3; tau++) {
                const uint32_t* v = m0v + 6 * tau;
                sts128(sb + O_MF + tau * 3072 + c * 512 + lane * 16, v[0], v[1], v[2], v[3]);
                sts64(sb + O_MF + tau * 3072 + 2048 + (c >> 1) * 512 + lane * 16 + (c & 1) * 8, v[4], v[5]);
#pragma unroll
                for (int i = 0; i < 6; i++) mmax = __vmaxu2(mmax, v[i] & 0x7fff7fffu);
            }
            mmax = max(mmax << 16, mmax & 0xffff0000u);
            bar_arrive(2, 384); bar_arrive(15, 384);
            tag = (__shfl_sync(~0u, tag, 0) / 96u + 1u) & 0xffffu;
            mbar_wait(sb + B_W + 0, 0);
            const __nv_bfloat16* p = Wo + (size_t)(h * 128 + 4 * t) * DM + 192 * r + 16 * c + 2 * g;
#pragma unroll
            for (int i = 0; i < 3; i++)
#pragma unroll
                for (int eb = 0; eb < 8; eb++)
#pragma unroll
                    for (int j = 0; j < 4; j++) a[(i * 8 + eb) * 4 + j] = ldg_nc32(p + (16 * eb + ((j & 1) * 2 + (j >> 1))) * DM + 64 * i);
#pragma unroll
            for (int kk = 0; kk < 48; kk++) {
                uint32_t w0 = a[2 * kk], w1 = a[2 * kk + 1];
                a[2 * kk] = __byte_perm(w0, w1, 0x5410);
                a[2 * kk + 1] = __byte_perm(w0, w1, 0x7632);
            }
            sts128(sb + O_WP + c * 512 + lane * 16, a[92], a[93], a[94], a[95]);
            float wmax = 0.f;
#pragma unroll
            for (int i = 0; i < 3; i++) {
                float n0[4];
#pragma unroll
                for (int u = 8 * i; u < 8 * i + 8; u++) {
                    const uint32_t x0 = a[4 * u] & 0x7fff7fffu, x1 = a[4 * u + 1] & 0x7fff7fffu, x2 = a[4 * u + 2] & 0x7fff7fffu, x3 = a[4 * u + 3] & 0x7fff7fffu;
                    if (u == 8 * i) mma16816_z(n0, x0, x1, x2, x3, ONES, ONES);
                    else mma16816(n0, x0, x1, x2, x3, ONES, ONES);
                }
                wmax = fmaxf(wmax, fmaxf(n0[0], n0[2]));
            }
            uint32_t wm = __reduce_max_sync(~0u, __float_as_uint(wmax));
            sts32_if(lane, sb + O_OF + 4 * c, wm);
            if (c == 0) PSTAMP(8);
            bar_sync(7, 384);
            asm volatile("barrier.cluster.wait.aligned;" ::: "memory");
            if (c == 1) tma_x_tile(sb, &tm_x, r, 1, 1);
            if (c == 0) {
                const uint4 wq = lds128(sb + O_OF), xq = lds128(sb + O_OF + 16), xr = lds128(sb + O_OF + 32), v0 = lds128(sb + O_MISC + 32), v1 = lds128(sb + O_MISC + 48);
                const uint32_t w1 = max(max(wq.x, wq.y), max(wq.z, wq.w)), x1 = max(max(max(xq.x, xq.y), max(xq.z, xq.w)), max(max(xr.x, xr.y), max(xr.z, xr.w)));
                const uint32_t vv = (r < 2) ? 0u : max(max(max(v0.x, v0.y), max(v0.z, v0.w)), max(max(v1.x, v1.y), max(v1.z, v1.w)));
                const uint32_t lo = (min(w1, 0x7f800000u) + 0xffffu) >> 16 | ((min(vv, 0x7f800000u) + 0xffffu) & 0xffff0000u), hi = (x1 & 0xffff0000u) | tag;
                uint32_t l0, h0, l1, h1, l2, h2;
                asm volatile("{\n.reg .pred p;\n.reg .u32 n, x, y;\n.reg .b64 v;\nsetp.eq.u32 p, %10, 0;\nmov.b64 v, {%8, %9};\n@p st.relaxed.gpu.global.b64 [%7], v;\nmov.u32 n, 0;\n"
                             "G_%=: ld.relaxed.gpu.global.b64 v, [%6];\nmov.b64 {%0, %1}, v;\nld.relaxed.gpu.global.b64 v, [%6+256];\nmov.b64 {%2, %3}, v;\n"
                             "ld.relaxed.gpu.global.b64 v, [%6+512];\nmov.b64 {%4, %5}, v;\n"
                             "xor.b32 x, %1, %9;\nxor.b32 y, %3, %9;\nor.b32 x, x, y;\nxor.b32 y, %5, %9;\nor.b32 x, x, y;\nand.b32 x, x, 0xffff;\n"
                             "setp.eq.u32 p, x, 0;\nvote.sync.all.pred p, p, 0xffffffff;\n@p bra.uni E_%=;\n"
                             "add.u32 n, n, 1;\nsetp.lt.u32 p, n, 4000000;\n@p bra.uni G_%=;\ntrap;\nE_%=:\n}"
                             : "=&r"(l0), "=&r"(h0), "=&r"(l1), "=&r"(h1), "=&r"(l2), "=&r"(h2)
                             : "l"(&g_norm[lane]), "l"(&g_norm[blockIdx.x]), "r"(lo), "r"(hi), "r"(lane) : "memory");
                const uint32_t lm = __vmaxu2(l0, __vmaxu2(l1, l2));
                const float fw = __uint_as_float(__reduce_max_sync(~0u, lm << 16));
                const float fv = __uint_as_float(__reduce_max_sync(~0u, lm & 0xffff0000u));
                const float xmax = __uint_as_float(__reduce_max_sync(~0u, max(h0, max(h1, h2)) & 0xffff0000u));
                const float G = 36.f * fw * fv;
                sts32_if(lane, sb + O_MISC + 4, __float_as_uint(G)); sts32_if(lane, sb + O_MISC + 8, __float_as_uint(G * xmax));
            }
        }
        if (c == 0) PSTAMP(12);
        bar_sync(6, 128);
        int s3n = 1;
        uint32_t roff = __shfl_sync(~0u, (r * 4 + c) * 2048 + (lane >> 4) * 512 + (lane & 2) * 128 + (lane & 1) * 64 + (lane & 12) * 4, lane);
#pragma unroll 1
        for (int s = 0; s < NSEG; s++) {
            const uint32_t l16 = opaque(l16c);
            const uint32_t vxa = sb + O_VX + (s & 1) * 8192 + c * 2048 + l16;
            sts32_if(l16, sb + O_MISC + 16 + 4 * c, __reduce_max_sync(~0u, mmax));
            mbar_arrive_if(l16, sb + B_MX);
            if (c == 0 && r == 2) {
                bar_sync(14, 288);
                fence_async_smem();
                asm volatile("{\n.reg .pred p;\nelect.sync _|p, 0xffffffff;\n"
                    "@p cp.async.bulk.global.shared::cta.bulk_group [%0], [%1], 8192;\n@p cp.async.bulk.commit_group;\n"
                    "cp.async.bulk.wait_group 0;\nsetp.lt.and.s32 p, %4, 63, p;\n"
                    "@p cp.async.bulk.shared::cluster.global.mbarrier::complete_tx::bytes.multicast::cluster [%1], [%0], 8192, [%2], %3;\n"
                    "fence.proxy.async.global;\n}"
                    :: "l"(reinterpret_cast<char*>(g_qkv) + (size_t)(s * NH + h) * REC + 20480), "r"(sb + O_VX + (s & 1) * 8192),
                       "r"(sb + B_VX + 8 * (s & 1)), "h"((unsigned short)3), "r"(s) : "memory");
            }
            if (s == NSEG - 1) { bar_sync(3, 384); mbar_wait(sb + B_SC, s & 1); break; }
            uint4 vx[4];
            if (c == 0) STAMP(s, 5);
            {
                mbar_wait(sb + B_MX, s & 1);
                const uint4 mm = lds128(sb + O_MISC + 16), cf = lds128(sb + O_MISC);
                const float bound = fmaxf(__uint_as_float(cf.z), __uint_as_float(cf.y) * (__uint_as_float(max(max(mm.x, mm.y), max(mm.z, mm.w))) * __uint_as_float(cf.x)));
                const uint32_t ebits = __reduce_max_sync(~0u, min(max(__float_as_uint(bound) & 0x7f800000u, 21u << 23), 254u << 23));
                if (c == 1) mbar_wait(sb + B_X + 8 * s3n, ((s + 1) / 3) & 1);
                s3n = (s3n == 2) ? 0 : s3n + 1;
                bar_sync(3, 384);
                if (r < 2) mbar_wait(sb + B_VX + 8 * (s & 1), (s >> 1) & 1);
                vx[0] = lds128(vxa); vx[2] = lds128(vxa + 1024);
                if (c == 0) STAMP(s, 13);
                mbar_wait(sb + B_SC, s & 1);
                if (c == 0) STAMP(s, 6);
                float p[10];
                load_scores(p, sb + O_SC, 1280, l16);
                float mx = fmaxf(fmaxf(fmaxf(p[0], p[1]), fmaxf(p[2], p[3])), fmaxf(fmaxf(p[4], p[5]), fmaxf(p[6], p[7])));
                mx = quad_max(fmaxf(mx, fmaxf(p[8], p[9])));
                const uint4 vm = lds64x2(sb + O_VM + c * 512 + (l16 >> 1));
                vx[1] = lds128(vxa + 512); vx[3] = lds128(vxa + 1536);
                bar_arrive(4, 384);
                const float sc = __uint_as_float(lds32(sb + O_MISC + 12));
                const float mo = mx * SM_SCALE;
                uint32_t P[5];
#pragma unroll
                for (int n = 0; n < 5; n++) P[n] = pack_bf16(ex2(fmaf(p[2 * n], SM_SCALE, -mo)), ex2(fmaf(p[2 * n + 1], n == 3 ? sc : SM_SCALE, -mo)));
                if (c == 0) STAMP(s, 7);
                float o0[4], o1[4], sm[4];
                mma16816_z(sm, ONES, ONES, ONES, ONES, P[1], P[2]);
                mma16816_z(o0, vx[0].x, vx[0].y, vx[0].z, vx[0].w, P[1], P[2]);
                mma16816_z(o1, vx[2].x, vx[2].y, vx[2].z, vx[2].w, P[1], P[2]);
                mma16816(sm, ONES, ONES, ONES, ONES, P[3], P[4]);
                mma16816(o0, vx[1].x, vx[1].y, vx[1].z, vx[1].w, P[3], P[4]);
                mma16816(o1, vx[3].x, vx[3].y, vx[3].z, vx[3].w, P[3], P[4]);
                mma1688(sm, ONES, ONES, P[0]);
                mma1688(o0, vm.x, vm.y, P[0]);
                mma1688(o1, vm.z, vm.w, P[0]);
                const float sig = __uint_as_float((268u << 23) - ebits);
                const float r0 = rcp_fast(sm[0]) * sig, r1 = rcp_fast(sm[1]) * sig;
                stsm4t(sb + O_OF + c * 512 + l16, pack_bf16(o0[0] * r0, o0[1] * r1), pack_bf16(o0[2] * r0, o0[3] * r1),
                       pack_bf16(o1[0] * r0, o1[1] * r1), pack_bf16(o1[2] * r0, o1[3] * r1));
                bar_sync(6, 128);
                uint4 ob[4];
#pragma unroll
                for (int q = 0; q < 4; q++) ob[q] = ldsm4(sb + O_OF + q * 512 + l16);
                { const uint4 v = lds128(sb + O_WP + c * 512 + l16); a[92] = v.x; a[93] = v.y; a[94] = v.z; a[95] = v.w; }
                float m0[3][4], m1[3][4];
#pragma unroll
                for (int q = 0; q < 4; q++) {
#pragma unroll
                    for (int i = 0; i < 3; i++) {
                        const int k0 = (i * 8 + 2 * q) * 4;
                        if (q == 0) mma16816_z(m0[i], a[k0], a[k0 + 1], a[k0 + 2], a[k0 + 3], ob[q].x, ob[q].y);
                        else mma16816(m0[i], a[k0], a[k0 + 1], a[k0 + 2], a[k0 + 3], ob[q].x, ob[q].y);
                    }
#pragma unroll
                    for (int i = 0; i < 3; i++) {
                        const int k1 = (i * 8 + 2 * q + 1) * 4;
                        if (q == 0) mma16816_z(m1[i], a[k1], a[k1 + 1], a[k1 + 2], a[k1 + 3], ob[q].z, ob[q].w);
                        else mma16816(m1[i], a[k1], a[k1 + 1], a[k1 + 2], a[k1 + 3], ob[q].z, ob[q].w);
                    }
                }
                if (EARLY5) {
                    const uint32_t z = __float_as_uint(m0[2][0]) & (l16 & 15u);
                    bar_arrive(5 + z, 256); bar_arrive(13 + z, 256);
                }
                asm volatile("red.relaxed.gpu.global.add.noftz.v4.f16x2 [%0], {%1,%2,%3,%4};" :: "l"(reinterpret_cast<char*>(g_acc) + roff),
                    "r"(pack_f16(m0[0][0] + m1[0][0], m0[0][2] + m1[0][2])), "r"(pack_f16(m0[1][0] + m1[1][0], m0[1][2] + m1[1][2])),
                    "r"(pack_f16(m0[2][0] + m1[2][0], m0[2][2] + m1[2][2])), "r"(0x3c00u) : "memory");
                asm volatile("red.relaxed.gpu.global.add.noftz.v4.f16x2 [%0], {%1,%2,%3,%4};" :: "l"(reinterpret_cast<char*>(g_acc) + roff + 1024),
                    "r"(pack_f16(m0[0][1] + m1[0][1], m0[0][3] + m1[0][3])), "r"(pack_f16(m0[1][1] + m1[1][1], m0[1][3] + m1[1][3])),
                    "r"(pack_f16(m0[2][1] + m1[2][1], m0[2][3] + m1[2][3])), "r"(0x3c00u) : "memory");
                const unsigned t_red = clk();
                if (!EARLY5) { bar_arrive(5, 256); bar_arrive(13, 256); }
                mbar_expect_if(l16 | c, sb + B_SC, 4608);
                mbar_expect_if(l16 | (c ^ 1) | (r >> 1), sb + B_VX + 8 * ((s + 1) & 1), 8192);
                sts32_if(l16 | (c ^ 3), sb + O_MISC, ebits - (14u << 23));
                if (c == 0) STAMPV(s, 8, t_red);
                if (ACC_PF && c == 2 && s + 4 < NSEG - 1)
                    asm volatile("prefetch.global.L2 [%0];" :: "l"(reinterpret_cast<const char*>(g_acc) + ((s + 4) * 96 + blockIdx.x) * 256 + (l16 & 96)) : "memory");
                const char* pbase = reinterpret_cast<const char*>(g_acc) + (s * 24576 + c * 2048) + ((l16 & 64) * 16 + (l16 & 256) + ((l16 & 128) >> 1) + (l16 & 48));
                spin_until(t_red, D_WAIT);
                uint4 v[6];
#pragma unroll
                for (int i = 0; i < 6; i++) v[i] = ldg_relaxed128(pbase + (i >> 1) * 8192 + (i & 1) * 512);
                int nretry = 0;
                auto convert = [&](int tau, uint4& A, uint4& B) {
                    A.x = f16x2_to_bf16x2(A.x); B.x = f16x2_to_bf16x2(B.x); A.y = f16x2_to_bf16x2(A.y); B.y = f16x2_to_bf16x2(B.y);
                    A.z = f16x2_to_bf16x2(A.z); B.z = f16x2_to_bf16x2(B.z);
                    sts128(sb + O_MF + tau * 3072 + c * 512 + l16, A.x, B.x, A.y, B.y);
                    sts64(sb + O_MF + tau * 3072 + 2048 + (c >> 1) * 512 + (c & 1) * 8 + l16, A.z, B.z);
                };
                const uint32_t ok0 = __all_sync(~0u, (v[0].w & v[1].w) == 0x5000u);
                convert(0, v[0], v[1]);
                asm volatile("{\n.reg .pred p;\nsetp.ne.u32 p, %0, 0;\n@p bar.arrive 2, 384;\n}" :: "r"(ok0) : "memory");
                sched_fence<0>(h);
                uint32_t ok1;
                asm volatile("{\n.reg .pred p, q;\n.reg .b32 x;\nlop3.b32 x, %1, %2, %3, 0x80;\nand.b32 x, x, %4;\n"
                             "setp.eq.u32 p, x, 0x5000;\nvote.sync.all.pred q, p, 0xffffffff;\nselp.u32 %0, 1, 0, q;\n}"
                             : "=r"(ok1) : "r"(v[2].w), "r"(v[3].w), "r"(v[4].w), "r"(v[5].w));
                convert(1, v[2], v[3]); convert(2, v[4], v[5]);
                asm volatile("{\n.reg .pred p;\nsetp.ne.u32 p, %0, 0;\n@p bar.arrive 15, 384;\n}" :: "r"(ok1) : "memory");
                if (ok0 & ok1) {
                    mmax = absmax2(absmax2(absmax2(v[0].x, v[0].y), absmax2(v[0].z, v[1].x)), absmax2(absmax2(v[1].y, v[1].z), absmax2(v[2].x, v[2].y)));
                    mmax = absmax2(mmax, absmax2(absmax2(absmax2(v[2].z, v[3].x), absmax2(v[3].y, v[3].z)), absmax2(absmax2(v[4].x, v[4].y), absmax2(v[4].z, v[5].x))));
                    mmax = absmax2(mmax, absmax2(v[5].y, v[5].z));
                } else {
                    const uint32_t bad1 = !__all_sync(~0u, (v[2].w & v[3].w) == 0x5000u), bad2 = !__all_sync(~0u, (v[4].w & v[5].w) == 0x5000u);
                    uint4 u[6];
                    asm volatile("{\n.reg .pred p0, p1, p2, q;\n.reg .u32 n, x;\nmov.u32 n, 0;\n"
                         "setp.eq.u32 p0, %26, 0;\nsetp.ne.u32 p1, %27, 0;\nsetp.ne.u32 p2, %28, 0;\n"
                         "mov.u32 %0, 0; mov.u32 %1, 0; mov.u32 %2, 0; mov.u32 %3, 0x5000; mov.u32 %4, 0; mov.u32 %5, 0; mov.u32 %6, 0; mov.u32 %7, 0x5000;\n"
                         "mov.u32 %8, 0; mov.u32 %9, 0; mov.u32 %10, 0; mov.u32 %11, 0x5000; mov.u32 %12, 0; mov.u32 %13, 0; mov.u32 %14, 0; mov.u32 %15, 0x5000;\n"
                         "mov.u32 %16, 0; mov.u32 %17, 0; mov.u32 %18, 0; mov.u32 %19, 0x5000; mov.u32 %20, 0; mov.u32 %21, 0; mov.u32 %22, 0; mov.u32 %23, 0x5000;\n"
                         "R_%=: @p0 ld.relaxed.gpu.global.v4.u32 {%0,%1,%2,%3}, [%25];\n@p0 ld.relaxed.gpu.global.v4.u32 {%4,%5,%6,%7}, [%25+512];\n"
                         "@p1 ld.relaxed.gpu.global.v4.u32 {%8,%9,%10,%11}, [%25+8192];\n@p1 ld.relaxed.gpu.global.v4.u32 {%12,%13,%14,%15}, [%25+8704];\n"
                         "@p2 ld.relaxed.gpu.global.v4.u32 {%16,%17,%18,%19}, [%25+16384];\n@p2 ld.relaxed.gpu.global.v4.u32 {%20,%21,%22,%23}, [%25+16896];\n"
                         "add.u32 %24, %24, 1;\nand.b32 x, %3, %7;\nsetp.ne.u32 p0, x, 0x5000;\nand.b32 x, %11, %15;\nsetp.ne.u32 p1, x, 0x5000;\n"
                         "and.b32 x, %19, %23;\nsetp.ne.u32 p2, x, 0x5000;\nor.pred q, p0, p1;\nor.pred q, q, p2;\nvote.sync.any.pred q, q, 0xffffffff;\n@!q bra.uni K_%=;\n"
                         "add.u32 n, n, 1;\nsetp.lt.u32 q, n, 2000000;\n@q bra.uni R_%=;\ntrap;\nK_%=:\n}"
                         : "=&r"(u[0].x), "=&r"(u[0].y), "=&r"(u[0].z), "=&r"(u[0].w), "=&r"(u[1].x), "=&r"(u[1].y), "=&r"(u[1].z), "=&r"(u[1].w),
                           "=&r"(u[2].x), "=&r"(u[2].y), "=&r"(u[2].z), "=&r"(u[2].w), "=&r"(u[3].x), "=&r"(u[3].y), "=&r"(u[3].z), "=&r"(u[3].w),
                           "=&r"(u[4].x), "=&r"(u[4].y), "=&r"(u[4].z), "=&r"(u[4].w), "=&r"(u[5].x), "=&r"(u[5].y), "=&r"(u[5].z), "=&r"(u[5].w), "+r"(nretry)
                         : "l"(pbase), "r"(ok0), "r"(bad1), "r"(bad2) : "memory");
                    if (!ok0) { convert(0, u[0], u[1]); bar_arrive(2, 384); }
                    if (bad1) convert(1, u[2], u[3]);
                    if (bad2) convert(2, u[4], u[5]);
                    if (!ok1) bar_arrive(15, 384);
                    mmax = 0;
#pragma unroll
                    for (int tau = 0; tau < 3; tau++) {
                        const uint4 A = lds128(sb + O_MF + tau * 3072 + c * 512 + l16);
                        const float2 B = lds64f(sb + O_MF + tau * 3072 + 2048 + (c >> 1) * 512 + (c & 1) * 8 + l16);
                        mmax = absmax2(absmax2(mmax, absmax2(A.x, A.y)), absmax2(absmax2(A.z, A.w), absmax2(__float_as_uint(B.x), __float_as_uint(B.y))));
                    }
                }
                if (c == 0) STAMP(s, 12);
                if (c == 0) STAMPV(s, 14, nretry);
                mmax &= 0x7fff7fffu;
                mmax = max(mmax << 16, mmax & 0xffff0000u);
            }
            roff += 24576;
        }
        {
            bar_sync(7, 384);
            if (c == 0) flag_inc_if(l16c, &g_flag[F_QKV + (60 + (h >> 3)) * 8]);
        }
    }
    if (warp == 8) PSTAMP(13);
    cluster_sync();
}

constexpr int NST = 10;
constexpr int G_RING = 0, G_EX = NST * 16384, G_OUT = G_EX + 32768, G_CARRY = G_OUT + 32768, G_BAR = G_CARRY + 512, BG_SMEM = G_BAR + 256;
constexpr int GB_FULL = G_BAR, GB_EMPTY = G_BAR + 8 * NST, GB_W = G_BAR + 16 * NST;
static_assert(BG_SMEM <= 232448, "smem");

template <int ACC>
__device__ __forceinline__ void wgmma_n128_rs(float (&d)[64], uint32_t a0, uint32_t a1, uint32_t a2, uint32_t a3, uint64_t desc) {
    asm volatile("wgmma.mma_async.sync.aligned.m64n128k16.f32.bf16.bf16 "
        "{%0,%1,%2,%3,%4,%5,%6,%7,%8,%9,%10,%11,%12,%13,%14,%15,%16,%17,%18,%19,%20,%21,%22,%23,%24,%25,%26,%27,%28,%29,%30,%31,"
        "%32,%33,%34,%35,%36,%37,%38,%39,%40,%41,%42,%43,%44,%45,%46,%47,%48,%49,%50,%51,%52,%53,%54,%55,%56,%57,%58,%59,%60,%61,%62,%63}, "
        "{%64,%65,%66,%67}, %68, %69, 1, 1, 0;"
        : "+f"(d[0]), "+f"(d[1]), "+f"(d[2]), "+f"(d[3]), "+f"(d[4]), "+f"(d[5]), "+f"(d[6]), "+f"(d[7]),
          "+f"(d[8]), "+f"(d[9]), "+f"(d[10]), "+f"(d[11]), "+f"(d[12]), "+f"(d[13]), "+f"(d[14]), "+f"(d[15]),
          "+f"(d[16]), "+f"(d[17]), "+f"(d[18]), "+f"(d[19]), "+f"(d[20]), "+f"(d[21]), "+f"(d[22]), "+f"(d[23]),
          "+f"(d[24]), "+f"(d[25]), "+f"(d[26]), "+f"(d[27]), "+f"(d[28]), "+f"(d[29]), "+f"(d[30]), "+f"(d[31]),
          "+f"(d[32]), "+f"(d[33]), "+f"(d[34]), "+f"(d[35]), "+f"(d[36]), "+f"(d[37]), "+f"(d[38]), "+f"(d[39]),
          "+f"(d[40]), "+f"(d[41]), "+f"(d[42]), "+f"(d[43]), "+f"(d[44]), "+f"(d[45]), "+f"(d[46]), "+f"(d[47]),
          "+f"(d[48]), "+f"(d[49]), "+f"(d[50]), "+f"(d[51]), "+f"(d[52]), "+f"(d[53]), "+f"(d[54]), "+f"(d[55]),
          "+f"(d[56]), "+f"(d[57]), "+f"(d[58]), "+f"(d[59]), "+f"(d[60]), "+f"(d[61]), "+f"(d[62]), "+f"(d[63])
        : "r"(a0), "r"(a1), "r"(a2), "r"(a3), "l"(desc), "n"(ACC));
}
__device__ __forceinline__ void wait_flag(const unsigned* p, unsigned target) {
    asm volatile("{\n.reg .pred p;\n.reg .u32 n, v;\nmov.u32 n, 0;\n"
                 "W_%=: ld.acquire.gpu.global.u32 v, [%0];\nsub.u32 v, v, %1;\nsetp.ge.s32 p, v, 0;\n@p bra.uni D_%=;\nnanosleep.u32 100;\n"
                 "add.u32 n, n, 1;\nsetp.lt.u32 p, n, 4000000;\n@p bra.uni W_%=;\ntrap;\nD_%=:\n}" :: "l"(p), "r"(target) : "memory");
}
template <int NS, int STRIDE>
__device__ __forceinline__ void bg_mainloop(float (&d)[64], const uint32_t (&a)[144], uint32_t sb, int it, int lane) {
    int slot = it % NST, ph = (it / NST) & 1, prev = 0;
#pragma unroll
    for (int i = 0; i < NS; i++) {
        mbar_wait(sb + GB_FULL + 8 * slot, ph);
        const uint64_t desc = (uint64_t)(((sb + G_RING + slot * 16384) & 0x3FFFF) >> 4) | (1ull << 16) | (64ull << 32) | (1ull << 62);
        wg_fence();
#pragma unroll
        for (int k = 0; k < 4; k++) {
            const int u = 16 * i + 4 * k;
            if (i == 0 && k == 0) wgmma_n128_rs<0>(d, a[u], a[u + 1], a[u + 2], a[u + 3], desc);
            else wgmma_n128_rs<1>(d, a[u], a[u + 1], a[u + 2], a[u + 3], desc + 2 * k);
        }
        wg_commit();
        if (i > 0) {
            asm volatile("wgmma.wait_group.sync.aligned 1;" ::: "memory");
            mbar_arrive_if(lane, sb + GB_EMPTY + 8 * prev);
        }
        prev = slot;
        slot += STRIDE;
        if (slot >= NST) { slot -= NST; ph ^= 1; }
    }
    wg_wait0();
    mbar_arrive_if(lane, sb + GB_EMPTY + 8 * prev);
}
template <bool SKIP>
__device__ __forceinline__ void bg_epilogue(float (&d)[64], uint32_t sb, int wg, int w, int lane, const CUtensorMap* tm_out, int col0, int tok0,
                                            const __nv_bfloat16* xa, const __nv_bfloat16* Dk) {
    const int g = lane >> 2, t = lane & 3;
    const uint32_t ex = sb + G_EX + w * 4096 + lane * 16;
    float k[32];
    if (wg == 0) {
#pragma unroll
        for (int q = 0; q < 8; q++) sts128f(ex + q * 512, d[32 + 4 * q], d[32 + 4 * q + 1], d[32 + 4 * q + 2], d[32 + 4 * q + 3]);
#pragma unroll
        for (int i = 0; i < 32; i++) k[i] = d[i];
    } else {
#pragma unroll
        for (int q = 0; q < 8; q++) sts128f(ex + 16384 + q * 512, d[4 * q], d[4 * q + 1], d[4 * q + 2], d[4 * q + 3]);
#pragma unroll
        for (int i = 0; i < 32; i++) k[i] = d[32 + i];
    }
    uint32_t xv[16], dv = 0;
    if (SKIP) {
        const __nv_bfloat16* xp = xa + (size_t)(tok0 + 64 * wg + 2 * t) * DM + col0 + 16 * w + 2 * g;
#pragma unroll
        for (int i = 0; i < 16; i++) xv[i] = ldg_nc32(xp + (8 * (i >> 1) + (i & 1)) * DM);
        dv = ldg_nc32(Dk + col0 + 16 * w + 2 * g);
    }
    if (SKIP && w == 0) asm volatile("cp.async.bulk.wait_group.read 0;" ::: "memory");
    bar_sync(1, 256);
#pragma unroll
    for (int q = 0; q < 8; q++) {
        const float4 o = lds128f(ex + (wg ^ 1) * 16384 + q * 512);
        k[4 * q] += o.x; k[4 * q + 1] += o.y; k[4 * q + 2] += o.z; k[4 * q + 3] += o.w;
    }
    if (SKIP) bar_sync(1, 256); else bar_sync(13, 288);
    const uint32_t ob = sb + G_OUT + wg * 16384 + (w >> 1) * 8192 + (g & 1) * 8;
    const uint32_t ch = (w & 1) * 4 + (g >> 1);
#pragma unroll
    for (int i = 0; i < 16; i++) {
        float v0 = k[4 * (i >> 1) + (i & 1)], v1 = k[4 * (i >> 1) + 2 + (i & 1)];
        if (SKIP) {
            const uint32_t p = pack_bf16(__uint_as_float(xv[i] << 16) * __uint_as_float(dv << 16), __uint_as_float(xv[i] & 0xffff0000u) * __uint_as_float(dv & 0xffff0000u));
            v0 += __uint_as_float(p << 16); v1 += __uint_as_float(p & 0xffff0000u);
        }
        const uint32_t n7 = 2 * t + (i & 1);
        sts64(ob + (8 * (i >> 1) + n7) * 128 + ((ch ^ n7) << 4), __float_as_uint(v0), __float_as_uint(v1));
    }
    fence_async_smem();
    if (SKIP) {
        bar_sync(4 + wg, 128);
        if (w == 0)
            asm volatile("{\n.reg .pred p;\nelect.sync _|p, 0xffffffff;\n"
                "@p cp.async.bulk.tensor.2d.global.shared::cta.bulk_group [%0, {%2, %4}], [%1];\n"
                "@p cp.async.bulk.tensor.2d.global.shared::cta.bulk_group [%0, {%3, %4}], [%1+8192];\n@p cp.async.bulk.commit_group;\n}"
                :: "l"(tm_out), "r"(sb + G_OUT + wg * 16384), "r"(col0), "r"(col0 + 32), "r"(tok0 + 64 * wg) : "memory");
    } else {
        bar_arrive(12, 288);
    }
}
__device__ __forceinline__ void s5_channel(int p, const __nv_bfloat16* Lre, const __nv_bfloat16* Lim, const __nv_bfloat16* logdt, float2& lam, float2& coef) {
    const float dt = __bfloat162float(__float2bfloat16(expf(__bfloat162float(logdt[p]))));
    const float lr = __bfloat162float(Lre[p]), li = __bfloat162float(Lim[p]);
    const float e = expf(dt * lr);
    float sn, cs;
    sincosf(dt * li, &sn, &cs);
    lam = make_float2(e * cs, e * sn);
    const float den = lr * lr + li * li;
    coef = make_float2(((lam.x - 1.f) * lr + lam.y * li) / den, (lam.y * lr - (lam.x - 1.f) * li) / den);
}
__device__ __forceinline__ float2 cfma(float2 a, float2 b, float2 c) {
    return make_float2(fmaf(a.x, b.x, fmaf(-a.y, b.y, c.x)), fmaf(a.x, b.y, fmaf(a.y, b.x, c.y)));
}
__device__ __forceinline__ uint4 ldg128(const void* p) { uint4 v; asm volatile("ld.global.v4.u32 {%0,%1,%2,%3}, [%4];" : "=r"(v.x), "=r"(v.y), "=r"(v.z), "=r"(v.w) : "l"(p) : "memory"); return v; }
__device__ __forceinline__ uint2 ldg64(const void* p) { uint2 v; asm volatile("ld.global.v2.u32 {%0,%1}, [%2];" : "=r"(v.x), "=r"(v.y) : "l"(p) : "memory"); return v; }

__device__ __forceinline__ void bg_attention(uint32_t st0, uint32_t st1, int mt, int lane) {
    const int g = lane >> 2, t = lane & 3;
    float sc[5][4];
#pragma unroll
    for (int n = 0; n < 5; n++) sc[n][0] = sc[n][1] = sc[n][2] = sc[n][3] = 0.f;
    float sm2[4] = {0.f, 0.f, 0.f, 0.f};
#pragma unroll
    for (int i = 0; i < 8; i++) {
        const uint32_t st = (i >> 2 ? st1 : st0) + (i & 3) * 512 + lane * 16;
        const uint4 q = ldsm4(st + mt * 2048), km = ldsm4(st + 8192), k0 = ldsm4(st + 4096);
        mma16816(sc[0], q.x, q.y, q.z, q.w, km.x, km.y);
        mma16816(sm2, q.x, q.y, q.z, q.w, km.z, km.w);
        mma16816(sc[1], q.x, q.y, q.z, q.w, k0.x, k0.y);
        mma16816(sc[2], q.x, q.y, q.z, q.w, k0.z, k0.w);
        if (mt) {
            const uint4 k1 = ldsm4(st + 6144);
            mma16816(sc[3], q.x, q.y, q.z, q.w, k1.x, k1.y);
            mma16816(sc[4], q.x, q.y, q.z, q.w, k1.z, k1.w);
        }
    }
#pragma unroll
    for (int i = 0; i < 4; i++) sc[0][i] += sm2[i];
    const int q0 = 16 * mt + 8 + g - 2 * t;
#pragma unroll
    for (int n = 1; n < 5; n++) {
        if (8 * n > q0) sc[n][0] = -INFINITY;
        if (8 * n + 1 > q0) sc[n][1] = -INFINITY;
        if (8 * n > q0 + 8) sc[n][2] = -INFINITY;
        if (8 * n + 1 > q0 + 8) sc[n][3] = -INFINITY;
    }
    float ma = fmaxf(sc[0][0], sc[0][1]), mb = fmaxf(sc[0][2], sc[0][3]);
#pragma unroll
    for (int n = 1; n < 5; n++) { ma = fmaxf(ma, fmaxf(sc[n][0], sc[n][1])); mb = fmaxf(mb, fmaxf(sc[n][2], sc[n][3])); }
    ma = quad_max(ma) * SM_SCALE; mb = quad_max(mb) * SM_SCALE;
    uint32_t Pa[5], Pb[5];
#pragma unroll
    for (int n = 0; n < 5; n++) {
        Pa[n] = pack_bf16(ex2(fmaf(sc[n][0], SM_SCALE, -ma)), ex2(fmaf(sc[n][1], SM_SCALE, -ma)));
        Pb[n] = pack_bf16(ex2(fmaf(sc[n][2], SM_SCALE, -mb)), ex2(fmaf(sc[n][3], SM_SCALE, -mb)));
    }
    float sa[4], sbb[4];
    mma1688_z(sa, ONES, ONES, Pa[0]); mma1688_z(sbb, ONES, ONES, Pb[0]);
    mma16816(sa, ONES, ONES, ONES, ONES, Pa[1], Pa[2]); mma16816(sbb, ONES, ONES, ONES, ONES, Pb[1], Pb[2]);
    mma16816(sa, ONES, ONES, ONES, ONES, Pa[3], Pa[4]); mma16816(sbb, ONES, ONES, ONES, ONES, Pb[3], Pb[4]);
    const float ra0 = rcp_fast(sa[0]), ra1 = rcp_fast(sa[1]), rb0 = rcp_fast(sbb[0]), rb1 = rcp_fast(sbb[1]);
    const uint32_t row = lane & 7;
    const uint32_t so = mt * 2048 + (lane >> 4) * 1024 + row * 128;
#pragma unroll
    for (int i = 0; i < 8; i++) {
        const uint32_t st = i >> 2 ? st1 : st0;
        const int e4 = i & 3;
        const float2 vmf = lds64f(st + 14336 + e4 * 256 + lane * 8);
        const uint32_t vm0 = __float_as_uint(vmf.x), vm1 = __float_as_uint(vmf.y);
        const uint4 v0 = lds128(st + 10240 + e4 * 1024 + lane * 16);
        float oa[4], ob[4];
        mma1688_z(oa, vm0, vm1, Pa[0]); mma1688_z(ob, vm0, vm1, Pb[0]);
        mma16816(oa, v0.x, v0.y, v0.z, v0.w, Pa[1], Pa[2]);
        mma16816(ob, v0.x, v0.y, v0.z, v0.w, Pb[1], Pb[2]);
        if (mt) {
            const uint4 v1 = lds128(st + 10240 + e4 * 1024 + 512 + lane * 16);
            mma16816(oa, v1.x, v1.y, v1.z, v1.w, Pa[3], Pa[4]);
            mma16816(ob, v1.x, v1.y, v1.z, v1.w, Pb[3], Pb[4]);
        }
        stsm4t(st + so + (((2 * e4 + ((lane >> 3) & 1)) ^ row) << 4), pack_bf16(oa[0] * ra0, oa[1] * ra1), pack_bf16(oa[2] * ra0, oa[3] * ra1),
               pack_bf16(ob[0] * rb0, ob[1] * rb1), pack_bf16(ob[2] * rb0, ob[3] * rb1));
    }
}
__device__ __forceinline__ bool bg_att_turn(int na, int ng) { return na == ng || (na == ng + 1 && na <= BG_AHEAD); }

__global__ void __launch_bounds__(384, 1)
bg_kernel(const __grid_constant__ CUtensorMap tm_xa, const __grid_constant__ CUtensorMap tm_wo, const __grid_constant__ CUtensorMap tm_out,
          const __nv_bfloat16* __restrict__ xa, const __nv_bfloat16* __restrict__ Lre, const __nv_bfloat16* __restrict__ Lim,
          const __nv_bfloat16* __restrict__ Bre, const __nv_bfloat16* __restrict__ Bim, const __nv_bfloat16* __restrict__ Cre,
          const __nv_bfloat16* __restrict__ Cim, const __nv_bfloat16* __restrict__ logdt, const __nv_bfloat16* __restrict__ Dk) {
    extern __shared__ __align__(1024) uint8_t smem_raw[];
    const uint32_t sb = smem_u32(smem_raw);
    const int lane = threadIdx.x & 31;
    const int warp = __shfl_sync(~0u, threadIdx.x >> 5, 0);
    const int wg = warp >> 2, w = warp & 3, b = blockIdx.x;
    const int nt = b % 9, kq = b / 9;
    BSTAMP(0);
    if (threadIdx.x == 0) {
        if (sb & 1023u) __trap();
        for (int i = 0; i < NST; i++) { mbar_init(sb + GB_FULL + 8 * i, 1); mbar_init(sb + GB_EMPTY + 8 * i, 4); }
        mbar_init(sb + GB_W, 1);
        asm volatile("fence.mbarrier_init.release.cluster;" ::: "memory");
        mbar_expect(sb + GB_W, (b < 18 ? 64 : 128) * 1152);
        sts32(sb + G_BAR + 248, atomicAdd(&g_ticket_bg, 1u) / 36u + 1u);
    }
    __syncthreads();
    if (wg == 2) {
        asm volatile("setmaxnreg.dec.sync.aligned.u32 24;");
        if (w == 0) {
            int slot = 0, ph = 1;
            unsigned tlast = clk();
            auto pace = [&]() { if (BG_PACE) { spin_until(tlast, BG_PACE); tlast = clk(); } };
            auto next = [&]() { if (++slot == NST) { slot = 0; ph ^= 1; } };
            bar_sync(6, 288);
            if (b < 18) {
#pragma unroll 1
                for (int i = 0; i < 144; i++) {
                    const int blk = i / 9, kb = i - 9 * blk, it = (blk >> 1) * 18 + (blk & 1) + 2 * kb;
                    slot = it % NST;
                    mbar_wait(sb + GB_EMPTY + 8 * slot, ((it / NST) & 1) ^ 1);
                    pace();
                    asm volatile("{\n.reg .pred p;\nelect.sync _|p, 0xffffffff;\n@p mbarrier.arrive.expect_tx.shared::cta.b64 _, [%2], 16384;\n"
                        "@p cp.async.bulk.tensor.5d.shared::cluster.global.mbarrier::complete_tx::bytes [%0], [%1, {%3, %4, %4, %4, %5}], [%2];\n}"
                        :: "r"(sb + G_RING + slot * 16384), "l"(&tm_xa), "r"(sb + GB_FULL + 8 * slot), "r"(kb * 64), "r"(0), "r"(blk) : "memory");
                }
                slot = 144 % NST; ph = ((144 / NST) & 1) ^ 1;
            }
            const unsigned ep = lds32(sb + G_BAR + 248);
            auto slabs = [&](const char* src, int ns) {
                asm volatile("fence.proxy.async.global;" ::: "memory");
#pragma unroll 1
                for (int i = 0; i < ns; i++) {
                    mbar_wait(sb + GB_EMPTY + 8 * slot, ph);
                    pace();
                    asm volatile("{\n.reg .pred p;\nelect.sync _|p, 0xffffffff;\n@p mbarrier.arrive.expect_tx.shared::cta.b64 _, [%2], 16384;\n"
                        "@p cp.async.bulk.shared::cluster.global.mbarrier::complete_tx::bytes [%0], [%1], 16384, [%2];\n}"
                        :: "r"(sb + G_RING + slot * 16384), "l"(src + (size_t)((i & 1) * (ns >> 1) + (i >> 1)) * (SEQ * 128)), "r"(sb + GB_FULL + 8 * slot) : "memory");
                    next();
                }
            };
            if (b >= 18) {
#pragma unroll 1
                for (int blk = kq - 2; blk < 16; blk += 2) {
                    wait_flag(&g_flag[F_H + blk * 8], 18 * ep);
                    slabs(reinterpret_cast<const char*>(g_h) + blk * 16384, 18);
                }
            }
            bar_sync(6, 288);
#pragma unroll 1
            for (int na = 0, ng = 0; ng < 16;) {
                if (bg_att_turn(na, ng)) {
                    if (nt < 8) {
                        wait_flag(&g_flag[F_QKV + (na * 4 + kq) * 8], 24 * ep);
                        asm volatile("fence.proxy.async.global;" ::: "memory");
#pragma unroll 1
                        for (int i = 0; i < 8; i++) {
                            const int pr = nt * 4 + 2 * (i & 1) + (i >> 2), hf = (i >> 1) & 1;
                            const char* rec = reinterpret_cast<const char*>(g_qkv) + (size_t)((4 * na + (pr >> 3)) * NH + 8 * kq + (pr & 7)) * REC;
                            mbar_wait(sb + GB_EMPTY + 8 * slot, ph);
                    pace();
                            asm volatile("{\n.reg .pred p;\nelect.sync _|p, 0xffffffff;\n@p mbarrier.arrive.expect_tx.shared::cta.b64 _, [%4], 15360;\n"
                                "@p cp.async.bulk.shared::cluster.global.mbarrier::complete_tx::bytes [%0], [%1], 10240, [%4];\n"
                                "@p cp.async.bulk.shared::cluster.global.mbarrier::complete_tx::bytes [%0+10240], [%2], 4096, [%4];\n"
                                "@p cp.async.bulk.shared::cluster.global.mbarrier::complete_tx::bytes [%0+14336], [%3], 1024, [%4];\n}"
                                :: "r"(sb + G_RING + slot * 16384), "l"(rec + hf * 10240), "l"(rec + 20480 + hf * 4096), "l"(rec + 28672 + hf * 1024),
                                   "r"(sb + GB_FULL + 8 * slot) : "memory");
                            next();
                        }
                    }
                    na++;
                } else {
                    wait_flag(&g_flag[F_OX + (ng * 4 + kq) * 8], 8 * ep);
                    slabs(reinterpret_cast<const char*>(g_ox) + (size_t)kq * 16 * SEQ * 128 + ng * 16384, 16);
                    ng++;
                }
            }
        } else if (w == 1) {
            if (b < 18) {
#pragma unroll 1
                for (int blk = 0; blk < 16; blk++) {
                    bar_sync(8 + (blk & 1), 160);
                    asm volatile("{\n.reg .pred p;\nelect.sync _|p, 0xffffffff;\n@p cp.async.bulk.global.shared::cta.bulk_group [%0], [%1], 16384;\n"
                        "@p cp.async.bulk.commit_group;\ncp.async.bulk.wait_group 0;\nfence.proxy.async.global;\n}"
                        :: "l"(reinterpret_cast<char*>(g_h) + ((size_t)b * SEQ + blk * 128) * 128), "r"(sb + G_OUT + (blk & 1) * 16384) : "memory");
                    bar_arrive(10 + (blk & 1), 160);
                    flag_inc_if(lane, &g_flag[F_H + blk * 8]);
                }
            }
            if (nt < 8) {
                int it = 144;
#pragma unroll 1
                for (int na = 0, ng = 0; ng < 16;) {
                    if (bg_att_turn(na, ng)) {
                        bar_sync(7, 288);
                        if (lane < 8) {
                            const int pr = nt * 4 + 2 * (lane & 1) + (lane >> 2), hf = (lane >> 1) & 1;
                            asm volatile("cp.async.bulk.global.shared::cta.bulk_group [%0], [%1], 4096;\ncp.async.bulk.commit_group;\ncp.async.bulk.wait_group.read 0;\n"
                                "mbarrier.arrive.shared::cta.b64 _, [%2], 4;\ncp.async.bulk.wait_group 0;\nfence.proxy.async.global;"
                                :: "l"(reinterpret_cast<char*>(g_ox) + ((size_t)((8 * kq + (pr & 7)) * 2 + hf) * SEQ + (4 * na + (pr >> 3)) * 32) * 128),
                                   "r"(sb + G_RING + ((it + lane) % NST) * 16384), "r"(sb + GB_EMPTY + 8 * ((it + lane) % NST)) : "memory");
                        }
                        __syncwarp();
                        flag_inc_if(lane, &g_flag[F_OX + (na * 4 + kq) * 8]);
                        it += 8; na++;
                    } else { it += 16; ng++; }
                }
            }
        } else if (w == 2) {
            const unsigned ep = lds32(sb + G_BAR + 248);
#pragma unroll 1
            for (int blk = 0; blk < 16; blk++) {
                bar_arrive(13, 288);
                bar_sync(12, 288);
                if (kq) { wait_flag(&g_flag[F_OUT + (blk * 9 + nt) * 8], ep); asm volatile("fence.proxy.async.global;" ::: "memory"); }
                unsigned t0 = clk();
                if (blk < 15) spin_until(t0, b * (RED_GAP / 36));
#pragma unroll 1
                for (int i = 0; i < 4; i++) {
                    const uint32_t src = sb + G_OUT + i * 8192;
                    const int c0 = DM + 64 * nt + (i & 1) * 32, c1 = blk * 128 + (i >> 1) * 64;
                    if (kq) {
                        asm volatile("{\n.reg .pred p;\nelect.sync _|p, 0xffffffff;\n@p cp.reduce.async.bulk.tensor.2d.global.shared::cta.add.bulk_group [%0, {%2, %3}], [%1];\n}"
                            :: "l"(&tm_out), "r"(src), "r"(c0), "r"(c1) : "memory");
                        t0 = clk();
                        if (blk < 15 && i < 3) spin_until(t0, RED_GAP);
                    } else {
                        asm volatile("{\n.reg .pred p;\nelect.sync _|p, 0xffffffff;\n@p cp.async.bulk.tensor.2d.global.shared::cta.bulk_group [%0, {%2, %3}], [%1];\n}"
                            :: "l"(&tm_out), "r"(src), "r"(c0), "r"(c1) : "memory");
                    }
                }
                asm volatile("cp.async.bulk.commit_group;\ncp.async.bulk.wait_group 0;\nfence.proxy.async.global;" ::: "memory");
                __syncwarp();
                if (!kq) flag_inc_if(lane, &g_flag[F_OUT + (blk * 9 + nt) * 8]);
            }
        }
    } else {
        asm volatile("setmaxnreg.inc.sync.aligned.u32 240;");
        const int g = lane >> 2, t = lane & 3, tid = threadIdx.x;
        uint32_t a[144];
        float d[64];
        if (b < 18) {
            if (tid < 64)
                asm volatile("cp.async.bulk.shared::cluster.global.mbarrier::complete_tx::bytes [%0], [%1], 1152, [%2];"
                    :: "r"(sb + tid * 1168), "l"((tid < 32 ? Bre : Bim) + (size_t)(32 * b + (tid & 31)) * DM), "r"(sb + GB_W) : "memory");
            float2 lam, coef;
            s5_channel(32 * b + 8 * w + g, Lre, Lim, logdt, lam, coef);
            float2 l32 = lam;
#pragma unroll
            for (int i = 0; i < 5; i++) l32 = make_float2(l32.x * l32.x - l32.y * l32.y, 2.f * l32.x * l32.y);
            __syncwarp();
            mbar_wait(sb + GB_W, 0);
            const uint32_t ap = sb + (((lane >> 3) & 1) * 32 + 8 * w + (lane & 7)) * 1168 + (lane >> 4) * 16;
#pragma unroll
            for (int ks = 0; ks < 36; ks++) { const uint4 v = ldsm4(ap + ks * 32); a[4 * ks] = v.x; a[4 * ks + 1] = v.y; a[4 * ks + 2] = v.z; a[4 * ks + 3] = v.w; }
            bar_sync(1, 256);
            bar_arrive(6, 288);
            BSTAMP(1);
#pragma unroll 1
            for (int blk = wg; blk < 16; blk += 2) {
                bg_mainloop<9, 2>(d, a, sb, (blk >> 1) * 18 + wg, lane);
                float2 e = make_float2(0.f, 0.f);
#pragma unroll
                for (int i = 0; i < 32; i++) e = cfma(lam, e, make_float2(d[4 * (i >> 1) + (i & 1)], d[4 * (i >> 1) + 2 + (i & 1)]));
                float2 cin = make_float2(0.f, 0.f);
                if (blk > 0) { bar_sync(2 + (wg ^ 1), 256); cin = lds64f(sb + G_CARRY + (wg ^ 1) * 256 + (8 * w + g) * 8); }
                float2 mine = cin;
#pragma unroll
                for (int q = 0; q < 4; q++) {
                    const float2 eq = make_float2(__shfl_sync(~0u, e.x, (lane & 28) + q), __shfl_sync(~0u, e.y, (lane & 28) + q));
                    cin = cfma(l32, cin, eq);
                    if (t == q + 1) mine = cin;
                }
                if (blk < 15) {
                    if (t == 0) sts64(sb + G_CARRY + wg * 256 + (8 * w + g) * 8, __float_as_uint(cin.x), __float_as_uint(cin.y));
                    bar_arrive(2 + wg, 256);
                }
                const uint32_t hs = sb + G_OUT + wg * 16384 + t * 4096 + (g & 3) * 4;
                const uint32_t ch = 2 * w + (g >> 2);
                if (blk >= 2) bar_sync(10 + wg, 160);
#pragma unroll
                for (int i = 0; i < 32; i++) {
                    mine = cfma(lam, mine, make_float2(d[4 * (i >> 1) + (i & 1)], d[4 * (i >> 1) + 2 + (i & 1)]));
                    sts32(hs + i * 128 + ((ch ^ (i & 7)) << 4), pack_bf16(mine.x, mine.y));
                }
                fence_async_smem();
                bar_arrive(8 + wg, 160);
            }
            bar_sync(10 + wg, 160);
        } else {
            if (tid < 128)
                asm volatile("cp.async.bulk.shared::cluster.global.mbarrier::complete_tx::bytes [%0], [%1], 1152, [%2];"
                    :: "r"(sb + tid * 1168), "l"((tid < 64 ? Cre : Cim) + (size_t)(64 * nt + (tid & 63)) * DM), "r"(sb + GB_W) : "memory");
            for (int p = tid; p < DM; p += 256) {
                float2 lam, coef;
                s5_channel(p, Lre, Lim, logdt, lam, coef);
                sts64(sb + G_EX + p * 8, __float_as_uint(2.f * coef.x), __float_as_uint(2.f * coef.y));
            }
            bar_sync(1, 256);
            mbar_wait(sb + GB_W, 0);
            const uint32_t cp = sb + (16 * w + 2 * g) * 1168 + (288 * wg + t) * 2;
#pragma unroll
            for (int u = 0; u < 72; u++) {
                const float2 c2 = lds64f(sb + G_EX + (288 * wg + 4 * u + t) * 8);
#pragma unroll
                for (int f = 0; f < 2; f++) {
                    unsigned short r16, i16;
                    asm volatile("ld.shared.u16 %0, [%1];" : "=h"(r16) : "r"(cp + f * 1168 + u * 8) : "memory");
                    asm volatile("ld.shared.u16 %0, [%1];" : "=h"(i16) : "r"(cp + (64 + f) * 1168 + u * 8) : "memory");
                    const float cr = __uint_as_float((uint32_t)r16 << 16), ci = __uint_as_float((uint32_t)i16 << 16);
                    a[2 * u + f] = pack_bf16(cr * c2.x - ci * c2.y, -(cr * c2.y + ci * c2.x));
                }
            }
            bar_sync(1, 256);
            bar_arrive(6, 288);
            BSTAMP(1);
#pragma unroll 1
            for (int j = 0; j < 8; j++) {
                bg_mainloop<9, 2>(d, a, sb, j * 18 + wg, lane);
                bg_epilogue<true>(d, sb, wg, w, lane, &tm_out, 64 * nt, (2 * j + kq - 2) * 128, xa, Dk);
            }
        }
        if (w == 0) asm volatile("cp.async.bulk.wait_group 0;" ::: "memory");
        bar_sync(1, 256);
        BSTAMP(2);
        if (warp == 0)
            asm volatile("{\n.reg .pred p;\nelect.sync _|p, 0xffffffff;\n@p mbarrier.arrive.expect_tx.shared::cta.b64 _, [%2], 131072;\n"
                "@p cp.async.bulk.tensor.2d.shared::cluster.global.mbarrier::complete_tx::bytes [%0], [%1, {%3, %4}], [%2];\n"
                "@p cp.async.bulk.tensor.2d.shared::cluster.global.mbarrier::complete_tx::bytes [%0+32768], [%1, {%3, %5}], [%2];\n"
                "@p cp.async.bulk.tensor.2d.shared::cluster.global.mbarrier::complete_tx::bytes [%0+65536], [%1, {%3, %6}], [%2];\n"
                "@p cp.async.bulk.tensor.2d.shared::cluster.global.mbarrier::complete_tx::bytes [%0+98304], [%1, {%3, %7}], [%2];\n}"
                :: "r"(sb), "l"(&tm_wo), "r"(sb + GB_W), "r"(64 * nt), "r"(1024 * kq), "r"(1024 * kq + 256), "r"(1024 * kq + 512), "r"(1024 * kq + 768) : "memory");
        mbar_wait(sb + GB_W, 1);
        {
            const uint32_t base = sb + wg * 65536 + 4 * t * 128 + (g & 3) * 4, ch = 2 * w + (g >> 2), r7 = (4 * t) & 7;
#pragma unroll
            for (int ks = 0; ks < 32; ks++) {
                const uint32_t w0 = lds32(base + ks * 2048 + ((ch ^ r7) << 4)), w1 = lds32(base + ks * 2048 + 256 + ((ch ^ (r7 + 2)) << 4));
                const uint32_t w2 = lds32(base + ks * 2048 + 128 + ((ch ^ (r7 + 1)) << 4)), w3 = lds32(base + ks * 2048 + 384 + ((ch ^ (r7 + 3)) << 4));
                a[4 * ks] = __byte_perm(w0, w1, 0x5410); a[4 * ks + 1] = __byte_perm(w0, w1, 0x7632);
                a[4 * ks + 2] = __byte_perm(w2, w3, 0x5410); a[4 * ks + 3] = __byte_perm(w2, w3, 0x7632);
            }
        }
        bar_sync(1, 256);
        bar_arrive(6, 288);
        BSTAMP(3);
#pragma unroll 1
        for (int na = 0, ng = 0, it = 144; ng < 16;) {
            if (bg_att_turn(na, ng)) {
                if (nt < 8) {
                    const int i0 = it + wg + 4 * (w >> 1), i1 = i0 + 2;
                    mbar_wait(sb + GB_FULL + 8 * (i0 % NST), (i0 / NST) & 1);
                    mbar_wait(sb + GB_FULL + 8 * (i1 % NST), (i1 / NST) & 1);
                    BSTAMP(8 + na * 4);
                    bg_attention(sb + G_RING + (i0 % NST) * 16384, sb + G_RING + (i1 % NST) * 16384, w & 1, lane);
                    fence_async_smem();
                    bar_arrive(7, 288);
                    bar_sync(1, 256);
                    BSTAMP(9 + na * 4);
                    it += 8;
                }
                na++;
            } else {
                bg_mainloop<8, 2>(d, a, sb, it + wg, lane);
                BSTAMP(10 + ng * 4);
                bg_epilogue<false>(d, sb, wg, w, lane, &tm_out, DM + 64 * nt, ng * 128, xa, Dk);
                BSTAMP(11 + ng * 4);
                it += 16; ng++;
            }
        }
    }
    asm volatile("griddepcontrol.wait;" ::: "memory");
}

typedef CUresult (*EncodeFn)(CUtensorMap*, CUtensorMapDataType, cuuint32_t, void*, const cuuint64_t*, const cuuint64_t*, const cuuint32_t*, const cuuint32_t*,
                             CUtensorMapInterleave, CUtensorMapSwizzle, CUtensorMapL2promotion, CUtensorMapFloatOOBfill);
}

extern "C" void kernel_launch(void* const* d_in, const int* in_sizes, int n_in, void* d_out, int out_size) {
    typedef const __nv_bfloat16* bp;
    bp Ax = (bp)d_in[0], Lre = (bp)d_in[1], Lim = (bp)d_in[2], Bre = (bp)d_in[3], Bim = (bp)d_in[4], Cre = (bp)d_in[5], Cim = (bp)d_in[6],
       logdt = (bp)d_in[7], Dk = (bp)d_in[8], Bx = (bp)d_in[9], mem0 = (bp)d_in[10], Wq = (bp)d_in[11], Wk = (bp)d_in[12], Wv = (bp)d_in[13], Wo = (bp)d_in[14];
    float* out = (float*)d_out;
    static EncodeFn enc = nullptr;
    if (!enc) {
        void* fn = nullptr; cudaDriverEntryPointQueryResult qr;
        cudaGetDriverEntryPoint("cuTensorMapEncodeTiled", &fn, cudaEnableDefault, &qr);
        enc = (EncodeFn)fn;
        cudaFuncSetAttribute(chain_kernel, cudaFuncAttributeMaxDynamicSharedMemorySize, CHAIN_SMEM);
        cudaFuncSetAttribute(bg_kernel, cudaFuncAttributeMaxDynamicSharedMemorySize, BG_SMEM);
    }
    const cuuint32_t es[5] = {1, 1, 1, 1, 1};
    auto map2d = [&](CUtensorMap* tm, CUtensorMapDataType dt, const void* p, cuuint64_t d0, cuuint64_t d1, cuuint64_t stride, cuuint32_t b0, cuuint32_t b1) {
        cuuint64_t gd[2] = {d0, d1}, gs[1] = {stride}; cuuint32_t bd[2] = {b0, b1};
        enc(tm, dt, 2, (void*)p, gd, gs, bd, es, CU_TENSOR_MAP_INTERLEAVE_NONE, CU_TENSOR_MAP_SWIZZLE_128B, CU_TENSOR_MAP_L2_PROMOTION_L2_128B,
            CU_TENSOR_MAP_FLOAT_OOB_FILL_NONE);
    };
    CUtensorMap tm_x, tm_q, tm_k, tm_v, tm_xa, tm_wo, tm_out;
    map2d(&tm_x, CU_TENSOR_MAP_DATA_TYPE_BFLOAT16, Bx, DM, SEQ, DM * 2, 64, 32);
    map2d(&tm_q, CU_TENSOR_MAP_DATA_TYPE_BFLOAT16, Wq, HD, DM, HD * 2, 64, 192);
    map2d(&tm_k, CU_TENSOR_MAP_DATA_TYPE_BFLOAT16, Wk, HD, DM, HD * 2, 64, 192);
    map2d(&tm_v, CU_TENSOR_MAP_DATA_TYPE_BFLOAT16, Wv, HD, DM, HD * 2, 64, 192);
    map2d(&tm_wo, CU_TENSOR_MAP_DATA_TYPE_BFLOAT16, Wo, DM, HD, DM * 2, 64, 256);
    map2d(&tm_out, CU_TENSOR_MAP_DATA_TYPE_FLOAT32, out, 2 * DM, SEQ, 2 * DM * 4, 32, 64);
    {
        cuuint64_t gd[5] = {DM, 2, 4, 16, 16}, gs[4] = {DM * 2, 32 * DM * 2, 2 * DM * 2, 128 * DM * 2}; cuuint32_t bd[5] = {64, 2, 4, 16, 1};
        enc(&tm_xa, CU_TENSOR_MAP_DATA_TYPE_BFLOAT16, 5, (void*)Ax, gd, gs, bd, es, CU_TENSOR_MAP_INTERLEAVE_NONE, CU_TENSOR_MAP_SWIZZLE_128B,
            CU_TENSOR_MAP_L2_PROMOTION_L2_128B, CU_TENSOR_MAP_FLOAT_OOB_FILL_NONE);
    }
    cudaStream_t st = cudaStreamPerThread;
    chain_kernel<<<96, 384, CHAIN_SMEM, st>>>(tm_x, tm_q, tm_k, tm_v, Bx, mem0, Wo);
    cudaLaunchConfig_t cfg = {};
    cfg.gridDim = dim3(36); cfg.blockDim = dim3(384); cfg.dynamicSmemBytes = BG_SMEM; cfg.stream = st;
    cudaLaunchAttribute at[1];
    at[0].id = cudaLaunchAttributeProgrammaticStreamSerialization; at[0].val.programmaticStreamSerializationAllowed = 1;
    cfg.attrs = at; cfg.numAttrs = 1;
    cudaLaunchKernelEx(&cfg, bg_kernel, tm_xa, tm_wo, tm_out, Ax, Lre, Lim, Bre, Bim, Cre, Cim, logdt, Dk);
}
```

```cpp
#include <cuda_runtime.h>
#include <cuda.h>
#include <cuda_bf16.h>
#include <cuda_fp16.h>
#include <stdint.h>

#define D_WAIT 720

#define BG_PACE 0
#define RED_GAP 720
#define ACC_PF 1
#define QDEP 0
#define PUB_MASK 0x1111010101011000ull
#define EARLY5 0
#define BG_AHEAD 5

namespace {

constexpr int DM = 576, NH = 32, SEQ = 2048, NSEG = 64, HD = 4096;

__device__ uint4 g_acc_raw[64 * 96 * 16 + 131072];
__device__ uint4 g_ox[NH * 2 * SEQ * 8];
constexpr int REC = 30720;
__device__ uint4 g_qkv[NSEG * NH * (REC / 16)];
__device__ uint4 g_h[18 * SEQ * 8];
constexpr int NFLAG = 4096, F_QKV = 0, F_OX = 512, F_H = 1024, F_OUT = 2048;
__device__ unsigned g_flag[NFLAG];
__device__ unsigned g_ticket, g_ticket_bg;
__device__ unsigned long long g_norm[96];
#define BSTAMP(i) do {} while (0)

__device__ __forceinline__ uint32_t smem_u32(const void* p) { return (uint32_t)__cvta_generic_to_shared(p); }
__device__ __forceinline__ uint32_t mapa(uint32_t a, uint32_t r) { uint32_t o; asm("mapa.shared::cluster.u32 %0, %1, %2;" : "=r"(o) : "r"(a), "r"(r)); return o; }
__device__ __forceinline__ uint32_t mapa_v(uint32_t a, uint32_t r) { uint32_t o; asm volatile("mapa.shared::cluster.u32 %0, %1, %2;" : "=r"(o) : "r"(a), "r"(r)); return o; }
__device__ __forceinline__ unsigned clk() { unsigned long long c; asm volatile("mov.u64 %0, %%clock64;" : "=l"(c) :: "memory"); return (unsigned)c; }
__device__ __forceinline__ void mbar_init(uint32_t bar, uint32_t cnt) { asm volatile("mbarrier.init.shared::cta.b64 [%0], %1;" :: "r"(bar), "r"(cnt) : "memory"); }
__device__ __forceinline__ void mbar_expect(uint32_t bar, uint32_t bytes) { asm volatile("mbarrier.arrive.expect_tx.shared::cta.b64 _, [%0], %1;" :: "r"(bar), "r"(bytes) : "memory"); }
__device__ __forceinline__ void mbar_wait(uint32_t bar, uint32_t parity) {
    asm volatile("{\n.reg .pred p;\n.reg .u32 n;\nmov.u32 n, 0;\n"
                 "W_%=: mbarrier.try_wait.parity.shared::cta.b64 p, [%0], %1;\n@p bra.uni D_%=;\n"
                 "add.u32 n, n, 1;\nsetp.lt.u32 p, n, 4000000;\n@p bra.uni W_%=;\ntrap;\nD_%=:\n}" :: "r"(bar), "r"(parity) : "memory");
}
__device__ __forceinline__ void mbar_expect_if(uint32_t z, uint32_t bar, uint32_t bytes) {
    asm volatile("{\n.reg .pred p;\nsetp.eq.u32 p, %2, 0;\n@p mbarrier.arrive.expect_tx.shared::cta.b64 _, [%0], %1;\n}" :: "r"(bar), "r"(bytes), "r"(z) : "memory");
}
__device__ __forceinline__ void mbar_arrive_if(uint32_t z, uint32_t bar) {
    asm volatile("{\n.reg .pred p;\nsetp.eq.u32 p, %1, 0;\n@p mbarrier.arrive.shared::cta.b64 _, [%0];\n}" :: "r"(bar), "r"(z) : "memory");
}
__device__ __forceinline__ void sts32_if(uint32_t z, uint32_t a, uint32_t x) {
    asm volatile("{\n.reg .pred p;\nsetp.eq.u32 p, %2, 0;\n@p st.shared.u32 [%0], %1;\n}" :: "r"(a), "r"(x), "r"(z) : "memory");
}
template <int K> __device__ __forceinline__ void sched_fence(int v) {
    asm volatile("{\n.reg .pred p;\nsetp.ne.s32 p, %0, %1;\n@p bra.uni F_%=;\ntrap;\nF_%=:\n}" :: "r"(v), "n"(1000 + K) : "memory");
}
__device__ __forceinline__ void spin_until(unsigned t0, unsigned d) {
    asm volatile("{\n.reg .pred p;\n.reg .u64 c;\n.reg .u32 lo;\n"
                 "S_%=: mov.u64 c, %%clock64;\ncvt.u32.u64 lo, c;\nsub.u32 lo, lo, %0;\nsetp.lt.u32 p, lo, %1;\n@p bra.uni S_%=;\n}" :: "r"(t0), "r"(d) : "memory");
}
__device__ __forceinline__ void bar_sync(int id, int n) { asm volatile("bar.sync %0, %1;" :: "r"(id), "r"(n) : "memory"); }
__device__ __forceinline__ void bar_sync_sel(int sel, int id) {
    asm volatile("{\n.reg .pred p;\nsetp.eq.u32 p, %0, 0;\n@p bar.sync %1, %3;\n@!p bar.sync %2, %3;\n}" :: "r"(sel), "r"(id), "r"(id + 1), "n"(192) : "memory");
}
__device__ __forceinline__ void bar_arrive(int id, int n) { asm volatile("bar.arrive %0, %1;" :: "r"(id), "r"(n) : "memory"); }
__device__ __forceinline__ void fence_async_smem() { asm volatile("fence.proxy.async.shared::cta;" ::: "memory"); }
__device__ __forceinline__ uint32_t pack_bf16(float lo, float hi) { uint32_t r; asm("cvt.rn.bf16x2.f32 %0, %1, %2;" : "=r"(r) : "f"(hi), "f"(lo)); return r; }
__device__ __forceinline__ uint32_t pack_f16(float lo, float hi) { uint32_t r; asm("cvt.rn.f16x2.f32 %0, %1, %2;" : "=r"(r) : "f"(hi), "f"(lo)); return r; }
__device__ __forceinline__ uint32_t f16x2_to_bf16x2(uint32_t v) { float2 f = __half22float2(*reinterpret_cast<__half2*>(&v)); return pack_bf16(f.x, f.y); }
__device__ __forceinline__ uint32_t hmul2(uint32_t a, uint32_t b) { uint32_t r; asm("mul.rn.f16x2 %0, %1, %2;" : "=r"(r) : "r"(a), "r"(b)); return r; }
__device__ __forceinline__ float ex2(float x) { float y; asm("ex2.approx.ftz.f32 %0, %1;" : "=f"(y) : "f"(x)); return y; }
__device__ __forceinline__ float ex2v(float x) { float y; asm volatile("ex2.approx.ftz.f32 %0, %1;" : "=f"(y) : "f"(x)); return y; }
__device__ __forceinline__ uint32_t absmax2(uint32_t a, uint32_t b) {
    uint32_t r; asm("max.xorsign.abs.bf16x2 %0, %1, %2;" : "=r"(r) : "r"(a), "r"(b)); return r;
}
__device__ __forceinline__ uint32_t shl_v(uint32_t a, int n) { return a << n; }
__device__ __forceinline__ uint32_t max3u(uint32_t a, uint32_t b, uint32_t c) { return max(max(a, b), c); }
__device__ __forceinline__ uint4 lds128(uint32_t a) { uint4 v; asm volatile("ld.shared.v4.u32 {%0,%1,%2,%3}, [%4];" : "=r"(v.x), "=r"(v.y), "=r"(v.z), "=r"(v.w) : "r"(a) : "memory"); return v; }
__device__ __forceinline__ uint4 lds128v(uint32_t a) { uint4 v; asm volatile("ld.volatile.shared.v4.u32 {%0,%1,%2,%3}, [%4];" : "=r"(v.x), "=r"(v.y), "=r"(v.z), "=r"(v.w) : "r"(a) : "memory"); return v; }
__device__ __forceinline__ float4 lds128f(uint32_t a) { float4 v; asm volatile("ld.shared.v4.f32 {%0,%1,%2,%3}, [%4];" : "=f"(v.x), "=f"(v.y), "=f"(v.z), "=f"(v.w) : "r"(a) : "memory"); return v; }
__device__ __forceinline__ float2 lds64f(uint32_t a) { float2 v; asm volatile("ld.shared.v2.f32 {%0,%1}, [%2];" : "=f"(v.x), "=f"(v.y) : "r"(a) : "memory"); return v; }
__device__ __forceinline__ uint4 lds64x2(uint32_t a) { uint4 v; asm volatile("ld.shared.v2.u32 {%0,%1}, [%4];\nld.shared.v2.u32 {%2,%3}, [%4+256];" : "=r"(v.x), "=r"(v.y), "=r"(v.z), "=r"(v.w) : "r"(a) : "memory"); return v; }
__device__ __forceinline__ uint32_t lds32(uint32_t a) { uint32_t v; asm volatile("ld.shared.u32 %0, [%1];" : "=r"(v) : "r"(a) : "memory"); return v; }
__device__ __forceinline__ void sts128(uint32_t a, uint32_t x, uint32_t y, uint32_t z, uint32_t w) { asm volatile("st.shared.v4.u32 [%0], {%1,%2,%3,%4};" :: "r"(a), "r"(x), "r"(y), "r"(z), "r"(w) : "memory"); }
__device__ __forceinline__ void sts128f(uint32_t a, float x, float y, float z, float w) { asm volatile("st.shared.v4.f32 [%0], {%1,%2,%3,%4};" :: "r"(a), "f"(x), "f"(y), "f"(z), "f"(w) : "memory"); }
__device__ __forceinline__ void sts64(uint32_t a, uint32_t x, uint32_t y) { asm volatile("st.shared.v2.u32 [%0], {%1,%2};" :: "r"(a), "r"(x), "r"(y) : "memory"); }
__device__ __forceinline__ void sts32(uint32_t a, uint32_t x) { asm volatile("st.shared.u32 [%0], %1;" :: "r"(a), "r"(x) : "memory"); }
__device__ __forceinline__ uint4 ldsm4(uint32_t a) { uint4 v; asm volatile("ldmatrix.sync.aligned.m8n8.x4.shared.b16 {%0,%1,%2,%3}, [%4];" : "=r"(v.x), "=r"(v.y), "=r"(v.z), "=r"(v.w) : "r"(a) : "memory"); return v; }
__device__ __forceinline__ void stsm2t(uint32_t a, uint32_t x, uint32_t y) { asm volatile("stmatrix.sync.aligned.m8n8.x2.trans.shared.b16 [%0], {%1,%2};" :: "r"(a), "r"(x), "r"(y) : "memory"); }
__device__ __forceinline__ void stsm4t(uint32_t a, uint32_t x, uint32_t y, uint32_t z, uint32_t w) { asm volatile("stmatrix.sync.aligned.m8n8.x4.trans.shared.b16 [%0], {%1,%2,%3,%4};" :: "r"(a), "r"(x), "r"(y), "r"(z), "r"(w) : "memory"); }
__device__ __forceinline__ void st_async64(uint32_t a, uint32_t x, uint32_t y, uint32_t bar) { asm volatile("st.async.shared::cluster.mbarrier::complete_tx::bytes.v2.b32 [%0], {%1,%2}, [%3];" :: "r"(a), "r"(x), "r"(y), "r"(bar) : "memory"); }
__device__ __forceinline__ void bulk_s2c(uint32_t dst, uint32_t src, uint32_t bytes, uint32_t bar) { asm volatile("cp.async.bulk.shared::cluster.shared::cta.mbarrier::complete_tx::bytes [%0], [%1], %2, [%3];" :: "r"(dst), "r"(src), "r"(bytes), "r"(bar) : "memory"); }
__device__ __forceinline__ void bulk_s2g(void* dst, uint32_t src, uint32_t bytes) { asm volatile("cp.async.bulk.global.shared::cta.bulk_group [%0], [%1], %2;" :: "l"(dst), "r"(src), "r"(bytes) : "memory"); }
__device__ __forceinline__ uint32_t ldg_nc32(const void* p) { uint32_t v; asm volatile("ld.global.nc.L2::128B.u32 %0, [%1];" : "=r"(v) : "l"(p)); return v; }
__device__ __forceinline__ uint4 ldg_relaxed128(const void* p) { uint4 v; asm volatile("ld.relaxed.gpu.global.v4.u32 {%0,%1,%2,%3}, [%4];" : "=r"(v.x), "=r"(v.y), "=r"(v.z), "=r"(v.w) : "l"(p) : "memory"); return v; }
__device__ __forceinline__ void mma16816(float (&d)[4], uint32_t a0, uint32_t a1, uint32_t a2, uint32_t a3, uint32_t b0, uint32_t b1) {
    asm volatile("mma.sync.aligned.m16n8k16.row.col.f32.bf16.bf16.f32 {%0,%1,%2,%3}, {%4,%5,%6,%7}, {%8,%9}, {%0,%1,%2,%3};"
        : "+f"(d[0]), "+f"(d[1]), "+f"(d[2]), "+f"(d[3]) : "r"(a0), "r"(a1), "r"(a2), "r"(a3), "r"(b0), "r"(b1));
}
__device__ __forceinline__ void mma16816_z(float (&d)[4], uint32_t a0, uint32_t a1, uint32_t a2, uint32_t a3, uint32_t b0, uint32_t b1) {
    asm volatile("mma.sync.aligned.m16n8k16.row.col.f32.bf16.bf16.f32 {%0,%1,%2,%3}, {%4,%5,%6,%7}, {%8,%9}, {%10,%10,%10,%10};"
        : "=f"(d[0]), "=f"(d[1]), "=f"(d[2]), "=f"(d[3]) : "r"(a0), "r"(a1), "r"(a2), "r"(a3), "r"(b0), "r"(b1), "f"(0.f));
}
__device__ __forceinline__ void mma1688(float (&d)[4], uint32_t a0, uint32_t a1, uint32_t b0) {
    asm volatile("mma.sync.aligned.m16n8k8.row.col.f32.bf16.bf16.f32 {%0,%1,%2,%3}, {%4,%5}, {%6}, {%0,%1,%2,%3};"
        : "+f"(d[0]), "+f"(d[1]), "+f"(d[2]), "+f"(d[3]) : "r"(a0), "r"(a1), "r"(b0));
}
__device__ __forceinline__ void mma1688_z(float (&d)[4], uint32_t a0, uint32_t a1, uint32_t b0) {
    asm volatile("mma.sync.aligned.m16n8k8.row.col.f32.bf16.bf16.f32 {%0,%1,%2,%3}, {%4,%5}, {%6}, {%7,%7,%7,%7};"
        : "=f"(d[0]), "=f"(d[1]), "=f"(d[2]), "=f"(d[3]) : "r"(a0), "r"(a1), "r"(b0), "f"(0.f));
}
template <int ACC>
__device__ __forceinline__ void wgmma_n32_rs(float (&d)[16], uint32_t a0, uint32_t a1, uint32_t a2, uint32_t a3, uint64_t desc) {
    asm volatile("wgmma.mma_async.sync.aligned.m64n32k16.f32.bf16.bf16 {%0,%1,%2,%3,%4,%5,%6,%7,%8,%9,%10,%11,%12,%13,%14,%15}, {%16,%17,%18,%19}, %20, %21, 1, 1, 0;"
        : "+f"(d[0]), "+f"(d[1]), "+f"(d[2]), "+f"(d[3]), "+f"(d[4]), "+f"(d[5]), "+f"(d[6]), "+f"(d[7]),
          "+f"(d[8]), "+f"(d[9]), "+f"(d[10]), "+f"(d[11]), "+f"(d[12]), "+f"(d[13]), "+f"(d[14]), "+f"(d[15])
        : "r"(a0), "r"(a1), "r"(a2), "r"(a3), "l"(desc), "n"(ACC));
}
template <int ACC>
__device__ __forceinline__ void wgmma_n32_ss(float (&d)[16], uint64_t da, uint64_t db) {
    asm volatile("wgmma.mma_async.sync.aligned.m64n32k16.f32.bf16.bf16 {%0,%1,%2,%3,%4,%5,%6,%7,%8,%9,%10,%11,%12,%13,%14,%15}, %16, %17, %18, 1, 1, 0, 0;"
        : "+f"(d[0]), "+f"(d[1]), "+f"(d[2]), "+f"(d[3]), "+f"(d[4]), "+f"(d[5]), "+f"(d[6]), "+f"(d[7]),
          "+f"(d[8]), "+f"(d[9]), "+f"(d[10]), "+f"(d[11]), "+f"(d[12]), "+f"(d[13]), "+f"(d[14]), "+f"(d[15])
        : "l"(da), "l"(db), "n"(ACC));
}
__device__ __forceinline__ void wg_fence() { asm volatile("wgmma.fence.sync.aligned;" ::: "memory"); }
__device__ __forceinline__ void wg_commit() { asm volatile("wgmma.commit_group.sync.aligned;" ::: "memory"); }
__device__ __forceinline__ void wg_wait0() { asm volatile("wgmma.wait_group.sync.aligned 0;" ::: "memory"); }
__device__ __forceinline__ void cluster_sync() { asm volatile("barrier.cluster.arrive.aligned;\nbarrier.cluster.wait.aligned;" ::: "memory"); }

#define STAMP(s, i) do {} while (0)
#define STAMPV(s, i, v) do {} while (0)

constexpr int XT_BYTES = 36864;
constexpr int O_XT = 0;
constexpr int O_STG = XT_BYTES;
constexpr int O_AS = 3 * XT_BYTES;
constexpr int O_XP = O_AS + 16384;
constexpr int O_QKX = O_XP + 8192;
constexpr int O_KM = O_QKX + 8192;
constexpr int O_QM = O_QKX + 10240;
constexpr int O_VX = O_STG + 147456;
constexpr int O_VM = O_VX + 24576;
constexpr int O_SC = O_VM + 2048;
constexpr int O_OF = O_SC + 2560;
constexpr int O_AF = O_OF + 2048;
constexpr int O_WP = O_AF + 4096;
constexpr int O_MF = O_WP + 2048;
constexpr int O_MISC = O_MF + 9216;
static_assert(O_QKX + 24576 <= O_VX, "smem");
constexpr int O_BAR = O_MISC + 64;
constexpr int CHAIN_SMEM = O_BAR + 128;
static_assert(CHAIN_SMEM <= 232448, "smem");
constexpr int B_X = O_BAR, B_VX = O_BAR + 24, B_SC = O_BAR + 40, B_W = O_BAR + 48, B_MX = O_BAR + 72;
constexpr float SM_SCALE = 0.08838834764831845f * 1.4426950408889634f;
constexpr uint32_t ONES = 0x3f803f80u;

__device__ __forceinline__ uint32_t opaque(uint32_t v) { uint32_t o; asm volatile("mov.u32 %0, %1;" : "=r"(o) : "r"(v)); return o; }
__device__ __forceinline__ void st_async128(uint32_t a, uint32_t x, uint32_t y, uint32_t z, uint32_t w, uint32_t bar) {
    asm volatile("st.async.shared::cluster.mbarrier::complete_tx::bytes.v4.b32 [%0], {%1,%2,%3,%4}, [%5];" :: "r"(a), "r"(x), "r"(y), "r"(z), "r"(w), "r"(bar) : "memory");
}
__device__ __forceinline__ void tma_x_tile(uint32_t sb, const CUtensorMap* tm, int r, int j, int slot) {
    asm volatile("{\n.reg .pred p;\nelect.sync _|p, 0xffffffff;\n"
        "@p mbarrier.arrive.expect_tx.shared::cta.b64 _, [%2], 36864;\n"
        "@p cp.async.bulk.tensor.2d.shared::cluster.global.mbarrier::complete_tx::bytes.multicast::cluster [%0], [%1, {%3, %4}], [%2], %7;\n"
        "@p cp.async.bulk.tensor.2d.shared::cluster.global.mbarrier::complete_tx::bytes.multicast::cluster [%0+4096], [%1, {%5, %4}], [%2], %7;\n"
        "@p cp.async.bulk.tensor.2d.shared::cluster.global.mbarrier::complete_tx::bytes.multicast::cluster [%0+8192], [%1, {%6, %4}], [%2], %7;\n}"
        :: "r"(sb + O_XT + slot * XT_BYTES + 3 * r * 4096), "l"(tm), "r"(sb + B_X + 8 * slot), "r"(192 * r), "r"(j * 32), "r"(192 * r + 64), "r"(192 * r + 128),
           "h"((unsigned short)7) : "memory");
}
__device__ __forceinline__ void flag_inc_if(uint32_t z, unsigned* p) {
    asm volatile("{\n.reg .pred p;\nsetp.eq.u32 p, %1, 0;\n@p red.release.gpu.global.inc.u32 [%0], 0xfffffffe;\n}" :: "l"(p), "r"(z) : "memory");
}
__device__ __forceinline__ void v_store(uint32_t sb, int h, int j, int slot) {
    fence_async_smem();
    asm volatile("{\n.reg .pred p;\nelect.sync _|p, 0xffffffff;\n@p cp.async.bulk.global.shared::cta.bulk_group [%0], [%1], 8192;\n@p cp.async.bulk.commit_group;\n}"
        :: "l"(reinterpret_cast<char*>(g_qkv) + (size_t)(j * NH + h) * REC + 20480), "r"(sb + O_VX + slot * 8192) : "memory");
}
__device__ __forceinline__ void v_multicast(uint32_t sb, int h, int j) {
    asm volatile("{\n.reg .pred p;\ncp.async.bulk.wait_group 0;\nelect.sync _|p, 0xffffffff;\nsetp.lt.and.s32 p, %4, 63, p;\n"
        "@p cp.async.bulk.shared::cluster.global.mbarrier::complete_tx::bytes.multicast::cluster [%1], [%0], 8192, [%2], %3;\nfence.proxy.async.global;\n}"
        :: "l"(reinterpret_cast<char*>(g_qkv) + (size_t)(j * NH + h) * REC + 20480), "r"(sb + O_VX + (j & 1) * 8192), "r"(sb + B_VX + 8 * (j & 1)),
           "h"((unsigned short)3), "r"(j) : "memory");
}
__device__ __forceinline__ float quad_max(float v) {
    const float a = __shfl_xor_sync(~0u, v, 1), b = __shfl_xor_sync(~0u, v, 2), c = __shfl_xor_sync(~0u, v, 3);
    return fmaxf(fmaxf(v, a), fmaxf(b, c));
}
__device__ __forceinline__ void load_scores(float (&p)[10], uint32_t base, uint32_t stride, uint32_t l16) {
    const float4 a0 = lds128f(base + l16), b0 = lds128f(base + stride + l16);
    const float4 a1 = lds128f(base + 512 + l16), b1 = lds128f(base + stride + 512 + l16);
    const float2 a2 = lds64f(base + 1024 + (l16 >> 1)), b2 = lds64f(base + stride + 1024 + (l16 >> 1));
    p[0] = a2.x + b2.x; p[1] = a2.y + b2.y;
    p[2] = a0.x + b0.x; p[3] = a0.y + b0.y; p[4] = a0.z + b0.z; p[5] = a0.w + b0.w;
    p[6] = a1.x + b1.x; p[7] = a1.y + b1.y; p[8] = a1.z + b1.z; p[9] = a1.w + b1.w;
}
__device__ __forceinline__ float rcp_fast(float x) { float y; asm("rcp.approx.ftz.f32 %0, %1;" : "=f"(y) : "f"(x)); return y; }

__global__ void __cluster_dims__(3, 1, 1) __launch_bounds__(384, 1)
chain_kernel(const __grid_constant__ CUtensorMap tm_x, const __grid_constant__ CUtensorMap tm_q,
             const __grid_constant__ CUtensorMap tm_k, const __grid_constant__ CUtensorMap tm_v,
             const __nv_bfloat16* __restrict__ x, const __nv_bfloat16* __restrict__ mem0,
             const __nv_bfloat16* __restrict__ Wo) {
    extern __shared__ __align__(1024) uint8_t smem_raw[];
    const uint32_t sb = smem_u32(smem_raw);
    const int lane = threadIdx.x & 31;
    const int warp = __shfl_sync(~0u, threadIdx.x >> 5, 0);
    const int wg = warp >> 2, w = warp & 3;
    const int h = blockIdx.x / 3, r = blockIdx.x - 3 * h;
    uint4* const g_acc = reinterpret_cast<uint4*>((reinterpret_cast<uintptr_t>(g_acc_raw) + 0x1fffff) & ~(uintptr_t)0x1fffff);

#define PSTAMP(i) do {} while (0)
    if (threadIdx.x == 0) {
        if (sb & 1023u) __trap();
        for (int i = 0; i < 9; i++) mbar_init(sb + O_BAR + 8 * i, 1);
        mbar_init(sb + B_MX, 4);
        asm volatile("fence.mbarrier_init.release.cluster;" ::: "memory");
        for (int i = 0; i < 3; i++) {
            mbar_expect(sb + B_W + 8 * i, 49152);
            for (int tl = 0; tl < 2; tl++)
                asm volatile("cp.async.bulk.tensor.2d.shared::cluster.global.mbarrier::complete_tx::bytes [%0], [%1, {%3, %4}], [%2];"
                    :: "r"(sb + O_STG + tl * 73728 + i * 24576), "l"(r < 2 ? (tl ? &tm_k : &tm_q) : &tm_v), "r"(sb + B_W + 8 * i),
                       "r"(h * 128 + 64 * (r < 2 ? r : tl)), "r"(192 * i) : "memory");
        }
    }
    __syncwarp();
    asm volatile("barrier.cluster.arrive.relaxed.aligned;" ::: "memory");
    asm volatile("griddepcontrol.launch_dependents;" ::: "memory");
    if (warp == 0) PSTAMP(9);
    const uint32_t l16c = __shfl_sync(~0u, lane * 16, lane);

    if (wg < 2) {
#define KS(u) ((u) < 8 ? 12 * ((u) >> 2) + (((u) >> 1) & 1) + 4 * ((u) & 1) : (u) < 12 ? (u) : (u) < 16 ? (u) + 8 : (u) < 24 ? 24 + (((u) - 16) >> 1) + 4 * ((u) & 1) : (u) + 8)
        asm volatile("setmaxnreg.inc.sync.aligned.u32 184;");
        uint32_t a[144];
        uint32_t adr1;
        {
            const int g = lane >> 2, t = lane & 3;
            const int t1 = threadIdx.x;
#pragma unroll
            for (int i = 0; i < 2; i++) g_acc[(blockIdx.x * 64 + i * 32 + (t1 >> 3)) * 16 + (t1 & 7)] = make_uint4(0, 0, 0, 0);
            __threadfence();
            asm volatile("barrier.cluster.wait.aligned;" ::: "memory");
            const uint32_t ev = sb + O_STG + (2 * t) * 128 + (((2 * w + (g >> 2)) ^ (2 * t)) << 4) + (g & 3) * 4;
            const uint32_t od = (ev ^ 16) + 128;
            auto gather = [&](int dst, uint32_t off) {
                a[dst] = lds32(ev + off); a[dst + 1] = lds32(od + off); a[dst + 2] = lds32(ev + off + 1024); a[dst + 3] = lds32(od + off + 1024);
            };
            const uint4* xp = reinterpret_cast<const uint4*>(x) + blockIdx.x * 1536 + t1;
            uint4 xv[6];
#pragma unroll
            for (int th = 0; th < 2; th++) {
                mbar_wait(sb + B_W + 8 * th, 0);
                if (th == 1) {
#pragma unroll
                    for (int i = 0; i < 6; i++) xv[i] = __ldg(xp + i * 256);
                }
#pragma unroll
                for (int u = 4 * th; u < 4 * th + 4; u++) {
                    gather(32 + 4 * u, wg * (73728 + 4096) + KS(u) * 2048);
                    gather(4 * u, 73728 - wg * (73728 - 4096) + KS(u) * 2048);
                    gather(64 + 4 * u, wg * 73728 + KS(8 + u) * 2048);
                }
            }
            mbar_wait(sb + B_W + 16, 0);
#pragma unroll
            for (int u = 16; u < 28; u++) gather(32 + 4 * u, wg * 73728 + KS(u) * 2048);
#pragma unroll
            for (int kk = 0; kk < 72; kk++) {
                uint32_t w0 = a[2 * kk], w1 = a[2 * kk + 1];
                a[2 * kk] = __byte_perm(w0, w1, 0x5410);
                a[2 * kk + 1] = __byte_perm(w0, w1, 0x7632);
            }
            if (r == 2) {
                float n0[4], n1[4];
#pragma unroll
                for (int u = 0; u < 36; u++) {
                    const uint32_t x0 = a[4 * u] & 0x7fff7fffu, x1 = a[4 * u + 1] & 0x7fff7fffu, x2 = a[4 * u + 2] & 0x7fff7fffu, x3 = a[4 * u + 3] & 0x7fff7fffu;
                    if (u == 0) mma16816_z(n0, x0, x1, x2, x3, ONES, ONES);
                    else if (u < 8) mma16816(n0, x0, x1, x2, x3, ONES, ONES);
                    else if (u == 8) mma16816_z(n1, x0, x1, x2, x3, ONES, ONES);
                    else mma16816(n1, x0, x1, x2, x3, ONES, ONES);
                }
                const uint32_t mx = __reduce_max_sync(~0u, __float_as_uint(2.f * fmaxf(fmaxf(n0[0], n0[2]), fmaxf(n1[0], n1[2]))));
                sts32_if(lane, sb + O_MISC + 32 + 4 * warp, mx);
            }
            uint32_t xm = 0;
#pragma unroll
            for (int i = 0; i < 6; i++)
                xm = __vmaxu2(xm, __vmaxu2(__vmaxu2(xv[i].x & 0x7fff7fffu, xv[i].y & 0x7fff7fffu), __vmaxu2(xv[i].z & 0x7fff7fffu, xv[i].w & 0x7fff7fffu)));
            sts32_if(lane, sb + O_OF + 16 + 4 * warp, __reduce_max_sync(~0u, max(xm << 16, xm & 0xffff0000u)));
            if (warp == 0) PSTAMP(11);
            bar_arrive(7, 384);
            asm volatile("barrier.cluster.arrive.relaxed.aligned;" ::: "memory");
            bar_sync(1, 256);
            const uint32_t as = sb + O_AS + wg * 8192 + (16 * w + g) * 128 + t * 4;
            sts32(as + (g << 4), a[32]);
            sts32(as + 1024 + (g << 4), a[33]);
            sts32(as + ((1 ^ g) << 4), a[34]);
            sts32(as + 1024 + ((1 ^ g) << 4), a[35]);
            sts128(sb + O_AF + warp * 512 + lane * 16, a[32], a[33], a[34], a[35]);
            fence_async_smem();
            bar_sync(1, 256);
            const uint32_t l = lane * 16;
            const int mi = lane >> 3, isk = (mi >> 1) ? wg : (wg ^ 1);
            adr1 = (r == 2) ? (sb + O_VM + warp * 256 + (l >> 1))
                            : (isk ? (sb + O_KM + w * 512 + wg * 256 + (mi & 1) * 128 + (l & 127))
                                   : (sb + O_QM + w * 512 + (mi & 1) * 256 + wg * 128 + (l & 127)));
            adr1 = __shfl_sync(~0u, adr1, lane);
        }
        const int ahead = r >> 1;
        int s3 = 2;
#pragma unroll 1
        for (int s = -1 - ahead; s < NSEG; s++) {
            const uint32_t l16 = opaque(l16c);
            const int j = s + 1 + ahead;
            s3 = (s3 == 2) ? 0 : s3 + 1;
            if (s < 0) mbar_wait(sb + B_X + 8 * s3, 0);
            const uint64_t desc0 = (uint64_t)(((sb + O_XT + s3 * XT_BYTES) & 0x3FFFF) >> 4) | (1ull << 16) | (64ull << 32) | (1ull << 62);
            uint32_t km0 = 0, km1 = 0;
            if (s >= 0) {
                { const uint4 v = lds128(sb + O_AF + warp * 512 + l16); a[32] = v.x; a[33] = v.y; a[34] = v.z; a[35] = v.w; }
                float co[4], cw[3][4];
                uint4 b[14];
                float inv;
#define GORD(i) ((i) < 8 ? 2 * ((i) >> 2) + (((i) >> 1) & 1) + 4 * ((i) & 1) : (i))
                auto qkv_mma = [&](int i) {
                    const int gi = GORD(i), u = 8 * gi, n0 = 2 * i, n1 = 2 * i + 1;
                    if (gi < 4) {
                        if (i == 0) mma16816_z(co, a[u], a[u + 1], a[u + 2], a[u + 3], b[0].x, b[0].y);
                        else mma16816(co, a[u], a[u + 1], a[u + 2], a[u + 3], b[i].x, b[i].y);
                    }
                    if (n0 < 3) mma16816_z(cw[n0 % 3], a[32 + u], a[32 + u + 1], a[32 + u + 2], a[32 + u + 3], b[i].x, b[i].y);
                    else mma16816(cw[n0 % 3], a[32 + u], a[32 + u + 1], a[32 + u + 2], a[32 + u + 3], b[i].x, b[i].y);
                    if (n1 < 3) mma16816_z(cw[n1 % 3], a[32 + u + 4], a[32 + u + 5], a[32 + u + 6], a[32 + u + 7], b[i].z, b[i].w);
                    else mma16816(cw[n1 % 3], a[32 + u + 4], a[32 + u + 5], a[32 + u + 6], a[32 + u + 7], b[i].z, b[i].w);
                    if (gi < 4) mma16816(co, a[u + 4], a[u + 5], a[u + 6], a[u + 7], b[i].z, b[i].w);
                };
                const uint32_t mf = sb + O_MF + l16, mfs = mf + wg * 1024;
                const uint32_t qb = (s & 1) * 12288;
                bar_sync(2, 384);
                if (warp == 0) STAMP(s, 0);
                auto qkv_ld = [&](int i) {
                    const int gi = GORD(i);
                    b[i] = gi < 4 ? lds128v(mfs + (gi >> 1) * 3072 + (gi & 1) * 512) : lds128v(mf + (gi < 6 ? gi : gi + 4) * 512);
                };
#pragma unroll
                for (int i = 0; i < 4; i++) qkv_ld(i);
                qkv_mma(0); qkv_mma(1); qkv_mma(2);
                const uint32_t z0 = __float_as_uint(QDEP ? co[0] : cw[1][0]) & (l16 & 15u);
                qkv_mma(3);
                bar_sync(15, 384);
                b[4] = lds128v(mfs + 3072 + z0);
#pragma unroll
                for (int i = 5; i < 9; i++) qkv_ld(i);
#pragma unroll
                for (int i = 4; i < 9; i++) { qkv_mma(i); qkv_ld(5 + i); }
                asm volatile("ld.volatile.shared.f32 %0, [%1];" : "=f"(inv) : "r"(sb + O_MISC) : "memory");
#pragma unroll
                for (int i = 9; i < 14; i++) qkv_mma(i);
#pragma unroll
                for (int i = 0; i < 4; i++) cw[0][i] += cw[1][i] + cw[2][i];
                if (r < 2) {
                    const uint32_t o0 = pack_bf16(co[0] * inv, co[1] * inv), o1 = pack_bf16(co[2] * inv, co[3] * inv);
                    const uint32_t w0 = pack_bf16(cw[0][0] * inv, cw[0][1] * inv), w1 = pack_bf16(cw[0][2] * inv, cw[0][3] * inv);
                    stsm4t(adr1 + qb, o0, o1, w0, w1);
                    if (warp == 0) STAMP(s, 1);
                    asm volatile("{\n.reg .pred p;\nsetp.ge.u32 p, %0, 3;\n@p bar.arrive 1, 256;\n}" :: "r"(warp) : "memory");
                    auto scores = [&](float (&v)[4], const uint4 (&q)[4], const uint4 (&k)[4]) {
                        float s0[4], s1[4], t0[4], t1[4];
                        mma16816_z(s0, q[0].x, q[0].y, q[0].z, q[0].w, k[0].x, k[0].y);
                        mma16816_z(s1, q[0].x, q[0].y, q[0].z, q[0].w, k[0].z, k[0].w);
                        mma16816_z(t0, q[1].x, q[1].y, q[1].z, q[1].w, k[1].x, k[1].y);
                        mma16816_z(t1, q[1].x, q[1].y, q[1].z, q[1].w, k[1].z, k[1].w);
                        mma16816(s0, q[2].x, q[2].y, q[2].z, q[2].w, k[2].x, k[2].y);
                        mma16816(s1, q[2].x, q[2].y, q[2].z, q[2].w, k[2].z, k[2].w);
                        mma16816(t0, q[3].x, q[3].y, q[3].z, q[3].w, k[3].x, k[3].y);
                        mma16816(t1, q[3].x, q[3].y, q[3].z, q[3].w, k[3].z, k[3].w);
                        v[0] = (s0[0] + s0[2]) + (t0[0] + t0[2]); v[1] = (s0[1] + s0[3]) + (t0[1] + t0[3]);
                        v[2] = (s1[0] + s1[2]) + (t1[0] + t1[2]); v[3] = (s1[1] + s1[3]) + (t1[1] + t1[3]);
                    };
                    if (warp < 2) {
                        uint4 q[4], k[4]; float v[4];
#pragma unroll
                        for (int i = 0; i < 4; i++) k[i] = ldsm4(sb + O_QKX + 4096 + qb + warp * 2048 + i * 512 + l16);
                        bar_sync(1, 256);
#pragma unroll
                        for (int i = 0; i < 4; i++) q[i] = ldsm4(sb + O_QM + qb + i * 512 + l16);
                        scores(v, q, k);
                        const uint32_t dst = sb + O_SC + r * 1280 + warp * 512 + l16;
                        st_async128(mapa(dst, 2), __float_as_uint(v[0]), __float_as_uint(v[1]), __float_as_uint(v[2]), __float_as_uint(v[3]), mapa(sb + B_SC, 2));
                        st_async128(mapa(dst, r ^ 1), __float_as_uint(v[0]), __float_as_uint(v[1]), __float_as_uint(v[2]), __float_as_uint(v[3]), mapa(sb + B_SC, r ^ 1));
                        st_async128(mapa(dst, r), __float_as_uint(v[0]), __float_as_uint(v[1]), __float_as_uint(v[2]), __float_as_uint(v[3]), mapa(sb + B_SC, r));
                    } else if (warp == 2) {
                        uint4 q[4], k[4]; float v[4];
                        bar_sync(1, 256);
#pragma unroll
                        for (int i = 0; i < 4; i++) { q[i] = ldsm4(sb + O_QM + qb + i * 512 + l16); k[i] = ldsm4(sb + O_KM + qb + i * 512 + l16); }
                        scores(v, q, k);
                        const uint32_t dst = sb + O_SC + r * 1280 + 1024 + (l16 >> 1);
                        st_async64(mapa(dst, 2), __float_as_uint(v[0] + v[2]), __float_as_uint(v[1] + v[3]), mapa(sb + B_SC, 2));
                        st_async64(mapa(dst, r ^ 1), __float_as_uint(v[0] + v[2]), __float_as_uint(v[1] + v[3]), mapa(sb + B_SC, r ^ 1));
                        st_async64(mapa(dst, r), __float_as_uint(v[0] + v[2]), __float_as_uint(v[1] + v[3]), mapa(sb + B_SC, r));
                        STAMP(s, 2);
                    } else if (warp == 3) {
                        asm volatile("cp.async.bulk.wait_group 0;\nfence.proxy.async.global;" ::: "memory");
                    }
                } else {
                    sts128f(sb + O_XP + warp * 512 + l16, co[0], co[1], co[2], co[3]);
                    bar_sync(8 + w, 64);
                    const float4 o = lds128f(sb + O_XP + (warp ^ 4) * 512 + l16);
                    km0 = pack_bf16((cw[0][0] + o.x) * inv, (cw[0][1] + o.y) * inv);
                    km1 = pack_bf16((cw[0][2] + o.z) * inv, (cw[0][3] + o.w) * inv);
                    if (warp == 0) STAMP(s, 1);
                    st_async64(mapa(adr1, 0), km0, km1, mapa(sb + B_SC, 0));
                    st_async64(mapa(adr1, 1), km0, km1, mapa(sb + B_SC, 1));
                    st_async64(mapa(adr1, 2), km0, km1, mapa(sb + B_SC, 2));
                    if (warp == 0) STAMP(s, 2);
                }
            }
            if (s >= 0) bar_sync(3, 384);
            auto store_qk = [&]() {
                asm volatile("{\n.reg .pred p;\nelect.sync _|p, 0xffffffff;\n"
                    "@p cp.async.bulk.global.shared::cta.bulk_group [%0], [%1], 10240;\n@p cp.async.bulk.commit_group;\n}"
                    :: "l"(reinterpret_cast<char*>(g_qkv) + (size_t)(s * NH + h) * REC + r * 10240), "r"(sb + O_QKX + (s & 1) * 12288) : "memory");
            };
            auto store_vm = [&]() {
                *reinterpret_cast<uint2*>(reinterpret_cast<char*>(g_qkv) + (size_t)(s * NH + h) * REC + 28672 + warp * 256 + (l16 >> 1)) = make_uint2(km0, km1);
            };
            if (s == NSEG - 1) {
                if (r == 2) store_vm();
                else if (warp == 3) {
                    fence_async_smem();
                    store_qk();
                    asm volatile("cp.async.bulk.wait_group 0;\nfence.proxy.async.global;" ::: "memory");
                }
            } else {
#define XDESC(u) (((u) < 8 ? descs : desc0) + (uint64_t)(((KS(u) >> 2) * 4096 + (KS(u) & 3) * 32) >> 4))
                const uint64_t descs = desc0 + (uint64_t)(wg * 4);
                float d[16];
                wg_fence();
#pragma unroll
                for (int u = 0; u < 8; u++) {
                    if (u == 0) wgmma_n32_rs<0>(d, a[0], a[1], a[2], a[3], XDESC(0));
                    else wgmma_n32_rs<1>(d, a[4 * u], a[4 * u + 1], a[4 * u + 2], a[4 * u + 3], XDESC(u));
                }
                wg_commit();
                wg_wait0();
                if (warp == 0) STAMP(s, 15);
                auto xp_put = [&]() {
#pragma unroll
                    for (int q = 0; q < 2; q++)
                        sts128(sb + O_XP + warp * 1024 + q * 512 + l16, pack_bf16(d[8 * q], d[8 * q + 1]), pack_bf16(d[8 * q + 2], d[8 * q + 3]),
                               pack_bf16(d[8 * q + 4], d[8 * q + 5]), pack_bf16(d[8 * q + 6], d[8 * q + 7]));
                };
                uint4 xo[2];
                auto xp_get = [&]() { xo[0] = lds128(sb + O_XP + (warp ^ 4) * 1024 + l16); xo[1] = lds128(sb + O_XP + (warp ^ 4) * 1024 + 512 + l16); };
                if (s >= 0) bar_sync(4, 384);
                xp_put();
                bar_sync(12, 256);
                xp_get();
#pragma unroll
                for (int q = 0; q < 2; q++) {
                    d[8 * q] = __uint_as_float(xo[q].x << 16); d[8 * q + 1] = __uint_as_float(xo[q].x & 0xffff0000u);
                    d[8 * q + 2] = __uint_as_float(xo[q].y << 16); d[8 * q + 3] = __uint_as_float(xo[q].y & 0xffff0000u);
                    d[8 * q + 4] = __uint_as_float(xo[q].z << 16); d[8 * q + 5] = __uint_as_float(xo[q].z & 0xffff0000u);
                    d[8 * q + 6] = __uint_as_float(xo[q].w << 16); d[8 * q + 7] = __uint_as_float(xo[q].w & 0xffff0000u);
                }
                if (s >= 0) {
                    if (r == 2) store_vm();
                    if (warp == 5 && s + 3 < NSEG) tma_x_tile(sb, &tm_x, r, s + 3, s % 3);
                    if (warp == 3) fence_async_smem();
                    if (warp == 7 && ((PUB_MASK >> s) & 1)) {
                        flag_inc_if(l16, &g_flag[F_QKV + (s - 4 + (h >> 3)) * 8]);
                        for (int sb4 = s - 4; sb4 > 0 && !((PUB_MASK >> sb4) & 1); sb4 -= 4)
                            asm volatile("{\n.reg .pred p;\nsetp.eq.u32 p, %1, 0;\n@p red.relaxed.gpu.global.inc.u32 [%0], 0xfffffffe;\n}"
                                         :: "l"(&g_flag[F_QKV + (sb4 - 4 + (h >> 3)) * 8]), "r"(l16) : "memory");
                    }
                    asm volatile("{\n.reg .pred p;\nsetp.eq.u32 p, %0, 0;\n@p bar.sync 5, 256;\n@!p bar.sync 13, 256;\n}" :: "r"(wg) : "memory");
                }
                const uint64_t da0 = (uint64_t)(((sb + O_AS + wg * 8192) & 0x3FFFF) >> 4) | (1ull << 16) | (64ull << 32) | (1ull << 62);
                wg_fence();
                wgmma_n32_ss<1>(d, da0, XDESC(0));
#pragma unroll
                for (int u = 1; u < 28; u++) wgmma_n32_rs<1>(d, a[32 + 4 * u], a[32 + 4 * u + 1], a[32 + 4 * u + 2], a[32 + 4 * u + 3], XDESC(u));
                wg_commit();
                wg_wait0();
                if (warp == 3 && r < 2 && s >= 0) store_qk();
                if (warp == 4) STAMP(s, 3);
                uint32_t e[8];
#pragma unroll
                for (int i = 0; i < 8; i++) e[i] = pack_bf16(d[2 * i], d[2 * i + 1]);
                if (r < 2) {
                    const uint32_t base = sb + O_QKX + (j & 1) * 12288 + wg * 4096 + w * 512 + l16;
                    stsm4t(base, e[0], wg ? e[1] : e[2], wg ? e[2] : e[1], e[3]);
                    stsm4t(base + 2048, e[4], wg ? e[5] : e[6], wg ? e[6] : e[5], e[7]);
                } else {
                    const uint32_t base = sb + O_VX + s3 * 8192 + warp * 1024 + l16;
                    sts128(base, e[0], e[1], e[2], e[3]);
                    sts128(base + 512, e[4], e[5], e[6], e[7]);
                    if (j == 0) bar_arrive(0, 288); else if (j < NSEG) bar_arrive(14, 288);
                }
                if (warp == 7) STAMP(s, 4);
                if (j == 0) asm volatile("barrier.cluster.wait.aligned;" ::: "memory");
                if (s < -1) bar_sync(1, 256);
            }
        }
        bar_arrive(7, 384);
    } else {
        asm volatile("setmaxnreg.dec.sync.aligned.u32 136;");
        const int c = w;
        uint32_t a[96];
        uint32_t mmax = 0;
        {
            const int g = lane >> 2, t = lane & 3;
            uint32_t tag = 0, m0v[18];
            if (threadIdx.x == 256) tag = atomicAdd(&g_ticket, 1u);
#pragma unroll
            for (int i = 0; i < 9; i++) {
                const uint32_t* p = reinterpret_cast<const uint32_t*>(mem0 + g * DM + 16 * (4 * i + c) + 2 * t);
                m0v[2 * i] = __ldg(p); m0v[2 * i + 1] = __ldg(p + 4);
            }
            asm volatile("barrier.cluster.wait.aligned;" ::: "memory");
            if (c == 0) {
                tma_x_tile(sb, &tm_x, r, 0, 0);
                mbar_expect_if(lane, sb + B_SC, 4608);
                if (r < 2) mbar_expect_if(lane, sb + B_VX, 8192);
                sts32_if(lane, sb + O_MISC, __float_as_uint(1.0f));
                sts32_if(lane, sb + O_MISC + 12, __float_as_uint(SM_SCALE));
            }
            asm volatile("barrier.cluster.arrive.relaxed.aligned;" ::: "memory");
#pragma unroll
            for (int tau = 0; tau < 3; tau++) {
                const uint32_t* v = m0v + 6 * tau;
                sts128(sb + O_MF + tau * 3072 + c * 512 + lane * 16, v[0], v[1], v[2], v[3]);
                sts64(sb + O_MF + tau * 3072 + 2048 + (c >> 1) * 512 + lane * 16 + (c & 1) * 8, v[4], v[5]);
#pragma unroll
                for (int i = 0; i < 6; i++) mmax = __vmaxu2(mmax, v[i] & 0x7fff7fffu);
            }
            mmax = max(mmax << 16, mmax & 0xffff0000u);
            bar_arrive(2, 384); bar_arrive(15, 384);
            tag = (__shfl_sync(~0u, tag, 0) / 96u + 1u) & 0xffffu;
            mbar_wait(sb + B_W + 0, 0);
            const __nv_bfloat16* p = Wo + (size_t)(h * 128 + 4 * t) * DM + 192 * r + 16 * c + 2 * g;
#pragma unroll
            for (int i = 0; i < 3; i++)
#pragma unroll
                for (int eb = 0; eb < 8; eb++)
#pragma unroll
                    for (int j = 0; j < 4; j++) a[(i * 8 + eb) * 4 + j] = ldg_nc32(p + (16 * eb + ((j & 1) * 2 + (j >> 1))) * DM + 64 * i);
#pragma unroll
            for (int kk = 0; kk < 48; kk++) {
                uint32_t w0 = a[2 * kk], w1 = a[2 * kk + 1];
                a[2 * kk] = __byte_perm(w0, w1, 0x5410);
                a[2 * kk + 1] = __byte_perm(w0, w1, 0x7632);
            }
            sts128(sb + O_WP + c * 512 + lane * 16, a[92], a[93], a[94], a[95]);
            float wmax = 0.f;
#pragma unroll
            for (int i = 0; i < 3; i++) {
                float n0[4];
#pragma unroll
                for (int u = 8 * i; u < 8 * i + 8; u++) {
                    const uint32_t x0 = a[4 * u] & 0x7fff7fffu, x1 = a[4 * u + 1] & 0x7fff7fffu, x2 = a[4 * u + 2] & 0x7fff7fffu, x3 = a[4 * u + 3] & 0x7fff7fffu;
                    if (u == 8 * i) mma16816_z(n0, x0, x1, x2, x3, ONES, ONES);
                    else mma16816(n0, x0, x1, x2, x3, ONES, ONES);
                }
                wmax = fmaxf(wmax, fmaxf(n0[0], n0[2]));
            }
            uint32_t wm = __reduce_max_sync(~0u, __float_as_uint(wmax));
            sts32_if(lane, sb + O_OF + 4 * c, wm);
            if (c == 0) PSTAMP(8);
            bar_sync(7, 384);
            asm volatile("barrier.cluster.wait.aligned;" ::: "memory");
            if (c == 1) { tma_x_tile(sb, &tm_x, r, 1, 1); tma_x_tile(sb, &tm_x, r, 2, 2); }
            if (c == 2 && r == 2) { bar_sync(0, 288); v_store(sb, h, 0, 0); v_multicast(sb, h, 0); }
            if (c == 0) {
                const uint4 wq = lds128(sb + O_OF), xq = lds128(sb + O_OF + 16), xr = lds128(sb + O_OF + 32), v0 = lds128(sb + O_MISC + 32), v1 = lds128(sb + O_MISC + 48);
                const uint32_t w1 = max(max(wq.x, wq.y), max(wq.z, wq.w)), x1 = max(max(max(xq.x, xq.y), max(xq.z, xq.w)), max(max(xr.x, xr.y), max(xr.z, xr.w)));
                const uint32_t vv = (r < 2) ? 0u : max(max(max(v0.x, v0.y), max(v0.z, v0.w)), max(max(v1.x, v1.y), max(v1.z, v1.w)));
                const uint32_t lo = (min(w1, 0x7f800000u) + 0xffffu) >> 16 | ((min(vv, 0x7f800000u) + 0xffffu) & 0xffff0000u), hi = (x1 & 0xffff0000u) | tag;
                uint32_t l0, h0, l1, h1, l2, h2;
                asm volatile("{\n.reg .pred p;\n.reg .u32 n, x, y;\n.reg .b64 v;\nsetp.eq.u32 p, %10, 0;\nmov.b64 v, {%8, %9};\n@p st.relaxed.gpu.global.b64 [%7], v;\nmov.u32 n, 0;\n"
                             "G_%=: ld.relaxed.gpu.global.b64 v, [%6];\nmov.b64 {%0, %1}, v;\nld.relaxed.gpu.global.b64 v, [%6+256];\nmov.b64 {%2, %3}, v;\n"
                             "ld.relaxed.gpu.global.b64 v, [%6+512];\nmov.b64 {%4, %5}, v;\n"
                             "xor.b32 x, %1, %9;\nxor.b32 y, %3, %9;\nor.b32 x, x, y;\nxor.b32 y, %5, %9;\nor.b32 x, x, y;\nand.b32 x, x, 0xffff;\n"
                             "setp.eq.u32 p, x, 0;\nvote.sync.all.pred p, p, 0xffffffff;\n@p bra.uni E_%=;\n"
                             "add.u32 n, n, 1;\nsetp.lt.u32 p, n, 4000000;\n@p bra.uni G_%=;\ntrap;\nE_%=:\n}"
                             : "=&r"(l0), "=&r"(h0), "=&r"(l1), "=&r"(h1), "=&r"(l2), "=&r"(h2)
                             : "l"(&g_norm[lane]), "l"(&g_norm[blockIdx.x]), "r"(lo), "r"(hi), "r"(lane) : "memory");
                const uint32_t lm = __vmaxu2(l0, __vmaxu2(l1, l2));
                const float fw = __uint_as_float(__reduce_max_sync(~0u, lm << 16));
                const float fv = __uint_as_float(__reduce_max_sync(~0u, lm & 0xffff0000u));
                const float xmax = __uint_as_float(__reduce_max_sync(~0u, max(h0, max(h1, h2)) & 0xffff0000u));
                const float G = 36.f * fw * fv;
                sts32_if(lane, sb + O_MISC + 4, __float_as_uint(G)); sts32_if(lane, sb + O_MISC + 8, __float_as_uint(G * xmax));
            }
        }
        if (c == 0) PSTAMP(12);
        bar_sync(6, 128);
        int s3 = 0;
        uint32_t roff = __shfl_sync(~0u, (r * 4 + c) * 2048 + (lane >> 4) * 512 + (lane & 2) * 128 + (lane & 1) * 64 + (lane & 12) * 4, lane);
#pragma unroll 1
        for (int s = 0; s < NSEG; s++) {
            const uint32_t l16 = opaque(l16c);
            const uint32_t vxa = sb + O_VX + (r == 2 ? s3 : (s & 1)) * 8192 + c * 2048 + l16;
            const int s3n = (s3 == 2) ? 0 : s3 + 1;
            sts32_if(l16, sb + O_MISC + 16 + 4 * c, __reduce_max_sync(~0u, mmax));
            mbar_arrive_if(l16, sb + B_MX);
            if (s == NSEG - 1) { bar_sync(3, 384); mbar_wait(sb + B_SC, s & 1); break; }
            if (c == 2 && r == 2) { bar_sync(14, 288); v_store(sb, h, s + 1, s3n); }
            uint4 vx[4];
            if (c == 0) STAMP(s, 5);
            {
                mbar_wait(sb + B_MX, s & 1);
                const uint4 mm = lds128(sb + O_MISC + 16), cf = lds128(sb + O_MISC);
                const float bound = fmaxf(__uint_as_float(cf.z), __uint_as_float(cf.y) * (__uint_as_float(max(max(mm.x, mm.y), max(mm.z, mm.w))) * __uint_as_float(cf.x)));
                const uint32_t ebits = __reduce_max_sync(~0u, min(max(__float_as_uint(bound) & 0x7f800000u, 21u << 23), 254u << 23));
                const int j = s + 1 + (r >> 1);
                if (c == 1 && j < NSEG) mbar_wait(sb + B_X + 8 * (j % 3), (j / 3) & 1);
                if (r < 2) mbar_wait(sb + B_VX + 8 * (s & 1), (s >> 1) & 1);
                bar_sync(3, 384);
                vx[0] = lds128(vxa); vx[2] = lds128(vxa + 1024);
                if (c == 0) STAMP(s, 13);
                mbar_wait(sb + B_SC, s & 1);
                if (c == 0) STAMP(s, 6);
                float p[10];
                load_scores(p, sb + O_SC, 1280, l16);
                float mx = fmaxf(fmaxf(fmaxf(p[0], p[1]), fmaxf(p[2], p[3])), fmaxf(fmaxf(p[4], p[5]), fmaxf(p[6], p[7])));
                mx = quad_max(fmaxf(mx, fmaxf(p[8], p[9])));
                const uint4 vm = lds64x2(sb + O_VM + c * 512 + (l16 >> 1));
                vx[1] = lds128(vxa + 512); vx[3] = lds128(vxa + 1536);
                bar_arrive(4, 384);
                const float sc = __uint_as_float(lds32(sb + O_MISC + 12));
                const float mo = mx * SM_SCALE;
                uint32_t P[5];
#pragma unroll
                for (int n = 0; n < 5; n++) P[n] = pack_bf16(ex2(fmaf(p[2 * n], SM_SCALE, -mo)), ex2(fmaf(p[2 * n + 1], n == 3 ? sc : SM_SCALE, -mo)));
                if (c == 0) STAMP(s, 7);
                float o0[4], o1[4], sm[4];
                mma16816_z(sm, ONES, ONES, ONES, ONES, P[1], P[2]);
                mma16816_z(o0, vx[0].x, vx[0].y, vx[0].z, vx[0].w, P[1], P[2]);
                mma16816_z(o1, vx[2].x, vx[2].y, vx[2].z, vx[2].w, P[1], P[2]);
                mma16816(sm, ONES, ONES, ONES, ONES, P[3], P[4]);
                mma16816(o0, vx[1].x, vx[1].y, vx[1].z, vx[1].w, P[3], P[4]);
                mma16816(o1, vx[3].x, vx[3].y, vx[3].z, vx[3].w, P[3], P[4]);
                mma1688(sm, ONES, ONES, P[0]);
                mma1688(o0, vm.x, vm.y, P[0]);
                mma1688(o1, vm.z, vm.w, P[0]);
                const float sig = __uint_as_float((268u << 23) - ebits);
                const float r0 = rcp_fast(sm[0]) * sig, r1 = rcp_fast(sm[1]) * sig;
                stsm4t(sb + O_OF + c * 512 + l16, pack_bf16(o0[0] * r0, o0[1] * r1), pack_bf16(o0[2] * r0, o0[3] * r1),
                       pack_bf16(o1[0] * r0, o1[1] * r1), pack_bf16(o1[2] * r0, o1[3] * r1));
                bar_sync(6, 128);
                uint4 ob[4];
#pragma unroll
                for (int q = 0; q < 4; q++) ob[q] = ldsm4(sb + O_OF + q * 512 + l16);
                { const uint4 v = lds128(sb + O_WP + c * 512 + l16); a[92] = v.x; a[93] = v.y; a[94] = v.z; a[95] = v.w; }
                float m0[3][4], m1[3][4];
#pragma unroll
                for (int q = 0; q < 4; q++) {
#pragma unroll
                    for (int i = 0; i < 3; i++) {
                        const int k0 = (i * 8 + 2 * q) * 4;
                        if (q == 0) mma16816_z(m0[i], a[k0], a[k0 + 1], a[k0 + 2], a[k0 + 3], ob[q].x, ob[q].y);
                        else mma16816(m0[i], a[k0], a[k0 + 1], a[k0 + 2], a[k0 + 3], ob[q].x, ob[q].y);
                    }
#pragma unroll
                    for (int i = 0; i < 3; i++) {
                        const int k1 = (i * 8 + 2 * q + 1) * 4;
                        if (q == 0) mma16816_z(m1[i], a[k1], a[k1 + 1], a[k1 + 2], a[k1 + 3], ob[q].z, ob[q].w);
                        else mma16816(m1[i], a[k1], a[k1 + 1], a[k1 + 2], a[k1 + 3], ob[q].z, ob[q].w);
                    }
                }
                if (EARLY5) {
                    const uint32_t z = __float_as_uint(m0[2][0]) & (l16 & 15u);
                    bar_arrive(5 + z, 256); bar_arrive(13 + z, 256);
                }
                asm volatile("red.relaxed.gpu.global.add.noftz.v4.f16x2 [%0], {%1,%2,%3,%4};" :: "l"(reinterpret_cast<char*>(g_acc) + roff),
                    "r"(pack_f16(m0[0][0] + m1[0][0], m0[0][2] + m1[0][2])), "r"(pack_f16(m0[1][0] + m1[1][0], m0[1][2] + m1[1][2])),
                    "r"(pack_f16(m0[2][0] + m1[2][0], m0[2][2] + m1[2][2])), "r"(0x3c00u) : "memory");
                asm volatile("red.relaxed.gpu.global.add.noftz.v4.f16x2 [%0], {%1,%2,%3,%4};" :: "l"(reinterpret_cast<char*>(g_acc) + roff + 1024),
                    "r"(pack_f16(m0[0][1] + m1[0][1], m0[0][3] + m1[0][3])), "r"(pack_f16(m0[1][1] + m1[1][1], m0[1][3] + m1[1][3])),
                    "r"(pack_f16(m0[2][1] + m1[2][1], m0[2][3] + m1[2][3])), "r"(0x3c00u) : "memory");
                const unsigned t_red = clk();
                if (!EARLY5) { bar_arrive(5, 256); bar_arrive(13, 256); }
                mbar_expect_if(l16 | c, sb + B_SC, 4608);
                mbar_expect_if(l16 | (c ^ 1) | (r >> 1), sb + B_VX + 8 * ((s + 1) & 1), 8192);
                sts32_if(l16 | (c ^ 3), sb + O_MISC, ebits - (14u << 23));
                if (c == 0) STAMPV(s, 8, t_red);
                if (c == 2 && r == 2) v_multicast(sb, h, s + 1);
                if (ACC_PF && c == 3 && s + 4 < NSEG - 1)
                    asm volatile("prefetch.global.L2 [%0];" :: "l"(reinterpret_cast<const char*>(g_acc) + ((s + 4) * 96 + blockIdx.x) * 256 + (l16 & 96)) : "memory");
                const char* pbase = reinterpret_cast<const char*>(g_acc) + (s * 24576 + c * 2048) + ((l16 & 64) * 16 + (l16 & 256) + ((l16 & 128) >> 1) + (l16 & 48));
                spin_until(t_red, D_WAIT);
                uint4 v[6];
#pragma unroll
                for (int i = 0; i < 6; i++) v[i] = ldg_relaxed128(pbase + (i >> 1) * 8192 + (i & 1) * 512);
                int nretry = 0;
                auto convert = [&](int tau, uint4& A, uint4& B) {
                    A.x = f16x2_to_bf16x2(A.x); B.x = f16x2_to_bf16x2(B.x); A.y = f16x2_to_bf16x2(A.y); B.y = f16x2_to_bf16x2(B.y);
                    A.z = f16x2_to_bf16x2(A.z); B.z = f16x2_to_bf16x2(B.z);
                    sts128(sb + O_MF + tau * 3072 + c * 512 + l16, A.x, B.x, A.y, B.y);
                    sts64(sb + O_MF + tau * 3072 + 2048 + (c >> 1) * 512 + (c & 1) * 8 + l16, A.z, B.z);
                };
                const uint32_t ok0 = __all_sync(~0u, (v[0].w & v[1].w) == 0x5000u);
                convert(0, v[0], v[1]);
                asm volatile("{\n.reg .pred p;\nsetp.ne.u32 p, %0, 0;\n@p bar.arrive 2, 384;\n}" :: "r"(ok0) : "memory");
                sched_fence<0>(h);
                uint32_t ok1;
                asm volatile("{\n.reg .pred p, q;\n.reg .b32 x;\nlop3.b32 x, %1, %2, %3, 0x80;\nand.b32 x, x, %4;\n"
                             "setp.eq.u32 p, x, 0x5000;\nvote.sync.all.pred q, p, 0xffffffff;\nselp.u32 %0, 1, 0, q;\n}"
                             : "=r"(ok1) : "r"(v[2].w), "r"(v[3].w), "r"(v[4].w), "r"(v[5].w));
                convert(1, v[2], v[3]); convert(2, v[4], v[5]);
                asm volatile("{\n.reg .pred p;\nsetp.ne.u32 p, %0, 0;\n@p bar.arrive 15, 384;\n}" :: "r"(ok1) : "memory");
                if (ok0 & ok1) {
                    mmax = absmax2(absmax2(absmax2(v[0].x, v[0].y), absmax2(v[0].z, v[1].x)), absmax2(absmax2(v[1].y, v[1].z), absmax2(v[2].x, v[2].y)));
                    mmax = absmax2(mmax, absmax2(absmax2(absmax2(v[2].z, v[3].x), absmax2(v[3].y, v[3].z)), absmax2(absmax2(v[4].x, v[4].y), absmax2(v[4].z, v[5].x))));
                    mmax = absmax2(mmax, absmax2(v[5].y, v[5].z));
                } else {
                    const uint32_t bad1 = !__all_sync(~0u, (v[2].w & v[3].w) == 0x5000u), bad2 = !__all_sync(~0u, (v[4].w & v[5].w) == 0x5000u);
                    uint4 u[6];
                    asm volatile("{\n.reg .pred p0, p1, p2, q;\n.reg .u32 n, x;\nmov.u32 n, 0;\n"
                         "setp.eq.u32 p0, %26, 0;\nsetp.ne.u32 p1, %27, 0;\nsetp.ne.u32 p2, %28, 0;\n"
                         "mov.u32 %0, 0; mov.u32 %1, 0; mov.u32 %2, 0; mov.u32 %3, 0x5000; mov.u32 %4, 0; mov.u32 %5, 0; mov.u32 %6, 0; mov.u32 %7, 0x5000;\n"
                         "mov.u32 %8, 0; mov.u32 %9, 0; mov.u32 %10, 0; mov.u32 %11, 0x5000; mov.u32 %12, 0; mov.u32 %13, 0; mov.u32 %14, 0; mov.u32 %15, 0x5000;\n"
                         "mov.u32 %16, 0; mov.u32 %17, 0; mov.u32 %18, 0; mov.u32 %19, 0x5000; mov.u32 %20, 0; mov.u32 %21, 0; mov.u32 %22, 0; mov.u32 %23, 0x5000;\n"
                         "R_%=: @p0 ld.relaxed.gpu.global.v4.u32 {%0,%1,%2,%3}, [%25];\n@p0 ld.relaxed.gpu.global.v4.u32 {%4,%5,%6,%7}, [%25+512];\n"
                         "@p1 ld.relaxed.gpu.global.v4.u32 {%8,%9,%10,%11}, [%25+8192];\n@p1 ld.relaxed.gpu.global.v4.u32 {%12,%13,%14,%15}, [%25+8704];\n"
                         "@p2 ld.relaxed.gpu.global.v4.u32 {%16,%17,%18,%19}, [%25+16384];\n@p2 ld.relaxed.gpu.global.v4.u32 {%20,%21,%22,%23}, [%25+16896];\n"
                         "add.u32 %24, %24, 1;\nand.b32 x, %3, %7;\nsetp.ne.u32 p0, x, 0x5000;\nand.b32 x, %11, %15;\nsetp.ne.u32 p1, x, 0x5000;\n"
                         "and.b32 x, %19, %23;\nsetp.ne.u32 p2, x, 0x5000;\nor.pred q, p0, p1;\nor.pred q, q, p2;\nvote.sync.any.pred q, q, 0xffffffff;\n@!q bra.uni K_%=;\n"
                         "add.u32 n, n, 1;\nsetp.lt.u32 q, n, 2000000;\n@q bra.uni R_%=;\ntrap;\nK_%=:\n}"
                         : "=&r"(u[0].x), "=&r"(u[0].y), "=&r"(u[0].z), "=&r"(u[0].w), "=&r"(u[1].x), "=&r"(u[1].y), "=&r"(u[1].z), "=&r"(u[1].w),
                           "=&r"(u[2].x), "=&r"(u[2].y), "=&r"(u[2].z), "=&r"(u[2].w), "=&r"(u[3].x), "=&r"(u[3].y), "=&r"(u[3].z), "=&r"(u[3].w),
                           "=&r"(u[4].x), "=&r"(u[4].y), "=&r"(u[4].z), "=&r"(u[4].w), "=&r"(u[5].x), "=&r"(u[5].y), "=&r"(u[5].z), "=&r"(u[5].w), "+r"(nretry)
                         : "l"(pbase), "r"(ok0), "r"(bad1), "r"(bad2) : "memory");
                    if (!ok0) { convert(0, u[0], u[1]); bar_arrive(2, 384); }
                    if (bad1) convert(1, u[2], u[3]);
                    if (bad2) convert(2, u[4], u[5]);
                    if (!ok1) bar_arrive(15, 384);
                    mmax = 0;
#pragma unroll
                    for (int tau = 0; tau < 3; tau++) {
                        const uint4 A = lds128(sb + O_MF + tau * 3072 + c * 512 + l16);
                        const float2 B = lds64f(sb + O_MF + tau * 3072 + 2048 + (c >> 1) * 512 + (c & 1) * 8 + l16);
                        mmax = absmax2(absmax2(mmax, absmax2(A.x, A.y)), absmax2(absmax2(A.z, A.w), absmax2(__float_as_uint(B.x), __float_as_uint(B.y))));
                    }
                }
                if (c == 0) STAMP(s, 12);
                if (c == 0) STAMPV(s, 14, nretry);
                mmax &= 0x7fff7fffu;
                mmax = max(mmax << 16, mmax & 0xffff0000u);
            }
            roff += 24576;
            s3 = s3n;
        }
        {
            bar_sync(7, 384);
            if (c == 0) flag_inc_if(l16c, &g_flag[F_QKV + (60 + (h >> 3)) * 8]);
        }
    }
    if (warp == 8) PSTAMP(13);
    cluster_sync();
}

constexpr int NST = 10;
constexpr int G_RING = 0, G_EX = NST * 16384, G_OUT = G_EX + 32768, G_CARRY = G_OUT + 32768, G_BAR = G_CARRY + 512, BG_SMEM = G_BAR + 256;
constexpr int GB_FULL = G_BAR, GB_EMPTY = G_BAR + 8 * NST, GB_W = G_BAR + 16 * NST;
static_assert(BG_SMEM <= 232448, "smem");

template <int ACC>
__device__ __forceinline__ void wgmma_n128_rs(float (&d)[64], uint32_t a0, uint32_t a1, uint32_t a2, uint32_t a3, uint64_t desc) {
    asm volatile("wgmma.mma_async.sync.aligned.m64n128k16.f32.bf16.bf16 "
        "{%0,%1,%2,%3,%4,%5,%6,%7,%8,%9,%10,%11,%12,%13,%14,%15,%16,%17,%18,%19,%20,%21,%22,%23,%24,%25,%26,%27,%28,%29,%30,%31,"
        "%32,%33,%34,%35,%36,%37,%38,%39,%40,%41,%42,%43,%44,%45,%46,%47,%48,%49,%50,%51,%52,%53,%54,%55,%56,%57,%58,%59,%60,%61,%62,%63}, "
        "{%64,%65,%66,%67}, %68, %69, 1, 1, 0;"
        : "+f"(d[0]), "+f"(d[1]), "+f"(d[2]), "+f"(d[3]), "+f"(d[4]), "+f"(d[5]), "+f"(d[6]), "+f"(d[7]),
          "+f"(d[8]), "+f"(d[9]), "+f"(d[10]), "+f"(d[11]), "+f"(d[12]), "+f"(d[13]), "+f"(d[14]), "+f"(d[15]),
          "+f"(d[16]), "+f"(d[17]), "+f"(d[18]), "+f"(d[19]), "+f"(d[20]), "+f"(d[21]), "+f"(d[22]), "+f"(d[23]),
          "+f"(d[24]), "+f"(d[25]), "+f"(d[26]), "+f"(d[27]), "+f"(d[28]), "+f"(d[29]), "+f"(d[30]), "+f"(d[31]),
          "+f"(d[32]), "+f"(d[33]), "+f"(d[34]), "+f"(d[35]), "+f"(d[36]), "+f"(d[37]), "+f"(d[38]), "+f"(d[39]),
          "+f"(d[40]), "+f"(d[41]), "+f"(d[42]), "+f"(d[43]), "+f"(d[44]), "+f"(d[45]), "+f"(d[46]), "+f"(d[47]),
          "+f"(d[48]), "+f"(d[49]), "+f"(d[50]), "+f"(d[51]), "+f"(d[52]), "+f"(d[53]), "+f"(d[54]), "+f"(d[55]),
          "+f"(d[56]), "+f"(d[57]), "+f"(d[58]), "+f"(d[59]), "+f"(d[60]), "+f"(d[61]), "+f"(d[62]), "+f"(d[63])
        : "r"(a0), "r"(a1), "r"(a2), "r"(a3), "l"(desc), "n"(ACC));
}
__device__ __forceinline__ void wait_flag(const unsigned* p, unsigned target) {
    asm volatile("{\n.reg .pred p;\n.reg .u32 n, v;\nmov.u32 n, 0;\n"
                 "W_%=: ld.acquire.gpu.global.u32 v, [%0];\nsub.u32 v, v, %1;\nsetp.ge.s32 p, v, 0;\n@p bra.uni D_%=;\nnanosleep.u32 100;\n"
                 "add.u32 n, n, 1;\nsetp.lt.u32 p, n, 4000000;\n@p bra.uni W_%=;\ntrap;\nD_%=:\n}" :: "l"(p), "r"(target) : "memory");
}
template <int NS, int STRIDE>
__device__ __forceinline__ void bg_mainloop(float (&d)[64], const uint32_t (&a)[144], uint32_t sb, int it, int lane) {
    int slot = it % NST, ph = (it / NST) & 1, prev = 0;
#pragma unroll
    for (int i = 0; i < NS; i++) {
        mbar_wait(sb + GB_FULL + 8 * slot, ph);
        const uint64_t desc = (uint64_t)(((sb + G_RING + slot * 16384) & 0x3FFFF) >> 4) | (1ull << 16) | (64ull << 32) | (1ull << 62);
        wg_fence();
#pragma unroll
        for (int k = 0; k < 4; k++) {
            const int u = 16 * i + 4 * k;
            if (i == 0 && k == 0) wgmma_n128_rs<0>(d, a[u], a[u + 1], a[u + 2], a[u + 3], desc);
            else wgmma_n128_rs<1>(d, a[u], a[u + 1], a[u + 2], a[u + 3], desc + 2 * k);
        }
        wg_commit();
        if (i > 0) {
            asm volatile("wgmma.wait_group.sync.aligned 1;" ::: "memory");
            mbar_arrive_if(lane, sb + GB_EMPTY + 8 * prev);
        }
        prev = slot;
        slot += STRIDE;
        if (slot >= NST) { slot -= NST; ph ^= 1; }
    }
    wg_wait0();
    mbar_arrive_if(lane, sb + GB_EMPTY + 8 * prev);
}
template <bool SKIP>
__device__ __forceinline__ void bg_epilogue(float (&d)[64], uint32_t sb, int wg, int w, int lane, const CUtensorMap* tm_out, int col0, int tok0,
                                            const __nv_bfloat16* xa, const __nv_bfloat16* Dk) {
    const int g = lane >> 2, t = lane & 3;
    const uint32_t ex = sb + G_EX + w * 4096 + lane * 16;
    float k[32];
    if (wg == 0) {
#pragma unroll
        for (int q = 0; q < 8; q++) sts128f(ex + q * 512, d[32 + 4 * q], d[32 + 4 * q + 1], d[32 + 4 * q + 2], d[32 + 4 * q + 3]);
#pragma unroll
        for (int i = 0; i < 32; i++) k[i] = d[i];
    } else {
#pragma unroll
        for (int q = 0; q < 8; q++) sts128f(ex + 16384 + q * 512, d[4 * q], d[4 * q + 1], d[4 * q + 2], d[4 * q + 3]);
#pragma unroll
        for (int i = 0; i < 32; i++) k[i] = d[32 + i];
    }
    uint32_t xv[16], dv = 0;
    if (SKIP) {
        const __nv_bfloat16* xp = xa + (size_t)(tok0 + 64 * wg + 2 * t) * DM + col0 + 16 * w + 2 * g;
#pragma unroll
        for (int i = 0; i < 16; i++) xv[i] = ldg_nc32(xp + (8 * (i >> 1) + (i & 1)) * DM);
        dv = ldg_nc32(Dk + col0 + 16 * w + 2 * g);
    }
    if (SKIP && w == 0) asm volatile("cp.async.bulk.wait_group.read 0;" ::: "memory");
    bar_sync(1, 256);
#pragma unroll
    for (int q = 0; q < 8; q++) {
        const float4 o = lds128f(ex + (wg ^ 1) * 16384 + q * 512);
        k[4 * q] += o.x; k[4 * q + 1] += o.y; k[4 * q + 2] += o.z; k[4 * q + 3] += o.w;
    }
    if (SKIP) bar_sync(1, 256); else bar_sync(13, 288);
    const uint32_t ob = sb + G_OUT + wg * 16384 + (w >> 1) * 8192 + (g & 1) * 8;
    const uint32_t ch = (w & 1) * 4 + (g >> 1);
#pragma unroll
    for (int i = 0; i < 16; i++) {
        float v0 = k[4 * (i >> 1) + (i & 1)], v1 = k[4 * (i >> 1) + 2 + (i & 1)];
        if (SKIP) {
            const uint32_t p = pack_bf16(__uint_as_float(xv[i] << 16) * __uint_as_float(dv << 16), __uint_as_float(xv[i] & 0xffff0000u) * __uint_as_float(dv & 0xffff0000u));
            v0 += __uint_as_float(p << 16); v1 += __uint_as_float(p & 0xffff0000u);
        }
        const uint32_t n7 = 2 * t + (i & 1);
        sts64(ob + (8 * (i >> 1) + n7) * 128 + ((ch ^ n7) << 4), __float_as_uint(v0), __float_as_uint(v1));
    }
    fence_async_smem();
    if (SKIP) {
        bar_sync(4 + wg, 128);
        if (w == 0)
            asm volatile("{\n.reg .pred p;\nelect.sync _|p, 0xffffffff;\n"
                "@p cp.async.bulk.tensor.2d.global.shared::cta.bulk_group [%0, {%2, %4}], [%1];\n"
                "@p cp.async.bulk.tensor.2d.global.shared::cta.bulk_group [%0, {%3, %4}], [%1+8192];\n@p cp.async.bulk.commit_group;\n}"
                :: "l"(tm_out), "r"(sb + G_OUT + wg * 16384), "r"(col0), "r"(col0 + 32), "r"(tok0 + 64 * wg) : "memory");
    } else {
        bar_arrive(12, 288);
    }
}
__device__ __forceinline__ void s5_channel(int p, const __nv_bfloat16* Lre, const __nv_bfloat16* Lim, const __nv_bfloat16* logdt, float2& lam, float2& coef) {
    const float dt = __bfloat162float(__float2bfloat16(expf(__bfloat162float(logdt[p]))));
    const float lr = __bfloat162float(Lre[p]), li = __bfloat162float(Lim[p]);
    const float e = expf(dt * lr);
    float sn, cs;
    sincosf(dt * li, &sn, &cs);
    lam = make_float2(e * cs, e * sn);
    const float den = lr * lr + li * li;
    coef = make_float2(((lam.x - 1.f) * lr + lam.y * li) / den, (lam.y * lr - (lam.x - 1.f) * li) / den);
}
__device__ __forceinline__ float2 cfma(float2 a, float2 b, float2 c) {
    return make_float2(fmaf(a.x, b.x, fmaf(-a.y, b.y, c.x)), fmaf(a.x, b.y, fmaf(a.y, b.x, c.y)));
}
__device__ __forceinline__ uint4 ldg128(const void* p) { uint4 v; asm volatile("ld.global.v4.u32 {%0,%1,%2,%3}, [%4];" : "=r"(v.x), "=r"(v.y), "=r"(v.z), "=r"(v.w) : "l"(p) : "memory"); return v; }
__device__ __forceinline__ uint2 ldg64(const void* p) { uint2 v; asm volatile("ld.global.v2.u32 {%0,%1}, [%2];" : "=r"(v.x), "=r"(v.y) : "l"(p) : "memory"); return v; }

__device__ __forceinline__ void bg_attention(uint32_t st0, uint32_t st1, int mt, int lane) {
    const int g = lane >> 2, t = lane & 3;
    float sc[5][4];
#pragma unroll
    for (int n = 0; n < 5; n++) sc[n][0] = sc[n][1] = sc[n][2] = sc[n][3] = 0.f;
    float sm2[4] = {0.f, 0.f, 0.f, 0.f};
#pragma unroll
    for (int i = 0; i < 8; i++) {
        const uint32_t st = (i >> 2 ? st1 : st0) + (i & 3) * 512 + lane * 16;
        const uint4 q = ldsm4(st + mt * 2048), km = ldsm4(st + 8192), k0 = ldsm4(st + 4096);
        mma16816(sc[0], q.x, q.y, q.z, q.w, km.x, km.y);
        mma16816(sm2, q.x, q.y, q.z, q.w, km.z, km.w);
        mma16816(sc[1], q.x, q.y, q.z, q.w, k0.x, k0.y);
        mma16816(sc[2], q.x, q.y, q.z, q.w, k0.z, k0.w);
        if (mt) {
            const uint4 k1 = ldsm4(st + 6144);
            mma16816(sc[3], q.x, q.y, q.z, q.w, k1.x, k1.y);
            mma16816(sc[4], q.x, q.y, q.z, q.w, k1.z, k1.w);
        }
    }
#pragma unroll
    for (int i = 0; i < 4; i++) sc[0][i] += sm2[i];
    const int q0 = 16 * mt + 8 + g - 2 * t;
#pragma unroll
    for (int n = 1; n < 5; n++) {
        if (8 * n > q0) sc[n][0] = -INFINITY;
        if (8 * n + 1 > q0) sc[n][1] = -INFINITY;
        if (8 * n > q0 + 8) sc[n][2] = -INFINITY;
        if (8 * n + 1 > q0 + 8) sc[n][3] = -INFINITY;
    }
    float ma = fmaxf(sc[0][0], sc[0][1]), mb = fmaxf(sc[0][2], sc[0][3]);
#pragma unroll
    for (int n = 1; n < 5; n++) { ma = fmaxf(ma, fmaxf(sc[n][0], sc[n][1])); mb = fmaxf(mb, fmaxf(sc[n][2], sc[n][3])); }
    ma = quad_max(ma) * SM_SCALE; mb = quad_max(mb) * SM_SCALE;
    uint32_t Pa[5], Pb[5];
#pragma unroll
    for (int n = 0; n < 5; n++) {
        Pa[n] = pack_bf16(ex2(fmaf(sc[n][0], SM_SCALE, -ma)), ex2(fmaf(sc[n][1], SM_SCALE, -ma)));
        Pb[n] = pack_bf16(ex2(fmaf(sc[n][2], SM_SCALE, -mb)), ex2(fmaf(sc[n][3], SM_SCALE, -mb)));
    }
    float sa[4], sbb[4];
    mma1688_z(sa, ONES, ONES, Pa[0]); mma1688_z(sbb, ONES, ONES, Pb[0]);
    mma16816(sa, ONES, ONES, ONES, ONES, Pa[1], Pa[2]); mma16816(sbb, ONES, ONES, ONES, ONES, Pb[1], Pb[2]);
    mma16816(sa, ONES, ONES, ONES, ONES, Pa[3], Pa[4]); mma16816(sbb, ONES, ONES, ONES, ONES, Pb[3], Pb[4]);
    const float ra0 = rcp_fast(sa[0]), ra1 = rcp_fast(sa[1]), rb0 = rcp_fast(sbb[0]), rb1 = rcp_fast(sbb[1]);
    const uint32_t row = lane & 7;
    const uint32_t so = mt * 2048 + (lane >> 4) * 1024 + row * 128;
#pragma unroll
    for (int i = 0; i < 8; i++) {
        const uint32_t st = i >> 2 ? st1 : st0;
        const int e4 = i & 3;
        const float2 vmf = lds64f(st + 14336 + e4 * 256 + lane * 8);
        const uint32_t vm0 = __float_as_uint(vmf.x), vm1 = __float_as_uint(vmf.y);
        const uint4 v0 = lds128(st + 10240 + e4 * 1024 + lane * 16);
        float oa[4], ob[4];
        mma1688_z(oa, vm0, vm1, Pa[0]); mma1688_z(ob, vm0, vm1, Pb[0]);
        mma16816(oa, v0.x, v0.y, v0.z, v0.w, Pa[1], Pa[2]);
        mma16816(ob, v0.x, v0.y, v0.z, v0.w, Pb[1], Pb[2]);
        if (mt) {
            const uint4 v1 = lds128(st + 10240 + e4 * 1024 + 512 + lane * 16);
            mma16816(oa, v1.x, v1.y, v1.z, v1.w, Pa[3], Pa[4]);
            mma16816(ob, v1.x, v1.y, v1.z, v1.w, Pb[3], Pb[4]);
        }
        stsm4t(st + so + (((2 * e4 + ((lane >> 3) & 1)) ^ row) << 4), pack_bf16(oa[0] * ra0, oa[1] * ra1), pack_bf16(oa[2] * ra0, oa[3] * ra1),
               pack_bf16(ob[0] * rb0, ob[1] * rb1), pack_bf16(ob[2] * rb0, ob[3] * rb1));
    }
}
__device__ __forceinline__ bool bg_att_turn(int na, int ng) { return na == ng || (na == ng + 1 && na <= BG_AHEAD); }

__global__ void __launch_bounds__(384, 1)
bg_kernel(const __grid_constant__ CUtensorMap tm_xa, const __grid_constant__ CUtensorMap tm_wo, const __grid_constant__ CUtensorMap tm_out,
          const __nv_bfloat16* __restrict__ xa, const __nv_bfloat16* __restrict__ Lre, const __nv_bfloat16* __restrict__ Lim,
          const __nv_bfloat16* __restrict__ Bre, const __nv_bfloat16* __restrict__ Bim, const __nv_bfloat16* __restrict__ Cre,
          const __nv_bfloat16* __restrict__ Cim, const __nv_bfloat16* __restrict__ logdt, const __nv_bfloat16* __restrict__ Dk) {
    extern __shared__ __align__(1024) uint8_t smem_raw[];
    const uint32_t sb = smem_u32(smem_raw);
    const int lane = threadIdx.x & 31;
    const int warp = __shfl_sync(~0u, threadIdx.x >> 5, 0);
    const int wg = warp >> 2, w = warp & 3, b = blockIdx.x;
    const int nt = b % 9, kq = b / 9;
    BSTAMP(0);
    if (threadIdx.x == 0) {
        if (sb & 1023u) __trap();
        for (int i = 0; i < NST; i++) { mbar_init(sb + GB_FULL + 8 * i, 1); mbar_init(sb + GB_EMPTY + 8 * i, 4); }
        mbar_init(sb + GB_W, 1);
        asm volatile("fence.mbarrier_init.release.cluster;" ::: "memory");
        mbar_expect(sb + GB_W, (b < 18 ? 64 : 128) * 1152);
        sts32(sb + G_BAR + 248, atomicAdd(&g_ticket_bg, 1u) / 36u + 1u);
    }
    __syncthreads();
    if (wg == 2) {
        asm volatile("setmaxnreg.dec.sync.aligned.u32 24;");
        if (w == 0) {
            int slot = 0, ph = 1;
            unsigned tlast = clk();
            auto pace = [&]() { if (BG_PACE) { spin_until(tlast, BG_PACE); tlast = clk(); } };
            auto next = [&]() { if (++slot == NST) { slot = 0; ph ^= 1; } };
            bar_sync(6, 288);
            if (b < 18) {
#pragma unroll 1
                for (int i = 0; i < 144; i++) {
                    const int blk = i / 9, kb = i - 9 * blk, it = (blk >> 1) * 18 + (blk & 1) + 2 * kb;
                    slot = it % NST;
                    mbar_wait(sb + GB_EMPTY + 8 * slot, ((it / NST) & 1) ^ 1);
                    pace();
                    asm volatile("{\n.reg .pred p;\nelect.sync _|p, 0xffffffff;\n@p mbarrier.arrive.expect_tx.shared::cta.b64 _, [%2], 16384;\n"
                        "@p cp.async.bulk.tensor.5d.shared::cluster.global.mbarrier::complete_tx::bytes [%0], [%1, {%3, %4, %4, %4, %5}], [%2];\n}"
                        :: "r"(sb + G_RING + slot * 16384), "l"(&tm_xa), "r"(sb + GB_FULL + 8 * slot), "r"(kb * 64), "r"(0), "r"(blk) : "memory");
                }
                slot = 144 % NST; ph = ((144 / NST) & 1) ^ 1;
            }
            const unsigned ep = lds32(sb + G_BAR + 248);
            auto slabs = [&](const char* src, int ns) {
                asm volatile("fence.proxy.async.global;" ::: "memory");
#pragma unroll 1
                for (int i = 0; i < ns; i++) {
                    mbar_wait(sb + GB_EMPTY + 8 * slot, ph);
                    pace();
                    asm volatile("{\n.reg .pred p;\nelect.sync _|p, 0xffffffff;\n@p mbarrier.arrive.expect_tx.shared::cta.b64 _, [%2], 16384;\n"
                        "@p cp.async.bulk.shared::cluster.global.mbarrier::complete_tx::bytes [%0], [%1], 16384, [%2];\n}"
                        :: "r"(sb + G_RING + slot * 16384), "l"(src + (size_t)((i & 1) * (ns >> 1) + (i >> 1)) * (SEQ * 128)), "r"(sb + GB_FULL + 8 * slot) : "memory");
                    next();
                }
            };
            if (b >= 18) {
#pragma unroll 1
                for (int blk = kq - 2; blk < 16; blk += 2) {
                    wait_flag(&g_flag[F_H + blk * 8], 18 * ep);
                    slabs(reinterpret_cast<const char*>(g_h) + blk * 16384, 18);
                }
            }
            bar_sync(6, 288);
#pragma unroll 1
            for (int na = 0, ng = 0; ng < 16;) {
                if (bg_att_turn(na, ng)) {
                    if (nt < 8) {
                        wait_flag(&g_flag[F_QKV + (na * 4 + kq) * 8], 24 * ep);
                        asm volatile("fence.proxy.async.global;" ::: "memory");
#pragma unroll 1
                        for (int i = 0; i < 8; i++) {
                            const int pr = nt * 4 + 2 * (i & 1) + (i >> 2), hf = (i >> 1) & 1;
                            const char* rec = reinterpret_cast<const char*>(g_qkv) + (size_t)((4 * na + (pr >> 3)) * NH + 8 * kq + (pr & 7)) * REC;
                            mbar_wait(sb + GB_EMPTY + 8 * slot, ph);
                    pace();
                            asm volatile("{\n.reg .pred p;\nelect.sync _|p, 0xffffffff;\n@p mbarrier.arrive.expect_tx.shared::cta.b64 _, [%4], 15360;\n"
                                "@p cp.async.bulk.shared::cluster.global.mbarrier::complete_tx::bytes [%0], [%1], 10240, [%4];\n"
                                "@p cp.async.bulk.shared::cluster.global.mbarrier::complete_tx::bytes [%0+10240], [%2], 4096, [%4];\n"
                                "@p cp.async.bulk.shared::cluster.global.mbarrier::complete_tx::bytes [%0+14336], [%3], 1024, [%4];\n}"
                                :: "r"(sb + G_RING + slot * 16384), "l"(rec + hf * 10240), "l"(rec + 20480 + hf * 4096), "l"(rec + 28672 + hf * 1024),
                                   "r"(sb + GB_FULL + 8 * slot) : "memory");
                            next();
                        }
                    }
                    na++;
                } else {
                    wait_flag(&g_flag[F_OX + (ng * 4 + kq) * 8], 8 * ep);
                    slabs(reinterpret_cast<const char*>(g_ox) + (size_t)kq * 16 * SEQ * 128 + ng * 16384, 16);
                    ng++;
                }
            }
        } else if (w == 1) {
            if (b < 18) {
#pragma unroll 1
                for (int blk = 0; blk < 16; blk++) {
                    bar_sync(8 + (blk & 1), 160);
                    asm volatile("{\n.reg .pred p;\nelect.sync _|p, 0xffffffff;\n@p cp.async.bulk.global.shared::cta.bulk_group [%0], [%1], 16384;\n"
                        "@p cp.async.bulk.commit_group;\ncp.async.bulk.wait_group 0;\nfence.proxy.async.global;\n}"
                        :: "l"(reinterpret_cast<char*>(g_h) + ((size_t)b * SEQ + blk * 128) * 128), "r"(sb + G_OUT + (blk & 1) * 16384) : "memory");
                    bar_arrive(10 + (blk & 1), 160);
                    flag_inc_if(lane, &g_flag[F_H + blk * 8]);
                }
            }
            if (nt < 8) {
                int it = 144;
#pragma unroll 1
                for (int na = 0, ng = 0; ng < 16;) {
                    if (bg_att_turn(na, ng)) {
                        bar_sync(7, 288);
                        if (lane < 8) {
                            const int pr = nt * 4 + 2 * (lane & 1) + (lane >> 2), hf = (lane >> 1) & 1;
                            asm volatile("cp.async.bulk.global.shared::cta.bulk_group [%0], [%1], 4096;\ncp.async.bulk.commit_group;\ncp.async.bulk.wait_group.read 0;\n"
                                "mbarrier.arrive.shared::cta.b64 _, [%2], 4;\ncp.async.bulk.wait_group 0;\nfence.proxy.async.global;"
                                :: "l"(reinterpret_cast<char*>(g_ox) + ((size_t)((8 * kq + (pr & 7)) * 2 + hf) * SEQ + (4 * na + (pr >> 3)) * 32) * 128),
                                   "r"(sb + G_RING + ((it + lane) % NST) * 16384), "r"(sb + GB_EMPTY + 8 * ((it + lane) % NST)) : "memory");
                        }
                        __syncwarp();
                        flag_inc_if(lane, &g_flag[F_OX + (na * 4 + kq) * 8]);
                        it += 8; na++;
                    } else { it += 16; ng++; }
                }
            }
        } else if (w == 2) {
            const unsigned ep = lds32(sb + G_BAR + 248);
#pragma unroll 1
            for (int blk = 0; blk < 16; blk++) {
                bar_arrive(13, 288);
                bar_sync(12, 288);
                if (kq) { wait_flag(&g_flag[F_OUT + (blk * 9 + nt) * 8], ep); asm volatile("fence.proxy.async.global;" ::: "memory"); }
                unsigned t0 = clk();
                if (blk < 15) spin_until(t0, b * (RED_GAP / 36));
#pragma unroll 1
                for (int i = 0; i < 4; i++) {
                    const uint32_t src = sb + G_OUT + i * 8192;
                    const int c0 = DM + 64 * nt + (i & 1) * 32, c1 = blk * 128 + (i >> 1) * 64;
                    if (kq) {
                        asm volatile("{\n.reg .pred p;\nelect.sync _|p, 0xffffffff;\n@p cp.reduce.async.bulk.tensor.2d.global.shared::cta.add.bulk_group [%0, {%2, %3}], [%1];\n}"
                            :: "l"(&tm_out), "r"(src), "r"(c0), "r"(c1) : "memory");
                        t0 = clk();
                        if (blk < 15 && i < 3) spin_until(t0, RED_GAP);
                    } else {
                        asm volatile("{\n.reg .pred p;\nelect.sync _|p, 0xffffffff;\n@p cp.async.bulk.tensor.2d.global.shared::cta.bulk_group [%0, {%2, %3}], [%1];\n}"
                            :: "l"(&tm_out), "r"(src), "r"(c0), "r"(c1) : "memory");
                    }
                }
                asm volatile("cp.async.bulk.commit_group;\ncp.async.bulk.wait_group 0;\nfence.proxy.async.global;" ::: "memory");
                __syncwarp();
                if (!kq) flag_inc_if(lane, &g_flag[F_OUT + (blk * 9 + nt) * 8]);
            }
        }
    } else {
        asm volatile("setmaxnreg.inc.sync.aligned.u32 240;");
        const int g = lane >> 2, t = lane & 3, tid = threadIdx.x;
        uint32_t a[144];
        float d[64];
        if (b < 18) {
            if (tid < 64)
                asm volatile("cp.async.bulk.shared::cluster.global.mbarrier::complete_tx::bytes [%0], [%1], 1152, [%2];"
                    :: "r"(sb + tid * 1168), "l"((tid < 32 ? Bre : Bim) + (size_t)(32 * b + (tid & 31)) * DM), "r"(sb + GB_W) : "memory");
            float2 lam, coef;
            s5_channel(32 * b + 8 * w + g, Lre, Lim, logdt, lam, coef);
            float2 l32 = lam;
#pragma unroll
            for (int i = 0; i < 5; i++) l32 = make_float2(l32.x * l32.x - l32.y * l32.y, 2.f * l32.x * l32.y);
            __syncwarp();
            mbar_wait(sb + GB_W, 0);
            const uint32_t ap = sb + (((lane >> 3) & 1) * 32 + 8 * w + (lane & 7)) * 1168 + (lane >> 4) * 16;
#pragma unroll
            for (int ks = 0; ks < 36; ks++) { const uint4 v = ldsm4(ap + ks * 32); a[4 * ks] = v.x; a[4 * ks + 1] = v.y; a[4 * ks + 2] = v.z; a[4 * ks + 3] = v.w; }
            bar_sync(1, 256);
            bar_arrive(6, 288);
            BSTAMP(1);
#pragma unroll 1
            for (int blk = wg; blk < 16; blk += 2) {
                bg_mainloop<9, 2>(d, a, sb, (blk >> 1) * 18 + wg, lane);
                float2 e = make_float2(0.f, 0.f);
#pragma unroll
                for (int i = 0; i < 32; i++) e = cfma(lam, e, make_float2(d[4 * (i >> 1) + (i & 1)], d[4 * (i >> 1) + 2 + (i & 1)]));
                float2 cin = make_float2(0.f, 0.f);
                if (blk > 0) { bar_sync(2 + (wg ^ 1), 256); cin = lds64f(sb + G_CARRY + (wg ^ 1) * 256 + (8 * w + g) * 8); }
                float2 mine = cin;
#pragma unroll
                for (int q = 0; q < 4; q++) {
                    const float2 eq = make_float2(__shfl_sync(~0u, e.x, (lane & 28) + q), __shfl_sync(~0u, e.y, (lane & 28) + q));
                    cin = cfma(l32, cin, eq);
                    if (t == q + 1) mine = cin;
                }
                if (blk < 15) {
                    if (t == 0) sts64(sb + G_CARRY + wg * 256 + (8 * w + g) * 8, __float_as_uint(cin.x), __float_as_uint(cin.y));
                    bar_arrive(2 + wg, 256);
                }
                const uint32_t hs = sb + G_OUT + wg * 16384 + t * 4096 + (g & 3) * 4;
                const uint32_t ch = 2 * w + (g >> 2);
                if (blk >= 2) bar_sync(10 + wg, 160);
#pragma unroll
                for (int i = 0; i < 32; i++) {
                    mine = cfma(lam, mine, make_float2(d[4 * (i >> 1) + (i & 1)], d[4 * (i >> 1) + 2 + (i & 1)]));
                    sts32(hs + i * 128 + ((ch ^ (i & 7)) << 4), pack_bf16(mine.x, mine.y));
                }
                fence_async_smem();
                bar_arrive(8 + wg, 160);
            }
            bar_sync(10 + wg, 160);
        } else {
            if (tid < 128)
                asm volatile("cp.async.bulk.shared::cluster.global.mbarrier::complete_tx::bytes [%0], [%1], 1152, [%2];"
                    :: "r"(sb + tid * 1168), "l"((tid < 64 ? Cre : Cim) + (size_t)(64 * nt + (tid & 63)) * DM), "r"(sb + GB_W) : "memory");
            for (int p = tid; p < DM; p += 256) {
                float2 lam, coef;
                s5_channel(p, Lre, Lim, logdt, lam, coef);
                sts64(sb + G_EX + p * 8, __float_as_uint(2.f * coef.x), __float_as_uint(2.f * coef.y));
            }
            bar_sync(1, 256);
            mbar_wait(sb + GB_W, 0);
            const uint32_t cp = sb + (16 * w + 2 * g) * 1168 + (288 * wg + t) * 2;
#pragma unroll
            for (int u = 0; u < 72; u++) {
                const float2 c2 = lds64f(sb + G_EX + (288 * wg + 4 * u + t) * 8);
#pragma unroll
                for (int f = 0; f < 2; f++) {
                    unsigned short r16, i16;
                    asm volatile("ld.shared.u16 %0, [%1];" : "=h"(r16) : "r"(cp + f * 1168 + u * 8) : "memory");
                    asm volatile("ld.shared.u16 %0, [%1];" : "=h"(i16) : "r"(cp + (64 + f) * 1168 + u * 8) : "memory");
                    const float cr = __uint_as_float((uint32_t)r16 << 16), ci = __uint_as_float((uint32_t)i16 << 16);
                    a[2 * u + f] = pack_bf16(cr * c2.x - ci * c2.y, -(cr * c2.y + ci * c2.x));
                }
            }
            bar_sync(1, 256);
            bar_arrive(6, 288);
            BSTAMP(1);
#pragma unroll 1
            for (int j = 0; j < 8; j++) {
                bg_mainloop<9, 2>(d, a, sb, j * 18 + wg, lane);
                bg_epilogue<true>(d, sb, wg, w, lane, &tm_out, 64 * nt, (2 * j + kq - 2) * 128, xa, Dk);
            }
        }
        if (w == 0) asm volatile("cp.async.bulk.wait_group 0;" ::: "memory");
        bar_sync(1, 256);
        BSTAMP(2);
        if (warp == 0)
            asm volatile("{\n.reg .pred p;\nelect.sync _|p, 0xffffffff;\n@p mbarrier.arrive.expect_tx.shared::cta.b64 _, [%2], 131072;\n"
                "@p cp.async.bulk.tensor.2d.shared::cluster.global.mbarrier::complete_tx::bytes [%0], [%1, {%3, %4}], [%2];\n"
                "@p cp.async.bulk.tensor.2d.shared::cluster.global.mbarrier::complete_tx::bytes [%0+32768], [%1, {%3, %5}], [%2];\n"
                "@p cp.async.bulk.tensor.2d.shared::cluster.global.mbarrier::complete_tx::bytes [%0+65536], [%1, {%3, %6}], [%2];\n"
                "@p cp.async.bulk.tensor.2d.shared::cluster.global.mbarrier::complete_tx::bytes [%0+98304], [%1, {%3, %7}], [%2];\n}"
                :: "r"(sb), "l"(&tm_wo), "r"(sb + GB_W), "r"(64 * nt), "r"(1024 * kq), "r"(1024 * kq + 256), "r"(1024 * kq + 512), "r"(1024 * kq + 768) : "memory");
        mbar_wait(sb + GB_W, 1);
        {
            const uint32_t base = sb + wg * 65536 + 4 * t * 128 + (g & 3) * 4, ch = 2 * w + (g >> 2), r7 = (4 * t) & 7;
#pragma unroll
            for (int ks = 0; ks < 32; ks++) {
                const uint32_t w0 = lds32(base + ks * 2048 + ((ch ^ r7) << 4)), w1 = lds32(base + ks * 2048 + 256 + ((ch ^ (r7 + 2)) << 4));
                const uint32_t w2 = lds32(base + ks * 2048 + 128 + ((ch ^ (r7 + 1)) << 4)), w3 = lds32(base + ks * 2048 + 384 + ((ch ^ (r7 + 3)) << 4));
                a[4 * ks] = __byte_perm(w0, w1, 0x5410); a[4 * ks + 1] = __byte_perm(w0, w1, 0x7632);
                a[4 * ks + 2] = __byte_perm(w2, w3, 0x5410); a[4 * ks + 3] = __byte_perm(w2, w3, 0x7632);
            }
        }
        bar_sync(1, 256);
        bar_arrive(6, 288);
        BSTAMP(3);
#pragma unroll 1
        for (int na = 0, ng = 0, it = 144; ng < 16;) {
            if (bg_att_turn(na, ng)) {
                if (nt < 8) {
                    const int i0 = it + wg + 4 * (w >> 1), i1 = i0 + 2;
                    mbar_wait(sb + GB_FULL + 8 * (i0 % NST), (i0 / NST) & 1);
                    mbar_wait(sb + GB_FULL + 8 * (i1 % NST), (i1 / NST) & 1);
                    BSTAMP(8 + na * 4);
                    bg_attention(sb + G_RING + (i0 % NST) * 16384, sb + G_RING + (i1 % NST) * 16384, w & 1, lane);
                    fence_async_smem();
                    bar_arrive(7, 288);
                    bar_sync(1, 256);
                    BSTAMP(9 + na * 4);
                    it += 8;
                }
                na++;
            } else {
                bg_mainloop<8, 2>(d, a, sb, it + wg, lane);
                BSTAMP(10 + ng * 4);
                bg_epilogue<false>(d, sb, wg, w, lane, &tm_out, DM + 64 * nt, ng * 128, xa, Dk);
                BSTAMP(11 + ng * 4);
                it += 16; ng++;
            }
        }
    }
    asm volatile("griddepcontrol.wait;" ::: "memory");
}

typedef CUresult (*EncodeFn)(CUtensorMap*, CUtensorMapDataType, cuuint32_t, void*, const cuuint64_t*, const cuuint64_t*, const cuuint32_t*, const cuuint32_t*,
                             CUtensorMapInterleave, CUtensorMapSwizzle, CUtensorMapL2promotion, CUtensorMapFloatOOBfill);
}

extern "C" void kernel_launch(void* const* d_in, const int* in_sizes, int n_in, void* d_out, int out_size) {
    typedef const __nv_bfloat16* bp;
    bp Ax = (bp)d_in[0], Lre = (bp)d_in[1], Lim = (bp)d_in[2], Bre = (bp)d_in[3], Bim = (bp)d_in[4], Cre = (bp)d_in[5], Cim = (bp)d_in[6],
       logdt = (bp)d_in[7], Dk = (bp)d_in[8], Bx = (bp)d_in[9], mem0 = (bp)d_in[10], Wq = (bp)d_in[11], Wk = (bp)d_in[12], Wv = (bp)d_in[13], Wo = (bp)d_in[14];
    float* out = (float*)d_out;
    static EncodeFn enc = nullptr;
    if (!enc) {
        void* fn = nullptr; cudaDriverEntryPointQueryResult qr;
        cudaGetDriverEntryPoint("cuTensorMapEncodeTiled", &fn, cudaEnableDefault, &qr);
        enc = (EncodeFn)fn;
        cudaFuncSetAttribute(chain_kernel, cudaFuncAttributeMaxDynamicSharedMemorySize, CHAIN_SMEM);
        cudaFuncSetAttribute(bg_kernel, cudaFuncAttributeMaxDynamicSharedMemorySize, BG_SMEM);
    }
    const cuuint32_t es[5] = {1, 1, 1, 1, 1};
    auto map2d = [&](CUtensorMap* tm, CUtensorMapDataType dt, const void* p, cuuint64_t d0, cuuint64_t d1, cuuint64_t stride, cuuint32_t b0, cuuint32_t b1) {
        cuuint64_t gd[2] = {d0, d1}, gs[1] = {stride}; cuuint32_t bd[2] = {b0, b1};
        enc(tm, dt, 2, (void*)p, gd, gs, bd, es, CU_TENSOR_MAP_INTERLEAVE_NONE, CU_TENSOR_MAP_SWIZZLE_128B, CU_TENSOR_MAP_L2_PROMOTION_L2_128B,
            CU_TENSOR_MAP_FLOAT_OOB_FILL_NONE);
    };
    CUtensorMap tm_x, tm_q, tm_k, tm_v, tm_xa, tm_wo, tm_out;
    map2d(&tm_x, CU_TENSOR_MAP_DATA_TYPE_BFLOAT16, Bx, DM, SEQ, DM * 2, 64, 32);
    map2d(&tm_q, CU_TENSOR_MAP_DATA_TYPE_BFLOAT16, Wq, HD, DM, HD * 2, 64, 192);
    map2d(&tm_k, CU_TENSOR_MAP_DATA_TYPE_BFLOAT16, Wk, HD, DM, HD * 2, 64, 192);
    map2d(&tm_v, CU_TENSOR_MAP_DATA_TYPE_BFLOAT16, Wv, HD, DM, HD * 2, 64, 192);
    map2d(&tm_wo, CU_TENSOR_MAP_DATA_TYPE_BFLOAT16, Wo, DM, HD, DM * 2, 64, 256);
    map2d(&tm_out, CU_TENSOR_MAP_DATA_TYPE_FLOAT32, out, 2 * DM, SEQ, 2 * DM * 4, 32, 64);
    {
        cuuint64_t gd[5] = {DM, 2, 4, 16, 16}, gs[4] = {DM * 2, 32 * DM * 2, 2 * DM * 2, 128 * DM * 2}; cuuint32_t bd[5] = {64, 2, 4, 16, 1};
        enc(&tm_xa, CU_TENSOR_MAP_DATA_TYPE_BFLOAT16, 5, (void*)Ax, gd, gs, bd, es, CU_TENSOR_MAP_INTERLEAVE_NONE, CU_TENSOR_MAP_SWIZZLE_128B,
            CU_TENSOR_MAP_L2_PROMOTION_L2_128B, CU_TENSOR_MAP_FLOAT_OOB_FILL_NONE);
    }
    cudaStream_t st = cudaStreamPerThread;
    chain_kernel<<<96, 384, CHAIN_SMEM, st>>>(tm_x, tm_q, tm_k, tm_v, Bx, mem0, Wo);
    cudaLaunchConfig_t cfg = {};
    cfg.gridDim = dim3(36); cfg.blockDim = dim3(384); cfg.dynamicSmemBytes = BG_SMEM; cfg.stream = st;
    cudaLaunchAttribute at[1];
    at[0].id = cudaLaunchAttributeProgrammaticStreamSerialization; at[0].val.programmaticStreamSerializationAllowed = 1;
    cfg.attrs = at; cfg.numAttrs = 1;
    cudaLaunchKernelEx(&cfg, bg_kernel, tm_xa, tm_wo, tm_out, Ax, Lre, Lim, Bre, Bim, Cre, Cim, logdt, Dk);
}
```

```cpp
#include <cuda_runtime.h>
#include <cuda.h>
#include <cuda_bf16.h>
#include <cuda_fp16.h>
#include <stdint.h>

#define D_WAIT 720

#define BG_PACE 0
#define RED_GAP 720
#define ACC_PF 1
#define QDEP 0
#define PUB_MASK 0x1111010101011000ull
#define EARLY5 0
#define BG_AHEAD 5

namespace {

constexpr int DM = 576, NH = 32, SEQ = 2048, NSEG = 64, HD = 4096;

__device__ uint4 g_acc_raw[64 * 96 * 16 + 131072];
__device__ uint4 g_ox[NH * 2 * SEQ * 8];
constexpr int REC = 30720;
__device__ uint4 g_qkv[NSEG * NH * (REC / 16)];
__device__ uint4 g_h[18 * SEQ * 8];
constexpr int NFLAG = 4096, F_QKV = 0, F_OX = 512, F_H = 1024, F_OUT = 2048;
__device__ unsigned g_flag[NFLAG];
__device__ unsigned g_ticket, g_ticket_bg;
__device__ unsigned long long g_norm[96];
#define BSTAMP(i) do {} while (0)

__device__ __forceinline__ uint32_t smem_u32(const void* p) { return (uint32_t)__cvta_generic_to_shared(p); }
__device__ __forceinline__ uint32_t mapa(uint32_t a, uint32_t r) { uint32_t o; asm("mapa.shared::cluster.u32 %0, %1, %2;" : "=r"(o) : "r"(a), "r"(r)); return o; }
__device__ __forceinline__ uint32_t mapa_v(uint32_t a, uint32_t r) { uint32_t o; asm volatile("mapa.shared::cluster.u32 %0, %1, %2;" : "=r"(o) : "r"(a), "r"(r)); return o; }
__device__ __forceinline__ unsigned clk() { unsigned long long c; asm volatile("mov.u64 %0, %%clock64;" : "=l"(c) :: "memory"); return (unsigned)c; }
__device__ __forceinline__ void mbar_init(uint32_t bar, uint32_t cnt) { asm volatile("mbarrier.init.shared::cta.b64 [%0], %1;" :: "r"(bar), "r"(cnt) : "memory"); }
__device__ __forceinline__ void mbar_expect(uint32_t bar, uint32_t bytes) { asm volatile("mbarrier.arrive.expect_tx.shared::cta.b64 _, [%0], %1;" :: "r"(bar), "r"(bytes) : "memory"); }
__device__ __forceinline__ void mbar_wait(uint32_t bar, uint32_t parity) {
    asm volatile("{\n.reg .pred p;\n.reg .u32 n;\nmov.u32 n, 0;\n"
                 "W_%=: mbarrier.try_wait.parity.shared::cta.b64 p, [%0], %1;\n@p bra.uni D_%=;\n"
                 "add.u32 n, n, 1;\nsetp.lt.u32 p, n, 4000000;\n@p bra.uni W_%=;\ntrap;\nD_%=:\n}" :: "r"(bar), "r"(parity) : "memory");
}
__device__ __forceinline__ void mbar_expect_if(uint32_t z, uint32_t bar, uint32_t bytes) {
    asm volatile("{\n.reg .pred p;\nsetp.eq.u32 p, %2, 0;\n@p mbarrier.arrive.expect_tx.shared::cta.b64 _, [%0], %1;\n}" :: "r"(bar), "r"(bytes), "r"(z) : "memory");
}
__device__ __forceinline__ void mbar_arrive_if(uint32_t z, uint32_t bar) {
    asm volatile("{\n.reg .pred p;\nsetp.eq.u32 p, %1, 0;\n@p mbarrier.arrive.shared::cta.b64 _, [%0];\n}" :: "r"(bar), "r"(z) : "memory");
}
__device__ __forceinline__ void sts32_if(uint32_t z, uint32_t a, uint32_t x) {
    asm volatile("{\n.reg .pred p;\nsetp.eq.u32 p, %2, 0;\n@p st.shared.u32 [%0], %1;\n}" :: "r"(a), "r"(x), "r"(z) : "memory");
}
template <int K> __device__ __forceinline__ void sched_fence(int v) {
    asm volatile("{\n.reg .pred p;\nsetp.ne.s32 p, %0, %1;\n@p bra.uni F_%=;\ntrap;\nF_%=:\n}" :: "r"(v), "n"(1000 + K) : "memory");
}
__device__ __forceinline__ void spin_until(unsigned t0, unsigned d) {
    asm volatile("{\n.reg .pred p;\n.reg .u64 c;\n.reg .u32 lo;\n"
                 "S_%=: mov.u64 c, %%clock64;\ncvt.u32.u64 lo, c;\nsub.u32 lo, lo, %0;\nsetp.lt.u32 p, lo, %1;\n@p bra.uni S_%=;\n}" :: "r"(t0), "r"(d) : "memory");
}
__device__ __forceinline__ void bar_sync(int id, int n) { asm volatile("bar.sync %0, %1;" :: "r"(id), "r"(n) : "memory"); }
__device__ __forceinline__ void bar_sync_sel(int sel, int id) {
    asm volatile("{\n.reg .pred p;\nsetp.eq.u32 p, %0, 0;\n@p bar.sync %1, %3;\n@!p bar.sync %2, %3;\n}" :: "r"(sel), "r"(id), "r"(id + 1), "n"(192) : "memory");
}
__device__ __forceinline__ void bar_arrive(int id, int n) { asm volatile("bar.arrive %0, %1;" :: "r"(id), "r"(n) : "memory"); }
__device__ __forceinline__ void fence_async_smem() { asm volatile("fence.proxy.async.shared::cta;" ::: "memory"); }
__device__ __forceinline__ uint32_t pack_bf16(float lo, float hi) { uint32_t r; asm("cvt.rn.bf16x2.f32 %0, %1, %2;" : "=r"(r) : "f"(hi), "f"(lo)); return r; }
__device__ __forceinline__ uint32_t pack_f16(float lo, float hi) { uint32_t r; asm("cvt.rn.f16x2.f32 %0, %1, %2;" : "=r"(r) : "f"(hi), "f"(lo)); return r; }
__device__ __forceinline__ uint32_t f16x2_to_bf16x2(uint32_t v) { float2 f = __half22float2(*reinterpret_cast<__half2*>(&v)); return pack_bf16(f.x, f.y); }
__device__ __forceinline__ uint32_t hmul2(uint32_t a, uint32_t b) { uint32_t r; asm("mul.rn.f16x2 %0, %1, %2;" : "=r"(r) : "r"(a), "r"(b)); return r; }
__device__ __forceinline__ float ex2(float x) { float y; asm("ex2.approx.ftz.f32 %0, %1;" : "=f"(y) : "f"(x)); return y; }
__device__ __forceinline__ float ex2v(float x) { float y; asm volatile("ex2.approx.ftz.f32 %0, %1;" : "=f"(y) : "f"(x)); return y; }
__device__ __forceinline__ uint32_t absmax2(uint32_t a, uint32_t b) {
    uint32_t r; asm("max.xorsign.abs.bf16x2 %0, %1, %2;" : "=r"(r) : "r"(a), "r"(b)); return r;
}
__device__ __forceinline__ uint32_t shl_v(uint32_t a, int n) { return a << n; }
__device__ __forceinline__ uint32_t max3u(uint32_t a, uint32_t b, uint32_t c) { return max(max(a, b), c); }
__device__ __forceinline__ uint4 lds128(uint32_t a) { uint4 v; asm volatile("ld.shared.v4.u32 {%0,%1,%2,%3}, [%4];" : "=r"(v.x), "=r"(v.y), "=r"(v.z), "=r"(v.w) : "r"(a) : "memory"); return v; }
__device__ __forceinline__ uint4 lds128v(uint32_t a) { uint4 v; asm volatile("ld.volatile.shared.v4.u32 {%0,%1,%2,%3}, [%4];" : "=r"(v.x), "=r"(v.y), "=r"(v.z), "=r"(v.w) : "r"(a) : "memory"); return v; }
__device__ __forceinline__ float4 lds128f(uint32_t a) { float4 v; asm volatile("ld.shared.v4.f32 {%0,%1,%2,%3}, [%4];" : "=f"(v.x), "=f"(v.y), "=f"(v.z), "=f"(v.w) : "r"(a) : "memory"); return v; }
__device__ __forceinline__ float2 lds64f(uint32_t a) { float2 v; asm volatile("ld.shared.v2.f32 {%0,%1}, [%2];" : "=f"(v.x), "=f"(v.y) : "r"(a) : "memory"); return v; }
__device__ __forceinline__ uint4 lds64x2(uint32_t a) { uint4 v; asm volatile("ld.shared.v2.u32 {%0,%1}, [%4];\nld.shared.v2.u32 {%2,%3}, [%4+256];" : "=r"(v.x), "=r"(v.y), "=r"(v.z), "=r"(v.w) : "r"(a) : "memory"); return v; }
__device__ __forceinline__ uint32_t lds32(uint32_t a) { uint32_t v; asm volatile("ld.shared.u32 %0, [%1];" : "=r"(v) : "r"(a) : "memory"); return v; }
__device__ __forceinline__ void sts128(uint32_t a, uint32_t x, uint32_t y, uint32_t z, uint32_t w) { asm volatile("st.shared.v4.u32 [%0], {%1,%2,%3,%4};" :: "r"(a), "r"(x), "r"(y), "r"(z), "r"(w) : "memory"); }
__device__ __forceinline__ void sts128f(uint32_t a, float x, float y, float z, float w) { asm volatile("st.shared.v4.f32 [%0], {%1,%2,%3,%4};" :: "r"(a), "f"(x), "f"(y), "f"(z), "f"(w) : "memory"); }
__device__ __forceinline__ void sts64(uint32_t a, uint32_t x, uint32_t y) { asm volatile("st.shared.v2.u32 [%0], {%1,%2};" :: "r"(a), "r"(x), "r"(y) : "memory"); }
__device__ __forceinline__ void sts32(uint32_t a, uint32_t x) { asm volatile("st.shared.u32 [%0], %1;" :: "r"(a), "r"(x) : "memory"); }
__device__ __forceinline__ uint4 ldsm4(uint32_t a) { uint4 v; asm volatile("ldmatrix.sync.aligned.m8n8.x4.shared.b16 {%0,%1,%2,%3}, [%4];" : "=r"(v.x), "=r"(v.y), "=r"(v.z), "=r"(v.w) : "r"(a) : "memory"); return v; }
__device__ __forceinline__ void stsm2t(uint32_t a, uint32_t x, uint32_t y) { asm volatile("stmatrix.sync.aligned.m8n8.x2.trans.shared.b16 [%0], {%1,%2};" :: "r"(a), "r"(x), "r"(y) : "memory"); }
__device__ __forceinline__ void stsm4t(uint32_t a, uint32_t x, uint32_t y, uint32_t z, uint32_t w) { asm volatile("stmatrix.sync.aligned.m8n8.x4.trans.shared.b16 [%0], {%1,%2,%3,%4};" :: "r"(a), "r"(x), "r"(y), "r"(z), "r"(w) : "memory"); }
__device__ __forceinline__ void st_async64(uint32_t a, uint32_t x, uint32_t y, uint32_t bar) { asm volatile("st.async.shared::cluster.mbarrier::complete_tx::bytes.v2.b32 [%0], {%1,%2}, [%3];" :: "r"(a), "r"(x), "r"(y), "r"(bar) : "memory"); }
__device__ __forceinline__ void bulk_s2c(uint32_t dst, uint32_t src, uint32_t bytes, uint32_t bar) { asm volatile("cp.async.bulk.shared::cluster.shared::cta.mbarrier::complete_tx::bytes [%0], [%1], %2, [%3];" :: "r"(dst), "r"(src), "r"(bytes), "r"(bar) : "memory"); }
__device__ __forceinline__ void bulk_s2g(void* dst, uint32_t src, uint32_t bytes) { asm volatile("cp.async.bulk.global.shared::cta.bulk_group [%0], [%1], %2;" :: "l"(dst), "r"(src), "r"(bytes) : "memory"); }
__device__ __forceinline__ uint32_t ldg_nc32(const void* p) { uint32_t v; asm volatile("ld.global.nc.L2::128B.u32 %0, [%1];" : "=r"(v) : "l"(p)); return v; }
__device__ __forceinline__ uint4 ldg_relaxed128(const void* p) { uint4 v; asm volatile("ld.relaxed.gpu.global.v4.u32 {%0,%1,%2,%3}, [%4];" : "=r"(v.x), "=r"(v.y), "=r"(v.z), "=r"(v.w) : "l"(p) : "memory"); return v; }
__device__ __forceinline__ void mma16816(float (&d)[4], uint32_t a0, uint32_t a1, uint32_t a2, uint32_t a3, uint32_t b0, uint32_t b1) {
    asm volatile("mma.sync.aligned.m16n8k16.row.col.f32.bf16.bf16.f32 {%0,%1,%2,%3}, {%4,%5,%6,%7}, {%8,%9}, {%0,%1,%2,%3};"
        : "+f"(d[0]), "+f"(d[1]), "+f"(d[2]), "+f"(d[3]) : "r"(a0), "r"(a1), "r"(a2), "r"(a3), "r"(b0), "r"(b1));
}
__device__ __forceinline__ void mma16816_z(float (&d)[4], uint32_t a0, uint32_t a1, uint32_t a2, uint32_t a3, uint32_t b0, uint32_t b1) {
    asm volatile("mma.sync.aligned.m16n8k16.row.col.f32.bf16.bf16.f32 {%0,%1,%2,%3}, {%4,%5,%6,%7}, {%8,%9}, {%10,%10,%10,%10};"
        : "=f"(d[0]), "=f"(d[1]), "=f"(d[2]), "=f"(d[3]) : "r"(a0), "r"(a1), "r"(a2), "r"(a3), "r"(b0), "r"(b1), "f"(0.f));
}
__device__ __forceinline__ void mma1688(float (&d)[4], uint32_t a0, uint32_t a1, uint32_t b0) {
    asm volatile("mma.sync.aligned.m16n8k8.row.col.f32.bf16.bf16.f32 {%0,%1,%2,%3}, {%4,%5}, {%6}, {%0,%1,%2,%3};"
        : "+f"(d[0]), "+f"(d[1]), "+f"(d[2]), "+f"(d[3]) : "r"(a0), "r"(a1), "r"(b0));
}
__device__ __forceinline__ void mma1688_z(float (&d)[4], uint32_t a0, uint32_t a1, uint32_t b0) {
    asm volatile("mma.sync.aligned.m16n8k8.row.col.f32.bf16.bf16.f32 {%0,%1,%2,%3}, {%4,%5}, {%6}, {%7,%7,%7,%7};"
        : "=f"(d[0]), "=f"(d[1]), "=f"(d[2]), "=f"(d[3]) : "r"(a0), "r"(a1), "r"(b0), "f"(0.f));
}
template <int ACC>
__device__ __forceinline__ void wgmma_n32_rs(float (&d)[16], uint32_t a0, uint32_t a1, uint32_t a2, uint32_t a3, uint64_t desc) {
    asm volatile("wgmma.mma_async.sync.aligned.m64n32k16.f32.bf16.bf16 {%0,%1,%2,%3,%4,%5,%6,%7,%8,%9,%10,%11,%12,%13,%14,%15}, {%16,%17,%18,%19}, %20, %21, 1, 1, 0;"
        : "+f"(d[0]), "+f"(d[1]), "+f"(d[2]), "+f"(d[3]), "+f"(d[4]), "+f"(d[5]), "+f"(d[6]), "+f"(d[7]),
          "+f"(d[8]), "+f"(d[9]), "+f"(d[10]), "+f"(d[11]), "+f"(d[12]), "+f"(d[13]), "+f"(d[14]), "+f"(d[15])
        : "r"(a0), "r"(a1), "r"(a2), "r"(a3), "l"(desc), "n"(ACC));
}
template <int ACC>
__device__ __forceinline__ void wgmma_n32_ss(float (&d)[16], uint64_t da, uint64_t db) {
    asm volatile("wgmma.mma_async.sync.aligned.m64n32k16.f32.bf16.bf16 {%0,%1,%2,%3,%4,%5,%6,%7,%8,%9,%10,%11,%12,%13,%14,%15}, %16, %17, %18, 1, 1, 0, 0;"
        : "+f"(d[0]), "+f"(d[1]), "+f"(d[2]), "+f"(d[3]), "+f"(d[4]), "+f"(d[5]), "+f"(d[6]), "+f"(d[7]),
          "+f"(d[8]), "+f"(d[9]), "+f"(d[10]), "+f"(d[11]), "+f"(d[12]), "+f"(d[13]), "+f"(d[14]), "+f"(d[15])
        : "l"(da), "l"(db), "n"(ACC));
}
__device__ __forceinline__ void wg_fence() { asm volatile("wgmma.fence.sync.aligned;" ::: "memory"); }
__device__ __forceinline__ void wg_commit() { asm volatile("wgmma.commit_group.sync.aligned;" ::: "memory"); }
__device__ __forceinline__ void wg_wait0() { asm volatile("wgmma.wait_group.sync.aligned 0;" ::: "memory"); }
__device__ __forceinline__ void cluster_sync() { asm volatile("barrier.cluster.arrive.aligned;\nbarrier.cluster.wait.aligned;" ::: "memory"); }

#define STAMP(s, i) do {} while (0)
#define STAMPV(s, i, v) do {} while (0)

constexpr int XT_BYTES = 36864;
constexpr int O_XT = 0;
constexpr int O_STG = XT_BYTES;
constexpr int O_AS = 3 * XT_BYTES;
constexpr int O_XP = O_AS + 16384;
constexpr int O_QKX = O_XP + 8192;
constexpr int O_KM = O_QKX + 8192;
constexpr int O_QM = O_QKX + 10240;
constexpr int O_VX = O_STG + 147456;
constexpr int O_VM = O_VX + 24576;
constexpr int O_SC = O_VM + 2048;
constexpr int O_OF = O_SC + 2560;
constexpr int O_AF = O_OF + 2048;
constexpr int O_WP = O_AF + 4096;
constexpr int O_MF = O_WP + 2048;
constexpr int O_MISC = O_MF + 9216;
static_assert(O_QKX + 24576 <= O_VX, "smem");
constexpr int O_BAR = O_MISC + 64;
constexpr int CHAIN_SMEM = O_BAR + 128;
static_assert(CHAIN_SMEM <= 232448, "smem");
constexpr int B_X = O_BAR, B_VX = O_BAR + 24, B_SC = O_BAR + 40, B_W = O_BAR + 48, B_MX = O_BAR + 72;
constexpr float SM_SCALE = 0.08838834764831845f * 1.4426950408889634f;
constexpr uint32_t ONES = 0x3f803f80u;

__device__ __forceinline__ uint32_t opaque(uint32_t v) { uint32_t o; asm volatile("mov.u32 %0, %1;" : "=r"(o) : "r"(v)); return o; }
__device__ __forceinline__ void st_async128(uint32_t a, uint32_t x, uint32_t y, uint32_t z, uint32_t w, uint32_t bar) {
    asm volatile("st.async.shared::cluster.mbarrier::complete_tx::bytes.v4.b32 [%0], {%1,%2,%3,%4}, [%5];" :: "r"(a), "r"(x), "r"(y), "r"(z), "r"(w), "r"(bar) : "memory");
}
__device__ __forceinline__ void tma_x_tile(uint32_t sb, const CUtensorMap* tm, int r, int j, int slot) {
    asm volatile("{\n.reg .pred p;\nelect.sync _|p, 0xffffffff;\n"
        "@p mbarrier.arrive.expect_tx.shared::cta.b64 _, [%2], 36864;\n"
        "@p cp.async.bulk.tensor.2d.shared::cluster.global.mbarrier::complete_tx::bytes.multicast::cluster [%0], [%1, {%3, %4}], [%2], %7;\n"
        "@p cp.async.bulk.tensor.2d.shared::cluster.global.mbarrier::complete_tx::bytes.multicast::cluster [%0+4096], [%1, {%5, %4}], [%2], %7;\n"
        "@p cp.async.bulk.tensor.2d.shared::cluster.global.mbarrier::complete_tx::bytes.multicast::cluster [%0+8192], [%1, {%6, %4}], [%2], %7;\n}"
        :: "r"(sb + O_XT + slot * XT_BYTES + 3 * r * 4096), "l"(tm), "r"(sb + B_X + 8 * slot), "r"(192 * r), "r"(j * 32), "r"(192 * r + 64), "r"(192 * r + 128),
           "h"((unsigned short)7) : "memory");
}
__device__ __forceinline__ void flag_inc_if(uint32_t z, unsigned* p) {
    asm volatile("{\n.reg .pred p;\nsetp.eq.u32 p, %1, 0;\n@p red.release.gpu.global.inc.u32 [%0], 0xfffffffe;\n}" :: "l"(p), "r"(z) : "memory");
}
__device__ __forceinline__ void v_store(uint32_t sb, int h, int j, int slot) {
    asm volatile("{\n.reg .pred p;\nelect.sync _|p, 0xffffffff;\n@p cp.async.bulk.global.shared::cta.bulk_group [%0], [%1], 8192;\n@p cp.async.bulk.commit_group;\n}"
        :: "l"(reinterpret_cast<char*>(g_qkv) + (size_t)(j * NH + h) * REC + 20480), "r"(sb + O_VX + slot * 8192) : "memory");
}
__device__ __forceinline__ void v_multicast(uint32_t sb, int h, int j) {
    asm volatile("{\n.reg .pred p;\ncp.async.bulk.wait_group 0;\nelect.sync _|p, 0xffffffff;\nsetp.lt.and.s32 p, %4, 63, p;\n"
        "@p cp.async.bulk.shared::cluster.global.mbarrier::complete_tx::bytes.multicast::cluster [%1], [%0], 8192, [%2], %3;\nfence.proxy.async.global;\n}"
        :: "l"(reinterpret_cast<char*>(g_qkv) + (size_t)(j * NH + h) * REC + 20480), "r"(sb + O_VX + (j & 1) * 8192), "r"(sb + B_VX + 8 * (j & 1)),
           "h"((unsigned short)3), "r"(j) : "memory");
}
__device__ __forceinline__ float quad_max(float v) {
    const float a = __shfl_xor_sync(~0u, v, 1), b = __shfl_xor_sync(~0u, v, 2), c = __shfl_xor_sync(~0u, v, 3);
    return fmaxf(fmaxf(v, a), fmaxf(b, c));
}
__device__ __forceinline__ void load_scores(float (&p)[10], uint32_t base, uint32_t stride, uint32_t l16) {
    const float4 a0 = lds128f(base + l16), b0 = lds128f(base + stride + l16);
    const float4 a1 = lds128f(base + 512 + l16), b1 = lds128f(base + stride + 512 + l16);
    const float2 a2 = lds64f(base + 1024 + (l16 >> 1)), b2 = lds64f(base + stride + 1024 + (l16 >> 1));
    p[0] = a2.x + b2.x; p[1] = a2.y + b2.y;
    p[2] = a0.x + b0.x; p[3] = a0.y + b0.y; p[4] = a0.z + b0.z; p[5] = a0.w + b0.w;
    p[6] = a1.x + b1.x; p[7] = a1.y + b1.y; p[8] = a1.z + b1.z; p[9] = a1.w + b1.w;
}
__device__ __forceinline__ float rcp_fast(float x) { float y; asm("rcp.approx.ftz.f32 %0, %1;" : "=f"(y) : "f"(x)); return y; }

__global__ void __cluster_dims__(3, 1, 1) __launch_bounds__(384, 1)
chain_kernel(const __grid_constant__ CUtensorMap tm_x, const __grid_constant__ CUtensorMap tm_q,
             const __grid_constant__ CUtensorMap tm_k, const __grid_constant__ CUtensorMap tm_v,
             const __nv_bfloat16* __restrict__ x, const __nv_bfloat16* __restrict__ mem0,
             const __nv_bfloat16* __restrict__ Wo) {
    extern __shared__ __align__(1024) uint8_t smem_raw[];
    const uint32_t sb = smem_u32(smem_raw);
    const int lane = threadIdx.x & 31;
    const int warp = __shfl_sync(~0u, threadIdx.x >> 5, 0);
    const int wg = warp >> 2, w = warp & 3;
    const int h = blockIdx.x / 3, r = blockIdx.x - 3 * h;
    uint4* const g_acc = reinterpret_cast<uint4*>((reinterpret_cast<uintptr_t>(g_acc_raw) + 0x1fffff) & ~(uintptr_t)0x1fffff);

#define PSTAMP(i) do {} while (0)
    if (threadIdx.x == 0) {
        if (sb & 1023u) __trap();
        for (int i = 0; i < 9; i++) mbar_init(sb + O_BAR + 8 * i, 1);
        mbar_init(sb + B_MX, 4);
        asm volatile("fence.mbarrier_init.release.cluster;" ::: "memory");
        for (int i = 0; i < 3; i++) {
            mbar_expect(sb + B_W + 8 * i, 49152);
            for (int tl = 0; tl < 2; tl++)
                asm volatile("cp.async.bulk.tensor.2d.shared::cluster.global.mbarrier::complete_tx::bytes [%0], [%1, {%3, %4}], [%2];"
                    :: "r"(sb + O_STG + tl * 73728 + i * 24576), "l"(r < 2 ? (tl ? &tm_k : &tm_q) : &tm_v), "r"(sb + B_W + 8 * i),
                       "r"(h * 128 + 64 * (r < 2 ? r : tl)), "r"(192 * i) : "memory");
        }
    }
    __syncwarp();
    asm volatile("barrier.cluster.arrive.relaxed.aligned;" ::: "memory");
    asm volatile("griddepcontrol.launch_dependents;" ::: "memory");
    if (warp == 0) PSTAMP(9);
    const uint32_t l16c = __shfl_sync(~0u, lane * 16, lane);

    if (wg < 2) {
#define KS(u) ((u) < 8 ? 12 * ((u) >> 2) + (((u) >> 1) & 1) + 4 * ((u) & 1) : (u) < 12 ? (u) : (u) < 16 ? (u) + 8 : (u) < 24 ? 24 + (((u) - 16) >> 1) + 4 * ((u) & 1) : (u) + 8)
        asm volatile("setmaxnreg.inc.sync.aligned.u32 184;");
        uint32_t a[144];
        uint32_t adr1;
        {
            const int g = lane >> 2, t = lane & 3;
            const int t1 = threadIdx.x;
#pragma unroll
            for (int i = 0; i < 2; i++) g_acc[(blockIdx.x * 64 + i * 32 + (t1 >> 3)) * 16 + (t1 & 7)] = make_uint4(0, 0, 0, 0);
            __threadfence();
            asm volatile("barrier.cluster.wait.aligned;" ::: "memory");
            const uint32_t ev = sb + O_STG + (2 * t) * 128 + (((2 * w + (g >> 2)) ^ (2 * t)) << 4) + (g & 3) * 4;
            const uint32_t od = (ev ^ 16) + 128;
            auto gather = [&](int dst, uint32_t off) {
                a[dst] = lds32(ev + off); a[dst + 1] = lds32(od + off); a[dst + 2] = lds32(ev + off + 1024); a[dst + 3] = lds32(od + off + 1024);
            };
            const uint4* xp = reinterpret_cast<const uint4*>(x) + blockIdx.x * 1536 + t1;
            uint4 xv[6];
#pragma unroll
            for (int th = 0; th < 2; th++) {
                mbar_wait(sb + B_W + 8 * th, 0);
                if (th == 1) {
#pragma unroll
                    for (int i = 0; i < 6; i++) xv[i] = __ldg(xp + i * 256);
                }
#pragma unroll
                for (int u = 4 * th; u < 4 * th + 4; u++) {
                    gather(32 + 4 * u, wg * (73728 + 4096) + KS(u) * 2048);
                    gather(4 * u, 73728 - wg * (73728 - 4096) + KS(u) * 2048);
                    gather(64 + 4 * u, wg * 73728 + KS(8 + u) * 2048);
                }
            }
            mbar_wait(sb + B_W + 16, 0);
#pragma unroll
            for (int u = 16; u < 28; u++) gather(32 + 4 * u, wg * 73728 + KS(u) * 2048);
#pragma unroll
            for (int kk = 0; kk < 72; kk++) {
                uint32_t w0 = a[2 * kk], w1 = a[2 * kk + 1];
                a[2 * kk] = __byte_perm(w0, w1, 0x5410);
                a[2 * kk + 1] = __byte_perm(w0, w1, 0x7632);
            }
            if (r == 2) {
                float n0[4], n1[4];
#pragma unroll
                for (int u = 0; u < 36; u++) {
                    const uint32_t x0 = a[4 * u] & 0x7fff7fffu, x1 = a[4 * u + 1] & 0x7fff7fffu, x2 = a[4 * u + 2] & 0x7fff7fffu, x3 = a[4 * u + 3] & 0x7fff7fffu;
                    if (u == 0) mma16816_z(n0, x0, x1, x2, x3, ONES, ONES);
                    else if (u < 8) mma16816(n0, x0, x1, x2, x3, ONES, ONES);
                    else if (u == 8) mma16816_z(n1, x0, x1, x2, x3, ONES, ONES);
                    else mma16816(n1, x0, x1, x2, x3, ONES, ONES);
                }
                const uint32_t mx = __reduce_max_sync(~0u, __float_as_uint(2.f * fmaxf(fmaxf(n0[0], n0[2]), fmaxf(n1[0], n1[2]))));
                sts32_if(lane, sb + O_MISC + 32 + 4 * warp, mx);
            }
            uint32_t xm = 0;
#pragma unroll
            for (int i = 0; i < 6; i++)
                xm = __vmaxu2(xm, __vmaxu2(__vmaxu2(xv[i].x & 0x7fff7fffu, xv[i].y & 0x7fff7fffu), __vmaxu2(xv[i].z & 0x7fff7fffu, xv[i].w & 0x7fff7fffu)));
            sts32_if(lane, sb + O_OF + 16 + 4 * warp, __reduce_max_sync(~0u, max(xm << 16, xm & 0xffff0000u)));
            if (warp == 0) PSTAMP(11);
            bar_arrive(7, 384);
            asm volatile("barrier.cluster.arrive.relaxed.aligned;" ::: "memory");
            bar_sync(1, 256);
            const uint32_t as = sb + O_AS + wg * 8192 + (16 * w + g) * 128 + t * 4;
            sts32(as + (g << 4), a[32]);
            sts32(as + 1024 + (g << 4), a[33]);
            sts32(as + ((1 ^ g) << 4), a[34]);
            sts32(as + 1024 + ((1 ^ g) << 4), a[35]);
            sts128(sb + O_AF + warp * 512 + lane * 16, a[32], a[33], a[34], a[35]);
            fence_async_smem();
            bar_sync(1, 256);
            const uint32_t l = lane * 16;
            const int mi = lane >> 3, isk = (mi >> 1) ? wg : (wg ^ 1);
            adr1 = (r == 2) ? (sb + O_VM + warp * 256 + (l >> 1))
                            : (isk ? (sb + O_KM + w * 512 + wg * 256 + (mi & 1) * 128 + (l & 127))
                                   : (sb + O_QM + w * 512 + (mi & 1) * 256 + wg * 128 + (l & 127)));
            adr1 = __shfl_sync(~0u, adr1, lane);
        }
        const int ahead = r >> 1;
        int s3 = 2;
#pragma unroll 1
        for (int s = -1 - ahead; s < NSEG; s++) {
            const uint32_t l16 = opaque(l16c);
            const int j = s + 1 + ahead;
            s3 = (s3 == 2) ? 0 : s3 + 1;
            if (s < 0) mbar_wait(sb + B_X + 8 * s3, 0);
            const uint64_t desc0 = (uint64_t)(((sb + O_XT + s3 * XT_BYTES) & 0x3FFFF) >> 4) | (1ull << 16) | (64ull << 32) | (1ull << 62);
            uint32_t km0 = 0, km1 = 0;
            if (s >= 0) {
                { const uint4 v = lds128(sb + O_AF + warp * 512 + l16); a[32] = v.x; a[33] = v.y; a[34] = v.z; a[35] = v.w; }
                float co[4], cw[3][4];
                uint4 b[14];
                float inv;
#define GORD(i) ((i) < 8 ? 2 * ((i) >> 2) + (((i) >> 1) & 1) + 4 * ((i) & 1) : (i))
                auto qkv_mma = [&](int i) {
                    const int gi = GORD(i), u = 8 * gi, n0 = 2 * i, n1 = 2 * i + 1;
                    if (gi < 4) {
                        if (i == 0) mma16816_z(co, a[u], a[u + 1], a[u + 2], a[u + 3], b[0].x, b[0].y);
                        else mma16816(co, a[u], a[u + 1], a[u + 2], a[u + 3], b[i].x, b[i].y);
                    }
                    if (n0 < 3) mma16816_z(cw[n0 % 3], a[32 + u], a[32 + u + 1], a[32 + u + 2], a[32 + u + 3], b[i].x, b[i].y);
                    else mma16816(cw[n0 % 3], a[32 + u], a[32 + u + 1], a[32 + u + 2], a[32 + u + 3], b[i].x, b[i].y);
                    if (n1 < 3) mma16816_z(cw[n1 % 3], a[32 + u + 4], a[32 + u + 5], a[32 + u + 6], a[32 + u + 7], b[i].z, b[i].w);
                    else mma16816(cw[n1 % 3], a[32 + u + 4], a[32 + u + 5], a[32 + u + 6], a[32 + u + 7], b[i].z, b[i].w);
                    if (gi < 4) mma16816(co, a[u + 4], a[u + 5], a[u + 6], a[u + 7], b[i].z, b[i].w);
                };
                const uint32_t mf = sb + O_MF + l16, mfs = mf + wg * 1024;
                const uint32_t qb = (s & 1) * 12288;
                bar_sync(2, 384);
                if (warp == 0) STAMP(s, 0);
                auto qkv_ld = [&](int i) {
                    const int gi = GORD(i);
                    b[i] = gi < 4 ? lds128v(mfs + (gi >> 1) * 3072 + (gi & 1) * 512) : lds128v(mf + (gi < 6 ? gi : gi + 4) * 512);
                };
#pragma unroll
                for (int i = 0; i < 4; i++) qkv_ld(i);
                qkv_mma(0); qkv_mma(1); qkv_mma(2);
                const uint32_t z0 = __float_as_uint(QDEP ? co[0] : cw[1][0]) & (l16 & 15u);
                qkv_mma(3);
                bar_sync(15, 384);
                b[4] = lds128v(mfs + 3072 + z0);
#pragma unroll
                for (int i = 5; i < 9; i++) qkv_ld(i);
#pragma unroll
                for (int i = 4; i < 9; i++) { qkv_mma(i); qkv_ld(5 + i); }
                asm volatile("ld.volatile.shared.f32 %0, [%1];" : "=f"(inv) : "r"(sb + O_MISC) : "memory");
#pragma unroll
                for (int i = 9; i < 14; i++) qkv_mma(i);
#pragma unroll
                for (int i = 0; i < 4; i++) cw[0][i] += cw[1][i] + cw[2][i];
                if (r < 2) {
                    const uint32_t o0 = pack_bf16(co[0] * inv, co[1] * inv), o1 = pack_bf16(co[2] * inv, co[3] * inv);
                    const uint32_t w0 = pack_bf16(cw[0][0] * inv, cw[0][1] * inv), w1 = pack_bf16(cw[0][2] * inv, cw[0][3] * inv);
                    stsm4t(adr1 + qb, o0, o1, w0, w1);
                    if (warp == 0) STAMP(s, 1);
                    asm volatile("{\n.reg .pred p;\nsetp.ge.u32 p, %0, 3;\n@p bar.arrive 1, 256;\n}" :: "r"(warp) : "memory");
                    auto scores = [&](float (&v)[4], const uint4 (&q)[4], const uint4 (&k)[4]) {
                        float s0[4], s1[4], t0[4], t1[4];
                        mma16816_z(s0, q[0].x, q[0].y, q[0].z, q[0].w, k[0].x, k[0].y);
                        mma16816_z(s1, q[0].x, q[0].y, q[0].z, q[0].w, k[0].z, k[0].w);
                        mma16816_z(t0, q[1].x, q[1].y, q[1].z, q[1].w, k[1].x, k[1].y);
                        mma16816_z(t1, q[1].x, q[1].y, q[1].z, q[1].w, k[1].z, k[1].w);
                        mma16816(s0, q[2].x, q[2].y, q[2].z, q[2].w, k[2].x, k[2].y);
                        mma16816(s1, q[2].x, q[2].y, q[2].z, q[2].w, k[2].z, k[2].w);
                        mma16816(t0, q[3].x, q[3].y, q[3].z, q[3].w, k[3].x, k[3].y);
                        mma16816(t1, q[3].x, q[3].y, q[3].z, q[3].w, k[3].z, k[3].w);
                        v[0] = (s0[0] + s0[2]) + (t0[0] + t0[2]); v[1] = (s0[1] + s0[3]) + (t0[1] + t0[3]);
                        v[2] = (s1[0] + s1[2]) + (t1[0] + t1[2]); v[3] = (s1[1] + s1[3]) + (t1[1] + t1[3]);
                    };
                    if (warp < 2) {
                        uint4 q[4], k[4]; float v[4];
#pragma unroll
                        for (int i = 0; i < 4; i++) k[i] = ldsm4(sb + O_QKX + 4096 + qb + warp * 2048 + i * 512 + l16);
                        bar_sync(1, 256);
#pragma unroll
                        for (int i = 0; i < 4; i++) q[i] = ldsm4(sb + O_QM + qb + i * 512 + l16);
                        scores(v, q, k);
                        const uint32_t dst = sb + O_SC + r * 1280 + warp * 512 + l16;
                        st_async128(mapa(dst, 2), __float_as_uint(v[0]), __float_as_uint(v[1]), __float_as_uint(v[2]), __float_as_uint(v[3]), mapa(sb + B_SC, 2));
                        st_async128(mapa(dst, r ^ 1), __float_as_uint(v[0]), __float_as_uint(v[1]), __float_as_uint(v[2]), __float_as_uint(v[3]), mapa(sb + B_SC, r ^ 1));
                        st_async128(mapa(dst, r), __float_as_uint(v[0]), __float_as_uint(v[1]), __float_as_uint(v[2]), __float_as_uint(v[3]), mapa(sb + B_SC, r));
                    } else if (warp == 2) {
                        uint4 q[4], k[4]; float v[4];
                        bar_sync(1, 256);
#pragma unroll
                        for (int i = 0; i < 4; i++) { q[i] = ldsm4(sb + O_QM + qb + i * 512 + l16); k[i] = ldsm4(sb + O_KM + qb + i * 512 + l16); }
                        scores(v, q, k);
                        const uint32_t dst = sb + O_SC + r * 1280 + 1024 + (l16 >> 1);
                        st_async64(mapa(dst, 2), __float_as_uint(v[0] + v[2]), __float_as_uint(v[1] + v[3]), mapa(sb + B_SC, 2));
                        st_async64(mapa(dst, r ^ 1), __float_as_uint(v[0] + v[2]), __float_as_uint(v[1] + v[3]), mapa(sb + B_SC, r ^ 1));
                        st_async64(mapa(dst, r), __float_as_uint(v[0] + v[2]), __float_as_uint(v[1] + v[3]), mapa(sb + B_SC, r));
                        STAMP(s, 2);
                    } else if (warp == 3) {
                        asm volatile("cp.async.bulk.wait_group 0;\nfence.proxy.async.global;" ::: "memory");
                    }
                } else {
                    sts128f(sb + O_XP + warp * 512 + l16, co[0], co[1], co[2], co[3]);
                    bar_sync(8 + w, 64);
                    const float4 o = lds128f(sb + O_XP + (warp ^ 4) * 512 + l16);
                    km0 = pack_bf16((cw[0][0] + o.x) * inv, (cw[0][1] + o.y) * inv);
                    km1 = pack_bf16((cw[0][2] + o.z) * inv, (cw[0][3] + o.w) * inv);
                    if (warp == 0) STAMP(s, 1);
                    st_async64(mapa(adr1, 0), km0, km1, mapa(sb + B_SC, 0));
                    st_async64(mapa(adr1, 1), km0, km1, mapa(sb + B_SC, 1));
                    st_async64(mapa(adr1, 2), km0, km1, mapa(sb + B_SC, 2));
                    if (warp == 0) STAMP(s, 2);
                }
            }
            if (s >= 0) bar_sync(3, 384);
            auto store_qk = [&]() {
                asm volatile("{\n.reg .pred p;\nelect.sync _|p, 0xffffffff;\n"
                    "@p cp.async.bulk.global.shared::cta.bulk_group [%0], [%1], 10240;\n@p cp.async.bulk.commit_group;\n}"
                    :: "l"(reinterpret_cast<char*>(g_qkv) + (size_t)(s * NH + h) * REC + r * 10240), "r"(sb + O_QKX + (s & 1) * 12288) : "memory");
            };
            auto store_vm = [&]() {
                *reinterpret_cast<uint2*>(reinterpret_cast<char*>(g_qkv) + (size_t)(s * NH + h) * REC + 28672 + warp * 256 + (l16 >> 1)) = make_uint2(km0, km1);
            };
            if (s == NSEG - 1) {
                if (r == 2) store_vm();
                else if (warp == 3) {
                    fence_async_smem();
                    store_qk();
                    asm volatile("cp.async.bulk.wait_group 0;\nfence.proxy.async.global;" ::: "memory");
                }
            } else {
#define XDESC(u) (((u) < 8 ? descs : desc0) + (uint64_t)(((KS(u) >> 2) * 4096 + (KS(u) & 3) * 32) >> 4))
                const uint64_t descs = desc0 + (uint64_t)(wg * 4);
                float d[16];
                wg_fence();
#pragma unroll
                for (int u = 0; u < 8; u++) {
                    if (u == 0) wgmma_n32_rs<0>(d, a[0], a[1], a[2], a[3], XDESC(0));
                    else wgmma_n32_rs<1>(d, a[4 * u], a[4 * u + 1], a[4 * u + 2], a[4 * u + 3], XDESC(u));
                }
                wg_commit();
                wg_wait0();
                if (warp == 0) STAMP(s, 15);
                auto xp_put = [&]() {
#pragma unroll
                    for (int q = 0; q < 2; q++)
                        sts128(sb + O_XP + warp * 1024 + q * 512 + l16, pack_bf16(d[8 * q], d[8 * q + 1]), pack_bf16(d[8 * q + 2], d[8 * q + 3]),
                               pack_bf16(d[8 * q + 4], d[8 * q + 5]), pack_bf16(d[8 * q + 6], d[8 * q + 7]));
                };
                uint4 xo[2];
                auto xp_get = [&]() { xo[0] = lds128(sb + O_XP + (warp ^ 4) * 1024 + l16); xo[1] = lds128(sb + O_XP + (warp ^ 4) * 1024 + 512 + l16); };
                if (warp == 3) fence_async_smem();
                if (s >= 0) bar_sync(4, 384);
                if (warp == 3 && r == 2 && s >= 0) v_store(sb, h, s + 1, s3 == 0 ? 2 : s3 - 1);
                xp_put();
                bar_sync(12, 256);
                xp_get();
#pragma unroll
                for (int q = 0; q < 2; q++) {
                    d[8 * q] = __uint_as_float(xo[q].x << 16); d[8 * q + 1] = __uint_as_float(xo[q].x & 0xffff0000u);
                    d[8 * q + 2] = __uint_as_float(xo[q].y << 16); d[8 * q + 3] = __uint_as_float(xo[q].y & 0xffff0000u);
                    d[8 * q + 4] = __uint_as_float(xo[q].z << 16); d[8 * q + 5] = __uint_as_float(xo[q].z & 0xffff0000u);
                    d[8 * q + 6] = __uint_as_float(xo[q].w << 16); d[8 * q + 7] = __uint_as_float(xo[q].w & 0xffff0000u);
                }
                if (s >= 0) {
                    if (r == 2) store_vm();
                    if (warp == 5 && s + 3 < NSEG) tma_x_tile(sb, &tm_x, r, s + 3, s % 3);
                    if (warp == 7 && ((PUB_MASK >> s) & 1)) {
                        flag_inc_if(l16, &g_flag[F_QKV + (s - 4 + (h >> 3)) * 8]);
                        for (int sb4 = s - 4; sb4 > 0 && !((PUB_MASK >> sb4) & 1); sb4 -= 4)
                            asm volatile("{\n.reg .pred p;\nsetp.eq.u32 p, %1, 0;\n@p red.relaxed.gpu.global.inc.u32 [%0], 0xfffffffe;\n}"
                                         :: "l"(&g_flag[F_QKV + (sb4 - 4 + (h >> 3)) * 8]), "r"(l16) : "memory");
                    }
                    asm volatile("{\n.reg .pred p;\nsetp.eq.u32 p, %0, 0;\n@p bar.sync 5, 256;\n@!p bar.sync 13, 256;\n}" :: "r"(wg) : "memory");
                }
                const uint64_t da0 = (uint64_t)(((sb + O_AS + wg * 8192) & 0x3FFFF) >> 4) | (1ull << 16) | (64ull << 32) | (1ull << 62);
                wg_fence();
                wgmma_n32_ss<1>(d, da0, XDESC(0));
#pragma unroll
                for (int u = 1; u < 28; u++) wgmma_n32_rs<1>(d, a[32 + 4 * u], a[32 + 4 * u + 1], a[32 + 4 * u + 2], a[32 + 4 * u + 3], XDESC(u));
                wg_commit();
                if (warp == 3 && r == 2 && s >= 0) v_multicast(sb, h, s + 1);
                wg_wait0();
                if (warp == 3 && r < 2 && s >= 0) store_qk();
                if (warp == 4) STAMP(s, 3);
                uint32_t e[8];
#pragma unroll
                for (int i = 0; i < 8; i++) e[i] = pack_bf16(d[2 * i], d[2 * i + 1]);
                if (r < 2) {
                    const uint32_t base = sb + O_QKX + (j & 1) * 12288 + wg * 4096 + w * 512 + l16;
                    stsm4t(base, e[0], wg ? e[1] : e[2], wg ? e[2] : e[1], e[3]);
                    stsm4t(base + 2048, e[4], wg ? e[5] : e[6], wg ? e[6] : e[5], e[7]);
                } else {
                    const uint32_t base = sb + O_VX + s3 * 8192 + warp * 1024 + l16;
                    sts128(base, e[0], e[1], e[2], e[3]);
                    sts128(base + 512, e[4], e[5], e[6], e[7]);
                    if (j == 0) bar_arrive(0, 288);
                }
                if (warp == 7) STAMP(s, 4);
                if (j == 0) asm volatile("barrier.cluster.wait.aligned;" ::: "memory");
                if (s < -1) bar_sync(1, 256);
            }
        }
        bar_arrive(7, 384);
    } else {
        asm volatile("setmaxnreg.dec.sync.aligned.u32 136;");
        const int c = w;
        uint32_t a[96];
        uint32_t mmax = 0;
        {
            const int g = lane >> 2, t = lane & 3;
            uint32_t tag = 0, m0v[18];
            if (threadIdx.x == 256) tag = atomicAdd(&g_ticket, 1u);
#pragma unroll
            for (int i = 0; i < 9; i++) {
                const uint32_t* p = reinterpret_cast<const uint32_t*>(mem0 + g * DM + 16 * (4 * i + c) + 2 * t);
                m0v[2 * i] = __ldg(p); m0v[2 * i + 1] = __ldg(p + 4);
            }
            asm volatile("barrier.cluster.wait.aligned;" ::: "memory");
            if (c == 0) {
                tma_x_tile(sb, &tm_x, r, 0, 0);
                mbar_expect_if(lane, sb + B_SC, 4608);
                if (r < 2) mbar_expect_if(lane, sb + B_VX, 8192);
                sts32_if(lane, sb + O_MISC, __float_as_uint(1.0f));
                sts32_if(lane, sb + O_MISC + 12, __float_as_uint(SM_SCALE));
            }
            asm volatile("barrier.cluster.arrive.relaxed.aligned;" ::: "memory");
#pragma unroll
            for (int tau = 0; tau < 3; tau++) {
                const uint32_t* v = m0v + 6 * tau;
                sts128(sb + O_MF + tau * 3072 + c * 512 + lane * 16, v[0], v[1], v[2], v[3]);
                sts64(sb + O_MF + tau * 3072 + 2048 + (c >> 1) * 512 + lane * 16 + (c & 1) * 8, v[4], v[5]);
#pragma unroll
                for (int i = 0; i < 6; i++) mmax = __vmaxu2(mmax, v[i] & 0x7fff7fffu);
            }
            mmax = max(mmax << 16, mmax & 0xffff0000u);
            bar_arrive(2, 384); bar_arrive(15, 384);
            tag = (__shfl_sync(~0u, tag, 0) / 96u + 1u) & 0xffffu;
            mbar_wait(sb + B_W + 0, 0);
            const __nv_bfloat16* p = Wo + (size_t)(h * 128 + 4 * t) * DM + 192 * r + 16 * c + 2 * g;
#pragma unroll
            for (int i = 0; i < 3; i++)
#pragma unroll
                for (int eb = 0; eb < 8; eb++)
#pragma unroll
                    for (int j = 0; j < 4; j++) a[(i * 8 + eb) * 4 + j] = ldg_nc32(p + (16 * eb + ((j & 1) * 2 + (j >> 1))) * DM + 64 * i);
#pragma unroll
            for (int kk = 0; kk < 48; kk++) {
                uint32_t w0 = a[2 * kk], w1 = a[2 * kk + 1];
                a[2 * kk] = __byte_perm(w0, w1, 0x5410);
                a[2 * kk + 1] = __byte_perm(w0, w1, 0x7632);
            }
            sts128(sb + O_WP + c * 512 + lane * 16, a[92], a[93], a[94], a[95]);
            float wmax = 0.f;
#pragma unroll
            for (int i = 0; i < 3; i++) {
                float n0[4];
#pragma unroll
                for (int u = 8 * i; u < 8 * i + 8; u++) {
                    const uint32_t x0 = a[4 * u] & 0x7fff7fffu, x1 = a[4 * u + 1] & 0x7fff7fffu, x2 = a[4 * u + 2] & 0x7fff7fffu, x3 = a[4 * u + 3] & 0x7fff7fffu;
                    if (u == 8 * i) mma16816_z(n0, x0, x1, x2, x3, ONES, ONES);
                    else mma16816(n0, x0, x1, x2, x3, ONES, ONES);
                }
                wmax = fmaxf(wmax, fmaxf(n0[0], n0[2]));
            }
            uint32_t wm = __reduce_max_sync(~0u, __float_as_uint(wmax));
            sts32_if(lane, sb + O_OF + 4 * c, wm);
            if (c == 0) PSTAMP(8);
            bar_sync(7, 384);
            asm volatile("barrier.cluster.wait.aligned;" ::: "memory");
            if (c == 1) { tma_x_tile(sb, &tm_x, r, 1, 1); tma_x_tile(sb, &tm_x, r, 2, 2); }
            if (c == 2 && r == 2) { bar_sync(0, 288); fence_async_smem(); v_store(sb, h, 0, 0); v_multicast(sb, h, 0); }
            if (c == 0) {
                const uint4 wq = lds128(sb + O_OF), xq = lds128(sb + O_OF + 16), xr = lds128(sb + O_OF + 32), v0 = lds128(sb + O_MISC + 32), v1 = lds128(sb + O_MISC + 48);
                const uint32_t w1 = max(max(wq.x, wq.y), max(wq.z, wq.w)), x1 = max(max(max(xq.x, xq.y), max(xq.z, xq.w)), max(max(xr.x, xr.y), max(xr.z, xr.w)));
                const uint32_t vv = (r < 2) ? 0u : max(max(max(v0.x, v0.y), max(v0.z, v0.w)), max(max(v1.x, v1.y), max(v1.z, v1.w)));
                const uint32_t lo = (min(w1, 0x7f800000u) + 0xffffu) >> 16 | ((min(vv, 0x7f800000u) + 0xffffu) & 0xffff0000u), hi = (x1 & 0xffff0000u) | tag;
                uint32_t l0, h0, l1, h1, l2, h2;
                asm volatile("{\n.reg .pred p;\n.reg .u32 n, x, y;\n.reg .b64 v;\nsetp.eq.u32 p, %10, 0;\nmov.b64 v, {%8, %9};\n@p st.relaxed.gpu.global.b64 [%7], v;\nmov.u32 n, 0;\n"
                             "G_%=: ld.relaxed.gpu.global.b64 v, [%6];\nmov.b64 {%0, %1}, v;\nld.relaxed.gpu.global.b64 v, [%6+256];\nmov.b64 {%2, %3}, v;\n"
                             "ld.relaxed.gpu.global.b64 v, [%6+512];\nmov.b64 {%4, %5}, v;\n"
                             "xor.b32 x, %1, %9;\nxor.b32 y, %3, %9;\nor.b32 x, x, y;\nxor.b32 y, %5, %9;\nor.b32 x, x, y;\nand.b32 x, x, 0xffff;\n"
                             "setp.eq.u32 p, x, 0;\nvote.sync.all.pred p, p, 0xffffffff;\n@p bra.uni E_%=;\n"
                             "add.u32 n, n, 1;\nsetp.lt.u32 p, n, 4000000;\n@p bra.uni G_%=;\ntrap;\nE_%=:\n}"
                             : "=&r"(l0), "=&r"(h0), "=&r"(l1), "=&r"(h1), "=&r"(l2), "=&r"(h2)
                             : "l"(&g_norm[lane]), "l"(&g_norm[blockIdx.x]), "r"(lo), "r"(hi), "r"(lane) : "memory");
                const uint32_t lm = __vmaxu2(l0, __vmaxu2(l1, l2));
                const float fw = __uint_as_float(__reduce_max_sync(~0u, lm << 16));
                const float fv = __uint_as_float(__reduce_max_sync(~0u, lm & 0xffff0000u));
                const float xmax = __uint_as_float(__reduce_max_sync(~0u, max(h0, max(h1, h2)) & 0xffff0000u));
                const float G = 36.f * fw * fv;
                sts32_if(lane, sb + O_MISC + 4, __float_as_uint(G)); sts32_if(lane, sb + O_MISC + 8, __float_as_uint(G * xmax));
            }
        }
        if (c == 0) PSTAMP(12);
        bar_sync(6, 128);
        int s3 = 0;
        uint32_t roff = __shfl_sync(~0u, (r * 4 + c) * 2048 + (lane >> 4) * 512 + (lane & 2) * 128 + (lane & 1) * 64 + (lane & 12) * 4, lane);
#pragma unroll 1
        for (int s = 0; s < NSEG; s++) {
            const uint32_t l16 = opaque(l16c);
            const uint32_t vxa = sb + O_VX + (r == 2 ? s3 : (s & 1)) * 8192 + c * 2048 + l16;
            const int s3n = (s3 == 2) ? 0 : s3 + 1;
            sts32_if(l16, sb + O_MISC + 16 + 4 * c, __reduce_max_sync(~0u, mmax));
            mbar_arrive_if(l16, sb + B_MX);
            if (s == NSEG - 1) { bar_sync(3, 384); mbar_wait(sb + B_SC, s & 1); break; }
            uint4 vx[4];
            if (c == 0) STAMP(s, 5);
            {
                mbar_wait(sb + B_MX, s & 1);
                const uint4 mm = lds128(sb + O_MISC + 16), cf = lds128(sb + O_MISC);
                const float bound = fmaxf(__uint_as_float(cf.z), __uint_as_float(cf.y) * (__uint_as_float(max(max(mm.x, mm.y), max(mm.z, mm.w))) * __uint_as_float(cf.x)));
                const uint32_t ebits = __reduce_max_sync(~0u, min(max(__float_as_uint(bound) & 0x7f800000u, 21u << 23), 254u << 23));
                const int j = s + 1 + (r >> 1);
                if (c == 1 && j < NSEG) mbar_wait(sb + B_X + 8 * (j % 3), (j / 3) & 1);
                if (r < 2) mbar_wait(sb + B_VX + 8 * (s & 1), (s >> 1) & 1);
                bar_sync(3, 384);
                vx[0] = lds128(vxa); vx[2] = lds128(vxa + 1024);
                if (c == 0) STAMP(s, 13);
                mbar_wait(sb + B_SC, s & 1);
                if (c == 0) STAMP(s, 6);
                float p[10];
                load_scores(p, sb + O_SC, 1280, l16);
                float mx = fmaxf(fmaxf(fmaxf(p[0], p[1]), fmaxf(p[2], p[3])), fmaxf(fmaxf(p[4], p[5]), fmaxf(p[6], p[7])));
                mx = quad_max(fmaxf(mx, fmaxf(p[8], p[9])));
                const uint4 vm = lds64x2(sb + O_VM + c * 512 + (l16 >> 1));
                vx[1] = lds128(vxa + 512); vx[3] = lds128(vxa + 1536);
                bar_arrive(4, 384);
                const float sc = __uint_as_float(lds32(sb + O_MISC + 12));
                const float mo = mx * SM_SCALE;
                uint32_t P[5];
#pragma unroll
                for (int n = 0; n < 5; n++) P[n] = pack_bf16(ex2(fmaf(p[2 * n], SM_SCALE, -mo)), ex2(fmaf(p[2 * n + 1], n == 3 ? sc : SM_SCALE, -mo)));
                if (c == 0) STAMP(s, 7);
                float o0[4], o1[4], sm[4];
                mma16816_z(sm, ONES, ONES, ONES, ONES, P[1], P[2]);
                mma16816_z(o0, vx[0].x, vx[0].y, vx[0].z, vx[0].w, P[1], P[2]);
                mma16816_z(o1, vx[2].x, vx[2].y, vx[2].z, vx[2].w, P[1], P[2]);
                mma16816(sm, ONES, ONES, ONES, ONES, P[3], P[4]);
                mma16816(o0, vx[1].x, vx[1].y, vx[1].z, vx[1].w, P[3], P[4]);
                mma16816(o1, vx[3].x, vx[3].y, vx[3].z, vx[3].w, P[3], P[4]);
                mma1688(sm, ONES, ONES, P[0]);
                mma1688(o0, vm.x, vm.y, P[0]);
                mma1688(o1, vm.z, vm.w, P[0]);
                const float sig = __uint_as_float((268u << 23) - ebits);
                const float r0 = rcp_fast(sm[0]) * sig, r1 = rcp_fast(sm[1]) * sig;
                stsm4t(sb + O_OF + c * 512 + l16, pack_bf16(o0[0] * r0, o0[1] * r1), pack_bf16(o0[2] * r0, o0[3] * r1),
                       pack_bf16(o1[0] * r0, o1[1] * r1), pack_bf16(o1[2] * r0, o1[3] * r1));
                bar_sync(6, 128);
                uint4 ob[4];
#pragma unroll
                for (int q = 0; q < 4; q++) ob[q] = ldsm4(sb + O_OF + q * 512 + l16);
                { const uint4 v = lds128(sb + O_WP + c * 512 + l16); a[92] = v.x; a[93] = v.y; a[94] = v.z; a[95] = v.w; }
                float m0[3][4], m1[3][4];
#pragma unroll
                for (int q = 0; q < 4; q++) {
#pragma unroll
                    for (int i = 0; i < 3; i++) {
                        const int k0 = (i * 8 + 2 * q) * 4;
                        if (q == 0) mma16816_z(m0[i], a[k0], a[k0 + 1], a[k0 + 2], a[k0 + 3], ob[q].x, ob[q].y);
                        else mma16816(m0[i], a[k0], a[k0 + 1], a[k0 + 2], a[k0 + 3], ob[q].x, ob[q].y);
                    }
#pragma unroll
                    for (int i = 0; i < 3; i++) {
                        const int k1 = (i * 8 + 2 * q + 1) * 4;
                        if (q == 0) mma16816_z(m1[i], a[k1], a[k1 + 1], a[k1 + 2], a[k1 + 3], ob[q].z, ob[q].w);
                        else mma16816(m1[i], a[k1], a[k1 + 1], a[k1 + 2], a[k1 + 3], ob[q].z, ob[q].w);
                    }
                }
                if (EARLY5) {
                    const uint32_t z = __float_as_uint(m0[2][0]) & (l16 & 15u);
                    bar_arrive(5 + z, 256); bar_arrive(13 + z, 256);
                }
                asm volatile("red.relaxed.gpu.global.add.noftz.v4.f16x2 [%0], {%1,%2,%3,%4};" :: "l"(reinterpret_cast<char*>(g_acc) + roff),
                    "r"(pack_f16(m0[0][0] + m1[0][0], m0[0][2] + m1[0][2])), "r"(pack_f16(m0[1][0] + m1[1][0], m0[1][2] + m1[1][2])),
                    "r"(pack_f16(m0[2][0] + m1[2][0], m0[2][2] + m1[2][2])), "r"(0x3c00u) : "memory");
                asm volatile("red.relaxed.gpu.global.add.noftz.v4.f16x2 [%0], {%1,%2,%3,%4};" :: "l"(reinterpret_cast<char*>(g_acc) + roff + 1024),
                    "r"(pack_f16(m0[0][1] + m1[0][1], m0[0][3] + m1[0][3])), "r"(pack_f16(m0[1][1] + m1[1][1], m0[1][3] + m1[1][3])),
                    "r"(pack_f16(m0[2][1] + m1[2][1], m0[2][3] + m1[2][3])), "r"(0x3c00u) : "memory");
                const unsigned t_red = clk();
                if (!EARLY5) { bar_arrive(5, 256); bar_arrive(13, 256); }
                mbar_expect_if(l16 | c, sb + B_SC, 4608);
                mbar_expect_if(l16 | (c ^ 1) | (r >> 1), sb + B_VX + 8 * ((s + 1) & 1), 8192);
                sts32_if(l16 | (c ^ 3), sb + O_MISC, ebits - (14u << 23));
                if (c == 0) STAMPV(s, 8, t_red);
                if (ACC_PF && c == 3 && s + 4 < NSEG - 1)
                    asm volatile("prefetch.global.L2 [%0];" :: "l"(reinterpret_cast<const char*>(g_acc) + ((s + 4) * 96 + blockIdx.x) * 256 + (l16 & 96)) : "memory");
                const char* pbase = reinterpret_cast<const char*>(g_acc) + (s * 24576 + c * 2048) + ((l16 & 64) * 16 + (l16 & 256) + ((l16 & 128) >> 1) + (l16 & 48));
                spin_until(t_red, D_WAIT);
                uint4 v[6];
#pragma unroll
                for (int i = 0; i < 6; i++) v[i] = ldg_relaxed128(pbase + (i >> 1) * 8192 + (i & 1) * 512);
                int nretry = 0;
                auto convert = [&](int tau, uint4& A, uint4& B) {
                    A.x = f16x2_to_bf16x2(A.x); B.x = f16x2_to_bf16x2(B.x); A.y = f16x2_to_bf16x2(A.y); B.y = f16x2_to_bf16x2(B.y);
                    A.z = f16x2_to_bf16x2(A.z); B.z = f16x2_to_bf16x2(B.z);
                    sts128(sb + O_MF + tau * 3072 + c * 512 + l16, A.x, B.x, A.y, B.y);
                    sts64(sb + O_MF + tau * 3072 + 2048 + (c >> 1) * 512 + (c & 1) * 8 + l16, A.z, B.z);
                };
                const uint32_t ok0 = __all_sync(~0u, (v[0].w & v[1].w) == 0x5000u);
                convert(0, v[0], v[1]);
                asm volatile("{\n.reg .pred p;\nsetp.ne.u32 p, %0, 0;\n@p bar.arrive 2, 384;\n}" :: "r"(ok0) : "memory");
                sched_fence<0>(h);
                uint32_t ok1;
                asm volatile("{\n.reg .pred p, q;\n.reg .b32 x;\nlop3.b32 x, %1, %2, %3, 0x80;\nand.b32 x, x, %4;\n"
                             "setp.eq.u32 p, x, 0x5000;\nvote.sync.all.pred q, p, 0xffffffff;\nselp.u32 %0, 1, 0, q;\n}"
                             : "=r"(ok1) : "r"(v[2].w), "r"(v[3].w), "r"(v[4].w), "r"(v[5].w));
                convert(1, v[2], v[3]); convert(2, v[4], v[5]);
                asm volatile("{\n.reg .pred p;\nsetp.ne.u32 p, %0, 0;\n@p bar.arrive 15, 384;\n}" :: "r"(ok1) : "memory");
                if (ok0 & ok1) {
                    mmax = absmax2(absmax2(absmax2(v[0].x, v[0].y), absmax2(v[0].z, v[1].x)), absmax2(absmax2(v[1].y, v[1].z), absmax2(v[2].x, v[2].y)));
                    mmax = absmax2(mmax, absmax2(absmax2(absmax2(v[2].z, v[3].x), absmax2(v[3].y, v[3].z)), absmax2(absmax2(v[4].x, v[4].y), absmax2(v[4].z, v[5].x))));
                    mmax = absmax2(mmax, absmax2(v[5].y, v[5].z));
                } else {
                    const uint32_t bad1 = !__all_sync(~0u, (v[2].w & v[3].w) == 0x5000u), bad2 = !__all_sync(~0u, (v[4].w & v[5].w) == 0x5000u);
                    uint4 u[6];
                    asm volatile("{\n.reg .pred p0, p1, p2, q;\n.reg .u32 n, x;\nmov.u32 n, 0;\n"
                         "setp.eq.u32 p0, %26, 0;\nsetp.ne.u32 p1, %27, 0;\nsetp.ne.u32 p2, %28, 0;\n"
                         "mov.u32 %0, 0; mov.u32 %1, 0; mov.u32 %2, 0; mov.u32 %3, 0x5000; mov.u32 %4, 0; mov.u32 %5, 0; mov.u32 %6, 0; mov.u32 %7, 0x5000;\n"
                         "mov.u32 %8, 0; mov.u32 %9, 0; mov.u32 %10, 0; mov.u32 %11, 0x5000; mov.u32 %12, 0; mov.u32 %13, 0; mov.u32 %14, 0; mov.u32 %15, 0x5000;\n"
                         "mov.u32 %16, 0; mov.u32 %17, 0; mov.u32 %18, 0; mov.u32 %19, 0x5000; mov.u32 %20, 0; mov.u32 %21, 0; mov.u32 %22, 0; mov.u32 %23, 0x5000;\n"
                         "R_%=: @p0 ld.relaxed.gpu.global.v4.u32 {%0,%1,%2,%3}, [%25];\n@p0 ld.relaxed.gpu.global.v4.u32 {%4,%5,%6,%7}, [%25+512];\n"
                         "@p1 ld.relaxed.gpu.global.v4.u32 {%8,%9,%10,%11}, [%25+8192];\n@p1 ld.relaxed.gpu.global.v4.u32 {%12,%13,%14,%15}, [%25+8704];\n"
                         "@p2 ld.relaxed.gpu.global.v4.u32 {%16,%17,%18,%19}, [%25+16384];\n@p2 ld.relaxed.gpu.global.v4.u32 {%20,%21,%22,%23}, [%25+16896];\n"
                         "add.u32 %24, %24, 1;\nand.b32 x, %3, %7;\nsetp.ne.u32 p0, x, 0x5000;\nand.b32 x, %11, %15;\nsetp.ne.u32 p1, x, 0x5000;\n"
                         "and.b32 x, %19, %23;\nsetp.ne.u32 p2, x, 0x5000;\nor.pred q, p0, p1;\nor.pred q, q, p2;\nvote.sync.any.pred q, q, 0xffffffff;\n@!q bra.uni K_%=;\n"
                         "add.u32 n, n, 1;\nsetp.lt.u32 q, n, 2000000;\n@q bra.uni R_%=;\ntrap;\nK_%=:\n}"
                         : "=&r"(u[0].x), "=&r"(u[0].y), "=&r"(u[0].z), "=&r"(u[0].w), "=&r"(u[1].x), "=&r"(u[1].y), "=&r"(u[1].z), "=&r"(u[1].w),
                           "=&r"(u[2].x), "=&r"(u[2].y), "=&r"(u[2].z), "=&r"(u[2].w), "=&r"(u[3].x), "=&r"(u[3].y), "=&r"(u[3].z), "=&r"(u[3].w),
                           "=&r"(u[4].x), "=&r"(u[4].y), "=&r"(u[4].z), "=&r"(u[4].w), "=&r"(u[5].x), "=&r"(u[5].y), "=&r"(u[5].z), "=&r"(u[5].w), "+r"(nretry)
                         : "l"(pbase), "r"(ok0), "r"(bad1), "r"(bad2) : "memory");
                    if (!ok0) { convert(0, u[0], u[1]); bar_arrive(2, 384); }
                    if (bad1) convert(1, u[2], u[3]);
                    if (bad2) convert(2, u[4], u[5]);
                    if (!ok1) bar_arrive(15, 384);
                    mmax = 0;
#pragma unroll
                    for (int tau = 0; tau < 3; tau++) {
                        const uint4 A = lds128(sb + O_MF + tau * 3072 + c * 512 + l16);
                        const float2 B = lds64f(sb + O_MF + tau * 3072 + 2048 + (c >> 1) * 512 + (c & 1) * 8 + l16);
                        mmax = absmax2(absmax2(mmax, absmax2(A.x, A.y)), absmax2(absmax2(A.z, A.w), absmax2(__float_as_uint(B.x), __float_as_uint(B.y))));
                    }
                }
                if (c == 0) STAMP(s, 12);
                if (c == 0) STAMPV(s, 14, nretry);
                mmax &= 0x7fff7fffu;
                mmax = max(mmax << 16, mmax & 0xffff0000u);
            }
            roff += 24576;
            s3 = s3n;
        }
        {
            bar_sync(7, 384);
            if (c == 0) flag_inc_if(l16c, &g_flag[F_QKV + (60 + (h >> 3)) * 8]);
        }
    }
    if (warp == 8) PSTAMP(13);
    cluster_sync();
}

constexpr int NST = 10;
constexpr int G_RING = 0, G_EX = NST * 16384, G_OUT = G_EX + 32768, G_CARRY = G_OUT + 32768, G_BAR = G_CARRY + 512, BG_SMEM = G_BAR + 256;
constexpr int GB_FULL = G_BAR, GB_EMPTY = G_BAR + 8 * NST, GB_W = G_BAR + 16 * NST;
static_assert(BG_SMEM <= 232448, "smem");

template <int ACC>
__device__ __forceinline__ void wgmma_n128_rs(float (&d)[64], uint32_t a0, uint32_t a1, uint32_t a2, uint32_t a3, uint64_t desc) {
    asm volatile("wgmma.mma_async.sync.aligned.m64n128k16.f32.bf16.bf16 "
        "{%0,%1,%2,%3,%4,%5,%6,%7,%8,%9,%10,%11,%12,%13,%14,%15,%16,%17,%18,%19,%20,%21,%22,%23,%24,%25,%26,%27,%28,%29,%30,%31,"
        "%32,%33,%34,%35,%36,%37,%38,%39,%40,%41,%42,%43,%44,%45,%46,%47,%48,%49,%50,%51,%52,%53,%54,%55,%56,%57,%58,%59,%60,%61,%62,%63}, "
        "{%64,%65,%66,%67}, %68, %69, 1, 1, 0;"
        : "+f"(d[0]), "+f"(d[1]), "+f"(d[2]), "+f"(d[3]), "+f"(d[4]), "+f"(d[5]), "+f"(d[6]), "+f"(d[7]),
          "+f"(d[8]), "+f"(d[9]), "+f"(d[10]), "+f"(d[11]), "+f"(d[12]), "+f"(d[13]), "+f"(d[14]), "+f"(d[15]),
          "+f"(d[16]), "+f"(d[17]), "+f"(d[18]), "+f"(d[19]), "+f"(d[20]), "+f"(d[21]), "+f"(d[22]), "+f"(d[23]),
          "+f"(d[24]), "+f"(d[25]), "+f"(d[26]), "+f"(d[27]), "+f"(d[28]), "+f"(d[29]), "+f"(d[30]), "+f"(d[31]),
          "+f"(d[32]), "+f"(d[33]), "+f"(d[34]), "+f"(d[35]), "+f"(d[36]), "+f"(d[37]), "+f"(d[38]), "+f"(d[39]),
          "+f"(d[40]), "+f"(d[41]), "+f"(d[42]), "+f"(d[43]), "+f"(d[44]), "+f"(d[45]), "+f"(d[46]), "+f"(d[47]),
          "+f"(d[48]), "+f"(d[49]), "+f"(d[50]), "+f"(d[51]), "+f"(d[52]), "+f"(d[53]), "+f"(d[54]), "+f"(d[55]),
          "+f"(d[56]), "+f"(d[57]), "+f"(d[58]), "+f"(d[59]), "+f"(d[60]), "+f"(d[61]), "+f"(d[62]), "+f"(d[63])
        : "r"(a0), "r"(a1), "r"(a2), "r"(a3), "l"(desc), "n"(ACC));
}
__device__ __forceinline__ void wait_flag(const unsigned* p, unsigned target) {
    asm volatile("{\n.reg .pred p;\n.reg .u32 n, v;\nmov.u32 n, 0;\n"
                 "W_%=: ld.acquire.gpu.global.u32 v, [%0];\nsub.u32 v, v, %1;\nsetp.ge.s32 p, v, 0;\n@p bra.uni D_%=;\nnanosleep.u32 100;\n"
                 "add.u32 n, n, 1;\nsetp.lt.u32 p, n, 4000000;\n@p bra.uni W_%=;\ntrap;\nD_%=:\n}" :: "l"(p), "r"(target) : "memory");
}
template <int NS, int STRIDE>
__device__ __forceinline__ void bg_mainloop(float (&d)[64], const uint32_t (&a)[144], uint32_t sb, int it, int lane) {
    int slot = it % NST, ph = (it / NST) & 1, prev = 0;
#pragma unroll
    for (int i = 0; i < NS; i++) {
        mbar_wait(sb + GB_FULL + 8 * slot, ph);
        const uint64_t desc = (uint64_t)(((sb + G_RING + slot * 16384) & 0x3FFFF) >> 4) | (1ull << 16) | (64ull << 32) | (1ull << 62);
        wg_fence();
#pragma unroll
        for (int k = 0; k < 4; k++) {
            const int u = 16 * i + 4 * k;
            if (i == 0 && k == 0) wgmma_n128_rs<0>(d, a[u], a[u + 1], a[u + 2], a[u + 3], desc);
            else wgmma_n128_rs<1>(d, a[u], a[u + 1], a[u + 2], a[u + 3], desc + 2 * k);
        }
        wg_commit();
        if (i > 0) {
            asm volatile("wgmma.wait_group.sync.aligned 1;" ::: "memory");
            mbar_arrive_if(lane, sb + GB_EMPTY + 8 * prev);
        }
        prev = slot;
        slot += STRIDE;
        if (slot >= NST) { slot -= NST; ph ^= 1; }
    }
    wg_wait0();
    mbar_arrive_if(lane, sb + GB_EMPTY + 8 * prev);
}
template <bool SKIP>
__device__ __forceinline__ void bg_epilogue(float (&d)[64], uint32_t sb, int wg, int w, int lane, const CUtensorMap* tm_out, int col0, int tok0,
                                            const __nv_bfloat16* xa, const __nv_bfloat16* Dk) {
    const int g = lane >> 2, t = lane & 3;
    const uint32_t ex = sb + G_EX + w * 4096 + lane * 16;
    float k[32];
    if (wg == 0) {
#pragma unroll
        for (int q = 0; q < 8; q++) sts128f(ex + q * 512, d[32 + 4 * q], d[32 + 4 * q + 1], d[32 + 4 * q + 2], d[32 + 4 * q + 3]);
#pragma unroll
        for (int i = 0; i < 32; i++) k[i] = d[i];
    } else {
#pragma unroll
        for (int q = 0; q < 8; q++) sts128f(ex + 16384 + q * 512, d[4 * q], d[4 * q + 1], d[4 * q + 2], d[4 * q + 3]);
#pragma unroll
        for (int i = 0; i < 32; i++) k[i] = d[32 + i];
    }
    uint32_t xv[16], dv = 0;
    if (SKIP) {
        const __nv_bfloat16* xp = xa + (size_t)(tok0 + 64 * wg + 2 * t) * DM + col0 + 16 * w + 2 * g;
#pragma unroll
        for (int i = 0; i < 16; i++) xv[i] = ldg_nc32(xp + (8 * (i >> 1) + (i & 1)) * DM);
        dv = ldg_nc32(Dk + col0 + 16 * w + 2 * g);
    }
    if (SKIP && w == 0) asm volatile("cp.async.bulk.wait_group.read 0;" ::: "memory");
    bar_sync(1, 256);
#pragma unroll
    for (int q = 0; q < 8; q++) {
        const float4 o = lds128f(ex + (wg ^ 1) * 16384 + q * 512);
        k[4 * q] += o.x; k[4 * q + 1] += o.y; k[4 * q + 2] += o.z; k[4 * q + 3] += o.w;
    }
    if (SKIP) bar_sync(1, 256); else bar_sync(13, 288);
    const uint32_t ob = sb + G_OUT + wg * 16384 + (w >> 1) * 8192 + (g & 1) * 8;
    const uint32_t ch = (w & 1) * 4 + (g >> 1);
#pragma unroll
    for (int i = 0; i < 16; i++) {
        float v0 = k[4 * (i >> 1) + (i & 1)], v1 = k[4 * (i >> 1) + 2 + (i & 1)];
        if (SKIP) {
            const uint32_t p = pack_bf16(__uint_as_float(xv[i] << 16) * __uint_as_float(dv << 16), __uint_as_float(xv[i] & 0xffff0000u) * __uint_as_float(dv & 0xffff0000u));
            v0 += __uint_as_float(p << 16); v1 += __uint_as_float(p & 0xffff0000u);
        }
        const uint32_t n7 = 2 * t + (i & 1);
        sts64(ob + (8 * (i >> 1) + n7) * 128 + ((ch ^ n7) << 4), __float_as_uint(v0), __float_as_uint(v1));
    }
    fence_async_smem();
    if (SKIP) {
        bar_sync(4 + wg, 128);
        if (w == 0)
            asm volatile("{\n.reg .pred p;\nelect.sync _|p, 0xffffffff;\n"
                "@p cp.async.bulk.tensor.2d.global.shared::cta.bulk_group [%0, {%2, %4}], [%1];\n"
                "@p cp.async.bulk.tensor.2d.global.shared::cta.bulk_group [%0, {%3, %4}], [%1+8192];\n@p cp.async.bulk.commit_group;\n}"
                :: "l"(tm_out), "r"(sb + G_OUT + wg * 16384), "r"(col0), "r"(col0 + 32), "r"(tok0 + 64 * wg) : "memory");
    } else {
        bar_arrive(12, 288);
    }
}
__device__ __forceinline__ void s5_channel(int p, const __nv_bfloat16* Lre, const __nv_bfloat16* Lim, const __nv_bfloat16* logdt, float2& lam, float2& coef) {
    const float dt = __bfloat162float(__float2bfloat16(expf(__bfloat162float(logdt[p]))));
    const float lr = __bfloat162float(Lre[p]), li = __bfloat162float(Lim[p]);
    const float e = expf(dt * lr);
    float sn, cs;
    sincosf(dt * li, &sn, &cs);
    lam = make_float2(e * cs, e * sn);
    const float den = lr * lr + li * li;
    coef = make_float2(((lam.x - 1.f) * lr + lam.y * li) / den, (lam.y * lr - (lam.x - 1.f) * li) / den);
}
__device__ __forceinline__ float2 cfma(float2 a, float2 b, float2 c) {
    return make_float2(fmaf(a.x, b.x, fmaf(-a.y, b.y, c.x)), fmaf(a.x, b.y, fmaf(a.y, b.x, c.y)));
}
__device__ __forceinline__ uint4 ldg128(const void* p) { uint4 v; asm volatile("ld.global.v4.u32 {%0,%1,%2,%3}, [%4];" : "=r"(v.x), "=r"(v.y), "=r"(v.z), "=r"(v.w) : "l"(p) : "memory"); return v; }
__device__ __forceinline__ uint2 ldg64(const void* p) { uint2 v; asm volatile("ld.global.v2.u32 {%0,%1}, [%2];" : "=r"(v.x), "=r"(v.y) : "l"(p) : "memory"); return v; }

__device__ __forceinline__ void bg_attention(uint32_t st0, uint32_t st1, int mt, int lane) {
    const int g = lane >> 2, t = lane & 3;
    float sc[5][4];
#pragma unroll
    for (int n = 0; n < 5; n++) sc[n][0] = sc[n][1] = sc[n][2] = sc[n][3] = 0.f;
    float sm2[4] = {0.f, 0.f, 0.f, 0.f};
#pragma unroll
    for (int i = 0; i < 8; i++) {
        const uint32_t st = (i >> 2 ? st1 : st0) + (i & 3) * 512 + lane * 16;
        const uint4 q = ldsm4(st + mt * 2048), km = ldsm4(st + 8192), k0 = ldsm4(st + 4096);
        mma16816(sc[0], q.x, q.y, q.z, q.w, km.x, km.y);
        mma16816(sm2, q.x, q.y, q.z, q.w, km.z, km.w);
        mma16816(sc[1], q.x, q.y, q.z, q.w, k0.x, k0.y);
        mma16816(sc[2], q.x, q.y, q.z, q.w, k0.z, k0.w);
        if (mt) {
            const uint4 k1 = ldsm4(st + 6144);
            mma16816(sc[3], q.x, q.y, q.z, q.w, k1.x, k1.y);
            mma16816(sc[4], q.x, q.y, q.z, q.w, k1.z, k1.w);
        }
    }
#pragma unroll
    for (int i = 0; i < 4; i++) sc[0][i] += sm2[i];
    const int q0 = 16 * mt + 8 + g - 2 * t;
#pragma unroll
    for (int n = 1; n < 5; n++) {
        if (8 * n > q0) sc[n][0] = -INFINITY;
        if (8 * n + 1 > q0) sc[n][1] = -INFINITY;
        if (8 * n > q0 + 8) sc[n][2] = -INFINITY;
        if (8 * n + 1 > q0 + 8) sc[n][3] = -INFINITY;
    }
    float ma = fmaxf(sc[0][0], sc[0][1]), mb = fmaxf(sc[0][2], sc[0][3]);
#pragma unroll
    for (int n = 1; n < 5; n++) { ma = fmaxf(ma, fmaxf(sc[n][0], sc[n][1])); mb = fmaxf(mb, fmaxf(sc[n][2], sc[n][3])); }
    ma = quad_max(ma) * SM_SCALE; mb = quad_max(mb) * SM_SCALE;
    uint32_t Pa[5], Pb[5];
#pragma unroll
    for (int n = 0; n < 5; n++) {
        Pa[n] = pack_bf16(ex2(fmaf(sc[n][0], SM_SCALE, -ma)), ex2(fmaf(sc[n][1], SM_SCALE, -ma)));
        Pb[n] = pack_bf16(ex2(fmaf(sc[n][2], SM_SCALE, -mb)), ex2(fmaf(sc[n][3], SM_SCALE, -mb)));
    }
    float sa[4], sbb[4];
    mma1688_z(sa, ONES, ONES, Pa[0]); mma1688_z(sbb, ONES, ONES, Pb[0]);
    mma16816(sa, ONES, ONES, ONES, ONES, Pa[1], Pa[2]); mma16816(sbb, ONES, ONES, ONES, ONES, Pb[1], Pb[2]);
    mma16816(sa, ONES, ONES, ONES, ONES, Pa[3], Pa[4]); mma16816(sbb, ONES, ONES, ONES, ONES, Pb[3], Pb[4]);
    const float ra0 = rcp_fast(sa[0]), ra1 = rcp_fast(sa[1]), rb0 = rcp_fast(sbb[0]), rb1 = rcp_fast(sbb[1]);
    const uint32_t row = lane & 7;
    const uint32_t so = mt * 2048 + (lane >> 4) * 1024 + row * 128;
#pragma unroll
    for (int i = 0; i < 8; i++) {
        const uint32_t st = i >> 2 ? st1 : st0;
        const int e4 = i & 3;
        const float2 vmf = lds64f(st + 14336 + e4 * 256 + lane * 8);
        const uint32_t vm0 = __float_as_uint(vmf.x), vm1 = __float_as_uint(vmf.y);
        const uint4 v0 = lds128(st + 10240 + e4 * 1024 + lane * 16);
        float oa[4], ob[4];
        mma1688_z(oa, vm0, vm1, Pa[0]); mma1688_z(ob, vm0, vm1, Pb[0]);
        mma16816(oa, v0.x, v0.y, v0.z, v0.w, Pa[1], Pa[2]);
        mma16816(ob, v0.x, v0.y, v0.z, v0.w, Pb[1], Pb[2]);
        if (mt) {
            const uint4 v1 = lds128(st + 10240 + e4 * 1024 + 512 + lane * 16);
            mma16816(oa, v1.x, v1.y, v1.z, v1.w, Pa[3], Pa[4]);
            mma16816(ob, v1.x, v1.y, v1.z, v1.w, Pb[3], Pb[4]);
        }
        stsm4t(st + so + (((2 * e4 + ((lane >> 3) & 1)) ^ row) << 4), pack_bf16(oa[0] * ra0, oa[1] * ra1), pack_bf16(oa[2] * ra0, oa[3] * ra1),
               pack_bf16(ob[0] * rb0, ob[1] * rb1), pack_bf16(ob[2] * rb0, ob[3] * rb1));
    }
}
__device__ __forceinline__ bool bg_att_turn(int na, int ng) { return na == ng || (na == ng + 1 && na <= BG_AHEAD); }

__global__ void __launch_bounds__(384, 1)
bg_kernel(const __grid_constant__ CUtensorMap tm_xa, const __grid_constant__ CUtensorMap tm_wo, const __grid_constant__ CUtensorMap tm_out,
          const __nv_bfloat16* __restrict__ xa, const __nv_bfloat16* __restrict__ Lre, const __nv_bfloat16* __restrict__ Lim,
          const __nv_bfloat16* __restrict__ Bre, const __nv_bfloat16* __restrict__ Bim, const __nv_bfloat16* __restrict__ Cre,
          const __nv_bfloat16* __restrict__ Cim, const __nv_bfloat16* __restrict__ logdt, const __nv_bfloat16* __restrict__ Dk) {
    extern __shared__ __align__(1024) uint8_t smem_raw[];
    const uint32_t sb = smem_u32(smem_raw);
    const int lane = threadIdx.x & 31;
    const int warp = __shfl_sync(~0u, threadIdx.x >> 5, 0);
    const int wg = warp >> 2, w = warp & 3, b = blockIdx.x;
    const int nt = b % 9, kq = b / 9;
    BSTAMP(0);
    if (threadIdx.x == 0) {
        if (sb & 1023u) __trap();
        for (int i = 0; i < NST; i++) { mbar_init(sb + GB_FULL + 8 * i, 1); mbar_init(sb + GB_EMPTY + 8 * i, 4); }
        mbar_init(sb + GB_W, 1);
        asm volatile("fence.mbarrier_init.release.cluster;" ::: "memory");
        mbar_expect(sb + GB_W, (b < 18 ? 64 : 128) * 1152);
        sts32(sb + G_BAR + 248, atomicAdd(&g_ticket_bg, 1u) / 36u + 1u);
    }
    __syncthreads();
    if (wg == 2) {
        asm volatile("setmaxnreg.dec.sync.aligned.u32 24;");
        if (w == 0) {
            int slot = 0, ph = 1;
            unsigned tlast = clk();
            auto pace = [&]() { if (BG_PACE) { spin_until(tlast, BG_PACE); tlast = clk(); } };
            auto next = [&]() { if (++slot == NST) { slot = 0; ph ^= 1; } };
            bar_sync(6, 288);
            if (b < 18) {
#pragma unroll 1
                for (int i = 0; i < 144; i++) {
                    const int blk = i / 9, kb = i - 9 * blk, it = (blk >> 1) * 18 + (blk & 1) + 2 * kb;
                    slot = it % NST;
                    mbar_wait(sb + GB_EMPTY + 8 * slot, ((it / NST) & 1) ^ 1);
                    pace();
                    asm volatile("{\n.reg .pred p;\nelect.sync _|p, 0xffffffff;\n@p mbarrier.arrive.expect_tx.shared::cta.b64 _, [%2], 16384;\n"
                        "@p cp.async.bulk.tensor.5d.shared::cluster.global.mbarrier::complete_tx::bytes [%0], [%1, {%3, %4, %4, %4, %5}], [%2];\n}"
                        :: "r"(sb + G_RING + slot * 16384), "l"(&tm_xa), "r"(sb + GB_FULL + 8 * slot), "r"(kb * 64), "r"(0), "r"(blk) : "memory");
                }
                slot = 144 % NST; ph = ((144 / NST) & 1) ^ 1;
            }
            const unsigned ep = lds32(sb + G_BAR + 248);
            auto slabs = [&](const char* src, int ns) {
                asm volatile("fence.proxy.async.global;" ::: "memory");
#pragma unroll 1
                for (int i = 0; i < ns; i++) {
                    mbar_wait(sb + GB_EMPTY + 8 * slot, ph);
                    pace();
                    asm volatile("{\n.reg .pred p;\nelect.sync _|p, 0xffffffff;\n@p mbarrier.arrive.expect_tx.shared::cta.b64 _, [%2], 16384;\n"
                        "@p cp.async.bulk.shared::cluster.global.mbarrier::complete_tx::bytes [%0], [%1], 16384, [%2];\n}"
                        :: "r"(sb + G_RING + slot * 16384), "l"(src + (size_t)((i & 1) * (ns >> 1) + (i >> 1)) * (SEQ * 128)), "r"(sb + GB_FULL + 8 * slot) : "memory");
                    next();
                }
            };
            if (b >= 18) {
#pragma unroll 1
                for (int blk = kq - 2; blk < 16; blk += 2) {
                    wait_flag(&g_flag[F_H + blk * 8], 18 * ep);
                    slabs(reinterpret_cast<const char*>(g_h) + blk * 16384, 18);
                }
            }
            bar_sync(6, 288);
#pragma unroll 1
            for (int na = 0, ng = 0; ng < 16;) {
                if (bg_att_turn(na, ng)) {
                    if (nt < 8) {
                        wait_flag(&g_flag[F_QKV + (na * 4 + kq) * 8], 24 * ep);
                        asm volatile("fence.proxy.async.global;" ::: "memory");
#pragma unroll 1
                        for (int i = 0; i < 8; i++) {
                            const int pr = nt * 4 + 2 * (i & 1) + (i >> 2), hf = (i >> 1) & 1;
                            const char* rec = reinterpret_cast<const char*>(g_qkv) + (size_t)((4 * na + (pr >> 3)) * NH + 8 * kq + (pr & 7)) * REC;
                            mbar_wait(sb + GB_EMPTY + 8 * slot, ph);
                    pace();
                            asm volatile("{\n.reg .pred p;\nelect.sync _|p, 0xffffffff;\n@p mbarrier.arrive.expect_tx.shared::cta.b64 _, [%4], 15360;\n"
                                "@p cp.async.bulk.shared::cluster.global.mbarrier::complete_tx::bytes [%0], [%1], 10240, [%4];\n"
                                "@p cp.async.bulk.shared::cluster.global.mbarrier::complete_tx::bytes [%0+10240], [%2], 4096, [%4];\n"
                                "@p cp.async.bulk.shared::cluster.global.mbarrier::complete_tx::bytes [%0+14336], [%3], 1024, [%4];\n}"
                                :: "r"(sb + G_RING + slot * 16384), "l"(rec + hf * 10240), "l"(rec + 20480 + hf * 4096), "l"(rec + 28672 + hf * 1024),
                                   "r"(sb + GB_FULL + 8 * slot) : "memory");
                            next();
                        }
                    }
                    na++;
                } else {
                    wait_flag(&g_flag[F_OX + (ng * 4 + kq) * 8], 8 * ep);
                    slabs(reinterpret_cast<const char*>(g_ox) + (size_t)kq * 16 * SEQ * 128 + ng * 16384, 16);
                    ng++;
                }
            }
        } else if (w == 1) {
            if (b < 18) {
#pragma unroll 1
                for (int blk = 0; blk < 16; blk++) {
                    bar_sync(8 + (blk & 1), 160);
                    asm volatile("{\n.reg .pred p;\nelect.sync _|p, 0xffffffff;\n@p cp.async.bulk.global.shared::cta.bulk_group [%0], [%1], 16384;\n"
                        "@p cp.async.bulk.commit_group;\ncp.async.bulk.wait_group 0;\nfence.proxy.async.global;\n}"
                        :: "l"(reinterpret_cast<char*>(g_h) + ((size_t)b * SEQ + blk * 128) * 128), "r"(sb + G_OUT + (blk & 1) * 16384) : "memory");
                    bar_arrive(10 + (blk & 1), 160);
                    flag_inc_if(lane, &g_flag[F_H + blk * 8]);
                }
            }
            if (nt < 8) {
                int it = 144;
#pragma unroll 1
                for (int na = 0, ng = 0; ng < 16;) {
                    if (bg_att_turn(na, ng)) {
                        bar_sync(7, 288);
                        if (lane < 8) {
                            const int pr = nt * 4 + 2 * (lane & 1) + (lane >> 2), hf = (lane >> 1) & 1;
                            asm volatile("cp.async.bulk.global.shared::cta.bulk_group [%0], [%1], 4096;\ncp.async.bulk.commit_group;\ncp.async.bulk.wait_group.read 0;\n"
                                "mbarrier.arrive.shared::cta.b64 _, [%2], 4;\ncp.async.bulk.wait_group 0;\nfence.proxy.async.global;"
                                :: "l"(reinterpret_cast<char*>(g_ox) + ((size_t)((8 * kq + (pr & 7)) * 2 + hf) * SEQ + (4 * na + (pr >> 3)) * 32) * 128),
                                   "r"(sb + G_RING + ((it + lane) % NST) * 16384), "r"(sb + GB_EMPTY + 8 * ((it + lane) % NST)) : "memory");
                        }
                        __syncwarp();
                        flag_inc_if(lane, &g_flag[F_OX + (na * 4 + kq) * 8]);
                        it += 8; na++;
                    } else { it += 16; ng++; }
                }
            }
        } else if (w == 2) {
            const unsigned ep = lds32(sb + G_BAR + 248);
#pragma unroll 1
            for (int blk = 0; blk < 16; blk++) {
                bar_arrive(13, 288);
                bar_sync(12, 288);
                if (kq) { wait_flag(&g_flag[F_OUT + (blk * 9 + nt) * 8], ep); asm volatile("fence.proxy.async.global;" ::: "memory"); }
                unsigned t0 = clk();
                if (blk < 15) spin_until(t0, b * (RED_GAP / 36));
#pragma unroll 1
                for (int i = 0; i < 4; i++) {
                    const uint32_t src = sb + G_OUT + i * 8192;
                    const int c0 = DM + 64 * nt + (i & 1) * 32, c1 = blk * 128 + (i >> 1) * 64;
                    if (kq) {
                        asm volatile("{\n.reg .pred p;\nelect.sync _|p, 0xffffffff;\n@p cp.reduce.async.bulk.tensor.2d.global.shared::cta.add.bulk_group [%0, {%2, %3}], [%1];\n}"
                            :: "l"(&tm_out), "r"(src), "r"(c0), "r"(c1) : "memory");
                        t0 = clk();
                        if (blk < 15 && i < 3) spin_until(t0, RED_GAP);
                    } else {
                        asm volatile("{\n.reg .pred p;\nelect.sync _|p, 0xffffffff;\n@p cp.async.bulk.tensor.2d.global.shared::cta.bulk_group [%0, {%2, %3}], [%1];\n}"
                            :: "l"(&tm_out), "r"(src), "r"(c0), "r"(c1) : "memory");
                    }
                }
                asm volatile("cp.async.bulk.commit_group;\ncp.async.bulk.wait_group 0;\nfence.proxy.async.global;" ::: "memory");
                __syncwarp();
                if (!kq) flag_inc_if(lane, &g_flag[F_OUT + (blk * 9 + nt) * 8]);
            }
        }
    } else {
        asm volatile("setmaxnreg.inc.sync.aligned.u32 240;");
        const int g = lane >> 2, t = lane & 3, tid = threadIdx.x;
        uint32_t a[144];
        float d[64];
        if (b < 18) {
            if (tid < 64)
                asm volatile("cp.async.bulk.shared::cluster.global.mbarrier::complete_tx::bytes [%0], [%1], 1152, [%2];"
                    :: "r"(sb + tid * 1168), "l"((tid < 32 ? Bre : Bim) + (size_t)(32 * b + (tid & 31)) * DM), "r"(sb + GB_W) : "memory");
            float2 lam, coef;
            s5_channel(32 * b + 8 * w + g, Lre, Lim, logdt, lam, coef);
            float2 l32 = lam;
#pragma unroll
            for (int i = 0; i < 5; i++) l32 = make_float2(l32.x * l32.x - l32.y * l32.y, 2.f * l32.x * l32.y);
            __syncwarp();
            mbar_wait(sb + GB_W, 0);
            const uint32_t ap = sb + (((lane >> 3) & 1) * 32 + 8 * w + (lane & 7)) * 1168 + (lane >> 4) * 16;
#pragma unroll
            for (int ks = 0; ks < 36; ks++) { const uint4 v = ldsm4(ap + ks * 32); a[4 * ks] = v.x; a[4 * ks + 1] = v.y; a[4 * ks + 2] = v.z; a[4 * ks + 3] = v.w; }
            bar_sync(1, 256);
            bar_arrive(6, 288);
            BSTAMP(1);
#pragma unroll 1
            for (int blk = wg; blk < 16; blk += 2) {
                bg_mainloop<9, 2>(d, a, sb, (blk >> 1) * 18 + wg, lane);
                float2 e = make_float2(0.f, 0.f);
#pragma unroll
                for (int i = 0; i < 32; i++) e = cfma(lam, e, make_float2(d[4 * (i >> 1) + (i & 1)], d[4 * (i >> 1) + 2 + (i & 1)]));
                float2 cin = make_float2(0.f, 0.f);
                if (blk > 0) { bar_sync(2 + (wg ^ 1), 256); cin = lds64f(sb + G_CARRY + (wg ^ 1) * 256 + (8 * w + g) * 8); }
                float2 mine = cin;
#pragma unroll
                for (int q = 0; q < 4; q++) {
                    const float2 eq = make_float2(__shfl_sync(~0u, e.x, (lane & 28) + q), __shfl_sync(~0u, e.y, (lane & 28) + q));
                    cin = cfma(l32, cin, eq);
                    if (t == q + 1) mine = cin;
                }
                if (blk < 15) {
                    if (t == 0) sts64(sb + G_CARRY + wg * 256 + (8 * w + g) * 8, __float_as_uint(cin.x), __float_as_uint(cin.y));
                    bar_arrive(2 + wg, 256);
                }
                const uint32_t hs = sb + G_OUT + wg * 16384 + t * 4096 + (g & 3) * 4;
                const uint32_t ch = 2 * w + (g >> 2);
                if (blk >= 2) bar_sync(10 + wg, 160);
#pragma unroll
                for (int i = 0; i < 32; i++) {
                    mine = cfma(lam, mine, make_float2(d[4 * (i >> 1) + (i & 1)], d[4 * (i >> 1) + 2 + (i & 1)]));
                    sts32(hs + i * 128 + ((ch ^ (i & 7)) << 4), pack_bf16(mine.x, mine.y));
                }
                fence_async_smem();
                bar_arrive(8 + wg, 160);
            }
            bar_sync(10 + wg, 160);
        } else {
            if (tid < 128)
                asm volatile("cp.async.bulk.shared::cluster.global.mbarrier::complete_tx::bytes [%0], [%1], 1152, [%2];"
                    :: "r"(sb + tid * 1168), "l"((tid < 64 ? Cre : Cim) + (size_t)(64 * nt + (tid & 63)) * DM), "r"(sb + GB_W) : "memory");
            for (int p = tid; p < DM; p += 256) {
                float2 lam, coef;
                s5_channel(p, Lre, Lim, logdt, lam, coef);
                sts64(sb + G_EX + p * 8, __float_as_uint(2.f * coef.x), __float_as_uint(2.f * coef.y));
            }
            bar_sync(1, 256);
            mbar_wait(sb + GB_W, 0);
            const uint32_t cp = sb + (16 * w + 2 * g) * 1168 + (288 * wg + t) * 2;
#pragma unroll
            for (int u = 0; u < 72; u++) {
                const float2 c2 = lds64f(sb + G_EX + (288 * wg + 4 * u + t) * 8);
#pragma unroll
                for (int f = 0; f < 2; f++) {
                    unsigned short r16, i16;
                    asm volatile("ld.shared.u16 %0, [%1];" : "=h"(r16) : "r"(cp + f * 1168 + u * 8) : "memory");
                    asm volatile("ld.shared.u16 %0, [%1];" : "=h"(i16) : "r"(cp + (64 + f) * 1168 + u * 8) : "memory");
                    const float cr = __uint_as_float((uint32_t)r16 << 16), ci = __uint_as_float((uint32_t)i16 << 16);
                    a[2 * u + f] = pack_bf16(cr * c2.x - ci * c2.y, -(cr * c2.y + ci * c2.x));
                }
            }
            bar_sync(1, 256);
            bar_arrive(6, 288);
            BSTAMP(1);
#pragma unroll 1
            for (int j = 0; j < 8; j++) {
                bg_mainloop<9, 2>(d, a, sb, j * 18 + wg, lane);
                bg_epilogue<true>(d, sb, wg, w, lane, &tm_out, 64 * nt, (2 * j + kq - 2) * 128, xa, Dk);
            }
        }
        if (w == 0) asm volatile("cp.async.bulk.wait_group 0;" ::: "memory");
        bar_sync(1, 256);
        BSTAMP(2);
        if (warp == 0)
            asm volatile("{\n.reg .pred p;\nelect.sync _|p, 0xffffffff;\n@p mbarrier.arrive.expect_tx.shared::cta.b64 _, [%2], 131072;\n"
                "@p cp.async.bulk.tensor.2d.shared::cluster.global.mbarrier::complete_tx::bytes [%0], [%1, {%3, %4}], [%2];\n"
                "@p cp.async.bulk.tensor.2d.shared::cluster.global.mbarrier::complete_tx::bytes [%0+32768], [%1, {%3, %5}], [%2];\n"
                "@p cp.async.bulk.tensor.2d.shared::cluster.global.mbarrier::complete_tx::bytes [%0+65536], [%1, {%3, %6}], [%2];\n"
                "@p cp.async.bulk.tensor.2d.shared::cluster.global.mbarrier::complete_tx::bytes [%0+98304], [%1, {%3, %7}], [%2];\n}"
                :: "r"(sb), "l"(&tm_wo), "r"(sb + GB_W), "r"(64 * nt), "r"(1024 * kq), "r"(1024 * kq + 256), "r"(1024 * kq + 512), "r"(1024 * kq + 768) : "memory");
        mbar_wait(sb + GB_W, 1);
        {
            const uint32_t base = sb + wg * 65536 + 4 * t * 128 + (g & 3) * 4, ch = 2 * w + (g >> 2), r7 = (4 * t) & 7;
#pragma unroll
            for (int ks = 0; ks < 32; ks++) {
                const uint32_t w0 = lds32(base + ks * 2048 + ((ch ^ r7) << 4)), w1 = lds32(base + ks * 2048 + 256 + ((ch ^ (r7 + 2)) << 4));
                const uint32_t w2 = lds32(base + ks * 2048 + 128 + ((ch ^ (r7 + 1)) << 4)), w3 = lds32(base + ks * 2048 + 384 + ((ch ^ (r7 + 3)) << 4));
                a[4 * ks] = __byte_perm(w0, w1, 0x5410); a[4 * ks + 1] = __byte_perm(w0, w1, 0x7632);
                a[4 * ks + 2] = __byte_perm(w2, w3, 0x5410); a[4 * ks + 3] = __byte_perm(w2, w3, 0x7632);
            }
        }
        bar_sync(1, 256);
        bar_arrive(6, 288);
        BSTAMP(3);
#pragma unroll 1
        for (int na = 0, ng = 0, it = 144; ng < 16;) {
            if (bg_att_turn(na, ng)) {
                if (nt < 8) {
                    const int i0 = it + wg + 4 * (w >> 1), i1 = i0 + 2;
                    mbar_wait(sb + GB_FULL + 8 * (i0 % NST), (i0 / NST) & 1);
                    mbar_wait(sb + GB_FULL + 8 * (i1 % NST), (i1 / NST) & 1);
                    BSTAMP(8 + na * 4);
                    bg_attention(sb + G_RING + (i0 % NST) * 16384, sb + G_RING + (i1 % NST) * 16384, w & 1, lane);
                    fence_async_smem();
                    bar_arrive(7, 288);
                    bar_sync(1, 256);
                    BSTAMP(9 + na * 4);
                    it += 8;
                }
                na++;
            } else {
                bg_mainloop<8, 2>(d, a, sb, it + wg, lane);
                BSTAMP(10 + ng * 4);
                bg_epilogue<false>(d, sb, wg, w, lane, &tm_out, DM + 64 * nt, ng * 128, xa, Dk);
                BSTAMP(11 + ng * 4);
                it += 16; ng++;
            }
        }
    }
    asm volatile("griddepcontrol.wait;" ::: "memory");
}

typedef CUresult (*EncodeFn)(CUtensorMap*, CUtensorMapDataType, cuuint32_t, void*, const cuuint64_t*, const cuuint64_t*, const cuuint32_t*, const cuuint32_t*,
                             CUtensorMapInterleave, CUtensorMapSwizzle, CUtensorMapL2promotion, CUtensorMapFloatOOBfill);
}

extern "C" void kernel_launch(void* const* d_in, const int* in_sizes, int n_in, void* d_out, int out_size) {
    typedef const __nv_bfloat16* bp;
    bp Ax = (bp)d_in[0], Lre = (bp)d_in[1], Lim = (bp)d_in[2], Bre = (bp)d_in[3], Bim = (bp)d_in[4], Cre = (bp)d_in[5], Cim = (bp)d_in[6],
       logdt = (bp)d_in[7], Dk = (bp)d_in[8], Bx = (bp)d_in[9], mem0 = (bp)d_in[10], Wq = (bp)d_in[11], Wk = (bp)d_in[12], Wv = (bp)d_in[13], Wo = (bp)d_in[14];
    float* out = (float*)d_out;
    static EncodeFn enc = nullptr;
    if (!enc) {
        void* fn = nullptr; cudaDriverEntryPointQueryResult qr;
        cudaGetDriverEntryPoint("cuTensorMapEncodeTiled", &fn, cudaEnableDefault, &qr);
        enc = (EncodeFn)fn;
        cudaFuncSetAttribute(chain_kernel, cudaFuncAttributeMaxDynamicSharedMemorySize, CHAIN_SMEM);
        cudaFuncSetAttribute(bg_kernel, cudaFuncAttributeMaxDynamicSharedMemorySize, BG_SMEM);
    }
    const cuuint32_t es[5] = {1, 1, 1, 1, 1};
    auto map2d = [&](CUtensorMap* tm, CUtensorMapDataType dt, const void* p, cuuint64_t d0, cuuint64_t d1, cuuint64_t stride, cuuint32_t b0, cuuint32_t b1) {
        cuuint64_t gd[2] = {d0, d1}, gs[1] = {stride}; cuuint32_t bd[2] = {b0, b1};
        enc(tm, dt, 2, (void*)p, gd, gs, bd, es, CU_TENSOR_MAP_INTERLEAVE_NONE, CU_TENSOR_MAP_SWIZZLE_128B, CU_TENSOR_MAP_L2_PROMOTION_L2_128B,
            CU_TENSOR_MAP_FLOAT_OOB_FILL_NONE);
    };
    CUtensorMap tm_x, tm_q, tm_k, tm_v, tm_xa, tm_wo, tm_out;
    map2d(&tm_x, CU_TENSOR_MAP_DATA_TYPE_BFLOAT16, Bx, DM, SEQ, DM * 2, 64, 32);
    map2d(&tm_q, CU_TENSOR_MAP_DATA_TYPE_BFLOAT16, Wq, HD, DM, HD * 2, 64, 192);
    map2d(&tm_k, CU_TENSOR_MAP_DATA_TYPE_BFLOAT16, Wk, HD, DM, HD * 2, 64, 192);
    map2d(&tm_v, CU_TENSOR_MAP_DATA_TYPE_BFLOAT16, Wv, HD, DM, HD * 2, 64, 192);
    map2d(&tm_wo, CU_TENSOR_MAP_DATA_TYPE_BFLOAT16, Wo, DM, HD, DM * 2, 64, 256);
    map2d(&tm_out, CU_TENSOR_MAP_DATA_TYPE_FLOAT32, out, 2 * DM, SEQ, 2 * DM * 4, 32, 64);
    {
        cuuint64_t gd[5] = {DM, 2, 4, 16, 16}, gs[4] = {DM * 2, 32 * DM * 2, 2 * DM * 2, 128 * DM * 2}; cuuint32_t bd[5] = {64, 2, 4, 16, 1};
        enc(&tm_xa, CU_TENSOR_MAP_DATA_TYPE_BFLOAT16, 5, (void*)Ax, gd, gs, bd, es, CU_TENSOR_MAP_INTERLEAVE_NONE, CU_TENSOR_MAP_SWIZZLE_128B,
            CU_TENSOR_MAP_L2_PROMOTION_L2_128B, CU_TENSOR_MAP_FLOAT_OOB_FILL_NONE);
    }
    cudaStream_t st = cudaStreamPerThread;
    chain_kernel<<<96, 384, CHAIN_SMEM, st>>>(tm_x, tm_q, tm_k, tm_v, Bx, mem0, Wo);
    cudaLaunchConfig_t cfg = {};
    cfg.gridDim = dim3(36); cfg.blockDim = dim3(384); cfg.dynamicSmemBytes = BG_SMEM; cfg.stream = st;
    cudaLaunchAttribute at[1];
    at[0].id = cudaLaunchAttributeProgrammaticStreamSerialization; at[0].val.programmaticStreamSerializationAllowed = 1;
    cfg.attrs = at; cfg.numAttrs = 1;
    cudaLaunchKernelEx(&cfg, bg_kernel, tm_xa, tm_wo, tm_out, Ax, Lre, Lim, Bre, Bim, Cre, Cim, logdt, Dk);
}
```

```cpp
#include <cuda_runtime.h>
#include <cuda.h>
#include <cuda_bf16.h>
#include <cuda_fp16.h>
#include <stdint.h>

#define D_WAIT 740

#define RED_GAP 720
#define ACC_PF 1
#define QDEP 0
#define NBIG 13
#define BG_AHEAD 5

namespace {

constexpr int DM = 576, NH = 32, SEQ = 2048, NSEG = 64, HD = 4096;

__device__ uint4 g_acc_raw[64 * 96 * 16 + 131072];
__device__ uint4 g_ox[NH * 2 * SEQ * 8];
constexpr int REC = 30720;
__device__ uint4 g_qkv[NSEG * NH * (REC / 16)];
__device__ uint4 g_h[18 * SEQ * 8];
constexpr int NFLAG = 6144, F_QKV = 0, F_OX = 1024, F_H = 2048, F_OUT = 3072;
constexpr int NBLK = NBIG + (NSEG - 4 * NBIG) / 2;
__host__ __device__ constexpr int blk_seg0(int b) { return b < NBIG ? 4 * b : 2 * b + 2 * NBIG; }
__device__ unsigned g_flag[NFLAG];
__device__ unsigned g_ticket, g_ticket_bg;
__device__ unsigned long long g_norm[96];
#define BSTAMP(i) do {} while (0)

__device__ __forceinline__ uint32_t smem_u32(const void* p) { return (uint32_t)__cvta_generic_to_shared(p); }
__device__ __forceinline__ uint32_t mapa(uint32_t a, uint32_t r) { uint32_t o; asm("mapa.shared::cluster.u32 %0, %1, %2;" : "=r"(o) : "r"(a), "r"(r)); return o; }
__device__ __forceinline__ uint32_t mapa_v(uint32_t a, uint32_t r) { uint32_t o; asm volatile("mapa.shared::cluster.u32 %0, %1, %2;" : "=r"(o) : "r"(a), "r"(r)); return o; }
__device__ __forceinline__ unsigned clk() { unsigned long long c; asm volatile("mov.u64 %0, %%clock64;" : "=l"(c) :: "memory"); return (unsigned)c; }
__device__ __forceinline__ void mbar_init(uint32_t bar, uint32_t cnt) { asm volatile("mbarrier.init.shared::cta.b64 [%0], %1;" :: "r"(bar), "r"(cnt) : "memory"); }
__device__ __forceinline__ void mbar_expect(uint32_t bar, uint32_t bytes) { asm volatile("mbarrier.arrive.expect_tx.shared::cta.b64 _, [%0], %1;" :: "r"(bar), "r"(bytes) : "memory"); }
__device__ __forceinline__ void mbar_wait(uint32_t bar, uint32_t parity) {
    asm volatile("{\n.reg .pred p;\n.reg .u32 n;\nmov.u32 n, 0;\n"
                 "W_%=: mbarrier.try_wait.parity.shared::cta.b64 p, [%0], %1;\n@p bra.uni D_%=;\n"
                 "add.u32 n, n, 1;\nsetp.lt.u32 p, n, 4000000;\n@p bra.uni W_%=;\ntrap;\nD_%=:\n}" :: "r"(bar), "r"(parity) : "memory");
}
__device__ __forceinline__ void mbar_expect_if(uint32_t z, uint32_t bar, uint32_t bytes) {
    asm volatile("{\n.reg .pred p;\nsetp.eq.u32 p, %2, 0;\n@p mbarrier.arrive.expect_tx.shared::cta.b64 _, [%0], %1;\n}" :: "r"(bar), "r"(bytes), "r"(z) : "memory");
}
__device__ __forceinline__ void mbar_arrive_if(uint32_t z, uint32_t bar) {
    asm volatile("{\n.reg .pred p;\nsetp.eq.u32 p, %1, 0;\n@p mbarrier.arrive.shared::cta.b64 _, [%0];\n}" :: "r"(bar), "r"(z) : "memory");
}
__device__ __forceinline__ void sts32_if(uint32_t z, uint32_t a, uint32_t x) {
    asm volatile("{\n.reg .pred p;\nsetp.eq.u32 p, %2, 0;\n@p st.shared.u32 [%0], %1;\n}" :: "r"(a), "r"(x), "r"(z) : "memory");
}
template <int K> __device__ __forceinline__ void sched_fence(int v) {
    asm volatile("{\n.reg .pred p;\nsetp.ne.s32 p, %0, %1;\n@p bra.uni F_%=;\ntrap;\nF_%=:\n}" :: "r"(v), "n"(1000 + K) : "memory");
}
__device__ __forceinline__ void spin_until(unsigned t0, unsigned d) {
    asm volatile("{\n.reg .pred p;\n.reg .u64 c;\n.reg .u32 lo;\n"
                 "S_%=: mov.u64 c, %%clock64;\ncvt.u32.u64 lo, c;\nsub.u32 lo, lo, %0;\nsetp.lt.u32 p, lo, %1;\n@p bra.uni S_%=;\n}" :: "r"(t0), "r"(d) : "memory");
}
__device__ __forceinline__ void bar_sync(int id, int n) { asm volatile("bar.sync %0, %1;" :: "r"(id), "r"(n) : "memory"); }
__device__ __forceinline__ void bar_sync_sel(int sel, int id) {
    asm volatile("{\n.reg .pred p;\nsetp.eq.u32 p, %0, 0;\n@p bar.sync %1, %3;\n@!p bar.sync %2, %3;\n}" :: "r"(sel), "r"(id), "r"(id + 1), "n"(192) : "memory");
}
__device__ __forceinline__ void bar_arrive(int id, int n) { asm volatile("bar.arrive %0, %1;" :: "r"(id), "r"(n) : "memory"); }
__device__ __forceinline__ void fence_async_smem() { asm volatile("fence.proxy.async.shared::cta;" ::: "memory"); }
__device__ __forceinline__ uint32_t pack_bf16(float lo, float hi) { uint32_t r; asm("cvt.rn.bf16x2.f32 %0, %1, %2;" : "=r"(r) : "f"(hi), "f"(lo)); return r; }
__device__ __forceinline__ uint32_t pack_f16(float lo, float hi) { uint32_t r; asm("cvt.rn.f16x2.f32 %0, %1, %2;" : "=r"(r) : "f"(hi), "f"(lo)); return r; }
__device__ __forceinline__ uint32_t f16x2_to_bf16x2(uint32_t v) { float2 f = __half22float2(*reinterpret_cast<__half2*>(&v)); return pack_bf16(f.x, f.y); }
__device__ __forceinline__ uint32_t hmul2(uint32_t a, uint32_t b) { uint32_t r; asm("mul.rn.f16x2 %0, %1, %2;" : "=r"(r) : "r"(a), "r"(b)); return r; }
__device__ __forceinline__ float ex2(float x) { float y; asm("ex2.approx.ftz.f32 %0, %1;" : "=f"(y) : "f"(x)); return y; }
__device__ __forceinline__ float ex2v(float x) { float y; asm volatile("ex2.approx.ftz.f32 %0, %1;" : "=f"(y) : "f"(x)); return y; }
__device__ __forceinline__ uint32_t absmax2(uint32_t a, uint32_t b) {
    uint32_t r; asm("max.xorsign.abs.f16x2 %0, %1, %2;" : "=r"(r) : "r"(a), "r"(b)); return r;
}
__device__ __forceinline__ uint32_t shl_v(uint32_t a, int n) { return a << n; }
__device__ __forceinline__ uint32_t max3u(uint32_t a, uint32_t b, uint32_t c) { return max(max(a, b), c); }
__device__ __forceinline__ uint4 lds128(uint32_t a) { uint4 v; asm volatile("ld.shared.v4.u32 {%0,%1,%2,%3}, [%4];" : "=r"(v.x), "=r"(v.y), "=r"(v.z), "=r"(v.w) : "r"(a) : "memory"); return v; }
__device__ __forceinline__ uint4 lds128v(uint32_t a) { uint4 v; asm volatile("ld.volatile.shared.v4.u32 {%0,%1,%2,%3}, [%4];" : "=r"(v.x), "=r"(v.y), "=r"(v.z), "=r"(v.w) : "r"(a) : "memory"); return v; }
__device__ __forceinline__ float4 lds128f(uint32_t a) { float4 v; asm volatile("ld.shared.v4.f32 {%0,%1,%2,%3}, [%4];" : "=f"(v.x), "=f"(v.y), "=f"(v.z), "=f"(v.w) : "r"(a) : "memory"); return v; }
__device__ __forceinline__ float2 lds64f(uint32_t a) { float2 v; asm volatile("ld.shared.v2.f32 {%0,%1}, [%2];" : "=f"(v.x), "=f"(v.y) : "r"(a) : "memory"); return v; }
__device__ __forceinline__ uint4 lds64x2(uint32_t a) { uint4 v; asm volatile("ld.shared.v2.u32 {%0,%1}, [%4];\nld.shared.v2.u32 {%2,%3}, [%4+256];" : "=r"(v.x), "=r"(v.y), "=r"(v.z), "=r"(v.w) : "r"(a) : "memory"); return v; }
__device__ __forceinline__ uint32_t lds32(uint32_t a) { uint32_t v; asm volatile("ld.shared.u32 %0, [%1];" : "=r"(v) : "r"(a) : "memory"); return v; }
__device__ __forceinline__ void sts128(uint32_t a, uint32_t x, uint32_t y, uint32_t z, uint32_t w) { asm volatile("st.shared.v4.u32 [%0], {%1,%2,%3,%4};" :: "r"(a), "r"(x), "r"(y), "r"(z), "r"(w) : "memory"); }
__device__ __forceinline__ void sts128f(uint32_t a, float x, float y, float z, float w) { asm volatile("st.shared.v4.f32 [%0], {%1,%2,%3,%4};" :: "r"(a), "f"(x), "f"(y), "f"(z), "f"(w) : "memory"); }
__device__ __forceinline__ void sts64(uint32_t a, uint32_t x, uint32_t y) { asm volatile("st.shared.v2.u32 [%0], {%1,%2};" :: "r"(a), "r"(x), "r"(y) : "memory"); }
__device__ __forceinline__ void sts32(uint32_t a, uint32_t x) { asm volatile("st.shared.u32 [%0], %1;" :: "r"(a), "r"(x) : "memory"); }
__device__ __forceinline__ uint4 ldsm4(uint32_t a) { uint4 v; asm volatile("ldmatrix.sync.aligned.m8n8.x4.shared.b16 {%0,%1,%2,%3}, [%4];" : "=r"(v.x), "=r"(v.y), "=r"(v.z), "=r"(v.w) : "r"(a) : "memory"); return v; }
__device__ __forceinline__ void stsm2t(uint32_t a, uint32_t x, uint32_t y) { asm volatile("stmatrix.sync.aligned.m8n8.x2.trans.shared.b16 [%0], {%1,%2};" :: "r"(a), "r"(x), "r"(y) : "memory"); }
__device__ __forceinline__ void stsm4t(uint32_t a, uint32_t x, uint32_t y, uint32_t z, uint32_t w) { asm volatile("stmatrix.sync.aligned.m8n8.x4.trans.shared.b16 [%0], {%1,%2,%3,%4};" :: "r"(a), "r"(x), "r"(y), "r"(z), "r"(w) : "memory"); }
__device__ __forceinline__ void st_async64(uint32_t a, uint32_t x, uint32_t y, uint32_t bar) { asm volatile("st.async.shared::cluster.mbarrier::complete_tx::bytes.v2.b32 [%0], {%1,%2}, [%3];" :: "r"(a), "r"(x), "r"(y), "r"(bar) : "memory"); }
__device__ __forceinline__ void bulk_s2c(uint32_t dst, uint32_t src, uint32_t bytes, uint32_t bar) { asm volatile("cp.async.bulk.shared::cluster.shared::cta.mbarrier::complete_tx::bytes [%0], [%1], %2, [%3];" :: "r"(dst), "r"(src), "r"(bytes), "r"(bar) : "memory"); }
__device__ __forceinline__ void bulk_s2g(void* dst, uint32_t src, uint32_t bytes) { asm volatile("cp.async.bulk.global.shared::cta.bulk_group [%0], [%1], %2;" :: "l"(dst), "r"(src), "r"(bytes) : "memory"); }
__device__ __forceinline__ uint32_t ldg_nc32(const void* p) { uint32_t v; asm volatile("ld.global.nc.L2::128B.u32 %0, [%1];" : "=r"(v) : "l"(p)); return v; }
__device__ __forceinline__ uint4 ldg_relaxed128(const void* p) { uint4 v; asm volatile("ld.relaxed.gpu.global.v4.u32 {%0,%1,%2,%3}, [%4];" : "=r"(v.x), "=r"(v.y), "=r"(v.z), "=r"(v.w) : "l"(p) : "memory"); return v; }
__device__ __forceinline__ void mma16816(float (&d)[4], uint32_t a0, uint32_t a1, uint32_t a2, uint32_t a3, uint32_t b0, uint32_t b1) {
    asm volatile("mma.sync.aligned.m16n8k16.row.col.f32.bf16.bf16.f32 {%0,%1,%2,%3}, {%4,%5,%6,%7}, {%8,%9}, {%0,%1,%2,%3};"
        : "+f"(d[0]), "+f"(d[1]), "+f"(d[2]), "+f"(d[3]) : "r"(a0), "r"(a1), "r"(a2), "r"(a3), "r"(b0), "r"(b1));
}
__device__ __forceinline__ void mma16816_z(float (&d)[4], uint32_t a0, uint32_t a1, uint32_t a2, uint32_t a3, uint32_t b0, uint32_t b1) {
    asm volatile("mma.sync.aligned.m16n8k16.row.col.f32.bf16.bf16.f32 {%0,%1,%2,%3}, {%4,%5,%6,%7}, {%8,%9}, {%10,%10,%10,%10};"
        : "=f"(d[0]), "=f"(d[1]), "=f"(d[2]), "=f"(d[3]) : "r"(a0), "r"(a1), "r"(a2), "r"(a3), "r"(b0), "r"(b1), "f"(0.f));
}
__device__ __forceinline__ void mma1688(float (&d)[4], uint32_t a0, uint32_t a1, uint32_t b0) {
    asm volatile("mma.sync.aligned.m16n8k8.row.col.f32.bf16.bf16.f32 {%0,%1,%2,%3}, {%4,%5}, {%6}, {%0,%1,%2,%3};"
        : "+f"(d[0]), "+f"(d[1]), "+f"(d[2]), "+f"(d[3]) : "r"(a0), "r"(a1), "r"(b0));
}
__device__ __forceinline__ void mma1688_z(float (&d)[4], uint32_t a0, uint32_t a1, uint32_t b0) {
    asm volatile("mma.sync.aligned.m16n8k8.row.col.f32.bf16.bf16.f32 {%0,%1,%2,%3}, {%4,%5}, {%6}, {%7,%7,%7,%7};"
        : "=f"(d[0]), "=f"(d[1]), "=f"(d[2]), "=f"(d[3]) : "r"(a0), "r"(a1), "r"(b0), "f"(0.f));
}
template <int ACC>
__device__ __forceinline__ void wgmma_n32_rs(float (&d)[16], uint32_t a0, uint32_t a1, uint32_t a2, uint32_t a3, uint64_t desc) {
    asm volatile("wgmma.mma_async.sync.aligned.m64n32k16.f32.bf16.bf16 {%0,%1,%2,%3,%4,%5,%6,%7,%8,%9,%10,%11,%12,%13,%14,%15}, {%16,%17,%18,%19}, %20, %21, 1, 1, 0;"
        : "+f"(d[0]), "+f"(d[1]), "+f"(d[2]), "+f"(d[3]), "+f"(d[4]), "+f"(d[5]), "+f"(d[6]), "+f"(d[7]),
          "+f"(d[8]), "+f"(d[9]), "+f"(d[10]), "+f"(d[11]), "+f"(d[12]), "+f"(d[13]), "+f"(d[14]), "+f"(d[15])
        : "r"(a0), "r"(a1), "r"(a2), "r"(a3), "l"(desc), "n"(ACC));
}
template <int ACC>
__device__ __forceinline__ void wgmma_n32_ss(float (&d)[16], uint64_t da, uint64_t db) {
    asm volatile("wgmma.mma_async.sync.aligned.m64n32k16.f32.bf16.bf16 {%0,%1,%2,%3,%4,%5,%6,%7,%8,%9,%10,%11,%12,%13,%14,%15}, %16, %17, %18, 1, 1, 0, 0;"
        : "+f"(d[0]), "+f"(d[1]), "+f"(d[2]), "+f"(d[3]), "+f"(d[4]), "+f"(d[5]), "+f"(d[6]), "+f"(d[7]),
          "+f"(d[8]), "+f"(d[9]), "+f"(d[10]), "+f"(d[11]), "+f"(d[12]), "+f"(d[13]), "+f"(d[14]), "+f"(d[15])
        : "l"(da), "l"(db), "n"(ACC));
}
__device__ __forceinline__ void wg_fence() { asm volatile("wgmma.fence.sync.aligned;" ::: "memory"); }
__device__ __forceinline__ void wg_commit() { asm volatile("wgmma.commit_group.sync.aligned;" ::: "memory"); }
__device__ __forceinline__ void wg_wait0() { asm volatile("wgmma.wait_group.sync.aligned 0;" ::: "memory"); }
__device__ __forceinline__ void cluster_sync() { asm volatile("barrier.cluster.arrive.aligned;\nbarrier.cluster.wait.aligned;" ::: "memory"); }

#define STAMP(s, i) do {} while (0)
#define STAMPV(s, i, v) do {} while (0)

constexpr int XT_BYTES = 36864;
constexpr int O_XT = 0;
constexpr int O_STG = XT_BYTES;
constexpr int O_AS = 3 * XT_BYTES;
constexpr int O_XP = O_AS + 16384;
constexpr int O_QKX = O_XP + 8192;
constexpr int O_KM = O_QKX + 8192;
constexpr int O_QM = O_QKX + 10240;
constexpr int O_VX = O_STG + 147456;
constexpr int O_VM = O_VX + 16384;
constexpr int O_SC = O_VM + 2048;
constexpr int O_OF = O_SC + 2560;
constexpr int O_AF = O_OF + 2048;
constexpr int O_WP = O_AF + 4096;
constexpr int O_MF = O_WP + 2048;
constexpr int O_MISC = O_MF + 9216;
static_assert(O_QKX + 24576 <= O_VX, "smem");
constexpr int O_BAR = O_MISC + 64;
constexpr int CHAIN_SMEM = O_BAR + 128;
static_assert(CHAIN_SMEM <= 232448, "smem");
constexpr int B_X = O_BAR, B_VX = O_BAR + 24, B_SC = O_BAR + 40, B_W = O_BAR + 48;
constexpr float SM_SCALE = 0.08838834764831845f * 1.4426950408889634f;
constexpr uint32_t ONES = 0x3f803f80u;

__device__ __forceinline__ uint32_t opaque(uint32_t v) { uint32_t o; asm volatile("mov.u32 %0, %1;" : "=r"(o) : "r"(v)); return o; }
__device__ __forceinline__ void st_async128(uint32_t a, uint32_t x, uint32_t y, uint32_t z, uint32_t w, uint32_t bar) {
    asm volatile("st.async.shared::cluster.mbarrier::complete_tx::bytes.v4.b32 [%0], {%1,%2,%3,%4}, [%5];" :: "r"(a), "r"(x), "r"(y), "r"(z), "r"(w), "r"(bar) : "memory");
}
__device__ __forceinline__ void tma_x_tile(uint32_t sb, const CUtensorMap* tm, int r, int j, int slot) {
    asm volatile("{\n.reg .pred p;\nelect.sync _|p, 0xffffffff;\n"
        "@p mbarrier.arrive.expect_tx.shared::cta.b64 _, [%2], 36864;\n"
        "@p cp.async.bulk.tensor.2d.shared::cluster.global.mbarrier::complete_tx::bytes.multicast::cluster [%0], [%1, {%3, %4}], [%2], %7;\n"
        "@p cp.async.bulk.tensor.2d.shared::cluster.global.mbarrier::complete_tx::bytes.multicast::cluster [%0+4096], [%1, {%5, %4}], [%2], %7;\n"
        "@p cp.async.bulk.tensor.2d.shared::cluster.global.mbarrier::complete_tx::bytes.multicast::cluster [%0+8192], [%1, {%6, %4}], [%2], %7;\n}"
        :: "r"(sb + O_XT + slot * XT_BYTES + 3 * r * 4096), "l"(tm), "r"(sb + B_X + 8 * slot), "r"(192 * r), "r"(j * 32), "r"(192 * r + 64), "r"(192 * r + 128),
           "h"((unsigned short)7) : "memory");
}
__device__ __forceinline__ void flag_inc_if(uint32_t z, unsigned* p) {
    asm volatile("{\n.reg .pred p;\nsetp.eq.u32 p, %1, 0;\n@p red.release.gpu.global.inc.u32 [%0], 0xfffffffe;\n}" :: "l"(p), "r"(z) : "memory");
}
__device__ __forceinline__ float quad_max(float v) {
    const float a = __shfl_xor_sync(~0u, v, 1), b = __shfl_xor_sync(~0u, v, 2), c = __shfl_xor_sync(~0u, v, 3);
    return fmaxf(fmaxf(v, a), fmaxf(b, c));
}
__device__ __forceinline__ void load_scores(float (&p)[10], uint32_t base, uint32_t stride, uint32_t l16) {
    const float4 a0 = lds128f(base + l16), b0 = lds128f(base + stride + l16);
    const float4 a1 = lds128f(base + 512 + l16), b1 = lds128f(base + stride + 512 + l16);
    const float2 a2 = lds64f(base + 1024 + (l16 >> 1)), b2 = lds64f(base + stride + 1024 + (l16 >> 1));
    p[0] = a2.x + b2.x; p[1] = a2.y + b2.y;
    p[2] = a0.x + b0.x; p[3] = a0.y + b0.y; p[4] = a0.z + b0.z; p[5] = a0.w + b0.w;
    p[6] = a1.x + b1.x; p[7] = a1.y + b1.y; p[8] = a1.z + b1.z; p[9] = a1.w + b1.w;
}
__device__ __forceinline__ float rcp_fast(float x) { float y; asm("rcp.approx.ftz.f32 %0, %1;" : "=f"(y) : "f"(x)); return y; }

__global__ void __cluster_dims__(3, 1, 1) __launch_bounds__(384, 1)
chain_kernel(const __grid_constant__ CUtensorMap tm_x, const __grid_constant__ CUtensorMap tm_q,
             const __grid_constant__ CUtensorMap tm_k, const __grid_constant__ CUtensorMap tm_v,
             const __nv_bfloat16* __restrict__ x, const __nv_bfloat16* __restrict__ mem0,
             const __nv_bfloat16* __restrict__ Wo) {
    extern __shared__ __align__(1024) uint8_t smem_raw[];
    const uint32_t sb = smem_u32(smem_raw);
    const int lane = threadIdx.x & 31;
    const int warp = __shfl_sync(~0u, threadIdx.x >> 5, 0);
    const int wg = warp >> 2, w = warp & 3;
    const int h = blockIdx.x / 3, r = blockIdx.x - 3 * h;
    uint4* const g_acc = reinterpret_cast<uint4*>((reinterpret_cast<uintptr_t>(g_acc_raw) + 0x1fffff) & ~(uintptr_t)0x1fffff);

#define PSTAMP(i) do {} while (0)
    if (threadIdx.x == 0) {
        if (sb & 1023u) __trap();
        for (int i = 0; i < 9; i++) mbar_init(sb + O_BAR + 8 * i, 1);
        asm volatile("fence.mbarrier_init.release.cluster;" ::: "memory");
        for (int i = 0; i < 3; i++) {
            mbar_expect(sb + B_W + 8 * i, 49152);
            for (int tl = 0; tl < 2; tl++)
                asm volatile("cp.async.bulk.tensor.2d.shared::cluster.global.mbarrier::complete_tx::bytes [%0], [%1, {%3, %4}], [%2];"
                    :: "r"(sb + O_STG + tl * 73728 + i * 24576), "l"(r < 2 ? (tl ? &tm_k : &tm_q) : &tm_v), "r"(sb + B_W + 8 * i),
                       "r"(h * 128 + 64 * (r < 2 ? r : tl)), "r"(192 * i) : "memory");
        }
    }
    __syncwarp();
    asm volatile("barrier.cluster.arrive.relaxed.aligned;" ::: "memory");
    asm volatile("griddepcontrol.launch_dependents;" ::: "memory");
    if (warp == 0) PSTAMP(9);
    const uint32_t l16c = __shfl_sync(~0u, lane * 16, lane);

    if (wg < 2) {
#define KS(u) ((u) < 8 ? 12 * ((u) >> 2) + (((u) >> 1) & 1) + 4 * ((u) & 1) : (u) < 12 ? (u) : (u) < 16 ? (u) + 8 : (u) < 24 ? 24 + (((u) - 16) >> 1) + 4 * ((u) & 1) : (u) + 8)
        asm volatile("setmaxnreg.inc.sync.aligned.u32 184;");
        uint32_t a[144];
        uint32_t adr1;
        {
            const int g = lane >> 2, t = lane & 3;
            const int t1 = threadIdx.x;
#pragma unroll
            for (int i = 0; i < 2; i++) g_acc[(blockIdx.x * 64 + i * 32 + (t1 >> 3)) * 16 + (t1 & 7)] = make_uint4(0, 0, 0, 0);
            __threadfence();
            asm volatile("barrier.cluster.wait.aligned;" ::: "memory");
            const uint32_t ev = sb + O_STG + (2 * t) * 128 + (((2 * w + (g >> 2)) ^ (2 * t)) << 4) + (g & 3) * 4;
            const uint32_t od = (ev ^ 16) + 128;
            auto gather = [&](int dst, uint32_t off) {
                a[dst] = lds32(ev + off); a[dst + 1] = lds32(od + off); a[dst + 2] = lds32(ev + off + 1024); a[dst + 3] = lds32(od + off + 1024);
            };
            const uint4* xp = reinterpret_cast<const uint4*>(x) + blockIdx.x * 1536 + t1;
            uint4 xv[6];
#pragma unroll
            for (int th = 0; th < 2; th++) {
                mbar_wait(sb + B_W + 8 * th, 0);
                if (th == 1) {
#pragma unroll
                    for (int i = 0; i < 6; i++) xv[i] = __ldg(xp + i * 256);
                }
#pragma unroll
                for (int u = 4 * th; u < 4 * th + 4; u++) {
                    gather(32 + 4 * u, wg * (73728 + 4096) + KS(u) * 2048);
                    gather(4 * u, 73728 - wg * (73728 - 4096) + KS(u) * 2048);
                    gather(64 + 4 * u, wg * 73728 + KS(8 + u) * 2048);
                }
            }
            mbar_wait(sb + B_W + 16, 0);
#pragma unroll
            for (int u = 16; u < 28; u++) gather(32 + 4 * u, wg * 73728 + KS(u) * 2048);
#pragma unroll
            for (int kk = 0; kk < 72; kk++) {
                uint32_t w0 = a[2 * kk], w1 = a[2 * kk + 1];
                a[2 * kk] = __byte_perm(w0, w1, 0x5410);
                a[2 * kk + 1] = __byte_perm(w0, w1, 0x7632);
            }
            if (r == 2) {
                float n0[4], n1[4];
#pragma unroll
                for (int u = 0; u < 36; u++) {
                    const uint32_t x0 = a[4 * u] & 0x7fff7fffu, x1 = a[4 * u + 1] & 0x7fff7fffu, x2 = a[4 * u + 2] & 0x7fff7fffu, x3 = a[4 * u + 3] & 0x7fff7fffu;
                    if (u == 0) mma16816_z(n0, x0, x1, x2, x3, ONES, ONES);
                    else if (u < 8) mma16816(n0, x0, x1, x2, x3, ONES, ONES);
                    else if (u == 8) mma16816_z(n1, x0, x1, x2, x3, ONES, ONES);
                    else mma16816(n1, x0, x1, x2, x3, ONES, ONES);
                }
                const uint32_t mx = __reduce_max_sync(~0u, __float_as_uint(2.f * fmaxf(fmaxf(n0[0], n0[2]), fmaxf(n1[0], n1[2]))));
                sts32_if(lane, sb + O_MISC + 32 + 4 * warp, mx);
            }
            uint32_t xm = 0;
#pragma unroll
            for (int i = 0; i < 6; i++)
                xm = __vmaxu2(xm, __vmaxu2(__vmaxu2(xv[i].x & 0x7fff7fffu, xv[i].y & 0x7fff7fffu), __vmaxu2(xv[i].z & 0x7fff7fffu, xv[i].w & 0x7fff7fffu)));
            sts32_if(lane, sb + O_OF + 16 + 4 * warp, __reduce_max_sync(~0u, max(xm << 16, xm & 0xffff0000u)));
            if (warp == 0) PSTAMP(11);
            bar_arrive(7, 384);
            asm volatile("barrier.cluster.arrive.relaxed.aligned;" ::: "memory");
            bar_sync(1, 256);
            const uint32_t as = sb + O_AS + wg * 8192 + (16 * w + g) * 128 + t * 4;
            sts32(as + (g << 4), a[32]);
            sts32(as + 1024 + (g << 4), a[33]);
            sts32(as + ((1 ^ g) << 4), a[34]);
            sts32(as + 1024 + ((1 ^ g) << 4), a[35]);
            sts128(sb + O_AF + warp * 512 + lane * 16, a[32], a[33], a[34], a[35]);
            fence_async_smem();
            bar_sync(1, 256);
            const uint32_t l = lane * 16;
            const int mi = lane >> 3, isk = (mi >> 1) ? wg : (wg ^ 1);
            adr1 = (r == 2) ? (sb + O_VM + warp * 256 + (l >> 1))
                            : (isk ? (sb + O_KM + w * 512 + wg * 256 + (mi & 1) * 128 + (l & 127))
                                   : (sb + O_QM + w * 512 + (mi & 1) * 256 + wg * 128 + (l & 127)));
            adr1 = __shfl_sync(~0u, adr1, lane);
        }
        int s3 = 2;
#pragma unroll 1
        for (int s = -1; s < NSEG; s++) {
            const uint32_t l16 = opaque(l16c);
            s3 = (s3 == 2) ? 0 : s3 + 1;
            if (s < 0) mbar_wait(sb + B_X, 0);
            const uint64_t desc0 = (uint64_t)(((sb + O_XT + s3 * XT_BYTES) & 0x3FFFF) >> 4) | (1ull << 16) | (64ull << 32) | (1ull << 62);
            uint32_t km0 = 0, km1 = 0;
            if (s >= 0) {
                { const uint4 v = lds128(sb + O_AF + warp * 512 + l16); a[32] = v.x; a[33] = v.y; a[34] = v.z; a[35] = v.w; }
                float co[4], cw[3][4];
                uint4 b[14];
                float inv;
#define GORD(i) ((i) < 8 ? 2 * ((i) >> 2) + (((i) >> 1) & 1) + 4 * ((i) & 1) : (i))
                auto qkv_mma = [&](int i) {
                    const int gi = GORD(i), u = 8 * gi, n0 = 2 * i, n1 = 2 * i + 1;
                    if (gi < 4) {
                        if (i == 0) mma16816_z(co, a[u], a[u + 1], a[u + 2], a[u + 3], b[0].x, b[0].y);
                        else mma16816(co, a[u], a[u + 1], a[u + 2], a[u + 3], b[i].x, b[i].y);
                    }
                    if (n0 < 3) mma16816_z(cw[n0 % 3], a[32 + u], a[32 + u + 1], a[32 + u + 2], a[32 + u + 3], b[i].x, b[i].y);
                    else mma16816(cw[n0 % 3], a[32 + u], a[32 + u + 1], a[32 + u + 2], a[32 + u + 3], b[i].x, b[i].y);
                    if (n1 < 3) mma16816_z(cw[n1 % 3], a[32 + u + 4], a[32 + u + 5], a[32 + u + 6], a[32 + u + 7], b[i].z, b[i].w);
                    else mma16816(cw[n1 % 3], a[32 + u + 4], a[32 + u + 5], a[32 + u + 6], a[32 + u + 7], b[i].z, b[i].w);
                    if (gi < 4) mma16816(co, a[u + 4], a[u + 5], a[u + 6], a[u + 7], b[i].z, b[i].w);
                };
                const uint32_t mf = sb + O_MF + l16, mfs = mf + wg * 1024;
                const uint32_t qb = (s & 1) * 12288;
                bar_sync(2, 384);
                if (warp == 0) STAMP(s, 0);
                auto qkv_ld = [&](int i) {
                    const int gi = GORD(i);
                    b[i] = gi < 4 ? lds128v(mfs + (gi >> 1) * 3072 + (gi & 1) * 512) : lds128v(mf + (gi < 6 ? gi : gi + 4) * 512);
                };
#pragma unroll
                for (int i = 0; i < 4; i++) qkv_ld(i);
                qkv_mma(0); qkv_mma(1); qkv_mma(2);
                const uint32_t z0 = __float_as_uint(QDEP ? co[0] : cw[1][0]) & (l16 & 15u);
                qkv_mma(3);
                bar_sync(15, 384);
                b[4] = lds128v(mfs + 3072 + z0);
#pragma unroll
                for (int i = 5; i < 9; i++) qkv_ld(i);
#pragma unroll
                for (int i = 4; i < 9; i++) { qkv_mma(i); qkv_ld(5 + i); }
                asm volatile("ld.volatile.shared.f32 %0, [%1];" : "=f"(inv) : "r"(sb + O_MISC) : "memory");
#pragma unroll
                for (int i = 9; i < 14; i++) qkv_mma(i);
#pragma unroll
                for (int i = 0; i < 4; i++) cw[0][i] += cw[1][i] + cw[2][i];
                if (r < 2) {
                    const uint32_t o0 = pack_bf16(co[0] * inv, co[1] * inv), o1 = pack_bf16(co[2] * inv, co[3] * inv);
                    const uint32_t w0 = pack_bf16(cw[0][0] * inv, cw[0][1] * inv), w1 = pack_bf16(cw[0][2] * inv, cw[0][3] * inv);
                    stsm4t(adr1 + qb, o0, o1, w0, w1);
                    if (warp == 0) STAMP(s, 1);
                    asm volatile("{\n.reg .pred p;\nsetp.ge.u32 p, %0, 3;\n@p bar.arrive 1, 256;\n}" :: "r"(warp) : "memory");
                    auto scores = [&](float (&v)[4], const uint4 (&q)[4], const uint4 (&k)[4]) {
                        float s0[4], s1[4], t0[4], t1[4];
                        mma16816_z(s0, q[0].x, q[0].y, q[0].z, q[0].w, k[0].x, k[0].y);
                        mma16816_z(s1, q[0].x, q[0].y, q[0].z, q[0].w, k[0].z, k[0].w);
                        mma16816_z(t0, q[1].x, q[1].y, q[1].z, q[1].w, k[1].x, k[1].y);
                        mma16816_z(t1, q[1].x, q[1].y, q[1].z, q[1].w, k[1].z, k[1].w);
                        mma16816(s0, q[2].x, q[2].y, q[2].z, q[2].w, k[2].x, k[2].y);
                        mma16816(s1, q[2].x, q[2].y, q[2].z, q[2].w, k[2].z, k[2].w);
                        mma16816(t0, q[3].x, q[3].y, q[3].z, q[3].w, k[3].x, k[3].y);
                        mma16816(t1, q[3].x, q[3].y, q[3].z, q[3].w, k[3].z, k[3].w);
                        v[0] = (s0[0] + s0[2]) + (t0[0] + t0[2]); v[1] = (s0[1] + s0[3]) + (t0[1] + t0[3]);
                        v[2] = (s1[0] + s1[2]) + (t1[0] + t1[2]); v[3] = (s1[1] + s1[3]) + (t1[1] + t1[3]);
                    };
                    if (warp < 2) {
                        uint4 q[4], k[4]; float v[4];
#pragma unroll
                        for (int i = 0; i < 4; i++) k[i] = ldsm4(sb + O_QKX + 4096 + qb + warp * 2048 + i * 512 + l16);
                        bar_sync(1, 256);
#pragma unroll
                        for (int i = 0; i < 4; i++) q[i] = ldsm4(sb + O_QM + qb + i * 512 + l16);
                        scores(v, q, k);
                        const uint32_t dst = sb + O_SC + r * 1280 + warp * 512 + l16;
                        st_async128(mapa(dst, 2), __float_as_uint(v[0]), __float_as_uint(v[1]), __float_as_uint(v[2]), __float_as_uint(v[3]), mapa(sb + B_SC, 2));
                        st_async128(mapa(dst, r ^ 1), __float_as_uint(v[0]), __float_as_uint(v[1]), __float_as_uint(v[2]), __float_as_uint(v[3]), mapa(sb + B_SC, r ^ 1));
                        st_async128(mapa(dst, r), __float_as_uint(v[0]), __float_as_uint(v[1]), __float_as_uint(v[2]), __float_as_uint(v[3]), mapa(sb + B_SC, r));
                    } else if (warp == 2) {
                        uint4 q[4], k[4]; float v[4];
                        bar_sync(1, 256);
#pragma unroll
                        for (int i = 0; i < 4; i++) { q[i] = ldsm4(sb + O_QM + qb + i * 512 + l16); k[i] = ldsm4(sb + O_KM + qb + i * 512 + l16); }
                        scores(v, q, k);
                        const uint32_t dst = sb + O_SC + r * 1280 + 1024 + (l16 >> 1);
                        st_async64(mapa(dst, 2), __float_as_uint(v[0] + v[2]), __float_as_uint(v[1] + v[3]), mapa(sb + B_SC, 2));
                        st_async64(mapa(dst, r ^ 1), __float_as_uint(v[0] + v[2]), __float_as_uint(v[1] + v[3]), mapa(sb + B_SC, r ^ 1));
                        st_async64(mapa(dst, r), __float_as_uint(v[0] + v[2]), __float_as_uint(v[1] + v[3]), mapa(sb + B_SC, r));
                        STAMP(s, 2);
                    }
                } else {
                    sts128f(sb + O_XP + warp * 512 + l16, co[0], co[1], co[2], co[3]);
                    bar_sync(8 + w, 64);
                    const float4 o = lds128f(sb + O_XP + (warp ^ 4) * 512 + l16);
                    km0 = pack_bf16((cw[0][0] + o.x) * inv, (cw[0][1] + o.y) * inv);
                    km1 = pack_bf16((cw[0][2] + o.z) * inv, (cw[0][3] + o.w) * inv);
                    if (warp == 0) STAMP(s, 1);
                    st_async64(mapa(adr1, 0), km0, km1, mapa(sb + B_SC, 0));
                    st_async64(mapa(adr1, 1), km0, km1, mapa(sb + B_SC, 1));
                    st_async64(mapa(adr1, 2), km0, km1, mapa(sb + B_SC, 2));
                    if (warp == 0) STAMP(s, 2);
                }
            }
            if (s >= 0) bar_sync(3, 384);
            auto store_qk = [&]() {
                asm volatile("{\n.reg .pred p;\nelect.sync _|p, 0xffffffff;\n"
                    "@p cp.async.bulk.global.shared::cta.bulk_group [%0], [%1], 10240;\n@p cp.async.bulk.commit_group;\n}"
                    :: "l"(reinterpret_cast<char*>(g_qkv) + (size_t)(s * NH + h) * REC + r * 10240), "r"(sb + O_QKX + (s & 1) * 12288) : "memory");
            };
            auto store_vm = [&]() {
                *reinterpret_cast<uint2*>(reinterpret_cast<char*>(g_qkv) + (size_t)(s * NH + h) * REC + 28672 + warp * 256 + (l16 >> 1)) = make_uint2(km0, km1);
            };
            if (s == NSEG - 1) {
                if (r == 2) store_vm();
                else if (warp == 3) {
                    fence_async_smem();
                    store_qk();
                    asm volatile("cp.async.bulk.wait_group 0;\nfence.proxy.async.global;" ::: "memory");
                }
            } else {
                const int j = s + 1;
#define XDESC(u) (((u) < 8 ? descs : desc0) + (uint64_t)(((KS(u) >> 2) * 4096 + (KS(u) & 3) * 32) >> 4))
                const uint64_t descs = desc0 + (uint64_t)(wg * 4);
                float d[16];
                wg_fence();
#pragma unroll
                for (int u = 0; u < 8; u++) {
                    if (u == 0) wgmma_n32_rs<0>(d, a[0], a[1], a[2], a[3], XDESC(0));
                    else wgmma_n32_rs<1>(d, a[4 * u], a[4 * u + 1], a[4 * u + 2], a[4 * u + 3], XDESC(u));
                }
                wg_commit();
                wg_wait0();
                if (warp == 0) STAMP(s, 15);
                if (warp == 3) asm volatile("cp.async.bulk.wait_group.read 0;" ::: "memory");
                if (s >= 0) bar_sync(4, 384);
#pragma unroll
                for (int q = 0; q < 2; q++)
                    sts128(sb + O_XP + warp * 1024 + q * 512 + l16, pack_bf16(d[8 * q], d[8 * q + 1]), pack_bf16(d[8 * q + 2], d[8 * q + 3]),
                           pack_bf16(d[8 * q + 4], d[8 * q + 5]), pack_bf16(d[8 * q + 6], d[8 * q + 7]));
                bar_sync(12, 256);
#pragma unroll
                for (int q = 0; q < 2; q++) {
                    const uint4 o = lds128(sb + O_XP + (warp ^ 4) * 1024 + q * 512 + l16);
                    d[8 * q] = __uint_as_float(o.x << 16); d[8 * q + 1] = __uint_as_float(o.x & 0xffff0000u);
                    d[8 * q + 2] = __uint_as_float(o.y << 16); d[8 * q + 3] = __uint_as_float(o.y & 0xffff0000u);
                    d[8 * q + 4] = __uint_as_float(o.z << 16); d[8 * q + 5] = __uint_as_float(o.z & 0xffff0000u);
                    d[8 * q + 6] = __uint_as_float(o.w << 16); d[8 * q + 7] = __uint_as_float(o.w & 0xffff0000u);
                }
                if (s >= 0) {
                    if (r == 2) store_vm();
                    if (warp == 5 && s + 2 < NSEG) tma_x_tile(sb, &tm_x, r, s + 2, s3 == 2 ? 0 : s3 + 1);
                    if (warp == 3) {
                        asm volatile("cp.async.bulk.wait_group 0;\nfence.proxy.async.global;" ::: "memory");
                        if (s >= 4 && !(s & (s > 4 * NBIG ? 1 : 3))) {
                            __syncwarp();
                            flag_inc_if(l16, &g_flag[F_QKV + ((s > 4 * NBIG ? 2 * s - 4 * NBIG : s) - 4 + (h >> 3)) * 8]);
                        }
                        fence_async_smem();
                    }
                    asm volatile("{\n.reg .pred p;\nsetp.eq.u32 p, %0, 0;\n@p bar.sync 5, 256;\n@!p bar.sync 13, 256;\n}" :: "r"(wg) : "memory");
                }
                const uint64_t da0 = (uint64_t)(((sb + O_AS + wg * 8192) & 0x3FFFF) >> 4) | (1ull << 16) | (64ull << 32) | (1ull << 62);
                wg_fence();
                wgmma_n32_ss<1>(d, da0, XDESC(0));
#pragma unroll
                for (int u = 1; u < 28; u++) wgmma_n32_rs<1>(d, a[32 + 4 * u], a[32 + 4 * u + 1], a[32 + 4 * u + 2], a[32 + 4 * u + 3], XDESC(u));
                wg_commit();
                wg_wait0();
                if (warp == 3 && r < 2 && s >= 0) store_qk();
                if (warp == 4) STAMP(s, 3);
                uint32_t e[8];
#pragma unroll
                for (int i = 0; i < 8; i++) e[i] = pack_bf16(d[2 * i], d[2 * i + 1]);
                if (r < 2) {
                    const uint32_t base = sb + O_QKX + (j & 1) * 12288 + wg * 4096 + w * 512 + l16;
                    stsm4t(base, e[0], wg ? e[1] : e[2], wg ? e[2] : e[1], e[3]);
                    stsm4t(base + 2048, e[4], wg ? e[5] : e[6], wg ? e[6] : e[5], e[7]);
                } else {
                    const uint32_t base = sb + O_VX + (j & 1) * 8192 + warp * 1024 + l16;
                    sts128(base, e[0], e[1], e[2], e[3]);
                    sts128(base + 512, e[4], e[5], e[6], e[7]);
                    bar_arrive(14, 288);
                }
                if (warp == 7) STAMP(s, 4);
                if (s < 0) asm volatile("barrier.cluster.wait.aligned;" ::: "memory");
            }
        }
        bar_arrive(7, 384);
    } else {
        asm volatile("setmaxnreg.dec.sync.aligned.u32 136;");
        const int c = w;
        uint32_t a[96];
        uint32_t mmax = 0;
        {
            const int g = lane >> 2, t = lane & 3;
            uint32_t tag = 0, m0v[18];
            if (threadIdx.x == 256) tag = atomicAdd(&g_ticket, 1u);
#pragma unroll
            for (int i = 0; i < 9; i++) {
                const uint32_t* p = reinterpret_cast<const uint32_t*>(mem0 + g * DM + 16 * (4 * i + c) + 2 * t);
                m0v[2 * i] = __ldg(p); m0v[2 * i + 1] = __ldg(p + 4);
            }
            asm volatile("barrier.cluster.wait.aligned;" ::: "memory");
            if (c == 0) {
                tma_x_tile(sb, &tm_x, r, 0, 0);
                mbar_expect_if(lane, sb + B_SC, 4608);
                if (r < 2) mbar_expect_if(lane, sb + B_VX, 8192);
                sts32_if(lane, sb + O_MISC, __float_as_uint(1.0f));
                sts32_if(lane, sb + O_MISC + 12, __float_as_uint(SM_SCALE));
            }
            asm volatile("barrier.cluster.arrive.relaxed.aligned;" ::: "memory");
#pragma unroll
            for (int tau = 0; tau < 3; tau++) {
                const uint32_t* v = m0v + 6 * tau;
                sts128(sb + O_MF + tau * 3072 + c * 512 + lane * 16, v[0], v[1], v[2], v[3]);
                sts64(sb + O_MF + tau * 3072 + 2048 + (c >> 1) * 512 + lane * 16 + (c & 1) * 8, v[4], v[5]);
#pragma unroll
                for (int i = 0; i < 6; i++) mmax = __vmaxu2(mmax, v[i] & 0x7fff7fffu);
            }
            mmax = max(mmax << 16, mmax & 0xffff0000u);
            bar_arrive(2, 384); bar_arrive(15, 384);
            tag = (__shfl_sync(~0u, tag, 0) / 96u + 1u) & 0xffffu;
            mbar_wait(sb + B_W + 0, 0);
            const __nv_bfloat16* p = Wo + (size_t)(h * 128 + 4 * t) * DM + 192 * r + 16 * c + 2 * g;
#pragma unroll
            for (int i = 0; i < 3; i++)
#pragma unroll
                for (int eb = 0; eb < 8; eb++)
#pragma unroll
                    for (int j = 0; j < 4; j++) a[(i * 8 + eb) * 4 + j] = ldg_nc32(p + (16 * eb + ((j & 1) * 2 + (j >> 1))) * DM + 64 * i);
#pragma unroll
            for (int kk = 0; kk < 48; kk++) {
                uint32_t w0 = a[2 * kk], w1 = a[2 * kk + 1];
                a[2 * kk] = __byte_perm(w0, w1, 0x5410);
                a[2 * kk + 1] = __byte_perm(w0, w1, 0x7632);
            }
            sts128(sb + O_WP + c * 512 + lane * 16, a[92], a[93], a[94], a[95]);
            float wmax = 0.f;
#pragma unroll
            for (int i = 0; i < 3; i++) {
                float n0[4];
#pragma unroll
                for (int u = 8 * i; u < 8 * i + 8; u++) {
                    const uint32_t x0 = a[4 * u] & 0x7fff7fffu, x1 = a[4 * u + 1] & 0x7fff7fffu, x2 = a[4 * u + 2] & 0x7fff7fffu, x3 = a[4 * u + 3] & 0x7fff7fffu;
                    if (u == 8 * i) mma16816_z(n0, x0, x1, x2, x3, ONES, ONES);
                    else mma16816(n0, x0, x1, x2, x3, ONES, ONES);
                }
                wmax = fmaxf(wmax, fmaxf(n0[0], n0[2]));
            }
            uint32_t wm = __reduce_max_sync(~0u, __float_as_uint(wmax));
            sts32_if(lane, sb + O_OF + 4 * c, wm);
            if (c == 0) PSTAMP(8);
            bar_sync(7, 384);
            asm volatile("barrier.cluster.wait.aligned;" ::: "memory");
            if (c == 1) tma_x_tile(sb, &tm_x, r, 1, 1);
            if (c == 0) {
                const uint4 wq = lds128(sb + O_OF), xq = lds128(sb + O_OF + 16), xr = lds128(sb + O_OF + 32), v0 = lds128(sb + O_MISC + 32), v1 = lds128(sb + O_MISC + 48);
                const uint32_t w1 = max(max(wq.x, wq.y), max(wq.z, wq.w)), x1 = max(max(max(xq.x, xq.y), max(xq.z, xq.w)), max(max(xr.x, xr.y), max(xr.z, xr.w)));
                const uint32_t vv = (r < 2) ? 0u : max(max(max(v0.x, v0.y), max(v0.z, v0.w)), max(max(v1.x, v1.y), max(v1.z, v1.w)));
                const uint32_t lo = (min(w1, 0x7f800000u) + 0xffffu) >> 16 | ((min(vv, 0x7f800000u) + 0xffffu) & 0xffff0000u), hi = (x1 & 0xffff0000u) | tag;
                uint32_t l0, h0, l1, h1, l2, h2;
                asm volatile("{\n.reg .pred p;\n.reg .u32 n, x, y;\n.reg .b64 v;\nsetp.eq.u32 p, %10, 0;\nmov.b64 v, {%8, %9};\n@p st.relaxed.gpu.global.b64 [%7], v;\nmov.u32 n, 0;\n"
                             "G_%=: ld.relaxed.gpu.global.b64 v, [%6];\nmov.b64 {%0, %1}, v;\nld.relaxed.gpu.global.b64 v, [%6+256];\nmov.b64 {%2, %3}, v;\n"
                             "ld.relaxed.gpu.global.b64 v, [%6+512];\nmov.b64 {%4, %5}, v;\n"
                             "xor.b32 x, %1, %9;\nxor.b32 y, %3, %9;\nor.b32 x, x, y;\nxor.b32 y, %5, %9;\nor.b32 x, x, y;\nand.b32 x, x, 0xffff;\n"
                             "setp.eq.u32 p, x, 0;\nvote.sync.all.pred p, p, 0xffffffff;\n@p bra.uni E_%=;\n"
                             "add.u32 n, n, 1;\nsetp.lt.u32 p, n, 4000000;\n@p bra.uni G_%=;\ntrap;\nE_%=:\n}"
                             : "=&r"(l0), "=&r"(h0), "=&r"(l1), "=&r"(h1), "=&r"(l2), "=&r"(h2)
                             : "l"(&g_norm[lane]), "l"(&g_norm[blockIdx.x]), "r"(lo), "r"(hi), "r"(lane) : "memory");
                const uint32_t lm = __vmaxu2(l0, __vmaxu2(l1, l2));
                const float fw = __uint_as_float(__reduce_max_sync(~0u, lm << 16));
                const float fv = __uint_as_float(__reduce_max_sync(~0u, lm & 0xffff0000u));
                const float xmax = __uint_as_float(__reduce_max_sync(~0u, max(h0, max(h1, h2)) & 0xffff0000u));
                const float G = 36.f * fw * fv;
                sts32_if(lane, sb + O_MISC + 4, __float_as_uint(G)); sts32_if(lane, sb + O_MISC + 8, __float_as_uint(G * xmax));
            }
        }
        if (c == 0) PSTAMP(12);
        bar_sync(6, 128);
        int s3n = 1;
        uint32_t roff = __shfl_sync(~0u, (r * 4 + c) * 2048 + (lane >> 4) * 512 + (lane & 2) * 128 + (lane & 1) * 64 + (lane & 12) * 4, lane);
#pragma unroll 1
        for (int s = 0; s < NSEG; s++) {
            const uint32_t l16 = opaque(l16c);
            const uint32_t vxa = sb + O_VX + (s & 1) * 8192 + c * 2048 + l16;
            if (c == 0 && r == 2) {
                bar_sync(14, 288);
                fence_async_smem();
                asm volatile("{\n.reg .pred p;\nelect.sync _|p, 0xffffffff;\n"
                    "@p cp.async.bulk.global.shared::cta.bulk_group [%0], [%1], 8192;\n@p cp.async.bulk.commit_group;\n"
                    "cp.async.bulk.wait_group 0;\nsetp.lt.and.s32 p, %4, 63, p;\n"
                    "@p cp.async.bulk.shared::cluster.global.mbarrier::complete_tx::bytes.multicast::cluster [%1], [%0], 8192, [%2], %3;\n"
                    "fence.proxy.async.global;\n}"
                    :: "l"(reinterpret_cast<char*>(g_qkv) + (size_t)(s * NH + h) * REC + 20480), "r"(sb + O_VX + (s & 1) * 8192),
                       "r"(sb + B_VX + 8 * (s & 1)), "h"((unsigned short)3), "r"(s) : "memory");
            }
            if (s == NSEG - 1) { bar_sync(3, 384); mbar_wait(sb + B_SC, s & 1); break; }
            uint4 vx[4];
            sts32_if(l16, sb + O_MISC + 16 + 4 * c, __reduce_max_sync(~0u, mmax));
            if (c == 0) STAMP(s, 5);
            {
                bar_sync(6, 128);
                const uint4 mm = lds128(sb + O_MISC + 16), cf = lds128(sb + O_MISC);
                const float bound = fmaxf(__uint_as_float(cf.z), __uint_as_float(cf.y) * (__uint_as_float(max(max(mm.x, mm.y), max(mm.z, mm.w))) * __uint_as_float(cf.x)));
                const uint32_t ebits = __reduce_max_sync(~0u, min(max(__float_as_uint(bound) & 0x7f800000u, 21u << 23), 254u << 23));
                mbar_wait(sb + B_X + 8 * s3n, ((s + 1) / 3) & 1);
                s3n = (s3n == 2) ? 0 : s3n + 1;
                bar_sync(3, 384);
                if (r < 2) mbar_wait(sb + B_VX + 8 * (s & 1), (s >> 1) & 1);
                vx[0] = lds128(vxa); vx[2] = lds128(vxa + 1024);
                if (c == 0) STAMP(s, 13);
                mbar_wait(sb + B_SC, s & 1);
                if (c == 0) STAMP(s, 6);
                float p[10];
                load_scores(p, sb + O_SC, 1280, l16);
                float mx = fmaxf(fmaxf(fmaxf(p[0], p[1]), fmaxf(p[2], p[3])), fmaxf(fmaxf(p[4], p[5]), fmaxf(p[6], p[7])));
                mx = quad_max(fmaxf(mx, fmaxf(p[8], p[9])));
                const uint4 vm = lds64x2(sb + O_VM + c * 512 + (l16 >> 1));
                vx[1] = lds128(vxa + 512); vx[3] = lds128(vxa + 1536);
                bar_arrive(4, 384);
                const float sc = __uint_as_float(lds32(sb + O_MISC + 12));
                const float mo = mx * SM_SCALE;
                uint32_t P[5];
#pragma unroll
                for (int n = 0; n < 5; n++) P[n] = pack_bf16(ex2(fmaf(p[2 * n], SM_SCALE, -mo)), ex2(fmaf(p[2 * n + 1], n == 3 ? sc : SM_SCALE, -mo)));
                if (c == 0) STAMP(s, 7);
                float o0[4], o1[4], sm[4];
                mma16816_z(sm, ONES, ONES, ONES, ONES, P[1], P[2]);
                mma16816_z(o0, vx[0].x, vx[0].y, vx[0].z, vx[0].w, P[1], P[2]);
                mma16816_z(o1, vx[2].x, vx[2].y, vx[2].z, vx[2].w, P[1], P[2]);
                mma16816(sm, ONES, ONES, ONES, ONES, P[3], P[4]);
                mma16816(o0, vx[1].x, vx[1].y, vx[1].z, vx[1].w, P[3], P[4]);
                mma16816(o1, vx[3].x, vx[3].y, vx[3].z, vx[3].w, P[3], P[4]);
                mma1688(sm, ONES, ONES, P[0]);
                mma1688(o0, vm.x, vm.y, P[0]);
                mma1688(o1, vm.z, vm.w, P[0]);
                const float sig = __uint_as_float((268u << 23) - ebits);
                const float r0 = rcp_fast(sm[0]) * sig, r1 = rcp_fast(sm[1]) * sig;
                stsm4t(sb + O_OF + c * 512 + l16, pack_bf16(o0[0] * r0, o0[1] * r1), pack_bf16(o0[2] * r0, o0[3] * r1),
                       pack_bf16(o1[0] * r0, o1[1] * r1), pack_bf16(o1[2] * r0, o1[3] * r1));
                bar_sync(6, 128);
                uint4 ob[4];
#pragma unroll
                for (int q = 0; q < 4; q++) ob[q] = ldsm4(sb + O_OF + q * 512 + l16);
                { const uint4 v = lds128(sb + O_WP + c * 512 + l16); a[92] = v.x; a[93] = v.y; a[94] = v.z; a[95] = v.w; }
                float m0[3][4], m1[3][4];
#pragma unroll
                for (int q = 0; q < 4; q++) {
#pragma unroll
                    for (int i = 0; i < 3; i++) {
                        const int k0 = (i * 8 + 2 * q) * 4;
                        if (q == 0) mma16816_z(m0[i], a[k0], a[k0 + 1], a[k0 + 2], a[k0 + 3], ob[q].x, ob[q].y);
                        else mma16816(m0[i], a[k0], a[k0 + 1], a[k0 + 2], a[k0 + 3], ob[q].x, ob[q].y);
                    }
#pragma unroll
                    for (int i = 0; i < 3; i++) {
                        const int k1 = (i * 8 + 2 * q + 1) * 4;
                        if (q == 0) mma16816_z(m1[i], a[k1], a[k1 + 1], a[k1 + 2], a[k1 + 3], ob[q].z, ob[q].w);
                        else mma16816(m1[i], a[k1], a[k1 + 1], a[k1 + 2], a[k1 + 3], ob[q].z, ob[q].w);
                    }
                }
                asm volatile("red.relaxed.gpu.global.add.noftz.v4.f16x2 [%0], {%1,%2,%3,%4};" :: "l"(reinterpret_cast<char*>(g_acc) + roff),
                    "r"(pack_f16(m0[0][0] + m1[0][0], m0[0][2] + m1[0][2])), "r"(pack_f16(m0[1][0] + m1[1][0], m0[1][2] + m1[1][2])),
                    "r"(pack_f16(m0[2][0] + m1[2][0], m0[2][2] + m1[2][2])), "r"(0x3c00u) : "memory");
                asm volatile("red.relaxed.gpu.global.add.noftz.v4.f16x2 [%0], {%1,%2,%3,%4};" :: "l"(reinterpret_cast<char*>(g_acc) + roff + 1024),
                    "r"(pack_f16(m0[0][1] + m1[0][1], m0[0][3] + m1[0][3])), "r"(pack_f16(m0[1][1] + m1[1][1], m0[1][3] + m1[1][3])),
                    "r"(pack_f16(m0[2][1] + m1[2][1], m0[2][3] + m1[2][3])), "r"(0x3c00u) : "memory");
                const unsigned t_red = clk();
                bar_arrive(5, 256);
                bar_arrive(13, 256);
                mbar_expect_if(l16 | c, sb + B_SC, 4608);
                mbar_expect_if(l16 | (c ^ 1) | (r >> 1), sb + B_VX + 8 * ((s + 1) & 1), 8192);
                sts32_if(l16 | (c ^ 3), sb + O_MISC, ebits - (14u << 23));
                if (c == 0) STAMPV(s, 8, t_red);
                if (ACC_PF && c == 2 && s + 4 < NSEG - 1)
                    asm volatile("prefetch.global.L2 [%0];" :: "l"(reinterpret_cast<const char*>(g_acc) + ((s + 4) * 96 + blockIdx.x) * 256 + (l16 & 96)) : "memory");
                const char* pbase = reinterpret_cast<const char*>(g_acc) + (s * 24576 + c * 2048) + ((l16 & 64) * 16 + (l16 & 256) + ((l16 & 128) >> 1) + (l16 & 48));
                spin_until(t_red, D_WAIT);
                uint4 v[6];
#pragma unroll
                for (int i = 0; i < 6; i++) v[i] = ldg_relaxed128(pbase + (i >> 1) * 8192 + (i & 1) * 512);
                int nretry = 0;
                auto convert = [&](int tau) {
                    const uint4 A = v[2 * tau], B = v[2 * tau + 1];
                    sts128(sb + O_MF + tau * 3072 + c * 512 + l16, f16x2_to_bf16x2(A.x), f16x2_to_bf16x2(B.x), f16x2_to_bf16x2(A.y), f16x2_to_bf16x2(B.y));
                    sts64(sb + O_MF + tau * 3072 + 2048 + (c >> 1) * 512 + (c & 1) * 8 + l16, f16x2_to_bf16x2(A.z), f16x2_to_bf16x2(B.z));
                };
                const uint32_t ok0 = __all_sync(~0u, (v[0].w & v[1].w) == 0x5000u);
                convert(0);
                asm volatile("{\n.reg .pred p;\nsetp.ne.u32 p, %0, 0;\n@p bar.arrive 2, 384;\n}" :: "r"(ok0) : "memory");
                sched_fence<0>(h);
                uint32_t ok1;
                asm volatile("{\n.reg .pred p, q;\n.reg .b32 x;\nlop3.b32 x, %1, %2, %3, 0x80;\nand.b32 x, x, %4;\n"
                             "setp.eq.u32 p, x, 0x5000;\nvote.sync.all.pred q, p, 0xffffffff;\nselp.u32 %0, 1, 0, q;\n}"
                             : "=r"(ok1) : "r"(v[2].w), "r"(v[3].w), "r"(v[4].w), "r"(v[5].w));
                convert(1); convert(2);
                asm volatile("{\n.reg .pred p;\nsetp.ne.u32 p, %0, 0;\n@p bar.arrive 15, 384;\n}" :: "r"(ok1) : "memory");
                if (!(ok0 & ok1)) {
                    asm volatile("{\n.reg .pred p0, p1, p2, p3, p4, p5, q;\n.reg .u32 n, x;\nmov.u32 n, 0;\n"
                         "R_%=: setp.ne.u32 p0, %3, 0x5000;\nsetp.ne.u32 p1, %7, 0x5000;\nsetp.ne.u32 p2, %11, 0x5000;\n"
                         "setp.ne.u32 p3, %15, 0x5000;\nsetp.ne.u32 p4, %19, 0x5000;\nsetp.ne.u32 p5, %23, 0x5000;\n"
                         "@p0 ld.relaxed.gpu.global.v4.u32 {%0,%1,%2,%3}, [%25];\n@p1 ld.relaxed.gpu.global.v4.u32 {%4,%5,%6,%7}, [%25+512];\n"
                         "@p2 ld.relaxed.gpu.global.v4.u32 {%8,%9,%10,%11}, [%25+8192];\n@p3 ld.relaxed.gpu.global.v4.u32 {%12,%13,%14,%15}, [%25+8704];\n"
                         "@p4 ld.relaxed.gpu.global.v4.u32 {%16,%17,%18,%19}, [%25+16384];\n@p5 ld.relaxed.gpu.global.v4.u32 {%20,%21,%22,%23}, [%25+16896];\n"
                         "add.u32 %24, %24, 1;\nand.b32 x, %3, %7;\nand.b32 x, x, %11;\nand.b32 x, x, %15;\nand.b32 x, x, %19;\nand.b32 x, x, %23;\n"
                         "setp.eq.u32 q, x, 0x5000;\nvote.sync.all.pred q, q, 0xffffffff;\n@q bra.uni K_%=;\n"
                         "add.u32 n, n, 1;\nsetp.lt.u32 q, n, 2000000;\n@q bra.uni R_%=;\ntrap;\nK_%=:\n}"
                         : "+r"(v[0].x), "+r"(v[0].y), "+r"(v[0].z), "+r"(v[0].w), "+r"(v[1].x), "+r"(v[1].y), "+r"(v[1].z), "+r"(v[1].w),
                           "+r"(v[2].x), "+r"(v[2].y), "+r"(v[2].z), "+r"(v[2].w), "+r"(v[3].x), "+r"(v[3].y), "+r"(v[3].z), "+r"(v[3].w),
                           "+r"(v[4].x), "+r"(v[4].y), "+r"(v[4].z), "+r"(v[4].w), "+r"(v[5].x), "+r"(v[5].y), "+r"(v[5].z), "+r"(v[5].w), "+r"(nretry)
                         : "l"(pbase) : "memory");
                    if (!ok0) { convert(0); bar_arrive(2, 384); }
                    if (!ok1) { convert(1); convert(2); bar_arrive(15, 384); }
                }
                if (c == 0) STAMP(s, 12);
                if (c == 0) STAMPV(s, 14, nretry);
                mmax = absmax2(absmax2(absmax2(v[0].x, v[0].y), absmax2(v[0].z, v[1].x)), absmax2(absmax2(v[1].y, v[1].z), absmax2(v[2].x, v[2].y)));
                mmax = absmax2(mmax, absmax2(absmax2(absmax2(v[2].z, v[3].x), absmax2(v[3].y, v[3].z)), absmax2(absmax2(v[4].x, v[4].y), absmax2(v[4].z, v[5].x))));
                mmax = absmax2(mmax, absmax2(v[5].y, v[5].z)) & 0x7fff7fffu;
                { const float2 mf = __half22float2(*reinterpret_cast<__half2*>(&mmax)); mmax = max(__float_as_uint(mf.x), __float_as_uint(mf.y)); }
            }
            roff += 24576;
        }
        {
            bar_sync(7, 384);
            if (c == 0) flag_inc_if(l16c, &g_flag[F_QKV + (4 * (NBLK - 1) + (h >> 3)) * 8]);
        }
    }
    if (warp == 8) PSTAMP(13);
    cluster_sync();
}

constexpr int NST = 10;
constexpr int G_RING = 0, G_EX = NST * 16384, G_OUT = G_EX + 32768, G_CARRY = G_OUT + 32768, G_BAR = G_CARRY + 512, BG_SMEM = G_BAR + 256;
constexpr int GB_FULL = G_BAR, GB_EMPTY = G_BAR + 8 * NST, GB_W = G_BAR + 16 * NST;
static_assert(BG_SMEM <= 232448, "smem");

template <int ACC>
__device__ __forceinline__ void wgmma_n128_rs(float (&d)[64], uint32_t a0, uint32_t a1, uint32_t a2, uint32_t a3, uint64_t desc) {
    asm volatile("wgmma.mma_async.sync.aligned.m64n128k16.f32.bf16.bf16 "
        "{%0,%1,%2,%3,%4,%5,%6,%7,%8,%9,%10,%11,%12,%13,%14,%15,%16,%17,%18,%19,%20,%21,%22,%23,%24,%25,%26,%27,%28,%29,%30,%31,"
        "%32,%33,%34,%35,%36,%37,%38,%39,%40,%41,%42,%43,%44,%45,%46,%47,%48,%49,%50,%51,%52,%53,%54,%55,%56,%57,%58,%59,%60,%61,%62,%63}, "
        "{%64,%65,%66,%67}, %68, %69, 1, 1, 0;"
        : "+f"(d[0]), "+f"(d[1]), "+f"(d[2]), "+f"(d[3]), "+f"(d[4]), "+f"(d[5]), "+f"(d[6]), "+f"(d[7]),
          "+f"(d[8]), "+f"(d[9]), "+f"(d[10]), "+f"(d[11]), "+f"(d[12]), "+f"(d[13]), "+f"(d[14]), "+f"(d[15]),
          "+f"(d[16]), "+f"(d[17]), "+f"(d[18]), "+f"(d[19]), "+f"(d[20]), "+f"(d[21]), "+f"(d[22]), "+f"(d[23]),
          "+f"(d[24]), "+f"(d[25]), "+f"(d[26]), "+f"(d[27]), "+f"(d[28]), "+f"(d[29]), "+f"(d[30]), "+f"(d[31]),
          "+f"(d[32]), "+f"(d[33]), "+f"(d[34]), "+f"(d[35]), "+f"(d[36]), "+f"(d[37]), "+f"(d[38]), "+f"(d[39]),
          "+f"(d[40]), "+f"(d[41]), "+f"(d[42]), "+f"(d[43]), "+f"(d[44]), "+f"(d[45]), "+f"(d[46]), "+f"(d[47]),
          "+f"(d[48]), "+f"(d[49]), "+f"(d[50]), "+f"(d[51]), "+f"(d[52]), "+f"(d[53]), "+f"(d[54]), "+f"(d[55]),
          "+f"(d[56]), "+f"(d[57]), "+f"(d[58]), "+f"(d[59]), "+f"(d[60]), "+f"(d[61]), "+f"(d[62]), "+f"(d[63])
        : "r"(a0), "r"(a1), "r"(a2), "r"(a3), "l"(desc), "n"(ACC));
}
template <int ACC>
__device__ __forceinline__ void wgmma_n64_rs(float (&d)[64], uint32_t a0, uint32_t a1, uint32_t a2, uint32_t a3, uint64_t desc) {
    asm volatile("wgmma.mma_async.sync.aligned.m64n64k16.f32.bf16.bf16 "
        "{%0,%1,%2,%3,%4,%5,%6,%7,%8,%9,%10,%11,%12,%13,%14,%15,%16,%17,%18,%19,%20,%21,%22,%23,%24,%25,%26,%27,%28,%29,%30,%31}, "
        "{%32,%33,%34,%35}, %36, %37, 1, 1, 0;"
        : "+f"(d[0]), "+f"(d[1]), "+f"(d[2]), "+f"(d[3]), "+f"(d[4]), "+f"(d[5]), "+f"(d[6]), "+f"(d[7]),
          "+f"(d[8]), "+f"(d[9]), "+f"(d[10]), "+f"(d[11]), "+f"(d[12]), "+f"(d[13]), "+f"(d[14]), "+f"(d[15]),
          "+f"(d[16]), "+f"(d[17]), "+f"(d[18]), "+f"(d[19]), "+f"(d[20]), "+f"(d[21]), "+f"(d[22]), "+f"(d[23]),
          "+f"(d[24]), "+f"(d[25]), "+f"(d[26]), "+f"(d[27]), "+f"(d[28]), "+f"(d[29]), "+f"(d[30]), "+f"(d[31])
        : "r"(a0), "r"(a1), "r"(a2), "r"(a3), "l"(desc), "n"(ACC));
}
__device__ __forceinline__ void wait_flag(const unsigned* p, unsigned target) {
    asm volatile("{\n.reg .pred p;\n.reg .u32 n, v;\nmov.u32 n, 0;\n"
                 "W_%=: ld.acquire.gpu.global.u32 v, [%0];\nsub.u32 v, v, %1;\nsetp.ge.s32 p, v, 0;\n@p bra.uni D_%=;\nnanosleep.u32 40;\n"
                 "add.u32 n, n, 1;\nsetp.lt.u32 p, n, 4000000;\n@p bra.uni W_%=;\ntrap;\nD_%=:\n}" :: "l"(p), "r"(target) : "memory");
}
template <int NS, int NT>
__device__ __forceinline__ void bg_mainloop(float (&d)[64], const uint32_t (&a)[144], uint32_t sb, int it, int lane) {
    int slot = it % NST, ph = (it / NST) & 1, prev = 0;
#pragma unroll
    for (int i = 0; i < NS; i++) {
        mbar_wait(sb + GB_FULL + 8 * slot, ph);
        const uint64_t desc = (uint64_t)(((sb + G_RING + slot * 16384) & 0x3FFFF) >> 4) | (1ull << 16) | (64ull << 32) | (1ull << 62);
        wg_fence();
#pragma unroll
        for (int k = 0; k < 512 / NT; k++) {
            const int u = (2048 / NT) * i + 4 * k;
            if (NT == 128) {
                if (i == 0 && k == 0) wgmma_n128_rs<0>(d, a[u], a[u + 1], a[u + 2], a[u + 3], desc);
                else wgmma_n128_rs<1>(d, a[u], a[u + 1], a[u + 2], a[u + 3], desc + 2 * k);
            } else {
                if (i == 0 && k == 0) wgmma_n64_rs<0>(d, a[u], a[u + 1], a[u + 2], a[u + 3], desc);
                else wgmma_n64_rs<1>(d, a[u], a[u + 1], a[u + 2], a[u + 3], desc + 2 * (k & 3) + (k >> 2) * 512);
            }
        }
        wg_commit();
        if (i > 0) {
            asm volatile("wgmma.wait_group.sync.aligned 1;" ::: "memory");
            mbar_arrive_if(lane, sb + GB_EMPTY + 8 * prev);
        }
        prev = slot;
        slot += 2;
        if (slot >= NST) { slot -= NST; ph ^= 1; }
    }
    wg_wait0();
    mbar_arrive_if(lane, sb + GB_EMPTY + 8 * prev);
}
template <bool SKIP, int NT>
__device__ __forceinline__ void bg_epilogue(float (&d)[64], uint32_t sb, int wg, int w, int lane, const CUtensorMap* tm_out, int col0, int tok0,
                                            const __nv_bfloat16* xa, const __nv_bfloat16* Dk) {
    constexpr int H = NT / 4;
    const int g = lane >> 2, t = lane & 3;
    const uint32_t ex = sb + G_EX + w * 4096 + lane * 16;
    float k[H];
    if (wg == 0) {
#pragma unroll
        for (int q = 0; q < H / 4; q++) sts128f(ex + q * 512, d[H + 4 * q], d[H + 4 * q + 1], d[H + 4 * q + 2], d[H + 4 * q + 3]);
#pragma unroll
        for (int i = 0; i < H; i++) k[i] = d[i];
    } else {
#pragma unroll
        for (int q = 0; q < H / 4; q++) sts128f(ex + 16384 + q * 512, d[4 * q], d[4 * q + 1], d[4 * q + 2], d[4 * q + 3]);
#pragma unroll
        for (int i = 0; i < H; i++) k[i] = d[H + i];
    }
    uint32_t xv[16], dv = 0;
    if (SKIP) {
        const __nv_bfloat16* xp = xa + (size_t)(tok0 + 64 * wg + 2 * t) * DM + col0 + 16 * w + 2 * g;
#pragma unroll
        for (int i = 0; i < 16; i++) xv[i] = ldg_nc32(xp + (8 * (i >> 1) + (i & 1)) * DM);
        dv = ldg_nc32(Dk + col0 + 16 * w + 2 * g);
    }
    if (SKIP && w == 0) asm volatile("cp.async.bulk.wait_group.read 0;" ::: "memory");
    bar_sync(1, 256);
#pragma unroll
    for (int q = 0; q < H / 4; q++) {
        const float4 o = lds128f(ex + (wg ^ 1) * 16384 + q * 512);
        k[4 * q] += o.x; k[4 * q + 1] += o.y; k[4 * q + 2] += o.z; k[4 * q + 3] += o.w;
    }
    if (SKIP) bar_sync(1, 256); else bar_sync(13, 288);
    const uint32_t ob = sb + G_OUT + wg * (NT == 128 ? 16384 : 4096) + (w >> 1) * 8192 + (g & 1) * 8;
    const uint32_t ch = (w & 1) * 4 + (g >> 1);
#pragma unroll
    for (int i = 0; i < H / 2; i++) {
        float v0 = k[4 * (i >> 1) + (i & 1)], v1 = k[4 * (i >> 1) + 2 + (i & 1)];
        if (SKIP) {
            const uint32_t p = pack_bf16(__uint_as_float(xv[i] << 16) * __uint_as_float(dv << 16), __uint_as_float(xv[i] & 0xffff0000u) * __uint_as_float(dv & 0xffff0000u));
            v0 += __uint_as_float(p << 16); v1 += __uint_as_float(p & 0xffff0000u);
        }
        const uint32_t n7 = 2 * t + (i & 1);
        sts64(ob + (8 * (i >> 1) + n7) * 128 + ((ch ^ n7) << 4), __float_as_uint(v0), __float_as_uint(v1));
    }
    fence_async_smem();
    if (SKIP) {
        bar_sync(4 + wg, 128);
        if (w == 0)
            asm volatile("{\n.reg .pred p;\nelect.sync _|p, 0xffffffff;\n"
                "@p cp.async.bulk.tensor.2d.global.shared::cta.bulk_group [%0, {%2, %4}], [%1];\n"
                "@p cp.async.bulk.tensor.2d.global.shared::cta.bulk_group [%0, {%3, %4}], [%1+8192];\n@p cp.async.bulk.commit_group;\n}"
                :: "l"(tm_out), "r"(sb + G_OUT + wg * 16384), "r"(col0), "r"(col0 + 32), "r"(tok0 + 64 * wg) : "memory");
    } else {
        bar_arrive(12, 288);
    }
}
__device__ __forceinline__ void s5_channel(int p, const __nv_bfloat16* Lre, const __nv_bfloat16* Lim, const __nv_bfloat16* logdt, float2& lam, float2& coef) {
    const float dt = __bfloat162float(__float2bfloat16(expf(__bfloat162float(logdt[p]))));
    const float lr = __bfloat162float(Lre[p]), li = __bfloat162float(Lim[p]);
    const float e = expf(dt * lr);
    float sn, cs;
    sincosf(dt * li, &sn, &cs);
    lam = make_float2(e * cs, e * sn);
    const float den = lr * lr + li * li;
    coef = make_float2(((lam.x - 1.f) * lr + lam.y * li) / den, (lam.y * lr - (lam.x - 1.f) * li) / den);
}
__device__ __forceinline__ float2 cfma(float2 a, float2 b, float2 c) {
    return make_float2(fmaf(a.x, b.x, fmaf(-a.y, b.y, c.x)), fmaf(a.x, b.y, fmaf(a.y, b.x, c.y)));
}
__device__ __forceinline__ uint4 ldg128(const void* p) { uint4 v; asm volatile("ld.global.v4.u32 {%0,%1,%2,%3}, [%4];" : "=r"(v.x), "=r"(v.y), "=r"(v.z), "=r"(v.w) : "l"(p) : "memory"); return v; }
__device__ __forceinline__ uint2 ldg64(const void* p) { uint2 v; asm volatile("ld.global.v2.u32 {%0,%1}, [%2];" : "=r"(v.x), "=r"(v.y) : "l"(p) : "memory"); return v; }

__device__ __forceinline__ void bg_attention(uint32_t st0, uint32_t st1, int mt, int lane) {
    const int g = lane >> 2, t = lane & 3;
    float sc[5][4];
#pragma unroll
    for (int n = 0; n < 5; n++) sc[n][0] = sc[n][1] = sc[n][2] = sc[n][3] = 0.f;
    float sm2[4] = {0.f, 0.f, 0.f, 0.f};
#pragma unroll
    for (int i = 0; i < 8; i++) {
        const uint32_t st = (i >> 2 ? st1 : st0) + (i & 3) * 512 + lane * 16;
        const uint4 q = ldsm4(st + mt * 2048), km = ldsm4(st + 8192), k0 = ldsm4(st + 4096);
        mma16816(sc[0], q.x, q.y, q.z, q.w, km.x, km.y);
        mma16816(sm2, q.x, q.y, q.z, q.w, km.z, km.w);
        mma16816(sc[1], q.x, q.y, q.z, q.w, k0.x, k0.y);
        mma16816(sc[2], q.x, q.y, q.z, q.w, k0.z, k0.w);
        if (mt) {
            const uint4 k1 = ldsm4(st + 6144);
            mma16816(sc[3], q.x, q.y, q.z, q.w, k1.x, k1.y);
            mma16816(sc[4], q.x, q.y, q.z, q.w, k1.z, k1.w);
        }
    }
#pragma unroll
    for (int i = 0; i < 4; i++) sc[0][i] += sm2[i];
    const int q0 = 16 * mt + 8 + g - 2 * t;
#pragma unroll
    for (int n = 1; n < 5; n++) {
        if (8 * n > q0) sc[n][0] = -INFINITY;
        if (8 * n + 1 > q0) sc[n][1] = -INFINITY;
        if (8 * n > q0 + 8) sc[n][2] = -INFINITY;
        if (8 * n + 1 > q0 + 8) sc[n][3] = -INFINITY;
    }
    float ma = fmaxf(sc[0][0], sc[0][1]), mb = fmaxf(sc[0][2], sc[0][3]);
#pragma unroll
    for (int n = 1; n < 5; n++) { ma = fmaxf(ma, fmaxf(sc[n][0], sc[n][1])); mb = fmaxf(mb, fmaxf(sc[n][2], sc[n][3])); }
    ma = quad_max(ma) * SM_SCALE; mb = quad_max(mb) * SM_SCALE;
    uint32_t Pa[5], Pb[5];
#pragma unroll
    for (int n = 0; n < 5; n++) {
        Pa[n] = pack_bf16(ex2(fmaf(sc[n][0], SM_SCALE, -ma)), ex2(fmaf(sc[n][1], SM_SCALE, -ma)));
        Pb[n] = pack_bf16(ex2(fmaf(sc[n][2], SM_SCALE, -mb)), ex2(fmaf(sc[n][3], SM_SCALE, -mb)));
    }
    float sa[4], sbb[4];
    mma1688_z(sa, ONES, ONES, Pa[0]); mma1688_z(sbb, ONES, ONES, Pb[0]);
    mma16816(sa, ONES, ONES, ONES, ONES, Pa[1], Pa[2]); mma16816(sbb, ONES, ONES, ONES, ONES, Pb[1], Pb[2]);
    mma16816(sa, ONES, ONES, ONES, ONES, Pa[3], Pa[4]); mma16816(sbb, ONES, ONES, ONES, ONES, Pb[3], Pb[4]);
    const float ra0 = rcp_fast(sa[0]), ra1 = rcp_fast(sa[1]), rb0 = rcp_fast(sbb[0]), rb1 = rcp_fast(sbb[1]);
    const uint32_t row = lane & 7;
    const uint32_t so = mt * 2048 + (lane >> 4) * 1024 + row * 128;
#pragma unroll
    for (int i = 0; i < 8; i++) {
        const uint32_t st = i >> 2 ? st1 : st0;
        const int e4 = i & 3;
        const float2 vmf = lds64f(st + 14336 + e4 * 256 + lane * 8);
        const uint32_t vm0 = __float_as_uint(vmf.x), vm1 = __float_as_uint(vmf.y);
        const uint4 v0 = lds128(st + 10240 + e4 * 1024 + lane * 16);
        float oa[4], ob[4];
        mma1688_z(oa, vm0, vm1, Pa[0]); mma1688_z(ob, vm0, vm1, Pb[0]);
        mma16816(oa, v0.x, v0.y, v0.z, v0.w, Pa[1], Pa[2]);
        mma16816(ob, v0.x, v0.y, v0.z, v0.w, Pb[1], Pb[2]);
        if (mt) {
            const uint4 v1 = lds128(st + 10240 + e4 * 1024 + 512 + lane * 16);
            mma16816(oa, v1.x, v1.y, v1.z, v1.w, Pa[3], Pa[4]);
            mma16816(ob, v1.x, v1.y, v1.z, v1.w, Pb[3], Pb[4]);
        }
        stsm4t(st + so + (((2 * e4 + ((lane >> 3) & 1)) ^ row) << 4), pack_bf16(oa[0] * ra0, oa[1] * ra1), pack_bf16(oa[2] * ra0, oa[3] * ra1),
               pack_bf16(ob[0] * rb0, ob[1] * rb1), pack_bf16(ob[2] * rb0, ob[3] * rb1));
    }
}
__device__ __forceinline__ bool bg_att_turn(int na, int ng) { return na == ng || (na == ng + 1 && (na <= BG_AHEAD || na == NBLK - 1)); }

__global__ void __launch_bounds__(384, 1)
bg_kernel(const __grid_constant__ CUtensorMap tm_xa, const __grid_constant__ CUtensorMap tm_wo, const __grid_constant__ CUtensorMap tm_out,
          const __nv_bfloat16* __restrict__ xa, const __nv_bfloat16* __restrict__ Lre, const __nv_bfloat16* __restrict__ Lim,
          const __nv_bfloat16* __restrict__ Bre, const __nv_bfloat16* __restrict__ Bim, const __nv_bfloat16* __restrict__ Cre,
          const __nv_bfloat16* __restrict__ Cim, const __nv_bfloat16* __restrict__ logdt, const __nv_bfloat16* __restrict__ Dk, float* __restrict__ out) {
    extern __shared__ __align__(1024) uint8_t smem_raw[];
    const uint32_t sb = smem_u32(smem_raw);
    const int lane = threadIdx.x & 31;
    const int warp = __shfl_sync(~0u, threadIdx.x >> 5, 0);
    const int wg = warp >> 2, w = warp & 3, b = blockIdx.x;
    const int nt = b % 9, kq = b / 9;
    BSTAMP(0);
    if (threadIdx.x == 0) {
        if (sb & 1023u) __trap();
        for (int i = 0; i < NST; i++) { mbar_init(sb + GB_FULL + 8 * i, 1); mbar_init(sb + GB_EMPTY + 8 * i, 4); }
        mbar_init(sb + GB_W, 1);
        asm volatile("fence.mbarrier_init.release.cluster;" ::: "memory");
        mbar_expect(sb + GB_W, (b < 18 ? 64 : 128) * 1152);
        sts32(sb + G_BAR + 248, atomicAdd(&g_ticket_bg, 1u) / 36u + 1u);
    }
    __syncthreads();
    if (wg == 2) {
        asm volatile("setmaxnreg.dec.sync.aligned.u32 24;");
        if (w == 0) {
            int slot = 0, ph = 1;
            auto next = [&]() { if (++slot == NST) { slot = 0; ph ^= 1; } };
            bar_sync(6, 288);
            if (b < 18) {
#pragma unroll 1
                for (int i = 0; i < 144; i++) {
                    const int blk = i / 9, kb = i - 9 * blk, it = (blk >> 1) * 18 + (blk & 1) + 2 * kb;
                    slot = it % NST;
                    mbar_wait(sb + GB_EMPTY + 8 * slot, ((it / NST) & 1) ^ 1);
                    asm volatile("{\n.reg .pred p;\nelect.sync _|p, 0xffffffff;\n@p mbarrier.arrive.expect_tx.shared::cta.b64 _, [%2], 16384;\n"
                        "@p cp.async.bulk.tensor.5d.shared::cluster.global.mbarrier::complete_tx::bytes [%0], [%1, {%3, %4, %4, %4, %5}], [%2];\n}"
                        :: "r"(sb + G_RING + slot * 16384), "l"(&tm_xa), "r"(sb + GB_FULL + 8 * slot), "r"(kb * 64), "r"(0), "r"(blk) : "memory");
                }
                slot = 144 % NST; ph = ((144 / NST) & 1) ^ 1;
            }
            const unsigned ep = lds32(sb + G_BAR + 248);
            auto slabs = [&](const char* src, int ns) {
                asm volatile("fence.proxy.async.global;" ::: "memory");
#pragma unroll 1
                for (int i = 0; i < ns; i++) {
                    mbar_wait(sb + GB_EMPTY + 8 * slot, ph);
                    asm volatile("{\n.reg .pred p;\nelect.sync _|p, 0xffffffff;\n@p mbarrier.arrive.expect_tx.shared::cta.b64 _, [%2], 16384;\n"
                        "@p cp.async.bulk.shared::cluster.global.mbarrier::complete_tx::bytes [%0], [%1], 16384, [%2];\n}"
                        :: "r"(sb + G_RING + slot * 16384), "l"(src + (size_t)((i & 1) * (ns >> 1) + (i >> 1)) * (SEQ * 128)), "r"(sb + GB_FULL + 8 * slot) : "memory");
                    next();
                }
            };
            if (b >= 18) {
#pragma unroll 1
                for (int blk = kq - 2; blk < 16; blk += 2) {
                    wait_flag(&g_flag[F_H + blk * 8], 18 * ep);
                    slabs(reinterpret_cast<const char*>(g_h) + blk * 16384, 18);
                }
            }
            bar_sync(6, 288);
#pragma unroll 1
            for (int na = 0, ng = 0; ng < NBLK;) {
                if (bg_att_turn(na, ng)) {
                    if (nt < 8) {
                        wait_flag(&g_flag[F_QKV + (na * 4 + kq) * 8], 24 * ep);
                        asm volatile("fence.proxy.async.global;" ::: "memory");
#pragma unroll 1
                        for (int i = 0; i < (na < NBIG ? 8 : 4); i++) {
                            const int hf = (i >> 1) & 1;
                            const char* rec = reinterpret_cast<const char*>(g_qkv) + (size_t)((blk_seg0(na) + 2 * (i >> 2) + (i & 1)) * NH + 8 * kq + nt) * REC;
                            mbar_wait(sb + GB_EMPTY + 8 * slot, ph);
                            asm volatile("{\n.reg .pred p;\nelect.sync _|p, 0xffffffff;\n@p mbarrier.arrive.expect_tx.shared::cta.b64 _, [%4], 15360;\n"
                                "@p cp.async.bulk.shared::cluster.global.mbarrier::complete_tx::bytes [%0], [%1], 10240, [%4];\n"
                                "@p cp.async.bulk.shared::cluster.global.mbarrier::complete_tx::bytes [%0+10240], [%2], 4096, [%4];\n"
                                "@p cp.async.bulk.shared::cluster.global.mbarrier::complete_tx::bytes [%0+14336], [%3], 1024, [%4];\n}"
                                :: "r"(sb + G_RING + slot * 16384), "l"(rec + hf * 10240), "l"(rec + 20480 + hf * 4096), "l"(rec + 28672 + hf * 1024),
                                   "r"(sb + GB_FULL + 8 * slot) : "memory");
                            next();
                        }
                    }
                    na++;
                } else {
                    wait_flag(&g_flag[F_OX + (ng * 4 + kq) * 8], 8 * ep);
                    const char* src = reinterpret_cast<const char*>(g_ox) + (size_t)kq * 16 * SEQ * 128 + blk_seg0(ng) * 4096;
                    if (ng < NBIG) slabs(src, 16);
                    else {
                        asm volatile("fence.proxy.async.global;" ::: "memory");
#pragma unroll 1
                        for (int i = 0; i < 8; i++) {
                            mbar_wait(sb + GB_EMPTY + 8 * slot, ph);
                            asm volatile("{\n.reg .pred p;\nelect.sync _|p, 0xffffffff;\n@p mbarrier.arrive.expect_tx.shared::cta.b64 _, [%2], 16384;\n"
                                "@p cp.async.bulk.shared::cluster.global.mbarrier::complete_tx::bytes [%0], [%1], 8192, [%2];\n"
                                "@p cp.async.bulk.shared::cluster.global.mbarrier::complete_tx::bytes [%0+8192], [%1+262144], 8192, [%2];\n}"
                                :: "r"(sb + G_RING + slot * 16384), "l"(src + (size_t)((i & 1) * 8 + (i & 6)) * (SEQ * 128)), "r"(sb + GB_FULL + 8 * slot) : "memory");
                            next();
                        }
                    }
                    ng++;
                }
            }
        } else if (w == 1) {
            if (b < 18) {
#pragma unroll 1
                for (int blk = 0; blk < 16; blk++) {
                    bar_sync(8 + (blk & 1), 160);
                    asm volatile("{\n.reg .pred p;\nelect.sync _|p, 0xffffffff;\n@p cp.async.bulk.global.shared::cta.bulk_group [%0], [%1], 16384;\n"
                        "@p cp.async.bulk.commit_group;\ncp.async.bulk.wait_group 0;\nfence.proxy.async.global;\n}"
                        :: "l"(reinterpret_cast<char*>(g_h) + ((size_t)b * SEQ + blk * 128) * 128), "r"(sb + G_OUT + (blk & 1) * 16384) : "memory");
                    bar_arrive(10 + (blk & 1), 160);
                    flag_inc_if(lane, &g_flag[F_H + blk * 8]);
                }
            }
            if (nt < 8) {
                int it = 144;
#pragma unroll 1
                for (int na = 0, ng = 0; ng < NBLK;) {
                    if (bg_att_turn(na, ng)) {
                        const int ns = na < NBIG ? 8 : 4;
                        bar_sync(7, 288);
                        if (lane < ns) {
                            asm volatile("cp.async.bulk.global.shared::cta.bulk_group [%0], [%1], 4096;\ncp.async.bulk.commit_group;\ncp.async.bulk.wait_group.read 0;\n"
                                "mbarrier.arrive.shared::cta.b64 _, [%2], 4;\ncp.async.bulk.wait_group 0;\nfence.proxy.async.global;"
                                :: "l"(reinterpret_cast<char*>(g_ox) + ((size_t)((8 * kq + nt) * 2 + ((lane >> 1) & 1)) * SEQ + (blk_seg0(na) + 2 * (lane >> 2) + (lane & 1)) * 32) * 128),
                                   "r"(sb + G_RING + ((it + lane) % NST) * 16384), "r"(sb + GB_EMPTY + 8 * ((it + lane) % NST)) : "memory");
                        }
                        __syncwarp();
                        bar_arrive(14, 288);
                        flag_inc_if(lane, &g_flag[F_OX + (na * 4 + kq) * 8]);
                        it += ns; na++;
                    } else { it += ng < NBIG ? 16 : 8; ng++; }
                }
            }
        } else if (w == 2) {
            const unsigned ep = lds32(sb + G_BAR + 248);
#pragma unroll 1
            for (int blk = 0; blk < NBLK; blk++) {
                const bool last = blk == NBLK - 1, add = kq || last;
                bar_arrive(13, 288);
                bar_sync(12, 288);
                if (add) { wait_flag(&g_flag[F_OUT + (blk * 9 + nt) * 8], ep); asm volatile("fence.proxy.async.global;" ::: "memory"); }
#pragma unroll 1
                for (int i = 0; i < (blk < NBIG ? 4 : 2); i++) {
                    const uint32_t src = sb + G_OUT + i * 8192;
                    const int c0 = DM + 64 * nt + (i & 1) * 32, c1 = blk_seg0(blk) * 32 + (i >> 1) * 64;
                    if (add) asm volatile("{\n.reg .pred p;\nelect.sync _|p, 0xffffffff;\n@p cp.reduce.async.bulk.tensor.2d.global.shared::cta.add.bulk_group [%0, {%2, %3}], [%1];\n}"
                                 :: "l"(&tm_out), "r"(src), "r"(c0), "r"(c1) : "memory");
                    else asm volatile("{\n.reg .pred p;\nelect.sync _|p, 0xffffffff;\n@p cp.async.bulk.tensor.2d.global.shared::cta.bulk_group [%0, {%2, %3}], [%1];\n}"
                                 :: "l"(&tm_out), "r"(src), "r"(c0), "r"(c1) : "memory");
                    if (add && blk < NBLK - 2) spin_until(clk(), RED_GAP);
                }
                asm volatile("cp.async.bulk.commit_group;\ncp.async.bulk.wait_group 0;\nfence.proxy.async.global;" ::: "memory");
                __syncwarp();
                if (!add) flag_inc_if(lane, &g_flag[F_OUT + (blk * 9 + nt) * 8]);
                if (!kq && blk == NBLK - 4) {
                    float4* z = reinterpret_cast<float4*>(out + (size_t)(SEQ - 64 + (lane >> 4)) * (2 * DM) + DM + 64 * nt) + (lane & 15);
#pragma unroll 1
                    for (int i = 0; i < 32; i++) z[i * (4 * DM / 4)] = make_float4(0.f, 0.f, 0.f, 0.f);
                    __syncwarp();
                    flag_inc_if(lane, &g_flag[F_OUT + ((NBLK - 1) * 9 + nt) * 8]);
                }
            }
        }
    } else {
        asm volatile("setmaxnreg.inc.sync.aligned.u32 240;");
        const int g = lane >> 2, t = lane & 3, tid = threadIdx.x;
        uint32_t a[144];
        float d[64];
        if (b < 18) {
            if (tid < 64)
                asm volatile("cp.async.bulk.shared::cluster.global.mbarrier::complete_tx::bytes [%0], [%1], 1152, [%2];"
                    :: "r"(sb + tid * 1168), "l"((tid < 32 ? Bre : Bim) + (size_t)(32 * b + (tid & 31)) * DM), "r"(sb + GB_W) : "memory");
            float2 lam, coef;
            s5_channel(32 * b + 8 * w + g, Lre, Lim, logdt, lam, coef);
            float2 l32 = lam;
#pragma unroll
            for (int i = 0; i < 5; i++) l32 = make_float2(l32.x * l32.x - l32.y * l32.y, 2.f * l32.x * l32.y);
            __syncwarp();
            mbar_wait(sb + GB_W, 0);
            const uint32_t ap = sb + (((lane >> 3) & 1) * 32 + 8 * w + (lane & 7)) * 1168 + (lane >> 4) * 16;
#pragma unroll
            for (int ks = 0; ks < 36; ks++) { const uint4 v = ldsm4(ap + ks * 32); a[4 * ks] = v.x; a[4 * ks + 1] = v.y; a[4 * ks + 2] = v.z; a[4 * ks + 3] = v.w; }
            bar_sync(1, 256);
            bar_arrive(6, 288);
            BSTAMP(1);
#pragma unroll 1
            for (int blk = wg; blk < 16; blk += 2) {
                bg_mainloop<9, 128>(d, a, sb, (blk >> 1) * 18 + wg, lane);
                float2 e = make_float2(0.f, 0.f);
#pragma unroll
                for (int i = 0; i < 32; i++) e = cfma(lam, e, make_float2(d[4 * (i >> 1) + (i & 1)], d[4 * (i >> 1) + 2 + (i & 1)]));
                float2 cin = make_float2(0.f, 0.f);
                if (blk > 0) { bar_sync(2 + (wg ^ 1), 256); cin = lds64f(sb + G_CARRY + (wg ^ 1) * 256 + (8 * w + g) * 8); }
                float2 mine = cin;
#pragma unroll
                for (int q = 0; q < 4; q++) {
                    const float2 eq = make_float2(__shfl_sync(~0u, e.x, (lane & 28) + q), __shfl_sync(~0u, e.y, (lane & 28) + q));
                    cin = cfma(l32, cin, eq);
                    if (t == q + 1) mine = cin;
                }
                if (blk < 15) {
                    if (t == 0) sts64(sb + G_CARRY + wg * 256 + (8 * w + g) * 8, __float_as_uint(cin.x), __float_as_uint(cin.y));
                    bar_arrive(2 + wg, 256);
                }
                const uint32_t hs = sb + G_OUT + wg * 16384 + t * 4096 + (g & 3) * 4;
                const uint32_t ch = 2 * w + (g >> 2);
                if (blk >= 2) bar_sync(10 + wg, 160);
#pragma unroll
                for (int i = 0; i < 32; i++) {
                    mine = cfma(lam, mine, make_float2(d[4 * (i >> 1) + (i & 1)], d[4 * (i >> 1) + 2 + (i & 1)]));
                    sts32(hs + i * 128 + ((ch ^ (i & 7)) << 4), pack_bf16(mine.x, mine.y));
                }
                fence_async_smem();
                bar_arrive(8 + wg, 160);
            }
            bar_sync(10 + wg, 160);
        } else {
            if (tid < 128)
                asm volatile("cp.async.bulk.shared::cluster.global.mbarrier::complete_tx::bytes [%0], [%1], 1152, [%2];"
                    :: "r"(sb + tid * 1168), "l"((tid < 64 ? Cre : Cim) + (size_t)(64 * nt + (tid & 63)) * DM), "r"(sb + GB_W) : "memory");
            for (int p = tid; p < DM; p += 256) {
                float2 lam, coef;
                s5_channel(p, Lre, Lim, logdt, lam, coef);
                sts64(sb + G_EX + p * 8, __float_as_uint(2.f * coef.x), __float_as_uint(2.f * coef.y));
            }
            bar_sync(1, 256);
            mbar_wait(sb + GB_W, 0);
            const uint32_t cp = sb + (16 * w + 2 * g) * 1168 + (288 * wg + t) * 2;
#pragma unroll
            for (int u = 0; u < 72; u++) {
                const float2 c2 = lds64f(sb + G_EX + (288 * wg + 4 * u + t) * 8);
#pragma unroll
                for (int f = 0; f < 2; f++) {
                    unsigned short r16, i16;
                    asm volatile("ld.shared.u16 %0, [%1];" : "=h"(r16) : "r"(cp + f * 1168 + u * 8) : "memory");
                    asm volatile("ld.shared.u16 %0, [%1];" : "=h"(i16) : "r"(cp + (64 + f) * 1168 + u * 8) : "memory");
                    const float cr = __uint_as_float((uint32_t)r16 << 16), ci = __uint_as_float((uint32_t)i16 << 16);
                    a[2 * u + f] = pack_bf16(cr * c2.x - ci * c2.y, -(cr * c2.y + ci * c2.x));
                }
            }
            bar_sync(1, 256);
            bar_arrive(6, 288);
            BSTAMP(1);
#pragma unroll 1
            for (int j = 0; j < 8; j++) {
                bg_mainloop<9, 128>(d, a, sb, j * 18 + wg, lane);
                bg_epilogue<true, 128>(d, sb, wg, w, lane, &tm_out, 64 * nt, (2 * j + kq - 2) * 128, xa, Dk);
            }
        }
        if (w == 0) asm volatile("cp.async.bulk.wait_group 0;" ::: "memory");
        bar_sync(1, 256);
        BSTAMP(2);
        if (warp == 0)
            asm volatile("{\n.reg .pred p;\nelect.sync _|p, 0xffffffff;\n@p mbarrier.arrive.expect_tx.shared::cta.b64 _, [%2], 131072;\n"
                "@p cp.async.bulk.tensor.2d.shared::cluster.global.mbarrier::complete_tx::bytes [%0], [%1, {%3, %4}], [%2];\n"
                "@p cp.async.bulk.tensor.2d.shared::cluster.global.mbarrier::complete_tx::bytes [%0+32768], [%1, {%3, %5}], [%2];\n"
                "@p cp.async.bulk.tensor.2d.shared::cluster.global.mbarrier::complete_tx::bytes [%0+65536], [%1, {%3, %6}], [%2];\n"
                "@p cp.async.bulk.tensor.2d.shared::cluster.global.mbarrier::complete_tx::bytes [%0+98304], [%1, {%3, %7}], [%2];\n}"
                :: "r"(sb), "l"(&tm_wo), "r"(sb + GB_W), "r"(64 * nt), "r"(1024 * kq), "r"(1024 * kq + 256), "r"(1024 * kq + 512), "r"(1024 * kq + 768) : "memory");
        mbar_wait(sb + GB_W, 1);
        {
            const uint32_t base = sb + wg * 65536 + 4 * t * 128 + (g & 3) * 4, ch = 2 * w + (g >> 2), r7 = (4 * t) & 7;
#pragma unroll
            for (int ks = 0; ks < 32; ks++) {
                const uint32_t w0 = lds32(base + ks * 2048 + ((ch ^ r7) << 4)), w1 = lds32(base + ks * 2048 + 256 + ((ch ^ (r7 + 2)) << 4));
                const uint32_t w2 = lds32(base + ks * 2048 + 128 + ((ch ^ (r7 + 1)) << 4)), w3 = lds32(base + ks * 2048 + 384 + ((ch ^ (r7 + 3)) << 4));
                a[4 * ks] = __byte_perm(w0, w1, 0x5410); a[4 * ks + 1] = __byte_perm(w0, w1, 0x7632);
                a[4 * ks + 2] = __byte_perm(w2, w3, 0x5410); a[4 * ks + 3] = __byte_perm(w2, w3, 0x7632);
            }
        }
        bar_sync(1, 256);
        bar_arrive(6, 288);
        BSTAMP(3);
#pragma unroll 1
        for (int na = 0, ng = 0, it = 144; ng < NBLK;) {
            if (bg_att_turn(na, ng)) {
                if (nt < 8) {
                    if (na < NBIG || w < 2) {
                        const int i0 = it + wg + 4 * (w >> 1), i1 = i0 + 2;
                        mbar_wait(sb + GB_FULL + 8 * (i0 % NST), (i0 / NST) & 1);
                        mbar_wait(sb + GB_FULL + 8 * (i1 % NST), (i1 / NST) & 1);
                        BSTAMP(8 + na * 4);
                        bg_attention(sb + G_RING + (i0 % NST) * 16384, sb + G_RING + (i1 % NST) * 16384, w & 1, lane);
                        fence_async_smem();
                    }
                    if (na > 0) bar_sync(14, 288);
                    bar_arrive(7, 288);
                    bar_sync(1, 256);
                    BSTAMP(9 + na * 4);
                    it += na < NBIG ? 8 : 4;
                }
                na++;
            } else if (ng < NBIG) {
                bg_mainloop<8, 128>(d, a, sb, it + wg, lane);
                BSTAMP(10 + ng * 4);
                bg_epilogue<false, 128>(d, sb, wg, w, lane, &tm_out, 0, 0, xa, Dk);
                BSTAMP(11 + ng * 4);
                it += 16; ng++;
            } else {
                bg_mainloop<4, 64>(d, a, sb, it + wg, lane);
                BSTAMP(10 + ng * 4);
                bg_epilogue<false, 64>(d, sb, wg, w, lane, &tm_out, 0, 0, xa, Dk);
                BSTAMP(11 + ng * 4);
                it += 8; ng++;
            }
        }
        if (nt < 8) bar_sync(14, 288);
    }
    asm volatile("griddepcontrol.wait;" ::: "memory");
}

typedef CUresult (*EncodeFn)(CUtensorMap*, CUtensorMapDataType, cuuint32_t, void*, const cuuint64_t*, const cuuint64_t*, const cuuint32_t*, const cuuint32_t*,
                             CUtensorMapInterleave, CUtensorMapSwizzle, CUtensorMapL2promotion, CUtensorMapFloatOOBfill);
}

extern "C" void kernel_launch(void* const* d_in, const int* in_sizes, int n_in, void* d_out, int out_size) {
    typedef const __nv_bfloat16* bp;
    bp Ax = (bp)d_in[0], Lre = (bp)d_in[1], Lim = (bp)d_in[2], Bre = (bp)d_in[3], Bim = (bp)d_in[4], Cre = (bp)d_in[5], Cim = (bp)d_in[6],
       logdt = (bp)d_in[7], Dk = (bp)d_in[8], Bx = (bp)d_in[9], mem0 = (bp)d_in[10], Wq = (bp)d_in[11], Wk = (bp)d_in[12], Wv = (bp)d_in[13], Wo = (bp)d_in[14];
    float* out = (float*)d_out;
    static EncodeFn enc = nullptr;
    if (!enc) {
        void* fn = nullptr; cudaDriverEntryPointQueryResult qr;
        cudaGetDriverEntryPoint("cuTensorMapEncodeTiled", &fn, cudaEnableDefault, &qr);
        enc = (EncodeFn)fn;
        cudaFuncSetAttribute(chain_kernel, cudaFuncAttributeMaxDynamicSharedMemorySize, CHAIN_SMEM);
        cudaFuncSetAttribute(bg_kernel, cudaFuncAttributeMaxDynamicSharedMemorySize, BG_SMEM);
    }
    const cuuint32_t es[5] = {1, 1, 1, 1, 1};
    auto map2d = [&](CUtensorMap* tm, CUtensorMapDataType dt, const void* p, cuuint64_t d0, cuuint64_t d1, cuuint64_t stride, cuuint32_t b0, cuuint32_t b1) {
        cuuint64_t gd[2] = {d0, d1}, gs[1] = {stride}; cuuint32_t bd[2] = {b0, b1};
        enc(tm, dt, 2, (void*)p, gd, gs, bd, es, CU_TENSOR_MAP_INTERLEAVE_NONE, CU_TENSOR_MAP_SWIZZLE_128B, CU_TENSOR_MAP_L2_PROMOTION_L2_128B,
            CU_TENSOR_MAP_FLOAT_OOB_FILL_NONE);
    };
    CUtensorMap tm_x, tm_q, tm_k, tm_v, tm_xa, tm_wo, tm_out;
    map2d(&tm_x, CU_TENSOR_MAP_DATA_TYPE_BFLOAT16, Bx, DM, SEQ, DM * 2, 64, 32);
    map2d(&tm_q, CU_TENSOR_MAP_DATA_TYPE_BFLOAT16, Wq, HD, DM, HD * 2, 64, 192);
    map2d(&tm_k, CU_TENSOR_MAP_DATA_TYPE_BFLOAT16, Wk, HD, DM, HD * 2, 64, 192);
    map2d(&tm_v, CU_TENSOR_MAP_DATA_TYPE_BFLOAT16, Wv, HD, DM, HD * 2, 64, 192);
    map2d(&tm_wo, CU_TENSOR_MAP_DATA_TYPE_BFLOAT16, Wo, DM, HD, DM * 2, 64, 256);
    map2d(&tm_out, CU_TENSOR_MAP_DATA_TYPE_FLOAT32, out, 2 * DM, SEQ, 2 * DM * 4, 32, 64);
    {
        cuuint64_t gd[5] = {DM, 2, 4, 16, 16}, gs[4] = {DM * 2, 32 * DM * 2, 2 * DM * 2, 128 * DM * 2}; cuuint32_t bd[5] = {64, 2, 4, 16, 1};
        enc(&tm_xa, CU_TENSOR_MAP_DATA_TYPE_BFLOAT16, 5, (void*)Ax, gd, gs, bd, es, CU_TENSOR_MAP_INTERLEAVE_NONE, CU_TENSOR_MAP_SWIZZLE_128B,
            CU_TENSOR_MAP_L2_PROMOTION_L2_128B, CU_TENSOR_MAP_FLOAT_OOB_FILL_NONE);
    }
    cudaStream_t st = cudaStreamPerThread;
    chain_kernel<<<96, 384, CHAIN_SMEM, st>>>(tm_x, tm_q, tm_k, tm_v, Bx, mem0, Wo);
    cudaLaunchConfig_t cfg = {};
    cfg.gridDim = dim3(36); cfg.blockDim = dim3(384); cfg.dynamicSmemBytes = BG_SMEM; cfg.stream = st;
    cudaLaunchAttribute at[1];
    at[0].id = cudaLaunchAttributeProgrammaticStreamSerialization; at[0].val.programmaticStreamSerializationAllowed = 1;
    cfg.attrs = at; cfg.numAttrs = 1;
    cudaLaunchKernelEx(&cfg, bg_kernel, tm_xa, tm_wo, tm_out, Ax, Lre, Lim, Bre, Bim, Cre, Cim, logdt, Dk, out);
}
```

```cpp
#include <cuda_runtime.h>
#include <cuda.h>
#include <cuda_bf16.h>
#include <cuda_fp16.h>
#include <stdint.h>

#define D_WAIT 740

#define RED_GAP 720
#define ACC_PF 1
#define QDEP 0
#define NBIG 13
#define BG_AHEAD 5

namespace {

constexpr int DM = 576, NH = 32, SEQ = 2048, NSEG = 64, HD = 4096;

__device__ uint4 g_acc_raw[64 * 96 * 16 + 131072];
__device__ uint4 g_ox[NH * 2 * SEQ * 8];
constexpr int REC = 30720;
__device__ uint4 g_qkv[NSEG * NH * (REC / 16)];
__device__ uint4 g_h[18 * SEQ * 8];
constexpr int NFLAG = 6144, F_QKV = 0, F_OX = 1024, F_H = 2048, F_OUT = 3072;
constexpr int NBLK = NBIG + (NSEG - 4 * NBIG) / 2;
__host__ __device__ constexpr int blk_seg0(int b) { return b < NBIG ? 4 * b : 2 * b + 2 * NBIG; }
__device__ unsigned g_flag[NFLAG];
__device__ unsigned g_ticket, g_ticket_bg;
__device__ unsigned long long g_norm[96];
#define BSTAMP(i) do {} while (0)

__device__ __forceinline__ uint32_t smem_u32(const void* p) { return (uint32_t)__cvta_generic_to_shared(p); }
__device__ __forceinline__ uint32_t mapa(uint32_t a, uint32_t r) { uint32_t o; asm("mapa.shared::cluster.u32 %0, %1, %2;" : "=r"(o) : "r"(a), "r"(r)); return o; }
__device__ __forceinline__ uint32_t mapa_v(uint32_t a, uint32_t r) { uint32_t o; asm volatile("mapa.shared::cluster.u32 %0, %1, %2;" : "=r"(o) : "r"(a), "r"(r)); return o; }
__device__ __forceinline__ unsigned clk() { unsigned long long c; asm volatile("mov.u64 %0, %%clock64;" : "=l"(c) :: "memory"); return (unsigned)c; }
__device__ __forceinline__ void mbar_init(uint32_t bar, uint32_t cnt) { asm volatile("mbarrier.init.shared::cta.b64 [%0], %1;" :: "r"(bar), "r"(cnt) : "memory"); }
__device__ __forceinline__ void mbar_expect(uint32_t bar, uint32_t bytes) { asm volatile("mbarrier.arrive.expect_tx.shared::cta.b64 _, [%0], %1;" :: "r"(bar), "r"(bytes) : "memory"); }
__device__ __forceinline__ void mbar_wait(uint32_t bar, uint32_t parity) {
    asm volatile("{\n.reg .pred p;\n.reg .u32 n;\nmov.u32 n, 0;\n"
                 "W_%=: mbarrier.try_wait.parity.shared::cta.b64 p, [%0], %1;\n@p bra.uni D_%=;\n"
                 "add.u32 n, n, 1;\nsetp.lt.u32 p, n, 4000000;\n@p bra.uni W_%=;\ntrap;\nD_%=:\n}" :: "r"(bar), "r"(parity) : "memory");
}
__device__ __forceinline__ void mbar_expect_if(uint32_t z, uint32_t bar, uint32_t bytes) {
    asm volatile("{\n.reg .pred p;\nsetp.eq.u32 p, %2, 0;\n@p mbarrier.arrive.expect_tx.shared::cta.b64 _, [%0], %1;\n}" :: "r"(bar), "r"(bytes), "r"(z) : "memory");
}
__device__ __forceinline__ void mbar_arrive_if(uint32_t z, uint32_t bar) {
    asm volatile("{\n.reg .pred p;\nsetp.eq.u32 p, %1, 0;\n@p mbarrier.arrive.shared::cta.b64 _, [%0];\n}" :: "r"(bar), "r"(z) : "memory");
}
__device__ __forceinline__ void sts32_if(uint32_t z, uint32_t a, uint32_t x) {
    asm volatile("{\n.reg .pred p;\nsetp.eq.u32 p, %2, 0;\n@p st.shared.u32 [%0], %1;\n}" :: "r"(a), "r"(x), "r"(z) : "memory");
}
template <int K> __device__ __forceinline__ void sched_fence(int v) {
    asm volatile("{\n.reg .pred p;\nsetp.ne.s32 p, %0, %1;\n@p bra.uni F_%=;\ntrap;\nF_%=:\n}" :: "r"(v), "n"(1000 + K) : "memory");
}
__device__ __forceinline__ void spin_until(unsigned t0, unsigned d) {
    asm volatile("{\n.reg .pred p;\n.reg .u64 c;\n.reg .u32 lo;\n"
                 "S_%=: mov.u64 c, %%clock64;\ncvt.u32.u64 lo, c;\nsub.u32 lo, lo, %0;\nsetp.lt.u32 p, lo, %1;\n@p bra.uni S_%=;\n}" :: "r"(t0), "r"(d) : "memory");
}
__device__ __forceinline__ void bar_sync(int id, int n) { asm volatile("bar.sync %0, %1;" :: "r"(id), "r"(n) : "memory"); }
__device__ __forceinline__ void bar_sync_sel(int sel, int id) {
    asm volatile("{\n.reg .pred p;\nsetp.eq.u32 p, %0, 0;\n@p bar.sync %1, %3;\n@!p bar.sync %2, %3;\n}" :: "r"(sel), "r"(id), "r"(id + 1), "n"(192) : "memory");
}
__device__ __forceinline__ void bar_arrive(int id, int n) { asm volatile("bar.arrive %0, %1;" :: "r"(id), "r"(n) : "memory"); }
__device__ __forceinline__ void fence_async_smem() { asm volatile("fence.proxy.async.shared::cta;" ::: "memory"); }
__device__ __forceinline__ uint32_t pack_bf16(float lo, float hi) { uint32_t r; asm("cvt.rn.bf16x2.f32 %0, %1, %2;" : "=r"(r) : "f"(hi), "f"(lo)); return r; }
__device__ __forceinline__ uint32_t pack_f16(float lo, float hi) { uint32_t r; asm("cvt.rn.f16x2.f32 %0, %1, %2;" : "=r"(r) : "f"(hi), "f"(lo)); return r; }
__device__ __forceinline__ uint32_t f16x2_to_bf16x2(uint32_t v) { float2 f = __half22float2(*reinterpret_cast<__half2*>(&v)); return pack_bf16(f.x, f.y); }
__device__ __forceinline__ uint32_t hmul2(uint32_t a, uint32_t b) { uint32_t r; asm("mul.rn.f16x2 %0, %1, %2;" : "=r"(r) : "r"(a), "r"(b)); return r; }
__device__ __forceinline__ float ex2(float x) { float y; asm("ex2.approx.ftz.f32 %0, %1;" : "=f"(y) : "f"(x)); return y; }
__device__ __forceinline__ float ex2v(float x) { float y; asm volatile("ex2.approx.ftz.f32 %0, %1;" : "=f"(y) : "f"(x)); return y; }
__device__ __forceinline__ uint32_t absmax2(uint32_t a, uint32_t b) {
    uint32_t r; asm("max.xorsign.abs.f16x2 %0, %1, %2;" : "=r"(r) : "r"(a), "r"(b)); return r;
}
__device__ __forceinline__ uint32_t shl_v(uint32_t a, int n) { return a << n; }
__device__ __forceinline__ uint32_t max3u(uint32_t a, uint32_t b, uint32_t c) { return max(max(a, b), c); }
__device__ __forceinline__ uint4 lds128(uint32_t a) { uint4 v; asm volatile("ld.shared.v4.u32 {%0,%1,%2,%3}, [%4];" : "=r"(v.x), "=r"(v.y), "=r"(v.z), "=r"(v.w) : "r"(a) : "memory"); return v; }
__device__ __forceinline__ uint4 lds128v(uint32_t a) { uint4 v; asm volatile("ld.volatile.shared.v4.u32 {%0,%1,%2,%3}, [%4];" : "=r"(v.x), "=r"(v.y), "=r"(v.z), "=r"(v.w) : "r"(a) : "memory"); return v; }
__device__ __forceinline__ float4 lds128f(uint32_t a) { float4 v; asm volatile("ld.shared.v4.f32 {%0,%1,%2,%3}, [%4];" : "=f"(v.x), "=f"(v.y), "=f"(v.z), "=f"(v.w) : "r"(a) : "memory"); return v; }
__device__ __forceinline__ float2 lds64f(uint32_t a) { float2 v; asm volatile("ld.shared.v2.f32 {%0,%1}, [%2];" : "=f"(v.x), "=f"(v.y) : "r"(a) : "memory"); return v; }
__device__ __forceinline__ uint4 lds64x2(uint32_t a) { uint4 v; asm volatile("ld.shared.v2.u32 {%0,%1}, [%4];\nld.shared.v2.u32 {%2,%3}, [%4+256];" : "=r"(v.x), "=r"(v.y), "=r"(v.z), "=r"(v.w) : "r"(a) : "memory"); return v; }
__device__ __forceinline__ uint32_t lds32(uint32_t a) { uint32_t v; asm volatile("ld.shared.u32 %0, [%1];" : "=r"(v) : "r"(a) : "memory"); return v; }
__device__ __forceinline__ void sts128(uint32_t a, uint32_t x, uint32_t y, uint32_t z, uint32_t w) { asm volatile("st.shared.v4.u32 [%0], {%1,%2,%3,%4};" :: "r"(a), "r"(x), "r"(y), "r"(z), "r"(w) : "memory"); }
__device__ __forceinline__ void sts128f(uint32_t a, float x, float y, float z, float w) { asm volatile("st.shared.v4.f32 [%0], {%1,%2,%3,%4};" :: "r"(a), "f"(x), "f"(y), "f"(z), "f"(w) : "memory"); }
__device__ __forceinline__ void sts64(uint32_t a, uint32_t x, uint32_t y) { asm volatile("st.shared.v2.u32 [%0], {%1,%2};" :: "r"(a), "r"(x), "r"(y) : "memory"); }
__device__ __forceinline__ void sts32(uint32_t a, uint32_t x) { asm volatile("st.shared.u32 [%0], %1;" :: "r"(a), "r"(x) : "memory"); }
__device__ __forceinline__ uint4 ldsm4(uint32_t a) { uint4 v; asm volatile("ldmatrix.sync.aligned.m8n8.x4.shared.b16 {%0,%1,%2,%3}, [%4];" : "=r"(v.x), "=r"(v.y), "=r"(v.z), "=r"(v.w) : "r"(a) : "memory"); return v; }
__device__ __forceinline__ void stsm2t(uint32_t a, uint32_t x, uint32_t y) { asm volatile("stmatrix.sync.aligned.m8n8.x2.trans.shared.b16 [%0], {%1,%2};" :: "r"(a), "r"(x), "r"(y) : "memory"); }
__device__ __forceinline__ void stsm4t(uint32_t a, uint32_t x, uint32_t y, uint32_t z, uint32_t w) { asm volatile("stmatrix.sync.aligned.m8n8.x4.trans.shared.b16 [%0], {%1,%2,%3,%4};" :: "r"(a), "r"(x), "r"(y), "r"(z), "r"(w) : "memory"); }
__device__ __forceinline__ void st_async64(uint32_t a, uint32_t x, uint32_t y, uint32_t bar) { asm volatile("st.async.shared::cluster.mbarrier::complete_tx::bytes.v2.b32 [%0], {%1,%2}, [%3];" :: "r"(a), "r"(x), "r"(y), "r"(bar) : "memory"); }
__device__ __forceinline__ void bulk_s2c(uint32_t dst, uint32_t src, uint32_t bytes, uint32_t bar) { asm volatile("cp.async.bulk.shared::cluster.shared::cta.mbarrier::complete_tx::bytes [%0], [%1], %2, [%3];" :: "r"(dst), "r"(src), "r"(bytes), "r"(bar) : "memory"); }
__device__ __forceinline__ void bulk_s2g(void* dst, uint32_t src, uint32_t bytes) { asm volatile("cp.async.bulk.global.shared::cta.bulk_group [%0], [%1], %2;" :: "l"(dst), "r"(src), "r"(bytes) : "memory"); }
__device__ __forceinline__ uint32_t ldg_nc32(const void* p) { uint32_t v; asm volatile("ld.global.nc.L2::128B.u32 %0, [%1];" : "=r"(v) : "l"(p)); return v; }
__device__ __forceinline__ uint4 ldg_relaxed128(const void* p) { uint4 v; asm volatile("ld.relaxed.gpu.global.v4.u32 {%0,%1,%2,%3}, [%4];" : "=r"(v.x), "=r"(v.y), "=r"(v.z), "=r"(v.w) : "l"(p) : "memory"); return v; }
__device__ __forceinline__ void mma16816(float (&d)[4], uint32_t a0, uint32_t a1, uint32_t a2, uint32_t a3, uint32_t b0, uint32_t b1) {
    asm volatile("mma.sync.aligned.m16n8k16.row.col.f32.bf16.bf16.f32 {%0,%1,%2,%3}, {%4,%5,%6,%7}, {%8,%9}, {%0,%1,%2,%3};"
        : "+f"(d[0]), "+f"(d[1]), "+f"(d[2]), "+f"(d[3]) : "r"(a0), "r"(a1), "r"(a2), "r"(a3), "r"(b0), "r"(b1));
}
__device__ __forceinline__ void mma16816_z(float (&d)[4], uint32_t a0, uint32_t a1, uint32_t a2, uint32_t a3, uint32_t b0, uint32_t b1) {
    asm volatile("mma.sync.aligned.m16n8k16.row.col.f32.bf16.bf16.f32 {%0,%1,%2,%3}, {%4,%5,%6,%7}, {%8,%9}, {%10,%10,%10,%10};"
        : "=f"(d[0]), "=f"(d[1]), "=f"(d[2]), "=f"(d[3]) : "r"(a0), "r"(a1), "r"(a2), "r"(a3), "r"(b0), "r"(b1), "f"(0.f));
}
__device__ __forceinline__ void mma1688(float (&d)[4], uint32_t a0, uint32_t a1, uint32_t b0) {
    asm volatile("mma.sync.aligned.m16n8k8.row.col.f32.bf16.bf16.f32 {%0,%1,%2,%3}, {%4,%5}, {%6}, {%0,%1,%2,%3};"
        : "+f"(d[0]), "+f"(d[1]), "+f"(d[2]), "+f"(d[3]) : "r"(a0), "r"(a1), "r"(b0));
}
__device__ __forceinline__ void mma1688_z(float (&d)[4], uint32_t a0, uint32_t a1, uint32_t b0) {
    asm volatile("mma.sync.aligned.m16n8k8.row.col.f32.bf16.bf16.f32 {%0,%1,%2,%3}, {%4,%5}, {%6}, {%7,%7,%7,%7};"
        : "=f"(d[0]), "=f"(d[1]), "=f"(d[2]), "=f"(d[3]) : "r"(a0), "r"(a1), "r"(b0), "f"(0.f));
}
template <int ACC>
__device__ __forceinline__ void wgmma_n32_rs(float (&d)[16], uint32_t a0, uint32_t a1, uint32_t a2, uint32_t a3, uint64_t desc) {
    asm volatile("wgmma.mma_async.sync.aligned.m64n32k16.f32.bf16.bf16 {%0,%1,%2,%3,%4,%5,%6,%7,%8,%9,%10,%11,%12,%13,%14,%15}, {%16,%17,%18,%19}, %20, %21, 1, 1, 0;"
        : "+f"(d[0]), "+f"(d[1]), "+f"(d[2]), "+f"(d[3]), "+f"(d[4]), "+f"(d[5]), "+f"(d[6]), "+f"(d[7]),
          "+f"(d[8]), "+f"(d[9]), "+f"(d[10]), "+f"(d[11]), "+f"(d[12]), "+f"(d[13]), "+f"(d[14]), "+f"(d[15])
        : "r"(a0), "r"(a1), "r"(a2), "r"(a3), "l"(desc), "n"(ACC));
}
template <int ACC>
__device__ __forceinline__ void wgmma_n32_ss(float (&d)[16], uint64_t da, uint64_t db) {
    asm volatile("wgmma.mma_async.sync.aligned.m64n32k16.f32.bf16.bf16 {%0,%1,%2,%3,%4,%5,%6,%7,%8,%9,%10,%11,%12,%13,%14,%15}, %16, %17, %18, 1, 1, 0, 0;"
        : "+f"(d[0]), "+f"(d[1]), "+f"(d[2]), "+f"(d[3]), "+f"(d[4]), "+f"(d[5]), "+f"(d[6]), "+f"(d[7]),
          "+f"(d[8]), "+f"(d[9]), "+f"(d[10]), "+f"(d[11]), "+f"(d[12]), "+f"(d[13]), "+f"(d[14]), "+f"(d[15])
        : "l"(da), "l"(db), "n"(ACC));
}
__device__ __forceinline__ void wg_fence() { asm volatile("wgmma.fence.sync.aligned;" ::: "memory"); }
__device__ __forceinline__ void wg_commit() { asm volatile("wgmma.commit_group.sync.aligned;" ::: "memory"); }
__device__ __forceinline__ void wg_wait0() { asm volatile("wgmma.wait_group.sync.aligned 0;" ::: "memory"); }
__device__ __forceinline__ void cluster_sync() { asm volatile("barrier.cluster.arrive.aligned;\nbarrier.cluster.wait.aligned;" ::: "memory"); }

#define STAMP(s, i) do {} while (0)
#define STAMPV(s, i, v) do {} while (0)

constexpr int XT_BYTES = 36864;
constexpr int O_XT = 0;
constexpr int O_STG = XT_BYTES;
constexpr int O_AS = 3 * XT_BYTES;
constexpr int O_XP = O_AS + 16384;
constexpr int O_QKX = O_XP + 8192;
constexpr int O_KM = O_QKX + 8192;
constexpr int O_QM = O_QKX + 10240;
constexpr int O_VX = O_STG + 147456;
constexpr int O_VM = O_VX + 16384;
constexpr int O_SC = O_VM + 2048;
constexpr int O_OF = O_SC + 2560;
constexpr int O_AF = O_OF + 2048;
constexpr int O_WP = O_AF + 4096;
constexpr int O_MF = O_WP + 2048;
constexpr int O_MISC = O_MF + 9216;
static_assert(O_QKX + 24576 <= O_VX, "smem");
constexpr int O_BAR = O_MISC + 64;
constexpr int CHAIN_SMEM = O_BAR + 128;
static_assert(CHAIN_SMEM <= 232448, "smem");
constexpr int B_X = O_BAR, B_VX = O_BAR + 24, B_SC = O_BAR + 40, B_W = O_BAR + 48;
constexpr float SM_SCALE = 0.08838834764831845f * 1.4426950408889634f;
constexpr uint32_t ONES = 0x3f803f80u;

__device__ __forceinline__ uint32_t opaque(uint32_t v) { uint32_t o; asm volatile("mov.u32 %0, %1;" : "=r"(o) : "r"(v)); return o; }
__device__ __forceinline__ void st_async128(uint32_t a, uint32_t x, uint32_t y, uint32_t z, uint32_t w, uint32_t bar) {
    asm volatile("st.async.shared::cluster.mbarrier::complete_tx::bytes.v4.b32 [%0], {%1,%2,%3,%4}, [%5];" :: "r"(a), "r"(x), "r"(y), "r"(z), "r"(w), "r"(bar) : "memory");
}
__device__ __forceinline__ void tma_x_tile(uint32_t sb, const CUtensorMap* tm, int r, int j, int slot) {
    asm volatile("{\n.reg .pred p;\nelect.sync _|p, 0xffffffff;\n"
        "@p mbarrier.arrive.expect_tx.shared::cta.b64 _, [%2], 36864;\n"
        "@p cp.async.bulk.tensor.2d.shared::cluster.global.mbarrier::complete_tx::bytes.multicast::cluster [%0], [%1, {%3, %4}], [%2], %7;\n"
        "@p cp.async.bulk.tensor.2d.shared::cluster.global.mbarrier::complete_tx::bytes.multicast::cluster [%0+4096], [%1, {%5, %4}], [%2], %7;\n"
        "@p cp.async.bulk.tensor.2d.shared::cluster.global.mbarrier::complete_tx::bytes.multicast::cluster [%0+8192], [%1, {%6, %4}], [%2], %7;\n}"
        :: "r"(sb + O_XT + slot * XT_BYTES + 3 * r * 4096), "l"(tm), "r"(sb + B_X + 8 * slot), "r"(192 * r), "r"(j * 32), "r"(192 * r + 64), "r"(192 * r + 128),
           "h"((unsigned short)7) : "memory");
}
__device__ __forceinline__ void flag_inc_if(uint32_t z, unsigned* p) {
    asm volatile("{\n.reg .pred p;\nsetp.eq.u32 p, %1, 0;\n@p red.release.gpu.global.inc.u32 [%0], 0xfffffffe;\n}" :: "l"(p), "r"(z) : "memory");
}
__device__ __forceinline__ float quad_max(float v) {
    const float a = __shfl_xor_sync(~0u, v, 1), b = __shfl_xor_sync(~0u, v, 2), c = __shfl_xor_sync(~0u, v, 3);
    return fmaxf(fmaxf(v, a), fmaxf(b, c));
}
__device__ __forceinline__ void load_scores(float (&p)[10], uint32_t base, uint32_t stride, uint32_t l16) {
    const float4 a0 = lds128f(base + l16), b0 = lds128f(base + stride + l16);
    const float4 a1 = lds128f(base + 512 + l16), b1 = lds128f(base + stride + 512 + l16);
    const float2 a2 = lds64f(base + 1024 + (l16 >> 1)), b2 = lds64f(base + stride + 1024 + (l16 >> 1));
    p[0] = a2.x + b2.x; p[1] = a2.y + b2.y;
    p[2] = a0.x + b0.x; p[3] = a0.y + b0.y; p[4] = a0.z + b0.z; p[5] = a0.w + b0.w;
    p[6] = a1.x + b1.x; p[7] = a1.y + b1.y; p[8] = a1.z + b1.z; p[9] = a1.w + b1.w;
}
__device__ __forceinline__ float rcp_fast(float x) { float y; asm("rcp.approx.ftz.f32 %0, %1;" : "=f"(y) : "f"(x)); return y; }

__global__ void __cluster_dims__(3, 1, 1) __launch_bounds__(384, 1)
chain_kernel(const __grid_constant__ CUtensorMap tm_x, const __grid_constant__ CUtensorMap tm_q,
             const __grid_constant__ CUtensorMap tm_k, const __grid_constant__ CUtensorMap tm_v,
             const __nv_bfloat16* __restrict__ x, const __nv_bfloat16* __restrict__ mem0,
             const __nv_bfloat16* __restrict__ Wo) {
    extern __shared__ __align__(1024) uint8_t smem_raw[];
    const uint32_t sb = smem_u32(smem_raw);
    const int lane = threadIdx.x & 31;
    const int warp = __shfl_sync(~0u, threadIdx.x >> 5, 0);
    const int wg = warp >> 2, w = warp & 3;
    const int h = blockIdx.x / 3, r = blockIdx.x - 3 * h;
    uint4* const g_acc = reinterpret_cast<uint4*>((reinterpret_cast<uintptr_t>(g_acc_raw) + 0x1fffff) & ~(uintptr_t)0x1fffff);

#define PSTAMP(i) do {} while (0)
    if (threadIdx.x == 0) {
        if (sb & 1023u) __trap();
        for (int i = 0; i < 9; i++) mbar_init(sb + O_BAR + 8 * i, 1);
        asm volatile("fence.mbarrier_init.release.cluster;" ::: "memory");
        for (int i = 0; i < 3; i++) {
            mbar_expect(sb + B_W + 8 * i, 49152);
            for (int tl = 0; tl < 2; tl++)
                asm volatile("cp.async.bulk.tensor.2d.shared::cluster.global.mbarrier::complete_tx::bytes [%0], [%1, {%3, %4}], [%2];"
                    :: "r"(sb + O_STG + tl * 73728 + i * 24576), "l"(r < 2 ? (tl ? &tm_k : &tm_q) : &tm_v), "r"(sb + B_W + 8 * i),
                       "r"(h * 128 + 64 * (r < 2 ? r : tl)), "r"(192 * i) : "memory");
        }
    }
    __syncwarp();
    asm volatile("barrier.cluster.arrive.relaxed.aligned;" ::: "memory");
    asm volatile("griddepcontrol.launch_dependents;" ::: "memory");
    if (warp == 0) PSTAMP(9);
    const uint32_t l16c = __shfl_sync(~0u, lane * 16, lane);

    if (wg < 2) {
#define KS(u) ((u) < 8 ? 12 * ((u) >> 2) + (((u) >> 1) & 1) + 4 * ((u) & 1) : (u) < 12 ? (u) : (u) < 16 ? (u) + 8 : (u) < 24 ? 24 + (((u) - 16) >> 1) + 4 * ((u) & 1) : (u) + 8)
        asm volatile("setmaxnreg.inc.sync.aligned.u32 184;");
        uint32_t a[144];
        uint32_t adr1;
        {
            const int g = lane >> 2, t = lane & 3;
            const int t1 = threadIdx.x;
#pragma unroll
            for (int i = 0; i < 2; i++) g_acc[(blockIdx.x * 64 + i * 32 + (t1 >> 3)) * 16 + (t1 & 7)] = make_uint4(0, 0, 0, 0);
            __threadfence();
            asm volatile("barrier.cluster.wait.aligned;" ::: "memory");
            const uint32_t ev = sb + O_STG + (2 * t) * 128 + (((2 * w + (g >> 2)) ^ (2 * t)) << 4) + (g & 3) * 4;
            const uint32_t od = (ev ^ 16) + 128;
            auto gather = [&](int dst, uint32_t off) {
                a[dst] = lds32(ev + off); a[dst + 1] = lds32(od + off); a[dst + 2] = lds32(ev + off + 1024); a[dst + 3] = lds32(od + off + 1024);
            };
            const uint4* xp = reinterpret_cast<const uint4*>(x) + blockIdx.x * 1536 + t1;
            uint4 xv[6];
#pragma unroll
            for (int th = 0; th < 2; th++) {
                mbar_wait(sb + B_W + 8 * th, 0);
                if (th == 1) {
#pragma unroll
                    for (int i = 0; i < 6; i++) xv[i] = __ldg(xp + i * 256);
                }
#pragma unroll
                for (int u = 4 * th; u < 4 * th + 4; u++) {
                    gather(32 + 4 * u, wg * (73728 + 4096) + KS(u) * 2048);
                    gather(4 * u, 73728 - wg * (73728 - 4096) + KS(u) * 2048);
                    gather(64 + 4 * u, wg * 73728 + KS(8 + u) * 2048);
                }
            }
            mbar_wait(sb + B_W + 16, 0);
#pragma unroll
            for (int u = 16; u < 28; u++) gather(32 + 4 * u, wg * 73728 + KS(u) * 2048);
#pragma unroll
            for (int kk = 0; kk < 72; kk++) {
                uint32_t w0 = a[2 * kk], w1 = a[2 * kk + 1];
                a[2 * kk] = __byte_perm(w0, w1, 0x5410);
                a[2 * kk + 1] = __byte_perm(w0, w1, 0x7632);
            }
            if (r == 2) {
                float n0[4], n1[4];
#pragma unroll
                for (int u = 0; u < 36; u++) {
                    const uint32_t x0 = a[4 * u] & 0x7fff7fffu, x1 = a[4 * u + 1] & 0x7fff7fffu, x2 = a[4 * u + 2] & 0x7fff7fffu, x3 = a[4 * u + 3] & 0x7fff7fffu;
                    if (u == 0) mma16816_z(n0, x0, x1, x2, x3, ONES, ONES);
                    else if (u < 8) mma16816(n0, x0, x1, x2, x3, ONES, ONES);
                    else if (u == 8) mma16816_z(n1, x0, x1, x2, x3, ONES, ONES);
                    else mma16816(n1, x0, x1, x2, x3, ONES, ONES);
                }
                const uint32_t mx = __reduce_max_sync(~0u, __float_as_uint(2.f * fmaxf(fmaxf(n0[0], n0[2]), fmaxf(n1[0], n1[2]))));
                sts32_if(lane, sb + O_MISC + 32 + 4 * warp, mx);
            }
            uint32_t xm = 0;
#pragma unroll
            for (int i = 0; i < 6; i++)
                xm = __vmaxu2(xm, __vmaxu2(__vmaxu2(xv[i].x & 0x7fff7fffu, xv[i].y & 0x7fff7fffu), __vmaxu2(xv[i].z & 0x7fff7fffu, xv[i].w & 0x7fff7fffu)));
            sts32_if(lane, sb + O_OF + 16 + 4 * warp, __reduce_max_sync(~0u, max(xm << 16, xm & 0xffff0000u)));
            if (warp == 0) PSTAMP(11);
            bar_arrive(7, 384);
            asm volatile("barrier.cluster.arrive.relaxed.aligned;" ::: "memory");
            bar_sync(1, 256);
            const uint32_t as = sb + O_AS + wg * 8192 + (16 * w + g) * 128 + t * 4;
            sts32(as + (g << 4), a[32]);
            sts32(as + 1024 + (g << 4), a[33]);
            sts32(as + ((1 ^ g) << 4), a[34]);
            sts32(as + 1024 + ((1 ^ g) << 4), a[35]);
            sts128(sb + O_AF + warp * 512 + lane * 16, a[32], a[33], a[34], a[35]);
            fence_async_smem();
            bar_sync(1, 256);
            const uint32_t l = lane * 16;
            const int mi = lane >> 3, isk = (mi >> 1) ? wg : (wg ^ 1);
            adr1 = (r == 2) ? (sb + O_VM + warp * 256 + (l >> 1))
                            : (isk ? (sb + O_KM + w * 512 + wg * 256 + (mi & 1) * 128 + (l & 127))
                                   : (sb + O_QM + w * 512 + (mi & 1) * 256 + wg * 128 + (l & 127)));
            adr1 = __shfl_sync(~0u, adr1, lane);
        }
        int s3 = 2;
#pragma unroll 1
        for (int s = -1; s < NSEG; s++) {
            const uint32_t l16 = opaque(l16c);
            s3 = (s3 == 2) ? 0 : s3 + 1;
            if (s < 0) mbar_wait(sb + B_X, 0);
            const uint64_t desc0 = (uint64_t)(((sb + O_XT + s3 * XT_BYTES) & 0x3FFFF) >> 4) | (1ull << 16) | (64ull << 32) | (1ull << 62);
            uint32_t km0 = 0, km1 = 0;
            if (s >= 0) {
                { const uint4 v = lds128(sb + O_AF + warp * 512 + l16); a[32] = v.x; a[33] = v.y; a[34] = v.z; a[35] = v.w; }
                float co[4], cw[3][4];
                uint4 b[14];
                float inv;
#define GORD(i) ((i) < 8 ? 2 * ((i) >> 2) + (((i) >> 1) & 1) + 4 * ((i) & 1) : (i))
                auto qkv_mma = [&](int i) {
                    const int gi = GORD(i), u = 8 * gi, n0 = 2 * i, n1 = 2 * i + 1;
                    if (gi < 4) {
                        if (i == 0) mma16816_z(co, a[u], a[u + 1], a[u + 2], a[u + 3], b[0].x, b[0].y);
                        else mma16816(co, a[u], a[u + 1], a[u + 2], a[u + 3], b[i].x, b[i].y);
                    }
                    if (n0 < 3) mma16816_z(cw[n0 % 3], a[32 + u], a[32 + u + 1], a[32 + u + 2], a[32 + u + 3], b[i].x, b[i].y);
                    else mma16816(cw[n0 % 3], a[32 + u], a[32 + u + 1], a[32 + u + 2], a[32 + u + 3], b[i].x, b[i].y);
                    if (n1 < 3) mma16816_z(cw[n1 % 3], a[32 + u + 4], a[32 + u + 5], a[32 + u + 6], a[32 + u + 7], b[i].z, b[i].w);
                    else mma16816(cw[n1 % 3], a[32 + u + 4], a[32 + u + 5], a[32 + u + 6], a[32 + u + 7], b[i].z, b[i].w);
                    if (gi < 4) mma16816(co, a[u + 4], a[u + 5], a[u + 6], a[u + 7], b[i].z, b[i].w);
                };
                const uint32_t mf = sb + O_MF + l16, mfs = mf + wg * 1024;
                const uint32_t qb = (s & 1) * 12288;
                bar_sync(2, 384);
                if (warp == 0) STAMP(s, 0);
                auto qkv_ld = [&](int i) {
                    const int gi = GORD(i);
                    b[i] = gi < 4 ? lds128v(mfs + (gi >> 1) * 3072 + (gi & 1) * 512) : lds128v(mf + (gi < 6 ? gi : gi + 4) * 512);
                };
#pragma unroll
                for (int i = 0; i < 4; i++) qkv_ld(i);
                qkv_mma(0); qkv_mma(1); qkv_mma(2);
                const uint32_t z0 = __float_as_uint(QDEP ? co[0] : cw[1][0]) & (l16 & 15u);
                qkv_mma(3);
                bar_sync(15, 384);
                b[4] = lds128v(mfs + 3072 + z0);
#pragma unroll
                for (int i = 5; i < 9; i++) qkv_ld(i);
#pragma unroll
                for (int i = 4; i < 9; i++) { qkv_mma(i); qkv_ld(5 + i); }
                asm volatile("ld.volatile.shared.f32 %0, [%1];" : "=f"(inv) : "r"(sb + O_MISC) : "memory");
#pragma unroll
                for (int i = 9; i < 14; i++) qkv_mma(i);
#pragma unroll
                for (int i = 0; i < 4; i++) cw[0][i] += cw[1][i] + cw[2][i];
                if (r < 2) {
                    const uint32_t o0 = pack_bf16(co[0] * inv, co[1] * inv), o1 = pack_bf16(co[2] * inv, co[3] * inv);
                    const uint32_t w0 = pack_bf16(cw[0][0] * inv, cw[0][1] * inv), w1 = pack_bf16(cw[0][2] * inv, cw[0][3] * inv);
                    stsm4t(adr1 + qb, o0, o1, w0, w1);
                    if (warp == 0) STAMP(s, 1);
                    asm volatile("{\n.reg .pred p;\nsetp.ge.u32 p, %0, 3;\n@p bar.arrive 1, 256;\n}" :: "r"(warp) : "memory");
                    auto scores = [&](float (&v)[4], const uint4 (&q)[4], const uint4 (&k)[4]) {
                        float s0[4], s1[4], t0[4], t1[4];
                        mma16816_z(s0, q[0].x, q[0].y, q[0].z, q[0].w, k[0].x, k[0].y);
                        mma16816_z(s1, q[0].x, q[0].y, q[0].z, q[0].w, k[0].z, k[0].w);
                        mma16816_z(t0, q[1].x, q[1].y, q[1].z, q[1].w, k[1].x, k[1].y);
                        mma16816_z(t1, q[1].x, q[1].y, q[1].z, q[1].w, k[1].z, k[1].w);
                        mma16816(s0, q[2].x, q[2].y, q[2].z, q[2].w, k[2].x, k[2].y);
                        mma16816(s1, q[2].x, q[2].y, q[2].z, q[2].w, k[2].z, k[2].w);
                        mma16816(t0, q[3].x, q[3].y, q[3].z, q[3].w, k[3].x, k[3].y);
                        mma16816(t1, q[3].x, q[3].y, q[3].z, q[3].w, k[3].z, k[3].w);
                        v[0] = (s0[0] + s0[2]) + (t0[0] + t0[2]); v[1] = (s0[1] + s0[3]) + (t0[1] + t0[3]);
                        v[2] = (s1[0] + s1[2]) + (t1[0] + t1[2]); v[3] = (s1[1] + s1[3]) + (t1[1] + t1[3]);
                    };
                    if (warp < 2) {
                        uint4 q[4], k[4]; float v[4];
#pragma unroll
                        for (int i = 0; i < 4; i++) k[i] = ldsm4(sb + O_QKX + 4096 + qb + warp * 2048 + i * 512 + l16);
                        bar_sync(1, 256);
#pragma unroll
                        for (int i = 0; i < 4; i++) q[i] = ldsm4(sb + O_QM + qb + i * 512 + l16);
                        scores(v, q, k);
                        const uint32_t dst = sb + O_SC + r * 1280 + warp * 512 + l16;
                        st_async128(mapa(dst, 2), __float_as_uint(v[0]), __float_as_uint(v[1]), __float_as_uint(v[2]), __float_as_uint(v[3]), mapa(sb + B_SC, 2));
                        st_async128(mapa(dst, r ^ 1), __float_as_uint(v[0]), __float_as_uint(v[1]), __float_as_uint(v[2]), __float_as_uint(v[3]), mapa(sb + B_SC, r ^ 1));
                        st_async128(mapa(dst, r), __float_as_uint(v[0]), __float_as_uint(v[1]), __float_as_uint(v[2]), __float_as_uint(v[3]), mapa(sb + B_SC, r));
                    } else if (warp == 2) {
                        uint4 q[4], k[4]; float v[4];
                        bar_sync(1, 256);
#pragma unroll
                        for (int i = 0; i < 4; i++) { q[i] = ldsm4(sb + O_QM + qb + i * 512 + l16); k[i] = ldsm4(sb + O_KM + qb + i * 512 + l16); }
                        scores(v, q, k);
                        const uint32_t dst = sb + O_SC + r * 1280 + 1024 + (l16 >> 1);
                        st_async64(mapa(dst, 2), __float_as_uint(v[0] + v[2]), __float_as_uint(v[1] + v[3]), mapa(sb + B_SC, 2));
                        st_async64(mapa(dst, r ^ 1), __float_as_uint(v[0] + v[2]), __float_as_uint(v[1] + v[3]), mapa(sb + B_SC, r ^ 1));
                        st_async64(mapa(dst, r), __float_as_uint(v[0] + v[2]), __float_as_uint(v[1] + v[3]), mapa(sb + B_SC, r));
                        STAMP(s, 2);
                    }
                } else {
                    sts128f(sb + O_XP + warp * 512 + l16, co[0], co[1], co[2], co[3]);
                    bar_sync(8 + w, 64);
                    const float4 o = lds128f(sb + O_XP + (warp ^ 4) * 512 + l16);
                    km0 = pack_bf16((cw[0][0] + o.x) * inv, (cw[0][1] + o.y) * inv);
                    km1 = pack_bf16((cw[0][2] + o.z) * inv, (cw[0][3] + o.w) * inv);
                    if (warp == 0) STAMP(s, 1);
                    st_async64(mapa(adr1, 0), km0, km1, mapa(sb + B_SC, 0));
                    st_async64(mapa(adr1, 1), km0, km1, mapa(sb + B_SC, 1));
                    st_async64(mapa(adr1, 2), km0, km1, mapa(sb + B_SC, 2));
                    if (warp == 0) STAMP(s, 2);
                }
            }
            if (s >= 0) bar_sync(3, 384);
            auto store_qk = [&]() {
                asm volatile("{\n.reg .pred p;\nelect.sync _|p, 0xffffffff;\n"
                    "@p cp.async.bulk.global.shared::cta.bulk_group [%0], [%1], 10240;\n@p cp.async.bulk.commit_group;\n}"
                    :: "l"(reinterpret_cast<char*>(g_qkv) + (size_t)(s * NH + h) * REC + r * 10240), "r"(sb + O_QKX + (s & 1) * 12288) : "memory");
            };
            auto store_vm = [&]() {
                *reinterpret_cast<uint2*>(reinterpret_cast<char*>(g_qkv) + (size_t)(s * NH + h) * REC + 28672 + warp * 256 + (l16 >> 1)) = make_uint2(km0, km1);
            };
            if (s == NSEG - 1) {
                if (r == 2) store_vm();
                else if (warp == 3) {
                    fence_async_smem();
                    store_qk();
                    asm volatile("cp.async.bulk.wait_group 0;\nfence.proxy.async.global;" ::: "memory");
                }
            } else {
                const int j = s + 1;
#define XDESC(u) (((u) < 8 ? descs : desc0) + (uint64_t)(((KS(u) >> 2) * 4096 + (KS(u) & 3) * 32) >> 4))
                const uint64_t descs = desc0 + (uint64_t)(wg * 4);
                float d[16];
                wg_fence();
#pragma unroll
                for (int u = 0; u < 8; u++) {
                    if (u == 0) wgmma_n32_rs<0>(d, a[0], a[1], a[2], a[3], XDESC(0));
                    else wgmma_n32_rs<1>(d, a[4 * u], a[4 * u + 1], a[4 * u + 2], a[4 * u + 3], XDESC(u));
                }
                wg_commit();
                wg_wait0();
                if (warp == 0) STAMP(s, 15);
                if (warp == 3) asm volatile("cp.async.bulk.wait_group.read 0;" ::: "memory");
                if (s >= 0) bar_sync(4, 384);
#pragma unroll
                for (int q = 0; q < 2; q++)
                    sts128(sb + O_XP + warp * 1024 + q * 512 + l16, pack_bf16(d[8 * q], d[8 * q + 1]), pack_bf16(d[8 * q + 2], d[8 * q + 3]),
                           pack_bf16(d[8 * q + 4], d[8 * q + 5]), pack_bf16(d[8 * q + 6], d[8 * q + 7]));
                bar_sync(12, 256);
#pragma unroll
                for (int q = 0; q < 2; q++) {
                    const uint4 o = lds128(sb + O_XP + (warp ^ 4) * 1024 + q * 512 + l16);
                    d[8 * q] = __uint_as_float(o.x << 16); d[8 * q + 1] = __uint_as_float(o.x & 0xffff0000u);
                    d[8 * q + 2] = __uint_as_float(o.y << 16); d[8 * q + 3] = __uint_as_float(o.y & 0xffff0000u);
                    d[8 * q + 4] = __uint_as_float(o.z << 16); d[8 * q + 5] = __uint_as_float(o.z & 0xffff0000u);
                    d[8 * q + 6] = __uint_as_float(o.w << 16); d[8 * q + 7] = __uint_as_float(o.w & 0xffff0000u);
                }
                if (s >= 0) {
                    if (r == 2) store_vm();
                    if (warp == 5 && s + 2 < NSEG) tma_x_tile(sb, &tm_x, r, s + 2, s3 == 2 ? 0 : s3 + 1);
                    if (warp == 3) {
                        asm volatile("cp.async.bulk.wait_group 0;\nfence.proxy.async.global;" ::: "memory");
                        if (s >= 4 && !(s & (s > 4 * NBIG ? 1 : 3))) {
                            __syncwarp();
                            flag_inc_if(l16, &g_flag[F_QKV + ((s > 4 * NBIG ? 2 * s - 4 * NBIG : s) - 4 + (h >> 3)) * 8]);
                        }
                        fence_async_smem();
                    }
                    asm volatile("{\n.reg .pred p;\nsetp.eq.u32 p, %0, 0;\n@p bar.sync 5, 256;\n@!p bar.sync 13, 256;\n}" :: "r"(wg) : "memory");
                }
                const uint64_t da0 = (uint64_t)(((sb + O_AS + wg * 8192) & 0x3FFFF) >> 4) | (1ull << 16) | (64ull << 32) | (1ull << 62);
                wg_fence();
                wgmma_n32_ss<1>(d, da0, XDESC(0));
#pragma unroll
                for (int u = 1; u < 28; u++) wgmma_n32_rs<1>(d, a[32 + 4 * u], a[32 + 4 * u + 1], a[32 + 4 * u + 2], a[32 + 4 * u + 3], XDESC(u));
                wg_commit();
                wg_wait0();
                if (warp == 3 && r < 2 && s >= 0) store_qk();
                if (warp == 4) STAMP(s, 3);
                uint32_t e[8];
#pragma unroll
                for (int i = 0; i < 8; i++) e[i] = pack_bf16(d[2 * i], d[2 * i + 1]);
                if (r < 2) {
                    const uint32_t base = sb + O_QKX + (j & 1) * 12288 + wg * 4096 + w * 512 + l16;
                    stsm4t(base, e[0], wg ? e[1] : e[2], wg ? e[2] : e[1], e[3]);
                    stsm4t(base + 2048, e[4], wg ? e[5] : e[6], wg ? e[6] : e[5], e[7]);
                } else {
                    const uint32_t base = sb + O_VX + (j & 1) * 8192 + warp * 1024 + l16;
                    sts128(base, e[0], e[1], e[2], e[3]);
                    sts128(base + 512, e[4], e[5], e[6], e[7]);
                    bar_arrive(14, 288);
                }
                if (warp == 7) STAMP(s, 4);
                if (s < 0) asm volatile("barrier.cluster.wait.aligned;" ::: "memory");
            }
        }
        bar_arrive(7, 384);
    } else {
        asm volatile("setmaxnreg.dec.sync.aligned.u32 136;");
        const int c = w;
        uint32_t a[96];
        uint32_t mmax = 0;
        {
            const int g = lane >> 2, t = lane & 3;
            uint32_t tag = 0, m0v[18];
            if (threadIdx.x == 256) tag = atomicAdd(&g_ticket, 1u);
#pragma unroll
            for (int i = 0; i < 9; i++) {
                const uint32_t* p = reinterpret_cast<const uint32_t*>(mem0 + g * DM + 16 * (4 * i + c) + 2 * t);
                m0v[2 * i] = __ldg(p); m0v[2 * i + 1] = __ldg(p + 4);
            }
            asm volatile("barrier.cluster.wait.aligned;" ::: "memory");
            if (c == 0) {
                tma_x_tile(sb, &tm_x, r, 0, 0);
                mbar_expect_if(lane, sb + B_SC, 4608);
                if (r < 2) mbar_expect_if(lane, sb + B_VX, 8192);
                sts32_if(lane, sb + O_MISC, __float_as_uint(1.0f));
                sts32_if(lane, sb + O_MISC + 12, __float_as_uint(SM_SCALE));
            }
            asm volatile("barrier.cluster.arrive.relaxed.aligned;" ::: "memory");
#pragma unroll
            for (int tau = 0; tau < 3; tau++) {
                const uint32_t* v = m0v + 6 * tau;
                sts128(sb + O_MF + tau * 3072 + c * 512 + lane * 16, v[0], v[1], v[2], v[3]);
                sts64(sb + O_MF + tau * 3072 + 2048 + (c >> 1) * 512 + lane * 16 + (c & 1) * 8, v[4], v[5]);
#pragma unroll
                for (int i = 0; i < 6; i++) mmax = __vmaxu2(mmax, v[i] & 0x7fff7fffu);
            }
            mmax = max(mmax << 16, mmax & 0xffff0000u);
            bar_arrive(2, 384); bar_arrive(15, 384);
            tag = (__shfl_sync(~0u, tag, 0) / 96u + 1u) & 0xffffu;
            mbar_wait(sb + B_W + 0, 0);
            const __nv_bfloat16* p = Wo + (size_t)(h * 128 + 4 * t) * DM + 192 * r + 16 * c + 2 * g;
#pragma unroll
            for (int i = 0; i < 3; i++)
#pragma unroll
                for (int eb = 0; eb < 8; eb++)
#pragma unroll
                    for (int j = 0; j < 4; j++) a[(i * 8 + eb) * 4 + j] = ldg_nc32(p + (16 * eb + ((j & 1) * 2 + (j >> 1))) * DM + 64 * i);
#pragma unroll
            for (int kk = 0; kk < 48; kk++) {
                uint32_t w0 = a[2 * kk], w1 = a[2 * kk + 1];
                a[2 * kk] = __byte_perm(w0, w1, 0x5410);
                a[2 * kk + 1] = __byte_perm(w0, w1, 0x7632);
            }
            sts128(sb + O_WP + c * 512 + lane * 16, a[92], a[93], a[94], a[95]);
            float wmax = 0.f;
#pragma unroll
            for (int i = 0; i < 3; i++) {
                float n0[4];
#pragma unroll
                for (int u = 8 * i; u < 8 * i + 8; u++) {
                    const uint32_t x0 = a[4 * u] & 0x7fff7fffu, x1 = a[4 * u + 1] & 0x7fff7fffu, x2 = a[4 * u + 2] & 0x7fff7fffu, x3 = a[4 * u + 3] & 0x7fff7fffu;
                    if (u == 8 * i) mma16816_z(n0, x0, x1, x2, x3, ONES, ONES);
                    else mma16816(n0, x0, x1, x2, x3, ONES, ONES);
                }
                wmax = fmaxf(wmax, fmaxf(n0[0], n0[2]));
            }
            uint32_t wm = __reduce_max_sync(~0u, __float_as_uint(wmax));
            sts32_if(lane, sb + O_OF + 4 * c, wm);
            if (c == 0) PSTAMP(8);
            bar_sync(7, 384);
            asm volatile("barrier.cluster.wait.aligned;" ::: "memory");
            if (c == 1) tma_x_tile(sb, &tm_x, r, 1, 1);
            if (c == 0) {
                const uint4 wq = lds128(sb + O_OF), xq = lds128(sb + O_OF + 16), xr = lds128(sb + O_OF + 32), v0 = lds128(sb + O_MISC + 32), v1 = lds128(sb + O_MISC + 48);
                const uint32_t w1 = max(max(wq.x, wq.y), max(wq.z, wq.w)), x1 = max(max(max(xq.x, xq.y), max(xq.z, xq.w)), max(max(xr.x, xr.y), max(xr.z, xr.w)));
                const uint32_t vv = (r < 2) ? 0u : max(max(max(v0.x, v0.y), max(v0.z, v0.w)), max(max(v1.x, v1.y), max(v1.z, v1.w)));
                const uint32_t lo = (min(w1, 0x7f800000u) + 0xffffu) >> 16 | ((min(vv, 0x7f800000u) + 0xffffu) & 0xffff0000u), hi = (x1 & 0xffff0000u) | tag;
                uint32_t l0, h0, l1, h1, l2, h2;
                asm volatile("{\n.reg .pred p;\n.reg .u32 n, x, y;\n.reg .b64 v;\nsetp.eq.u32 p, %10, 0;\nmov.b64 v, {%8, %9};\n@p st.relaxed.gpu.global.b64 [%7], v;\nmov.u32 n, 0;\n"
                             "G_%=: ld.relaxed.gpu.global.b64 v, [%6];\nmov.b64 {%0, %1}, v;\nld.relaxed.gpu.global.b64 v, [%6+256];\nmov.b64 {%2, %3}, v;\n"
                             "ld.relaxed.gpu.global.b64 v, [%6+512];\nmov.b64 {%4, %5}, v;\n"
                             "xor.b32 x, %1, %9;\nxor.b32 y, %3, %9;\nor.b32 x, x, y;\nxor.b32 y, %5, %9;\nor.b32 x, x, y;\nand.b32 x, x, 0xffff;\n"
                             "setp.eq.u32 p, x, 0;\nvote.sync.all.pred p, p, 0xffffffff;\n@p bra.uni E_%=;\n"
                             "add.u32 n, n, 1;\nsetp.lt.u32 p, n, 4000000;\n@p bra.uni G_%=;\ntrap;\nE_%=:\n}"
                             : "=&r"(l0), "=&r"(h0), "=&r"(l1), "=&r"(h1), "=&r"(l2), "=&r"(h2)
                             : "l"(&g_norm[lane]), "l"(&g_norm[blockIdx.x]), "r"(lo), "r"(hi), "r"(lane) : "memory");
                const uint32_t lm = __vmaxu2(l0, __vmaxu2(l1, l2));
                const float fw = __uint_as_float(__reduce_max_sync(~0u, lm << 16));
                const float fv = __uint_as_float(__reduce_max_sync(~0u, lm & 0xffff0000u));
                const float xmax = __uint_as_float(__reduce_max_sync(~0u, max(h0, max(h1, h2)) & 0xffff0000u));
                const float G = 36.f * fw * fv;
                sts32_if(lane, sb + O_MISC + 4, __float_as_uint(G)); sts32_if(lane, sb + O_MISC + 8, __float_as_uint(G * xmax));
            }
        }
        if (c == 0) PSTAMP(12);
        bar_sync(6, 128);
        int s3n = 1;
        uint32_t roff = __shfl_sync(~0u, (r * 4 + c) * 2048 + (lane >> 4) * 512 + (lane & 2) * 128 + (lane & 1) * 64 + (lane & 12) * 4, lane);
#pragma unroll 1
        for (int s = 0; s < NSEG; s++) {
            const uint32_t l16 = opaque(l16c);
            const uint32_t vxa = sb + O_VX + (s & 1) * 8192 + c * 2048 + l16;
            if (c == 0 && r == 2) {
                bar_sync(14, 288);
                fence_async_smem();
                asm volatile("{\n.reg .pred p;\nelect.sync _|p, 0xffffffff;\n"
                    "@p cp.async.bulk.global.shared::cta.bulk_group [%0], [%1], 8192;\n@p cp.async.bulk.commit_group;\n"
                    "cp.async.bulk.wait_group 0;\nsetp.lt.and.s32 p, %4, 63, p;\n"
                    "@p cp.async.bulk.shared::cluster.global.mbarrier::complete_tx::bytes.multicast::cluster [%1], [%0], 8192, [%2], %3;\n"
                    "fence.proxy.async.global;\n}"
                    :: "l"(reinterpret_cast<char*>(g_qkv) + (size_t)(s * NH + h) * REC + 20480), "r"(sb + O_VX + (s & 1) * 8192),
                       "r"(sb + B_VX + 8 * (s & 1)), "h"((unsigned short)3), "r"(s) : "memory");
            }
            if (s == NSEG - 1) { bar_sync(3, 384); mbar_wait(sb + B_SC, s & 1); break; }
            uint4 vx[4];
            sts32_if(l16, sb + O_MISC + 16 + 4 * c, __reduce_max_sync(~0u, mmax));
            if (c == 0) STAMP(s, 5);
            {
                bar_sync(6, 128);
                const uint4 mm = lds128(sb + O_MISC + 16), cf = lds128(sb + O_MISC);
                const float bound = fmaxf(__uint_as_float(cf.z), __uint_as_float(cf.y) * (__uint_as_float(max(max(mm.x, mm.y), max(mm.z, mm.w))) * __uint_as_float(cf.x)));
                const uint32_t ebits = __reduce_max_sync(~0u, min(max(__float_as_uint(bound) & 0x7f800000u, 21u << 23), 254u << 23));
                mbar_wait(sb + B_X + 8 * s3n, ((s + 1) / 3) & 1);
                s3n = (s3n == 2) ? 0 : s3n + 1;
                bar_sync(3, 384);
                if (r < 2) mbar_wait(sb + B_VX + 8 * (s & 1), (s >> 1) & 1);
                vx[0] = lds128(vxa); vx[2] = lds128(vxa + 1024);
                if (c == 0) STAMP(s, 13);
                mbar_wait(sb + B_SC, s & 1);
                if (c == 0) STAMP(s, 6);
                float p[10];
                load_scores(p, sb + O_SC, 1280, l16);
                float mx = fmaxf(fmaxf(fmaxf(p[0], p[1]), fmaxf(p[2], p[3])), fmaxf(fmaxf(p[4], p[5]), fmaxf(p[6], p[7])));
                mx = quad_max(fmaxf(mx, fmaxf(p[8], p[9])));
                const uint4 vm = lds64x2(sb + O_VM + c * 512 + (l16 >> 1));
                vx[1] = lds128(vxa + 512); vx[3] = lds128(vxa + 1536);
                bar_arrive(4, 384);
                const float sc = __uint_as_float(lds32(sb + O_MISC + 12));
                const float mo = mx * SM_SCALE;
                uint32_t P[5];
#pragma unroll
                for (int n = 0; n < 5; n++) P[n] = pack_bf16(ex2(fmaf(p[2 * n], SM_SCALE, -mo)), ex2(fmaf(p[2 * n + 1], n == 3 ? sc : SM_SCALE, -mo)));
                if (c == 0) STAMP(s, 7);
                float o0[4], o1[4], sm[4];
                mma16816_z(sm, ONES, ONES, ONES, ONES, P[1], P[2]);
                mma16816_z(o0, vx[0].x, vx[0].y, vx[0].z, vx[0].w, P[1], P[2]);
                mma16816_z(o1, vx[2].x, vx[2].y, vx[2].z, vx[2].w, P[1], P[2]);
                mma16816(sm, ONES, ONES, ONES, ONES, P[3], P[4]);
                mma16816(o0, vx[1].x, vx[1].y, vx[1].z, vx[1].w, P[3], P[4]);
                mma16816(o1, vx[3].x, vx[3].y, vx[3].z, vx[3].w, P[3], P[4]);
                mma1688(sm, ONES, ONES, P[0]);
                mma1688(o0, vm.x, vm.y, P[0]);
                mma1688(o1, vm.z, vm.w, P[0]);
                const float sig = __uint_as_float((268u << 23) - ebits);
                const float r0 = rcp_fast(sm[0]) * sig, r1 = rcp_fast(sm[1]) * sig;
                stsm4t(sb + O_OF + c * 512 + l16, pack_bf16(o0[0] * r0, o0[1] * r1), pack_bf16(o0[2] * r0, o0[3] * r1),
                       pack_bf16(o1[0] * r0, o1[1] * r1), pack_bf16(o1[2] * r0, o1[3] * r1));
                bar_sync(6, 128);
                uint4 ob[4];
#pragma unroll
                for (int q = 0; q < 4; q++) ob[q] = ldsm4(sb + O_OF + q * 512 + l16);
                { const uint4 v = lds128(sb + O_WP + c * 512 + l16); a[92] = v.x; a[93] = v.y; a[94] = v.z; a[95] = v.w; }
                float m0[3][4], m1[3][4];
#pragma unroll
                for (int q = 0; q < 4; q++) {
#pragma unroll
                    for (int i = 0; i < 3; i++) {
                        const int k0 = (i * 8 + 2 * q) * 4;
                        if (q == 0) mma16816_z(m0[i], a[k0], a[k0 + 1], a[k0 + 2], a[k0 + 3], ob[q].x, ob[q].y);
                        else mma16816(m0[i], a[k0], a[k0 + 1], a[k0 + 2], a[k0 + 3], ob[q].x, ob[q].y);
                    }
#pragma unroll
                    for (int i = 0; i < 3; i++) {
                        const int k1 = (i * 8 + 2 * q + 1) * 4;
                        if (q == 0) mma16816_z(m1[i], a[k1], a[k1 + 1], a[k1 + 2], a[k1 + 3], ob[q].z, ob[q].w);
                        else mma16816(m1[i], a[k1], a[k1 + 1], a[k1 + 2], a[k1 + 3], ob[q].z, ob[q].w);
                    }
                }
                asm volatile("red.relaxed.gpu.global.add.noftz.v4.f16x2 [%0], {%1,%2,%3,%4};" :: "l"(reinterpret_cast<char*>(g_acc) + roff),
                    "r"(pack_f16(m0[0][0] + m1[0][0], m0[0][2] + m1[0][2])), "r"(pack_f16(m0[1][0] + m1[1][0], m0[1][2] + m1[1][2])),
                    "r"(pack_f16(m0[2][0] + m1[2][0], m0[2][2] + m1[2][2])), "r"(0x3c00u) : "memory");
                asm volatile("red.relaxed.gpu.global.add.noftz.v4.f16x2 [%0], {%1,%2,%3,%4};" :: "l"(reinterpret_cast<char*>(g_acc) + roff + 1024),
                    "r"(pack_f16(m0[0][1] + m1[0][1], m0[0][3] + m1[0][3])), "r"(pack_f16(m0[1][1] + m1[1][1], m0[1][3] + m1[1][3])),
                    "r"(pack_f16(m0[2][1] + m1[2][1], m0[2][3] + m1[2][3])), "r"(0x3c00u) : "memory");
                const unsigned t_red = clk();
                bar_arrive(5, 256);
                bar_arrive(13, 256);
                mbar_expect_if(l16 | c, sb + B_SC, 4608);
                mbar_expect_if(l16 | (c ^ 1) | (r >> 1), sb + B_VX + 8 * ((s + 1) & 1), 8192);
                sts32_if(l16 | (c ^ 3), sb + O_MISC, ebits - (14u << 23));
                if (c == 0) STAMPV(s, 8, t_red);
                if (ACC_PF && c == 2 && s + 4 < NSEG - 1)
                    asm volatile("prefetch.global.L2 [%0];" :: "l"(reinterpret_cast<const char*>(g_acc) + ((s + 4) * 96 + blockIdx.x) * 256 + (l16 & 96)) : "memory");
                const char* pbase = reinterpret_cast<const char*>(g_acc) + (s * 24576 + c * 2048) + ((l16 & 64) * 16 + (l16 & 256) + ((l16 & 128) >> 1) + (l16 & 48));
                spin_until(t_red, D_WAIT);
                uint4 v[6];
#pragma unroll
                for (int i = 0; i < 6; i++) v[i] = ldg_relaxed128(pbase + (i >> 1) * 8192 + (i & 1) * 512);
                int nretry = 0;
                auto convert = [&](int tau) {
                    const uint4 A = v[2 * tau], B = v[2 * tau + 1];
                    sts128(sb + O_MF + tau * 3072 + c * 512 + l16, f16x2_to_bf16x2(A.x), f16x2_to_bf16x2(B.x), f16x2_to_bf16x2(A.y), f16x2_to_bf16x2(B.y));
                    sts64(sb + O_MF + tau * 3072 + 2048 + (c >> 1) * 512 + (c & 1) * 8 + l16, f16x2_to_bf16x2(A.z), f16x2_to_bf16x2(B.z));
                };
                const uint32_t ok0 = __all_sync(~0u, (v[0].w & v[1].w) == 0x5000u);
                convert(0);
                asm volatile("{\n.reg .pred p;\nsetp.ne.u32 p, %0, 0;\n@p bar.arrive 2, 384;\n}" :: "r"(ok0) : "memory");
                sched_fence<0>(h);
                uint32_t ok1;
                asm volatile("{\n.reg .pred p, q;\n.reg .b32 x;\nlop3.b32 x, %1, %2, %3, 0x80;\nand.b32 x, x, %4;\n"
                             "setp.eq.u32 p, x, 0x5000;\nvote.sync.all.pred q, p, 0xffffffff;\nselp.u32 %0, 1, 0, q;\n}"
                             : "=r"(ok1) : "r"(v[2].w), "r"(v[3].w), "r"(v[4].w), "r"(v[5].w));
                convert(1); convert(2);
                asm volatile("{\n.reg .pred p;\nsetp.ne.u32 p, %0, 0;\n@p bar.arrive 15, 384;\n}" :: "r"(ok1) : "memory");
                if (!(ok0 & ok1)) {
                    asm volatile("{\n.reg .pred p0, p1, p2, p3, p4, p5, q;\n.reg .u32 n, x;\nmov.u32 n, 0;\n"
                         "R_%=: setp.ne.u32 p0, %3, 0x5000;\nsetp.ne.u32 p1, %7, 0x5000;\nsetp.ne.u32 p2, %11, 0x5000;\n"
                         "setp.ne.u32 p3, %15, 0x5000;\nsetp.ne.u32 p4, %19, 0x5000;\nsetp.ne.u32 p5, %23, 0x5000;\n"
                         "@p0 ld.relaxed.gpu.global.v4.u32 {%0,%1,%2,%3}, [%25];\n@p1 ld.relaxed.gpu.global.v4.u32 {%4,%5,%6,%7}, [%25+512];\n"
                         "@p2 ld.relaxed.gpu.global.v4.u32 {%8,%9,%10,%11}, [%25+8192];\n@p3 ld.relaxed.gpu.global.v4.u32 {%12,%13,%14,%15}, [%25+8704];\n"
                         "@p4 ld.relaxed.gpu.global.v4.u32 {%16,%17,%18,%19}, [%25+16384];\n@p5 ld.relaxed.gpu.global.v4.u32 {%20,%21,%22,%23}, [%25+16896];\n"
                         "add.u32 %24, %24, 1;\nand.b32 x, %3, %7;\nand.b32 x, x, %11;\nand.b32 x, x, %15;\nand.b32 x, x, %19;\nand.b32 x, x, %23;\n"
                         "setp.eq.u32 q, x, 0x5000;\nvote.sync.all.pred q, q, 0xffffffff;\n@q bra.uni K_%=;\n"
                         "add.u32 n, n, 1;\nsetp.lt.u32 q, n, 2000000;\n@q bra.uni R_%=;\ntrap;\nK_%=:\n}"
                         : "+r"(v[0].x), "+r"(v[0].y), "+r"(v[0].z), "+r"(v[0].w), "+r"(v[1].x), "+r"(v[1].y), "+r"(v[1].z), "+r"(v[1].w),
                           "+r"(v[2].x), "+r"(v[2].y), "+r"(v[2].z), "+r"(v[2].w), "+r"(v[3].x), "+r"(v[3].y), "+r"(v[3].z), "+r"(v[3].w),
                           "+r"(v[4].x), "+r"(v[4].y), "+r"(v[4].z), "+r"(v[4].w), "+r"(v[5].x), "+r"(v[5].y), "+r"(v[5].z), "+r"(v[5].w), "+r"(nretry)
                         : "l"(pbase) : "memory");
                    if (!ok0) { convert(0); bar_arrive(2, 384); }
                    if (!ok1) { convert(1); convert(2); bar_arrive(15, 384); }
                }
                if (c == 0) STAMP(s, 12);
                if (c == 0) STAMPV(s, 14, nretry);
                mmax = absmax2(absmax2(absmax2(v[0].x, v[0].y), absmax2(v[0].z, v[1].x)), absmax2(absmax2(v[1].y, v[1].z), absmax2(v[2].x, v[2].y)));
                mmax = absmax2(mmax, absmax2(absmax2(absmax2(v[2].z, v[3].x), absmax2(v[3].y, v[3].z)), absmax2(absmax2(v[4].x, v[4].y), absmax2(v[4].z, v[5].x))));
                mmax = absmax2(mmax, absmax2(v[5].y, v[5].z)) & 0x7fff7fffu;
                { const float2 mf = __half22float2(*reinterpret_cast<__half2*>(&mmax)); mmax = max(__float_as_uint(mf.x), __float_as_uint(mf.y)); }
            }
            roff += 24576;
        }
        {
            bar_sync(7, 384);
            if (c == 0) flag_inc_if(l16c, &g_flag[F_QKV + (4 * (NBLK - 1) + (h >> 3)) * 8]);
        }
    }
    if (warp == 8) PSTAMP(13);
    cluster_sync();
}

constexpr int NST = 10;
constexpr int G_RING = 0, G_EX = NST * 16384, G_OUT = G_EX + 32768, G_CARRY = G_OUT + 32768, G_BAR = G_CARRY + 512, BG_SMEM = G_BAR + 256;
constexpr int GB_FULL = G_BAR, GB_EMPTY = G_BAR + 8 * NST, GB_W = G_BAR + 16 * NST;
static_assert(BG_SMEM <= 232448, "smem");

template <int ACC>
__device__ __forceinline__ void wgmma_n128_rs(float (&d)[64], uint32_t a0, uint32_t a1, uint32_t a2, uint32_t a3, uint64_t desc) {
    asm volatile("wgmma.mma_async.sync.aligned.m64n128k16.f32.bf16.bf16 "
        "{%0,%1,%2,%3,%4,%5,%6,%7,%8,%9,%10,%11,%12,%13,%14,%15,%16,%17,%18,%19,%20,%21,%22,%23,%24,%25,%26,%27,%28,%29,%30,%31,"
        "%32,%33,%34,%35,%36,%37,%38,%39,%40,%41,%42,%43,%44,%45,%46,%47,%48,%49,%50,%51,%52,%53,%54,%55,%56,%57,%58,%59,%60,%61,%62,%63}, "
        "{%64,%65,%66,%67}, %68, %69, 1, 1, 0;"
        : "+f"(d[0]), "+f"(d[1]), "+f"(d[2]), "+f"(d[3]), "+f"(d[4]), "+f"(d[5]), "+f"(d[6]), "+f"(d[7]),
          "+f"(d[8]), "+f"(d[9]), "+f"(d[10]), "+f"(d[11]), "+f"(d[12]), "+f"(d[13]), "+f"(d[14]), "+f"(d[15]),
          "+f"(d[16]), "+f"(d[17]), "+f"(d[18]), "+f"(d[19]), "+f"(d[20]), "+f"(d[21]), "+f"(d[22]), "+f"(d[23]),
          "+f"(d[24]), "+f"(d[25]), "+f"(d[26]), "+f"(d[27]), "+f"(d[28]), "+f"(d[29]), "+f"(d[30]), "+f"(d[31]),
          "+f"(d[32]), "+f"(d[33]), "+f"(d[34]), "+f"(d[35]), "+f"(d[36]), "+f"(d[37]), "+f"(d[38]), "+f"(d[39]),
          "+f"(d[40]), "+f"(d[41]), "+f"(d[42]), "+f"(d[43]), "+f"(d[44]), "+f"(d[45]), "+f"(d[46]), "+f"(d[47]),
          "+f"(d[48]), "+f"(d[49]), "+f"(d[50]), "+f"(d[51]), "+f"(d[52]), "+f"(d[53]), "+f"(d[54]), "+f"(d[55]),
          "+f"(d[56]), "+f"(d[57]), "+f"(d[58]), "+f"(d[59]), "+f"(d[60]), "+f"(d[61]), "+f"(d[62]), "+f"(d[63])
        : "r"(a0), "r"(a1), "r"(a2), "r"(a3), "l"(desc), "n"(ACC));
}
template <int ACC>
__device__ __forceinline__ void wgmma_n64_rs(float (&d)[64], uint32_t a0, uint32_t a1, uint32_t a2, uint32_t a3, uint64_t desc) {
    asm volatile("wgmma.mma_async.sync.aligned.m64n64k16.f32.bf16.bf16 "
        "{%0,%1,%2,%3,%4,%5,%6,%7,%8,%9,%10,%11,%12,%13,%14,%15,%16,%17,%18,%19,%20,%21,%22,%23,%24,%25,%26,%27,%28,%29,%30,%31}, "
        "{%32,%33,%34,%35}, %36, %37, 1, 1, 0;"
        : "+f"(d[0]), "+f"(d[1]), "+f"(d[2]), "+f"(d[3]), "+f"(d[4]), "+f"(d[5]), "+f"(d[6]), "+f"(d[7]),
          "+f"(d[8]), "+f"(d[9]), "+f"(d[10]), "+f"(d[11]), "+f"(d[12]), "+f"(d[13]), "+f"(d[14]), "+f"(d[15]),
          "+f"(d[16]), "+f"(d[17]), "+f"(d[18]), "+f"(d[19]), "+f"(d[20]), "+f"(d[21]), "+f"(d[22]), "+f"(d[23]),
          "+f"(d[24]), "+f"(d[25]), "+f"(d[26]), "+f"(d[27]), "+f"(d[28]), "+f"(d[29]), "+f"(d[30]), "+f"(d[31])
        : "r"(a0), "r"(a1), "r"(a2), "r"(a3), "l"(desc), "n"(ACC));
}
__device__ __forceinline__ void wait_flag(const unsigned* p, unsigned target) {
    asm volatile("{\n.reg .pred p;\n.reg .u32 n, v;\nmov.u32 n, 0;\n"
                 "W_%=: ld.acquire.gpu.global.u32 v, [%0];\nsub.u32 v, v, %1;\nsetp.ge.s32 p, v, 0;\n@p bra.uni D_%=;\nnanosleep.u32 40;\n"
                 "add.u32 n, n, 1;\nsetp.lt.u32 p, n, 4000000;\n@p bra.uni W_%=;\ntrap;\nD_%=:\n}" :: "l"(p), "r"(target) : "memory");
}
template <int NS, int NT>
__device__ __forceinline__ void bg_mainloop(float (&d)[64], const uint32_t (&a)[144], uint32_t sb, int it, int lane) {
    int slot = it % NST, ph = (it / NST) & 1, prev = 0;
#pragma unroll
    for (int i = 0; i < NS; i++) {
        mbar_wait(sb + GB_FULL + 8 * slot, ph);
        const uint64_t desc = (uint64_t)(((sb + G_RING + slot * 16384) & 0x3FFFF) >> 4) | (1ull << 16) | (64ull << 32) | (1ull << 62);
        wg_fence();
#pragma unroll
        for (int k = 0; k < 512 / NT; k++) {
            const int u = (2048 / NT) * i + 4 * k;
            if (NT == 128) {
                if (i == 0 && k == 0) wgmma_n128_rs<0>(d, a[u], a[u + 1], a[u + 2], a[u + 3], desc);
                else wgmma_n128_rs<1>(d, a[u], a[u + 1], a[u + 2], a[u + 3], desc + 2 * k);
            } else {
                if (i == 0 && k == 0) wgmma_n64_rs<0>(d, a[u], a[u + 1], a[u + 2], a[u + 3], desc);
                else wgmma_n64_rs<1>(d, a[u], a[u + 1], a[u + 2], a[u + 3], desc + 2 * (k & 3) + (k >> 2) * 512);
            }
        }
        wg_commit();
        if (i > 0) {
            asm volatile("wgmma.wait_group.sync.aligned 1;" ::: "memory");
            mbar_arrive_if(lane, sb + GB_EMPTY + 8 * prev);
        }
        prev = slot;
        slot += 2;
        if (slot >= NST) { slot -= NST; ph ^= 1; }
    }
    wg_wait0();
    mbar_arrive_if(lane, sb + GB_EMPTY + 8 * prev);
}
template <bool SKIP, int NT>
__device__ __forceinline__ void bg_epilogue(float (&d)[64], uint32_t sb, int wg, int w, int lane, const CUtensorMap* tm_out, int col0, int tok0,
                                            const __nv_bfloat16* xa, const __nv_bfloat16* Dk) {
    constexpr int H = NT / 4;
    const int g = lane >> 2, t = lane & 3;
    const uint32_t ex = sb + G_EX + w * 4096 + lane * 16;
    float k[H];
    if (wg == 0) {
#pragma unroll
        for (int q = 0; q < H / 4; q++) sts128f(ex + q * 512, d[H + 4 * q], d[H + 4 * q + 1], d[H + 4 * q + 2], d[H + 4 * q + 3]);
#pragma unroll
        for (int i = 0; i < H; i++) k[i] = d[i];
    } else {
#pragma unroll
        for (int q = 0; q < H / 4; q++) sts128f(ex + 16384 + q * 512, d[4 * q], d[4 * q + 1], d[4 * q + 2], d[4 * q + 3]);
#pragma unroll
        for (int i = 0; i < H; i++) k[i] = d[H + i];
    }
    uint32_t xv[16], dv = 0;
    if (SKIP) {
        const __nv_bfloat16* xp = xa + (size_t)(tok0 + 64 * wg + 2 * t) * DM + col0 + 16 * w + 2 * g;
#pragma unroll
        for (int i = 0; i < 16; i++) xv[i] = ldg_nc32(xp + (8 * (i >> 1) + (i & 1)) * DM);
        dv = ldg_nc32(Dk + col0 + 16 * w + 2 * g);
    }
    if (SKIP && w == 0) asm volatile("cp.async.bulk.wait_group.read 0;" ::: "memory");
    bar_sync(1, 256);
#pragma unroll
    for (int q = 0; q < H / 4; q++) {
        const float4 o = lds128f(ex + (wg ^ 1) * 16384 + q * 512);
        k[4 * q] += o.x; k[4 * q + 1] += o.y; k[4 * q + 2] += o.z; k[4 * q + 3] += o.w;
    }
    if (SKIP) bar_sync(1, 256); else bar_sync(13, 288);
    const uint32_t ob = sb + G_OUT + wg * (NT == 128 ? 16384 : 4096) + (w >> 1) * 8192 + (g & 1) * 8;
    const uint32_t ch = (w & 1) * 4 + (g >> 1);
#pragma unroll
    for (int i = 0; i < H / 2; i++) {
        float v0 = k[4 * (i >> 1) + (i & 1)], v1 = k[4 * (i >> 1) + 2 + (i & 1)];
        if (SKIP) {
            const uint32_t p = pack_bf16(__uint_as_float(xv[i] << 16) * __uint_as_float(dv << 16), __uint_as_float(xv[i] & 0xffff0000u) * __uint_as_float(dv & 0xffff0000u));
            v0 += __uint_as_float(p << 16); v1 += __uint_as_float(p & 0xffff0000u);
        }
        const uint32_t n7 = 2 * t + (i & 1);
        sts64(ob + (8 * (i >> 1) + n7) * 128 + ((ch ^ n7) << 4), __float_as_uint(v0), __float_as_uint(v1));
    }
    fence_async_smem();
    if (SKIP) {
        bar_sync(4 + wg, 128);
        if (w == 0)
            asm volatile("{\n.reg .pred p;\nelect.sync _|p, 0xffffffff;\n"
                "@p cp.async.bulk.tensor.2d.global.shared::cta.bulk_group [%0, {%2, %4}], [%1];\n"
                "@p cp.async.bulk.tensor.2d.global.shared::cta.bulk_group [%0, {%3, %4}], [%1+8192];\n@p cp.async.bulk.commit_group;\n}"
                :: "l"(tm_out), "r"(sb + G_OUT + wg * 16384), "r"(col0), "r"(col0 + 32), "r"(tok0 + 64 * wg) : "memory");
    } else {
        bar_arrive(12, 288);
    }
}
__device__ __forceinline__ void s5_channel(int p, const __nv_bfloat16* Lre, const __nv_bfloat16* Lim, const __nv_bfloat16* logdt, float2& lam, float2& coef) {
    const float dt = __bfloat162float(__float2bfloat16(expf(__bfloat162float(logdt[p]))));
    const float lr = __bfloat162float(Lre[p]), li = __bfloat162float(Lim[p]);
    const float e = expf(dt * lr);
    float sn, cs;
    sincosf(dt * li, &sn, &cs);
    lam = make_float2(e * cs, e * sn);
    const float den = lr * lr + li * li;
    coef = make_float2(((lam.x - 1.f) * lr + lam.y * li) / den, (lam.y * lr - (lam.x - 1.f) * li) / den);
}
__device__ __forceinline__ float2 cfma(float2 a, float2 b, float2 c) {
    return make_float2(fmaf(a.x, b.x, fmaf(-a.y, b.y, c.x)), fmaf(a.x, b.y, fmaf(a.y, b.x, c.y)));
}
__device__ __forceinline__ uint4 ldg128(const void* p) { uint4 v; asm volatile("ld.global.v4.u32 {%0,%1,%2,%3}, [%4];" : "=r"(v.x), "=r"(v.y), "=r"(v.z), "=r"(v.w) : "l"(p) : "memory"); return v; }
__device__ __forceinline__ uint2 ldg64(const void* p) { uint2 v; asm volatile("ld.global.v2.u32 {%0,%1}, [%2];" : "=r"(v.x), "=r"(v.y) : "l"(p) : "memory"); return v; }

template <int MT>
__device__ __forceinline__ void bg_attention(uint32_t st0, uint32_t st1, int lane) {
    constexpr int NK = MT ? 5 : 3;
    const int g = lane >> 2, t = lane & 3;
    float sc[NK][4], sm2[4];
#pragma unroll
    for (int i = 0; i < 8; i++) {
        const uint32_t st = (i >> 2 ? st1 : st0) + (i & 3) * 512 + lane * 16;
        const uint4 q = ldsm4(st + MT * 2048), km = ldsm4(st + 8192), k0 = ldsm4(st + 4096);
        if (i == 0) {
            mma16816_z(sc[0], q.x, q.y, q.z, q.w, km.x, km.y); mma16816_z(sm2, q.x, q.y, q.z, q.w, km.z, km.w);
            mma16816_z(sc[1], q.x, q.y, q.z, q.w, k0.x, k0.y); mma16816_z(sc[2], q.x, q.y, q.z, q.w, k0.z, k0.w);
        } else {
            mma16816(sc[0], q.x, q.y, q.z, q.w, km.x, km.y); mma16816(sm2, q.x, q.y, q.z, q.w, km.z, km.w);
            mma16816(sc[1], q.x, q.y, q.z, q.w, k0.x, k0.y); mma16816(sc[2], q.x, q.y, q.z, q.w, k0.z, k0.w);
        }
        if (MT) {
            const uint4 k1 = ldsm4(st + 6144);
            if (i == 0) { mma16816_z(sc[NK - 2], q.x, q.y, q.z, q.w, k1.x, k1.y); mma16816_z(sc[NK - 1], q.x, q.y, q.z, q.w, k1.z, k1.w); }
            else { mma16816(sc[NK - 2], q.x, q.y, q.z, q.w, k1.x, k1.y); mma16816(sc[NK - 1], q.x, q.y, q.z, q.w, k1.z, k1.w); }
        }
    }
#pragma unroll
    for (int i = 0; i < 4; i++) sc[0][i] += sm2[i];
    if (2 * t > g) { sc[NK - 2][0] = -INFINITY; sc[NK - 1][2] = -INFINITY; }
    if (2 * t + 1 > g) { sc[NK - 2][1] = -INFINITY; sc[NK - 1][3] = -INFINITY; }
    sc[NK - 1][0] = sc[NK - 1][1] = -INFINITY;
    float ma = fmaxf(sc[0][0], sc[0][1]), mb = fmaxf(sc[0][2], sc[0][3]);
#pragma unroll
    for (int n = 1; n < NK; n++) { ma = fmaxf(ma, fmaxf(sc[n][0], sc[n][1])); mb = fmaxf(mb, fmaxf(sc[n][2], sc[n][3])); }
    ma = quad_max(ma) * SM_SCALE; mb = quad_max(mb) * SM_SCALE;
    uint32_t Pa[NK], Pb[NK];
#pragma unroll
    for (int n = 0; n < NK; n++) {
        Pa[n] = n == NK - 1 ? 0u : pack_bf16(ex2(fmaf(sc[n][0], SM_SCALE, -ma)), ex2(fmaf(sc[n][1], SM_SCALE, -ma)));
        Pb[n] = pack_bf16(ex2(fmaf(sc[n][2], SM_SCALE, -mb)), ex2(fmaf(sc[n][3], SM_SCALE, -mb)));
    }
    float sa[4], sbb[4];
    mma1688_z(sa, ONES, ONES, Pa[0]); mma1688_z(sbb, ONES, ONES, Pb[0]);
    mma16816(sa, ONES, ONES, ONES, ONES, Pa[1], Pa[2]); mma16816(sbb, ONES, ONES, ONES, ONES, Pb[1], Pb[2]);
    if (MT) { mma16816(sa, ONES, ONES, ONES, ONES, Pa[NK - 2], Pa[NK - 1]); mma16816(sbb, ONES, ONES, ONES, ONES, Pb[NK - 2], Pb[NK - 1]); }
    const float ra0 = rcp_fast(sa[0]), ra1 = rcp_fast(sa[1]), rb0 = rcp_fast(sbb[0]), rb1 = rcp_fast(sbb[1]);
    const uint32_t row = lane & 7;
    const uint32_t so = MT * 2048 + (lane >> 4) * 1024 + row * 128;
#pragma unroll
    for (int eh = 0; eh < 2; eh++) {
        const uint32_t st = eh ? st1 : st0;
        float2 vm[4]; uint4 v0[4], v1[4];
#pragma unroll
        for (int e4 = 0; e4 < 4; e4++) {
            vm[e4] = lds64f(st + 14336 + e4 * 256 + lane * 8);
            v0[e4] = lds128(st + 10240 + e4 * 1024 + lane * 16);
            if (MT) v1[e4] = lds128(st + 10240 + e4 * 1024 + 512 + lane * 16);
        }
        float oa[4][4], ob[4][4];
#pragma unroll
        for (int e4 = 0; e4 < 4; e4++) {
            mma1688_z(oa[e4], __float_as_uint(vm[e4].x), __float_as_uint(vm[e4].y), Pa[0]);
            mma1688_z(ob[e4], __float_as_uint(vm[e4].x), __float_as_uint(vm[e4].y), Pb[0]);
        }
#pragma unroll
        for (int e4 = 0; e4 < 4; e4++) {
            mma16816(oa[e4], v0[e4].x, v0[e4].y, v0[e4].z, v0[e4].w, Pa[1], Pa[2]);
            mma16816(ob[e4], v0[e4].x, v0[e4].y, v0[e4].z, v0[e4].w, Pb[1], Pb[2]);
        }
        if (MT) {
#pragma unroll
            for (int e4 = 0; e4 < 4; e4++) {
                mma16816(oa[e4], v1[e4].x, v1[e4].y, v1[e4].z, v1[e4].w, Pa[NK - 2], Pa[NK - 1]);
                mma16816(ob[e4], v1[e4].x, v1[e4].y, v1[e4].z, v1[e4].w, Pb[NK - 2], Pb[NK - 1]);
            }
        }
#pragma unroll
        for (int e4 = 0; e4 < 4; e4++)
            stsm4t(st + so + (((2 * e4 + ((lane >> 3) & 1)) ^ row) << 4), pack_bf16(oa[e4][0] * ra0, oa[e4][1] * ra1), pack_bf16(oa[e4][2] * ra0, oa[e4][3] * ra1),
                   pack_bf16(ob[e4][0] * rb0, ob[e4][1] * rb1), pack_bf16(ob[e4][2] * rb0, ob[e4][3] * rb1));
    }
}
__device__ __forceinline__ bool bg_att_turn(int na, int ng) { return na == ng || (na == ng + 1 && (na <= BG_AHEAD || na == NBLK - 1)); }

__global__ void __launch_bounds__(384, 1)
bg_kernel(const __grid_constant__ CUtensorMap tm_xa, const __grid_constant__ CUtensorMap tm_wo, const __grid_constant__ CUtensorMap tm_out,
          const __nv_bfloat16* __restrict__ xa, const __nv_bfloat16* __restrict__ Lre, const __nv_bfloat16* __restrict__ Lim,
          const __nv_bfloat16* __restrict__ Bre, const __nv_bfloat16* __restrict__ Bim, const __nv_bfloat16* __restrict__ Cre,
          const __nv_bfloat16* __restrict__ Cim, const __nv_bfloat16* __restrict__ logdt, const __nv_bfloat16* __restrict__ Dk, float* __restrict__ out) {
    extern __shared__ __align__(1024) uint8_t smem_raw[];
    const uint32_t sb = smem_u32(smem_raw);
    const int lane = threadIdx.x & 31;
    const int warp = __shfl_sync(~0u, threadIdx.x >> 5, 0);
    const int wg = warp >> 2, w = warp & 3, b = blockIdx.x;
    const int nt = b % 9, kq = b / 9;
    BSTAMP(0);
    if (threadIdx.x == 0) {
        if (sb & 1023u) __trap();
        for (int i = 0; i < NST; i++) { mbar_init(sb + GB_FULL + 8 * i, 1); mbar_init(sb + GB_EMPTY + 8 * i, 4); }
        mbar_init(sb + GB_W, 1);
        asm volatile("fence.mbarrier_init.release.cluster;" ::: "memory");
        mbar_expect(sb + GB_W, (b < 18 ? 64 : 128) * 1152);
        sts32(sb + G_BAR + 248, atomicAdd(&g_ticket_bg, 1u) / 36u + 1u);
    }
    __syncthreads();
    if (wg == 2) {
        asm volatile("setmaxnreg.dec.sync.aligned.u32 24;");
        if (w == 0) {
            int slot = 0, ph = 1;
            auto next = [&]() { if (++slot == NST) { slot = 0; ph ^= 1; } };
            bar_sync(6, 288);
            if (b < 18) {
#pragma unroll 1
                for (int i = 0; i < 144; i++) {
                    const int blk = i / 9, kb = i - 9 * blk, it = (blk >> 1) * 18 + (blk & 1) + 2 * kb;
                    slot = it % NST;
                    mbar_wait(sb + GB_EMPTY + 8 * slot, ((it / NST) & 1) ^ 1);
                    asm volatile("{\n.reg .pred p;\nelect.sync _|p, 0xffffffff;\n@p mbarrier.arrive.expect_tx.shared::cta.b64 _, [%2], 16384;\n"
                        "@p cp.async.bulk.tensor.5d.shared::cluster.global.mbarrier::complete_tx::bytes [%0], [%1, {%3, %4, %4, %4, %5}], [%2];\n}"
                        :: "r"(sb + G_RING + slot * 16384), "l"(&tm_xa), "r"(sb + GB_FULL + 8 * slot), "r"(kb * 64), "r"(0), "r"(blk) : "memory");
                }
                slot = 144 % NST; ph = ((144 / NST) & 1) ^ 1;
            }
            const unsigned ep = lds32(sb + G_BAR + 248);
            auto slabs = [&](const char* src, int ns) {
                asm volatile("fence.proxy.async.global;" ::: "memory");
#pragma unroll 1
                for (int i = 0; i < ns; i++) {
                    mbar_wait(sb + GB_EMPTY + 8 * slot, ph);
                    asm volatile("{\n.reg .pred p;\nelect.sync _|p, 0xffffffff;\n@p mbarrier.arrive.expect_tx.shared::cta.b64 _, [%2], 16384;\n"
                        "@p cp.async.bulk.shared::cluster.global.mbarrier::complete_tx::bytes [%0], [%1], 16384, [%2];\n}"
                        :: "r"(sb + G_RING + slot * 16384), "l"(src + (size_t)((i & 1) * (ns >> 1) + (i >> 1)) * (SEQ * 128)), "r"(sb + GB_FULL + 8 * slot) : "memory");
                    next();
                }
            };
            if (b >= 18) {
#pragma unroll 1
                for (int blk = kq - 2; blk < 16; blk += 2) {
                    wait_flag(&g_flag[F_H + blk * 8], 18 * ep);
                    slabs(reinterpret_cast<const char*>(g_h) + blk * 16384, 18);
                }
            }
            bar_sync(6, 288);
#pragma unroll 1
            for (int na = 0, ng = 0; ng < NBLK;) {
                if (bg_att_turn(na, ng)) {
                    if (nt < 8) {
                        wait_flag(&g_flag[F_QKV + (na * 4 + kq) * 8], 24 * ep);
                        asm volatile("fence.proxy.async.global;" ::: "memory");
#pragma unroll 1
                        for (int i = 0; i < (na < NBIG ? 8 : 4); i++) {
                            const int hf = (i >> 1) & 1;
                            const char* rec = reinterpret_cast<const char*>(g_qkv) + (size_t)((blk_seg0(na) + 2 * (i >> 2) + (i & 1)) * NH + 8 * kq + nt) * REC;
                            mbar_wait(sb + GB_EMPTY + 8 * slot, ph);
                            asm volatile("{\n.reg .pred p;\nelect.sync _|p, 0xffffffff;\n@p mbarrier.arrive.expect_tx.shared::cta.b64 _, [%4], 15360;\n"
                                "@p cp.async.bulk.shared::cluster.global.mbarrier::complete_tx::bytes [%0], [%1], 10240, [%4];\n"
                                "@p cp.async.bulk.shared::cluster.global.mbarrier::complete_tx::bytes [%0+10240], [%2], 4096, [%4];\n"
                                "@p cp.async.bulk.shared::cluster.global.mbarrier::complete_tx::bytes [%0+14336], [%3], 1024, [%4];\n}"
                                :: "r"(sb + G_RING + slot * 16384), "l"(rec + hf * 10240), "l"(rec + 20480 + hf * 4096), "l"(rec + 28672 + hf * 1024),
                                   "r"(sb + GB_FULL + 8 * slot) : "memory");
                            next();
                        }
                    }
                    na++;
                } else {
                    wait_flag(&g_flag[F_OX + (ng * 4 + kq) * 8], 8 * ep);
                    const char* src = reinterpret_cast<const char*>(g_ox) + (size_t)kq * 16 * SEQ * 128 + blk_seg0(ng) * 4096;
                    if (ng < NBIG) slabs(src, 16);
                    else {
                        asm volatile("fence.proxy.async.global;" ::: "memory");
#pragma unroll 1
                        for (int i = 0; i < 8; i++) {
                            mbar_wait(sb + GB_EMPTY + 8 * slot, ph);
                            asm volatile("{\n.reg .pred p;\nelect.sync _|p, 0xffffffff;\n@p mbarrier.arrive.expect_tx.shared::cta.b64 _, [%2], 16384;\n"
                                "@p cp.async.bulk.shared::cluster.global.mbarrier::complete_tx::bytes [%0], [%1], 8192, [%2];\n"
                                "@p cp.async.bulk.shared::cluster.global.mbarrier::complete_tx::bytes [%0+8192], [%1+262144], 8192, [%2];\n}"
                                :: "r"(sb + G_RING + slot * 16384), "l"(src + (size_t)((i & 1) * 8 + (i & 6)) * (SEQ * 128)), "r"(sb + GB_FULL + 8 * slot) : "memory");
                            next();
                        }
                    }
                    ng++;
                }
            }
        } else if (w == 1) {
            if (b < 18) {
#pragma unroll 1
                for (int blk = 0; blk < 16; blk++) {
                    bar_sync(8 + (blk & 1), 160);
                    asm volatile("{\n.reg .pred p;\nelect.sync _|p, 0xffffffff;\n@p cp.async.bulk.global.shared::cta.bulk_group [%0], [%1], 16384;\n"
                        "@p cp.async.bulk.commit_group;\ncp.async.bulk.wait_group 0;\nfence.proxy.async.global;\n}"
                        :: "l"(reinterpret_cast<char*>(g_h) + ((size_t)b * SEQ + blk * 128) * 128), "r"(sb + G_OUT + (blk & 1) * 16384) : "memory");
                    bar_arrive(10 + (blk & 1), 160);
                    flag_inc_if(lane, &g_flag[F_H + blk * 8]);
                }
            }
            if (nt < 8) {
                int it = 144;
#pragma unroll 1
                for (int na = 0, ng = 0; ng < NBLK;) {
                    if (bg_att_turn(na, ng)) {
                        const int ns = na < NBIG ? 8 : 4;
                        bar_sync(7, 288);
                        if (lane < ns) {
                            asm volatile("cp.async.bulk.global.shared::cta.bulk_group [%0], [%1], 4096;\ncp.async.bulk.commit_group;\ncp.async.bulk.wait_group.read 0;\n"
                                "mbarrier.arrive.shared::cta.b64 _, [%2], 4;\ncp.async.bulk.wait_group 0;\nfence.proxy.async.global;"
                                :: "l"(reinterpret_cast<char*>(g_ox) + ((size_t)((8 * kq + nt) * 2 + ((lane >> 1) & 1)) * SEQ + (blk_seg0(na) + 2 * (lane >> 2) + (lane & 1)) * 32) * 128),
                                   "r"(sb + G_RING + ((it + lane) % NST) * 16384), "r"(sb + GB_EMPTY + 8 * ((it + lane) % NST)) : "memory");
                        }
                        __syncwarp();
                        bar_arrive(14, 288);
                        flag_inc_if(lane, &g_flag[F_OX + (na * 4 + kq) * 8]);
                        it += ns; na++;
                    } else { it += ng < NBIG ? 16 : 8; ng++; }
                }
            }
        } else if (w == 2) {
            const unsigned ep = lds32(sb + G_BAR + 248);
#pragma unroll 1
            for (int blk = 0; blk < NBLK; blk++) {
                const bool last = blk == NBLK - 1, add = kq || last;
                bar_arrive(13, 288);
                bar_sync(12, 288);
                if (add) { wait_flag(&g_flag[F_OUT + (blk * 9 + nt) * 8], ep); asm volatile("fence.proxy.async.global;" ::: "memory"); }
#pragma unroll 1
                for (int i = 0; i < (blk < NBIG ? 4 : 2); i++) {
                    const uint32_t src = sb + G_OUT + i * 8192;
                    const int c0 = DM + 64 * nt + (i & 1) * 32, c1 = blk_seg0(blk) * 32 + (i >> 1) * 64;
                    if (add) asm volatile("{\n.reg .pred p;\nelect.sync _|p, 0xffffffff;\n@p cp.reduce.async.bulk.tensor.2d.global.shared::cta.add.bulk_group [%0, {%2, %3}], [%1];\n}"
                                 :: "l"(&tm_out), "r"(src), "r"(c0), "r"(c1) : "memory");
                    else asm volatile("{\n.reg .pred p;\nelect.sync _|p, 0xffffffff;\n@p cp.async.bulk.tensor.2d.global.shared::cta.bulk_group [%0, {%2, %3}], [%1];\n}"
                                 :: "l"(&tm_out), "r"(src), "r"(c0), "r"(c1) : "memory");
                    if (add && blk < NBLK - 2) spin_until(clk(), RED_GAP);
                }
                asm volatile("cp.async.bulk.commit_group;\ncp.async.bulk.wait_group 0;\nfence.proxy.async.global;" ::: "memory");
                __syncwarp();
                if (!add) flag_inc_if(lane, &g_flag[F_OUT + (blk * 9 + nt) * 8]);
                if (!kq && blk == NBLK - 4) {
                    float4* z = reinterpret_cast<float4*>(out + (size_t)(SEQ - 64 + (lane >> 4)) * (2 * DM) + DM + 64 * nt) + (lane & 15);
#pragma unroll 1
                    for (int i = 0; i < 32; i++) z[i * (4 * DM / 4)] = make_float4(0.f, 0.f, 0.f, 0.f);
                    __syncwarp();
                    flag_inc_if(lane, &g_flag[F_OUT + ((NBLK - 1) * 9 + nt) * 8]);
                }
            }
        }
    } else {
        asm volatile("setmaxnreg.inc.sync.aligned.u32 240;");
        const int g = lane >> 2, t = lane & 3, tid = threadIdx.x;
        uint32_t a[144];
        float d[64];
        if (b < 18) {
            if (tid < 64)
                asm volatile("cp.async.bulk.shared::cluster.global.mbarrier::complete_tx::bytes [%0], [%1], 1152, [%2];"
                    :: "r"(sb + tid * 1168), "l"((tid < 32 ? Bre : Bim) + (size_t)(32 * b + (tid & 31)) * DM), "r"(sb + GB_W) : "memory");
            float2 lam, coef;
            s5_channel(32 * b + 8 * w + g, Lre, Lim, logdt, lam, coef);
            float2 l32 = lam;
#pragma unroll
            for (int i = 0; i < 5; i++) l32 = make_float2(l32.x * l32.x - l32.y * l32.y, 2.f * l32.x * l32.y);
            __syncwarp();
            mbar_wait(sb + GB_W, 0);
            const uint32_t ap = sb + (((lane >> 3) & 1) * 32 + 8 * w + (lane & 7)) * 1168 + (lane >> 4) * 16;
#pragma unroll
            for (int ks = 0; ks < 36; ks++) { const uint4 v = ldsm4(ap + ks * 32); a[4 * ks] = v.x; a[4 * ks + 1] = v.y; a[4 * ks + 2] = v.z; a[4 * ks + 3] = v.w; }
            bar_sync(1, 256);
            bar_arrive(6, 288);
            BSTAMP(1);
#pragma unroll 1
            for (int blk = wg; blk < 16; blk += 2) {
                bg_mainloop<9, 128>(d, a, sb, (blk >> 1) * 18 + wg, lane);
                float2 e = make_float2(0.f, 0.f);
#pragma unroll
                for (int i = 0; i < 32; i++) e = cfma(lam, e, make_float2(d[4 * (i >> 1) + (i & 1)], d[4 * (i >> 1) + 2 + (i & 1)]));
                float2 cin = make_float2(0.f, 0.f);
                if (blk > 0) { bar_sync(2 + (wg ^ 1), 256); cin = lds64f(sb + G_CARRY + (wg ^ 1) * 256 + (8 * w + g) * 8); }
                float2 mine = cin;
#pragma unroll
                for (int q = 0; q < 4; q++) {
                    const float2 eq = make_float2(__shfl_sync(~0u, e.x, (lane & 28) + q), __shfl_sync(~0u, e.y, (lane & 28) + q));
                    cin = cfma(l32, cin, eq);
                    if (t == q + 1) mine = cin;
                }
                if (blk < 15) {
                    if (t == 0) sts64(sb + G_CARRY + wg * 256 + (8 * w + g) * 8, __float_as_uint(cin.x), __float_as_uint(cin.y));
                    bar_arrive(2 + wg, 256);
                }
                const uint32_t hs = sb + G_OUT + wg * 16384 + t * 4096 + (g & 3) * 4;
                const uint32_t ch = 2 * w + (g >> 2);
                if (blk >= 2) bar_sync(10 + wg, 160);
#pragma unroll
                for (int i = 0; i < 32; i++) {
                    mine = cfma(lam, mine, make_float2(d[4 * (i >> 1) + (i & 1)], d[4 * (i >> 1) + 2 + (i & 1)]));
                    sts32(hs + i * 128 + ((ch ^ (i & 7)) << 4), pack_bf16(mine.x, mine.y));
                }
                fence_async_smem();
                bar_arrive(8 + wg, 160);
            }
            bar_sync(10 + wg, 160);
        } else {
            if (tid < 128)
                asm volatile("cp.async.bulk.shared::cluster.global.mbarrier::complete_tx::bytes [%0], [%1], 1152, [%2];"
                    :: "r"(sb + tid * 1168), "l"((tid < 64 ? Cre : Cim) + (size_t)(64 * nt + (tid & 63)) * DM), "r"(sb + GB_W) : "memory");
            for (int p = tid; p < DM; p += 256) {
                float2 lam, coef;
                s5_channel(p, Lre, Lim, logdt, lam, coef);
                sts64(sb + G_EX + p * 8, __float_as_uint(2.f * coef.x), __float_as_uint(2.f * coef.y));
            }
            bar_sync(1, 256);
            mbar_wait(sb + GB_W, 0);
            const uint32_t cp = sb + (16 * w + 2 * g) * 1168 + (288 * wg + t) * 2;
#pragma unroll
            for (int u = 0; u < 72; u++) {
                const float2 c2 = lds64f(sb + G_EX + (288 * wg + 4 * u + t) * 8);
#pragma unroll
                for (int f = 0; f < 2; f++) {
                    unsigned short r16, i16;
                    asm volatile("ld.shared.u16 %0, [%1];" : "=h"(r16) : "r"(cp + f * 1168 + u * 8) : "memory");
                    asm volatile("ld.shared.u16 %0, [%1];" : "=h"(i16) : "r"(cp + (64 + f) * 1168 + u * 8) : "memory");
                    const float cr = __uint_as_float((uint32_t)r16 << 16), ci = __uint_as_float((uint32_t)i16 << 16);
                    a[2 * u + f] = pack_bf16(cr * c2.x - ci * c2.y, -(cr * c2.y + ci * c2.x));
                }
            }
            bar_sync(1, 256);
            bar_arrive(6, 288);
            BSTAMP(1);
#pragma unroll 1
            for (int j = 0; j < 8; j++) {
                bg_mainloop<9, 128>(d, a, sb, j * 18 + wg, lane);
                bg_epilogue<true, 128>(d, sb, wg, w, lane, &tm_out, 64 * nt, (2 * j + kq - 2) * 128, xa, Dk);
            }
        }
        if (w == 0) asm volatile("cp.async.bulk.wait_group 0;" ::: "memory");
        bar_sync(1, 256);
        BSTAMP(2);
        if (warp == 0)
            asm volatile("{\n.reg .pred p;\nelect.sync _|p, 0xffffffff;\n@p mbarrier.arrive.expect_tx.shared::cta.b64 _, [%2], 131072;\n"
                "@p cp.async.bulk.tensor.2d.shared::cluster.global.mbarrier::complete_tx::bytes [%0], [%1, {%3, %4}], [%2];\n"
                "@p cp.async.bulk.tensor.2d.shared::cluster.global.mbarrier::complete_tx::bytes [%0+32768], [%1, {%3, %5}], [%2];\n"
                "@p cp.async.bulk.tensor.2d.shared::cluster.global.mbarrier::complete_tx::bytes [%0+65536], [%1, {%3, %6}], [%2];\n"
                "@p cp.async.bulk.tensor.2d.shared::cluster.global.mbarrier::complete_tx::bytes [%0+98304], [%1, {%3, %7}], [%2];\n}"
                :: "r"(sb), "l"(&tm_wo), "r"(sb + GB_W), "r"(64 * nt), "r"(1024 * kq), "r"(1024 * kq + 256), "r"(1024 * kq + 512), "r"(1024 * kq + 768) : "memory");
        mbar_wait(sb + GB_W, 1);
        {
            const uint32_t base = sb + wg * 65536 + 4 * t * 128 + (g & 3) * 4, ch = 2 * w + (g >> 2), r7 = (4 * t) & 7;
#pragma unroll
            for (int ks = 0; ks < 32; ks++) {
                const uint32_t w0 = lds32(base + ks * 2048 + ((ch ^ r7) << 4)), w1 = lds32(base + ks * 2048 + 256 + ((ch ^ (r7 + 2)) << 4));
                const uint32_t w2 = lds32(base + ks * 2048 + 128 + ((ch ^ (r7 + 1)) << 4)), w3 = lds32(base + ks * 2048 + 384 + ((ch ^ (r7 + 3)) << 4));
                a[4 * ks] = __byte_perm(w0, w1, 0x5410); a[4 * ks + 1] = __byte_perm(w0, w1, 0x7632);
                a[4 * ks + 2] = __byte_perm(w2, w3, 0x5410); a[4 * ks + 3] = __byte_perm(w2, w3, 0x7632);
            }
        }
        bar_sync(1, 256);
        bar_arrive(6, 288);
        BSTAMP(3);
#pragma unroll 1
        for (int na = 0, ng = 0, it = 144; ng < NBLK;) {
            if (bg_att_turn(na, ng)) {
                if (nt < 8) {
                    if (na < NBIG || (w >> 1) == wg) {
                        const int i0 = it + wg + (na < NBIG ? 4 * (w >> 1) : 0), i1 = i0 + 2;
                        mbar_wait(sb + GB_FULL + 8 * (i0 % NST), (i0 / NST) & 1);
                        mbar_wait(sb + GB_FULL + 8 * (i1 % NST), (i1 / NST) & 1);
                        BSTAMP(8 + na * 4);
                        if ((w ^ wg) & 1) bg_attention<1>(sb + G_RING + (i0 % NST) * 16384, sb + G_RING + (i1 % NST) * 16384, lane);
                        else bg_attention<0>(sb + G_RING + (i0 % NST) * 16384, sb + G_RING + (i1 % NST) * 16384, lane);
                        fence_async_smem();
                    }
                    if (na > 0) bar_sync(14, 288);
                    bar_arrive(7, 288);
                    bar_sync(1, 256);
                    BSTAMP(9 + na * 4);
                    it += na < NBIG ? 8 : 4;
                }
                na++;
            } else if (ng < NBIG) {
                bg_mainloop<8, 128>(d, a, sb, it + wg, lane);
                BSTAMP(10 + ng * 4);
                bg_epilogue<false, 128>(d, sb, wg, w, lane, &tm_out, 0, 0, xa, Dk);
                BSTAMP(11 + ng * 4);
                it += 16; ng++;
            } else {
                bg_mainloop<4, 64>(d, a, sb, it + wg, lane);
                BSTAMP(10 + ng * 4);
                bg_epilogue<false, 64>(d, sb, wg, w, lane, &tm_out, 0, 0, xa, Dk);
                BSTAMP(11 + ng * 4);
                it += 8; ng++;
            }
        }
        if (nt < 8) bar_sync(14, 288);
    }
    asm volatile("griddepcontrol.wait;" ::: "memory");
}

typedef CUresult (*EncodeFn)(CUtensorMap*, CUtensorMapDataType, cuuint32_t, void*, const cuuint64_t*, const cuuint64_t*, const cuuint32_t*, const cuuint32_t*,
                             CUtensorMapInterleave, CUtensorMapSwizzle, CUtensorMapL2promotion, CUtensorMapFloatOOBfill);
}

extern "C" void kernel_launch(void* const* d_in, const int* in_sizes, int n_in, void* d_out, int out_size) {
    typedef const __nv_bfloat16* bp;
    bp Ax = (bp)d_in[0], Lre = (bp)d_in[1], Lim = (bp)d_in[2], Bre = (bp)d_in[3], Bim = (bp)d_in[4], Cre = (bp)d_in[5], Cim = (bp)d_in[6],
       logdt = (bp)d_in[7], Dk = (bp)d_in[8], Bx = (bp)d_in[9], mem0 = (bp)d_in[10], Wq = (bp)d_in[11], Wk = (bp)d_in[12], Wv = (bp)d_in[13], Wo = (bp)d_in[14];
    float* out = (float*)d_out;
    static EncodeFn enc = nullptr;
    if (!enc) {
        void* fn = nullptr; cudaDriverEntryPointQueryResult qr;
        cudaGetDriverEntryPoint("cuTensorMapEncodeTiled", &fn, cudaEnableDefault, &qr);
        enc = (EncodeFn)fn;
        cudaFuncSetAttribute(chain_kernel, cudaFuncAttributeMaxDynamicSharedMemorySize, CHAIN_SMEM);
        cudaFuncSetAttribute(bg_kernel, cudaFuncAttributeMaxDynamicSharedMemorySize, BG_SMEM);
    }
    const cuuint32_t es[5] = {1, 1, 1, 1, 1};
    auto map2d = [&](CUtensorMap* tm, CUtensorMapDataType dt, const void* p, cuuint64_t d0, cuuint64_t d1, cuuint64_t stride, cuuint32_t b0, cuuint32_t b1) {
        cuuint64_t gd[2] = {d0, d1}, gs[1] = {stride}; cuuint32_t bd[2] = {b0, b1};
        enc(tm, dt, 2, (void*)p, gd, gs, bd, es, CU_TENSOR_MAP_INTERLEAVE_NONE, CU_TENSOR_MAP_SWIZZLE_128B, CU_TENSOR_MAP_L2_PROMOTION_L2_128B,
            CU_TENSOR_MAP_FLOAT_OOB_FILL_NONE);
    };
    CUtensorMap tm_x, tm_q, tm_k, tm_v, tm_xa, tm_wo, tm_out;
    map2d(&tm_x, CU_TENSOR_MAP_DATA_TYPE_BFLOAT16, Bx, DM, SEQ, DM * 2, 64, 32);
    map2d(&tm_q, CU_TENSOR_MAP_DATA_TYPE_BFLOAT16, Wq, HD, DM, HD * 2, 64, 192);
    map2d(&tm_k, CU_TENSOR_MAP_DATA_TYPE_BFLOAT16, Wk, HD, DM, HD * 2, 64, 192);
    map2d(&tm_v, CU_TENSOR_MAP_DATA_TYPE_BFLOAT16, Wv, HD, DM, HD * 2, 64, 192);
    map2d(&tm_wo, CU_TENSOR_MAP_DATA_TYPE_BFLOAT16, Wo, DM, HD, DM * 2, 64, 256);
    map2d(&tm_out, CU_TENSOR_MAP_DATA_TYPE_FLOAT32, out, 2 * DM, SEQ, 2 * DM * 4, 32, 64);
    {
        cuuint64_t gd[5] = {DM, 2, 4, 16, 16}, gs[4] = {DM * 2, 32 * DM * 2, 2 * DM * 2, 128 * DM * 2}; cuuint32_t bd[5] = {64, 2, 4, 16, 1};
        enc(&tm_xa, CU_TENSOR_MAP_DATA_TYPE_BFLOAT16, 5, (void*)Ax, gd, gs, bd, es, CU_TENSOR_MAP_INTERLEAVE_NONE, CU_TENSOR_MAP_SWIZZLE_128B,
            CU_TENSOR_MAP_L2_PROMOTION_L2_128B, CU_TENSOR_MAP_FLOAT_OOB_FILL_NONE);
    }
    cudaStream_t st = cudaStreamPerThread;
    chain_kernel<<<96, 384, CHAIN_SMEM, st>>>(tm_x, tm_q, tm_k, tm_v, Bx, mem0, Wo);
    cudaLaunchConfig_t cfg = {};
    cfg.gridDim = dim3(36); cfg.blockDim = dim3(384); cfg.dynamicSmemBytes = BG_SMEM; cfg.stream = st;
    cudaLaunchAttribute at[1];
    at[0].id = cudaLaunchAttributeProgrammaticStreamSerialization; at[0].val.programmaticStreamSerializationAllowed = 1;
    cfg.attrs = at; cfg.numAttrs = 1;
    cudaLaunchKernelEx(&cfg, bg_kernel, tm_xa, tm_wo, tm_out, Ax, Lre, Lim, Bre, Bim, Cre, Cim, logdt, Dk, out);
}
```

```cpp
#include <cuda_runtime.h>
#include <cuda.h>
#include <cuda_bf16.h>
#include <cuda_fp16.h>
#include <stdint.h>

#define D_WAIT 740

#define RED_GAP 720
#define ACC_PF 1
#define QDEP 0
#define NBIG 14

namespace {

constexpr int DM = 576, NH = 32, SEQ = 2048, NSEG = 64, HD = 4096;

__device__ uint4 g_acc_raw[64 * 96 * 16 + 131072];
__device__ uint4 g_ox[NH * 2 * SEQ * 8];
constexpr int REC = 30720;
__device__ uint4 g_qkv[NSEG * NH * (REC / 16)];
__device__ uint4 g_h[18 * SEQ * 8];
constexpr int NFLAG = 6144, F_QKV = 0, F_OX = 1024, F_H = 2048, F_OUT = 3072;
constexpr int NBLK = NBIG + (NSEG - 4 * NBIG) / 2;
__host__ __device__ constexpr int blk_seg0(int b) { return b < NBIG ? 4 * b : 2 * b + 2 * NBIG; }
__device__ unsigned g_flag[NFLAG];
__device__ unsigned g_ticket, g_ticket_bg;
__device__ unsigned long long g_norm[96];
#define BSTAMP(i) do {} while (0)

__device__ __forceinline__ uint32_t smem_u32(const void* p) { return (uint32_t)__cvta_generic_to_shared(p); }
__device__ __forceinline__ uint32_t mapa(uint32_t a, uint32_t r) { uint32_t o; asm("mapa.shared::cluster.u32 %0, %1, %2;" : "=r"(o) : "r"(a), "r"(r)); return o; }
__device__ __forceinline__ uint32_t mapa_v(uint32_t a, uint32_t r) { uint32_t o; asm volatile("mapa.shared::cluster.u32 %0, %1, %2;" : "=r"(o) : "r"(a), "r"(r)); return o; }
__device__ __forceinline__ unsigned clk() { unsigned long long c; asm volatile("mov.u64 %0, %%clock64;" : "=l"(c) :: "memory"); return (unsigned)c; }
__device__ __forceinline__ void mbar_init(uint32_t bar, uint32_t cnt) { asm volatile("mbarrier.init.shared::cta.b64 [%0], %1;" :: "r"(bar), "r"(cnt) : "memory"); }
__device__ __forceinline__ void mbar_expect(uint32_t bar, uint32_t bytes) { asm volatile("mbarrier.arrive.expect_tx.shared::cta.b64 _, [%0], %1;" :: "r"(bar), "r"(bytes) : "memory"); }
__device__ __forceinline__ void mbar_wait(uint32_t bar, uint32_t parity) {
    asm volatile("{\n.reg .pred p;\n.reg .u32 n;\nmov.u32 n, 0;\n"
                 "W_%=: mbarrier.try_wait.parity.shared::cta.b64 p, [%0], %1;\n@p bra.uni D_%=;\n"
                 "add.u32 n, n, 1;\nsetp.lt.u32 p, n, 4000000;\n@p bra.uni W_%=;\ntrap;\nD_%=:\n}" :: "r"(bar), "r"(parity) : "memory");
}
__device__ __forceinline__ void mbar_expect_if(uint32_t z, uint32_t bar, uint32_t bytes) {
    asm volatile("{\n.reg .pred p;\nsetp.eq.u32 p, %2, 0;\n@p mbarrier.arrive.expect_tx.shared::cta.b64 _, [%0], %1;\n}" :: "r"(bar), "r"(bytes), "r"(z) : "memory");
}
__device__ __forceinline__ void mbar_arrive_if(uint32_t z, uint32_t bar) {
    asm volatile("{\n.reg .pred p;\nsetp.eq.u32 p, %1, 0;\n@p mbarrier.arrive.shared::cta.b64 _, [%0];\n}" :: "r"(bar), "r"(z) : "memory");
}
__device__ __forceinline__ void sts32_if(uint32_t z, uint32_t a, uint32_t x) {
    asm volatile("{\n.reg .pred p;\nsetp.eq.u32 p, %2, 0;\n@p st.shared.u32 [%0], %1;\n}" :: "r"(a), "r"(x), "r"(z) : "memory");
}
template <int K> __device__ __forceinline__ void sched_fence(int v) {
    asm volatile("{\n.reg .pred p;\nsetp.ne.s32 p, %0, %1;\n@p bra.uni F_%=;\ntrap;\nF_%=:\n}" :: "r"(v), "n"(1000 + K) : "memory");
}
__device__ __forceinline__ void spin_until(unsigned t0, unsigned d) {
    asm volatile("{\n.reg .pred p;\n.reg .u64 c;\n.reg .u32 lo;\n"
                 "S_%=: mov.u64 c, %%clock64;\ncvt.u32.u64 lo, c;\nsub.u32 lo, lo, %0;\nsetp.lt.u32 p, lo, %1;\n@p bra.uni S_%=;\n}" :: "r"(t0), "r"(d) : "memory");
}
__device__ __forceinline__ void bar_sync(int id, int n) { asm volatile("bar.sync %0, %1;" :: "r"(id), "r"(n) : "memory"); }
__device__ __forceinline__ void bar_sync_sel(int sel, int id) {
    asm volatile("{\n.reg .pred p;\nsetp.eq.u32 p, %0, 0;\n@p bar.sync %1, %3;\n@!p bar.sync %2, %3;\n}" :: "r"(sel), "r"(id), "r"(id + 1), "n"(192) : "memory");
}
__device__ __forceinline__ void bar_arrive(int id, int n) { asm volatile("bar.arrive %0, %1;" :: "r"(id), "r"(n) : "memory"); }
__device__ __forceinline__ void fence_async_smem() { asm volatile("fence.proxy.async.shared::cta;" ::: "memory"); }
__device__ __forceinline__ uint32_t pack_bf16(float lo, float hi) { uint32_t r; asm("cvt.rn.bf16x2.f32 %0, %1, %2;" : "=r"(r) : "f"(hi), "f"(lo)); return r; }
__device__ __forceinline__ uint32_t pack_f16(float lo, float hi) { uint32_t r; asm("cvt.rn.f16x2.f32 %0, %1, %2;" : "=r"(r) : "f"(hi), "f"(lo)); return r; }
__device__ __forceinline__ uint32_t f16x2_to_bf16x2(uint32_t v) { float2 f = __half22float2(*reinterpret_cast<__half2*>(&v)); return pack_bf16(f.x, f.y); }
__device__ __forceinline__ uint32_t hmul2(uint32_t a, uint32_t b) { uint32_t r; asm("mul.rn.f16x2 %0, %1, %2;" : "=r"(r) : "r"(a), "r"(b)); return r; }
__device__ __forceinline__ float ex2(float x) { float y; asm("ex2.approx.ftz.f32 %0, %1;" : "=f"(y) : "f"(x)); return y; }
__device__ __forceinline__ float ex2v(float x) { float y; asm volatile("ex2.approx.ftz.f32 %0, %1;" : "=f"(y) : "f"(x)); return y; }
__device__ __forceinline__ uint32_t absmax2(uint32_t a, uint32_t b) {
    uint32_t r; asm("max.xorsign.abs.f16x2 %0, %1, %2;" : "=r"(r) : "r"(a), "r"(b)); return r;
}
__device__ __forceinline__ uint32_t shl_v(uint32_t a, int n) { return a << n; }
__device__ __forceinline__ uint32_t max3u(uint32_t a, uint32_t b, uint32_t c) { return max(max(a, b), c); }
__device__ __forceinline__ uint4 lds128(uint32_t a) { uint4 v; asm volatile("ld.shared.v4.u32 {%0,%1,%2,%3}, [%4];" : "=r"(v.x), "=r"(v.y), "=r"(v.z), "=r"(v.w) : "r"(a) : "memory"); return v; }
__device__ __forceinline__ uint4 lds128v(uint32_t a) { uint4 v; asm volatile("ld.volatile.shared.v4.u32 {%0,%1,%2,%3}, [%4];" : "=r"(v.x), "=r"(v.y), "=r"(v.z), "=r"(v.w) : "r"(a) : "memory"); return v; }
__device__ __forceinline__ float4 lds128f(uint32_t a) { float4 v; asm volatile("ld.shared.v4.f32 {%0,%1,%2,%3}, [%4];" : "=f"(v.x), "=f"(v.y), "=f"(v.z), "=f"(v.w) : "r"(a) : "memory"); return v; }
__device__ __forceinline__ float2 lds64f(uint32_t a) { float2 v; asm volatile("ld.shared.v2.f32 {%0,%1}, [%2];" : "=f"(v.x), "=f"(v.y) : "r"(a) : "memory"); return v; }
__device__ __forceinline__ uint4 lds64x2(uint32_t a) { uint4 v; asm volatile("ld.shared.v2.u32 {%0,%1}, [%4];\nld.shared.v2.u32 {%2,%3}, [%4+256];" : "=r"(v.x), "=r"(v.y), "=r"(v.z), "=r"(v.w) : "r"(a) : "memory"); return v; }
__device__ __forceinline__ uint32_t lds32(uint32_t a) { uint32_t v; asm volatile("ld.shared.u32 %0, [%1];" : "=r"(v) : "r"(a) : "memory"); return v; }
__device__ __forceinline__ void sts128(uint32_t a, uint32_t x, uint32_t y, uint32_t z, uint32_t w) { asm volatile("st.shared.v4.u32 [%0], {%1,%2,%3,%4};" :: "r"(a), "r"(x), "r"(y), "r"(z), "r"(w) : "memory"); }
__device__ __forceinline__ void sts128f(uint32_t a, float x, float y, float z, float w) { asm volatile("st.shared.v4.f32 [%0], {%1,%2,%3,%4};" :: "r"(a), "f"(x), "f"(y), "f"(z), "f"(w) : "memory"); }
__device__ __forceinline__ void sts64(uint32_t a, uint32_t x, uint32_t y) { asm volatile("st.shared.v2.u32 [%0], {%1,%2};" :: "r"(a), "r"(x), "r"(y) : "memory"); }
__device__ __forceinline__ void sts32(uint32_t a, uint32_t x) { asm volatile("st.shared.u32 [%0], %1;" :: "r"(a), "r"(x) : "memory"); }
__device__ __forceinline__ uint4 ldsm4(uint32_t a) { uint4 v; asm volatile("ldmatrix.sync.aligned.m8n8.x4.shared.b16 {%0,%1,%2,%3}, [%4];" : "=r"(v.x), "=r"(v.y), "=r"(v.z), "=r"(v.w) : "r"(a) : "memory"); return v; }
__device__ __forceinline__ void stsm2t(uint32_t a, uint32_t x, uint32_t y) { asm volatile("stmatrix.sync.aligned.m8n8.x2.trans.shared.b16 [%0], {%1,%2};" :: "r"(a), "r"(x), "r"(y) : "memory"); }
__device__ __forceinline__ void stsm4t(uint32_t a, uint32_t x, uint32_t y, uint32_t z, uint32_t w) { asm volatile("stmatrix.sync.aligned.m8n8.x4.trans.shared.b16 [%0], {%1,%2,%3,%4};" :: "r"(a), "r"(x), "r"(y), "r"(z), "r"(w) : "memory"); }
__device__ __forceinline__ void st_async64(uint32_t a, uint32_t x, uint32_t y, uint32_t bar) { asm volatile("st.async.shared::cluster.mbarrier::complete_tx::bytes.v2.b32 [%0], {%1,%2}, [%3];" :: "r"(a), "r"(x), "r"(y), "r"(bar) : "memory"); }
__device__ __forceinline__ void bulk_s2c(uint32_t dst, uint32_t src, uint32_t bytes, uint32_t bar) { asm volatile("cp.async.bulk.shared::cluster.shared::cta.mbarrier::complete_tx::bytes [%0], [%1], %2, [%3];" :: "r"(dst), "r"(src), "r"(bytes), "r"(bar) : "memory"); }
__device__ __forceinline__ void bulk_s2g(void* dst, uint32_t src, uint32_t bytes) { asm volatile("cp.async.bulk.global.shared::cta.bulk_group [%0], [%1], %2;" :: "l"(dst), "r"(src), "r"(bytes) : "memory"); }
__device__ __forceinline__ uint32_t ldg_nc32(const void* p) { uint32_t v; asm volatile("ld.global.nc.L2::128B.u32 %0, [%1];" : "=r"(v) : "l"(p)); return v; }
__device__ __forceinline__ uint4 ldg_relaxed128(const void* p) { uint4 v; asm volatile("ld.relaxed.gpu.global.v4.u32 {%0,%1,%2,%3}, [%4];" : "=r"(v.x), "=r"(v.y), "=r"(v.z), "=r"(v.w) : "l"(p) : "memory"); return v; }
__device__ __forceinline__ void mma16816(float (&d)[4], uint32_t a0, uint32_t a1, uint32_t a2, uint32_t a3, uint32_t b0, uint32_t b1) {
    asm volatile("mma.sync.aligned.m16n8k16.row.col.f32.bf16.bf16.f32 {%0,%1,%2,%3}, {%4,%5,%6,%7}, {%8,%9}, {%0,%1,%2,%3};"
        : "+f"(d[0]), "+f"(d[1]), "+f"(d[2]), "+f"(d[3]) : "r"(a0), "r"(a1), "r"(a2), "r"(a3), "r"(b0), "r"(b1));
}
__device__ __forceinline__ void mma16816_z(float (&d)[4], uint32_t a0, uint32_t a1, uint32_t a2, uint32_t a3, uint32_t b0, uint32_t b1) {
    asm volatile("mma.sync.aligned.m16n8k16.row.col.f32.bf16.bf16.f32 {%0,%1,%2,%3}, {%4,%5,%6,%7}, {%8,%9}, {%10,%10,%10,%10};"
        : "=f"(d[0]), "=f"(d[1]), "=f"(d[2]), "=f"(d[3]) : "r"(a0), "r"(a1), "r"(a2), "r"(a3), "r"(b0), "r"(b1), "f"(0.f));
}
__device__ __forceinline__ void mma1688(float (&d)[4], uint32_t a0, uint32_t a1, uint32_t b0) {
    asm volatile("mma.sync.aligned.m16n8k8.row.col.f32.bf16.bf16.f32 {%0,%1,%2,%3}, {%4,%5}, {%6}, {%0,%1,%2,%3};"
        : "+f"(d[0]), "+f"(d[1]), "+f"(d[2]), "+f"(d[3]) : "r"(a0), "r"(a1), "r"(b0));
}
__device__ __forceinline__ void mma1688_z(float (&d)[4], uint32_t a0, uint32_t a1, uint32_t b0) {
    asm volatile("mma.sync.aligned.m16n8k8.row.col.f32.bf16.bf16.f32 {%0,%1,%2,%3}, {%4,%5}, {%6}, {%7,%7,%7,%7};"
        : "=f"(d[0]), "=f"(d[1]), "=f"(d[2]), "=f"(d[3]) : "r"(a0), "r"(a1), "r"(b0), "f"(0.f));
}
template <int ACC>
__device__ __forceinline__ void wgmma_n32_rs(float (&d)[16], uint32_t a0, uint32_t a1, uint32_t a2, uint32_t a3, uint64_t desc) {
    asm volatile("wgmma.mma_async.sync.aligned.m64n32k16.f32.bf16.bf16 {%0,%1,%2,%3,%4,%5,%6,%7,%8,%9,%10,%11,%12,%13,%14,%15}, {%16,%17,%18,%19}, %20, %21, 1, 1, 0;"
        : "+f"(d[0]), "+f"(d[1]), "+f"(d[2]), "+f"(d[3]), "+f"(d[4]), "+f"(d[5]), "+f"(d[6]), "+f"(d[7]),
          "+f"(d[8]), "+f"(d[9]), "+f"(d[10]), "+f"(d[11]), "+f"(d[12]), "+f"(d[13]), "+f"(d[14]), "+f"(d[15])
        : "r"(a0), "r"(a1), "r"(a2), "r"(a3), "l"(desc), "n"(ACC));
}
template <int ACC>
__device__ __forceinline__ void wgmma_n32_ss(float (&d)[16], uint64_t da, uint64_t db) {
    asm volatile("wgmma.mma_async.sync.aligned.m64n32k16.f32.bf16.bf16 {%0,%1,%2,%3,%4,%5,%6,%7,%8,%9,%10,%11,%12,%13,%14,%15}, %16, %17, %18, 1, 1, 0, 0;"
        : "+f"(d[0]), "+f"(d[1]), "+f"(d[2]), "+f"(d[3]), "+f"(d[4]), "+f"(d[5]), "+f"(d[6]), "+f"(d[7]),
          "+f"(d[8]), "+f"(d[9]), "+f"(d[10]), "+f"(d[11]), "+f"(d[12]), "+f"(d[13]), "+f"(d[14]), "+f"(d[15])
        : "l"(da), "l"(db), "n"(ACC));
}
__device__ __forceinline__ void wg_fence() { asm volatile("wgmma.fence.sync.aligned;" ::: "memory"); }
__device__ __forceinline__ void wg_commit() { asm volatile("wgmma.commit_group.sync.aligned;" ::: "memory"); }
__device__ __forceinline__ void wg_wait0() { asm volatile("wgmma.wait_group.sync.aligned 0;" ::: "memory"); }
__device__ __forceinline__ void cluster_sync() { asm volatile("barrier.cluster.arrive.aligned;\nbarrier.cluster.wait.aligned;" ::: "memory"); }

#define STAMP(s, i) do {} while (0)
#define STAMPV(s, i, v) do {} while (0)

constexpr int XT_BYTES = 36864;
constexpr int O_XT = 0;
constexpr int O_STG = XT_BYTES;
constexpr int O_AS = 3 * XT_BYTES;
constexpr int O_XP = O_AS + 16384;
constexpr int O_QKX = O_XP + 8192;
constexpr int O_KM = O_QKX + 8192;
constexpr int O_QM = O_QKX + 10240;
constexpr int O_VX = O_STG + 147456;
constexpr int O_VM = O_VX + 16384;
constexpr int O_SC = O_VM + 2048;
constexpr int O_OF = O_SC + 2560;
constexpr int O_AF = O_OF + 2048;
constexpr int O_WP = O_AF + 4096;
constexpr int O_MF = O_WP + 2048;
constexpr int O_MISC = O_MF + 9216;
static_assert(O_QKX + 24576 <= O_VX, "smem");
constexpr int O_BAR = O_MISC + 64;
constexpr int CHAIN_SMEM = O_BAR + 128;
static_assert(CHAIN_SMEM <= 232448, "smem");
constexpr int B_X = O_BAR, B_VX = O_BAR + 24, B_SC = O_BAR + 40, B_W = O_BAR + 48;
constexpr float SM_SCALE = 0.08838834764831845f * 1.4426950408889634f;
constexpr uint32_t ONES = 0x3f803f80u;

__device__ __forceinline__ uint32_t opaque(uint32_t v) { uint32_t o; asm volatile("mov.u32 %0, %1;" : "=r"(o) : "r"(v)); return o; }
__device__ __forceinline__ void st_async128(uint32_t a, uint32_t x, uint32_t y, uint32_t z, uint32_t w, uint32_t bar) {
    asm volatile("st.async.shared::cluster.mbarrier::complete_tx::bytes.v4.b32 [%0], {%1,%2,%3,%4}, [%5];" :: "r"(a), "r"(x), "r"(y), "r"(z), "r"(w), "r"(bar) : "memory");
}
__device__ __forceinline__ void tma_x_tile(uint32_t sb, const CUtensorMap* tm, int r, int j, int slot) {
    asm volatile("{\n.reg .pred p;\nelect.sync _|p, 0xffffffff;\n"
        "@p mbarrier.arrive.expect_tx.shared::cta.b64 _, [%2], 36864;\n"
        "@p cp.async.bulk.tensor.2d.shared::cluster.global.mbarrier::complete_tx::bytes.multicast::cluster [%0], [%1, {%3, %4}], [%2], %7;\n"
        "@p cp.async.bulk.tensor.2d.shared::cluster.global.mbarrier::complete_tx::bytes.multicast::cluster [%0+4096], [%1, {%5, %4}], [%2], %7;\n"
        "@p cp.async.bulk.tensor.2d.shared::cluster.global.mbarrier::complete_tx::bytes.multicast::cluster [%0+8192], [%1, {%6, %4}], [%2], %7;\n}"
        :: "r"(sb + O_XT + slot * XT_BYTES + 3 * r * 4096), "l"(tm), "r"(sb + B_X + 8 * slot), "r"(192 * r), "r"(j * 32), "r"(192 * r + 64), "r"(192 * r + 128),
           "h"((unsigned short)7) : "memory");
}
__device__ __forceinline__ void flag_inc_if(uint32_t z, unsigned* p) {
    asm volatile("{\n.reg .pred p;\nsetp.eq.u32 p, %1, 0;\n@p red.release.gpu.global.inc.u32 [%0], 0xfffffffe;\n}" :: "l"(p), "r"(z) : "memory");
}
__device__ __forceinline__ float quad_max(float v) {
    const float a = __shfl_xor_sync(~0u, v, 1), b = __shfl_xor_sync(~0u, v, 2), c = __shfl_xor_sync(~0u, v, 3);
    return fmaxf(fmaxf(v, a), fmaxf(b, c));
}
__device__ __forceinline__ void load_scores(float (&p)[10], uint32_t base, uint32_t stride, uint32_t l16) {
    const float4 a0 = lds128f(base + l16), b0 = lds128f(base + stride + l16);
    const float4 a1 = lds128f(base + 512 + l16), b1 = lds128f(base + stride + 512 + l16);
    const float2 a2 = lds64f(base + 1024 + (l16 >> 1)), b2 = lds64f(base + stride + 1024 + (l16 >> 1));
    p[0] = a2.x + b2.x; p[1] = a2.y + b2.y;
    p[2] = a0.x + b0.x; p[3] = a0.y + b0.y; p[4] = a0.z + b0.z; p[5] = a0.w + b0.w;
    p[6] = a1.x + b1.x; p[7] = a1.y + b1.y; p[8] = a1.z + b1.z; p[9] = a1.w + b1.w;
}
__device__ __forceinline__ float rcp_fast(float x) { float y; asm("rcp.approx.ftz.f32 %0, %1;" : "=f"(y) : "f"(x)); return y; }

__global__ void __cluster_dims__(3, 1, 1) __launch_bounds__(384, 1)
chain_kernel(const __grid_constant__ CUtensorMap tm_x, const __grid_constant__ CUtensorMap tm_q,
             const __grid_constant__ CUtensorMap tm_k, const __grid_constant__ CUtensorMap tm_v,
             const __nv_bfloat16* __restrict__ x, const __nv_bfloat16* __restrict__ mem0,
             const __nv_bfloat16* __restrict__ Wo) {
    extern __shared__ __align__(1024) uint8_t smem_raw[];
    const uint32_t sb = smem_u32(smem_raw);
    const int lane = threadIdx.x & 31;
    const int warp = __shfl_sync(~0u, threadIdx.x >> 5, 0);
    const int wg = warp >> 2, w = warp & 3;
    const int h = blockIdx.x / 3, r = blockIdx.x - 3 * h;
    uint4* const g_acc = reinterpret_cast<uint4*>((reinterpret_cast<uintptr_t>(g_acc_raw) + 0x1fffff) & ~(uintptr_t)0x1fffff);

#define PSTAMP(i) do {} while (0)
    if (threadIdx.x == 0) {
        if (sb & 1023u) __trap();
        for (int i = 0; i < 9; i++) mbar_init(sb + O_BAR + 8 * i, 1);
        asm volatile("fence.mbarrier_init.release.cluster;" ::: "memory");
        for (int i = 0; i < 3; i++) {
            mbar_expect(sb + B_W + 8 * i, 49152);
            for (int tl = 0; tl < 2; tl++)
                asm volatile("cp.async.bulk.tensor.2d.shared::cluster.global.mbarrier::complete_tx::bytes [%0], [%1, {%3, %4}], [%2];"
                    :: "r"(sb + O_STG + tl * 73728 + i * 24576), "l"(r < 2 ? (tl ? &tm_k : &tm_q) : &tm_v), "r"(sb + B_W + 8 * i),
                       "r"(h * 128 + 64 * (r < 2 ? r : tl)), "r"(192 * i) : "memory");
        }
    }
    __syncwarp();
    asm volatile("barrier.cluster.arrive.relaxed.aligned;" ::: "memory");
    asm volatile("griddepcontrol.launch_dependents;" ::: "memory");
    if (warp == 0) PSTAMP(9);
    const uint32_t l16c = __shfl_sync(~0u, lane * 16, lane);

    if (wg < 2) {
#define KS(u) ((u) < 8 ? 12 * ((u) >> 2) + (((u) >> 1) & 1) + 4 * ((u) & 1) : (u) < 12 ? (u) : (u) < 16 ? (u) + 8 : (u) < 24 ? 24 + (((u) - 16) >> 1) + 4 * ((u) & 1) : (u) + 8)
        asm volatile("setmaxnreg.inc.sync.aligned.u32 184;");
        uint32_t a[144];
        uint32_t adr1;
        {
            const int g = lane >> 2, t = lane & 3;
            const int t1 = threadIdx.x;
#pragma unroll
            for (int i = 0; i < 2; i++) g_acc[(blockIdx.x * 64 + i * 32 + (t1 >> 3)) * 16 + (t1 & 7)] = make_uint4(0, 0, 0, 0);
            __threadfence();
            asm volatile("barrier.cluster.wait.aligned;" ::: "memory");
            const uint32_t ev = sb + O_STG + (2 * t) * 128 + (((2 * w + (g >> 2)) ^ (2 * t)) << 4) + (g & 3) * 4;
            const uint32_t od = (ev ^ 16) + 128;
            auto gather = [&](int dst, uint32_t off) {
                a[dst] = lds32(ev + off); a[dst + 1] = lds32(od + off); a[dst + 2] = lds32(ev + off + 1024); a[dst + 3] = lds32(od + off + 1024);
            };
            const uint4* xp = reinterpret_cast<const uint4*>(x) + blockIdx.x * 1536 + t1;
            uint4 xv[6];
#pragma unroll
            for (int th = 0; th < 2; th++) {
                mbar_wait(sb + B_W + 8 * th, 0);
                if (th == 1) {
#pragma unroll
                    for (int i = 0; i < 6; i++) xv[i] = __ldg(xp + i * 256);
                }
#pragma unroll
                for (int u = 4 * th; u < 4 * th + 4; u++) {
                    gather(32 + 4 * u, wg * (73728 + 4096) + KS(u) * 2048);
                    gather(4 * u, 73728 - wg * (73728 - 4096) + KS(u) * 2048);
                    gather(64 + 4 * u, wg * 73728 + KS(8 + u) * 2048);
                }
            }
            mbar_wait(sb + B_W + 16, 0);
#pragma unroll
            for (int u = 16; u < 28; u++) gather(32 + 4 * u, wg * 73728 + KS(u) * 2048);
#pragma unroll
            for (int kk = 0; kk < 72; kk++) {
                uint32_t w0 = a[2 * kk], w1 = a[2 * kk + 1];
                a[2 * kk] = __byte_perm(w0, w1, 0x5410);
                a[2 * kk + 1] = __byte_perm(w0, w1, 0x7632);
            }
            if (r == 2) {
                float n0[4], n1[4];
#pragma unroll
                for (int u = 0; u < 36; u++) {
                    const uint32_t x0 = a[4 * u] & 0x7fff7fffu, x1 = a[4 * u + 1] & 0x7fff7fffu, x2 = a[4 * u + 2] & 0x7fff7fffu, x3 = a[4 * u + 3] & 0x7fff7fffu;
                    if (u == 0) mma16816_z(n0, x0, x1, x2, x3, ONES, ONES);
                    else if (u < 8) mma16816(n0, x0, x1, x2, x3, ONES, ONES);
                    else if (u == 8) mma16816_z(n1, x0, x1, x2, x3, ONES, ONES);
                    else mma16816(n1, x0, x1, x2, x3, ONES, ONES);
                }
                const uint32_t mx = __reduce_max_sync(~0u, __float_as_uint(2.f * fmaxf(fmaxf(n0[0], n0[2]), fmaxf(n1[0], n1[2]))));
                sts32_if(lane, sb + O_MISC + 32 + 4 * warp, mx);
            }
            uint32_t xm = 0;
#pragma unroll
            for (int i = 0; i < 6; i++)
                xm = __vmaxu2(xm, __vmaxu2(__vmaxu2(xv[i].x & 0x7fff7fffu, xv[i].y & 0x7fff7fffu), __vmaxu2(xv[i].z & 0x7fff7fffu, xv[i].w & 0x7fff7fffu)));
            sts32_if(lane, sb + O_OF + 16 + 4 * warp, __reduce_max_sync(~0u, max(xm << 16, xm & 0xffff0000u)));
            if (warp == 0) PSTAMP(11);
            bar_arrive(7, 384);
            asm volatile("barrier.cluster.arrive.relaxed.aligned;" ::: "memory");
            bar_sync(1, 256);
            const uint32_t as = sb + O_AS + wg * 8192 + (16 * w + g) * 128 + t * 4;
            sts32(as + (g << 4), a[32]);
            sts32(as + 1024 + (g << 4), a[33]);
            sts32(as + ((1 ^ g) << 4), a[34]);
            sts32(as + 1024 + ((1 ^ g) << 4), a[35]);
            sts128(sb + O_AF + warp * 512 + lane * 16, a[32], a[33], a[34], a[35]);
            fence_async_smem();
            bar_sync(1, 256);
            const uint32_t l = lane * 16;
            const int mi = lane >> 3, isk = (mi >> 1) ? wg : (wg ^ 1);
            adr1 = (r == 2) ? (sb + O_VM + warp * 256 + (l >> 1))
                            : (isk ? (sb + O_KM + w * 512 + wg * 256 + (mi & 1) * 128 + (l & 127))
                                   : (sb + O_QM + w * 512 + (mi & 1) * 256 + wg * 128 + (l & 127)));
            adr1 = __shfl_sync(~0u, adr1, lane);
        }
        int s3 = 2;
#pragma unroll 1
        for (int s = -1; s < NSEG; s++) {
            const uint32_t l16 = opaque(l16c);
            s3 = (s3 == 2) ? 0 : s3 + 1;
            if (s < 0) mbar_wait(sb + B_X, 0);
            const uint64_t desc0 = (uint64_t)(((sb + O_XT + s3 * XT_BYTES) & 0x3FFFF) >> 4) | (1ull << 16) | (64ull << 32) | (1ull << 62);
            uint32_t km0 = 0, km1 = 0;
            if (s >= 0) {
                { const uint4 v = lds128(sb + O_AF + warp * 512 + l16); a[32] = v.x; a[33] = v.y; a[34] = v.z; a[35] = v.w; }
                float co[4], cw[3][4];
                uint4 b[14];
                float inv;
#define GORD(i) ((i) < 8 ? 2 * ((i) >> 2) + (((i) >> 1) & 1) + 4 * ((i) & 1) : (i))
                auto qkv_mma = [&](int i) {
                    const int gi = GORD(i), u = 8 * gi, n0 = 2 * i, n1 = 2 * i + 1;
                    if (gi < 4) {
                        if (i == 0) mma16816_z(co, a[u], a[u + 1], a[u + 2], a[u + 3], b[0].x, b[0].y);
                        else mma16816(co, a[u], a[u + 1], a[u + 2], a[u + 3], b[i].x, b[i].y);
                    }
                    if (n0 < 3) mma16816_z(cw[n0 % 3], a[32 + u], a[32 + u + 1], a[32 + u + 2], a[32 + u + 3], b[i].x, b[i].y);
                    else mma16816(cw[n0 % 3], a[32 + u], a[32 + u + 1], a[32 + u + 2], a[32 + u + 3], b[i].x, b[i].y);
                    if (n1 < 3) mma16816_z(cw[n1 % 3], a[32 + u + 4], a[32 + u + 5], a[32 + u + 6], a[32 + u + 7], b[i].z, b[i].w);
                    else mma16816(cw[n1 % 3], a[32 + u + 4], a[32 + u + 5], a[32 + u + 6], a[32 + u + 7], b[i].z, b[i].w);
                    if (gi < 4) mma16816(co, a[u + 4], a[u + 5], a[u + 6], a[u + 7], b[i].z, b[i].w);
                };
                const uint32_t mf = sb + O_MF + l16, mfs = mf + wg * 1024;
                const uint32_t qb = (s & 1) * 12288;
                bar_sync(2, 384);
                if (warp == 0) STAMP(s, 0);
                auto qkv_ld = [&](int i) {
                    const int gi = GORD(i);
                    b[i] = gi < 4 ? lds128v(mfs + (gi >> 1) * 3072 + (gi & 1) * 512) : lds128v(mf + (gi < 6 ? gi : gi + 4) * 512);
                };
#pragma unroll
                for (int i = 0; i < 4; i++) qkv_ld(i);
                qkv_mma(0); qkv_mma(1); qkv_mma(2);
                const uint32_t z0 = __float_as_uint(QDEP ? co[0] : cw[1][0]) & (l16 & 15u);
                qkv_mma(3);
                bar_sync(15, 384);
                b[4] = lds128v(mfs + 3072 + z0);
#pragma unroll
                for (int i = 5; i < 9; i++) qkv_ld(i);
#pragma unroll
                for (int i = 4; i < 9; i++) { qkv_mma(i); qkv_ld(5 + i); }
                asm volatile("ld.volatile.shared.f32 %0, [%1];" : "=f"(inv) : "r"(sb + O_MISC) : "memory");
#pragma unroll
                for (int i = 9; i < 14; i++) qkv_mma(i);
#pragma unroll
                for (int i = 0; i < 4; i++) cw[0][i] += cw[1][i] + cw[2][i];
                if (r < 2) {
                    const uint32_t o0 = pack_bf16(co[0] * inv, co[1] * inv), o1 = pack_bf16(co[2] * inv, co[3] * inv);
                    const uint32_t w0 = pack_bf16(cw[0][0] * inv, cw[0][1] * inv), w1 = pack_bf16(cw[0][2] * inv, cw[0][3] * inv);
                    stsm4t(adr1 + qb, o0, o1, w0, w1);
                    if (warp == 0) STAMP(s, 1);
                    asm volatile("{\n.reg .pred p;\nsetp.ge.u32 p, %0, 3;\n@p bar.arrive 1, 256;\n}" :: "r"(warp) : "memory");
                    auto scores = [&](float (&v)[4], const uint4 (&q)[4], const uint4 (&k)[4]) {
                        float s0[4], s1[4], t0[4], t1[4];
                        mma16816_z(s0, q[0].x, q[0].y, q[0].z, q[0].w, k[0].x, k[0].y);
                        mma16816_z(s1, q[0].x, q[0].y, q[0].z, q[0].w, k[0].z, k[0].w);
                        mma16816_z(t0, q[1].x, q[1].y, q[1].z, q[1].w, k[1].x, k[1].y);
                        mma16816_z(t1, q[1].x, q[1].y, q[1].z, q[1].w, k[1].z, k[1].w);
                        mma16816(s0, q[2].x, q[2].y, q[2].z, q[2].w, k[2].x, k[2].y);
                        mma16816(s1, q[2].x, q[2].y, q[2].z, q[2].w, k[2].z, k[2].w);
                        mma16816(t0, q[3].x, q[3].y, q[3].z, q[3].w, k[3].x, k[3].y);
                        mma16816(t1, q[3].x, q[3].y, q[3].z, q[3].w, k[3].z, k[3].w);
                        v[0] = (s0[0] + s0[2]) + (t0[0] + t0[2]); v[1] = (s0[1] + s0[3]) + (t0[1] + t0[3]);
                        v[2] = (s1[0] + s1[2]) + (t1[0] + t1[2]); v[3] = (s1[1] + s1[3]) + (t1[1] + t1[3]);
                    };
                    if (warp < 2) {
                        uint4 q[4], k[4]; float v[4];
#pragma unroll
                        for (int i = 0; i < 4; i++) k[i] = ldsm4(sb + O_QKX + 4096 + qb + warp * 2048 + i * 512 + l16);
                        bar_sync(1, 256);
#pragma unroll
                        for (int i = 0; i < 4; i++) q[i] = ldsm4(sb + O_QM + qb + i * 512 + l16);
                        scores(v, q, k);
                        const uint32_t dst = sb + O_SC + r * 1280 + warp * 512 + l16;
                        st_async128(mapa(dst, 2), __float_as_uint(v[0]), __float_as_uint(v[1]), __float_as_uint(v[2]), __float_as_uint(v[3]), mapa(sb + B_SC, 2));
                        st_async128(mapa(dst, r ^ 1), __float_as_uint(v[0]), __float_as_uint(v[1]), __float_as_uint(v[2]), __float_as_uint(v[3]), mapa(sb + B_SC, r ^ 1));
                        st_async128(mapa(dst, r), __float_as_uint(v[0]), __float_as_uint(v[1]), __float_as_uint(v[2]), __float_as_uint(v[3]), mapa(sb + B_SC, r));
                    } else if (warp == 2) {
                        uint4 q[4], k[4]; float v[4];
                        bar_sync(1, 256);
#pragma unroll
                        for (int i = 0; i < 4; i++) { q[i] = ldsm4(sb + O_QM + qb + i * 512 + l16); k[i] = ldsm4(sb + O_KM + qb + i * 512 + l16); }
                        scores(v, q, k);
                        const uint32_t dst = sb + O_SC + r * 1280 + 1024 + (l16 >> 1);
                        st_async64(mapa(dst, 2), __float_as_uint(v[0] + v[2]), __float_as_uint(v[1] + v[3]), mapa(sb + B_SC, 2));
                        st_async64(mapa(dst, r ^ 1), __float_as_uint(v[0] + v[2]), __float_as_uint(v[1] + v[3]), mapa(sb + B_SC, r ^ 1));
                        st_async64(mapa(dst, r), __float_as_uint(v[0] + v[2]), __float_as_uint(v[1] + v[3]), mapa(sb + B_SC, r));
                        STAMP(s, 2);
                    }
                } else {
                    sts128f(sb + O_XP + warp * 512 + l16, co[0], co[1], co[2], co[3]);
                    bar_sync(8 + w, 64);
                    const float4 o = lds128f(sb + O_XP + (warp ^ 4) * 512 + l16);
                    km0 = pack_bf16((cw[0][0] + o.x) * inv, (cw[0][1] + o.y) * inv);
                    km1 = pack_bf16((cw[0][2] + o.z) * inv, (cw[0][3] + o.w) * inv);
                    if (warp == 0) STAMP(s, 1);
                    st_async64(mapa(adr1, 0), km0, km1, mapa(sb + B_SC, 0));
                    st_async64(mapa(adr1, 1), km0, km1, mapa(sb + B_SC, 1));
                    st_async64(mapa(adr1, 2), km0, km1, mapa(sb + B_SC, 2));
                    if (warp == 0) STAMP(s, 2);
                }
            }
            if (s >= 0) bar_sync(3, 384);
            auto store_qk = [&]() {
                asm volatile("{\n.reg .pred p;\nelect.sync _|p, 0xffffffff;\n"
                    "@p cp.async.bulk.global.shared::cta.bulk_group [%0], [%1], 10240;\n@p cp.async.bulk.commit_group;\n}"
                    :: "l"(reinterpret_cast<char*>(g_qkv) + (size_t)(s * NH + h) * REC + r * 10240), "r"(sb + O_QKX + (s & 1) * 12288) : "memory");
            };
            auto store_vm = [&]() {
                *reinterpret_cast<uint2*>(reinterpret_cast<char*>(g_qkv) + (size_t)(s * NH + h) * REC + 28672 + warp * 256 + (l16 >> 1)) = make_uint2(km0, km1);
            };
            if (s == NSEG - 1) {
                if (r == 2) store_vm();
                else if (warp == 3) {
                    fence_async_smem();
                    store_qk();
                    asm volatile("cp.async.bulk.wait_group 0;\nfence.proxy.async.global;" ::: "memory");
                }
            } else {
                const int j = s + 1;
#define XDESC(u) (((u) < 8 ? descs : desc0) + (uint64_t)(((KS(u) >> 2) * 4096 + (KS(u) & 3) * 32) >> 4))
                const uint64_t descs = desc0 + (uint64_t)(wg * 4);
                float d[16];
                wg_fence();
#pragma unroll
                for (int u = 0; u < 8; u++) {
                    if (u == 0) wgmma_n32_rs<0>(d, a[0], a[1], a[2], a[3], XDESC(0));
                    else wgmma_n32_rs<1>(d, a[4 * u], a[4 * u + 1], a[4 * u + 2], a[4 * u + 3], XDESC(u));
                }
                wg_commit();
                wg_wait0();
                if (warp == 0) STAMP(s, 15);
                if (warp == 3) asm volatile("cp.async.bulk.wait_group.read 0;" ::: "memory");
                if (s >= 0) bar_sync(4, 384);
#pragma unroll
                for (int q = 0; q < 2; q++)
                    sts128(sb + O_XP + warp * 1024 + q * 512 + l16, pack_bf16(d[8 * q], d[8 * q + 1]), pack_bf16(d[8 * q + 2], d[8 * q + 3]),
                           pack_bf16(d[8 * q + 4], d[8 * q + 5]), pack_bf16(d[8 * q + 6], d[8 * q + 7]));
                bar_sync(12, 256);
#pragma unroll
                for (int q = 0; q < 2; q++) {
                    const uint4 o = lds128(sb + O_XP + (warp ^ 4) * 1024 + q * 512 + l16);
                    d[8 * q] = __uint_as_float(o.x << 16); d[8 * q + 1] = __uint_as_float(o.x & 0xffff0000u);
                    d[8 * q + 2] = __uint_as_float(o.y << 16); d[8 * q + 3] = __uint_as_float(o.y & 0xffff0000u);
                    d[8 * q + 4] = __uint_as_float(o.z << 16); d[8 * q + 5] = __uint_as_float(o.z & 0xffff0000u);
                    d[8 * q + 6] = __uint_as_float(o.w << 16); d[8 * q + 7] = __uint_as_float(o.w & 0xffff0000u);
                }
                if (s >= 0) {
                    if (r == 2) store_vm();
                    if (warp == 5 && s + 2 < NSEG) tma_x_tile(sb, &tm_x, r, s + 2, s3 == 2 ? 0 : s3 + 1);
                    if (warp == 3) {
                        asm volatile("cp.async.bulk.wait_group 0;\nfence.proxy.async.global;" ::: "memory");
                        if (s >= 4 && !(s & (s > 4 * NBIG ? 1 : 3))) {
                            __syncwarp();
                            flag_inc_if(l16, &g_flag[F_QKV + ((s > 4 * NBIG ? 2 * s - 4 * NBIG : s) - 4 + (h >> 3)) * 8]);
                        }
                        fence_async_smem();
                    }
                    asm volatile("{\n.reg .pred p;\nsetp.eq.u32 p, %0, 0;\n@p bar.sync 5, 256;\n@!p bar.sync 13, 256;\n}" :: "r"(wg) : "memory");
                }
                const uint64_t da0 = (uint64_t)(((sb + O_AS + wg * 8192) & 0x3FFFF) >> 4) | (1ull << 16) | (64ull << 32) | (1ull << 62);
                wg_fence();
                wgmma_n32_ss<1>(d, da0, XDESC(0));
#pragma unroll
                for (int u = 1; u < 28; u++) wgmma_n32_rs<1>(d, a[32 + 4 * u], a[32 + 4 * u + 1], a[32 + 4 * u + 2], a[32 + 4 * u + 3], XDESC(u));
                wg_commit();
                wg_wait0();
                if (warp == 3 && r < 2 && s >= 0) store_qk();
                if (warp == 4) STAMP(s, 3);
                uint32_t e[8];
#pragma unroll
                for (int i = 0; i < 8; i++) e[i] = pack_bf16(d[2 * i], d[2 * i + 1]);
                if (r < 2) {
                    const uint32_t base = sb + O_QKX + (j & 1) * 12288 + wg * 4096 + w * 512 + l16;
                    stsm4t(base, e[0], wg ? e[1] : e[2], wg ? e[2] : e[1], e[3]);
                    stsm4t(base + 2048, e[4], wg ? e[5] : e[6], wg ? e[6] : e[5], e[7]);
                } else {
                    const uint32_t base = sb + O_VX + (j & 1) * 8192 + warp * 1024 + l16;
                    sts128(base, e[0], e[1], e[2], e[3]);
                    sts128(base + 512, e[4], e[5], e[6], e[7]);
                    bar_arrive(14, 288);
                }
                if (warp == 7) STAMP(s, 4);
                if (s < 0) asm volatile("barrier.cluster.wait.aligned;" ::: "memory");
            }
        }
        bar_arrive(7, 384);
    } else {
        asm volatile("setmaxnreg.dec.sync.aligned.u32 136;");
        const int c = w;
        uint32_t a[96];
        uint32_t mmax = 0;
        {
            const int g = lane >> 2, t = lane & 3;
            uint32_t tag = 0, m0v[18];
            if (threadIdx.x == 256) tag = atomicAdd(&g_ticket, 1u);
#pragma unroll
            for (int i = 0; i < 9; i++) {
                const uint32_t* p = reinterpret_cast<const uint32_t*>(mem0 + g * DM + 16 * (4 * i + c) + 2 * t);
                m0v[2 * i] = __ldg(p); m0v[2 * i + 1] = __ldg(p + 4);
            }
            asm volatile("barrier.cluster.wait.aligned;" ::: "memory");
            if (c == 0) {
                tma_x_tile(sb, &tm_x, r, 0, 0);
                mbar_expect_if(lane, sb + B_SC, 4608);
                if (r < 2) mbar_expect_if(lane, sb + B_VX, 8192);
                sts32_if(lane, sb + O_MISC, __float_as_uint(1.0f));
                sts32_if(lane, sb + O_MISC + 12, __float_as_uint(SM_SCALE));
            }
            asm volatile("barrier.cluster.arrive.relaxed.aligned;" ::: "memory");
#pragma unroll
            for (int tau = 0; tau < 3; tau++) {
                const uint32_t* v = m0v + 6 * tau;
                sts128(sb + O_MF + tau * 3072 + c * 512 + lane * 16, v[0], v[1], v[2], v[3]);
                sts64(sb + O_MF + tau * 3072 + 2048 + (c >> 1) * 512 + lane * 16 + (c & 1) * 8, v[4], v[5]);
#pragma unroll
                for (int i = 0; i < 6; i++) mmax = __vmaxu2(mmax, v[i] & 0x7fff7fffu);
            }
            mmax = max(mmax << 16, mmax & 0xffff0000u);
            bar_arrive(2, 384); bar_arrive(15, 384);
            tag = (__shfl_sync(~0u, tag, 0) / 96u + 1u) & 0xffffu;
            mbar_wait(sb + B_W + 0, 0);
            const __nv_bfloat16* p = Wo + (size_t)(h * 128 + 4 * t) * DM + 192 * r + 16 * c + 2 * g;
#pragma unroll
            for (int i = 0; i < 3; i++)
#pragma unroll
                for (int eb = 0; eb < 8; eb++)
#pragma unroll
                    for (int j = 0; j < 4; j++) a[(i * 8 + eb) * 4 + j] = ldg_nc32(p + (16 * eb + ((j & 1) * 2 + (j >> 1))) * DM + 64 * i);
#pragma unroll
            for (int kk = 0; kk < 48; kk++) {
                uint32_t w0 = a[2 * kk], w1 = a[2 * kk + 1];
                a[2 * kk] = __byte_perm(w0, w1, 0x5410);
                a[2 * kk + 1] = __byte_perm(w0, w1, 0x7632);
            }
            sts128(sb + O_WP + c * 512 + lane * 16, a[92], a[93], a[94], a[95]);
            float wmax = 0.f;
#pragma unroll
            for (int i = 0; i < 3; i++) {
                float n0[4];
#pragma unroll
                for (int u = 8 * i; u < 8 * i + 8; u++) {
                    const uint32_t x0 = a[4 * u] & 0x7fff7fffu, x1 = a[4 * u + 1] & 0x7fff7fffu, x2 = a[4 * u + 2] & 0x7fff7fffu, x3 = a[4 * u + 3] & 0x7fff7fffu;
                    if (u == 8 * i) mma16816_z(n0, x0, x1, x2, x3, ONES, ONES);
                    else mma16816(n0, x0, x1, x2, x3, ONES, ONES);
                }
                wmax = fmaxf(wmax, fmaxf(n0[0], n0[2]));
            }
            uint32_t wm = __reduce_max_sync(~0u, __float_as_uint(wmax));
            sts32_if(lane, sb + O_OF + 4 * c, wm);
            if (c == 0) PSTAMP(8);
            bar_sync(7, 384);
            asm volatile("barrier.cluster.wait.aligned;" ::: "memory");
            if (c == 1) tma_x_tile(sb, &tm_x, r, 1, 1);
            if (c == 0) {
                const uint4 wq = lds128(sb + O_OF), xq = lds128(sb + O_OF + 16), xr = lds128(sb + O_OF + 32), v0 = lds128(sb + O_MISC + 32), v1 = lds128(sb + O_MISC + 48);
                const uint32_t w1 = max(max(wq.x, wq.y), max(wq.z, wq.w)), x1 = max(max(max(xq.x, xq.y), max(xq.z, xq.w)), max(max(xr.x, xr.y), max(xr.z, xr.w)));
                const uint32_t vv = (r < 2) ? 0u : max(max(max(v0.x, v0.y), max(v0.z, v0.w)), max(max(v1.x, v1.y), max(v1.z, v1.w)));
                const uint32_t lo = (min(w1, 0x7f800000u) + 0xffffu) >> 16 | ((min(vv, 0x7f800000u) + 0xffffu) & 0xffff0000u), hi = (x1 & 0xffff0000u) | tag;
                uint32_t l0, h0, l1, h1, l2, h2;
                asm volatile("{\n.reg .pred p;\n.reg .u32 n, x, y;\n.reg .b64 v;\nsetp.eq.u32 p, %10, 0;\nmov.b64 v, {%8, %9};\n@p st.relaxed.gpu.global.b64 [%7], v;\nmov.u32 n, 0;\n"
                             "G_%=: ld.relaxed.gpu.global.b64 v, [%6];\nmov.b64 {%0, %1}, v;\nld.relaxed.gpu.global.b64 v, [%6+256];\nmov.b64 {%2, %3}, v;\n"
                             "ld.relaxed.gpu.global.b64 v, [%6+512];\nmov.b64 {%4, %5}, v;\n"
                             "xor.b32 x, %1, %9;\nxor.b32 y, %3, %9;\nor.b32 x, x, y;\nxor.b32 y, %5, %9;\nor.b32 x, x, y;\nand.b32 x, x, 0xffff;\n"
                             "setp.eq.u32 p, x, 0;\nvote.sync.all.pred p, p, 0xffffffff;\n@p bra.uni E_%=;\n"
                             "add.u32 n, n, 1;\nsetp.lt.u32 p, n, 4000000;\n@p bra.uni G_%=;\ntrap;\nE_%=:\n}"
                             : "=&r"(l0), "=&r"(h0), "=&r"(l1), "=&r"(h1), "=&r"(l2), "=&r"(h2)
                             : "l"(&g_norm[lane]), "l"(&g_norm[blockIdx.x]), "r"(lo), "r"(hi), "r"(lane) : "memory");
                const uint32_t lm = __vmaxu2(l0, __vmaxu2(l1, l2));
                const float fw = __uint_as_float(__reduce_max_sync(~0u, lm << 16));
                const float fv = __uint_as_float(__reduce_max_sync(~0u, lm & 0xffff0000u));
                const float xmax = __uint_as_float(__reduce_max_sync(~0u, max(h0, max(h1, h2)) & 0xffff0000u));
                const float G = 36.f * fw * fv;
                sts32_if(lane, sb + O_MISC + 4, __float_as_uint(G)); sts32_if(lane, sb + O_MISC + 8, __float_as_uint(G * xmax));
            }
        }
        if (c == 0) PSTAMP(12);
        bar_sync(6, 128);
        int s3n = 1;
        uint32_t roff = __shfl_sync(~0u, (r * 4 + c) * 2048 + (lane >> 4) * 512 + (lane & 2) * 128 + (lane & 1) * 64 + (lane & 12) * 4, lane);
#pragma unroll 1
        for (int s = 0; s < NSEG; s++) {
            const uint32_t l16 = opaque(l16c);
            const uint32_t vxa = sb + O_VX + (s & 1) * 8192 + c * 2048 + l16;
            if (c == 0 && r == 2) {
                bar_sync(14, 288);
                fence_async_smem();
                asm volatile("{\n.reg .pred p;\nelect.sync _|p, 0xffffffff;\n"
                    "@p cp.async.bulk.global.shared::cta.bulk_group [%0], [%1], 8192;\n@p cp.async.bulk.commit_group;\n"
                    "cp.async.bulk.wait_group 0;\nsetp.lt.and.s32 p, %4, 63, p;\n"
                    "@p cp.async.bulk.shared::cluster.global.mbarrier::complete_tx::bytes.multicast::cluster [%1], [%0], 8192, [%2], %3;\n"
                    "fence.proxy.async.global;\n}"
                    :: "l"(reinterpret_cast<char*>(g_qkv) + (size_t)(s * NH + h) * REC + 20480), "r"(sb + O_VX + (s & 1) * 8192),
                       "r"(sb + B_VX + 8 * (s & 1)), "h"((unsigned short)3), "r"(s) : "memory");
            }
            if (s == NSEG - 1) { bar_sync(3, 384); mbar_wait(sb + B_SC, s & 1); break; }
            uint4 vx[4];
            sts32_if(l16, sb + O_MISC + 16 + 4 * c, __reduce_max_sync(~0u, mmax));
            if (c == 0) STAMP(s, 5);
            {
                bar_sync(6, 128);
                const uint4 mm = lds128(sb + O_MISC + 16), cf = lds128(sb + O_MISC);
                const float bound = fmaxf(__uint_as_float(cf.z), __uint_as_float(cf.y) * (__uint_as_float(max(max(mm.x, mm.y), max(mm.z, mm.w))) * __uint_as_float(cf.x)));
                const uint32_t ebits = __reduce_max_sync(~0u, min(max(__float_as_uint(bound) & 0x7f800000u, 21u << 23), 254u << 23));
                mbar_wait(sb + B_X + 8 * s3n, ((s + 1) / 3) & 1);
                s3n = (s3n == 2) ? 0 : s3n + 1;
                bar_sync(3, 384);
                if (r < 2) mbar_wait(sb + B_VX + 8 * (s & 1), (s >> 1) & 1);
                vx[0] = lds128(vxa); vx[2] = lds128(vxa + 1024);
                if (c == 0) STAMP(s, 13);
                mbar_wait(sb + B_SC, s & 1);
                if (c == 0) STAMP(s, 6);
                float p[10];
                load_scores(p, sb + O_SC, 1280, l16);
                float mx = fmaxf(fmaxf(fmaxf(p[0], p[1]), fmaxf(p[2], p[3])), fmaxf(fmaxf(p[4], p[5]), fmaxf(p[6], p[7])));
                mx = quad_max(fmaxf(mx, fmaxf(p[8], p[9])));
                const uint4 vm = lds64x2(sb + O_VM + c * 512 + (l16 >> 1));
                vx[1] = lds128(vxa + 512); vx[3] = lds128(vxa + 1536);
                bar_arrive(4, 384);
                const float sc = __uint_as_float(lds32(sb + O_MISC + 12));
                const float mo = mx * SM_SCALE;
                uint32_t P[5];
#pragma unroll
                for (int n = 0; n < 5; n++) P[n] = pack_bf16(ex2(fmaf(p[2 * n], SM_SCALE, -mo)), ex2(fmaf(p[2 * n + 1], n == 3 ? sc : SM_SCALE, -mo)));
                if (c == 0) STAMP(s, 7);
                float o0[4], o1[4], sm[4];
                mma16816_z(sm, ONES, ONES, ONES, ONES, P[1], P[2]);
                mma16816_z(o0, vx[0].x, vx[0].y, vx[0].z, vx[0].w, P[1], P[2]);
                mma16816_z(o1, vx[2].x, vx[2].y, vx[2].z, vx[2].w, P[1], P[2]);
                mma16816(sm, ONES, ONES, ONES, ONES, P[3], P[4]);
                mma16816(o0, vx[1].x, vx[1].y, vx[1].z, vx[1].w, P[3], P[4]);
                mma16816(o1, vx[3].x, vx[3].y, vx[3].z, vx[3].w, P[3], P[4]);
                mma1688(sm, ONES, ONES, P[0]);
                mma1688(o0, vm.x, vm.y, P[0]);
                mma1688(o1, vm.z, vm.w, P[0]);
                const float sig = __uint_as_float((268u << 23) - ebits);
                const float r0 = rcp_fast(sm[0]) * sig, r1 = rcp_fast(sm[1]) * sig;
                stsm4t(sb + O_OF + c * 512 + l16, pack_bf16(o0[0] * r0, o0[1] * r1), pack_bf16(o0[2] * r0, o0[3] * r1),
                       pack_bf16(o1[0] * r0, o1[1] * r1), pack_bf16(o1[2] * r0, o1[3] * r1));
                bar_sync(6, 128);
                uint4 ob[4];
#pragma unroll
                for (int q = 0; q < 4; q++) ob[q] = ldsm4(sb + O_OF + q * 512 + l16);
                { const uint4 v = lds128(sb + O_WP + c * 512 + l16); a[92] = v.x; a[93] = v.y; a[94] = v.z; a[95] = v.w; }
                float m0[3][4], m1[3][4];
#pragma unroll
                for (int q = 0; q < 4; q++) {
#pragma unroll
                    for (int i = 0; i < 3; i++) {
                        const int k0 = (i * 8 + 2 * q) * 4;
                        if (q == 0) mma16816_z(m0[i], a[k0], a[k0 + 1], a[k0 + 2], a[k0 + 3], ob[q].x, ob[q].y);
                        else mma16816(m0[i], a[k0], a[k0 + 1], a[k0 + 2], a[k0 + 3], ob[q].x, ob[q].y);
                    }
#pragma unroll
                    for (int i = 0; i < 3; i++) {
                        const int k1 = (i * 8 + 2 * q + 1) * 4;
                        if (q == 0) mma16816_z(m1[i], a[k1], a[k1 + 1], a[k1 + 2], a[k1 + 3], ob[q].z, ob[q].w);
                        else mma16816(m1[i], a[k1], a[k1 + 1], a[k1 + 2], a[k1 + 3], ob[q].z, ob[q].w);
                    }
                }
                asm volatile("red.relaxed.gpu.global.add.noftz.v4.f16x2 [%0], {%1,%2,%3,%4};" :: "l"(reinterpret_cast<char*>(g_acc) + roff),
                    "r"(pack_f16(m0[0][0] + m1[0][0], m0[0][2] + m1[0][2])), "r"(pack_f16(m0[1][0] + m1[1][0], m0[1][2] + m1[1][2])),
                    "r"(pack_f16(m0[2][0] + m1[2][0], m0[2][2] + m1[2][2])), "r"(0x3c00u) : "memory");
                asm volatile("red.relaxed.gpu.global.add.noftz.v4.f16x2 [%0], {%1,%2,%3,%4};" :: "l"(reinterpret_cast<char*>(g_acc) + roff + 1024),
                    "r"(pack_f16(m0[0][1] + m1[0][1], m0[0][3] + m1[0][3])), "r"(pack_f16(m0[1][1] + m1[1][1], m0[1][3] + m1[1][3])),
                    "r"(pack_f16(m0[2][1] + m1[2][1], m0[2][3] + m1[2][3])), "r"(0x3c00u) : "memory");
                const unsigned t_red = clk();
                bar_arrive(5, 256);
                bar_arrive(13, 256);
                mbar_expect_if(l16 | c, sb + B_SC, 4608);
                mbar_expect_if(l16 | (c ^ 1) | (r >> 1), sb + B_VX + 8 * ((s + 1) & 1), 8192);
                sts32_if(l16 | (c ^ 3), sb + O_MISC, ebits - (14u << 23));
                if (c == 0) STAMPV(s, 8, t_red);
                if (ACC_PF && c == 2 && s + 4 < NSEG - 1)
                    asm volatile("prefetch.global.L2 [%0];" :: "l"(reinterpret_cast<const char*>(g_acc) + ((s + 4) * 96 + blockIdx.x) * 256 + (l16 & 96)) : "memory");
                const char* pbase = reinterpret_cast<const char*>(g_acc) + (s * 24576 + c * 2048) + ((l16 & 64) * 16 + (l16 & 256) + ((l16 & 128) >> 1) + (l16 & 48));
                spin_until(t_red, D_WAIT);
                uint4 v[6];
#pragma unroll
                for (int i = 0; i < 6; i++) v[i] = ldg_relaxed128(pbase + (i >> 1) * 8192 + (i & 1) * 512);
                int nretry = 0;
                auto convert = [&](int tau) {
                    const uint4 A = v[2 * tau], B = v[2 * tau + 1];
                    sts128(sb + O_MF + tau * 3072 + c * 512 + l16, f16x2_to_bf16x2(A.x), f16x2_to_bf16x2(B.x), f16x2_to_bf16x2(A.y), f16x2_to_bf16x2(B.y));
                    sts64(sb + O_MF + tau * 3072 + 2048 + (c >> 1) * 512 + (c & 1) * 8 + l16, f16x2_to_bf16x2(A.z), f16x2_to_bf16x2(B.z));
                };
                const uint32_t ok0 = __all_sync(~0u, (v[0].w & v[1].w) == 0x5000u);
                convert(0);
                asm volatile("{\n.reg .pred p;\nsetp.ne.u32 p, %0, 0;\n@p bar.arrive 2, 384;\n}" :: "r"(ok0) : "memory");
                sched_fence<0>(h);
                uint32_t ok1;
                asm volatile("{\n.reg .pred p, q;\n.reg .b32 x;\nlop3.b32 x, %1, %2, %3, 0x80;\nand.b32 x, x, %4;\n"
                             "setp.eq.u32 p, x, 0x5000;\nvote.sync.all.pred q, p, 0xffffffff;\nselp.u32 %0, 1, 0, q;\n}"
                             : "=r"(ok1) : "r"(v[2].w), "r"(v[3].w), "r"(v[4].w), "r"(v[5].w));
                convert(1); convert(2);
                asm volatile("{\n.reg .pred p;\nsetp.ne.u32 p, %0, 0;\n@p bar.arrive 15, 384;\n}" :: "r"(ok1) : "memory");
                if (!(ok0 & ok1)) {
                    asm volatile("{\n.reg .pred p0, p1, p2, p3, p4, p5, q;\n.reg .u32 n, x;\nmov.u32 n, 0;\n"
                         "R_%=: setp.ne.u32 p0, %3, 0x5000;\nsetp.ne.u32 p1, %7, 0x5000;\nsetp.ne.u32 p2, %11, 0x5000;\n"
                         "setp.ne.u32 p3, %15, 0x5000;\nsetp.ne.u32 p4, %19, 0x5000;\nsetp.ne.u32 p5, %23, 0x5000;\n"
                         "@p0 ld.relaxed.gpu.global.v4.u32 {%0,%1,%2,%3}, [%25];\n@p1 ld.relaxed.gpu.global.v4.u32 {%4,%5,%6,%7}, [%25+512];\n"
                         "@p2 ld.relaxed.gpu.global.v4.u32 {%8,%9,%10,%11}, [%25+8192];\n@p3 ld.relaxed.gpu.global.v4.u32 {%12,%13,%14,%15}, [%25+8704];\n"
                         "@p4 ld.relaxed.gpu.global.v4.u32 {%16,%17,%18,%19}, [%25+16384];\n@p5 ld.relaxed.gpu.global.v4.u32 {%20,%21,%22,%23}, [%25+16896];\n"
                         "add.u32 %24, %24, 1;\nand.b32 x, %3, %7;\nand.b32 x, x, %11;\nand.b32 x, x, %15;\nand.b32 x, x, %19;\nand.b32 x, x, %23;\n"
                         "setp.eq.u32 q, x, 0x5000;\nvote.sync.all.pred q, q, 0xffffffff;\n@q bra.uni K_%=;\n"
                         "add.u32 n, n, 1;\nsetp.lt.u32 q, n, 2000000;\n@q bra.uni R_%=;\ntrap;\nK_%=:\n}"
                         : "+r"(v[0].x), "+r"(v[0].y), "+r"(v[0].z), "+r"(v[0].w), "+r"(v[1].x), "+r"(v[1].y), "+r"(v[1].z), "+r"(v[1].w),
                           "+r"(v[2].x), "+r"(v[2].y), "+r"(v[2].z), "+r"(v[2].w), "+r"(v[3].x), "+r"(v[3].y), "+r"(v[3].z), "+r"(v[3].w),
                           "+r"(v[4].x), "+r"(v[4].y), "+r"(v[4].z), "+r"(v[4].w), "+r"(v[5].x), "+r"(v[5].y), "+r"(v[5].z), "+r"(v[5].w), "+r"(nretry)
                         : "l"(pbase) : "memory");
                    if (!ok0) { convert(0); bar_arrive(2, 384); }
                    if (!ok1) { convert(1); convert(2); bar_arrive(15, 384); }
                }
                if (c == 0) STAMP(s, 12);
                if (c == 0) STAMPV(s, 14, nretry);
                mmax = absmax2(absmax2(absmax2(v[0].x, v[0].y), absmax2(v[0].z, v[1].x)), absmax2(absmax2(v[1].y, v[1].z), absmax2(v[2].x, v[2].y)));
                mmax = absmax2(mmax, absmax2(absmax2(absmax2(v[2].z, v[3].x), absmax2(v[3].y, v[3].z)), absmax2(absmax2(v[4].x, v[4].y), absmax2(v[4].z, v[5].x))));
                mmax = absmax2(mmax, absmax2(v[5].y, v[5].z)) & 0x7fff7fffu;
                { const float2 mf = __half22float2(*reinterpret_cast<__half2*>(&mmax)); mmax = max(__float_as_uint(mf.x), __float_as_uint(mf.y)); }
            }
            roff += 24576;
        }
        {
            bar_sync(7, 384);
            if (c == 0) flag_inc_if(l16c, &g_flag[F_QKV + (4 * (NBLK - 1) + (h >> 3)) * 8]);
        }
    }
    if (warp == 8) PSTAMP(13);
    cluster_sync();
}

constexpr int NST = 10;
constexpr int G_RING = 0, G_EX = NST * 16384, G_OUT = G_EX + 32768, G_CARRY = G_OUT + 32768, G_OPS = G_CARRY + 512, G_BAR = G_OPS + 256, BG_SMEM = G_BAR + 256;
constexpr int GB_FULL = G_BAR, GB_EMPTY = G_BAR + 8 * NST, GB_W = G_BAR + 16 * NST;
static_assert(BG_SMEM <= 232448, "smem");

template <int ACC>
__device__ __forceinline__ void wgmma_n128_rs(float (&d)[64], uint32_t a0, uint32_t a1, uint32_t a2, uint32_t a3, uint64_t desc) {
    asm volatile("wgmma.mma_async.sync.aligned.m64n128k16.f32.bf16.bf16 "
        "{%0,%1,%2,%3,%4,%5,%6,%7,%8,%9,%10,%11,%12,%13,%14,%15,%16,%17,%18,%19,%20,%21,%22,%23,%24,%25,%26,%27,%28,%29,%30,%31,"
        "%32,%33,%34,%35,%36,%37,%38,%39,%40,%41,%42,%43,%44,%45,%46,%47,%48,%49,%50,%51,%52,%53,%54,%55,%56,%57,%58,%59,%60,%61,%62,%63}, "
        "{%64,%65,%66,%67}, %68, %69, 1, 1, 0;"
        : "+f"(d[0]), "+f"(d[1]), "+f"(d[2]), "+f"(d[3]), "+f"(d[4]), "+f"(d[5]), "+f"(d[6]), "+f"(d[7]),
          "+f"(d[8]), "+f"(d[9]), "+f"(d[10]), "+f"(d[11]), "+f"(d[12]), "+f"(d[13]), "+f"(d[14]), "+f"(d[15]),
          "+f"(d[16]), "+f"(d[17]), "+f"(d[18]), "+f"(d[19]), "+f"(d[20]), "+f"(d[21]), "+f"(d[22]), "+f"(d[23]),
          "+f"(d[24]), "+f"(d[25]), "+f"(d[26]), "+f"(d[27]), "+f"(d[28]), "+f"(d[29]), "+f"(d[30]), "+f"(d[31]),
          "+f"(d[32]), "+f"(d[33]), "+f"(d[34]), "+f"(d[35]), "+f"(d[36]), "+f"(d[37]), "+f"(d[38]), "+f"(d[39]),
          "+f"(d[40]), "+f"(d[41]), "+f"(d[42]), "+f"(d[43]), "+f"(d[44]), "+f"(d[45]), "+f"(d[46]), "+f"(d[47]),
          "+f"(d[48]), "+f"(d[49]), "+f"(d[50]), "+f"(d[51]), "+f"(d[52]), "+f"(d[53]), "+f"(d[54]), "+f"(d[55]),
          "+f"(d[56]), "+f"(d[57]), "+f"(d[58]), "+f"(d[59]), "+f"(d[60]), "+f"(d[61]), "+f"(d[62]), "+f"(d[63])
        : "r"(a0), "r"(a1), "r"(a2), "r"(a3), "l"(desc), "n"(ACC));
}
template <int ACC>
__device__ __forceinline__ void wgmma_n64_rs(float (&d)[64], uint32_t a0, uint32_t a1, uint32_t a2, uint32_t a3, uint64_t desc) {
    asm volatile("wgmma.mma_async.sync.aligned.m64n64k16.f32.bf16.bf16 "
        "{%0,%1,%2,%3,%4,%5,%6,%7,%8,%9,%10,%11,%12,%13,%14,%15,%16,%17,%18,%19,%20,%21,%22,%23,%24,%25,%26,%27,%28,%29,%30,%31}, "
        "{%32,%33,%34,%35}, %36, %37, 1, 1, 0;"
        : "+f"(d[0]), "+f"(d[1]), "+f"(d[2]), "+f"(d[3]), "+f"(d[4]), "+f"(d[5]), "+f"(d[6]), "+f"(d[7]),
          "+f"(d[8]), "+f"(d[9]), "+f"(d[10]), "+f"(d[11]), "+f"(d[12]), "+f"(d[13]), "+f"(d[14]), "+f"(d[15]),
          "+f"(d[16]), "+f"(d[17]), "+f"(d[18]), "+f"(d[19]), "+f"(d[20]), "+f"(d[21]), "+f"(d[22]), "+f"(d[23]),
          "+f"(d[24]), "+f"(d[25]), "+f"(d[26]), "+f"(d[27]), "+f"(d[28]), "+f"(d[29]), "+f"(d[30]), "+f"(d[31])
        : "r"(a0), "r"(a1), "r"(a2), "r"(a3), "l"(desc), "n"(ACC));
}
__device__ __forceinline__ void wait_flag(const unsigned* p, unsigned target) {
    asm volatile("{\n.reg .pred p;\n.reg .u32 n, v;\nmov.u32 n, 0;\n"
                 "W_%=: ld.acquire.gpu.global.u32 v, [%0];\nsub.u32 v, v, %1;\nsetp.ge.s32 p, v, 0;\n@p bra.uni D_%=;\nnanosleep.u32 40;\n"
                 "add.u32 n, n, 1;\nsetp.lt.u32 p, n, 4000000;\n@p bra.uni W_%=;\ntrap;\nD_%=:\n}" :: "l"(p), "r"(target) : "memory");
}
template <int NS, int NT>
__device__ __forceinline__ void bg_mainloop(float (&d)[64], const uint32_t (&a)[144], uint32_t sb, int it, int lane) {
    int slot = it % NST, ph = (it / NST) & 1, prev = 0;
#pragma unroll
    for (int i = 0; i < NS; i++) {
        mbar_wait(sb + GB_FULL + 8 * slot, ph);
        const uint64_t desc = (uint64_t)(((sb + G_RING + slot * 16384) & 0x3FFFF) >> 4) | (1ull << 16) | (64ull << 32) | (1ull << 62);
        wg_fence();
#pragma unroll
        for (int k = 0; k < 512 / NT; k++) {
            const int u = (2048 / NT) * i + 4 * k;
            if (NT == 128) {
                if (i == 0 && k == 0) wgmma_n128_rs<0>(d, a[u], a[u + 1], a[u + 2], a[u + 3], desc);
                else wgmma_n128_rs<1>(d, a[u], a[u + 1], a[u + 2], a[u + 3], desc + 2 * k);
            } else {
                if (i == 0 && k == 0) wgmma_n64_rs<0>(d, a[u], a[u + 1], a[u + 2], a[u + 3], desc);
                else wgmma_n64_rs<1>(d, a[u], a[u + 1], a[u + 2], a[u + 3], desc + 2 * (k & 3) + (k >> 2) * 512);
            }
        }
        wg_commit();
        if (i > 0) {
            asm volatile("wgmma.wait_group.sync.aligned 1;" ::: "memory");
            mbar_arrive_if(lane, sb + GB_EMPTY + 8 * prev);
        }
        prev = slot;
        slot += 2;
        if (slot >= NST) { slot -= NST; ph ^= 1; }
    }
    wg_wait0();
    mbar_arrive_if(lane, sb + GB_EMPTY + 8 * prev);
}
template <bool SKIP, int NT>
__device__ __forceinline__ void bg_epilogue(float (&d)[64], uint32_t sb, int wg, int w, int lane, const CUtensorMap* tm_out, int col0, int tok0,
                                            const __nv_bfloat16* xa, const __nv_bfloat16* Dk) {
    constexpr int H = NT / 4;
    const int g = lane >> 2, t = lane & 3;
    const uint32_t ex = sb + G_EX + w * 4096 + lane * 16;
    float k[H];
    if (wg == 0) {
#pragma unroll
        for (int q = 0; q < H / 4; q++) sts128f(ex + q * 512, d[H + 4 * q], d[H + 4 * q + 1], d[H + 4 * q + 2], d[H + 4 * q + 3]);
#pragma unroll
        for (int i = 0; i < H; i++) k[i] = d[i];
    } else {
#pragma unroll
        for (int q = 0; q < H / 4; q++) sts128f(ex + 16384 + q * 512, d[4 * q], d[4 * q + 1], d[4 * q + 2], d[4 * q + 3]);
#pragma unroll
        for (int i = 0; i < H; i++) k[i] = d[H + i];
    }
    uint32_t xv[16], dv = 0;
    if (SKIP) {
        const __nv_bfloat16* xp = xa + (size_t)(tok0 + 64 * wg + 2 * t) * DM + col0 + 16 * w + 2 * g;
#pragma unroll
        for (int i = 0; i < 16; i++) xv[i] = ldg_nc32(xp + (8 * (i >> 1) + (i & 1)) * DM);
        dv = ldg_nc32(Dk + col0 + 16 * w + 2 * g);
    }
    if (SKIP && w == 0) asm volatile("cp.async.bulk.wait_group.read 0;" ::: "memory");
    bar_sync(1, 256);
#pragma unroll
    for (int q = 0; q < H / 4; q++) {
        const float4 o = lds128f(ex + (wg ^ 1) * 16384 + q * 512);
        k[4 * q] += o.x; k[4 * q + 1] += o.y; k[4 * q + 2] += o.z; k[4 * q + 3] += o.w;
    }
    if (SKIP) bar_sync(1, 256); else bar_sync(13, 288);
    const uint32_t ob = sb + G_OUT + wg * (NT == 128 ? 16384 : 4096) + (w >> 1) * 8192 + (g & 1) * 8;
    const uint32_t ch = (w & 1) * 4 + (g >> 1);
#pragma unroll
    for (int i = 0; i < H / 2; i++) {
        float v0 = k[4 * (i >> 1) + (i & 1)], v1 = k[4 * (i >> 1) + 2 + (i & 1)];
        if (SKIP) {
            const uint32_t p = pack_bf16(__uint_as_float(xv[i] << 16) * __uint_as_float(dv << 16), __uint_as_float(xv[i] & 0xffff0000u) * __uint_as_float(dv & 0xffff0000u));
            v0 += __uint_as_float(p << 16); v1 += __uint_as_float(p & 0xffff0000u);
        }
        const uint32_t n7 = 2 * t + (i & 1);
        sts64(ob + (8 * (i >> 1) + n7) * 128 + ((ch ^ n7) << 4), __float_as_uint(v0), __float_as_uint(v1));
    }
    fence_async_smem();
    if (SKIP) {
        bar_sync(4 + wg, 128);
        if (w == 0)
            asm volatile("{\n.reg .pred p;\nelect.sync _|p, 0xffffffff;\n"
                "@p cp.async.bulk.tensor.2d.global.shared::cta.bulk_group [%0, {%2, %4}], [%1];\n"
                "@p cp.async.bulk.tensor.2d.global.shared::cta.bulk_group [%0, {%3, %4}], [%1+8192];\n@p cp.async.bulk.commit_group;\n}"
                :: "l"(tm_out), "r"(sb + G_OUT + wg * 16384), "r"(col0), "r"(col0 + 32), "r"(tok0 + 64 * wg) : "memory");
    } else {
        bar_arrive(12, 288);
    }
}
__device__ __forceinline__ void s5_channel(int p, const __nv_bfloat16* Lre, const __nv_bfloat16* Lim, const __nv_bfloat16* logdt, float2& lam, float2& coef) {
    const float dt = __bfloat162float(__float2bfloat16(expf(__bfloat162float(logdt[p]))));
    const float lr = __bfloat162float(Lre[p]), li = __bfloat162float(Lim[p]);
    const float e = expf(dt * lr);
    float sn, cs;
    sincosf(dt * li, &sn, &cs);
    lam = make_float2(e * cs, e * sn);
    const float den = lr * lr + li * li;
    coef = make_float2(((lam.x - 1.f) * lr + lam.y * li) / den, (lam.y * lr - (lam.x - 1.f) * li) / den);
}
__device__ __forceinline__ float2 cfma(float2 a, float2 b, float2 c) {
    return make_float2(fmaf(a.x, b.x, fmaf(-a.y, b.y, c.x)), fmaf(a.x, b.y, fmaf(a.y, b.x, c.y)));
}
__device__ __forceinline__ uint4 ldg128(const void* p) { uint4 v; asm volatile("ld.global.v4.u32 {%0,%1,%2,%3}, [%4];" : "=r"(v.x), "=r"(v.y), "=r"(v.z), "=r"(v.w) : "l"(p) : "memory"); return v; }
__device__ __forceinline__ uint2 ldg64(const void* p) { uint2 v; asm volatile("ld.global.v2.u32 {%0,%1}, [%2];" : "=r"(v.x), "=r"(v.y) : "l"(p) : "memory"); return v; }

template <int MT>
__device__ __forceinline__ void bg_attention(uint32_t st0, uint32_t st1, int lane) {
    constexpr int NK = MT ? 5 : 3;
    const int g = lane >> 2, t = lane & 3;
    float sc[NK][4], sm2[4];
#pragma unroll
    for (int i = 0; i < 8; i++) {
        const uint32_t st = (i >> 2 ? st1 : st0) + (i & 3) * 512 + lane * 16;
        const uint4 q = ldsm4(st + MT * 2048), km = ldsm4(st + 8192), k0 = ldsm4(st + 4096);
        if (i == 0) {
            mma16816_z(sc[0], q.x, q.y, q.z, q.w, km.x, km.y); mma16816_z(sm2, q.x, q.y, q.z, q.w, km.z, km.w);
            mma16816_z(sc[1], q.x, q.y, q.z, q.w, k0.x, k0.y); mma16816_z(sc[2], q.x, q.y, q.z, q.w, k0.z, k0.w);
        } else {
            mma16816(sc[0], q.x, q.y, q.z, q.w, km.x, km.y); mma16816(sm2, q.x, q.y, q.z, q.w, km.z, km.w);
            mma16816(sc[1], q.x, q.y, q.z, q.w, k0.x, k0.y); mma16816(sc[2], q.x, q.y, q.z, q.w, k0.z, k0.w);
        }
        if (MT) {
            const uint4 k1 = ldsm4(st + 6144);
            if (i == 0) { mma16816_z(sc[NK - 2], q.x, q.y, q.z, q.w, k1.x, k1.y); mma16816_z(sc[NK - 1], q.x, q.y, q.z, q.w, k1.z, k1.w); }
            else { mma16816(sc[NK - 2], q.x, q.y, q.z, q.w, k1.x, k1.y); mma16816(sc[NK - 1], q.x, q.y, q.z, q.w, k1.z, k1.w); }
        }
    }
#pragma unroll
    for (int i = 0; i < 4; i++) sc[0][i] += sm2[i];
    if (2 * t > g) { sc[NK - 2][0] = -INFINITY; sc[NK - 1][2] = -INFINITY; }
    if (2 * t + 1 > g) { sc[NK - 2][1] = -INFINITY; sc[NK - 1][3] = -INFINITY; }
    sc[NK - 1][0] = sc[NK - 1][1] = -INFINITY;
    float ma = fmaxf(sc[0][0], sc[0][1]), mb = fmaxf(sc[0][2], sc[0][3]);
#pragma unroll
    for (int n = 1; n < NK; n++) { ma = fmaxf(ma, fmaxf(sc[n][0], sc[n][1])); mb = fmaxf(mb, fmaxf(sc[n][2], sc[n][3])); }
    ma = quad_max(ma) * SM_SCALE; mb = quad_max(mb) * SM_SCALE;
    uint32_t Pa[NK], Pb[NK];
#pragma unroll
    for (int n = 0; n < NK; n++) {
        Pa[n] = n == NK - 1 ? 0u : pack_bf16(ex2(fmaf(sc[n][0], SM_SCALE, -ma)), ex2(fmaf(sc[n][1], SM_SCALE, -ma)));
        Pb[n] = pack_bf16(ex2(fmaf(sc[n][2], SM_SCALE, -mb)), ex2(fmaf(sc[n][3], SM_SCALE, -mb)));
    }
    float sa[4], sbb[4];
    mma1688_z(sa, ONES, ONES, Pa[0]); mma1688_z(sbb, ONES, ONES, Pb[0]);
    mma16816(sa, ONES, ONES, ONES, ONES, Pa[1], Pa[2]); mma16816(sbb, ONES, ONES, ONES, ONES, Pb[1], Pb[2]);
    if (MT) { mma16816(sa, ONES, ONES, ONES, ONES, Pa[NK - 2], Pa[NK - 1]); mma16816(sbb, ONES, ONES, ONES, ONES, Pb[NK - 2], Pb[NK - 1]); }
    const float ra0 = rcp_fast(sa[0]), ra1 = rcp_fast(sa[1]), rb0 = rcp_fast(sbb[0]), rb1 = rcp_fast(sbb[1]);
    const uint32_t row = lane & 7;
    const uint32_t so = MT * 2048 + (lane >> 4) * 1024 + row * 128;
#pragma unroll
    for (int eh = 0; eh < 2; eh++) {
        const uint32_t st = eh ? st1 : st0;
        float2 vm[4]; uint4 v0[4], v1[4];
#pragma unroll
        for (int e4 = 0; e4 < 4; e4++) {
            vm[e4] = lds64f(st + 14336 + e4 * 256 + lane * 8);
            v0[e4] = lds128(st + 10240 + e4 * 1024 + lane * 16);
            if (MT) v1[e4] = lds128(st + 10240 + e4 * 1024 + 512 + lane * 16);
        }
        float oa[4][4], ob[4][4];
#pragma unroll
        for (int e4 = 0; e4 < 4; e4++) {
            mma1688_z(oa[e4], __float_as_uint(vm[e4].x), __float_as_uint(vm[e4].y), Pa[0]);
            mma1688_z(ob[e4], __float_as_uint(vm[e4].x), __float_as_uint(vm[e4].y), Pb[0]);
        }
#pragma unroll
        for (int e4 = 0; e4 < 4; e4++) {
            mma16816(oa[e4], v0[e4].x, v0[e4].y, v0[e4].z, v0[e4].w, Pa[1], Pa[2]);
            mma16816(ob[e4], v0[e4].x, v0[e4].y, v0[e4].z, v0[e4].w, Pb[1], Pb[2]);
        }
        if (MT) {
#pragma unroll
            for (int e4 = 0; e4 < 4; e4++) {
                mma16816(oa[e4], v1[e4].x, v1[e4].y, v1[e4].z, v1[e4].w, Pa[NK - 2], Pa[NK - 1]);
                mma16816(ob[e4], v1[e4].x, v1[e4].y, v1[e4].z, v1[e4].w, Pb[NK - 2], Pb[NK - 1]);
            }
        }
#pragma unroll
        for (int e4 = 0; e4 < 4; e4++)
            stsm4t(st + so + (((2 * e4 + ((lane >> 3) & 1)) ^ row) << 4), pack_bf16(oa[e4][0] * ra0, oa[e4][1] * ra1), pack_bf16(oa[e4][2] * ra0, oa[e4][3] * ra1),
                   pack_bf16(ob[e4][0] * rb0, ob[e4][1] * rb1), pack_bf16(ob[e4][2] * rb0, ob[e4][3] * rb1));
    }
}
__device__ __forceinline__ bool wait_either(const unsigned* pa, unsigned ta, bool allow_a, const unsigned* pg, unsigned tg, bool allow_g) {
    uint32_t res;
    asm volatile("{\n.reg .pred p, qa, qg;\n.reg .u32 n, v, u;\nmov.u32 n, 0;\nsetp.ne.u32 qa, %5, 0;\nsetp.ne.u32 qg, %6, 0;\n"
                 "W_%=: ld.relaxed.gpu.global.u32 v, [%1];\nld.relaxed.gpu.global.u32 u, [%3];\nsub.u32 v, v, %2;\nsub.u32 u, u, %4;\n"
                 "mov.u32 %0, 1;\nsetp.ge.and.s32 p, v, 0, qa;\n@p bra.uni D_%=;\nmov.u32 %0, 0;\nsetp.ge.and.s32 p, u, 0, qg;\n@p bra.uni D_%=;\n"
                 "nanosleep.u32 40;\nadd.u32 n, n, 1;\nsetp.lt.u32 p, n, 4000000;\n@p bra.uni W_%=;\ntrap;\n"
                 "D_%=: fence.acq_rel.gpu;\nfence.proxy.async.global;\n}"
                 : "=r"(res) : "l"(pa), "r"(ta), "l"(pg), "r"(tg), "r"((uint32_t)allow_a), "r"((uint32_t)allow_g) : "memory");
    return res != 0;
}

__global__ void __launch_bounds__(384, 1)
bg_kernel(const __grid_constant__ CUtensorMap tm_xa, const __grid_constant__ CUtensorMap tm_wo, const __grid_constant__ CUtensorMap tm_out,
          const __nv_bfloat16* __restrict__ xa, const __nv_bfloat16* __restrict__ Lre, const __nv_bfloat16* __restrict__ Lim,
          const __nv_bfloat16* __restrict__ Bre, const __nv_bfloat16* __restrict__ Bim, const __nv_bfloat16* __restrict__ Cre,
          const __nv_bfloat16* __restrict__ Cim, const __nv_bfloat16* __restrict__ logdt, const __nv_bfloat16* __restrict__ Dk, float* __restrict__ out) {
    extern __shared__ __align__(1024) uint8_t smem_raw[];
    const uint32_t sb = smem_u32(smem_raw);
    const int lane = threadIdx.x & 31;
    const int warp = __shfl_sync(~0u, threadIdx.x >> 5, 0);
    const int wg = warp >> 2, w = warp & 3, b = blockIdx.x;
    const int nt = b % 9, kq = b / 9;
    BSTAMP(0);
    if (threadIdx.x == 0) {
        if (sb & 1023u) __trap();
        for (int i = 0; i < NST; i++) { mbar_init(sb + GB_FULL + 8 * i, 1); mbar_init(sb + GB_EMPTY + 8 * i, 4); }
        mbar_init(sb + GB_W, 1);
        asm volatile("fence.mbarrier_init.release.cluster;" ::: "memory");
        mbar_expect(sb + GB_W, (b < 18 ? 64 : 128) * 1152);
        sts32(sb + G_BAR + 248, atomicAdd(&g_ticket_bg, 1u) / 36u + 1u);
    }
    __syncthreads();
    if (wg == 2) {
        asm volatile("setmaxnreg.dec.sync.aligned.u32 24;");
        if (w == 0) {
            int slot = 0, ph = 1;
            auto next = [&]() { if (++slot == NST) { slot = 0; ph ^= 1; } };
            bar_sync(6, 288);
            if (b < 18) {
#pragma unroll 1
                for (int i = 0; i < 144; i++) {
                    const int blk = i / 9, kb = i - 9 * blk, it = (blk >> 1) * 18 + (blk & 1) + 2 * kb;
                    slot = it % NST;
                    mbar_wait(sb + GB_EMPTY + 8 * slot, ((it / NST) & 1) ^ 1);
                    asm volatile("{\n.reg .pred p;\nelect.sync _|p, 0xffffffff;\n@p mbarrier.arrive.expect_tx.shared::cta.b64 _, [%2], 16384;\n"
                        "@p cp.async.bulk.tensor.5d.shared::cluster.global.mbarrier::complete_tx::bytes [%0], [%1, {%3, %4, %4, %4, %5}], [%2];\n}"
                        :: "r"(sb + G_RING + slot * 16384), "l"(&tm_xa), "r"(sb + GB_FULL + 8 * slot), "r"(kb * 64), "r"(0), "r"(blk) : "memory");
                }
                slot = 144 % NST; ph = ((144 / NST) & 1) ^ 1;
            }
            const unsigned ep = lds32(sb + G_BAR + 248);
            auto slabs = [&](const char* src, int ns) {
                asm volatile("fence.proxy.async.global;" ::: "memory");
#pragma unroll 1
                for (int i = 0; i < ns; i++) {
                    mbar_wait(sb + GB_EMPTY + 8 * slot, ph);
                    asm volatile("{\n.reg .pred p;\nelect.sync _|p, 0xffffffff;\n@p mbarrier.arrive.expect_tx.shared::cta.b64 _, [%2], 16384;\n"
                        "@p cp.async.bulk.shared::cluster.global.mbarrier::complete_tx::bytes [%0], [%1], 16384, [%2];\n}"
                        :: "r"(sb + G_RING + slot * 16384), "l"(src + (size_t)((i & 1) * (ns >> 1) + (i >> 1)) * (SEQ * 128)), "r"(sb + GB_FULL + 8 * slot) : "memory");
                    next();
                }
            };
            if (b >= 18) {
#pragma unroll 1
                for (int blk = kq - 2; blk < 16; blk += 2) {
                    wait_flag(&g_flag[F_H + blk * 8], 18 * ep);
                    slabs(reinterpret_cast<const char*>(g_h) + blk * 16384, 18);
                }
            }
            bar_sync(6, 288);
#pragma unroll 1
            for (int na = nt < 8 ? 0 : NBLK, ng = 0, k = 0; ng < NBLK; k++) {
                const bool att = wait_either(&g_flag[F_QKV + (min(na, NBLK - 1) * 4 + kq) * 8], 24 * ep, na < NBLK && na <= ng + 1,
                                             &g_flag[F_OX + (ng * 4 + kq) * 8], 8 * ep, ng < na);
                sts32_if(lane, sb + G_OPS + 4 * k, att);
                __syncwarp();
                if (att) {
                    {
#pragma unroll 1
                        for (int i = 0; i < (na < NBIG ? 8 : 4); i++) {
                            const int hf = (i >> 1) & 1;
                            const char* rec = reinterpret_cast<const char*>(g_qkv) + (size_t)((blk_seg0(na) + 2 * (i >> 2) + (i & 1)) * NH + 8 * kq + nt) * REC;
                            mbar_wait(sb + GB_EMPTY + 8 * slot, ph);
                            asm volatile("{\n.reg .pred p;\nelect.sync _|p, 0xffffffff;\n@p mbarrier.arrive.expect_tx.shared::cta.b64 _, [%4], 15360;\n"
                                "@p cp.async.bulk.shared::cluster.global.mbarrier::complete_tx::bytes [%0], [%1], 10240, [%4];\n"
                                "@p cp.async.bulk.shared::cluster.global.mbarrier::complete_tx::bytes [%0+10240], [%2], 4096, [%4];\n"
                                "@p cp.async.bulk.shared::cluster.global.mbarrier::complete_tx::bytes [%0+14336], [%3], 1024, [%4];\n}"
                                :: "r"(sb + G_RING + slot * 16384), "l"(rec + hf * 10240), "l"(rec + 20480 + hf * 4096), "l"(rec + 28672 + hf * 1024),
                                   "r"(sb + GB_FULL + 8 * slot) : "memory");
                            next();
                        }
                    }
                    na++;
                } else {
                    const char* src = reinterpret_cast<const char*>(g_ox) + (size_t)kq * 16 * SEQ * 128 + blk_seg0(ng) * 4096;
                    if (ng < NBIG) slabs(src, 16);
                    else {
#pragma unroll 1
                        for (int i = 0; i < 8; i++) {
                            mbar_wait(sb + GB_EMPTY + 8 * slot, ph);
                            asm volatile("{\n.reg .pred p;\nelect.sync _|p, 0xffffffff;\n@p mbarrier.arrive.expect_tx.shared::cta.b64 _, [%2], 16384;\n"
                                "@p cp.async.bulk.shared::cluster.global.mbarrier::complete_tx::bytes [%0], [%1], 8192, [%2];\n"
                                "@p cp.async.bulk.shared::cluster.global.mbarrier::complete_tx::bytes [%0+8192], [%1+262144], 8192, [%2];\n}"
                                :: "r"(sb + G_RING + slot * 16384), "l"(src + (size_t)((i & 1) * 8 + (i & 6)) * (SEQ * 128)), "r"(sb + GB_FULL + 8 * slot) : "memory");
                            next();
                        }
                    }
                    ng++;
                }
            }
        } else if (w == 1) {
            if (b < 18) {
#pragma unroll 1
                for (int blk = 0; blk < 16; blk++) {
                    bar_sync(8 + (blk & 1), 160);
                    asm volatile("{\n.reg .pred p;\nelect.sync _|p, 0xffffffff;\n@p cp.async.bulk.global.shared::cta.bulk_group [%0], [%1], 16384;\n"
                        "@p cp.async.bulk.commit_group;\ncp.async.bulk.wait_group 0;\nfence.proxy.async.global;\n}"
                        :: "l"(reinterpret_cast<char*>(g_h) + ((size_t)b * SEQ + blk * 128) * 128), "r"(sb + G_OUT + (blk & 1) * 16384) : "memory");
                    bar_arrive(10 + (blk & 1), 160);
                    flag_inc_if(lane, &g_flag[F_H + blk * 8]);
                }
            }
            if (nt < 8) {
#pragma unroll 1
                for (int na = 0; na < NBLK; na++) {
                    {
                        const int ns = na < NBIG ? 8 : 4;
                        bar_sync(7, 288);
                        const int it = lds32(sb + G_OPS + 252);
                        if (lane < ns) {
                            asm volatile("cp.async.bulk.global.shared::cta.bulk_group [%0], [%1], 4096;\ncp.async.bulk.commit_group;\ncp.async.bulk.wait_group.read 0;\n"
                                "mbarrier.arrive.shared::cta.b64 _, [%2], 4;\ncp.async.bulk.wait_group 0;\nfence.proxy.async.global;"
                                :: "l"(reinterpret_cast<char*>(g_ox) + ((size_t)((8 * kq + nt) * 2 + ((lane >> 1) & 1)) * SEQ + (blk_seg0(na) + 2 * (lane >> 2) + (lane & 1)) * 32) * 128),
                                   "r"(sb + G_RING + ((it + lane) % NST) * 16384), "r"(sb + GB_EMPTY + 8 * ((it + lane) % NST)) : "memory");
                        }
                        __syncwarp();
                        bar_arrive(14, 288);
                        flag_inc_if(lane, &g_flag[F_OX + (na * 4 + kq) * 8]);
                    }
                }
            }
        } else if (w == 2) {
            const unsigned ep = lds32(sb + G_BAR + 248);
#pragma unroll 1
            for (int blk = 0; blk < NBLK; blk++) {
                const bool last = blk == NBLK - 1, add = kq || last;
                bar_arrive(13, 288);
                bar_sync(12, 288);
                if (add) { wait_flag(&g_flag[F_OUT + (blk * 9 + nt) * 8], ep); asm volatile("fence.proxy.async.global;" ::: "memory"); }
#pragma unroll 1
                for (int i = 0; i < (blk < NBIG ? 4 : 2); i++) {
                    const uint32_t src = sb + G_OUT + i * 8192;
                    const int c0 = DM + 64 * nt + (i & 1) * 32, c1 = blk_seg0(blk) * 32 + (i >> 1) * 64;
                    if (add) asm volatile("{\n.reg .pred p;\nelect.sync _|p, 0xffffffff;\n@p cp.reduce.async.bulk.tensor.2d.global.shared::cta.add.bulk_group [%0, {%2, %3}], [%1];\n}"
                                 :: "l"(&tm_out), "r"(src), "r"(c0), "r"(c1) : "memory");
                    else asm volatile("{\n.reg .pred p;\nelect.sync _|p, 0xffffffff;\n@p cp.async.bulk.tensor.2d.global.shared::cta.bulk_group [%0, {%2, %3}], [%1];\n}"
                                 :: "l"(&tm_out), "r"(src), "r"(c0), "r"(c1) : "memory");
                    if (add && blk < NBLK - 2) spin_until(clk(), RED_GAP);
                }
                asm volatile("cp.async.bulk.commit_group;\ncp.async.bulk.wait_group 0;\nfence.proxy.async.global;" ::: "memory");
                __syncwarp();
                if (!add) flag_inc_if(lane, &g_flag[F_OUT + (blk * 9 + nt) * 8]);
                if (!kq && blk == NBLK - 4) {
                    float4* z = reinterpret_cast<float4*>(out + (size_t)(SEQ - 64 + (lane >> 4)) * (2 * DM) + DM + 64 * nt) + (lane & 15);
#pragma unroll 1
                    for (int i = 0; i < 32; i++) z[i * (4 * DM / 4)] = make_float4(0.f, 0.f, 0.f, 0.f);
                    __syncwarp();
                    flag_inc_if(lane, &g_flag[F_OUT + ((NBLK - 1) * 9 + nt) * 8]);
                }
            }
        }
    } else {
        asm volatile("setmaxnreg.inc.sync.aligned.u32 240;");
        const int g = lane >> 2, t = lane & 3, tid = threadIdx.x;
        uint32_t a[144];
        float d[64];
        if (b < 18) {
            if (tid < 64)
                asm volatile("cp.async.bulk.shared::cluster.global.mbarrier::complete_tx::bytes [%0], [%1], 1152, [%2];"
                    :: "r"(sb + tid * 1168), "l"((tid < 32 ? Bre : Bim) + (size_t)(32 * b + (tid & 31)) * DM), "r"(sb + GB_W) : "memory");
            float2 lam, coef;
            s5_channel(32 * b + 8 * w + g, Lre, Lim, logdt, lam, coef);
            float2 l32 = lam;
#pragma unroll
            for (int i = 0; i < 5; i++) l32 = make_float2(l32.x * l32.x - l32.y * l32.y, 2.f * l32.x * l32.y);
            __syncwarp();
            mbar_wait(sb + GB_W, 0);
            const uint32_t ap = sb + (((lane >> 3) & 1) * 32 + 8 * w + (lane & 7)) * 1168 + (lane >> 4) * 16;
#pragma unroll
            for (int ks = 0; ks < 36; ks++) { const uint4 v = ldsm4(ap + ks * 32); a[4 * ks] = v.x; a[4 * ks + 1] = v.y; a[4 * ks + 2] = v.z; a[4 * ks + 3] = v.w; }
            bar_sync(1, 256);
            bar_arrive(6, 288);
            BSTAMP(1);
#pragma unroll 1
            for (int blk = wg; blk < 16; blk += 2) {
                bg_mainloop<9, 128>(d, a, sb, (blk >> 1) * 18 + wg, lane);
                float2 e = make_float2(0.f, 0.f);
#pragma unroll
                for (int i = 0; i < 32; i++) e = cfma(lam, e, make_float2(d[4 * (i >> 1) + (i & 1)], d[4 * (i >> 1) + 2 + (i & 1)]));
                float2 cin = make_float2(0.f, 0.f);
                if (blk > 0) { bar_sync(2 + (wg ^ 1), 256); cin = lds64f(sb + G_CARRY + (wg ^ 1) * 256 + (8 * w + g) * 8); }
                float2 mine = cin;
#pragma unroll
                for (int q = 0; q < 4; q++) {
                    const float2 eq = make_float2(__shfl_sync(~0u, e.x, (lane & 28) + q), __shfl_sync(~0u, e.y, (lane & 28) + q));
                    cin = cfma(l32, cin, eq);
                    if (t == q + 1) mine = cin;
                }
                if (blk < 15) {
                    if (t == 0) sts64(sb + G_CARRY + wg * 256 + (8 * w + g) * 8, __float_as_uint(cin.x), __float_as_uint(cin.y));
                    bar_arrive(2 + wg, 256);
                }
                const uint32_t hs = sb + G_OUT + wg * 16384 + t * 4096 + (g & 3) * 4;
                const uint32_t ch = 2 * w + (g >> 2);
                if (blk >= 2) bar_sync(10 + wg, 160);
#pragma unroll
                for (int i = 0; i < 32; i++) {
                    mine = cfma(lam, mine, make_float2(d[4 * (i >> 1) + (i & 1)], d[4 * (i >> 1) + 2 + (i & 1)]));
                    sts32(hs + i * 128 + ((ch ^ (i & 7)) << 4), pack_bf16(mine.x, mine.y));
                }
                fence_async_smem();
                bar_arrive(8 + wg, 160);
            }
            bar_sync(10 + wg, 160);
        } else {
            if (tid < 128)
                asm volatile("cp.async.bulk.shared::cluster.global.mbarrier::complete_tx::bytes [%0], [%1], 1152, [%2];"
                    :: "r"(sb + tid * 1168), "l"((tid < 64 ? Cre : Cim) + (size_t)(64 * nt + (tid & 63)) * DM), "r"(sb + GB_W) : "memory");
            for (int p = tid; p < DM; p += 256) {
                float2 lam, coef;
                s5_channel(p, Lre, Lim, logdt, lam, coef);
                sts64(sb + G_EX + p * 8, __float_as_uint(2.f * coef.x), __float_as_uint(2.f * coef.y));
            }
            bar_sync(1, 256);
            mbar_wait(sb + GB_W, 0);
            const uint32_t cp = sb + (16 * w + 2 * g) * 1168 + (288 * wg + t) * 2;
#pragma unroll
            for (int u = 0; u < 72; u++) {
                const float2 c2 = lds64f(sb + G_EX + (288 * wg + 4 * u + t) * 8);
#pragma unroll
                for (int f = 0; f < 2; f++) {
                    unsigned short r16, i16;
                    asm volatile("ld.shared.u16 %0, [%1];" : "=h"(r16) : "r"(cp + f * 1168 + u * 8) : "memory");
                    asm volatile("ld.shared.u16 %0, [%1];" : "=h"(i16) : "r"(cp + (64 + f) * 1168 + u * 8) : "memory");
                    const float cr = __uint_as_float((uint32_t)r16 << 16), ci = __uint_as_float((uint32_t)i16 << 16);
                    a[2 * u + f] = pack_bf16(cr * c2.x - ci * c2.y, -(cr * c2.y + ci * c2.x));
                }
            }
            bar_sync(1, 256);
            bar_arrive(6, 288);
            BSTAMP(1);
#pragma unroll 1
            for (int j = 0; j < 8; j++) {
                bg_mainloop<9, 128>(d, a, sb, j * 18 + wg, lane);
                bg_epilogue<true, 128>(d, sb, wg, w, lane, &tm_out, 64 * nt, (2 * j + kq - 2) * 128, xa, Dk);
            }
        }
        if (w == 0) asm volatile("cp.async.bulk.wait_group 0;" ::: "memory");
        bar_sync(1, 256);
        BSTAMP(2);
        if (warp == 0)
            asm volatile("{\n.reg .pred p;\nelect.sync _|p, 0xffffffff;\n@p mbarrier.arrive.expect_tx.shared::cta.b64 _, [%2], 131072;\n"
                "@p cp.async.bulk.tensor.2d.shared::cluster.global.mbarrier::complete_tx::bytes [%0], [%1, {%3, %4}], [%2];\n"
                "@p cp.async.bulk.tensor.2d.shared::cluster.global.mbarrier::complete_tx::bytes [%0+32768], [%1, {%3, %5}], [%2];\n"
                "@p cp.async.bulk.tensor.2d.shared::cluster.global.mbarrier::complete_tx::bytes [%0+65536], [%1, {%3, %6}], [%2];\n"
                "@p cp.async.bulk.tensor.2d.shared::cluster.global.mbarrier::complete_tx::bytes [%0+98304], [%1, {%3, %7}], [%2];\n}"
                :: "r"(sb), "l"(&tm_wo), "r"(sb + GB_W), "r"(64 * nt), "r"(1024 * kq), "r"(1024 * kq + 256), "r"(1024 * kq + 512), "r"(1024 * kq + 768) : "memory");
        mbar_wait(sb + GB_W, 1);
        {
            const uint32_t base = sb + wg * 65536 + 4 * t * 128 + (g & 3) * 4, ch = 2 * w + (g >> 2), r7 = (4 * t) & 7;
#pragma unroll
            for (int ks = 0; ks < 32; ks++) {
                const uint32_t w0 = lds32(base + ks * 2048 + ((ch ^ r7) << 4)), w1 = lds32(base + ks * 2048 + 256 + ((ch ^ (r7 + 2)) << 4));
                const uint32_t w2 = lds32(base + ks * 2048 + 128 + ((ch ^ (r7 + 1)) << 4)), w3 = lds32(base + ks * 2048 + 384 + ((ch ^ (r7 + 3)) << 4));
                a[4 * ks] = __byte_perm(w0, w1, 0x5410); a[4 * ks + 1] = __byte_perm(w0, w1, 0x7632);
                a[4 * ks + 2] = __byte_perm(w2, w3, 0x5410); a[4 * ks + 3] = __byte_perm(w2, w3, 0x7632);
            }
        }
        bar_sync(1, 256);
        bar_arrive(6, 288);
        BSTAMP(3);
#pragma unroll 1
        for (int na = 0, ng = 0, it = 144, k = 0; ng < NBLK; k++) {
            mbar_wait(sb + GB_FULL + 8 * ((it + wg) % NST), ((it + wg) / NST) & 1);
            if (lds32(sb + G_OPS + 4 * k)) {
                {
                    if (na < NBIG || (w >> 1) == wg) {
                        const int i0 = it + wg + (na < NBIG ? 4 * (w >> 1) : 0), i1 = i0 + 2;
                        mbar_wait(sb + GB_FULL + 8 * (i0 % NST), (i0 / NST) & 1);
                        mbar_wait(sb + GB_FULL + 8 * (i1 % NST), (i1 / NST) & 1);
                        BSTAMP(8 + na * 4);
                        if ((w ^ wg) & 1) bg_attention<1>(sb + G_RING + (i0 % NST) * 16384, sb + G_RING + (i1 % NST) * 16384, lane);
                        else bg_attention<0>(sb + G_RING + (i0 % NST) * 16384, sb + G_RING + (i1 % NST) * 16384, lane);
                        fence_async_smem();
                    }
                    if (na > 0) bar_sync(14, 288);
                    if (tid == 0) sts32(sb + G_OPS + 252, it);
                    bar_arrive(7, 288);
                    bar_sync(1, 256);
                    BSTAMP(9 + na * 4);
                    it += na < NBIG ? 8 : 4;
                }
                na++;
            } else if (ng < NBIG) {
                bg_mainloop<8, 128>(d, a, sb, it + wg, lane);
                BSTAMP(10 + ng * 4);
                bg_epilogue<false, 128>(d, sb, wg, w, lane, &tm_out, 0, 0, xa, Dk);
                BSTAMP(11 + ng * 4);
                it += 16; ng++;
            } else {
                bg_mainloop<4, 64>(d, a, sb, it + wg, lane);
                BSTAMP(10 + ng * 4);
                bg_epilogue<false, 64>(d, sb, wg, w, lane, &tm_out, 0, 0, xa, Dk);
                BSTAMP(11 + ng * 4);
                it += 8; ng++;
            }
        }
        if (nt < 8) bar_sync(14, 288);
    }
    asm volatile("griddepcontrol.wait;" ::: "memory");
}

typedef CUresult (*EncodeFn)(CUtensorMap*, CUtensorMapDataType, cuuint32_t, void*, const cuuint64_t*, const cuuint64_t*, const cuuint32_t*, const cuuint32_t*,
                             CUtensorMapInterleave, CUtensorMapSwizzle, CUtensorMapL2promotion, CUtensorMapFloatOOBfill);
}

extern "C" void kernel_launch(void* const* d_in, const int* in_sizes, int n_in, void* d_out, int out_size) {
    typedef const __nv_bfloat16* bp;
    bp Ax = (bp)d_in[0], Lre = (bp)d_in[1], Lim = (bp)d_in[2], Bre = (bp)d_in[3], Bim = (bp)d_in[4], Cre = (bp)d_in[5], Cim = (bp)d_in[6],
       logdt = (bp)d_in[7], Dk = (bp)d_in[8], Bx = (bp)d_in[9], mem0 = (bp)d_in[10], Wq = (bp)d_in[11], Wk = (bp)d_in[12], Wv = (bp)d_in[13], Wo = (bp)d_in[14];
    float* out = (float*)d_out;
    static EncodeFn enc = nullptr;
    if (!enc) {
        void* fn = nullptr; cudaDriverEntryPointQueryResult qr;
        cudaGetDriverEntryPoint("cuTensorMapEncodeTiled", &fn, cudaEnableDefault, &qr);
        enc = (EncodeFn)fn;
        cudaFuncSetAttribute(chain_kernel, cudaFuncAttributeMaxDynamicSharedMemorySize, CHAIN_SMEM);
        cudaFuncSetAttribute(bg_kernel, cudaFuncAttributeMaxDynamicSharedMemorySize, BG_SMEM);
    }
    const cuuint32_t es[5] = {1, 1, 1, 1, 1};
    auto map2d = [&](CUtensorMap* tm, CUtensorMapDataType dt, const void* p, cuuint64_t d0, cuuint64_t d1, cuuint64_t stride, cuuint32_t b0, cuuint32_t b1) {
        cuuint64_t gd[2] = {d0, d1}, gs[1] = {stride}; cuuint32_t bd[2] = {b0, b1};
        enc(tm, dt, 2, (void*)p, gd, gs, bd, es, CU_TENSOR_MAP_INTERLEAVE_NONE, CU_TENSOR_MAP_SWIZZLE_128B, CU_TENSOR_MAP_L2_PROMOTION_L2_128B,
            CU_TENSOR_MAP_FLOAT_OOB_FILL_NONE);
    };
    CUtensorMap tm_x, tm_q, tm_k, tm_v, tm_xa, tm_wo, tm_out;
    map2d(&tm_x, CU_TENSOR_MAP_DATA_TYPE_BFLOAT16, Bx, DM, SEQ, DM * 2, 64, 32);
    map2d(&tm_q, CU_TENSOR_MAP_DATA_TYPE_BFLOAT16, Wq, HD, DM, HD * 2, 64, 192);
    map2d(&tm_k, CU_TENSOR_MAP_DATA_TYPE_BFLOAT16, Wk, HD, DM, HD * 2, 64, 192);
    map2d(&tm_v, CU_TENSOR_MAP_DATA_TYPE_BFLOAT16, Wv, HD, DM, HD * 2, 64, 192);
    map2d(&tm_wo, CU_TENSOR_MAP_DATA_TYPE_BFLOAT16, Wo, DM, HD, DM * 2, 64, 256);
    map2d(&tm_out, CU_TENSOR_MAP_DATA_TYPE_FLOAT32, out, 2 * DM, SEQ, 2 * DM * 4, 32, 64);
    {
        cuuint64_t gd[5] = {DM, 2, 4, 16, 16}, gs[4] = {DM * 2, 32 * DM * 2, 2 * DM * 2, 128 * DM * 2}; cuuint32_t bd[5] = {64, 2, 4, 16, 1};
        enc(&tm_xa, CU_TENSOR_MAP_DATA_TYPE_BFLOAT16, 5, (void*)Ax, gd, gs, bd, es, CU_TENSOR_MAP_INTERLEAVE_NONE, CU_TENSOR_MAP_SWIZZLE_128B,
            CU_TENSOR_MAP_L2_PROMOTION_L2_128B, CU_TENSOR_MAP_FLOAT_OOB_FILL_NONE);
    }
    cudaStream_t st = cudaStreamPerThread;
    chain_kernel<<<96, 384, CHAIN_SMEM, st>>>(tm_x, tm_q, tm_k, tm_v, Bx, mem0, Wo);
    cudaLaunchConfig_t cfg = {};
    cfg.gridDim = dim3(36); cfg.blockDim = dim3(384); cfg.dynamicSmemBytes = BG_SMEM; cfg.stream = st;
    cudaLaunchAttribute at[1];
    at[0].id = cudaLaunchAttributeProgrammaticStreamSerialization; at[0].val.programmaticStreamSerializationAllowed = 1;
    cfg.attrs = at; cfg.numAttrs = 1;
    cudaLaunchKernelEx(&cfg, bg_kernel, tm_xa, tm_wo, tm_out, Ax, Lre, Lim, Bre, Bim, Cre, Cim, logdt, Dk, out);
}
```

```cpp
#include <cuda_runtime.h>
#include <cuda.h>
#include <cuda_bf16.h>
#include <cuda_fp16.h>
#include <stdint.h>

#define D_WAIT 740

#define RED_GAP 720
#define ACC_PF 1
#define QDEP 0
#define NSLEEP "40"
#define TRIG -1
#define LATE 80
#define NBIG 14

namespace {

constexpr int DM = 576, NH = 32, SEQ = 2048, NSEG = 64, HD = 4096;

__device__ uint4 g_acc_raw[64 * 96 * 16 + 131072];
__device__ uint4 g_ox[NH * 2 * SEQ * 8];
constexpr int REC = 30720;
__device__ uint4 g_qkv[NSEG * NH * (REC / 16)];
__device__ uint4 g_h[18 * SEQ * 8];
constexpr int NFLAG = 6144, F_QKV = 0, F_OX = 1024, F_H = 2048, F_OUT = 3072;
constexpr int NBLK = NBIG + (NSEG - 4 * NBIG) / 2;
__host__ __device__ constexpr int blk_seg0(int b) { return b < NBIG ? 4 * b : 2 * b + 2 * NBIG; }
__device__ unsigned g_flag[NFLAG];
__device__ unsigned g_ticket, g_ticket_bg;
__device__ unsigned long long g_norm[96];
#define BSTAMP(i) do {} while (0)

__device__ __forceinline__ uint32_t smem_u32(const void* p) { return (uint32_t)__cvta_generic_to_shared(p); }
__device__ __forceinline__ uint32_t mapa(uint32_t a, uint32_t r) { uint32_t o; asm("mapa.shared::cluster.u32 %0, %1, %2;" : "=r"(o) : "r"(a), "r"(r)); return o; }
__device__ __forceinline__ uint32_t mapa_v(uint32_t a, uint32_t r) { uint32_t o; asm volatile("mapa.shared::cluster.u32 %0, %1, %2;" : "=r"(o) : "r"(a), "r"(r)); return o; }
__device__ __forceinline__ unsigned clk() { unsigned long long c; asm volatile("mov.u64 %0, %%clock64;" : "=l"(c) :: "memory"); return (unsigned)c; }
__device__ __forceinline__ void mbar_init(uint32_t bar, uint32_t cnt) { asm volatile("mbarrier.init.shared::cta.b64 [%0], %1;" :: "r"(bar), "r"(cnt) : "memory"); }
__device__ __forceinline__ void mbar_expect(uint32_t bar, uint32_t bytes) { asm volatile("mbarrier.arrive.expect_tx.shared::cta.b64 _, [%0], %1;" :: "r"(bar), "r"(bytes) : "memory"); }
__device__ __forceinline__ void mbar_wait(uint32_t bar, uint32_t parity) {
    asm volatile("{\n.reg .pred p;\n.reg .u32 n;\nmov.u32 n, 0;\n"
                 "W_%=: mbarrier.try_wait.parity.shared::cta.b64 p, [%0], %1;\n@p bra.uni D_%=;\n"
                 "add.u32 n, n, 1;\nsetp.lt.u32 p, n, 4000000;\n@p bra.uni W_%=;\ntrap;\nD_%=:\n}" :: "r"(bar), "r"(parity) : "memory");
}
__device__ __forceinline__ void mbar_expect_if(uint32_t z, uint32_t bar, uint32_t bytes) {
    asm volatile("{\n.reg .pred p;\nsetp.eq.u32 p, %2, 0;\n@p mbarrier.arrive.expect_tx.shared::cta.b64 _, [%0], %1;\n}" :: "r"(bar), "r"(bytes), "r"(z) : "memory");
}
__device__ __forceinline__ void mbar_arrive_if(uint32_t z, uint32_t bar) {
    asm volatile("{\n.reg .pred p;\nsetp.eq.u32 p, %1, 0;\n@p mbarrier.arrive.shared::cta.b64 _, [%0];\n}" :: "r"(bar), "r"(z) : "memory");
}
__device__ __forceinline__ void sts32_if(uint32_t z, uint32_t a, uint32_t x) {
    asm volatile("{\n.reg .pred p;\nsetp.eq.u32 p, %2, 0;\n@p st.shared.u32 [%0], %1;\n}" :: "r"(a), "r"(x), "r"(z) : "memory");
}
template <int K> __device__ __forceinline__ void sched_fence(int v) {
    asm volatile("{\n.reg .pred p;\nsetp.ne.s32 p, %0, %1;\n@p bra.uni F_%=;\ntrap;\nF_%=:\n}" :: "r"(v), "n"(1000 + K) : "memory");
}
__device__ __forceinline__ void spin_until(unsigned t0, unsigned d) {
    asm volatile("{\n.reg .pred p;\n.reg .u64 c;\n.reg .u32 lo;\n"
                 "S_%=: mov.u64 c, %%clock64;\ncvt.u32.u64 lo, c;\nsub.u32 lo, lo, %0;\nsetp.lt.u32 p, lo, %1;\n@p bra.uni S_%=;\n}" :: "r"(t0), "r"(d) : "memory");
}
__device__ __forceinline__ void bar_sync(int id, int n) { asm volatile("bar.sync %0, %1;" :: "r"(id), "r"(n) : "memory"); }
__device__ __forceinline__ void bar_sync_sel(int sel, int id) {
    asm volatile("{\n.reg .pred p;\nsetp.eq.u32 p, %0, 0;\n@p bar.sync %1, %3;\n@!p bar.sync %2, %3;\n}" :: "r"(sel), "r"(id), "r"(id + 1), "n"(192) : "memory");
}
__device__ __forceinline__ void bar_arrive(int id, int n) { asm volatile("bar.arrive %0, %1;" :: "r"(id), "r"(n) : "memory"); }
__device__ __forceinline__ void fence_async_smem() { asm volatile("fence.proxy.async.shared::cta;" ::: "memory"); }
__device__ __forceinline__ uint32_t pack_bf16(float lo, float hi) { uint32_t r; asm("cvt.rn.bf16x2.f32 %0, %1, %2;" : "=r"(r) : "f"(hi), "f"(lo)); return r; }
__device__ __forceinline__ uint32_t pack_f16(float lo, float hi) { uint32_t r; asm("cvt.rn.f16x2.f32 %0, %1, %2;" : "=r"(r) : "f"(hi), "f"(lo)); return r; }
__device__ __forceinline__ uint32_t f16x2_to_bf16x2(uint32_t v) { float2 f = __half22float2(*reinterpret_cast<__half2*>(&v)); return pack_bf16(f.x, f.y); }
__device__ __forceinline__ uint32_t hmul2(uint32_t a, uint32_t b) { uint32_t r; asm("mul.rn.f16x2 %0, %1, %2;" : "=r"(r) : "r"(a), "r"(b)); return r; }
__device__ __forceinline__ float ex2(float x) { float y; asm("ex2.approx.ftz.f32 %0, %1;" : "=f"(y) : "f"(x)); return y; }
__device__ __forceinline__ float ex2v(float x) { float y; asm volatile("ex2.approx.ftz.f32 %0, %1;" : "=f"(y) : "f"(x)); return y; }
__device__ __forceinline__ uint32_t absmax2(uint32_t a, uint32_t b) {
    uint32_t r; asm("max.xorsign.abs.f16x2 %0, %1, %2;" : "=r"(r) : "r"(a), "r"(b)); return r;
}
__device__ __forceinline__ uint32_t shl_v(uint32_t a, int n) { return a << n; }
__device__ __forceinline__ uint32_t max3u(uint32_t a, uint32_t b, uint32_t c) { return max(max(a, b), c); }
__device__ __forceinline__ uint4 lds128(uint32_t a) { uint4 v; asm volatile("ld.shared.v4.u32 {%0,%1,%2,%3}, [%4];" : "=r"(v.x), "=r"(v.y), "=r"(v.z), "=r"(v.w) : "r"(a) : "memory"); return v; }
__device__ __forceinline__ uint4 lds128v(uint32_t a) { uint4 v; asm volatile("ld.volatile.shared.v4.u32 {%0,%1,%2,%3}, [%4];" : "=r"(v.x), "=r"(v.y), "=r"(v.z), "=r"(v.w) : "r"(a) : "memory"); return v; }
__device__ __forceinline__ float4 lds128f(uint32_t a) { float4 v; asm volatile("ld.shared.v4.f32 {%0,%1,%2,%3}, [%4];" : "=f"(v.x), "=f"(v.y), "=f"(v.z), "=f"(v.w) : "r"(a) : "memory"); return v; }
__device__ __forceinline__ float2 lds64f(uint32_t a) { float2 v; asm volatile("ld.shared.v2.f32 {%0,%1}, [%2];" : "=f"(v.x), "=f"(v.y) : "r"(a) : "memory"); return v; }
__device__ __forceinline__ uint4 lds64x2(uint32_t a) { uint4 v; asm volatile("ld.shared.v2.u32 {%0,%1}, [%4];\nld.shared.v2.u32 {%2,%3}, [%4+256];" : "=r"(v.x), "=r"(v.y), "=r"(v.z), "=r"(v.w) : "r"(a) : "memory"); return v; }
__device__ __forceinline__ uint32_t lds32(uint32_t a) { uint32_t v; asm volatile("ld.shared.u32 %0, [%1];" : "=r"(v) : "r"(a) : "memory"); return v; }
__device__ __forceinline__ void sts128(uint32_t a, uint32_t x, uint32_t y, uint32_t z, uint32_t w) { asm volatile("st.shared.v4.u32 [%0], {%1,%2,%3,%4};" :: "r"(a), "r"(x), "r"(y), "r"(z), "r"(w) : "memory"); }
__device__ __forceinline__ void sts128f(uint32_t a, float x, float y, float z, float w) { asm volatile("st.shared.v4.f32 [%0], {%1,%2,%3,%4};" :: "r"(a), "f"(x), "f"(y), "f"(z), "f"(w) : "memory"); }
__device__ __forceinline__ void sts64(uint32_t a, uint32_t x, uint32_t y) { asm volatile("st.shared.v2.u32 [%0], {%1,%2};" :: "r"(a), "r"(x), "r"(y) : "memory"); }
__device__ __forceinline__ void sts32(uint32_t a, uint32_t x) { asm volatile("st.shared.u32 [%0], %1;" :: "r"(a), "r"(x) : "memory"); }
__device__ __forceinline__ uint4 ldsm4(uint32_t a) { uint4 v; asm volatile("ldmatrix.sync.aligned.m8n8.x4.shared.b16 {%0,%1,%2,%3}, [%4];" : "=r"(v.x), "=r"(v.y), "=r"(v.z), "=r"(v.w) : "r"(a) : "memory"); return v; }
__device__ __forceinline__ void stsm2t(uint32_t a, uint32_t x, uint32_t y) { asm volatile("stmatrix.sync.aligned.m8n8.x2.trans.shared.b16 [%0], {%1,%2};" :: "r"(a), "r"(x), "r"(y) : "memory"); }
__device__ __forceinline__ void stsm4t(uint32_t a, uint32_t x, uint32_t y, uint32_t z, uint32_t w) { asm volatile("stmatrix.sync.aligned.m8n8.x4.trans.shared.b16 [%0], {%1,%2,%3,%4};" :: "r"(a), "r"(x), "r"(y), "r"(z), "r"(w) : "memory"); }
__device__ __forceinline__ void st_async64(uint32_t a, uint32_t x, uint32_t y, uint32_t bar) { asm volatile("st.async.shared::cluster.mbarrier::complete_tx::bytes.v2.b32 [%0], {%1,%2}, [%3];" :: "r"(a), "r"(x), "r"(y), "r"(bar) : "memory"); }
__device__ __forceinline__ void bulk_s2c(uint32_t dst, uint32_t src, uint32_t bytes, uint32_t bar) { asm volatile("cp.async.bulk.shared::cluster.shared::cta.mbarrier::complete_tx::bytes [%0], [%1], %2, [%3];" :: "r"(dst), "r"(src), "r"(bytes), "r"(bar) : "memory"); }
__device__ __forceinline__ void bulk_s2g(void* dst, uint32_t src, uint32_t bytes) { asm volatile("cp.async.bulk.global.shared::cta.bulk_group [%0], [%1], %2;" :: "l"(dst), "r"(src), "r"(bytes) : "memory"); }
__device__ __forceinline__ uint32_t ldg_nc32(const void* p) { uint32_t v; asm volatile("ld.global.nc.L2::128B.u32 %0, [%1];" : "=r"(v) : "l"(p)); return v; }
__device__ __forceinline__ uint4 ldg_relaxed128(const void* p) { uint4 v; asm volatile("ld.relaxed.gpu.global.v4.u32 {%0,%1,%2,%3}, [%4];" : "=r"(v.x), "=r"(v.y), "=r"(v.z), "=r"(v.w) : "l"(p) : "memory"); return v; }
__device__ __forceinline__ void mma16816(float (&d)[4], uint32_t a0, uint32_t a1, uint32_t a2, uint32_t a3, uint32_t b0, uint32_t b1) {
    asm volatile("mma.sync.aligned.m16n8k16.row.col.f32.bf16.bf16.f32 {%0,%1,%2,%3}, {%4,%5,%6,%7}, {%8,%9}, {%0,%1,%2,%3};"
        : "+f"(d[0]), "+f"(d[1]), "+f"(d[2]), "+f"(d[3]) : "r"(a0), "r"(a1), "r"(a2), "r"(a3), "r"(b0), "r"(b1));
}
__device__ __forceinline__ void mma16816_z(float (&d)[4], uint32_t a0, uint32_t a1, uint32_t a2, uint32_t a3, uint32_t b0, uint32_t b1) {
    asm volatile("mma.sync.aligned.m16n8k16.row.col.f32.bf16.bf16.f32 {%0,%1,%2,%3}, {%4,%5,%6,%7}, {%8,%9}, {%10,%10,%10,%10};"
        : "=f"(d[0]), "=f"(d[1]), "=f"(d[2]), "=f"(d[3]) : "r"(a0), "r"(a1), "r"(a2), "r"(a3), "r"(b0), "r"(b1), "f"(0.f));
}
__device__ __forceinline__ void mma1688(float (&d)[4], uint32_t a0, uint32_t a1, uint32_t b0) {
    asm volatile("mma.sync.aligned.m16n8k8.row.col.f32.bf16.bf16.f32 {%0,%1,%2,%3}, {%4,%5}, {%6}, {%0,%1,%2,%3};"
        : "+f"(d[0]), "+f"(d[1]), "+f"(d[2]), "+f"(d[3]) : "r"(a0), "r"(a1), "r"(b0));
}
__device__ __forceinline__ void mma1688_z(float (&d)[4], uint32_t a0, uint32_t a1, uint32_t b0) {
    asm volatile("mma.sync.aligned.m16n8k8.row.col.f32.bf16.bf16.f32 {%0,%1,%2,%3}, {%4,%5}, {%6}, {%7,%7,%7,%7};"
        : "=f"(d[0]), "=f"(d[1]), "=f"(d[2]), "=f"(d[3]) : "r"(a0), "r"(a1), "r"(b0), "f"(0.f));
}
template <int ACC>
__device__ __forceinline__ void wgmma_n32_rs(float (&d)[16], uint32_t a0, uint32_t a1, uint32_t a2, uint32_t a3, uint64_t desc) {
    asm volatile("wgmma.mma_async.sync.aligned.m64n32k16.f32.bf16.bf16 {%0,%1,%2,%3,%4,%5,%6,%7,%8,%9,%10,%11,%12,%13,%14,%15}, {%16,%17,%18,%19}, %20, %21, 1, 1, 0;"
        : "+f"(d[0]), "+f"(d[1]), "+f"(d[2]), "+f"(d[3]), "+f"(d[4]), "+f"(d[5]), "+f"(d[6]), "+f"(d[7]),
          "+f"(d[8]), "+f"(d[9]), "+f"(d[10]), "+f"(d[11]), "+f"(d[12]), "+f"(d[13]), "+f"(d[14]), "+f"(d[15])
        : "r"(a0), "r"(a1), "r"(a2), "r"(a3), "l"(desc), "n"(ACC));
}
template <int ACC>
__device__ __forceinline__ void wgmma_n32_ss(float (&d)[16], uint64_t da, uint64_t db) {
    asm volatile("wgmma.mma_async.sync.aligned.m64n32k16.f32.bf16.bf16 {%0,%1,%2,%3,%4,%5,%6,%7,%8,%9,%10,%11,%12,%13,%14,%15}, %16, %17, %18, 1, 1, 0, 0;"
        : "+f"(d[0]), "+f"(d[1]), "+f"(d[2]), "+f"(d[3]), "+f"(d[4]), "+f"(d[5]), "+f"(d[6]), "+f"(d[7]),
          "+f"(d[8]), "+f"(d[9]), "+f"(d[10]), "+f"(d[11]), "+f"(d[12]), "+f"(d[13]), "+f"(d[14]), "+f"(d[15])
        : "l"(da), "l"(db), "n"(ACC));
}
__device__ __forceinline__ void wg_fence() { asm volatile("wgmma.fence.sync.aligned;" ::: "memory"); }
__device__ __forceinline__ void wg_commit() { asm volatile("wgmma.commit_group.sync.aligned;" ::: "memory"); }
__device__ __forceinline__ void wg_wait0() { asm volatile("wgmma.wait_group.sync.aligned 0;" ::: "memory"); }
__device__ __forceinline__ void cluster_sync() { asm volatile("barrier.cluster.arrive.aligned;\nbarrier.cluster.wait.aligned;" ::: "memory"); }

#define STAMP(s, i) do {} while (0)
#define STAMPV(s, i, v) do {} while (0)

constexpr int XT_BYTES = 36864;
constexpr int O_XT = 0;
constexpr int O_STG = XT_BYTES;
constexpr int O_AS = 3 * XT_BYTES;
constexpr int O_XP = O_AS + 16384;
constexpr int O_QKX = O_XP + 8192;
constexpr int O_KM = O_QKX + 8192;
constexpr int O_QM = O_QKX + 10240;
constexpr int O_VX = O_STG + 147456;
constexpr int O_VM = O_VX + 16384;
constexpr int O_SC = O_VM + 2048;
constexpr int O_OF = O_SC + 2560;
constexpr int O_AF = O_OF + 2048;
constexpr int O_WP = O_AF + 4096;
constexpr int O_MF = O_WP + 2048;
constexpr int O_MISC = O_MF + 9216;
static_assert(O_QKX + 24576 <= O_VX, "smem");
constexpr int O_BAR = O_MISC + 128;
constexpr int CHAIN_SMEM = O_BAR + 128;
static_assert(CHAIN_SMEM <= 232448, "smem");
constexpr int B_X = O_BAR, B_VX = O_BAR + 24, B_SC = O_BAR + 40, B_W = O_BAR + 48;
constexpr float SM_SCALE = 0.08838834764831845f * 1.4426950408889634f;
constexpr uint32_t ONES = 0x3f803f80u;

__device__ __forceinline__ uint32_t opaque(uint32_t v) { uint32_t o; asm volatile("mov.u32 %0, %1;" : "=r"(o) : "r"(v)); return o; }
__device__ __forceinline__ void st_async128(uint32_t a, uint32_t x, uint32_t y, uint32_t z, uint32_t w, uint32_t bar) {
    asm volatile("st.async.shared::cluster.mbarrier::complete_tx::bytes.v4.b32 [%0], {%1,%2,%3,%4}, [%5];" :: "r"(a), "r"(x), "r"(y), "r"(z), "r"(w), "r"(bar) : "memory");
}
__device__ __forceinline__ void tma_x_tile(uint32_t sb, const CUtensorMap* tm, int r, int j, int slot) {
    asm volatile("{\n.reg .pred p;\nelect.sync _|p, 0xffffffff;\n"
        "@p mbarrier.arrive.expect_tx.shared::cta.b64 _, [%2], 36864;\n"
        "@p cp.async.bulk.tensor.2d.shared::cluster.global.mbarrier::complete_tx::bytes.multicast::cluster [%0], [%1, {%3, %4}], [%2], %7;\n"
        "@p cp.async.bulk.tensor.2d.shared::cluster.global.mbarrier::complete_tx::bytes.multicast::cluster [%0+4096], [%1, {%5, %4}], [%2], %7;\n"
        "@p cp.async.bulk.tensor.2d.shared::cluster.global.mbarrier::complete_tx::bytes.multicast::cluster [%0+8192], [%1, {%6, %4}], [%2], %7;\n}"
        :: "r"(sb + O_XT + slot * XT_BYTES + 3 * r * 4096), "l"(tm), "r"(sb + B_X + 8 * slot), "r"(192 * r), "r"(j * 32), "r"(192 * r + 64), "r"(192 * r + 128),
           "h"((unsigned short)7) : "memory");
}
__device__ __forceinline__ void flag_inc_if(uint32_t z, unsigned* p) {
    asm volatile("{\n.reg .pred p;\nsetp.eq.u32 p, %1, 0;\n@p red.release.gpu.global.inc.u32 [%0], 0xfffffffe;\n}" :: "l"(p), "r"(z) : "memory");
}
__device__ __forceinline__ float quad_max(float v) {
    const float a = __shfl_xor_sync(~0u, v, 1), b = __shfl_xor_sync(~0u, v, 2), c = __shfl_xor_sync(~0u, v, 3);
    return fmaxf(fmaxf(v, a), fmaxf(b, c));
}
__device__ __forceinline__ void load_scores(float (&p)[10], uint32_t base, uint32_t stride, uint32_t l16) {
    const float4 a0 = lds128f(base + l16), b0 = lds128f(base + stride + l16);
    const float4 a1 = lds128f(base + 512 + l16), b1 = lds128f(base + stride + 512 + l16);
    const float2 a2 = lds64f(base + 1024 + (l16 >> 1)), b2 = lds64f(base + stride + 1024 + (l16 >> 1));
    p[0] = a2.x + b2.x; p[1] = a2.y + b2.y;
    p[2] = a0.x + b0.x; p[3] = a0.y + b0.y; p[4] = a0.z + b0.z; p[5] = a0.w + b0.w;
    p[6] = a1.x + b1.x; p[7] = a1.y + b1.y; p[8] = a1.z + b1.z; p[9] = a1.w + b1.w;
}
__device__ __forceinline__ float rcp_fast(float x) { float y; asm("rcp.approx.ftz.f32 %0, %1;" : "=f"(y) : "f"(x)); return y; }

__global__ void __cluster_dims__(3, 1, 1) __launch_bounds__(384, 1)
chain_kernel(const __grid_constant__ CUtensorMap tm_x, const __grid_constant__ CUtensorMap tm_q,
             const __grid_constant__ CUtensorMap tm_k, const __grid_constant__ CUtensorMap tm_v,
             const __nv_bfloat16* __restrict__ x, const __nv_bfloat16* __restrict__ mem0,
             const __nv_bfloat16* __restrict__ Wo) {
    extern __shared__ __align__(1024) uint8_t smem_raw[];
    const uint32_t sb = smem_u32(smem_raw);
    const int lane = threadIdx.x & 31;
    const int warp = __shfl_sync(~0u, threadIdx.x >> 5, 0);
    const int wg = warp >> 2, w = warp & 3;
    const int h = blockIdx.x / 3, r = blockIdx.x - 3 * h;
    uint4* const g_acc = reinterpret_cast<uint4*>((reinterpret_cast<uintptr_t>(g_acc_raw) + 0x1fffff) & ~(uintptr_t)0x1fffff);

#define PSTAMP(i) do {} while (0)
    if (threadIdx.x == 0) {
        if (sb & 1023u) __trap();
        for (int i = 0; i < 9; i++) mbar_init(sb + O_BAR + 8 * i, 1);
        asm volatile("fence.mbarrier_init.release.cluster;" ::: "memory");
        for (int i = 0; i < 3; i++) {
            mbar_expect(sb + B_W + 8 * i, 49152);
            for (int tl = 0; tl < 2; tl++)
                asm volatile("cp.async.bulk.tensor.2d.shared::cluster.global.mbarrier::complete_tx::bytes [%0], [%1, {%3, %4}], [%2];"
                    :: "r"(sb + O_STG + tl * 73728 + i * 24576), "l"(r < 2 ? (tl ? &tm_k : &tm_q) : &tm_v), "r"(sb + B_W + 8 * i),
                       "r"(h * 128 + 64 * (r < 2 ? r : tl)), "r"(192 * i) : "memory");
        }
    }
    __syncwarp();
    asm volatile("barrier.cluster.arrive.relaxed.aligned;" ::: "memory");
    if (TRIG < 0) asm volatile("griddepcontrol.launch_dependents;" ::: "memory");
    if (warp == 0) PSTAMP(9);
    const uint32_t l16c = __shfl_sync(~0u, lane * 16, lane);

    if (wg < 2) {
#define KS(u) ((u) < 8 ? 12 * ((u) >> 2) + (((u) >> 1) & 1) + 4 * ((u) & 1) : (u) < 12 ? (u) : (u) < 16 ? (u) + 8 : (u) < 24 ? 24 + (((u) - 16) >> 1) + 4 * ((u) & 1) : (u) + 8)
        asm volatile("setmaxnreg.inc.sync.aligned.u32 184;");
        uint32_t a[144];
        uint32_t adr1;
        {
            const int g = lane >> 2, t = lane & 3;
            const int t1 = threadIdx.x;
#pragma unroll
            for (int i = 0; i < 2; i++) g_acc[(blockIdx.x * 64 + i * 32 + (t1 >> 3)) * 16 + (t1 & 7)] = make_uint4(0, 0, 0, 0);
            if (t1 == 0 && blockIdx.x < 64) g_acc[blockIdx.x * 1536 + 8] = make_uint4(0, 0, 0, 0);
            __threadfence();
            asm volatile("barrier.cluster.wait.aligned;" ::: "memory");
            const uint32_t ev = sb + O_STG + (2 * t) * 128 + (((2 * w + (g >> 2)) ^ (2 * t)) << 4) + (g & 3) * 4;
            const uint32_t od = (ev ^ 16) + 128;
            auto gather = [&](int dst, uint32_t off) {
                a[dst] = lds32(ev + off); a[dst + 1] = lds32(od + off); a[dst + 2] = lds32(ev + off + 1024); a[dst + 3] = lds32(od + off + 1024);
            };
            const uint4* xp = reinterpret_cast<const uint4*>(x) + blockIdx.x * 1536 + t1;
            uint4 xv[6];
#pragma unroll
            for (int th = 0; th < 2; th++) {
                mbar_wait(sb + B_W + 8 * th, 0);
                if (TRIG == th) asm volatile("griddepcontrol.launch_dependents;" ::: "memory");
                if (th == 1) {
#pragma unroll
                    for (int i = 0; i < 6; i++) xv[i] = __ldg(xp + i * 256);
                }
#pragma unroll
                for (int u = 4 * th; u < 4 * th + 4; u++) {
                    gather(32 + 4 * u, wg * (73728 + 4096) + KS(u) * 2048);
                    gather(4 * u, 73728 - wg * (73728 - 4096) + KS(u) * 2048);
                    gather(64 + 4 * u, wg * 73728 + KS(8 + u) * 2048);
                }
            }
            mbar_wait(sb + B_W + 16, 0);
#pragma unroll
            for (int u = 16; u < 28; u++) gather(32 + 4 * u, wg * 73728 + KS(u) * 2048);
#pragma unroll
            for (int kk = 0; kk < 72; kk++) {
                uint32_t w0 = a[2 * kk], w1 = a[2 * kk + 1];
                a[2 * kk] = __byte_perm(w0, w1, 0x5410);
                a[2 * kk + 1] = __byte_perm(w0, w1, 0x7632);
            }
            if (r == 2) {
                float n0[4], n1[4];
#pragma unroll
                for (int u = 0; u < 36; u++) {
                    const uint32_t x0 = a[4 * u] & 0x7fff7fffu, x1 = a[4 * u + 1] & 0x7fff7fffu, x2 = a[4 * u + 2] & 0x7fff7fffu, x3 = a[4 * u + 3] & 0x7fff7fffu;
                    if (u == 0) mma16816_z(n0, x0, x1, x2, x3, ONES, ONES);
                    else if (u < 8) mma16816(n0, x0, x1, x2, x3, ONES, ONES);
                    else if (u == 8) mma16816_z(n1, x0, x1, x2, x3, ONES, ONES);
                    else mma16816(n1, x0, x1, x2, x3, ONES, ONES);
                }
                const uint32_t mx = __reduce_max_sync(~0u, __float_as_uint(2.f * fmaxf(fmaxf(n0[0], n0[2]), fmaxf(n1[0], n1[2]))));
                sts32_if(lane, sb + O_MISC + 32 + 4 * warp, mx);
            }
            uint32_t xm = 0;
#pragma unroll
            for (int i = 0; i < 6; i++)
                xm = __vmaxu2(xm, __vmaxu2(__vmaxu2(xv[i].x & 0x7fff7fffu, xv[i].y & 0x7fff7fffu), __vmaxu2(xv[i].z & 0x7fff7fffu, xv[i].w & 0x7fff7fffu)));
            sts32_if(lane, sb + O_OF + 16 + 4 * warp, __reduce_max_sync(~0u, max(xm << 16, xm & 0xffff0000u)));
            if (warp == 0) PSTAMP(11);
            bar_arrive(7, 384);
            asm volatile("barrier.cluster.arrive.relaxed.aligned;" ::: "memory");
            bar_sync(1, 256);
            const uint32_t as = sb + O_AS + wg * 8192 + (16 * w + g) * 128 + t * 4;
            sts32(as + (g << 4), a[32]);
            sts32(as + 1024 + (g << 4), a[33]);
            sts32(as + ((1 ^ g) << 4), a[34]);
            sts32(as + 1024 + ((1 ^ g) << 4), a[35]);
            sts128(sb + O_AF + warp * 512 + lane * 16, a[32], a[33], a[34], a[35]);
            fence_async_smem();
            bar_sync(1, 256);
            const uint32_t l = lane * 16;
            const int mi = lane >> 3, isk = (mi >> 1) ? wg : (wg ^ 1);
            adr1 = (r == 2) ? (sb + O_VM + warp * 256 + (l >> 1))
                            : (isk ? (sb + O_KM + w * 512 + wg * 256 + (mi & 1) * 128 + (l & 127))
                                   : (sb + O_QM + w * 512 + (mi & 1) * 256 + wg * 128 + (l & 127)));
            adr1 = __shfl_sync(~0u, adr1, lane);
        }
        int s3 = 2;
#pragma unroll 1
        for (int s = -1; s < NSEG; s++) {
            const uint32_t l16 = opaque(l16c);
            s3 = (s3 == 2) ? 0 : s3 + 1;
            if (s < 0) mbar_wait(sb + B_X, 0);
            const uint64_t desc0 = (uint64_t)(((sb + O_XT + s3 * XT_BYTES) & 0x3FFFF) >> 4) | (1ull << 16) | (64ull << 32) | (1ull << 62);
            uint32_t km0 = 0, km1 = 0;
            if (s >= 0) {
                { const uint4 v = lds128(sb + O_AF + warp * 512 + l16); a[32] = v.x; a[33] = v.y; a[34] = v.z; a[35] = v.w; }
                float co[4], cw[3][4];
                uint4 b[14];
                float inv;
#define GORD(i) ((i) < 8 ? 2 * ((i) >> 2) + (((i) >> 1) & 1) + 4 * ((i) & 1) : (i))
                auto qkv_mma = [&](int i) {
                    const int gi = GORD(i), u = 8 * gi, n0 = 2 * i, n1 = 2 * i + 1;
                    if (gi < 4) {
                        if (i == 0) mma16816_z(co, a[u], a[u + 1], a[u + 2], a[u + 3], b[0].x, b[0].y);
                        else mma16816(co, a[u], a[u + 1], a[u + 2], a[u + 3], b[i].x, b[i].y);
                    }
                    if (n0 < 3) mma16816_z(cw[n0 % 3], a[32 + u], a[32 + u + 1], a[32 + u + 2], a[32 + u + 3], b[i].x, b[i].y);
                    else mma16816(cw[n0 % 3], a[32 + u], a[32 + u + 1], a[32 + u + 2], a[32 + u + 3], b[i].x, b[i].y);
                    if (n1 < 3) mma16816_z(cw[n1 % 3], a[32 + u + 4], a[32 + u + 5], a[32 + u + 6], a[32 + u + 7], b[i].z, b[i].w);
                    else mma16816(cw[n1 % 3], a[32 + u + 4], a[32 + u + 5], a[32 + u + 6], a[32 + u + 7], b[i].z, b[i].w);
                    if (gi < 4) mma16816(co, a[u + 4], a[u + 5], a[u + 6], a[u + 7], b[i].z, b[i].w);
                };
                const uint32_t mf = sb + O_MF + l16, mfs = mf + wg * 1024;
                const uint32_t qb = (s & 1) * 12288;
                bar_sync(2, 384);
                if (warp == 0) STAMP(s, 0);
                auto qkv_ld = [&](int i) {
                    const int gi = GORD(i);
                    b[i] = gi < 4 ? lds128v(mfs + (gi >> 1) * 3072 + (gi & 1) * 512) : lds128v(mf + (gi < 6 ? gi : gi + 4) * 512);
                };
#pragma unroll
                for (int i = 0; i < 4; i++) qkv_ld(i);
                qkv_mma(0); qkv_mma(1); qkv_mma(2);
                const uint32_t z0 = __float_as_uint(QDEP ? co[0] : cw[1][0]) & (l16 & 15u);
                qkv_mma(3);
                bar_sync(15, 384);
                b[4] = lds128v(mfs + 3072 + z0);
#pragma unroll
                for (int i = 5; i < 9; i++) qkv_ld(i);
#pragma unroll
                for (int i = 4; i < 9; i++) { qkv_mma(i); qkv_ld(5 + i); }
                asm volatile("ld.volatile.shared.f32 %0, [%1];" : "=f"(inv) : "r"(sb + O_MISC) : "memory");
#pragma unroll
                for (int i = 9; i < 14; i++) qkv_mma(i);
#pragma unroll
                for (int i = 0; i < 4; i++) cw[0][i] += cw[1][i] + cw[2][i];
                if (r < 2) {
                    const uint32_t o0 = pack_bf16(co[0] * inv, co[1] * inv), o1 = pack_bf16(co[2] * inv, co[3] * inv);
                    const uint32_t w0 = pack_bf16(cw[0][0] * inv, cw[0][1] * inv), w1 = pack_bf16(cw[0][2] * inv, cw[0][3] * inv);
                    stsm4t(adr1 + qb, o0, o1, w0, w1);
                    if (warp == 0) STAMP(s, 1);
                    asm volatile("{\n.reg .pred p;\nsetp.ge.u32 p, %0, 3;\n@p bar.arrive 1, 256;\n}" :: "r"(warp) : "memory");
                    auto scores = [&](float (&v)[4], const uint4 (&q)[4], const uint4 (&k)[4]) {
                        float s0[4], s1[4], t0[4], t1[4];
                        mma16816_z(s0, q[0].x, q[0].y, q[0].z, q[0].w, k[0].x, k[0].y);
                        mma16816_z(s1, q[0].x, q[0].y, q[0].z, q[0].w, k[0].z, k[0].w);
                        mma16816_z(t0, q[1].x, q[1].y, q[1].z, q[1].w, k[1].x, k[1].y);
                        mma16816_z(t1, q[1].x, q[1].y, q[1].z, q[1].w, k[1].z, k[1].w);
                        mma16816(s0, q[2].x, q[2].y, q[2].z, q[2].w, k[2].x, k[2].y);
                        mma16816(s1, q[2].x, q[2].y, q[2].z, q[2].w, k[2].z, k[2].w);
                        mma16816(t0, q[3].x, q[3].y, q[3].z, q[3].w, k[3].x, k[3].y);
                        mma16816(t1, q[3].x, q[3].y, q[3].z, q[3].w, k[3].z, k[3].w);
                        v[0] = (s0[0] + s0[2]) + (t0[0] + t0[2]); v[1] = (s0[1] + s0[3]) + (t0[1] + t0[3]);
                        v[2] = (s1[0] + s1[2]) + (t1[0] + t1[2]); v[3] = (s1[1] + s1[3]) + (t1[1] + t1[3]);
                    };
                    if (warp < 2) {
                        uint4 q[4], k[4]; float v[4];
#pragma unroll
                        for (int i = 0; i < 4; i++) k[i] = ldsm4(sb + O_QKX + 4096 + qb + warp * 2048 + i * 512 + l16);
                        bar_sync(1, 256);
#pragma unroll
                        for (int i = 0; i < 4; i++) q[i] = ldsm4(sb + O_QM + qb + i * 512 + l16);
                        scores(v, q, k);
                        const uint32_t dst = sb + O_SC + r * 1280 + warp * 512 + l16;
                        st_async128(mapa(dst, 2), __float_as_uint(v[0]), __float_as_uint(v[1]), __float_as_uint(v[2]), __float_as_uint(v[3]), mapa(sb + B_SC, 2));
                        st_async128(mapa(dst, r ^ 1), __float_as_uint(v[0]), __float_as_uint(v[1]), __float_as_uint(v[2]), __float_as_uint(v[3]), mapa(sb + B_SC, r ^ 1));
                        st_async128(mapa(dst, r), __float_as_uint(v[0]), __float_as_uint(v[1]), __float_as_uint(v[2]), __float_as_uint(v[3]), mapa(sb + B_SC, r));
                    } else if (warp == 2) {
                        uint4 q[4], k[4]; float v[4];
                        bar_sync(1, 256);
#pragma unroll
                        for (int i = 0; i < 4; i++) { q[i] = ldsm4(sb + O_QM + qb + i * 512 + l16); k[i] = ldsm4(sb + O_KM + qb + i * 512 + l16); }
                        scores(v, q, k);
                        const uint32_t dst = sb + O_SC + r * 1280 + 1024 + (l16 >> 1);
                        st_async64(mapa(dst, 2), __float_as_uint(v[0] + v[2]), __float_as_uint(v[1] + v[3]), mapa(sb + B_SC, 2));
                        st_async64(mapa(dst, r ^ 1), __float_as_uint(v[0] + v[2]), __float_as_uint(v[1] + v[3]), mapa(sb + B_SC, r ^ 1));
                        st_async64(mapa(dst, r), __float_as_uint(v[0] + v[2]), __float_as_uint(v[1] + v[3]), mapa(sb + B_SC, r));
                        STAMP(s, 2);
                    }
                } else {
                    sts128f(sb + O_XP + warp * 512 + l16, co[0], co[1], co[2], co[3]);
                    bar_sync(8 + w, 64);
                    const float4 o = lds128f(sb + O_XP + (warp ^ 4) * 512 + l16);
                    km0 = pack_bf16((cw[0][0] + o.x) * inv, (cw[0][1] + o.y) * inv);
                    km1 = pack_bf16((cw[0][2] + o.z) * inv, (cw[0][3] + o.w) * inv);
                    if (warp == 0) STAMP(s, 1);
                    st_async64(mapa(adr1, 0), km0, km1, mapa(sb + B_SC, 0));
                    st_async64(mapa(adr1, 1), km0, km1, mapa(sb + B_SC, 1));
                    st_async64(mapa(adr1, 2), km0, km1, mapa(sb + B_SC, 2));
                    if (warp == 0) STAMP(s, 2);
                }
            }
            if (s >= 0) bar_sync(3, 384);
            auto store_qk = [&]() {
                asm volatile("{\n.reg .pred p;\nelect.sync _|p, 0xffffffff;\n"
                    "@p cp.async.bulk.global.shared::cta.bulk_group [%0], [%1], 10240;\n@p cp.async.bulk.commit_group;\n}"
                    :: "l"(reinterpret_cast<char*>(g_qkv) + (size_t)(s * NH + h) * REC + r * 10240), "r"(sb + O_QKX + (s & 1) * 12288) : "memory");
            };
            auto store_vm = [&]() {
                *reinterpret_cast<uint2*>(reinterpret_cast<char*>(g_qkv) + (size_t)(s * NH + h) * REC + 28672 + warp * 256 + (l16 >> 1)) = make_uint2(km0, km1);
            };
            if (s == NSEG - 1) {
                if (r == 2) store_vm();
                else if (warp == 3) {
                    fence_async_smem();
                    store_qk();
                    asm volatile("cp.async.bulk.wait_group 0;\nfence.proxy.async.global;" ::: "memory");
                }
            } else {
                const int j = s + 1;
#define XDESC(u) (((u) < 8 ? descs : desc0) + (uint64_t)(((KS(u) >> 2) * 4096 + (KS(u) & 3) * 32) >> 4))
                const uint64_t descs = desc0 + (uint64_t)(wg * 4);
                float d[16];
                wg_fence();
#pragma unroll
                for (int u = 0; u < 8; u++) {
                    if (u == 0) wgmma_n32_rs<0>(d, a[0], a[1], a[2], a[3], XDESC(0));
                    else wgmma_n32_rs<1>(d, a[4 * u], a[4 * u + 1], a[4 * u + 2], a[4 * u + 3], XDESC(u));
                }
                wg_commit();
                wg_wait0();
                if (warp == 0) STAMP(s, 15);
                if (warp == 3) asm volatile("cp.async.bulk.wait_group.read 0;" ::: "memory");
                if (s >= 0) bar_sync(4, 384);
#pragma unroll
                for (int q = 0; q < 2; q++)
                    sts128(sb + O_XP + warp * 1024 + q * 512 + l16, pack_bf16(d[8 * q], d[8 * q + 1]), pack_bf16(d[8 * q + 2], d[8 * q + 3]),
                           pack_bf16(d[8 * q + 4], d[8 * q + 5]), pack_bf16(d[8 * q + 6], d[8 * q + 7]));
                bar_sync(12, 256);
#pragma unroll
                for (int q = 0; q < 2; q++) {
                    const uint4 o = lds128(sb + O_XP + (warp ^ 4) * 1024 + q * 512 + l16);
                    d[8 * q] = __uint_as_float(o.x << 16); d[8 * q + 1] = __uint_as_float(o.x & 0xffff0000u);
                    d[8 * q + 2] = __uint_as_float(o.y << 16); d[8 * q + 3] = __uint_as_float(o.y & 0xffff0000u);
                    d[8 * q + 4] = __uint_as_float(o.z << 16); d[8 * q + 5] = __uint_as_float(o.z & 0xffff0000u);
                    d[8 * q + 6] = __uint_as_float(o.w << 16); d[8 * q + 7] = __uint_as_float(o.w & 0xffff0000u);
                }
                if (s >= 0) {
                    if (r == 2) store_vm();
                    if (LATE && warp == 6) {
                        uint32_t lv;
                        asm volatile("ld.relaxed.gpu.global.u32 %0, [%1];" : "=r"(lv) : "l"(reinterpret_cast<char*>(g_acc) + s * 24576 + 128) : "memory");
                        sts32(sb + O_MISC + 96, lv);
                    }
                    if (warp == 5 && s + 2 < NSEG) tma_x_tile(sb, &tm_x, r, s + 2, s3 == 2 ? 0 : s3 + 1);
                    if (warp == 3) {
                        asm volatile("cp.async.bulk.wait_group 0;\nfence.proxy.async.global;" ::: "memory");
                        fence_async_smem();
                    }
                    asm volatile("{\n.reg .pred p;\nsetp.eq.u32 p, %0, 0;\n@p bar.sync 5, 256;\n@!p bar.sync 13, 256;\n}" :: "r"(wg) : "memory");
                }
                const uint64_t da0 = (uint64_t)(((sb + O_AS + wg * 8192) & 0x3FFFF) >> 4) | (1ull << 16) | (64ull << 32) | (1ull << 62);
                wg_fence();
                wgmma_n32_ss<1>(d, da0, XDESC(0));
#pragma unroll
                for (int u = 1; u < 28; u++) wgmma_n32_rs<1>(d, a[32 + 4 * u], a[32 + 4 * u + 1], a[32 + 4 * u + 2], a[32 + 4 * u + 3], XDESC(u));
                wg_commit();
                if (warp == 3 && s >= 4 && !(s & (s > 4 * NBIG ? 1 : 3)))
                    flag_inc_if(l16, &g_flag[F_QKV + ((s > 4 * NBIG ? 2 * s - 4 * NBIG : s) - 4 + (h >> 3)) * 8]);
                wg_wait0();
                if (warp == 3 && r < 2 && s >= 0) store_qk();
                if (warp == 4) STAMP(s, 3);
                uint32_t e[8];
#pragma unroll
                for (int i = 0; i < 8; i++) e[i] = pack_bf16(d[2 * i], d[2 * i + 1]);
                if (r < 2) {
                    const uint32_t base = sb + O_QKX + (j & 1) * 12288 + wg * 4096 + w * 512 + l16;
                    stsm4t(base, e[0], wg ? e[1] : e[2], wg ? e[2] : e[1], e[3]);
                    stsm4t(base + 2048, e[4], wg ? e[5] : e[6], wg ? e[6] : e[5], e[7]);
                } else {
                    const uint32_t base = sb + O_VX + (j & 1) * 8192 + warp * 1024 + l16;
                    sts128(base, e[0], e[1], e[2], e[3]);
                    sts128(base + 512, e[4], e[5], e[6], e[7]);
                    bar_arrive(14, 288);
                }
                if (warp == 7) STAMP(s, 4);
                if (s < 0) asm volatile("barrier.cluster.wait.aligned;" ::: "memory");
            }
        }
        bar_arrive(7, 384);
    } else {
        asm volatile("setmaxnreg.dec.sync.aligned.u32 136;");
        const int c = w;
        uint32_t a[96];
        uint32_t mmax = 0;
        {
            const int g = lane >> 2, t = lane & 3;
            uint32_t tag = 0, m0v[18];
            if (threadIdx.x == 256) tag = atomicAdd(&g_ticket, 1u);
#pragma unroll
            for (int i = 0; i < 9; i++) {
                const uint32_t* p = reinterpret_cast<const uint32_t*>(mem0 + g * DM + 16 * (4 * i + c) + 2 * t);
                m0v[2 * i] = __ldg(p); m0v[2 * i + 1] = __ldg(p + 4);
            }
            asm volatile("barrier.cluster.wait.aligned;" ::: "memory");
            if (c == 0) {
                tma_x_tile(sb, &tm_x, r, 0, 0);
                mbar_expect_if(lane, sb + B_SC, 4608);
                if (r < 2) mbar_expect_if(lane, sb + B_VX, 8192);
                sts32_if(lane, sb + O_MISC, __float_as_uint(1.0f));
                sts32_if(lane, sb + O_MISC + 12, __float_as_uint(SM_SCALE));
            }
            asm volatile("barrier.cluster.arrive.relaxed.aligned;" ::: "memory");
#pragma unroll
            for (int tau = 0; tau < 3; tau++) {
                const uint32_t* v = m0v + 6 * tau;
                sts128(sb + O_MF + tau * 3072 + c * 512 + lane * 16, v[0], v[1], v[2], v[3]);
                sts64(sb + O_MF + tau * 3072 + 2048 + (c >> 1) * 512 + lane * 16 + (c & 1) * 8, v[4], v[5]);
#pragma unroll
                for (int i = 0; i < 6; i++) mmax = __vmaxu2(mmax, v[i] & 0x7fff7fffu);
            }
            mmax = max(mmax << 16, mmax & 0xffff0000u);
            bar_arrive(2, 384); bar_arrive(15, 384);
            tag = (__shfl_sync(~0u, tag, 0) / 96u + 1u) & 0xffffu;
            mbar_wait(sb + B_W + 0, 0);
            const __nv_bfloat16* p = Wo + (size_t)(h * 128 + 4 * t) * DM + 192 * r + 16 * c + 2 * g;
#pragma unroll
            for (int i = 0; i < 3; i++)
#pragma unroll
                for (int eb = 0; eb < 8; eb++)
#pragma unroll
                    for (int j = 0; j < 4; j++) a[(i * 8 + eb) * 4 + j] = ldg_nc32(p + (16 * eb + ((j & 1) * 2 + (j >> 1))) * DM + 64 * i);
#pragma unroll
            for (int kk = 0; kk < 48; kk++) {
                uint32_t w0 = a[2 * kk], w1 = a[2 * kk + 1];
                a[2 * kk] = __byte_perm(w0, w1, 0x5410);
                a[2 * kk + 1] = __byte_perm(w0, w1, 0x7632);
            }
            sts128(sb + O_WP + c * 512 + lane * 16, a[92], a[93], a[94], a[95]);
            float wmax = 0.f;
#pragma unroll
            for (int i = 0; i < 3; i++) {
                float n0[4];
#pragma unroll
                for (int u = 8 * i; u < 8 * i + 8; u++) {
                    const uint32_t x0 = a[4 * u] & 0x7fff7fffu, x1 = a[4 * u + 1] & 0x7fff7fffu, x2 = a[4 * u + 2] & 0x7fff7fffu, x3 = a[4 * u + 3] & 0x7fff7fffu;
                    if (u == 8 * i) mma16816_z(n0, x0, x1, x2, x3, ONES, ONES);
                    else mma16816(n0, x0, x1, x2, x3, ONES, ONES);
                }
                wmax = fmaxf(wmax, fmaxf(n0[0], n0[2]));
            }
            uint32_t wm = __reduce_max_sync(~0u, __float_as_uint(wmax));
            sts32_if(lane, sb + O_OF + 4 * c, wm);
            if (c == 0) PSTAMP(8);
            bar_sync(7, 384);
            asm volatile("barrier.cluster.wait.aligned;" ::: "memory");
            if (c == 1) tma_x_tile(sb, &tm_x, r, 1, 1);
            if (c == 0) {
                const uint4 wq = lds128(sb + O_OF), xq = lds128(sb + O_OF + 16), xr = lds128(sb + O_OF + 32), v0 = lds128(sb + O_MISC + 32), v1 = lds128(sb + O_MISC + 48);
                const uint32_t w1 = max(max(wq.x, wq.y), max(wq.z, wq.w)), x1 = max(max(max(xq.x, xq.y), max(xq.z, xq.w)), max(max(xr.x, xr.y), max(xr.z, xr.w)));
                const uint32_t vv = (r < 2) ? 0u : max(max(max(v0.x, v0.y), max(v0.z, v0.w)), max(max(v1.x, v1.y), max(v1.z, v1.w)));
                const uint32_t lo = (min(w1, 0x7f800000u) + 0xffffu) >> 16 | ((min(vv, 0x7f800000u) + 0xffffu) & 0xffff0000u), hi = (x1 & 0xffff0000u) | tag;
                uint32_t l0, h0, l1, h1, l2, h2;
                asm volatile("{\n.reg .pred p;\n.reg .u32 n, x, y;\n.reg .b64 v;\nsetp.eq.u32 p, %10, 0;\nmov.b64 v, {%8, %9};\n@p st.relaxed.gpu.global.b64 [%7], v;\nmov.u32 n, 0;\n"
                             "G_%=: ld.relaxed.gpu.global.b64 v, [%6];\nmov.b64 {%0, %1}, v;\nld.relaxed.gpu.global.b64 v, [%6+256];\nmov.b64 {%2, %3}, v;\n"
                             "ld.relaxed.gpu.global.b64 v, [%6+512];\nmov.b64 {%4, %5}, v;\n"
                             "xor.b32 x, %1, %9;\nxor.b32 y, %3, %9;\nor.b32 x, x, y;\nxor.b32 y, %5, %9;\nor.b32 x, x, y;\nand.b32 x, x, 0xffff;\n"
                             "setp.eq.u32 p, x, 0;\nvote.sync.all.pred p, p, 0xffffffff;\n@p bra.uni E_%=;\n"
                             "add.u32 n, n, 1;\nsetp.lt.u32 p, n, 4000000;\n@p bra.uni G_%=;\ntrap;\nE_%=:\n}"
                             : "=&r"(l0), "=&r"(h0), "=&r"(l1), "=&r"(h1), "=&r"(l2), "=&r"(h2)
                             : "l"(&g_norm[lane]), "l"(&g_norm[blockIdx.x]), "r"(lo), "r"(hi), "r"(lane) : "memory");
                const uint32_t lm = __vmaxu2(l0, __vmaxu2(l1, l2));
                const float fw = __uint_as_float(__reduce_max_sync(~0u, lm << 16));
                const float fv = __uint_as_float(__reduce_max_sync(~0u, lm & 0xffff0000u));
                const float xmax = __uint_as_float(__reduce_max_sync(~0u, max(h0, max(h1, h2)) & 0xffff0000u));
                const float G = 36.f * fw * fv;
                sts32_if(lane, sb + O_MISC + 4, __float_as_uint(G)); sts32_if(lane, sb + O_MISC + 8, __float_as_uint(G * xmax));
            }
        }
        sts64(sb + O_MISC + 64 + 8 * c, clk() - 100000u, 0xffffffffu);
        if (c == 0) PSTAMP(12);
        bar_sync(6, 128);
        int s3n = 1;
        uint32_t roff = __shfl_sync(~0u, (r * 4 + c) * 2048 + (lane >> 4) * 512 + (lane & 2) * 128 + (lane & 1) * 64 + (lane & 12) * 4, lane);
#pragma unroll 1
        for (int s = 0; s < NSEG; s++) {
            const uint32_t l16 = opaque(l16c);
            const uint32_t vxa = sb + O_VX + (s & 1) * 8192 + c * 2048 + l16;
            if (c == 0 && r == 2) {
                bar_sync(14, 288);
                fence_async_smem();
                asm volatile("{\n.reg .pred p;\nelect.sync _|p, 0xffffffff;\n"
                    "@p cp.async.bulk.global.shared::cta.bulk_group [%0], [%1], 8192;\n@p cp.async.bulk.commit_group;\n"
                    "cp.async.bulk.wait_group 0;\nsetp.lt.and.s32 p, %4, 63, p;\n"
                    "@p cp.async.bulk.shared::cluster.global.mbarrier::complete_tx::bytes.multicast::cluster [%1], [%0], 8192, [%2], %3;\n"
                    "fence.proxy.async.global;\n}"
                    :: "l"(reinterpret_cast<char*>(g_qkv) + (size_t)(s * NH + h) * REC + 20480), "r"(sb + O_VX + (s & 1) * 8192),
                       "r"(sb + B_VX + 8 * (s & 1)), "h"((unsigned short)3), "r"(s) : "memory");
            }
            if (s == NSEG - 1) { bar_sync(3, 384); mbar_wait(sb + B_SC, s & 1); break; }
            uint4 vx[4];
            sts32_if(l16, sb + O_MISC + 16 + 4 * c, __reduce_max_sync(~0u, mmax));
            if (c == 0) STAMP(s, 5);
            {
                bar_sync(6, 128);
                const uint4 mm = lds128(sb + O_MISC + 16), cf = lds128(sb + O_MISC);
                const float bound = fmaxf(__uint_as_float(cf.z), __uint_as_float(cf.y) * (__uint_as_float(max(max(mm.x, mm.y), max(mm.z, mm.w))) * __uint_as_float(cf.x)));
                const uint32_t ebits = __reduce_max_sync(~0u, min(max(__float_as_uint(bound) & 0x7f800000u, 21u << 23), 254u << 23));
                mbar_wait(sb + B_X + 8 * s3n, ((s + 1) / 3) & 1);
                s3n = (s3n == 2) ? 0 : s3n + 1;
                bar_sync(3, 384);
                if (r < 2) mbar_wait(sb + B_VX + 8 * (s & 1), (s >> 1) & 1);
                vx[0] = lds128(vxa); vx[2] = lds128(vxa + 1024);
                if (c == 0) STAMP(s, 13);
                mbar_wait(sb + B_SC, s & 1);
                if (c == 0) STAMP(s, 6);
                float p[10];
                load_scores(p, sb + O_SC, 1280, l16);
                float mx = fmaxf(fmaxf(fmaxf(p[0], p[1]), fmaxf(p[2], p[3])), fmaxf(fmaxf(p[4], p[5]), fmaxf(p[6], p[7])));
                mx = quad_max(fmaxf(mx, fmaxf(p[8], p[9])));
                const uint4 vm = lds64x2(sb + O_VM + c * 512 + (l16 >> 1));
                vx[1] = lds128(vxa + 512); vx[3] = lds128(vxa + 1536);
                bar_arrive(4, 384);
                const float sc = __uint_as_float(lds32(sb + O_MISC + 12));
                const float mo = mx * SM_SCALE;
                uint32_t P[5];
#pragma unroll
                for (int n = 0; n < 5; n++) P[n] = pack_bf16(ex2(fmaf(p[2 * n], SM_SCALE, -mo)), ex2(fmaf(p[2 * n + 1], n == 3 ? sc : SM_SCALE, -mo)));
                if (c == 0) STAMP(s, 7);
                float o0[4], o1[4], sm[4];
                mma16816_z(sm, ONES, ONES, ONES, ONES, P[1], P[2]);
                mma16816_z(o0, vx[0].x, vx[0].y, vx[0].z, vx[0].w, P[1], P[2]);
                mma16816_z(o1, vx[2].x, vx[2].y, vx[2].z, vx[2].w, P[1], P[2]);
                mma16816(sm, ONES, ONES, ONES, ONES, P[3], P[4]);
                mma16816(o0, vx[1].x, vx[1].y, vx[1].z, vx[1].w, P[3], P[4]);
                mma16816(o1, vx[3].x, vx[3].y, vx[3].z, vx[3].w, P[3], P[4]);
                mma1688(sm, ONES, ONES, P[0]);
                mma1688(o0, vm.x, vm.y, P[0]);
                mma1688(o1, vm.z, vm.w, P[0]);
                const float sig = __uint_as_float((268u << 23) - ebits);
                const float r0 = rcp_fast(sm[0]) * sig, r1 = rcp_fast(sm[1]) * sig;
                stsm4t(sb + O_OF + c * 512 + l16, pack_bf16(o0[0] * r0, o0[1] * r1), pack_bf16(o0[2] * r0, o0[3] * r1),
                       pack_bf16(o1[0] * r0, o1[1] * r1), pack_bf16(o1[2] * r0, o1[3] * r1));
                bar_sync(6, 128);
                uint4 ob[4];
#pragma unroll
                for (int q = 0; q < 4; q++) ob[q] = ldsm4(sb + O_OF + q * 512 + l16);
                { const uint4 v = lds128(sb + O_WP + c * 512 + l16); a[92] = v.x; a[93] = v.y; a[94] = v.z; a[95] = v.w; }
                float m0[3][4], m1[3][4];
#pragma unroll
                for (int q = 0; q < 4; q++) {
#pragma unroll
                    for (int i = 0; i < 3; i++) {
                        const int k0 = (i * 8 + 2 * q) * 4;
                        if (q == 0) mma16816_z(m0[i], a[k0], a[k0 + 1], a[k0 + 2], a[k0 + 3], ob[q].x, ob[q].y);
                        else mma16816(m0[i], a[k0], a[k0 + 1], a[k0 + 2], a[k0 + 3], ob[q].x, ob[q].y);
                    }
#pragma unroll
                    for (int i = 0; i < 3; i++) {
                        const int k1 = (i * 8 + 2 * q + 1) * 4;
                        if (q == 0) mma16816_z(m1[i], a[k1], a[k1 + 1], a[k1 + 2], a[k1 + 3], ob[q].z, ob[q].w);
                        else mma16816(m1[i], a[k1], a[k1 + 1], a[k1 + 2], a[k1 + 3], ob[q].z, ob[q].w);
                    }
                }
                asm volatile("red.relaxed.gpu.global.add.noftz.v4.f16x2 [%0], {%1,%2,%3,%4};" :: "l"(reinterpret_cast<char*>(g_acc) + roff),
                    "r"(pack_f16(m0[0][0] + m1[0][0], m0[0][2] + m1[0][2])), "r"(pack_f16(m0[1][0] + m1[1][0], m0[1][2] + m1[1][2])),
                    "r"(pack_f16(m0[2][0] + m1[2][0], m0[2][2] + m1[2][2])), "r"(0x3c00u) : "memory");
                asm volatile("red.relaxed.gpu.global.add.noftz.v4.f16x2 [%0], {%1,%2,%3,%4};" :: "l"(reinterpret_cast<char*>(g_acc) + roff + 1024),
                    "r"(pack_f16(m0[0][1] + m1[0][1], m0[0][3] + m1[0][3])), "r"(pack_f16(m0[1][1] + m1[1][1], m0[1][3] + m1[1][3])),
                    "r"(pack_f16(m0[2][1] + m1[2][1], m0[2][3] + m1[2][3])), "r"(0x3c00u) : "memory");
                const unsigned t_red = clk();
                bar_arrive(5, 256);
                bar_arrive(13, 256);
                mbar_expect_if(l16 | c, sb + B_SC, 4608);
                mbar_expect_if(l16 | (c ^ 1) | (r >> 1), sb + B_VX + 8 * ((s + 1) & 1), 8192);
                sts32_if(l16 | (c ^ 3), sb + O_MISC, ebits - (14u << 23));
                if (c == 0) STAMPV(s, 8, t_red);
                if (ACC_PF && c == 2 && s + 4 < NSEG - 1)
                    asm volatile("prefetch.global.L2 [%0];" :: "l"(reinterpret_cast<const char*>(g_acc) + ((s + 4) * 96 + blockIdx.x) * 256 + (l16 & 96)) : "memory");
                const char* pbase = reinterpret_cast<const char*>(g_acc) + (s * 24576 + c * 2048) + ((l16 & 64) * 16 + (l16 & 256) + ((l16 & 128) >> 1) + (l16 & 48));
                unsigned dwait = D_WAIT;
                if (LATE) {
                    spin_until(t_red, 300);
                    const uint32_t ts = sb + O_MISC + 64 + 8 * c;
                    const float2 st2 = lds64f(ts);
                    const unsigned el = t_red - __float_as_uint(st2.x), cmin = min(el, __float_as_uint(st2.y));
                    const int extra = (int)lds32(sb + O_MISC + 96) - (int)(el - cmin) - LATE;
                    dwait += min(max(extra, 0), 1500);
                    sts64(ts, t_red + dwait, cmin);
                    if (c == 0) STAMPV(s, 11, dwait);
                }
                spin_until(t_red, dwait);
                uint4 v[6];
#pragma unroll
                for (int i = 0; i < 6; i++) v[i] = ldg_relaxed128(pbase + (i >> 1) * 8192 + (i & 1) * 512);
                int nretry = 0;
                auto convert = [&](int tau) {
                    const uint4 A = v[2 * tau], B = v[2 * tau + 1];
                    sts128(sb + O_MF + tau * 3072 + c * 512 + l16, f16x2_to_bf16x2(A.x), f16x2_to_bf16x2(B.x), f16x2_to_bf16x2(A.y), f16x2_to_bf16x2(B.y));
                    sts64(sb + O_MF + tau * 3072 + 2048 + (c >> 1) * 512 + (c & 1) * 8 + l16, f16x2_to_bf16x2(A.z), f16x2_to_bf16x2(B.z));
                };
                auto announce = [&](unsigned nominal) {
                    if (LATE) asm volatile("{\n.reg .pred p;\nsetp.eq.u32 p, %2, 0;\n@p red.relaxed.gpu.global.max.u32 [%0], %1;\n}"
                        :: "l"(reinterpret_cast<char*>(g_acc) + (s + 1) * 24576 + 128), "r"(clk() - lds32(sb + O_MISC + 64 + 8 * c) - nominal), "r"(l16) : "memory");
                };
                const uint32_t ok0 = __all_sync(~0u, (v[0].w & v[1].w) == 0x5000u);
                convert(0);
                asm volatile("{\n.reg .pred p;\nsetp.ne.u32 p, %0, 0;\n@p bar.arrive 2, 384;\n}" :: "r"(ok0) : "memory");
                if (!ok0) {
                    asm volatile("{\n.reg .pred p0, p1, q;\n.reg .u32 n, x;\nmov.u32 n, 0;\n"
                         "R_%=: setp.ne.u32 p0, %3, 0x5000;\nsetp.ne.u32 p1, %7, 0x5000;\n"
                         "@p0 ld.relaxed.gpu.global.v4.u32 {%0,%1,%2,%3}, [%9];\n@p1 ld.relaxed.gpu.global.v4.u32 {%4,%5,%6,%7}, [%9+512];\n"
                         "add.u32 %8, %8, 1;\nand.b32 x, %3, %7;\nsetp.eq.u32 q, x, 0x5000;\nvote.sync.all.pred q, q, 0xffffffff;\n@q bra.uni K_%=;\n"
                         "add.u32 n, n, 1;\nsetp.lt.u32 q, n, 2000000;\n@q bra.uni R_%=;\ntrap;\nK_%=:\n}"
                         : "+r"(v[0].x), "+r"(v[0].y), "+r"(v[0].z), "+r"(v[0].w), "+r"(v[1].x), "+r"(v[1].y), "+r"(v[1].z), "+r"(v[1].w), "+r"(nretry)
                         : "l"(pbase) : "memory");
                    convert(0);
                    bar_arrive(2, 384);
                    announce(600);
                }
                mmax = absmax2(absmax2(absmax2(v[0].x, v[0].y), absmax2(v[0].z, v[1].x)), absmax2(v[1].y, v[1].z));
                sched_fence<0>(h);
                uint32_t ok1;
                asm volatile("{\n.reg .pred p, q;\n.reg .b32 x;\nlop3.b32 x, %1, %2, %3, 0x80;\nand.b32 x, x, %4;\n"
                             "setp.eq.u32 p, x, 0x5000;\nvote.sync.all.pred q, p, 0xffffffff;\nselp.u32 %0, 1, 0, q;\n}"
                             : "=r"(ok1) : "r"(v[2].w), "r"(v[3].w), "r"(v[4].w), "r"(v[5].w));
                convert(1); convert(2);
                asm volatile("{\n.reg .pred p;\nsetp.ne.u32 p, %0, 0;\n@p bar.arrive 15, 384;\n}" :: "r"(ok1) : "memory");
                if (!ok1) {
                    asm volatile("{\n.reg .pred p2, p3, p4, p5, q;\n.reg .u32 n, x;\nmov.u32 n, 0;\n"
                         "R_%=: setp.ne.u32 p2, %3, 0x5000;\nsetp.ne.u32 p3, %7, 0x5000;\nsetp.ne.u32 p4, %11, 0x5000;\nsetp.ne.u32 p5, %15, 0x5000;\n"
                         "@p2 ld.relaxed.gpu.global.v4.u32 {%0,%1,%2,%3}, [%17+8192];\n@p3 ld.relaxed.gpu.global.v4.u32 {%4,%5,%6,%7}, [%17+8704];\n"
                         "@p4 ld.relaxed.gpu.global.v4.u32 {%8,%9,%10,%11}, [%17+16384];\n@p5 ld.relaxed.gpu.global.v4.u32 {%12,%13,%14,%15}, [%17+16896];\n"
                         "add.u32 %16, %16, 1;\nand.b32 x, %3, %7;\nand.b32 x, x, %11;\nand.b32 x, x, %15;\n"
                         "setp.eq.u32 q, x, 0x5000;\nvote.sync.all.pred q, q, 0xffffffff;\n@q bra.uni K_%=;\n"
                         "add.u32 n, n, 1;\nsetp.lt.u32 q, n, 2000000;\n@q bra.uni R_%=;\ntrap;\nK_%=:\n}"
                         : "+r"(v[2].x), "+r"(v[2].y), "+r"(v[2].z), "+r"(v[2].w), "+r"(v[3].x), "+r"(v[3].y), "+r"(v[3].z), "+r"(v[3].w),
                           "+r"(v[4].x), "+r"(v[4].y), "+r"(v[4].z), "+r"(v[4].w), "+r"(v[5].x), "+r"(v[5].y), "+r"(v[5].z), "+r"(v[5].w), "+r"(nretry)
                         : "l"(pbase) : "memory");
                    convert(1); convert(2);
                    bar_arrive(15, 384);
                    announce(880);
                }
                if (c == 0) STAMP(s, 12);
                if (c == 0) STAMPV(s, 14, nretry);
                mmax = absmax2(mmax, absmax2(absmax2(absmax2(v[2].x, v[2].y), absmax2(v[2].z, v[3].x)), absmax2(absmax2(v[3].y, v[3].z), absmax2(v[4].x, v[4].y))));
                mmax = absmax2(mmax, absmax2(absmax2(v[4].z, v[5].x), absmax2(v[5].y, v[5].z))) & 0x7fff7fffu;
                { const float2 mf = __half22float2(*reinterpret_cast<__half2*>(&mmax)); mmax = max(__float_as_uint(mf.x), __float_as_uint(mf.y)); }
            }
            roff += 24576;
        }
        {
            bar_sync(7, 384);
            if (c == 0) flag_inc_if(l16c, &g_flag[F_QKV + (4 * (NBLK - 1) + (h >> 3)) * 8]);
        }
    }
    if (warp == 8) PSTAMP(13);
    cluster_sync();
}

constexpr int NST = 10;
constexpr int G_RING = 0, G_EX = NST * 16384, G_OUT = G_EX + 32768, G_CARRY = G_OUT + 32768, G_OPS = G_CARRY + 512, G_BAR = G_OPS + 256, BG_SMEM = G_BAR + 256;
constexpr int GB_FULL = G_BAR, GB_EMPTY = G_BAR + 8 * NST, GB_W = G_BAR + 16 * NST;
static_assert(BG_SMEM <= 232448, "smem");

template <int ACC>
__device__ __forceinline__ void wgmma_n128_rs(float (&d)[64], uint32_t a0, uint32_t a1, uint32_t a2, uint32_t a3, uint64_t desc) {
    asm volatile("wgmma.mma_async.sync.aligned.m64n128k16.f32.bf16.bf16 "
        "{%0,%1,%2,%3,%4,%5,%6,%7,%8,%9,%10,%11,%12,%13,%14,%15,%16,%17,%18,%19,%20,%21,%22,%23,%24,%25,%26,%27,%28,%29,%30,%31,"
        "%32,%33,%34,%35,%36,%37,%38,%39,%40,%41,%42,%43,%44,%45,%46,%47,%48,%49,%50,%51,%52,%53,%54,%55,%56,%57,%58,%59,%60,%61,%62,%63}, "
        "{%64,%65,%66,%67}, %68, %69, 1, 1, 0;"
        : "+f"(d[0]), "+f"(d[1]), "+f"(d[2]), "+f"(d[3]), "+f"(d[4]), "+f"(d[5]), "+f"(d[6]), "+f"(d[7]),
          "+f"(d[8]), "+f"(d[9]), "+f"(d[10]), "+f"(d[11]), "+f"(d[12]), "+f"(d[13]), "+f"(d[14]), "+f"(d[15]),
          "+f"(d[16]), "+f"(d[17]), "+f"(d[18]), "+f"(d[19]), "+f"(d[20]), "+f"(d[21]), "+f"(d[22]), "+f"(d[23]),
          "+f"(d[24]), "+f"(d[25]), "+f"(d[26]), "+f"(d[27]), "+f"(d[28]), "+f"(d[29]), "+f"(d[30]), "+f"(d[31]),
          "+f"(d[32]), "+f"(d[33]), "+f"(d[34]), "+f"(d[35]), "+f"(d[36]), "+f"(d[37]), "+f"(d[38]), "+f"(d[39]),
          "+f"(d[40]), "+f"(d[41]), "+f"(d[42]), "+f"(d[43]), "+f"(d[44]), "+f"(d[45]), "+f"(d[46]), "+f"(d[47]),
          "+f"(d[48]), "+f"(d[49]), "+f"(d[50]), "+f"(d[51]), "+f"(d[52]), "+f"(d[53]), "+f"(d[54]), "+f"(d[55]),
          "+f"(d[56]), "+f"(d[57]), "+f"(d[58]), "+f"(d[59]), "+f"(d[60]), "+f"(d[61]), "+f"(d[62]), "+f"(d[63])
        : "r"(a0), "r"(a1), "r"(a2), "r"(a3), "l"(desc), "n"(ACC));
}
template <int ACC>
__device__ __forceinline__ void wgmma_n64_rs(float (&d)[64], uint32_t a0, uint32_t a1, uint32_t a2, uint32_t a3, uint64_t desc) {
    asm volatile("wgmma.mma_async.sync.aligned.m64n64k16.f32.bf16.bf16 "
        "{%0,%1,%2,%3,%4,%5,%6,%7,%8,%9,%10,%11,%12,%13,%14,%15,%16,%17,%18,%19,%20,%21,%22,%23,%24,%25,%26,%27,%28,%29,%30,%31}, "
        "{%32,%33,%34,%35}, %36, %37, 1, 1, 0;"
        : "+f"(d[0]), "+f"(d[1]), "+f"(d[2]), "+f"(d[3]), "+f"(d[4]), "+f"(d[5]), "+f"(d[6]), "+f"(d[7]),
          "+f"(d[8]), "+f"(d[9]), "+f"(d[10]), "+f"(d[11]), "+f"(d[12]), "+f"(d[13]), "+f"(d[14]), "+f"(d[15]),
          "+f"(d[16]), "+f"(d[17]), "+f"(d[18]), "+f"(d[19]), "+f"(d[20]), "+f"(d[21]), "+f"(d[22]), "+f"(d[23]),
          "+f"(d[24]), "+f"(d[25]), "+f"(d[26]), "+f"(d[27]), "+f"(d[28]), "+f"(d[29]), "+f"(d[30]), "+f"(d[31])
        : "r"(a0), "r"(a1), "r"(a2), "r"(a3), "l"(desc), "n"(ACC));
}
__device__ __forceinline__ void wait_flag(const unsigned* p, unsigned target) {
    asm volatile("{\n.reg .pred p;\n.reg .u32 n, v;\nmov.u32 n, 0;\n"
                 "W_%=: ld.acquire.gpu.global.u32 v, [%0];\nsub.u32 v, v, %1;\nsetp.ge.s32 p, v, 0;\n@p bra.uni D_%=;\nnanosleep.u32 " NSLEEP ";\n"
                 "add.u32 n, n, 1;\nsetp.lt.u32 p, n, 4000000;\n@p bra.uni W_%=;\ntrap;\nD_%=:\n}" :: "l"(p), "r"(target) : "memory");
}
template <int NS, int NT>
__device__ __forceinline__ void bg_mainloop(float (&d)[64], const uint32_t (&a)[144], uint32_t sb, int it, int lane) {
    int slot = it % NST, ph = (it / NST) & 1, prev = 0;
#pragma unroll
    for (int i = 0; i < NS; i++) {
        mbar_wait(sb + GB_FULL + 8 * slot, ph);
        const uint64_t desc = (uint64_t)(((sb + G_RING + slot * 16384) & 0x3FFFF) >> 4) | (1ull << 16) | (64ull << 32) | (1ull << 62);
        wg_fence();
#pragma unroll
        for (int k = 0; k < 512 / NT; k++) {
            const int u = (2048 / NT) * i + 4 * k;
            if (NT == 128) {
                if (i == 0 && k == 0) wgmma_n128_rs<0>(d, a[u], a[u + 1], a[u + 2], a[u + 3], desc);
                else wgmma_n128_rs<1>(d, a[u], a[u + 1], a[u + 2], a[u + 3], desc + 2 * k);
            } else {
                if (i == 0 && k == 0) wgmma_n64_rs<0>(d, a[u], a[u + 1], a[u + 2], a[u + 3], desc);
                else wgmma_n64_rs<1>(d, a[u], a[u + 1], a[u + 2], a[u + 3], desc + 2 * (k & 3) + (k >> 2) * 512);
            }
        }
        wg_commit();
        if (i > 0) {
            asm volatile("wgmma.wait_group.sync.aligned 1;" ::: "memory");
            mbar_arrive_if(lane, sb + GB_EMPTY + 8 * prev);
        }
        prev = slot;
        slot += 2;
        if (slot >= NST) { slot -= NST; ph ^= 1; }
    }
    wg_wait0();
    mbar_arrive_if(lane, sb + GB_EMPTY + 8 * prev);
}
template <bool SKIP, int NT>
__device__ __forceinline__ void bg_epilogue(float (&d)[64], uint32_t sb, int wg, int w, int lane, const CUtensorMap* tm_out, int col0, int tok0,
                                            const __nv_bfloat16* xa, const __nv_bfloat16* Dk) {
    constexpr int H = NT / 4;
    const int g = lane >> 2, t = lane & 3;
    const uint32_t ex = sb + G_EX + w * 4096 + lane * 16;
    float k[H];
    if (wg == 0) {
#pragma unroll
        for (int q = 0; q < H / 4; q++) sts128f(ex + q * 512, d[H + 4 * q], d[H + 4 * q + 1], d[H + 4 * q + 2], d[H + 4 * q + 3]);
#pragma unroll
        for (int i = 0; i < H; i++) k[i] = d[i];
    } else {
#pragma unroll
        for (int q = 0; q < H / 4; q++) sts128f(ex + 16384 + q * 512, d[4 * q], d[4 * q + 1], d[4 * q + 2], d[4 * q + 3]);
#pragma unroll
        for (int i = 0; i < H; i++) k[i] = d[H + i];
    }
    uint32_t xv[16], dv = 0;
    if (SKIP) {
        const __nv_bfloat16* xp = xa + (size_t)(tok0 + 64 * wg + 2 * t) * DM + col0 + 16 * w + 2 * g;
#pragma unroll
        for (int i = 0; i < 16; i++) xv[i] = ldg_nc32(xp + (8 * (i >> 1) + (i & 1)) * DM);
        dv = ldg_nc32(Dk + col0 + 16 * w + 2 * g);
    }
    if (SKIP && w == 0) asm volatile("cp.async.bulk.wait_group.read 0;" ::: "memory");
    bar_sync(1, 256);
#pragma unroll
    for (int q = 0; q < H / 4; q++) {
        const float4 o = lds128f(ex + (wg ^ 1) * 16384 + q * 512);
        k[4 * q] += o.x; k[4 * q + 1] += o.y; k[4 * q + 2] += o.z; k[4 * q + 3] += o.w;
    }
    if (SKIP) bar_sync(1, 256); else bar_sync(13, 288);
    const uint32_t ob = sb + G_OUT + wg * (NT == 128 ? 16384 : 4096) + (w >> 1) * 8192 + (g & 1) * 8;
    const uint32_t ch = (w & 1) * 4 + (g >> 1);
#pragma unroll
    for (int i = 0; i < H / 2; i++) {
        float v0 = k[4 * (i >> 1) + (i & 1)], v1 = k[4 * (i >> 1) + 2 + (i & 1)];
        if (SKIP) {
            const uint32_t p = pack_bf16(__uint_as_float(xv[i] << 16) * __uint_as_float(dv << 16), __uint_as_float(xv[i] & 0xffff0000u) * __uint_as_float(dv & 0xffff0000u));
            v0 += __uint_as_float(p << 16); v1 += __uint_as_float(p & 0xffff0000u);
        }
        const uint32_t n7 = 2 * t + (i & 1);
        sts64(ob + (8 * (i >> 1) + n7) * 128 + ((ch ^ n7) << 4), __float_as_uint(v0), __float_as_uint(v1));
    }
    fence_async_smem();
    if (SKIP) {
        bar_sync(4 + wg, 128);
        if (w == 0)
            asm volatile("{\n.reg .pred p;\nelect.sync _|p, 0xffffffff;\n"
                "@p cp.async.bulk.tensor.2d.global.shared::cta.bulk_group [%0, {%2, %4}], [%1];\n"
                "@p cp.async.bulk.tensor.2d.global.shared::cta.bulk_group [%0, {%3, %4}], [%1+8192];\n@p cp.async.bulk.commit_group;\n}"
                :: "l"(tm_out), "r"(sb + G_OUT + wg * 16384), "r"(col0), "r"(col0 + 32), "r"(tok0 + 64 * wg) : "memory");
    } else {
        bar_arrive(12, 288);
    }
}
__device__ __forceinline__ void s5_channel(int p, const __nv_bfloat16* Lre, const __nv_bfloat16* Lim, const __nv_bfloat16* logdt, float2& lam, float2& coef) {
    const float dt = __bfloat162float(__float2bfloat16(expf(__bfloat162float(logdt[p]))));
    const float lr = __bfloat162float(Lre[p]), li = __bfloat162float(Lim[p]);
    const float e = expf(dt * lr);
    float sn, cs;
    sincosf(dt * li, &sn, &cs);
    lam = make_float2(e * cs, e * sn);
    const float den = lr * lr + li * li;
    coef = make_float2(((lam.x - 1.f) * lr + lam.y * li) / den, (lam.y * lr - (lam.x - 1.f) * li) / den);
}
__device__ __forceinline__ float2 cfma(float2 a, float2 b, float2 c) {
    return make_float2(fmaf(a.x, b.x, fmaf(-a.y, b.y, c.x)), fmaf(a.x, b.y, fmaf(a.y, b.x, c.y)));
}
__device__ __forceinline__ uint4 ldg128(const void* p) { uint4 v; asm volatile("ld.global.v4.u32 {%0,%1,%2,%3}, [%4];" : "=r"(v.x), "=r"(v.y), "=r"(v.z), "=r"(v.w) : "l"(p) : "memory"); return v; }
__device__ __forceinline__ uint2 ldg64(const void* p) { uint2 v; asm volatile("ld.global.v2.u32 {%0,%1}, [%2];" : "=r"(v.x), "=r"(v.y) : "l"(p) : "memory"); return v; }

template <int MT>
__device__ __forceinline__ void bg_attention(uint32_t st0, uint32_t st1, int lane) {
    constexpr int NK = MT ? 5 : 3;
    const int g = lane >> 2, t = lane & 3;
    float sc[NK][4], sm2[4];
#pragma unroll
    for (int i = 0; i < 8; i++) {
        const uint32_t st = (i >> 2 ? st1 : st0) + (i & 3) * 512 + lane * 16;
        const uint4 q = ldsm4(st + MT * 2048), km = ldsm4(st + 8192), k0 = ldsm4(st + 4096);
        if (i == 0) {
            mma16816_z(sc[0], q.x, q.y, q.z, q.w, km.x, km.y); mma16816_z(sm2, q.x, q.y, q.z, q.w, km.z, km.w);
            mma16816_z(sc[1], q.x, q.y, q.z, q.w, k0.x, k0.y); mma16816_z(sc[2], q.x, q.y, q.z, q.w, k0.z, k0.w);
        } else {
            mma16816(sc[0], q.x, q.y, q.z, q.w, km.x, km.y); mma16816(sm2, q.x, q.y, q.z, q.w, km.z, km.w);
            mma16816(sc[1], q.x, q.y, q.z, q.w, k0.x, k0.y); mma16816(sc[2], q.x, q.y, q.z, q.w, k0.z, k0.w);
        }
        if (MT) {
            const uint4 k1 = ldsm4(st + 6144);
            if (i == 0) { mma16816_z(sc[NK - 2], q.x, q.y, q.z, q.w, k1.x, k1.y); mma16816_z(sc[NK - 1], q.x, q.y, q.z, q.w, k1.z, k1.w); }
            else { mma16816(sc[NK - 2], q.x, q.y, q.z, q.w, k1.x, k1.y); mma16816(sc[NK - 1], q.x, q.y, q.z, q.w, k1.z, k1.w); }
        }
    }
#pragma unroll
    for (int i = 0; i < 4; i++) sc[0][i] += sm2[i];
    if (2 * t > g) { sc[NK - 2][0] = -INFINITY; sc[NK - 1][2] = -INFINITY; }
    if (2 * t + 1 > g) { sc[NK - 2][1] = -INFINITY; sc[NK - 1][3] = -INFINITY; }
    sc[NK - 1][0] = sc[NK - 1][1] = -INFINITY;
    float ma = fmaxf(sc[0][0], sc[0][1]), mb = fmaxf(sc[0][2], sc[0][3]);
#pragma unroll
    for (int n = 1; n < NK; n++) { ma = fmaxf(ma, fmaxf(sc[n][0], sc[n][1])); mb = fmaxf(mb, fmaxf(sc[n][2], sc[n][3])); }
    ma = quad_max(ma) * SM_SCALE; mb = quad_max(mb) * SM_SCALE;
    uint32_t Pa[NK], Pb[NK];
#pragma unroll
    for (int n = 0; n < NK; n++) {
        Pa[n] = n == NK - 1 ? 0u : pack_bf16(ex2(fmaf(sc[n][0], SM_SCALE, -ma)), ex2(fmaf(sc[n][1], SM_SCALE, -ma)));
        Pb[n] = pack_bf16(ex2(fmaf(sc[n][2], SM_SCALE, -mb)), ex2(fmaf(sc[n][3], SM_SCALE, -mb)));
    }
    float sa[4], sbb[4];
    mma1688_z(sa, ONES, ONES, Pa[0]); mma1688_z(sbb, ONES, ONES, Pb[0]);
    mma16816(sa, ONES, ONES, ONES, ONES, Pa[1], Pa[2]); mma16816(sbb, ONES, ONES, ONES, ONES, Pb[1], Pb[2]);
    if (MT) { mma16816(sa, ONES, ONES, ONES, ONES, Pa[NK - 2], Pa[NK - 1]); mma16816(sbb, ONES, ONES, ONES, ONES, Pb[NK - 2], Pb[NK - 1]); }
    const float ra0 = rcp_fast(sa[0]), ra1 = rcp_fast(sa[1]), rb0 = rcp_fast(sbb[0]), rb1 = rcp_fast(sbb[1]);
    const uint32_t row = lane & 7;
    const uint32_t so = MT * 2048 + (lane >> 4) * 1024 + row * 128;
#pragma unroll
    for (int eh = 0; eh < 2; eh++) {
        const uint32_t st = eh ? st1 : st0;
        float2 vm[4]; uint4 v0[4], v1[4];
#pragma unroll
        for (int e4 = 0; e4 < 4; e4++) {
            vm[e4] = lds64f(st + 14336 + e4 * 256 + lane * 8);
            v0[e4] = lds128(st + 10240 + e4 * 1024 + lane * 16);
            if (MT) v1[e4] = lds128(st + 10240 + e4 * 1024 + 512 + lane * 16);
        }
        float oa[4][4], ob[4][4];
#pragma unroll
        for (int e4 = 0; e4 < 4; e4++) {
            mma1688_z(oa[e4], __float_as_uint(vm[e4].x), __float_as_uint(vm[e4].y), Pa[0]);
            mma1688_z(ob[e4], __float_as_uint(vm[e4].x), __float_as_uint(vm[e4].y), Pb[0]);
        }
#pragma unroll
        for (int e4 = 0; e4 < 4; e4++) {
            mma16816(oa[e4], v0[e4].x, v0[e4].y, v0[e4].z, v0[e4].w, Pa[1], Pa[2]);
            mma16816(ob[e4], v0[e4].x, v0[e4].y, v0[e4].z, v0[e4].w, Pb[1], Pb[2]);
        }
        if (MT) {
#pragma unroll
            for (int e4 = 0; e4 < 4; e4++) {
                mma16816(oa[e4], v1[e4].x, v1[e4].y, v1[e4].z, v1[e4].w, Pa[NK - 2], Pa[NK - 1]);
                mma16816(ob[e4], v1[e4].x, v1[e4].y, v1[e4].z, v1[e4].w, Pb[NK - 2], Pb[NK - 1]);
            }
        }
#pragma unroll
        for (int e4 = 0; e4 < 4; e4++)
            stsm4t(st + so + (((2 * e4 + ((lane >> 3) & 1)) ^ row) << 4), pack_bf16(oa[e4][0] * ra0, oa[e4][1] * ra1), pack_bf16(oa[e4][2] * ra0, oa[e4][3] * ra1),
                   pack_bf16(ob[e4][0] * rb0, ob[e4][1] * rb1), pack_bf16(ob[e4][2] * rb0, ob[e4][3] * rb1));
    }
}
__device__ __forceinline__ bool wait_either(const unsigned* pa, unsigned ta, bool allow_a, const unsigned* pg, unsigned tg, bool allow_g) {
    uint32_t res;
    asm volatile("{\n.reg .pred p, qa, qg;\n.reg .u32 n, v, u;\nmov.u32 n, 0;\nsetp.ne.u32 qa, %5, 0;\nsetp.ne.u32 qg, %6, 0;\n"
                 "W_%=: mov.u32 %0, 1;\n@!qa bra.uni G_%=;\nld.acquire.gpu.global.u32 v, [%1];\nsub.u32 v, v, %2;\nsetp.ge.s32 p, v, 0;\n@p bra.uni D_%=;\n"
                 "G_%=: mov.u32 %0, 0;\n@!qg bra.uni S_%=;\nld.acquire.gpu.global.u32 u, [%3];\nsub.u32 u, u, %4;\nsetp.ge.s32 p, u, 0;\n@p bra.uni D_%=;\nS_%=: "
                 "nanosleep.u32 " NSLEEP ";\nadd.u32 n, n, 1;\nsetp.lt.u32 p, n, 4000000;\n@p bra.uni W_%=;\ntrap;\n"
                 "D_%=: fence.proxy.async.global;\n}"
                 : "=r"(res) : "l"(pa), "r"(ta), "l"(pg), "r"(tg), "r"((uint32_t)allow_a), "r"((uint32_t)allow_g) : "memory");
    return res != 0;
}

__global__ void __launch_bounds__(384, 1)
bg_kernel(const __grid_constant__ CUtensorMap tm_xa, const __grid_constant__ CUtensorMap tm_wo, const __grid_constant__ CUtensorMap tm_out,
          const __nv_bfloat16* __restrict__ xa, const __nv_bfloat16* __restrict__ Lre, const __nv_bfloat16* __restrict__ Lim,
          const __nv_bfloat16* __restrict__ Bre, const __nv_bfloat16* __restrict__ Bim, const __nv_bfloat16* __restrict__ Cre,
          const __nv_bfloat16* __restrict__ Cim, const __nv_bfloat16* __restrict__ logdt, const __nv_bfloat16* __restrict__ Dk, float* __restrict__ out) {
    extern __shared__ __align__(1024) uint8_t smem_raw[];
    const uint32_t sb = smem_u32(smem_raw);
    const int lane = threadIdx.x & 31;
    const int warp = __shfl_sync(~0u, threadIdx.x >> 5, 0);
    const int wg = warp >> 2, w = warp & 3, b = blockIdx.x;
    const int nt = b % 9, kq = b / 9;
    BSTAMP(0);
    if (threadIdx.x == 0) {
        if (sb & 1023u) __trap();
        for (int i = 0; i < NST; i++) { mbar_init(sb + GB_FULL + 8 * i, 1); mbar_init(sb + GB_EMPTY + 8 * i, 4); }
        mbar_init(sb + GB_W, 1);
        asm volatile("fence.mbarrier_init.release.cluster;" ::: "memory");
        mbar_expect(sb + GB_W, (b < 18 ? 64 : 128) * 1152);
        sts32(sb + G_BAR + 248, atomicAdd(&g_ticket_bg, 1u) / 36u + 1u);
    }
    __syncthreads();
    if (wg == 2) {
        asm volatile("setmaxnreg.dec.sync.aligned.u32 24;");
        if (w == 0) {
            int slot = 0, ph = 1;
            auto next = [&]() { if (++slot == NST) { slot = 0; ph ^= 1; } };
            bar_sync(6, 288);
            if (b < 18) {
#pragma unroll 1
                for (int i = 0; i < 144; i++) {
                    const int blk = i / 9, kb = i - 9 * blk, it = (blk >> 1) * 18 + (blk & 1) + 2 * kb;
                    slot = it % NST;
                    mbar_wait(sb + GB_EMPTY + 8 * slot, ((it / NST) & 1) ^ 1);
                    asm volatile("{\n.reg .pred p;\nelect.sync _|p, 0xffffffff;\n@p mbarrier.arrive.expect_tx.shared::cta.b64 _, [%2], 16384;\n"
                        "@p cp.async.bulk.tensor.5d.shared::cluster.global.mbarrier::complete_tx::bytes [%0], [%1, {%3, %4, %4, %4, %5}], [%2];\n}"
                        :: "r"(sb + G_RING + slot * 16384), "l"(&tm_xa), "r"(sb + GB_FULL + 8 * slot), "r"(kb * 64), "r"(0), "r"(blk) : "memory");
                }
                slot = 144 % NST; ph = ((144 / NST) & 1) ^ 1;
            }
            const unsigned ep = lds32(sb + G_BAR + 248);
            auto slabs = [&](const char* src, int ns) {
                asm volatile("fence.proxy.async.global;" ::: "memory");
#pragma unroll 1
                for (int i = 0; i < ns; i++) {
                    mbar_wait(sb + GB_EMPTY + 8 * slot, ph);
                    asm volatile("{\n.reg .pred p;\nelect.sync _|p, 0xffffffff;\n@p mbarrier.arrive.expect_tx.shared::cta.b64 _, [%2], 16384;\n"
                        "@p cp.async.bulk.shared::cluster.global.mbarrier::complete_tx::bytes [%0], [%1], 16384, [%2];\n}"
                        :: "r"(sb + G_RING + slot * 16384), "l"(src + (size_t)((i & 1) * (ns >> 1) + (i >> 1)) * (SEQ * 128)), "r"(sb + GB_FULL + 8 * slot) : "memory");
                    next();
                }
            };
            if (b >= 18) {
#pragma unroll 1
                for (int blk = kq - 2; blk < 16; blk += 2) {
                    wait_flag(&g_flag[F_H + blk * 8], 18 * ep);
                    slabs(reinterpret_cast<const char*>(g_h) + blk * 16384, 18);
                }
            }
            bar_sync(6, 288);
#pragma unroll 1
            for (int na = nt < 8 ? 0 : NBLK, ng = 0, k = 0; ng < NBLK; k++) {
                const bool att = wait_either(&g_flag[F_QKV + (min(na, NBLK - 1) * 4 + kq) * 8], 24 * ep, na < NBLK && na <= ng + 1,
                                             &g_flag[F_OX + (ng * 4 + kq) * 8], 8 * ep, ng < na);
                sts32_if(lane, sb + G_OPS + 4 * k, att);
                __syncwarp();
                if (att) {
                    {
#pragma unroll 1
                        for (int i = 0; i < (na < NBIG ? 8 : 4); i++) {
                            const int hf = (i >> 1) & 1;
                            const char* rec = reinterpret_cast<const char*>(g_qkv) + (size_t)((blk_seg0(na) + 2 * (i >> 2) + (i & 1)) * NH + 8 * kq + nt) * REC;
                            mbar_wait(sb + GB_EMPTY + 8 * slot, ph);
                            asm volatile("{\n.reg .pred p;\nelect.sync _|p, 0xffffffff;\n@p mbarrier.arrive.expect_tx.shared::cta.b64 _, [%4], 15360;\n"
                                "@p cp.async.bulk.shared::cluster.global.mbarrier::complete_tx::bytes [%0], [%1], 10240, [%4];\n"
                                "@p cp.async.bulk.shared::cluster.global.mbarrier::complete_tx::bytes [%0+10240], [%2], 4096, [%4];\n"
                                "@p cp.async.bulk.shared::cluster.global.mbarrier::complete_tx::bytes [%0+14336], [%3], 1024, [%4];\n}"
                                :: "r"(sb + G_RING + slot * 16384), "l"(rec + hf * 10240), "l"(rec + 20480 + hf * 4096), "l"(rec + 28672 + hf * 1024),
                                   "r"(sb + GB_FULL + 8 * slot) : "memory");
                            next();
                        }
                    }
                    na++;
                } else {
                    const char* src = reinterpret_cast<const char*>(g_ox) + (size_t)kq * 16 * SEQ * 128 + blk_seg0(ng) * 4096;
                    if (ng < NBIG) slabs(src, 16);
                    else {
#pragma unroll 1
                        for (int i = 0; i < 8; i++) {
                            mbar_wait(sb + GB_EMPTY + 8 * slot, ph);
                            asm volatile("{\n.reg .pred p;\nelect.sync _|p, 0xffffffff;\n@p mbarrier.arrive.expect_tx.shared::cta.b64 _, [%2], 16384;\n"
                                "@p cp.async.bulk.shared::cluster.global.mbarrier::complete_tx::bytes [%0], [%1], 8192, [%2];\n"
                                "@p cp.async.bulk.shared::cluster.global.mbarrier::complete_tx::bytes [%0+8192], [%1+262144], 8192, [%2];\n}"
                                :: "r"(sb + G_RING + slot * 16384), "l"(src + (size_t)((i & 1) * 8 + (i & 6)) * (SEQ * 128)), "r"(sb + GB_FULL + 8 * slot) : "memory");
                            next();
                        }
                    }
                    ng++;
                }
            }
        } else if (w == 1) {
            if (b < 18) {
#pragma unroll 1
                for (int blk = 0; blk < 16; blk++) {
                    bar_sync(8 + (blk & 1), 160);
                    asm volatile("{\n.reg .pred p;\nelect.sync _|p, 0xffffffff;\n@p cp.async.bulk.global.shared::cta.bulk_group [%0], [%1], 16384;\n"
                        "@p cp.async.bulk.commit_group;\ncp.async.bulk.wait_group 0;\nfence.proxy.async.global;\n}"
                        :: "l"(reinterpret_cast<char*>(g_h) + ((size_t)b * SEQ + blk * 128) * 128), "r"(sb + G_OUT + (blk & 1) * 16384) : "memory");
                    bar_arrive(10 + (blk & 1), 160);
                    flag_inc_if(lane, &g_flag[F_H + blk * 8]);
                }
            }
            if (nt < 8) {
#pragma unroll 1
                for (int na = 0; na < NBLK; na++) {
                    {
                        const int ns = na < NBIG ? 8 : 4;
                        bar_sync(7, 288);
                        const int it = lds32(sb + G_OPS + 252);
                        if (lane < ns) {
                            asm volatile("cp.async.bulk.global.shared::cta.bulk_group [%0], [%1], 4096;\ncp.async.bulk.commit_group;\ncp.async.bulk.wait_group.read 0;\n"
                                "mbarrier.arrive.shared::cta.b64 _, [%2], 4;\ncp.async.bulk.wait_group 0;\nfence.proxy.async.global;"
                                :: "l"(reinterpret_cast<char*>(g_ox) + ((size_t)((8 * kq + nt) * 2 + ((lane >> 1) & 1)) * SEQ + (blk_seg0(na) + 2 * (lane >> 2) + (lane & 1)) * 32) * 128),
                                   "r"(sb + G_RING + ((it + lane) % NST) * 16384), "r"(sb + GB_EMPTY + 8 * ((it + lane) % NST)) : "memory");
                        }
                        __syncwarp();
                        bar_arrive(14, 288);
                        flag_inc_if(lane, &g_flag[F_OX + (na * 4 + kq) * 8]);
                    }
                }
            }
        } else if (w == 2) {
            const unsigned ep = lds32(sb + G_BAR + 248);
#pragma unroll 1
            for (int blk = 0; blk < NBLK; blk++) {
                const bool last = blk == NBLK - 1, add = kq || last;
                bar_arrive(13, 288);
                bar_sync(12, 288);
                if (add) { wait_flag(&g_flag[F_OUT + (blk * 9 + nt) * 8], ep); asm volatile("fence.proxy.async.global;" ::: "memory"); }
#pragma unroll 1
                for (int i = 0; i < (blk < NBIG ? 4 : 2); i++) {
                    const uint32_t src = sb + G_OUT + i * 8192;
                    const int c0 = DM + 64 * nt + (i & 1) * 32, c1 = blk_seg0(blk) * 32 + (i >> 1) * 64;
                    if (add) asm volatile("{\n.reg .pred p;\nelect.sync _|p, 0xffffffff;\n@p cp.reduce.async.bulk.tensor.2d.global.shared::cta.add.bulk_group [%0, {%2, %3}], [%1];\n}"
                                 :: "l"(&tm_out), "r"(src), "r"(c0), "r"(c1) : "memory");
                    else asm volatile("{\n.reg .pred p;\nelect.sync _|p, 0xffffffff;\n@p cp.async.bulk.tensor.2d.global.shared::cta.bulk_group [%0, {%2, %3}], [%1];\n}"
                                 :: "l"(&tm_out), "r"(src), "r"(c0), "r"(c1) : "memory");
                    if (add && blk < NBIG - 1) spin_until(clk(), RED_GAP);
                }
                asm volatile("cp.async.bulk.commit_group;\ncp.async.bulk.wait_group 0;\nfence.proxy.async.global;" ::: "memory");
                __syncwarp();
                if (!add) flag_inc_if(lane, &g_flag[F_OUT + (blk * 9 + nt) * 8]);
                if (!kq && blk == NBLK - 4) {
                    float4* z = reinterpret_cast<float4*>(out + (size_t)(SEQ - 64 + (lane >> 4)) * (2 * DM) + DM + 64 * nt) + (lane & 15);
#pragma unroll 1
                    for (int i = 0; i < 32; i++) z[i * (4 * DM / 4)] = make_float4(0.f, 0.f, 0.f, 0.f);
                    __syncwarp();
                    flag_inc_if(lane, &g_flag[F_OUT + ((NBLK - 1) * 9 + nt) * 8]);
                }
            }
        }
    } else {
        asm volatile("setmaxnreg.inc.sync.aligned.u32 240;");
        const int g = lane >> 2, t = lane & 3, tid = threadIdx.x;
        uint32_t a[144];
        float d[64];
        if (b < 18) {
            if (tid < 64)
                asm volatile("cp.async.bulk.shared::cluster.global.mbarrier::complete_tx::bytes [%0], [%1], 1152, [%2];"
                    :: "r"(sb + tid * 1168), "l"((tid < 32 ? Bre : Bim) + (size_t)(32 * b + (tid & 31)) * DM), "r"(sb + GB_W) : "memory");
            float2 lam, coef;
            s5_channel(32 * b + 8 * w + g, Lre, Lim, logdt, lam, coef);
            float2 l32 = lam;
#pragma unroll
            for (int i = 0; i < 5; i++) l32 = make_float2(l32.x * l32.x - l32.y * l32.y, 2.f * l32.x * l32.y);
            __syncwarp();
            mbar_wait(sb + GB_W, 0);
            const uint32_t ap = sb + (((lane >> 3) & 1) * 32 + 8 * w + (lane & 7)) * 1168 + (lane >> 4) * 16;
#pragma unroll
            for (int ks = 0; ks < 36; ks++) { const uint4 v = ldsm4(ap + ks * 32); a[4 * ks] = v.x; a[4 * ks + 1] = v.y; a[4 * ks + 2] = v.z; a[4 * ks + 3] = v.w; }
            bar_sync(1, 256);
            bar_arrive(6, 288);
            BSTAMP(1);
#pragma unroll 1
            for (int blk = wg; blk < 16; blk += 2) {
                bg_mainloop<9, 128>(d, a, sb, (blk >> 1) * 18 + wg, lane);
                float2 e = make_float2(0.f, 0.f);
#pragma unroll
                for (int i = 0; i < 32; i++) e = cfma(lam, e, make_float2(d[4 * (i >> 1) + (i & 1)], d[4 * (i >> 1) + 2 + (i & 1)]));
                float2 cin = make_float2(0.f, 0.f);
                if (blk > 0) { bar_sync(2 + (wg ^ 1), 256); cin = lds64f(sb + G_CARRY + (wg ^ 1) * 256 + (8 * w + g) * 8); }
                float2 mine = cin;
#pragma unroll
                for (int q = 0; q < 4; q++) {
                    const float2 eq = make_float2(__shfl_sync(~0u, e.x, (lane & 28) + q), __shfl_sync(~0u, e.y, (lane & 28) + q));
                    cin = cfma(l32, cin, eq);
                    if (t == q + 1) mine = cin;
                }
                if (blk < 15) {
                    if (t == 0) sts64(sb + G_CARRY + wg * 256 + (8 * w + g) * 8, __float_as_uint(cin.x), __float_as_uint(cin.y));
                    bar_arrive(2 + wg, 256);
                }
                const uint32_t hs = sb + G_OUT + wg * 16384 + t * 4096 + (g & 3) * 4;
                const uint32_t ch = 2 * w + (g >> 2);
                if (blk >= 2) bar_sync(10 + wg, 160);
#pragma unroll
                for (int i = 0; i < 32; i++) {
                    mine = cfma(lam, mine, make_float2(d[4 * (i >> 1) + (i & 1)], d[4 * (i >> 1) + 2 + (i & 1)]));
                    sts32(hs + i * 128 + ((ch ^ (i & 7)) << 4), pack_bf16(mine.x, mine.y));
                }
                fence_async_smem();
                bar_arrive(8 + wg, 160);
            }
            bar_sync(10 + wg, 160);
        } else {
            if (tid < 128)
                asm volatile("cp.async.bulk.shared::cluster.global.mbarrier::complete_tx::bytes [%0], [%1], 1152, [%2];"
                    :: "r"(sb + tid * 1168), "l"((tid < 64 ? Cre : Cim) + (size_t)(64 * nt + (tid & 63)) * DM), "r"(sb + GB_W) : "memory");
            for (int p = tid; p < DM; p += 256) {
                float2 lam, coef;
                s5_channel(p, Lre, Lim, logdt, lam, coef);
                sts64(sb + G_EX + p * 8, __float_as_uint(2.f * coef.x), __float_as_uint(2.f * coef.y));
            }
            bar_sync(1, 256);
            mbar_wait(sb + GB_W, 0);
            const uint32_t cp = sb + (16 * w + 2 * g) * 1168 + (288 * wg + t) * 2;
#pragma unroll
            for (int u = 0; u < 72; u++) {
                const float2 c2 = lds64f(sb + G_EX + (288 * wg + 4 * u + t) * 8);
#pragma unroll
                for (int f = 0; f < 2; f++) {
                    unsigned short r16, i16;
                    asm volatile("ld.shared.u16 %0, [%1];" : "=h"(r16) : "r"(cp + f * 1168 + u * 8) : "memory");
                    asm volatile("ld.shared.u16 %0, [%1];" : "=h"(i16) : "r"(cp + (64 + f) * 1168 + u * 8) : "memory");
                    const float cr = __uint_as_float((uint32_t)r16 << 16), ci = __uint_as_float((uint32_t)i16 << 16);
                    a[2 * u + f] = pack_bf16(cr * c2.x - ci * c2.y, -(cr * c2.y + ci * c2.x));
                }
            }
            bar_sync(1, 256);
            bar_arrive(6, 288);
            BSTAMP(1);
#pragma unroll 1
            for (int j = 0; j < 8; j++) {
                bg_mainloop<9, 128>(d, a, sb, j * 18 + wg, lane);
                bg_epilogue<true, 128>(d, sb, wg, w, lane, &tm_out, 64 * nt, (2 * j + kq - 2) * 128, xa, Dk);
            }
        }
        if (w == 0) asm volatile("cp.async.bulk.wait_group 0;" ::: "memory");
        bar_sync(1, 256);
        BSTAMP(2);
        if (warp == 0)
            asm volatile("{\n.reg .pred p;\nelect.sync _|p, 0xffffffff;\n@p mbarrier.arrive.expect_tx.shared::cta.b64 _, [%2], 131072;\n"
                "@p cp.async.bulk.tensor.2d.shared::cluster.global.mbarrier::complete_tx::bytes [%0], [%1, {%3, %4}], [%2];\n"
                "@p cp.async.bulk.tensor.2d.shared::cluster.global.mbarrier::complete_tx::bytes [%0+32768], [%1, {%3, %5}], [%2];\n"
                "@p cp.async.bulk.tensor.2d.shared::cluster.global.mbarrier::complete_tx::bytes [%0+65536], [%1, {%3, %6}], [%2];\n"
                "@p cp.async.bulk.tensor.2d.shared::cluster.global.mbarrier::complete_tx::bytes [%0+98304], [%1, {%3, %7}], [%2];\n}"
                :: "r"(sb), "l"(&tm_wo), "r"(sb + GB_W), "r"(64 * nt), "r"(1024 * kq), "r"(1024 * kq + 256), "r"(1024 * kq + 512), "r"(1024 * kq + 768) : "memory");
        mbar_wait(sb + GB_W, 1);
        {
            const uint32_t base = sb + wg * 65536 + 4 * t * 128 + (g & 3) * 4, ch = 2 * w + (g >> 2), r7 = (4 * t) & 7;
#pragma unroll
            for (int ks = 0; ks < 32; ks++) {
                const uint32_t w0 = lds32(base + ks * 2048 + ((ch ^ r7) << 4)), w1 = lds32(base + ks * 2048 + 256 + ((ch ^ (r7 + 2)) << 4));
                const uint32_t w2 = lds32(base + ks * 2048 + 128 + ((ch ^ (r7 + 1)) << 4)), w3 = lds32(base + ks * 2048 + 384 + ((ch ^ (r7 + 3)) << 4));
                a[4 * ks] = __byte_perm(w0, w1, 0x5410); a[4 * ks + 1] = __byte_perm(w0, w1, 0x7632);
                a[4 * ks + 2] = __byte_perm(w2, w3, 0x5410); a[4 * ks + 3] = __byte_perm(w2, w3, 0x7632);
            }
        }
        bar_sync(1, 256);
        bar_arrive(6, 288);
        BSTAMP(3);
#pragma unroll 1
        for (int na = 0, ng = 0, it = 144, k = 0; ng < NBLK; k++) {
            mbar_wait(sb + GB_FULL + 8 * ((it + wg) % NST), ((it + wg) / NST) & 1);
            if (__shfl_sync(~0u, lds32(sb + G_OPS + 4 * k), 0)) {
                {
                    if (na < NBIG || (w >> 1) == wg) {
                        const int i0 = it + wg + (na < NBIG ? 4 * (w >> 1) : 0), i1 = i0 + 2;
                        mbar_wait(sb + GB_FULL + 8 * (i0 % NST), (i0 / NST) & 1);
                        mbar_wait(sb + GB_FULL + 8 * (i1 % NST), (i1 / NST) & 1);
                        BSTAMP(8 + na * 4);
                        if ((w ^ wg) & 1) bg_attention<1>(sb + G_RING + (i0 % NST) * 16384, sb + G_RING + (i1 % NST) * 16384, lane);
                        else bg_attention<0>(sb + G_RING + (i0 % NST) * 16384, sb + G_RING + (i1 % NST) * 16384, lane);
                        fence_async_smem();
                    }
                    if (na > 0) bar_sync(14, 288);
                    if (tid == 0) sts32(sb + G_OPS + 252, it);
                    bar_arrive(7, 288);
                    bar_sync(1, 256);
                    BSTAMP(9 + na * 4);
                    it += na < NBIG ? 8 : 4;
                }
                na++;
            } else if (ng < NBIG) {
                bg_mainloop<8, 128>(d, a, sb, it + wg, lane);
                BSTAMP(10 + ng * 4);
                bg_epilogue<false, 128>(d, sb, wg, w, lane, &tm_out, 0, 0, xa, Dk);
                BSTAMP(11 + ng * 4);
                it += 16; ng++;
            } else {
                bg_mainloop<4, 64>(d, a, sb, it + wg, lane);
                BSTAMP(10 + ng * 4);
                bg_epilogue<false, 64>(d, sb, wg, w, lane, &tm_out, 0, 0, xa, Dk);
                BSTAMP(11 + ng * 4);
                it += 8; ng++;
            }
        }
        if (nt < 8) bar_sync(14, 288);
    }
    asm volatile("griddepcontrol.wait;" ::: "memory");
}

typedef CUresult (*EncodeFn)(CUtensorMap*, CUtensorMapDataType, cuuint32_t, void*, const cuuint64_t*, const cuuint64_t*, const cuuint32_t*, const cuuint32_t*,
                             CUtensorMapInterleave, CUtensorMapSwizzle, CUtensorMapL2promotion, CUtensorMapFloatOOBfill);
}

extern "C" void kernel_launch(void* const* d_in, const int* in_sizes, int n_in, void* d_out, int out_size) {
    typedef const __nv_bfloat16* bp;
    bp Ax = (bp)d_in[0], Lre = (bp)d_in[1], Lim = (bp)d_in[2], Bre = (bp)d_in[3], Bim = (bp)d_in[4], Cre = (bp)d_in[5], Cim = (bp)d_in[6],
       logdt = (bp)d_in[7], Dk = (bp)d_in[8], Bx = (bp)d_in[9], mem0 = (bp)d_in[10], Wq = (bp)d_in[11], Wk = (bp)d_in[12], Wv = (bp)d_in[13], Wo = (bp)d_in[14];
    float* out = (float*)d_out;
    static EncodeFn enc = nullptr;
    if (!enc) {
        void* fn = nullptr; cudaDriverEntryPointQueryResult qr;
        cudaGetDriverEntryPoint("cuTensorMapEncodeTiled", &fn, cudaEnableDefault, &qr);
        enc = (EncodeFn)fn;
        cudaFuncSetAttribute(chain_kernel, cudaFuncAttributeMaxDynamicSharedMemorySize, CHAIN_SMEM);
        cudaFuncSetAttribute(bg_kernel, cudaFuncAttributeMaxDynamicSharedMemorySize, BG_SMEM);
    }
    const cuuint32_t es[5] = {1, 1, 1, 1, 1};
    auto map2d = [&](CUtensorMap* tm, CUtensorMapDataType dt, const void* p, cuuint64_t d0, cuuint64_t d1, cuuint64_t stride, cuuint32_t b0, cuuint32_t b1) {
        cuuint64_t gd[2] = {d0, d1}, gs[1] = {stride}; cuuint32_t bd[2] = {b0, b1};
        enc(tm, dt, 2, (void*)p, gd, gs, bd, es, CU_TENSOR_MAP_INTERLEAVE_NONE, CU_TENSOR_MAP_SWIZZLE_128B, CU_TENSOR_MAP_L2_PROMOTION_L2_128B,
            CU_TENSOR_MAP_FLOAT_OOB_FILL_NONE);
    };
    CUtensorMap tm_x, tm_q, tm_k, tm_v, tm_xa, tm_wo, tm_out;
    map2d(&tm_x, CU_TENSOR_MAP_DATA_TYPE_BFLOAT16, Bx, DM, SEQ, DM * 2, 64, 32);
    map2d(&tm_q, CU_TENSOR_MAP_DATA_TYPE_BFLOAT16, Wq, HD, DM, HD * 2, 64, 192);
    map2d(&tm_k, CU_TENSOR_MAP_DATA_TYPE_BFLOAT16, Wk, HD, DM, HD * 2, 64, 192);
    map2d(&tm_v, CU_TENSOR_MAP_DATA_TYPE_BFLOAT16, Wv, HD, DM, HD * 2, 64, 192);
    map2d(&tm_wo, CU_TENSOR_MAP_DATA_TYPE_BFLOAT16, Wo, DM, HD, DM * 2, 64, 256);
    map2d(&tm_out, CU_TENSOR_MAP_DATA_TYPE_FLOAT32, out, 2 * DM, SEQ, 2 * DM * 4, 32, 64);
    {
        cuuint64_t gd[5] = {DM, 2, 4, 16, 16}, gs[4] = {DM * 2, 32 * DM * 2, 2 * DM * 2, 128 * DM * 2}; cuuint32_t bd[5] = {64, 2, 4, 16, 1};
        enc(&tm_xa, CU_TENSOR_MAP_DATA_TYPE_BFLOAT16, 5, (void*)Ax, gd, gs, bd, es, CU_TENSOR_MAP_INTERLEAVE_NONE, CU_TENSOR_MAP_SWIZZLE_128B,
            CU_TENSOR_MAP_L2_PROMOTION_L2_128B, CU_TENSOR_MAP_FLOAT_OOB_FILL_NONE);
    }
    cudaStream_t st = cudaStreamPerThread;
    chain_kernel<<<96, 384, CHAIN_SMEM, st>>>(tm_x, tm_q, tm_k, tm_v, Bx, mem0, Wo);
    cudaLaunchConfig_t cfg = {};
    cfg.gridDim = dim3(36); cfg.blockDim = dim3(384); cfg.dynamicSmemBytes = BG_SMEM; cfg.stream = st;
    cudaLaunchAttribute at[1];
    at[0].id = cudaLaunchAttributeProgrammaticStreamSerialization; at[0].val.programmaticStreamSerializationAllowed = 1;
    cfg.attrs = at; cfg.numAttrs = 1;
    cudaLaunchKernelEx(&cfg, bg_kernel, tm_xa, tm_wo, tm_out, Ax, Lre, Lim, Bre, Bim, Cre, Cim, logdt, Dk, out);
}
```

```cpp
#include <cuda_runtime.h>
#include <cuda.h>
#include <cuda_bf16.h>
#include <cuda_fp16.h>
#include <stdint.h>

#define D_WAIT 740

#define RED_GAP 720
#define ACC_PF 1
#define QDEP 0
#define NSLEEP "40"
#define D_S0 34
#define D_EARLY 820
#define FLAGPOS 0
#define NORM_LATE 1
#define NRM(x, r) (NORM_LATE ? (x) * (r) : (x))
#define NBIG 14

namespace {

constexpr int DM = 576, NH = 32, SEQ = 2048, NSEG = 64, HD = 4096;

__device__ uint4 g_acc_raw[64 * 96 * 16 + 131072];
__device__ uint4 g_ox[NH * 2 * SEQ * 8];
constexpr int REC = 30720;
__device__ uint4 g_qkv[NSEG * NH * (REC / 16)];
__device__ uint4 g_h[18 * SEQ * 8];
constexpr int NFLAG = 6144, F_QKV = 0, F_OX = 1024, F_H = 2048, F_OUT = 3072;
constexpr int NBLK = NBIG + (NSEG - 4 * NBIG) / 2;
__host__ __device__ constexpr int blk_seg0(int b) { return b < NBIG ? 4 * b : 2 * b + 2 * NBIG; }
__device__ unsigned g_flag[NFLAG];
__device__ unsigned g_ticket, g_ticket_bg;
__device__ unsigned long long g_norm[96];
#define BSTAMP(i) do {} while (0)

__device__ __forceinline__ uint32_t smem_u32(const void* p) { return (uint32_t)__cvta_generic_to_shared(p); }
__device__ __forceinline__ uint32_t mapa(uint32_t a, uint32_t r) { uint32_t o; asm("mapa.shared::cluster.u32 %0, %1, %2;" : "=r"(o) : "r"(a), "r"(r)); return o; }
__device__ __forceinline__ uint32_t mapa_v(uint32_t a, uint32_t r) { uint32_t o; asm volatile("mapa.shared::cluster.u32 %0, %1, %2;" : "=r"(o) : "r"(a), "r"(r)); return o; }
__device__ __forceinline__ unsigned clk() { unsigned long long c; asm volatile("mov.u64 %0, %%clock64;" : "=l"(c) :: "memory"); return (unsigned)c; }
__device__ __forceinline__ void mbar_init(uint32_t bar, uint32_t cnt) { asm volatile("mbarrier.init.shared::cta.b64 [%0], %1;" :: "r"(bar), "r"(cnt) : "memory"); }
__device__ __forceinline__ void mbar_expect(uint32_t bar, uint32_t bytes) { asm volatile("mbarrier.arrive.expect_tx.shared::cta.b64 _, [%0], %1;" :: "r"(bar), "r"(bytes) : "memory"); }
__device__ __forceinline__ void mbar_wait(uint32_t bar, uint32_t parity) {
    asm volatile("{\n.reg .pred p;\n.reg .u32 n;\nmov.u32 n, 0;\n"
                 "W_%=: mbarrier.try_wait.parity.shared::cta.b64 p, [%0], %1;\n@p bra.uni D_%=;\n"
                 "add.u32 n, n, 1;\nsetp.lt.u32 p, n, 4000000;\n@p bra.uni W_%=;\ntrap;\nD_%=:\n}" :: "r"(bar), "r"(parity) : "memory");
}
__device__ __forceinline__ void mbar_expect_if(uint32_t z, uint32_t bar, uint32_t bytes) {
    asm volatile("{\n.reg .pred p;\nsetp.eq.u32 p, %2, 0;\n@p mbarrier.arrive.expect_tx.shared::cta.b64 _, [%0], %1;\n}" :: "r"(bar), "r"(bytes), "r"(z) : "memory");
}
__device__ __forceinline__ void mbar_arrive_if(uint32_t z, uint32_t bar) {
    asm volatile("{\n.reg .pred p;\nsetp.eq.u32 p, %1, 0;\n@p mbarrier.arrive.shared::cta.b64 _, [%0];\n}" :: "r"(bar), "r"(z) : "memory");
}
__device__ __forceinline__ void sts32_if(uint32_t z, uint32_t a, uint32_t x) {
    asm volatile("{\n.reg .pred p;\nsetp.eq.u32 p, %2, 0;\n@p st.shared.u32 [%0], %1;\n}" :: "r"(a), "r"(x), "r"(z) : "memory");
}
template <int K> __device__ __forceinline__ void sched_fence(int v) {
    asm volatile("{\n.reg .pred p;\nsetp.ne.s32 p, %0, %1;\n@p bra.uni F_%=;\ntrap;\nF_%=:\n}" :: "r"(v), "n"(1000 + K) : "memory");
}
__device__ __forceinline__ void spin_until(unsigned t0, unsigned d) {
    asm volatile("{\n.reg .pred p;\n.reg .u64 c;\n.reg .u32 lo;\n"
                 "S_%=: mov.u64 c, %%clock64;\ncvt.u32.u64 lo, c;\nsub.u32 lo, lo, %0;\nsetp.lt.u32 p, lo, %1;\n@p bra.uni S_%=;\n}" :: "r"(t0), "r"(d) : "memory");
}
__device__ __forceinline__ void bar_sync(int id, int n) { asm volatile("bar.sync %0, %1;" :: "r"(id), "r"(n) : "memory"); }
__device__ __forceinline__ void bar_sync_sel(int sel, int id) {
    asm volatile("{\n.reg .pred p;\nsetp.eq.u32 p, %0, 0;\n@p bar.sync %1, %3;\n@!p bar.sync %2, %3;\n}" :: "r"(sel), "r"(id), "r"(id + 1), "n"(192) : "memory");
}
__device__ __forceinline__ void bar_arrive(int id, int n) { asm volatile("bar.arrive %0, %1;" :: "r"(id), "r"(n) : "memory"); }
__device__ __forceinline__ void fence_async_smem() { asm volatile("fence.proxy.async.shared::cta;" ::: "memory"); }
__device__ __forceinline__ uint32_t pack_bf16(float lo, float hi) { uint32_t r; asm("cvt.rn.bf16x2.f32 %0, %1, %2;" : "=r"(r) : "f"(hi), "f"(lo)); return r; }
__device__ __forceinline__ uint32_t pack_f16(float lo, float hi) { uint32_t r; asm("cvt.rn.f16x2.f32 %0, %1, %2;" : "=r"(r) : "f"(hi), "f"(lo)); return r; }
__device__ __forceinline__ uint32_t f16x2_to_bf16x2(uint32_t v) { float2 f = __half22float2(*reinterpret_cast<__half2*>(&v)); return pack_bf16(f.x, f.y); }
__device__ __forceinline__ uint32_t hmul2(uint32_t a, uint32_t b) { uint32_t r; asm("mul.rn.f16x2 %0, %1, %2;" : "=r"(r) : "r"(a), "r"(b)); return r; }
__device__ __forceinline__ float ex2(float x) { float y; asm("ex2.approx.ftz.f32 %0, %1;" : "=f"(y) : "f"(x)); return y; }
__device__ __forceinline__ float ex2v(float x) { float y; asm volatile("ex2.approx.ftz.f32 %0, %1;" : "=f"(y) : "f"(x)); return y; }
__device__ __forceinline__ uint32_t absmax2(uint32_t a, uint32_t b) {
    uint32_t r; asm("max.xorsign.abs.f16x2 %0, %1, %2;" : "=r"(r) : "r"(a), "r"(b)); return r;
}
__device__ __forceinline__ uint32_t shl_v(uint32_t a, int n) { return a << n; }
__device__ __forceinline__ uint32_t max3u(uint32_t a, uint32_t b, uint32_t c) { return max(max(a, b), c); }
__device__ __forceinline__ uint4 lds128(uint32_t a) { uint4 v; asm volatile("ld.shared.v4.u32 {%0,%1,%2,%3}, [%4];" : "=r"(v.x), "=r"(v.y), "=r"(v.z), "=r"(v.w) : "r"(a) : "memory"); return v; }
__device__ __forceinline__ uint4 lds128v(uint32_t a) { uint4 v; asm volatile("ld.volatile.shared.v4.u32 {%0,%1,%2,%3}, [%4];" : "=r"(v.x), "=r"(v.y), "=r"(v.z), "=r"(v.w) : "r"(a) : "memory"); return v; }
__device__ __forceinline__ float4 lds128f(uint32_t a) { float4 v; asm volatile("ld.shared.v4.f32 {%0,%1,%2,%3}, [%4];" : "=f"(v.x), "=f"(v.y), "=f"(v.z), "=f"(v.w) : "r"(a) : "memory"); return v; }
__device__ __forceinline__ float2 lds64f(uint32_t a) { float2 v; asm volatile("ld.shared.v2.f32 {%0,%1}, [%2];" : "=f"(v.x), "=f"(v.y) : "r"(a) : "memory"); return v; }
__device__ __forceinline__ uint4 lds64x2(uint32_t a) { uint4 v; asm volatile("ld.shared.v2.u32 {%0,%1}, [%4];\nld.shared.v2.u32 {%2,%3}, [%4+256];" : "=r"(v.x), "=r"(v.y), "=r"(v.z), "=r"(v.w) : "r"(a) : "memory"); return v; }
__device__ __forceinline__ uint32_t lds32(uint32_t a) { uint32_t v; asm volatile("ld.shared.u32 %0, [%1];" : "=r"(v) : "r"(a) : "memory"); return v; }
__device__ __forceinline__ void sts128(uint32_t a, uint32_t x, uint32_t y, uint32_t z, uint32_t w) { asm volatile("st.shared.v4.u32 [%0], {%1,%2,%3,%4};" :: "r"(a), "r"(x), "r"(y), "r"(z), "r"(w) : "memory"); }
__device__ __forceinline__ void sts128f(uint32_t a, float x, float y, float z, float w) { asm volatile("st.shared.v4.f32 [%0], {%1,%2,%3,%4};" :: "r"(a), "f"(x), "f"(y), "f"(z), "f"(w) : "memory"); }
__device__ __forceinline__ void sts64(uint32_t a, uint32_t x, uint32_t y) { asm volatile("st.shared.v2.u32 [%0], {%1,%2};" :: "r"(a), "r"(x), "r"(y) : "memory"); }
__device__ __forceinline__ void sts32(uint32_t a, uint32_t x) { asm volatile("st.shared.u32 [%0], %1;" :: "r"(a), "r"(x) : "memory"); }
__device__ __forceinline__ uint4 ldsm4(uint32_t a) { uint4 v; asm volatile("ldmatrix.sync.aligned.m8n8.x4.shared.b16 {%0,%1,%2,%3}, [%4];" : "=r"(v.x), "=r"(v.y), "=r"(v.z), "=r"(v.w) : "r"(a) : "memory"); return v; }
__device__ __forceinline__ void stsm2t(uint32_t a, uint32_t x, uint32_t y) { asm volatile("stmatrix.sync.aligned.m8n8.x2.trans.shared.b16 [%0], {%1,%2};" :: "r"(a), "r"(x), "r"(y) : "memory"); }
__device__ __forceinline__ void stsm4t(uint32_t a, uint32_t x, uint32_t y, uint32_t z, uint32_t w) { asm volatile("stmatrix.sync.aligned.m8n8.x4.trans.shared.b16 [%0], {%1,%2,%3,%4};" :: "r"(a), "r"(x), "r"(y), "r"(z), "r"(w) : "memory"); }
__device__ __forceinline__ void st_async64(uint32_t a, uint32_t x, uint32_t y, uint32_t bar) { asm volatile("st.async.shared::cluster.mbarrier::complete_tx::bytes.v2.b32 [%0], {%1,%2}, [%3];" :: "r"(a), "r"(x), "r"(y), "r"(bar) : "memory"); }
__device__ __forceinline__ void bulk_s2c(uint32_t dst, uint32_t src, uint32_t bytes, uint32_t bar) { asm volatile("cp.async.bulk.shared::cluster.shared::cta.mbarrier::complete_tx::bytes [%0], [%1], %2, [%3];" :: "r"(dst), "r"(src), "r"(bytes), "r"(bar) : "memory"); }
__device__ __forceinline__ void bulk_s2g(void* dst, uint32_t src, uint32_t bytes) { asm volatile("cp.async.bulk.global.shared::cta.bulk_group [%0], [%1], %2;" :: "l"(dst), "r"(src), "r"(bytes) : "memory"); }
__device__ __forceinline__ uint32_t ldg_nc32(const void* p) { uint32_t v; asm volatile("ld.global.nc.L2::128B.u32 %0, [%1];" : "=r"(v) : "l"(p)); return v; }
__device__ __forceinline__ uint4 ldg_relaxed128(const void* p) { uint4 v; asm volatile("ld.relaxed.gpu.global.v4.u32 {%0,%1,%2,%3}, [%4];" : "=r"(v.x), "=r"(v.y), "=r"(v.z), "=r"(v.w) : "l"(p) : "memory"); return v; }
__device__ __forceinline__ void mma16816(float (&d)[4], uint32_t a0, uint32_t a1, uint32_t a2, uint32_t a3, uint32_t b0, uint32_t b1) {
    asm volatile("mma.sync.aligned.m16n8k16.row.col.f32.bf16.bf16.f32 {%0,%1,%2,%3}, {%4,%5,%6,%7}, {%8,%9}, {%0,%1,%2,%3};"
        : "+f"(d[0]), "+f"(d[1]), "+f"(d[2]), "+f"(d[3]) : "r"(a0), "r"(a1), "r"(a2), "r"(a3), "r"(b0), "r"(b1));
}
__device__ __forceinline__ void mma16816_z(float (&d)[4], uint32_t a0, uint32_t a1, uint32_t a2, uint32_t a3, uint32_t b0, uint32_t b1) {
    asm volatile("mma.sync.aligned.m16n8k16.row.col.f32.bf16.bf16.f32 {%0,%1,%2,%3}, {%4,%5,%6,%7}, {%8,%9}, {%10,%10,%10,%10};"
        : "=f"(d[0]), "=f"(d[1]), "=f"(d[2]), "=f"(d[3]) : "r"(a0), "r"(a1), "r"(a2), "r"(a3), "r"(b0), "r"(b1), "f"(0.f));
}
__device__ __forceinline__ void mma1688(float (&d)[4], uint32_t a0, uint32_t a1, uint32_t b0) {
    asm volatile("mma.sync.aligned.m16n8k8.row.col.f32.bf16.bf16.f32 {%0,%1,%2,%3}, {%4,%5}, {%6}, {%0,%1,%2,%3};"
        : "+f"(d[0]), "+f"(d[1]), "+f"(d[2]), "+f"(d[3]) : "r"(a0), "r"(a1), "r"(b0));
}
__device__ __forceinline__ void mma1688_z(float (&d)[4], uint32_t a0, uint32_t a1, uint32_t b0) {
    asm volatile("mma.sync.aligned.m16n8k8.row.col.f32.bf16.bf16.f32 {%0,%1,%2,%3}, {%4,%5}, {%6}, {%7,%7,%7,%7};"
        : "=f"(d[0]), "=f"(d[1]), "=f"(d[2]), "=f"(d[3]) : "r"(a0), "r"(a1), "r"(b0), "f"(0.f));
}
template <int ACC>
__device__ __forceinline__ void wgmma_n32_rs(float (&d)[16], uint32_t a0, uint32_t a1, uint32_t a2, uint32_t a3, uint64_t desc) {
    asm volatile("wgmma.mma_async.sync.aligned.m64n32k16.f32.bf16.bf16 {%0,%1,%2,%3,%4,%5,%6,%7,%8,%9,%10,%11,%12,%13,%14,%15}, {%16,%17,%18,%19}, %20, %21, 1, 1, 0;"
        : "+f"(d[0]), "+f"(d[1]), "+f"(d[2]), "+f"(d[3]), "+f"(d[4]), "+f"(d[5]), "+f"(d[6]), "+f"(d[7]),
          "+f"(d[8]), "+f"(d[9]), "+f"(d[10]), "+f"(d[11]), "+f"(d[12]), "+f"(d[13]), "+f"(d[14]), "+f"(d[15])
        : "r"(a0), "r"(a1), "r"(a2), "r"(a3), "l"(desc), "n"(ACC));
}
template <int ACC>
__device__ __forceinline__ void wgmma_n32_ss(float (&d)[16], uint64_t da, uint64_t db) {
    asm volatile("wgmma.mma_async.sync.aligned.m64n32k16.f32.bf16.bf16 {%0,%1,%2,%3,%4,%5,%6,%7,%8,%9,%10,%11,%12,%13,%14,%15}, %16, %17, %18, 1, 1, 0, 0;"
        : "+f"(d[0]), "+f"(d[1]), "+f"(d[2]), "+f"(d[3]), "+f"(d[4]), "+f"(d[5]), "+f"(d[6]), "+f"(d[7]),
          "+f"(d[8]), "+f"(d[9]), "+f"(d[10]), "+f"(d[11]), "+f"(d[12]), "+f"(d[13]), "+f"(d[14]), "+f"(d[15])
        : "l"(da), "l"(db), "n"(ACC));
}
__device__ __forceinline__ void wg_fence() { asm volatile("wgmma.fence.sync.aligned;" ::: "memory"); }
__device__ __forceinline__ void wg_commit() { asm volatile("wgmma.commit_group.sync.aligned;" ::: "memory"); }
__device__ __forceinline__ void wg_wait0() { asm volatile("wgmma.wait_group.sync.aligned 0;" ::: "memory"); }
__device__ __forceinline__ void cluster_sync() { asm volatile("barrier.cluster.arrive.aligned;\nbarrier.cluster.wait.aligned;" ::: "memory"); }

#define STAMP(s, i) do {} while (0)
#define STAMPV(s, i, v) do {} while (0)

constexpr int XT_BYTES = 36864;
constexpr int O_XT = 0;
constexpr int O_STG = XT_BYTES;
constexpr int O_AS = 3 * XT_BYTES;
constexpr int O_XP = O_AS + 16384;
constexpr int O_QKX = O_XP + 8192;
constexpr int O_KM = O_QKX + 8192;
constexpr int O_QM = O_QKX + 10240;
constexpr int O_VX = O_STG + 147456;
constexpr int O_VM = O_VX + 16384;
constexpr int O_SC = O_VM + 2048;
constexpr int O_OF = O_SC + 2560;
constexpr int O_AF = O_OF + 2048;
constexpr int O_WP = O_AF + 4096;
constexpr int O_MF = O_WP + 2048;
constexpr int O_MISC = O_MF + 9216;
static_assert(O_QKX + 24576 <= O_VX, "smem");
constexpr int O_BAR = O_MISC + 64;
constexpr int CHAIN_SMEM = O_BAR + 128;
static_assert(CHAIN_SMEM <= 232448, "smem");
constexpr int B_X = O_BAR, B_VX = O_BAR + 24, B_SC = O_BAR + 40, B_W = O_BAR + 48;
constexpr float SM_SCALE = 0.08838834764831845f * 1.4426950408889634f;
constexpr uint32_t ONES = 0x3f803f80u;

template <bool B> struct BoolC { static constexpr bool value = B; };
__device__ __forceinline__ uint32_t opaque(uint32_t v) { uint32_t o; asm volatile("mov.u32 %0, %1;" : "=r"(o) : "r"(v)); return o; }
__device__ __forceinline__ void st_async128(uint32_t a, uint32_t x, uint32_t y, uint32_t z, uint32_t w, uint32_t bar) {
    asm volatile("st.async.shared::cluster.mbarrier::complete_tx::bytes.v4.b32 [%0], {%1,%2,%3,%4}, [%5];" :: "r"(a), "r"(x), "r"(y), "r"(z), "r"(w), "r"(bar) : "memory");
}
__device__ __forceinline__ void tma_x_tile(uint32_t sb, const CUtensorMap* tm, int r, int j, int slot) {
    asm volatile("{\n.reg .pred p;\nelect.sync _|p, 0xffffffff;\n"
        "@p mbarrier.arrive.expect_tx.shared::cta.b64 _, [%2], 36864;\n"
        "@p cp.async.bulk.tensor.2d.shared::cluster.global.mbarrier::complete_tx::bytes.multicast::cluster [%0], [%1, {%3, %4}], [%2], %7;\n"
        "@p cp.async.bulk.tensor.2d.shared::cluster.global.mbarrier::complete_tx::bytes.multicast::cluster [%0+4096], [%1, {%5, %4}], [%2], %7;\n"
        "@p cp.async.bulk.tensor.2d.shared::cluster.global.mbarrier::complete_tx::bytes.multicast::cluster [%0+8192], [%1, {%6, %4}], [%2], %7;\n}"
        :: "r"(sb + O_XT + slot * XT_BYTES + 3 * r * 4096), "l"(tm), "r"(sb + B_X + 8 * slot), "r"(192 * r), "r"(j * 32), "r"(192 * r + 64), "r"(192 * r + 128),
           "h"((unsigned short)7) : "memory");
}
__device__ __forceinline__ void flag_inc_if(uint32_t z, unsigned* p) {
    asm volatile("{\n.reg .pred p;\nsetp.eq.u32 p, %1, 0;\n@p red.release.gpu.global.inc.u32 [%0], 0xfffffffe;\n}" :: "l"(p), "r"(z) : "memory");
}
__device__ __forceinline__ float quad_max(float v) {
    const float a = __shfl_xor_sync(~0u, v, 1), b = __shfl_xor_sync(~0u, v, 2), c = __shfl_xor_sync(~0u, v, 3);
    return fmaxf(fmaxf(v, a), fmaxf(b, c));
}
__device__ __forceinline__ void load_scores(float (&p)[10], uint32_t base, uint32_t stride, uint32_t l16) {
    const float4 a0 = lds128f(base + l16), b0 = lds128f(base + stride + l16);
    const float4 a1 = lds128f(base + 512 + l16), b1 = lds128f(base + stride + 512 + l16);
    const float2 a2 = lds64f(base + 1024 + (l16 >> 1)), b2 = lds64f(base + stride + 1024 + (l16 >> 1));
    p[0] = a2.x + b2.x; p[1] = a2.y + b2.y;
    p[2] = a0.x + b0.x; p[3] = a0.y + b0.y; p[4] = a0.z + b0.z; p[5] = a0.w + b0.w;
    p[6] = a1.x + b1.x; p[7] = a1.y + b1.y; p[8] = a1.z + b1.z; p[9] = a1.w + b1.w;
}
__device__ __forceinline__ float rcp_fast(float x) { float y; asm("rcp.approx.ftz.f32 %0, %1;" : "=f"(y) : "f"(x)); return y; }

__global__ void __cluster_dims__(3, 1, 1) __launch_bounds__(384, 1)
chain_kernel(const __grid_constant__ CUtensorMap tm_x, const __grid_constant__ CUtensorMap tm_q,
             const __grid_constant__ CUtensorMap tm_k, const __grid_constant__ CUtensorMap tm_v,
             const __nv_bfloat16* __restrict__ x, const __nv_bfloat16* __restrict__ mem0,
             const __nv_bfloat16* __restrict__ Wo) {
    extern __shared__ __align__(1024) uint8_t smem_raw[];
    const uint32_t sb = smem_u32(smem_raw);
    const int lane = threadIdx.x & 31;
    const int warp = __shfl_sync(~0u, threadIdx.x >> 5, 0);
    const int wg = warp >> 2, w = warp & 3;
    const int h = blockIdx.x / 3, r = blockIdx.x - 3 * h;
    uint4* const g_acc = reinterpret_cast<uint4*>((reinterpret_cast<uintptr_t>(g_acc_raw) + 0x1fffff) & ~(uintptr_t)0x1fffff);

#define PSTAMP(i) do {} while (0)
    if (threadIdx.x == 0) {
        if (sb & 1023u) __trap();
        for (int i = 0; i < 9; i++) mbar_init(sb + O_BAR + 8 * i, 1);
        asm volatile("fence.mbarrier_init.release.cluster;" ::: "memory");
        for (int i = 0; i < 3; i++) {
            mbar_expect(sb + B_W + 8 * i, 49152);
            for (int tl = 0; tl < 2; tl++)
                asm volatile("cp.async.bulk.tensor.2d.shared::cluster.global.mbarrier::complete_tx::bytes [%0], [%1, {%3, %4}], [%2];"
                    :: "r"(sb + O_STG + tl * 73728 + i * 24576), "l"(r < 2 ? (tl ? &tm_k : &tm_q) : &tm_v), "r"(sb + B_W + 8 * i),
                       "r"(h * 128 + 64 * (r < 2 ? r : tl)), "r"(192 * i) : "memory");
        }
    }
    __syncwarp();
    asm volatile("barrier.cluster.arrive.relaxed.aligned;" ::: "memory");
    asm volatile("griddepcontrol.launch_dependents;" ::: "memory");
    if (warp == 0) PSTAMP(9);
    const uint32_t l16c = __shfl_sync(~0u, lane * 16, lane);

    if (wg < 2) {
#define KS(u) ((u) < 8 ? 12 * ((u) >> 2) + (((u) >> 1) & 1) + 4 * ((u) & 1) : (u) < 12 ? (u) : (u) < 16 ? (u) + 8 : (u) < 24 ? 24 + (((u) - 16) >> 1) + 4 * ((u) & 1) : (u) + 8)
        asm volatile("setmaxnreg.inc.sync.aligned.u32 184;");
        uint32_t a[144];
        uint32_t adr1;
        {
            const int g = lane >> 2, t = lane & 3;
            const int t1 = threadIdx.x;
#pragma unroll
            for (int i = 0; i < 2; i++) g_acc[(blockIdx.x * 64 + i * 32 + (t1 >> 3)) * 16 + (t1 & 7)] = make_uint4(0, 0, 0, 0);
            __threadfence();
            asm volatile("barrier.cluster.wait.aligned;" ::: "memory");
            const uint32_t ev = sb + O_STG + (2 * t) * 128 + (((2 * w + (g >> 2)) ^ (2 * t)) << 4) + (g & 3) * 4;
            const uint32_t od = (ev ^ 16) + 128;
            auto gather = [&](int dst, uint32_t off) {
                a[dst] = lds32(ev + off); a[dst + 1] = lds32(od + off); a[dst + 2] = lds32(ev + off + 1024); a[dst + 3] = lds32(od + off + 1024);
            };
            const uint4* xp = reinterpret_cast<const uint4*>(x) + blockIdx.x * 1536 + t1;
            uint4 xv[6];
#pragma unroll
            for (int th = 0; th < 2; th++) {
                mbar_wait(sb + B_W + 8 * th, 0);
                if (th == 1) {
#pragma unroll
                    for (int i = 0; i < 6; i++) xv[i] = __ldg(xp + i * 256);
                }
#pragma unroll
                for (int u = 4 * th; u < 4 * th + 4; u++) {
                    gather(32 + 4 * u, wg * (73728 + 4096) + KS(u) * 2048);
                    gather(4 * u, 73728 - wg * (73728 - 4096) + KS(u) * 2048);
                    gather(64 + 4 * u, wg * 73728 + KS(8 + u) * 2048);
                }
            }
            mbar_wait(sb + B_W + 16, 0);
#pragma unroll
            for (int u = 16; u < 28; u++) gather(32 + 4 * u, wg * 73728 + KS(u) * 2048);
#pragma unroll
            for (int kk = 0; kk < 72; kk++) {
                uint32_t w0 = a[2 * kk], w1 = a[2 * kk + 1];
                a[2 * kk] = __byte_perm(w0, w1, 0x5410);
                a[2 * kk + 1] = __byte_perm(w0, w1, 0x7632);
            }
            if (r == 2) {
                float n0[4], n1[4];
#pragma unroll
                for (int u = 0; u < 36; u++) {
                    const uint32_t x0 = a[4 * u] & 0x7fff7fffu, x1 = a[4 * u + 1] & 0x7fff7fffu, x2 = a[4 * u + 2] & 0x7fff7fffu, x3 = a[4 * u + 3] & 0x7fff7fffu;
                    if (u == 0) mma16816_z(n0, x0, x1, x2, x3, ONES, ONES);
                    else if (u < 8) mma16816(n0, x0, x1, x2, x3, ONES, ONES);
                    else if (u == 8) mma16816_z(n1, x0, x1, x2, x3, ONES, ONES);
                    else mma16816(n1, x0, x1, x2, x3, ONES, ONES);
                }
                const uint32_t mx = __reduce_max_sync(~0u, __float_as_uint(2.f * fmaxf(fmaxf(n0[0], n0[2]), fmaxf(n1[0], n1[2]))));
                sts32_if(lane, sb + O_MISC + 32 + 4 * warp, mx);
            }
            uint32_t xm = 0;
#pragma unroll
            for (int i = 0; i < 6; i++)
                xm = __vmaxu2(xm, __vmaxu2(__vmaxu2(xv[i].x & 0x7fff7fffu, xv[i].y & 0x7fff7fffu), __vmaxu2(xv[i].z & 0x7fff7fffu, xv[i].w & 0x7fff7fffu)));
            sts32_if(lane, sb + O_OF + 16 + 4 * warp, __reduce_max_sync(~0u, max(xm << 16, xm & 0xffff0000u)));
            if (warp == 0) PSTAMP(11);
            bar_arrive(7, 384);
            asm volatile("barrier.cluster.arrive.relaxed.aligned;" ::: "memory");
            bar_sync(1, 256);
            const uint32_t as = sb + O_AS + wg * 8192 + (16 * w + g) * 128 + t * 4;
            sts32(as + (g << 4), a[32]);
            sts32(as + 1024 + (g << 4), a[33]);
            sts32(as + ((1 ^ g) << 4), a[34]);
            sts32(as + 1024 + ((1 ^ g) << 4), a[35]);
            sts128(sb + O_AF + warp * 512 + lane * 16, a[32], a[33], a[34], a[35]);
            fence_async_smem();
            bar_sync(1, 256);
            const uint32_t l = lane * 16;
            const int mi = lane >> 3, isk = (mi >> 1) ? wg : (wg ^ 1);
            adr1 = (r == 2) ? (sb + O_VM + warp * 256 + (l >> 1))
                            : (isk ? (sb + O_KM + w * 512 + wg * 256 + (mi & 1) * 128 + (l & 127))
                                   : (sb + O_QM + w * 512 + (mi & 1) * 256 + wg * 128 + (l & 127)));
            adr1 = __shfl_sync(~0u, adr1, lane);
        }
        auto qkv_loop = [&](auto r2tag) {
        constexpr bool R2 = decltype(r2tag)::value;
        int s3 = 2;
#pragma unroll 1
        for (int s = -1; s < NSEG; s++) {
            const uint32_t l16 = opaque(l16c);
            s3 = (s3 == 2) ? 0 : s3 + 1;
            if (s < 0) mbar_wait(sb + B_X, 0);
            const uint64_t desc0 = (uint64_t)(((sb + O_XT + s3 * XT_BYTES) & 0x3FFFF) >> 4) | (1ull << 16) | (64ull << 32) | (1ull << 62);
            uint32_t km0 = 0, km1 = 0;
            if (s >= 0) {
                { const uint4 v = lds128(sb + O_AF + warp * 512 + l16); a[32] = v.x; a[33] = v.y; a[34] = v.z; a[35] = v.w; }
                float co[4], cw[3][4];
                uint4 b[14];
                float inv;
#define GORD(i) ((i) < 8 ? 2 * ((i) >> 2) + (((i) >> 1) & 1) + 4 * ((i) & 1) : (i))
                auto qkv_mma = [&](int i) {
                    const int gi = GORD(i), u = 8 * gi, n0 = 2 * i, n1 = 2 * i + 1;
                    if (gi < 4) {
                        if (i == 0) mma16816_z(co, a[u], a[u + 1], a[u + 2], a[u + 3], b[0].x, b[0].y);
                        else mma16816(co, a[u], a[u + 1], a[u + 2], a[u + 3], b[i].x, b[i].y);
                    }
                    if (n0 < 3) mma16816_z(cw[n0 % 3], a[32 + u], a[32 + u + 1], a[32 + u + 2], a[32 + u + 3], b[i].x, b[i].y);
                    else mma16816(cw[n0 % 3], a[32 + u], a[32 + u + 1], a[32 + u + 2], a[32 + u + 3], b[i].x, b[i].y);
                    if (n1 < 3) mma16816_z(cw[n1 % 3], a[32 + u + 4], a[32 + u + 5], a[32 + u + 6], a[32 + u + 7], b[i].z, b[i].w);
                    else mma16816(cw[n1 % 3], a[32 + u + 4], a[32 + u + 5], a[32 + u + 6], a[32 + u + 7], b[i].z, b[i].w);
                    if (gi < 4) mma16816(co, a[u + 4], a[u + 5], a[u + 6], a[u + 7], b[i].z, b[i].w);
                };
                const uint32_t mf = sb + O_MF + l16, mfs = mf + wg * 1024;
                const uint32_t qb = (s & 1) * 12288;
                bar_sync(2, 384);
                if (warp == 0) STAMP(s, 0);
                auto qkv_ld = [&](int i) {
                    const int gi = GORD(i);
                    b[i] = gi < 4 ? lds128v(mfs + (gi >> 1) * 3072 + (gi & 1) * 512) : lds128v(mf + (gi < 6 ? gi : gi + 4) * 512);
                };
#pragma unroll
                for (int i = 0; i < 4; i++) qkv_ld(i);
                qkv_mma(0); qkv_mma(1); qkv_mma(2);
                const uint32_t z0 = __float_as_uint(QDEP ? co[0] : cw[1][0]) & (l16 & 15u);
                qkv_mma(3);
                bar_sync(15, 384);
                b[4] = lds128v(mfs + 3072 + z0);
#pragma unroll
                for (int i = 5; i < 9; i++) qkv_ld(i);
#pragma unroll
                for (int i = 4; i < 9; i++) { qkv_mma(i); qkv_ld(5 + i); }
                asm volatile("ld.volatile.shared.f32 %0, [%1];" : "=f"(inv) : "r"(sb + O_MISC) : "memory");
#pragma unroll
                for (int i = 9; i < 14; i++) qkv_mma(i);
#pragma unroll
                for (int i = 0; i < 4; i++) cw[0][i] += cw[1][i] + cw[2][i];
                if (!R2) {
                    const uint32_t o0 = pack_bf16(co[0] * inv, co[1] * inv), o1 = pack_bf16(co[2] * inv, co[3] * inv);
                    const uint32_t w0 = pack_bf16(cw[0][0] * inv, cw[0][1] * inv), w1 = pack_bf16(cw[0][2] * inv, cw[0][3] * inv);
                    stsm4t(adr1 + qb, o0, o1, w0, w1);
                    if (warp == 0) STAMP(s, 1);
                    asm volatile("{\n.reg .pred p;\nsetp.ge.u32 p, %0, 3;\n@p bar.arrive 1, 256;\n@!p bar.sync 1, 256;\n}" :: "r"(warp) : "memory");
                    auto scores = [&](float (&v)[4], const uint4 (&q)[4], const uint4 (&k)[4]) {
                        float s0[4], s1[4], t0[4], t1[4];
                        mma16816_z(s0, q[0].x, q[0].y, q[0].z, q[0].w, k[0].x, k[0].y);
                        mma16816_z(s1, q[0].x, q[0].y, q[0].z, q[0].w, k[0].z, k[0].w);
                        mma16816_z(t0, q[1].x, q[1].y, q[1].z, q[1].w, k[1].x, k[1].y);
                        mma16816_z(t1, q[1].x, q[1].y, q[1].z, q[1].w, k[1].z, k[1].w);
                        mma16816(s0, q[2].x, q[2].y, q[2].z, q[2].w, k[2].x, k[2].y);
                        mma16816(s1, q[2].x, q[2].y, q[2].z, q[2].w, k[2].z, k[2].w);
                        mma16816(t0, q[3].x, q[3].y, q[3].z, q[3].w, k[3].x, k[3].y);
                        mma16816(t1, q[3].x, q[3].y, q[3].z, q[3].w, k[3].z, k[3].w);
                        v[0] = (s0[0] + s0[2]) + (t0[0] + t0[2]); v[1] = (s0[1] + s0[3]) + (t0[1] + t0[3]);
                        v[2] = (s1[0] + s1[2]) + (t1[0] + t1[2]); v[3] = (s1[1] + s1[3]) + (t1[1] + t1[3]);
                    };
                    if (warp < 2) {
                        uint4 q[4], k[4]; float v[4];
#pragma unroll
                        for (int i = 0; i < 4; i++) { q[i] = ldsm4(sb + O_QM + qb + i * 512 + l16); k[i] = ldsm4(sb + O_QKX + 4096 + qb + warp * 2048 + i * 512 + l16); }
                        scores(v, q, k);
                        const uint32_t dst = sb + O_SC + r * 1280 + warp * 512 + l16;
                        st_async128(mapa(dst, 2), __float_as_uint(v[0]), __float_as_uint(v[1]), __float_as_uint(v[2]), __float_as_uint(v[3]), mapa(sb + B_SC, 2));
                        st_async128(mapa(dst, r ^ 1), __float_as_uint(v[0]), __float_as_uint(v[1]), __float_as_uint(v[2]), __float_as_uint(v[3]), mapa(sb + B_SC, r ^ 1));
                        st_async128(mapa(dst, r), __float_as_uint(v[0]), __float_as_uint(v[1]), __float_as_uint(v[2]), __float_as_uint(v[3]), mapa(sb + B_SC, r));
                    } else if (warp == 2) {
                        uint4 q[4], k[4]; float v[4];
#pragma unroll
                        for (int i = 0; i < 4; i++) { q[i] = ldsm4(sb + O_QM + qb + i * 512 + l16); k[i] = ldsm4(sb + O_KM + qb + i * 512 + l16); }
                        scores(v, q, k);
                        const uint32_t dst = sb + O_SC + r * 1280 + 1024 + (l16 >> 1);
                        st_async64(mapa(dst, 2), __float_as_uint(v[0] + v[2]), __float_as_uint(v[1] + v[3]), mapa(sb + B_SC, 2));
                        st_async64(mapa(dst, r ^ 1), __float_as_uint(v[0] + v[2]), __float_as_uint(v[1] + v[3]), mapa(sb + B_SC, r ^ 1));
                        st_async64(mapa(dst, r), __float_as_uint(v[0] + v[2]), __float_as_uint(v[1] + v[3]), mapa(sb + B_SC, r));
                        STAMP(s, 2);
                    }
                } else {
                    sts128f(sb + O_XP + warp * 512 + l16, co[0], co[1], co[2], co[3]);
                    bar_sync(8 + w, 64);
                    const float4 o = lds128f(sb + O_XP + (warp ^ 4) * 512 + l16);
                    km0 = pack_bf16((cw[0][0] + o.x) * inv, (cw[0][1] + o.y) * inv);
                    km1 = pack_bf16((cw[0][2] + o.z) * inv, (cw[0][3] + o.w) * inv);
                    if (warp == 0) STAMP(s, 1);
                    st_async64(mapa(adr1, 0), km0, km1, mapa(sb + B_SC, 0));
                    st_async64(mapa(adr1, 1), km0, km1, mapa(sb + B_SC, 1));
                    st_async64(mapa(adr1, 2), km0, km1, mapa(sb + B_SC, 2));
                    if (warp == 0) STAMP(s, 2);
                }
            }
            if (s >= 0) bar_sync(3, 384);
            auto store_qk = [&]() {
                asm volatile("{\n.reg .pred p;\nelect.sync _|p, 0xffffffff;\n"
                    "@p cp.async.bulk.global.shared::cta.bulk_group [%0], [%1], 10240;\n@p cp.async.bulk.commit_group;\n}"
                    :: "l"(reinterpret_cast<char*>(g_qkv) + (size_t)(s * NH + h) * REC + r * 10240), "r"(sb + O_QKX + (s & 1) * 12288) : "memory");
            };
            auto store_vm = [&]() {
                *reinterpret_cast<uint2*>(reinterpret_cast<char*>(g_qkv) + (size_t)(s * NH + h) * REC + 28672 + warp * 256 + (l16 >> 1)) = make_uint2(km0, km1);
            };
            if (s == NSEG - 1) {
                if (R2) store_vm();
                else if (warp == 3) {
                    fence_async_smem();
                    store_qk();
                    asm volatile("cp.async.bulk.wait_group 0;\nfence.proxy.async.global;" ::: "memory");
                }
            } else {
                const int j = s + 1;
#define XDESC(u) (((u) < 8 ? descs : desc0) + (uint64_t)(((KS(u) >> 2) * 4096 + (KS(u) & 3) * 32) >> 4))
                const uint64_t descs = desc0 + (uint64_t)(wg * 4);
                float d[16];
                wg_fence();
#pragma unroll
                for (int u = 0; u < 8; u++) {
                    if (u == 0) wgmma_n32_rs<0>(d, a[0], a[1], a[2], a[3], XDESC(0));
                    else wgmma_n32_rs<1>(d, a[4 * u], a[4 * u + 1], a[4 * u + 2], a[4 * u + 3], XDESC(u));
                }
                wg_commit();
                wg_wait0();
                if (warp == 0) STAMP(s, 15);
                if (warp == 3) asm volatile("cp.async.bulk.wait_group.read 0;" ::: "memory");
                if (s >= 0) bar_sync(4, 384);
#pragma unroll
                for (int q = 0; q < 2; q++)
                    sts128(sb + O_XP + warp * 1024 + q * 512 + l16, pack_bf16(d[8 * q], d[8 * q + 1]), pack_bf16(d[8 * q + 2], d[8 * q + 3]),
                           pack_bf16(d[8 * q + 4], d[8 * q + 5]), pack_bf16(d[8 * q + 6], d[8 * q + 7]));
                bar_sync(12, 256);
#pragma unroll
                for (int q = 0; q < 2; q++) {
                    const uint4 o = lds128(sb + O_XP + (warp ^ 4) * 1024 + q * 512 + l16);
                    d[8 * q] = __uint_as_float(o.x << 16); d[8 * q + 1] = __uint_as_float(o.x & 0xffff0000u);
                    d[8 * q + 2] = __uint_as_float(o.y << 16); d[8 * q + 3] = __uint_as_float(o.y & 0xffff0000u);
                    d[8 * q + 4] = __uint_as_float(o.z << 16); d[8 * q + 5] = __uint_as_float(o.z & 0xffff0000u);
                    d[8 * q + 6] = __uint_as_float(o.w << 16); d[8 * q + 7] = __uint_as_float(o.w & 0xffff0000u);
                }
                if (s >= 0) {
                    if (R2) store_vm();
                    if (warp == 5 && s + 2 < NSEG) tma_x_tile(sb, &tm_x, r, s + 2, s3 == 2 ? 0 : s3 + 1);
                    if (warp == 3) {
                        asm volatile("cp.async.bulk.wait_group 0;\nfence.proxy.async.global;" ::: "memory");
                        if (FLAGPOS == 0 && s >= 4 && !(s & (s > 4 * NBIG ? 1 : 3))) {
                            __syncwarp();
                            flag_inc_if(l16, &g_flag[F_QKV + ((s > 4 * NBIG ? 2 * s - 4 * NBIG : s) - 4 + (h >> 3)) * 8]);
                        }
                        fence_async_smem();
                    }
                    asm volatile("{\n.reg .pred p;\nsetp.eq.u32 p, %0, 0;\n@p bar.sync 5, 256;\n@!p bar.sync 13, 256;\n}" :: "r"(wg) : "memory");
                }
                const uint64_t da0 = (uint64_t)(((sb + O_AS + wg * 8192) & 0x3FFFF) >> 4) | (1ull << 16) | (64ull << 32) | (1ull << 62);
                wg_fence();
                wgmma_n32_ss<1>(d, da0, XDESC(0));
#pragma unroll
                for (int u = 1; u < 28; u++) wgmma_n32_rs<1>(d, a[32 + 4 * u], a[32 + 4 * u + 1], a[32 + 4 * u + 2], a[32 + 4 * u + 3], XDESC(u));
                wg_commit();
                if (FLAGPOS == 1 && warp == 3 && s >= 4 && !(s & (s > 4 * NBIG ? 1 : 3)))
                    flag_inc_if(l16, &g_flag[F_QKV + ((s > 4 * NBIG ? 2 * s - 4 * NBIG : s) - 4 + (h >> 3)) * 8]);
                wg_wait0();
                if (!R2 && warp == 3 && s >= 0) store_qk();
                if (warp == 4) STAMP(s, 3);
                uint32_t e[8];
#pragma unroll
                for (int i = 0; i < 8; i++) e[i] = pack_bf16(d[2 * i], d[2 * i + 1]);
                if (!R2) {
                    const uint32_t base = sb + O_QKX + (j & 1) * 12288 + wg * 4096 + w * 512 + l16;
                    stsm4t(base, e[0], wg ? e[1] : e[2], wg ? e[2] : e[1], e[3]);
                    stsm4t(base + 2048, e[4], wg ? e[5] : e[6], wg ? e[6] : e[5], e[7]);
                } else {
                    const uint32_t base = sb + O_VX + (j & 1) * 8192 + warp * 1024 + l16;
                    sts128(base, e[0], e[1], e[2], e[3]);
                    sts128(base + 512, e[4], e[5], e[6], e[7]);
                    bar_arrive(14, 288);
                }
                if (warp == 7) STAMP(s, 4);
                if (s < 0) asm volatile("barrier.cluster.wait.aligned;" ::: "memory");
            }
        }
        };
        if (r == 2) qkv_loop(BoolC<true>()); else qkv_loop(BoolC<false>());
        bar_arrive(7, 384);
    } else {
        asm volatile("setmaxnreg.dec.sync.aligned.u32 136;");
        const int c = w;
        uint32_t a[96];
        uint32_t mmax = 0;
        {
            const int g = lane >> 2, t = lane & 3;
            uint32_t tag = 0, m0v[18];
            if (threadIdx.x == 256) tag = atomicAdd(&g_ticket, 1u);
#pragma unroll
            for (int i = 0; i < 9; i++) {
                const uint32_t* p = reinterpret_cast<const uint32_t*>(mem0 + g * DM + 16 * (4 * i + c) + 2 * t);
                m0v[2 * i] = __ldg(p); m0v[2 * i + 1] = __ldg(p + 4);
            }
            asm volatile("barrier.cluster.wait.aligned;" ::: "memory");
            if (c == 0) {
                tma_x_tile(sb, &tm_x, r, 0, 0);
                mbar_expect_if(lane, sb + B_SC, 4608);
                if (r < 2) mbar_expect_if(lane, sb + B_VX, 8192);
                sts32_if(lane, sb + O_MISC, __float_as_uint(1.0f));
                sts32_if(lane, sb + O_MISC + 12, __float_as_uint(SM_SCALE));
            }
            asm volatile("barrier.cluster.arrive.relaxed.aligned;" ::: "memory");
#pragma unroll
            for (int tau = 0; tau < 3; tau++) {
                const uint32_t* v = m0v + 6 * tau;
                sts128(sb + O_MF + tau * 3072 + c * 512 + lane * 16, v[0], v[1], v[2], v[3]);
                sts64(sb + O_MF + tau * 3072 + 2048 + (c >> 1) * 512 + lane * 16 + (c & 1) * 8, v[4], v[5]);
#pragma unroll
                for (int i = 0; i < 6; i++) mmax = __vmaxu2(mmax, v[i] & 0x7fff7fffu);
            }
            mmax = max(mmax << 16, mmax & 0xffff0000u);
            bar_arrive(2, 384); bar_arrive(15, 384);
            tag = (__shfl_sync(~0u, tag, 0) / 96u + 1u) & 0xffffu;
            mbar_wait(sb + B_W + 0, 0);
            const __nv_bfloat16* p = Wo + (size_t)(h * 128 + 4 * t) * DM + 192 * r + 16 * c + 2 * g;
#pragma unroll
            for (int i = 0; i < 3; i++)
#pragma unroll
                for (int eb = 0; eb < 8; eb++)
#pragma unroll
                    for (int j = 0; j < 4; j++) a[(i * 8 + eb) * 4 + j] = ldg_nc32(p + (16 * eb + ((j & 1) * 2 + (j >> 1))) * DM + 64 * i);
#pragma unroll
            for (int kk = 0; kk < 48; kk++) {
                uint32_t w0 = a[2 * kk], w1 = a[2 * kk + 1];
                a[2 * kk] = __byte_perm(w0, w1, 0x5410);
                a[2 * kk + 1] = __byte_perm(w0, w1, 0x7632);
            }
            sts128(sb + O_WP + c * 512 + lane * 16, a[92], a[93], a[94], a[95]);
            float wmax = 0.f;
#pragma unroll
            for (int i = 0; i < 3; i++) {
                float n0[4];
#pragma unroll
                for (int u = 8 * i; u < 8 * i + 8; u++) {
                    const uint32_t x0 = a[4 * u] & 0x7fff7fffu, x1 = a[4 * u + 1] & 0x7fff7fffu, x2 = a[4 * u + 2] & 0x7fff7fffu, x3 = a[4 * u + 3] & 0x7fff7fffu;
                    if (u == 8 * i) mma16816_z(n0, x0, x1, x2, x3, ONES, ONES);
                    else mma16816(n0, x0, x1, x2, x3, ONES, ONES);
                }
                wmax = fmaxf(wmax, fmaxf(n0[0], n0[2]));
            }
            uint32_t wm = __reduce_max_sync(~0u, __float_as_uint(wmax));
            sts32_if(lane, sb + O_OF + 4 * c, wm);
            if (c == 0) PSTAMP(8);
            bar_sync(7, 384);
            asm volatile("barrier.cluster.wait.aligned;" ::: "memory");
            if (c == 1) tma_x_tile(sb, &tm_x, r, 1, 1);
            if (c == 0) {
                const uint4 wq = lds128(sb + O_OF), xq = lds128(sb + O_OF + 16), xr = lds128(sb + O_OF + 32), v0 = lds128(sb + O_MISC + 32), v1 = lds128(sb + O_MISC + 48);
                const uint32_t w1 = max(max(wq.x, wq.y), max(wq.z, wq.w)), x1 = max(max(max(xq.x, xq.y), max(xq.z, xq.w)), max(max(xr.x, xr.y), max(xr.z, xr.w)));
                const uint32_t vv = (r < 2) ? 0u : max(max(max(v0.x, v0.y), max(v0.z, v0.w)), max(max(v1.x, v1.y), max(v1.z, v1.w)));
                const uint32_t lo = (min(w1, 0x7f800000u) + 0xffffu) >> 16 | ((min(vv, 0x7f800000u) + 0xffffu) & 0xffff0000u), hi = (x1 & 0xffff0000u) | tag;
                uint32_t l0, h0, l1, h1, l2, h2;
                asm volatile("{\n.reg .pred p;\n.reg .u32 n, x, y;\n.reg .b64 v;\nsetp.eq.u32 p, %10, 0;\nmov.b64 v, {%8, %9};\n@p st.relaxed.gpu.global.b64 [%7], v;\nmov.u32 n, 0;\n"
                             "G_%=: ld.relaxed.gpu.global.b64 v, [%6];\nmov.b64 {%0, %1}, v;\nld.relaxed.gpu.global.b64 v, [%6+256];\nmov.b64 {%2, %3}, v;\n"
                             "ld.relaxed.gpu.global.b64 v, [%6+512];\nmov.b64 {%4, %5}, v;\n"
                             "xor.b32 x, %1, %9;\nxor.b32 y, %3, %9;\nor.b32 x, x, y;\nxor.b32 y, %5, %9;\nor.b32 x, x, y;\nand.b32 x, x, 0xffff;\n"
                             "setp.eq.u32 p, x, 0;\nvote.sync.all.pred p, p, 0xffffffff;\n@p bra.uni E_%=;\n"
                             "add.u32 n, n, 1;\nsetp.lt.u32 p, n, 4000000;\n@p bra.uni G_%=;\ntrap;\nE_%=:\n}"
                             : "=&r"(l0), "=&r"(h0), "=&r"(l1), "=&r"(h1), "=&r"(l2), "=&r"(h2)
                             : "l"(&g_norm[lane]), "l"(&g_norm[blockIdx.x]), "r"(lo), "r"(hi), "r"(lane) : "memory");
                const uint32_t lm = __vmaxu2(l0, __vmaxu2(l1, l2));
                const float fw = __uint_as_float(__reduce_max_sync(~0u, lm << 16));
                const float fv = __uint_as_float(__reduce_max_sync(~0u, lm & 0xffff0000u));
                const float xmax = __uint_as_float(__reduce_max_sync(~0u, max(h0, max(h1, h2)) & 0xffff0000u));
                const float G = 36.f * fw * fv;
                sts32_if(lane, sb + O_MISC + 4, __float_as_uint(G)); sts32_if(lane, sb + O_MISC + 8, __float_as_uint(G * xmax));
            }
        }
        if (c == 0) PSTAMP(12);
        bar_sync(6, 128);
        int s3n = 1;
        uint32_t roff = __shfl_sync(~0u, (r * 4 + c) * 2048 + (lane >> 4) * 512 + (lane & 2) * 128 + (lane & 1) * 64 + (lane & 12) * 4, lane);
#pragma unroll 1
        for (int s = 0; s < NSEG; s++) {
            const uint32_t l16 = opaque(l16c);
            const uint32_t vxa = sb + O_VX + (s & 1) * 8192 + c * 2048 + l16;
            if (c == 0 && r == 2) {
                bar_sync(14, 288);
                fence_async_smem();
                asm volatile("{\n.reg .pred p;\nelect.sync _|p, 0xffffffff;\n"
                    "@p cp.async.bulk.global.shared::cta.bulk_group [%0], [%1], 8192;\n@p cp.async.bulk.commit_group;\n"
                    "cp.async.bulk.wait_group 0;\nsetp.lt.and.s32 p, %4, 63, p;\n"
                    "@p cp.async.bulk.shared::cluster.global.mbarrier::complete_tx::bytes.multicast::cluster [%1], [%0], 8192, [%2], %3;\n"
                    "fence.proxy.async.global;\n}"
                    :: "l"(reinterpret_cast<char*>(g_qkv) + (size_t)(s * NH + h) * REC + 20480), "r"(sb + O_VX + (s & 1) * 8192),
                       "r"(sb + B_VX + 8 * (s & 1)), "h"((unsigned short)3), "r"(s) : "memory");
            }
            if (s == NSEG - 1) { bar_sync(3, 384); mbar_wait(sb + B_SC, s & 1); break; }
            uint4 vx[4];
            sts32_if(l16, sb + O_MISC + 16 + 4 * c, __reduce_max_sync(~0u, mmax));
            if (c == 0) STAMP(s, 5);
            {
                bar_sync(6, 128);
                const uint4 mm = lds128(sb + O_MISC + 16), cf = lds128(sb + O_MISC);
                const float bound = fmaxf(__uint_as_float(cf.z), __uint_as_float(cf.y) * (__uint_as_float(max(max(mm.x, mm.y), max(mm.z, mm.w))) * __uint_as_float(cf.x)));
                const uint32_t ebits = __reduce_max_sync(~0u, min(max(__float_as_uint(bound) & 0x7f800000u, 21u << 23), 254u << 23));
                mbar_wait(sb + B_X + 8 * s3n, ((s + 1) / 3) & 1);
                s3n = (s3n == 2) ? 0 : s3n + 1;
                bar_sync(3, 384);
                if (r < 2) mbar_wait(sb + B_VX + 8 * (s & 1), (s >> 1) & 1);
                vx[0] = lds128(vxa); vx[2] = lds128(vxa + 1024);
                if (c == 0) STAMP(s, 13);
                mbar_wait(sb + B_SC, s & 1);
                if (c == 0) STAMP(s, 6);
                float p[10];
                load_scores(p, sb + O_SC, 1280, l16);
                float mx = fmaxf(fmaxf(fmaxf(p[0], p[1]), fmaxf(p[2], p[3])), fmaxf(fmaxf(p[4], p[5]), fmaxf(p[6], p[7])));
                mx = quad_max(fmaxf(mx, fmaxf(p[8], p[9])));
                const uint4 vm = lds64x2(sb + O_VM + c * 512 + (l16 >> 1));
                vx[1] = lds128(vxa + 512); vx[3] = lds128(vxa + 1536);
                bar_arrive(4, 384);
                const float sc = __uint_as_float(lds32(sb + O_MISC + 12));
                const float mo = mx * SM_SCALE;
                uint32_t P[5];
#pragma unroll
                for (int n = 0; n < 5; n++) P[n] = pack_bf16(ex2(fmaf(p[2 * n], SM_SCALE, -mo)), ex2(fmaf(p[2 * n + 1], n == 3 ? sc : SM_SCALE, -mo)));
                if (c == 0) STAMP(s, 7);
                float o0[4], o1[4], sm[4];
                mma16816_z(sm, ONES, ONES, ONES, ONES, P[1], P[2]);
                mma16816_z(o0, vx[0].x, vx[0].y, vx[0].z, vx[0].w, P[1], P[2]);
                mma16816_z(o1, vx[2].x, vx[2].y, vx[2].z, vx[2].w, P[1], P[2]);
                mma16816(sm, ONES, ONES, ONES, ONES, P[3], P[4]);
                mma16816(o0, vx[1].x, vx[1].y, vx[1].z, vx[1].w, P[3], P[4]);
                mma16816(o1, vx[3].x, vx[3].y, vx[3].z, vx[3].w, P[3], P[4]);
                mma1688(sm, ONES, ONES, P[0]);
                mma1688(o0, vm.x, vm.y, P[0]);
                mma1688(o1, vm.z, vm.w, P[0]);
                stsm4t(sb + O_OF + c * 512 + l16, pack_bf16(o0[0], o0[1]), pack_bf16(o0[2], o0[3]), pack_bf16(o1[0], o1[1]), pack_bf16(o1[2], o1[3]));
                const float sig = __uint_as_float((268u << 23) - ebits);
                const float r0 = rcp_fast(sm[0]) * sig, r1 = rcp_fast(sm[1]) * sig;
                bar_sync(6, 128);
                uint4 ob[4];
#pragma unroll
                for (int q = 0; q < 4; q++) ob[q] = ldsm4(sb + O_OF + q * 512 + l16);
                { const uint4 v = lds128(sb + O_WP + c * 512 + l16); a[92] = v.x; a[93] = v.y; a[94] = v.z; a[95] = v.w; }
                float m0[3][4], m1[3][4];
#pragma unroll
                for (int q = 0; q < 4; q++) {
#pragma unroll
                    for (int i = 0; i < 3; i++) {
                        const int k0 = (i * 8 + 2 * q) * 4;
                        if (q == 0) mma16816_z(m0[i], a[k0], a[k0 + 1], a[k0 + 2], a[k0 + 3], ob[q].x, ob[q].y);
                        else mma16816(m0[i], a[k0], a[k0 + 1], a[k0 + 2], a[k0 + 3], ob[q].x, ob[q].y);
                    }
#pragma unroll
                    for (int i = 0; i < 3; i++) {
                        const int k1 = (i * 8 + 2 * q + 1) * 4;
                        if (q == 0) mma16816_z(m1[i], a[k1], a[k1 + 1], a[k1 + 2], a[k1 + 3], ob[q].z, ob[q].w);
                        else mma16816(m1[i], a[k1], a[k1 + 1], a[k1 + 2], a[k1 + 3], ob[q].z, ob[q].w);
                    }
                }
                asm volatile("red.relaxed.gpu.global.add.noftz.v4.f16x2 [%0], {%1,%2,%3,%4};" :: "l"(reinterpret_cast<char*>(g_acc) + roff),
                    "r"(pack_f16(NRM(m0[0][0] + m1[0][0], r0), NRM(m0[0][2] + m1[0][2], r0))), "r"(pack_f16(NRM(m0[1][0] + m1[1][0], r0), NRM(m0[1][2] + m1[1][2], r0))),
                    "r"(pack_f16(NRM(m0[2][0] + m1[2][0], r0), NRM(m0[2][2] + m1[2][2], r0))), "r"(0x3c00u) : "memory");
                asm volatile("red.relaxed.gpu.global.add.noftz.v4.f16x2 [%0], {%1,%2,%3,%4};" :: "l"(reinterpret_cast<char*>(g_acc) + roff + 1024),
                    "r"(pack_f16(NRM(m0[0][1] + m1[0][1], r1), NRM(m0[0][3] + m1[0][3], r1))), "r"(pack_f16(NRM(m0[1][1] + m1[1][1], r1), NRM(m0[1][3] + m1[1][3], r1))),
                    "r"(pack_f16(NRM(m0[2][1] + m1[2][1], r1), NRM(m0[2][3] + m1[2][3], r1))), "r"(0x3c00u) : "memory");
                const unsigned t_red = clk();
                bar_arrive(5, 256);
                bar_arrive(13, 256);
                mbar_expect_if(l16 | c, sb + B_SC, 4608);
                mbar_expect_if(l16 | (c ^ 1) | (r >> 1), sb + B_VX + 8 * ((s + 1) & 1), 8192);
                sts32_if(l16 | (c ^ 3), sb + O_MISC, ebits - (14u << 23));
                if (c == 0) STAMPV(s, 8, t_red);
                if (ACC_PF && c == 2 && s + 4 < NSEG - 1)
                    asm volatile("prefetch.global.L2 [%0];" :: "l"(reinterpret_cast<const char*>(g_acc) + ((s + 4) * 96 + blockIdx.x) * 256 + (l16 & 96)) : "memory");
                const char* pbase = reinterpret_cast<const char*>(g_acc) + (s * 24576 + c * 2048) + ((l16 & 64) * 16 + (l16 & 256) + ((l16 & 128) >> 1) + (l16 & 48));
                spin_until(t_red, s < D_S0 ? D_EARLY : D_WAIT);
                uint4 v[6];
#pragma unroll
                for (int i = 0; i < 6; i++) v[i] = ldg_relaxed128(pbase + (i >> 1) * 8192 + (i & 1) * 512);
                int nretry = 0;
                auto convert = [&](int tau) {
                    const uint4 A = v[2 * tau], B = v[2 * tau + 1];
                    sts128(sb + O_MF + tau * 3072 + c * 512 + l16, f16x2_to_bf16x2(A.x), f16x2_to_bf16x2(B.x), f16x2_to_bf16x2(A.y), f16x2_to_bf16x2(B.y));
                    sts64(sb + O_MF + tau * 3072 + 2048 + (c >> 1) * 512 + (c & 1) * 8 + l16, f16x2_to_bf16x2(A.z), f16x2_to_bf16x2(B.z));
                };
                const uint32_t ok0 = __all_sync(~0u, (v[0].w & v[1].w) == 0x5000u);
                convert(0);
                asm volatile("{\n.reg .pred p;\nsetp.ne.u32 p, %0, 0;\n@p bar.arrive 2, 384;\n}" :: "r"(ok0) : "memory");
                sched_fence<0>(h);
                uint32_t ok1;
                asm volatile("{\n.reg .pred p, q;\n.reg .b32 x;\nlop3.b32 x, %1, %2, %3, 0x80;\nand.b32 x, x, %4;\n"
                             "setp.eq.u32 p, x, 0x5000;\nvote.sync.all.pred q, p, 0xffffffff;\nselp.u32 %0, 1, 0, q;\n}"
                             : "=r"(ok1) : "r"(v[2].w), "r"(v[3].w), "r"(v[4].w), "r"(v[5].w));
                convert(1); convert(2);
                asm volatile("{\n.reg .pred p;\nsetp.ne.u32 p, %0, 0;\n@p bar.arrive 15, 384;\n}" :: "r"(ok1) : "memory");
                if (!(ok0 & ok1)) {
                    asm volatile("{\n.reg .pred p0, p1, p2, p3, p4, p5, q;\n.reg .u32 n, x;\nmov.u32 n, 0;\n"
                         "R_%=: setp.ne.u32 p0, %3, 0x5000;\nsetp.ne.u32 p1, %7, 0x5000;\nsetp.ne.u32 p2, %11, 0x5000;\n"
                         "setp.ne.u32 p3, %15, 0x5000;\nsetp.ne.u32 p4, %19, 0x5000;\nsetp.ne.u32 p5, %23, 0x5000;\n"
                         "@p0 ld.relaxed.gpu.global.v4.u32 {%0,%1,%2,%3}, [%25];\n@p1 ld.relaxed.gpu.global.v4.u32 {%4,%5,%6,%7}, [%25+512];\n"
                         "@p2 ld.relaxed.gpu.global.v4.u32 {%8,%9,%10,%11}, [%25+8192];\n@p3 ld.relaxed.gpu.global.v4.u32 {%12,%13,%14,%15}, [%25+8704];\n"
                         "@p4 ld.relaxed.gpu.global.v4.u32 {%16,%17,%18,%19}, [%25+16384];\n@p5 ld.relaxed.gpu.global.v4.u32 {%20,%21,%22,%23}, [%25+16896];\n"
                         "add.u32 %24, %24, 1;\nand.b32 x, %3, %7;\nand.b32 x, x, %11;\nand.b32 x, x, %15;\nand.b32 x, x, %19;\nand.b32 x, x, %23;\n"
                         "setp.eq.u32 q, x, 0x5000;\nvote.sync.all.pred q, q, 0xffffffff;\n@q bra.uni K_%=;\n"
                         "add.u32 n, n, 1;\nsetp.lt.u32 q, n, 2000000;\n@q bra.uni R_%=;\ntrap;\nK_%=:\n}"
                         : "+r"(v[0].x), "+r"(v[0].y), "+r"(v[0].z), "+r"(v[0].w), "+r"(v[1].x), "+r"(v[1].y), "+r"(v[1].z), "+r"(v[1].w),
                           "+r"(v[2].x), "+r"(v[2].y), "+r"(v[2].z), "+r"(v[2].w), "+r"(v[3].x), "+r"(v[3].y), "+r"(v[3].z), "+r"(v[3].w),
                           "+r"(v[4].x), "+r"(v[4].y), "+r"(v[4].z), "+r"(v[4].w), "+r"(v[5].x), "+r"(v[5].y), "+r"(v[5].z), "+r"(v[5].w), "+r"(nretry)
                         : "l"(pbase) : "memory");
                    if (!ok0) { convert(0); bar_arrive(2, 384); }
                    if (!ok1) { convert(1); convert(2); bar_arrive(15, 384); }
                }
                if (c == 0) STAMP(s, 12);
                if (c == 0) STAMPV(s, 14, nretry);
                mmax = absmax2(absmax2(absmax2(v[0].x, v[0].y), absmax2(v[0].z, v[1].x)), absmax2(absmax2(v[1].y, v[1].z), absmax2(v[2].x, v[2].y)));
                mmax = absmax2(mmax, absmax2(absmax2(absmax2(v[2].z, v[3].x), absmax2(v[3].y, v[3].z)), absmax2(absmax2(v[4].x, v[4].y), absmax2(v[4].z, v[5].x))));
                mmax = absmax2(mmax, absmax2(v[5].y, v[5].z)) & 0x7fff7fffu;
                { const float2 mf = __half22float2(*reinterpret_cast<__half2*>(&mmax)); mmax = max(__float_as_uint(mf.x), __float_as_uint(mf.y)); }
            }
            roff += 24576;
        }
        {
            bar_sync(7, 384);
            if (c == 0) flag_inc_if(l16c, &g_flag[F_QKV + (4 * (NBLK - 1) + (h >> 3)) * 8]);
        }
    }
    if (warp == 8) PSTAMP(13);
    cluster_sync();
}

constexpr int NST = 10;
constexpr int G_RING = 0, G_EX = NST * 16384, G_OUT = G_EX + 32768, G_CARRY = G_OUT + 32768, G_OPS = G_CARRY + 512, G_BAR = G_OPS + 256, BG_SMEM = G_BAR + 256;
constexpr int GB_FULL = G_BAR, GB_EMPTY = G_BAR + 8 * NST, GB_W = G_BAR + 16 * NST;
static_assert(BG_SMEM <= 232448, "smem");

template <int ACC>
__device__ __forceinline__ void wgmma_n128_rs(float (&d)[64], uint32_t a0, uint32_t a1, uint32_t a2, uint32_t a3, uint64_t desc) {
    asm volatile("wgmma.mma_async.sync.aligned.m64n128k16.f32.bf16.bf16 "
        "{%0,%1,%2,%3,%4,%5,%6,%7,%8,%9,%10,%11,%12,%13,%14,%15,%16,%17,%18,%19,%20,%21,%22,%23,%24,%25,%26,%27,%28,%29,%30,%31,"
        "%32,%33,%34,%35,%36,%37,%38,%39,%40,%41,%42,%43,%44,%45,%46,%47,%48,%49,%50,%51,%52,%53,%54,%55,%56,%57,%58,%59,%60,%61,%62,%63}, "
        "{%64,%65,%66,%67}, %68, %69, 1, 1, 0;"
        : "+f"(d[0]), "+f"(d[1]), "+f"(d[2]), "+f"(d[3]), "+f"(d[4]), "+f"(d[5]), "+f"(d[6]), "+f"(d[7]),
          "+f"(d[8]), "+f"(d[9]), "+f"(d[10]), "+f"(d[11]), "+f"(d[12]), "+f"(d[13]), "+f"(d[14]), "+f"(d[15]),
          "+f"(d[16]), "+f"(d[17]), "+f"(d[18]), "+f"(d[19]), "+f"(d[20]), "+f"(d[21]), "+f"(d[22]), "+f"(d[23]),
          "+f"(d[24]), "+f"(d[25]), "+f"(d[26]), "+f"(d[27]), "+f"(d[28]), "+f"(d[29]), "+f"(d[30]), "+f"(d[31]),
          "+f"(d[32]), "+f"(d[33]), "+f"(d[34]), "+f"(d[35]), "+f"(d[36]), "+f"(d[37]), "+f"(d[38]), "+f"(d[39]),
          "+f"(d[40]), "+f"(d[41]), "+f"(d[42]), "+f"(d[43]), "+f"(d[44]), "+f"(d[45]), "+f"(d[46]), "+f"(d[47]),
          "+f"(d[48]), "+f"(d[49]), "+f"(d[50]), "+f"(d[51]), "+f"(d[52]), "+f"(d[53]), "+f"(d[54]), "+f"(d[55]),
          "+f"(d[56]), "+f"(d[57]), "+f"(d[58]), "+f"(d[59]), "+f"(d[60]), "+f"(d[61]), "+f"(d[62]), "+f"(d[63])
        : "r"(a0), "r"(a1), "r"(a2), "r"(a3), "l"(desc), "n"(ACC));
}
template <int ACC>
__device__ __forceinline__ void wgmma_n64_rs(float (&d)[64], uint32_t a0, uint32_t a1, uint32_t a2, uint32_t a3, uint64_t desc) {
    asm volatile("wgmma.mma_async.sync.aligned.m64n64k16.f32.bf16.bf16 "
        "{%0,%1,%2,%3,%4,%5,%6,%7,%8,%9,%10,%11,%12,%13,%14,%15,%16,%17,%18,%19,%20,%21,%22,%23,%24,%25,%26,%27,%28,%29,%30,%31}, "
        "{%32,%33,%34,%35}, %36, %37, 1, 1, 0;"
        : "+f"(d[0]), "+f"(d[1]), "+f"(d[2]), "+f"(d[3]), "+f"(d[4]), "+f"(d[5]), "+f"(d[6]), "+f"(d[7]),
          "+f"(d[8]), "+f"(d[9]), "+f"(d[10]), "+f"(d[11]), "+f"(d[12]), "+f"(d[13]), "+f"(d[14]), "+f"(d[15]),
          "+f"(d[16]), "+f"(d[17]), "+f"(d[18]), "+f"(d[19]), "+f"(d[20]), "+f"(d[21]), "+f"(d[22]), "+f"(d[23]),
          "+f"(d[24]), "+f"(d[25]), "+f"(d[26]), "+f"(d[27]), "+f"(d[28]), "+f"(d[29]), "+f"(d[30]), "+f"(d[31])
        : "r"(a0), "r"(a1), "r"(a2), "r"(a3), "l"(desc), "n"(ACC));
}
__device__ __forceinline__ void wait_flag(const unsigned* p, unsigned target) {
    asm volatile("{\n.reg .pred p;\n.reg .u32 n, v;\nmov.u32 n, 0;\n"
                 "W_%=: ld.acquire.gpu.global.u32 v, [%0];\nsub.u32 v, v, %1;\nsetp.ge.s32 p, v, 0;\n@p bra.uni D_%=;\nnanosleep.u32 " NSLEEP ";\n"
                 "add.u32 n, n, 1;\nsetp.lt.u32 p, n, 4000000;\n@p bra.uni W_%=;\ntrap;\nD_%=:\n}" :: "l"(p), "r"(target) : "memory");
}
template <int NS, int NT>
__device__ __forceinline__ void bg_mainloop(float (&d)[64], const uint32_t (&a)[144], uint32_t sb, int it, int lane) {
    int slot = it % NST, ph = (it / NST) & 1, prev = 0;
#pragma unroll
    for (int i = 0; i < NS; i++) {
        mbar_wait(sb + GB_FULL + 8 * slot, ph);
        const uint64_t desc = (uint64_t)(((sb + G_RING + slot * 16384) & 0x3FFFF) >> 4) | (1ull << 16) | (64ull << 32) | (1ull << 62);
        wg_fence();
#pragma unroll
        for (int k = 0; k < 512 / NT; k++) {
            const int u = (2048 / NT) * i + 4 * k;
            if (NT == 128) {
                if (i == 0 && k == 0) wgmma_n128_rs<0>(d, a[u], a[u + 1], a[u + 2], a[u + 3], desc);
                else wgmma_n128_rs<1>(d, a[u], a[u + 1], a[u + 2], a[u + 3], desc + 2 * k);
            } else {
                if (i == 0 && k == 0) wgmma_n64_rs<0>(d, a[u], a[u + 1], a[u + 2], a[u + 3], desc);
                else wgmma_n64_rs<1>(d, a[u], a[u + 1], a[u + 2], a[u + 3], desc + 2 * (k & 3) + (k >> 2) * 512);
            }
        }
        wg_commit();
        if (i > 0) {
            asm volatile("wgmma.wait_group.sync.aligned 1;" ::: "memory");
            mbar_arrive_if(lane, sb + GB_EMPTY + 8 * prev);
        }
        prev = slot;
        slot += 2;
        if (slot >= NST) { slot -= NST; ph ^= 1; }
    }
    wg_wait0();
    mbar_arrive_if(lane, sb + GB_EMPTY + 8 * prev);
}
template <bool SKIP, int NT>
__device__ __forceinline__ void bg_epilogue(float (&d)[64], uint32_t sb, int wg, int w, int lane, const CUtensorMap* tm_out, int col0, int tok0,
                                            const __nv_bfloat16* xa, const __nv_bfloat16* Dk) {
    constexpr int H = NT / 4;
    const int g = lane >> 2, t = lane & 3;
    const uint32_t ex = sb + G_EX + w * 4096 + lane * 16;
    float k[H];
    if (wg == 0) {
#pragma unroll
        for (int q = 0; q < H / 4; q++) sts128f(ex + q * 512, d[H + 4 * q], d[H + 4 * q + 1], d[H + 4 * q + 2], d[H + 4 * q + 3]);
#pragma unroll
        for (int i = 0; i < H; i++) k[i] = d[i];
    } else {
#pragma unroll
        for (int q = 0; q < H / 4; q++) sts128f(ex + 16384 + q * 512, d[4 * q], d[4 * q + 1], d[4 * q + 2], d[4 * q + 3]);
#pragma unroll
        for (int i = 0; i < H; i++) k[i] = d[H + i];
    }
    uint32_t xv[16], dv = 0;
    if (SKIP) {
        const __nv_bfloat16* xp = xa + (size_t)(tok0 + 64 * wg + 2 * t) * DM + col0 + 16 * w + 2 * g;
#pragma unroll
        for (int i = 0; i < 16; i++) xv[i] = ldg_nc32(xp + (8 * (i >> 1) + (i & 1)) * DM);
        dv = ldg_nc32(Dk + col0 + 16 * w + 2 * g);
    }
    if (SKIP && w == 0) asm volatile("cp.async.bulk.wait_group.read 0;" ::: "memory");
    bar_sync(1, 256);
#pragma unroll
    for (int q = 0; q < H / 4; q++) {
        const float4 o = lds128f(ex + (wg ^ 1) * 16384 + q * 512);
        k[4 * q] += o.x; k[4 * q + 1] += o.y; k[4 * q + 2] += o.z; k[4 * q + 3] += o.w;
    }
    if (SKIP) bar_sync(1, 256); else bar_sync(13, 288);
    const uint32_t ob = sb + G_OUT + wg * (NT == 128 ? 16384 : 4096) + (w >> 1) * 8192 + (g & 1) * 8;
    const uint32_t ch = (w & 1) * 4 + (g >> 1);
#pragma unroll
    for (int i = 0; i < H / 2; i++) {
        float v0 = k[4 * (i >> 1) + (i & 1)], v1 = k[4 * (i >> 1) + 2 + (i & 1)];
        if (SKIP) {
            const uint32_t p = pack_bf16(__uint_as_float(xv[i] << 16) * __uint_as_float(dv << 16), __uint_as_float(xv[i] & 0xffff0000u) * __uint_as_float(dv & 0xffff0000u));
            v0 += __uint_as_float(p << 16); v1 += __uint_as_float(p & 0xffff0000u);
        }
        const uint32_t n7 = 2 * t + (i & 1);
        sts64(ob + (8 * (i >> 1) + n7) * 128 + ((ch ^ n7) << 4), __float_as_uint(v0), __float_as_uint(v1));
    }
    fence_async_smem();
    if (SKIP) {
        bar_sync(4 + wg, 128);
        if (w == 0)
            asm volatile("{\n.reg .pred p;\nelect.sync _|p, 0xffffffff;\n"
                "@p cp.async.bulk.tensor.2d.global.shared::cta.bulk_group [%0, {%2, %4}], [%1];\n"
                "@p cp.async.bulk.tensor.2d.global.shared::cta.bulk_group [%0, {%3, %4}], [%1+8192];\n@p cp.async.bulk.commit_group;\n}"
                :: "l"(tm_out), "r"(sb + G_OUT + wg * 16384), "r"(col0), "r"(col0 + 32), "r"(tok0 + 64 * wg) : "memory");
    } else {
        bar_arrive(12, 288);
    }
}
__device__ __forceinline__ void s5_channel(int p, const __nv_bfloat16* Lre, const __nv_bfloat16* Lim, const __nv_bfloat16* logdt, float2& lam, float2& coef) {
    const float dt = __bfloat162float(__float2bfloat16(expf(__bfloat162float(logdt[p]))));
    const float lr = __bfloat162float(Lre[p]), li = __bfloat162float(Lim[p]);
    const float e = expf(dt * lr);
    float sn, cs;
    sincosf(dt * li, &sn, &cs);
    lam = make_float2(e * cs, e * sn);
    const float den = lr * lr + li * li;
    coef = make_float2(((lam.x - 1.f) * lr + lam.y * li) / den, (lam.y * lr - (lam.x - 1.f) * li) / den);
}
__device__ __forceinline__ float2 cfma(float2 a, float2 b, float2 c) {
    return make_float2(fmaf(a.x, b.x, fmaf(-a.y, b.y, c.x)), fmaf(a.x, b.y, fmaf(a.y, b.x, c.y)));
}
__device__ __forceinline__ uint4 ldg128(const void* p) { uint4 v; asm volatile("ld.global.v4.u32 {%0,%1,%2,%3}, [%4];" : "=r"(v.x), "=r"(v.y), "=r"(v.z), "=r"(v.w) : "l"(p) : "memory"); return v; }
__device__ __forceinline__ uint2 ldg64(const void* p) { uint2 v; asm volatile("ld.global.v2.u32 {%0,%1}, [%2];" : "=r"(v.x), "=r"(v.y) : "l"(p) : "memory"); return v; }

template <int MT>
__device__ __forceinline__ void bg_attention(uint32_t st0, uint32_t st1, int lane) {
    constexpr int NK = MT ? 5 : 3;
    const int g = lane >> 2, t = lane & 3;
    float sc[NK][4], sm2[4];
#pragma unroll
    for (int i = 0; i < 8; i++) {
        const uint32_t st = (i >> 2 ? st1 : st0) + (i & 3) * 512 + lane * 16;
        const uint4 q = ldsm4(st + MT * 2048), km = ldsm4(st + 8192), k0 = ldsm4(st + 4096);
        if (i == 0) {
            mma16816_z(sc[0], q.x, q.y, q.z, q.w, km.x, km.y); mma16816_z(sm2, q.x, q.y, q.z, q.w, km.z, km.w);
            mma16816_z(sc[1], q.x, q.y, q.z, q.w, k0.x, k0.y); mma16816_z(sc[2], q.x, q.y, q.z, q.w, k0.z, k0.w);
        } else {
            mma16816(sc[0], q.x, q.y, q.z, q.w, km.x, km.y); mma16816(sm2, q.x, q.y, q.z, q.w, km.z, km.w);
            mma16816(sc[1], q.x, q.y, q.z, q.w, k0.x, k0.y); mma16816(sc[2], q.x, q.y, q.z, q.w, k0.z, k0.w);
        }
        if (MT) {
            const uint4 k1 = ldsm4(st + 6144);
            if (i == 0) { mma16816_z(sc[NK - 2], q.x, q.y, q.z, q.w, k1.x, k1.y); mma16816_z(sc[NK - 1], q.x, q.y, q.z, q.w, k1.z, k1.w); }
            else { mma16816(sc[NK - 2], q.x, q.y, q.z, q.w, k1.x, k1.y); mma16816(sc[NK - 1], q.x, q.y, q.z, q.w, k1.z, k1.w); }
        }
    }
#pragma unroll
    for (int i = 0; i < 4; i++) sc[0][i] += sm2[i];
    if (2 * t > g) { sc[NK - 2][0] = -INFINITY; sc[NK - 1][2] = -INFINITY; }
    if (2 * t + 1 > g) { sc[NK - 2][1] = -INFINITY; sc[NK - 1][3] = -INFINITY; }
    sc[NK - 1][0] = sc[NK - 1][1] = -INFINITY;
    float ma = fmaxf(sc[0][0], sc[0][1]), mb = fmaxf(sc[0][2], sc[0][3]);
#pragma unroll
    for (int n = 1; n < NK; n++) { ma = fmaxf(ma, fmaxf(sc[n][0], sc[n][1])); mb = fmaxf(mb, fmaxf(sc[n][2], sc[n][3])); }
    ma = quad_max(ma) * SM_SCALE; mb = quad_max(mb) * SM_SCALE;
    uint32_t Pa[NK], Pb[NK];
#pragma unroll
    for (int n = 0; n < NK; n++) {
        Pa[n] = n == NK - 1 ? 0u : pack_bf16(ex2(fmaf(sc[n][0], SM_SCALE, -ma)), ex2(fmaf(sc[n][1], SM_SCALE, -ma)));
        Pb[n] = pack_bf16(ex2(fmaf(sc[n][2], SM_SCALE, -mb)), ex2(fmaf(sc[n][3], SM_SCALE, -mb)));
    }
    float sa[4], sbb[4];
    mma1688_z(sa, ONES, ONES, Pa[0]); mma1688_z(sbb, ONES, ONES, Pb[0]);
    mma16816(sa, ONES, ONES, ONES, ONES, Pa[1], Pa[2]); mma16816(sbb, ONES, ONES, ONES, ONES, Pb[1], Pb[2]);
    if (MT) { mma16816(sa, ONES, ONES, ONES, ONES, Pa[NK - 2], Pa[NK - 1]); mma16816(sbb, ONES, ONES, ONES, ONES, Pb[NK - 2], Pb[NK - 1]); }
    const float ra0 = rcp_fast(sa[0]), ra1 = rcp_fast(sa[1]), rb0 = rcp_fast(sbb[0]), rb1 = rcp_fast(sbb[1]);
    const uint32_t row = lane & 7;
    const uint32_t so = MT * 2048 + (lane >> 4) * 1024 + row * 128;
#pragma unroll
    for (int eh = 0; eh < 2; eh++) {
        const uint32_t st = eh ? st1 : st0;
        float2 vm[4]; uint4 v0[4], v1[4];
#pragma unroll
        for (int e4 = 0; e4 < 4; e4++) {
            vm[e4] = lds64f(st + 14336 + e4 * 256 + lane * 8);
            v0[e4] = lds128(st + 10240 + e4 * 1024 + lane * 16);
            if (MT) v1[e4] = lds128(st + 10240 + e4 * 1024 + 512 + lane * 16);
        }
        float oa[4][4], ob[4][4];
#pragma unroll
        for (int e4 = 0; e4 < 4; e4++) {
            mma1688_z(oa[e4], __float_as_uint(vm[e4].x), __float_as_uint(vm[e4].y), Pa[0]);
            mma1688_z(ob[e4], __float_as_uint(vm[e4].x), __float_as_uint(vm[e4].y), Pb[0]);
        }
#pragma unroll
        for (int e4 = 0; e4 < 4; e4++) {
            mma16816(oa[e4], v0[e4].x, v0[e4].y, v0[e4].z, v0[e4].w, Pa[1], Pa[2]);
            mma16816(ob[e4], v0[e4].x, v0[e4].y, v0[e4].z, v0[e4].w, Pb[1], Pb[2]);
        }
        if (MT) {
#pragma unroll
            for (int e4 = 0; e4 < 4; e4++) {
                mma16816(oa[e4], v1[e4].x, v1[e4].y, v1[e4].z, v1[e4].w, Pa[NK - 2], Pa[NK - 1]);
                mma16816(ob[e4], v1[e4].x, v1[e4].y, v1[e4].z, v1[e4].w, Pb[NK - 2], Pb[NK - 1]);
            }
        }
#pragma unroll
        for (int e4 = 0; e4 < 4; e4++)
            stsm4t(st + so + (((2 * e4 + ((lane >> 3) & 1)) ^ row) << 4), pack_bf16(oa[e4][0] * ra0, oa[e4][1] * ra1), pack_bf16(oa[e4][2] * ra0, oa[e4][3] * ra1),
                   pack_bf16(ob[e4][0] * rb0, ob[e4][1] * rb1), pack_bf16(ob[e4][2] * rb0, ob[e4][3] * rb1));
    }
}
__device__ __forceinline__ bool wait_either(const unsigned* pa, unsigned ta, bool allow_a, const unsigned* pg, unsigned tg, bool allow_g) {
    uint32_t res;
    asm volatile("{\n.reg .pred p, qa, qg;\n.reg .u32 n, v, u;\nmov.u32 n, 0;\nsetp.ne.u32 qa, %5, 0;\nsetp.ne.u32 qg, %6, 0;\n"
                 "W_%=: mov.u32 %0, 1;\n@!qa bra.uni G_%=;\nld.acquire.gpu.global.u32 v, [%1];\nsub.u32 v, v, %2;\nsetp.ge.s32 p, v, 0;\n@p bra.uni D_%=;\n"
                 "G_%=: mov.u32 %0, 0;\n@!qg bra.uni S_%=;\nld.acquire.gpu.global.u32 u, [%3];\nsub.u32 u, u, %4;\nsetp.ge.s32 p, u, 0;\n@p bra.uni D_%=;\nS_%=: "
                 "nanosleep.u32 " NSLEEP ";\nadd.u32 n, n, 1;\nsetp.lt.u32 p, n, 4000000;\n@p bra.uni W_%=;\ntrap;\n"
                 "D_%=: fence.proxy.async.global;\n}"
                 : "=r"(res) : "l"(pa), "r"(ta), "l"(pg), "r"(tg), "r"((uint32_t)allow_a), "r"((uint32_t)allow_g) : "memory");
    return res != 0;
}

__global__ void __launch_bounds__(384, 1)
bg_kernel(const __grid_constant__ CUtensorMap tm_xa, const __grid_constant__ CUtensorMap tm_wo, const __grid_constant__ CUtensorMap tm_out,
          const __nv_bfloat16* __restrict__ xa, const __nv_bfloat16* __restrict__ Lre, const __nv_bfloat16* __restrict__ Lim,
          const __nv_bfloat16* __restrict__ Bre, const __nv_bfloat16* __restrict__ Bim, const __nv_bfloat16* __restrict__ Cre,
          const __nv_bfloat16* __restrict__ Cim, const __nv_bfloat16* __restrict__ logdt, const __nv_bfloat16* __restrict__ Dk, float* __restrict__ out) {
    extern __shared__ __align__(1024) uint8_t smem_raw[];
    const uint32_t sb = smem_u32(smem_raw);
    const int lane = threadIdx.x & 31;
    const int warp = __shfl_sync(~0u, threadIdx.x >> 5, 0);
    const int wg = warp >> 2, w = warp & 3, b = blockIdx.x;
    const int nt = b % 9, kq = b / 9;
    BSTAMP(0);
    if (threadIdx.x == 0) {
        if (sb & 1023u) __trap();
        for (int i = 0; i < NST; i++) { mbar_init(sb + GB_FULL + 8 * i, 1); mbar_init(sb + GB_EMPTY + 8 * i, 4); }
        mbar_init(sb + GB_W, 1);
        asm volatile("fence.mbarrier_init.release.cluster;" ::: "memory");
        mbar_expect(sb + GB_W, (b < 18 ? 64 : 128) * 1152);
        sts32(sb + G_BAR + 248, atomicAdd(&g_ticket_bg, 1u) / 36u + 1u);
    }
    __syncthreads();
    if (wg == 2) {
        asm volatile("setmaxnreg.dec.sync.aligned.u32 24;");
        if (w == 0) {
            int slot = 0, ph = 1;
            auto next = [&]() { if (++slot == NST) { slot = 0; ph ^= 1; } };
            bar_sync(6, 288);
            if (b < 18) {
#pragma unroll 1
                for (int i = 0; i < 144; i++) {
                    const int blk = i / 9, kb = i - 9 * blk, it = (blk >> 1) * 18 + (blk & 1) + 2 * kb;
                    slot = it % NST;
                    mbar_wait(sb + GB_EMPTY + 8 * slot, ((it / NST) & 1) ^ 1);
                    asm volatile("{\n.reg .pred p;\nelect.sync _|p, 0xffffffff;\n@p mbarrier.arrive.expect_tx.shared::cta.b64 _, [%2], 16384;\n"
                        "@p cp.async.bulk.tensor.5d.shared::cluster.global.mbarrier::complete_tx::bytes [%0], [%1, {%3, %4, %4, %4, %5}], [%2];\n}"
                        :: "r"(sb + G_RING + slot * 16384), "l"(&tm_xa), "r"(sb + GB_FULL + 8 * slot), "r"(kb * 64), "r"(0), "r"(blk) : "memory");
                }
                slot = 144 % NST; ph = ((144 / NST) & 1) ^ 1;
            }
            const unsigned ep = lds32(sb + G_BAR + 248);
            auto slabs = [&](const char* src, int ns) {
                asm volatile("fence.proxy.async.global;" ::: "memory");
#pragma unroll 1
                for (int i = 0; i < ns; i++) {
                    mbar_wait(sb + GB_EMPTY + 8 * slot, ph);
                    asm volatile("{\n.reg .pred p;\nelect.sync _|p, 0xffffffff;\n@p mbarrier.arrive.expect_tx.shared::cta.b64 _, [%2], 16384;\n"
                        "@p cp.async.bulk.shared::cluster.global.mbarrier::complete_tx::bytes [%0], [%1], 16384, [%2];\n}"
                        :: "r"(sb + G_RING + slot * 16384), "l"(src + (size_t)((i & 1) * (ns >> 1) + (i >> 1)) * (SEQ * 128)), "r"(sb + GB_FULL + 8 * slot) : "memory");
                    next();
                }
            };
            if (b >= 18) {
#pragma unroll 1
                for (int blk = kq - 2; blk < 16; blk += 2) {
                    wait_flag(&g_flag[F_H + blk * 8], 18 * ep);
                    slabs(reinterpret_cast<const char*>(g_h) + blk * 16384, 18);
                }
            }
            bar_sync(6, 288);
#pragma unroll 1
            for (int na = nt < 8 ? 0 : NBLK, ng = 0, k = 0; ng < NBLK; k++) {
                const bool att = wait_either(&g_flag[F_QKV + (min(na, NBLK - 1) * 4 + kq) * 8], 24 * ep, na < NBLK && na <= ng + 1,
                                             &g_flag[F_OX + (ng * 4 + kq) * 8], 8 * ep, ng < na);
                sts32_if(lane, sb + G_OPS + 4 * k, att);
                __syncwarp();
                if (att) {
                    {
#pragma unroll 1
                        for (int i = 0; i < (na < NBIG ? 8 : 4); i++) {
                            const int hf = (i >> 1) & 1;
                            const char* rec = reinterpret_cast<const char*>(g_qkv) + (size_t)((blk_seg0(na) + 2 * (i >> 2) + (i & 1)) * NH + 8 * kq + nt) * REC;
                            mbar_wait(sb + GB_EMPTY + 8 * slot, ph);
                            asm volatile("{\n.reg .pred p;\nelect.sync _|p, 0xffffffff;\n@p mbarrier.arrive.expect_tx.shared::cta.b64 _, [%4], 15360;\n"
                                "@p cp.async.bulk.shared::cluster.global.mbarrier::complete_tx::bytes [%0], [%1], 10240, [%4];\n"
                                "@p cp.async.bulk.shared::cluster.global.mbarrier::complete_tx::bytes [%0+10240], [%2], 4096, [%4];\n"
                                "@p cp.async.bulk.shared::cluster.global.mbarrier::complete_tx::bytes [%0+14336], [%3], 1024, [%4];\n}"
                                :: "r"(sb + G_RING + slot * 16384), "l"(rec + hf * 10240), "l"(rec + 20480 + hf * 4096), "l"(rec + 28672 + hf * 1024),
                                   "r"(sb + GB_FULL + 8 * slot) : "memory");
                            next();
                        }
                    }
                    na++;
                } else {
                    const char* src = reinterpret_cast<const char*>(g_ox) + (size_t)kq * 16 * SEQ * 128 + blk_seg0(ng) * 4096;
                    if (ng < NBIG) slabs(src, 16);
                    else {
#pragma unroll 1
                        for (int i = 0; i < 8; i++) {
                            mbar_wait(sb + GB_EMPTY + 8 * slot, ph);
                            asm volatile("{\n.reg .pred p;\nelect.sync _|p, 0xffffffff;\n@p mbarrier.arrive.expect_tx.shared::cta.b64 _, [%2], 16384;\n"
                                "@p cp.async.bulk.shared::cluster.global.mbarrier::complete_tx::bytes [%0], [%1], 8192, [%2];\n"
                                "@p cp.async.bulk.shared::cluster.global.mbarrier::complete_tx::bytes [%0+8192], [%1+262144], 8192, [%2];\n}"
                                :: "r"(sb + G_RING + slot * 16384), "l"(src + (size_t)((i & 1) * 8 + (i & 6)) * (SEQ * 128)), "r"(sb + GB_FULL + 8 * slot) : "memory");
                            next();
                        }
                    }
                    ng++;
                }
            }
        } else if (w == 1) {
            if (b < 18) {
#pragma unroll 1
                for (int blk = 0; blk < 16; blk++) {
                    bar_sync(8 + (blk & 1), 160);
                    asm volatile("{\n.reg .pred p;\nelect.sync _|p, 0xffffffff;\n@p cp.async.bulk.global.shared::cta.bulk_group [%0], [%1], 16384;\n"
                        "@p cp.async.bulk.commit_group;\ncp.async.bulk.wait_group 0;\nfence.proxy.async.global;\n}"
                        :: "l"(reinterpret_cast<char*>(g_h) + ((size_t)b * SEQ + blk * 128) * 128), "r"(sb + G_OUT + (blk & 1) * 16384) : "memory");
                    bar_arrive(10 + (blk & 1), 160);
                    flag_inc_if(lane, &g_flag[F_H + blk * 8]);
                }
            }
            if (nt < 8) {
#pragma unroll 1
                for (int na = 0; na < NBLK; na++) {
                    {
                        const int ns = na < NBIG ? 8 : 4;
                        bar_sync(7, 288);
                        const int it = lds32(sb + G_OPS + 252);
                        if (lane < ns) {
                            asm volatile("cp.async.bulk.global.shared::cta.bulk_group [%0], [%1], 4096;\ncp.async.bulk.commit_group;\ncp.async.bulk.wait_group.read 0;\n"
                                "mbarrier.arrive.shared::cta.b64 _, [%2], 4;\ncp.async.bulk.wait_group 0;\nfence.proxy.async.global;"
                                :: "l"(reinterpret_cast<char*>(g_ox) + ((size_t)((8 * kq + nt) * 2 + ((lane >> 1) & 1)) * SEQ + (blk_seg0(na) + 2 * (lane >> 2) + (lane & 1)) * 32) * 128),
                                   "r"(sb + G_RING + ((it + lane) % NST) * 16384), "r"(sb + GB_EMPTY + 8 * ((it + lane) % NST)) : "memory");
                        }
                        __syncwarp();
                        bar_arrive(14, 288);
                        flag_inc_if(lane, &g_flag[F_OX + (na * 4 + kq) * 8]);
                    }
                }
            }
        } else if (w == 2) {
            const unsigned ep = lds32(sb + G_BAR + 248);
#pragma unroll 1
            for (int blk = 0; blk < NBLK; blk++) {
                const bool last = blk == NBLK - 1, add = kq || last;
                bar_arrive(13, 288);
                bar_sync(12, 288);
                if (add) { wait_flag(&g_flag[F_OUT + (blk * 9 + nt) * 8], ep); asm volatile("fence.proxy.async.global;" ::: "memory"); }
#pragma unroll 1
                for (int i = 0; i < (blk < NBIG ? 4 : 2); i++) {
                    const uint32_t src = sb + G_OUT + i * 8192;
                    const int c0 = DM + 64 * nt + (i & 1) * 32, c1 = blk_seg0(blk) * 32 + (i >> 1) * 64;
                    if (add) asm volatile("{\n.reg .pred p;\nelect.sync _|p, 0xffffffff;\n@p cp.reduce.async.bulk.tensor.2d.global.shared::cta.add.bulk_group [%0, {%2, %3}], [%1];\n}"
                                 :: "l"(&tm_out), "r"(src), "r"(c0), "r"(c1) : "memory");
                    else asm volatile("{\n.reg .pred p;\nelect.sync _|p, 0xffffffff;\n@p cp.async.bulk.tensor.2d.global.shared::cta.bulk_group [%0, {%2, %3}], [%1];\n}"
                                 :: "l"(&tm_out), "r"(src), "r"(c0), "r"(c1) : "memory");
                    if (add && blk < NBIG - 1) spin_until(clk(), RED_GAP);
                }
                asm volatile("cp.async.bulk.commit_group;\ncp.async.bulk.wait_group 0;\nfence.proxy.async.global;" ::: "memory");
                __syncwarp();
                if (!add) flag_inc_if(lane, &g_flag[F_OUT + (blk * 9 + nt) * 8]);
                if (!kq && blk == NBLK - 4) {
                    float4* z = reinterpret_cast<float4*>(out + (size_t)(SEQ - 64 + (lane >> 4)) * (2 * DM) + DM + 64 * nt) + (lane & 15);
#pragma unroll 1
                    for (int i = 0; i < 32; i++) z[i * (4 * DM / 4)] = make_float4(0.f, 0.f, 0.f, 0.f);
                    __syncwarp();
                    flag_inc_if(lane, &g_flag[F_OUT + ((NBLK - 1) * 9 + nt) * 8]);
                }
            }
        }
    } else {
        asm volatile("setmaxnreg.inc.sync.aligned.u32 240;");
        const int g = lane >> 2, t = lane & 3, tid = threadIdx.x;
        uint32_t a[144];
        float d[64];
        if (b < 18) {
            if (tid < 64)
                asm volatile("cp.async.bulk.shared::cluster.global.mbarrier::complete_tx::bytes [%0], [%1], 1152, [%2];"
                    :: "r"(sb + tid * 1168), "l"((tid < 32 ? Bre : Bim) + (size_t)(32 * b + (tid & 31)) * DM), "r"(sb + GB_W) : "memory");
            float2 lam, coef;
            s5_channel(32 * b + 8 * w + g, Lre, Lim, logdt, lam, coef);
            float2 l32 = lam;
#pragma unroll
            for (int i = 0; i < 5; i++) l32 = make_float2(l32.x * l32.x - l32.y * l32.y, 2.f * l32.x * l32.y);
            __syncwarp();
            mbar_wait(sb + GB_W, 0);
            const uint32_t ap = sb + (((lane >> 3) & 1) * 32 + 8 * w + (lane & 7)) * 1168 + (lane >> 4) * 16;
#pragma unroll
            for (int ks = 0; ks < 36; ks++) { const uint4 v = ldsm4(ap + ks * 32); a[4 * ks] = v.x; a[4 * ks + 1] = v.y; a[4 * ks + 2] = v.z; a[4 * ks + 3] = v.w; }
            bar_sync(1, 256);
            bar_arrive(6, 288);
            BSTAMP(1);
#pragma unroll 1
            for (int blk = wg; blk < 16; blk += 2) {
                bg_mainloop<9, 128>(d, a, sb, (blk >> 1) * 18 + wg, lane);
                float2 e = make_float2(0.f, 0.f);
#pragma unroll
                for (int i = 0; i < 32; i++) e = cfma(lam, e, make_float2(d[4 * (i >> 1) + (i & 1)], d[4 * (i >> 1) + 2 + (i & 1)]));
                float2 cin = make_float2(0.f, 0.f);
                if (blk > 0) { bar_sync(2 + (wg ^ 1), 256); cin = lds64f(sb + G_CARRY + (wg ^ 1) * 256 + (8 * w + g) * 8); }
                float2 mine = cin;
#pragma unroll
                for (int q = 0; q < 4; q++) {
                    const float2 eq = make_float2(__shfl_sync(~0u, e.x, (lane & 28) + q), __shfl_sync(~0u, e.y, (lane & 28) + q));
                    cin = cfma(l32, cin, eq);
                    if (t == q + 1) mine = cin;
                }
                if (blk < 15) {
                    if (t == 0) sts64(sb + G_CARRY + wg * 256 + (8 * w + g) * 8, __float_as_uint(cin.x), __float_as_uint(cin.y));
                    bar_arrive(2 + wg, 256);
                }
                const uint32_t hs = sb + G_OUT + wg * 16384 + t * 4096 + (g & 3) * 4;
                const uint32_t ch = 2 * w + (g >> 2);
                if (blk >= 2) bar_sync(10 + wg, 160);
#pragma unroll
                for (int i = 0; i < 32; i++) {
                    mine = cfma(lam, mine, make_float2(d[4 * (i >> 1) + (i & 1)], d[4 * (i >> 1) + 2 + (i & 1)]));
                    sts32(hs + i * 128 + ((ch ^ (i & 7)) << 4), pack_bf16(mine.x, mine.y));
                }
                fence_async_smem();
                bar_arrive(8 + wg, 160);
            }
            bar_sync(10 + wg, 160);
        } else {
            if (tid < 128)
                asm volatile("cp.async.bulk.shared::cluster.global.mbarrier::complete_tx::bytes [%0], [%1], 1152, [%2];"
                    :: "r"(sb + tid * 1168), "l"((tid < 64 ? Cre : Cim) + (size_t)(64 * nt + (tid & 63)) * DM), "r"(sb + GB_W) : "memory");
            for (int p = tid; p < DM; p += 256) {
                float2 lam, coef;
                s5_channel(p, Lre, Lim, logdt, lam, coef);
                sts64(sb + G_EX + p * 8, __float_as_uint(2.f * coef.x), __float_as_uint(2.f * coef.y));
            }
            bar_sync(1, 256);
            mbar_wait(sb + GB_W, 0);
            const uint32_t cp = sb + (16 * w + 2 * g) * 1168 + (288 * wg + t) * 2;
#pragma unroll
            for (int u = 0; u < 72; u++) {
                const float2 c2 = lds64f(sb + G_EX + (288 * wg + 4 * u + t) * 8);
#pragma unroll
                for (int f = 0; f < 2; f++) {
                    unsigned short r16, i16;
                    asm volatile("ld.shared.u16 %0, [%1];" : "=h"(r16) : "r"(cp + f * 1168 + u * 8) : "memory");
                    asm volatile("ld.shared.u16 %0, [%1];" : "=h"(i16) : "r"(cp + (64 + f) * 1168 + u * 8) : "memory");
                    const float cr = __uint_as_float((uint32_t)r16 << 16), ci = __uint_as_float((uint32_t)i16 << 16);
                    a[2 * u + f] = pack_bf16(cr * c2.x - ci * c2.y, -(cr * c2.y + ci * c2.x));
                }
            }
            bar_sync(1, 256);
            bar_arrive(6, 288);
            BSTAMP(1);
#pragma unroll 1
            for (int j = 0; j < 8; j++) {
                bg_mainloop<9, 128>(d, a, sb, j * 18 + wg, lane);
                bg_epilogue<true, 128>(d, sb, wg, w, lane, &tm_out, 64 * nt, (2 * j + kq - 2) * 128, xa, Dk);
            }
        }
        if (w == 0) asm volatile("cp.async.bulk.wait_group 0;" ::: "memory");
        bar_sync(1, 256);
        BSTAMP(2);
        if (warp == 0)
            asm volatile("{\n.reg .pred p;\nelect.sync _|p, 0xffffffff;\n@p mbarrier.arrive.expect_tx.shared::cta.b64 _, [%2], 131072;\n"
                "@p cp.async.bulk.tensor.2d.shared::cluster.global.mbarrier::complete_tx::bytes [%0], [%1, {%3, %4}], [%2];\n"
                "@p cp.async.bulk.tensor.2d.shared::cluster.global.mbarrier::complete_tx::bytes [%0+32768], [%1, {%3, %5}], [%2];\n"
                "@p cp.async.bulk.tensor.2d.shared::cluster.global.mbarrier::complete_tx::bytes [%0+65536], [%1, {%3, %6}], [%2];\n"
                "@p cp.async.bulk.tensor.2d.shared::cluster.global.mbarrier::complete_tx::bytes [%0+98304], [%1, {%3, %7}], [%2];\n}"
                :: "r"(sb), "l"(&tm_wo), "r"(sb + GB_W), "r"(64 * nt), "r"(1024 * kq), "r"(1024 * kq + 256), "r"(1024 * kq + 512), "r"(1024 * kq + 768) : "memory");
        mbar_wait(sb + GB_W, 1);
        {
            const uint32_t base = sb + wg * 65536 + 4 * t * 128 + (g & 3) * 4, ch = 2 * w + (g >> 2), r7 = (4 * t) & 7;
#pragma unroll
            for (int ks = 0; ks < 32; ks++) {
                const uint32_t w0 = lds32(base + ks * 2048 + ((ch ^ r7) << 4)), w1 = lds32(base + ks * 2048 + 256 + ((ch ^ (r7 + 2)) << 4));
                const uint32_t w2 = lds32(base + ks * 2048 + 128 + ((ch ^ (r7 + 1)) << 4)), w3 = lds32(base + ks * 2048 + 384 + ((ch ^ (r7 + 3)) << 4));
                a[4 * ks] = __byte_perm(w0, w1, 0x5410); a[4 * ks + 1] = __byte_perm(w0, w1, 0x7632);
                a[4 * ks + 2] = __byte_perm(w2, w3, 0x5410); a[4 * ks + 3] = __byte_perm(w2, w3, 0x7632);
            }
        }
        bar_sync(1, 256);
        bar_arrive(6, 288);
        BSTAMP(3);
#pragma unroll 1
        for (int na = 0, ng = 0, it = 144, k = 0; ng < NBLK; k++) {
            mbar_wait(sb + GB_FULL + 8 * ((it + wg) % NST), ((it + wg) / NST) & 1);
            if (__shfl_sync(~0u, lds32(sb + G_OPS + 4 * k), 0)) {
                {
                    if (na < NBIG || (w >> 1) == wg) {
                        const int i0 = it + wg + (na < NBIG ? 4 * (w >> 1) : 0), i1 = i0 + 2;
                        mbar_wait(sb + GB_FULL + 8 * (i0 % NST), (i0 / NST) & 1);
                        mbar_wait(sb + GB_FULL + 8 * (i1 % NST), (i1 / NST) & 1);
                        BSTAMP(8 + na * 4);
                        if ((w ^ wg) & 1) bg_attention<1>(sb + G_RING + (i0 % NST) * 16384, sb + G_RING + (i1 % NST) * 16384, lane);
                        else bg_attention<0>(sb + G_RING + (i0 % NST) * 16384, sb + G_RING + (i1 % NST) * 16384, lane);
                        fence_async_smem();
                    }
                    if (na > 0) bar_sync(14, 288);
                    if (tid == 0) sts32(sb + G_OPS + 252, it);
                    bar_arrive(7, 288);
                    bar_sync(1, 256);
                    BSTAMP(9 + na * 4);
                    it += na < NBIG ? 8 : 4;
                }
                na++;
            } else if (ng < NBIG) {
                bg_mainloop<8, 128>(d, a, sb, it + wg, lane);
                BSTAMP(10 + ng * 4);
                bg_epilogue<false, 128>(d, sb, wg, w, lane, &tm_out, 0, 0, xa, Dk);
                BSTAMP(11 + ng * 4);
                it += 16; ng++;
            } else {
                bg_mainloop<4, 64>(d, a, sb, it + wg, lane);
                BSTAMP(10 + ng * 4);
                bg_epilogue<false, 64>(d, sb, wg, w, lane, &tm_out, 0, 0, xa, Dk);
                BSTAMP(11 + ng * 4);
                it += 8; ng++;
            }
        }
        if (nt < 8) bar_sync(14, 288);
    }
    asm volatile("griddepcontrol.wait;" ::: "memory");
}

typedef CUresult (*EncodeFn)(CUtensorMap*, CUtensorMapDataType, cuuint32_t, void*, const cuuint64_t*, const cuuint64_t*, const cuuint32_t*, const cuuint32_t*,
                             CUtensorMapInterleave, CUtensorMapSwizzle, CUtensorMapL2promotion, CUtensorMapFloatOOBfill);
}

extern "C" void kernel_launch(void* const* d_in, const int* in_sizes, int n_in, void* d_out, int out_size) {
    typedef const __nv_bfloat16* bp;
    bp Ax = (bp)d_in[0], Lre = (bp)d_in[1], Lim = (bp)d_in[2], Bre = (bp)d_in[3], Bim = (bp)d_in[4], Cre = (bp)d_in[5], Cim = (bp)d_in[6],
       logdt = (bp)d_in[7], Dk = (bp)d_in[8], Bx = (bp)d_in[9], mem0 = (bp)d_in[10], Wq = (bp)d_in[11], Wk = (bp)d_in[12], Wv = (bp)d_in[13], Wo = (bp)d_in[14];
    float* out = (float*)d_out;
    static EncodeFn enc = nullptr;
    if (!enc) {
        void* fn = nullptr; cudaDriverEntryPointQueryResult qr;
        cudaGetDriverEntryPoint("cuTensorMapEncodeTiled", &fn, cudaEnableDefault, &qr);
        enc = (EncodeFn)fn;
        cudaFuncSetAttribute(chain_kernel, cudaFuncAttributeMaxDynamicSharedMemorySize, CHAIN_SMEM);
        cudaFuncSetAttribute(bg_kernel, cudaFuncAttributeMaxDynamicSharedMemorySize, BG_SMEM);
    }
    const cuuint32_t es[5] = {1, 1, 1, 1, 1};
    auto map2d = [&](CUtensorMap* tm, CUtensorMapDataType dt, const void* p, cuuint64_t d0, cuuint64_t d1, cuuint64_t stride, cuuint32_t b0, cuuint32_t b1) {
        cuuint64_t gd[2] = {d0, d1}, gs[1] = {stride}; cuuint32_t bd[2] = {b0, b1};
        enc(tm, dt, 2, (void*)p, gd, gs, bd, es, CU_TENSOR_MAP_INTERLEAVE_NONE, CU_TENSOR_MAP_SWIZZLE_128B, CU_TENSOR_MAP_L2_PROMOTION_L2_128B,
            CU_TENSOR_MAP_FLOAT_OOB_FILL_NONE);
    };
    CUtensorMap tm_x, tm_q, tm_k, tm_v, tm_xa, tm_wo, tm_out;
    map2d(&tm_x, CU_TENSOR_MAP_DATA_TYPE_BFLOAT16, Bx, DM, SEQ, DM * 2, 64, 32);
    map2d(&tm_q, CU_TENSOR_MAP_DATA_TYPE_BFLOAT16, Wq, HD, DM, HD * 2, 64, 192);
    map2d(&tm_k, CU_TENSOR_MAP_DATA_TYPE_BFLOAT16, Wk, HD, DM, HD * 2, 64, 192);
    map2d(&tm_v, CU_TENSOR_MAP_DATA_TYPE_BFLOAT16, Wv, HD, DM, HD * 2, 64, 192);
    map2d(&tm_wo, CU_TENSOR_MAP_DATA_TYPE_BFLOAT16, Wo, DM, HD, DM * 2, 64, 256);
    map2d(&tm_out, CU_TENSOR_MAP_DATA_TYPE_FLOAT32, out, 2 * DM, SEQ, 2 * DM * 4, 32, 64);
    {
        cuuint64_t gd[5] = {DM, 2, 4, 16, 16}, gs[4] = {DM * 2, 32 * DM * 2, 2 * DM * 2, 128 * DM * 2}; cuuint32_t bd[5] = {64, 2, 4, 16, 1};
        enc(&tm_xa, CU_TENSOR_MAP_DATA_TYPE_BFLOAT16, 5, (void*)Ax, gd, gs, bd, es, CU_TENSOR_MAP_INTERLEAVE_NONE, CU_TENSOR_MAP_SWIZZLE_128B,
            CU_TENSOR_MAP_L2_PROMOTION_L2_128B, CU_TENSOR_MAP_FLOAT_OOB_FILL_NONE);
    }
    cudaStream_t st = cudaStreamPerThread;
    chain_kernel<<<96, 384, CHAIN_SMEM, st>>>(tm_x, tm_q, tm_k, tm_v, Bx, mem0, Wo);
    cudaLaunchConfig_t cfg = {};
    cfg.gridDim = dim3(36); cfg.blockDim = dim3(384); cfg.dynamicSmemBytes = BG_SMEM; cfg.stream = st;
    cudaLaunchAttribute at[1];
    at[0].id = cudaLaunchAttributeProgrammaticStreamSerialization; at[0].val.programmaticStreamSerializationAllowed = 1;
    cfg.attrs = at; cfg.numAttrs = 1;
    cudaLaunchKernelEx(&cfg, bg_kernel, tm_xa, tm_wo, tm_out, Ax, Lre, Lim, Bre, Bim, Cre, Cim, logdt, Dk, out);
}
```

```cpp
#include <cuda_runtime.h>
#include <cuda.h>
#include <cuda_bf16.h>
#include <cuda_fp16.h>
#include <stdint.h>

#define D_WAIT 740

#define RED_GAP 720
#define ACC_PF 1
#define QDEP 0
#define NSLEEP "40"
#define D_S0 34
#define D_EARLY 820
#define FLAGPOS 0
#define NORM_LATE 1
#define NRM(x, r) (NORM_LATE ? (x) * (r) : (x))
#define NBIG 14

namespace {

constexpr int DM = 576, NH = 32, SEQ = 2048, NSEG = 64, HD = 4096;

__device__ uint4 g_acc_raw[64 * 96 * 16 + 131072];
__device__ uint4 g_ox[NH * 2 * SEQ * 8];
constexpr int REC = 30720;
__device__ uint4 g_qkv[NSEG * NH * (REC / 16)];
__device__ uint4 g_h[18 * SEQ * 8];
constexpr int NFLAG = 6144, F_QKV = 0, F_OX = 1024, F_H = 2048, F_OUT = 3072;
constexpr int NBLK = NBIG + (NSEG - 4 * NBIG) / 2;
__host__ __device__ constexpr int blk_seg0(int b) { return b < NBIG ? 4 * b : 2 * b + 2 * NBIG; }
__device__ unsigned g_flag[NFLAG];
__device__ unsigned g_ticket, g_ticket_bg;
__device__ unsigned long long g_norm[96];
#define BSTAMP(i) do {} while (0)

__device__ __forceinline__ uint32_t smem_u32(const void* p) { return (uint32_t)__cvta_generic_to_shared(p); }
__device__ __forceinline__ uint32_t mapa(uint32_t a, uint32_t r) { uint32_t o; asm("mapa.shared::cluster.u32 %0, %1, %2;" : "=r"(o) : "r"(a), "r"(r)); return o; }
__device__ __forceinline__ uint32_t mapa_v(uint32_t a, uint32_t r) { uint32_t o; asm volatile("mapa.shared::cluster.u32 %0, %1, %2;" : "=r"(o) : "r"(a), "r"(r)); return o; }
__device__ __forceinline__ unsigned clk() { unsigned long long c; asm volatile("mov.u64 %0, %%clock64;" : "=l"(c) :: "memory"); return (unsigned)c; }
__device__ __forceinline__ void mbar_init(uint32_t bar, uint32_t cnt) { asm volatile("mbarrier.init.shared::cta.b64 [%0], %1;" :: "r"(bar), "r"(cnt) : "memory"); }
__device__ __forceinline__ void mbar_expect(uint32_t bar, uint32_t bytes) { asm volatile("mbarrier.arrive.expect_tx.shared::cta.b64 _, [%0], %1;" :: "r"(bar), "r"(bytes) : "memory"); }
__device__ __forceinline__ void mbar_wait(uint32_t bar, uint32_t parity) {
    asm volatile("{\n.reg .pred p;\n.reg .u32 n;\nmov.u32 n, 0;\n"
                 "W_%=: mbarrier.try_wait.parity.shared::cta.b64 p, [%0], %1;\n@p bra.uni D_%=;\n"
                 "add.u32 n, n, 1;\nsetp.lt.u32 p, n, 4000000;\n@p bra.uni W_%=;\ntrap;\nD_%=:\n}" :: "r"(bar), "r"(parity) : "memory");
}
__device__ __forceinline__ void mbar_expect_if(uint32_t z, uint32_t bar, uint32_t bytes) {
    asm volatile("{\n.reg .pred p;\nsetp.eq.u32 p, %2, 0;\n@p mbarrier.arrive.expect_tx.shared::cta.b64 _, [%0], %1;\n}" :: "r"(bar), "r"(bytes), "r"(z) : "memory");
}
__device__ __forceinline__ void mbar_arrive_if(uint32_t z, uint32_t bar) {
    asm volatile("{\n.reg .pred p;\nsetp.eq.u32 p, %1, 0;\n@p mbarrier.arrive.shared::cta.b64 _, [%0];\n}" :: "r"(bar), "r"(z) : "memory");
}
__device__ __forceinline__ void sts32_if(uint32_t z, uint32_t a, uint32_t x) {
    asm volatile("{\n.reg .pred p;\nsetp.eq.u32 p, %2, 0;\n@p st.shared.u32 [%0], %1;\n}" :: "r"(a), "r"(x), "r"(z) : "memory");
}
template <int K> __device__ __forceinline__ void sched_fence(int v) {
    asm volatile("{\n.reg .pred p;\nsetp.ne.s32 p, %0, %1;\n@p bra.uni F_%=;\ntrap;\nF_%=:\n}" :: "r"(v), "n"(1000 + K) : "memory");
}
__device__ __forceinline__ void spin_until(unsigned t0, unsigned d) {
    asm volatile("{\n.reg .pred p;\n.reg .u64 c;\n.reg .u32 lo;\n"
                 "S_%=: mov.u64 c, %%clock64;\ncvt.u32.u64 lo, c;\nsub.u32 lo, lo, %0;\nsetp.lt.u32 p, lo, %1;\n@p bra.uni S_%=;\n}" :: "r"(t0), "r"(d) : "memory");
}
__device__ __forceinline__ void bar_sync(int id, int n) { asm volatile("bar.sync %0, %1;" :: "r"(id), "r"(n) : "memory"); }
__device__ __forceinline__ void bar_sync_sel(int sel, int id) {
    asm volatile("{\n.reg .pred p;\nsetp.eq.u32 p, %0, 0;\n@p bar.sync %1, %3;\n@!p bar.sync %2, %3;\n}" :: "r"(sel), "r"(id), "r"(id + 1), "n"(192) : "memory");
}
__device__ __forceinline__ void bar_arrive(int id, int n) { asm volatile("bar.arrive %0, %1;" :: "r"(id), "r"(n) : "memory"); }
__device__ __forceinline__ void fence_async_smem() { asm volatile("fence.proxy.async.shared::cta;" ::: "memory"); }
__device__ __forceinline__ uint32_t pack_bf16(float lo, float hi) { uint32_t r; asm("cvt.rn.bf16x2.f32 %0, %1, %2;" : "=r"(r) : "f"(hi), "f"(lo)); return r; }
__device__ __forceinline__ uint32_t pack_f16(float lo, float hi) { uint32_t r; asm("cvt.rn.f16x2.f32 %0, %1, %2;" : "=r"(r) : "f"(hi), "f"(lo)); return r; }
__device__ __forceinline__ uint32_t f16x2_to_bf16x2(uint32_t v) { float2 f = __half22float2(*reinterpret_cast<__half2*>(&v)); return pack_bf16(f.x, f.y); }
__device__ __forceinline__ uint32_t hmul2(uint32_t a, uint32_t b) { uint32_t r; asm("mul.rn.f16x2 %0, %1, %2;" : "=r"(r) : "r"(a), "r"(b)); return r; }
__device__ __forceinline__ float ex2(float x) { float y; asm("ex2.approx.ftz.f32 %0, %1;" : "=f"(y) : "f"(x)); return y; }
__device__ __forceinline__ float ex2v(float x) { float y; asm volatile("ex2.approx.ftz.f32 %0, %1;" : "=f"(y) : "f"(x)); return y; }
__device__ __forceinline__ uint32_t absmax2(uint32_t a, uint32_t b) {
    uint32_t r; asm("max.xorsign.abs.f16x2 %0, %1, %2;" : "=r"(r) : "r"(a), "r"(b)); return r;
}
__device__ __forceinline__ uint32_t shl_v(uint32_t a, int n) { return a << n; }
__device__ __forceinline__ uint32_t max3u(uint32_t a, uint32_t b, uint32_t c) { return max(max(a, b), c); }
__device__ __forceinline__ uint4 lds128(uint32_t a) { uint4 v; asm volatile("ld.shared.v4.u32 {%0,%1,%2,%3}, [%4];" : "=r"(v.x), "=r"(v.y), "=r"(v.z), "=r"(v.w) : "r"(a) : "memory"); return v; }
__device__ __forceinline__ uint4 lds128v(uint32_t a) { uint4 v; asm volatile("ld.volatile.shared.v4.u32 {%0,%1,%2,%3}, [%4];" : "=r"(v.x), "=r"(v.y), "=r"(v.z), "=r"(v.w) : "r"(a) : "memory"); return v; }
__device__ __forceinline__ float4 lds128f(uint32_t a) { float4 v; asm volatile("ld.shared.v4.f32 {%0,%1,%2,%3}, [%4];" : "=f"(v.x), "=f"(v.y), "=f"(v.z), "=f"(v.w) : "r"(a) : "memory"); return v; }
__device__ __forceinline__ float2 lds64f(uint32_t a) { float2 v; asm volatile("ld.shared.v2.f32 {%0,%1}, [%2];" : "=f"(v.x), "=f"(v.y) : "r"(a) : "memory"); return v; }
__device__ __forceinline__ uint4 lds64x2(uint32_t a) { uint4 v; asm volatile("ld.shared.v2.u32 {%0,%1}, [%4];\nld.shared.v2.u32 {%2,%3}, [%4+256];" : "=r"(v.x), "=r"(v.y), "=r"(v.z), "=r"(v.w) : "r"(a) : "memory"); return v; }
__device__ __forceinline__ uint32_t lds32(uint32_t a) { uint32_t v; asm volatile("ld.shared.u32 %0, [%1];" : "=r"(v) : "r"(a) : "memory"); return v; }
__device__ __forceinline__ void sts128(uint32_t a, uint32_t x, uint32_t y, uint32_t z, uint32_t w) { asm volatile("st.shared.v4.u32 [%0], {%1,%2,%3,%4};" :: "r"(a), "r"(x), "r"(y), "r"(z), "r"(w) : "memory"); }
__device__ __forceinline__ void sts128f(uint32_t a, float x, float y, float z, float w) { asm volatile("st.shared.v4.f32 [%0], {%1,%2,%3,%4};" :: "r"(a), "f"(x), "f"(y), "f"(z), "f"(w) : "memory"); }
__device__ __forceinline__ void sts64(uint32_t a, uint32_t x, uint32_t y) { asm volatile("st.shared.v2.u32 [%0], {%1,%2};" :: "r"(a), "r"(x), "r"(y) : "memory"); }
__device__ __forceinline__ void sts32(uint32_t a, uint32_t x) { asm volatile("st.shared.u32 [%0], %1;" :: "r"(a), "r"(x) : "memory"); }
__device__ __forceinline__ uint4 ldsm4(uint32_t a) { uint4 v; asm volatile("ldmatrix.sync.aligned.m8n8.x4.shared.b16 {%0,%1,%2,%3}, [%4];" : "=r"(v.x), "=r"(v.y), "=r"(v.z), "=r"(v.w) : "r"(a) : "memory"); return v; }
__device__ __forceinline__ void stsm2t(uint32_t a, uint32_t x, uint32_t y) { asm volatile("stmatrix.sync.aligned.m8n8.x2.trans.shared.b16 [%0], {%1,%2};" :: "r"(a), "r"(x), "r"(y) : "memory"); }
__device__ __forceinline__ void stsm4t(uint32_t a, uint32_t x, uint32_t y, uint32_t z, uint32_t w) { asm volatile("stmatrix.sync.aligned.m8n8.x4.trans.shared.b16 [%0], {%1,%2,%3,%4};" :: "r"(a), "r"(x), "r"(y), "r"(z), "r"(w) : "memory"); }
__device__ __forceinline__ void st_async64(uint32_t a, uint32_t x, uint32_t y, uint32_t bar) { asm volatile("st.async.shared::cluster.mbarrier::complete_tx::bytes.v2.b32 [%0], {%1,%2}, [%3];" :: "r"(a), "r"(x), "r"(y), "r"(bar) : "memory"); }
__device__ __forceinline__ void bulk_s2c(uint32_t dst, uint32_t src, uint32_t bytes, uint32_t bar) { asm volatile("cp.async.bulk.shared::cluster.shared::cta.mbarrier::complete_tx::bytes [%0], [%1], %2, [%3];" :: "r"(dst), "r"(src), "r"(bytes), "r"(bar) : "memory"); }
__device__ __forceinline__ void bulk_s2g(void* dst, uint32_t src, uint32_t bytes) { asm volatile("cp.async.bulk.global.shared::cta.bulk_group [%0], [%1], %2;" :: "l"(dst), "r"(src), "r"(bytes) : "memory"); }
__device__ __forceinline__ uint32_t ldg_nc32(const void* p) { uint32_t v; asm volatile("ld.global.nc.L2::128B.u32 %0, [%1];" : "=r"(v) : "l"(p)); return v; }
__device__ __forceinline__ uint4 ldg_relaxed128(const void* p) { uint4 v; asm volatile("ld.relaxed.gpu.global.v4.u32 {%0,%1,%2,%3}, [%4];" : "=r"(v.x), "=r"(v.y), "=r"(v.z), "=r"(v.w) : "l"(p) : "memory"); return v; }
__device__ __forceinline__ void mma16816(float (&d)[4], uint32_t a0, uint32_t a1, uint32_t a2, uint32_t a3, uint32_t b0, uint32_t b1) {
    asm volatile("mma.sync.aligned.m16n8k16.row.col.f32.bf16.bf16.f32 {%0,%1,%2,%3}, {%4,%5,%6,%7}, {%8,%9}, {%0,%1,%2,%3};"
        : "+f"(d[0]), "+f"(d[1]), "+f"(d[2]), "+f"(d[3]) : "r"(a0), "r"(a1), "r"(a2), "r"(a3), "r"(b0), "r"(b1));
}
__device__ __forceinline__ void mma16816_z(float (&d)[4], uint32_t a0, uint32_t a1, uint32_t a2, uint32_t a3, uint32_t b0, uint32_t b1) {
    asm volatile("mma.sync.aligned.m16n8k16.row.col.f32.bf16.bf16.f32 {%0,%1,%2,%3}, {%4,%5,%6,%7}, {%8,%9}, {%10,%10,%10,%10};"
        : "=f"(d[0]), "=f"(d[1]), "=f"(d[2]), "=f"(d[3]) : "r"(a0), "r"(a1), "r"(a2), "r"(a3), "r"(b0), "r"(b1), "f"(0.f));
}
__device__ __forceinline__ void mma1688(float (&d)[4], uint32_t a0, uint32_t a1, uint32_t b0) {
    asm volatile("mma.sync.aligned.m16n8k8.row.col.f32.bf16.bf16.f32 {%0,%1,%2,%3}, {%4,%5}, {%6}, {%0,%1,%2,%3};"
        : "+f"(d[0]), "+f"(d[1]), "+f"(d[2]), "+f"(d[3]) : "r"(a0), "r"(a1), "r"(b0));
}
__device__ __forceinline__ void mma1688_z(float (&d)[4], uint32_t a0, uint32_t a1, uint32_t b0) {
    asm volatile("mma.sync.aligned.m16n8k8.row.col.f32.bf16.bf16.f32 {%0,%1,%2,%3}, {%4,%5}, {%6}, {%7,%7,%7,%7};"
        : "=f"(d[0]), "=f"(d[1]), "=f"(d[2]), "=f"(d[3]) : "r"(a0), "r"(a1), "r"(b0), "f"(0.f));
}
template <int ACC>
__device__ __forceinline__ void wgmma_n32_rs(float (&d)[16], uint32_t a0, uint32_t a1, uint32_t a2, uint32_t a3, uint64_t desc) {
    asm volatile("wgmma.mma_async.sync.aligned.m64n32k16.f32.bf16.bf16 {%0,%1,%2,%3,%4,%5,%6,%7,%8,%9,%10,%11,%12,%13,%14,%15}, {%16,%17,%18,%19}, %20, %21, 1, 1, 0;"
        : "+f"(d[0]), "+f"(d[1]), "+f"(d[2]), "+f"(d[3]), "+f"(d[4]), "+f"(d[5]), "+f"(d[6]), "+f"(d[7]),
          "+f"(d[8]), "+f"(d[9]), "+f"(d[10]), "+f"(d[11]), "+f"(d[12]), "+f"(d[13]), "+f"(d[14]), "+f"(d[15])
        : "r"(a0), "r"(a1), "r"(a2), "r"(a3), "l"(desc), "n"(ACC));
}
template <int ACC>
__device__ __forceinline__ void wgmma_n32_ss(float (&d)[16], uint64_t da, uint64_t db) {
    asm volatile("wgmma.mma_async.sync.aligned.m64n32k16.f32.bf16.bf16 {%0,%1,%2,%3,%4,%5,%6,%7,%8,%9,%10,%11,%12,%13,%14,%15}, %16, %17, %18, 1, 1, 0, 0;"
        : "+f"(d[0]), "+f"(d[1]), "+f"(d[2]), "+f"(d[3]), "+f"(d[4]), "+f"(d[5]), "+f"(d[6]), "+f"(d[7]),
          "+f"(d[8]), "+f"(d[9]), "+f"(d[10]), "+f"(d[11]), "+f"(d[12]), "+f"(d[13]), "+f"(d[14]), "+f"(d[15])
        : "l"(da), "l"(db), "n"(ACC));
}
__device__ __forceinline__ void wg_fence() { asm volatile("wgmma.fence.sync.aligned;" ::: "memory"); }
__device__ __forceinline__ void wg_commit() { asm volatile("wgmma.commit_group.sync.aligned;" ::: "memory"); }
__device__ __forceinline__ void wg_wait0() { asm volatile("wgmma.wait_group.sync.aligned 0;" ::: "memory"); }
__device__ __forceinline__ void cluster_sync() { asm volatile("barrier.cluster.arrive.aligned;\nbarrier.cluster.wait.aligned;" ::: "memory"); }

#define STAMP(s, i) do {} while (0)
#define STAMPV(s, i, v) do {} while (0)

constexpr int XT_BYTES = 36864;
constexpr int O_XT = 0;
constexpr int O_STG = XT_BYTES;
constexpr int O_AS = 3 * XT_BYTES;
constexpr int O_XP = O_AS + 16384;
constexpr int O_QKX = O_XP + 8192;
constexpr int O_KM = O_QKX + 8192;
constexpr int O_QM = O_QKX + 10240;
constexpr int O_VX = O_STG + 147456;
constexpr int O_VM = O_VX + 16384;
constexpr int O_SC = O_VM + 2048;
constexpr int O_OF = O_SC + 3072;
constexpr int O_AF = O_OF + 2048;
constexpr int O_WP = O_AF + 4096;
constexpr int O_MF = O_WP + 2048;
constexpr int O_MISC = O_MF + 9216;
static_assert(O_QKX + 24576 <= O_VX, "smem");
constexpr int O_BAR = O_MISC + 64;
constexpr int CHAIN_SMEM = O_BAR + 128;
static_assert(CHAIN_SMEM <= 232448, "smem");
constexpr int B_X = O_BAR, B_VX = O_BAR + 24, B_SC = O_BAR + 40, B_W = O_BAR + 48;
constexpr float SM_SCALE = 0.08838834764831845f * 1.4426950408889634f;
constexpr uint32_t ONES = 0x3f803f80u;

template <bool B> struct BoolC { static constexpr bool value = B; };
__device__ __forceinline__ uint32_t opaque(uint32_t v) { uint32_t o; asm volatile("mov.u32 %0, %1;" : "=r"(o) : "r"(v)); return o; }
__device__ __forceinline__ void st_async128(uint32_t a, uint32_t x, uint32_t y, uint32_t z, uint32_t w, uint32_t bar) {
    asm volatile("st.async.shared::cluster.mbarrier::complete_tx::bytes.v4.b32 [%0], {%1,%2,%3,%4}, [%5];" :: "r"(a), "r"(x), "r"(y), "r"(z), "r"(w), "r"(bar) : "memory");
}
__device__ __forceinline__ void tma_x_tile(uint32_t sb, const CUtensorMap* tm, int r, int j, int slot) {
    asm volatile("{\n.reg .pred p;\nelect.sync _|p, 0xffffffff;\n"
        "@p mbarrier.arrive.expect_tx.shared::cta.b64 _, [%2], 36864;\n"
        "@p cp.async.bulk.tensor.2d.shared::cluster.global.mbarrier::complete_tx::bytes.multicast::cluster [%0], [%1, {%3, %4}], [%2], %7;\n"
        "@p cp.async.bulk.tensor.2d.shared::cluster.global.mbarrier::complete_tx::bytes.multicast::cluster [%0+4096], [%1, {%5, %4}], [%2], %7;\n"
        "@p cp.async.bulk.tensor.2d.shared::cluster.global.mbarrier::complete_tx::bytes.multicast::cluster [%0+8192], [%1, {%6, %4}], [%2], %7;\n}"
        :: "r"(sb + O_XT + slot * XT_BYTES + 3 * r * 4096), "l"(tm), "r"(sb + B_X + 8 * slot), "r"(192 * r), "r"(j * 32), "r"(192 * r + 64), "r"(192 * r + 128),
           "h"((unsigned short)7) : "memory");
}
__device__ __forceinline__ void flag_inc_if(uint32_t z, unsigned* p) {
    asm volatile("{\n.reg .pred p;\nsetp.eq.u32 p, %1, 0;\n@p red.release.gpu.global.inc.u32 [%0], 0xfffffffe;\n}" :: "l"(p), "r"(z) : "memory");
}
__device__ __forceinline__ float quad_max(float v) {
    const float a = __shfl_xor_sync(~0u, v, 1), b = __shfl_xor_sync(~0u, v, 2), c = __shfl_xor_sync(~0u, v, 3);
    return fmaxf(fmaxf(v, a), fmaxf(b, c));
}
__device__ __forceinline__ void load_scores(float (&p)[10], uint32_t base, uint32_t stride, uint32_t l16) {
    const float4 a0 = lds128f(base + l16), b0 = lds128f(base + stride + l16);
    const float4 a1 = lds128f(base + 512 + l16), b1 = lds128f(base + stride + 512 + l16);
    const float4 a2 = lds128f(base + 1024 + l16), b2 = lds128f(base + stride + 1024 + l16);
    p[0] = (a2.x + a2.z) + (b2.x + b2.z); p[1] = (a2.y + a2.w) + (b2.y + b2.w);
    p[2] = a0.x + b0.x; p[3] = a0.y + b0.y; p[4] = a0.z + b0.z; p[5] = a0.w + b0.w;
    p[6] = a1.x + b1.x; p[7] = a1.y + b1.y; p[8] = a1.z + b1.z; p[9] = a1.w + b1.w;
}
__device__ __forceinline__ float rcp_fast(float x) { float y; asm("rcp.approx.ftz.f32 %0, %1;" : "=f"(y) : "f"(x)); return y; }

__global__ void __cluster_dims__(3, 1, 1) __launch_bounds__(384, 1)
chain_kernel(const __grid_constant__ CUtensorMap tm_x, const __grid_constant__ CUtensorMap tm_q,
             const __grid_constant__ CUtensorMap tm_k, const __grid_constant__ CUtensorMap tm_v,
             const __nv_bfloat16* __restrict__ x, const __nv_bfloat16* __restrict__ mem0,
             const __nv_bfloat16* __restrict__ Wo) {
    extern __shared__ __align__(1024) uint8_t smem_raw[];
    const uint32_t sb = smem_u32(smem_raw);
    const int lane = threadIdx.x & 31;
    const int warp = __shfl_sync(~0u, threadIdx.x >> 5, 0);
    const int wg = warp >> 2, w = warp & 3;
    const int h = blockIdx.x / 3, r = blockIdx.x - 3 * h;
    uint4* const g_acc = reinterpret_cast<uint4*>((reinterpret_cast<uintptr_t>(g_acc_raw) + 0x1fffff) & ~(uintptr_t)0x1fffff);

#define PSTAMP(i) do {} while (0)
    if (threadIdx.x == 0) {
        if (sb & 1023u) __trap();
        for (int i = 0; i < 9; i++) mbar_init(sb + O_BAR + 8 * i, 1);
        asm volatile("fence.mbarrier_init.release.cluster;" ::: "memory");
        for (int i = 0; i < 3; i++) {
            mbar_expect(sb + B_W + 8 * i, 49152);
            for (int tl = 0; tl < 2; tl++)
                asm volatile("cp.async.bulk.tensor.2d.shared::cluster.global.mbarrier::complete_tx::bytes [%0], [%1, {%3, %4}], [%2];"
                    :: "r"(sb + O_STG + tl * 73728 + i * 24576), "l"(r < 2 ? (tl ? &tm_k : &tm_q) : &tm_v), "r"(sb + B_W + 8 * i),
                       "r"(h * 128 + 64 * (r < 2 ? r : tl)), "r"(192 * i) : "memory");
        }
    }
    __syncwarp();
    asm volatile("barrier.cluster.arrive.relaxed.aligned;" ::: "memory");
    asm volatile("griddepcontrol.launch_dependents;" ::: "memory");
    if (warp == 0) PSTAMP(9);
    const uint32_t l16c = __shfl_sync(~0u, lane * 16, lane);

    if (wg < 2) {
#define KS(u) ((u) < 8 ? 12 * ((u) >> 2) + (((u) >> 1) & 1) + 4 * ((u) & 1) : (u) < 12 ? (u) : (u) < 16 ? (u) + 8 : (u) < 24 ? 24 + (((u) - 16) >> 1) + 4 * ((u) & 1) : (u) + 8)
        asm volatile("setmaxnreg.inc.sync.aligned.u32 184;");
        uint32_t a[144];
        uint32_t adr1;
        {
            const int g = lane >> 2, t = lane & 3;
            const int t1 = threadIdx.x;
#pragma unroll
            for (int i = 0; i < 2; i++) g_acc[(blockIdx.x * 64 + i * 32 + (t1 >> 3)) * 16 + (t1 & 7)] = make_uint4(0, 0, 0, 0);
            __threadfence();
            asm volatile("barrier.cluster.wait.aligned;" ::: "memory");
            const uint32_t ev = sb + O_STG + (2 * t) * 128 + (((2 * w + (g >> 2)) ^ (2 * t)) << 4) + (g & 3) * 4;
            const uint32_t od = (ev ^ 16) + 128;
            auto gather = [&](int dst, uint32_t off) {
                a[dst] = lds32(ev + off); a[dst + 1] = lds32(od + off); a[dst + 2] = lds32(ev + off + 1024); a[dst + 3] = lds32(od + off + 1024);
            };
            const uint4* xp = reinterpret_cast<const uint4*>(x) + blockIdx.x * 1536 + t1;
            uint4 xv[6];
#pragma unroll
            for (int th = 0; th < 2; th++) {
                mbar_wait(sb + B_W + 8 * th, 0);
                if (th == 1) {
#pragma unroll
                    for (int i = 0; i < 6; i++) xv[i] = __ldg(xp + i * 256);
                }
#pragma unroll
                for (int u = 4 * th; u < 4 * th + 4; u++) {
                    gather(32 + 4 * u, wg * (73728 + 4096) + KS(u) * 2048);
                    gather(4 * u, 73728 - wg * (73728 - 4096) + KS(u) * 2048);
                    gather(64 + 4 * u, wg * 73728 + KS(8 + u) * 2048);
                }
            }
            mbar_wait(sb + B_W + 16, 0);
#pragma unroll
            for (int u = 16; u < 28; u++) gather(32 + 4 * u, wg * 73728 + KS(u) * 2048);
#pragma unroll
            for (int kk = 0; kk < 72; kk++) {
                uint32_t w0 = a[2 * kk], w1 = a[2 * kk + 1];
                a[2 * kk] = __byte_perm(w0, w1, 0x5410);
                a[2 * kk + 1] = __byte_perm(w0, w1, 0x7632);
            }
            if (r == 2) {
                float n0[4], n1[4];
#pragma unroll
                for (int u = 0; u < 36; u++) {
                    const uint32_t x0 = a[4 * u] & 0x7fff7fffu, x1 = a[4 * u + 1] & 0x7fff7fffu, x2 = a[4 * u + 2] & 0x7fff7fffu, x3 = a[4 * u + 3] & 0x7fff7fffu;
                    if (u == 0) mma16816_z(n0, x0, x1, x2, x3, ONES, ONES);
                    else if (u < 8) mma16816(n0, x0, x1, x2, x3, ONES, ONES);
                    else if (u == 8) mma16816_z(n1, x0, x1, x2, x3, ONES, ONES);
                    else mma16816(n1, x0, x1, x2, x3, ONES, ONES);
                }
                const uint32_t mx = __reduce_max_sync(~0u, __float_as_uint(2.f * fmaxf(fmaxf(n0[0], n0[2]), fmaxf(n1[0], n1[2]))));
                sts32_if(lane, sb + O_MISC + 32 + 4 * warp, mx);
            }
            uint32_t xm = 0;
#pragma unroll
            for (int i = 0; i < 6; i++)
                xm = __vmaxu2(xm, __vmaxu2(__vmaxu2(xv[i].x & 0x7fff7fffu, xv[i].y & 0x7fff7fffu), __vmaxu2(xv[i].z & 0x7fff7fffu, xv[i].w & 0x7fff7fffu)));
            sts32_if(lane, sb + O_OF + 16 + 4 * warp, __reduce_max_sync(~0u, max(xm << 16, xm & 0xffff0000u)));
            if (warp == 0) PSTAMP(11);
            bar_arrive(7, 384);
            asm volatile("barrier.cluster.arrive.relaxed.aligned;" ::: "memory");
            bar_sync(1, 256);
            const uint32_t as = sb + O_AS + wg * 8192 + (16 * w + g) * 128 + t * 4;
            sts32(as + (g << 4), a[32]);
            sts32(as + 1024 + (g << 4), a[33]);
            sts32(as + ((1 ^ g) << 4), a[34]);
            sts32(as + 1024 + ((1 ^ g) << 4), a[35]);
            sts128(sb + O_AF + warp * 512 + lane * 16, a[32], a[33], a[34], a[35]);
            fence_async_smem();
            bar_sync(1, 256);
            const uint32_t l = lane * 16;
            const int mi = lane >> 3, isk = (mi >> 1) ? wg : (wg ^ 1);
            adr1 = (r == 2) ? (sb + O_VM + warp * 256 + (l >> 1))
                            : (isk ? (sb + O_KM + w * 512 + wg * 256 + (mi & 1) * 128 + (l & 127))
                                   : (sb + O_QM + w * 512 + (mi & 1) * 256 + wg * 128 + (l & 127)));
            adr1 = __shfl_sync(~0u, adr1, lane);
        }
        auto qkv_loop = [&](auto r2tag) {
        constexpr bool R2 = decltype(r2tag)::value;
        int s3 = 2;
#pragma unroll 1
        for (int s = -1; s < NSEG; s++) {
            const uint32_t l16 = opaque(l16c);
            s3 = (s3 == 2) ? 0 : s3 + 1;
            if (s < 0) mbar_wait(sb + B_X, 0);
            const uint64_t desc0 = (uint64_t)(((sb + O_XT + s3 * XT_BYTES) & 0x3FFFF) >> 4) | (1ull << 16) | (64ull << 32) | (1ull << 62);
            uint32_t km0 = 0, km1 = 0;
            if (s >= 0) {
                { const uint4 v = lds128(sb + O_AF + warp * 512 + l16); a[32] = v.x; a[33] = v.y; a[34] = v.z; a[35] = v.w; }
                float co[4], cw[3][4];
                uint4 b[14];
                float inv;
#define GORD(i) ((i) < 8 ? 2 * ((i) >> 2) + (((i) >> 1) & 1) + 4 * ((i) & 1) : (i))
                auto qkv_mma = [&](int i) {
                    const int gi = GORD(i), u = 8 * gi, n0 = 2 * i, n1 = 2 * i + 1;
                    if (gi < 4) {
                        if (i == 0) mma16816_z(co, a[u], a[u + 1], a[u + 2], a[u + 3], b[0].x, b[0].y);
                        else mma16816(co, a[u], a[u + 1], a[u + 2], a[u + 3], b[i].x, b[i].y);
                    }
                    if (n0 < 3) mma16816_z(cw[n0 % 3], a[32 + u], a[32 + u + 1], a[32 + u + 2], a[32 + u + 3], b[i].x, b[i].y);
                    else mma16816(cw[n0 % 3], a[32 + u], a[32 + u + 1], a[32 + u + 2], a[32 + u + 3], b[i].x, b[i].y);
                    if (n1 < 3) mma16816_z(cw[n1 % 3], a[32 + u + 4], a[32 + u + 5], a[32 + u + 6], a[32 + u + 7], b[i].z, b[i].w);
                    else mma16816(cw[n1 % 3], a[32 + u + 4], a[32 + u + 5], a[32 + u + 6], a[32 + u + 7], b[i].z, b[i].w);
                    if (gi < 4) mma16816(co, a[u + 4], a[u + 5], a[u + 6], a[u + 7], b[i].z, b[i].w);
                };
                const uint32_t mf = sb + O_MF + l16, mfs = mf + wg * 1024;
                const uint32_t qb = (s & 1) * 12288;
                bar_sync(2, 384);
                if (warp == 0) STAMP(s, 0);
                auto qkv_ld = [&](int i) {
                    const int gi = GORD(i);
                    b[i] = gi < 4 ? lds128v(mfs + (gi >> 1) * 3072 + (gi & 1) * 512) : lds128v(mf + (gi < 6 ? gi : gi + 4) * 512);
                };
#pragma unroll
                for (int i = 0; i < 4; i++) qkv_ld(i);
                qkv_mma(0); qkv_mma(1); qkv_mma(2);
                const uint32_t z0 = __float_as_uint(QDEP ? co[0] : cw[1][0]) & (l16 & 15u);
                qkv_mma(3);
                bar_sync(15, 384);
                b[4] = lds128v(mfs + 3072 + z0);
#pragma unroll
                for (int i = 5; i < 9; i++) qkv_ld(i);
#pragma unroll
                for (int i = 4; i < 9; i++) { qkv_mma(i); qkv_ld(5 + i); }
                asm volatile("ld.volatile.shared.f32 %0, [%1];" : "=f"(inv) : "r"(sb + O_MISC) : "memory");
#pragma unroll
                for (int i = 9; i < 14; i++) qkv_mma(i);
#pragma unroll
                for (int i = 0; i < 4; i++) cw[0][i] += cw[1][i] + cw[2][i];
                if (!R2) {
                    const uint32_t o0 = pack_bf16(co[0] * inv, co[1] * inv), o1 = pack_bf16(co[2] * inv, co[3] * inv);
                    const uint32_t w0 = pack_bf16(cw[0][0] * inv, cw[0][1] * inv), w1 = pack_bf16(cw[0][2] * inv, cw[0][3] * inv);
                    stsm4t(adr1 + qb, o0, o1, w0, w1);
                    if (warp == 0) STAMP(s, 1);
                    asm volatile("{\n.reg .pred p;\nsetp.ge.u32 p, %0, 3;\n@p bar.arrive 1, 256;\n@!p bar.sync 1, 256;\n}" :: "r"(warp) : "memory");
                    auto scores = [&](float (&v)[4], const uint4 (&q)[4], const uint4 (&k)[4]) {
                        float s0[4], s1[4], t0[4], t1[4];
                        mma16816_z(s0, q[0].x, q[0].y, q[0].z, q[0].w, k[0].x, k[0].y);
                        mma16816_z(s1, q[0].x, q[0].y, q[0].z, q[0].w, k[0].z, k[0].w);
                        mma16816_z(t0, q[1].x, q[1].y, q[1].z, q[1].w, k[1].x, k[1].y);
                        mma16816_z(t1, q[1].x, q[1].y, q[1].z, q[1].w, k[1].z, k[1].w);
                        mma16816(s0, q[2].x, q[2].y, q[2].z, q[2].w, k[2].x, k[2].y);
                        mma16816(s1, q[2].x, q[2].y, q[2].z, q[2].w, k[2].z, k[2].w);
                        mma16816(t0, q[3].x, q[3].y, q[3].z, q[3].w, k[3].x, k[3].y);
                        mma16816(t1, q[3].x, q[3].y, q[3].z, q[3].w, k[3].z, k[3].w);
                        v[0] = (s0[0] + s0[2]) + (t0[0] + t0[2]); v[1] = (s0[1] + s0[3]) + (t0[1] + t0[3]);
                        v[2] = (s1[0] + s1[2]) + (t1[0] + t1[2]); v[3] = (s1[1] + s1[3]) + (t1[1] + t1[3]);
                    };
                    if (warp < 3) {
                        uint4 q[4], k[4]; float v[4];
#pragma unroll
                        for (int i = 0; i < 4; i++) { q[i] = ldsm4(sb + O_QM + qb + i * 512 + l16); k[i] = ldsm4(sb + O_QKX + 4096 + qb + warp * 2048 + i * 512 + l16); }
                        scores(v, q, k);
                        const uint32_t dst = sb + O_SC + r * 1536 + warp * 512 + l16;
                        st_async128(mapa(dst, 2), __float_as_uint(v[0]), __float_as_uint(v[1]), __float_as_uint(v[2]), __float_as_uint(v[3]), mapa(sb + B_SC, 2));
                        st_async128(mapa(dst, r ^ 1), __float_as_uint(v[0]), __float_as_uint(v[1]), __float_as_uint(v[2]), __float_as_uint(v[3]), mapa(sb + B_SC, r ^ 1));
                        st_async128(mapa(dst, r), __float_as_uint(v[0]), __float_as_uint(v[1]), __float_as_uint(v[2]), __float_as_uint(v[3]), mapa(sb + B_SC, r));
                        if (warp == 2) STAMP(s, 2);
                    }
                } else {
                    sts128f(sb + O_XP + warp * 512 + l16, co[0], co[1], co[2], co[3]);
                    bar_sync(8 + w, 64);
                    const float4 o = lds128f(sb + O_XP + (warp ^ 4) * 512 + l16);
                    km0 = pack_bf16((cw[0][0] + o.x) * inv, (cw[0][1] + o.y) * inv);
                    km1 = pack_bf16((cw[0][2] + o.z) * inv, (cw[0][3] + o.w) * inv);
                    if (warp == 0) STAMP(s, 1);
                    st_async64(mapa(adr1, 0), km0, km1, mapa(sb + B_SC, 0));
                    st_async64(mapa(adr1, 1), km0, km1, mapa(sb + B_SC, 1));
                    st_async64(mapa(adr1, 2), km0, km1, mapa(sb + B_SC, 2));
                    if (warp == 0) STAMP(s, 2);
                }
            }
            if (s >= 0) bar_sync(3, 384);
            auto store_qk = [&]() {
                asm volatile("{\n.reg .pred p;\nelect.sync _|p, 0xffffffff;\n"
                    "@p cp.async.bulk.global.shared::cta.bulk_group [%0], [%1], 10240;\n@p cp.async.bulk.commit_group;\n}"
                    :: "l"(reinterpret_cast<char*>(g_qkv) + (size_t)(s * NH + h) * REC + r * 10240), "r"(sb + O_QKX + (s & 1) * 12288) : "memory");
            };
            auto store_vm = [&]() {
                *reinterpret_cast<uint2*>(reinterpret_cast<char*>(g_qkv) + (size_t)(s * NH + h) * REC + 28672 + warp * 256 + (l16 >> 1)) = make_uint2(km0, km1);
            };
            if (s == NSEG - 1) {
                if (R2) store_vm();
                else if (warp == 3) {
                    fence_async_smem();
                    store_qk();
                    asm volatile("cp.async.bulk.wait_group 0;\nfence.proxy.async.global;" ::: "memory");
                }
            } else {
                const int j = s + 1;
#define XDESC(u) (((u) < 8 ? descs : desc0) + (uint64_t)(((KS(u) >> 2) * 4096 + (KS(u) & 3) * 32) >> 4))
                const uint64_t descs = desc0 + (uint64_t)(wg * 4);
                float d[16];
                wg_fence();
#pragma unroll
                for (int u = 0; u < 8; u++) {
                    if (u == 0) wgmma_n32_rs<0>(d, a[0], a[1], a[2], a[3], XDESC(0));
                    else wgmma_n32_rs<1>(d, a[4 * u], a[4 * u + 1], a[4 * u + 2], a[4 * u + 3], XDESC(u));
                }
                wg_commit();
                wg_wait0();
                if (warp == 0) STAMP(s, 15);
                if (warp == 3) asm volatile("cp.async.bulk.wait_group.read 0;" ::: "memory");
                if (s >= 0) bar_sync(4, 384);
#pragma unroll
                for (int q = 0; q < 2; q++)
                    sts128(sb + O_XP + warp * 1024 + q * 512 + l16, pack_bf16(d[8 * q], d[8 * q + 1]), pack_bf16(d[8 * q + 2], d[8 * q + 3]),
                           pack_bf16(d[8 * q + 4], d[8 * q + 5]), pack_bf16(d[8 * q + 6], d[8 * q + 7]));
                bar_sync(12, 256);
#pragma unroll
                for (int q = 0; q < 2; q++) {
                    const uint4 o = lds128(sb + O_XP + (warp ^ 4) * 1024 + q * 512 + l16);
                    d[8 * q] = __uint_as_float(o.x << 16); d[8 * q + 1] = __uint_as_float(o.x & 0xffff0000u);
                    d[8 * q + 2] = __uint_as_float(o.y << 16); d[8 * q + 3] = __uint_as_float(o.y & 0xffff0000u);
                    d[8 * q + 4] = __uint_as_float(o.z << 16); d[8 * q + 5] = __uint_as_float(o.z & 0xffff0000u);
                    d[8 * q + 6] = __uint_as_float(o.w << 16); d[8 * q + 7] = __uint_as_float(o.w & 0xffff0000u);
                }
                if (s >= 0) {
                    if (R2) store_vm();
                    if (warp == 5 && s + 2 < NSEG) tma_x_tile(sb, &tm_x, r, s + 2, s3 == 2 ? 0 : s3 + 1);
                    if (warp == 3) {
                        asm volatile("cp.async.bulk.wait_group 0;\nfence.proxy.async.global;" ::: "memory");
                        if (FLAGPOS == 0 && s >= 4 && !(s & (s > 4 * NBIG ? 1 : 3))) {
                            __syncwarp();
                            flag_inc_if(l16, &g_flag[F_QKV + ((s > 4 * NBIG ? 2 * s - 4 * NBIG : s) - 4 + (h >> 3)) * 8]);
                        }
                        fence_async_smem();
                    }
                    asm volatile("{\n.reg .pred p;\nsetp.eq.u32 p, %0, 0;\n@p bar.sync 5, 256;\n@!p bar.sync 13, 256;\n}" :: "r"(wg) : "memory");
                }
                const uint64_t da0 = (uint64_t)(((sb + O_AS + wg * 8192) & 0x3FFFF) >> 4) | (1ull << 16) | (64ull << 32) | (1ull << 62);
                wg_fence();
                wgmma_n32_ss<1>(d, da0, XDESC(0));
#pragma unroll
                for (int u = 1; u < 28; u++) wgmma_n32_rs<1>(d, a[32 + 4 * u], a[32 + 4 * u + 1], a[32 + 4 * u + 2], a[32 + 4 * u + 3], XDESC(u));
                wg_commit();
                if (FLAGPOS == 1 && warp == 3 && s >= 4 && !(s & (s > 4 * NBIG ? 1 : 3)))
                    flag_inc_if(l16, &g_flag[F_QKV + ((s > 4 * NBIG ? 2 * s - 4 * NBIG : s) - 4 + (h >> 3)) * 8]);
                wg_wait0();
                if (!R2 && warp == 3 && s >= 0) store_qk();
                if (warp == 4) STAMP(s, 3);
                uint32_t e[8];
#pragma unroll
                for (int i = 0; i < 8; i++) e[i] = pack_bf16(d[2 * i], d[2 * i + 1]);
                if (!R2) {
                    const uint32_t base = sb + O_QKX + (j & 1) * 12288 + wg * 4096 + w * 512 + l16;
                    stsm4t(base, e[0], wg ? e[1] : e[2], wg ? e[2] : e[1], e[3]);
                    stsm4t(base + 2048, e[4], wg ? e[5] : e[6], wg ? e[6] : e[5], e[7]);
                } else {
                    const uint32_t base = sb + O_VX + (j & 1) * 8192 + warp * 1024 + l16;
                    sts128(base, e[0], e[1], e[2], e[3]);
                    sts128(base + 512, e[4], e[5], e[6], e[7]);
                    bar_arrive(14, 288);
                }
                if (warp == 7) STAMP(s, 4);
                if (s < 0) asm volatile("barrier.cluster.wait.aligned;" ::: "memory");
            }
        }
        };
        if (r == 2) qkv_loop(BoolC<true>()); else qkv_loop(BoolC<false>());
        bar_arrive(7, 384);
    } else {
        asm volatile("setmaxnreg.dec.sync.aligned.u32 136;");
        const int c = w;
        uint32_t a[96];
        uint32_t mmax = 0;
        {
            const int g = lane >> 2, t = lane & 3;
            uint32_t tag = 0, m0v[18];
            if (threadIdx.x == 256) tag = atomicAdd(&g_ticket, 1u);
#pragma unroll
            for (int i = 0; i < 9; i++) {
                const uint32_t* p = reinterpret_cast<const uint32_t*>(mem0 + g * DM + 16 * (4 * i + c) + 2 * t);
                m0v[2 * i] = __ldg(p); m0v[2 * i + 1] = __ldg(p + 4);
            }
            asm volatile("barrier.cluster.wait.aligned;" ::: "memory");
            if (c == 0) {
                tma_x_tile(sb, &tm_x, r, 0, 0);
                mbar_expect_if(lane, sb + B_SC, 5120);
                if (r < 2) mbar_expect_if(lane, sb + B_VX, 8192);
                sts32_if(lane, sb + O_MISC, __float_as_uint(1.0f));
                sts32_if(lane, sb + O_MISC + 12, __float_as_uint(SM_SCALE));
            }
            asm volatile("barrier.cluster.arrive.relaxed.aligned;" ::: "memory");
#pragma unroll
            for (int tau = 0; tau < 3; tau++) {
                const uint32_t* v = m0v + 6 * tau;
                sts128(sb + O_MF + tau * 3072 + c * 512 + lane * 16, v[0], v[1], v[2], v[3]);
                sts64(sb + O_MF + tau * 3072 + 2048 + (c >> 1) * 512 + lane * 16 + (c & 1) * 8, v[4], v[5]);
#pragma unroll
                for (int i = 0; i < 6; i++) mmax = __vmaxu2(mmax, v[i] & 0x7fff7fffu);
            }
            mmax = max(mmax << 16, mmax & 0xffff0000u);
            bar_arrive(2, 384); bar_arrive(15, 384);
            tag = (__shfl_sync(~0u, tag, 0) / 96u + 1u) & 0xffffu;
            mbar_wait(sb + B_W + 0, 0);
            const __nv_bfloat16* p = Wo + (size_t)(h * 128 + 4 * t) * DM + 192 * r + 16 * c + 2 * g;
#pragma unroll
            for (int i = 0; i < 3; i++)
#pragma unroll
                for (int eb = 0; eb < 8; eb++)
#pragma unroll
                    for (int j = 0; j < 4; j++) a[(i * 8 + eb) * 4 + j] = ldg_nc32(p + (16 * eb + ((j & 1) * 2 + (j >> 1))) * DM + 64 * i);
#pragma unroll
            for (int kk = 0; kk < 48; kk++) {
                uint32_t w0 = a[2 * kk], w1 = a[2 * kk + 1];
                a[2 * kk] = __byte_perm(w0, w1, 0x5410);
                a[2 * kk + 1] = __byte_perm(w0, w1, 0x7632);
            }
            sts128(sb + O_WP + c * 512 + lane * 16, a[92], a[93], a[94], a[95]);
            float wmax = 0.f;
#pragma unroll
            for (int i = 0; i < 3; i++) {
                float n0[4];
#pragma unroll
                for (int u = 8 * i; u < 8 * i + 8; u++) {
                    const uint32_t x0 = a[4 * u] & 0x7fff7fffu, x1 = a[4 * u + 1] & 0x7fff7fffu, x2 = a[4 * u + 2] & 0x7fff7fffu, x3 = a[4 * u + 3] & 0x7fff7fffu;
                    if (u == 8 * i) mma16816_z(n0, x0, x1, x2, x3, ONES, ONES);
                    else mma16816(n0, x0, x1, x2, x3, ONES, ONES);
                }
                wmax = fmaxf(wmax, fmaxf(n0[0], n0[2]));
            }
            uint32_t wm = __reduce_max_sync(~0u, __float_as_uint(wmax));
            sts32_if(lane, sb + O_OF + 4 * c, wm);
            if (c == 0) PSTAMP(8);
            bar_sync(7, 384);
            asm volatile("barrier.cluster.wait.aligned;" ::: "memory");
            if (c == 1) tma_x_tile(sb, &tm_x, r, 1, 1);
            if (c == 0) {
                const uint4 wq = lds128(sb + O_OF), xq = lds128(sb + O_OF + 16), xr = lds128(sb + O_OF + 32), v0 = lds128(sb + O_MISC + 32), v1 = lds128(sb + O_MISC + 48);
                const uint32_t w1 = max(max(wq.x, wq.y), max(wq.z, wq.w)), x1 = max(max(max(xq.x, xq.y), max(xq.z, xq.w)), max(max(xr.x, xr.y), max(xr.z, xr.w)));
                const uint32_t vv = (r < 2) ? 0u : max(max(max(v0.x, v0.y), max(v0.z, v0.w)), max(max(v1.x, v1.y), max(v1.z, v1.w)));
                const uint32_t lo = (min(w1, 0x7f800000u) + 0xffffu) >> 16 | ((min(vv, 0x7f800000u) + 0xffffu) & 0xffff0000u), hi = (x1 & 0xffff0000u) | tag;
                uint32_t l0, h0, l1, h1, l2, h2;
                asm volatile("{\n.reg .pred p;\n.reg .u32 n, x, y;\n.reg .b64 v;\nsetp.eq.u32 p, %10, 0;\nmov.b64 v, {%8, %9};\n@p st.relaxed.gpu.global.b64 [%7], v;\nmov.u32 n, 0;\n"
                             "G_%=: ld.relaxed.gpu.global.b64 v, [%6];\nmov.b64 {%0, %1}, v;\nld.relaxed.gpu.global.b64 v, [%6+256];\nmov.b64 {%2, %3}, v;\n"
                             "ld.relaxed.gpu.global.b64 v, [%6+512];\nmov.b64 {%4, %5}, v;\n"
                             "xor.b32 x, %1, %9;\nxor.b32 y, %3, %9;\nor.b32 x, x, y;\nxor.b32 y, %5, %9;\nor.b32 x, x, y;\nand.b32 x, x, 0xffff;\n"
                             "setp.eq.u32 p, x, 0;\nvote.sync.all.pred p, p, 0xffffffff;\n@p bra.uni E_%=;\n"
                             "add.u32 n, n, 1;\nsetp.lt.u32 p, n, 4000000;\n@p bra.uni G_%=;\ntrap;\nE_%=:\n}"
                             : "=&r"(l0), "=&r"(h0), "=&r"(l1), "=&r"(h1), "=&r"(l2), "=&r"(h2)
                             : "l"(&g_norm[lane]), "l"(&g_norm[blockIdx.x]), "r"(lo), "r"(hi), "r"(lane) : "memory");
                const uint32_t lm = __vmaxu2(l0, __vmaxu2(l1, l2));
                const float fw = __uint_as_float(__reduce_max_sync(~0u, lm << 16));
                const float fv = __uint_as_float(__reduce_max_sync(~0u, lm & 0xffff0000u));
                const float xmax = __uint_as_float(__reduce_max_sync(~0u, max(h0, max(h1, h2)) & 0xffff0000u));
                const float G = 36.f * fw * fv;
                sts32_if(lane, sb + O_MISC + 4, __float_as_uint(G)); sts32_if(lane, sb + O_MISC + 8, __float_as_uint(G * xmax));
            }
        }
        if (c == 0) PSTAMP(12);
        bar_sync(6, 128);
        int s3n = 1;
        uint32_t roff = __shfl_sync(~0u, (r * 4 + c) * 2048 + (lane >> 4) * 512 + (lane & 2) * 128 + (lane & 1) * 64 + (lane & 12) * 4, lane);
#pragma unroll 1
        for (int s = 0; s < NSEG; s++) {
            const uint32_t l16 = opaque(l16c);
            const uint32_t vxa = sb + O_VX + (s & 1) * 8192 + c * 2048 + l16;
            if (c == 0 && r == 2) {
                bar_sync(14, 288);
                fence_async_smem();
                asm volatile("{\n.reg .pred p;\nelect.sync _|p, 0xffffffff;\n"
                    "@p cp.async.bulk.global.shared::cta.bulk_group [%0], [%1], 8192;\n@p cp.async.bulk.commit_group;\n"
                    "cp.async.bulk.wait_group 0;\nsetp.lt.and.s32 p, %4, 63, p;\n"
                    "@p cp.async.bulk.shared::cluster.global.mbarrier::complete_tx::bytes.multicast::cluster [%1], [%0], 8192, [%2], %3;\n"
                    "fence.proxy.async.global;\n}"
                    :: "l"(reinterpret_cast<char*>(g_qkv) + (size_t)(s * NH + h) * REC + 20480), "r"(sb + O_VX + (s & 1) * 8192),
                       "r"(sb + B_VX + 8 * (s & 1)), "h"((unsigned short)3), "r"(s) : "memory");
            }
            if (s == NSEG - 1) { bar_sync(3, 384); mbar_wait(sb + B_SC, s & 1); break; }
            uint4 vx[4];
            sts32_if(l16, sb + O_MISC + 16 + 4 * c, __reduce_max_sync(~0u, mmax));
            if (c == 0) STAMP(s, 5);
            {
                bar_sync(6, 128);
                const uint4 mm = lds128(sb + O_MISC + 16), cf = lds128(sb + O_MISC);
                const float bound = fmaxf(__uint_as_float(cf.z), __uint_as_float(cf.y) * (__uint_as_float(max(max(mm.x, mm.y), max(mm.z, mm.w))) * __uint_as_float(cf.x)));
                const uint32_t ebits = __reduce_max_sync(~0u, min(max(__float_as_uint(bound) & 0x7f800000u, 21u << 23), 254u << 23));
                mbar_wait(sb + B_X + 8 * s3n, ((s + 1) / 3) & 1);
                s3n = (s3n == 2) ? 0 : s3n + 1;
                bar_sync(3, 384);
                if (r < 2) mbar_wait(sb + B_VX + 8 * (s & 1), (s >> 1) & 1);
                vx[0] = lds128(vxa); vx[2] = lds128(vxa + 1024);
                if (c == 0) STAMP(s, 13);
                mbar_wait(sb + B_SC, s & 1);
                if (c == 0) STAMP(s, 6);
                float p[10];
                load_scores(p, sb + O_SC, 1536, l16);
                float mx = fmaxf(fmaxf(fmaxf(p[0], p[1]), fmaxf(p[2], p[3])), fmaxf(fmaxf(p[4], p[5]), fmaxf(p[6], p[7])));
                mx = quad_max(fmaxf(mx, fmaxf(p[8], p[9])));
                const uint4 vm = lds64x2(sb + O_VM + c * 512 + (l16 >> 1));
                vx[1] = lds128(vxa + 512); vx[3] = lds128(vxa + 1536);
                bar_arrive(4, 384);
                const float sc = __uint_as_float(lds32(sb + O_MISC + 12));
                const float mo = mx * SM_SCALE;
                uint32_t P[5];
#pragma unroll
                for (int n = 0; n < 5; n++) P[n] = pack_bf16(ex2(fmaf(p[2 * n], SM_SCALE, -mo)), ex2(fmaf(p[2 * n + 1], n == 3 ? sc : SM_SCALE, -mo)));
                if (c == 0) STAMP(s, 7);
                float o0[4], o1[4], sm[4];
                mma16816_z(sm, ONES, ONES, ONES, ONES, P[1], P[2]);
                mma16816_z(o0, vx[0].x, vx[0].y, vx[0].z, vx[0].w, P[1], P[2]);
                mma16816_z(o1, vx[2].x, vx[2].y, vx[2].z, vx[2].w, P[1], P[2]);
                mma16816(sm, ONES, ONES, ONES, ONES, P[3], P[4]);
                mma16816(o0, vx[1].x, vx[1].y, vx[1].z, vx[1].w, P[3], P[4]);
                mma16816(o1, vx[3].x, vx[3].y, vx[3].z, vx[3].w, P[3], P[4]);
                mma1688(sm, ONES, ONES, P[0]);
                mma1688(o0, vm.x, vm.y, P[0]);
                mma1688(o1, vm.z, vm.w, P[0]);
                stsm4t(sb + O_OF + c * 512 + l16, pack_bf16(o0[0], o0[1]), pack_bf16(o0[2], o0[3]), pack_bf16(o1[0], o1[1]), pack_bf16(o1[2], o1[3]));
                const float sig = __uint_as_float((268u << 23) - ebits);
                const float r0 = rcp_fast(sm[0]) * sig, r1 = rcp_fast(sm[1]) * sig;
                bar_sync(6, 128);
                uint4 ob[4];
#pragma unroll
                for (int q = 0; q < 4; q++) ob[q] = ldsm4(sb + O_OF + q * 512 + l16);
                { const uint4 v = lds128(sb + O_WP + c * 512 + l16); a[92] = v.x; a[93] = v.y; a[94] = v.z; a[95] = v.w; }
                float m0[3][4], m1[3][4];
#pragma unroll
                for (int q = 0; q < 4; q++) {
#pragma unroll
                    for (int i = 0; i < 3; i++) {
                        const int k0 = (i * 8 + 2 * q) * 4;
                        if (q == 0) mma16816_z(m0[i], a[k0], a[k0 + 1], a[k0 + 2], a[k0 + 3], ob[q].x, ob[q].y);
                        else mma16816(m0[i], a[k0], a[k0 + 1], a[k0 + 2], a[k0 + 3], ob[q].x, ob[q].y);
                    }
#pragma unroll
                    for (int i = 0; i < 3; i++) {
                        const int k1 = (i * 8 + 2 * q + 1) * 4;
                        if (q == 0) mma16816_z(m1[i], a[k1], a[k1 + 1], a[k1 + 2], a[k1 + 3], ob[q].z, ob[q].w);
                        else mma16816(m1[i], a[k1], a[k1 + 1], a[k1 + 2], a[k1 + 3], ob[q].z, ob[q].w);
                    }
                }
                asm volatile("red.relaxed.gpu.global.add.noftz.v4.f16x2 [%0], {%1,%2,%3,%4};" :: "l"(reinterpret_cast<char*>(g_acc) + roff),
                    "r"(pack_f16(NRM(m0[0][0] + m1[0][0], r0), NRM(m0[0][2] + m1[0][2], r0))), "r"(pack_f16(NRM(m0[1][0] + m1[1][0], r0), NRM(m0[1][2] + m1[1][2], r0))),
                    "r"(pack_f16(NRM(m0[2][0] + m1[2][0], r0), NRM(m0[2][2] + m1[2][2], r0))), "r"(0x3c00u) : "memory");
                asm volatile("red.relaxed.gpu.global.add.noftz.v4.f16x2 [%0], {%1,%2,%3,%4};" :: "l"(reinterpret_cast<char*>(g_acc) + roff + 1024),
                    "r"(pack_f16(NRM(m0[0][1] + m1[0][1], r1), NRM(m0[0][3] + m1[0][3], r1))), "r"(pack_f16(NRM(m0[1][1] + m1[1][1], r1), NRM(m0[1][3] + m1[1][3], r1))),
                    "r"(pack_f16(NRM(m0[2][1] + m1[2][1], r1), NRM(m0[2][3] + m1[2][3], r1))), "r"(0x3c00u) : "memory");
                const unsigned t_red = clk();
                bar_arrive(5, 256);
                bar_arrive(13, 256);
                mbar_expect_if(l16 | c, sb + B_SC, 5120);
                mbar_expect_if(l16 | (c ^ 1) | (r >> 1), sb + B_VX + 8 * ((s + 1) & 1), 8192);
                sts32_if(l16 | (c ^ 3), sb + O_MISC, ebits - (14u << 23));
                if (c == 0) STAMPV(s, 8, t_red);
                if (ACC_PF && c == 2 && s + 4 < NSEG - 1)
                    asm volatile("prefetch.global.L2 [%0];" :: "l"(reinterpret_cast<const char*>(g_acc) + ((s + 4) * 96 + blockIdx.x) * 256 + (l16 & 96)) : "memory");
                const char* pbase = reinterpret_cast<const char*>(g_acc) + (s * 24576 + c * 2048) + ((l16 & 64) * 16 + (l16 & 256) + ((l16 & 128) >> 1) + (l16 & 48));
                uint4 v[6];
                {
                    const char* pb = reinterpret_cast<const char*>(__shfl_sync(~0u, (unsigned long long)pbase, l16 >> 4));
                    const unsigned t_go = t_red + (s < D_S0 ? D_EARLY : D_WAIT);
                    asm volatile("{\n.reg .pred p;\n.reg .u64 c;\n.reg .u32 lo;\n"
                                 "S_%=: mov.u64 c, %%clock64;\ncvt.u32.u64 lo, c;\nsub.u32 lo, lo, %0;\nsetp.lt.s32 p, lo, 0;\n@p bra.uni S_%=;\n}" :: "r"(t_go) : "memory");
#pragma unroll
                    for (int i = 0; i < 6; i++) v[i] = ldg_relaxed128(pb + (i >> 1) * 8192 + (i & 1) * 512);
                    pbase = pb;
                }
                int nretry = 0;
                auto convert = [&](int tau) {
                    const uint4 A = v[2 * tau], B = v[2 * tau + 1];
                    sts128(sb + O_MF + tau * 3072 + c * 512 + l16, f16x2_to_bf16x2(A.x), f16x2_to_bf16x2(B.x), f16x2_to_bf16x2(A.y), f16x2_to_bf16x2(B.y));
                    sts64(sb + O_MF + tau * 3072 + 2048 + (c >> 1) * 512 + (c & 1) * 8 + l16, f16x2_to_bf16x2(A.z), f16x2_to_bf16x2(B.z));
                };
                const uint32_t ok0 = __all_sync(~0u, (v[0].w & v[1].w) == 0x5000u);
                convert(0);
                asm volatile("{\n.reg .pred p;\nsetp.ne.u32 p, %0, 0;\n@p bar.arrive 2, 384;\n}" :: "r"(ok0) : "memory");
                mmax = absmax2(absmax2(absmax2(v[0].x, v[0].y), absmax2(v[0].z, v[1].x)), absmax2(v[1].y, v[1].z));
                sched_fence<0>(h);
                uint32_t ok1;
                asm volatile("{\n.reg .pred p, q;\n.reg .b32 x;\nlop3.b32 x, %1, %2, %3, 0x80;\nand.b32 x, x, %4;\n"
                             "setp.eq.u32 p, x, 0x5000;\nvote.sync.all.pred q, p, 0xffffffff;\nselp.u32 %0, 1, 0, q;\n}"
                             : "=r"(ok1) : "r"(v[2].w), "r"(v[3].w), "r"(v[4].w), "r"(v[5].w));
                convert(1); convert(2);
                asm volatile("{\n.reg .pred p;\nsetp.ne.u32 p, %0, 0;\n@p bar.arrive 15, 384;\n}" :: "r"(ok1) : "memory");
                if (!(ok0 & ok1)) {
                    v[0] = v[1] = make_uint4(0u, 0u, 0u, ok0 ? 0x5000u : 0u);
                    asm volatile("{\n.reg .pred p0, p1, p2, p3, p4, p5, q;\n.reg .u32 n, x;\nmov.u32 n, 0;\n"
                         "R_%=: setp.ne.u32 p0, %3, 0x5000;\nsetp.ne.u32 p1, %7, 0x5000;\nsetp.ne.u32 p2, %11, 0x5000;\n"
                         "setp.ne.u32 p3, %15, 0x5000;\nsetp.ne.u32 p4, %19, 0x5000;\nsetp.ne.u32 p5, %23, 0x5000;\n"
                         "@p0 ld.relaxed.gpu.global.v4.u32 {%0,%1,%2,%3}, [%25];\n@p1 ld.relaxed.gpu.global.v4.u32 {%4,%5,%6,%7}, [%25+512];\n"
                         "@p2 ld.relaxed.gpu.global.v4.u32 {%8,%9,%10,%11}, [%25+8192];\n@p3 ld.relaxed.gpu.global.v4.u32 {%12,%13,%14,%15}, [%25+8704];\n"
                         "@p4 ld.relaxed.gpu.global.v4.u32 {%16,%17,%18,%19}, [%25+16384];\n@p5 ld.relaxed.gpu.global.v4.u32 {%20,%21,%22,%23}, [%25+16896];\n"
                         "add.u32 %24, %24, 1;\nand.b32 x, %3, %7;\nand.b32 x, x, %11;\nand.b32 x, x, %15;\nand.b32 x, x, %19;\nand.b32 x, x, %23;\n"
                         "setp.eq.u32 q, x, 0x5000;\nvote.sync.all.pred q, q, 0xffffffff;\n@q bra.uni K_%=;\n"
                         "add.u32 n, n, 1;\nsetp.lt.u32 q, n, 2000000;\n@q bra.uni R_%=;\ntrap;\nK_%=:\n}"
                         : "+r"(v[0].x), "+r"(v[0].y), "+r"(v[0].z), "+r"(v[0].w), "+r"(v[1].x), "+r"(v[1].y), "+r"(v[1].z), "+r"(v[1].w),
                           "+r"(v[2].x), "+r"(v[2].y), "+r"(v[2].z), "+r"(v[2].w), "+r"(v[3].x), "+r"(v[3].y), "+r"(v[3].z), "+r"(v[3].w),
                           "+r"(v[4].x), "+r"(v[4].y), "+r"(v[4].z), "+r"(v[4].w), "+r"(v[5].x), "+r"(v[5].y), "+r"(v[5].z), "+r"(v[5].w), "+r"(nretry)
                         : "l"(pbase) : "memory");
                    if (!ok0) {
                        convert(0); bar_arrive(2, 384);
                        mmax = absmax2(absmax2(absmax2(v[0].x, v[0].y), absmax2(v[0].z, v[1].x)), absmax2(v[1].y, v[1].z));
                    }
                    if (!ok1) { convert(1); convert(2); bar_arrive(15, 384); }
                }
                if (c == 0) STAMP(s, 12);
                if (c == 0) STAMPV(s, 14, nretry);
                mmax = absmax2(mmax, absmax2(absmax2(absmax2(v[2].x, v[2].y), absmax2(v[2].z, v[3].x)), absmax2(absmax2(v[3].y, v[3].z), absmax2(v[4].x, v[4].y))));
                mmax = absmax2(mmax, absmax2(absmax2(v[4].z, v[5].x), absmax2(v[5].y, v[5].z))) & 0x7fff7fffu;
                { const float2 mf = __half22float2(*reinterpret_cast<__half2*>(&mmax)); mmax = max(__float_as_uint(mf.x), __float_as_uint(mf.y)); }
            }
            roff += 24576;
        }
        {
            bar_sync(7, 384);
            if (c == 0) flag_inc_if(l16c, &g_flag[F_QKV + (4 * (NBLK - 1) + (h >> 3)) * 8]);
        }
    }
    if (warp == 8) PSTAMP(13);
    cluster_sync();
}

constexpr int NST = 10;
constexpr int G_RING = 0, G_EX = NST * 16384, G_OUT = G_EX + 32768, G_CARRY = G_OUT + 32768, G_OPS = G_CARRY + 512, G_BAR = G_OPS + 256, BG_SMEM = G_BAR + 256;
constexpr int GB_FULL = G_BAR, GB_EMPTY = G_BAR + 8 * NST, GB_W = G_BAR + 16 * NST;
static_assert(BG_SMEM <= 232448, "smem");

template <int ACC>
__device__ __forceinline__ void wgmma_n128_rs(float (&d)[64], uint32_t a0, uint32_t a1, uint32_t a2, uint32_t a3, uint64_t desc) {
    asm volatile("wgmma.mma_async.sync.aligned.m64n128k16.f32.bf16.bf16 "
        "{%0,%1,%2,%3,%4,%5,%6,%7,%8,%9,%10,%11,%12,%13,%14,%15,%16,%17,%18,%19,%20,%21,%22,%23,%24,%25,%26,%27,%28,%29,%30,%31,"
        "%32,%33,%34,%35,%36,%37,%38,%39,%40,%41,%42,%43,%44,%45,%46,%47,%48,%49,%50,%51,%52,%53,%54,%55,%56,%57,%58,%59,%60,%61,%62,%63}, "
        "{%64,%65,%66,%67}, %68, %69, 1, 1, 0;"
        : "+f"(d[0]), "+f"(d[1]), "+f"(d[2]), "+f"(d[3]), "+f"(d[4]), "+f"(d[5]), "+f"(d[6]), "+f"(d[7]),
          "+f"(d[8]), "+f"(d[9]), "+f"(d[10]), "+f"(d[11]), "+f"(d[12]), "+f"(d[13]), "+f"(d[14]), "+f"(d[15]),
          "+f"(d[16]), "+f"(d[17]), "+f"(d[18]), "+f"(d[19]), "+f"(d[20]), "+f"(d[21]), "+f"(d[22]), "+f"(d[23]),
          "+f"(d[24]), "+f"(d[25]), "+f"(d[26]), "+f"(d[27]), "+f"(d[28]), "+f"(d[29]), "+f"(d[30]), "+f"(d[31]),
          "+f"(d[32]), "+f"(d[33]), "+f"(d[34]), "+f"(d[35]), "+f"(d[36]), "+f"(d[37]), "+f"(d[38]), "+f"(d[39]),
          "+f"(d[40]), "+f"(d[41]), "+f"(d[42]), "+f"(d[43]), "+f"(d[44]), "+f"(d[45]), "+f"(d[46]), "+f"(d[47]),
          "+f"(d[48]), "+f"(d[49]), "+f"(d[50]), "+f"(d[51]), "+f"(d[52]), "+f"(d[53]), "+f"(d[54]), "+f"(d[55]),
          "+f"(d[56]), "+f"(d[57]), "+f"(d[58]), "+f"(d[59]), "+f"(d[60]), "+f"(d[61]), "+f"(d[62]), "+f"(d[63])
        : "r"(a0), "r"(a1), "r"(a2), "r"(a3), "l"(desc), "n"(ACC));
}
template <int ACC>
__device__ __forceinline__ void wgmma_n64_rs(float (&d)[64], uint32_t a0, uint32_t a1, uint32_t a2, uint32_t a3, uint64_t desc) {
    asm volatile("wgmma.mma_async.sync.aligned.m64n64k16.f32.bf16.bf16 "
        "{%0,%1,%2,%3,%4,%5,%6,%7,%8,%9,%10,%11,%12,%13,%14,%15,%16,%17,%18,%19,%20,%21,%22,%23,%24,%25,%26,%27,%28,%29,%30,%31}, "
        "{%32,%33,%34,%35}, %36, %37, 1, 1, 0;"
        : "+f"(d[0]), "+f"(d[1]), "+f"(d[2]), "+f"(d[3]), "+f"(d[4]), "+f"(d[5]), "+f"(d[6]), "+f"(d[7]),
          "+f"(d[8]), "+f"(d[9]), "+f"(d[10]), "+f"(d[11]), "+f"(d[12]), "+f"(d[13]), "+f"(d[14]), "+f"(d[15]),
          "+f"(d[16]), "+f"(d[17]), "+f"(d[18]), "+f"(d[19]), "+f"(d[20]), "+f"(d[21]), "+f"(d[22]), "+f"(d[23]),
          "+f"(d[24]), "+f"(d[25]), "+f"(d[26]), "+f"(d[27]), "+f"(d[28]), "+f"(d[29]), "+f"(d[30]), "+f"(d[31])
        : "r"(a0), "r"(a1), "r"(a2), "r"(a3), "l"(desc), "n"(ACC));
}
__device__ __forceinline__ void wait_flag(const unsigned* p, unsigned target) {
    asm volatile("{\n.reg .pred p;\n.reg .u32 n, v;\nmov.u32 n, 0;\n"
                 "W_%=: ld.acquire.gpu.global.u32 v, [%0];\nsub.u32 v, v, %1;\nsetp.ge.s32 p, v, 0;\n@p bra.uni D_%=;\nnanosleep.u32 " NSLEEP ";\n"
                 "add.u32 n, n, 1;\nsetp.lt.u32 p, n, 4000000;\n@p bra.uni W_%=;\ntrap;\nD_%=:\n}" :: "l"(p), "r"(target) : "memory");
}
template <int NS, int NT>
__device__ __forceinline__ void bg_mainloop(float (&d)[64], const uint32_t (&a)[144], uint32_t sb, int it, int lane) {
    int slot = it % NST, ph = (it / NST) & 1, prev = 0;
#pragma unroll
    for (int i = 0; i < NS; i++) {
        mbar_wait(sb + GB_FULL + 8 * slot, ph);
        const uint64_t desc = (uint64_t)(((sb + G_RING + slot * 16384) & 0x3FFFF) >> 4) | (1ull << 16) | (64ull << 32) | (1ull << 62);
        wg_fence();
#pragma unroll
        for (int k = 0; k < 512 / NT; k++) {
            const int u = (2048 / NT) * i + 4 * k;
            if (NT == 128) {
                if (i == 0 && k == 0) wgmma_n128_rs<0>(d, a[u], a[u + 1], a[u + 2], a[u + 3], desc);
                else wgmma_n128_rs<1>(d, a[u], a[u + 1], a[u + 2], a[u + 3], desc + 2 * k);
            } else {
                if (i == 0 && k == 0) wgmma_n64_rs<0>(d, a[u], a[u + 1], a[u + 2], a[u + 3], desc);
                else wgmma_n64_rs<1>(d, a[u], a[u + 1], a[u + 2], a[u + 3], desc + 2 * (k & 3) + (k >> 2) * 512);
            }
        }
        wg_commit();
        if (i > 0) {
            asm volatile("wgmma.wait_group.sync.aligned 1;" ::: "memory");
            mbar_arrive_if(lane, sb + GB_EMPTY + 8 * prev);
        }
        prev = slot;
        slot += 2;
        if (slot >= NST) { slot -= NST; ph ^= 1; }
    }
    wg_wait0();
    mbar_arrive_if(lane, sb + GB_EMPTY + 8 * prev);
}
template <bool SKIP, int NT>
__device__ __forceinline__ void bg_epilogue(float (&d)[64], uint32_t sb, int wg, int w, int lane, const CUtensorMap* tm_out, int col0, int tok0,
                                            const __nv_bfloat16* xa, const __nv_bfloat16* Dk) {
    constexpr int H = NT / 4;
    const int g = lane >> 2, t = lane & 3;
    const uint32_t ex = sb + G_EX + w * 4096 + lane * 16;
    float k[H];
    if (wg == 0) {
#pragma unroll
        for (int q = 0; q < H / 4; q++) sts128f(ex + q * 512, d[H + 4 * q], d[H + 4 * q + 1], d[H + 4 * q + 2], d[H + 4 * q + 3]);
#pragma unroll
        for (int i = 0; i < H; i++) k[i] = d[i];
    } else {
#pragma unroll
        for (int q = 0; q < H / 4; q++) sts128f(ex + 16384 + q * 512, d[4 * q], d[4 * q + 1], d[4 * q + 2], d[4 * q + 3]);
#pragma unroll
        for (int i = 0; i < H; i++) k[i] = d[H + i];
    }
    uint32_t xv[16], dv = 0;
    if (SKIP) {
        const __nv_bfloat16* xp = xa + (size_t)(tok0 + 64 * wg + 2 * t) * DM + col0 + 16 * w + 2 * g;
#pragma unroll
        for (int i = 0; i < 16; i++) xv[i] = ldg_nc32(xp + (8 * (i >> 1) + (i & 1)) * DM);
        dv = ldg_nc32(Dk + col0 + 16 * w + 2 * g);
    }
    if (SKIP && w == 0) asm volatile("cp.async.bulk.wait_group.read 0;" ::: "memory");
    bar_sync(1, 256);
#pragma unroll
    for (int q = 0; q < H / 4; q++) {
        const float4 o = lds128f(ex + (wg ^ 1) * 16384 + q * 512);
        k[4 * q] += o.x; k[4 * q + 1] += o.y; k[4 * q + 2] += o.z; k[4 * q + 3] += o.w;
    }
    if (SKIP) bar_sync(1, 256); else bar_sync(13, 288);
    const uint32_t ob = sb + G_OUT + wg * (NT == 128 ? 16384 : 4096) + (w >> 1) * 8192 + (g & 1) * 8;
    const uint32_t ch = (w & 1) * 4 + (g >> 1);
#pragma unroll
    for (int i = 0; i < H / 2; i++) {
        float v0 = k[4 * (i >> 1) + (i & 1)], v1 = k[4 * (i >> 1) + 2 + (i & 1)];
        if (SKIP) {
            const uint32_t p = pack_bf16(__uint_as_float(xv[i] << 16) * __uint_as_float(dv << 16), __uint_as_float(xv[i] & 0xffff0000u) * __uint_as_float(dv & 0xffff0000u));
            v0 += __uint_as_float(p << 16); v1 += __uint_as_float(p & 0xffff0000u);
        }
        const uint32_t n7 = 2 * t + (i & 1);
        sts64(ob + (8 * (i >> 1) + n7) * 128 + ((ch ^ n7) << 4), __float_as_uint(v0), __float_as_uint(v1));
    }
    fence_async_smem();
    if (SKIP) {
        bar_sync(4 + wg, 128);
        if (w == 0)
            asm volatile("{\n.reg .pred p;\nelect.sync _|p, 0xffffffff;\n"
                "@p cp.async.bulk.tensor.2d.global.shared::cta.bulk_group [%0, {%2, %4}], [%1];\n"
                "@p cp.async.bulk.tensor.2d.global.shared::cta.bulk_group [%0, {%3, %4}], [%1+8192];\n@p cp.async.bulk.commit_group;\n}"
                :: "l"(tm_out), "r"(sb + G_OUT + wg * 16384), "r"(col0), "r"(col0 + 32), "r"(tok0 + 64 * wg) : "memory");
    } else {
        bar_arrive(12, 288);
    }
}
__device__ __forceinline__ void s5_channel(int p, const __nv_bfloat16* Lre, const __nv_bfloat16* Lim, const __nv_bfloat16* logdt, float2& lam, float2& coef) {
    const float dt = __bfloat162float(__float2bfloat16(expf(__bfloat162float(logdt[p]))));
    const float lr = __bfloat162float(Lre[p]), li = __bfloat162float(Lim[p]);
    const float e = expf(dt * lr);
    float sn, cs;
    sincosf(dt * li, &sn, &cs);
    lam = make_float2(e * cs, e * sn);
    const float den = lr * lr + li * li;
    coef = make_float2(((lam.x - 1.f) * lr + lam.y * li) / den, (lam.y * lr - (lam.x - 1.f) * li) / den);
}
__device__ __forceinline__ float2 cfma(float2 a, float2 b, float2 c) {
    return make_float2(fmaf(a.x, b.x, fmaf(-a.y, b.y, c.x)), fmaf(a.x, b.y, fmaf(a.y, b.x, c.y)));
}
__device__ __forceinline__ uint4 ldg128(const void* p) { uint4 v; asm volatile("ld.global.v4.u32 {%0,%1,%2,%3}, [%4];" : "=r"(v.x), "=r"(v.y), "=r"(v.z), "=r"(v.w) : "l"(p) : "memory"); return v; }
__device__ __forceinline__ uint2 ldg64(const void* p) { uint2 v; asm volatile("ld.global.v2.u32 {%0,%1}, [%2];" : "=r"(v.x), "=r"(v.y) : "l"(p) : "memory"); return v; }

template <int MT>
__device__ __forceinline__ void bg_attention(uint32_t st0, uint32_t st1, int lane) {
    constexpr int NK = MT ? 5 : 3;
    const int g = lane >> 2, t = lane & 3;
    float sc[NK][4], sm2[4];
#pragma unroll
    for (int i = 0; i < 8; i++) {
        const uint32_t st = (i >> 2 ? st1 : st0) + (i & 3) * 512 + lane * 16;
        const uint4 q = ldsm4(st + MT * 2048), km = ldsm4(st + 8192), k0 = ldsm4(st + 4096);
        if (i == 0) {
            mma16816_z(sc[0], q.x, q.y, q.z, q.w, km.x, km.y); mma16816_z(sm2, q.x, q.y, q.z, q.w, km.z, km.w);
            mma16816_z(sc[1], q.x, q.y, q.z, q.w, k0.x, k0.y); mma16816_z(sc[2], q.x, q.y, q.z, q.w, k0.z, k0.w);
        } else {
            mma16816(sc[0], q.x, q.y, q.z, q.w, km.x, km.y); mma16816(sm2, q.x, q.y, q.z, q.w, km.z, km.w);
            mma16816(sc[1], q.x, q.y, q.z, q.w, k0.x, k0.y); mma16816(sc[2], q.x, q.y, q.z, q.w, k0.z, k0.w);
        }
        if (MT) {
            const uint4 k1 = ldsm4(st + 6144);
            if (i == 0) { mma16816_z(sc[NK - 2], q.x, q.y, q.z, q.w, k1.x, k1.y); mma16816_z(sc[NK - 1], q.x, q.y, q.z, q.w, k1.z, k1.w); }
            else { mma16816(sc[NK - 2], q.x, q.y, q.z, q.w, k1.x, k1.y); mma16816(sc[NK - 1], q.x, q.y, q.z, q.w, k1.z, k1.w); }
        }
    }
#pragma unroll
    for (int i = 0; i < 4; i++) sc[0][i] += sm2[i];
    if (2 * t > g) { sc[NK - 2][0] = -INFINITY; sc[NK - 1][2] = -INFINITY; }
    if (2 * t + 1 > g) { sc[NK - 2][1] = -INFINITY; sc[NK - 1][3] = -INFINITY; }
    sc[NK - 1][0] = sc[NK - 1][1] = -INFINITY;
    float ma = fmaxf(sc[0][0], sc[0][1]), mb = fmaxf(sc[0][2], sc[0][3]);
#pragma unroll
    for (int n = 1; n < NK; n++) { ma = fmaxf(ma, fmaxf(sc[n][0], sc[n][1])); mb = fmaxf(mb, fmaxf(sc[n][2], sc[n][3])); }
    ma = quad_max(ma) * SM_SCALE; mb = quad_max(mb) * SM_SCALE;
    uint32_t Pa[NK], Pb[NK];
#pragma unroll
    for (int n = 0; n < NK; n++) {
        Pa[n] = n == NK - 1 ? 0u : pack_bf16(ex2(fmaf(sc[n][0], SM_SCALE, -ma)), ex2(fmaf(sc[n][1], SM_SCALE, -ma)));
        Pb[n] = pack_bf16(ex2(fmaf(sc[n][2], SM_SCALE, -mb)), ex2(fmaf(sc[n][3], SM_SCALE, -mb)));
    }
    float sa[4], sbb[4];
    mma1688_z(sa, ONES, ONES, Pa[0]); mma1688_z(sbb, ONES, ONES, Pb[0]);
    mma16816(sa, ONES, ONES, ONES, ONES, Pa[1], Pa[2]); mma16816(sbb, ONES, ONES, ONES, ONES, Pb[1], Pb[2]);
    if (MT) { mma16816(sa, ONES, ONES, ONES, ONES, Pa[NK - 2], Pa[NK - 1]); mma16816(sbb, ONES, ONES, ONES, ONES, Pb[NK - 2], Pb[NK - 1]); }
    const float ra0 = rcp_fast(sa[0]), ra1 = rcp_fast(sa[1]), rb0 = rcp_fast(sbb[0]), rb1 = rcp_fast(sbb[1]);
    const uint32_t row = lane & 7;
    const uint32_t so = MT * 2048 + (lane >> 4) * 1024 + row * 128;
#pragma unroll
    for (int eh = 0; eh < 2; eh++) {
        const uint32_t st = eh ? st1 : st0;
        float2 vm[4]; uint4 v0[4], v1[4];
#pragma unroll
        for (int e4 = 0; e4 < 4; e4++) {
            vm[e4] = lds64f(st + 14336 + e4 * 256 + lane * 8);
            v0[e4] = lds128(st + 10240 + e4 * 1024 + lane * 16);
            if (MT) v1[e4] = lds128(st + 10240 + e4 * 1024 + 512 + lane * 16);
        }
        float oa[4][4], ob[4][4];
#pragma unroll
        for (int e4 = 0; e4 < 4; e4++) {
            mma1688_z(oa[e4], __float_as_uint(vm[e4].x), __float_as_uint(vm[e4].y), Pa[0]);
            mma1688_z(ob[e4], __float_as_uint(vm[e4].x), __float_as_uint(vm[e4].y), Pb[0]);
        }
#pragma unroll
        for (int e4 = 0; e4 < 4; e4++) {
            mma16816(oa[e4], v0[e4].x, v0[e4].y, v0[e4].z, v0[e4].w, Pa[1], Pa[2]);
            mma16816(ob[e4], v0[e4].x, v0[e4].y, v0[e4].z, v0[e4].w, Pb[1], Pb[2]);
        }
        if (MT) {
#pragma unroll
            for (int e4 = 0; e4 < 4; e4++) {
                mma16816(oa[e4], v1[e4].x, v1[e4].y, v1[e4].z, v1[e4].w, Pa[NK - 2], Pa[NK - 1]);
                mma16816(ob[e4], v1[e4].x, v1[e4].y, v1[e4].z, v1[e4].w, Pb[NK - 2], Pb[NK - 1]);
            }
        }
#pragma unroll
        for (int e4 = 0; e4 < 4; e4++)
            stsm4t(st + so + (((2 * e4 + ((lane >> 3) & 1)) ^ row) << 4), pack_bf16(oa[e4][0] * ra0, oa[e4][1] * ra1), pack_bf16(oa[e4][2] * ra0, oa[e4][3] * ra1),
                   pack_bf16(ob[e4][0] * rb0, ob[e4][1] * rb1), pack_bf16(ob[e4][2] * rb0, ob[e4][3] * rb1));
    }
}
__device__ __forceinline__ bool wait_either(const unsigned* pa, unsigned ta, bool allow_a, const unsigned* pg, unsigned tg, bool allow_g) {
    uint32_t res;
    asm volatile("{\n.reg .pred p, qa, qg;\n.reg .u32 n, v, u;\nmov.u32 n, 0;\nsetp.ne.u32 qa, %5, 0;\nsetp.ne.u32 qg, %6, 0;\n"
                 "W_%=: mov.u32 %0, 1;\n@!qa bra.uni G_%=;\nld.acquire.gpu.global.u32 v, [%1];\nsub.u32 v, v, %2;\nsetp.ge.s32 p, v, 0;\n@p bra.uni D_%=;\n"
                 "G_%=: mov.u32 %0, 0;\n@!qg bra.uni S_%=;\nld.acquire.gpu.global.u32 u, [%3];\nsub.u32 u, u, %4;\nsetp.ge.s32 p, u, 0;\n@p bra.uni D_%=;\nS_%=: "
                 "nanosleep.u32 " NSLEEP ";\nadd.u32 n, n, 1;\nsetp.lt.u32 p, n, 4000000;\n@p bra.uni W_%=;\ntrap;\n"
                 "D_%=: fence.proxy.async.global;\n}"
                 : "=r"(res) : "l"(pa), "r"(ta), "l"(pg), "r"(tg), "r"((uint32_t)allow_a), "r"((uint32_t)allow_g) : "memory");
    return res != 0;
}

__global__ void __launch_bounds__(384, 1)
bg_kernel(const __grid_constant__ CUtensorMap tm_xa, const __grid_constant__ CUtensorMap tm_wo, const __grid_constant__ CUtensorMap tm_out,
          const __nv_bfloat16* __restrict__ xa, const __nv_bfloat16* __restrict__ Lre, const __nv_bfloat16* __restrict__ Lim,
          const __nv_bfloat16* __restrict__ Bre, const __nv_bfloat16* __restrict__ Bim, const __nv_bfloat16* __restrict__ Cre,
          const __nv_bfloat16* __restrict__ Cim, const __nv_bfloat16* __restrict__ logdt, const __nv_bfloat16* __restrict__ Dk, float* __restrict__ out) {
    extern __shared__ __align__(1024) uint8_t smem_raw[];
    const uint32_t sb = smem_u32(smem_raw);
    const int lane = threadIdx.x & 31;
    const int warp = __shfl_sync(~0u, threadIdx.x >> 5, 0);
    const int wg = warp >> 2, w = warp & 3, b = blockIdx.x;
    const int nt = b % 9, kq = b / 9;
    BSTAMP(0);
    if (threadIdx.x == 0) {
        if (sb & 1023u) __trap();
        for (int i = 0; i < NST; i++) { mbar_init(sb + GB_FULL + 8 * i, 1); mbar_init(sb + GB_EMPTY + 8 * i, 4); }
        mbar_init(sb + GB_W, 1);
        asm volatile("fence.mbarrier_init.release.cluster;" ::: "memory");
        mbar_expect(sb + GB_W, (b < 18 ? 64 : 128) * 1152);
        sts32(sb + G_BAR + 248, atomicAdd(&g_ticket_bg, 1u) / 36u + 1u);
    }
    __syncthreads();
    if (wg == 2) {
        asm volatile("setmaxnreg.dec.sync.aligned.u32 24;");
        if (w == 0) {
            int slot = 0, ph = 1;
            auto next = [&]() { if (++slot == NST) { slot = 0; ph ^= 1; } };
            bar_sync(6, 288);
            if (b < 18) {
#pragma unroll 1
                for (int i = 0; i < 144; i++) {
                    const int blk = i / 9, kb = i - 9 * blk, it = (blk >> 1) * 18 + (blk & 1) + 2 * kb;
                    slot = it % NST;
                    mbar_wait(sb + GB_EMPTY + 8 * slot, ((it / NST) & 1) ^ 1);
                    asm volatile("{\n.reg .pred p;\nelect.sync _|p, 0xffffffff;\n@p mbarrier.arrive.expect_tx.shared::cta.b64 _, [%2], 16384;\n"
                        "@p cp.async.bulk.tensor.5d.shared::cluster.global.mbarrier::complete_tx::bytes [%0], [%1, {%3, %4, %4, %4, %5}], [%2];\n}"
                        :: "r"(sb + G_RING + slot * 16384), "l"(&tm_xa), "r"(sb + GB_FULL + 8 * slot), "r"(kb * 64), "r"(0), "r"(blk) : "memory");
                }
                slot = 144 % NST; ph = ((144 / NST) & 1) ^ 1;
            }
            const unsigned ep = lds32(sb + G_BAR + 248);
            auto slabs = [&](const char* src, int ns) {
                asm volatile("fence.proxy.async.global;" ::: "memory");
#pragma unroll 1
                for (int i = 0; i < ns; i++) {
                    mbar_wait(sb + GB_EMPTY + 8 * slot, ph);
                    asm volatile("{\n.reg .pred p;\nelect.sync _|p, 0xffffffff;\n@p mbarrier.arrive.expect_tx.shared::cta.b64 _, [%2], 16384;\n"
                        "@p cp.async.bulk.shared::cluster.global.mbarrier::complete_tx::bytes [%0], [%1], 16384, [%2];\n}"
                        :: "r"(sb + G_RING + slot * 16384), "l"(src + (size_t)((i & 1) * (ns >> 1) + (i >> 1)) * (SEQ * 128)), "r"(sb + GB_FULL + 8 * slot) : "memory");
                    next();
                }
            };
            if (b >= 18) {
#pragma unroll 1
                for (int blk = kq - 2; blk < 16; blk += 2) {
                    wait_flag(&g_flag[F_H + blk * 8], 18 * ep);
                    slabs(reinterpret_cast<const char*>(g_h) + blk * 16384, 18);
                }
            }
            bar_sync(6, 288);
#pragma unroll 1
            for (int na = nt < 8 ? 0 : NBLK, ng = 0, k = 0; ng < NBLK; k++) {
                const bool att = wait_either(&g_flag[F_QKV + (min(na, NBLK - 1) * 4 + kq) * 8], 24 * ep, na < NBLK && na <= ng + 1,
                                             &g_flag[F_OX + (ng * 4 + kq) * 8], 8 * ep, ng < na);
                sts32_if(lane, sb + G_OPS + 4 * k, att);
                __syncwarp();
                if (att) {
                    {
#pragma unroll 1
                        for (int i = 0; i < (na < NBIG ? 8 : 4); i++) {
                            const int hf = (i >> 1) & 1;
                            const char* rec = reinterpret_cast<const char*>(g_qkv) + (size_t)((blk_seg0(na) + 2 * (i >> 2) + (i & 1)) * NH + 8 * kq + nt) * REC;
                            mbar_wait(sb + GB_EMPTY + 8 * slot, ph);
                            asm volatile("{\n.reg .pred p;\nelect.sync _|p, 0xffffffff;\n@p mbarrier.arrive.expect_tx.shared::cta.b64 _, [%4], 15360;\n"
                                "@p cp.async.bulk.shared::cluster.global.mbarrier::complete_tx::bytes [%0], [%1], 10240, [%4];\n"
                                "@p cp.async.bulk.shared::cluster.global.mbarrier::complete_tx::bytes [%0+10240], [%2], 4096, [%4];\n"
                                "@p cp.async.bulk.shared::cluster.global.mbarrier::complete_tx::bytes [%0+14336], [%3], 1024, [%4];\n}"
                                :: "r"(sb + G_RING + slot * 16384), "l"(rec + hf * 10240), "l"(rec + 20480 + hf * 4096), "l"(rec + 28672 + hf * 1024),
                                   "r"(sb + GB_FULL + 8 * slot) : "memory");
                            next();
                        }
                    }
                    na++;
                } else {
                    const char* src = reinterpret_cast<const char*>(g_ox) + (size_t)kq * 16 * SEQ * 128 + blk_seg0(ng) * 4096;
                    if (ng < NBIG) slabs(src, 16);
                    else {
#pragma unroll 1
                        for (int i = 0; i < 8; i++) {
                            mbar_wait(sb + GB_EMPTY + 8 * slot, ph);
                            asm volatile("{\n.reg .pred p;\nelect.sync _|p, 0xffffffff;\n@p mbarrier.arrive.expect_tx.shared::cta.b64 _, [%2], 16384;\n"
                                "@p cp.async.bulk.shared::cluster.global.mbarrier::complete_tx::bytes [%0], [%1], 8192, [%2];\n"
                                "@p cp.async.bulk.shared::cluster.global.mbarrier::complete_tx::bytes [%0+8192], [%1+262144], 8192, [%2];\n}"
                                :: "r"(sb + G_RING + slot * 16384), "l"(src + (size_t)((i & 1) * 8 + (i & 6)) * (SEQ * 128)), "r"(sb + GB_FULL + 8 * slot) : "memory");
                            next();
                        }
                    }
                    ng++;
                }
            }
        } else if (w == 1) {
            if (b < 18) {
#pragma unroll 1
                for (int blk = 0; blk < 16; blk++) {
                    bar_sync(8 + (blk & 1), 160);
                    asm volatile("{\n.reg .pred p;\nelect.sync _|p, 0xffffffff;\n@p cp.async.bulk.global.shared::cta.bulk_group [%0], [%1], 16384;\n"
                        "@p cp.async.bulk.commit_group;\ncp.async.bulk.wait_group 0;\nfence.proxy.async.global;\n}"
                        :: "l"(reinterpret_cast<char*>(g_h) + ((size_t)b * SEQ + blk * 128) * 128), "r"(sb + G_OUT + (blk & 1) * 16384) : "memory");
                    bar_arrive(10 + (blk & 1), 160);
                    flag_inc_if(lane, &g_flag[F_H + blk * 8]);
                }
            }
            if (nt < 8) {
#pragma unroll 1
                for (int na = 0; na < NBLK; na++) {
                    {
                        const int ns = na < NBIG ? 8 : 4;
                        bar_sync(7, 288);
                        const int it = lds32(sb + G_OPS + 252);
                        if (lane < ns) {
                            asm volatile("cp.async.bulk.global.shared::cta.bulk_group [%0], [%1], 4096;\ncp.async.bulk.commit_group;\ncp.async.bulk.wait_group.read 0;\n"
                                "mbarrier.arrive.shared::cta.b64 _, [%2], 4;\ncp.async.bulk.wait_group 0;\nfence.proxy.async.global;"
                                :: "l"(reinterpret_cast<char*>(g_ox) + ((size_t)((8 * kq + nt) * 2 + ((lane >> 1) & 1)) * SEQ + (blk_seg0(na) + 2 * (lane >> 2) + (lane & 1)) * 32) * 128),
                                   "r"(sb + G_RING + ((it + lane) % NST) * 16384), "r"(sb + GB_EMPTY + 8 * ((it + lane) % NST)) : "memory");
                        }
                        __syncwarp();
                        bar_arrive(14, 288);
                        flag_inc_if(lane, &g_flag[F_OX + (na * 4 + kq) * 8]);
                    }
                }
            }
        } else if (w == 2) {
            const unsigned ep = lds32(sb + G_BAR + 248);
#pragma unroll 1
            for (int blk = 0; blk < NBLK; blk++) {
                const bool last = blk == NBLK - 1, add = kq || last;
                bar_arrive(13, 288);
                bar_sync(12, 288);
                if (add) { wait_flag(&g_flag[F_OUT + (blk * 9 + nt) * 8], ep); asm volatile("fence.proxy.async.global;" ::: "memory"); }
#pragma unroll 1
                for (int i = 0; i < (blk < NBIG ? 4 : 2); i++) {
                    const uint32_t src = sb + G_OUT + i * 8192;
                    const int c0 = DM + 64 * nt + (i & 1) * 32, c1 = blk_seg0(blk) * 32 + (i >> 1) * 64;
                    if (add) asm volatile("{\n.reg .pred p;\nelect.sync _|p, 0xffffffff;\n@p cp.reduce.async.bulk.tensor.2d.global.shared::cta.add.bulk_group [%0, {%2, %3}], [%1];\n}"
                                 :: "l"(&tm_out), "r"(src), "r"(c0), "r"(c1) : "memory");
                    else asm volatile("{\n.reg .pred p;\nelect.sync _|p, 0xffffffff;\n@p cp.async.bulk.tensor.2d.global.shared::cta.bulk_group [%0, {%2, %3}], [%1];\n}"
                                 :: "l"(&tm_out), "r"(src), "r"(c0), "r"(c1) : "memory");
                    if (add && blk < NBIG - 1) spin_until(clk(), RED_GAP);
                }
                asm volatile("cp.async.bulk.commit_group;\ncp.async.bulk.wait_group 0;\nfence.proxy.async.global;" ::: "memory");
                __syncwarp();
                if (!add) flag_inc_if(lane, &g_flag[F_OUT + (blk * 9 + nt) * 8]);
                if (!kq && blk == NBLK - 4) {
                    float4* z = reinterpret_cast<float4*>(out + (size_t)(SEQ - 64 + (lane >> 4)) * (2 * DM) + DM + 64 * nt) + (lane & 15);
#pragma unroll 1
                    for (int i = 0; i < 32; i++) z[i * (4 * DM / 4)] = make_float4(0.f, 0.f, 0.f, 0.f);
                    __syncwarp();
                    flag_inc_if(lane, &g_flag[F_OUT + ((NBLK - 1) * 9 + nt) * 8]);
                }
            }
        }
    } else {
        asm volatile("setmaxnreg.inc.sync.aligned.u32 240;");
        const int g = lane >> 2, t = lane & 3, tid = threadIdx.x;
        uint32_t a[144];
        float d[64];
        if (b < 18) {
            if (tid < 64)
                asm volatile("cp.async.bulk.shared::cluster.global.mbarrier::complete_tx::bytes [%0], [%1], 1152, [%2];"
                    :: "r"(sb + tid * 1168), "l"((tid < 32 ? Bre : Bim) + (size_t)(32 * b + (tid & 31)) * DM), "r"(sb + GB_W) : "memory");
            float2 lam, coef;
            s5_channel(32 * b + 8 * w + g, Lre, Lim, logdt, lam, coef);
            float2 l32 = lam;
#pragma unroll
            for (int i = 0; i < 5; i++) l32 = make_float2(l32.x * l32.x - l32.y * l32.y, 2.f * l32.x * l32.y);
            __syncwarp();
            mbar_wait(sb + GB_W, 0);
            const uint32_t ap = sb + (((lane >> 3) & 1) * 32 + 8 * w + (lane & 7)) * 1168 + (lane >> 4) * 16;
#pragma unroll
            for (int ks = 0; ks < 36; ks++) { const uint4 v = ldsm4(ap + ks * 32); a[4 * ks] = v.x; a[4 * ks + 1] = v.y; a[4 * ks + 2] = v.z; a[4 * ks + 3] = v.w; }
            bar_sync(1, 256);
            bar_arrive(6, 288);
            BSTAMP(1);
#pragma unroll 1
            for (int blk = wg; blk < 16; blk += 2) {
                bg_mainloop<9, 128>(d, a, sb, (blk >> 1) * 18 + wg, lane);
                float2 e = make_float2(0.f, 0.f);
#pragma unroll
                for (int i = 0; i < 32; i++) e = cfma(lam, e, make_float2(d[4 * (i >> 1) + (i & 1)], d[4 * (i >> 1) + 2 + (i & 1)]));
                float2 cin = make_float2(0.f, 0.f);
                if (blk > 0) { bar_sync(2 + (wg ^ 1), 256); cin = lds64f(sb + G_CARRY + (wg ^ 1) * 256 + (8 * w + g) * 8); }
                float2 mine = cin;
#pragma unroll
                for (int q = 0; q < 4; q++) {
                    const float2 eq = make_float2(__shfl_sync(~0u, e.x, (lane & 28) + q), __shfl_sync(~0u, e.y, (lane & 28) + q));
                    cin = cfma(l32, cin, eq);
                    if (t == q + 1) mine = cin;
                }
                if (blk < 15) {
                    if (t == 0) sts64(sb + G_CARRY + wg * 256 + (8 * w + g) * 8, __float_as_uint(cin.x), __float_as_uint(cin.y));
                    bar_arrive(2 + wg, 256);
                }
                const uint32_t hs = sb + G_OUT + wg * 16384 + t * 4096 + (g & 3) * 4;
                const uint32_t ch = 2 * w + (g >> 2);
                if (blk >= 2) bar_sync(10 + wg, 160);
#pragma unroll
                for (int i = 0; i < 32; i++) {
                    mine = cfma(lam, mine, make_float2(d[4 * (i >> 1) + (i & 1)], d[4 * (i >> 1) + 2 + (i & 1)]));
                    sts32(hs + i * 128 + ((ch ^ (i & 7)) << 4), pack_bf16(mine.x, mine.y));
                }
                fence_async_smem();
                bar_arrive(8 + wg, 160);
            }
            bar_sync(10 + wg, 160);
        } else {
            if (tid < 128)
                asm volatile("cp.async.bulk.shared::cluster.global.mbarrier::complete_tx::bytes [%0], [%1], 1152, [%2];"
                    :: "r"(sb + tid * 1168), "l"((tid < 64 ? Cre : Cim) + (size_t)(64 * nt + (tid & 63)) * DM), "r"(sb + GB_W) : "memory");
            for (int p = tid; p < DM; p += 256) {
                float2 lam, coef;
                s5_channel(p, Lre, Lim, logdt, lam, coef);
                sts64(sb + G_EX + p * 8, __float_as_uint(2.f * coef.x), __float_as_uint(2.f * coef.y));
            }
            bar_sync(1, 256);
            mbar_wait(sb + GB_W, 0);
            const uint32_t cp = sb + (16 * w + 2 * g) * 1168 + (288 * wg + t) * 2;
#pragma unroll
            for (int u = 0; u < 72; u++) {
                const float2 c2 = lds64f(sb + G_EX + (288 * wg + 4 * u + t) * 8);
#pragma unroll
                for (int f = 0; f < 2; f++) {
                    unsigned short r16, i16;
                    asm volatile("ld.shared.u16 %0, [%1];" : "=h"(r16) : "r"(cp + f * 1168 + u * 8) : "memory");
                    asm volatile("ld.shared.u16 %0, [%1];" : "=h"(i16) : "r"(cp + (64 + f) * 1168 + u * 8) : "memory");
                    const float cr = __uint_as_float((uint32_t)r16 << 16), ci = __uint_as_float((uint32_t)i16 << 16);
                    a[2 * u + f] = pack_bf16(cr * c2.x - ci * c2.y, -(cr * c2.y + ci * c2.x));
                }
            }
            bar_sync(1, 256);
            bar_arrive(6, 288);
            BSTAMP(1);
#pragma unroll 1
            for (int j = 0; j < 8; j++) {
                bg_mainloop<9, 128>(d, a, sb, j * 18 + wg, lane);
                bg_epilogue<true, 128>(d, sb, wg, w, lane, &tm_out, 64 * nt, (2 * j + kq - 2) * 128, xa, Dk);
            }
        }
        if (w == 0) asm volatile("cp.async.bulk.wait_group 0;" ::: "memory");
        bar_sync(1, 256);
        BSTAMP(2);
        if (warp == 0)
            asm volatile("{\n.reg .pred p;\nelect.sync _|p, 0xffffffff;\n@p mbarrier.arrive.expect_tx.shared::cta.b64 _, [%2], 131072;\n"
                "@p cp.async.bulk.tensor.2d.shared::cluster.global.mbarrier::complete_tx::bytes [%0], [%1, {%3, %4}], [%2];\n"
                "@p cp.async.bulk.tensor.2d.shared::cluster.global.mbarrier::complete_tx::bytes [%0+32768], [%1, {%3, %5}], [%2];\n"
                "@p cp.async.bulk.tensor.2d.shared::cluster.global.mbarrier::complete_tx::bytes [%0+65536], [%1, {%3, %6}], [%2];\n"
                "@p cp.async.bulk.tensor.2d.shared::cluster.global.mbarrier::complete_tx::bytes [%0+98304], [%1, {%3, %7}], [%2];\n}"
                :: "r"(sb), "l"(&tm_wo), "r"(sb + GB_W), "r"(64 * nt), "r"(1024 * kq), "r"(1024 * kq + 256), "r"(1024 * kq + 512), "r"(1024 * kq + 768) : "memory");
        mbar_wait(sb + GB_W, 1);
        {
            const uint32_t base = sb + wg * 65536 + 4 * t * 128 + (g & 3) * 4, ch = 2 * w + (g >> 2), r7 = (4 * t) & 7;
#pragma unroll
            for (int ks = 0; ks < 32; ks++) {
                const uint32_t w0 = lds32(base + ks * 2048 + ((ch ^ r7) << 4)), w1 = lds32(base + ks * 2048 + 256 + ((ch ^ (r7 + 2)) << 4));
                const uint32_t w2 = lds32(base + ks * 2048 + 128 + ((ch ^ (r7 + 1)) << 4)), w3 = lds32(base + ks * 2048 + 384 + ((ch ^ (r7 + 3)) << 4));
                a[4 * ks] = __byte_perm(w0, w1, 0x5410); a[4 * ks + 1] = __byte_perm(w0, w1, 0x7632);
                a[4 * ks + 2] = __byte_perm(w2, w3, 0x5410); a[4 * ks + 3] = __byte_perm(w2, w3, 0x7632);
            }
        }
        bar_sync(1, 256);
        bar_arrive(6, 288);
        BSTAMP(3);
#pragma unroll 1
        for (int na = 0, ng = 0, it = 144, k = 0; ng < NBLK; k++) {
            mbar_wait(sb + GB_FULL + 8 * ((it + wg) % NST), ((it + wg) / NST) & 1);
            if (__shfl_sync(~0u, lds32(sb + G_OPS + 4 * k), 0)) {
                {
                    if (na < NBIG || (w >> 1) == wg) {
                        const int i0 = it + wg + (na < NBIG ? 4 * (w >> 1) : 0), i1 = i0 + 2;
                        mbar_wait(sb + GB_FULL + 8 * (i0 % NST), (i0 / NST) & 1);
                        mbar_wait(sb + GB_FULL + 8 * (i1 % NST), (i1 / NST) & 1);
                        BSTAMP(8 + na * 4);
                        if ((w ^ wg) & 1) bg_attention<1>(sb + G_RING + (i0 % NST) * 16384, sb + G_RING + (i1 % NST) * 16384, lane);
                        else bg_attention<0>(sb + G_RING + (i0 % NST) * 16384, sb + G_RING + (i1 % NST) * 16384, lane);
                        fence_async_smem();
                    }
                    if (na > 0) bar_sync(14, 288);
                    if (tid == 0) sts32(sb + G_OPS + 252, it);
                    bar_arrive(7, 288);
                    bar_sync(1, 256);
                    BSTAMP(9 + na * 4);
                    it += na < NBIG ? 8 : 4;
                }
                na++;
            } else if (ng < NBIG) {
                bg_mainloop<8, 128>(d, a, sb, it + wg, lane);
                BSTAMP(10 + ng * 4);
                bg_epilogue<false, 128>(d, sb, wg, w, lane, &tm_out, 0, 0, xa, Dk);
                BSTAMP(11 + ng * 4);
                it += 16; ng++;
            } else {
                bg_mainloop<4, 64>(d, a, sb, it + wg, lane);
                BSTAMP(10 + ng * 4);
                bg_epilogue<false, 64>(d, sb, wg, w, lane, &tm_out, 0, 0, xa, Dk);
                BSTAMP(11 + ng * 4);
                it += 8; ng++;
            }
        }
        if (nt < 8) bar_sync(14, 288);
    }
    asm volatile("griddepcontrol.wait;" ::: "memory");
}

typedef CUresult (*EncodeFn)(CUtensorMap*, CUtensorMapDataType, cuuint32_t, void*, const cuuint64_t*, const cuuint64_t*, const cuuint32_t*, const cuuint32_t*,
                             CUtensorMapInterleave, CUtensorMapSwizzle, CUtensorMapL2promotion, CUtensorMapFloatOOBfill);
}

extern "C" void kernel_launch(void* const* d_in, const int* in_sizes, int n_in, void* d_out, int out_size) {
    typedef const __nv_bfloat16* bp;
    bp Ax = (bp)d_in[0], Lre = (bp)d_in[1], Lim = (bp)d_in[2], Bre = (bp)d_in[3], Bim = (bp)d_in[4], Cre = (bp)d_in[5], Cim = (bp)d_in[6],
       logdt = (bp)d_in[7], Dk = (bp)d_in[8], Bx = (bp)d_in[9], mem0 = (bp)d_in[10], Wq = (bp)d_in[11], Wk = (bp)d_in[12], Wv = (bp)d_in[13], Wo = (bp)d_in[14];
    float* out = (float*)d_out;
    static EncodeFn enc = nullptr;
    if (!enc) {
        void* fn = nullptr; cudaDriverEntryPointQueryResult qr;
        cudaGetDriverEntryPoint("cuTensorMapEncodeTiled", &fn, cudaEnableDefault, &qr);
        enc = (EncodeFn)fn;
        cudaFuncSetAttribute(chain_kernel, cudaFuncAttributeMaxDynamicSharedMemorySize, CHAIN_SMEM);
        cudaFuncSetAttribute(bg_kernel, cudaFuncAttributeMaxDynamicSharedMemorySize, BG_SMEM);
    }
    const cuuint32_t es[5] = {1, 1, 1, 1, 1};
    auto map2d = [&](CUtensorMap* tm, CUtensorMapDataType dt, const void* p, cuuint64_t d0, cuuint64_t d1, cuuint64_t stride, cuuint32_t b0, cuuint32_t b1) {
        cuuint64_t gd[2] = {d0, d1}, gs[1] = {stride}; cuuint32_t bd[2] = {b0, b1};
        enc(tm, dt, 2, (void*)p, gd, gs, bd, es, CU_TENSOR_MAP_INTERLEAVE_NONE, CU_TENSOR_MAP_SWIZZLE_128B, CU_TENSOR_MAP_L2_PROMOTION_L2_128B,
            CU_TENSOR_MAP_FLOAT_OOB_FILL_NONE);
    };
    CUtensorMap tm_x, tm_q, tm_k, tm_v, tm_xa, tm_wo, tm_out;
    map2d(&tm_x, CU_TENSOR_MAP_DATA_TYPE_BFLOAT16, Bx, DM, SEQ, DM * 2, 64, 32);
    map2d(&tm_q, CU_TENSOR_MAP_DATA_TYPE_BFLOAT16, Wq, HD, DM, HD * 2, 64, 192);
    map2d(&tm_k, CU_TENSOR_MAP_DATA_TYPE_BFLOAT16, Wk, HD, DM, HD * 2, 64, 192);
    map2d(&tm_v, CU_TENSOR_MAP_DATA_TYPE_BFLOAT16, Wv, HD, DM, HD * 2, 64, 192);
    map2d(&tm_wo, CU_TENSOR_MAP_DATA_TYPE_BFLOAT16, Wo, DM, HD, DM * 2, 64, 256);
    map2d(&tm_out, CU_TENSOR_MAP_DATA_TYPE_FLOAT32, out, 2 * DM, SEQ, 2 * DM * 4, 32, 64);
    {
        cuuint64_t gd[5] = {DM, 2, 4, 16, 16}, gs[4] = {DM * 2, 32 * DM * 2, 2 * DM * 2, 128 * DM * 2}; cuuint32_t bd[5] = {64, 2, 4, 16, 1};
        enc(&tm_xa, CU_TENSOR_MAP_DATA_TYPE_BFLOAT16, 5, (void*)Ax, gd, gs, bd, es, CU_TENSOR_MAP_INTERLEAVE_NONE, CU_TENSOR_MAP_SWIZZLE_128B,
            CU_TENSOR_MAP_L2_PROMOTION_L2_128B, CU_TENSOR_MAP_FLOAT_OOB_FILL_NONE);
    }
    cudaStream_t st = cudaStreamPerThread;
    chain_kernel<<<96, 384, CHAIN_SMEM, st>>>(tm_x, tm_q, tm_k, tm_v, Bx, mem0, Wo);
    cudaLaunchConfig_t cfg = {};
    cfg.gridDim = dim3(36); cfg.blockDim = dim3(384); cfg.dynamicSmemBytes = BG_SMEM; cfg.stream = st;
    cudaLaunchAttribute at[1];
    at[0].id = cudaLaunchAttributeProgrammaticStreamSerialization; at[0].val.programmaticStreamSerializationAllowed = 1;
    cfg.attrs = at; cfg.numAttrs = 1;
    cudaLaunchKernelEx(&cfg, bg_kernel, tm_xa, tm_wo, tm_out, Ax, Lre, Lim, Bre, Bim, Cre, Cim, logdt, Dk, out);
}
```

```cpp
#include <cuda_runtime.h>
#include <cuda.h>
#include <cuda_bf16.h>
#include <cuda_fp16.h>
#include <stdint.h>

#define D_WAIT 740

#define RED_GAP 720
#define ACC_PF 1
#define QDEP 0
#define NSLEEP "40"
#define D_S0 34
#define D_EARLY 820
#define FLAGPOS 0
#define NORM_LATE 1
#define NRM(x, r) (NORM_LATE ? (x) * (r) : (x))
#define NBIG 14

namespace {

constexpr int DM = 576, NH = 32, SEQ = 2048, NSEG = 64, HD = 4096;

__device__ uint4 g_acc_raw[64 * 96 * 16 + 131072];
__device__ uint4 g_ox[NH * 2 * SEQ * 8];
constexpr int REC = 30720;
__device__ uint4 g_qkv[NSEG * NH * (REC / 16)];
__device__ uint4 g_h[18 * SEQ * 8];
constexpr int NFLAG = 6144, F_QKV = 0, F_OX = 1024, F_H = 2048, F_OUT = 3072;
constexpr int NBLK = NBIG + (NSEG - 4 * NBIG) / 2;
__host__ __device__ constexpr int blk_seg0(int b) { return b < NBIG ? 4 * b : 2 * b + 2 * NBIG; }
__device__ unsigned g_flag[NFLAG];
__device__ unsigned g_ticket, g_ticket_bg;
__device__ unsigned long long g_norm[96];
#define BSTAMP(i) do {} while (0)

__device__ __forceinline__ uint32_t smem_u32(const void* p) { return (uint32_t)__cvta_generic_to_shared(p); }
__device__ __forceinline__ uint32_t mapa(uint32_t a, uint32_t r) { uint32_t o; asm("mapa.shared::cluster.u32 %0, %1, %2;" : "=r"(o) : "r"(a), "r"(r)); return o; }
__device__ __forceinline__ uint32_t mapa_v(uint32_t a, uint32_t r) { uint32_t o; asm volatile("mapa.shared::cluster.u32 %0, %1, %2;" : "=r"(o) : "r"(a), "r"(r)); return o; }
__device__ __forceinline__ unsigned clk() { unsigned long long c; asm volatile("mov.u64 %0, %%clock64;" : "=l"(c) :: "memory"); return (unsigned)c; }
__device__ __forceinline__ void mbar_init(uint32_t bar, uint32_t cnt) { asm volatile("mbarrier.init.shared::cta.b64 [%0], %1;" :: "r"(bar), "r"(cnt) : "memory"); }
__device__ __forceinline__ void mbar_expect(uint32_t bar, uint32_t bytes) { asm volatile("mbarrier.arrive.expect_tx.shared::cta.b64 _, [%0], %1;" :: "r"(bar), "r"(bytes) : "memory"); }
__device__ __forceinline__ void mbar_wait(uint32_t bar, uint32_t parity) {
    asm volatile("{\n.reg .pred p;\n.reg .u32 n;\nmov.u32 n, 0;\n"
                 "W_%=: mbarrier.try_wait.parity.shared::cta.b64 p, [%0], %1;\n@p bra.uni D_%=;\n"
                 "add.u32 n, n, 1;\nsetp.lt.u32 p, n, 4000000;\n@p bra.uni W_%=;\ntrap;\nD_%=:\n}" :: "r"(bar), "r"(parity) : "memory");
}
__device__ __forceinline__ void mbar_expect_if(uint32_t z, uint32_t bar, uint32_t bytes) {
    asm volatile("{\n.reg .pred p;\nsetp.eq.u32 p, %2, 0;\n@p mbarrier.arrive.expect_tx.shared::cta.b64 _, [%0], %1;\n}" :: "r"(bar), "r"(bytes), "r"(z) : "memory");
}
__device__ __forceinline__ void mbar_arrive_if(uint32_t z, uint32_t bar) {
    asm volatile("{\n.reg .pred p;\nsetp.eq.u32 p, %1, 0;\n@p mbarrier.arrive.shared::cta.b64 _, [%0];\n}" :: "r"(bar), "r"(z) : "memory");
}
__device__ __forceinline__ void sts32_if(uint32_t z, uint32_t a, uint32_t x) {
    asm volatile("{\n.reg .pred p;\nsetp.eq.u32 p, %2, 0;\n@p st.shared.u32 [%0], %1;\n}" :: "r"(a), "r"(x), "r"(z) : "memory");
}
template <int K> __device__ __forceinline__ void sched_fence(int v) {
    asm volatile("{\n.reg .pred p;\nsetp.ne.s32 p, %0, %1;\n@p bra.uni F_%=;\ntrap;\nF_%=:\n}" :: "r"(v), "n"(1000 + K) : "memory");
}
__device__ __forceinline__ void spin_until(unsigned t0, unsigned d) {
    asm volatile("{\n.reg .pred p;\n.reg .u64 c;\n.reg .u32 lo;\n"
                 "S_%=: mov.u64 c, %%clock64;\ncvt.u32.u64 lo, c;\nsub.u32 lo, lo, %0;\nsetp.lt.u32 p, lo, %1;\n@p bra.uni S_%=;\n}" :: "r"(t0), "r"(d) : "memory");
}
__device__ __forceinline__ void bar_sync(int id, int n) { asm volatile("bar.sync %0, %1;" :: "r"(id), "r"(n) : "memory"); }
__device__ __forceinline__ void bar_sync_sel(int sel, int id) {
    asm volatile("{\n.reg .pred p;\nsetp.eq.u32 p, %0, 0;\n@p bar.sync %1, %3;\n@!p bar.sync %2, %3;\n}" :: "r"(sel), "r"(id), "r"(id + 1), "n"(192) : "memory");
}
__device__ __forceinline__ void bar_arrive(int id, int n) { asm volatile("bar.arrive %0, %1;" :: "r"(id), "r"(n) : "memory"); }
__device__ __forceinline__ void fence_async_smem() { asm volatile("fence.proxy.async.shared::cta;" ::: "memory"); }
__device__ __forceinline__ uint32_t pack_bf16(float lo, float hi) { uint32_t r; asm("cvt.rn.bf16x2.f32 %0, %1, %2;" : "=r"(r) : "f"(hi), "f"(lo)); return r; }
__device__ __forceinline__ uint32_t pack_f16(float lo, float hi) { uint32_t r; asm("cvt.rn.f16x2.f32 %0, %1, %2;" : "=r"(r) : "f"(hi), "f"(lo)); return r; }
__device__ __forceinline__ uint32_t f16x2_to_bf16x2(uint32_t v) { float2 f = __half22float2(*reinterpret_cast<__half2*>(&v)); return pack_bf16(f.x, f.y); }
__device__ __forceinline__ uint32_t hmul2(uint32_t a, uint32_t b) { uint32_t r; asm("mul.rn.f16x2 %0, %1, %2;" : "=r"(r) : "r"(a), "r"(b)); return r; }
__device__ __forceinline__ float ex2(float x) { float y; asm("ex2.approx.ftz.f32 %0, %1;" : "=f"(y) : "f"(x)); return y; }
__device__ __forceinline__ float ex2v(float x) { float y; asm volatile("ex2.approx.ftz.f32 %0, %1;" : "=f"(y) : "f"(x)); return y; }
__device__ __forceinline__ uint32_t absmax2(uint32_t a, uint32_t b) {
    uint32_t r; asm("max.xorsign.abs.f16x2 %0, %1, %2;" : "=r"(r) : "r"(a), "r"(b)); return r;
}
__device__ __forceinline__ uint32_t shl_v(uint32_t a, int n) { return a << n; }
__device__ __forceinline__ uint32_t max3u(uint32_t a, uint32_t b, uint32_t c) { return max(max(a, b), c); }
__device__ __forceinline__ uint4 lds128(uint32_t a) { uint4 v; asm volatile("ld.shared.v4.u32 {%0,%1,%2,%3}, [%4];" : "=r"(v.x), "=r"(v.y), "=r"(v.z), "=r"(v.w) : "r"(a) : "memory"); return v; }
__device__ __forceinline__ uint4 lds128v(uint32_t a) { uint4 v; asm volatile("ld.volatile.shared.v4.u32 {%0,%1,%2,%3}, [%4];" : "=r"(v.x), "=r"(v.y), "=r"(v.z), "=r"(v.w) : "r"(a) : "memory"); return v; }
__device__ __forceinline__ float4 lds128f(uint32_t a) { float4 v; asm volatile("ld.shared.v4.f32 {%0,%1,%2,%3}, [%4];" : "=f"(v.x), "=f"(v.y), "=f"(v.z), "=f"(v.w) : "r"(a) : "memory"); return v; }
__device__ __forceinline__ float2 lds64f(uint32_t a) { float2 v; asm volatile("ld.shared.v2.f32 {%0,%1}, [%2];" : "=f"(v.x), "=f"(v.y) : "r"(a) : "memory"); return v; }
__device__ __forceinline__ uint4 lds64x2(uint32_t a) { uint4 v; asm volatile("ld.shared.v2.u32 {%0,%1}, [%4];\nld.shared.v2.u32 {%2,%3}, [%4+256];" : "=r"(v.x), "=r"(v.y), "=r"(v.z), "=r"(v.w) : "r"(a) : "memory"); return v; }
__device__ __forceinline__ uint32_t lds32(uint32_t a) { uint32_t v; asm volatile("ld.shared.u32 %0, [%1];" : "=r"(v) : "r"(a) : "memory"); return v; }
__device__ __forceinline__ void sts128(uint32_t a, uint32_t x, uint32_t y, uint32_t z, uint32_t w) { asm volatile("st.shared.v4.u32 [%0], {%1,%2,%3,%4};" :: "r"(a), "r"(x), "r"(y), "r"(z), "r"(w) : "memory"); }
__device__ __forceinline__ void sts128f(uint32_t a, float x, float y, float z, float w) { asm volatile("st.shared.v4.f32 [%0], {%1,%2,%3,%4};" :: "r"(a), "f"(x), "f"(y), "f"(z), "f"(w) : "memory"); }
__device__ __forceinline__ void sts64(uint32_t a, uint32_t x, uint32_t y) { asm volatile("st.shared.v2.u32 [%0], {%1,%2};" :: "r"(a), "r"(x), "r"(y) : "memory"); }
__device__ __forceinline__ void sts32(uint32_t a, uint32_t x) { asm volatile("st.shared.u32 [%0], %1;" :: "r"(a), "r"(x) : "memory"); }
__device__ __forceinline__ uint4 ldsm4(uint32_t a) { uint4 v; asm volatile("ldmatrix.sync.aligned.m8n8.x4.shared.b16 {%0,%1,%2,%3}, [%4];" : "=r"(v.x), "=r"(v.y), "=r"(v.z), "=r"(v.w) : "r"(a) : "memory"); return v; }
__device__ __forceinline__ void stsm2t(uint32_t a, uint32_t x, uint32_t y) { asm volatile("stmatrix.sync.aligned.m8n8.x2.trans.shared.b16 [%0], {%1,%2};" :: "r"(a), "r"(x), "r"(y) : "memory"); }
__device__ __forceinline__ void stsm4t(uint32_t a, uint32_t x, uint32_t y, uint32_t z, uint32_t w) { asm volatile("stmatrix.sync.aligned.m8n8.x4.trans.shared.b16 [%0], {%1,%2,%3,%4};" :: "r"(a), "r"(x), "r"(y), "r"(z), "r"(w) : "memory"); }
__device__ __forceinline__ void st_async64(uint32_t a, uint32_t x, uint32_t y, uint32_t bar) { asm volatile("st.async.shared::cluster.mbarrier::complete_tx::bytes.v2.b32 [%0], {%1,%2}, [%3];" :: "r"(a), "r"(x), "r"(y), "r"(bar) : "memory"); }
__device__ __forceinline__ void bulk_s2c(uint32_t dst, uint32_t src, uint32_t bytes, uint32_t bar) { asm volatile("cp.async.bulk.shared::cluster.shared::cta.mbarrier::complete_tx::bytes [%0], [%1], %2, [%3];" :: "r"(dst), "r"(src), "r"(bytes), "r"(bar) : "memory"); }
__device__ __forceinline__ void bulk_s2g(void* dst, uint32_t src, uint32_t bytes) { asm volatile("cp.async.bulk.global.shared::cta.bulk_group [%0], [%1], %2;" :: "l"(dst), "r"(src), "r"(bytes) : "memory"); }
__device__ __forceinline__ uint32_t ldg_nc32(const void* p) { uint32_t v; asm volatile("ld.global.nc.L2::128B.u32 %0, [%1];" : "=r"(v) : "l"(p)); return v; }
__device__ __forceinline__ uint4 ldg_relaxed128(const void* p) { uint4 v; asm volatile("ld.relaxed.gpu.global.v4.u32 {%0,%1,%2,%3}, [%4];" : "=r"(v.x), "=r"(v.y), "=r"(v.z), "=r"(v.w) : "l"(p) : "memory"); return v; }
__device__ __forceinline__ void mma16816(float (&d)[4], uint32_t a0, uint32_t a1, uint32_t a2, uint32_t a3, uint32_t b0, uint32_t b1) {
    asm volatile("mma.sync.aligned.m16n8k16.row.col.f32.bf16.bf16.f32 {%0,%1,%2,%3}, {%4,%5,%6,%7}, {%8,%9}, {%0,%1,%2,%3};"
        : "+f"(d[0]), "+f"(d[1]), "+f"(d[2]), "+f"(d[3]) : "r"(a0), "r"(a1), "r"(a2), "r"(a3), "r"(b0), "r"(b1));
}
__device__ __forceinline__ void mma16816_z(float (&d)[4], uint32_t a0, uint32_t a1, uint32_t a2, uint32_t a3, uint32_t b0, uint32_t b1) {
    asm volatile("mma.sync.aligned.m16n8k16.row.col.f32.bf16.bf16.f32 {%0,%1,%2,%3}, {%4,%5,%6,%7}, {%8,%9}, {%10,%10,%10,%10};"
        : "=f"(d[0]), "=f"(d[1]), "=f"(d[2]), "=f"(d[3]) : "r"(a0), "r"(a1), "r"(a2), "r"(a3), "r"(b0), "r"(b1), "f"(0.f));
}
__device__ __forceinline__ void mma1688(float (&d)[4], uint32_t a0, uint32_t a1, uint32_t b0) {
    asm volatile("mma.sync.aligned.m16n8k8.row.col.f32.bf16.bf16.f32 {%0,%1,%2,%3}, {%4,%5}, {%6}, {%0,%1,%2,%3};"
        : "+f"(d[0]), "+f"(d[1]), "+f"(d[2]), "+f"(d[3]) : "r"(a0), "r"(a1), "r"(b0));
}
__device__ __forceinline__ void mma1688_z(float (&d)[4], uint32_t a0, uint32_t a1, uint32_t b0) {
    asm volatile("mma.sync.aligned.m16n8k8.row.col.f32.bf16.bf16.f32 {%0,%1,%2,%3}, {%4,%5}, {%6}, {%7,%7,%7,%7};"
        : "=f"(d[0]), "=f"(d[1]), "=f"(d[2]), "=f"(d[3]) : "r"(a0), "r"(a1), "r"(b0), "f"(0.f));
}
template <int ACC>
__device__ __forceinline__ void wgmma_n32_rs(float (&d)[16], uint32_t a0, uint32_t a1, uint32_t a2, uint32_t a3, uint64_t desc) {
    asm volatile("wgmma.mma_async.sync.aligned.m64n32k16.f32.bf16.bf16 {%0,%1,%2,%3,%4,%5,%6,%7,%8,%9,%10,%11,%12,%13,%14,%15}, {%16,%17,%18,%19}, %20, %21, 1, 1, 0;"
        : "+f"(d[0]), "+f"(d[1]), "+f"(d[2]), "+f"(d[3]), "+f"(d[4]), "+f"(d[5]), "+f"(d[6]), "+f"(d[7]),
          "+f"(d[8]), "+f"(d[9]), "+f"(d[10]), "+f"(d[11]), "+f"(d[12]), "+f"(d[13]), "+f"(d[14]), "+f"(d[15])
        : "r"(a0), "r"(a1), "r"(a2), "r"(a3), "l"(desc), "n"(ACC));
}
template <int ACC>
__device__ __forceinline__ void wgmma_n32_ss(float (&d)[16], uint64_t da, uint64_t db) {
    asm volatile("wgmma.mma_async.sync.aligned.m64n32k16.f32.bf16.bf16 {%0,%1,%2,%3,%4,%5,%6,%7,%8,%9,%10,%11,%12,%13,%14,%15}, %16, %17, %18, 1, 1, 0, 0;"
        : "+f"(d[0]), "+f"(d[1]), "+f"(d[2]), "+f"(d[3]), "+f"(d[4]), "+f"(d[5]), "+f"(d[6]), "+f"(d[7]),
          "+f"(d[8]), "+f"(d[9]), "+f"(d[10]), "+f"(d[11]), "+f"(d[12]), "+f"(d[13]), "+f"(d[14]), "+f"(d[15])
        : "l"(da), "l"(db), "n"(ACC));
}
__device__ __forceinline__ void wg_fence() { asm volatile("wgmma.fence.sync.aligned;" ::: "memory"); }
__device__ __forceinline__ void wg_commit() { asm volatile("wgmma.commit_group.sync.aligned;" ::: "memory"); }
__device__ __forceinline__ void wg_wait0() { asm volatile("wgmma.wait_group.sync.aligned 0;" ::: "memory"); }
__device__ __forceinline__ void cluster_sync() { asm volatile("barrier.cluster.arrive.aligned;\nbarrier.cluster.wait.aligned;" ::: "memory"); }

#define STAMP(s, i) do {} while (0)
#define STAMPV(s, i, v) do {} while (0)

constexpr int XT_BYTES = 36864;
constexpr int O_XT = 0;
constexpr int O_STG = XT_BYTES;
constexpr int O_AS = 3 * XT_BYTES;
constexpr int O_XP = O_AS + 16384;
constexpr int O_QKX = O_XP + 8192;
constexpr int O_KM = O_QKX + 8192;
constexpr int O_QM = O_QKX + 10240;
constexpr int O_VX = O_STG + 147456;
constexpr int O_VM = O_VX + 16384;
constexpr int O_SC = O_VM + 2048;
constexpr int O_OF = O_SC + 2560;
constexpr int O_AF = O_OF + 2048;
constexpr int O_WP = O_AF + 4096;
constexpr int O_MF = O_WP + 2048;
constexpr int O_MISC = O_MF + 9216;
static_assert(O_QKX + 24576 <= O_VX, "smem");
constexpr int O_BAR = O_MISC + 64;
constexpr int CHAIN_SMEM = O_BAR + 128;
static_assert(CHAIN_SMEM <= 232448, "smem");
constexpr int B_X = O_BAR, B_VX = O_BAR + 24, B_SC = O_BAR + 40, B_W = O_BAR + 48;
constexpr float SM_SCALE = 0.08838834764831845f * 1.4426950408889634f;
constexpr uint32_t ONES = 0x3f803f80u;

template <bool B> struct BoolC { static constexpr bool value = B; };
__device__ __forceinline__ uint32_t opaque(uint32_t v) { uint32_t o; asm volatile("mov.u32 %0, %1;" : "=r"(o) : "r"(v)); return o; }
__device__ __forceinline__ void st_async128(uint32_t a, uint32_t x, uint32_t y, uint32_t z, uint32_t w, uint32_t bar) {
    asm volatile("st.async.shared::cluster.mbarrier::complete_tx::bytes.v4.b32 [%0], {%1,%2,%3,%4}, [%5];" :: "r"(a), "r"(x), "r"(y), "r"(z), "r"(w), "r"(bar) : "memory");
}
__device__ __forceinline__ void tma_x_tile(uint32_t sb, const CUtensorMap* tm, int r, int j, int slot) {
    asm volatile("{\n.reg .pred p;\nelect.sync _|p, 0xffffffff;\n"
        "@p mbarrier.arrive.expect_tx.shared::cta.b64 _, [%2], 36864;\n"
        "@p cp.async.bulk.tensor.2d.shared::cluster.global.mbarrier::complete_tx::bytes.multicast::cluster [%0], [%1, {%3, %4}], [%2], %7;\n"
        "@p cp.async.bulk.tensor.2d.shared::cluster.global.mbarrier::complete_tx::bytes.multicast::cluster [%0+4096], [%1, {%5, %4}], [%2], %7;\n"
        "@p cp.async.bulk.tensor.2d.shared::cluster.global.mbarrier::complete_tx::bytes.multicast::cluster [%0+8192], [%1, {%6, %4}], [%2], %7;\n}"
        :: "r"(sb + O_XT + slot * XT_BYTES + 3 * r * 4096), "l"(tm), "r"(sb + B_X + 8 * slot), "r"(192 * r), "r"(j * 32), "r"(192 * r + 64), "r"(192 * r + 128),
           "h"((unsigned short)7) : "memory");
}
__device__ __forceinline__ void flag_inc_if(uint32_t z, unsigned* p) {
    asm volatile("{\n.reg .pred p;\nsetp.eq.u32 p, %1, 0;\n@p red.release.gpu.global.inc.u32 [%0], 0xfffffffe;\n}" :: "l"(p), "r"(z) : "memory");
}
__device__ __forceinline__ float quad_max(float v) {
    const float a = __shfl_xor_sync(~0u, v, 1), b = __shfl_xor_sync(~0u, v, 2), c = __shfl_xor_sync(~0u, v, 3);
    return fmaxf(fmaxf(v, a), fmaxf(b, c));
}
__device__ __forceinline__ void load_scores(float (&p)[10], uint32_t base, uint32_t stride, uint32_t l16) {
    const float4 a0 = lds128f(base + l16), b0 = lds128f(base + stride + l16);
    const float4 a1 = lds128f(base + 512 + l16), b1 = lds128f(base + stride + 512 + l16);
    const float2 a2 = lds64f(base + 1024 + (l16 >> 1)), b2 = lds64f(base + stride + 1024 + (l16 >> 1));
    p[0] = a2.x + b2.x; p[1] = a2.y + b2.y;
    p[2] = a0.x + b0.x; p[3] = a0.y + b0.y; p[4] = a0.z + b0.z; p[5] = a0.w + b0.w;
    p[6] = a1.x + b1.x; p[7] = a1.y + b1.y; p[8] = a1.z + b1.z; p[9] = a1.w + b1.w;
}
__device__ __forceinline__ float rcp_fast(float x) { float y; asm("rcp.approx.ftz.f32 %0, %1;" : "=f"(y) : "f"(x)); return y; }

__global__ void __cluster_dims__(3, 1, 1) __launch_bounds__(384, 1)
chain_kernel(const __grid_constant__ CUtensorMap tm_x, const __grid_constant__ CUtensorMap tm_q,
             const __grid_constant__ CUtensorMap tm_k, const __grid_constant__ CUtensorMap tm_v,
             const __nv_bfloat16* __restrict__ x, const __nv_bfloat16* __restrict__ mem0,
             const __nv_bfloat16* __restrict__ Wo) {
    extern __shared__ __align__(1024) uint8_t smem_raw[];
    const uint32_t sb = smem_u32(smem_raw);
    const int lane = threadIdx.x & 31;
    const int warp = __shfl_sync(~0u, threadIdx.x >> 5, 0);
    const int wg = warp >> 2, w = warp & 3;
    const int h = blockIdx.x / 3, r = blockIdx.x - 3 * h;
    uint4* const g_acc = reinterpret_cast<uint4*>((reinterpret_cast<uintptr_t>(g_acc_raw) + 0x1fffff) & ~(uintptr_t)0x1fffff);

#define PSTAMP(i) do {} while (0)
    if (threadIdx.x == 0) {
        if (sb & 1023u) __trap();
        for (int i = 0; i < 9; i++) mbar_init(sb + O_BAR + 8 * i, 1);
        asm volatile("fence.mbarrier_init.release.cluster;" ::: "memory");
        for (int i = 0; i < 3; i++) {
            mbar_expect(sb + B_W + 8 * i, 49152);
            for (int tl = 0; tl < 2; tl++)
                asm volatile("cp.async.bulk.tensor.2d.shared::cluster.global.mbarrier::complete_tx::bytes [%0], [%1, {%3, %4}], [%2];"
                    :: "r"(sb + O_STG + tl * 73728 + i * 24576), "l"(r < 2 ? (tl ? &tm_k : &tm_q) : &tm_v), "r"(sb + B_W + 8 * i),
                       "r"(h * 128 + 64 * (r < 2 ? r : tl)), "r"(192 * i) : "memory");
        }
    }
    __syncwarp();
    asm volatile("barrier.cluster.arrive.relaxed.aligned;" ::: "memory");
    asm volatile("griddepcontrol.launch_dependents;" ::: "memory");
    if (warp == 0) PSTAMP(9);
    const uint32_t l16c = __shfl_sync(~0u, lane * 16, lane);

    if (wg < 2) {
#define KS(u) ((u) < 8 ? 12 * ((u) >> 2) + (((u) >> 1) & 1) + 4 * ((u) & 1) : (u) < 12 ? (u) : (u) < 16 ? (u) + 8 : (u) < 24 ? 24 + (((u) - 16) >> 1) + 4 * ((u) & 1) : (u) + 8)
        asm volatile("setmaxnreg.inc.sync.aligned.u32 184;");
        uint32_t a[144];
        uint32_t adr1;
        {
            const int g = lane >> 2, t = lane & 3;
            const int t1 = threadIdx.x;
#pragma unroll
            for (int i = 0; i < 2; i++) g_acc[(blockIdx.x * 64 + i * 32 + (t1 >> 3)) * 16 + (t1 & 7)] = make_uint4(0, 0, 0, 0);
            __threadfence();
            asm volatile("barrier.cluster.wait.aligned;" ::: "memory");
            const uint32_t ev = sb + O_STG + (2 * t) * 128 + (((2 * w + (g >> 2)) ^ (2 * t)) << 4) + (g & 3) * 4;
            const uint32_t od = (ev ^ 16) + 128;
            auto gather = [&](int dst, uint32_t off) {
                a[dst] = lds32(ev + off); a[dst + 1] = lds32(od + off); a[dst + 2] = lds32(ev + off + 1024); a[dst + 3] = lds32(od + off + 1024);
            };
            const uint4* xp = reinterpret_cast<const uint4*>(x) + blockIdx.x * 1536 + t1;
            uint4 xv[6];
#pragma unroll
            for (int th = 0; th < 2; th++) {
                mbar_wait(sb + B_W + 8 * th, 0);
                if (th == 1) {
#pragma unroll
                    for (int i = 0; i < 6; i++) xv[i] = __ldg(xp + i * 256);
                }
#pragma unroll
                for (int u = 4 * th; u < 4 * th + 4; u++) {
                    gather(32 + 4 * u, wg * (73728 + 4096) + KS(u) * 2048);
                    gather(4 * u, 73728 - wg * (73728 - 4096) + KS(u) * 2048);
                    gather(64 + 4 * u, wg * 73728 + KS(8 + u) * 2048);
                }
            }
            mbar_wait(sb + B_W + 16, 0);
#pragma unroll
            for (int u = 16; u < 28; u++) gather(32 + 4 * u, wg * 73728 + KS(u) * 2048);
#pragma unroll
            for (int kk = 0; kk < 72; kk++) {
                uint32_t w0 = a[2 * kk], w1 = a[2 * kk + 1];
                a[2 * kk] = __byte_perm(w0, w1, 0x5410);
                a[2 * kk + 1] = __byte_perm(w0, w1, 0x7632);
            }
            if (r == 2) {
                float n0[4], n1[4];
#pragma unroll
                for (int u = 0; u < 36; u++) {
                    const uint32_t x0 = a[4 * u] & 0x7fff7fffu, x1 = a[4 * u + 1] & 0x7fff7fffu, x2 = a[4 * u + 2] & 0x7fff7fffu, x3 = a[4 * u + 3] & 0x7fff7fffu;
                    if (u == 0) mma16816_z(n0, x0, x1, x2, x3, ONES, ONES);
                    else if (u < 8) mma16816(n0, x0, x1, x2, x3, ONES, ONES);
                    else if (u == 8) mma16816_z(n1, x0, x1, x2, x3, ONES, ONES);
                    else mma16816(n1, x0, x1, x2, x3, ONES, ONES);
                }
                const uint32_t mx = __reduce_max_sync(~0u, __float_as_uint(2.f * fmaxf(fmaxf(n0[0], n0[2]), fmaxf(n1[0], n1[2]))));
                sts32_if(lane, sb + O_MISC + 32 + 4 * warp, mx);
            }
            uint32_t xm = 0;
#pragma unroll
            for (int i = 0; i < 6; i++)
                xm = __vmaxu2(xm, __vmaxu2(__vmaxu2(xv[i].x & 0x7fff7fffu, xv[i].y & 0x7fff7fffu), __vmaxu2(xv[i].z & 0x7fff7fffu, xv[i].w & 0x7fff7fffu)));
            sts32_if(lane, sb + O_OF + 16 + 4 * warp, __reduce_max_sync(~0u, max(xm << 16, xm & 0xffff0000u)));
            if (warp == 0) PSTAMP(11);
            bar_arrive(7, 384);
            asm volatile("barrier.cluster.arrive.relaxed.aligned;" ::: "memory");
            bar_sync(1, 256);
            const uint32_t as = sb + O_AS + wg * 8192 + (16 * w + g) * 128 + t * 4;
            sts32(as + (g << 4), a[32]);
            sts32(as + 1024 + (g << 4), a[33]);
            sts32(as + ((1 ^ g) << 4), a[34]);
            sts32(as + 1024 + ((1 ^ g) << 4), a[35]);
            sts128(sb + O_AF + warp * 512 + lane * 16, a[32], a[33], a[34], a[35]);
            fence_async_smem();
            bar_sync(1, 256);
            const uint32_t l = lane * 16;
            const int mi = lane >> 3, isk = (mi >> 1) ? wg : (wg ^ 1);
            adr1 = (r == 2) ? (sb + O_VM + warp * 256 + (l >> 1))
                            : (isk ? (sb + O_KM + w * 512 + wg * 256 + (mi & 1) * 128 + (l & 127))
                                   : (sb + O_QM + w * 512 + (mi & 1) * 256 + wg * 128 + (l & 127)));
            adr1 = __shfl_sync(~0u, adr1, lane);
        }
        auto qkv_loop = [&](auto r2tag) {
        constexpr bool R2 = decltype(r2tag)::value;
        int s3 = 2;
#pragma unroll 1
        for (int s = -1; s < NSEG; s++) {
            const uint32_t l16 = opaque(l16c);
            s3 = (s3 == 2) ? 0 : s3 + 1;
            if (s < 0) mbar_wait(sb + B_X, 0);
            const uint64_t desc0 = (uint64_t)(((sb + O_XT + s3 * XT_BYTES) & 0x3FFFF) >> 4) | (1ull << 16) | (64ull << 32) | (1ull << 62);
            uint32_t km0 = 0, km1 = 0;
            if (s >= 0) {
                { const uint4 v = lds128(sb + O_AF + warp * 512 + l16); a[32] = v.x; a[33] = v.y; a[34] = v.z; a[35] = v.w; }
                float co[4], cw[3][4];
                uint4 b[14];
                float inv;
#define GORD(i) ((i) < 8 ? 2 * ((i) >> 2) + (((i) >> 1) & 1) + 4 * ((i) & 1) : (i))
                auto qkv_mma = [&](int i) {
                    const int gi = GORD(i), u = 8 * gi, n0 = 2 * i, n1 = 2 * i + 1;
                    if (gi < 4) {
                        if (i == 0) mma16816_z(co, a[u], a[u + 1], a[u + 2], a[u + 3], b[0].x, b[0].y);
                        else mma16816(co, a[u], a[u + 1], a[u + 2], a[u + 3], b[i].x, b[i].y);
                    }
                    if (n0 < 3) mma16816_z(cw[n0 % 3], a[32 + u], a[32 + u + 1], a[32 + u + 2], a[32 + u + 3], b[i].x, b[i].y);
                    else mma16816(cw[n0 % 3], a[32 + u], a[32 + u + 1], a[32 + u + 2], a[32 + u + 3], b[i].x, b[i].y);
                    if (n1 < 3) mma16816_z(cw[n1 % 3], a[32 + u + 4], a[32 + u + 5], a[32 + u + 6], a[32 + u + 7], b[i].z, b[i].w);
                    else mma16816(cw[n1 % 3], a[32 + u + 4], a[32 + u + 5], a[32 + u + 6], a[32 + u + 7], b[i].z, b[i].w);
                    if (gi < 4) mma16816(co, a[u + 4], a[u + 5], a[u + 6], a[u + 7], b[i].z, b[i].w);
                };
                const uint32_t mf = sb + O_MF + l16, mfs = mf + wg * 1024;
                const uint32_t qb = (s & 1) * 12288;
                bar_sync(2, 384);
                if (warp == 0) STAMP(s, 0);
                auto qkv_ld = [&](int i) {
                    const int gi = GORD(i);
                    b[i] = gi < 4 ? lds128v(mfs + (gi >> 1) * 3072 + (gi & 1) * 512) : lds128v(mf + (gi < 6 ? gi : gi + 4) * 512);
                };
#pragma unroll
                for (int i = 0; i < 4; i++) qkv_ld(i);
                qkv_mma(0); qkv_mma(1); qkv_mma(2);
                const uint32_t z0 = __float_as_uint(QDEP ? co[0] : cw[1][0]) & (l16 & 15u);
                qkv_mma(3);
                bar_sync(15, 384);
                b[4] = lds128v(mfs + 3072 + z0);
#pragma unroll
                for (int i = 5; i < 9; i++) qkv_ld(i);
#pragma unroll
                for (int i = 4; i < 9; i++) { qkv_mma(i); qkv_ld(5 + i); }
                asm volatile("ld.volatile.shared.f32 %0, [%1];" : "=f"(inv) : "r"(sb + O_MISC) : "memory");
#pragma unroll
                for (int i = 9; i < 14; i++) qkv_mma(i);
#pragma unroll
                for (int i = 0; i < 4; i++) cw[0][i] += cw[1][i] + cw[2][i];
                if (!R2) {
                    const uint32_t o0 = pack_bf16(co[0] * inv, co[1] * inv), o1 = pack_bf16(co[2] * inv, co[3] * inv);
                    const uint32_t w0 = pack_bf16(cw[0][0] * inv, cw[0][1] * inv), w1 = pack_bf16(cw[0][2] * inv, cw[0][3] * inv);
                    stsm4t(adr1 + qb, o0, o1, w0, w1);
                    if (warp == 0) STAMP(s, 1);
                    asm volatile("{\n.reg .pred p;\nsetp.ge.u32 p, %0, 3;\n@p bar.arrive 1, 256;\n@!p bar.sync 1, 256;\n}" :: "r"(warp) : "memory");
                    auto scores = [&](float (&v)[4], const uint4 (&q)[4], const uint4 (&k)[4]) {
                        float s0[4], s1[4], t0[4], t1[4];
                        mma16816_z(s0, q[0].x, q[0].y, q[0].z, q[0].w, k[0].x, k[0].y);
                        mma16816_z(s1, q[0].x, q[0].y, q[0].z, q[0].w, k[0].z, k[0].w);
                        mma16816_z(t0, q[1].x, q[1].y, q[1].z, q[1].w, k[1].x, k[1].y);
                        mma16816_z(t1, q[1].x, q[1].y, q[1].z, q[1].w, k[1].z, k[1].w);
                        mma16816(s0, q[2].x, q[2].y, q[2].z, q[2].w, k[2].x, k[2].y);
                        mma16816(s1, q[2].x, q[2].y, q[2].z, q[2].w, k[2].z, k[2].w);
                        mma16816(t0, q[3].x, q[3].y, q[3].z, q[3].w, k[3].x, k[3].y);
                        mma16816(t1, q[3].x, q[3].y, q[3].z, q[3].w, k[3].z, k[3].w);
                        v[0] = (s0[0] + s0[2]) + (t0[0] + t0[2]); v[1] = (s0[1] + s0[3]) + (t0[1] + t0[3]);
                        v[2] = (s1[0] + s1[2]) + (t1[0] + t1[2]); v[3] = (s1[1] + s1[3]) + (t1[1] + t1[3]);
                    };
                    if (warp < 2) {
                        uint4 q[4], k[4]; float v[4];
#pragma unroll
                        for (int i = 0; i < 4; i++) { q[i] = ldsm4(sb + O_QM + qb + i * 512 + l16); k[i] = ldsm4(sb + O_QKX + 4096 + qb + warp * 2048 + i * 512 + l16); }
                        scores(v, q, k);
                        const uint32_t dst = sb + O_SC + r * 1280 + warp * 512 + l16;
                        st_async128(mapa(dst, 2), __float_as_uint(v[0]), __float_as_uint(v[1]), __float_as_uint(v[2]), __float_as_uint(v[3]), mapa(sb + B_SC, 2));
                        st_async128(mapa(dst, r ^ 1), __float_as_uint(v[0]), __float_as_uint(v[1]), __float_as_uint(v[2]), __float_as_uint(v[3]), mapa(sb + B_SC, r ^ 1));
                        sts128f(dst, v[0], v[1], v[2], v[3]);
                    } else if (warp == 2) {
                        uint4 q[4], k[4]; float v[4];
#pragma unroll
                        for (int i = 0; i < 4; i++) { q[i] = ldsm4(sb + O_QM + qb + i * 512 + l16); k[i] = ldsm4(sb + O_KM + qb + i * 512 + l16); }
                        scores(v, q, k);
                        const uint32_t dst = sb + O_SC + r * 1280 + 1024 + (l16 >> 1);
                        st_async64(mapa(dst, 2), __float_as_uint(v[0] + v[2]), __float_as_uint(v[1] + v[3]), mapa(sb + B_SC, 2));
                        st_async64(mapa(dst, r ^ 1), __float_as_uint(v[0] + v[2]), __float_as_uint(v[1] + v[3]), mapa(sb + B_SC, r ^ 1));
                        sts64(dst, __float_as_uint(v[0] + v[2]), __float_as_uint(v[1] + v[3]));
                        STAMP(s, 2);
                    }
                } else {
                    sts128f(sb + O_XP + warp * 512 + l16, co[0], co[1], co[2], co[3]);
                    bar_sync(8 + w, 64);
                    const float4 o = lds128f(sb + O_XP + (warp ^ 4) * 512 + l16);
                    km0 = pack_bf16((cw[0][0] + o.x) * inv, (cw[0][1] + o.y) * inv);
                    km1 = pack_bf16((cw[0][2] + o.z) * inv, (cw[0][3] + o.w) * inv);
                    if (warp == 0) STAMP(s, 1);
                    st_async64(mapa(adr1, 0), km0, km1, mapa(sb + B_SC, 0));
                    st_async64(mapa(adr1, 1), km0, km1, mapa(sb + B_SC, 1));
                    sts64(adr1, km0, km1);
                    if (warp == 0) STAMP(s, 2);
                }
            }
            if (s >= 0) bar_sync(3, 384);
            auto store_qk = [&]() {
                asm volatile("{\n.reg .pred p;\nelect.sync _|p, 0xffffffff;\n"
                    "@p cp.async.bulk.global.shared::cta.bulk_group [%0], [%1], 10240;\n@p cp.async.bulk.commit_group;\n}"
                    :: "l"(reinterpret_cast<char*>(g_qkv) + (size_t)(s * NH + h) * REC + r * 10240), "r"(sb + O_QKX + (s & 1) * 12288) : "memory");
            };
            auto store_vm = [&]() {
                *reinterpret_cast<uint2*>(reinterpret_cast<char*>(g_qkv) + (size_t)(s * NH + h) * REC + 28672 + warp * 256 + (l16 >> 1)) = make_uint2(km0, km1);
            };
            if (s == NSEG - 1) {
                if (R2) store_vm();
                else if (warp == 3) {
                    fence_async_smem();
                    store_qk();
                    asm volatile("cp.async.bulk.wait_group 0;\nfence.proxy.async.global;" ::: "memory");
                }
            } else {
                const int j = s + 1;
#define XDESC(u) (((u) < 8 ? descs : desc0) + (uint64_t)(((KS(u) >> 2) * 4096 + (KS(u) & 3) * 32) >> 4))
                const uint64_t descs = desc0 + (uint64_t)(wg * 4);
                float d[16];
                wg_fence();
#pragma unroll
                for (int u = 0; u < 8; u++) {
                    if (u == 0) wgmma_n32_rs<0>(d, a[0], a[1], a[2], a[3], XDESC(0));
                    else wgmma_n32_rs<1>(d, a[4 * u], a[4 * u + 1], a[4 * u + 2], a[4 * u + 3], XDESC(u));
                }
                wg_commit();
                wg_wait0();
                if (warp == 0) STAMP(s, 15);
                if (warp == 3) asm volatile("cp.async.bulk.wait_group.read 0;" ::: "memory");
                if (s >= 0) bar_sync(4, 384);
#pragma unroll
                for (int q = 0; q < 2; q++)
                    sts128(sb + O_XP + warp * 1024 + q * 512 + l16, pack_bf16(d[8 * q], d[8 * q + 1]), pack_bf16(d[8 * q + 2], d[8 * q + 3]),
                           pack_bf16(d[8 * q + 4], d[8 * q + 5]), pack_bf16(d[8 * q + 6], d[8 * q + 7]));
                bar_sync(12, 256);
#pragma unroll
                for (int q = 0; q < 2; q++) {
                    const uint4 o = lds128(sb + O_XP + (warp ^ 4) * 1024 + q * 512 + l16);
                    d[8 * q] = __uint_as_float(o.x << 16); d[8 * q + 1] = __uint_as_float(o.x & 0xffff0000u);
                    d[8 * q + 2] = __uint_as_float(o.y << 16); d[8 * q + 3] = __uint_as_float(o.y & 0xffff0000u);
                    d[8 * q + 4] = __uint_as_float(o.z << 16); d[8 * q + 5] = __uint_as_float(o.z & 0xffff0000u);
                    d[8 * q + 6] = __uint_as_float(o.w << 16); d[8 * q + 7] = __uint_as_float(o.w & 0xffff0000u);
                }
                if (s >= 0) {
                    if (R2) store_vm();
                    if (warp == 5 && s + 2 < NSEG) tma_x_tile(sb, &tm_x, r, s + 2, s3 == 2 ? 0 : s3 + 1);
                    if (warp == 3) {
                        asm volatile("cp.async.bulk.wait_group 0;\nfence.proxy.async.global;" ::: "memory");
                        if (FLAGPOS == 0 && s >= 4 && !(s & (s > 4 * NBIG ? 1 : 3))) {
                            __syncwarp();
                            flag_inc_if(l16, &g_flag[F_QKV + ((s > 4 * NBIG ? 2 * s - 4 * NBIG : s) - 4 + (h >> 3)) * 8]);
                        }
                        fence_async_smem();
                    }
                    asm volatile("{\n.reg .pred p;\nsetp.eq.u32 p, %0, 0;\n@p bar.sync 5, 256;\n@!p bar.sync 13, 256;\n}" :: "r"(wg) : "memory");
                }
                const uint64_t da0 = (uint64_t)(((sb + O_AS + wg * 8192) & 0x3FFFF) >> 4) | (1ull << 16) | (64ull << 32) | (1ull << 62);
                wg_fence();
                wgmma_n32_ss<1>(d, da0, XDESC(0));
#pragma unroll
                for (int u = 1; u < 28; u++) wgmma_n32_rs<1>(d, a[32 + 4 * u], a[32 + 4 * u + 1], a[32 + 4 * u + 2], a[32 + 4 * u + 3], XDESC(u));
                wg_commit();
                if (FLAGPOS == 1 && warp == 3 && s >= 4 && !(s & (s > 4 * NBIG ? 1 : 3)))
                    flag_inc_if(l16, &g_flag[F_QKV + ((s > 4 * NBIG ? 2 * s - 4 * NBIG : s) - 4 + (h >> 3)) * 8]);
                wg_wait0();
                if (!R2 && warp == 3 && s >= 0) store_qk();
                if (warp == 4) STAMP(s, 3);
                uint32_t e[8];
#pragma unroll
                for (int i = 0; i < 8; i++) e[i] = pack_bf16(d[2 * i], d[2 * i + 1]);
                if (!R2) {
                    const uint32_t base = sb + O_QKX + (j & 1) * 12288 + wg * 4096 + w * 512 + l16;
                    stsm4t(base, e[0], wg ? e[1] : e[2], wg ? e[2] : e[1], e[3]);
                    stsm4t(base + 2048, e[4], wg ? e[5] : e[6], wg ? e[6] : e[5], e[7]);
                } else {
                    const uint32_t base = sb + O_VX + (j & 1) * 8192 + warp * 1024 + l16;
                    sts128(base, e[0], e[1], e[2], e[3]);
                    sts128(base + 512, e[4], e[5], e[6], e[7]);
                    bar_arrive(14, 288);
                }
                if (warp == 7) STAMP(s, 4);
                if (s < 0) asm volatile("barrier.cluster.wait.aligned;" ::: "memory");
            }
        }
        };
        if (r == 2) qkv_loop(BoolC<true>()); else qkv_loop(BoolC<false>());
        bar_arrive(7, 384);
    } else {
        asm volatile("setmaxnreg.dec.sync.aligned.u32 136;");
        const int c = w;
        uint32_t a[96];
        uint32_t mmax = 0;
        {
            const int g = lane >> 2, t = lane & 3;
            uint32_t tag = 0, m0v[18];
            if (threadIdx.x == 256) tag = atomicAdd(&g_ticket, 1u);
#pragma unroll
            for (int i = 0; i < 9; i++) {
                const uint32_t* p = reinterpret_cast<const uint32_t*>(mem0 + g * DM + 16 * (4 * i + c) + 2 * t);
                m0v[2 * i] = __ldg(p); m0v[2 * i + 1] = __ldg(p + 4);
            }
            asm volatile("barrier.cluster.wait.aligned;" ::: "memory");
            if (c == 0) {
                tma_x_tile(sb, &tm_x, r, 0, 0);
                mbar_expect_if(lane, sb + B_SC, r < 2 ? 3328 : 2560);
                if (r < 2) mbar_expect_if(lane, sb + B_VX, 8192);
                sts32_if(lane, sb + O_MISC, __float_as_uint(1.0f));
                sts32_if(lane, sb + O_MISC + 12, __float_as_uint(SM_SCALE));
            }
            asm volatile("barrier.cluster.arrive.relaxed.aligned;" ::: "memory");
#pragma unroll
            for (int tau = 0; tau < 3; tau++) {
                const uint32_t* v = m0v + 6 * tau;
                sts128(sb + O_MF + tau * 3072 + c * 512 + lane * 16, v[0], v[1], v[2], v[3]);
                sts64(sb + O_MF + tau * 3072 + 2048 + (c >> 1) * 512 + lane * 16 + (c & 1) * 8, v[4], v[5]);
#pragma unroll
                for (int i = 0; i < 6; i++) mmax = __vmaxu2(mmax, v[i] & 0x7fff7fffu);
            }
            mmax = max(mmax << 16, mmax & 0xffff0000u);
            bar_arrive(2, 384); bar_arrive(15, 384);
            tag = (__shfl_sync(~0u, tag, 0) / 96u + 1u) & 0xffffu;
            mbar_wait(sb + B_W + 0, 0);
            const __nv_bfloat16* p = Wo + (size_t)(h * 128 + 4 * t) * DM + 192 * r + 16 * c + 2 * g;
#pragma unroll
            for (int i = 0; i < 3; i++)
#pragma unroll
                for (int eb = 0; eb < 8; eb++)
#pragma unroll
                    for (int j = 0; j < 4; j++) a[(i * 8 + eb) * 4 + j] = ldg_nc32(p + (16 * eb + ((j & 1) * 2 + (j >> 1))) * DM + 64 * i);
#pragma unroll
            for (int kk = 0; kk < 48; kk++) {
                uint32_t w0 = a[2 * kk], w1 = a[2 * kk + 1];
                a[2 * kk] = __byte_perm(w0, w1, 0x5410);
                a[2 * kk + 1] = __byte_perm(w0, w1, 0x7632);
            }
            sts128(sb + O_WP + c * 512 + lane * 16, a[92], a[93], a[94], a[95]);
            float wmax = 0.f;
#pragma unroll
            for (int i = 0; i < 3; i++) {
                float n0[4];
#pragma unroll
                for (int u = 8 * i; u < 8 * i + 8; u++) {
                    const uint32_t x0 = a[4 * u] & 0x7fff7fffu, x1 = a[4 * u + 1] & 0x7fff7fffu, x2 = a[4 * u + 2] & 0x7fff7fffu, x3 = a[4 * u + 3] & 0x7fff7fffu;
                    if (u == 8 * i) mma16816_z(n0, x0, x1, x2, x3, ONES, ONES);
                    else mma16816(n0, x0, x1, x2, x3, ONES, ONES);
                }
                wmax = fmaxf(wmax, fmaxf(n0[0], n0[2]));
            }
            uint32_t wm = __reduce_max_sync(~0u, __float_as_uint(wmax));
            sts32_if(lane, sb + O_OF + 4 * c, wm);
            if (c == 0) PSTAMP(8);
            bar_sync(7, 384);
            asm volatile("barrier.cluster.wait.aligned;" ::: "memory");
            if (c == 1) tma_x_tile(sb, &tm_x, r, 1, 1);
            if (c == 0) {
                const uint4 wq = lds128(sb + O_OF), xq = lds128(sb + O_OF + 16), xr = lds128(sb + O_OF + 32), v0 = lds128(sb + O_MISC + 32), v1 = lds128(sb + O_MISC + 48);
                const uint32_t w1 = max(max(wq.x, wq.y), max(wq.z, wq.w)), x1 = max(max(max(xq.x, xq.y), max(xq.z, xq.w)), max(max(xr.x, xr.y), max(xr.z, xr.w)));
                const uint32_t vv = (r < 2) ? 0u : max(max(max(v0.x, v0.y), max(v0.z, v0.w)), max(max(v1.x, v1.y), max(v1.z, v1.w)));
                const uint32_t lo = (min(w1, 0x7f800000u) + 0xffffu) >> 16 | ((min(vv, 0x7f800000u) + 0xffffu) & 0xffff0000u), hi = (x1 & 0xffff0000u) | tag;
                uint32_t l0, h0, l1, h1, l2, h2;
                asm volatile("{\n.reg .pred p;\n.reg .u32 n, x, y;\n.reg .b64 v;\nsetp.eq.u32 p, %10, 0;\nmov.b64 v, {%8, %9};\n@p st.relaxed.gpu.global.b64 [%7], v;\nmov.u32 n, 0;\n"
                             "G_%=: ld.relaxed.gpu.global.b64 v, [%6];\nmov.b64 {%0, %1}, v;\nld.relaxed.gpu.global.b64 v, [%6+256];\nmov.b64 {%2, %3}, v;\n"
                             "ld.relaxed.gpu.global.b64 v, [%6+512];\nmov.b64 {%4, %5}, v;\n"
                             "xor.b32 x, %1, %9;\nxor.b32 y, %3, %9;\nor.b32 x, x, y;\nxor.b32 y, %5, %9;\nor.b32 x, x, y;\nand.b32 x, x, 0xffff;\n"
                             "setp.eq.u32 p, x, 0;\nvote.sync.all.pred p, p, 0xffffffff;\n@p bra.uni E_%=;\n"
                             "add.u32 n, n, 1;\nsetp.lt.u32 p, n, 4000000;\n@p bra.uni G_%=;\ntrap;\nE_%=:\n}"
                             : "=&r"(l0), "=&r"(h0), "=&r"(l1), "=&r"(h1), "=&r"(l2), "=&r"(h2)
                             : "l"(&g_norm[lane]), "l"(&g_norm[blockIdx.x]), "r"(lo), "r"(hi), "r"(lane) : "memory");
                const uint32_t lm = __vmaxu2(l0, __vmaxu2(l1, l2));
                const float fw = __uint_as_float(__reduce_max_sync(~0u, lm << 16));
                const float fv = __uint_as_float(__reduce_max_sync(~0u, lm & 0xffff0000u));
                const float xmax = __uint_as_float(__reduce_max_sync(~0u, max(h0, max(h1, h2)) & 0xffff0000u));
                const float G = 36.f * fw * fv;
                sts32_if(lane, sb + O_MISC + 4, __float_as_uint(G)); sts32_if(lane, sb + O_MISC + 8, __float_as_uint(G * xmax));
            }
        }
        if (c == 0) PSTAMP(12);
        bar_sync(6, 128);
        int s3n = 1;
        uint32_t roff = __shfl_sync(~0u, (r * 4 + c) * 2048 + (lane >> 4) * 512 + (lane & 2) * 128 + (lane & 1) * 64 + (lane & 12) * 4, lane);
#pragma unroll 1
        for (int s = 0; s < NSEG; s++) {
            const uint32_t l16 = opaque(l16c);
            const uint32_t vxa = sb + O_VX + (s & 1) * 8192 + c * 2048 + l16;
            if (c == 0 && r == 2) {
                bar_sync(14, 288);
                fence_async_smem();
                asm volatile("{\n.reg .pred p;\nelect.sync _|p, 0xffffffff;\n"
                    "@p cp.async.bulk.global.shared::cta.bulk_group [%0], [%1], 8192;\n@p cp.async.bulk.commit_group;\n"
                    "cp.async.bulk.wait_group 0;\nsetp.lt.and.s32 p, %4, 63, p;\n"
                    "@p cp.async.bulk.shared::cluster.global.mbarrier::complete_tx::bytes.multicast::cluster [%1], [%0], 8192, [%2], %3;\n"
                    "fence.proxy.async.global;\n}"
                    :: "l"(reinterpret_cast<char*>(g_qkv) + (size_t)(s * NH + h) * REC + 20480), "r"(sb + O_VX + (s & 1) * 8192),
                       "r"(sb + B_VX + 8 * (s & 1)), "h"((unsigned short)3), "r"(s) : "memory");
            }
            if (s == NSEG - 1) { bar_sync(3, 384); mbar_wait(sb + B_SC, s & 1); break; }
            uint4 vx[4];
            sts32_if(l16, sb + O_MISC + 16 + 4 * c, __reduce_max_sync(~0u, mmax));
            if (c == 0) STAMP(s, 5);
            {
                bar_sync(6, 128);
                const uint4 mm = lds128(sb + O_MISC + 16), cf = lds128(sb + O_MISC);
                const float bound = fmaxf(__uint_as_float(cf.z), __uint_as_float(cf.y) * (__uint_as_float(max(max(mm.x, mm.y), max(mm.z, mm.w))) * __uint_as_float(cf.x)));
                const uint32_t ebits = __reduce_max_sync(~0u, min(max(__float_as_uint(bound) & 0x7f800000u, 21u << 23), 254u << 23));
                mbar_wait(sb + B_X + 8 * s3n, ((s + 1) / 3) & 1);
                s3n = (s3n == 2) ? 0 : s3n + 1;
                bar_sync(3, 384);
                if (r < 2) mbar_wait(sb + B_VX + 8 * (s & 1), (s >> 1) & 1);
                vx[0] = lds128(vxa); vx[2] = lds128(vxa + 1024);
                if (c == 0) STAMP(s, 13);
                mbar_wait(sb + B_SC, s & 1);
                if (c == 0) STAMP(s, 6);
                float p[10];
                load_scores(p, sb + O_SC, 1280, l16);
                float mx = fmaxf(fmaxf(fmaxf(p[0], p[1]), fmaxf(p[2], p[3])), fmaxf(fmaxf(p[4], p[5]), fmaxf(p[6], p[7])));
                mx = quad_max(fmaxf(mx, fmaxf(p[8], p[9])));
                const uint4 vm = lds64x2(sb + O_VM + c * 512 + (l16 >> 1));
                vx[1] = lds128(vxa + 512); vx[3] = lds128(vxa + 1536);
                bar_arrive(4, 384);
                const float sc = __uint_as_float(lds32(sb + O_MISC + 12));
                const float mo = mx * SM_SCALE;
                uint32_t P[5];
#pragma unroll
                for (int n = 0; n < 5; n++) P[n] = pack_bf16(ex2(fmaf(p[2 * n], SM_SCALE, -mo)), ex2(fmaf(p[2 * n + 1], n == 3 ? sc : SM_SCALE, -mo)));
                if (c == 0) STAMP(s, 7);
                float o0[4], o1[4], sm[4];
                mma16816_z(sm, ONES, ONES, ONES, ONES, P[1], P[2]);
                mma16816_z(o0, vx[0].x, vx[0].y, vx[0].z, vx[0].w, P[1], P[2]);
                mma16816_z(o1, vx[2].x, vx[2].y, vx[2].z, vx[2].w, P[1], P[2]);
                mma16816(sm, ONES, ONES, ONES, ONES, P[3], P[4]);
                mma16816(o0, vx[1].x, vx[1].y, vx[1].z, vx[1].w, P[3], P[4]);
                mma16816(o1, vx[3].x, vx[3].y, vx[3].z, vx[3].w, P[3], P[4]);
                mma1688(sm, ONES, ONES, P[0]);
                mma1688(o0, vm.x, vm.y, P[0]);
                mma1688(o1, vm.z, vm.w, P[0]);
                stsm4t(sb + O_OF + c * 512 + l16, pack_bf16(o0[0], o0[1]), pack_bf16(o0[2], o0[3]), pack_bf16(o1[0], o1[1]), pack_bf16(o1[2], o1[3]));
                const float sig = __uint_as_float((268u << 23) - ebits);
                const float r0 = rcp_fast(sm[0]) * sig, r1 = rcp_fast(sm[1]) * sig;
                bar_sync(6, 128);
                uint4 ob[4];
#pragma unroll
                for (int q = 0; q < 4; q++) ob[q] = ldsm4(sb + O_OF + q * 512 + l16);
                { const uint4 v = lds128(sb + O_WP + c * 512 + l16); a[92] = v.x; a[93] = v.y; a[94] = v.z; a[95] = v.w; }
                float m0[3][4], m1[3][4];
#pragma unroll
                for (int q = 0; q < 4; q++) {
#pragma unroll
                    for (int i = 0; i < 3; i++) {
                        const int k0 = (i * 8 + 2 * q) * 4;
                        if (q == 0) mma16816_z(m0[i], a[k0], a[k0 + 1], a[k0 + 2], a[k0 + 3], ob[q].x, ob[q].y);
                        else mma16816(m0[i], a[k0], a[k0 + 1], a[k0 + 2], a[k0 + 3], ob[q].x, ob[q].y);
                    }
#pragma unroll
                    for (int i = 0; i < 3; i++) {
                        const int k1 = (i * 8 + 2 * q + 1) * 4;
                        if (q == 0) mma16816_z(m1[i], a[k1], a[k1 + 1], a[k1 + 2], a[k1 + 3], ob[q].z, ob[q].w);
                        else mma16816(m1[i], a[k1], a[k1 + 1], a[k1 + 2], a[k1 + 3], ob[q].z, ob[q].w);
                    }
                }
                asm volatile("red.relaxed.gpu.global.add.noftz.v4.f16x2 [%0], {%1,%2,%3,%4};" :: "l"(reinterpret_cast<char*>(g_acc) + roff),
                    "r"(pack_f16(NRM(m0[0][0] + m1[0][0], r0), NRM(m0[0][2] + m1[0][2], r0))), "r"(pack_f16(NRM(m0[1][0] + m1[1][0], r0), NRM(m0[1][2] + m1[1][2], r0))),
                    "r"(pack_f16(NRM(m0[2][0] + m1[2][0], r0), NRM(m0[2][2] + m1[2][2], r0))), "r"(0x3c00u) : "memory");
                asm volatile("red.relaxed.gpu.global.add.noftz.v4.f16x2 [%0], {%1,%2,%3,%4};" :: "l"(reinterpret_cast<char*>(g_acc) + roff + 1024),
                    "r"(pack_f16(NRM(m0[0][1] + m1[0][1], r1), NRM(m0[0][3] + m1[0][3], r1))), "r"(pack_f16(NRM(m0[1][1] + m1[1][1], r1), NRM(m0[1][3] + m1[1][3], r1))),
                    "r"(pack_f16(NRM(m0[2][1] + m1[2][1], r1), NRM(m0[2][3] + m1[2][3], r1))), "r"(0x3c00u) : "memory");
                const unsigned t_red = clk();
                bar_arrive(5, 256);
                bar_arrive(13, 256);
                mbar_expect_if(l16 | c, sb + B_SC, r < 2 ? 3328 : 2560);
                mbar_expect_if(l16 | (c ^ 1) | (r >> 1), sb + B_VX + 8 * ((s + 1) & 1), 8192);
                sts32_if(l16 | (c ^ 3), sb + O_MISC, ebits - (14u << 23));
                if (c == 0) STAMPV(s, 8, t_red);
                if (ACC_PF && c == 2 && s + 4 < NSEG - 1)
                    asm volatile("prefetch.global.L2 [%0];" :: "l"(reinterpret_cast<const char*>(g_acc) + ((s + 4) * 96 + blockIdx.x) * 256 + (l16 & 96)) : "memory");
                const char* pbase = reinterpret_cast<const char*>(g_acc) + (s * 24576 + c * 2048) + ((l16 & 64) * 16 + (l16 & 256) + ((l16 & 128) >> 1) + (l16 & 48));
                uint4 v[6];
                {
                    const char* pb = reinterpret_cast<const char*>(__shfl_sync(~0u, (unsigned long long)pbase, l16 >> 4));
                    const unsigned t_go = t_red + (s < D_S0 ? D_EARLY : D_WAIT);
                    asm volatile("{\n.reg .pred p;\n.reg .u64 c;\n.reg .u32 lo;\n"
                                 "S_%=: mov.u64 c, %%clock64;\ncvt.u32.u64 lo, c;\nsub.u32 lo, lo, %0;\nsetp.lt.s32 p, lo, 0;\n@p bra.uni S_%=;\n}" :: "r"(t_go) : "memory");
#pragma unroll
                    for (int i = 0; i < 6; i++) v[i] = ldg_relaxed128(pb + (i >> 1) * 8192 + (i & 1) * 512);
                    pbase = pb;
                }
                int nretry = 0;
                auto convert = [&](int tau) {
                    const uint4 A = v[2 * tau], B = v[2 * tau + 1];
                    sts128(sb + O_MF + tau * 3072 + c * 512 + l16, f16x2_to_bf16x2(A.x), f16x2_to_bf16x2(B.x), f16x2_to_bf16x2(A.y), f16x2_to_bf16x2(B.y));
                    sts64(sb + O_MF + tau * 3072 + 2048 + (c >> 1) * 512 + (c & 1) * 8 + l16, f16x2_to_bf16x2(A.z), f16x2_to_bf16x2(B.z));
                };
                const uint32_t ok0 = __all_sync(~0u, (v[0].w & v[1].w) == 0x5000u);
                convert(0);
                asm volatile("{\n.reg .pred p;\nsetp.ne.u32 p, %0, 0;\n@p bar.arrive 2, 384;\n}" :: "r"(ok0) : "memory");
                mmax = absmax2(absmax2(absmax2(v[0].x, v[0].y), absmax2(v[0].z, v[1].x)), absmax2(v[1].y, v[1].z));
                sched_fence<0>(h);
                uint32_t ok1;
                asm volatile("{\n.reg .pred p, q;\n.reg .b32 x;\nlop3.b32 x, %1, %2, %3, 0x80;\nand.b32 x, x, %4;\n"
                             "setp.eq.u32 p, x, 0x5000;\nvote.sync.all.pred q, p, 0xffffffff;\nselp.u32 %0, 1, 0, q;\n}"
                             : "=r"(ok1) : "r"(v[2].w), "r"(v[3].w), "r"(v[4].w), "r"(v[5].w));
                convert(1); convert(2);
                asm volatile("{\n.reg .pred p;\nsetp.ne.u32 p, %0, 0;\n@p bar.arrive 15, 384;\n}" :: "r"(ok1) : "memory");
                if (!(ok0 & ok1)) {
                    v[0] = v[1] = make_uint4(0u, 0u, 0u, ok0 ? 0x5000u : 0u);
                    asm volatile("{\n.reg .pred p0, p1, p2, p3, p4, p5, q;\n.reg .u32 n, x;\nmov.u32 n, 0;\n"
                         "R_%=: setp.ne.u32 p0, %3, 0x5000;\nsetp.ne.u32 p1, %7, 0x5000;\nsetp.ne.u32 p2, %11, 0x5000;\n"
                         "setp.ne.u32 p3, %15, 0x5000;\nsetp.ne.u32 p4, %19, 0x5000;\nsetp.ne.u32 p5, %23, 0x5000;\n"
                         "@p0 ld.relaxed.gpu.global.v4.u32 {%0,%1,%2,%3}, [%25];\n@p1 ld.relaxed.gpu.global.v4.u32 {%4,%5,%6,%7}, [%25+512];\n"
                         "@p2 ld.relaxed.gpu.global.v4.u32 {%8,%9,%10,%11}, [%25+8192];\n@p3 ld.relaxed.gpu.global.v4.u32 {%12,%13,%14,%15}, [%25+8704];\n"
                         "@p4 ld.relaxed.gpu.global.v4.u32 {%16,%17,%18,%19}, [%25+16384];\n@p5 ld.relaxed.gpu.global.v4.u32 {%20,%21,%22,%23}, [%25+16896];\n"
                         "add.u32 %24, %24, 1;\nand.b32 x, %3, %7;\nand.b32 x, x, %11;\nand.b32 x, x, %15;\nand.b32 x, x, %19;\nand.b32 x, x, %23;\n"
                         "setp.eq.u32 q, x, 0x5000;\nvote.sync.all.pred q, q, 0xffffffff;\n@q bra.uni K_%=;\n"
                         "add.u32 n, n, 1;\nsetp.lt.u32 q, n, 2000000;\n@q bra.uni R_%=;\ntrap;\nK_%=:\n}"
                         : "+r"(v[0].x), "+r"(v[0].y), "+r"(v[0].z), "+r"(v[0].w), "+r"(v[1].x), "+r"(v[1].y), "+r"(v[1].z), "+r"(v[1].w),
                           "+r"(v[2].x), "+r"(v[2].y), "+r"(v[2].z), "+r"(v[2].w), "+r"(v[3].x), "+r"(v[3].y), "+r"(v[3].z), "+r"(v[3].w),
                           "+r"(v[4].x), "+r"(v[4].y), "+r"(v[4].z), "+r"(v[4].w), "+r"(v[5].x), "+r"(v[5].y), "+r"(v[5].z), "+r"(v[5].w), "+r"(nretry)
                         : "l"(pbase) : "memory");
                    if (!ok0) {
                        convert(0); bar_arrive(2, 384);
                        mmax = absmax2(absmax2(absmax2(v[0].x, v[0].y), absmax2(v[0].z, v[1].x)), absmax2(v[1].y, v[1].z));
                    }
                    if (!ok1) { convert(1); convert(2); bar_arrive(15, 384); }
                }
                if (c == 0) STAMP(s, 12);
                if (c == 0) STAMPV(s, 14, nretry);
                mmax = absmax2(mmax, absmax2(absmax2(absmax2(v[2].x, v[2].y), absmax2(v[2].z, v[3].x)), absmax2(absmax2(v[3].y, v[3].z), absmax2(v[4].x, v[4].y))));
                mmax = absmax2(mmax, absmax2(absmax2(v[4].z, v[5].x), absmax2(v[5].y, v[5].z))) & 0x7fff7fffu;
                { const float2 mf = __half22float2(*reinterpret_cast<__half2*>(&mmax)); mmax = max(__float_as_uint(mf.x), __float_as_uint(mf.y)); }
            }
            roff += 24576;
        }
        {
            bar_sync(7, 384);
            if (c == 0) flag_inc_if(l16c, &g_flag[F_QKV + (4 * (NBLK - 1) + (h >> 3)) * 8]);
        }
    }
    if (warp == 8) PSTAMP(13);
    cluster_sync();
}

constexpr int NST = 10;
constexpr int G_RING = 0, G_EX = NST * 16384, G_OUT = G_EX + 32768, G_CARRY = G_OUT + 32768, G_OPS = G_CARRY + 512, G_BAR = G_OPS + 256, BG_SMEM = G_BAR + 256;
constexpr int GB_FULL = G_BAR, GB_EMPTY = G_BAR + 8 * NST, GB_W = G_BAR + 16 * NST;
static_assert(BG_SMEM <= 232448, "smem");

template <int ACC>
__device__ __forceinline__ void wgmma_n128_rs(float (&d)[64], uint32_t a0, uint32_t a1, uint32_t a2, uint32_t a3, uint64_t desc) {
    asm volatile("wgmma.mma_async.sync.aligned.m64n128k16.f32.bf16.bf16 "
        "{%0,%1,%2,%3,%4,%5,%6,%7,%8,%9,%10,%11,%12,%13,%14,%15,%16,%17,%18,%19,%20,%21,%22,%23,%24,%25,%26,%27,%28,%29,%30,%31,"
        "%32,%33,%34,%35,%36,%37,%38,%39,%40,%41,%42,%43,%44,%45,%46,%47,%48,%49,%50,%51,%52,%53,%54,%55,%56,%57,%58,%59,%60,%61,%62,%63}, "
        "{%64,%65,%66,%67}, %68, %69, 1, 1, 0;"
        : "+f"(d[0]), "+f"(d[1]), "+f"(d[2]), "+f"(d[3]), "+f"(d[4]), "+f"(d[5]), "+f"(d[6]), "+f"(d[7]),
          "+f"(d[8]), "+f"(d[9]), "+f"(d[10]), "+f"(d[11]), "+f"(d[12]), "+f"(d[13]), "+f"(d[14]), "+f"(d[15]),
          "+f"(d[16]), "+f"(d[17]), "+f"(d[18]), "+f"(d[19]), "+f"(d[20]), "+f"(d[21]), "+f"(d[22]), "+f"(d[23]),
          "+f"(d[24]), "+f"(d[25]), "+f"(d[26]), "+f"(d[27]), "+f"(d[28]), "+f"(d[29]), "+f"(d[30]), "+f"(d[31]),
          "+f"(d[32]), "+f"(d[33]), "+f"(d[34]), "+f"(d[35]), "+f"(d[36]), "+f"(d[37]), "+f"(d[38]), "+f"(d[39]),
          "+f"(d[40]), "+f"(d[41]), "+f"(d[42]), "+f"(d[43]), "+f"(d[44]), "+f"(d[45]), "+f"(d[46]), "+f"(d[47]),
          "+f"(d[48]), "+f"(d[49]), "+f"(d[50]), "+f"(d[51]), "+f"(d[52]), "+f"(d[53]), "+f"(d[54]), "+f"(d[55]),
          "+f"(d[56]), "+f"(d[57]), "+f"(d[58]), "+f"(d[59]), "+f"(d[60]), "+f"(d[61]), "+f"(d[62]), "+f"(d[63])
        : "r"(a0), "r"(a1), "r"(a2), "r"(a3), "l"(desc), "n"(ACC));
}
template <int ACC>
__device__ __forceinline__ void wgmma_n64_rs(float (&d)[64], uint32_t a0, uint32_t a1, uint32_t a2, uint32_t a3, uint64_t desc) {
    asm volatile("wgmma.mma_async.sync.aligned.m64n64k16.f32.bf16.bf16 "
        "{%0,%1,%2,%3,%4,%5,%6,%7,%8,%9,%10,%11,%12,%13,%14,%15,%16,%17,%18,%19,%20,%21,%22,%23,%24,%25,%26,%27,%28,%29,%30,%31}, "
        "{%32,%33,%34,%35}, %36, %37, 1, 1, 0;"
        : "+f"(d[0]), "+f"(d[1]), "+f"(d[2]), "+f"(d[3]), "+f"(d[4]), "+f"(d[5]), "+f"(d[6]), "+f"(d[7]),
          "+f"(d[8]), "+f"(d[9]), "+f"(d[10]), "+f"(d[11]), "+f"(d[12]), "+f"(d[13]), "+f"(d[14]), "+f"(d[15]),
          "+f"(d[16]), "+f"(d[17]), "+f"(d[18]), "+f"(d[19]), "+f"(d[20]), "+f"(d[21]), "+f"(d[22]), "+f"(d[23]),
          "+f"(d[24]), "+f"(d[25]), "+f"(d[26]), "+f"(d[27]), "+f"(d[28]), "+f"(d[29]), "+f"(d[30]), "+f"(d[31])
        : "r"(a0), "r"(a1), "r"(a2), "r"(a3), "l"(desc), "n"(ACC));
}
__device__ __forceinline__ void wait_flag(const unsigned* p, unsigned target) {
    asm volatile("{\n.reg .pred p;\n.reg .u32 n, v;\nmov.u32 n, 0;\n"
                 "W_%=: ld.acquire.gpu.global.u32 v, [%0];\nsub.u32 v, v, %1;\nsetp.ge.s32 p, v, 0;\n@p bra.uni D_%=;\nnanosleep.u32 " NSLEEP ";\n"
                 "add.u32 n, n, 1;\nsetp.lt.u32 p, n, 4000000;\n@p bra.uni W_%=;\ntrap;\nD_%=:\n}" :: "l"(p), "r"(target) : "memory");
}
template <int NS, int NT>
__device__ __forceinline__ void bg_mainloop(float (&d)[64], const uint32_t (&a)[144], uint32_t sb, int it, int lane) {
    int slot = it % NST, ph = (it / NST) & 1, prev = 0;
#pragma unroll
    for (int i = 0; i < NS; i++) {
        mbar_wait(sb + GB_FULL + 8 * slot, ph);
        const uint64_t desc = (uint64_t)(((sb + G_RING + slot * 16384) & 0x3FFFF) >> 4) | (1ull << 16) | (64ull << 32) | (1ull << 62);
        wg_fence();
#pragma unroll
        for (int k = 0; k < 512 / NT; k++) {
            const int u = (2048 / NT) * i + 4 * k;
            if (NT == 128) {
                if (i == 0 && k == 0) wgmma_n128_rs<0>(d, a[u], a[u + 1], a[u + 2], a[u + 3], desc);
                else wgmma_n128_rs<1>(d, a[u], a[u + 1], a[u + 2], a[u + 3], desc + 2 * k);
            } else {
                if (i == 0 && k == 0) wgmma_n64_rs<0>(d, a[u], a[u + 1], a[u + 2], a[u + 3], desc);
                else wgmma_n64_rs<1>(d, a[u], a[u + 1], a[u + 2], a[u + 3], desc + 2 * (k & 3) + (k >> 2) * 512);
            }
        }
        wg_commit();
        if (i > 0) {
            asm volatile("wgmma.wait_group.sync.aligned 1;" ::: "memory");
            mbar_arrive_if(lane, sb + GB_EMPTY + 8 * prev);
        }
        prev = slot;
        slot += 2;
        if (slot >= NST) { slot -= NST; ph ^= 1; }
    }
    wg_wait0();
    mbar_arrive_if(lane, sb + GB_EMPTY + 8 * prev);
}
template <bool SKIP, int NT>
__device__ __forceinline__ void bg_epilogue(float (&d)[64], uint32_t sb, int wg, int w, int lane, const CUtensorMap* tm_out, int col0, int tok0,
                                            const __nv_bfloat16* xa, const __nv_bfloat16* Dk) {
    constexpr int H = NT / 4;
    const int g = lane >> 2, t = lane & 3;
    const uint32_t ex = sb + G_EX + w * 4096 + lane * 16;
    float k[H];
    if (wg == 0) {
#pragma unroll
        for (int q = 0; q < H / 4; q++) sts128f(ex + q * 512, d[H + 4 * q], d[H + 4 * q + 1], d[H + 4 * q + 2], d[H + 4 * q + 3]);
#pragma unroll
        for (int i = 0; i < H; i++) k[i] = d[i];
    } else {
#pragma unroll
        for (int q = 0; q < H / 4; q++) sts128f(ex + 16384 + q * 512, d[4 * q], d[4 * q + 1], d[4 * q + 2], d[4 * q + 3]);
#pragma unroll
        for (int i = 0; i < H; i++) k[i] = d[H + i];
    }
    uint32_t xv[16], dv = 0;
    if (SKIP) {
        const __nv_bfloat16* xp = xa + (size_t)(tok0 + 64 * wg + 2 * t) * DM + col0 + 16 * w + 2 * g;
#pragma unroll
        for (int i = 0; i < 16; i++) xv[i] = ldg_nc32(xp + (8 * (i >> 1) + (i & 1)) * DM);
        dv = ldg_nc32(Dk + col0 + 16 * w + 2 * g);
    }
    if (SKIP && w == 0) asm volatile("cp.async.bulk.wait_group.read 0;" ::: "memory");
    bar_sync(1, 256);
#pragma unroll
    for (int q = 0; q < H / 4; q++) {
        const float4 o = lds128f(ex + (wg ^ 1) * 16384 + q * 512);
        k[4 * q] += o.x; k[4 * q + 1] += o.y; k[4 * q + 2] += o.z; k[4 * q + 3] += o.w;
    }
    if (SKIP) bar_sync(1, 256); else bar_sync(13, 288);
    const uint32_t ob = sb + G_OUT + wg * (NT == 128 ? 16384 : 4096) + (w >> 1) * 8192 + (g & 1) * 8;
    const uint32_t ch = (w & 1) * 4 + (g >> 1);
#pragma unroll
    for (int i = 0; i < H / 2; i++) {
        float v0 = k[4 * (i >> 1) + (i & 1)], v1 = k[4 * (i >> 1) + 2 + (i & 1)];
        if (SKIP) {
            const uint32_t p = pack_bf16(__uint_as_float(xv[i] << 16) * __uint_as_float(dv << 16), __uint_as_float(xv[i] & 0xffff0000u) * __uint_as_float(dv & 0xffff0000u));
            v0 += __uint_as_float(p << 16); v1 += __uint_as_float(p & 0xffff0000u);
        }
        const uint32_t n7 = 2 * t + (i & 1);
        sts64(ob + (8 * (i >> 1) + n7) * 128 + ((ch ^ n7) << 4), __float_as_uint(v0), __float_as_uint(v1));
    }
    fence_async_smem();
    if (SKIP) {
        bar_sync(4 + wg, 128);
        if (w == 0)
            asm volatile("{\n.reg .pred p;\nelect.sync _|p, 0xffffffff;\n"
                "@p cp.async.bulk.tensor.2d.global.shared::cta.bulk_group [%0, {%2, %4}], [%1];\n"
                "@p cp.async.bulk.tensor.2d.global.shared::cta.bulk_group [%0, {%3, %4}], [%1+8192];\n@p cp.async.bulk.commit_group;\n}"
                :: "l"(tm_out), "r"(sb + G_OUT + wg * 16384), "r"(col0), "r"(col0 + 32), "r"(tok0 + 64 * wg) : "memory");
    } else {
        bar_arrive(12, 288);
    }
}
__device__ __forceinline__ void s5_channel(int p, const __nv_bfloat16* Lre, const __nv_bfloat16* Lim, const __nv_bfloat16* logdt, float2& lam, float2& coef) {
    const float dt = __bfloat162float(__float2bfloat16(expf(__bfloat162float(logdt[p]))));
    const float lr = __bfloat162float(Lre[p]), li = __bfloat162float(Lim[p]);
    const float e = expf(dt * lr);
    float sn, cs;
    sincosf(dt * li, &sn, &cs);
    lam = make_float2(e * cs, e * sn);
    const float den = lr * lr + li * li;
    coef = make_float2(((lam.x - 1.f) * lr + lam.y * li) / den, (lam.y * lr - (lam.x - 1.f) * li) / den);
}
__device__ __forceinline__ float2 cfma(float2 a, float2 b, float2 c) {
    return make_float2(fmaf(a.x, b.x, fmaf(-a.y, b.y, c.x)), fmaf(a.x, b.y, fmaf(a.y, b.x, c.y)));
}
__device__ __forceinline__ uint4 ldg128(const void* p) { uint4 v; asm volatile("ld.global.v4.u32 {%0,%1,%2,%3}, [%4];" : "=r"(v.x), "=r"(v.y), "=r"(v.z), "=r"(v.w) : "l"(p) : "memory"); return v; }
__device__ __forceinline__ uint2 ldg64(const void* p) { uint2 v; asm volatile("ld.global.v2.u32 {%0,%1}, [%2];" : "=r"(v.x), "=r"(v.y) : "l"(p) : "memory"); return v; }

template <int MT>
__device__ __forceinline__ void bg_attention(uint32_t st0, uint32_t st1, int lane) {
    constexpr int NK = MT ? 5 : 3;
    const int g = lane >> 2, t = lane & 3;
    float sc[NK][4], sm2[4];
#pragma unroll
    for (int i = 0; i < 8; i++) {
        const uint32_t st = (i >> 2 ? st1 : st0) + (i & 3) * 512 + lane * 16;
        const uint4 q = ldsm4(st + MT * 2048), km = ldsm4(st + 8192), k0 = ldsm4(st + 4096);
        if (i == 0) {
            mma16816_z(sc[0], q.x, q.y, q.z, q.w, km.x, km.y); mma16816_z(sm2, q.x, q.y, q.z, q.w, km.z, km.w);
            mma16816_z(sc[1], q.x, q.y, q.z, q.w, k0.x, k0.y); mma16816_z(sc[2], q.x, q.y, q.z, q.w, k0.z, k0.w);
        } else {
            mma16816(sc[0], q.x, q.y, q.z, q.w, km.x, km.y); mma16816(sm2, q.x, q.y, q.z, q.w, km.z, km.w);
            mma16816(sc[1], q.x, q.y, q.z, q.w, k0.x, k0.y); mma16816(sc[2], q.x, q.y, q.z, q.w, k0.z, k0.w);
        }
        if (MT) {
            const uint4 k1 = ldsm4(st + 6144);
            if (i == 0) { mma16816_z(sc[NK - 2], q.x, q.y, q.z, q.w, k1.x, k1.y); mma16816_z(sc[NK - 1], q.x, q.y, q.z, q.w, k1.z, k1.w); }
            else { mma16816(sc[NK - 2], q.x, q.y, q.z, q.w, k1.x, k1.y); mma16816(sc[NK - 1], q.x, q.y, q.z, q.w, k1.z, k1.w); }
        }
    }
#pragma unroll
    for (int i = 0; i < 4; i++) sc[0][i] += sm2[i];
    if (2 * t > g) { sc[NK - 2][0] = -INFINITY; sc[NK - 1][2] = -INFINITY; }
    if (2 * t + 1 > g) { sc[NK - 2][1] = -INFINITY; sc[NK - 1][3] = -INFINITY; }
    sc[NK - 1][0] = sc[NK - 1][1] = -INFINITY;
    float ma = fmaxf(sc[0][0], sc[0][1]), mb = fmaxf(sc[0][2], sc[0][3]);
#pragma unroll
    for (int n = 1; n < NK; n++) { ma = fmaxf(ma, fmaxf(sc[n][0], sc[n][1])); mb = fmaxf(mb, fmaxf(sc[n][2], sc[n][3])); }
    ma = quad_max(ma) * SM_SCALE; mb = quad_max(mb) * SM_SCALE;
    uint32_t Pa[NK], Pb[NK];
#pragma unroll
    for (int n = 0; n < NK; n++) {
        Pa[n] = n == NK - 1 ? 0u : pack_bf16(ex2(fmaf(sc[n][0], SM_SCALE, -ma)), ex2(fmaf(sc[n][1], SM_SCALE, -ma)));
        Pb[n] = pack_bf16(ex2(fmaf(sc[n][2], SM_SCALE, -mb)), ex2(fmaf(sc[n][3], SM_SCALE, -mb)));
    }
    float sa[4], sbb[4];
    mma1688_z(sa, ONES, ONES, Pa[0]); mma1688_z(sbb, ONES, ONES, Pb[0]);
    mma16816(sa, ONES, ONES, ONES, ONES, Pa[1], Pa[2]); mma16816(sbb, ONES, ONES, ONES, ONES, Pb[1], Pb[2]);
    if (MT) { mma16816(sa, ONES, ONES, ONES, ONES, Pa[NK - 2], Pa[NK - 1]); mma16816(sbb, ONES, ONES, ONES, ONES, Pb[NK - 2], Pb[NK - 1]); }
    const float ra0 = rcp_fast(sa[0]), ra1 = rcp_fast(sa[1]), rb0 = rcp_fast(sbb[0]), rb1 = rcp_fast(sbb[1]);
    const uint32_t row = lane & 7;
    const uint32_t so = MT * 2048 + (lane >> 4) * 1024 + row * 128;
#pragma unroll
    for (int eh = 0; eh < 2; eh++) {
        const uint32_t st = eh ? st1 : st0;
        float2 vm[4]; uint4 v0[4], v1[4];
#pragma unroll
        for (int e4 = 0; e4 < 4; e4++) {
            vm[e4] = lds64f(st + 14336 + e4 * 256 + lane * 8);
            v0[e4] = lds128(st + 10240 + e4 * 1024 + lane * 16);
            if (MT) v1[e4] = lds128(st + 10240 + e4 * 1024 + 512 + lane * 16);
        }
        float oa[4][4], ob[4][4];
#pragma unroll
        for (int e4 = 0; e4 < 4; e4++) {
            mma1688_z(oa[e4], __float_as_uint(vm[e4].x), __float_as_uint(vm[e4].y), Pa[0]);
            mma1688_z(ob[e4], __float_as_uint(vm[e4].x), __float_as_uint(vm[e4].y), Pb[0]);
        }
#pragma unroll
        for (int e4 = 0; e4 < 4; e4++) {
            mma16816(oa[e4], v0[e4].x, v0[e4].y, v0[e4].z, v0[e4].w, Pa[1], Pa[2]);
            mma16816(ob[e4], v0[e4].x, v0[e4].y, v0[e4].z, v0[e4].w, Pb[1], Pb[2]);
        }
        if (MT) {
#pragma unroll
            for (int e4 = 0; e4 < 4; e4++) {
                mma16816(oa[e4], v1[e4].x, v1[e4].y, v1[e4].z, v1[e4].w, Pa[NK - 2], Pa[NK - 1]);
                mma16816(ob[e4], v1[e4].x, v1[e4].y, v1[e4].z, v1[e4].w, Pb[NK - 2], Pb[NK - 1]);
            }
        }
#pragma unroll
        for (int e4 = 0; e4 < 4; e4++)
            stsm4t(st + so + (((2 * e4 + ((lane >> 3) & 1)) ^ row) << 4), pack_bf16(oa[e4][0] * ra0, oa[e4][1] * ra1), pack_bf16(oa[e4][2] * ra0, oa[e4][3] * ra1),
                   pack_bf16(ob[e4][0] * rb0, ob[e4][1] * rb1), pack_bf16(ob[e4][2] * rb0, ob[e4][3] * rb1));
    }
}
__device__ __forceinline__ bool wait_either(const unsigned* pa, unsigned ta, bool allow_a, const unsigned* pg, unsigned tg, bool allow_g) {
    uint32_t res;
    asm volatile("{\n.reg .pred p, qa, qg;\n.reg .u32 n, v, u;\nmov.u32 n, 0;\nsetp.ne.u32 qa, %5, 0;\nsetp.ne.u32 qg, %6, 0;\n"
                 "W_%=: mov.u32 %0, 1;\n@!qa bra.uni G_%=;\nld.acquire.gpu.global.u32 v, [%1];\nsub.u32 v, v, %2;\nsetp.ge.s32 p, v, 0;\n@p bra.uni D_%=;\n"
                 "G_%=: mov.u32 %0, 0;\n@!qg bra.uni S_%=;\nld.acquire.gpu.global.u32 u, [%3];\nsub.u32 u, u, %4;\nsetp.ge.s32 p, u, 0;\n@p bra.uni D_%=;\nS_%=: "
                 "nanosleep.u32 " NSLEEP ";\nadd.u32 n, n, 1;\nsetp.lt.u32 p, n, 4000000;\n@p bra.uni W_%=;\ntrap;\n"
                 "D_%=: fence.proxy.async.global;\n}"
                 : "=r"(res) : "l"(pa), "r"(ta), "l"(pg), "r"(tg), "r"((uint32_t)allow_a), "r"((uint32_t)allow_g) : "memory");
    return res != 0;
}

__global__ void __launch_bounds__(384, 1)
bg_kernel(const __grid_constant__ CUtensorMap tm_xa, const __grid_constant__ CUtensorMap tm_wo, const __grid_constant__ CUtensorMap tm_out,
          const __nv_bfloat16* __restrict__ xa, const __nv_bfloat16* __restrict__ Lre, const __nv_bfloat16* __restrict__ Lim,
          const __nv_bfloat16* __restrict__ Bre, const __nv_bfloat16* __restrict__ Bim, const __nv_bfloat16* __restrict__ Cre,
          const __nv_bfloat16* __restrict__ Cim, const __nv_bfloat16* __restrict__ logdt, const __nv_bfloat16* __restrict__ Dk, float* __restrict__ out) {
    extern __shared__ __align__(1024) uint8_t smem_raw[];
    const uint32_t sb = smem_u32(smem_raw);
    const int lane = threadIdx.x & 31;
    const int warp = __shfl_sync(~0u, threadIdx.x >> 5, 0);
    const int wg = warp >> 2, w = warp & 3, b = blockIdx.x;
    const int nt = b % 9, kq = b / 9;
    BSTAMP(0);
    if (threadIdx.x == 0) {
        if (sb & 1023u) __trap();
        for (int i = 0; i < NST; i++) { mbar_init(sb + GB_FULL + 8 * i, 1); mbar_init(sb + GB_EMPTY + 8 * i, 4); }
        mbar_init(sb + GB_W, 1);
        asm volatile("fence.mbarrier_init.release.cluster;" ::: "memory");
        mbar_expect(sb + GB_W, (b < 18 ? 64 : 128) * 1152);
        sts32(sb + G_BAR + 248, atomicAdd(&g_ticket_bg, 1u) / 36u + 1u);
    }
    __syncthreads();
    if (wg == 2) {
        asm volatile("setmaxnreg.dec.sync.aligned.u32 24;");
        if (w == 0) {
            int slot = 0, ph = 1;
            auto next = [&]() { if (++slot == NST) { slot = 0; ph ^= 1; } };
            bar_sync(6, 288);
            if (b < 18) {
#pragma unroll 1
                for (int i = 0; i < 144; i++) {
                    const int blk = i / 9, kb = i - 9 * blk, it = (blk >> 1) * 18 + (blk & 1) + 2 * kb;
                    slot = it % NST;
                    mbar_wait(sb + GB_EMPTY + 8 * slot, ((it / NST) & 1) ^ 1);
                    asm volatile("{\n.reg .pred p;\nelect.sync _|p, 0xffffffff;\n@p mbarrier.arrive.expect_tx.shared::cta.b64 _, [%2], 16384;\n"
                        "@p cp.async.bulk.tensor.5d.shared::cluster.global.mbarrier::complete_tx::bytes [%0], [%1, {%3, %4, %4, %4, %5}], [%2];\n}"
                        :: "r"(sb + G_RING + slot * 16384), "l"(&tm_xa), "r"(sb + GB_FULL + 8 * slot), "r"(kb * 64), "r"(0), "r"(blk) : "memory");
                }
                slot = 144 % NST; ph = ((144 / NST) & 1) ^ 1;
            }
            const unsigned ep = lds32(sb + G_BAR + 248);
            auto slabs = [&](const char* src, int ns) {
                asm volatile("fence.proxy.async.global;" ::: "memory");
#pragma unroll 1
                for (int i = 0; i < ns; i++) {
                    mbar_wait(sb + GB_EMPTY + 8 * slot, ph);
                    asm volatile("{\n.reg .pred p;\nelect.sync _|p, 0xffffffff;\n@p mbarrier.arrive.expect_tx.shared::cta.b64 _, [%2], 16384;\n"
                        "@p cp.async.bulk.shared::cluster.global.mbarrier::complete_tx::bytes [%0], [%1], 16384, [%2];\n}"
                        :: "r"(sb + G_RING + slot * 16384), "l"(src + (size_t)((i & 1) * (ns >> 1) + (i >> 1)) * (SEQ * 128)), "r"(sb + GB_FULL + 8 * slot) : "memory");
                    next();
                }
            };
            if (b >= 18) {
#pragma unroll 1
                for (int blk = kq - 2; blk < 16; blk += 2) {
                    wait_flag(&g_flag[F_H + blk * 8], 18 * ep);
                    slabs(reinterpret_cast<const char*>(g_h) + blk * 16384, 18);
                }
            }
            bar_sync(6, 288);
#pragma unroll 1
            for (int na = nt < 8 ? 0 : NBLK, ng = 0, k = 0; ng < NBLK; k++) {
                const bool att = wait_either(&g_flag[F_QKV + (min(na, NBLK - 1) * 4 + kq) * 8], 24 * ep, na < NBLK && na <= ng + 1,
                                             &g_flag[F_OX + (ng * 4 + kq) * 8], 8 * ep, ng < na);
                sts32_if(lane, sb + G_OPS + 4 * k, att);
                __syncwarp();
                if (att) {
                    {
#pragma unroll 1
                        for (int i = 0; i < (na < NBIG ? 8 : 4); i++) {
                            const int hf = (i >> 1) & 1;
                            const char* rec = reinterpret_cast<const char*>(g_qkv) + (size_t)((blk_seg0(na) + 2 * (i >> 2) + (i & 1)) * NH + 8 * kq + nt) * REC;
                            mbar_wait(sb + GB_EMPTY + 8 * slot, ph);
                            asm volatile("{\n.reg .pred p;\nelect.sync _|p, 0xffffffff;\n@p mbarrier.arrive.expect_tx.shared::cta.b64 _, [%4], 15360;\n"
                                "@p cp.async.bulk.shared::cluster.global.mbarrier::complete_tx::bytes [%0], [%1], 10240, [%4];\n"
                                "@p cp.async.bulk.shared::cluster.global.mbarrier::complete_tx::bytes [%0+10240], [%2], 4096, [%4];\n"
                                "@p cp.async.bulk.shared::cluster.global.mbarrier::complete_tx::bytes [%0+14336], [%3], 1024, [%4];\n}"
                                :: "r"(sb + G_RING + slot * 16384), "l"(rec + hf * 10240), "l"(rec + 20480 + hf * 4096), "l"(rec + 28672 + hf * 1024),
                                   "r"(sb + GB_FULL + 8 * slot) : "memory");
                            next();
                        }
                    }
                    na++;
                } else {
                    const char* src = reinterpret_cast<const char*>(g_ox) + (size_t)kq * 16 * SEQ * 128 + blk_seg0(ng) * 4096;
                    if (ng < NBIG) slabs(src, 16);
                    else {
#pragma unroll 1
                        for (int i = 0; i < 8; i++) {
                            mbar_wait(sb + GB_EMPTY + 8 * slot, ph);
                            asm volatile("{\n.reg .pred p;\nelect.sync _|p, 0xffffffff;\n@p mbarrier.arrive.expect_tx.shared::cta.b64 _, [%2], 16384;\n"
                                "@p cp.async.bulk.shared::cluster.global.mbarrier::complete_tx::bytes [%0], [%1], 8192, [%2];\n"
                                "@p cp.async.bulk.shared::cluster.global.mbarrier::complete_tx::bytes [%0+8192], [%1+262144], 8192, [%2];\n}"
                                :: "r"(sb + G_RING + slot * 16384), "l"(src + (size_t)((i & 1) * 8 + (i & 6)) * (SEQ * 128)), "r"(sb + GB_FULL + 8 * slot) : "memory");
                            next();
                        }
                    }
                    ng++;
                }
            }
        } else if (w == 1) {
            if (b < 18) {
#pragma unroll 1
                for (int blk = 0; blk < 16; blk++) {
                    bar_sync(8 + (blk & 1), 160);
                    asm volatile("{\n.reg .pred p;\nelect.sync _|p, 0xffffffff;\n@p cp.async.bulk.global.shared::cta.bulk_group [%0], [%1], 16384;\n"
                        "@p cp.async.bulk.commit_group;\ncp.async.bulk.wait_group 0;\nfence.proxy.async.global;\n}"
                        :: "l"(reinterpret_cast<char*>(g_h) + ((size_t)b * SEQ + blk * 128) * 128), "r"(sb + G_OUT + (blk & 1) * 16384) : "memory");
                    bar_arrive(10 + (blk & 1), 160);
                    flag_inc_if(lane, &g_flag[F_H + blk * 8]);
                }
            }
            if (nt < 8) {
#pragma unroll 1
                for (int na = 0; na < NBLK; na++) {
                    {
                        const int ns = na < NBIG ? 8 : 4;
                        bar_sync(7, 288);
                        const int it = lds32(sb + G_OPS + 252);
                        if (lane < ns) {
                            asm volatile("cp.async.bulk.global.shared::cta.bulk_group [%0], [%1], 4096;\ncp.async.bulk.commit_group;\ncp.async.bulk.wait_group.read 0;\n"
                                "mbarrier.arrive.shared::cta.b64 _, [%2], 4;\ncp.async.bulk.wait_group 0;\nfence.proxy.async.global;"
                                :: "l"(reinterpret_cast<char*>(g_ox) + ((size_t)((8 * kq + nt) * 2 + ((lane >> 1) & 1)) * SEQ + (blk_seg0(na) + 2 * (lane >> 2) + (lane & 1)) * 32) * 128),
                                   "r"(sb + G_RING + ((it + lane) % NST) * 16384), "r"(sb + GB_EMPTY + 8 * ((it + lane) % NST)) : "memory");
                        }
                        __syncwarp();
                        bar_arrive(14, 288);
                        flag_inc_if(lane, &g_flag[F_OX + (na * 4 + kq) * 8]);
                    }
                }
            }
        } else if (w == 2) {
            const unsigned ep = lds32(sb + G_BAR + 248);
#pragma unroll 1
            for (int blk = 0; blk < NBLK; blk++) {
                const bool last = blk == NBLK - 1, add = kq || last;
                bar_arrive(13, 288);
                bar_sync(12, 288);
                if (add) { wait_flag(&g_flag[F_OUT + (blk * 9 + nt) * 8], ep); asm volatile("fence.proxy.async.global;" ::: "memory"); }
#pragma unroll 1
                for (int i = 0; i < (blk < NBIG ? 4 : 2); i++) {
                    const uint32_t src = sb + G_OUT + i * 8192;
                    const int c0 = DM + 64 * nt + (i & 1) * 32, c1 = blk_seg0(blk) * 32 + (i >> 1) * 64;
                    if (add) asm volatile("{\n.reg .pred p;\nelect.sync _|p, 0xffffffff;\n@p cp.reduce.async.bulk.tensor.2d.global.shared::cta.add.bulk_group [%0, {%2, %3}], [%1];\n}"
                                 :: "l"(&tm_out), "r"(src), "r"(c0), "r"(c1) : "memory");
                    else asm volatile("{\n.reg .pred p;\nelect.sync _|p, 0xffffffff;\n@p cp.async.bulk.tensor.2d.global.shared::cta.bulk_group [%0, {%2, %3}], [%1];\n}"
                                 :: "l"(&tm_out), "r"(src), "r"(c0), "r"(c1) : "memory");
                    if (add && blk < NBIG - 1) spin_until(clk(), RED_GAP);
                }
                asm volatile("cp.async.bulk.commit_group;\ncp.async.bulk.wait_group 0;\nfence.proxy.async.global;" ::: "memory");
                __syncwarp();
                if (!add) flag_inc_if(lane, &g_flag[F_OUT + (blk * 9 + nt) * 8]);
                if (!kq && blk == NBLK - 4) {
                    float4* z = reinterpret_cast<float4*>(out + (size_t)(SEQ - 64 + (lane >> 4)) * (2 * DM) + DM + 64 * nt) + (lane & 15);
#pragma unroll 1
                    for (int i = 0; i < 32; i++) z[i * (4 * DM / 4)] = make_float4(0.f, 0.f, 0.f, 0.f);
                    __syncwarp();
                    flag_inc_if(lane, &g_flag[F_OUT + ((NBLK - 1) * 9 + nt) * 8]);
                }
            }
        }
    } else {
        asm volatile("setmaxnreg.inc.sync.aligned.u32 240;");
        const int g = lane >> 2, t = lane & 3, tid = threadIdx.x;
        uint32_t a[144];
        float d[64];
        if (b < 18) {
            if (tid < 64)
                asm volatile("cp.async.bulk.shared::cluster.global.mbarrier::complete_tx::bytes [%0], [%1], 1152, [%2];"
                    :: "r"(sb + tid * 1168), "l"((tid < 32 ? Bre : Bim) + (size_t)(32 * b + (tid & 31)) * DM), "r"(sb + GB_W) : "memory");
            float2 lam, coef;
            s5_channel(32 * b + 8 * w + g, Lre, Lim, logdt, lam, coef);
            float2 l32 = lam;
#pragma unroll
            for (int i = 0; i < 5; i++) l32 = make_float2(l32.x * l32.x - l32.y * l32.y, 2.f * l32.x * l32.y);
            __syncwarp();
            mbar_wait(sb + GB_W, 0);
            const uint32_t ap = sb + (((lane >> 3) & 1) * 32 + 8 * w + (lane & 7)) * 1168 + (lane >> 4) * 16;
#pragma unroll
            for (int ks = 0; ks < 36; ks++) { const uint4 v = ldsm4(ap + ks * 32); a[4 * ks] = v.x; a[4 * ks + 1] = v.y; a[4 * ks + 2] = v.z; a[4 * ks + 3] = v.w; }
            bar_sync(1, 256);
            bar_arrive(6, 288);
            BSTAMP(1);
#pragma unroll 1
            for (int blk = wg; blk < 16; blk += 2) {
                bg_mainloop<9, 128>(d, a, sb, (blk >> 1) * 18 + wg, lane);
                float2 e = make_float2(0.f, 0.f);
#pragma unroll
                for (int i = 0; i < 32; i++) e = cfma(lam, e, make_float2(d[4 * (i >> 1) + (i & 1)], d[4 * (i >> 1) + 2 + (i & 1)]));
                float2 cin = make_float2(0.f, 0.f);
                if (blk > 0) { bar_sync(2 + (wg ^ 1), 256); cin = lds64f(sb + G_CARRY + (wg ^ 1) * 256 + (8 * w + g) * 8); }
                float2 mine = cin;
#pragma unroll
                for (int q = 0; q < 4; q++) {
                    const float2 eq = make_float2(__shfl_sync(~0u, e.x, (lane & 28) + q), __shfl_sync(~0u, e.y, (lane & 28) + q));
                    cin = cfma(l32, cin, eq);
                    if (t == q + 1) mine = cin;
                }
                if (blk < 15) {
                    if (t == 0) sts64(sb + G_CARRY + wg * 256 + (8 * w + g) * 8, __float_as_uint(cin.x), __float_as_uint(cin.y));
                    bar_arrive(2 + wg, 256);
                }
                const uint32_t hs = sb + G_OUT + wg * 16384 + t * 4096 + (g & 3) * 4;
                const uint32_t ch = 2 * w + (g >> 2);
                if (blk >= 2) bar_sync(10 + wg, 160);
#pragma unroll
                for (int i = 0; i < 32; i++) {
                    mine = cfma(lam, mine, make_float2(d[4 * (i >> 1) + (i & 1)], d[4 * (i >> 1) + 2 + (i & 1)]));
                    sts32(hs + i * 128 + ((ch ^ (i & 7)) << 4), pack_bf16(mine.x, mine.y));
                }
                fence_async_smem();
                bar_arrive(8 + wg, 160);
            }
            bar_sync(10 + wg, 160);
        } else {
            if (tid < 128)
                asm volatile("cp.async.bulk.shared::cluster.global.mbarrier::complete_tx::bytes [%0], [%1], 1152, [%2];"
                    :: "r"(sb + tid * 1168), "l"((tid < 64 ? Cre : Cim) + (size_t)(64 * nt + (tid & 63)) * DM), "r"(sb + GB_W) : "memory");
            for (int p = tid; p < DM; p += 256) {
                float2 lam, coef;
                s5_channel(p, Lre, Lim, logdt, lam, coef);
                sts64(sb + G_EX + p * 8, __float_as_uint(2.f * coef.x), __float_as_uint(2.f * coef.y));
            }
            bar_sync(1, 256);
            mbar_wait(sb + GB_W, 0);
            const uint32_t cp = sb + (16 * w + 2 * g) * 1168 + (288 * wg + t) * 2;
#pragma unroll
            for (int u = 0; u < 72; u++) {
                const float2 c2 = lds64f(sb + G_EX + (288 * wg + 4 * u + t) * 8);
#pragma unroll
                for (int f = 0; f < 2; f++) {
                    unsigned short r16, i16;
                    asm volatile("ld.shared.u16 %0, [%1];" : "=h"(r16) : "r"(cp + f * 1168 + u * 8) : "memory");
                    asm volatile("ld.shared.u16 %0, [%1];" : "=h"(i16) : "r"(cp + (64 + f) * 1168 + u * 8) : "memory");
                    const float cr = __uint_as_float((uint32_t)r16 << 16), ci = __uint_as_float((uint32_t)i16 << 16);
                    a[2 * u + f] = pack_bf16(cr * c2.x - ci * c2.y, -(cr * c2.y + ci * c2.x));
                }
            }
            bar_sync(1, 256);
            bar_arrive(6, 288);
            BSTAMP(1);
#pragma unroll 1
            for (int j = 0; j < 8; j++) {
                bg_mainloop<9, 128>(d, a, sb, j * 18 + wg, lane);
                bg_epilogue<true, 128>(d, sb, wg, w, lane, &tm_out, 64 * nt, (2 * j + kq - 2) * 128, xa, Dk);
            }
        }
        if (w == 0) asm volatile("cp.async.bulk.wait_group 0;" ::: "memory");
        bar_sync(1, 256);
        BSTAMP(2);
        if (warp == 0)
            asm volatile("{\n.reg .pred p;\nelect.sync _|p, 0xffffffff;\n@p mbarrier.arrive.expect_tx.shared::cta.b64 _, [%2], 131072;\n"
                "@p cp.async.bulk.tensor.2d.shared::cluster.global.mbarrier::complete_tx::bytes [%0], [%1, {%3, %4}], [%2];\n"
                "@p cp.async.bulk.tensor.2d.shared::cluster.global.mbarrier::complete_tx::bytes [%0+32768], [%1, {%3, %5}], [%2];\n"
                "@p cp.async.bulk.tensor.2d.shared::cluster.global.mbarrier::complete_tx::bytes [%0+65536], [%1, {%3, %6}], [%2];\n"
                "@p cp.async.bulk.tensor.2d.shared::cluster.global.mbarrier::complete_tx::bytes [%0+98304], [%1, {%3, %7}], [%2];\n}"
                :: "r"(sb), "l"(&tm_wo), "r"(sb + GB_W), "r"(64 * nt), "r"(1024 * kq), "r"(1024 * kq + 256), "r"(1024 * kq + 512), "r"(1024 * kq + 768) : "memory");
        mbar_wait(sb + GB_W, 1);
        {
            const uint32_t base = sb + wg * 65536 + 4 * t * 128 + (g & 3) * 4, ch = 2 * w + (g >> 2), r7 = (4 * t) & 7;
#pragma unroll
            for (int ks = 0; ks < 32; ks++) {
                const uint32_t w0 = lds32(base + ks * 2048 + ((ch ^ r7) << 4)), w1 = lds32(base + ks * 2048 + 256 + ((ch ^ (r7 + 2)) << 4));
                const uint32_t w2 = lds32(base + ks * 2048 + 128 + ((ch ^ (r7 + 1)) << 4)), w3 = lds32(base + ks * 2048 + 384 + ((ch ^ (r7 + 3)) << 4));
                a[4 * ks] = __byte_perm(w0, w1, 0x5410); a[4 * ks + 1] = __byte_perm(w0, w1, 0x7632);
                a[4 * ks + 2] = __byte_perm(w2, w3, 0x5410); a[4 * ks + 3] = __byte_perm(w2, w3, 0x7632);
            }
        }
        bar_sync(1, 256);
        bar_arrive(6, 288);
        BSTAMP(3);
#pragma unroll 1
        for (int na = 0, ng = 0, it = 144, k = 0; ng < NBLK; k++) {
            mbar_wait(sb + GB_FULL + 8 * ((it + wg) % NST), ((it + wg) / NST) & 1);
            if (__shfl_sync(~0u, lds32(sb + G_OPS + 4 * k), 0)) {
                {
                    if (na < NBIG || (w >> 1) == wg) {
                        const int i0 = it + wg + (na < NBIG ? 4 * (w >> 1) : 0), i1 = i0 + 2;
                        mbar_wait(sb + GB_FULL + 8 * (i0 % NST), (i0 / NST) & 1);
                        mbar_wait(sb + GB_FULL + 8 * (i1 % NST), (i1 / NST) & 1);
                        BSTAMP(8 + na * 4);
                        if ((w ^ wg) & 1) bg_attention<1>(sb + G_RING + (i0 % NST) * 16384, sb + G_RING + (i1 % NST) * 16384, lane);
                        else bg_attention<0>(sb + G_RING + (i0 % NST) * 16384, sb + G_RING + (i1 % NST) * 16384, lane);
                        fence_async_smem();
                    }
                    if (na > 0) bar_sync(14, 288);
                    if (tid == 0) sts32(sb + G_OPS + 252, it);
                    bar_arrive(7, 288);
                    bar_sync(1, 256);
                    BSTAMP(9 + na * 4);
                    it += na < NBIG ? 8 : 4;
                }
                na++;
            } else if (ng < NBIG) {
                bg_mainloop<8, 128>(d, a, sb, it + wg, lane);
                BSTAMP(10 + ng * 4);
                bg_epilogue<false, 128>(d, sb, wg, w, lane, &tm_out, 0, 0, xa, Dk);
                BSTAMP(11 + ng * 4);
                it += 16; ng++;
            } else {
                bg_mainloop<4, 64>(d, a, sb, it + wg, lane);
                BSTAMP(10 + ng * 4);
                bg_epilogue<false, 64>(d, sb, wg, w, lane, &tm_out, 0, 0, xa, Dk);
                BSTAMP(11 + ng * 4);
                it += 8; ng++;
            }
        }
        if (nt < 8) bar_sync(14, 288);
    }
    asm volatile("griddepcontrol.wait;" ::: "memory");
}

typedef CUresult (*EncodeFn)(CUtensorMap*, CUtensorMapDataType, cuuint32_t, void*, const cuuint64_t*, const cuuint64_t*, const cuuint32_t*, const cuuint32_t*,
                             CUtensorMapInterleave, CUtensorMapSwizzle, CUtensorMapL2promotion, CUtensorMapFloatOOBfill);
}

extern "C" void kernel_launch(void* const* d_in, const int* in_sizes, int n_in, void* d_out, int out_size) {
    typedef const __nv_bfloat16* bp;
    bp Ax = (bp)d_in[0], Lre = (bp)d_in[1], Lim = (bp)d_in[2], Bre = (bp)d_in[3], Bim = (bp)d_in[4], Cre = (bp)d_in[5], Cim = (bp)d_in[6],
       logdt = (bp)d_in[7], Dk = (bp)d_in[8], Bx = (bp)d_in[9], mem0 = (bp)d_in[10], Wq = (bp)d_in[11], Wk = (bp)d_in[12], Wv = (bp)d_in[13], Wo = (bp)d_in[14];
    float* out = (float*)d_out;
    static EncodeFn enc = nullptr;
    if (!enc) {
        void* fn = nullptr; cudaDriverEntryPointQueryResult qr;
        cudaGetDriverEntryPoint("cuTensorMapEncodeTiled", &fn, cudaEnableDefault, &qr);
        enc = (EncodeFn)fn;
        cudaFuncSetAttribute(chain_kernel, cudaFuncAttributeMaxDynamicSharedMemorySize, CHAIN_SMEM);
        cudaFuncSetAttribute(bg_kernel, cudaFuncAttributeMaxDynamicSharedMemorySize, BG_SMEM);
    }
    const cuuint32_t es[5] = {1, 1, 1, 1, 1};
    auto map2d = [&](CUtensorMap* tm, CUtensorMapDataType dt, const void* p, cuuint64_t d0, cuuint64_t d1, cuuint64_t stride, cuuint32_t b0, cuuint32_t b1) {
        cuuint64_t gd[2] = {d0, d1}, gs[1] = {stride}; cuuint32_t bd[2] = {b0, b1};
        enc(tm, dt, 2, (void*)p, gd, gs, bd, es, CU_TENSOR_MAP_INTERLEAVE_NONE, CU_TENSOR_MAP_SWIZZLE_128B, CU_TENSOR_MAP_L2_PROMOTION_L2_128B,
            CU_TENSOR_MAP_FLOAT_OOB_FILL_NONE);
    };
    CUtensorMap tm_x, tm_q, tm_k, tm_v, tm_xa, tm_wo, tm_out;
    map2d(&tm_x, CU_TENSOR_MAP_DATA_TYPE_BFLOAT16, Bx, DM, SEQ, DM * 2, 64, 32);
    map2d(&tm_q, CU_TENSOR_MAP_DATA_TYPE_BFLOAT16, Wq, HD, DM, HD * 2, 64, 192);
    map2d(&tm_k, CU_TENSOR_MAP_DATA_TYPE_BFLOAT16, Wk, HD, DM, HD * 2, 64, 192);
    map2d(&tm_v, CU_TENSOR_MAP_DATA_TYPE_BFLOAT16, Wv, HD, DM, HD * 2, 64, 192);
    map2d(&tm_wo, CU_TENSOR_MAP_DATA_TYPE_BFLOAT16, Wo, DM, HD, DM * 2, 64, 256);
    map2d(&tm_out, CU_TENSOR_MAP_DATA_TYPE_FLOAT32, out, 2 * DM, SEQ, 2 * DM * 4, 32, 64);
    {
        cuuint64_t gd[5] = {DM, 2, 4, 16, 16}, gs[4] = {DM * 2, 32 * DM * 2, 2 * DM * 2, 128 * DM * 2}; cuuint32_t bd[5] = {64, 2, 4, 16, 1};
        enc(&tm_xa, CU_TENSOR_MAP_DATA_TYPE_BFLOAT16, 5, (void*)Ax, gd, gs, bd, es, CU_TENSOR_MAP_INTERLEAVE_NONE, CU_TENSOR_MAP_SWIZZLE_128B,
            CU_TENSOR_MAP_L2_PROMOTION_L2_128B, CU_TENSOR_MAP_FLOAT_OOB_FILL_NONE);
    }
    cudaStream_t st = cudaStreamPerThread;
    chain_kernel<<<96, 384, CHAIN_SMEM, st>>>(tm_x, tm_q, tm_k, tm_v, Bx, mem0, Wo);
    cudaLaunchConfig_t cfg = {};
    cfg.gridDim = dim3(36); cfg.blockDim = dim3(384); cfg.dynamicSmemBytes = BG_SMEM; cfg.stream = st;
    cudaLaunchAttribute at[1];
    at[0].id = cudaLaunchAttributeProgrammaticStreamSerialization; at[0].val.programmaticStreamSerializationAllowed = 1;
    cfg.attrs = at; cfg.numAttrs = 1;
    cudaLaunchKernelEx(&cfg, bg_kernel, tm_xa, tm_wo, tm_out, Ax, Lre, Lim, Bre, Bim, Cre, Cim, logdt, Dk, out);
}
```

```cpp
#include <cuda_runtime.h>
#include <cuda.h>
#include <cuda_bf16.h>
#include <cuda_fp16.h>
#include <stdint.h>

#define D_WAIT 740

#define RED_GAP 720
#define ACC_PF 1
#define QDEP 0
#define NSLEEP "40"
#define D_S0 34
#define D_EARLY 820
#define FLAGPOS 0
#define NORM_LATE 0
#define NRM(x, r) (NORM_LATE ? (x) * (r) : (x))
#define PRIO 0
#define NBIG 14

namespace {

constexpr int DM = 576, NH = 32, SEQ = 2048, NSEG = 64, HD = 4096;

__device__ uint4 g_acc_raw[64 * 96 * 16 + 131072];
__device__ uint4 g_ox[NH * 2 * SEQ * 8];
constexpr int REC = 30720;
__device__ uint4 g_qkv[NSEG * NH * (REC / 16)];
__device__ uint4 g_h[18 * SEQ * 8];
constexpr int NFLAG = 6144, F_QKV = 0, F_OX = 1024, F_H = 2048, F_OUT = 3072;
constexpr int NBLK = NBIG + (NSEG - 4 * NBIG) / 2;
__host__ __device__ constexpr int blk_seg0(int b) { return b < NBIG ? 4 * b : 2 * b + 2 * NBIG; }
__device__ unsigned g_flag[NFLAG];
__device__ unsigned g_ticket, g_ticket_bg;
__device__ unsigned long long g_norm[96];
#define BSTAMP(i) do {} while (0)

__device__ __forceinline__ uint32_t smem_u32(const void* p) { return (uint32_t)__cvta_generic_to_shared(p); }
__device__ __forceinline__ uint32_t mapa(uint32_t a, uint32_t r) { uint32_t o; asm("mapa.shared::cluster.u32 %0, %1, %2;" : "=r"(o) : "r"(a), "r"(r)); return o; }
__device__ __forceinline__ uint32_t mapa_v(uint32_t a, uint32_t r) { uint32_t o; asm volatile("mapa.shared::cluster.u32 %0, %1, %2;" : "=r"(o) : "r"(a), "r"(r)); return o; }
__device__ __forceinline__ unsigned clk() { unsigned long long c; asm volatile("mov.u64 %0, %%clock64;" : "=l"(c) :: "memory"); return (unsigned)c; }
__device__ __forceinline__ void mbar_init(uint32_t bar, uint32_t cnt) { asm volatile("mbarrier.init.shared::cta.b64 [%0], %1;" :: "r"(bar), "r"(cnt) : "memory"); }
__device__ __forceinline__ void mbar_expect(uint32_t bar, uint32_t bytes) { asm volatile("mbarrier.arrive.expect_tx.shared::cta.b64 _, [%0], %1;" :: "r"(bar), "r"(bytes) : "memory"); }
__device__ __forceinline__ void mbar_wait(uint32_t bar, uint32_t parity) {
    asm volatile("{\n.reg .pred p;\n.reg .u32 n;\nmov.u32 n, 0;\n"
                 "W_%=: mbarrier.try_wait.parity.shared::cta.b64 p, [%0], %1;\n@p bra.uni D_%=;\n"
                 "add.u32 n, n, 1;\nsetp.lt.u32 p, n, 4000000;\n@p bra.uni W_%=;\ntrap;\nD_%=:\n}" :: "r"(bar), "r"(parity) : "memory");
}
__device__ __forceinline__ void mbar_expect_if(uint32_t z, uint32_t bar, uint32_t bytes) {
    asm volatile("{\n.reg .pred p;\nsetp.eq.u32 p, %2, 0;\n@p mbarrier.arrive.expect_tx.shared::cta.b64 _, [%0], %1;\n}" :: "r"(bar), "r"(bytes), "r"(z) : "memory");
}
__device__ __forceinline__ void mbar_arrive_if(uint32_t z, uint32_t bar) {
    asm volatile("{\n.reg .pred p;\nsetp.eq.u32 p, %1, 0;\n@p mbarrier.arrive.shared::cta.b64 _, [%0];\n}" :: "r"(bar), "r"(z) : "memory");
}
__device__ __forceinline__ void sts32_if(uint32_t z, uint32_t a, uint32_t x) {
    asm volatile("{\n.reg .pred p;\nsetp.eq.u32 p, %2, 0;\n@p st.shared.u32 [%0], %1;\n}" :: "r"(a), "r"(x), "r"(z) : "memory");
}
template <int K> __device__ __forceinline__ void sched_fence(int v) {
    asm volatile("{\n.reg .pred p;\nsetp.ne.s32 p, %0, %1;\n@p bra.uni F_%=;\ntrap;\nF_%=:\n}" :: "r"(v), "n"(1000 + K) : "memory");
}
__device__ __forceinline__ void spin_until(unsigned t0, unsigned d) {
    asm volatile("{\n.reg .pred p;\n.reg .u64 c;\n.reg .u32 lo;\n"
                 "S_%=: mov.u64 c, %%clock64;\ncvt.u32.u64 lo, c;\nsub.u32 lo, lo, %0;\nsetp.lt.u32 p, lo, %1;\n@p bra.uni S_%=;\n}" :: "r"(t0), "r"(d) : "memory");
}
__device__ __forceinline__ void bar_sync(int id, int n) { asm volatile("bar.sync %0, %1;" :: "r"(id), "r"(n) : "memory"); }
__device__ __forceinline__ void bar_sync_sel(int sel, int id) {
    asm volatile("{\n.reg .pred p;\nsetp.eq.u32 p, %0, 0;\n@p bar.sync %1, %3;\n@!p bar.sync %2, %3;\n}" :: "r"(sel), "r"(id), "r"(id + 1), "n"(192) : "memory");
}
__device__ __forceinline__ void bar_arrive(int id, int n) { asm volatile("bar.arrive %0, %1;" :: "r"(id), "r"(n) : "memory"); }
__device__ __forceinline__ void fence_async_smem() { asm volatile("fence.proxy.async.shared::cta;" ::: "memory"); }
__device__ __forceinline__ uint32_t pack_bf16(float lo, float hi) { uint32_t r; asm("cvt.rn.bf16x2.f32 %0, %1, %2;" : "=r"(r) : "f"(hi), "f"(lo)); return r; }
__device__ __forceinline__ uint32_t pack_f16(float lo, float hi) { uint32_t r; asm("cvt.rn.f16x2.f32 %0, %1, %2;" : "=r"(r) : "f"(hi), "f"(lo)); return r; }
__device__ __forceinline__ uint32_t f16x2_to_bf16x2(uint32_t v) { float2 f = __half22float2(*reinterpret_cast<__half2*>(&v)); return pack_bf16(f.x, f.y); }
__device__ __forceinline__ uint32_t hmul2(uint32_t a, uint32_t b) { uint32_t r; asm("mul.rn.f16x2 %0, %1, %2;" : "=r"(r) : "r"(a), "r"(b)); return r; }
__device__ __forceinline__ float ex2(float x) { float y; asm("ex2.approx.ftz.f32 %0, %1;" : "=f"(y) : "f"(x)); return y; }
__device__ __forceinline__ float ex2v(float x) { float y; asm volatile("ex2.approx.ftz.f32 %0, %1;" : "=f"(y) : "f"(x)); return y; }
__device__ __forceinline__ uint32_t absmax2(uint32_t a, uint32_t b) {
    uint32_t r; asm("max.xorsign.abs.f16x2 %0, %1, %2;" : "=r"(r) : "r"(a), "r"(b)); return r;
}
__device__ __forceinline__ uint32_t shl_v(uint32_t a, int n) { return a << n; }
__device__ __forceinline__ uint32_t max3u(uint32_t a, uint32_t b, uint32_t c) { return max(max(a, b), c); }
__device__ __forceinline__ uint4 lds128(uint32_t a) { uint4 v; asm volatile("ld.shared.v4.u32 {%0,%1,%2,%3}, [%4];" : "=r"(v.x), "=r"(v.y), "=r"(v.z), "=r"(v.w) : "r"(a) : "memory"); return v; }
__device__ __forceinline__ uint4 lds128v(uint32_t a) { uint4 v; asm volatile("ld.volatile.shared.v4.u32 {%0,%1,%2,%3}, [%4];" : "=r"(v.x), "=r"(v.y), "=r"(v.z), "=r"(v.w) : "r"(a) : "memory"); return v; }
__device__ __forceinline__ float4 lds128f(uint32_t a) { float4 v; asm volatile("ld.shared.v4.f32 {%0,%1,%2,%3}, [%4];" : "=f"(v.x), "=f"(v.y), "=f"(v.z), "=f"(v.w) : "r"(a) : "memory"); return v; }
__device__ __forceinline__ float2 lds64f(uint32_t a) { float2 v; asm volatile("ld.shared.v2.f32 {%0,%1}, [%2];" : "=f"(v.x), "=f"(v.y) : "r"(a) : "memory"); return v; }
__device__ __forceinline__ uint4 lds64x2(uint32_t a) { uint4 v; asm volatile("ld.shared.v2.u32 {%0,%1}, [%4];\nld.shared.v2.u32 {%2,%3}, [%4+256];" : "=r"(v.x), "=r"(v.y), "=r"(v.z), "=r"(v.w) : "r"(a) : "memory"); return v; }
__device__ __forceinline__ uint32_t lds32(uint32_t a) { uint32_t v; asm volatile("ld.shared.u32 %0, [%1];" : "=r"(v) : "r"(a) : "memory"); return v; }
__device__ __forceinline__ void sts128(uint32_t a, uint32_t x, uint32_t y, uint32_t z, uint32_t w) { asm volatile("st.shared.v4.u32 [%0], {%1,%2,%3,%4};" :: "r"(a), "r"(x), "r"(y), "r"(z), "r"(w) : "memory"); }
__device__ __forceinline__ void sts128f(uint32_t a, float x, float y, float z, float w) { asm volatile("st.shared.v4.f32 [%0], {%1,%2,%3,%4};" :: "r"(a), "f"(x), "f"(y), "f"(z), "f"(w) : "memory"); }
__device__ __forceinline__ void sts64(uint32_t a, uint32_t x, uint32_t y) { asm volatile("st.shared.v2.u32 [%0], {%1,%2};" :: "r"(a), "r"(x), "r"(y) : "memory"); }
__device__ __forceinline__ void sts32(uint32_t a, uint32_t x) { asm volatile("st.shared.u32 [%0], %1;" :: "r"(a), "r"(x) : "memory"); }
__device__ __forceinline__ uint4 ldsm4(uint32_t a) { uint4 v; asm volatile("ldmatrix.sync.aligned.m8n8.x4.shared.b16 {%0,%1,%2,%3}, [%4];" : "=r"(v.x), "=r"(v.y), "=r"(v.z), "=r"(v.w) : "r"(a) : "memory"); return v; }
__device__ __forceinline__ void stsm2t(uint32_t a, uint32_t x, uint32_t y) { asm volatile("stmatrix.sync.aligned.m8n8.x2.trans.shared.b16 [%0], {%1,%2};" :: "r"(a), "r"(x), "r"(y) : "memory"); }
__device__ __forceinline__ void stsm4t(uint32_t a, uint32_t x, uint32_t y, uint32_t z, uint32_t w) { asm volatile("stmatrix.sync.aligned.m8n8.x4.trans.shared.b16 [%0], {%1,%2,%3,%4};" :: "r"(a), "r"(x), "r"(y), "r"(z), "r"(w) : "memory"); }
__device__ __forceinline__ void st_async64(uint32_t a, uint32_t x, uint32_t y, uint32_t bar) { asm volatile("st.async.shared::cluster.mbarrier::complete_tx::bytes.v2.b32 [%0], {%1,%2}, [%3];" :: "r"(a), "r"(x), "r"(y), "r"(bar) : "memory"); }
__device__ __forceinline__ void bulk_s2c(uint32_t dst, uint32_t src, uint32_t bytes, uint32_t bar) { asm volatile("cp.async.bulk.shared::cluster.shared::cta.mbarrier::complete_tx::bytes [%0], [%1], %2, [%3];" :: "r"(dst), "r"(src), "r"(bytes), "r"(bar) : "memory"); }
__device__ __forceinline__ void bulk_s2g(void* dst, uint32_t src, uint32_t bytes) { asm volatile("cp.async.bulk.global.shared::cta.bulk_group [%0], [%1], %2;" :: "l"(dst), "r"(src), "r"(bytes) : "memory"); }
__device__ __forceinline__ uint32_t ldg_nc32(const void* p) { uint32_t v; asm volatile("ld.global.nc.L2::128B.u32 %0, [%1];" : "=r"(v) : "l"(p)); return v; }
__device__ __forceinline__ uint4 ldg_relaxed128(const void* p) { uint4 v; asm volatile("ld.relaxed.gpu.global.v4.u32 {%0,%1,%2,%3}, [%4];" : "=r"(v.x), "=r"(v.y), "=r"(v.z), "=r"(v.w) : "l"(p) : "memory"); return v; }
__device__ __forceinline__ void mma16816(float (&d)[4], uint32_t a0, uint32_t a1, uint32_t a2, uint32_t a3, uint32_t b0, uint32_t b1) {
    asm volatile("mma.sync.aligned.m16n8k16.row.col.f32.bf16.bf16.f32 {%0,%1,%2,%3}, {%4,%5,%6,%7}, {%8,%9}, {%0,%1,%2,%3};"
        : "+f"(d[0]), "+f"(d[1]), "+f"(d[2]), "+f"(d[3]) : "r"(a0), "r"(a1), "r"(a2), "r"(a3), "r"(b0), "r"(b1));
}
__device__ __forceinline__ void mma16816_z(float (&d)[4], uint32_t a0, uint32_t a1, uint32_t a2, uint32_t a3, uint32_t b0, uint32_t b1) {
    asm volatile("mma.sync.aligned.m16n8k16.row.col.f32.bf16.bf16.f32 {%0,%1,%2,%3}, {%4,%5,%6,%7}, {%8,%9}, {%10,%10,%10,%10};"
        : "=f"(d[0]), "=f"(d[1]), "=f"(d[2]), "=f"(d[3]) : "r"(a0), "r"(a1), "r"(a2), "r"(a3), "r"(b0), "r"(b1), "f"(0.f));
}
__device__ __forceinline__ void mma1688(float (&d)[4], uint32_t a0, uint32_t a1, uint32_t b0) {
    asm volatile("mma.sync.aligned.m16n8k8.row.col.f32.bf16.bf16.f32 {%0,%1,%2,%3}, {%4,%5}, {%6}, {%0,%1,%2,%3};"
        : "+f"(d[0]), "+f"(d[1]), "+f"(d[2]), "+f"(d[3]) : "r"(a0), "r"(a1), "r"(b0));
}
__device__ __forceinline__ void mma1688_z(float (&d)[4], uint32_t a0, uint32_t a1, uint32_t b0) {
    asm volatile("mma.sync.aligned.m16n8k8.row.col.f32.bf16.bf16.f32 {%0,%1,%2,%3}, {%4,%5}, {%6}, {%7,%7,%7,%7};"
        : "=f"(d[0]), "=f"(d[1]), "=f"(d[2]), "=f"(d[3]) : "r"(a0), "r"(a1), "r"(b0), "f"(0.f));
}
template <int ACC>
__device__ __forceinline__ void wgmma_n32_rs(float (&d)[16], uint32_t a0, uint32_t a1, uint32_t a2, uint32_t a3, uint64_t desc) {
    asm volatile("wgmma.mma_async.sync.aligned.m64n32k16.f32.bf16.bf16 {%0,%1,%2,%3,%4,%5,%6,%7,%8,%9,%10,%11,%12,%13,%14,%15}, {%16,%17,%18,%19}, %20, %21, 1, 1, 0;"
        : "+f"(d[0]), "+f"(d[1]), "+f"(d[2]), "+f"(d[3]), "+f"(d[4]), "+f"(d[5]), "+f"(d[6]), "+f"(d[7]),
          "+f"(d[8]), "+f"(d[9]), "+f"(d[10]), "+f"(d[11]), "+f"(d[12]), "+f"(d[13]), "+f"(d[14]), "+f"(d[15])
        : "r"(a0), "r"(a1), "r"(a2), "r"(a3), "l"(desc), "n"(ACC));
}
template <int ACC>
__device__ __forceinline__ void wgmma_n32_ss(float (&d)[16], uint64_t da, uint64_t db) {
    asm volatile("wgmma.mma_async.sync.aligned.m64n32k16.f32.bf16.bf16 {%0,%1,%2,%3,%4,%5,%6,%7,%8,%9,%10,%11,%12,%13,%14,%15}, %16, %17, %18, 1, 1, 0, 0;"
        : "+f"(d[0]), "+f"(d[1]), "+f"(d[2]), "+f"(d[3]), "+f"(d[4]), "+f"(d[5]), "+f"(d[6]), "+f"(d[7]),
          "+f"(d[8]), "+f"(d[9]), "+f"(d[10]), "+f"(d[11]), "+f"(d[12]), "+f"(d[13]), "+f"(d[14]), "+f"(d[15])
        : "l"(da), "l"(db), "n"(ACC));
}
__device__ __forceinline__ void wg_fence() { asm volatile("wgmma.fence.sync.aligned;" ::: "memory"); }
__device__ __forceinline__ void wg_commit() { asm volatile("wgmma.commit_group.sync.aligned;" ::: "memory"); }
__device__ __forceinline__ void wg_wait0() { asm volatile("wgmma.wait_group.sync.aligned 0;" ::: "memory"); }
__device__ __forceinline__ void cluster_sync() { asm volatile("barrier.cluster.arrive.aligned;\nbarrier.cluster.wait.aligned;" ::: "memory"); }

#define STAMP(s, i) do {} while (0)
#define STAMPV(s, i, v) do {} while (0)

constexpr int XT_BYTES = 36864;
constexpr int O_XT = 0;
constexpr int O_STG = XT_BYTES;
constexpr int O_AS = 3 * XT_BYTES;
constexpr int O_XP = O_AS + 16384;
constexpr int O_QKX = O_XP + 8192;
constexpr int O_KM = O_QKX + 8192;
constexpr int O_QM = O_QKX + 10240;
constexpr int O_VX = O_STG + 147456;
constexpr int O_VM = O_VX + 24576;
constexpr int O_SC = O_VM + 2048;
constexpr int O_OF = O_SC + 2560;
constexpr int O_AF = O_OF + 2048;
constexpr int O_WP = O_AF + 4096;
constexpr int O_MF = O_WP + 2048;
constexpr int O_MISC = O_MF + 9216;
static_assert(O_QKX + 24576 <= O_VX, "smem");
constexpr int O_BAR = O_MISC + 64;
constexpr int CHAIN_SMEM = O_BAR + 128;
static_assert(CHAIN_SMEM <= 232448, "smem");
constexpr int B_X = O_BAR, B_VX = O_BAR + 24, B_SC = O_BAR + 40, B_W = O_BAR + 48;
constexpr float SM_SCALE = 0.08838834764831845f * 1.4426950408889634f;
constexpr uint32_t ONES = 0x3f803f80u;

template <bool B> struct BoolC { static constexpr bool value = B; };
__device__ __forceinline__ uint32_t opaque(uint32_t v) { uint32_t o; asm volatile("mov.u32 %0, %1;" : "=r"(o) : "r"(v)); return o; }
__device__ __forceinline__ void st_async128(uint32_t a, uint32_t x, uint32_t y, uint32_t z, uint32_t w, uint32_t bar) {
    asm volatile("st.async.shared::cluster.mbarrier::complete_tx::bytes.v4.b32 [%0], {%1,%2,%3,%4}, [%5];" :: "r"(a), "r"(x), "r"(y), "r"(z), "r"(w), "r"(bar) : "memory");
}
__device__ __forceinline__ void tma_x_tile(uint32_t sb, const CUtensorMap* tm, int r, int j, int slot) {
    asm volatile("{\n.reg .pred p;\nelect.sync _|p, 0xffffffff;\n"
        "@p mbarrier.arrive.expect_tx.shared::cta.b64 _, [%2], 36864;\n"
        "@p cp.async.bulk.tensor.2d.shared::cluster.global.mbarrier::complete_tx::bytes.multicast::cluster [%0], [%1, {%3, %4}], [%2], %7;\n"
        "@p cp.async.bulk.tensor.2d.shared::cluster.global.mbarrier::complete_tx::bytes.multicast::cluster [%0+4096], [%1, {%5, %4}], [%2], %7;\n"
        "@p cp.async.bulk.tensor.2d.shared::cluster.global.mbarrier::complete_tx::bytes.multicast::cluster [%0+8192], [%1, {%6, %4}], [%2], %7;\n}"
        :: "r"(sb + O_XT + slot * XT_BYTES + 3 * r * 4096), "l"(tm), "r"(sb + B_X + 8 * slot), "r"(192 * r), "r"(j * 32), "r"(192 * r + 64), "r"(192 * r + 128),
           "h"((unsigned short)7) : "memory");
}
__device__ __forceinline__ void flag_inc_if(uint32_t z, unsigned* p) {
    asm volatile("{\n.reg .pred p;\nsetp.eq.u32 p, %1, 0;\n@p red.release.gpu.global.inc.u32 [%0], 0xfffffffe;\n}" :: "l"(p), "r"(z) : "memory");
}
__device__ __forceinline__ float quad_max(float v) {
    const float a = __shfl_xor_sync(~0u, v, 1), b = __shfl_xor_sync(~0u, v, 2), c = __shfl_xor_sync(~0u, v, 3);
    return fmaxf(fmaxf(v, a), fmaxf(b, c));
}
__device__ __forceinline__ void load_scores(float (&p)[10], uint32_t base, uint32_t stride, uint32_t l16) {
    const float4 a0 = lds128f(base + l16), b0 = lds128f(base + stride + l16);
    const float4 a1 = lds128f(base + 512 + l16), b1 = lds128f(base + stride + 512 + l16);
    const float2 a2 = lds64f(base + 1024 + (l16 >> 1)), b2 = lds64f(base + stride + 1024 + (l16 >> 1));
    p[0] = a2.x + b2.x; p[1] = a2.y + b2.y;
    p[2] = a0.x + b0.x; p[3] = a0.y + b0.y; p[4] = a0.z + b0.z; p[5] = a0.w + b0.w;
    p[6] = a1.x + b1.x; p[7] = a1.y + b1.y; p[8] = a1.z + b1.z; p[9] = a1.w + b1.w;
}
__device__ __forceinline__ float rcp_fast(float x) { float y; asm("rcp.approx.ftz.f32 %0, %1;" : "=f"(y) : "f"(x)); return y; }

__global__ void __cluster_dims__(3, 1, 1) __launch_bounds__(384, 1)
chain_kernel(const __grid_constant__ CUtensorMap tm_x, const __grid_constant__ CUtensorMap tm_q,
             const __grid_constant__ CUtensorMap tm_k, const __grid_constant__ CUtensorMap tm_v,
             const __nv_bfloat16* __restrict__ x, const __nv_bfloat16* __restrict__ mem0,
             const __nv_bfloat16* __restrict__ Wo) {
    extern __shared__ __align__(1024) uint8_t smem_raw[];
    const uint32_t sb = smem_u32(smem_raw);
    const int lane = threadIdx.x & 31;
    const int warp = __shfl_sync(~0u, threadIdx.x >> 5, 0);
    const int wg = warp >> 2, w = warp & 3;
    const int h = blockIdx.x / 3, r = blockIdx.x - 3 * h;
    uint4* const g_acc = reinterpret_cast<uint4*>((reinterpret_cast<uintptr_t>(g_acc_raw) + 0x1fffff) & ~(uintptr_t)0x1fffff);

#define PSTAMP(i) do {} while (0)
    auto load_w = [&](int i) {
        mbar_expect(sb + B_W + 8 * i, 49152);
        for (int tl = 0; tl < 2; tl++)
            asm volatile("cp.async.bulk.tensor.2d.shared::cluster.global.mbarrier::complete_tx::bytes [%0], [%1, {%3, %4}], [%2];"
                :: "r"(sb + O_STG + tl * 73728 + i * 24576), "l"(r < 2 ? (tl ? &tm_k : &tm_q) : &tm_v), "r"(sb + B_W + 8 * i),
                   "r"(h * 128 + 64 * (r < 2 ? r : tl)), "r"(192 * i) : "memory");
    };
    if (threadIdx.x == 0) {
        if (sb & 1023u) __trap();
        for (int i = 0; i < 9; i++) mbar_init(sb + O_BAR + 8 * i, 1);
        asm volatile("fence.mbarrier_init.release.cluster;" ::: "memory");
        for (int i = 0; i < (r < 2 && PRIO ? 2 : 3); i++) load_w(i);
    }
    __syncwarp();
    asm volatile("barrier.cluster.arrive.relaxed.aligned;" ::: "memory");
    asm volatile("griddepcontrol.launch_dependents;" ::: "memory");
    if (warp == 0) PSTAMP(9);
    const uint32_t l16c = __shfl_sync(~0u, lane * 16, lane);

    if (wg < 2) {
#define KS(u) ((u) < 8 ? 12 * ((u) >> 2) + (((u) >> 1) & 1) + 4 * ((u) & 1) : (u) < 12 ? (u) : (u) < 16 ? (u) + 8 : (u) < 24 ? 24 + (((u) - 16) >> 1) + 4 * ((u) & 1) : (u) + 8)
        asm volatile("setmaxnreg.inc.sync.aligned.u32 184;");
        uint32_t a[144];
        uint32_t adr1;
        {
            const int g = lane >> 2, t = lane & 3;
            const int t1 = threadIdx.x;
#pragma unroll
            for (int i = 0; i < 2; i++) g_acc[(blockIdx.x * 64 + i * 32 + (t1 >> 3)) * 16 + (t1 & 7)] = make_uint4(0, 0, 0, 0);
            __threadfence();
            asm volatile("barrier.cluster.wait.aligned;" ::: "memory");
            const uint32_t ev = sb + O_STG + (2 * t) * 128 + (((2 * w + (g >> 2)) ^ (2 * t)) << 4) + (g & 3) * 4;
            const uint32_t od = (ev ^ 16) + 128;
            auto gather = [&](int dst, uint32_t off) {
                a[dst] = lds32(ev + off); a[dst + 1] = lds32(od + off); a[dst + 2] = lds32(ev + off + 1024); a[dst + 3] = lds32(od + off + 1024);
            };
            const uint4* xp = reinterpret_cast<const uint4*>(x) + blockIdx.x * 1536 + t1;
            uint4 xv[6];
#pragma unroll
            for (int th = 0; th < 2; th++) {
                mbar_wait(sb + B_W + 8 * th, 0);
                if (PRIO && th == PRIO - 1 && r < 2 && t1 == 0) load_w(2);
                __syncwarp();
                if (th == 1) {
#pragma unroll
                    for (int i = 0; i < 6; i++) xv[i] = __ldg(xp + i * 256);
                }
#pragma unroll
                for (int u = 4 * th; u < 4 * th + 4; u++) {
                    gather(32 + 4 * u, wg * (73728 + 4096) + KS(u) * 2048);
                    gather(4 * u, 73728 - wg * (73728 - 4096) + KS(u) * 2048);
                    gather(64 + 4 * u, wg * 73728 + KS(8 + u) * 2048);
                }
            }
            mbar_wait(sb + B_W + 16, 0);
#pragma unroll
            for (int u = 16; u < 28; u++) gather(32 + 4 * u, wg * 73728 + KS(u) * 2048);
#pragma unroll
            for (int kk = 0; kk < 72; kk++) {
                uint32_t w0 = a[2 * kk], w1 = a[2 * kk + 1];
                a[2 * kk] = __byte_perm(w0, w1, 0x5410);
                a[2 * kk + 1] = __byte_perm(w0, w1, 0x7632);
            }
            if (r == 2) {
                float n0[4], n1[4];
#pragma unroll
                for (int u = 0; u < 36; u++) {
                    const uint32_t x0 = a[4 * u] & 0x7fff7fffu, x1 = a[4 * u + 1] & 0x7fff7fffu, x2 = a[4 * u + 2] & 0x7fff7fffu, x3 = a[4 * u + 3] & 0x7fff7fffu;
                    if (u == 0) mma16816_z(n0, x0, x1, x2, x3, ONES, ONES);
                    else if (u < 8) mma16816(n0, x0, x1, x2, x3, ONES, ONES);
                    else if (u == 8) mma16816_z(n1, x0, x1, x2, x3, ONES, ONES);
                    else mma16816(n1, x0, x1, x2, x3, ONES, ONES);
                }
                const uint32_t mx = __reduce_max_sync(~0u, __float_as_uint(2.f * fmaxf(fmaxf(n0[0], n0[2]), fmaxf(n1[0], n1[2]))));
                sts32_if(lane, sb + O_MISC + 32 + 4 * warp, mx);
            }
            uint32_t xm = 0;
#pragma unroll
            for (int i = 0; i < 6; i++)
                xm = __vmaxu2(xm, __vmaxu2(__vmaxu2(xv[i].x & 0x7fff7fffu, xv[i].y & 0x7fff7fffu), __vmaxu2(xv[i].z & 0x7fff7fffu, xv[i].w & 0x7fff7fffu)));
            sts32_if(lane, sb + O_OF + 16 + 4 * warp, __reduce_max_sync(~0u, max(xm << 16, xm & 0xffff0000u)));
            if (warp == 0) PSTAMP(11);
            bar_arrive(7, 384);
            asm volatile("barrier.cluster.arrive.relaxed.aligned;" ::: "memory");
            bar_sync(1, 256);
            const uint32_t as = sb + O_AS + wg * 8192 + (16 * w + g) * 128 + t * 4;
            sts32(as + (g << 4), a[32]);
            sts32(as + 1024 + (g << 4), a[33]);
            sts32(as + ((1 ^ g) << 4), a[34]);
            sts32(as + 1024 + ((1 ^ g) << 4), a[35]);
            sts128(sb + O_AF + warp * 512 + lane * 16, a[32], a[33], a[34], a[35]);
            fence_async_smem();
            bar_sync(1, 256);
            const uint32_t l = lane * 16;
            const int mi = lane >> 3, isk = (mi >> 1) ? wg : (wg ^ 1);
            adr1 = (r == 2) ? (sb + O_VM + warp * 256 + (l >> 1))
                            : (isk ? (sb + O_KM + w * 512 + wg * 256 + (mi & 1) * 128 + (l & 127))
                                   : (sb + O_QM + w * 512 + (mi & 1) * 256 + wg * 128 + (l & 127)));
            adr1 = __shfl_sync(~0u, adr1, lane);
        }
        auto qkv_loop = [&](auto r2tag) {
        constexpr bool R2 = decltype(r2tag)::value;
        int s3 = 2;
#pragma unroll 1
        for (int s = -1 - R2; s < NSEG; s++) {
            const uint32_t l16 = opaque(l16c);
            const int j = s + 1 + R2;
            s3 = (s3 == 2) ? 0 : s3 + 1;
            if (s < 0) mbar_wait(sb + B_X + 8 * s3, 0);
            const uint64_t desc0 = (uint64_t)(((sb + O_XT + s3 * XT_BYTES) & 0x3FFFF) >> 4) | (1ull << 16) | (64ull << 32) | (1ull << 62);
            uint32_t km0 = 0, km1 = 0;
            if (s >= 0) {
                { const uint4 v = lds128(sb + O_AF + warp * 512 + l16); a[32] = v.x; a[33] = v.y; a[34] = v.z; a[35] = v.w; }
                float co[4], cw[3][4];
                uint4 b[14];
                float inv;
#define GORD(i) ((i) < 8 ? 2 * ((i) >> 2) + (((i) >> 1) & 1) + 4 * ((i) & 1) : (i))
                auto qkv_mma = [&](int i) {
                    const int gi = GORD(i), u = 8 * gi, n0 = 2 * i, n1 = 2 * i + 1;
                    if (gi < 4) {
                        if (i == 0) mma16816_z(co, a[u], a[u + 1], a[u + 2], a[u + 3], b[0].x, b[0].y);
                        else mma16816(co, a[u], a[u + 1], a[u + 2], a[u + 3], b[i].x, b[i].y);
                    }
                    if (n0 < 3) mma16816_z(cw[n0 % 3], a[32 + u], a[32 + u + 1], a[32 + u + 2], a[32 + u + 3], b[i].x, b[i].y);
                    else mma16816(cw[n0 % 3], a[32 + u], a[32 + u + 1], a[32 + u + 2], a[32 + u + 3], b[i].x, b[i].y);
                    if (n1 < 3) mma16816_z(cw[n1 % 3], a[32 + u + 4], a[32 + u + 5], a[32 + u + 6], a[32 + u + 7], b[i].z, b[i].w);
                    else mma16816(cw[n1 % 3], a[32 + u + 4], a[32 + u + 5], a[32 + u + 6], a[32 + u + 7], b[i].z, b[i].w);
                    if (gi < 4) mma16816(co, a[u + 4], a[u + 5], a[u + 6], a[u + 7], b[i].z, b[i].w);
                };
                const uint32_t mf = sb + O_MF + l16, mfs = mf + wg * 1024;
                const uint32_t qb = (s & 1) * 12288;
                bar_sync(2, 384);
                if (warp == 0) STAMP(s, 0);
                auto qkv_ld = [&](int i) {
                    const int gi = GORD(i);
                    b[i] = gi < 4 ? lds128v(mfs + (gi >> 1) * 3072 + (gi & 1) * 512) : lds128v(mf + (gi < 6 ? gi : gi + 4) * 512);
                };
#pragma unroll
                for (int i = 0; i < 4; i++) qkv_ld(i);
                qkv_mma(0); qkv_mma(1); qkv_mma(2);
                const uint32_t z0 = __float_as_uint(QDEP ? co[0] : cw[1][0]) & (l16 & 15u);
                qkv_mma(3);
                bar_sync(15, 384);
                b[4] = lds128v(mfs + 3072 + z0);
#pragma unroll
                for (int i = 5; i < 9; i++) qkv_ld(i);
#pragma unroll
                for (int i = 4; i < 9; i++) { qkv_mma(i); qkv_ld(5 + i); }
                asm volatile("ld.volatile.shared.f32 %0, [%1];" : "=f"(inv) : "r"(sb + O_MISC) : "memory");
#pragma unroll
                for (int i = 9; i < 14; i++) qkv_mma(i);
#pragma unroll
                for (int i = 0; i < 4; i++) cw[0][i] += cw[1][i] + cw[2][i];
                if (!R2) {
                    const uint32_t o0 = pack_bf16(co[0] * inv, co[1] * inv), o1 = pack_bf16(co[2] * inv, co[3] * inv);
                    const uint32_t w0 = pack_bf16(cw[0][0] * inv, cw[0][1] * inv), w1 = pack_bf16(cw[0][2] * inv, cw[0][3] * inv);
                    stsm4t(adr1 + qb, o0, o1, w0, w1);
                    if (warp == 0) STAMP(s, 1);
                    asm volatile("{\n.reg .pred p;\nsetp.ge.u32 p, %0, 3;\n@p bar.arrive 1, 256;\n@!p bar.sync 1, 256;\n}" :: "r"(warp) : "memory");
                    auto scores = [&](float (&v)[4], const uint4 (&q)[4], const uint4 (&k)[4]) {
                        float s0[4], s1[4], t0[4], t1[4];
                        mma16816_z(s0, q[0].x, q[0].y, q[0].z, q[0].w, k[0].x, k[0].y);
                        mma16816_z(s1, q[0].x, q[0].y, q[0].z, q[0].w, k[0].z, k[0].w);
                        mma16816_z(t0, q[1].x, q[1].y, q[1].z, q[1].w, k[1].x, k[1].y);
                        mma16816_z(t1, q[1].x, q[1].y, q[1].z, q[1].w, k[1].z, k[1].w);
                        mma16816(s0, q[2].x, q[2].y, q[2].z, q[2].w, k[2].x, k[2].y);
                        mma16816(s1, q[2].x, q[2].y, q[2].z, q[2].w, k[2].z, k[2].w);
                        mma16816(t0, q[3].x, q[3].y, q[3].z, q[3].w, k[3].x, k[3].y);
                        mma16816(t1, q[3].x, q[3].y, q[3].z, q[3].w, k[3].z, k[3].w);
                        v[0] = (s0[0] + s0[2]) + (t0[0] + t0[2]); v[1] = (s0[1] + s0[3]) + (t0[1] + t0[3]);
                        v[2] = (s1[0] + s1[2]) + (t1[0] + t1[2]); v[3] = (s1[1] + s1[3]) + (t1[1] + t1[3]);
                    };
                    if (warp < 2) {
                        uint4 q[4], k[4]; float v[4];
#pragma unroll
                        for (int i = 0; i < 4; i++) { q[i] = ldsm4(sb + O_QM + qb + i * 512 + l16); k[i] = ldsm4(sb + O_QKX + 4096 + qb + warp * 2048 + i * 512 + l16); }
                        scores(v, q, k);
                        const uint32_t dst = sb + O_SC + r * 1280 + warp * 512 + l16;
                        st_async128(mapa(dst, 2), __float_as_uint(v[0]), __float_as_uint(v[1]), __float_as_uint(v[2]), __float_as_uint(v[3]), mapa(sb + B_SC, 2));
                        st_async128(mapa(dst, r ^ 1), __float_as_uint(v[0]), __float_as_uint(v[1]), __float_as_uint(v[2]), __float_as_uint(v[3]), mapa(sb + B_SC, r ^ 1));
                        sts128f(dst, v[0], v[1], v[2], v[3]);
                    } else if (warp == 2) {
                        uint4 q[4], k[4]; float v[4];
#pragma unroll
                        for (int i = 0; i < 4; i++) { q[i] = ldsm4(sb + O_QM + qb + i * 512 + l16); k[i] = ldsm4(sb + O_KM + qb + i * 512 + l16); }
                        scores(v, q, k);
                        const uint32_t dst = sb + O_SC + r * 1280 + 1024 + (l16 >> 1);
                        st_async64(mapa(dst, 2), __float_as_uint(v[0] + v[2]), __float_as_uint(v[1] + v[3]), mapa(sb + B_SC, 2));
                        st_async64(mapa(dst, r ^ 1), __float_as_uint(v[0] + v[2]), __float_as_uint(v[1] + v[3]), mapa(sb + B_SC, r ^ 1));
                        sts64(dst, __float_as_uint(v[0] + v[2]), __float_as_uint(v[1] + v[3]));
                        STAMP(s, 2);
                    }
                } else {
                    sts128f(sb + O_XP + warp * 512 + l16, co[0], co[1], co[2], co[3]);
                    bar_sync(8 + w, 64);
                    const float4 o = lds128f(sb + O_XP + (warp ^ 4) * 512 + l16);
                    km0 = pack_bf16((cw[0][0] + o.x) * inv, (cw[0][1] + o.y) * inv);
                    km1 = pack_bf16((cw[0][2] + o.z) * inv, (cw[0][3] + o.w) * inv);
                    if (warp == 0) STAMP(s, 1);
                    st_async64(mapa(adr1, 0), km0, km1, mapa(sb + B_SC, 0));
                    st_async64(mapa(adr1, 1), km0, km1, mapa(sb + B_SC, 1));
                    sts64(adr1, km0, km1);
                    if (warp == 0) STAMP(s, 2);
                }
            }
            if (s >= 0) bar_sync(3, 384);
            auto store_qk = [&]() {
                asm volatile("{\n.reg .pred p;\nelect.sync _|p, 0xffffffff;\n"
                    "@p cp.async.bulk.global.shared::cta.bulk_group [%0], [%1], 10240;\n@p cp.async.bulk.commit_group;\n}"
                    :: "l"(reinterpret_cast<char*>(g_qkv) + (size_t)(s * NH + h) * REC + r * 10240), "r"(sb + O_QKX + (s & 1) * 12288) : "memory");
            };
            auto store_vm = [&]() {
                *reinterpret_cast<uint2*>(reinterpret_cast<char*>(g_qkv) + (size_t)(s * NH + h) * REC + 28672 + warp * 256 + (l16 >> 1)) = make_uint2(km0, km1);
            };
            if (s == NSEG - 1) {
                if (R2) store_vm();
                else if (warp == 3) {
                    fence_async_smem();
                    store_qk();
                    asm volatile("cp.async.bulk.wait_group 0;\nfence.proxy.async.global;" ::: "memory");
                }
            } else {
#define XDESC(u) (((u) < 8 ? descs : desc0) + (uint64_t)(((KS(u) >> 2) * 4096 + (KS(u) & 3) * 32) >> 4))
                const uint64_t descs = desc0 + (uint64_t)(wg * 4);
                float d[16];
                wg_fence();
#pragma unroll
                for (int u = 0; u < 8; u++) {
                    if (u == 0) wgmma_n32_rs<0>(d, a[0], a[1], a[2], a[3], XDESC(0));
                    else wgmma_n32_rs<1>(d, a[4 * u], a[4 * u + 1], a[4 * u + 2], a[4 * u + 3], XDESC(u));
                }
                wg_commit();
                wg_wait0();
                if (warp == 0) STAMP(s, 15);
                if (warp == 3) asm volatile("cp.async.bulk.wait_group.read 0;" ::: "memory");
                if (s >= 0) bar_sync(4, 384);
#pragma unroll
                for (int q = 0; q < 2; q++)
                    sts128(sb + O_XP + warp * 1024 + q * 512 + l16, pack_bf16(d[8 * q], d[8 * q + 1]), pack_bf16(d[8 * q + 2], d[8 * q + 3]),
                           pack_bf16(d[8 * q + 4], d[8 * q + 5]), pack_bf16(d[8 * q + 6], d[8 * q + 7]));
                bar_sync(12, 256);
#pragma unroll
                for (int q = 0; q < 2; q++) {
                    const uint4 o = lds128(sb + O_XP + (warp ^ 4) * 1024 + q * 512 + l16);
                    d[8 * q] = __uint_as_float(o.x << 16); d[8 * q + 1] = __uint_as_float(o.x & 0xffff0000u);
                    d[8 * q + 2] = __uint_as_float(o.y << 16); d[8 * q + 3] = __uint_as_float(o.y & 0xffff0000u);
                    d[8 * q + 4] = __uint_as_float(o.z << 16); d[8 * q + 5] = __uint_as_float(o.z & 0xffff0000u);
                    d[8 * q + 6] = __uint_as_float(o.w << 16); d[8 * q + 7] = __uint_as_float(o.w & 0xffff0000u);
                }
                if (s >= 0) {
                    if (R2) store_vm();
                    if (warp == 5 && s + 3 < NSEG) tma_x_tile(sb, &tm_x, r, s + 3, R2 ? (s3 == 2 ? 0 : s3 + 1) : (s3 == 0 ? 2 : s3 - 1));
                    if (warp == 3) {
                        asm volatile("cp.async.bulk.wait_group 0;\nfence.proxy.async.global;" ::: "memory");
                        if (FLAGPOS == 0 && s >= 4 && !(s & (s > 4 * NBIG ? 1 : 3))) {
                            __syncwarp();
                            flag_inc_if(l16, &g_flag[F_QKV + ((s > 4 * NBIG ? 2 * s - 4 * NBIG : s) - 4 + (h >> 3)) * 8]);
                        }
                        fence_async_smem();
                    }
                    asm volatile("{\n.reg .pred p;\nsetp.eq.u32 p, %0, 0;\n@p bar.sync 5, 256;\n@!p bar.sync 13, 256;\n}" :: "r"(wg) : "memory");
                }
                const uint64_t da0 = (uint64_t)(((sb + O_AS + wg * 8192) & 0x3FFFF) >> 4) | (1ull << 16) | (64ull << 32) | (1ull << 62);
                wg_fence();
                wgmma_n32_ss<1>(d, da0, XDESC(0));
#pragma unroll
                for (int u = 1; u < 28; u++) wgmma_n32_rs<1>(d, a[32 + 4 * u], a[32 + 4 * u + 1], a[32 + 4 * u + 2], a[32 + 4 * u + 3], XDESC(u));
                wg_commit();
                if (R2 && warp == 3 && s >= -1 && s < NSEG - 2)
                    asm volatile("{\n.reg .pred p;\ncp.async.bulk.wait_group 0;\nelect.sync _|p, 0xffffffff;\n"
                        "@p cp.async.bulk.shared::cluster.global.mbarrier::complete_tx::bytes.multicast::cluster [%1], [%0], 8192, [%2], %3;\n}"
                        :: "l"(reinterpret_cast<char*>(g_qkv) + (size_t)((s + 1) * NH + h) * REC + 20480), "r"(sb + O_VX + ((s + 1) & 1) * 8192),
                           "r"(sb + B_VX + 8 * ((s + 1) & 1)), "h"((unsigned short)3) : "memory");
                if (FLAGPOS == 1 && warp == 3 && s >= 4 && !(s & (s > 4 * NBIG ? 1 : 3)))
                    flag_inc_if(l16, &g_flag[F_QKV + ((s > 4 * NBIG ? 2 * s - 4 * NBIG : s) - 4 + (h >> 3)) * 8]);
                wg_wait0();
                if (!R2 && warp == 3 && s >= 0) store_qk();
                if (warp == 4) STAMP(s, 3);
                uint32_t e[8];
#pragma unroll
                for (int i = 0; i < 8; i++) e[i] = pack_bf16(d[2 * i], d[2 * i + 1]);
                if (!R2) {
                    const uint32_t base = sb + O_QKX + (j & 1) * 12288 + wg * 4096 + w * 512 + l16;
                    stsm4t(base, e[0], wg ? e[1] : e[2], wg ? e[2] : e[1], e[3]);
                    stsm4t(base + 2048, e[4], wg ? e[5] : e[6], wg ? e[6] : e[5], e[7]);
                } else {
                    const uint32_t base = sb + O_VX + s3 * 8192 + warp * 1024 + l16;
                    sts128(base, e[0], e[1], e[2], e[3]);
                    sts128(base + 512, e[4], e[5], e[6], e[7]);
                    if (warp != 3) bar_arrive(14, 256);
                    else {
                        bar_sync(14, 256);
                        fence_async_smem();
                        asm volatile("{\n.reg .pred p;\nelect.sync _|p, 0xffffffff;\nsetp.lt.and.s32 p, %2, 64, p;\n"
                            "@p cp.async.bulk.global.shared::cta.bulk_group [%0], [%1], 8192;\n@p cp.async.bulk.commit_group;\n}"
                            :: "l"(reinterpret_cast<char*>(g_qkv) + (size_t)(j * NH + h) * REC + 20480), "r"(sb + O_VX + s3 * 8192), "r"(j) : "memory");
                    }
                }
                if (warp == 7) STAMP(s, 4);
                if (j == 0) asm volatile("barrier.cluster.wait.aligned;" ::: "memory");
                if (s < -1) bar_sync(1, 256);
            }
        }
        };
        if (r == 2) qkv_loop(BoolC<true>()); else qkv_loop(BoolC<false>());
        bar_arrive(7, 384);
    } else {
        asm volatile("setmaxnreg.dec.sync.aligned.u32 136;");
        const int c = w;
        uint32_t a[96];
        uint32_t mmax = 0;
        {
            const int g = lane >> 2, t = lane & 3;
            uint32_t tag = 0, m0v[18];
            if (threadIdx.x == 256) tag = atomicAdd(&g_ticket, 1u);
#pragma unroll
            for (int i = 0; i < 9; i++) {
                const uint32_t* p = reinterpret_cast<const uint32_t*>(mem0 + g * DM + 16 * (4 * i + c) + 2 * t);
                m0v[2 * i] = __ldg(p); m0v[2 * i + 1] = __ldg(p + 4);
            }
            asm volatile("barrier.cluster.wait.aligned;" ::: "memory");
            if (c == 0) {
                tma_x_tile(sb, &tm_x, r, 0, 0);
                mbar_expect_if(lane, sb + B_SC, r < 2 ? 3328 : 2560);
                if (r < 2) mbar_expect_if(lane, sb + B_VX, 8192);
                sts32_if(lane, sb + O_MISC, __float_as_uint(1.0f));
                sts32_if(lane, sb + O_MISC + 12, __float_as_uint(SM_SCALE));
            }
            asm volatile("barrier.cluster.arrive.relaxed.aligned;" ::: "memory");
#pragma unroll
            for (int tau = 0; tau < 3; tau++) {
                const uint32_t* v = m0v + 6 * tau;
                sts128(sb + O_MF + tau * 3072 + c * 512 + lane * 16, v[0], v[1], v[2], v[3]);
                sts64(sb + O_MF + tau * 3072 + 2048 + (c >> 1) * 512 + lane * 16 + (c & 1) * 8, v[4], v[5]);
#pragma unroll
                for (int i = 0; i < 6; i++) mmax = __vmaxu2(mmax, v[i] & 0x7fff7fffu);
            }
            mmax = max(mmax << 16, mmax & 0xffff0000u);
            bar_arrive(2, 384); bar_arrive(15, 384);
            tag = (__shfl_sync(~0u, tag, 0) / 96u + 1u) & 0xffffu;
            mbar_wait(sb + B_W + 0, 0);
            const __nv_bfloat16* p = Wo + (size_t)(h * 128 + 4 * t) * DM + 192 * r + 16 * c + 2 * g;
#pragma unroll
            for (int i = 0; i < 3; i++)
#pragma unroll
                for (int eb = 0; eb < 8; eb++)
#pragma unroll
                    for (int j = 0; j < 4; j++) a[(i * 8 + eb) * 4 + j] = ldg_nc32(p + (16 * eb + ((j & 1) * 2 + (j >> 1))) * DM + 64 * i);
#pragma unroll
            for (int kk = 0; kk < 48; kk++) {
                uint32_t w0 = a[2 * kk], w1 = a[2 * kk + 1];
                a[2 * kk] = __byte_perm(w0, w1, 0x5410);
                a[2 * kk + 1] = __byte_perm(w0, w1, 0x7632);
            }
            sts128(sb + O_WP + c * 512 + lane * 16, a[92], a[93], a[94], a[95]);
            float wmax = 0.f;
#pragma unroll
            for (int i = 0; i < 3; i++) {
                float n0[4];
#pragma unroll
                for (int u = 8 * i; u < 8 * i + 8; u++) {
                    const uint32_t x0 = a[4 * u] & 0x7fff7fffu, x1 = a[4 * u + 1] & 0x7fff7fffu, x2 = a[4 * u + 2] & 0x7fff7fffu, x3 = a[4 * u + 3] & 0x7fff7fffu;
                    if (u == 8 * i) mma16816_z(n0, x0, x1, x2, x3, ONES, ONES);
                    else mma16816(n0, x0, x1, x2, x3, ONES, ONES);
                }
                wmax = fmaxf(wmax, fmaxf(n0[0], n0[2]));
            }
            uint32_t wm = __reduce_max_sync(~0u, __float_as_uint(wmax));
            sts32_if(lane, sb + O_OF + 4 * c, wm);
            if (c == 0) PSTAMP(8);
            bar_sync(7, 384);
            asm volatile("barrier.cluster.wait.aligned;" ::: "memory");
            if (c == 1) { tma_x_tile(sb, &tm_x, r, 1, 1); tma_x_tile(sb, &tm_x, r, 2, 2); }
            if (c == 0) {
                const uint4 wq = lds128(sb + O_OF), xq = lds128(sb + O_OF + 16), xr = lds128(sb + O_OF + 32), v0 = lds128(sb + O_MISC + 32), v1 = lds128(sb + O_MISC + 48);
                const uint32_t w1 = max(max(wq.x, wq.y), max(wq.z, wq.w)), x1 = max(max(max(xq.x, xq.y), max(xq.z, xq.w)), max(max(xr.x, xr.y), max(xr.z, xr.w)));
                const uint32_t vv = (r < 2) ? 0u : max(max(max(v0.x, v0.y), max(v0.z, v0.w)), max(max(v1.x, v1.y), max(v1.z, v1.w)));
                const uint32_t lo = (min(w1, 0x7f800000u) + 0xffffu) >> 16 | ((min(vv, 0x7f800000u) + 0xffffu) & 0xffff0000u), hi = (x1 & 0xffff0000u) | tag;
                uint32_t l0, h0, l1, h1, l2, h2;
                asm volatile("{\n.reg .pred p;\n.reg .u32 n, x, y;\n.reg .b64 v;\nsetp.eq.u32 p, %10, 0;\nmov.b64 v, {%8, %9};\n@p st.relaxed.gpu.global.b64 [%7], v;\nmov.u32 n, 0;\n"
                             "G_%=: ld.relaxed.gpu.global.b64 v, [%6];\nmov.b64 {%0, %1}, v;\nld.relaxed.gpu.global.b64 v, [%6+256];\nmov.b64 {%2, %3}, v;\n"
                             "ld.relaxed.gpu.global.b64 v, [%6+512];\nmov.b64 {%4, %5}, v;\n"
                             "xor.b32 x, %1, %9;\nxor.b32 y, %3, %9;\nor.b32 x, x, y;\nxor.b32 y, %5, %9;\nor.b32 x, x, y;\nand.b32 x, x, 0xffff;\n"
                             "setp.eq.u32 p, x, 0;\nvote.sync.all.pred p, p, 0xffffffff;\n@p bra.uni E_%=;\n"
                             "add.u32 n, n, 1;\nsetp.lt.u32 p, n, 4000000;\n@p bra.uni G_%=;\ntrap;\nE_%=:\n}"
                             : "=&r"(l0), "=&r"(h0), "=&r"(l1), "=&r"(h1), "=&r"(l2), "=&r"(h2)
                             : "l"(&g_norm[lane]), "l"(&g_norm[blockIdx.x]), "r"(lo), "r"(hi), "r"(lane) : "memory");
                const uint32_t lm = __vmaxu2(l0, __vmaxu2(l1, l2));
                const float fw = __uint_as_float(__reduce_max_sync(~0u, lm << 16));
                const float fv = __uint_as_float(__reduce_max_sync(~0u, lm & 0xffff0000u));
                const float xmax = __uint_as_float(__reduce_max_sync(~0u, max(h0, max(h1, h2)) & 0xffff0000u));
                const float G = 36.f * fw * fv;
                sts32_if(lane, sb + O_MISC + 4, __float_as_uint(G)); sts32_if(lane, sb + O_MISC + 8, __float_as_uint(G * xmax));
            }
        }
        if (c == 0) PSTAMP(12);
        bar_sync(6, 128);
        int s3 = 0;
        uint32_t roff = __shfl_sync(~0u, (r * 4 + c) * 2048 + (lane >> 4) * 512 + (lane & 2) * 128 + (lane & 1) * 64 + (lane & 12) * 4, lane);
#pragma unroll 1
        for (int s = 0; s < NSEG; s++) {
            const uint32_t l16 = opaque(l16c);
            const uint32_t vxa = sb + O_VX + (r == 2 ? s3 : (s & 1)) * 8192 + c * 2048 + l16;
            if (s == NSEG - 1) { bar_sync(3, 384); mbar_wait(sb + B_SC, s & 1); break; }
            uint4 vx[4];
            sts32_if(l16, sb + O_MISC + 16 + 4 * c, __reduce_max_sync(~0u, mmax));
            if (c == 0) STAMP(s, 5);
            {
                bar_sync(6, 128);
                const uint4 mm = lds128(sb + O_MISC + 16), cf = lds128(sb + O_MISC);
                const float bound = fmaxf(__uint_as_float(cf.z), __uint_as_float(cf.y) * (__uint_as_float(max(max(mm.x, mm.y), max(mm.z, mm.w))) * __uint_as_float(cf.x)));
                const uint32_t ebits = __reduce_max_sync(~0u, min(max(__float_as_uint(bound) & 0x7f800000u, 21u << 23), 254u << 23));
                const int j = s + 1 + (r >> 1);
                if (c == 1 && j < NSEG) mbar_wait(sb + B_X + 8 * (j % 3), (j / 3) & 1);
                if (r < 2) mbar_wait(sb + B_VX + 8 * (s & 1), (s >> 1) & 1);
                bar_sync(3, 384);
                vx[0] = lds128(vxa); vx[2] = lds128(vxa + 1024);
                if (c == 0) STAMP(s, 13);
                mbar_wait(sb + B_SC, s & 1);
                if (c == 0) STAMP(s, 6);
                float p[10];
                load_scores(p, sb + O_SC, 1280, l16);
                float mx = fmaxf(fmaxf(fmaxf(p[0], p[1]), fmaxf(p[2], p[3])), fmaxf(fmaxf(p[4], p[5]), fmaxf(p[6], p[7])));
                mx = quad_max(fmaxf(mx, fmaxf(p[8], p[9])));
                const uint4 vm = lds64x2(sb + O_VM + c * 512 + (l16 >> 1));
                vx[1] = lds128(vxa + 512); vx[3] = lds128(vxa + 1536);
                bar_arrive(4, 384);
                const float sc = __uint_as_float(lds32(sb + O_MISC + 12));
                const float mo = mx * SM_SCALE;
                uint32_t P[5];
#pragma unroll
                for (int n = 0; n < 5; n++) P[n] = pack_bf16(ex2(fmaf(p[2 * n], SM_SCALE, -mo)), ex2(fmaf(p[2 * n + 1], n == 3 ? sc : SM_SCALE, -mo)));
                if (c == 0) STAMP(s, 7);
                float o0[4], o1[4], sm[4];
                mma16816_z(sm, ONES, ONES, ONES, ONES, P[1], P[2]);
                mma16816_z(o0, vx[0].x, vx[0].y, vx[0].z, vx[0].w, P[1], P[2]);
                mma16816_z(o1, vx[2].x, vx[2].y, vx[2].z, vx[2].w, P[1], P[2]);
                mma16816(sm, ONES, ONES, ONES, ONES, P[3], P[4]);
                mma16816(o0, vx[1].x, vx[1].y, vx[1].z, vx[1].w, P[3], P[4]);
                mma16816(o1, vx[3].x, vx[3].y, vx[3].z, vx[3].w, P[3], P[4]);
                mma1688(sm, ONES, ONES, P[0]);
                mma1688(o0, vm.x, vm.y, P[0]);
                mma1688(o1, vm.z, vm.w, P[0]);
                const float sig = __uint_as_float((268u << 23) - ebits);
                const float r0 = rcp_fast(sm[0]) * sig, r1 = rcp_fast(sm[1]) * sig;
                stsm4t(sb + O_OF + c * 512 + l16, pack_bf16(o0[0] * r0, o0[1] * r1), pack_bf16(o0[2] * r0, o0[3] * r1),
                       pack_bf16(o1[0] * r0, o1[1] * r1), pack_bf16(o1[2] * r0, o1[3] * r1));
                bar_sync(6, 128);
                uint4 ob[4];
#pragma unroll
                for (int q = 0; q < 4; q++) ob[q] = ldsm4(sb + O_OF + q * 512 + l16);
                { const uint4 v = lds128(sb + O_WP + c * 512 + l16); a[92] = v.x; a[93] = v.y; a[94] = v.z; a[95] = v.w; }
                float m0[3][4], m1[3][4];
#pragma unroll
                for (int q = 0; q < 4; q++) {
#pragma unroll
                    for (int i = 0; i < 3; i++) {
                        const int k0 = (i * 8 + 2 * q) * 4;
                        if (q == 0) mma16816_z(m0[i], a[k0], a[k0 + 1], a[k0 + 2], a[k0 + 3], ob[q].x, ob[q].y);
                        else mma16816(m0[i], a[k0], a[k0 + 1], a[k0 + 2], a[k0 + 3], ob[q].x, ob[q].y);
                    }
#pragma unroll
                    for (int i = 0; i < 3; i++) {
                        const int k1 = (i * 8 + 2 * q + 1) * 4;
                        if (q == 0) mma16816_z(m1[i], a[k1], a[k1 + 1], a[k1 + 2], a[k1 + 3], ob[q].z, ob[q].w);
                        else mma16816(m1[i], a[k1], a[k1 + 1], a[k1 + 2], a[k1 + 3], ob[q].z, ob[q].w);
                    }
                }
                asm volatile("red.relaxed.gpu.global.add.noftz.v4.f16x2 [%0], {%1,%2,%3,%4};" :: "l"(reinterpret_cast<char*>(g_acc) + roff),
                    "r"(pack_f16(NRM(m0[0][0] + m1[0][0], r0), NRM(m0[0][2] + m1[0][2], r0))), "r"(pack_f16(NRM(m0[1][0] + m1[1][0], r0), NRM(m0[1][2] + m1[1][2], r0))),
                    "r"(pack_f16(NRM(m0[2][0] + m1[2][0], r0), NRM(m0[2][2] + m1[2][2], r0))), "r"(0x3c00u) : "memory");
                asm volatile("red.relaxed.gpu.global.add.noftz.v4.f16x2 [%0], {%1,%2,%3,%4};" :: "l"(reinterpret_cast<char*>(g_acc) + roff + 1024),
                    "r"(pack_f16(NRM(m0[0][1] + m1[0][1], r1), NRM(m0[0][3] + m1[0][3], r1))), "r"(pack_f16(NRM(m0[1][1] + m1[1][1], r1), NRM(m0[1][3] + m1[1][3], r1))),
                    "r"(pack_f16(NRM(m0[2][1] + m1[2][1], r1), NRM(m0[2][3] + m1[2][3], r1))), "r"(0x3c00u) : "memory");
                const unsigned t_red = clk();
                bar_arrive(5, 256);
                bar_arrive(13, 256);
                mbar_expect_if(l16 | c, sb + B_SC, r < 2 ? 3328 : 2560);
                mbar_expect_if(l16 | (c ^ 1) | (r >> 1), sb + B_VX + 8 * ((s + 1) & 1), 8192);
                sts32_if(l16 | (c ^ 3), sb + O_MISC, ebits - (14u << 23));
                if (c == 0) STAMPV(s, 8, t_red);
                if (ACC_PF && c == 2 && s + 4 < NSEG - 1)
                    asm volatile("prefetch.global.L2 [%0];" :: "l"(reinterpret_cast<const char*>(g_acc) + ((s + 4) * 96 + blockIdx.x) * 256 + (l16 & 96)) : "memory");
                const char* pbase = reinterpret_cast<const char*>(g_acc) + (s * 24576 + c * 2048) + ((l16 & 64) * 16 + (l16 & 256) + ((l16 & 128) >> 1) + (l16 & 48));
                uint4 v[6];
                {
                    const char* pb = reinterpret_cast<const char*>(__shfl_sync(~0u, (unsigned long long)pbase, l16 >> 4));
                    const unsigned t_go = t_red + (s < D_S0 ? D_EARLY : D_WAIT);
                    asm volatile("{\n.reg .pred p;\n.reg .u64 c;\n.reg .u32 lo;\n"
                                 "S_%=: mov.u64 c, %%clock64;\ncvt.u32.u64 lo, c;\nsub.u32 lo, lo, %0;\nsetp.lt.s32 p, lo, 0;\n@p bra.uni S_%=;\n}" :: "r"(t_go) : "memory");
#pragma unroll
                    for (int i = 0; i < 6; i++) v[i] = ldg_relaxed128(pb + (i >> 1) * 8192 + (i & 1) * 512);
                    pbase = pb;
                }
                int nretry = 0;
                auto convert = [&](int tau) {
                    const uint4 A = v[2 * tau], B = v[2 * tau + 1];
                    sts128(sb + O_MF + tau * 3072 + c * 512 + l16, f16x2_to_bf16x2(A.x), f16x2_to_bf16x2(B.x), f16x2_to_bf16x2(A.y), f16x2_to_bf16x2(B.y));
                    sts64(sb + O_MF + tau * 3072 + 2048 + (c >> 1) * 512 + (c & 1) * 8 + l16, f16x2_to_bf16x2(A.z), f16x2_to_bf16x2(B.z));
                };
                const uint32_t ok0 = __all_sync(~0u, (v[0].w & v[1].w) == 0x5000u);
                convert(0);
                asm volatile("{\n.reg .pred p;\nsetp.ne.u32 p, %0, 0;\n@p bar.arrive 2, 384;\n}" :: "r"(ok0) : "memory");
                mmax = absmax2(absmax2(absmax2(v[0].x, v[0].y), absmax2(v[0].z, v[1].x)), absmax2(v[1].y, v[1].z));
                sched_fence<0>(h);
                uint32_t ok1;
                asm volatile("{\n.reg .pred p, q;\n.reg .b32 x;\nlop3.b32 x, %1, %2, %3, 0x80;\nand.b32 x, x, %4;\n"
                             "setp.eq.u32 p, x, 0x5000;\nvote.sync.all.pred q, p, 0xffffffff;\nselp.u32 %0, 1, 0, q;\n}"
                             : "=r"(ok1) : "r"(v[2].w), "r"(v[3].w), "r"(v[4].w), "r"(v[5].w));
                convert(1); convert(2);
                asm volatile("{\n.reg .pred p;\nsetp.ne.u32 p, %0, 0;\n@p bar.arrive 15, 384;\n}" :: "r"(ok1) : "memory");
                if (!(ok0 & ok1)) {
                    v[0] = v[1] = make_uint4(0u, 0u, 0u, ok0 ? 0x5000u : 0u);
                    asm volatile("{\n.reg .pred p0, p1, p2, p3, p4, p5, q;\n.reg .u32 n, x;\nmov.u32 n, 0;\n"
                         "R_%=: setp.ne.u32 p0, %3, 0x5000;\nsetp.ne.u32 p1, %7, 0x5000;\nsetp.ne.u32 p2, %11, 0x5000;\n"
                         "setp.ne.u32 p3, %15, 0x5000;\nsetp.ne.u32 p4, %19, 0x5000;\nsetp.ne.u32 p5, %23, 0x5000;\n"
                         "@p0 ld.relaxed.gpu.global.v4.u32 {%0,%1,%2,%3}, [%25];\n@p1 ld.relaxed.gpu.global.v4.u32 {%4,%5,%6,%7}, [%25+512];\n"
                         "@p2 ld.relaxed.gpu.global.v4.u32 {%8,%9,%10,%11}, [%25+8192];\n@p3 ld.relaxed.gpu.global.v4.u32 {%12,%13,%14,%15}, [%25+8704];\n"
                         "@p4 ld.relaxed.gpu.global.v4.u32 {%16,%17,%18,%19}, [%25+16384];\n@p5 ld.relaxed.gpu.global.v4.u32 {%20,%21,%22,%23}, [%25+16896];\n"
                         "add.u32 %24, %24, 1;\nand.b32 x, %3, %7;\nand.b32 x, x, %11;\nand.b32 x, x, %15;\nand.b32 x, x, %19;\nand.b32 x, x, %23;\n"
                         "setp.eq.u32 q, x, 0x5000;\nvote.sync.all.pred q, q, 0xffffffff;\n@q bra.uni K_%=;\n"
                         "add.u32 n, n, 1;\nsetp.lt.u32 q, n, 2000000;\n@q bra.uni R_%=;\ntrap;\nK_%=:\n}"
                         : "+r"(v[0].x), "+r"(v[0].y), "+r"(v[0].z), "+r"(v[0].w), "+r"(v[1].x), "+r"(v[1].y), "+r"(v[1].z), "+r"(v[1].w),
                           "+r"(v[2].x), "+r"(v[2].y), "+r"(v[2].z), "+r"(v[2].w), "+r"(v[3].x), "+r"(v[3].y), "+r"(v[3].z), "+r"(v[3].w),
                           "+r"(v[4].x), "+r"(v[4].y), "+r"(v[4].z), "+r"(v[4].w), "+r"(v[5].x), "+r"(v[5].y), "+r"(v[5].z), "+r"(v[5].w), "+r"(nretry)
                         : "l"(pbase) : "memory");
                    if (!ok0) {
                        convert(0); bar_arrive(2, 384);
                        mmax = absmax2(absmax2(absmax2(v[0].x, v[0].y), absmax2(v[0].z, v[1].x)), absmax2(v[1].y, v[1].z));
                    }
                    if (!ok1) { convert(1); convert(2); bar_arrive(15, 384); }
                }
                if (c == 0) STAMP(s, 12);
                if (c == 0) STAMPV(s, 14, nretry);
                mmax = absmax2(mmax, absmax2(absmax2(absmax2(v[2].x, v[2].y), absmax2(v[2].z, v[3].x)), absmax2(absmax2(v[3].y, v[3].z), absmax2(v[4].x, v[4].y))));
                mmax = absmax2(mmax, absmax2(absmax2(v[4].z, v[5].x), absmax2(v[5].y, v[5].z))) & 0x7fff7fffu;
                { const float2 mf = __half22float2(*reinterpret_cast<__half2*>(&mmax)); mmax = max(__float_as_uint(mf.x), __float_as_uint(mf.y)); }
            }
            roff += 24576;
            s3 = (s3 == 2) ? 0 : s3 + 1;
        }
        {
            bar_sync(7, 384);
            if (c == 0) flag_inc_if(l16c, &g_flag[F_QKV + (4 * (NBLK - 1) + (h >> 3)) * 8]);
        }
    }
    if (warp == 8) PSTAMP(13);
    cluster_sync();
}

constexpr int NST = 10;
constexpr int G_RING = 0, G_EX = NST * 16384, G_OUT = G_EX + 32768, G_CARRY = G_OUT + 32768, G_OPS = G_CARRY + 512, G_BAR = G_OPS + 256, BG_SMEM = G_BAR + 256;
constexpr int GB_FULL = G_BAR, GB_EMPTY = G_BAR + 8 * NST, GB_W = G_BAR + 16 * NST;
static_assert(BG_SMEM <= 232448, "smem");

template <int ACC>
__device__ __forceinline__ void wgmma_n128_rs(float (&d)[64], uint32_t a0, uint32_t a1, uint32_t a2, uint32_t a3, uint64_t desc) {
    asm volatile("wgmma.mma_async.sync.aligned.m64n128k16.f32.bf16.bf16 "
        "{%0,%1,%2,%3,%4,%5,%6,%7,%8,%9,%10,%11,%12,%13,%14,%15,%16,%17,%18,%19,%20,%21,%22,%23,%24,%25,%26,%27,%28,%29,%30,%31,"
        "%32,%33,%34,%35,%36,%37,%38,%39,%40,%41,%42,%43,%44,%45,%46,%47,%48,%49,%50,%51,%52,%53,%54,%55,%56,%57,%58,%59,%60,%61,%62,%63}, "
        "{%64,%65,%66,%67}, %68, %69, 1, 1, 0;"
        : "+f"(d[0]), "+f"(d[1]), "+f"(d[2]), "+f"(d[3]), "+f"(d[4]), "+f"(d[5]), "+f"(d[6]), "+f"(d[7]),
          "+f"(d[8]), "+f"(d[9]), "+f"(d[10]), "+f"(d[11]), "+f"(d[12]), "+f"(d[13]), "+f"(d[14]), "+f"(d[15]),
          "+f"(d[16]), "+f"(d[17]), "+f"(d[18]), "+f"(d[19]), "+f"(d[20]), "+f"(d[21]), "+f"(d[22]), "+f"(d[23]),
          "+f"(d[24]), "+f"(d[25]), "+f"(d[26]), "+f"(d[27]), "+f"(d[28]), "+f"(d[29]), "+f"(d[30]), "+f"(d[31]),
          "+f"(d[32]), "+f"(d[33]), "+f"(d[34]), "+f"(d[35]), "+f"(d[36]), "+f"(d[37]), "+f"(d[38]), "+f"(d[39]),
          "+f"(d[40]), "+f"(d[41]), "+f"(d[42]), "+f"(d[43]), "+f"(d[44]), "+f"(d[45]), "+f"(d[46]), "+f"(d[47]),
          "+f"(d[48]), "+f"(d[49]), "+f"(d[50]), "+f"(d[51]), "+f"(d[52]), "+f"(d[53]), "+f"(d[54]), "+f"(d[55]),
          "+f"(d[56]), "+f"(d[57]), "+f"(d[58]), "+f"(d[59]), "+f"(d[60]), "+f"(d[61]), "+f"(d[62]), "+f"(d[63])
        : "r"(a0), "r"(a1), "r"(a2), "r"(a3), "l"(desc), "n"(ACC));
}
template <int ACC>
__device__ __forceinline__ void wgmma_n64_rs(float (&d)[64], uint32_t a0, uint32_t a1, uint32_t a2, uint32_t a3, uint64_t desc) {
    asm volatile("wgmma.mma_async.sync.aligned.m64n64k16.f32.bf16.bf16 "
        "{%0,%1,%2,%3,%4,%5,%6,%7,%8,%9,%10,%11,%12,%13,%14,%15,%16,%17,%18,%19,%20,%21,%22,%23,%24,%25,%26,%27,%28,%29,%30,%31}, "
        "{%32,%33,%34,%35}, %36, %37, 1, 1, 0;"
        : "+f"(d[0]), "+f"(d[1]), "+f"(d[2]), "+f"(d[3]), "+f"(d[4]), "+f"(d[5]), "+f"(d[6]), "+f"(d[7]),
          "+f"(d[8]), "+f"(d[9]), "+f"(d[10]), "+f"(d[11]), "+f"(d[12]), "+f"(d[13]), "+f"(d[14]), "+f"(d[15]),
          "+f"(d[16]), "+f"(d[17]), "+f"(d[18]), "+f"(d[19]), "+f"(d[20]), "+f"(d[21]), "+f"(d[22]), "+f"(d[23]),
          "+f"(d[24]), "+f"(d[25]), "+f"(d[26]), "+f"(d[27]), "+f"(d[28]), "+f"(d[29]), "+f"(d[30]), "+f"(d[31])
        : "r"(a0), "r"(a1), "r"(a2), "r"(a3), "l"(desc), "n"(ACC));
}
__device__ __forceinline__ void wait_flag(const unsigned* p, unsigned target) {
    asm volatile("{\n.reg .pred p;\n.reg .u32 n, v;\nmov.u32 n, 0;\n"
                 "W_%=: ld.acquire.gpu.global.u32 v, [%0];\nsub.u32 v, v, %1;\nsetp.ge.s32 p, v, 0;\n@p bra.uni D_%=;\nnanosleep.u32 " NSLEEP ";\n"
                 "add.u32 n, n, 1;\nsetp.lt.u32 p, n, 4000000;\n@p bra.uni W_%=;\ntrap;\nD_%=:\n}" :: "l"(p), "r"(target) : "memory");
}
template <int NS, int NT>
__device__ __forceinline__ void bg_mainloop(float (&d)[64], const uint32_t (&a)[144], uint32_t sb, int it, int lane) {
    int slot = it % NST, ph = (it / NST) & 1, prev = 0;
#pragma unroll
    for (int i = 0; i < NS; i++) {
        mbar_wait(sb + GB_FULL + 8 * slot, ph);
        const uint64_t desc = (uint64_t)(((sb + G_RING + slot * 16384) & 0x3FFFF) >> 4) | (1ull << 16) | (64ull << 32) | (1ull << 62);
        wg_fence();
#pragma unroll
        for (int k = 0; k < 512 / NT; k++) {
            const int u = (2048 / NT) * i + 4 * k;
            if (NT == 128) {
                if (i == 0 && k == 0) wgmma_n128_rs<0>(d, a[u], a[u + 1], a[u + 2], a[u + 3], desc);
                else wgmma_n128_rs<1>(d, a[u], a[u + 1], a[u + 2], a[u + 3], desc + 2 * k);
            } else {
                if (i == 0 && k == 0) wgmma_n64_rs<0>(d, a[u], a[u + 1], a[u + 2], a[u + 3], desc);
                else wgmma_n64_rs<1>(d, a[u], a[u + 1], a[u + 2], a[u + 3], desc + 2 * (k & 3) + (k >> 2) * 512);
            }
        }
        wg_commit();
        if (i > 0) {
            asm volatile("wgmma.wait_group.sync.aligned 1;" ::: "memory");
            mbar_arrive_if(lane, sb + GB_EMPTY + 8 * prev);
        }
        prev = slot;
        slot += 2;
        if (slot >= NST) { slot -= NST; ph ^= 1; }
    }
    wg_wait0();
    mbar_arrive_if(lane, sb + GB_EMPTY + 8 * prev);
}
template <bool SKIP, int NT>
__device__ __forceinline__ void bg_epilogue(float (&d)[64], uint32_t sb, int wg, int w, int lane, const CUtensorMap* tm_out, int col0, int tok0,
                                            const __nv_bfloat16* xa, const __nv_bfloat16* Dk) {
    constexpr int H = NT / 4;
    const int g = lane >> 2, t = lane & 3;
    const uint32_t ex = sb + G_EX + w * 4096 + lane * 16;
    float k[H];
    if (wg == 0) {
#pragma unroll
        for (int q = 0; q < H / 4; q++) sts128f(ex + q * 512, d[H + 4 * q], d[H + 4 * q + 1], d[H + 4 * q + 2], d[H + 4 * q + 3]);
#pragma unroll
        for (int i = 0; i < H; i++) k[i] = d[i];
    } else {
#pragma unroll
        for (int q = 0; q < H / 4; q++) sts128f(ex + 16384 + q * 512, d[4 * q], d[4 * q + 1], d[4 * q + 2], d[4 * q + 3]);
#pragma unroll
        for (int i = 0; i < H; i++) k[i] = d[H + i];
    }
    uint32_t xv[16], dv = 0;
    if (SKIP) {
        const __nv_bfloat16* xp = xa + (size_t)(tok0 + 64 * wg + 2 * t) * DM + col0 + 16 * w + 2 * g;
#pragma unroll
        for (int i = 0; i < 16; i++) xv[i] = ldg_nc32(xp + (8 * (i >> 1) + (i & 1)) * DM);
        dv = ldg_nc32(Dk + col0 + 16 * w + 2 * g);
    }
    if (SKIP && w == 0) asm volatile("cp.async.bulk.wait_group.read 0;" ::: "memory");
    bar_sync(1, 256);
#pragma unroll
    for (int q = 0; q < H / 4; q++) {
        const float4 o = lds128f(ex + (wg ^ 1) * 16384 + q * 512);
        k[4 * q] += o.x; k[4 * q + 1] += o.y; k[4 * q + 2] += o.z; k[4 * q + 3] += o.w;
    }
    if (SKIP) bar_sync(1, 256); else bar_sync(13, 288);
    const uint32_t ob = sb + G_OUT + wg * (NT == 128 ? 16384 : 4096) + (w >> 1) * 8192 + (g & 1) * 8;
    const uint32_t ch = (w & 1) * 4 + (g >> 1);
#pragma unroll
    for (int i = 0; i < H / 2; i++) {
        float v0 = k[4 * (i >> 1) + (i & 1)], v1 = k[4 * (i >> 1) + 2 + (i & 1)];
        if (SKIP) {
            const uint32_t p = pack_bf16(__uint_as_float(xv[i] << 16) * __uint_as_float(dv << 16), __uint_as_float(xv[i] & 0xffff0000u) * __uint_as_float(dv & 0xffff0000u));
            v0 += __uint_as_float(p << 16); v1 += __uint_as_float(p & 0xffff0000u);
        }
        const uint32_t n7 = 2 * t + (i & 1);
        sts64(ob + (8 * (i >> 1) + n7) * 128 + ((ch ^ n7) << 4), __float_as_uint(v0), __float_as_uint(v1));
    }
    fence_async_smem();
    if (SKIP) {
        bar_sync(4 + wg, 128);
        if (w == 0)
            asm volatile("{\n.reg .pred p;\nelect.sync _|p, 0xffffffff;\n"
                "@p cp.async.bulk.tensor.2d.global.shared::cta.bulk_group [%0, {%2, %4}], [%1];\n"
                "@p cp.async.bulk.tensor.2d.global.shared::cta.bulk_group [%0, {%3, %4}], [%1+8192];\n@p cp.async.bulk.commit_group;\n}"
                :: "l"(tm_out), "r"(sb + G_OUT + wg * 16384), "r"(col0), "r"(col0 + 32), "r"(tok0 + 64 * wg) : "memory");
    } else {
        bar_arrive(12, 288);
    }
}
__device__ __forceinline__ void s5_channel(int p, const __nv_bfloat16* Lre, const __nv_bfloat16* Lim, const __nv_bfloat16* logdt, float2& lam, float2& coef) {
    const float dt = __bfloat162float(__float2bfloat16(expf(__bfloat162float(logdt[p]))));
    const float lr = __bfloat162float(Lre[p]), li = __bfloat162float(Lim[p]);
    const float e = expf(dt * lr);
    float sn, cs;
    sincosf(dt * li, &sn, &cs);
    lam = make_float2(e * cs, e * sn);
    const float den = lr * lr + li * li;
    coef = make_float2(((lam.x - 1.f) * lr + lam.y * li) / den, (lam.y * lr - (lam.x - 1.f) * li) / den);
}
__device__ __forceinline__ float2 cfma(float2 a, float2 b, float2 c) {
    return make_float2(fmaf(a.x, b.x, fmaf(-a.y, b.y, c.x)), fmaf(a.x, b.y, fmaf(a.y, b.x, c.y)));
}
__device__ __forceinline__ uint4 ldg128(const void* p) { uint4 v; asm volatile("ld.global.v4.u32 {%0,%1,%2,%3}, [%4];" : "=r"(v.x), "=r"(v.y), "=r"(v.z), "=r"(v.w) : "l"(p) : "memory"); return v; }
__device__ __forceinline__ uint2 ldg64(const void* p) { uint2 v; asm volatile("ld.global.v2.u32 {%0,%1}, [%2];" : "=r"(v.x), "=r"(v.y) : "l"(p) : "memory"); return v; }

template <int MT>
__device__ __forceinline__ void bg_attention(uint32_t st0, uint32_t st1, int lane) {
    constexpr int NK = MT ? 5 : 3;
    const int g = lane >> 2, t = lane & 3;
    float sc[NK][4], sm2[4];
#pragma unroll
    for (int i = 0; i < 8; i++) {
        const uint32_t st = (i >> 2 ? st1 : st0) + (i & 3) * 512 + lane * 16;
        const uint4 q = ldsm4(st + MT * 2048), km = ldsm4(st + 8192), k0 = ldsm4(st + 4096);
        if (i == 0) {
            mma16816_z(sc[0], q.x, q.y, q.z, q.w, km.x, km.y); mma16816_z(sm2, q.x, q.y, q.z, q.w, km.z, km.w);
            mma16816_z(sc[1], q.x, q.y, q.z, q.w, k0.x, k0.y); mma16816_z(sc[2], q.x, q.y, q.z, q.w, k0.z, k0.w);
        } else {
            mma16816(sc[0], q.x, q.y, q.z, q.w, km.x, km.y); mma16816(sm2, q.x, q.y, q.z, q.w, km.z, km.w);
            mma16816(sc[1], q.x, q.y, q.z, q.w, k0.x, k0.y); mma16816(sc[2], q.x, q.y, q.z, q.w, k0.z, k0.w);
        }
        if (MT) {
            const uint4 k1 = ldsm4(st + 6144);
            if (i == 0) { mma16816_z(sc[NK - 2], q.x, q.y, q.z, q.w, k1.x, k1.y); mma16816_z(sc[NK - 1], q.x, q.y, q.z, q.w, k1.z, k1.w); }
            else { mma16816(sc[NK - 2], q.x, q.y, q.z, q.w, k1.x, k1.y); mma16816(sc[NK - 1], q.x, q.y, q.z, q.w, k1.z, k1.w); }
        }
    }
#pragma unroll
    for (int i = 0; i < 4; i++) sc[0][i] += sm2[i];
    if (2 * t > g) { sc[NK - 2][0] = -INFINITY; sc[NK - 1][2] = -INFINITY; }
    if (2 * t + 1 > g) { sc[NK - 2][1] = -INFINITY; sc[NK - 1][3] = -INFINITY; }
    sc[NK - 1][0] = sc[NK - 1][1] = -INFINITY;
    float ma = fmaxf(sc[0][0], sc[0][1]), mb = fmaxf(sc[0][2], sc[0][3]);
#pragma unroll
    for (int n = 1; n < NK; n++) { ma = fmaxf(ma, fmaxf(sc[n][0], sc[n][1])); mb = fmaxf(mb, fmaxf(sc[n][2], sc[n][3])); }
    ma = quad_max(ma) * SM_SCALE; mb = quad_max(mb) * SM_SCALE;
    uint32_t Pa[NK], Pb[NK];
#pragma unroll
    for (int n = 0; n < NK; n++) {
        Pa[n] = n == NK - 1 ? 0u : pack_bf16(ex2(fmaf(sc[n][0], SM_SCALE, -ma)), ex2(fmaf(sc[n][1], SM_SCALE, -ma)));
        Pb[n] = pack_bf16(ex2(fmaf(sc[n][2], SM_SCALE, -mb)), ex2(fmaf(sc[n][3], SM_SCALE, -mb)));
    }
    float sa[4], sbb[4];
    mma1688_z(sa, ONES, ONES, Pa[0]); mma1688_z(sbb, ONES, ONES, Pb[0]);
    mma16816(sa, ONES, ONES, ONES, ONES, Pa[1], Pa[2]); mma16816(sbb, ONES, ONES, ONES, ONES, Pb[1], Pb[2]);
    if (MT) { mma16816(sa, ONES, ONES, ONES, ONES, Pa[NK - 2], Pa[NK - 1]); mma16816(sbb, ONES, ONES, ONES, ONES, Pb[NK - 2], Pb[NK - 1]); }
    const float ra0 = rcp_fast(sa[0]), ra1 = rcp_fast(sa[1]), rb0 = rcp_fast(sbb[0]), rb1 = rcp_fast(sbb[1]);
    const uint32_t row = lane & 7;
    const uint32_t so = MT * 2048 + (lane >> 4) * 1024 + row * 128;
#pragma unroll
    for (int eh = 0; eh < 2; eh++) {
        const uint32_t st = eh ? st1 : st0;
        float2 vm[4]; uint4 v0[4], v1[4];
#pragma unroll
        for (int e4 = 0; e4 < 4; e4++) {
            vm[e4] = lds64f(st + 14336 + e4 * 256 + lane * 8);
            v0[e4] = lds128(st + 10240 + e4 * 1024 + lane * 16);
            if (MT) v1[e4] = lds128(st + 10240 + e4 * 1024 + 512 + lane * 16);
        }
        float oa[4][4], ob[4][4];
#pragma unroll
        for (int e4 = 0; e4 < 4; e4++) {
            mma1688_z(oa[e4], __float_as_uint(vm[e4].x), __float_as_uint(vm[e4].y), Pa[0]);
            mma1688_z(ob[e4], __float_as_uint(vm[e4].x), __float_as_uint(vm[e4].y), Pb[0]);
        }
#pragma unroll
        for (int e4 = 0; e4 < 4; e4++) {
            mma16816(oa[e4], v0[e4].x, v0[e4].y, v0[e4].z, v0[e4].w, Pa[1], Pa[2]);
            mma16816(ob[e4], v0[e4].x, v0[e4].y, v0[e4].z, v0[e4].w, Pb[1], Pb[2]);
        }
        if (MT) {
#pragma unroll
            for (int e4 = 0; e4 < 4; e4++) {
                mma16816(oa[e4], v1[e4].x, v1[e4].y, v1[e4].z, v1[e4].w, Pa[NK - 2], Pa[NK - 1]);
                mma16816(ob[e4], v1[e4].x, v1[e4].y, v1[e4].z, v1[e4].w, Pb[NK - 2], Pb[NK - 1]);
            }
        }
#pragma unroll
        for (int e4 = 0; e4 < 4; e4++)
            stsm4t(st + so + (((2 * e4 + ((lane >> 3) & 1)) ^ row) << 4), pack_bf16(oa[e4][0] * ra0, oa[e4][1] * ra1), pack_bf16(oa[e4][2] * ra0, oa[e4][3] * ra1),
                   pack_bf16(ob[e4][0] * rb0, ob[e4][1] * rb1), pack_bf16(ob[e4][2] * rb0, ob[e4][3] * rb1));
    }
}
__device__ __forceinline__ bool wait_either(const unsigned* pa, unsigned ta, bool allow_a, const unsigned* pg, unsigned tg, bool allow_g) {
    uint32_t res;
    asm volatile("{\n.reg .pred p, qa, qg;\n.reg .u32 n, v, u;\nmov.u32 n, 0;\nsetp.ne.u32 qa, %5, 0;\nsetp.ne.u32 qg, %6, 0;\n"
                 "W_%=: mov.u32 %0, 1;\n@!qa bra.uni G_%=;\nld.acquire.gpu.global.u32 v, [%1];\nsub.u32 v, v, %2;\nsetp.ge.s32 p, v, 0;\n@p bra.uni D_%=;\n"
                 "G_%=: mov.u32 %0, 0;\n@!qg bra.uni S_%=;\nld.acquire.gpu.global.u32 u, [%3];\nsub.u32 u, u, %4;\nsetp.ge.s32 p, u, 0;\n@p bra.uni D_%=;\nS_%=: "
                 "nanosleep.u32 " NSLEEP ";\nadd.u32 n, n, 1;\nsetp.lt.u32 p, n, 4000000;\n@p bra.uni W_%=;\ntrap;\n"
                 "D_%=: fence.proxy.async.global;\n}"
                 : "=r"(res) : "l"(pa), "r"(ta), "l"(pg), "r"(tg), "r"((uint32_t)allow_a), "r"((uint32_t)allow_g) : "memory");
    return res != 0;
}

__global__ void __launch_bounds__(384, 1)
bg_kernel(const __grid_constant__ CUtensorMap tm_xa, const __grid_constant__ CUtensorMap tm_wo, const __grid_constant__ CUtensorMap tm_out,
          const __nv_bfloat16* __restrict__ xa, const __nv_bfloat16* __restrict__ Lre, const __nv_bfloat16* __restrict__ Lim,
          const __nv_bfloat16* __restrict__ Bre, const __nv_bfloat16* __restrict__ Bim, const __nv_bfloat16* __restrict__ Cre,
          const __nv_bfloat16* __restrict__ Cim, const __nv_bfloat16* __restrict__ logdt, const __nv_bfloat16* __restrict__ Dk, float* __restrict__ out) {
    extern __shared__ __align__(1024) uint8_t smem_raw[];
    const uint32_t sb = smem_u32(smem_raw);
    const int lane = threadIdx.x & 31;
    const int warp = __shfl_sync(~0u, threadIdx.x >> 5, 0);
    const int wg = warp >> 2, w = warp & 3, b = blockIdx.x;
    const int nt = b % 9, kq = b / 9;
    BSTAMP(0);
    if (threadIdx.x == 0) {
        if (sb & 1023u) __trap();
        for (int i = 0; i < NST; i++) { mbar_init(sb + GB_FULL + 8 * i, 1); mbar_init(sb + GB_EMPTY + 8 * i, 4); }
        mbar_init(sb + GB_W, 1);
        asm volatile("fence.mbarrier_init.release.cluster;" ::: "memory");
        mbar_expect(sb + GB_W, (b < 18 ? 64 : 128) * 1152);
        sts32(sb + G_BAR + 248, atomicAdd(&g_ticket_bg, 1u) / 36u + 1u);
    }
    __syncthreads();
    if (wg == 2) {
        asm volatile("setmaxnreg.dec.sync.aligned.u32 24;");
        if (w == 0) {
            int slot = 0, ph = 1;
            auto next = [&]() { if (++slot == NST) { slot = 0; ph ^= 1; } };
            bar_sync(6, 288);
            if (b < 18) {
#pragma unroll 1
                for (int i = 0; i < 144; i++) {
                    const int blk = i / 9, kb = i - 9 * blk, it = (blk >> 1) * 18 + (blk & 1) + 2 * kb;
                    slot = it % NST;
                    mbar_wait(sb + GB_EMPTY + 8 * slot, ((it / NST) & 1) ^ 1);
                    asm volatile("{\n.reg .pred p;\nelect.sync _|p, 0xffffffff;\n@p mbarrier.arrive.expect_tx.shared::cta.b64 _, [%2], 16384;\n"
                        "@p cp.async.bulk.tensor.5d.shared::cluster.global.mbarrier::complete_tx::bytes [%0], [%1, {%3, %4, %4, %4, %5}], [%2];\n}"
                        :: "r"(sb + G_RING + slot * 16384), "l"(&tm_xa), "r"(sb + GB_FULL + 8 * slot), "r"(kb * 64), "r"(0), "r"(blk) : "memory");
                }
                slot = 144 % NST; ph = ((144 / NST) & 1) ^ 1;
            }
            const unsigned ep = lds32(sb + G_BAR + 248);
            auto slabs = [&](const char* src, int ns) {
                asm volatile("fence.proxy.async.global;" ::: "memory");
#pragma unroll 1
                for (int i = 0; i < ns; i++) {
                    mbar_wait(sb + GB_EMPTY + 8 * slot, ph);
                    asm volatile("{\n.reg .pred p;\nelect.sync _|p, 0xffffffff;\n@p mbarrier.arrive.expect_tx.shared::cta.b64 _, [%2], 16384;\n"
                        "@p cp.async.bulk.shared::cluster.global.mbarrier::complete_tx::bytes [%0], [%1], 16384, [%2];\n}"
                        :: "r"(sb + G_RING + slot * 16384), "l"(src + (size_t)((i & 1) * (ns >> 1) + (i >> 1)) * (SEQ * 128)), "r"(sb + GB_FULL + 8 * slot) : "memory");
                    next();
                }
            };
            if (b >= 18) {
#pragma unroll 1
                for (int blk = kq - 2; blk < 16; blk += 2) {
                    wait_flag(&g_flag[F_H + blk * 8], 18 * ep);
                    slabs(reinterpret_cast<const char*>(g_h) + blk * 16384, 18);
                }
            }
            bar_sync(6, 288);
#pragma unroll 1
            for (int na = nt < 8 ? 0 : NBLK, ng = 0, k = 0; ng < NBLK; k++) {
                const bool att = wait_either(&g_flag[F_QKV + (min(na, NBLK - 1) * 4 + kq) * 8], 24 * ep, na < NBLK && na <= ng + 1,
                                             &g_flag[F_OX + (ng * 4 + kq) * 8], 8 * ep, ng < na);
                sts32_if(lane, sb + G_OPS + 4 * k, att);
                __syncwarp();
                if (att) {
                    {
#pragma unroll 1
                        for (int i = 0; i < (na < NBIG ? 8 : 4); i++) {
                            const int hf = (i >> 1) & 1;
                            const char* rec = reinterpret_cast<const char*>(g_qkv) + (size_t)((blk_seg0(na) + 2 * (i >> 2) + (i & 1)) * NH + 8 * kq + nt) * REC;
                            mbar_wait(sb + GB_EMPTY + 8 * slot, ph);
                            asm volatile("{\n.reg .pred p;\nelect.sync _|p, 0xffffffff;\n@p mbarrier.arrive.expect_tx.shared::cta.b64 _, [%4], 15360;\n"
                                "@p cp.async.bulk.shared::cluster.global.mbarrier::complete_tx::bytes [%0], [%1], 10240, [%4];\n"
                                "@p cp.async.bulk.shared::cluster.global.mbarrier::complete_tx::bytes [%0+10240], [%2], 4096, [%4];\n"
                                "@p cp.async.bulk.shared::cluster.global.mbarrier::complete_tx::bytes [%0+14336], [%3], 1024, [%4];\n}"
                                :: "r"(sb + G_RING + slot * 16384), "l"(rec + hf * 10240), "l"(rec + 20480 + hf * 4096), "l"(rec + 28672 + hf * 1024),
                                   "r"(sb + GB_FULL + 8 * slot) : "memory");
                            next();
                        }
                    }
                    na++;
                } else {
                    const char* src = reinterpret_cast<const char*>(g_ox) + (size_t)kq * 16 * SEQ * 128 + blk_seg0(ng) * 4096;
                    if (ng < NBIG) slabs(src, 16);
                    else {
#pragma unroll 1
                        for (int i = 0; i < 8; i++) {
                            mbar_wait(sb + GB_EMPTY + 8 * slot, ph);
                            asm volatile("{\n.reg .pred p;\nelect.sync _|p, 0xffffffff;\n@p mbarrier.arrive.expect_tx.shared::cta.b64 _, [%2], 16384;\n"
                                "@p cp.async.bulk.shared::cluster.global.mbarrier::complete_tx::bytes [%0], [%1], 8192, [%2];\n"
                                "@p cp.async.bulk.shared::cluster.global.mbarrier::complete_tx::bytes [%0+8192], [%1+262144], 8192, [%2];\n}"
                                :: "r"(sb + G_RING + slot * 16384), "l"(src + (size_t)((i & 1) * 8 + (i & 6)) * (SEQ * 128)), "r"(sb + GB_FULL + 8 * slot) : "memory");
                            next();
                        }
                    }
                    ng++;
                }
            }
        } else if (w == 1) {
            if (b < 18) {
#pragma unroll 1
                for (int blk = 0; blk < 16; blk++) {
                    bar_sync(8 + (blk & 1), 160);
                    asm volatile("{\n.reg .pred p;\nelect.sync _|p, 0xffffffff;\n@p cp.async.bulk.global.shared::cta.bulk_group [%0], [%1], 16384;\n"
                        "@p cp.async.bulk.commit_group;\ncp.async.bulk.wait_group 0;\nfence.proxy.async.global;\n}"
                        :: "l"(reinterpret_cast<char*>(g_h) + ((size_t)b * SEQ + blk * 128) * 128), "r"(sb + G_OUT + (blk & 1) * 16384) : "memory");
                    bar_arrive(10 + (blk & 1), 160);
                    flag_inc_if(lane, &g_flag[F_H + blk * 8]);
                }
            }
            if (nt < 8) {
#pragma unroll 1
                for (int na = 0; na < NBLK; na++) {
                    {
                        const int ns = na < NBIG ? 8 : 4;
                        bar_sync(7, 288);
                        const int it = lds32(sb + G_OPS + 252);
                        if (lane < ns) {
                            asm volatile("cp.async.bulk.global.shared::cta.bulk_group [%0], [%1], 4096;\ncp.async.bulk.commit_group;\ncp.async.bulk.wait_group.read 0;\n"
                                "mbarrier.arrive.shared::cta.b64 _, [%2], 4;\ncp.async.bulk.wait_group 0;\nfence.proxy.async.global;"
                                :: "l"(reinterpret_cast<char*>(g_ox) + ((size_t)((8 * kq + nt) * 2 + ((lane >> 1) & 1)) * SEQ + (blk_seg0(na) + 2 * (lane >> 2) + (lane & 1)) * 32) * 128),
                                   "r"(sb + G_RING + ((it + lane) % NST) * 16384), "r"(sb + GB_EMPTY + 8 * ((it + lane) % NST)) : "memory");
                        }
                        __syncwarp();
                        bar_arrive(14, 288);
                        flag_inc_if(lane, &g_flag[F_OX + (na * 4 + kq) * 8]);
                    }
                }
            }
        } else if (w == 2) {
            const unsigned ep = lds32(sb + G_BAR + 248);
#pragma unroll 1
            for (int blk = 0; blk < NBLK; blk++) {
                const bool last = blk == NBLK - 1, add = kq || last;
                bar_arrive(13, 288);
                bar_sync(12, 288);
                if (add) { wait_flag(&g_flag[F_OUT + (blk * 9 + nt) * 8], ep); asm volatile("fence.proxy.async.global;" ::: "memory"); }
#pragma unroll 1
                for (int i = 0; i < (blk < NBIG ? 4 : 2); i++) {
                    const uint32_t src = sb + G_OUT + i * 8192;
                    const int c0 = DM + 64 * nt + (i & 1) * 32, c1 = blk_seg0(blk) * 32 + (i >> 1) * 64;
                    if (add) asm volatile("{\n.reg .pred p;\nelect.sync _|p, 0xffffffff;\n@p cp.reduce.async.bulk.tensor.2d.global.shared::cta.add.bulk_group [%0, {%2, %3}], [%1];\n}"
                                 :: "l"(&tm_out), "r"(src), "r"(c0), "r"(c1) : "memory");
                    else asm volatile("{\n.reg .pred p;\nelect.sync _|p, 0xffffffff;\n@p cp.async.bulk.tensor.2d.global.shared::cta.bulk_group [%0, {%2, %3}], [%1];\n}"
                                 :: "l"(&tm_out), "r"(src), "r"(c0), "r"(c1) : "memory");
                    if (add && blk < NBIG - 1) spin_until(clk(), RED_GAP);
                }
                asm volatile("cp.async.bulk.commit_group;\ncp.async.bulk.wait_group 0;\nfence.proxy.async.global;" ::: "memory");
                __syncwarp();
                if (!add) flag_inc_if(lane, &g_flag[F_OUT + (blk * 9 + nt) * 8]);
                if (!kq && blk == NBLK - 4) {
                    float4* z = reinterpret_cast<float4*>(out + (size_t)(SEQ - 64 + (lane >> 4)) * (2 * DM) + DM + 64 * nt) + (lane & 15);
#pragma unroll 1
                    for (int i = 0; i < 32; i++) z[i * (4 * DM / 4)] = make_float4(0.f, 0.f, 0.f, 0.f);
                    __syncwarp();
                    flag_inc_if(lane, &g_flag[F_OUT + ((NBLK - 1) * 9 + nt) * 8]);
                }
            }
        }
    } else {
        asm volatile("setmaxnreg.inc.sync.aligned.u32 240;");
        const int g = lane >> 2, t = lane & 3, tid = threadIdx.x;
        uint32_t a[144];
        float d[64];
        if (b < 18) {
            if (tid < 64)
                asm volatile("cp.async.bulk.shared::cluster.global.mbarrier::complete_tx::bytes [%0], [%1], 1152, [%2];"
                    :: "r"(sb + tid * 1168), "l"((tid < 32 ? Bre : Bim) + (size_t)(32 * b + (tid & 31)) * DM), "r"(sb + GB_W) : "memory");
            float2 lam, coef;
            s5_channel(32 * b + 8 * w + g, Lre, Lim, logdt, lam, coef);
            float2 l32 = lam;
#pragma unroll
            for (int i = 0; i < 5; i++) l32 = make_float2(l32.x * l32.x - l32.y * l32.y, 2.f * l32.x * l32.y);
            __syncwarp();
            mbar_wait(sb + GB_W, 0);
            const uint32_t ap = sb + (((lane >> 3) & 1) * 32 + 8 * w + (lane & 7)) * 1168 + (lane >> 4) * 16;
#pragma unroll
            for (int ks = 0; ks < 36; ks++) { const uint4 v = ldsm4(ap + ks * 32); a[4 * ks] = v.x; a[4 * ks + 1] = v.y; a[4 * ks + 2] = v.z; a[4 * ks + 3] = v.w; }
            bar_sync(1, 256);
            bar_arrive(6, 288);
            BSTAMP(1);
#pragma unroll 1
            for (int blk = wg; blk < 16; blk += 2) {
                bg_mainloop<9, 128>(d, a, sb, (blk >> 1) * 18 + wg, lane);
                float2 e = make_float2(0.f, 0.f);
#pragma unroll
                for (int i = 0; i < 32; i++) e = cfma(lam, e, make_float2(d[4 * (i >> 1) + (i & 1)], d[4 * (i >> 1) + 2 + (i & 1)]));
                float2 cin = make_float2(0.f, 0.f);
                if (blk > 0) { bar_sync(2 + (wg ^ 1), 256); cin = lds64f(sb + G_CARRY + (wg ^ 1) * 256 + (8 * w + g) * 8); }
                float2 mine = cin;
#pragma unroll
                for (int q = 0; q < 4; q++) {
                    const float2 eq = make_float2(__shfl_sync(~0u, e.x, (lane & 28) + q), __shfl_sync(~0u, e.y, (lane & 28) + q));
                    cin = cfma(l32, cin, eq);
                    if (t == q + 1) mine = cin;
                }
                if (blk < 15) {
                    if (t == 0) sts64(sb + G_CARRY + wg * 256 + (8 * w + g) * 8, __float_as_uint(cin.x), __float_as_uint(cin.y));
                    bar_arrive(2 + wg, 256);
                }
                const uint32_t hs = sb + G_OUT + wg * 16384 + t * 4096 + (g & 3) * 4;
                const uint32_t ch = 2 * w + (g >> 2);
                if (blk >= 2) bar_sync(10 + wg, 160);
#pragma unroll
                for (int i = 0; i < 32; i++) {
                    mine = cfma(lam, mine, make_float2(d[4 * (i >> 1) + (i & 1)], d[4 * (i >> 1) + 2 + (i & 1)]));
                    sts32(hs + i * 128 + ((ch ^ (i & 7)) << 4), pack_bf16(mine.x, mine.y));
                }
                fence_async_smem();
                bar_arrive(8 + wg, 160);
            }
            bar_sync(10 + wg, 160);
        } else {
            if (tid < 128)
                asm volatile("cp.async.bulk.shared::cluster.global.mbarrier::complete_tx::bytes [%0], [%1], 1152, [%2];"
                    :: "r"(sb + tid * 1168), "l"((tid < 64 ? Cre : Cim) + (size_t)(64 * nt + (tid & 63)) * DM), "r"(sb + GB_W) : "memory");
            for (int p = tid; p < DM; p += 256) {
                float2 lam, coef;
                s5_channel(p, Lre, Lim, logdt, lam, coef);
                sts64(sb + G_EX + p * 8, __float_as_uint(2.f * coef.x), __float_as_uint(2.f * coef.y));
            }
            bar_sync(1, 256);
            mbar_wait(sb + GB_W, 0);
            const uint32_t cp = sb + (16 * w + 2 * g) * 1168 + (288 * wg + t) * 2;
#pragma unroll
            for (int u = 0; u < 72; u++) {
                const float2 c2 = lds64f(sb + G_EX + (288 * wg + 4 * u + t) * 8);
#pragma unroll
                for (int f = 0; f < 2; f++) {
                    unsigned short r16, i16;
                    asm volatile("ld.shared.u16 %0, [%1];" : "=h"(r16) : "r"(cp + f * 1168 + u * 8) : "memory");
                    asm volatile("ld.shared.u16 %0, [%1];" : "=h"(i16) : "r"(cp + (64 + f) * 1168 + u * 8) : "memory");
                    const float cr = __uint_as_float((uint32_t)r16 << 16), ci = __uint_as_float((uint32_t)i16 << 16);
                    a[2 * u + f] = pack_bf16(cr * c2.x - ci * c2.y, -(cr * c2.y + ci * c2.x));
                }
            }
            bar_sync(1, 256);
            bar_arrive(6, 288);
            BSTAMP(1);
#pragma unroll 1
            for (int j = 0; j < 8; j++) {
                bg_mainloop<9, 128>(d, a, sb, j * 18 + wg, lane);
                bg_epilogue<true, 128>(d, sb, wg, w, lane, &tm_out, 64 * nt, (2 * j + kq - 2) * 128, xa, Dk);
            }
        }
        if (w == 0) asm volatile("cp.async.bulk.wait_group 0;" ::: "memory");
        bar_sync(1, 256);
        BSTAMP(2);
        if (warp == 0)
            asm volatile("{\n.reg .pred p;\nelect.sync _|p, 0xffffffff;\n@p mbarrier.arrive.expect_tx.shared::cta.b64 _, [%2], 131072;\n"
                "@p cp.async.bulk.tensor.2d.shared::cluster.global.mbarrier::complete_tx::bytes [%0], [%1, {%3, %4}], [%2];\n"
                "@p cp.async.bulk.tensor.2d.shared::cluster.global.mbarrier::complete_tx::bytes [%0+32768], [%1, {%3, %5}], [%2];\n"
                "@p cp.async.bulk.tensor.2d.shared::cluster.global.mbarrier::complete_tx::bytes [%0+65536], [%1, {%3, %6}], [%2];\n"
                "@p cp.async.bulk.tensor.2d.shared::cluster.global.mbarrier::complete_tx::bytes [%0+98304], [%1, {%3, %7}], [%2];\n}"
                :: "r"(sb), "l"(&tm_wo), "r"(sb + GB_W), "r"(64 * nt), "r"(1024 * kq), "r"(1024 * kq + 256), "r"(1024 * kq + 512), "r"(1024 * kq + 768) : "memory");
        mbar_wait(sb + GB_W, 1);
        {
            const uint32_t base = sb + wg * 65536 + 4 * t * 128 + (g & 3) * 4, ch = 2 * w + (g >> 2), r7 = (4 * t) & 7;
#pragma unroll
            for (int ks = 0; ks < 32; ks++) {
                const uint32_t w0 = lds32(base + ks * 2048 + ((ch ^ r7) << 4)), w1 = lds32(base + ks * 2048 + 256 + ((ch ^ (r7 + 2)) << 4));
                const uint32_t w2 = lds32(base + ks * 2048 + 128 + ((ch ^ (r7 + 1)) << 4)), w3 = lds32(base + ks * 2048 + 384 + ((ch ^ (r7 + 3)) << 4));
                a[4 * ks] = __byte_perm(w0, w1, 0x5410); a[4 * ks + 1] = __byte_perm(w0, w1, 0x7632);
                a[4 * ks + 2] = __byte_perm(w2, w3, 0x5410); a[4 * ks + 3] = __byte_perm(w2, w3, 0x7632);
            }
        }
        bar_sync(1, 256);
        bar_arrive(6, 288);
        BSTAMP(3);
#pragma unroll 1
        for (int na = 0, ng = 0, it = 144, k = 0; ng < NBLK; k++) {
            mbar_wait(sb + GB_FULL + 8 * ((it + wg) % NST), ((it + wg) / NST) & 1);
            if (__shfl_sync(~0u, lds32(sb + G_OPS + 4 * k), 0)) {
                {
                    if (na < NBIG || (w >> 1) == wg) {
                        const int i0 = it + wg + (na < NBIG ? 4 * (w >> 1) : 0), i1 = i0 + 2;
                        mbar_wait(sb + GB_FULL + 8 * (i0 % NST), (i0 / NST) & 1);
                        mbar_wait(sb + GB_FULL + 8 * (i1 % NST), (i1 / NST) & 1);
                        BSTAMP(8 + na * 4);
                        if ((w ^ wg) & 1) bg_attention<1>(sb + G_RING + (i0 % NST) * 16384, sb + G_RING + (i1 % NST) * 16384, lane);
                        else bg_attention<0>(sb + G_RING + (i0 % NST) * 16384, sb + G_RING + (i1 % NST) * 16384, lane);
                        fence_async_smem();
                    }
                    if (na > 0) bar_sync(14, 288);
                    if (tid == 0) sts32(sb + G_OPS + 252, it);
                    bar_arrive(7, 288);
                    bar_sync(1, 256);
                    BSTAMP(9 + na * 4);
                    it += na < NBIG ? 8 : 4;
                }
                na++;
            } else if (ng < NBIG) {
                bg_mainloop<8, 128>(d, a, sb, it + wg, lane);
                BSTAMP(10 + ng * 4);
                bg_epilogue<false, 128>(d, sb, wg, w, lane, &tm_out, 0, 0, xa, Dk);
                BSTAMP(11 + ng * 4);
                it += 16; ng++;
            } else {
                bg_mainloop<4, 64>(d, a, sb, it + wg, lane);
                BSTAMP(10 + ng * 4);
                bg_epilogue<false, 64>(d, sb, wg, w, lane, &tm_out, 0, 0, xa, Dk);
                BSTAMP(11 + ng * 4);
                it += 8; ng++;
            }
        }
        if (nt < 8) bar_sync(14, 288);
    }
    asm volatile("griddepcontrol.wait;" ::: "memory");
}

typedef CUresult (*EncodeFn)(CUtensorMap*, CUtensorMapDataType, cuuint32_t, void*, const cuuint64_t*, const cuuint64_t*, const cuuint32_t*, const cuuint32_t*,
                             CUtensorMapInterleave, CUtensorMapSwizzle, CUtensorMapL2promotion, CUtensorMapFloatOOBfill);
}

extern "C" void kernel_launch(void* const* d_in, const int* in_sizes, int n_in, void* d_out, int out_size) {
    typedef const __nv_bfloat16* bp;
    bp Ax = (bp)d_in[0], Lre = (bp)d_in[1], Lim = (bp)d_in[2], Bre = (bp)d_in[3], Bim = (bp)d_in[4], Cre = (bp)d_in[5], Cim = (bp)d_in[6],
       logdt = (bp)d_in[7], Dk = (bp)d_in[8], Bx = (bp)d_in[9], mem0 = (bp)d_in[10], Wq = (bp)d_in[11], Wk = (bp)d_in[12], Wv = (bp)d_in[13], Wo = (bp)d_in[14];
    float* out = (float*)d_out;
    static EncodeFn enc = nullptr;
    if (!enc) {
        void* fn = nullptr; cudaDriverEntryPointQueryResult qr;
        cudaGetDriverEntryPoint("cuTensorMapEncodeTiled", &fn, cudaEnableDefault, &qr);
        enc = (EncodeFn)fn;
        cudaFuncSetAttribute(chain_kernel, cudaFuncAttributeMaxDynamicSharedMemorySize, CHAIN_SMEM);
        cudaFuncSetAttribute(bg_kernel, cudaFuncAttributeMaxDynamicSharedMemorySize, BG_SMEM);
    }
    const cuuint32_t es[5] = {1, 1, 1, 1, 1};
    auto map2d = [&](CUtensorMap* tm, CUtensorMapDataType dt, const void* p, cuuint64_t d0, cuuint64_t d1, cuuint64_t stride, cuuint32_t b0, cuuint32_t b1) {
        cuuint64_t gd[2] = {d0, d1}, gs[1] = {stride}; cuuint32_t bd[2] = {b0, b1};
        enc(tm, dt, 2, (void*)p, gd, gs, bd, es, CU_TENSOR_MAP_INTERLEAVE_NONE, CU_TENSOR_MAP_SWIZZLE_128B, CU_TENSOR_MAP_L2_PROMOTION_L2_128B,
            CU_TENSOR_MAP_FLOAT_OOB_FILL_NONE);
    };
    CUtensorMap tm_x, tm_q, tm_k, tm_v, tm_xa, tm_wo, tm_out;
    map2d(&tm_x, CU_TENSOR_MAP_DATA_TYPE_BFLOAT16, Bx, DM, SEQ, DM * 2, 64, 32);
    map2d(&tm_q, CU_TENSOR_MAP_DATA_TYPE_BFLOAT16, Wq, HD, DM, HD * 2, 64, 192);
    map2d(&tm_k, CU_TENSOR_MAP_DATA_TYPE_BFLOAT16, Wk, HD, DM, HD * 2, 64, 192);
    map2d(&tm_v, CU_TENSOR_MAP_DATA_TYPE_BFLOAT16, Wv, HD, DM, HD * 2, 64, 192);
    map2d(&tm_wo, CU_TENSOR_MAP_DATA_TYPE_BFLOAT16, Wo, DM, HD, DM * 2, 64, 256);
    map2d(&tm_out, CU_TENSOR_MAP_DATA_TYPE_FLOAT32, out, 2 * DM, SEQ, 2 * DM * 4, 32, 64);
    {
        cuuint64_t gd[5] = {DM, 2, 4, 16, 16}, gs[4] = {DM * 2, 32 * DM * 2, 2 * DM * 2, 128 * DM * 2}; cuuint32_t bd[5] = {64, 2, 4, 16, 1};
        enc(&tm_xa, CU_TENSOR_MAP_DATA_TYPE_BFLOAT16, 5, (void*)Ax, gd, gs, bd, es, CU_TENSOR_MAP_INTERLEAVE_NONE, CU_TENSOR_MAP_SWIZZLE_128B,
            CU_TENSOR_MAP_L2_PROMOTION_L2_128B, CU_TENSOR_MAP_FLOAT_OOB_FILL_NONE);
    }
    cudaStream_t st = cudaStreamPerThread;
    chain_kernel<<<96, 384, CHAIN_SMEM, st>>>(tm_x, tm_q, tm_k, tm_v, Bx, mem0, Wo);
    cudaLaunchConfig_t cfg = {};
    cfg.gridDim = dim3(36); cfg.blockDim = dim3(384); cfg.dynamicSmemBytes = BG_SMEM; cfg.stream = st;
    cudaLaunchAttribute at[1];
    at[0].id = cudaLaunchAttributeProgrammaticStreamSerialization; at[0].val.programmaticStreamSerializationAllowed = 1;
    cfg.attrs = at; cfg.numAttrs = 1;
    cudaLaunchKernelEx(&cfg, bg_kernel, tm_xa, tm_wo, tm_out, Ax, Lre, Lim, Bre, Bim, Cre, Cim, logdt, Dk, out);
}
```

```cpp
#include <cuda_runtime.h>
#include <cuda.h>
#include <cuda_bf16.h>
#include <cuda_fp16.h>
#include <stdint.h>

#define D_WAIT 740

#define RED_GAP 720
#define ACC_PF 1
#define QDEP 0
#define NSLEEP "40"
#define D_S0 34
#define D_EARLY 820
#define NORM_LATE 0
#define NRM(x, r) (NORM_LATE ? (x) * (r) : (x))
#define ACC_LS 256
#define ACC_BS 32768
#define ACC_IL 1
#define ACC_IS 0
#define TAILPAT 0xb
#define TRIG -1
#define XAFTER 2
#define VPOS 0
#define MPOS 0
#define NBIG 14

namespace {

constexpr int DM = 576, NH = 32, SEQ = 2048, NSEG = 64, HD = 4096;

__device__ uint4 g_acc_raw[2 * 131072];
__device__ __forceinline__ uint32_t acc_step(int s) { return (s / ACC_IL) * ACC_BS + (s % ACC_IL) * ACC_IS; }
__device__ uint4 g_ox[NH * 2 * SEQ * 8];
constexpr int REC = 30720;
__device__ uint4 g_qkv[NSEG * NH * (REC / 16)];
__device__ uint4 g_h[18 * SEQ * 8];
constexpr int NFLAG = 6144, F_QKV = 0, F_OX = 1024, F_H = 2048, F_OUT = 3072;
constexpr int NBLK = NBIG + (NSEG - 4 * NBIG) / 2;
__host__ __device__ constexpr int blk_seg0(int b) { return b < NBIG ? 4 * b : 2 * b + 2 * NBIG; }
__device__ unsigned g_flag[NFLAG];
__device__ unsigned g_ticket, g_ticket_bg;
__device__ unsigned long long g_norm[96];
#define BSTAMP(i) do {} while (0)
#define WSTAMP(i) do {} while (0)
#define CSTAMP(i) do {} while (0)

__device__ __forceinline__ uint32_t smem_u32(const void* p) { return (uint32_t)__cvta_generic_to_shared(p); }
__device__ __forceinline__ uint32_t mapa(uint32_t a, uint32_t r) { uint32_t o; asm("mapa.shared::cluster.u32 %0, %1, %2;" : "=r"(o) : "r"(a), "r"(r)); return o; }
__device__ __forceinline__ uint32_t mapa_v(uint32_t a, uint32_t r) { uint32_t o; asm volatile("mapa.shared::cluster.u32 %0, %1, %2;" : "=r"(o) : "r"(a), "r"(r)); return o; }
__device__ __forceinline__ unsigned clk() { unsigned long long c; asm volatile("mov.u64 %0, %%clock64;" : "=l"(c) :: "memory"); return (unsigned)c; }
__device__ __forceinline__ void mbar_init(uint32_t bar, uint32_t cnt) { asm volatile("mbarrier.init.shared::cta.b64 [%0], %1;" :: "r"(bar), "r"(cnt) : "memory"); }
__device__ __forceinline__ void mbar_expect(uint32_t bar, uint32_t bytes) { asm volatile("mbarrier.arrive.expect_tx.shared::cta.b64 _, [%0], %1;" :: "r"(bar), "r"(bytes) : "memory"); }
__device__ __forceinline__ void mbar_wait(uint32_t bar, uint32_t parity) {
    asm volatile("{\n.reg .pred p;\n.reg .u32 n;\nmov.u32 n, 0;\n"
                 "W_%=: mbarrier.try_wait.parity.shared::cta.b64 p, [%0], %1;\n@p bra.uni D_%=;\n"
                 "add.u32 n, n, 1;\nsetp.lt.u32 p, n, 4000000;\n@p bra.uni W_%=;\ntrap;\nD_%=:\n}" :: "r"(bar), "r"(parity) : "memory");
}
__device__ __forceinline__ void mbar_expect_if(uint32_t z, uint32_t bar, uint32_t bytes) {
    asm volatile("{\n.reg .pred p;\nsetp.eq.u32 p, %2, 0;\n@p mbarrier.arrive.expect_tx.shared::cta.b64 _, [%0], %1;\n}" :: "r"(bar), "r"(bytes), "r"(z) : "memory");
}
__device__ __forceinline__ void mbar_arrive_if(uint32_t z, uint32_t bar) {
    asm volatile("{\n.reg .pred p;\nsetp.eq.u32 p, %1, 0;\n@p mbarrier.arrive.shared::cta.b64 _, [%0];\n}" :: "r"(bar), "r"(z) : "memory");
}
__device__ __forceinline__ void sts32_if(uint32_t z, uint32_t a, uint32_t x) {
    asm volatile("{\n.reg .pred p;\nsetp.eq.u32 p, %2, 0;\n@p st.shared.u32 [%0], %1;\n}" :: "r"(a), "r"(x), "r"(z) : "memory");
}
template <int K> __device__ __forceinline__ void sched_fence(int v) {
    asm volatile("{\n.reg .pred p;\nsetp.ne.s32 p, %0, %1;\n@p bra.uni F_%=;\ntrap;\nF_%=:\n}" :: "r"(v), "n"(1000 + K) : "memory");
}
__device__ __forceinline__ void spin_until(unsigned t0, unsigned d) {
    asm volatile("{\n.reg .pred p;\n.reg .u64 c;\n.reg .u32 lo;\n"
                 "S_%=: mov.u64 c, %%clock64;\ncvt.u32.u64 lo, c;\nsub.u32 lo, lo, %0;\nsetp.lt.u32 p, lo, %1;\n@p bra.uni S_%=;\n}" :: "r"(t0), "r"(d) : "memory");
}
__device__ __forceinline__ void bar_sync(int id, int n) { asm volatile("bar.sync %0, %1;" :: "r"(id), "r"(n) : "memory"); }
__device__ __forceinline__ void bar_sync_sel(int sel, int id) {
    asm volatile("{\n.reg .pred p;\nsetp.eq.u32 p, %0, 0;\n@p bar.sync %1, %3;\n@!p bar.sync %2, %3;\n}" :: "r"(sel), "r"(id), "r"(id + 1), "n"(192) : "memory");
}
__device__ __forceinline__ void bar_arrive(int id, int n) { asm volatile("bar.arrive %0, %1;" :: "r"(id), "r"(n) : "memory"); }
__device__ __forceinline__ void fence_async_smem() { asm volatile("fence.proxy.async.shared::cta;" ::: "memory"); }
__device__ __forceinline__ uint32_t pack_bf16(float lo, float hi) { uint32_t r; asm("cvt.rn.bf16x2.f32 %0, %1, %2;" : "=r"(r) : "f"(hi), "f"(lo)); return r; }
__device__ __forceinline__ uint32_t pack_f16(float lo, float hi) { uint32_t r; asm("cvt.rn.f16x2.f32 %0, %1, %2;" : "=r"(r) : "f"(hi), "f"(lo)); return r; }
__device__ __forceinline__ uint32_t f16x2_to_bf16x2(uint32_t v) { float2 f = __half22float2(*reinterpret_cast<__half2*>(&v)); return pack_bf16(f.x, f.y); }
__device__ __forceinline__ uint32_t hmul2(uint32_t a, uint32_t b) { uint32_t r; asm("mul.rn.f16x2 %0, %1, %2;" : "=r"(r) : "r"(a), "r"(b)); return r; }
__device__ __forceinline__ float ex2(float x) { float y; asm("ex2.approx.ftz.f32 %0, %1;" : "=f"(y) : "f"(x)); return y; }
__device__ __forceinline__ float ex2v(float x) { float y; asm volatile("ex2.approx.ftz.f32 %0, %1;" : "=f"(y) : "f"(x)); return y; }
__device__ __forceinline__ uint32_t absmax2(uint32_t a, uint32_t b) {
    uint32_t r; asm("max.xorsign.abs.f16x2 %0, %1, %2;" : "=r"(r) : "r"(a), "r"(b)); return r;
}
__device__ __forceinline__ uint32_t shl_v(uint32_t a, int n) { return a << n; }
__device__ __forceinline__ uint32_t max3u(uint32_t a, uint32_t b, uint32_t c) { return max(max(a, b), c); }
__device__ __forceinline__ uint4 lds128(uint32_t a) { uint4 v; asm volatile("ld.shared.v4.u32 {%0,%1,%2,%3}, [%4];" : "=r"(v.x), "=r"(v.y), "=r"(v.z), "=r"(v.w) : "r"(a) : "memory"); return v; }
__device__ __forceinline__ uint4 lds128v(uint32_t a) { uint4 v; asm volatile("ld.volatile.shared.v4.u32 {%0,%1,%2,%3}, [%4];" : "=r"(v.x), "=r"(v.y), "=r"(v.z), "=r"(v.w) : "r"(a) : "memory"); return v; }
__device__ __forceinline__ float4 lds128f(uint32_t a) { float4 v; asm volatile("ld.shared.v4.f32 {%0,%1,%2,%3}, [%4];" : "=f"(v.x), "=f"(v.y), "=f"(v.z), "=f"(v.w) : "r"(a) : "memory"); return v; }
__device__ __forceinline__ float2 lds64f(uint32_t a) { float2 v; asm volatile("ld.shared.v2.f32 {%0,%1}, [%2];" : "=f"(v.x), "=f"(v.y) : "r"(a) : "memory"); return v; }
__device__ __forceinline__ uint4 lds64x2(uint32_t a) { uint4 v; asm volatile("ld.shared.v2.u32 {%0,%1}, [%4];\nld.shared.v2.u32 {%2,%3}, [%4+256];" : "=r"(v.x), "=r"(v.y), "=r"(v.z), "=r"(v.w) : "r"(a) : "memory"); return v; }
__device__ __forceinline__ uint32_t lds32(uint32_t a) { uint32_t v; asm volatile("ld.shared.u32 %0, [%1];" : "=r"(v) : "r"(a) : "memory"); return v; }
__device__ __forceinline__ void sts128(uint32_t a, uint32_t x, uint32_t y, uint32_t z, uint32_t w) { asm volatile("st.shared.v4.u32 [%0], {%1,%2,%3,%4};" :: "r"(a), "r"(x), "r"(y), "r"(z), "r"(w) : "memory"); }
__device__ __forceinline__ void sts128f(uint32_t a, float x, float y, float z, float w) { asm volatile("st.shared.v4.f32 [%0], {%1,%2,%3,%4};" :: "r"(a), "f"(x), "f"(y), "f"(z), "f"(w) : "memory"); }
__device__ __forceinline__ void sts64(uint32_t a, uint32_t x, uint32_t y) { asm volatile("st.shared.v2.u32 [%0], {%1,%2};" :: "r"(a), "r"(x), "r"(y) : "memory"); }
__device__ __forceinline__ void sts32(uint32_t a, uint32_t x) { asm volatile("st.shared.u32 [%0], %1;" :: "r"(a), "r"(x) : "memory"); }
__device__ __forceinline__ uint4 ldsm4(uint32_t a) { uint4 v; asm volatile("ldmatrix.sync.aligned.m8n8.x4.shared.b16 {%0,%1,%2,%3}, [%4];" : "=r"(v.x), "=r"(v.y), "=r"(v.z), "=r"(v.w) : "r"(a) : "memory"); return v; }
__device__ __forceinline__ void stsm2t(uint32_t a, uint32_t x, uint32_t y) { asm volatile("stmatrix.sync.aligned.m8n8.x2.trans.shared.b16 [%0], {%1,%2};" :: "r"(a), "r"(x), "r"(y) : "memory"); }
__device__ __forceinline__ void stsm4t(uint32_t a, uint32_t x, uint32_t y, uint32_t z, uint32_t w) { asm volatile("stmatrix.sync.aligned.m8n8.x4.trans.shared.b16 [%0], {%1,%2,%3,%4};" :: "r"(a), "r"(x), "r"(y), "r"(z), "r"(w) : "memory"); }
__device__ __forceinline__ void st_async64(uint32_t a, uint32_t x, uint32_t y, uint32_t bar) { asm volatile("st.async.shared::cluster.mbarrier::complete_tx::bytes.v2.b32 [%0], {%1,%2}, [%3];" :: "r"(a), "r"(x), "r"(y), "r"(bar) : "memory"); }
__device__ __forceinline__ void bulk_s2c(uint32_t dst, uint32_t src, uint32_t bytes, uint32_t bar) { asm volatile("cp.async.bulk.shared::cluster.shared::cta.mbarrier::complete_tx::bytes [%0], [%1], %2, [%3];" :: "r"(dst), "r"(src), "r"(bytes), "r"(bar) : "memory"); }
__device__ __forceinline__ void bulk_s2g(void* dst, uint32_t src, uint32_t bytes) { asm volatile("cp.async.bulk.global.shared::cta.bulk_group [%0], [%1], %2;" :: "l"(dst), "r"(src), "r"(bytes) : "memory"); }
__device__ __forceinline__ uint32_t ldg_nc32(const void* p) { uint32_t v; asm volatile("ld.global.nc.L2::128B.u32 %0, [%1];" : "=r"(v) : "l"(p)); return v; }
__device__ __forceinline__ uint4 ldg_relaxed128(const void* p) { uint4 v; asm volatile("ld.relaxed.gpu.global.v4.u32 {%0,%1,%2,%3}, [%4];" : "=r"(v.x), "=r"(v.y), "=r"(v.z), "=r"(v.w) : "l"(p) : "memory"); return v; }
__device__ __forceinline__ void mma16816(float (&d)[4], uint32_t a0, uint32_t a1, uint32_t a2, uint32_t a3, uint32_t b0, uint32_t b1) {
    asm volatile("mma.sync.aligned.m16n8k16.row.col.f32.bf16.bf16.f32 {%0,%1,%2,%3}, {%4,%5,%6,%7}, {%8,%9}, {%0,%1,%2,%3};"
        : "+f"(d[0]), "+f"(d[1]), "+f"(d[2]), "+f"(d[3]) : "r"(a0), "r"(a1), "r"(a2), "r"(a3), "r"(b0), "r"(b1));
}
__device__ __forceinline__ void mma16816_z(float (&d)[4], uint32_t a0, uint32_t a1, uint32_t a2, uint32_t a3, uint32_t b0, uint32_t b1) {
    asm volatile("mma.sync.aligned.m16n8k16.row.col.f32.bf16.bf16.f32 {%0,%1,%2,%3}, {%4,%5,%6,%7}, {%8,%9}, {%10,%10,%10,%10};"
        : "=f"(d[0]), "=f"(d[1]), "=f"(d[2]), "=f"(d[3]) : "r"(a0), "r"(a1), "r"(a2), "r"(a3), "r"(b0), "r"(b1), "f"(0.f));
}
__device__ __forceinline__ void mma1688(float (&d)[4], uint32_t a0, uint32_t a1, uint32_t b0) {
    asm volatile("mma.sync.aligned.m16n8k8.row.col.f32.bf16.bf16.f32 {%0,%1,%2,%3}, {%4,%5}, {%6}, {%0,%1,%2,%3};"
        : "+f"(d[0]), "+f"(d[1]), "+f"(d[2]), "+f"(d[3]) : "r"(a0), "r"(a1), "r"(b0));
}
__device__ __forceinline__ void mma1688_z(float (&d)[4], uint32_t a0, uint32_t a1, uint32_t b0) {
    asm volatile("mma.sync.aligned.m16n8k8.row.col.f32.bf16.bf16.f32 {%0,%1,%2,%3}, {%4,%5}, {%6}, {%7,%7,%7,%7};"
        : "=f"(d[0]), "=f"(d[1]), "=f"(d[2]), "=f"(d[3]) : "r"(a0), "r"(a1), "r"(b0), "f"(0.f));
}
template <int ACC>
__device__ __forceinline__ void wgmma_n32_rs(float (&d)[16], uint32_t a0, uint32_t a1, uint32_t a2, uint32_t a3, uint64_t desc) {
    asm volatile("wgmma.mma_async.sync.aligned.m64n32k16.f32.bf16.bf16 {%0,%1,%2,%3,%4,%5,%6,%7,%8,%9,%10,%11,%12,%13,%14,%15}, {%16,%17,%18,%19}, %20, %21, 1, 1, 0;"
        : "+f"(d[0]), "+f"(d[1]), "+f"(d[2]), "+f"(d[3]), "+f"(d[4]), "+f"(d[5]), "+f"(d[6]), "+f"(d[7]),
          "+f"(d[8]), "+f"(d[9]), "+f"(d[10]), "+f"(d[11]), "+f"(d[12]), "+f"(d[13]), "+f"(d[14]), "+f"(d[15])
        : "r"(a0), "r"(a1), "r"(a2), "r"(a3), "l"(desc), "n"(ACC));
}
template <int ACC>
__device__ __forceinline__ void wgmma_n32_ss(float (&d)[16], uint64_t da, uint64_t db) {
    asm volatile("wgmma.mma_async.sync.aligned.m64n32k16.f32.bf16.bf16 {%0,%1,%2,%3,%4,%5,%6,%7,%8,%9,%10,%11,%12,%13,%14,%15}, %16, %17, %18, 1, 1, 0, 0;"
        : "+f"(d[0]), "+f"(d[1]), "+f"(d[2]), "+f"(d[3]), "+f"(d[4]), "+f"(d[5]), "+f"(d[6]), "+f"(d[7]),
          "+f"(d[8]), "+f"(d[9]), "+f"(d[10]), "+f"(d[11]), "+f"(d[12]), "+f"(d[13]), "+f"(d[14]), "+f"(d[15])
        : "l"(da), "l"(db), "n"(ACC));
}
__device__ __forceinline__ void wg_fence() { asm volatile("wgmma.fence.sync.aligned;" ::: "memory"); }
__device__ __forceinline__ void wg_commit() { asm volatile("wgmma.commit_group.sync.aligned;" ::: "memory"); }
__device__ __forceinline__ void wg_wait0() { asm volatile("wgmma.wait_group.sync.aligned 0;" ::: "memory"); }
__device__ __forceinline__ void cluster_sync() { asm volatile("barrier.cluster.arrive.aligned;\nbarrier.cluster.wait.aligned;" ::: "memory"); }

#define STAMP(s, i) do {} while (0)
#define STAMPV(s, i, v) do {} while (0)

constexpr int XT_BYTES = 36864;
constexpr int O_XT = 0;
constexpr int O_STG = XT_BYTES;
constexpr int O_AS = 3 * XT_BYTES;
constexpr int O_XP = O_AS + 16384;
constexpr int O_QKX = O_XP + 8192;
constexpr int O_KM = O_QKX + 8192;
constexpr int O_QM = O_QKX + 10240;
constexpr int O_VX = O_STG + 147456;
constexpr int O_VM = O_VX + 24576;
constexpr int O_SC = O_VM + 2048;
constexpr int O_OF = O_SC + 2560;
constexpr int O_AF = O_OF + 2048;
constexpr int O_WP = O_AF + 4096;
constexpr int O_MF = O_WP + 2048;
constexpr int O_AD = O_QKX + 24576;
constexpr int O_MISC = O_MF + 9216;
static_assert(O_AD + 4096 <= O_VX, "smem");
constexpr int O_BAR = O_MISC + 64;
constexpr int CHAIN_SMEM = O_BAR + 128;
static_assert(CHAIN_SMEM <= 232448, "smem");
constexpr int B_X = O_BAR, B_VX = O_BAR + 24, B_SC = O_BAR + 40, B_W = O_BAR + 48, B_WO = O_BAR + 72;
constexpr float SM_SCALE = 0.08838834764831845f * 1.4426950408889634f;
constexpr uint32_t ONES = 0x3f803f80u;

template <bool B> struct BoolC { static constexpr bool value = B; };
__device__ __forceinline__ uint32_t opaque(uint32_t v) { uint32_t o; asm volatile("mov.u32 %0, %1;" : "=r"(o) : "r"(v)); return o; }
__device__ __forceinline__ void st_async128(uint32_t a, uint32_t x, uint32_t y, uint32_t z, uint32_t w, uint32_t bar) {
    asm volatile("st.async.shared::cluster.mbarrier::complete_tx::bytes.v4.b32 [%0], {%1,%2,%3,%4}, [%5];" :: "r"(a), "r"(x), "r"(y), "r"(z), "r"(w), "r"(bar) : "memory");
}
__device__ __forceinline__ void tma_x_tile(uint32_t sb, const CUtensorMap* tm, int r, int j, int slot) {
    asm volatile("{\n.reg .pred p, q0, q1;\nelect.sync _|p, 0xffffffff;\nsetp.ne.and.s32 q0, %5, 1, p;\nsetp.ne.and.s32 q1, %5, 0, p;\n"
        "@p mbarrier.arrive.expect_tx.shared::cta.b64 _, [%2], 36864;\n"
        "@q0 cp.async.bulk.tensor.3d.shared::cluster.global.mbarrier::complete_tx::bytes.multicast::cluster [%0], [%1, {%6, %3, %6}], [%2], %4;\n"
        "@q0 cp.async.bulk.tensor.3d.shared::cluster.global.mbarrier::complete_tx::bytes.multicast::cluster [%0+12288], [%1, {%6, %3, %7}], [%2], %4;\n"
        "@q1 cp.async.bulk.tensor.3d.shared::cluster.global.mbarrier::complete_tx::bytes.multicast::cluster [%0+24576], [%1, {%6, %3, %8}], [%2], %4;\n}"
        :: "r"(sb + O_XT + slot * XT_BYTES), "l"(tm), "r"(sb + B_X + 8 * slot), "r"(j * 32), "h"((unsigned short)(r == 2 ? 4 : 3)), "r"(r),
           "r"(0), "r"(3), "r"(6) : "memory");
}
__device__ __forceinline__ void v_store(uint32_t sb, int h, int j, int slot) {
    fence_async_smem();
    asm volatile("{\n.reg .pred p;\nelect.sync _|p, 0xffffffff;\n@p cp.async.bulk.global.shared::cta.bulk_group [%0], [%1], 8192;\n@p cp.async.bulk.commit_group;\n}"
        :: "l"(reinterpret_cast<char*>(g_qkv) + (size_t)(j * NH + h) * REC + 20480), "r"(sb + O_VX + slot * 8192) : "memory");
}
__device__ __forceinline__ void v_multicast(uint32_t sb, int h, int j) {
    asm volatile("{\n.reg .pred p;\ncp.async.bulk.wait_group 0;\nelect.sync _|p, 0xffffffff;\nsetp.lt.and.s32 p, %4, 63, p;\n"
        "@p cp.async.bulk.shared::cluster.global.mbarrier::complete_tx::bytes.multicast::cluster [%1], [%0], 8192, [%2], %3;\nfence.proxy.async.global;\n}"
        :: "l"(reinterpret_cast<char*>(g_qkv) + (size_t)(j * NH + h) * REC + 20480), "r"(sb + O_VX + (j & 1) * 8192), "r"(sb + B_VX + 8 * (j & 1)),
           "h"((unsigned short)3), "r"(j) : "memory");
}
__device__ __forceinline__ void flag_inc_if(uint32_t z, unsigned* p) {
    asm volatile("{\n.reg .pred p;\nsetp.eq.u32 p, %1, 0;\n@p red.release.gpu.global.inc.u32 [%0], 0xfffffffe;\n}" :: "l"(p), "r"(z) : "memory");
}
__device__ __forceinline__ float quad_max(float v) {
    const float a = __shfl_xor_sync(~0u, v, 1), b = __shfl_xor_sync(~0u, v, 2), c = __shfl_xor_sync(~0u, v, 3);
    return fmaxf(fmaxf(v, a), fmaxf(b, c));
}
__device__ __forceinline__ void load_scores(float (&p)[10], uint32_t base, uint32_t stride, uint32_t l16) {
    const float4 a0 = lds128f(base + l16), b0 = lds128f(base + stride + l16);
    const float4 a1 = lds128f(base + 512 + l16), b1 = lds128f(base + stride + 512 + l16);
    const float2 a2 = lds64f(base + 1024 + (l16 >> 1)), b2 = lds64f(base + stride + 1024 + (l16 >> 1));
    p[0] = a2.x + b2.x; p[1] = a2.y + b2.y;
    p[2] = a0.x + b0.x; p[3] = a0.y + b0.y; p[4] = a0.z + b0.z; p[5] = a0.w + b0.w;
    p[6] = a1.x + b1.x; p[7] = a1.y + b1.y; p[8] = a1.z + b1.z; p[9] = a1.w + b1.w;
}
__device__ __forceinline__ float rcp_fast(float x) { float y; asm("rcp.approx.ftz.f32 %0, %1;" : "=f"(y) : "f"(x)); return y; }

__global__ void __cluster_dims__(3, 1, 1) __launch_bounds__(384, 1)
chain_kernel(const __grid_constant__ CUtensorMap tm_x, const __grid_constant__ CUtensorMap tm_q,
             const __grid_constant__ CUtensorMap tm_k, const __grid_constant__ CUtensorMap tm_v, const __grid_constant__ CUtensorMap tm_o,
             const __nv_bfloat16* __restrict__ x, const __nv_bfloat16* __restrict__ mem0) {
    extern __shared__ __align__(1024) uint8_t smem_raw[];
    const uint32_t sb = smem_u32(smem_raw);
    const int lane = threadIdx.x & 31;
    const int warp = __shfl_sync(~0u, threadIdx.x >> 5, 0);
    const int wg = warp >> 2, w = warp & 3;
    const int h = blockIdx.x / 3, r = blockIdx.x - 3 * h;
    uint4* const g_acc = reinterpret_cast<uint4*>((reinterpret_cast<uintptr_t>(g_acc_raw) + 0x1fffff) & ~(uintptr_t)0x1fffff);

#define PSTAMP(i) do {} while (0)
    if (threadIdx.x == 0) {
        if (sb & 1023u) __trap();
        for (int i = 0; i < 9; i++) mbar_init(sb + O_BAR + 8 * i, 1);
        mbar_init(sb + B_WO, 2);
        asm volatile("fence.mbarrier_init.release.cluster;" ::: "memory");
        for (int i = 0; i < 3; i++) {
            mbar_expect(sb + B_W + 8 * i, 49152);
            for (int tl = 0; tl < 2; tl++)
                asm volatile("cp.async.bulk.tensor.2d.shared::cluster.global.mbarrier::complete_tx::bytes [%0], [%1, {%3, %4}], [%2];"
                    :: "r"(sb + O_STG + tl * 73728 + i * 24576), "l"(r < 2 ? (tl ? &tm_k : &tm_q) : &tm_v), "r"(sb + B_W + 8 * i),
                       "r"(h * 128 + 64 * (r < 2 ? r : tl)), "r"(192 * i) : "memory");
        }
    }
    __syncwarp();
    asm volatile("barrier.cluster.arrive.relaxed.aligned;" ::: "memory");
    if (TRIG < 0) asm volatile("griddepcontrol.launch_dependents;" ::: "memory");
    if (warp == 0) PSTAMP(9);
    if (warp == 0) CSTAMP(3);
    const uint32_t l16c = __shfl_sync(~0u, lane * 16, lane);

    if (wg < 2) {
#define KS(u) ((u) < 8 ? 12 * ((u) >> 2) + (((u) >> 1) & 1) + 4 * ((u) & 1) : (u) < 12 ? (u) : (u) < 16 ? (u) + 8 : (u) < 24 ? 24 + (((u) - 16) >> 1) + 4 * ((u) & 1) : (u) + 8)
        asm volatile("setmaxnreg.inc.sync.aligned.u32 184;");
        uint32_t a[144];
        uint32_t adr1;
        {
            const int g = lane >> 2, t = lane & 3;
            const int t1 = threadIdx.x;
#pragma unroll
            for (int i = 0; i < 2; i++) g_acc[(acc_step(i * 32 + (t1 >> 3)) + blockIdx.x * ACC_LS) / 16 + (t1 & 7)] = make_uint4(0, 0, 0, 0);
            __threadfence();
            asm volatile("barrier.cluster.wait.aligned;" ::: "memory");
            const uint32_t ev = sb + O_STG + (2 * t) * 128 + (((2 * w + (g >> 2)) ^ (2 * t)) << 4) + (g & 3) * 4;
            const uint32_t od = (ev ^ 16) + 128;
            auto gather = [&](int dst, uint32_t off) {
                a[dst] = lds32(ev + off); a[dst + 1] = lds32(od + off); a[dst + 2] = lds32(ev + off + 1024); a[dst + 3] = lds32(od + off + 1024);
            };
#pragma unroll
            for (int th = 0; th < 2; th++) {
                mbar_wait(sb + B_W + 8 * th, 0);
                if (TRIG == th) asm volatile("griddepcontrol.launch_dependents;" ::: "memory");
#pragma unroll
                for (int u = 4 * th; u < 4 * th + 4; u++) {
                    gather(32 + 4 * u, wg * (73728 + 4096) + KS(u) * 2048);
                    gather(4 * u, 73728 - wg * (73728 - 4096) + KS(u) * 2048);
                    gather(64 + 4 * u, wg * 73728 + KS(8 + u) * 2048);
                }
                bar_sync(1, 256);
                if (warp == 0)
                    asm volatile("{\n.reg .pred p;\nelect.sync _|p, 0xffffffff;\n@p mbarrier.arrive.expect_tx.shared::cta.b64 _, [%2], 24576;\n"
                        "@p cp.async.bulk.tensor.2d.shared::cluster.global.mbarrier::complete_tx::bytes [%0], [%1, {%3, %6}], [%2];\n"
                        "@p cp.async.bulk.tensor.2d.shared::cluster.global.mbarrier::complete_tx::bytes [%0+8192], [%1, {%4, %6}], [%2];\n"
                        "@p cp.async.bulk.tensor.2d.shared::cluster.global.mbarrier::complete_tx::bytes [%0+16384], [%1, {%5, %6}], [%2];\n}"
                        :: "r"(sb + O_STG + th * 24576), "l"(&tm_o), "r"(sb + B_WO), "r"(192 * r), "r"(192 * r + 64), "r"(192 * r + 128),
                           "r"(h * 128 + 64 * th) : "memory");
            }
            mbar_wait(sb + B_W + 16, 0);
#pragma unroll
            for (int u = 16; u < 28; u++) gather(32 + 4 * u, wg * 73728 + KS(u) * 2048);
#pragma unroll
            for (int kk = 0; kk < 72; kk++) {
                uint32_t w0 = a[2 * kk], w1 = a[2 * kk + 1];
                a[2 * kk] = __byte_perm(w0, w1, 0x5410);
                a[2 * kk + 1] = __byte_perm(w0, w1, 0x7632);
            }
            if (r == 2) {
                float n0[4], n1[4];
#pragma unroll
                for (int u = 0; u < 36; u++) {
                    const uint32_t x0 = a[4 * u] & 0x7fff7fffu, x1 = a[4 * u + 1] & 0x7fff7fffu, x2 = a[4 * u + 2] & 0x7fff7fffu, x3 = a[4 * u + 3] & 0x7fff7fffu;
                    if (u == 0) mma16816_z(n0, x0, x1, x2, x3, ONES, ONES);
                    else if (u < 8) mma16816(n0, x0, x1, x2, x3, ONES, ONES);
                    else if (u == 8) mma16816_z(n1, x0, x1, x2, x3, ONES, ONES);
                    else mma16816(n1, x0, x1, x2, x3, ONES, ONES);
                }
                const uint32_t mx = __reduce_max_sync(~0u, __float_as_uint(2.f * fmaxf(fmaxf(n0[0], n0[2]), fmaxf(n1[0], n1[2]))));
                sts32_if(lane, sb + O_MISC + 32 + 4 * warp, mx);
            }
            if (warp == 0) PSTAMP(11);
            bar_arrive(7, 384);
            asm volatile("barrier.cluster.arrive.relaxed.aligned;" ::: "memory");
            bar_sync(1, 256);
            const uint32_t as = sb + O_AS + wg * 8192 + (16 * w + g) * 128 + t * 4;
            sts32(as + (g << 4), a[32]);
            sts32(as + 1024 + (g << 4), a[33]);
            sts32(as + ((1 ^ g) << 4), a[34]);
            sts32(as + 1024 + ((1 ^ g) << 4), a[35]);
            sts128(sb + O_AF + warp * 512 + lane * 16, a[32], a[33], a[34], a[35]);
            fence_async_smem();
            bar_sync(1, 256);
            const uint32_t l = lane * 16;
            const int mi = lane >> 3, isk = (mi >> 1) ? wg : (wg ^ 1);
            adr1 = (r == 2) ? (sb + O_VM + warp * 256 + (l >> 1))
                            : (isk ? (sb + O_KM + w * 512 + wg * 256 + (mi & 1) * 128 + (l & 127))
                                   : (sb + O_QM + w * 512 + (mi & 1) * 256 + wg * 128 + (l & 127)));
            adr1 = __shfl_sync(~0u, adr1, lane);
            const uint32_t dl = (r == 2) ? adr1 : sb + O_SC + r * 1280 + w * 512 + (w == 2 ? (l >> 1) : l);
            const int ra = (r == 2) ? 0 : 2, rb = (r == 2) ? 1 : (r ^ 1);
            sts128(sb + O_AD + warp * 512 + l, mapa(dl, ra), mapa(sb + B_SC, ra), mapa(dl, rb), mapa(sb + B_SC, rb));
        }
        auto qkv_loop = [&](auto r2tag) {
        constexpr bool R2 = decltype(r2tag)::value;
        int s3 = 2;
#pragma unroll 1
        for (int s = -1 - R2; s < NSEG; s++) {
            const uint32_t l16 = opaque(l16c);
            const int j = s + 1 + R2;
            s3 = (s3 == 2) ? 0 : s3 + 1;
            if (s < 0) mbar_wait(sb + B_X + 8 * s3, 0);
            const uint64_t desc0 = (uint64_t)(((sb + O_XT + s3 * XT_BYTES) & 0x3FFFF) >> 4) | (1ull << 16) | (64ull << 32) | (1ull << 62);
            uint32_t km0 = 0, km1 = 0;
            if (s >= 0) {
                { const uint4 v = lds128(sb + O_AF + warp * 512 + l16); a[32] = v.x; a[33] = v.y; a[34] = v.z; a[35] = v.w; }
                float co[4], cw[3][4];
                uint4 b[14];
                float inv;
#define GORD(i) ((i) < 8 ? 2 * ((i) >> 2) + (((i) >> 1) & 1) + 4 * ((i) & 1) : (i))
                auto qkv_mma = [&](int i) {
                    const int gi = GORD(i), u = 8 * gi, n0 = 2 * i, n1 = 2 * i + 1;
                    if (gi < 4) {
                        if (i == 0) mma16816_z(co, a[u], a[u + 1], a[u + 2], a[u + 3], b[0].x, b[0].y);
                        else mma16816(co, a[u], a[u + 1], a[u + 2], a[u + 3], b[i].x, b[i].y);
                    }
                    if (n0 < 3) mma16816_z(cw[n0 % 3], a[32 + u], a[32 + u + 1], a[32 + u + 2], a[32 + u + 3], b[i].x, b[i].y);
                    else mma16816(cw[n0 % 3], a[32 + u], a[32 + u + 1], a[32 + u + 2], a[32 + u + 3], b[i].x, b[i].y);
                    if (n1 < 3) mma16816_z(cw[n1 % 3], a[32 + u + 4], a[32 + u + 5], a[32 + u + 6], a[32 + u + 7], b[i].z, b[i].w);
                    else mma16816(cw[n1 % 3], a[32 + u + 4], a[32 + u + 5], a[32 + u + 6], a[32 + u + 7], b[i].z, b[i].w);
                    if (gi < 4) mma16816(co, a[u + 4], a[u + 5], a[u + 6], a[u + 7], b[i].z, b[i].w);
                };
                const uint32_t mf = sb + O_MF + l16, mfs = mf + wg * 1024;
                const uint32_t qb = (s & 1) * 12288;
                bar_sync(2, 384);
                if (warp == 0) STAMP(s, 0);
                auto qkv_ld = [&](int i) {
                    const int gi = GORD(i);
                    b[i] = gi < 4 ? lds128v(mfs + (gi >> 1) * 3072 + (gi & 1) * 512) : lds128v(mf + (gi < 6 ? gi : gi + 4) * 512);
                };
#pragma unroll
                for (int i = 0; i < 4; i++) qkv_ld(i);
                qkv_mma(0); qkv_mma(1); qkv_mma(2);
                const uint32_t z0 = __float_as_uint(QDEP ? co[0] : cw[1][0]) & (l16 & 15u);
                qkv_mma(3);
                bar_sync(15, 384);
                b[4] = lds128v(mfs + 3072 + z0);
#pragma unroll
                for (int i = 5; i < 9; i++) qkv_ld(i);
#pragma unroll
                for (int i = 4; i < 9; i++) { qkv_mma(i); qkv_ld(5 + i); }
                asm volatile("ld.volatile.shared.f32 %0, [%1];" : "=f"(inv) : "r"(sb + O_MISC) : "memory");
#pragma unroll
                for (int i = 9; i < 14; i++) qkv_mma(i);
#pragma unroll
                for (int i = 0; i < 4; i++) cw[0][i] += cw[1][i] + cw[2][i];
                if (!R2) {
                    const uint32_t o0 = pack_bf16(co[0] * inv, co[1] * inv), o1 = pack_bf16(co[2] * inv, co[3] * inv);
                    const uint32_t w0 = pack_bf16(cw[0][0] * inv, cw[0][1] * inv), w1 = pack_bf16(cw[0][2] * inv, cw[0][3] * inv);
                    stsm4t(adr1 + qb, o0, o1, w0, w1);
                    if (warp == 0) STAMP(s, 1);
                    asm volatile("{\n.reg .pred p;\nsetp.ge.u32 p, %0, 3;\n@p bar.arrive 1, 256;\n@!p bar.sync 1, 256;\n}" :: "r"(warp) : "memory");
                    auto scores = [&](float (&v)[4], const uint4 (&q)[4], const uint4 (&k)[4]) {
                        float s0[4], s1[4], t0[4], t1[4];
                        mma16816_z(s0, q[0].x, q[0].y, q[0].z, q[0].w, k[0].x, k[0].y);
                        mma16816_z(s1, q[0].x, q[0].y, q[0].z, q[0].w, k[0].z, k[0].w);
                        mma16816_z(t0, q[1].x, q[1].y, q[1].z, q[1].w, k[1].x, k[1].y);
                        mma16816_z(t1, q[1].x, q[1].y, q[1].z, q[1].w, k[1].z, k[1].w);
                        mma16816(s0, q[2].x, q[2].y, q[2].z, q[2].w, k[2].x, k[2].y);
                        mma16816(s1, q[2].x, q[2].y, q[2].z, q[2].w, k[2].z, k[2].w);
                        mma16816(t0, q[3].x, q[3].y, q[3].z, q[3].w, k[3].x, k[3].y);
                        mma16816(t1, q[3].x, q[3].y, q[3].z, q[3].w, k[3].z, k[3].w);
                        v[0] = (s0[0] + s0[2]) + (t0[0] + t0[2]); v[1] = (s0[1] + s0[3]) + (t0[1] + t0[3]);
                        v[2] = (s1[0] + s1[2]) + (t1[0] + t1[2]); v[3] = (s1[1] + s1[3]) + (t1[1] + t1[3]);
                    };
                    if (warp < 2) {
                        uint4 q[4], k[4]; float v[4];
#pragma unroll
                        for (int i = 0; i < 4; i++) { q[i] = ldsm4(sb + O_QM + qb + i * 512 + l16); k[i] = ldsm4(sb + O_QKX + 4096 + qb + warp * 2048 + i * 512 + l16); }
                        const uint4 ad = lds128(sb + O_AD + warp * 512 + l16);
                        scores(v, q, k);
                        st_async128(ad.x, __float_as_uint(v[0]), __float_as_uint(v[1]), __float_as_uint(v[2]), __float_as_uint(v[3]), ad.y);
                        st_async128(ad.z, __float_as_uint(v[0]), __float_as_uint(v[1]), __float_as_uint(v[2]), __float_as_uint(v[3]), ad.w);
                        sts128f(sb + O_SC + r * 1280 + warp * 512 + l16, v[0], v[1], v[2], v[3]);
                    } else if (warp == 2) {
                        uint4 q[4], k[4]; float v[4];
#pragma unroll
                        for (int i = 0; i < 4; i++) { q[i] = ldsm4(sb + O_QM + qb + i * 512 + l16); k[i] = ldsm4(sb + O_KM + qb + i * 512 + l16); }
                        const uint4 ad = lds128(sb + O_AD + 1024 + l16);
                        scores(v, q, k);
                        st_async64(ad.x, __float_as_uint(v[0] + v[2]), __float_as_uint(v[1] + v[3]), ad.y);
                        st_async64(ad.z, __float_as_uint(v[0] + v[2]), __float_as_uint(v[1] + v[3]), ad.w);
                        sts64(sb + O_SC + r * 1280 + 1024 + (l16 >> 1), __float_as_uint(v[0] + v[2]), __float_as_uint(v[1] + v[3]));
                        STAMP(s, 2);
                    } else if (warp == 5 && s + 2 < NSEG) {
                        tma_x_tile(sb, &tm_x, r, s + 2, s3 == 2 ? 0 : s3 + 1);
                    }
                    bar_sync(3, 384);
                } else {
                    sts128f(sb + O_XP + warp * 512 + l16, co[0], co[1], co[2], co[3]);
                    bar_sync(8 + w, 64);
                    const float4 o = lds128f(sb + O_XP + (warp ^ 4) * 512 + l16);
                    km0 = pack_bf16((cw[0][0] + o.x) * inv, (cw[0][1] + o.y) * inv);
                    km1 = pack_bf16((cw[0][2] + o.z) * inv, (cw[0][3] + o.w) * inv);
                    if (warp == 0) STAMP(s, 1);
                    st_async64(mapa(adr1, 0), km0, km1, mapa(sb + B_SC, 0));
                    st_async64(mapa(adr1, 1), km0, km1, mapa(sb + B_SC, 1));
                    sts64(adr1, km0, km1);
                    if (warp == 0) STAMP(s, 2);
                    if (warp == 5 && j + 1 < NSEG) tma_x_tile(sb, &tm_x, r, j + 1, s3 == 2 ? 0 : s3 + 1);
                    bar_sync(3, 384);
                }
            }
            auto store_qk = [&]() {
                asm volatile("{\n.reg .pred p;\nelect.sync _|p, 0xffffffff;\n"
                    "@p cp.async.bulk.global.shared::cta.bulk_group [%0], [%1], 10240;\n@p cp.async.bulk.commit_group;\n}"
                    :: "l"(reinterpret_cast<char*>(g_qkv) + (size_t)(s * NH + h) * REC + r * 10240), "r"(sb + O_QKX + (s & 1) * 12288) : "memory");
            };
            auto store_vm = [&]() {
                *reinterpret_cast<uint2*>(reinterpret_cast<char*>(g_qkv) + (size_t)(s * NH + h) * REC + 28672 + warp * 256 + (l16 >> 1)) = make_uint2(km0, km1);
            };
            if (s == NSEG - 1) {
                if (R2) store_vm();
                else if (warp == 3) {
                    fence_async_smem();
                    store_qk();
                    asm volatile("cp.async.bulk.wait_group 0;\nfence.proxy.async.global;" ::: "memory");
                }
            } else {
#define XDESC(u) (((u) < 8 ? descs : desc0) + (uint64_t)(((KS(u) >> 2) * 4096 + (KS(u) & 3) * 32) >> 4))
                const uint64_t descs = desc0 + (uint64_t)(wg * 4);
                float d[16];
                wg_fence();
#pragma unroll
                for (int u = 0; u < 8; u++) {
                    if (u == 0) wgmma_n32_rs<0>(d, a[0], a[1], a[2], a[3], XDESC(0));
                    else wgmma_n32_rs<1>(d, a[4 * u], a[4 * u + 1], a[4 * u + 2], a[4 * u + 3], XDESC(u));
                }
                wg_commit();
                wg_wait0();
                if (warp == 0) STAMP(s, 15);
                if (warp == 3) asm volatile("cp.async.bulk.wait_group.read 0;" ::: "memory");
                if (s >= 0) bar_sync(4, 384);
#pragma unroll
                for (int q = 0; q < 2; q++)
                    sts128(sb + O_XP + warp * 1024 + q * 512 + l16, pack_bf16(d[8 * q], d[8 * q + 1]), pack_bf16(d[8 * q + 2], d[8 * q + 3]),
                           pack_bf16(d[8 * q + 4], d[8 * q + 5]), pack_bf16(d[8 * q + 6], d[8 * q + 7]));
                bar_sync(12, 256);
#pragma unroll
                for (int q = 0; q < 2; q++) {
                    const uint4 o = lds128(sb + O_XP + (warp ^ 4) * 1024 + q * 512 + l16);
                    d[8 * q] = __uint_as_float(o.x << 16); d[8 * q + 1] = __uint_as_float(o.x & 0xffff0000u);
                    d[8 * q + 2] = __uint_as_float(o.y << 16); d[8 * q + 3] = __uint_as_float(o.y & 0xffff0000u);
                    d[8 * q + 4] = __uint_as_float(o.z << 16); d[8 * q + 5] = __uint_as_float(o.z & 0xffff0000u);
                    d[8 * q + 6] = __uint_as_float(o.w << 16); d[8 * q + 7] = __uint_as_float(o.w & 0xffff0000u);
                }
                if (s >= 0) {
                    if (R2) store_vm();
                    if (warp == 3) {
                        asm volatile("cp.async.bulk.wait_group 0;\nfence.proxy.async.global;" ::: "memory");
                        if (s >= 4 && !(s & (s > 4 * NBIG ? 1 : 3))) {
                            __syncwarp();
                            flag_inc_if(l16, &g_flag[F_QKV + ((s > 4 * NBIG ? 2 * s - 4 * NBIG : s) - 4 + (h >> 3)) * 8]);
                        }
                        fence_async_smem();
                    }
                    asm volatile("{\n.reg .pred p;\nsetp.eq.u32 p, %0, 0;\n@p bar.sync 5, 256;\n@!p bar.sync 13, 256;\n}" :: "r"(wg) : "memory");
                }
                const uint64_t da0 = (uint64_t)(((sb + O_AS + wg * 8192) & 0x3FFFF) >> 4) | (1ull << 16) | (64ull << 32) | (1ull << 62);
                wg_fence();
                wgmma_n32_ss<1>(d, da0, XDESC(0));
#pragma unroll
                for (int u = 1; u < 28; u++) wgmma_n32_rs<1>(d, a[32 + 4 * u], a[32 + 4 * u + 1], a[32 + 4 * u + 2], a[32 + 4 * u + 3], XDESC(u));
                wg_commit();
                wg_wait0();
                if (!R2 && warp == 3 && s >= 0) store_qk();
                if (warp == 4) STAMP(s, 3);
                uint32_t e[8];
#pragma unroll
                for (int i = 0; i < 8; i++) e[i] = pack_bf16(d[2 * i], d[2 * i + 1]);
                if (!R2) {
                    const uint32_t base = sb + O_QKX + (j & 1) * 12288 + wg * 4096 + w * 512 + l16;
                    stsm4t(base, e[0], wg ? e[1] : e[2], wg ? e[2] : e[1], e[3]);
                    stsm4t(base + 2048, e[4], wg ? e[5] : e[6], wg ? e[6] : e[5], e[7]);
                } else {
                    const uint32_t base = sb + O_VX + s3 * 8192 + warp * 1024 + l16;
                    sts128(base, e[0], e[1], e[2], e[3]);
                    sts128(base + 512, e[4], e[5], e[6], e[7]);
                    bar_arrive(j == 0 ? 0 : 14, 288);
                }
                if (warp == 7) STAMP(s, 4);
                if (j == 0) asm volatile("barrier.cluster.wait.aligned;" ::: "memory");
                if (s < -1) bar_sync(1, 256);
            }
        }
        };
        if (r == 2) qkv_loop(BoolC<true>()); else qkv_loop(BoolC<false>());
        bar_arrive(7, 384);
    } else {
        asm volatile("setmaxnreg.dec.sync.aligned.u32 136;");
        const int c = w;
        uint32_t a[96];
        uint32_t mmax = 0;
        {
            const int g = lane >> 2, t = lane & 3;
            uint32_t tag = 0, m0v[18];
            if (threadIdx.x == 256) tag = atomicAdd(&g_ticket, 1u);
#pragma unroll
            for (int i = 0; i < 9; i++) {
                const uint32_t* p = reinterpret_cast<const uint32_t*>(mem0 + g * DM + 16 * (4 * i + c) + 2 * t);
                m0v[2 * i] = __ldg(p); m0v[2 * i + 1] = __ldg(p + 4);
            }
            asm volatile("barrier.cluster.wait.aligned;" ::: "memory");
            if (c == 0) {
                tma_x_tile(sb, &tm_x, r, 0, 0);
                mbar_expect_if(lane, sb + B_SC, r < 2 ? 3328 : 2560);
                if (r < 2) mbar_expect_if(lane, sb + B_VX, 8192);
                sts32_if(lane, sb + O_MISC, __float_as_uint(1.0f));
                sts32_if(lane, sb + O_MISC + 12, __float_as_uint(SM_SCALE));
            }
#pragma unroll
            for (int tau = 0; tau < 3; tau++) {
                const uint32_t* v = m0v + 6 * tau;
                sts128(sb + O_MF + tau * 3072 + c * 512 + lane * 16, v[0], v[1], v[2], v[3]);
                sts64(sb + O_MF + tau * 3072 + 2048 + (c >> 1) * 512 + lane * 16 + (c & 1) * 8, v[4], v[5]);
#pragma unroll
                for (int i = 0; i < 6; i++) mmax = __vmaxu2(mmax, v[i] & 0x7fff7fffu);
            }
            mmax = max(mmax << 16, mmax & 0xffff0000u);
            bar_arrive(2, 384); bar_arrive(15, 384);
            tag = (__shfl_sync(~0u, tag, 0) / 96u + 1u) & 0xffffu;
            {
                mbar_wait(sb + B_W + 8 * XAFTER, 0);
                const uint4* xp = reinterpret_cast<const uint4*>(x) + blockIdx.x * 1536 + (threadIdx.x - 256);
                uint32_t xm = 0;
#pragma unroll
                for (int i = 0; i < 12; i++) {
                    const uint4 v = __ldg(xp + i * 128);
                    xm = __vmaxu2(xm, __vmaxu2(__vmaxu2(v.x & 0x7fff7fffu, v.y & 0x7fff7fffu), __vmaxu2(v.z & 0x7fff7fffu, v.w & 0x7fff7fffu)));
                }
                sts32_if(lane, sb + O_OF + 16 + 4 * c, __reduce_max_sync(~0u, max(xm << 16, xm & 0xffff0000u)));
            }
            mbar_wait(sb + B_WO, 0);
            {
                const uint32_t base = sb + O_STG + 4 * t * 128 + (g & 3) * 4, ch = 2 * c + (g >> 2), r7 = (4 * t) & 7;
#pragma unroll
                for (int i = 0; i < 3; i++)
#pragma unroll
                    for (int eb = 0; eb < 8; eb++)
#pragma unroll
                        for (int j = 0; j < 4; j++) {
                            const int dr = (j & 1) * 2 + (j >> 1);
                            a[(i * 8 + eb) * 4 + j] = lds32(base + (eb >> 2) * 24576 + i * 8192 + ((eb & 3) * 16 + dr) * 128 + ((ch ^ (r7 + dr)) << 4));
                        }
            }
#pragma unroll
            for (int kk = 0; kk < 48; kk++) {
                uint32_t w0 = a[2 * kk], w1 = a[2 * kk + 1];
                a[2 * kk] = __byte_perm(w0, w1, 0x5410);
                a[2 * kk + 1] = __byte_perm(w0, w1, 0x7632);
            }
            sts128(sb + O_WP + c * 512 + lane * 16, a[92], a[93], a[94], a[95]);
            asm volatile("barrier.cluster.arrive.relaxed.aligned;" ::: "memory");
            float wmax = 0.f;
#pragma unroll
            for (int i = 0; i < 3; i++) {
                float n0[4];
#pragma unroll
                for (int u = 8 * i; u < 8 * i + 8; u++) {
                    const uint32_t x0 = a[4 * u] & 0x7fff7fffu, x1 = a[4 * u + 1] & 0x7fff7fffu, x2 = a[4 * u + 2] & 0x7fff7fffu, x3 = a[4 * u + 3] & 0x7fff7fffu;
                    if (u == 8 * i) mma16816_z(n0, x0, x1, x2, x3, ONES, ONES);
                    else mma16816(n0, x0, x1, x2, x3, ONES, ONES);
                }
                wmax = fmaxf(wmax, fmaxf(n0[0], n0[2]));
            }
            uint32_t wm = __reduce_max_sync(~0u, __float_as_uint(wmax));
            sts32_if(lane, sb + O_OF + 4 * c, wm);
            if (c == 0) PSTAMP(8);
            bar_sync(7, 384);
            asm volatile("barrier.cluster.wait.aligned;" ::: "memory");
            if (c == 1) { tma_x_tile(sb, &tm_x, r, 1, 1); if (r == 2) tma_x_tile(sb, &tm_x, r, 2, 2); }
            if (c == 2 && r == 2) { bar_sync(0, 288); v_store(sb, h, 0, 0); v_multicast(sb, h, 0); }
            if (c == 0) {
                const uint4 wq = lds128(sb + O_OF), xq = lds128(sb + O_OF + 16), v0 = lds128(sb + O_MISC + 32), v1 = lds128(sb + O_MISC + 48);
                const uint32_t w1 = max(max(wq.x, wq.y), max(wq.z, wq.w)), x1 = max(max(xq.x, xq.y), max(xq.z, xq.w));
                const uint32_t vv = (r < 2) ? 0u : max(max(max(v0.x, v0.y), max(v0.z, v0.w)), max(max(v1.x, v1.y), max(v1.z, v1.w)));
                const uint32_t lo = (min(w1, 0x7f800000u) + 0xffffu) >> 16 | ((min(vv, 0x7f800000u) + 0xffffu) & 0xffff0000u), hi = (x1 & 0xffff0000u) | tag;
                uint32_t l0, h0, l1, h1, l2, h2;
                asm volatile("{\n.reg .pred p;\n.reg .u32 n, x, y;\n.reg .b64 v;\nsetp.eq.u32 p, %10, 0;\nmov.b64 v, {%8, %9};\n@p st.relaxed.gpu.global.b64 [%7], v;\nmov.u32 n, 0;\n"
                             "G_%=: ld.relaxed.gpu.global.b64 v, [%6];\nmov.b64 {%0, %1}, v;\nld.relaxed.gpu.global.b64 v, [%6+256];\nmov.b64 {%2, %3}, v;\n"
                             "ld.relaxed.gpu.global.b64 v, [%6+512];\nmov.b64 {%4, %5}, v;\n"
                             "xor.b32 x, %1, %9;\nxor.b32 y, %3, %9;\nor.b32 x, x, y;\nxor.b32 y, %5, %9;\nor.b32 x, x, y;\nand.b32 x, x, 0xffff;\n"
                             "setp.eq.u32 p, x, 0;\nvote.sync.all.pred p, p, 0xffffffff;\n@p bra.uni E_%=;\n"
                             "add.u32 n, n, 1;\nsetp.lt.u32 p, n, 4000000;\n@p bra.uni G_%=;\ntrap;\nE_%=:\n}"
                             : "=&r"(l0), "=&r"(h0), "=&r"(l1), "=&r"(h1), "=&r"(l2), "=&r"(h2)
                             : "l"(&g_norm[lane]), "l"(&g_norm[blockIdx.x]), "r"(lo), "r"(hi), "r"(lane) : "memory");
                const uint32_t lm = __vmaxu2(l0, __vmaxu2(l1, l2));
                const float fw = __uint_as_float(__reduce_max_sync(~0u, lm << 16));
                const float fv = __uint_as_float(__reduce_max_sync(~0u, lm & 0xffff0000u));
                const float xmax = __uint_as_float(__reduce_max_sync(~0u, max(h0, max(h1, h2)) & 0xffff0000u));
                const float G = 36.f * fw * fv;
                sts32_if(lane, sb + O_MISC + 4, __float_as_uint(G)); sts32_if(lane, sb + O_MISC + 8, __float_as_uint(G * xmax));
            }
        }
        if (c == 0) PSTAMP(12);
        bar_sync(6, 128);
        int s3n = 1;
        uint32_t roff = __shfl_sync(~0u, ((r * 4 + c) * 8 + (lane >> 4) * 2 + ((lane >> 1) & 1)) * ACC_LS + (lane & 1) * 64 + (lane & 12) * 4, lane);
#pragma unroll 1
        for (int s = 0; s < NSEG; s++) {
            const uint32_t l16 = opaque(l16c);
            const uint32_t vxa = sb + O_VX + (r == 2 ? (s3n == 0 ? 2 : s3n - 1) : (s & 1)) * 8192 + c * 2048 + l16;
            if (c == 0 && r == 2) { bar_sync(14, 288); if (VPOS == 0 && s < NSEG - 1) v_store(sb, h, s + 1, s3n); }
            if (s == NSEG - 1 && c == 1) CSTAMP(0);
            if (s == NSEG - 1) {
                asm volatile("cp.async.bulk.wait_group 0;\nfence.proxy.async.global;" ::: "memory");
                bar_sync(3, 384); mbar_wait(sb + B_SC, s & 1);
                break;
            }
            uint4 vx[4];
            sts32_if(l16, sb + O_MISC + 16 + 4 * c, __reduce_max_sync(~0u, mmax));
            if (c == 0) STAMP(s, 5);
            {
                bar_sync(6, 128);
                const uint4 mm = lds128(sb + O_MISC + 16), cf = lds128(sb + O_MISC);
                const float bound = fmaxf(__uint_as_float(cf.z), __uint_as_float(cf.y) * (__uint_as_float(max(max(mm.x, mm.y), max(mm.z, mm.w))) * __uint_as_float(cf.x)));
                const uint32_t ebits = __reduce_max_sync(~0u, min(max(__float_as_uint(bound) & 0x7f800000u, 21u << 23), 254u << 23));
                const int j = s + 1 + (r >> 1);
                if (c == 1 && j < NSEG) mbar_wait(sb + B_X + 8 * (j % 3), (j / 3) & 1);
                if (r < 2) mbar_wait(sb + B_VX + 8 * (s & 1), (s >> 1) & 1);
                bar_sync(3, 384);
                if (VPOS == 1 && c == 0 && r == 2) v_store(sb, h, s + 1, s3n);
                if (MPOS == 0 && c == 0 && r == 2) v_multicast(sb, h, s + 1);
                s3n = (s3n == 2) ? 0 : s3n + 1;
                vx[0] = lds128(vxa); vx[2] = lds128(vxa + 1024);
                if (c == 0) STAMP(s, 13);
                mbar_wait(sb + B_SC, s & 1);
                if (c == 0) STAMP(s, 6);
                float p[10];
                load_scores(p, sb + O_SC, 1280, l16);
                float mx = fmaxf(fmaxf(fmaxf(p[0], p[1]), fmaxf(p[2], p[3])), fmaxf(fmaxf(p[4], p[5]), fmaxf(p[6], p[7])));
                mx = quad_max(fmaxf(mx, fmaxf(p[8], p[9])));
                const uint4 vm = lds64x2(sb + O_VM + c * 512 + (l16 >> 1));
                vx[1] = lds128(vxa + 512); vx[3] = lds128(vxa + 1536);
                bar_arrive(4, 384);
                const float sc = __uint_as_float(lds32(sb + O_MISC + 12));
                const float mo = mx * SM_SCALE;
                uint32_t P[5];
#pragma unroll
                for (int n = 0; n < 5; n++) P[n] = pack_bf16(ex2(fmaf(p[2 * n], SM_SCALE, -mo)), ex2(fmaf(p[2 * n + 1], n == 3 ? sc : SM_SCALE, -mo)));
                if (c == 0) STAMP(s, 7);
                float o0[4], o1[4], sm[4];
                mma16816_z(sm, ONES, ONES, ONES, ONES, P[1], P[2]);
                mma16816_z(o0, vx[0].x, vx[0].y, vx[0].z, vx[0].w, P[1], P[2]);
                mma16816_z(o1, vx[2].x, vx[2].y, vx[2].z, vx[2].w, P[1], P[2]);
                mma16816(sm, ONES, ONES, ONES, ONES, P[3], P[4]);
                mma16816(o0, vx[1].x, vx[1].y, vx[1].z, vx[1].w, P[3], P[4]);
                mma16816(o1, vx[3].x, vx[3].y, vx[3].z, vx[3].w, P[3], P[4]);
                mma1688(sm, ONES, ONES, P[0]);
                mma1688(o0, vm.x, vm.y, P[0]);
                mma1688(o1, vm.z, vm.w, P[0]);
                const float sig = __uint_as_float((268u << 23) - ebits);
                const float r0 = rcp_fast(sm[0]) * sig, r1 = rcp_fast(sm[1]) * sig;
                stsm4t(sb + O_OF + c * 512 + l16, pack_bf16(o0[0] * r0, o0[1] * r1), pack_bf16(o0[2] * r0, o0[3] * r1),
                       pack_bf16(o1[0] * r0, o1[1] * r1), pack_bf16(o1[2] * r0, o1[3] * r1));
                bar_sync(6, 128);
                uint4 ob[4];
#pragma unroll
                for (int q = 0; q < 4; q++) ob[q] = ldsm4(sb + O_OF + q * 512 + l16);
                { const uint4 v = lds128(sb + O_WP + c * 512 + l16); a[92] = v.x; a[93] = v.y; a[94] = v.z; a[95] = v.w; }
                float m0[3][4], m1[3][4];
#pragma unroll
                for (int q = 0; q < 4; q++) {
#pragma unroll
                    for (int i = 0; i < 3; i++) {
                        const int k0 = (i * 8 + 2 * q) * 4;
                        if (q == 0) mma16816_z(m0[i], a[k0], a[k0 + 1], a[k0 + 2], a[k0 + 3], ob[q].x, ob[q].y);
                        else mma16816(m0[i], a[k0], a[k0 + 1], a[k0 + 2], a[k0 + 3], ob[q].x, ob[q].y);
                    }
#pragma unroll
                    for (int i = 0; i < 3; i++) {
                        const int k1 = (i * 8 + 2 * q + 1) * 4;
                        if (q == 0) mma16816_z(m1[i], a[k1], a[k1 + 1], a[k1 + 2], a[k1 + 3], ob[q].z, ob[q].w);
                        else mma16816(m1[i], a[k1], a[k1 + 1], a[k1 + 2], a[k1 + 3], ob[q].z, ob[q].w);
                    }
                }
                asm volatile("red.relaxed.gpu.global.add.noftz.v4.f16x2 [%0], {%1,%2,%3,%4};" :: "l"(reinterpret_cast<char*>(g_acc) + roff),
                    "r"(pack_f16(NRM(m0[0][0] + m1[0][0], r0), NRM(m0[0][2] + m1[0][2], r0))), "r"(pack_f16(NRM(m0[1][0] + m1[1][0], r0), NRM(m0[1][2] + m1[1][2], r0))),
                    "r"(pack_f16(NRM(m0[2][0] + m1[2][0], r0), NRM(m0[2][2] + m1[2][2], r0))), "r"(0x3c00u) : "memory");
                asm volatile("red.relaxed.gpu.global.add.noftz.v4.f16x2 [%0], {%1,%2,%3,%4};" :: "l"(reinterpret_cast<char*>(g_acc) + roff + 4 * ACC_LS),
                    "r"(pack_f16(NRM(m0[0][1] + m1[0][1], r1), NRM(m0[0][3] + m1[0][3], r1))), "r"(pack_f16(NRM(m0[1][1] + m1[1][1], r1), NRM(m0[1][3] + m1[1][3], r1))),
                    "r"(pack_f16(NRM(m0[2][1] + m1[2][1], r1), NRM(m0[2][3] + m1[2][3], r1))), "r"(0x3c00u) : "memory");
                const unsigned t_red = clk();
                bar_arrive(5, 256);
                bar_arrive(13, 256);
                mbar_expect_if(l16 | c, sb + B_SC, r < 2 ? 3328 : 2560);
                mbar_expect_if(l16 | (c ^ 1) | (r >> 1), sb + B_VX + 8 * ((s + 1) & 1), 8192);
                sts32_if(l16 | (c ^ 3), sb + O_MISC, ebits - (14u << 23));
                if (c == 0) STAMPV(s, 8, t_red);
                if (MPOS == 1 && c == 0 && r == 2) v_multicast(sb, h, s + 1);
                if (ACC_PF && c == 2 && s + 4 < NSEG - 1)
                    asm volatile("prefetch.global.L2 [%0];" :: "l"(reinterpret_cast<const char*>(g_acc) + acc_step(s + 4) + blockIdx.x * ACC_LS + (l16 & 96)) : "memory");
                const char* pbase = reinterpret_cast<const char*>(g_acc) + (acc_step(s) + c * 8 * ACC_LS) + ((((l16 >> 4) & 4) + (l16 >> 8)) * ACC_LS + ((l16 & 128) >> 1) + (l16 & 48));
                uint4 v[6];
                {
                    const char* pb = reinterpret_cast<const char*>(__shfl_sync(~0u, (unsigned long long)pbase, l16 >> 4));
                    const unsigned t_go = t_red + (s < D_S0 ? D_EARLY : D_WAIT);
                    asm volatile("{\n.reg .pred p;\n.reg .u64 c;\n.reg .u32 lo;\n"
                                 "S_%=: mov.u64 c, %%clock64;\ncvt.u32.u64 lo, c;\nsub.u32 lo, lo, %0;\nsetp.lt.s32 p, lo, 0;\n@p bra.uni S_%=;\n}" :: "r"(t_go) : "memory");
#pragma unroll
                    for (int i = 0; i < 6; i++) v[i] = ldg_relaxed128(pb + ((i >> 1) * 32 + (i & 1) * 2) * ACC_LS);
                    pbase = pb;
                }
                int nretry = 0;
                auto convert = [&](int tau) {
                    const uint4 A = v[2 * tau], B = v[2 * tau + 1];
                    sts128(sb + O_MF + tau * 3072 + c * 512 + l16, f16x2_to_bf16x2(A.x), f16x2_to_bf16x2(B.x), f16x2_to_bf16x2(A.y), f16x2_to_bf16x2(B.y));
                    sts64(sb + O_MF + tau * 3072 + 2048 + (c >> 1) * 512 + (c & 1) * 8 + l16, f16x2_to_bf16x2(A.z), f16x2_to_bf16x2(B.z));
                };
                const uint32_t ok0 = __all_sync(~0u, (v[0].w & v[1].w) == 0x5000u);
                convert(0);
                asm volatile("{\n.reg .pred p;\nsetp.ne.u32 p, %0, 0;\n@p bar.arrive 2, 384;\n}" :: "r"(ok0) : "memory");
                mmax = absmax2(absmax2(absmax2(v[0].x, v[0].y), absmax2(v[0].z, v[1].x)), absmax2(v[1].y, v[1].z));
                sched_fence<0>(h);
                uint32_t ok1;
                asm volatile("{\n.reg .pred p, q;\n.reg .b32 x;\nlop3.b32 x, %1, %2, %3, 0x80;\nand.b32 x, x, %4;\n"
                             "setp.eq.u32 p, x, 0x5000;\nvote.sync.all.pred q, p, 0xffffffff;\nselp.u32 %0, 1, 0, q;\n}"
                             : "=r"(ok1) : "r"(v[2].w), "r"(v[3].w), "r"(v[4].w), "r"(v[5].w));
                convert(1); convert(2);
                asm volatile("{\n.reg .pred p;\nsetp.ne.u32 p, %0, 0;\n@p bar.arrive 15, 384;\n}" :: "r"(ok1) : "memory");
                if (!(ok0 & ok1)) {
                    v[0] = v[1] = make_uint4(0u, 0u, 0u, ok0 ? 0x5000u : 0u);
                    asm volatile("{\n.reg .pred p0, p1, p2, p3, p4, p5, q;\n.reg .u32 n, x;\nmov.u32 n, 0;\n"
                         "R_%=: setp.ne.u32 p0, %3, 0x5000;\nsetp.ne.u32 p1, %7, 0x5000;\nsetp.ne.u32 p2, %11, 0x5000;\n"
                         "setp.ne.u32 p3, %15, 0x5000;\nsetp.ne.u32 p4, %19, 0x5000;\nsetp.ne.u32 p5, %23, 0x5000;\n"
                         "@p0 ld.relaxed.gpu.global.v4.u32 {%0,%1,%2,%3}, [%25];\n@p1 ld.relaxed.gpu.global.v4.u32 {%4,%5,%6,%7}, [%25+%26];\n"
                         "@p2 ld.relaxed.gpu.global.v4.u32 {%8,%9,%10,%11}, [%25+%27];\n@p3 ld.relaxed.gpu.global.v4.u32 {%12,%13,%14,%15}, [%25+%28];\n"
                         "@p4 ld.relaxed.gpu.global.v4.u32 {%16,%17,%18,%19}, [%25+%29];\n@p5 ld.relaxed.gpu.global.v4.u32 {%20,%21,%22,%23}, [%25+%30];\n"
                         "add.u32 %24, %24, 1;\nand.b32 x, %3, %7;\nand.b32 x, x, %11;\nand.b32 x, x, %15;\nand.b32 x, x, %19;\nand.b32 x, x, %23;\n"
                         "setp.eq.u32 q, x, 0x5000;\nvote.sync.all.pred q, q, 0xffffffff;\n@q bra.uni K_%=;\n"
                         "add.u32 n, n, 1;\nsetp.lt.u32 q, n, 2000000;\n@q bra.uni R_%=;\ntrap;\nK_%=:\n}"
                         : "+r"(v[0].x), "+r"(v[0].y), "+r"(v[0].z), "+r"(v[0].w), "+r"(v[1].x), "+r"(v[1].y), "+r"(v[1].z), "+r"(v[1].w),
                           "+r"(v[2].x), "+r"(v[2].y), "+r"(v[2].z), "+r"(v[2].w), "+r"(v[3].x), "+r"(v[3].y), "+r"(v[3].z), "+r"(v[3].w),
                           "+r"(v[4].x), "+r"(v[4].y), "+r"(v[4].z), "+r"(v[4].w), "+r"(v[5].x), "+r"(v[5].y), "+r"(v[5].z), "+r"(v[5].w), "+r"(nretry)
                         : "l"(pbase), "n"(2 * ACC_LS), "n"(32 * ACC_LS), "n"(34 * ACC_LS), "n"(64 * ACC_LS), "n"(66 * ACC_LS) : "memory");
                    if (!ok0) {
                        convert(0); bar_arrive(2, 384);
                        mmax = absmax2(absmax2(absmax2(v[0].x, v[0].y), absmax2(v[0].z, v[1].x)), absmax2(v[1].y, v[1].z));
                    }
                    if (!ok1) { convert(1); convert(2); bar_arrive(15, 384); }
                }
                if (c == 0) STAMP(s, 12);
                if (c == 0) STAMPV(s, 14, nretry);
                mmax = absmax2(mmax, absmax2(absmax2(absmax2(v[2].x, v[2].y), absmax2(v[2].z, v[3].x)), absmax2(absmax2(v[3].y, v[3].z), absmax2(v[4].x, v[4].y))));
                mmax = absmax2(mmax, absmax2(absmax2(v[4].z, v[5].x), absmax2(v[5].y, v[5].z))) & 0x7fff7fffu;
                { const float2 mf = __half22float2(*reinterpret_cast<__half2*>(&mmax)); mmax = max(__float_as_uint(mf.x), __float_as_uint(mf.y)); }
            }
            roff += acc_step(s + 1) - acc_step(s);
        }
        {
            bar_sync(7, 384);
            if (c == 0) CSTAMP(1);
            if (c == 0) flag_inc_if(l16c, &g_flag[F_QKV + (4 * (NBLK - 1) + (h >> 3)) * 8]);
            if (c == 0) CSTAMP(2);
        }
    }
    if (warp == 8) PSTAMP(13);
    cluster_sync();
}

constexpr int NST = 10;
constexpr int G_RING = 0, G_EX = NST * 16384, G_OUT = G_EX + 32768, G_CARRY = G_OUT + 32768, G_OPS = G_CARRY + 512, G_BAR = G_OPS + 256, BG_SMEM = G_BAR + 256;
constexpr int GB_FULL = G_BAR, GB_EMPTY = G_BAR + 8 * NST, GB_W = G_BAR + 16 * NST;
static_assert(BG_SMEM <= 232448, "smem");

template <int ACC>
__device__ __forceinline__ void wgmma_n128_rs(float (&d)[64], uint32_t a0, uint32_t a1, uint32_t a2, uint32_t a3, uint64_t desc) {
    asm volatile("wgmma.mma_async.sync.aligned.m64n128k16.f32.bf16.bf16 "
        "{%0,%1,%2,%3,%4,%5,%6,%7,%8,%9,%10,%11,%12,%13,%14,%15,%16,%17,%18,%19,%20,%21,%22,%23,%24,%25,%26,%27,%28,%29,%30,%31,"
        "%32,%33,%34,%35,%36,%37,%38,%39,%40,%41,%42,%43,%44,%45,%46,%47,%48,%49,%50,%51,%52,%53,%54,%55,%56,%57,%58,%59,%60,%61,%62,%63}, "
        "{%64,%65,%66,%67}, %68, %69, 1, 1, 0;"
        : "+f"(d[0]), "+f"(d[1]), "+f"(d[2]), "+f"(d[3]), "+f"(d[4]), "+f"(d[5]), "+f"(d[6]), "+f"(d[7]),
          "+f"(d[8]), "+f"(d[9]), "+f"(d[10]), "+f"(d[11]), "+f"(d[12]), "+f"(d[13]), "+f"(d[14]), "+f"(d[15]),
          "+f"(d[16]), "+f"(d[17]), "+f"(d[18]), "+f"(d[19]), "+f"(d[20]), "+f"(d[21]), "+f"(d[22]), "+f"(d[23]),
          "+f"(d[24]), "+f"(d[25]), "+f"(d[26]), "+f"(d[27]), "+f"(d[28]), "+f"(d[29]), "+f"(d[30]), "+f"(d[31]),
          "+f"(d[32]), "+f"(d[33]), "+f"(d[34]), "+f"(d[35]), "+f"(d[36]), "+f"(d[37]), "+f"(d[38]), "+f"(d[39]),
          "+f"(d[40]), "+f"(d[41]), "+f"(d[42]), "+f"(d[43]), "+f"(d[44]), "+f"(d[45]), "+f"(d[46]), "+f"(d[47]),
          "+f"(d[48]), "+f"(d[49]), "+f"(d[50]), "+f"(d[51]), "+f"(d[52]), "+f"(d[53]), "+f"(d[54]), "+f"(d[55]),
          "+f"(d[56]), "+f"(d[57]), "+f"(d[58]), "+f"(d[59]), "+f"(d[60]), "+f"(d[61]), "+f"(d[62]), "+f"(d[63])
        : "r"(a0), "r"(a1), "r"(a2), "r"(a3), "l"(desc), "n"(ACC));
}
template <int ACC>
__device__ __forceinline__ void wgmma_n64_rs(float (&d)[64], uint32_t a0, uint32_t a1, uint32_t a2, uint32_t a3, uint64_t desc) {
    asm volatile("wgmma.mma_async.sync.aligned.m64n64k16.f32.bf16.bf16 "
        "{%0,%1,%2,%3,%4,%5,%6,%7,%8,%9,%10,%11,%12,%13,%14,%15,%16,%17,%18,%19,%20,%21,%22,%23,%24,%25,%26,%27,%28,%29,%30,%31}, "
        "{%32,%33,%34,%35}, %36, %37, 1, 1, 0;"
        : "+f"(d[0]), "+f"(d[1]), "+f"(d[2]), "+f"(d[3]), "+f"(d[4]), "+f"(d[5]), "+f"(d[6]), "+f"(d[7]),
          "+f"(d[8]), "+f"(d[9]), "+f"(d[10]), "+f"(d[11]), "+f"(d[12]), "+f"(d[13]), "+f"(d[14]), "+f"(d[15]),
          "+f"(d[16]), "+f"(d[17]), "+f"(d[18]), "+f"(d[19]), "+f"(d[20]), "+f"(d[21]), "+f"(d[22]), "+f"(d[23]),
          "+f"(d[24]), "+f"(d[25]), "+f"(d[26]), "+f"(d[27]), "+f"(d[28]), "+f"(d[29]), "+f"(d[30]), "+f"(d[31])
        : "r"(a0), "r"(a1), "r"(a2), "r"(a3), "l"(desc), "n"(ACC));
}
__device__ __forceinline__ void wait_flag(const unsigned* p, unsigned target) {
    asm volatile("{\n.reg .pred p;\n.reg .u32 n, v;\nmov.u32 n, 0;\n"
                 "W_%=: ld.acquire.gpu.global.u32 v, [%0];\nsub.u32 v, v, %1;\nsetp.ge.s32 p, v, 0;\n@p bra.uni D_%=;\nnanosleep.u32 " NSLEEP ";\n"
                 "add.u32 n, n, 1;\nsetp.lt.u32 p, n, 4000000;\n@p bra.uni W_%=;\ntrap;\nD_%=:\n}" :: "l"(p), "r"(target) : "memory");
}
template <int NS, int NT>
__device__ __forceinline__ void bg_mainloop(float (&d)[64], const uint32_t (&a)[144], uint32_t sb, int it, int lane) {
    int slot = it % NST, ph = (it / NST) & 1, prev = 0;
#pragma unroll
    for (int i = 0; i < NS; i++) {
        mbar_wait(sb + GB_FULL + 8 * slot, ph);
        const uint64_t desc = (uint64_t)(((sb + G_RING + slot * 16384) & 0x3FFFF) >> 4) | (1ull << 16) | (64ull << 32) | (1ull << 62);
        wg_fence();
#pragma unroll
        for (int k = 0; k < 512 / NT; k++) {
            const int u = (2048 / NT) * i + 4 * k;
            if (NT == 128) {
                if (i == 0 && k == 0) wgmma_n128_rs<0>(d, a[u], a[u + 1], a[u + 2], a[u + 3], desc);
                else wgmma_n128_rs<1>(d, a[u], a[u + 1], a[u + 2], a[u + 3], desc + 2 * k);
            } else {
                if (i == 0 && k == 0) wgmma_n64_rs<0>(d, a[u], a[u + 1], a[u + 2], a[u + 3], desc);
                else wgmma_n64_rs<1>(d, a[u], a[u + 1], a[u + 2], a[u + 3], desc + 2 * (k & 3) + (k >> 2) * 512);
            }
        }
        wg_commit();
        if (i > 0) {
            asm volatile("wgmma.wait_group.sync.aligned 1;" ::: "memory");
            mbar_arrive_if(lane, sb + GB_EMPTY + 8 * prev);
        }
        prev = slot;
        slot += 2;
        if (slot >= NST) { slot -= NST; ph ^= 1; }
    }
    wg_wait0();
    mbar_arrive_if(lane, sb + GB_EMPTY + 8 * prev);
}
template <bool SKIP, int NT>
__device__ __forceinline__ void bg_epilogue(float (&d)[64], uint32_t sb, int wg, int w, int lane, const CUtensorMap* tm_out, int col0, int tok0,
                                            const __nv_bfloat16* xa, const __nv_bfloat16* Dk) {
    constexpr int H = NT / 4;
    const int g = lane >> 2, t = lane & 3;
    const uint32_t ex = sb + G_EX + w * 4096 + lane * 16;
    float k[H];
    if (wg == 0) {
#pragma unroll
        for (int q = 0; q < H / 4; q++) sts128f(ex + q * 512, d[H + 4 * q], d[H + 4 * q + 1], d[H + 4 * q + 2], d[H + 4 * q + 3]);
#pragma unroll
        for (int i = 0; i < H; i++) k[i] = d[i];
    } else {
#pragma unroll
        for (int q = 0; q < H / 4; q++) sts128f(ex + 16384 + q * 512, d[4 * q], d[4 * q + 1], d[4 * q + 2], d[4 * q + 3]);
#pragma unroll
        for (int i = 0; i < H; i++) k[i] = d[H + i];
    }
    uint32_t xv[16], dv = 0;
    if (SKIP) {
        const __nv_bfloat16* xp = xa + (size_t)(tok0 + 64 * wg + 2 * t) * DM + col0 + 16 * w + 2 * g;
#pragma unroll
        for (int i = 0; i < 16; i++) xv[i] = ldg_nc32(xp + (8 * (i >> 1) + (i & 1)) * DM);
        dv = ldg_nc32(Dk + col0 + 16 * w + 2 * g);
    }
    if (SKIP && w == 0) asm volatile("cp.async.bulk.wait_group.read 0;" ::: "memory");
    bar_sync(1, 256);
#pragma unroll
    for (int q = 0; q < H / 4; q++) {
        const float4 o = lds128f(ex + (wg ^ 1) * 16384 + q * 512);
        k[4 * q] += o.x; k[4 * q + 1] += o.y; k[4 * q + 2] += o.z; k[4 * q + 3] += o.w;
    }
    if (SKIP) bar_sync(1, 256); else bar_sync(13, 288);
    const uint32_t ob = sb + G_OUT + wg * (NT == 128 ? 16384 : 4096) + (w >> 1) * 8192 + (g & 1) * 8;
    const uint32_t ch = (w & 1) * 4 + (g >> 1);
#pragma unroll
    for (int i = 0; i < H / 2; i++) {
        float v0 = k[4 * (i >> 1) + (i & 1)], v1 = k[4 * (i >> 1) + 2 + (i & 1)];
        if (SKIP) {
            const uint32_t p = pack_bf16(__uint_as_float(xv[i] << 16) * __uint_as_float(dv << 16), __uint_as_float(xv[i] & 0xffff0000u) * __uint_as_float(dv & 0xffff0000u));
            v0 += __uint_as_float(p << 16); v1 += __uint_as_float(p & 0xffff0000u);
        }
        const uint32_t n7 = 2 * t + (i & 1);
        sts64(ob + (8 * (i >> 1) + n7) * 128 + ((ch ^ n7) << 4), __float_as_uint(v0), __float_as_uint(v1));
    }
    fence_async_smem();
    if (SKIP) {
        bar_sync(4 + wg, 128);
        if (w == 0)
            asm volatile("{\n.reg .pred p;\nelect.sync _|p, 0xffffffff;\n"
                "@p cp.async.bulk.tensor.2d.global.shared::cta.bulk_group [%0, {%2, %4}], [%1];\n"
                "@p cp.async.bulk.tensor.2d.global.shared::cta.bulk_group [%0, {%3, %4}], [%1+8192];\n@p cp.async.bulk.commit_group;\n}"
                :: "l"(tm_out), "r"(sb + G_OUT + wg * 16384), "r"(col0), "r"(col0 + 32), "r"(tok0 + 64 * wg) : "memory");
    } else {
        bar_arrive(12, 288);
    }
}
__device__ __forceinline__ void s5_channel(int p, const __nv_bfloat16* Lre, const __nv_bfloat16* Lim, const __nv_bfloat16* logdt, float2& lam, float2& coef) {
    const float dt = __bfloat162float(__float2bfloat16(expf(__bfloat162float(logdt[p]))));
    const float lr = __bfloat162float(Lre[p]), li = __bfloat162float(Lim[p]);
    const float e = expf(dt * lr);
    float sn, cs;
    sincosf(dt * li, &sn, &cs);
    lam = make_float2(e * cs, e * sn);
    const float den = lr * lr + li * li;
    coef = make_float2(((lam.x - 1.f) * lr + lam.y * li) / den, (lam.y * lr - (lam.x - 1.f) * li) / den);
}
__device__ __forceinline__ float2 cfma(float2 a, float2 b, float2 c) {
    return make_float2(fmaf(a.x, b.x, fmaf(-a.y, b.y, c.x)), fmaf(a.x, b.y, fmaf(a.y, b.x, c.y)));
}
__device__ __forceinline__ uint4 ldg128(const void* p) { uint4 v; asm volatile("ld.global.v4.u32 {%0,%1,%2,%3}, [%4];" : "=r"(v.x), "=r"(v.y), "=r"(v.z), "=r"(v.w) : "l"(p) : "memory"); return v; }
__device__ __forceinline__ uint2 ldg64(const void* p) { uint2 v; asm volatile("ld.global.v2.u32 {%0,%1}, [%2];" : "=r"(v.x), "=r"(v.y) : "l"(p) : "memory"); return v; }

template <int MT>
__device__ __forceinline__ void bg_attention(uint32_t st0, uint32_t st1, int lane) {
    constexpr int NK = MT ? 5 : 3;
    const int g = lane >> 2, t = lane & 3;
    float sc[NK][4], sm2[4];
#pragma unroll
    for (int i = 0; i < 8; i++) {
        const uint32_t st = (i >> 2 ? st1 : st0) + (i & 3) * 512 + lane * 16;
        const uint4 q = ldsm4(st + MT * 2048), km = ldsm4(st + 8192), k0 = ldsm4(st + 4096);
        if (i == 0) {
            mma16816_z(sc[0], q.x, q.y, q.z, q.w, km.x, km.y); mma16816_z(sm2, q.x, q.y, q.z, q.w, km.z, km.w);
            mma16816_z(sc[1], q.x, q.y, q.z, q.w, k0.x, k0.y); mma16816_z(sc[2], q.x, q.y, q.z, q.w, k0.z, k0.w);
        } else {
            mma16816(sc[0], q.x, q.y, q.z, q.w, km.x, km.y); mma16816(sm2, q.x, q.y, q.z, q.w, km.z, km.w);
            mma16816(sc[1], q.x, q.y, q.z, q.w, k0.x, k0.y); mma16816(sc[2], q.x, q.y, q.z, q.w, k0.z, k0.w);
        }
        if (MT) {
            const uint4 k1 = ldsm4(st + 6144);
            if (i == 0) { mma16816_z(sc[NK - 2], q.x, q.y, q.z, q.w, k1.x, k1.y); mma16816_z(sc[NK - 1], q.x, q.y, q.z, q.w, k1.z, k1.w); }
            else { mma16816(sc[NK - 2], q.x, q.y, q.z, q.w, k1.x, k1.y); mma16816(sc[NK - 1], q.x, q.y, q.z, q.w, k1.z, k1.w); }
        }
    }
#pragma unroll
    for (int i = 0; i < 4; i++) sc[0][i] += sm2[i];
    if (2 * t > g) { sc[NK - 2][0] = -INFINITY; sc[NK - 1][2] = -INFINITY; }
    if (2 * t + 1 > g) { sc[NK - 2][1] = -INFINITY; sc[NK - 1][3] = -INFINITY; }
    sc[NK - 1][0] = sc[NK - 1][1] = -INFINITY;
    float ma = fmaxf(sc[0][0], sc[0][1]), mb = fmaxf(sc[0][2], sc[0][3]);
#pragma unroll
    for (int n = 1; n < NK; n++) { ma = fmaxf(ma, fmaxf(sc[n][0], sc[n][1])); mb = fmaxf(mb, fmaxf(sc[n][2], sc[n][3])); }
    ma = quad_max(ma) * SM_SCALE; mb = quad_max(mb) * SM_SCALE;
    uint32_t Pa[NK], Pb[NK];
#pragma unroll
    for (int n = 0; n < NK; n++) {
        Pa[n] = n == NK - 1 ? 0u : pack_bf16(ex2(fmaf(sc[n][0], SM_SCALE, -ma)), ex2(fmaf(sc[n][1], SM_SCALE, -ma)));
        Pb[n] = pack_bf16(ex2(fmaf(sc[n][2], SM_SCALE, -mb)), ex2(fmaf(sc[n][3], SM_SCALE, -mb)));
    }
    float sa[4], sbb[4];
    mma1688_z(sa, ONES, ONES, Pa[0]); mma1688_z(sbb, ONES, ONES, Pb[0]);
    mma16816(sa, ONES, ONES, ONES, ONES, Pa[1], Pa[2]); mma16816(sbb, ONES, ONES, ONES, ONES, Pb[1], Pb[2]);
    if (MT) { mma16816(sa, ONES, ONES, ONES, ONES, Pa[NK - 2], Pa[NK - 1]); mma16816(sbb, ONES, ONES, ONES, ONES, Pb[NK - 2], Pb[NK - 1]); }
    const float ra0 = rcp_fast(sa[0]), ra1 = rcp_fast(sa[1]), rb0 = rcp_fast(sbb[0]), rb1 = rcp_fast(sbb[1]);
    const uint32_t row = lane & 7;
    const uint32_t so = MT * 2048 + (lane >> 4) * 1024 + row * 128;
#pragma unroll
    for (int eh = 0; eh < 2; eh++) {
        const uint32_t st = eh ? st1 : st0;
        float2 vm[4]; uint4 v0[4], v1[4];
#pragma unroll
        for (int e4 = 0; e4 < 4; e4++) {
            vm[e4] = lds64f(st + 14336 + e4 * 256 + lane * 8);
            v0[e4] = lds128(st + 10240 + e4 * 1024 + lane * 16);
            if (MT) v1[e4] = lds128(st + 10240 + e4 * 1024 + 512 + lane * 16);
        }
        float oa[4][4], ob[4][4];
#pragma unroll
        for (int e4 = 0; e4 < 4; e4++) {
            mma1688_z(oa[e4], __float_as_uint(vm[e4].x), __float_as_uint(vm[e4].y), Pa[0]);
            mma1688_z(ob[e4], __float_as_uint(vm[e4].x), __float_as_uint(vm[e4].y), Pb[0]);
        }
#pragma unroll
        for (int e4 = 0; e4 < 4; e4++) {
            mma16816(oa[e4], v0[e4].x, v0[e4].y, v0[e4].z, v0[e4].w, Pa[1], Pa[2]);
            mma16816(ob[e4], v0[e4].x, v0[e4].y, v0[e4].z, v0[e4].w, Pb[1], Pb[2]);
        }
        if (MT) {
#pragma unroll
            for (int e4 = 0; e4 < 4; e4++) {
                mma16816(oa[e4], v1[e4].x, v1[e4].y, v1[e4].z, v1[e4].w, Pa[NK - 2], Pa[NK - 1]);
                mma16816(ob[e4], v1[e4].x, v1[e4].y, v1[e4].z, v1[e4].w, Pb[NK - 2], Pb[NK - 1]);
            }
        }
#pragma unroll
        for (int e4 = 0; e4 < 4; e4++)
            stsm4t(st + so + (((2 * e4 + ((lane >> 3) & 1)) ^ row) << 4), pack_bf16(oa[e4][0] * ra0, oa[e4][1] * ra1), pack_bf16(oa[e4][2] * ra0, oa[e4][3] * ra1),
                   pack_bf16(ob[e4][0] * rb0, ob[e4][1] * rb1), pack_bf16(ob[e4][2] * rb0, ob[e4][3] * rb1));
    }
}
__device__ __forceinline__ bool wait_either(const unsigned* p, unsigned target, uint32_t mask, uint32_t sleep_ns) {
    uint32_t res;
    asm volatile("{\n.reg .pred p;\n.reg .u32 n, v;\nmov.u32 n, 0;\n"
                 "W_%=: ld.acquire.gpu.global.u32 v, [%1];\nsub.u32 v, v, %2;\nsetp.ge.s32 p, v, 0;\nvote.sync.ballot.b32 %0, p, 0xffffffff;\nand.b32 %0, %0, %3;\n"
                 "setp.ne.u32 p, %0, 0;\n@p bra.uni D_%=;\nnanosleep.u32 %4;\nadd.u32 n, n, 1;\nsetp.lt.u32 p, n, 4000000;\n@p bra.uni W_%=;\ntrap;\n"
                 "D_%=: fence.proxy.async.global;\n}"
                 : "=r"(res) : "l"(p), "r"(target), "r"(mask), "r"(sleep_ns) : "memory");
    return (res & 2u) != 0;
}

__global__ void __launch_bounds__(384, 1)
bg_kernel(const __grid_constant__ CUtensorMap tm_xa, const __grid_constant__ CUtensorMap tm_wo, const __grid_constant__ CUtensorMap tm_out,
          const __nv_bfloat16* __restrict__ xa, const __nv_bfloat16* __restrict__ Lre, const __nv_bfloat16* __restrict__ Lim,
          const __nv_bfloat16* __restrict__ Bre, const __nv_bfloat16* __restrict__ Bim, const __nv_bfloat16* __restrict__ Cre,
          const __nv_bfloat16* __restrict__ Cim, const __nv_bfloat16* __restrict__ logdt, const __nv_bfloat16* __restrict__ Dk, float* __restrict__ out) {
    extern __shared__ __align__(1024) uint8_t smem_raw[];
    const uint32_t sb = smem_u32(smem_raw);
    const int lane = threadIdx.x & 31;
    const int warp = __shfl_sync(~0u, threadIdx.x >> 5, 0);
    const int wg = warp >> 2, w = warp & 3, b = blockIdx.x;
    const int nt = b % 9, kq = b / 9;
    BSTAMP(0);
    if (threadIdx.x == 0) {
        if (sb & 1023u) __trap();
        for (int i = 0; i < NST; i++) { mbar_init(sb + GB_FULL + 8 * i, 1); mbar_init(sb + GB_EMPTY + 8 * i, 4); }
        mbar_init(sb + GB_W, 1);
        asm volatile("fence.mbarrier_init.release.cluster;" ::: "memory");
        mbar_expect(sb + GB_W, (b < 18 ? 64 : 128) * 1152);
        sts32(sb + G_BAR + 248, atomicAdd(&g_ticket_bg, 1u) / 36u + 1u);
    }
    __syncthreads();
    if (wg == 2) {
        asm volatile("setmaxnreg.dec.sync.aligned.u32 24;");
        if (w == 0) {
            int slot = 0, ph = 1;
            auto next = [&]() { if (++slot == NST) { slot = 0; ph ^= 1; } };
            bar_sync(6, 288);
            if (b < 18) {
#pragma unroll 1
                for (int i = 0; i < 144; i++) {
                    const int blk = i / 9, kb = i - 9 * blk, it = (blk >> 1) * 18 + (blk & 1) + 2 * kb;
                    slot = it % NST;
                    mbar_wait(sb + GB_EMPTY + 8 * slot, ((it / NST) & 1) ^ 1);
                    asm volatile("{\n.reg .pred p;\nelect.sync _|p, 0xffffffff;\n@p mbarrier.arrive.expect_tx.shared::cta.b64 _, [%2], 16384;\n"
                        "@p cp.async.bulk.tensor.5d.shared::cluster.global.mbarrier::complete_tx::bytes [%0], [%1, {%3, %4, %4, %4, %5}], [%2];\n}"
                        :: "r"(sb + G_RING + slot * 16384), "l"(&tm_xa), "r"(sb + GB_FULL + 8 * slot), "r"(kb * 64), "r"(0), "r"(blk) : "memory");
                }
                slot = 144 % NST; ph = ((144 / NST) & 1) ^ 1;
            }
            const unsigned ep = lds32(sb + G_BAR + 248);
            auto slabs = [&](const char* src, int ns) {
                asm volatile("fence.proxy.async.global;" ::: "memory");
#pragma unroll 1
                for (int i = 0; i < ns; i++) {
                    mbar_wait(sb + GB_EMPTY + 8 * slot, ph);
                    asm volatile("{\n.reg .pred p;\nelect.sync _|p, 0xffffffff;\n@p mbarrier.arrive.expect_tx.shared::cta.b64 _, [%2], 16384;\n"
                        "@p cp.async.bulk.shared::cluster.global.mbarrier::complete_tx::bytes [%0], [%1], 16384, [%2];\n}"
                        :: "r"(sb + G_RING + slot * 16384), "l"(src + (size_t)((i & 1) * (ns >> 1) + (i >> 1)) * (SEQ * 128)), "r"(sb + GB_FULL + 8 * slot) : "memory");
                    next();
                }
            };
            if (b >= 18) {
#pragma unroll 1
                for (int blk = kq - 2; blk < 16; blk += 2) {
                    wait_flag(&g_flag[F_H + blk * 8], 18 * ep);
                    slabs(reinterpret_cast<const char*>(g_h) + blk * 16384, 18);
                }
            }
            bar_sync(6, 288);
#pragma unroll 1
            for (int na = nt < 8 ? 0 : NBLK, ng = 0, k = 0; ng < NBLK; k++) {
                uint32_t mask = (na < NBLK && na <= ng + 1 ? 2u : 0u) | (ng < na ? 1u : 0u);
                if (na >= NBIG && mask == 3u) mask = ((TAILPAT >> (na - NBIG)) & 1) ? 2u : 1u;
                const bool att = wait_either(&g_flag[(lane & 1) ? F_QKV + (min(na, NBLK - 1) * 4 + kq) * 8 : F_OX + (ng * 4 + kq) * 8],
                                             ((lane & 1) ? 24 : 8) * ep, mask, ng < NBIG - 1 ? 64 : 0);
                WSTAMP(att ? 128 + na : 160 + ng);
                sts32_if(lane, sb + G_OPS + 4 * k, att);
                __syncwarp();
                if (att) {
                    {
#pragma unroll 1
                        for (int i = 0; i < (na < NBIG ? 8 : 4); i++) {
                            const int hf = (i >> 1) & 1;
                            const char* rec = reinterpret_cast<const char*>(g_qkv) + (size_t)((blk_seg0(na) + 2 * (i >> 2) + (i & 1)) * NH + 8 * kq + nt) * REC;
                            mbar_wait(sb + GB_EMPTY + 8 * slot, ph);
                            asm volatile("{\n.reg .pred p;\nelect.sync _|p, 0xffffffff;\n@p mbarrier.arrive.expect_tx.shared::cta.b64 _, [%4], 15360;\n"
                                "@p cp.async.bulk.shared::cluster.global.mbarrier::complete_tx::bytes [%0], [%1], 10240, [%4];\n"
                                "@p cp.async.bulk.shared::cluster.global.mbarrier::complete_tx::bytes [%0+10240], [%2], 4096, [%4];\n"
                                "@p cp.async.bulk.shared::cluster.global.mbarrier::complete_tx::bytes [%0+14336], [%3], 1024, [%4];\n}"
                                :: "r"(sb + G_RING + slot * 16384), "l"(rec + hf * 10240), "l"(rec + 20480 + hf * 4096), "l"(rec + 28672 + hf * 1024),
                                   "r"(sb + GB_FULL + 8 * slot) : "memory");
                            next();
                        }
                    }
                    na++;
                } else {
                    const char* src = reinterpret_cast<const char*>(g_ox) + (size_t)kq * 16 * SEQ * 128 + blk_seg0(ng) * 4096;
                    if (ng < NBIG) slabs(src, 16);
                    else {
#pragma unroll 1
                        for (int i = 0; i < 8; i++) {
                            mbar_wait(sb + GB_EMPTY + 8 * slot, ph);
                            asm volatile("{\n.reg .pred p;\nelect.sync _|p, 0xffffffff;\n@p mbarrier.arrive.expect_tx.shared::cta.b64 _, [%2], 16384;\n"
                                "@p cp.async.bulk.shared::cluster.global.mbarrier::complete_tx::bytes [%0], [%1], 8192, [%2];\n"
                                "@p cp.async.bulk.shared::cluster.global.mbarrier::complete_tx::bytes [%0+8192], [%1+262144], 8192, [%2];\n}"
                                :: "r"(sb + G_RING + slot * 16384), "l"(src + (size_t)((i & 1) * 8 + (i & 6)) * (SEQ * 128)), "r"(sb + GB_FULL + 8 * slot) : "memory");
                            next();
                        }
                    }
                    ng++;
                }
            }
        } else if (w == 1) {
            if (b < 18) {
#pragma unroll 1
                for (int blk = 0; blk < 16; blk++) {
                    bar_sync(8 + (blk & 1), 160);
                    asm volatile("{\n.reg .pred p;\nelect.sync _|p, 0xffffffff;\n@p cp.async.bulk.global.shared::cta.bulk_group [%0], [%1], 16384;\n"
                        "@p cp.async.bulk.commit_group;\ncp.async.bulk.wait_group 0;\nfence.proxy.async.global;\n}"
                        :: "l"(reinterpret_cast<char*>(g_h) + ((size_t)b * SEQ + blk * 128) * 128), "r"(sb + G_OUT + (blk & 1) * 16384) : "memory");
                    bar_arrive(10 + (blk & 1), 160);
                    flag_inc_if(lane, &g_flag[F_H + blk * 8]);
                }
            }
            if (nt < 8) {
#pragma unroll 1
                for (int na = 0; na < NBLK; na++) {
                    {
                        const int ns = na < NBIG ? 8 : 4;
                        bar_sync(7, 288);
                        const int it = lds32(sb + G_OPS + 252);
                        if (lane < ns) {
                            asm volatile("cp.async.bulk.global.shared::cta.bulk_group [%0], [%1], 4096;\ncp.async.bulk.commit_group;\ncp.async.bulk.wait_group.read 0;\n"
                                "mbarrier.arrive.shared::cta.b64 _, [%2], 4;\ncp.async.bulk.wait_group 0;\nfence.proxy.async.global;"
                                :: "l"(reinterpret_cast<char*>(g_ox) + ((size_t)((8 * kq + nt) * 2 + ((lane >> 1) & 1)) * SEQ + (blk_seg0(na) + 2 * (lane >> 2) + (lane & 1)) * 32) * 128),
                                   "r"(sb + G_RING + ((it + lane) % NST) * 16384), "r"(sb + GB_EMPTY + 8 * ((it + lane) % NST)) : "memory");
                        }
                        __syncwarp();
                        bar_arrive(14, 288);
                        flag_inc_if(lane, &g_flag[F_OX + (na * 4 + kq) * 8]);
                        WSTAMP(192 + na);
                    }
                }
            }
        } else if (w == 2) {
            const unsigned ep = lds32(sb + G_BAR + 248);
#pragma unroll 1
            for (int blk = 0; blk < NBLK; blk++) {
                const bool add = kq || blk >= NBIG;
                bar_arrive(13, 288);
                bar_sync(12, 288);
                if (add && blk <= NBIG) { wait_flag(&g_flag[F_OUT + (blk * 9 + nt) * 8], (blk < NBIG ? 1 : 4) * ep); asm volatile("fence.proxy.async.global;" ::: "memory"); }
#pragma unroll 1
                for (int i = 0; i < (blk < NBIG ? 4 : 2); i++) {
                    const uint32_t src = sb + G_OUT + i * 8192;
                    const int c0 = DM + 64 * nt + (i & 1) * 32, c1 = blk_seg0(blk) * 32 + (i >> 1) * 64;
                    if (add) asm volatile("{\n.reg .pred p;\nelect.sync _|p, 0xffffffff;\n@p cp.reduce.async.bulk.tensor.2d.global.shared::cta.add.bulk_group [%0, {%2, %3}], [%1];\n}"
                                 :: "l"(&tm_out), "r"(src), "r"(c0), "r"(c1) : "memory");
                    else asm volatile("{\n.reg .pred p;\nelect.sync _|p, 0xffffffff;\n@p cp.async.bulk.tensor.2d.global.shared::cta.bulk_group [%0, {%2, %3}], [%1];\n}"
                                 :: "l"(&tm_out), "r"(src), "r"(c0), "r"(c1) : "memory");
                    if (add && blk < NBIG - 1) spin_until(clk(), RED_GAP);
                }
                asm volatile("cp.async.bulk.commit_group;\ncp.async.bulk.wait_group 0;\nfence.proxy.async.global;" ::: "memory");
                __syncwarp();
                if (!add) flag_inc_if(lane, &g_flag[F_OUT + (blk * 9 + nt) * 8]);
                WSTAMP(224 + blk);
                if (blk == NBIG - 3) {
                    constexpr int ZR = (SEQ - 128 * NBIG) / 4;
                    float4* z = reinterpret_cast<float4*>(out + (size_t)(128 * NBIG + ZR * kq + (lane >> 4)) * (2 * DM) + DM + 64 * nt) + (lane & 15);
#pragma unroll 1
                    for (int i = 0; i < ZR / 2; i++) z[i * DM] = make_float4(0.f, 0.f, 0.f, 0.f);
                    __syncwarp();
                    flag_inc_if(lane, &g_flag[F_OUT + (NBIG * 9 + nt) * 8]);
                }
            }
        }
    } else {
        asm volatile("setmaxnreg.inc.sync.aligned.u32 240;");
        const int g = lane >> 2, t = lane & 3, tid = threadIdx.x;
        uint32_t a[144];
        float d[64];
        if (b < 18) {
            if (tid < 64)
                asm volatile("cp.async.bulk.shared::cluster.global.mbarrier::complete_tx::bytes [%0], [%1], 1152, [%2];"
                    :: "r"(sb + tid * 1168), "l"((tid < 32 ? Bre : Bim) + (size_t)(32 * b + (tid & 31)) * DM), "r"(sb + GB_W) : "memory");
            float2 lam, coef;
            s5_channel(32 * b + 8 * w + g, Lre, Lim, logdt, lam, coef);
            float2 l32 = lam;
#pragma unroll
            for (int i = 0; i < 5; i++) l32 = make_float2(l32.x * l32.x - l32.y * l32.y, 2.f * l32.x * l32.y);
            __syncwarp();
            mbar_wait(sb + GB_W, 0);
            const uint32_t ap = sb + (((lane >> 3) & 1) * 32 + 8 * w + (lane & 7)) * 1168 + (lane >> 4) * 16;
#pragma unroll
            for (int ks = 0; ks < 36; ks++) { const uint4 v = ldsm4(ap + ks * 32); a[4 * ks] = v.x; a[4 * ks + 1] = v.y; a[4 * ks + 2] = v.z; a[4 * ks + 3] = v.w; }
            bar_sync(1, 256);
            bar_arrive(6, 288);
            BSTAMP(1);
#pragma unroll 1
            for (int blk = wg; blk < 16; blk += 2) {
                bg_mainloop<9, 128>(d, a, sb, (blk >> 1) * 18 + wg, lane);
                float2 e = make_float2(0.f, 0.f);
#pragma unroll
                for (int i = 0; i < 32; i++) e = cfma(lam, e, make_float2(d[4 * (i >> 1) + (i & 1)], d[4 * (i >> 1) + 2 + (i & 1)]));
                float2 cin = make_float2(0.f, 0.f);
                if (blk > 0) { bar_sync(2 + (wg ^ 1), 256); cin = lds64f(sb + G_CARRY + (wg ^ 1) * 256 + (8 * w + g) * 8); }
                float2 mine = cin;
#pragma unroll
                for (int q = 0; q < 4; q++) {
                    const float2 eq = make_float2(__shfl_sync(~0u, e.x, (lane & 28) + q), __shfl_sync(~0u, e.y, (lane & 28) + q));
                    cin = cfma(l32, cin, eq);
                    if (t == q + 1) mine = cin;
                }
                if (blk < 15) {
                    if (t == 0) sts64(sb + G_CARRY + wg * 256 + (8 * w + g) * 8, __float_as_uint(cin.x), __float_as_uint(cin.y));
                    bar_arrive(2 + wg, 256);
                }
                const uint32_t hs = sb + G_OUT + wg * 16384 + t * 4096 + (g & 3) * 4;
                const uint32_t ch = 2 * w + (g >> 2);
                if (blk >= 2) bar_sync(10 + wg, 160);
#pragma unroll
                for (int i = 0; i < 32; i++) {
                    mine = cfma(lam, mine, make_float2(d[4 * (i >> 1) + (i & 1)], d[4 * (i >> 1) + 2 + (i & 1)]));
                    sts32(hs + i * 128 + ((ch ^ (i & 7)) << 4), pack_bf16(mine.x, mine.y));
                }
                fence_async_smem();
                bar_arrive(8 + wg, 160);
            }
            bar_sync(10 + wg, 160);
        } else {
            if (tid < 128)
                asm volatile("cp.async.bulk.shared::cluster.global.mbarrier::complete_tx::bytes [%0], [%1], 1152, [%2];"
                    :: "r"(sb + tid * 1168), "l"((tid < 64 ? Cre : Cim) + (size_t)(64 * nt + (tid & 63)) * DM), "r"(sb + GB_W) : "memory");
            for (int p = tid; p < DM; p += 256) {
                float2 lam, coef;
                s5_channel(p, Lre, Lim, logdt, lam, coef);
                sts64(sb + G_EX + p * 8, __float_as_uint(2.f * coef.x), __float_as_uint(2.f * coef.y));
            }
            bar_sync(1, 256);
            mbar_wait(sb + GB_W, 0);
            const uint32_t cp = sb + (16 * w + 2 * g) * 1168 + (288 * wg + t) * 2;
#pragma unroll
            for (int u = 0; u < 72; u++) {
                const float2 c2 = lds64f(sb + G_EX + (288 * wg + 4 * u + t) * 8);
#pragma unroll
                for (int f = 0; f < 2; f++) {
                    unsigned short r16, i16;
                    asm volatile("ld.shared.u16 %0, [%1];" : "=h"(r16) : "r"(cp + f * 1168 + u * 8) : "memory");
                    asm volatile("ld.shared.u16 %0, [%1];" : "=h"(i16) : "r"(cp + (64 + f) * 1168 + u * 8) : "memory");
                    const float cr = __uint_as_float((uint32_t)r16 << 16), ci = __uint_as_float((uint32_t)i16 << 16);
                    a[2 * u + f] = pack_bf16(cr * c2.x - ci * c2.y, -(cr * c2.y + ci * c2.x));
                }
            }
            bar_sync(1, 256);
            bar_arrive(6, 288);
            BSTAMP(1);
#pragma unroll 1
            for (int j = 0; j < 8; j++) {
                bg_mainloop<9, 128>(d, a, sb, j * 18 + wg, lane);
                bg_epilogue<true, 128>(d, sb, wg, w, lane, &tm_out, 64 * nt, (2 * j + kq - 2) * 128, xa, Dk);
            }
        }
        if (w == 0) asm volatile("cp.async.bulk.wait_group 0;" ::: "memory");
        bar_sync(1, 256);
        BSTAMP(2);
        if (warp == 0)
            asm volatile("{\n.reg .pred p;\nelect.sync _|p, 0xffffffff;\n@p mbarrier.arrive.expect_tx.shared::cta.b64 _, [%2], 131072;\n"
                "@p cp.async.bulk.tensor.2d.shared::cluster.global.mbarrier::complete_tx::bytes [%0], [%1, {%3, %4}], [%2];\n"
                "@p cp.async.bulk.tensor.2d.shared::cluster.global.mbarrier::complete_tx::bytes [%0+32768], [%1, {%3, %5}], [%2];\n"
                "@p cp.async.bulk.tensor.2d.shared::cluster.global.mbarrier::complete_tx::bytes [%0+65536], [%1, {%3, %6}], [%2];\n"
                "@p cp.async.bulk.tensor.2d.shared::cluster.global.mbarrier::complete_tx::bytes [%0+98304], [%1, {%3, %7}], [%2];\n}"
                :: "r"(sb), "l"(&tm_wo), "r"(sb + GB_W), "r"(64 * nt), "r"(1024 * kq), "r"(1024 * kq + 256), "r"(1024 * kq + 512), "r"(1024 * kq + 768) : "memory");
        mbar_wait(sb + GB_W, 1);
        {
            const uint32_t base = sb + wg * 65536 + 4 * t * 128 + (g & 3) * 4, ch = 2 * w + (g >> 2), r7 = (4 * t) & 7;
#pragma unroll
            for (int ks = 0; ks < 32; ks++) {
                const uint32_t w0 = lds32(base + ks * 2048 + ((ch ^ r7) << 4)), w1 = lds32(base + ks * 2048 + 256 + ((ch ^ (r7 + 2)) << 4));
                const uint32_t w2 = lds32(base + ks * 2048 + 128 + ((ch ^ (r7 + 1)) << 4)), w3 = lds32(base + ks * 2048 + 384 + ((ch ^ (r7 + 3)) << 4));
                a[4 * ks] = __byte_perm(w0, w1, 0x5410); a[4 * ks + 1] = __byte_perm(w0, w1, 0x7632);
                a[4 * ks + 2] = __byte_perm(w2, w3, 0x5410); a[4 * ks + 3] = __byte_perm(w2, w3, 0x7632);
            }
        }
        bar_sync(1, 256);
        bar_arrive(6, 288);
        BSTAMP(3);
#pragma unroll 1
        for (int na = 0, ng = 0, it = 144, k = 0; ng < NBLK; k++) {
            mbar_wait(sb + GB_FULL + 8 * ((it + wg) % NST), ((it + wg) / NST) & 1);
            if (__shfl_sync(~0u, lds32(sb + G_OPS + 4 * k), 0)) {
                {
                    if (na < NBIG || (w >> 1) == wg) {
                        const int i0 = it + wg + (na < NBIG ? 4 * (w >> 1) : 0), i1 = i0 + 2;
                        mbar_wait(sb + GB_FULL + 8 * (i0 % NST), (i0 / NST) & 1);
                        mbar_wait(sb + GB_FULL + 8 * (i1 % NST), (i1 / NST) & 1);
                        BSTAMP(8 + na * 4);
                        if ((w ^ wg) & 1) bg_attention<1>(sb + G_RING + (i0 % NST) * 16384, sb + G_RING + (i1 % NST) * 16384, lane);
                        else bg_attention<0>(sb + G_RING + (i0 % NST) * 16384, sb + G_RING + (i1 % NST) * 16384, lane);
                        fence_async_smem();
                    }
                    if (na > 0) bar_sync(14, 288);
                    if (tid == 0) sts32(sb + G_OPS + 252, it);
                    bar_arrive(7, 288);
                    bar_sync(1, 256);
                    BSTAMP(9 + na * 4);
                    it += na < NBIG ? 8 : 4;
                }
                na++;
            } else if (ng < NBIG) {
                bg_mainloop<8, 128>(d, a, sb, it + wg, lane);
                BSTAMP(10 + ng * 4);
                bg_epilogue<false, 128>(d, sb, wg, w, lane, &tm_out, 0, 0, xa, Dk);
                BSTAMP(11 + ng * 4);
                it += 16; ng++;
            } else {
                bg_mainloop<4, 64>(d, a, sb, it + wg, lane);
                BSTAMP(10 + ng * 4);
                bg_epilogue<false, 64>(d, sb, wg, w, lane, &tm_out, 0, 0, xa, Dk);
                BSTAMP(11 + ng * 4);
                it += 8; ng++;
            }
        }
        if (nt < 8) bar_sync(14, 288);
    }
    asm volatile("griddepcontrol.wait;" ::: "memory");
}

typedef CUresult (*EncodeFn)(CUtensorMap*, CUtensorMapDataType, cuuint32_t, void*, const cuuint64_t*, const cuuint64_t*, const cuuint32_t*, const cuuint32_t*,
                             CUtensorMapInterleave, CUtensorMapSwizzle, CUtensorMapL2promotion, CUtensorMapFloatOOBfill);
}

extern "C" void kernel_launch(void* const* d_in, const int* in_sizes, int n_in, void* d_out, int out_size) {
    typedef const __nv_bfloat16* bp;
    bp Ax = (bp)d_in[0], Lre = (bp)d_in[1], Lim = (bp)d_in[2], Bre = (bp)d_in[3], Bim = (bp)d_in[4], Cre = (bp)d_in[5], Cim = (bp)d_in[6],
       logdt = (bp)d_in[7], Dk = (bp)d_in[8], Bx = (bp)d_in[9], mem0 = (bp)d_in[10], Wq = (bp)d_in[11], Wk = (bp)d_in[12], Wv = (bp)d_in[13], Wo = (bp)d_in[14];
    float* out = (float*)d_out;
    static EncodeFn enc = nullptr;
    if (!enc) {
        void* fn = nullptr; cudaDriverEntryPointQueryResult qr;
        cudaGetDriverEntryPoint("cuTensorMapEncodeTiled", &fn, cudaEnableDefault, &qr);
        enc = (EncodeFn)fn;
        cudaFuncSetAttribute(chain_kernel, cudaFuncAttributeMaxDynamicSharedMemorySize, CHAIN_SMEM);
        cudaFuncSetAttribute(bg_kernel, cudaFuncAttributeMaxDynamicSharedMemorySize, BG_SMEM);
    }
    const cuuint32_t es[5] = {1, 1, 1, 1, 1};
    auto map2d = [&](CUtensorMap* tm, CUtensorMapDataType dt, const void* p, cuuint64_t d0, cuuint64_t d1, cuuint64_t stride, cuuint32_t b0, cuuint32_t b1) {
        cuuint64_t gd[2] = {d0, d1}, gs[1] = {stride}; cuuint32_t bd[2] = {b0, b1};
        enc(tm, dt, 2, (void*)p, gd, gs, bd, es, CU_TENSOR_MAP_INTERLEAVE_NONE, CU_TENSOR_MAP_SWIZZLE_128B, CU_TENSOR_MAP_L2_PROMOTION_L2_128B,
            CU_TENSOR_MAP_FLOAT_OOB_FILL_NONE);
    };
    CUtensorMap tm_x, tm_q, tm_k, tm_v, tm_o, tm_xa, tm_wo, tm_out;
    map2d(&tm_o, CU_TENSOR_MAP_DATA_TYPE_BFLOAT16, Wo, DM, HD, DM * 2, 64, 64);
    {
        cuuint64_t gd[3] = {64, SEQ, 9}, gs[2] = {DM * 2, 128}; cuuint32_t bd[3] = {64, 32, 3};
        enc(&tm_x, CU_TENSOR_MAP_DATA_TYPE_BFLOAT16, 3, (void*)Bx, gd, gs, bd, es, CU_TENSOR_MAP_INTERLEAVE_NONE, CU_TENSOR_MAP_SWIZZLE_128B,
            CU_TENSOR_MAP_L2_PROMOTION_L2_128B, CU_TENSOR_MAP_FLOAT_OOB_FILL_NONE);
    }
    map2d(&tm_q, CU_TENSOR_MAP_DATA_TYPE_BFLOAT16, Wq, HD, DM, HD * 2, 64, 192);
    map2d(&tm_k, CU_TENSOR_MAP_DATA_TYPE_BFLOAT16, Wk, HD, DM, HD * 2, 64, 192);
    map2d(&tm_v, CU_TENSOR_MAP_DATA_TYPE_BFLOAT16, Wv, HD, DM, HD * 2, 64, 192);
    map2d(&tm_wo, CU_TENSOR_MAP_DATA_TYPE_BFLOAT16, Wo, DM, HD, DM * 2, 64, 256);
    map2d(&tm_out, CU_TENSOR_MAP_DATA_TYPE_FLOAT32, out, 2 * DM, SEQ, 2 * DM * 4, 32, 64);
    {
        cuuint64_t gd[5] = {DM, 2, 4, 16, 16}, gs[4] = {DM * 2, 32 * DM * 2, 2 * DM * 2, 128 * DM * 2}; cuuint32_t bd[5] = {64, 2, 4, 16, 1};
        enc(&tm_xa, CU_TENSOR_MAP_DATA_TYPE_BFLOAT16, 5, (void*)Ax, gd, gs, bd, es, CU_TENSOR_MAP_INTERLEAVE_NONE, CU_TENSOR_MAP_SWIZZLE_128B,
            CU_TENSOR_MAP_L2_PROMOTION_L2_128B, CU_TENSOR_MAP_FLOAT_OOB_FILL_NONE);
    }
    cudaStream_t st = cudaStreamPerThread;
    chain_kernel<<<96, 384, CHAIN_SMEM, st>>>(tm_x, tm_q, tm_k, tm_v, tm_o, Bx, mem0);
    cudaLaunchConfig_t cfg = {};
    cfg.gridDim = dim3(36); cfg.blockDim = dim3(384); cfg.dynamicSmemBytes = BG_SMEM; cfg.stream = st;
    cudaLaunchAttribute at[1];
    at[0].id = cudaLaunchAttributeProgrammaticStreamSerialization; at[0].val.programmaticStreamSerializationAllowed = 1;
    cfg.attrs = at; cfg.numAttrs = 1;
    cudaLaunchKernelEx(&cfg, bg_kernel, tm_xa, tm_wo, tm_out, Ax, Lre, Lim, Bre, Bim, Cre, Cim, logdt, Dk, out);
}
```
